```python
import torch

def _softmax(x, axis=-1):
    return torch.softmax(x, dim=axis)
def _gelu(x):
    return torch.nn.functional.gelu(x, approximate="tanh")
def _silu(x):
    return torch.nn.functional.silu(x)
def _sigmoid(x):
    return torch.sigmoid(x)
def _layernorm(x, axis=-1, eps=1e-5):
    m = x.mean(dim=axis, keepdim=True)
    v = x.var(dim=axis, keepdim=True, unbiased=False)
    return (x - m) / torch.sqrt(v + eps)
def _scatter_add(tgt, idx, src, axis=0):
    return tgt.clone().index_add_(axis, idx, src)
def _segment_sum(src, seg, n):
    out = torch.zeros((n,) + src.shape[1:], dtype=src.dtype)
    return out.index_add_(0, seg, src)
def _pad(x, pw):
    flat = tuple(v for pair in reversed(pw) for v in pair)
    return torch.nn.functional.pad(x, flat)

kernel_name = 'standalone__adm_resblock__diffusion'

def setup_inputs():

    _w = (lambda a: (lambda t: t.to(torch.bfloat16) if t.is_floating_point() else t)(torch.as_tensor(a)))
    B, C, HW, E = 2, 128, 64, 768
    sc = (9.0 * C) ** -0.5
    return {
        "x": _w((lambda *s: torch.randn(*s, dtype=torch.bfloat16) * 0.05)(B, C, HW, HW)),
        "t_emb": _w((lambda *s: torch.randn(*s, dtype=torch.bfloat16) * 0.4)(B, E)),
        "g1": _w(1.0 + 0.1 * (lambda *s: torch.randn(*s, dtype=torch.bfloat16) * 0.4)(C)),
        "be1": _w(0.1 * (lambda *s: torch.randn(*s, dtype=torch.bfloat16) * 0.4)(C)),
        "w1": _w((lambda *s: torch.randn(*s, dtype=torch.bfloat16) * 0.4)(C, C, 3, 3) * sc),
        "w_emb": _w((lambda *s: torch.randn(*s, dtype=torch.bfloat16) * 0.4)(E, C) * (E ** -0.5)),
        "g2": _w(1.0 + 0.1 * (lambda *s: torch.randn(*s, dtype=torch.bfloat16) * 0.4)(C)),
        "be2": _w(0.1 * (lambda *s: torch.randn(*s, dtype=torch.bfloat16) * 0.4)(C)),
        "w2": _w((lambda *s: torch.randn(*s, dtype=torch.bfloat16) * 0.4)(C, C, 3, 3) * sc),
    }

def reference(x, t_emb, g1, be1, w1, w_emb, g2, be2, w2):
    B, C, H, W = x.shape
    G, eps = 4, 1e-5
    def gn(z, gamma, beta):
        zr = z.reshape(B, G, (C // G) * H * W)
        mu = zr.mean(-1).reshape(B, G, 1)
        var = ((zr - mu) ** 2).mean(-1).reshape(B, G, 1)
        zn = ((zr - mu) / torch.sqrt(var + eps)).reshape(B, C, H, W)
        return zn * gamma.reshape(1, C, 1, 1) + beta.reshape(1, C, 1, 1)
    def conv3(z, w):
        zp = _pad(z, ((0, 0), (0, 0), (1, 1), (1, 1)))
        taps = [torch.einsum("bchw,oc->bohw", zp[:, :, i:i+H, j:j+W], w[:, :, i, j]) for i in range(3) for j in range(3)]
        out = taps[0]
        for t in taps[1:]:
            out = out + t
        return out
    h = conv3(_silu(gn(x, g1, be1)), w1)
    emb = _silu(t_emb) @ w_emb
    h = h + emb.reshape(B, C, 1, 1)
    h = conv3(_silu(gn(h, g2, be2)), w2)
    return x + h
```

```cpp
#include <cuda_runtime.h>
#include <cuda_bf16.h>
#include <stdint.h>

namespace {

constexpr int C = 128, HW = 64, NB = 2, E = 768;
constexpr int NCTA = NB * HW;
constexpr int NTHREADS = 15 * 32;
constexpr int CH_PITCH = 66 * 16;
constexpr int ROW_BYTES = 16 * CH_PITCH;
constexpr int STEP_BYTES = 4096;
constexpr int STAGE_BYTES = 3 * STEP_BYTES;
constexpr int NSTAGE = 24;
constexpr int NS = 13;

constexpr int SM_ACT = 0;
constexpr int SM_XRES = SM_ACT + 3 * ROW_BYTES;
constexpr int SM_W = SM_XRES + 16384;
constexpr int SM_COEF = SM_W + NS * STAGE_BYTES;
constexpr int SM_EMB = SM_COEF + 1024;
constexpr int SM_RED = SM_EMB + 512;
constexpr int SM_BAR = SM_RED + 128;
constexpr int BAR_WFULL = 0, BAR_WEMPTY = NS, BAR_ACT = 2 * NS, BAR_STATS = BAR_ACT + NSTAGE,
              BAR_HW = BAR_STATS + 1, BAR_OWN = BAR_HW + 1, BAR_HALO = BAR_OWN + 1  ,
              BAR_EMB = BAR_HALO + 2, NBAR = BAR_EMB + 1;
constexpr int SM_TOTAL = SM_BAR + NBAR * 8;
static_assert(SM_TOTAL <= 232448, "smem");
constexpr int OUT_PITCH = 144;

constexpr unsigned SPIN_LIMIT = 1u << 16;

__device__ __align__(128) unsigned char g_wt[2 * 72 * STEP_BYTES];
__device__ __align__(128) unsigned char g_h[NCTA * ROW_BYTES];
__device__ __align__(128) unsigned g_stats[2 * NB * 8 * HW];
__device__ __align__(128) unsigned g_emb[NB * C];
__device__ __align__(128) unsigned g_wflag[NCTA];
__device__ __align__(128) unsigned g_hflag[NCTA];
__device__ __align__(128) unsigned g_epoch[NCTA];
#define TL(i) do {} while (0)
#define TLG(i) do {} while (0)

__device__ __forceinline__ uint32_t smem_u32(const void* p) { return (uint32_t)__cvta_generic_to_shared(p); }
__device__ __forceinline__ void mbar_init(uint32_t bar, int cnt) {
    asm volatile("mbarrier.init.shared::cta.b64 [%0], %1;" ::"r"(bar), "r"(cnt) : "memory");
}
__device__ __forceinline__ void mbar_arrive(uint32_t bar) {
    asm volatile("mbarrier.arrive.shared::cta.b64 _, [%0];" ::"r"(bar) : "memory");
}
__device__ __forceinline__ void mbar_expect(uint32_t bar, uint32_t bytes) {
    asm volatile("mbarrier.arrive.expect_tx.shared::cta.b64 _, [%0], %1;" ::"r"(bar), "r"(bytes) : "memory");
}
__device__ __forceinline__ bool mbar_try(uint32_t bar, uint32_t par) {
    uint32_t ok;
    asm volatile("{\n.reg .pred p;\nmbarrier.try_wait.parity.shared::cta.b64 p, [%1], %2;\nselp.u32 %0, 1, 0, p;\n}"
                 : "=r"(ok) : "r"(bar), "r"(par) : "memory");
    return ok;
}
__device__ __forceinline__ void mbar_wait(uint32_t bar, uint32_t par) {
    unsigned it = 0;
    while (!mbar_try(bar, par)) { if (++it > SPIN_LIMIT) break; }
}
__device__ __forceinline__ void fence_async_smem() { asm volatile("fence.proxy.async.shared::cta;" ::: "memory"); }
__device__ __forceinline__ void fence_async_all() { asm volatile("fence.proxy.async;" ::: "memory"); }
__device__ __forceinline__ void bar_sync(int id, int n) { asm volatile("bar.sync %0, %1;" ::"r"(id), "r"(n) : "memory"); }
__device__ __forceinline__ void bulk_g2s(uint32_t dst, const void* src, uint32_t bytes, uint32_t bar) {
    asm volatile("cp.async.bulk.shared::cluster.global.mbarrier::complete_tx::bytes [%0], [%1], %2, [%3];"
                 ::"r"(dst), "l"(src), "r"(bytes), "r"(bar) : "memory");
}
__device__ __forceinline__ uint4 ld_relaxed_v4(const void* p) {
    uint4 v;
    asm volatile("ld.relaxed.gpu.global.v4.u32 {%0,%1,%2,%3}, [%4];" : "=r"(v.x), "=r"(v.y), "=r"(v.z), "=r"(v.w) : "l"(p) : "memory");
    return v;
}
__device__ __forceinline__ unsigned ld_relaxed(const void* p) {
    unsigned v;
    asm volatile("ld.relaxed.gpu.global.u32 %0, [%1];" : "=r"(v) : "l"(p) : "memory");
    return v;
}
__device__ __forceinline__ void st_relaxed(void* p, unsigned v) {
    asm volatile("st.relaxed.gpu.global.u32 [%0], %1;" ::"l"(p), "r"(v) : "memory");
}
__device__ __forceinline__ void fence_gpu() { asm volatile("fence.acq_rel.gpu;" ::: "memory"); }
__device__ __forceinline__ float bf_lo(uint32_t u) { return __uint_as_float(u << 16); }
__device__ __forceinline__ float bf_hi(uint32_t u) { return __uint_as_float(u & 0xffff0000u); }
__device__ __forceinline__ uint32_t pack_bf(float lo, float hi) {
    uint32_t r;
    asm("cvt.rn.bf16x2.f32 %0, %1, %2;" : "=r"(r) : "f"(hi), "f"(lo));
    return r;
}
__device__ __forceinline__ float tanh_fast(float x) {
    float r;
    asm("tanh.approx.f32 %0, %1;" : "=f"(r) : "f"(x));
    return r;
}
__device__ __forceinline__ float silu_half(float h) { return fmaf(h, tanh_fast(h), h); }
__device__ __forceinline__ unsigned tag_f(float v, unsigned tag) { return (__float_as_uint(v) & ~3u) | tag; }

#define R8(o) "+f"(d[o]), "+f"(d[o + 1]), "+f"(d[o + 2]), "+f"(d[o + 3]), "+f"(d[o + 4]), "+f"(d[o + 5]), "+f"(d[o + 6]), "+f"(d[o + 7])
__device__ __forceinline__ void wgmma128(float (&d)[64], uint64_t a, uint64_t b) {
    asm volatile(
        "wgmma.mma_async.sync.aligned.m64n128k16.f32.bf16.bf16 "
        "{%0,%1,%2,%3,%4,%5,%6,%7,%8,%9,%10,%11,%12,%13,%14,%15,%16,%17,%18,%19,%20,%21,%22,%23,%24,%25,%26,%27,%28,%29,%30,%31,"
        "%32,%33,%34,%35,%36,%37,%38,%39,%40,%41,%42,%43,%44,%45,%46,%47,%48,%49,%50,%51,%52,%53,%54,%55,%56,%57,%58,%59,%60,%61,%62,%63},"
        " %64, %65, 1, 1, 1, 0, 0;"
        : R8(0), R8(8), R8(16), R8(24), R8(32), R8(40), R8(48), R8(56)
        : "l"(a), "l"(b));
}
__device__ __forceinline__ uint64_t mkdesc(uint32_t addr, uint32_t lbo, uint32_t sbo) {
    return (uint64_t)((addr & 0x3FFFF) >> 4) | ((uint64_t)(lbo >> 4) << 16) | ((uint64_t)(sbo >> 4) << 32);
}
__device__ __forceinline__ void stage_pos(int conv, int s, int& ky, int& kc) {
    if (conv == 0) { kc = s / 3; ky = s - 3 * kc; }
    else { int o = s >> 3; kc = s & 7; ky = (o == 0) ? 1 : (o == 1 ? 0 : 2); }
}

__device__ __forceinline__ void fence_acc(float (&d)[64]) {
#pragma unroll
    for (int i = 0; i < 64; i++) asm volatile("" : "+f"(d[i])::"memory");
}
__device__ __forceinline__ void mma_loop(int conv, float (&d)[64], uint32_t sb, int& slot, uint32_t& wpar, int tid) {
    const uint32_t bars = sb + SM_BAR;
    const int lane = tid & 31;
    int prev = -1;
    fence_acc(d);
#pragma unroll 1
    for (int s = 0; s < NSTAGE; s++) {
        int ky, kc;
        stage_pos(conv, s, ky, kc);
        mbar_wait(bars + 8 * (BAR_ACT + s), conv);
        if (s == 0 && tid == 0) TL(8 + conv * 8);
        mbar_wait(bars + 8 * (BAR_WFULL + slot), wpar);
        if (s == 0 && tid == 0) TL(9 + conv * 8);
        const uint64_t da = mkdesc(sb + SM_ACT + ky * ROW_BYTES + kc * 2 * CH_PITCH, CH_PITCH, 128);
        const uint64_t db = mkdesc(sb + SM_W + slot * STAGE_BYTES, 2048, 128);
        asm volatile("wgmma.fence.sync.aligned;" ::: "memory");
        wgmma128(d, da, db);
        wgmma128(d, da + 1, db + (STEP_BYTES >> 4));
        wgmma128(d, da + 2, db + 2 * (STEP_BYTES >> 4));
        asm volatile("wgmma.commit_group.sync.aligned;" ::: "memory");
        asm volatile("wgmma.wait_group.sync.aligned 1;" ::: "memory");
        if (prev >= 0 && lane == 0) mbar_arrive(bars + 8 * (BAR_WEMPTY + prev));
        prev = slot;
        if (++slot == NS) { slot = 0; wpar ^= 1; }
    }
    asm volatile("wgmma.wait_group.sync.aligned 0;" ::: "memory");
    fence_acc(d);
    if (lane == 0) mbar_arrive(bars + 8 * (BAR_WEMPTY + prev));
    if (tid == 0) TL(10 + conv * 8);
}

__global__ void __launch_bounds__(NTHREADS, 1)
resblock_kernel(const __nv_bfloat16* __restrict__ x, const __nv_bfloat16* __restrict__ t_emb,
                const __nv_bfloat16* __restrict__ g1, const __nv_bfloat16* __restrict__ be1,
                const __nv_bfloat16* __restrict__ w1, const __nv_bfloat16* __restrict__ w_emb,
                const __nv_bfloat16* __restrict__ g2, const __nv_bfloat16* __restrict__ be2,
                const __nv_bfloat16* __restrict__ w2, __nv_bfloat16* __restrict__ out) {
    extern __shared__ __align__(128) unsigned char smem[];
    const uint32_t sb = smem_u32(smem);
    const uint32_t bars = sb + SM_BAR;
    const int tid = threadIdx.x, warp = tid >> 5, lane = tid & 31;
    const int cta = blockIdx.x, b = cta >> 6, r = cta & 63;
    if (tid == 0) { TL(0); TLG(1); }

    if (warp < 12) {
        const int wg = warp >> 2, wq = warp & 3;
        const int row = r - 1 + wg;
        const bool valid = (row >= 0) && (row < HW);
        uint32_t v[32];
        {
            const uint32_t* src = reinterpret_cast<const uint32_t*>(x + ((size_t)(b * C + wq * 32) * HW + (valid ? row : r)) * HW) + lane;
#pragma unroll
            for (int i = 0; i < 32; i++) v[i] = __ldg(src + (size_t)i * (HW * HW / 2));
        }
        unsigned epoch = 0;
        if (wg != 2) epoch = ld_relaxed(&g_epoch[cta]) + 1;
        if (tid < 96) {
            int ch = tid >> 1;
            *reinterpret_cast<uint4*>(smem + SM_ACT + ch * CH_PITCH + (tid & 1) * 65 * 16) = make_uint4(0, 0, 0, 0);
        }
        if (tid == 0) {
            for (int i = 0; i < NS; i++) { mbar_init(bars + 8 * (BAR_WFULL + i), 1); mbar_init(bars + 8 * (BAR_WEMPTY + i), 4); }
            for (int i = 0; i < NSTAGE; i++) mbar_init(bars + 8 * (BAR_ACT + i), 4);
            mbar_init(bars + 8 * BAR_STATS, 1);
            mbar_init(bars + 8 * BAR_HW, 4);
            mbar_init(bars + 8 * BAR_OWN, 1);
            mbar_init(bars + 8 * BAR_HALO, 1);
            mbar_init(bars + 8 * (BAR_HALO + 1), 1);
            mbar_init(bars + 8 * BAR_EMB, 1);
            fence_async_smem();
        }
        bar_sync(0, NTHREADS);
        if (wg == 1) {
            float s = 0.f, q = 0.f, s2 = 0.f, q2 = 0.f;
#pragma unroll
            for (int i = 0; i < 32; i++) {
                float lo = bf_lo(v[i]), hi = bf_hi(v[i]);
                s += lo; q = fmaf(lo, lo, q);
                s2 += hi; q2 = fmaf(hi, hi, q2);
            }
            if (tid == 128) TL(2);
            s += s2; q += q2;
            float give = (lane < 16) ? q : s, keep = (lane < 16) ? s : q;
            keep += __shfl_xor_sync(0xffffffffu, give, 16);
#pragma unroll
            for (int m = 8; m >= 1; m >>= 1) keep += __shfl_xor_sync(0xffffffffu, keep, m);
            if ((lane & 15) == 0) st_relaxed(&g_stats[((0 * NB + b) * 8 + wq * 2 + (lane >> 4)) * HW + r], tag_f(keep, epoch & 3));
            if (tid == 128) TL(3);
        }
        {
            const int sw = (lane >> 2) & 1;
            const uint32_t selA = sw ? 0x7632u : 0x5410u, selB = sw ? 0x5410u : 0x7632u;
            const int pxA = 2 * lane + sw, pxB = 2 * lane + (sw ^ 1);
#pragma unroll
            for (int c4 = 0; c4 < 4; c4++) {
                uint4 a, bb;
                a.x = __byte_perm(v[c4 * 8 + 0], v[c4 * 8 + 1], selA); bb.x = __byte_perm(v[c4 * 8 + 0], v[c4 * 8 + 1], selB);
                a.y = __byte_perm(v[c4 * 8 + 2], v[c4 * 8 + 3], selA); bb.y = __byte_perm(v[c4 * 8 + 2], v[c4 * 8 + 3], selB);
                a.z = __byte_perm(v[c4 * 8 + 4], v[c4 * 8 + 5], selA); bb.z = __byte_perm(v[c4 * 8 + 4], v[c4 * 8 + 5], selB);
                a.w = __byte_perm(v[c4 * 8 + 6], v[c4 * 8 + 7], selA); bb.w = __byte_perm(v[c4 * 8 + 6], v[c4 * 8 + 7], selB);
                if (!valid) { a = make_uint4(0, 0, 0, 0); bb = a; }
                const int chunk = wq * 4 + c4;
                unsigned char* dst = smem + SM_ACT + wg * ROW_BYTES + chunk * CH_PITCH + 16;
                *reinterpret_cast<uint4*>(dst + pxA * 16) = a;
                *reinterpret_cast<uint4*>(dst + pxB * 16) = bb;
                if (wg == 1) {
                    unsigned char* d2 = smem + SM_XRES + chunk * 1024;
                    *reinterpret_cast<uint4*>(d2 + pxA * 16) = a;
                    *reinterpret_cast<uint4*>(d2 + pxB * 16) = bb;
                }
            }
        }
        fence_async_smem();
        bar_sync(1, 384);

        if (wg == 0) {
            float d[64];
#pragma unroll
            for (int i = 0; i < 64; i++) d[i] = 0.f;
            const uint32_t frag_off = ((lane >> 4) * CH_PITCH) + (1 + wq * 16 + (lane & 15)) * 16;
            int slot = 0; uint32_t wpar = 0;
            mma_loop(0, d, sb, slot, wpar, tid);
            {
                {
                    mbar_wait(bars + 8 * BAR_EMB, 0);
                    const float* embs = reinterpret_cast<const float*>(smem + SM_EMB);
                    float st[8];
#pragma unroll
                    for (int g = 0; g < 4; g++) {
                        float s = 0.f, q = 0.f, s2 = 0.f, q2 = 0.f;
#pragma unroll
                        for (int jj = 0; jj < 4; jj++) {
                            const int j = g * 4 + jj;
                            const float2 e = *reinterpret_cast<const float2*>(embs + 8 * j + 2 * (lane & 3));
                            d[4 * j + 0] += e.x; d[4 * j + 1] += e.y; d[4 * j + 2] += e.x; d[4 * j + 3] += e.y;
                            s += d[4 * j + 0]; q = fmaf(d[4 * j + 0], d[4 * j + 0], q);
                            s2 += d[4 * j + 1]; q2 = fmaf(d[4 * j + 1], d[4 * j + 1], q2);
                            s += d[4 * j + 2]; q = fmaf(d[4 * j + 2], d[4 * j + 2], q);
                            s2 += d[4 * j + 3]; q2 = fmaf(d[4 * j + 3], d[4 * j + 3], q2);
                        }
                        st[2 * g] = s + s2; st[2 * g + 1] = q + q2;
                    }
                    {
                        const bool h16 = lane & 16, h8 = lane & 8, h4 = lane & 4;
                        float a[4];
#pragma unroll
                        for (int i = 0; i < 4; i++) {
                            float give = h16 ? st[i] : st[i + 4], keep = h16 ? st[i + 4] : st[i];
                            a[i] = keep + __shfl_xor_sync(0xffffffffu, give, 16);
                        }
                        float c2[2];
#pragma unroll
                        for (int i = 0; i < 2; i++) {
                            float give = h8 ? a[i] : a[i + 2], keep = h8 ? a[i + 2] : a[i];
                            c2[i] = keep + __shfl_xor_sync(0xffffffffu, give, 8);
                        }
                        float give = h4 ? c2[0] : c2[1], keep = h4 ? c2[1] : c2[0];
                        float t = keep + __shfl_xor_sync(0xffffffffu, give, 4);
                        t += __shfl_xor_sync(0xffffffffu, t, 2);
                        t += __shfl_xor_sync(0xffffffffu, t, 1);
                        float* red = reinterpret_cast<float*>(smem + SM_RED);
                        if ((lane & 3) == 0) red[(lane >> 2) * 4 + wq] = t;
                        bar_sync(2, 128);
                        if (tid < 8) {
                            const float4 p = *reinterpret_cast<const float4*>(red + tid * 4);
                            st_relaxed(&g_stats[((1 * NB + b) * 8 + tid) * HW + r], tag_f((p.x + p.y) + (p.z + p.w), epoch & 3));
                        }
                        if (tid == 0) TL(11);
                    }
                    const uint32_t hbase = sb + SM_ACT + ROW_BYTES + frag_off;
#pragma unroll
                    for (int j = 0; j < 16; j += 2) {
                        uint32_t p0 = pack_bf(d[4 * j + 0], d[4 * j + 1]), p1 = pack_bf(d[4 * j + 2], d[4 * j + 3]);
                        uint32_t p2 = pack_bf(d[4 * j + 4], d[4 * j + 5]), p3 = pack_bf(d[4 * j + 6], d[4 * j + 7]);
                        asm volatile("stmatrix.sync.aligned.m8n8.x4.shared.b16 [%0], {%1,%2,%3,%4};"
                                     ::"r"(hbase + j * CH_PITCH), "r"(p0), "r"(p1), "r"(p2), "r"(p3) : "memory");
                    }
                    fence_async_smem();
                    __syncwarp();
                    if (lane == 0) mbar_arrive(bars + 8 * BAR_HW);
                    const uint32_t xbase = sb + SM_XRES + (lane >> 4) * 1024 + (wq * 16 + (lane & 15)) * 16;
#pragma unroll
                    for (int j = 0; j < 16; j += 2) {
                        uint32_t p0, p1, p2, p3;
                        asm volatile("ldmatrix.sync.aligned.m8n8.x4.shared.b16 {%0,%1,%2,%3}, [%4];"
                                     : "=r"(p0), "=r"(p1), "=r"(p2), "=r"(p3) : "r"(xbase + j * 1024) : "memory");
                        d[4 * j + 0] = bf_lo(p0); d[4 * j + 1] = bf_hi(p0); d[4 * j + 2] = bf_lo(p1); d[4 * j + 3] = bf_hi(p1);
                        d[4 * j + 4] = bf_lo(p2); d[4 * j + 5] = bf_hi(p2); d[4 * j + 6] = bf_lo(p3); d[4 * j + 7] = bf_hi(p3);
                    }
                }
            }
            mma_loop(1, d, sb, slot, wpar, tid);
            bar_sync(2, 128);
            {
                const uint32_t obase = sb + SM_ACT + ((lane >> 4) * 8 + (lane & 7)) * OUT_PITCH + (wq * 16 + ((lane >> 3) & 1) * 8) * 2;
#pragma unroll
                for (int j = 0; j < 16; j += 2) {
                    uint32_t p0 = pack_bf(d[4 * j + 0], d[4 * j + 1]), p1 = pack_bf(d[4 * j + 2], d[4 * j + 3]);
                    uint32_t p2 = pack_bf(d[4 * j + 4], d[4 * j + 5]), p3 = pack_bf(d[4 * j + 6], d[4 * j + 7]);
                    asm volatile("stmatrix.sync.aligned.m8n8.x4.trans.shared.b16 [%0], {%1,%2,%3,%4};"
                                 ::"r"(obase + j * 8 * OUT_PITCH), "r"(p0), "r"(p1), "r"(p2), "r"(p3) : "memory");
                }
                bar_sync(2, 128);
                const int oc0 = tid >> 3, seg = tid & 7;
                __nv_bfloat16* dst = out + ((size_t)(b * C + oc0) * HW + r) * HW + seg * 8;
#pragma unroll
                for (int i = 0; i < 8; i++) {
                    const uint4 o = *reinterpret_cast<const uint4*>(smem + SM_ACT + (oc0 + 16 * i) * OUT_PITCH + seg * 16);
                    *reinterpret_cast<uint4*>(dst + (size_t)i * 16 * HW * HW) = o;
                }
                if (tid == 0) { g_epoch[cta] = epoch; TL(20); TLG(21); }
            }
        } else {
            const int par = wg - 1;
            const int csel = wq >> 1, px = (wq & 1) * 32 + lane;
#pragma unroll 1
            for (int conv = 0; conv < 2; conv++) {
                if (conv == 1) mbar_wait(bars + 8 * BAR_OWN, 0);
                mbar_wait(bars + 8 * BAR_STATS, conv);
#pragma unroll 1
                for (int s = par; s < NSTAGE; s += 2) {
                    int ky, kc;
                    stage_pos(conv, s, ky, kc);
                    const int irow = r - 1 + ky;
                    if (irow >= 0 && irow < HW) {
                        if (conv == 1 && ky != 1) mbar_wait(bars + 8 * (BAR_HALO + (ky >> 1)), 0);
                        const int chunk = 2 * kc + csel;
                        uint4* p = reinterpret_cast<uint4*>(smem + SM_ACT + ky * ROW_BYTES + chunk * CH_PITCH + (1 + px) * 16);
                        const float4* cf = reinterpret_cast<const float4*>(smem + SM_COEF + chunk * 64);
                        const uint4 u = *p;
                        const float4 a0 = cf[0], a1 = cf[1], b0 = cf[2], b1 = cf[3];
                        uint4 o;
                        o.x = pack_bf(silu_half(fmaf(bf_lo(u.x), a0.x, b0.x)), silu_half(fmaf(bf_hi(u.x), a0.y, b0.y)));
                        o.y = pack_bf(silu_half(fmaf(bf_lo(u.y), a0.z, b0.z)), silu_half(fmaf(bf_hi(u.y), a0.w, b0.w)));
                        o.z = pack_bf(silu_half(fmaf(bf_lo(u.z), a1.x, b1.x)), silu_half(fmaf(bf_hi(u.z), a1.y, b1.y)));
                        o.w = pack_bf(silu_half(fmaf(bf_lo(u.w), a1.z, b1.z)), silu_half(fmaf(bf_hi(u.w), a1.w, b1.w)));
                        *p = o;
                        fence_async_smem();
                    }
                    __syncwarp();
                    if (lane == 0) mbar_arrive(bars + 8 * (BAR_ACT + s));
                }
            }
        }
    } else if (warp == 12) {
        {
            const int l16 = lane & 15, cv = lane >> 4;
            const int oc = (cta & 15) * 8 + (l16 & 7), kc = cta >> 4, hh = l16 >> 3;
            const uint4* src = reinterpret_cast<const uint4*>((cv ? w2 : w1) + ((size_t)oc * C + kc * 16 + hh * 8) * 9);
            uint32_t w[36];
#pragma unroll
            for (int i = 0; i < 9; i++) {
                const uint4 t = __ldg(src + i);
                w[4 * i] = t.x; w[4 * i + 1] = t.y; w[4 * i + 2] = t.z; w[4 * i + 3] = t.w;
            }
            const unsigned epoch = ld_relaxed(&g_epoch[cta]) + 1;
            bar_sync(0, NTHREADS);
            unsigned char* dst = g_wt + (size_t)cv * 72 * STEP_BYTES + hh * 2048 + oc * 16;
#pragma unroll
            for (int tap = 0; tap < 9; tap++) {
                uint32_t o[4];
#pragma unroll
                for (int m = 0; m < 4; m++) {
                    const int i0 = 18 * m + tap, i1 = i0 + 9;
                    const uint32_t sel = ((i0 & 1) ? 0x32u : 0x10u) | ((i1 & 1) ? 0x7600u : 0x5400u);
                    o[m] = __byte_perm(w[i0 >> 1], w[i1 >> 1], sel);
                }
                const int ky = tap / 3, kx = tap % 3;
                const int kyo = (ky == 1) ? 0 : (ky == 0 ? 1 : 2);
                const int step = cv ? ((kyo * 8 + kc) * 3 + kx) : ((kc * 3 + ky) * 3 + kx);
                *reinterpret_cast<uint4*>(dst + step * STEP_BYTES) = make_uint4(o[0], o[1], o[2], o[3]);
            }
            if (lane == 0) TL(4);
            fence_async_all();
            __syncwarp();
            if (lane == 0) { fence_gpu(); st_relaxed(&g_wflag[cta], epoch); TL(5); }
            unsigned it = 0;
            while (true) {
                const uint4 f = ld_relaxed_v4(&g_wflag[lane * 4]);
                const bool ok = (f.x == epoch) & (f.y == epoch) & (f.z == epoch) & (f.w == epoch);
                if (__all_sync(0xffffffffu, ok)) break;
                if (++it > SPIN_LIMIT) break;
            }
            fence_gpu();
            fence_async_all();
            __syncwarp();
        }
        if (lane == 0) {
            TL(6);
            int slot = 0; uint32_t par = 1;
#pragma unroll 1
            for (int g = 0; g < 2 * NSTAGE; g++) {
                mbar_wait(bars + 8 * (BAR_WEMPTY + slot), par);
                mbar_expect(bars + 8 * (BAR_WFULL + slot), STAGE_BYTES);
                bulk_g2s(sb + SM_W + slot * STAGE_BYTES, g_wt + (size_t)g * STAGE_BYTES, STAGE_BYTES, bars + 8 * (BAR_WFULL + slot));
                if (++slot == NS) { slot = 0; par ^= 1; }
            }
        }
    } else if (warp == 13) {
        const uint2 ga1 = __ldg(reinterpret_cast<const uint2*>(g1) + lane), bt1 = __ldg(reinterpret_cast<const uint2*>(be1) + lane);
        const uint2 ga2 = __ldg(reinterpret_cast<const uint2*>(g2) + lane), bt2 = __ldg(reinterpret_cast<const uint2*>(be2) + lane);
        const unsigned tag = (ld_relaxed(&g_epoch[cta]) + 1) & 3;
        bar_sync(0, NTHREADS);
#pragma unroll 1
        for (int conv = 0; conv < 2; conv++) {
            const unsigned* src = &g_stats[((conv * NB + b) * 8 + (lane >> 2)) * HW + (lane & 3) * 4];
            uint4 f[4];
            unsigned it = 0;
            while (true) {
#pragma unroll
                for (int i = 0; i < 4; i++) f[i] = ld_relaxed_v4(src + 16 * i);
                unsigned bad = 0;
#pragma unroll
                for (int i = 0; i < 4; i++) bad |= (f[i].x ^ tag) | (f[i].y ^ tag) | (f[i].z ^ tag) | (f[i].w ^ tag);
                if (__all_sync(0xffffffffu, (bad & 3) == 0)) break;
                if (++it > SPIN_LIMIT) break;
            }
            if (lane == 0) TL(7 + conv * 8);
            float p[4];
#pragma unroll
            for (int i = 0; i < 4; i++)
                p[i] = (__uint_as_float(f[i].x) + __uint_as_float(f[i].y)) + (__uint_as_float(f[i].z) + __uint_as_float(f[i].w));
            float t = (p[0] + p[1]) + (p[2] + p[3]);
            t += __shfl_xor_sync(0xffffffffu, t, 1);
            t += __shfl_xor_sync(0xffffffffu, t, 2);
            const float o = __shfl_xor_sync(0xffffffffu, t, 4);
            const float sum = (lane & 4) ? o : t, sq = (lane & 4) ? t : o;
            const float inv_n = 1.0f / (32.0f * HW * HW);
            const float mean = sum * inv_n;
            const float var = fmaxf(fmaf(-mean, mean, sq * inv_n), 0.f);
            const float rs = 0.5f * rsqrtf(var + 1e-5f);
            const uint2 ga = conv ? ga2 : ga1, bt = conv ? bt2 : bt1;
            float4 a, bb;
            a.x = rs * bf_lo(ga.x); a.y = rs * bf_hi(ga.x); a.z = rs * bf_lo(ga.y); a.w = rs * bf_hi(ga.y);
            bb.x = fmaf(-mean, a.x, 0.5f * bf_lo(bt.x)); bb.y = fmaf(-mean, a.y, 0.5f * bf_hi(bt.x));
            bb.z = fmaf(-mean, a.z, 0.5f * bf_lo(bt.y)); bb.w = fmaf(-mean, a.w, 0.5f * bf_hi(bt.y));
            float4* cf = reinterpret_cast<float4*>(smem + SM_COEF + (lane >> 1) * 64 + (lane & 1) * 16);
            cf[0] = a; cf[2] = bb;
            __syncwarp();
            if (lane == 0) mbar_arrive(bars + 8 * BAR_STATS);
        }
    } else {
        const unsigned epoch = ld_relaxed(&g_epoch[cta]) + 1;
        bar_sync(0, NTHREADS);
        mbar_wait(bars + 8 * BAR_STATS, 0);
        {
            float e0 = 0.f, e1 = 0.f;
            const uint32_t* wsrc = reinterpret_cast<const uint32_t*>(w_emb) + r;
            const unsigned short* tsrc = reinterpret_cast<const unsigned short*>(t_emb) + b * E;
#pragma unroll 8
            for (int i = 0; i < E / 32; i++) {
                const int e = i * 32 + lane;
                const uint32_t wv = __ldg(wsrc + e * (C / 2));
                const float t = __uint_as_float((uint32_t)__ldg(tsrc + e) << 16);
                const float sv = silu_half(0.5f * t);
                e0 = fmaf(sv, bf_lo(wv), e0); e1 = fmaf(sv, bf_hi(wv), e1);
            }
            float give = (lane < 16) ? e1 : e0, keep = (lane < 16) ? e0 : e1;
            keep += __shfl_xor_sync(0xffffffffu, give, 16);
#pragma unroll
            for (int m = 8; m >= 1; m >>= 1) keep += __shfl_xor_sync(0xffffffffu, keep, m);
            if ((lane & 15) == 0) st_relaxed(&g_emb[b * C + 2 * r + (lane >> 4)], tag_f(keep, epoch & 3));
            unsigned it = 0;
            uint4 f;
            while (true) {
                f = ld_relaxed_v4(&g_emb[b * C + lane * 4]);
                const unsigned tag = epoch & 3;
                const unsigned bad = (f.x ^ tag) | (f.y ^ tag) | (f.z ^ tag) | (f.w ^ tag);
                if (__all_sync(0xffffffffu, (bad & 3) == 0)) break;
                if (++it > SPIN_LIMIT) break;
            }
            *reinterpret_cast<uint4*>(smem + SM_EMB + lane * 16) = f;
            __syncwarp();
            if (lane == 0) mbar_arrive(bars + 8 * BAR_EMB);
        }
        if (lane == 0) {
            mbar_wait(bars + 8 * BAR_HW, 0);
            asm volatile("cp.async.bulk.global.shared::cta.bulk_group [%0], [%1], %2;"
                         ::"l"(g_h + (size_t)cta * ROW_BYTES), "r"(sb + SM_ACT + ROW_BYTES), "r"(ROW_BYTES) : "memory");
            asm volatile("cp.async.bulk.commit_group;" ::: "memory");
            asm volatile("cp.async.bulk.wait_group.read 0;" ::: "memory");
            mbar_arrive(bars + 8 * BAR_OWN);
            TL(12);
            asm volatile("cp.async.bulk.wait_group 0;" ::: "memory");
            fence_async_all();
            fence_gpu();
            st_relaxed(&g_hflag[cta], epoch);
            TL(13);
        }
        __syncwarp();
        if (lane < 2) {
            const int irow = r - 1 + 2 * lane;
            if (irow >= 0 && irow < HW) {
                const int nb = cta - 1 + 2 * lane;
                unsigned it = 0;
                while (ld_relaxed(&g_hflag[nb]) != epoch) { if (++it > SPIN_LIMIT) break; }
                fence_gpu();
                fence_async_all();
                mbar_expect(bars + 8 * (BAR_HALO + lane), ROW_BYTES);
                bulk_g2s(sb + SM_ACT + 2 * lane * ROW_BYTES, g_h + (size_t)nb * ROW_BYTES, ROW_BYTES, bars + 8 * (BAR_HALO + lane));
                if (lane == 0) TL(14);
            }
        }
    }
}

}

extern "C" void kernel_launch(void* const* d_in, const int* in_sizes, int n_in, void* d_out, int out_size) {
    (void)in_sizes; (void)n_in; (void)out_size;
    static bool init = false;
    if (!init) {
        cudaFuncSetAttribute(resblock_kernel, cudaFuncAttributeMaxDynamicSharedMemorySize, SM_TOTAL);
        init = true;
    }
    resblock_kernel<<<NCTA, NTHREADS, SM_TOTAL>>>(
        (const __nv_bfloat16*)d_in[0], (const __nv_bfloat16*)d_in[1], (const __nv_bfloat16*)d_in[2],
        (const __nv_bfloat16*)d_in[3], (const __nv_bfloat16*)d_in[4], (const __nv_bfloat16*)d_in[5],
        (const __nv_bfloat16*)d_in[6], (const __nv_bfloat16*)d_in[7], (const __nv_bfloat16*)d_in[8],
        (__nv_bfloat16*)d_out);
}
```

```cpp
#include <cuda_runtime.h>
#include <cuda_bf16.h>
#include <stdint.h>

namespace {

constexpr int C = 128, HW = 64, NB = 2, E = 768;
constexpr int NCTA = NB * HW;
constexpr int NTHREADS = 15 * 32;
constexpr int CH_PITCH = 66 * 16;
constexpr int ROW_BYTES = 16 * CH_PITCH;
constexpr int STEP_BYTES = 4096;
constexpr int STAGE_BYTES = 3 * STEP_BYTES;
constexpr int NSTAGE = 24;
constexpr int NS = 13;

constexpr int SM_ACT = 0;
constexpr int SM_XRES = SM_ACT + 3 * ROW_BYTES;
constexpr int SM_W = SM_XRES + 16384;
constexpr int SM_COEF = SM_W + NS * STAGE_BYTES;
constexpr int SM_EMB = SM_COEF + 1024;
constexpr int SM_RED = SM_EMB + 512;
constexpr int SM_BAR = SM_RED + 128;
constexpr int BAR_WFULL = 0, BAR_WEMPTY = NS, BAR_ACT = 2 * NS, BAR_STATS = BAR_ACT + NSTAGE,
              BAR_HW = BAR_STATS + 1, BAR_OWN = BAR_HW + 1, BAR_HALO = BAR_OWN + 1  ,
              BAR_EMB = BAR_HALO + 2, NBAR = BAR_EMB + 1;
constexpr int SM_TOTAL = SM_BAR + NBAR * 8;
static_assert(SM_TOTAL <= 232448, "smem");
constexpr int OUT_PITCH = 144;

constexpr unsigned SPIN_LIMIT = 1u << 16;

__device__ __align__(128) unsigned char g_wt[2 * 72 * STEP_BYTES];
__device__ __align__(128) unsigned char g_h[NCTA * ROW_BYTES];
__device__ __align__(128) float g_acc[2 * 2 * NB * 32];
__device__ __align__(128) unsigned g_emb[NB * C];
__device__ __align__(128) unsigned g_wcnt[32];
__device__ __align__(128) unsigned g_hflag[NCTA * 32];
__device__ __align__(128) unsigned g_epoch[NCTA];
#define TL(i) do {} while (0)
#define TLG(i) do {} while (0)

__device__ __forceinline__ uint32_t smem_u32(const void* p) { return (uint32_t)__cvta_generic_to_shared(p); }
__device__ __forceinline__ void mbar_init(uint32_t bar, int cnt) {
    asm volatile("mbarrier.init.shared::cta.b64 [%0], %1;" ::"r"(bar), "r"(cnt) : "memory");
}
__device__ __forceinline__ void mbar_arrive(uint32_t bar) {
    asm volatile("mbarrier.arrive.shared::cta.b64 _, [%0];" ::"r"(bar) : "memory");
}
__device__ __forceinline__ void mbar_expect(uint32_t bar, uint32_t bytes) {
    asm volatile("mbarrier.arrive.expect_tx.shared::cta.b64 _, [%0], %1;" ::"r"(bar), "r"(bytes) : "memory");
}
__device__ __forceinline__ bool mbar_try(uint32_t bar, uint32_t par) {
    uint32_t ok;
    asm volatile("{\n.reg .pred p;\nmbarrier.try_wait.parity.shared::cta.b64 p, [%1], %2;\nselp.u32 %0, 1, 0, p;\n}"
                 : "=r"(ok) : "r"(bar), "r"(par) : "memory");
    return ok;
}
__device__ __forceinline__ void mbar_wait(uint32_t bar, uint32_t par) {
    unsigned it = 0;
    while (!mbar_try(bar, par)) { if (++it > SPIN_LIMIT) break; }
}
__device__ __forceinline__ void fence_async_smem() { asm volatile("fence.proxy.async.shared::cta;" ::: "memory"); }
__device__ __forceinline__ void fence_async_global() { asm volatile("fence.proxy.async.global;" ::: "memory"); }
__device__ __forceinline__ bool mbar_test(uint32_t bar, uint32_t par) {
    uint32_t ok;
    asm volatile("{\n.reg .pred p;\nmbarrier.test_wait.parity.shared::cta.b64 p, [%1], %2;\nselp.u32 %0, 1, 0, p;\n}"
                 : "=r"(ok) : "r"(bar), "r"(par) : "memory");
    return ok;
}
__device__ __forceinline__ void red_add4(float* p, float a, float b, float c, float d) {
    asm volatile("red.relaxed.gpu.global.add.v4.f32 [%0], {%1,%2,%3,%4};" ::"l"(p), "f"(a), "f"(b), "f"(c), "f"(d) : "memory");
}
__device__ __forceinline__ unsigned ld_acquire(const void* p) {
    unsigned v;
    asm volatile("ld.acquire.gpu.global.u32 %0, [%1];" : "=r"(v) : "l"(p) : "memory");
    return v;
}
__device__ __forceinline__ unsigned opaque(unsigned v) { asm volatile("" : "+r"(v)); return v; }
__device__ __forceinline__ void bar_sync(int id, int n) { asm volatile("bar.sync %0, %1;" ::"r"(id), "r"(n) : "memory"); }
__device__ __forceinline__ void bulk_g2s(uint32_t dst, const void* src, uint32_t bytes, uint32_t bar) {
    asm volatile("cp.async.bulk.shared::cluster.global.mbarrier::complete_tx::bytes [%0], [%1], %2, [%3];"
                 ::"r"(dst), "l"(src), "r"(bytes), "r"(bar) : "memory");
}
__device__ __forceinline__ uint4 ld_relaxed_v4(const void* p) {
    uint4 v;
    asm volatile("ld.relaxed.gpu.global.v4.u32 {%0,%1,%2,%3}, [%4];" : "=r"(v.x), "=r"(v.y), "=r"(v.z), "=r"(v.w) : "l"(p) : "memory");
    return v;
}
__device__ __forceinline__ unsigned ld_relaxed(const void* p) {
    unsigned v;
    asm volatile("ld.relaxed.gpu.global.u32 %0, [%1];" : "=r"(v) : "l"(p) : "memory");
    return v;
}
__device__ __forceinline__ void st_relaxed(void* p, unsigned v) {
    asm volatile("st.relaxed.gpu.global.u32 [%0], %1;" ::"l"(p), "r"(v) : "memory");
}
__device__ __forceinline__ void fence_gpu() { asm volatile("fence.acq_rel.gpu;" ::: "memory"); }
__device__ __forceinline__ float bf_lo(uint32_t u) { return __uint_as_float(u << 16); }
__device__ __forceinline__ float bf_hi(uint32_t u) { return __uint_as_float(u & 0xffff0000u); }
__device__ __forceinline__ uint32_t pack_bf(float lo, float hi) {
    uint32_t r;
    asm("cvt.rn.bf16x2.f32 %0, %1, %2;" : "=r"(r) : "f"(hi), "f"(lo));
    return r;
}
__device__ __forceinline__ float tanh_fast(float x) {
    float r;
    asm("tanh.approx.f32 %0, %1;" : "=f"(r) : "f"(x));
    return r;
}
__device__ __forceinline__ float silu_half(float h) { return fmaf(h, tanh_fast(h), h); }
__device__ __forceinline__ unsigned tag_f(float v, unsigned tag) { return (__float_as_uint(v) & ~3u) | tag; }

#define R8(o) "+f"(d[o]), "+f"(d[o + 1]), "+f"(d[o + 2]), "+f"(d[o + 3]), "+f"(d[o + 4]), "+f"(d[o + 5]), "+f"(d[o + 6]), "+f"(d[o + 7])
__device__ __forceinline__ void wgmma128(float (&d)[64], uint64_t a, uint64_t b) {
    asm volatile(
        "wgmma.mma_async.sync.aligned.m64n128k16.f32.bf16.bf16 "
        "{%0,%1,%2,%3,%4,%5,%6,%7,%8,%9,%10,%11,%12,%13,%14,%15,%16,%17,%18,%19,%20,%21,%22,%23,%24,%25,%26,%27,%28,%29,%30,%31,"
        "%32,%33,%34,%35,%36,%37,%38,%39,%40,%41,%42,%43,%44,%45,%46,%47,%48,%49,%50,%51,%52,%53,%54,%55,%56,%57,%58,%59,%60,%61,%62,%63},"
        " %64, %65, 1, 1, 1, 0, 0;"
        : R8(0), R8(8), R8(16), R8(24), R8(32), R8(40), R8(48), R8(56)
        : "l"(a), "l"(b));
}
__device__ __forceinline__ uint64_t mkdesc(uint32_t addr, uint32_t lbo, uint32_t sbo) {
    return (uint64_t)((addr & 0x3FFFF) >> 4) | ((uint64_t)(lbo >> 4) << 16) | ((uint64_t)(sbo >> 4) << 32);
}
__device__ __forceinline__ void stage_pos(int conv, int s, int& ky, int& kc) {
    if (conv == 0) { kc = s / 3; ky = s - 3 * kc; }
    else { int o = s >> 3; kc = s & 7; ky = (o == 0) ? 1 : (o == 1 ? 0 : 2); }
}

__device__ __forceinline__ void fence_acc(float (&d)[64]) {
#pragma unroll
    for (int i = 0; i < 64; i++) asm volatile("" : "+f"(d[i])::"memory");
}
__device__ __forceinline__ void mma_loop(int conv, float (&d)[64], uint32_t sb, int& slot, uint32_t& wpar, int tid) {
    const uint32_t bars = sb + SM_BAR;
    const int lane = tid & 31;
    int prev = -1;
    int ky, kc;
    stage_pos(conv, 0, ky, kc);
    uint64_t da = mkdesc(sb + SM_ACT + ky * ROW_BYTES + kc * 2 * CH_PITCH, CH_PITCH, 128);
    uint64_t db = mkdesc(sb + SM_W + slot * STAGE_BYTES, 2048, 128);
    mbar_wait(bars + 8 * BAR_ACT, conv);
    if (tid == 0) TL(8 + conv * 8);
    mbar_wait(bars + 8 * (BAR_WFULL + slot), wpar);
    if (tid == 0) TL(9 + conv * 8);
    fence_acc(d);
#pragma unroll 1
    for (int s = 0; s < NSTAGE; s++) {
        asm volatile("wgmma.fence.sync.aligned;" ::: "memory");
        wgmma128(d, da, db);
        const int cur = slot;
        if (++slot == NS) { slot = 0; wpar ^= 1; }
        const int sn = (s + 1 < NSTAGE) ? s + 1 : s;
        stage_pos(conv, sn, ky, kc);
        const uint64_t nda = mkdesc(sb + SM_ACT + ky * ROW_BYTES + kc * 2 * CH_PITCH, CH_PITCH, 128);
        const uint64_t ndb = mkdesc(sb + SM_W + slot * STAGE_BYTES, 2048, 128);
        const bool okA = mbar_test(bars + 8 * (BAR_ACT + sn), conv);
        const bool okW = mbar_test(bars + 8 * (BAR_WFULL + slot), wpar);
        wgmma128(d, da + 1, db + (STEP_BYTES >> 4));
        wgmma128(d, da + 2, db + 2 * (STEP_BYTES >> 4));
        asm volatile("wgmma.commit_group.sync.aligned;" ::: "memory");
        asm volatile("wgmma.wait_group.sync.aligned 1;" ::: "memory");
        if (prev >= 0 && lane == 0) mbar_arrive(bars + 8 * (BAR_WEMPTY + prev));
        prev = cur;
        if (!(okA && okW) && s + 1 < NSTAGE) {
            mbar_wait(bars + 8 * (BAR_ACT + sn), conv);
            mbar_wait(bars + 8 * (BAR_WFULL + slot), wpar);
        }
        if (tid == 0) TL(32 + conv * 24 + s);
        da = nda; db = ndb;
    }
    asm volatile("wgmma.wait_group.sync.aligned 0;" ::: "memory");
    fence_acc(d);
    if (lane == 0) mbar_arrive(bars + 8 * (BAR_WEMPTY + prev));
    if (tid == 0) TL(10 + conv * 8);
}

__global__ void __launch_bounds__(NTHREADS, 1)
resblock_kernel(const __nv_bfloat16* __restrict__ x, const __nv_bfloat16* __restrict__ t_emb,
                const __nv_bfloat16* __restrict__ g1, const __nv_bfloat16* __restrict__ be1,
                const __nv_bfloat16* __restrict__ w1, const __nv_bfloat16* __restrict__ w_emb,
                const __nv_bfloat16* __restrict__ g2, const __nv_bfloat16* __restrict__ be2,
                const __nv_bfloat16* __restrict__ w2, __nv_bfloat16* __restrict__ out) {
    extern __shared__ __align__(128) unsigned char smem[];
    const uint32_t sb = smem_u32(smem);
    const uint32_t bars = sb + SM_BAR;
    const int tid = threadIdx.x, warp = tid >> 5, lane = tid & 31;
    const int cta = blockIdx.x, b = cta >> 6, r = cta & 63;
    if (tid == 0) { TL(0); TLG(1); }

    if (warp < 12) {
        const int wg = warp >> 2, wq = warp & 3;
        const int row = r - 1 + wg;
        const bool valid = (row >= 0) && (row < HW);
        uint32_t v[32];
        {
            const uint32_t* src = reinterpret_cast<const uint32_t*>(x + ((size_t)(b * C + wq * 32) * HW + (valid ? row : r)) * HW) + lane;
#pragma unroll
            for (int i = 0; i < 32; i++) v[i] = __ldg(src + (size_t)i * (HW * HW / 2));
        }
        unsigned epoch = ld_relaxed(&g_epoch[cta]);
        if (tid < 96) {
            int ch = tid >> 1;
            *reinterpret_cast<uint4*>(smem + SM_ACT + ch * CH_PITCH + (tid & 1) * 65 * 16) = make_uint4(0, 0, 0, 0);
        }
        if (tid >= 256 && tid < 256 + NBAR) {
            const int i = tid - 256;
            const bool four = (i >= BAR_WEMPTY && i < BAR_STATS) || i == BAR_HW;
            mbar_init(bars + 8 * i, four ? 4 : 1);
            fence_async_smem();
        }
        bar_sync(0, NTHREADS);
        epoch = opaque(epoch) + 1;
        if (wg == 1) {
            float s = 0.f, q = 0.f, s2 = 0.f, q2 = 0.f;
#pragma unroll
            for (int i = 0; i < 32; i++) {
                float lo = bf_lo(v[i]), hi = bf_hi(v[i]);
                s += lo; q = fmaf(lo, lo, q);
                s2 += hi; q2 = fmaf(hi, hi, q2);
            }
            s += s2; q += q2;
            float give = (lane < 16) ? q : s, keep = (lane < 16) ? s : q;
            keep += __shfl_xor_sync(0xffffffffu, give, 16);
            if (tid == 128) TL(2);
#pragma unroll
            for (int m = 8; m >= 1; m >>= 1) keep += __shfl_xor_sync(0xffffffffu, keep, m);
            float* red = reinterpret_cast<float*>(smem + SM_RED);
            if ((lane & 15) == 0) red[wq * 2 + (lane >> 4)] = keep;
            bar_sync(3, 128);
            if (tid < 128 + 4) {
                const float2 p = *reinterpret_cast<const float2*>(red + lane * 2);
                red_add4(&g_acc[(((epoch & 1) * 2 + 0) * NB + b) * 32 + lane * 4], 1.f, p.x, p.y, 1.f);
            }
            if (tid == 128) TL(3);
        }
        {
            const int sw = (lane >> 2) & 1;
            const uint32_t selA = sw ? 0x7632u : 0x5410u, selB = sw ? 0x5410u : 0x7632u;
            const int pxA = 2 * lane + sw, pxB = 2 * lane + (sw ^ 1);
#pragma unroll
            for (int c4 = 0; c4 < 4; c4++) {
                uint4 a, bb;
                a.x = __byte_perm(v[c4 * 8 + 0], v[c4 * 8 + 1], selA); bb.x = __byte_perm(v[c4 * 8 + 0], v[c4 * 8 + 1], selB);
                a.y = __byte_perm(v[c4 * 8 + 2], v[c4 * 8 + 3], selA); bb.y = __byte_perm(v[c4 * 8 + 2], v[c4 * 8 + 3], selB);
                a.z = __byte_perm(v[c4 * 8 + 4], v[c4 * 8 + 5], selA); bb.z = __byte_perm(v[c4 * 8 + 4], v[c4 * 8 + 5], selB);
                a.w = __byte_perm(v[c4 * 8 + 6], v[c4 * 8 + 7], selA); bb.w = __byte_perm(v[c4 * 8 + 6], v[c4 * 8 + 7], selB);
                if (!valid) { a = make_uint4(0, 0, 0, 0); bb = a; }
                const int chunk = wq * 4 + c4;
                unsigned char* dst = smem + SM_ACT + wg * ROW_BYTES + chunk * CH_PITCH + 16;
                *reinterpret_cast<uint4*>(dst + pxA * 16) = a;
                *reinterpret_cast<uint4*>(dst + pxB * 16) = bb;
                if (wg == 1) {
                    unsigned char* d2 = smem + SM_XRES + chunk * 1024;
                    *reinterpret_cast<uint4*>(d2 + pxA * 16) = a;
                    *reinterpret_cast<uint4*>(d2 + pxB * 16) = bb;
                }
            }
        }
        fence_async_smem();
        bar_sync(1, 384);

        if (wg == 0) {
            float d[64];
#pragma unroll
            for (int i = 0; i < 64; i++) d[i] = 0.f;
            const uint32_t frag_off = ((lane >> 4) * CH_PITCH) + (1 + wq * 16 + (lane & 15)) * 16;
            int slot = 0; uint32_t wpar = 0;
            mma_loop(0, d, sb, slot, wpar, tid);
            {
                {
                    mbar_wait(bars + 8 * BAR_EMB, 0);
                    const float* embs = reinterpret_cast<const float*>(smem + SM_EMB);
                    float st[8];
#pragma unroll
                    for (int g = 0; g < 4; g++) {
                        float s = 0.f, q = 0.f, s2 = 0.f, q2 = 0.f;
#pragma unroll
                        for (int jj = 0; jj < 4; jj++) {
                            const int j = g * 4 + jj;
                            const float2 e = *reinterpret_cast<const float2*>(embs + 8 * j + 2 * (lane & 3));
                            d[4 * j + 0] += e.x; d[4 * j + 1] += e.y; d[4 * j + 2] += e.x; d[4 * j + 3] += e.y;
                            s += d[4 * j + 0]; q = fmaf(d[4 * j + 0], d[4 * j + 0], q);
                            s2 += d[4 * j + 1]; q2 = fmaf(d[4 * j + 1], d[4 * j + 1], q2);
                            s += d[4 * j + 2]; q = fmaf(d[4 * j + 2], d[4 * j + 2], q);
                            s2 += d[4 * j + 3]; q2 = fmaf(d[4 * j + 3], d[4 * j + 3], q2);
                        }
                        st[2 * g] = s + s2; st[2 * g + 1] = q + q2;
                    }
                    {
                        const bool h16 = lane & 16, h8 = lane & 8, h4 = lane & 4;
                        float a[4];
#pragma unroll
                        for (int i = 0; i < 4; i++) {
                            float give = h16 ? st[i] : st[i + 4], keep = h16 ? st[i + 4] : st[i];
                            a[i] = keep + __shfl_xor_sync(0xffffffffu, give, 16);
                        }
                        float c2[2];
#pragma unroll
                        for (int i = 0; i < 2; i++) {
                            float give = h8 ? a[i] : a[i + 2], keep = h8 ? a[i + 2] : a[i];
                            c2[i] = keep + __shfl_xor_sync(0xffffffffu, give, 8);
                        }
                        float give = h4 ? c2[0] : c2[1], keep = h4 ? c2[1] : c2[0];
                        float t = keep + __shfl_xor_sync(0xffffffffu, give, 4);
                        t += __shfl_xor_sync(0xffffffffu, t, 2);
                        t += __shfl_xor_sync(0xffffffffu, t, 1);
                        float* red = reinterpret_cast<float*>(smem + SM_RED);
                        if ((lane & 3) == 0) red[(lane >> 2) * 4 + wq] = t;
                        bar_sync(2, 128);
                        if (tid < 4) {
                            const float4 p = *reinterpret_cast<const float4*>(red + tid * 8);
                            const float4 p2 = *reinterpret_cast<const float4*>(red + tid * 8 + 4);
                            red_add4(&g_acc[(((epoch & 1) * 2 + 1) * NB + b) * 32 + tid * 4], 1.f,
                                     (p.x + p.y) + (p.z + p.w), (p2.x + p2.y) + (p2.z + p2.w), 1.f);
                        }
                        if (tid == 0) TL(11);
                    }
                    const uint32_t hbase = sb + SM_ACT + ROW_BYTES + frag_off;
                    uint32_t* hg = reinterpret_cast<uint32_t*>(g_h + (size_t)cta * ROW_BYTES + (1 + wq * 16) * 16) + lane;
#pragma unroll
                    for (int j = 0; j < 16; j += 2) {
                        uint32_t p0 = pack_bf(d[4 * j + 0], d[4 * j + 1]), p1 = pack_bf(d[4 * j + 2], d[4 * j + 3]);
                        uint32_t p2 = pack_bf(d[4 * j + 4], d[4 * j + 5]), p3 = pack_bf(d[4 * j + 6], d[4 * j + 7]);
                        asm volatile("stmatrix.sync.aligned.m8n8.x4.shared.b16 [%0], {%1,%2,%3,%4};"
                                     ::"r"(hbase + j * CH_PITCH), "r"(p0), "r"(p1), "r"(p2), "r"(p3) : "memory");
                        hg[j * (CH_PITCH / 4)] = p0; hg[j * (CH_PITCH / 4) + 32] = p1;
                        hg[(j + 1) * (CH_PITCH / 4)] = p2; hg[(j + 1) * (CH_PITCH / 4) + 32] = p3;
                    }
                    __syncwarp();
                    if (lane == 0) mbar_arrive(bars + 8 * BAR_HW);
                    if (tid == 0) TL(12);
                    const uint32_t xbase = sb + SM_XRES + (lane >> 4) * 1024 + (wq * 16 + (lane & 15)) * 16;
#pragma unroll
                    for (int j = 0; j < 16; j += 2) {
                        uint32_t p0, p1, p2, p3;
                        asm volatile("ldmatrix.sync.aligned.m8n8.x4.shared.b16 {%0,%1,%2,%3}, [%4];"
                                     : "=r"(p0), "=r"(p1), "=r"(p2), "=r"(p3) : "r"(xbase + j * 1024) : "memory");
                        d[4 * j + 0] = bf_lo(p0); d[4 * j + 1] = bf_hi(p0); d[4 * j + 2] = bf_lo(p1); d[4 * j + 3] = bf_hi(p1);
                        d[4 * j + 4] = bf_lo(p2); d[4 * j + 5] = bf_hi(p2); d[4 * j + 6] = bf_lo(p3); d[4 * j + 7] = bf_hi(p3);
                    }
                }
            }
            mma_loop(1, d, sb, slot, wpar, tid);
            bar_sync(2, 128);
            {
                const uint32_t obase = sb + SM_ACT + ((lane >> 4) * 8 + (lane & 7)) * OUT_PITCH + (wq * 16 + ((lane >> 3) & 1) * 8) * 2;
#pragma unroll
                for (int j = 0; j < 16; j += 2) {
                    uint32_t p0 = pack_bf(d[4 * j + 0], d[4 * j + 1]), p1 = pack_bf(d[4 * j + 2], d[4 * j + 3]);
                    uint32_t p2 = pack_bf(d[4 * j + 4], d[4 * j + 5]), p3 = pack_bf(d[4 * j + 6], d[4 * j + 7]);
                    asm volatile("stmatrix.sync.aligned.m8n8.x4.trans.shared.b16 [%0], {%1,%2,%3,%4};"
                                 ::"r"(obase + j * 8 * OUT_PITCH), "r"(p0), "r"(p1), "r"(p2), "r"(p3) : "memory");
                }
                bar_sync(2, 128);
                const int oc0 = tid >> 3, seg = tid & 7;
                __nv_bfloat16* dst = out + ((size_t)(b * C + oc0) * HW + r) * HW + seg * 8;
#pragma unroll
                for (int i = 0; i < 8; i++) {
                    const uint4 o = *reinterpret_cast<const uint4*>(smem + SM_ACT + (oc0 + 16 * i) * OUT_PITCH + seg * 16);
                    *reinterpret_cast<uint4*>(dst + (size_t)i * 16 * HW * HW) = o;
                }
                if (tid == 0) { g_epoch[cta] = epoch; TL(20); TLG(21); }
            }
        } else {
            const int par = wg - 1;
            const int csel = wq >> 1, px = (wq & 1) * 32 + lane;
#pragma unroll 1
            for (int conv = 0; conv < 2; conv++) {
                if (conv == 1) mbar_wait(bars + 8 * BAR_HW, 0);
                mbar_wait(bars + 8 * BAR_STATS, conv);
#pragma unroll 1
                for (int s = par; s < NSTAGE; s += 2) {
                    int ky, kc;
                    stage_pos(conv, s, ky, kc);
                    const int irow = r - 1 + ky;
                    if (irow >= 0 && irow < HW) {
                        if (conv == 1 && ky != 1) mbar_wait(bars + 8 * (BAR_HALO + (ky >> 1)), 0);
                        const int chunk = 2 * kc + csel;
                        uint4* p = reinterpret_cast<uint4*>(smem + SM_ACT + ky * ROW_BYTES + chunk * CH_PITCH + (1 + px) * 16);
                        const float4* cf = reinterpret_cast<const float4*>(smem + SM_COEF + chunk * 64);
                        const uint4 u = *p;
                        const float4 a0 = cf[0], a1 = cf[1], b0 = cf[2], b1 = cf[3];
                        uint4 o;
                        o.x = pack_bf(silu_half(fmaf(bf_lo(u.x), a0.x, b0.x)), silu_half(fmaf(bf_hi(u.x), a0.y, b0.y)));
                        o.y = pack_bf(silu_half(fmaf(bf_lo(u.y), a0.z, b0.z)), silu_half(fmaf(bf_hi(u.y), a0.w, b0.w)));
                        o.z = pack_bf(silu_half(fmaf(bf_lo(u.z), a1.x, b1.x)), silu_half(fmaf(bf_hi(u.z), a1.y, b1.y)));
                        o.w = pack_bf(silu_half(fmaf(bf_lo(u.w), a1.z, b1.z)), silu_half(fmaf(bf_hi(u.w), a1.w, b1.w)));
                        *p = o;
                        fence_async_smem();
                    }
                    __syncwarp();
                    if (lane == 0) mbar_arrive(bars + 8 * (BAR_ACT + s));
                }
            }
        }
    } else if (warp == 12) {
        {
            const int l16 = lane & 15, cv = lane >> 4;
            const int oc = (cta & 15) * 8 + (l16 & 7), kc = cta >> 4, hh = l16 >> 3;
            const uint4* src = reinterpret_cast<const uint4*>((cv ? w2 : w1) + ((size_t)oc * C + kc * 16 + hh * 8) * 9);
            uint32_t w[36];
#pragma unroll
            for (int i = 0; i < 9; i++) {
                const uint4 t = __ldg(src + i);
                w[4 * i] = t.x; w[4 * i + 1] = t.y; w[4 * i + 2] = t.z; w[4 * i + 3] = t.w;
            }
            unsigned epoch = ld_relaxed(&g_epoch[cta]);
            bar_sync(0, NTHREADS);
            epoch = opaque(epoch) + 1;
            unsigned char* dst = g_wt + (size_t)cv * 72 * STEP_BYTES + hh * 2048 + oc * 16;
#pragma unroll
            for (int tap = 0; tap < 9; tap++) {
                uint32_t o[4];
#pragma unroll
                for (int m = 0; m < 4; m++) {
                    const int i0 = 18 * m + tap, i1 = i0 + 9;
                    const uint32_t sel = ((i0 & 1) ? 0x32u : 0x10u) | ((i1 & 1) ? 0x7600u : 0x5400u);
                    o[m] = __byte_perm(w[i0 >> 1], w[i1 >> 1], sel);
                }
                const int ky = tap / 3, kx = tap % 3;
                const int kyo = (ky == 1) ? 0 : (ky == 0 ? 1 : 2);
                const int step = cv ? ((kyo * 8 + kc) * 3 + kx) : ((kc * 3 + ky) * 3 + kx);
                *reinterpret_cast<uint4*>(dst + step * STEP_BYTES) = make_uint4(o[0], o[1], o[2], o[3]);
            }
            if (lane == 0) TL(4);
            __syncwarp();
            if (lane == 0) {
                asm volatile("red.release.gpu.global.add.u32 [%0], 1;" ::"l"(g_wcnt) : "memory");
                TL(5);
                unsigned it = 0;
                while ((int)(ld_acquire(g_wcnt) - epoch * NCTA) < 0) { if (++it > SPIN_LIMIT) break; }
                fence_async_global();
            }
        }
        if (lane == 0) {
            TL(6);
            int slot = 0; uint32_t par = 1;
#pragma unroll 1
            for (int g = 0; g < 2 * NSTAGE; g++) {
                mbar_wait(bars + 8 * (BAR_WEMPTY + slot), par);
                mbar_expect(bars + 8 * (BAR_WFULL + slot), STAGE_BYTES);
                bulk_g2s(sb + SM_W + slot * STAGE_BYTES, g_wt + (size_t)g * STAGE_BYTES, STAGE_BYTES, bars + 8 * (BAR_WFULL + slot));
                if (++slot == NS) { slot = 0; par ^= 1; }
            }
        }
    } else if (warp == 13) {
        const uint2 ga1 = __ldg(reinterpret_cast<const uint2*>(g1) + lane), bt1 = __ldg(reinterpret_cast<const uint2*>(be1) + lane);
        const uint2 ga2 = __ldg(reinterpret_cast<const uint2*>(g2) + lane), bt2 = __ldg(reinterpret_cast<const uint2*>(be2) + lane);
        unsigned epoch = ld_relaxed(&g_epoch[cta]);
        bar_sync(0, NTHREADS);
        epoch = opaque(epoch) + 1;
        if (r == 0) {
            g_acc[((((epoch + 1) & 1) * 2 + 0) * NB + b) * 32 + lane] = 0.f;
            g_acc[((((epoch + 1) & 1) * 2 + 1) * NB + b) * 32 + lane] = 0.f;
        }
#pragma unroll 1
        for (int conv = 0; conv < 2; conv++) {
            const float* src = &g_acc[(((epoch & 1) * 2 + conv) * NB + b) * 32 + (lane >> 3) * 4];
            uint4 f;
            unsigned it = 0;
            while (true) {
                f = ld_relaxed_v4(src);
                const bool ok = (f.x == 0x42800000u) & (f.w == 0x42800000u);
                if (__all_sync(0xffffffffu, ok)) break;
                if (++it > SPIN_LIMIT) break;
            }
            if (lane == 0) TL(7 + conv * 8);
            const float sum = __uint_as_float(f.y), sq = __uint_as_float(f.z);
            const float inv_n = 1.0f / (32.0f * HW * HW);
            const float mean = sum * inv_n;
            const float var = fmaxf(fmaf(-mean, mean, sq * inv_n), 0.f);
            const float rs = 0.5f * rsqrtf(var + 1e-5f);
            const uint2 ga = conv ? ga2 : ga1, bt = conv ? bt2 : bt1;
            float4 a, bb;
            a.x = rs * bf_lo(ga.x); a.y = rs * bf_hi(ga.x); a.z = rs * bf_lo(ga.y); a.w = rs * bf_hi(ga.y);
            bb.x = fmaf(-mean, a.x, 0.5f * bf_lo(bt.x)); bb.y = fmaf(-mean, a.y, 0.5f * bf_hi(bt.x));
            bb.z = fmaf(-mean, a.z, 0.5f * bf_lo(bt.y)); bb.w = fmaf(-mean, a.w, 0.5f * bf_hi(bt.y));
            float4* cf = reinterpret_cast<float4*>(smem + SM_COEF + (lane >> 1) * 64 + (lane & 1) * 16);
            cf[0] = a; cf[2] = bb;
            __syncwarp();
            if (lane == 0) mbar_arrive(bars + 8 * BAR_STATS);
        }
    } else {
        unsigned epoch = ld_relaxed(&g_epoch[cta]);
        bar_sync(0, NTHREADS);
        epoch = opaque(epoch) + 1;
        mbar_wait(bars + 8 * BAR_STATS, 0);
        {
            float e0 = 0.f, e1 = 0.f;
            const uint32_t* wsrc = reinterpret_cast<const uint32_t*>(w_emb) + r;
            const unsigned short* tsrc = reinterpret_cast<const unsigned short*>(t_emb) + b * E;
#pragma unroll 8
            for (int i = 0; i < E / 32; i++) {
                const int e = i * 32 + lane;
                const uint32_t wv = __ldg(wsrc + e * (C / 2));
                const float t = __uint_as_float((uint32_t)__ldg(tsrc + e) << 16);
                const float sv = silu_half(0.5f * t);
                e0 = fmaf(sv, bf_lo(wv), e0); e1 = fmaf(sv, bf_hi(wv), e1);
            }
            float give = (lane < 16) ? e1 : e0, keep = (lane < 16) ? e0 : e1;
            keep += __shfl_xor_sync(0xffffffffu, give, 16);
#pragma unroll
            for (int m = 8; m >= 1; m >>= 1) keep += __shfl_xor_sync(0xffffffffu, keep, m);
            if ((lane & 15) == 0) st_relaxed(&g_emb[b * C + 2 * r + (lane >> 4)], tag_f(keep, epoch & 3));
            unsigned it = 0;
            uint4 f;
            while (true) {
                f = ld_relaxed_v4(&g_emb[b * C + lane * 4]);
                const unsigned tag = epoch & 3;
                const unsigned bad = (f.x ^ tag) | (f.y ^ tag) | (f.z ^ tag) | (f.w ^ tag);
                if (__all_sync(0xffffffffu, (bad & 3) == 0)) break;
                if (++it > SPIN_LIMIT) break;
                __nanosleep(200);
            }
            *reinterpret_cast<uint4*>(smem + SM_EMB + lane * 16) = f;
            __syncwarp();
            if (lane == 0) mbar_arrive(bars + 8 * BAR_EMB);
        }
        if (lane == 0) {
            mbar_wait(bars + 8 * BAR_HW, 0);
            asm volatile("st.release.gpu.global.u32 [%0], %1;" ::"l"(&g_hflag[cta * 32]), "r"(epoch) : "memory");
            TL(13);
        }
        __syncwarp();
        if (lane < 2) {
            const int irow = r - 1 + 2 * lane;
            if (irow >= 0 && irow < HW) {
                const int nb = cta - 1 + 2 * lane;
                unsigned it = 0;
                while (ld_acquire(&g_hflag[nb * 32]) != epoch) { if (++it > SPIN_LIMIT) break; }
                fence_async_global();
                mbar_expect(bars + 8 * (BAR_HALO + lane), ROW_BYTES);
                bulk_g2s(sb + SM_ACT + 2 * lane * ROW_BYTES, g_h + (size_t)nb * ROW_BYTES, ROW_BYTES, bars + 8 * (BAR_HALO + lane));
                if (lane == 0) TL(14);
            }
        }
    }
}

}

extern "C" void kernel_launch(void* const* d_in, const int* in_sizes, int n_in, void* d_out, int out_size) {
    (void)in_sizes; (void)n_in; (void)out_size;
    static bool init = false;
    if (!init) {
        cudaFuncSetAttribute(resblock_kernel, cudaFuncAttributeMaxDynamicSharedMemorySize, SM_TOTAL);
        init = true;
    }
    resblock_kernel<<<NCTA, NTHREADS, SM_TOTAL>>>(
        (const __nv_bfloat16*)d_in[0], (const __nv_bfloat16*)d_in[1], (const __nv_bfloat16*)d_in[2],
        (const __nv_bfloat16*)d_in[3], (const __nv_bfloat16*)d_in[4], (const __nv_bfloat16*)d_in[5],
        (const __nv_bfloat16*)d_in[6], (const __nv_bfloat16*)d_in[7], (const __nv_bfloat16*)d_in[8],
        (__nv_bfloat16*)d_out);
}
```

```cpp
#include <cuda_runtime.h>
#include <cuda_bf16.h>
#include <stdint.h>

namespace {

constexpr int C = 128, HW = 64, NB = 2, E = 768;
constexpr int NCTA = NB * HW;
constexpr int NTHREADS = 15 * 32;
constexpr int CH_PITCH = 66 * 16;
constexpr int ROW_BYTES = 16 * CH_PITCH;
constexpr int STEP_BYTES = 4096;
constexpr int STAGE_BYTES = 3 * STEP_BYTES;
constexpr int NSTAGE = 24;
constexpr int NS = 8;

constexpr int SM_ACT = 0;
constexpr int SM_STG = SM_ACT + 3 * ROW_BYTES;
constexpr int SM_W = SM_STG + 3 * 16384;
constexpr int SM_COEF = SM_W + NS * STAGE_BYTES;
constexpr int SM_EMB = SM_COEF + 1024;
constexpr int SM_RED = SM_EMB + 512;
constexpr int SM_BAR = SM_RED + 128;
constexpr int BAR_FULL = 0, BAR_WEMPTY = NSTAGE, BAR_STATS = BAR_WEMPTY + NS, BAR_HW = BAR_STATS + 1,
              BAR_HALO = BAR_HW + 1  , BAR_EMB = BAR_HALO + 2, BAR_WACQ = BAR_EMB + 1, BAR_XH = BAR_WACQ + 1,
              NBAR = BAR_XH + 1;
constexpr int SM_TOTAL = SM_BAR + NBAR * 8;
static_assert(SM_TOTAL <= 232448, "smem");
constexpr int OUT_PITCH = 144;

constexpr unsigned SPIN_LIMIT = 1u << 16;
constexpr unsigned EMB_EMPTY = 0xffffffffu;

struct Scratch {
    float acc[2 * NB * 32];
    unsigned wcnt[NB * 32];
    unsigned emb[NB * C];
    unsigned hflag[NCTA * 32];
    unsigned char wt[2 * 72 * STEP_BYTES];
    unsigned char h[NCTA * ROW_BYTES];
};
__device__ __align__(1024) Scratch g_s;
#define TL(i) do {} while (0)
#define TLG(i) do {} while (0)

__device__ __forceinline__ uint32_t smem_u32(const void* p) { return (uint32_t)__cvta_generic_to_shared(p); }
__device__ __forceinline__ void mbar_init(uint32_t bar, int cnt) {
    asm volatile("mbarrier.init.shared::cta.b64 [%0], %1;" ::"r"(bar), "r"(cnt) : "memory");
}
__device__ __forceinline__ void mbar_arrive(uint32_t bar) {
    asm volatile("mbarrier.arrive.shared::cta.b64 _, [%0];" ::"r"(bar) : "memory");
}
__device__ __forceinline__ void mbar_expect(uint32_t bar, uint32_t bytes) {
    asm volatile("mbarrier.arrive.expect_tx.shared::cta.b64 _, [%0], %1;" ::"r"(bar), "r"(bytes) : "memory");
}
__device__ __forceinline__ bool mbar_try(uint32_t bar, uint32_t par) {
    uint32_t ok;
    asm volatile("{\n.reg .pred p;\nmbarrier.try_wait.parity.shared::cta.b64 p, [%1], %2;\nselp.u32 %0, 1, 0, p;\n}"
                 : "=r"(ok) : "r"(bar), "r"(par) : "memory");
    return ok;
}
__device__ __forceinline__ void mbar_wait(uint32_t bar, uint32_t par) {
    unsigned it = 0;
#pragma unroll 1
    while (!mbar_try(bar, par) && ++it < SPIN_LIMIT) {}
}
__device__ __forceinline__ void fence_async_smem() { asm volatile("fence.proxy.async.shared::cta;" ::: "memory"); }
__device__ __forceinline__ void fence_async_global() { asm volatile("fence.proxy.async.global;" ::: "memory"); }
__device__ __forceinline__ void bar_sync(int id, int n) { asm volatile("bar.sync %0, %1;" ::"r"(id), "r"(n) : "memory"); }
__device__ __forceinline__ void bulk_g2s(uint32_t dst, const void* src, uint32_t bytes, uint32_t bar) {
    asm volatile("cp.async.bulk.shared::cluster.global.mbarrier::complete_tx::bytes [%0], [%1], %2, [%3];"
                 ::"r"(dst), "l"(src), "r"(bytes), "r"(bar) : "memory");
}
__device__ __forceinline__ uint4 ld_relaxed_v4(const void* p) {
    uint4 v;
    asm volatile("ld.relaxed.gpu.global.v4.u32 {%0,%1,%2,%3}, [%4];" : "=r"(v.x), "=r"(v.y), "=r"(v.z), "=r"(v.w) : "l"(p) : "memory");
    return v;
}
__device__ __forceinline__ unsigned ld_acquire(const void* p) {
    unsigned v;
    asm volatile("ld.acquire.gpu.global.u32 %0, [%1];" : "=r"(v) : "l"(p) : "memory");
    return v;
}
__device__ __forceinline__ void st_relaxed(void* p, unsigned v) {
    asm volatile("st.relaxed.gpu.global.u32 [%0], %1;" ::"l"(p), "r"(v) : "memory");
}
__device__ __forceinline__ void red_add4(float* p, float a, float b, float c, float d) {
    asm volatile("red.relaxed.gpu.global.add.v4.f32 [%0], {%1,%2,%3,%4};" ::"l"(p), "f"(a), "f"(b), "f"(c), "f"(d) : "memory");
}
__device__ __forceinline__ float bf_lo(uint32_t u) { return __uint_as_float(u << 16); }
__device__ __forceinline__ float bf_hi(uint32_t u) { return __uint_as_float(u & 0xffff0000u); }
__device__ __forceinline__ uint32_t pack_bf(float lo, float hi) {
    uint32_t r;
    asm("cvt.rn.bf16x2.f32 %0, %1, %2;" : "=r"(r) : "f"(hi), "f"(lo));
    return r;
}
__device__ __forceinline__ float tanh_fast(float x) {
    float r;
    asm("tanh.approx.f32 %0, %1;" : "=f"(r) : "f"(x));
    return r;
}
__device__ __forceinline__ float silu_half(float h) { return fmaf(h, tanh_fast(h), h); }
__device__ __forceinline__ void ldsm4(uint32_t (&u)[4], uint32_t a) {
    asm volatile("ldmatrix.sync.aligned.m8n8.x4.shared.b16 {%0,%1,%2,%3}, [%4];"
                 : "=r"(u[0]), "=r"(u[1]), "=r"(u[2]), "=r"(u[3]) : "r"(a) : "memory");
}
__device__ __forceinline__ void ldsm4t(uint32_t (&u)[4], uint32_t a) {
    asm volatile("ldmatrix.sync.aligned.m8n8.x4.trans.shared.b16 {%0,%1,%2,%3}, [%4];"
                 : "=r"(u[0]), "=r"(u[1]), "=r"(u[2]), "=r"(u[3]) : "r"(a) : "memory");
}
__device__ __forceinline__ void stsm4(uint32_t a, uint32_t p0, uint32_t p1, uint32_t p2, uint32_t p3) {
    asm volatile("stmatrix.sync.aligned.m8n8.x4.shared.b16 [%0], {%1,%2,%3,%4};" ::"r"(a), "r"(p0), "r"(p1), "r"(p2), "r"(p3) : "memory");
}
__device__ __forceinline__ void stsm4t(uint32_t a, uint32_t p0, uint32_t p1, uint32_t p2, uint32_t p3) {
    asm volatile("stmatrix.sync.aligned.m8n8.x4.trans.shared.b16 [%0], {%1,%2,%3,%4};" ::"r"(a), "r"(p0), "r"(p1), "r"(p2), "r"(p3) : "memory");
}

#define R8(o) "+f"(d[o]), "+f"(d[o + 1]), "+f"(d[o + 2]), "+f"(d[o + 3]), "+f"(d[o + 4]), "+f"(d[o + 5]), "+f"(d[o + 6]), "+f"(d[o + 7])
__device__ __forceinline__ void wgmma128(float (&d)[64], uint32_t alo, uint32_t blo) {
    asm volatile(
        "{\n.reg .b64 da, db;\nmov.b64 da, {%64, %66};\nmov.b64 db, {%65, %66};\n"
        "wgmma.mma_async.sync.aligned.m64n128k16.f32.bf16.bf16 "
        "{%0,%1,%2,%3,%4,%5,%6,%7,%8,%9,%10,%11,%12,%13,%14,%15,%16,%17,%18,%19,%20,%21,%22,%23,%24,%25,%26,%27,%28,%29,%30,%31,"
        "%32,%33,%34,%35,%36,%37,%38,%39,%40,%41,%42,%43,%44,%45,%46,%47,%48,%49,%50,%51,%52,%53,%54,%55,%56,%57,%58,%59,%60,%61,%62,%63},"
        " da, db, 1, 1, 1, 0, 0;\n}"
        : R8(0), R8(8), R8(16), R8(24), R8(32), R8(40), R8(48), R8(56)
        : "r"(alo), "r"(blo), "r"(8));
}
__host__ __device__ constexpr int stage_ky(int s) { return (s >> 3) == 0 ? 1 : ((s >> 3) == 1 ? 0 : 2); }
__device__ __forceinline__ void fence_acc(float (&d)[64]) {
#pragma unroll
    for (int i = 0; i < 64; i++) asm volatile("" : "+f"(d[i])::"memory");
}

__global__ void __launch_bounds__(NTHREADS, 1)
resblock_kernel(const __nv_bfloat16* __restrict__ x, const __nv_bfloat16* __restrict__ t_emb,
                const __nv_bfloat16* __restrict__ g1, const __nv_bfloat16* __restrict__ be1,
                const __nv_bfloat16* __restrict__ w1, const __nv_bfloat16* __restrict__ w_emb,
                const __nv_bfloat16* __restrict__ g2, const __nv_bfloat16* __restrict__ be2,
                const __nv_bfloat16* __restrict__ w2, __nv_bfloat16* __restrict__ out) {
    extern __shared__ __align__(128) unsigned char smem[];
    const uint32_t sb = smem_u32(smem);
    const uint32_t bars = sb + SM_BAR;
    const int tid = threadIdx.x, warp = tid >> 5, lane = tid & 31;
    const int cta = blockIdx.x, b = cta >> 6, r = cta & 63;
    if (tid == 0) { TL(0); TLG(1); }

    if (warp < 4) {
        const int wq = warp;
        if (tid < NBAR) {
            const int cnt = tid < BAR_WEMPTY ? 5 : (tid < BAR_STATS || tid == BAR_HW) ? 4 : (tid == BAR_XH ? 256 : 1);
            mbar_init(bars + 8 * tid, cnt);
        }
        if (tid < 96) {
            *reinterpret_cast<uint4*>(smem + SM_ACT + (tid >> 1) * CH_PITCH + (tid & 1) * 65 * 16) = make_uint4(0, 0, 0, 0);
        }
        if (r == 0 || r == HW - 1) {
            uint4* z = reinterpret_cast<uint4*>(smem + SM_ACT + (r == 0 ? 0 : 2 * ROW_BYTES));
            for (int i = tid; i < ROW_BYTES / 16; i += 128) z[i] = make_uint4(0, 0, 0, 0);
        }
        fence_async_smem();
        bar_sync(0, NTHREADS);

        float d[64];
#pragma unroll
        for (int i = 0; i < 64; i++) d[i] = 0.f;
        const uint32_t alo = (((sb + SM_ACT) & 0x3FFFF) >> 4) | ((CH_PITCH >> 4) << 16);
        const uint32_t blo = (((sb + SM_W) & 0x3FFFF) >> 4) | ((2048 >> 4) << 16);
#pragma unroll 1
        for (int conv = 0; conv < 2; conv++) {
            fence_acc(d);
#pragma unroll
            for (int s = 0; s < NSTAGE; s++) {
                mbar_wait(bars + 8 * (BAR_FULL + s), conv);
                if (s == 0 && tid == 0) TL(9 + conv * 8);
                asm volatile("wgmma.fence.sync.aligned;" ::: "memory");
#pragma unroll
                for (int kx = 0; kx < 3; kx++)
                    wgmma128(d, alo + ((stage_ky(s) * ROW_BYTES + (s & 7) * 2 * CH_PITCH) >> 4) + kx,
                             blo + (((s % NS) * STAGE_BYTES + kx * STEP_BYTES) >> 4));
                asm volatile("wgmma.commit_group.sync.aligned;" ::: "memory");
                if (s > 0) {
                    asm volatile("wgmma.wait_group.sync.aligned 1;" ::: "memory");
                    if (lane == 0) mbar_arrive(bars + 8 * (BAR_WEMPTY + (s - 1) % NS));
                }
            }
            asm volatile("wgmma.wait_group.sync.aligned 0;" ::: "memory");
            fence_acc(d);
            if (tid == 0) TL(10 + conv * 8);
            if (conv == 1) break;

            if (lane == 0) mbar_arrive(bars + 8 * (BAR_WEMPTY + (NSTAGE - 1) % NS));
            mbar_wait(bars + 8 * BAR_EMB, 0);
            const float* embs = reinterpret_cast<const float*>(smem + SM_EMB);
            float st[8];
#pragma unroll
            for (int g = 0; g < 4; g++) {
                float s = 0.f, q = 0.f, s2 = 0.f, q2 = 0.f;
#pragma unroll
                for (int jj = 0; jj < 4; jj++) {
                    const int j = g * 4 + jj;
                    const float2 e = *reinterpret_cast<const float2*>(embs + 8 * j + 2 * (lane & 3));
                    d[4 * j + 0] += e.x; d[4 * j + 1] += e.y; d[4 * j + 2] += e.x; d[4 * j + 3] += e.y;
                    s += d[4 * j + 0]; q = fmaf(d[4 * j + 0], d[4 * j + 0], q);
                    s2 += d[4 * j + 1]; q2 = fmaf(d[4 * j + 1], d[4 * j + 1], q2);
                    s += d[4 * j + 2]; q = fmaf(d[4 * j + 2], d[4 * j + 2], q);
                    s2 += d[4 * j + 3]; q2 = fmaf(d[4 * j + 3], d[4 * j + 3], q2);
                }
                st[2 * g] = s + s2; st[2 * g + 1] = q + q2;
            }
            {
                const bool h16 = lane & 16, h8 = lane & 8, h4 = lane & 4;
                float a[4];
#pragma unroll
                for (int i = 0; i < 4; i++) {
                    float give = h16 ? st[i] : st[i + 4], keep = h16 ? st[i + 4] : st[i];
                    a[i] = keep + __shfl_xor_sync(0xffffffffu, give, 16);
                }
                float c2[2];
#pragma unroll
                for (int i = 0; i < 2; i++) {
                    float give = h8 ? a[i] : a[i + 2], keep = h8 ? a[i + 2] : a[i];
                    c2[i] = keep + __shfl_xor_sync(0xffffffffu, give, 8);
                }
                float give = h4 ? c2[0] : c2[1], keep = h4 ? c2[1] : c2[0];
                float t = keep + __shfl_xor_sync(0xffffffffu, give, 4);
                t += __shfl_xor_sync(0xffffffffu, t, 2);
                t += __shfl_xor_sync(0xffffffffu, t, 1);
                float* red = reinterpret_cast<float*>(smem + SM_RED);
                if ((lane & 3) == 0) red[(lane >> 2) * 4 + wq] = t;
                bar_sync(2, 128);
                if (tid < 4) {
                    const float4 p = *reinterpret_cast<const float4*>(red + tid * 8);
                    const float4 p2 = *reinterpret_cast<const float4*>(red + tid * 8 + 4);
                    red_add4(&g_s.acc[(NB + b) * 32 + tid * 4], 1.f, (p.x + p.y) + (p.z + p.w), (p2.x + p2.y) + (p2.z + p2.w), 1.f);
                }
                if (tid == 0) TL(11);
            }
            const uint32_t hbase = sb + SM_ACT + ROW_BYTES + (lane >> 4) * CH_PITCH + (1 + wq * 16 + (lane & 15)) * 16;
            uint32_t* hg = reinterpret_cast<uint32_t*>(g_s.h + (size_t)cta * ROW_BYTES + (1 + wq * 16) * 16) + lane;
#pragma unroll
            for (int j = 0; j < 16; j += 2) {
                uint32_t p0 = pack_bf(d[4 * j + 0], d[4 * j + 1]), p1 = pack_bf(d[4 * j + 2], d[4 * j + 3]);
                uint32_t p2 = pack_bf(d[4 * j + 4], d[4 * j + 5]), p3 = pack_bf(d[4 * j + 6], d[4 * j + 7]);
                stsm4(hbase + j * CH_PITCH, p0, p1, p2, p3);
                hg[j * (CH_PITCH / 4)] = p0; hg[j * (CH_PITCH / 4) + 32] = p1;
                hg[(j + 1) * (CH_PITCH / 4)] = p2; hg[(j + 1) * (CH_PITCH / 4) + 32] = p3;
            }
            __syncwarp();
            if (lane == 0) mbar_arrive(bars + 8 * BAR_HW);
            if (tid == 0) TL(12);
            const uint32_t xbase = sb + SM_STG + 16384 + ((lane >> 4) * 8 + (lane & 7)) * 128 + (((2 * wq + ((lane >> 3) & 1)) ^ (lane & 7)) << 4);
#pragma unroll
            for (int j = 0; j < 16; j += 2) {
                uint32_t p[4];
                ldsm4t(p, xbase + j * 1024);
                d[4 * j + 0] = bf_lo(p[0]); d[4 * j + 1] = bf_hi(p[0]); d[4 * j + 2] = bf_lo(p[1]); d[4 * j + 3] = bf_hi(p[1]);
                d[4 * j + 4] = bf_lo(p[2]); d[4 * j + 5] = bf_hi(p[2]); d[4 * j + 6] = bf_lo(p[3]); d[4 * j + 7] = bf_hi(p[3]);
            }
        }
        {
            const uint32_t obase = sb + SM_STG + ((lane >> 4) * 8 + (lane & 7)) * OUT_PITCH + (wq * 16 + ((lane >> 3) & 1) * 8) * 2;
#pragma unroll
            for (int j = 0; j < 16; j += 2) {
                stsm4t(obase + j * 8 * OUT_PITCH, pack_bf(d[4 * j + 0], d[4 * j + 1]), pack_bf(d[4 * j + 2], d[4 * j + 3]),
                       pack_bf(d[4 * j + 4], d[4 * j + 5]), pack_bf(d[4 * j + 6], d[4 * j + 7]));
            }
            bar_sync(2, 128);
            const int oc0 = tid >> 3, seg = tid & 7;
            __nv_bfloat16* dst = out + ((size_t)(b * C + oc0) * HW + r) * HW + seg * 8;
#pragma unroll
            for (int i = 0; i < 8; i++) {
                const uint4 o = *reinterpret_cast<const uint4*>(smem + SM_STG + (oc0 + 16 * i) * OUT_PITCH + seg * 16);
                *reinterpret_cast<uint4*>(dst + (size_t)i * 16 * HW * HW) = o;
            }
            if (tid == 0) { TL(20); TLG(21); }
        }
    } else if (warp < 12) {
        const int nw = warp - 4;
        {
            const int c0 = nw * 16 + (lane >> 3), seg = lane & 7;
            const uint4* src = reinterpret_cast<const uint4*>(x + ((size_t)(b * C + c0) * HW + r) * HW) + seg;
            uint4 v[4];
#pragma unroll
            for (int i = 0; i < 4; i++) v[i] = __ldg(src + (size_t)i * 4 * (HW * HW / 8));
            bar_sync(0, NTHREADS);
            float s = 0.f, q = 0.f, s2 = 0.f, q2 = 0.f;
#pragma unroll
            for (int i = 0; i < 4; i++) {
                const uint32_t u[4] = {v[i].x, v[i].y, v[i].z, v[i].w};
#pragma unroll
                for (int k = 0; k < 4; k++) {
                    const float lo = bf_lo(u[k]), hi = bf_hi(u[k]);
                    s += lo; q = fmaf(lo, lo, q);
                    s2 += hi; q2 = fmaf(hi, hi, q2);
                }
            }
            s += s2; q += q2;
            float give = (lane < 16) ? q : s, keep = (lane < 16) ? s : q;
            keep += __shfl_xor_sync(0xffffffffu, give, 16);
            if (tid == 128) TL(2);
#pragma unroll
            for (int m = 8; m >= 1; m >>= 1) keep += __shfl_xor_sync(0xffffffffu, keep, m);
            float* red = reinterpret_cast<float*>(smem + SM_RED);
            if ((lane & 15) == 0) red[nw * 2 + (lane >> 4)] = keep;
            bar_sync(3, 256);
            if (tid < 128 + 4) {
                const float4 p = *reinterpret_cast<const float4*>(red + lane * 4);
                red_add4(&g_s.acc[b * 32 + lane * 4], 1.f, p.x + p.z, p.y + p.w, 1.f);
            }
            if (tid == 128) TL(3);
#pragma unroll
            for (int hrow = 0; hrow < 2; hrow++) {
                const int row = r - 1 + 2 * hrow;
                if (row >= 0 && row < HW) {
#pragma unroll
                    for (int i = 0; i < 4; i++) {
                        const int c = c0 + 4 * i;
                        const uint32_t dst = sb + SM_STG + hrow * 2 * 16384 + c * 128 + ((seg ^ (c & 7)) << 4);
                        asm volatile("cp.async.cg.shared.global [%0], [%1], 16;"
                                     ::"r"(dst), "l"(src + (ptrdiff_t)(2 * hrow - 1) * (HW / 8) + (size_t)i * 4 * (HW * HW / 8)) : "memory");
                    }
                }
            }
            asm volatile("cp.async.mbarrier.arrive.noinc.shared::cta.b64 [%0];" ::"r"(bars + 8 * BAR_XH) : "memory");
#pragma unroll
            for (int i = 0; i < 4; i++) {
                const int c = c0 + 4 * i;
                *reinterpret_cast<uint4*>(smem + SM_STG + 16384 + c * 128 + ((seg ^ (c & 7)) << 4)) = v[i];
            }
            bar_sync(3, 256);
        }
        const int par = nw >> 2;
        const int csel = (nw >> 1) & 1, half = nw & 1;
        const uint32_t act_off = sb + SM_ACT + csel * CH_PITCH + (1 + half * 32 + lane) * 16;
        const uint32_t stg_off = sb + SM_STG + (csel * 8 + (lane & 7)) * 128 + (((half * 4 + (lane >> 3)) ^ (lane & 7)) << 4);
        const unsigned char* coef = smem + SM_COEF + csel * 64 + (lane & 3) * 16;
#pragma unroll 1
        for (int conv = 0; conv < 2; conv++) {
            if (conv == 1) mbar_wait(bars + 8 * BAR_HW, 0);
            mbar_wait(bars + 8 * BAR_STATS, conv);
#pragma unroll 1
            for (int o = 0; o < 3; o++) {
                const int ky = (o == 0) ? 1 : (o == 1 ? 0 : 2);
                const int irow = r - 1 + ky;
                const bool valid = irow >= 0 && irow < HW;
                if (valid && o > 0) mbar_wait(bars + 8 * (conv ? BAR_HALO + o - 1 : BAR_XH), 0);
#pragma unroll 1
                for (int kc = par; kc < 8; kc += 2) {
                    if (valid) {
                        const uint32_t ao = act_off + ky * ROW_BYTES + kc * 2 * CH_PITCH;
                        uint32_t u[4];
                        if (conv == 0) ldsm4t(u, stg_off + ky * 16384 + kc * 2048);
                        else ldsm4(u, ao);
                        const float4 cf = *reinterpret_cast<const float4*>(coef + kc * 128);
#pragma unroll
                        for (int i = 0; i < 4; i++)
                            u[i] = pack_bf(silu_half(fmaf(bf_lo(u[i]), cf.x, cf.z)), silu_half(fmaf(bf_hi(u[i]), cf.y, cf.w)));
                        stsm4(ao, u[0], u[1], u[2], u[3]);
                        fence_async_smem();
                    }
                    __syncwarp();
                    if (lane == 0) mbar_arrive(bars + 8 * (BAR_FULL + o * 8 + kc));
                    if (tid == 128 && o == 0 && kc == 0) TL(8 + conv * 8);
                }
            }
        }
    } else if (warp == 12) {
        {
            const int l16 = lane & 15, cv = lane >> 4;
            const int oc = (cta & 15) * 8 + (l16 & 7), kc = cta >> 4, hh = l16 >> 3;
            const uint4* src = reinterpret_cast<const uint4*>((cv ? w2 : w1) + ((size_t)oc * C + kc * 16 + hh * 8) * 9);
            uint32_t w[36];
#pragma unroll
            for (int i = 0; i < 9; i++) {
                const uint4 t = __ldg(src + i);
                w[4 * i] = t.x; w[4 * i + 1] = t.y; w[4 * i + 2] = t.z; w[4 * i + 3] = t.w;
            }
            if (lane == 0) g_s.hflag[cta * 32] = 0;
            if (lane < 2) g_s.emb[b * C + 2 * r + lane] = EMB_EMPTY;
            if (r == 0 && lane < 16) g_s.acc[(NB + b) * 32 + lane] = 0.f;
            bar_sync(0, NTHREADS);
            unsigned char* dst = g_s.wt + (size_t)cv * 72 * STEP_BYTES + kc * STAGE_BYTES + hh * 2048 + oc * 16;
#pragma unroll
            for (int tap = 0; tap < 9; tap++) {
                uint32_t o[4];
#pragma unroll
                for (int m = 0; m < 4; m++) {
                    const int i0 = 18 * m + tap, i1 = i0 + 9;
                    const uint32_t sel = ((i0 & 1) ? 0x32u : 0x10u) | ((i1 & 1) ? 0x7600u : 0x5400u);
                    o[m] = __byte_perm(w[i0 >> 1], w[i1 >> 1], sel);
                }
                const int ky = tap / 3, kx = tap % 3;
                const int kyo = (ky == 1) ? 0 : (ky == 0 ? 1 : 2);
                *reinterpret_cast<uint4*>(dst + (kyo * 24 + kx) * STEP_BYTES) = make_uint4(o[0], o[1], o[2], o[3]);
            }
            if (lane == 0) TL(4);
            __syncwarp();
            if (lane < 2) asm volatile("red.release.gpu.global.add.u32 [%0], 1;" ::"l"(&g_s.wcnt[lane * 32]) : "memory");
        }
        if (lane == 0) {
            TL(5);
            unsigned it = 0;
            while (ld_acquire(&g_s.wcnt[b * 32]) < (unsigned)NCTA && ++it < SPIN_LIMIT) {}
            fence_async_global();
            TL(6);
            int slot = 0, st = 0; uint32_t par = 1;
#pragma unroll 1
            for (int g = 0; g < 2 * NSTAGE; g++) {
                mbar_wait(bars + 8 * (BAR_WEMPTY + slot), par);
                mbar_expect(bars + 8 * (BAR_FULL + st), STAGE_BYTES);
                bulk_g2s(sb + SM_W + slot * STAGE_BYTES, g_s.wt + (size_t)g * STAGE_BYTES, STAGE_BYTES, bars + 8 * (BAR_FULL + st));
                if (g == NS - 1) mbar_arrive(bars + 8 * BAR_WACQ);
                if (++slot == NS) { slot = 0; par ^= 1; }
                if (++st == NSTAGE) st = 0;
            }
        }
    } else if (warp == 13) {
        const uint2 ga1 = __ldg(reinterpret_cast<const uint2*>(g1) + lane), bt1 = __ldg(reinterpret_cast<const uint2*>(be1) + lane);
        const uint2 ga2 = __ldg(reinterpret_cast<const uint2*>(g2) + lane), bt2 = __ldg(reinterpret_cast<const uint2*>(be2) + lane);
        bar_sync(0, NTHREADS);
#pragma unroll 1
        for (int conv = 0; conv < 2; conv++) {
            if (conv == 1) mbar_wait(bars + 8 * BAR_HW, 0);
            const float* src = &g_s.acc[(conv * NB + b) * 32 + (lane >> 3) * 4];
            uint4 f;
            unsigned it = 0;
            while (true) {
                f = ld_relaxed_v4(src);
                const bool ok = (f.x == 0x42800000u) & (f.w == 0x42800000u);
                if (__all_sync(0xffffffffu, ok) || ++it > SPIN_LIMIT) break;
            }
            if (lane == 0) TL(7 + conv * 8);
            const float inv_n = 1.0f / (32.0f * HW * HW);
            const float mean = __uint_as_float(f.y) * inv_n;
            const float var = fmaxf(fmaf(-mean, mean, __uint_as_float(f.z) * inv_n), 0.f);
            const float rs = 0.5f * rsqrtf(var + 1e-5f);
            const uint2 ga = conv ? ga2 : ga1, bt = conv ? bt2 : bt1;
            float4 c0, c1;
            c0.x = rs * bf_lo(ga.x); c0.y = rs * bf_hi(ga.x); c1.x = rs * bf_lo(ga.y); c1.y = rs * bf_hi(ga.y);
            c0.z = fmaf(-mean, c0.x, 0.5f * bf_lo(bt.x)); c0.w = fmaf(-mean, c0.y, 0.5f * bf_hi(bt.x));
            c1.z = fmaf(-mean, c1.x, 0.5f * bf_lo(bt.y)); c1.w = fmaf(-mean, c1.y, 0.5f * bf_hi(bt.y));
            float4* cf = reinterpret_cast<float4*>(smem + SM_COEF + lane * 32);
            cf[0] = c0; cf[1] = c1;
            __syncwarp();
            if (lane == 0) mbar_arrive(bars + 8 * BAR_STATS);
        }
        if (r == 0) {
            if (lane < 16) g_s.acc[b * 32 + lane] = 0.f;
            if (lane == 0) g_s.wcnt[b * 32] = 0;
        }
    } else {
        bar_sync(0, NTHREADS);
        mbar_wait(bars + 8 * BAR_WACQ, 0);
        {
            float e0 = 0.f, e1 = 0.f;
            const uint32_t* wsrc = reinterpret_cast<const uint32_t*>(w_emb) + r;
            const unsigned short* tsrc = reinterpret_cast<const unsigned short*>(t_emb) + b * E;
#pragma unroll 8
            for (int i = 0; i < E / 32; i++) {
                const int e = i * 32 + lane;
                const uint32_t wv = __ldg(wsrc + e * (C / 2));
                const float t = __uint_as_float((uint32_t)__ldg(tsrc + e) << 16);
                const float sv = silu_half(0.5f * t);
                e0 = fmaf(sv, bf_lo(wv), e0); e1 = fmaf(sv, bf_hi(wv), e1);
            }
            float give = (lane < 16) ? e1 : e0, keep = (lane < 16) ? e0 : e1;
            keep += __shfl_xor_sync(0xffffffffu, give, 16);
#pragma unroll
            for (int m = 8; m >= 1; m >>= 1) keep += __shfl_xor_sync(0xffffffffu, keep, m);
            unsigned bits = __float_as_uint(keep);
            if (bits == EMB_EMPTY) bits = 0x7fffffffu;
            if ((lane & 15) == 0) st_relaxed(&g_s.emb[b * C + 2 * r + (lane >> 4)], bits);
            unsigned it = 0;
            uint4 f;
            while (true) {
                f = ld_relaxed_v4(&g_s.emb[b * C + lane * 4]);
                const bool ok = (f.x != EMB_EMPTY) & (f.y != EMB_EMPTY) & (f.z != EMB_EMPTY) & (f.w != EMB_EMPTY);
                if (__all_sync(0xffffffffu, ok) || ++it > SPIN_LIMIT) break;
                __nanosleep(200);
            }
            *reinterpret_cast<uint4*>(smem + SM_EMB + lane * 16) = f;
            __syncwarp();
            if (lane == 0) { mbar_arrive(bars + 8 * BAR_EMB); TL(19); }
        }
        if (lane == 0) {
            mbar_wait(bars + 8 * BAR_HW, 0);
            asm volatile("st.release.gpu.global.u32 [%0], %1;" ::"l"(&g_s.hflag[cta * 32]), "r"(1) : "memory");
            TL(13);
        }
        __syncwarp();
        if (lane < 2) {
            const int irow = r - 1 + 2 * lane;
            if (irow >= 0 && irow < HW) {
                const int nb = cta - 1 + 2 * lane;
                unsigned it = 0;
                while (ld_acquire(&g_s.hflag[nb * 32]) == 0 && ++it < SPIN_LIMIT) {}
                fence_async_global();
                mbar_expect(bars + 8 * (BAR_HALO + lane), ROW_BYTES);
                bulk_g2s(sb + SM_ACT + 2 * lane * ROW_BYTES, g_s.h + (size_t)nb * ROW_BYTES, ROW_BYTES, bars + 8 * (BAR_HALO + lane));
                if (lane == 0) TL(14);
            }
        }
    }
}

}

extern "C" void kernel_launch(void* const* d_in, const int* in_sizes, int n_in, void* d_out, int out_size) {
    (void)in_sizes; (void)n_in; (void)out_size;
    static bool init = false;
    if (!init) {
        cudaFuncSetAttribute(resblock_kernel, cudaFuncAttributeMaxDynamicSharedMemorySize, SM_TOTAL);
        init = true;
    }
    resblock_kernel<<<NCTA, NTHREADS, SM_TOTAL>>>(
        (const __nv_bfloat16*)d_in[0], (const __nv_bfloat16*)d_in[1], (const __nv_bfloat16*)d_in[2],
        (const __nv_bfloat16*)d_in[3], (const __nv_bfloat16*)d_in[4], (const __nv_bfloat16*)d_in[5],
        (const __nv_bfloat16*)d_in[6], (const __nv_bfloat16*)d_in[7], (const __nv_bfloat16*)d_in[8],
        (__nv_bfloat16*)d_out);
}
```

```cpp
#include <cuda_runtime.h>
#include <cuda_bf16.h>
#include <stdint.h>

namespace {

constexpr int C = 128, HW = 64, NB = 2, E = 768;
constexpr int NCTA = NB * HW;
constexpr int NTHREADS = 15 * 32;
constexpr int CH_PITCH = 66 * 16;
constexpr int ROW_BYTES = 16 * CH_PITCH;
constexpr int STEP_BYTES = 4096;
constexpr int STAGE_BYTES = 3 * STEP_BYTES;
constexpr int NSTAGE = 24;
constexpr int NS = 8;

constexpr int SM_ACT = 0;
constexpr int SM_STG = SM_ACT + 3 * ROW_BYTES;
constexpr int SM_W = SM_STG + 3 * 16384;
constexpr int SM_COEF = SM_W + NS * STAGE_BYTES;
constexpr int SM_EMB = SM_COEF + 1024;
constexpr int SM_RED = SM_EMB + 512;
constexpr int SM_BAR = SM_RED + 128;
constexpr int BAR_FULL = 0, BAR_WEMPTY = NSTAGE, BAR_STATS = BAR_WEMPTY + NS, BAR_HW = BAR_STATS + 1,
              BAR_HALO = BAR_HW + 1  , BAR_EMB = BAR_HALO + 2, BAR_WACQ = BAR_EMB + 1, BAR_XH = BAR_WACQ + 1,
              NBAR = BAR_XH + 1;
constexpr int SM_TOTAL = SM_BAR + NBAR * 8;
static_assert(SM_TOTAL <= 232448, "smem");
constexpr int OUT_PITCH = 144;

constexpr unsigned SPIN_LIMIT = 1u << 16;
constexpr unsigned EMB_EMPTY = 0xffffffffu;

struct Scratch {
    float acc[2 * NB * 32];
    unsigned wcnt[NB * 32];
    unsigned emb[NB * C];
    unsigned hflag[NCTA * 32];
    unsigned char wt[2 * 72 * STEP_BYTES];
    unsigned char h[NCTA * ROW_BYTES];
};
__device__ __align__(1024) Scratch g_s;
#define TL(i) do {} while (0)
#define TLG(i) do {} while (0)

__device__ __forceinline__ uint32_t smem_u32(const void* p) { return (uint32_t)__cvta_generic_to_shared(p); }
__device__ __forceinline__ void mbar_init(uint32_t bar, int cnt) {
    asm volatile("mbarrier.init.shared::cta.b64 [%0], %1;" ::"r"(bar), "r"(cnt) : "memory");
}
__device__ __forceinline__ void mbar_arrive(uint32_t bar) {
    asm volatile("mbarrier.arrive.shared::cta.b64 _, [%0];" ::"r"(bar) : "memory");
}
__device__ __forceinline__ void mbar_expect(uint32_t bar, uint32_t bytes) {
    asm volatile("mbarrier.arrive.expect_tx.shared::cta.b64 _, [%0], %1;" ::"r"(bar), "r"(bytes) : "memory");
}
__device__ __forceinline__ bool mbar_try(uint32_t bar, uint32_t par) {
    uint32_t ok;
    asm volatile("{\n.reg .pred p;\nmbarrier.try_wait.parity.shared::cta.b64 p, [%1], %2;\nselp.u32 %0, 1, 0, p;\n}"
                 : "=r"(ok) : "r"(bar), "r"(par) : "memory");
    return ok;
}
__device__ __forceinline__ void mbar_wait(uint32_t bar, uint32_t par) {
    unsigned it = 0;
#pragma unroll 1
    while (!mbar_try(bar, par) && ++it < SPIN_LIMIT) {}
}
__device__ __forceinline__ void fence_async_smem() { asm volatile("fence.proxy.async.shared::cta;" ::: "memory"); }
__device__ __forceinline__ void fence_async_global() { asm volatile("fence.proxy.async.global;" ::: "memory"); }
__device__ __forceinline__ void bar_sync(int id, int n) { asm volatile("bar.sync %0, %1;" ::"r"(id), "r"(n) : "memory"); }
__device__ __forceinline__ void bulk_g2s(uint32_t dst, const void* src, uint32_t bytes, uint32_t bar) {
    asm volatile("cp.async.bulk.shared::cluster.global.mbarrier::complete_tx::bytes [%0], [%1], %2, [%3];"
                 ::"r"(dst), "l"(src), "r"(bytes), "r"(bar) : "memory");
}
__device__ __forceinline__ uint4 ld_relaxed_v4(const void* p) {
    uint4 v;
    asm volatile("ld.relaxed.gpu.global.v4.u32 {%0,%1,%2,%3}, [%4];" : "=r"(v.x), "=r"(v.y), "=r"(v.z), "=r"(v.w) : "l"(p) : "memory");
    return v;
}
__device__ __forceinline__ unsigned ld_acquire(const void* p) {
    unsigned v;
    asm volatile("ld.acquire.gpu.global.u32 %0, [%1];" : "=r"(v) : "l"(p) : "memory");
    return v;
}
__device__ __forceinline__ void st_relaxed(void* p, unsigned v) {
    asm volatile("st.relaxed.gpu.global.u32 [%0], %1;" ::"l"(p), "r"(v) : "memory");
}
__device__ __forceinline__ void red_add4(float* p, float a, float b, float c, float d) {
    asm volatile("red.relaxed.gpu.global.add.v4.f32 [%0], {%1,%2,%3,%4};" ::"l"(p), "f"(a), "f"(b), "f"(c), "f"(d) : "memory");
}
__device__ __forceinline__ float bf_lo(uint32_t u) { return __uint_as_float(u << 16); }
__device__ __forceinline__ float bf_hi(uint32_t u) { return __uint_as_float(u & 0xffff0000u); }
__device__ __forceinline__ uint32_t pack_bf(float lo, float hi) {
    uint32_t r;
    asm("cvt.rn.bf16x2.f32 %0, %1, %2;" : "=r"(r) : "f"(hi), "f"(lo));
    return r;
}
__device__ __forceinline__ float tanh_fast(float x) {
    float r;
    asm("tanh.approx.f32 %0, %1;" : "=f"(r) : "f"(x));
    return r;
}
__device__ __forceinline__ float silu_half(float h) { return fmaf(h, tanh_fast(h), h); }
__device__ __forceinline__ void ldsm4(uint32_t (&u)[4], uint32_t a) {
    asm volatile("ldmatrix.sync.aligned.m8n8.x4.shared.b16 {%0,%1,%2,%3}, [%4];"
                 : "=r"(u[0]), "=r"(u[1]), "=r"(u[2]), "=r"(u[3]) : "r"(a) : "memory");
}
__device__ __forceinline__ void ldsm4t(uint32_t (&u)[4], uint32_t a) {
    asm volatile("ldmatrix.sync.aligned.m8n8.x4.trans.shared.b16 {%0,%1,%2,%3}, [%4];"
                 : "=r"(u[0]), "=r"(u[1]), "=r"(u[2]), "=r"(u[3]) : "r"(a) : "memory");
}
__device__ __forceinline__ void stsm4(uint32_t a, uint32_t p0, uint32_t p1, uint32_t p2, uint32_t p3) {
    asm volatile("stmatrix.sync.aligned.m8n8.x4.shared.b16 [%0], {%1,%2,%3,%4};" ::"r"(a), "r"(p0), "r"(p1), "r"(p2), "r"(p3) : "memory");
}
__device__ __forceinline__ void stsm4t(uint32_t a, uint32_t p0, uint32_t p1, uint32_t p2, uint32_t p3) {
    asm volatile("stmatrix.sync.aligned.m8n8.x4.trans.shared.b16 [%0], {%1,%2,%3,%4};" ::"r"(a), "r"(p0), "r"(p1), "r"(p2), "r"(p3) : "memory");
}

#define R8(o) "+f"(d[o]), "+f"(d[o + 1]), "+f"(d[o + 2]), "+f"(d[o + 3]), "+f"(d[o + 4]), "+f"(d[o + 5]), "+f"(d[o + 6]), "+f"(d[o + 7])
__device__ __forceinline__ void wgmma128(float (&d)[64], uint32_t alo, uint32_t blo) {
    asm volatile(
        "{\n.reg .b64 da, db;\nmov.b64 da, {%64, %66};\nmov.b64 db, {%65, %66};\n"
        "wgmma.mma_async.sync.aligned.m64n128k16.f32.bf16.bf16 "
        "{%0,%1,%2,%3,%4,%5,%6,%7,%8,%9,%10,%11,%12,%13,%14,%15,%16,%17,%18,%19,%20,%21,%22,%23,%24,%25,%26,%27,%28,%29,%30,%31,"
        "%32,%33,%34,%35,%36,%37,%38,%39,%40,%41,%42,%43,%44,%45,%46,%47,%48,%49,%50,%51,%52,%53,%54,%55,%56,%57,%58,%59,%60,%61,%62,%63},"
        " da, db, 1, 1, 1, 0, 0;\n}"
        : R8(0), R8(8), R8(16), R8(24), R8(32), R8(40), R8(48), R8(56)
        : "r"(alo), "r"(blo), "r"(8));
}
__host__ __device__ constexpr int stage_ky(int s) { return (s >> 3) == 0 ? 1 : ((s >> 3) == 1 ? 0 : 2); }
__device__ __forceinline__ void fence_acc(float (&d)[64]) {
#pragma unroll
    for (int i = 0; i < 64; i++) asm volatile("" : "+f"(d[i])::"memory");
}

__global__ void __launch_bounds__(NTHREADS, 1)
resblock_kernel(const __nv_bfloat16* __restrict__ x, const __nv_bfloat16* __restrict__ t_emb,
                const __nv_bfloat16* __restrict__ g1, const __nv_bfloat16* __restrict__ be1,
                const __nv_bfloat16* __restrict__ w1, const __nv_bfloat16* __restrict__ w_emb,
                const __nv_bfloat16* __restrict__ g2, const __nv_bfloat16* __restrict__ be2,
                const __nv_bfloat16* __restrict__ w2, __nv_bfloat16* __restrict__ out) {
    extern __shared__ __align__(128) unsigned char smem[];
    const uint32_t sb = smem_u32(smem);
    const uint32_t bars = sb + SM_BAR;
    const int tid = threadIdx.x, warp = tid >> 5, lane = tid & 31;
    const int cta = blockIdx.x, b = cta >> 6, r = cta & 63;
    if (tid == 0) { TL(0); TLG(1); }

    if (warp < 4) {
        const int wq = warp;
        if (tid < NBAR) {
            const int cnt = tid < BAR_WEMPTY ? 5 : (tid < BAR_STATS || tid == BAR_HW) ? 4 : (tid == BAR_XH ? 256 : 1);
            mbar_init(bars + 8 * tid, cnt);
        }
        if (tid < 96) {
            *reinterpret_cast<uint4*>(smem + SM_ACT + (tid >> 1) * CH_PITCH + (tid & 1) * 65 * 16) = make_uint4(0, 0, 0, 0);
        }
        if (r == 0 || r == HW - 1) {
            uint4* z = reinterpret_cast<uint4*>(smem + SM_ACT + (r == 0 ? 0 : 2 * ROW_BYTES));
            for (int i = tid; i < ROW_BYTES / 16; i += 128) z[i] = make_uint4(0, 0, 0, 0);
        }
        fence_async_smem();
        bar_sync(0, NTHREADS);

        float d[64];
#pragma unroll
        for (int i = 0; i < 64; i++) d[i] = 0.f;
        const uint32_t alo = (((sb + SM_ACT) & 0x3FFFF) >> 4) | ((CH_PITCH >> 4) << 16);
        const uint32_t blo = (((sb + SM_W) & 0x3FFFF) >> 4) | ((2048 >> 4) << 16);
#pragma unroll 1
        for (int conv = 0; conv < 2; conv++) {
            fence_acc(d);
#pragma unroll
            for (int s = 0; s < NSTAGE; s++) {
                mbar_wait(bars + 8 * (BAR_FULL + s), conv);
                if (s == 0 && tid == 0) TL(9 + conv * 8);
                asm volatile("wgmma.fence.sync.aligned;" ::: "memory");
#pragma unroll
                for (int kx = 0; kx < 3; kx++)
                    wgmma128(d, alo + ((stage_ky(s) * ROW_BYTES + (s & 7) * 2 * CH_PITCH) >> 4) + kx,
                             blo + (((s % NS) * STAGE_BYTES + kx * STEP_BYTES) >> 4));
                asm volatile("wgmma.commit_group.sync.aligned;" ::: "memory");
                if (s > 0) {
                    asm volatile("wgmma.wait_group.sync.aligned 1;" ::: "memory");
                    if (lane == 0) mbar_arrive(bars + 8 * (BAR_WEMPTY + (s - 1) % NS));
                }
            }
            asm volatile("wgmma.wait_group.sync.aligned 0;" ::: "memory");
            fence_acc(d);
            if (tid == 0) TL(10 + conv * 8);
            if (conv == 1) break;

            if (lane == 0) mbar_arrive(bars + 8 * (BAR_WEMPTY + (NSTAGE - 1) % NS));
            mbar_wait(bars + 8 * BAR_EMB, 0);
            const float* embs = reinterpret_cast<const float*>(smem + SM_EMB);
            float st[8];
#pragma unroll
            for (int g = 0; g < 4; g++) {
                float s = 0.f, q = 0.f, s2 = 0.f, q2 = 0.f;
#pragma unroll
                for (int jj = 0; jj < 4; jj++) {
                    const int j = g * 4 + jj;
                    const float2 e = *reinterpret_cast<const float2*>(embs + 8 * j + 2 * (lane & 3));
                    d[4 * j + 0] += e.x; d[4 * j + 1] += e.y; d[4 * j + 2] += e.x; d[4 * j + 3] += e.y;
                    s += d[4 * j + 0]; q = fmaf(d[4 * j + 0], d[4 * j + 0], q);
                    s2 += d[4 * j + 1]; q2 = fmaf(d[4 * j + 1], d[4 * j + 1], q2);
                    s += d[4 * j + 2]; q = fmaf(d[4 * j + 2], d[4 * j + 2], q);
                    s2 += d[4 * j + 3]; q2 = fmaf(d[4 * j + 3], d[4 * j + 3], q2);
                }
                st[2 * g] = s + s2; st[2 * g + 1] = q + q2;
            }
            {
                const bool h16 = lane & 16, h8 = lane & 8, h4 = lane & 4;
                float a[4];
#pragma unroll
                for (int i = 0; i < 4; i++) {
                    float give = h16 ? st[i] : st[i + 4], keep = h16 ? st[i + 4] : st[i];
                    a[i] = keep + __shfl_xor_sync(0xffffffffu, give, 16);
                }
                float c2[2];
#pragma unroll
                for (int i = 0; i < 2; i++) {
                    float give = h8 ? a[i] : a[i + 2], keep = h8 ? a[i + 2] : a[i];
                    c2[i] = keep + __shfl_xor_sync(0xffffffffu, give, 8);
                }
                float give = h4 ? c2[0] : c2[1], keep = h4 ? c2[1] : c2[0];
                float t = keep + __shfl_xor_sync(0xffffffffu, give, 4);
                t += __shfl_xor_sync(0xffffffffu, t, 2);
                t += __shfl_xor_sync(0xffffffffu, t, 1);
                float* red = reinterpret_cast<float*>(smem + SM_RED);
                if ((lane & 3) == 0) red[(lane >> 2) * 4 + wq] = t;
                bar_sync(2, 128);
                if (tid < 4) {
                    const float4 p = *reinterpret_cast<const float4*>(red + tid * 8);
                    const float4 p2 = *reinterpret_cast<const float4*>(red + tid * 8 + 4);
                    red_add4(&g_s.acc[(NB + b) * 32 + tid * 4], 1.f, (p.x + p.y) + (p.z + p.w), (p2.x + p2.y) + (p2.z + p2.w), 1.f);
                }
                if (tid == 0) TL(11);
            }
            const uint32_t hbase = sb + SM_ACT + ROW_BYTES + (lane >> 4) * CH_PITCH + (1 + wq * 16 + (lane & 15)) * 16;
            uint32_t* hg = reinterpret_cast<uint32_t*>(g_s.h + (size_t)cta * ROW_BYTES + (1 + wq * 16) * 16) + lane;
#pragma unroll
            for (int j = 0; j < 16; j += 2) {
                uint32_t p0 = pack_bf(d[4 * j + 0], d[4 * j + 1]), p1 = pack_bf(d[4 * j + 2], d[4 * j + 3]);
                uint32_t p2 = pack_bf(d[4 * j + 4], d[4 * j + 5]), p3 = pack_bf(d[4 * j + 6], d[4 * j + 7]);
                stsm4(hbase + j * CH_PITCH, p0, p1, p2, p3);
                hg[j * (CH_PITCH / 4)] = p0; hg[j * (CH_PITCH / 4) + 32] = p1;
                hg[(j + 1) * (CH_PITCH / 4)] = p2; hg[(j + 1) * (CH_PITCH / 4) + 32] = p3;
            }
            __syncwarp();
            if (lane == 0) mbar_arrive(bars + 8 * BAR_HW);
            if (tid == 0) TL(12);
            const uint32_t xbase = sb + SM_STG + 16384 + ((lane >> 4) * 8 + (lane & 7)) * 128 + (((2 * wq + ((lane >> 3) & 1)) ^ (lane & 7)) << 4);
#pragma unroll
            for (int j = 0; j < 16; j += 2) {
                uint32_t p[4];
                ldsm4t(p, xbase + j * 1024);
                d[4 * j + 0] = bf_lo(p[0]); d[4 * j + 1] = bf_hi(p[0]); d[4 * j + 2] = bf_lo(p[1]); d[4 * j + 3] = bf_hi(p[1]);
                d[4 * j + 4] = bf_lo(p[2]); d[4 * j + 5] = bf_hi(p[2]); d[4 * j + 6] = bf_lo(p[3]); d[4 * j + 7] = bf_hi(p[3]);
            }
        }
        {
            const uint32_t obase = sb + SM_STG + ((lane >> 4) * 8 + (lane & 7)) * OUT_PITCH + (wq * 16 + ((lane >> 3) & 1) * 8) * 2;
#pragma unroll
            for (int j = 0; j < 16; j += 2) {
                stsm4t(obase + j * 8 * OUT_PITCH, pack_bf(d[4 * j + 0], d[4 * j + 1]), pack_bf(d[4 * j + 2], d[4 * j + 3]),
                       pack_bf(d[4 * j + 4], d[4 * j + 5]), pack_bf(d[4 * j + 6], d[4 * j + 7]));
            }
            bar_sync(2, 128);
            const int oc0 = tid >> 3, seg = tid & 7;
            __nv_bfloat16* dst = out + ((size_t)(b * C + oc0) * HW + r) * HW + seg * 8;
#pragma unroll
            for (int i = 0; i < 8; i++) {
                const uint4 o = *reinterpret_cast<const uint4*>(smem + SM_STG + (oc0 + 16 * i) * OUT_PITCH + seg * 16);
                *reinterpret_cast<uint4*>(dst + (size_t)i * 16 * HW * HW) = o;
            }
            if (tid == 0) { TL(20); TLG(21); }
        }
    } else if (warp < 12) {
        const int nw = warp - 4;
        {
            const int c0 = nw * 16 + (lane >> 3), seg = lane & 7;
            const uint4* src = reinterpret_cast<const uint4*>(x + ((size_t)(b * C + c0) * HW + r) * HW) + seg;
            uint4 v[4];
#pragma unroll
            for (int i = 0; i < 4; i++) v[i] = __ldg(src + (size_t)i * 4 * (HW * HW / 8));
            bar_sync(0, NTHREADS);
            if (tid == 128) TL(30);
            float s = 0.f, q = 0.f, s2 = 0.f, q2 = 0.f;
#pragma unroll
            for (int i = 0; i < 4; i++) {
                const uint32_t u[4] = {v[i].x, v[i].y, v[i].z, v[i].w};
#pragma unroll
                for (int k = 0; k < 4; k++) {
                    const float lo = bf_lo(u[k]), hi = bf_hi(u[k]);
                    s += lo; q = fmaf(lo, lo, q);
                    s2 += hi; q2 = fmaf(hi, hi, q2);
                }
            }
            s += s2; q += q2;
            float give = (lane < 16) ? q : s, keep = (lane < 16) ? s : q;
            keep += __shfl_xor_sync(0xffffffffu, give, 16);
            if (tid == 128) TL(2);
#pragma unroll
            for (int m = 8; m >= 1; m >>= 1) keep += __shfl_xor_sync(0xffffffffu, keep, m);
            float* red = reinterpret_cast<float*>(smem + SM_RED);
            if ((lane & 15) == 0) red[nw * 2 + (lane >> 4)] = keep;
            bar_sync(3, 256);
            if (tid < 128 + 4) {
                const float4 p = *reinterpret_cast<const float4*>(red + lane * 4);
                red_add4(&g_s.acc[b * 32 + lane * 4], 1.f, p.x + p.z, p.y + p.w, 1.f);
            }
            if (tid == 128) TL(3);
#pragma unroll
            for (int hrow = 0; hrow < 2; hrow++) {
                const int row = r - 1 + 2 * hrow;
                if (row >= 0 && row < HW) {
#pragma unroll
                    for (int i = 0; i < 4; i++) {
                        const int c = c0 + 4 * i;
                        const uint32_t dst = sb + SM_STG + hrow * 2 * 16384 + c * 128 + ((seg ^ (c & 7)) << 4);
                        asm volatile("cp.async.cg.shared.global [%0], [%1], 16;"
                                     ::"r"(dst), "l"(src + (ptrdiff_t)(2 * hrow - 1) * (HW / 8) + (size_t)i * 4 * (HW * HW / 8)) : "memory");
                    }
                }
            }
            asm volatile("cp.async.mbarrier.arrive.noinc.shared::cta.b64 [%0];" ::"r"(bars + 8 * BAR_XH) : "memory");
#pragma unroll
            for (int i = 0; i < 4; i++) {
                const int c = c0 + 4 * i;
                *reinterpret_cast<uint4*>(smem + SM_STG + 16384 + c * 128 + ((seg ^ (c & 7)) << 4)) = v[i];
            }
            bar_sync(3, 256);
        }
        const int par = nw >> 2;
        const int csel = (nw >> 1) & 1, half = nw & 1;
        const uint32_t act_off = sb + SM_ACT + csel * CH_PITCH + (1 + half * 32 + lane) * 16;
        const uint32_t stg_off = sb + SM_STG + (csel * 8 + (lane & 7)) * 128 + (((half * 4 + (lane >> 3)) ^ (lane & 7)) << 4);
        const unsigned char* coef = smem + SM_COEF + csel * 64 + (lane & 3) * 16;
#pragma unroll 1
        for (int conv = 0; conv < 2; conv++) {
            if (conv == 1) mbar_wait(bars + 8 * BAR_HW, 0);
            mbar_wait(bars + 8 * BAR_STATS, conv);
            if (tid == 128) TL(22 + conv * 4);
#pragma unroll 1
            for (int o = 0; o < 3; o++) {
                const int ky = (o == 0) ? 1 : (o == 1 ? 0 : 2);
                const int irow = r - 1 + ky;
                const bool valid = irow >= 0 && irow < HW;
                if (valid && o > 0) mbar_wait(bars + 8 * (conv ? BAR_HALO + o - 1 : BAR_XH), 0);
#pragma unroll 1
                for (int kc = par; kc < 8; kc += 2) {
                    if (valid) {
                        const uint32_t ao = act_off + ky * ROW_BYTES + kc * 2 * CH_PITCH;
                        uint32_t u[4];
                        if (conv == 0) ldsm4t(u, stg_off + ky * 16384 + kc * 2048);
                        else ldsm4(u, ao);
                        const float4 cf = *reinterpret_cast<const float4*>(coef + kc * 128);
#pragma unroll
                        for (int i = 0; i < 4; i++)
                            u[i] = pack_bf(silu_half(fmaf(bf_lo(u[i]), cf.x, cf.z)), silu_half(fmaf(bf_hi(u[i]), cf.y, cf.w)));
                        stsm4(ao, u[0], u[1], u[2], u[3]);
                        if (tid == 128 && o == 0 && kc == 0) TL(23 + conv * 4);
                        fence_async_smem();
                        if (tid == 128 && o == 0 && kc == 0) TL(24 + conv * 4);
                    }
                    __syncwarp();
                    if (lane == 0) mbar_arrive(bars + 8 * (BAR_FULL + o * 8 + kc));
                    if (tid == 128 && o == 0 && kc == 0) TL(8 + conv * 8);
                }
            }
        }
    } else if (warp == 12) {
        {
            const int l16 = lane & 15, cv = lane >> 4;
            const int oc = (cta & 15) * 8 + (l16 & 7), kc = cta >> 4, hh = l16 >> 3;
            const uint4* src = reinterpret_cast<const uint4*>((cv ? w2 : w1) + ((size_t)oc * C + kc * 16 + hh * 8) * 9);
            uint32_t w[36];
#pragma unroll
            for (int i = 0; i < 9; i++) {
                const uint4 t = __ldg(src + i);
                w[4 * i] = t.x; w[4 * i + 1] = t.y; w[4 * i + 2] = t.z; w[4 * i + 3] = t.w;
            }
            if (lane == 0) g_s.hflag[cta * 32] = 0;
            if (lane < 2) g_s.emb[b * C + 2 * r + lane] = EMB_EMPTY;
            if (r == 0 && lane < 16) g_s.acc[(NB + b) * 32 + lane] = 0.f;
            bar_sync(0, NTHREADS);
            unsigned char* dst = g_s.wt + (size_t)cv * 72 * STEP_BYTES + kc * STAGE_BYTES + hh * 2048 + oc * 16;
#pragma unroll
            for (int tap = 0; tap < 9; tap++) {
                uint32_t o[4];
#pragma unroll
                for (int m = 0; m < 4; m++) {
                    const int i0 = 18 * m + tap, i1 = i0 + 9;
                    const uint32_t sel = ((i0 & 1) ? 0x32u : 0x10u) | ((i1 & 1) ? 0x7600u : 0x5400u);
                    o[m] = __byte_perm(w[i0 >> 1], w[i1 >> 1], sel);
                }
                const int ky = tap / 3, kx = tap % 3;
                const int kyo = (ky == 1) ? 0 : (ky == 0 ? 1 : 2);
                *reinterpret_cast<uint4*>(dst + (kyo * 24 + kx) * STEP_BYTES) = make_uint4(o[0], o[1], o[2], o[3]);
            }
            if (lane == 0) TL(4);
            __syncwarp();
            if (lane < 2) asm volatile("red.release.gpu.global.add.u32 [%0], 1;" ::"l"(&g_s.wcnt[lane * 32]) : "memory");
        }
        if (lane == 0) {
            TL(5);
            unsigned it = 0;
            while (ld_acquire(&g_s.wcnt[b * 32]) < (unsigned)NCTA && ++it < SPIN_LIMIT) {}
            fence_async_global();
            TL(6);
            int slot = 0, st = 0; uint32_t par = 1;
#pragma unroll 1
            for (int g = 0; g < 2 * NSTAGE; g++) {
                mbar_wait(bars + 8 * (BAR_WEMPTY + slot), par);
                mbar_expect(bars + 8 * (BAR_FULL + st), STAGE_BYTES);
                bulk_g2s(sb + SM_W + slot * STAGE_BYTES, g_s.wt + (size_t)g * STAGE_BYTES, STAGE_BYTES, bars + 8 * (BAR_FULL + st));
                if (g == NS - 1) mbar_arrive(bars + 8 * BAR_WACQ);
                if (++slot == NS) { slot = 0; par ^= 1; }
                if (++st == NSTAGE) st = 0;
            }
        }
    } else if (warp == 13) {
        const uint2 ga1 = __ldg(reinterpret_cast<const uint2*>(g1) + lane), bt1 = __ldg(reinterpret_cast<const uint2*>(be1) + lane);
        const uint2 ga2 = __ldg(reinterpret_cast<const uint2*>(g2) + lane), bt2 = __ldg(reinterpret_cast<const uint2*>(be2) + lane);
        bar_sync(0, NTHREADS);
#pragma unroll 1
        for (int conv = 0; conv < 2; conv++) {
            if (conv == 1) mbar_wait(bars + 8 * BAR_HW, 0);
            const float* src = &g_s.acc[(conv * NB + b) * 32 + (lane >> 3) * 4];
            uint4 f;
            unsigned it = 0;
            while (true) {
                f = ld_relaxed_v4(src);
                const bool ok = (f.x == 0x42800000u) & (f.w == 0x42800000u);
                if (__all_sync(0xffffffffu, ok) || ++it > SPIN_LIMIT) break;
            }
            if (lane == 0) TL(7 + conv * 8);
            const float inv_n = 1.0f / (32.0f * HW * HW);
            const float mean = __uint_as_float(f.y) * inv_n;
            const float var = fmaxf(fmaf(-mean, mean, __uint_as_float(f.z) * inv_n), 0.f);
            const float rs = 0.5f * rsqrtf(var + 1e-5f);
            const uint2 ga = conv ? ga2 : ga1, bt = conv ? bt2 : bt1;
            float4 c0, c1;
            c0.x = rs * bf_lo(ga.x); c0.y = rs * bf_hi(ga.x); c1.x = rs * bf_lo(ga.y); c1.y = rs * bf_hi(ga.y);
            c0.z = fmaf(-mean, c0.x, 0.5f * bf_lo(bt.x)); c0.w = fmaf(-mean, c0.y, 0.5f * bf_hi(bt.x));
            c1.z = fmaf(-mean, c1.x, 0.5f * bf_lo(bt.y)); c1.w = fmaf(-mean, c1.y, 0.5f * bf_hi(bt.y));
            float4* cf = reinterpret_cast<float4*>(smem + SM_COEF + lane * 32);
            cf[0] = c0; cf[1] = c1;
            __syncwarp();
            if (lane == 0) { mbar_arrive(bars + 8 * BAR_STATS); TL(25 + conv * 4); }
        }
        if (r == 0) {
            if (lane < 16) g_s.acc[b * 32 + lane] = 0.f;
            if (lane == 0) g_s.wcnt[b * 32] = 0;
        }
    } else {
        bar_sync(0, NTHREADS);
        mbar_wait(bars + 8 * BAR_WACQ, 0);
        {
            float e0 = 0.f, e1 = 0.f;
            const uint32_t* wsrc = reinterpret_cast<const uint32_t*>(w_emb) + r;
            const unsigned short* tsrc = reinterpret_cast<const unsigned short*>(t_emb) + b * E;
#pragma unroll 8
            for (int i = 0; i < E / 32; i++) {
                const int e = i * 32 + lane;
                const uint32_t wv = __ldg(wsrc + e * (C / 2));
                const float t = __uint_as_float((uint32_t)__ldg(tsrc + e) << 16);
                const float sv = silu_half(0.5f * t);
                e0 = fmaf(sv, bf_lo(wv), e0); e1 = fmaf(sv, bf_hi(wv), e1);
            }
            float give = (lane < 16) ? e1 : e0, keep = (lane < 16) ? e0 : e1;
            keep += __shfl_xor_sync(0xffffffffu, give, 16);
#pragma unroll
            for (int m = 8; m >= 1; m >>= 1) keep += __shfl_xor_sync(0xffffffffu, keep, m);
            unsigned bits = __float_as_uint(keep);
            if (bits == EMB_EMPTY) bits = 0x7fffffffu;
            if ((lane & 15) == 0) st_relaxed(&g_s.emb[b * C + 2 * r + (lane >> 4)], bits);
            unsigned it = 0;
            uint4 f;
            while (true) {
                f = ld_relaxed_v4(&g_s.emb[b * C + lane * 4]);
                const bool ok = (f.x != EMB_EMPTY) & (f.y != EMB_EMPTY) & (f.z != EMB_EMPTY) & (f.w != EMB_EMPTY);
                if (__all_sync(0xffffffffu, ok) || ++it > SPIN_LIMIT) break;
                __nanosleep(200);
            }
            *reinterpret_cast<uint4*>(smem + SM_EMB + lane * 16) = f;
            __syncwarp();
            if (lane == 0) { mbar_arrive(bars + 8 * BAR_EMB); TL(19); }
        }
        if (lane == 0) {
            mbar_wait(bars + 8 * BAR_HW, 0);
            asm volatile("st.release.gpu.global.u32 [%0], %1;" ::"l"(&g_s.hflag[cta * 32]), "r"(1) : "memory");
            TL(13);
        }
        __syncwarp();
        if (lane < 2) {
            const int irow = r - 1 + 2 * lane;
            if (irow >= 0 && irow < HW) {
                const int nb = cta - 1 + 2 * lane;
                unsigned it = 0;
                while (ld_acquire(&g_s.hflag[nb * 32]) == 0 && ++it < SPIN_LIMIT) {}
                fence_async_global();
                mbar_expect(bars + 8 * (BAR_HALO + lane), ROW_BYTES);
                bulk_g2s(sb + SM_ACT + 2 * lane * ROW_BYTES, g_s.h + (size_t)nb * ROW_BYTES, ROW_BYTES, bars + 8 * (BAR_HALO + lane));
                if (lane == 0) TL(14);
            }
        }
    }
}

}

extern "C" void kernel_launch(void* const* d_in, const int* in_sizes, int n_in, void* d_out, int out_size) {
    (void)in_sizes; (void)n_in; (void)out_size;
    static bool init = false;
    if (!init) {
        cudaFuncSetAttribute(resblock_kernel, cudaFuncAttributeMaxDynamicSharedMemorySize, SM_TOTAL);
        init = true;
    }
    resblock_kernel<<<NCTA, NTHREADS, SM_TOTAL>>>(
        (const __nv_bfloat16*)d_in[0], (const __nv_bfloat16*)d_in[1], (const __nv_bfloat16*)d_in[2],
        (const __nv_bfloat16*)d_in[3], (const __nv_bfloat16*)d_in[4], (const __nv_bfloat16*)d_in[5],
        (const __nv_bfloat16*)d_in[6], (const __nv_bfloat16*)d_in[7], (const __nv_bfloat16*)d_in[8],
        (__nv_bfloat16*)d_out);
}
```

```cpp
#include <cuda_runtime.h>
#include <cuda_bf16.h>
#include <stdint.h>

namespace {

constexpr int C = 128, HW = 64, NB = 2, E = 768;
constexpr int NCTA = NB * HW;
constexpr int NTHREADS = 15 * 32;
constexpr int CH_PITCH = 66 * 16;
constexpr int ROW_BYTES = 16 * CH_PITCH;
constexpr int STEP_BYTES = 4096;
constexpr int STAGE_BYTES = 3 * STEP_BYTES;
constexpr int NSTAGE = 24;
constexpr int NS = 8;

constexpr int SM_ACT = 0;
constexpr int SM_STG = SM_ACT + 3 * ROW_BYTES;
constexpr int SM_W = SM_STG + 3 * 16384;
constexpr int SM_COEF = SM_W + NS * STAGE_BYTES;
constexpr int SM_EMB = SM_COEF + 1024;
constexpr int SM_RED = SM_EMB + 512;
constexpr int SM_BNC = SM_RED + 128;
constexpr int SM_BAR = SM_BNC + 2 * 2304;
constexpr int BAR_FULL = 0, BAR_WEMPTY = NSTAGE, BAR_STATS = BAR_WEMPTY + NS, BAR_HW = BAR_STATS + 1,
              BAR_HALO = BAR_HW + 1  , BAR_EMB = BAR_HALO + 2, BAR_WACQ = BAR_EMB + 1, BAR_XH = BAR_WACQ + 1,
              NBAR = BAR_XH + 1;
constexpr int SM_TOTAL = SM_BAR + NBAR * 8;
static_assert(SM_TOTAL <= 232448, "smem");
constexpr int OUT_PITCH = 144;

constexpr unsigned SPIN_LIMIT = 1u << 16;
constexpr uint32_t SMEM_BASE = 0x400;

struct Scratch {
    float acc[2 * NB * 32];
    unsigned wcnt[2 * NB * 32];
    float emb[NB * C];
    unsigned hflag[NCTA * 32];
    unsigned char wt[2 * 72 * STEP_BYTES];
    unsigned char h[NCTA * ROW_BYTES];
};
__device__ __align__(1024) Scratch g_s;
#define TL(i) do {} while (0)
#define TLG(i) do {} while (0)

__device__ __forceinline__ uint32_t smem_u32(const void* p) { return (uint32_t)__cvta_generic_to_shared(p); }
__device__ __forceinline__ void mbar_init(uint32_t bar, int cnt) {
    asm volatile("mbarrier.init.shared::cta.b64 [%0], %1;" ::"r"(bar), "r"(cnt) : "memory");
}
__device__ __forceinline__ void mbar_arrive(uint32_t bar) {
    asm volatile("mbarrier.arrive.shared::cta.b64 _, [%0];" ::"r"(bar) : "memory");
}
__device__ __forceinline__ void mbar_expect(uint32_t bar, uint32_t bytes) {
    asm volatile("mbarrier.arrive.expect_tx.shared::cta.b64 _, [%0], %1;" ::"r"(bar), "r"(bytes) : "memory");
}
__device__ __forceinline__ bool mbar_try(uint32_t bar, uint32_t par) {
    uint32_t ok;
    asm volatile("{\n.reg .pred p;\nmbarrier.try_wait.parity.shared::cta.b64 p, [%1], %2;\nselp.u32 %0, 1, 0, p;\n}"
                 : "=r"(ok) : "r"(bar), "r"(par) : "memory");
    return ok;
}
__device__ __forceinline__ void mbar_wait(uint32_t bar, uint32_t par) {
    unsigned it = 0;
#pragma unroll 1
    while (!mbar_try(bar, par) && ++it < SPIN_LIMIT) {}
}
__device__ __forceinline__ void fence_async_smem() { asm volatile("fence.proxy.async.shared::cta;" ::: "memory"); }
__device__ __forceinline__ void fence_async_global() { asm volatile("fence.proxy.async.global;" ::: "memory"); }
__device__ __forceinline__ void bar_sync(int id, int n) { asm volatile("bar.sync %0, %1;" ::"r"(id), "r"(n) : "memory"); }
__device__ __forceinline__ void bulk_g2s(uint32_t dst, const void* src, uint32_t bytes, uint32_t bar) {
    asm volatile("cp.async.bulk.shared::cluster.global.mbarrier::complete_tx::bytes [%0], [%1], %2, [%3];"
                 ::"r"(dst), "l"(src), "r"(bytes), "r"(bar) : "memory");
}
__device__ __forceinline__ uint4 ld_relaxed_v4(const void* p) {
    uint4 v;
    asm volatile("ld.relaxed.gpu.global.v4.u32 {%0,%1,%2,%3}, [%4];" : "=r"(v.x), "=r"(v.y), "=r"(v.z), "=r"(v.w) : "l"(p) : "memory");
    return v;
}
__device__ __forceinline__ unsigned ld_acquire(const void* p) {
    unsigned v;
    asm volatile("ld.acquire.gpu.global.u32 %0, [%1];" : "=r"(v) : "l"(p) : "memory");
    return v;
}
__device__ __forceinline__ void st_relaxed(void* p, unsigned v) {
    asm volatile("st.relaxed.gpu.global.u32 [%0], %1;" ::"l"(p), "r"(v) : "memory");
}
__device__ __forceinline__ void red_add4(float* p, float a, float b, float c, float d) {
    asm volatile("red.relaxed.gpu.global.add.v4.f32 [%0], {%1,%2,%3,%4};" ::"l"(p), "f"(a), "f"(b), "f"(c), "f"(d) : "memory");
}
__device__ __forceinline__ float bf_lo(uint32_t u) { return __uint_as_float(u << 16); }
__device__ __forceinline__ float bf_hi(uint32_t u) { return __uint_as_float(u & 0xffff0000u); }
__device__ __forceinline__ uint32_t pack_bf(float lo, float hi) {
    uint32_t r;
    asm("cvt.rn.bf16x2.f32 %0, %1, %2;" : "=r"(r) : "f"(hi), "f"(lo));
    return r;
}
__device__ __forceinline__ float tanh_fast(float x) {
    float r;
    asm("tanh.approx.f32 %0, %1;" : "=f"(r) : "f"(x));
    return r;
}
__device__ __forceinline__ float silu_half(float h) { return fmaf(h, tanh_fast(h), h); }
__device__ __forceinline__ void ldsm4(uint32_t (&u)[4], uint32_t a) {
    asm volatile("ldmatrix.sync.aligned.m8n8.x4.shared.b16 {%0,%1,%2,%3}, [%4];"
                 : "=r"(u[0]), "=r"(u[1]), "=r"(u[2]), "=r"(u[3]) : "r"(a) : "memory");
}
__device__ __forceinline__ void ldsm4t(uint32_t (&u)[4], uint32_t a) {
    asm volatile("ldmatrix.sync.aligned.m8n8.x4.trans.shared.b16 {%0,%1,%2,%3}, [%4];"
                 : "=r"(u[0]), "=r"(u[1]), "=r"(u[2]), "=r"(u[3]) : "r"(a) : "memory");
}
__device__ __forceinline__ void stsm4(uint32_t a, uint32_t p0, uint32_t p1, uint32_t p2, uint32_t p3) {
    asm volatile("stmatrix.sync.aligned.m8n8.x4.shared.b16 [%0], {%1,%2,%3,%4};" ::"r"(a), "r"(p0), "r"(p1), "r"(p2), "r"(p3) : "memory");
}
__device__ __forceinline__ void stsm4t(uint32_t a, uint32_t p0, uint32_t p1, uint32_t p2, uint32_t p3) {
    asm volatile("stmatrix.sync.aligned.m8n8.x4.trans.shared.b16 [%0], {%1,%2,%3,%4};" ::"r"(a), "r"(p0), "r"(p1), "r"(p2), "r"(p3) : "memory");
}

#define R8(o) "+f"(d[o]), "+f"(d[o + 1]), "+f"(d[o + 2]), "+f"(d[o + 3]), "+f"(d[o + 4]), "+f"(d[o + 5]), "+f"(d[o + 6]), "+f"(d[o + 7])
template <uint32_t ALO, uint32_t BLO>
__device__ __forceinline__ void wgmma128(float (&d)[64]) {
    asm volatile(
        "wgmma.mma_async.sync.aligned.m64n128k16.f32.bf16.bf16 "
        "{%0,%1,%2,%3,%4,%5,%6,%7,%8,%9,%10,%11,%12,%13,%14,%15,%16,%17,%18,%19,%20,%21,%22,%23,%24,%25,%26,%27,%28,%29,%30,%31,"
        "%32,%33,%34,%35,%36,%37,%38,%39,%40,%41,%42,%43,%44,%45,%46,%47,%48,%49,%50,%51,%52,%53,%54,%55,%56,%57,%58,%59,%60,%61,%62,%63},"
        " %64, %65, 1, 1, 1, 0, 0;"
        : R8(0), R8(8), R8(16), R8(24), R8(32), R8(40), R8(48), R8(56)
        : "l"((8ull << 32) | ALO), "l"((8ull << 32) | BLO));
}
__host__ __device__ constexpr int stage_ky(int s) { return (s >> 3) == 0 ? 1 : ((s >> 3) == 1 ? 0 : 2); }
template <int S>
__device__ __forceinline__ void mma_stages(float (&d)[64], uint32_t bars, int conv, int tid) {
    constexpr uint32_t A = ((SMEM_BASE + SM_ACT + stage_ky(S) * ROW_BYTES + (S & 7) * 2 * CH_PITCH) >> 4) | ((CH_PITCH >> 4) << 16);
    constexpr uint32_t B = ((SMEM_BASE + SM_W + (S % NS) * STAGE_BYTES) >> 4) | ((2048 >> 4) << 16);
    mbar_wait(bars + 8 * (BAR_FULL + S), conv);
    if (S == 0 && tid == 0) TL(9 + conv * 8);
    asm volatile("wgmma.fence.sync.aligned;" ::: "memory");
    wgmma128<A, B>(d);
    wgmma128<A + 1, B + (STEP_BYTES >> 4)>(d);
    wgmma128<A + 2, B + 2 * (STEP_BYTES >> 4)>(d);
    asm volatile("wgmma.commit_group.sync.aligned;" ::: "memory");
    if (S > 0) {
        asm volatile("wgmma.wait_group.sync.aligned 1;" ::: "memory");
        if ((tid & 31) == 0) mbar_arrive(bars + 8 * (BAR_WEMPTY + (S + NS - 1) % NS));
    }
    if constexpr (S + 1 < NSTAGE) mma_stages<S + 1>(d, bars, conv, tid);
}
__device__ __forceinline__ void weight_block(const __nv_bfloat16* __restrict__ w, unsigned char* bounce, unsigned char* wt,
                                             int cta, int lane, bool sync_cta) {
    const int oc0 = (cta & 15) * 8, kc = cta >> 4;
    uint4 t[5];
#pragma unroll
    for (int k = 0; k < 5; k++) {
        const int i = lane + 32 * k, row = i / 18, piece = i - row * 18;
        if (i < 144) t[k] = __ldg(reinterpret_cast<const uint4*>(w + ((size_t)(oc0 + row) * C + kc * 16) * 9) + piece);
    }
    if (sync_cta) bar_sync(0, NTHREADS);
#pragma unroll
    for (int k = 0; k < 5; k++)
        if (lane + 32 * k < 144) *reinterpret_cast<uint4*>(bounce + (lane + 32 * k) * 16) = t[k];
    __syncwarp();
    if (lane < 16) {
        const int hh = lane >> 3;
        uint32_t v[36];
#pragma unroll
        for (int i = 0; i < 9; i++) {
            const uint4 q = *reinterpret_cast<const uint4*>(bounce + (lane & 7) * 288 + hh * 144 + i * 16);
            v[4 * i] = q.x; v[4 * i + 1] = q.y; v[4 * i + 2] = q.z; v[4 * i + 3] = q.w;
        }
        unsigned char* dst = wt + kc * STAGE_BYTES + hh * 2048 + (oc0 + (lane & 7)) * 16;
#pragma unroll
        for (int tap = 0; tap < 9; tap++) {
            uint32_t o[4];
#pragma unroll
            for (int m = 0; m < 4; m++) {
                const int i0 = 18 * m + tap, i1 = i0 + 9;
                const uint32_t sel = ((i0 & 1) ? 0x32u : 0x10u) | ((i1 & 1) ? 0x7600u : 0x5400u);
                o[m] = __byte_perm(v[i0 >> 1], v[i1 >> 1], sel);
            }
            const int ky = tap / 3, kx = tap % 3;
            const int kyo = (ky == 1) ? 0 : (ky == 0 ? 1 : 2);
            *reinterpret_cast<uint4*>(dst + (kyo * 24 + kx) * STEP_BYTES) = make_uint4(o[0], o[1], o[2], o[3]);
        }
    }
    __syncwarp();
}
__device__ __forceinline__ unsigned ld_relaxed(const void* p) {
    unsigned v;
    asm volatile("ld.relaxed.gpu.global.u32 %0, [%1];" : "=r"(v) : "l"(p) : "memory");
    return v;
}
__device__ __forceinline__ void fence_acquire() { asm volatile("fence.acquire.gpu;" ::: "memory"); }
__device__ __forceinline__ void fence_acc(float (&d)[64]) {
#pragma unroll
    for (int i = 0; i < 64; i++) asm volatile("" : "+f"(d[i])::"memory");
}

__global__ void __launch_bounds__(NTHREADS, 1)
resblock_kernel(const __nv_bfloat16* __restrict__ x, const __nv_bfloat16* __restrict__ t_emb,
                const __nv_bfloat16* __restrict__ g1, const __nv_bfloat16* __restrict__ be1,
                const __nv_bfloat16* __restrict__ w1, const __nv_bfloat16* __restrict__ w_emb,
                const __nv_bfloat16* __restrict__ g2, const __nv_bfloat16* __restrict__ be2,
                const __nv_bfloat16* __restrict__ w2, __nv_bfloat16* __restrict__ out) {
    extern __shared__ __align__(128) unsigned char smem[];
    const uint32_t sb = smem_u32(smem);
    const uint32_t bars = sb + SM_BAR;
    const int tid = threadIdx.x, warp = tid >> 5, lane = tid & 31;
    const int cta = blockIdx.x, b = cta >> 6, r = cta & 63;
    if (tid == 0) { TL(0); TLG(1); }
    if ((sb & 0xFFFFFFu) != SMEM_BASE) return;

    if (warp < 4) {
        const int wq = warp;
        if (wq == 0) {
            if (lane == 0) g_s.hflag[cta * 32] = 0;
            if (r == 0) {
                if (lane < 16) g_s.acc[(NB + b) * 32 + lane] = 0.f;
                *reinterpret_cast<float4*>(&g_s.emb[b * C + lane * 4]) = make_float4(0.f, 0.f, 0.f, 0.f);
            }
            weight_block(w1, smem + SM_BNC, g_s.wt, cta, lane, true);
            if (lane == 0) TL(4);
            if (lane < 2) asm volatile("red.release.gpu.global.add.u32 [%0], 1;" ::"l"(&g_s.wcnt[lane * 32]) : "memory");
            if (lane == 0) TL(5);
        } else {
            const int t = tid - 32;
            if (t < NBAR) {
                const int cnt = t < BAR_WEMPTY ? 5 : (t < BAR_STATS || t == BAR_HW) ? 4 : (t == BAR_XH ? 256 : 1);
                mbar_init(bars + 8 * t, cnt);
            }
            *reinterpret_cast<uint4*>(smem + SM_ACT + (t >> 1) * CH_PITCH + (t & 1) * 65 * 16) = make_uint4(0, 0, 0, 0);
            fence_async_smem();
            bar_sync(0, NTHREADS);
            if (r == 0 || r == HW - 1) {
                uint4* z = reinterpret_cast<uint4*>(smem + SM_ACT + (r == 0 ? 0 : 2 * ROW_BYTES));
                for (int i = t; i < ROW_BYTES / 16; i += 96) z[i] = make_uint4(0, 0, 0, 0);
                fence_async_smem();
            }
        }
        bar_sync(2, 128);

        float d[64];
#pragma unroll
        for (int i = 0; i < 64; i++) d[i] = 0.f;
#pragma unroll 1
        for (int conv = 0; conv < 2; conv++) {
            fence_acc(d);
            mma_stages<0>(d, bars, conv, tid);
            asm volatile("wgmma.wait_group.sync.aligned 0;" ::: "memory");
            fence_acc(d);
            if (tid == 0) TL(10 + conv * 8);
            if (conv == 1) break;

            if (lane == 0) mbar_arrive(bars + 8 * (BAR_WEMPTY + (NSTAGE - 1) % NS));
            mbar_wait(bars + 8 * BAR_EMB, 0);
            const float* embs = reinterpret_cast<const float*>(smem + SM_EMB);
            float st[8];
#pragma unroll
            for (int g = 0; g < 4; g++) {
                float s = 0.f, q = 0.f, s2 = 0.f, q2 = 0.f;
#pragma unroll
                for (int jj = 0; jj < 4; jj++) {
                    const int j = g * 4 + jj;
                    const float2 e = *reinterpret_cast<const float2*>(embs + 8 * j + 2 * (lane & 3));
                    d[4 * j + 0] += e.x; d[4 * j + 1] += e.y; d[4 * j + 2] += e.x; d[4 * j + 3] += e.y;
                    s += d[4 * j + 0]; q = fmaf(d[4 * j + 0], d[4 * j + 0], q);
                    s2 += d[4 * j + 1]; q2 = fmaf(d[4 * j + 1], d[4 * j + 1], q2);
                    s += d[4 * j + 2]; q = fmaf(d[4 * j + 2], d[4 * j + 2], q);
                    s2 += d[4 * j + 3]; q2 = fmaf(d[4 * j + 3], d[4 * j + 3], q2);
                }
                st[2 * g] = s + s2; st[2 * g + 1] = q + q2;
            }
            {
                const bool h16 = lane & 16, h8 = lane & 8, h4 = lane & 4;
                float a[4];
#pragma unroll
                for (int i = 0; i < 4; i++) {
                    float give = h16 ? st[i] : st[i + 4], keep = h16 ? st[i + 4] : st[i];
                    a[i] = keep + __shfl_xor_sync(0xffffffffu, give, 16);
                }
                float c2[2];
#pragma unroll
                for (int i = 0; i < 2; i++) {
                    float give = h8 ? a[i] : a[i + 2], keep = h8 ? a[i + 2] : a[i];
                    c2[i] = keep + __shfl_xor_sync(0xffffffffu, give, 8);
                }
                float give = h4 ? c2[0] : c2[1], keep = h4 ? c2[1] : c2[0];
                float t = keep + __shfl_xor_sync(0xffffffffu, give, 4);
                t += __shfl_xor_sync(0xffffffffu, t, 2);
                t += __shfl_xor_sync(0xffffffffu, t, 1);
                float* red = reinterpret_cast<float*>(smem + SM_RED);
                if ((lane & 3) == 0) red[(lane >> 2) * 4 + wq] = t;
                bar_sync(2, 128);
                if (tid < 4) {
                    const float4 p = *reinterpret_cast<const float4*>(red + tid * 8);
                    const float4 p2 = *reinterpret_cast<const float4*>(red + tid * 8 + 4);
                    red_add4(&g_s.acc[(NB + b) * 32 + tid * 4], 1.f, (p.x + p.y) + (p.z + p.w), (p2.x + p2.y) + (p2.z + p2.w), 1.f);
                }
                if (tid == 0) TL(11);
            }
            const uint32_t hbase = sb + SM_ACT + ROW_BYTES + (lane >> 4) * CH_PITCH + (1 + wq * 16 + (lane & 15)) * 16;
            uint32_t* hg = reinterpret_cast<uint32_t*>(g_s.h + (size_t)cta * ROW_BYTES + (1 + wq * 16) * 16) + lane;
#pragma unroll
            for (int j = 0; j < 16; j += 2) {
                uint32_t p0 = pack_bf(d[4 * j + 0], d[4 * j + 1]), p1 = pack_bf(d[4 * j + 2], d[4 * j + 3]);
                uint32_t p2 = pack_bf(d[4 * j + 4], d[4 * j + 5]), p3 = pack_bf(d[4 * j + 6], d[4 * j + 7]);
                stsm4(hbase + j * CH_PITCH, p0, p1, p2, p3);
                hg[j * (CH_PITCH / 4)] = p0; hg[j * (CH_PITCH / 4) + 32] = p1;
                hg[(j + 1) * (CH_PITCH / 4)] = p2; hg[(j + 1) * (CH_PITCH / 4) + 32] = p3;
            }
            __syncwarp();
            if (lane == 0) mbar_arrive(bars + 8 * BAR_HW);
            if (tid == 0) TL(12);
            const uint32_t xbase = sb + SM_STG + 16384 + ((lane >> 4) * 8 + (lane & 7)) * 128 + (((2 * wq + ((lane >> 3) & 1)) ^ (lane & 7)) << 4);
#pragma unroll
            for (int j = 0; j < 16; j += 2) {
                uint32_t p[4];
                ldsm4t(p, xbase + j * 1024);
                d[4 * j + 0] = bf_lo(p[0]); d[4 * j + 1] = bf_hi(p[0]); d[4 * j + 2] = bf_lo(p[1]); d[4 * j + 3] = bf_hi(p[1]);
                d[4 * j + 4] = bf_lo(p[2]); d[4 * j + 5] = bf_hi(p[2]); d[4 * j + 6] = bf_lo(p[3]); d[4 * j + 7] = bf_hi(p[3]);
            }
        }
        {
            const uint32_t obase = sb + SM_STG + ((lane >> 4) * 8 + (lane & 7)) * OUT_PITCH + (wq * 16 + ((lane >> 3) & 1) * 8) * 2;
#pragma unroll
            for (int j = 0; j < 16; j += 2) {
                stsm4t(obase + j * 8 * OUT_PITCH, pack_bf(d[4 * j + 0], d[4 * j + 1]), pack_bf(d[4 * j + 2], d[4 * j + 3]),
                       pack_bf(d[4 * j + 4], d[4 * j + 5]), pack_bf(d[4 * j + 6], d[4 * j + 7]));
            }
            bar_sync(2, 128);
            const int oc0 = tid >> 3, seg = tid & 7;
            __nv_bfloat16* dst = out + ((size_t)(b * C + oc0) * HW + r) * HW + seg * 8;
#pragma unroll
            for (int i = 0; i < 8; i++) {
                const uint4 o = *reinterpret_cast<const uint4*>(smem + SM_STG + (oc0 + 16 * i) * OUT_PITCH + seg * 16);
                *reinterpret_cast<uint4*>(dst + (size_t)i * 16 * HW * HW) = o;
            }
            if (tid == 0) { TL(20); TLG(21); }
        }
    } else if (warp < 12) {
        const int nw = warp - 4;
        {
            const int c0 = nw * 16 + (lane >> 3), seg = lane & 7;
            const uint4* src = reinterpret_cast<const uint4*>(x + ((size_t)(b * C + c0) * HW + r) * HW) + seg;
            uint4 v[4];
#pragma unroll
            for (int i = 0; i < 4; i++) v[i] = __ldg(src + (size_t)i * 4 * (HW * HW / 8));
            bar_sync(0, NTHREADS);
            if (tid == 128) TL(30);
            float s = 0.f, q = 0.f, s2 = 0.f, q2 = 0.f;
#pragma unroll
            for (int i = 0; i < 4; i++) {
                const uint32_t u[4] = {v[i].x, v[i].y, v[i].z, v[i].w};
#pragma unroll
                for (int k = 0; k < 4; k++) {
                    const float lo = bf_lo(u[k]), hi = bf_hi(u[k]);
                    s += lo; q = fmaf(lo, lo, q);
                    s2 += hi; q2 = fmaf(hi, hi, q2);
                }
            }
            s += s2; q += q2;
            float give = (lane < 16) ? q : s, keep = (lane < 16) ? s : q;
            keep += __shfl_xor_sync(0xffffffffu, give, 16);
            if (tid == 128) TL(2);
#pragma unroll
            for (int m = 8; m >= 1; m >>= 1) keep += __shfl_xor_sync(0xffffffffu, keep, m);
            float* red = reinterpret_cast<float*>(smem + SM_RED);
            if ((lane & 15) == 0) red[nw * 2 + (lane >> 4)] = keep;
            bar_sync(3, 256);
            if (tid < 128 + 4) {
                const float4 p = *reinterpret_cast<const float4*>(red + lane * 4);
                red_add4(&g_s.acc[b * 32 + lane * 4], 1.f, p.x + p.z, p.y + p.w, 1.f);
            }
            if (tid == 128) TL(3);
#pragma unroll
            for (int hrow = 0; hrow < 2; hrow++) {
                const int row = r - 1 + 2 * hrow;
                if (row >= 0 && row < HW) {
#pragma unroll
                    for (int i = 0; i < 4; i++) {
                        const int c = c0 + 4 * i;
                        const uint32_t dst = sb + SM_STG + hrow * 2 * 16384 + c * 128 + ((seg ^ (c & 7)) << 4);
                        asm volatile("cp.async.cg.shared.global [%0], [%1], 16;"
                                     ::"r"(dst), "l"(src + (ptrdiff_t)(2 * hrow - 1) * (HW / 8) + (size_t)i * 4 * (HW * HW / 8)) : "memory");
                    }
                }
            }
            asm volatile("cp.async.mbarrier.arrive.noinc.shared::cta.b64 [%0];" ::"r"(bars + 8 * BAR_XH) : "memory");
#pragma unroll
            for (int i = 0; i < 4; i++) {
                const int c = c0 + 4 * i;
                *reinterpret_cast<uint4*>(smem + SM_STG + 16384 + c * 128 + ((seg ^ (c & 7)) << 4)) = v[i];
            }
            bar_sync(3, 256);
        }
        const int par = nw >> 2;
        const int csel = (nw >> 1) & 1, half = nw & 1;
        const uint32_t act_off = sb + SM_ACT + csel * CH_PITCH + (1 + half * 32 + lane) * 16;
        const uint32_t stg_off = sb + SM_STG + (csel * 8 + (lane & 7)) * 128 + (((half * 4 + (lane >> 3)) ^ (lane & 7)) << 4);
        const unsigned char* coef = smem + SM_COEF + csel * 64 + (lane & 3) * 16;
        const int ntask = 12;
#pragma unroll 1
        for (int conv = 0; conv < 2; conv++) {
            if (conv == 1) mbar_wait(bars + 8 * BAR_HW, 0);
            uint32_t un[4];
            if (conv == 0) ldsm4t(un, stg_off + 16384 + par * 2048);
            else ldsm4(un, act_off + ROW_BYTES + par * 2 * CH_PITCH);
            mbar_wait(bars + 8 * BAR_STATS, conv);
            if (tid == 128) TL(22 + conv * 4);
            float4 cn = *reinterpret_cast<const float4*>(coef + par * 128);
#pragma unroll 1
            for (int t = 0; t < ntask; t++) {
                const int o = t >> 2, kc = par + 2 * (t & 3);
                const int ky = (o == 0) ? 1 : (o == 1 ? 0 : 2);
                const bool valid = !((ky == 0 && r == 0) || (ky == 2 && r == HW - 1));
                uint32_t u[4] = {un[0], un[1], un[2], un[3]};
                const float4 cf = cn;
                const int tn = t + 1, on = tn >> 2, kcn = par + 2 * (tn & 3);
                const int kyn = (on == 0) ? 1 : (on == 1 ? 0 : 2);
                const bool same_row = (tn & 3) != 0;
                if (same_row) {
                    if (conv == 0) ldsm4t(un, stg_off + kyn * 16384 + kcn * 2048);
                    else ldsm4(un, act_off + kyn * ROW_BYTES + kcn * 2 * CH_PITCH);
                }
                cn = *reinterpret_cast<const float4*>(coef + kcn * 128);
                if (valid) {
#pragma unroll
                    for (int i = 0; i < 4; i++)
                        u[i] = pack_bf(silu_half(fmaf(bf_lo(u[i]), cf.x, cf.z)), silu_half(fmaf(bf_hi(u[i]), cf.y, cf.w)));
                    stsm4(act_off + ky * ROW_BYTES + kc * 2 * CH_PITCH, u[0], u[1], u[2], u[3]);
                    fence_async_smem();
                }
                __syncwarp();
                if (lane == 0) mbar_arrive(bars + 8 * (BAR_FULL + o * 8 + kc));
                if (tid == 128 && t == 0) TL(8 + conv * 8);
                if (!same_row && tn < ntask) {
                    const bool vn = !((kyn == 0 && r == 0) || (kyn == 2 && r == HW - 1));
                    if (vn) mbar_wait(bars + 8 * (conv ? BAR_HALO + on - 1 : BAR_XH), 0);
                    if (conv == 0) ldsm4t(un, stg_off + kyn * 16384 + kcn * 2048);
                    else ldsm4(un, act_off + kyn * ROW_BYTES + kcn * 2 * CH_PITCH);
                }
            }
            if (tid == 128) TL(23 + conv * 4);
        }
    } else if (warp == 12) {
        bar_sync(0, NTHREADS);
        if (lane == 0) {
            unsigned it = 0;
            while (ld_relaxed(&g_s.wcnt[b * 32]) < (unsigned)NCTA && ++it < SPIN_LIMIT) {}
            fence_acquire();
            fence_async_global();
            TL(6);
            int slot = 0, st = 0; uint32_t par = 1;
#pragma unroll 1
            for (int g = 0; g < 2 * NSTAGE; g++) {
                if (g == NSTAGE) { mbar_wait(bars + 8 * BAR_EMB, 0); fence_async_global(); }
                mbar_wait(bars + 8 * (BAR_WEMPTY + slot), par);
                mbar_expect(bars + 8 * (BAR_FULL + st), STAGE_BYTES);
                bulk_g2s(sb + SM_W + slot * STAGE_BYTES, g_s.wt + (size_t)g * STAGE_BYTES, STAGE_BYTES, bars + 8 * (BAR_FULL + st));
                if (g == NS - 1) mbar_arrive(bars + 8 * BAR_WACQ);
                if (++slot == NS) { slot = 0; par ^= 1; }
                if (++st == NSTAGE) st = 0;
            }
        }
    } else if (warp == 13) {
        const uint2 ga1 = __ldg(reinterpret_cast<const uint2*>(g1) + lane), bt1 = __ldg(reinterpret_cast<const uint2*>(be1) + lane);
        const uint2 ga2 = __ldg(reinterpret_cast<const uint2*>(g2) + lane), bt2 = __ldg(reinterpret_cast<const uint2*>(be2) + lane);
        bar_sync(0, NTHREADS);
#pragma unroll 1
        for (int conv = 0; conv < 2; conv++) {
            if (conv == 1) mbar_wait(bars + 8 * BAR_HW, 0);
            const float* src = &g_s.acc[(conv * NB + b) * 32 + (lane >> 3) * 4];
            uint4 f;
            unsigned it = 0;
            while (true) {
                f = ld_relaxed_v4(src);
                const bool ok = (f.x == 0x42800000u) & (f.w == 0x42800000u);
                if (__all_sync(0xffffffffu, ok) || ++it > SPIN_LIMIT) break;
            }
            if (lane == 0) TL(7 + conv * 8);
            const float inv_n = 1.0f / (32.0f * HW * HW);
            const float mean = __uint_as_float(f.y) * inv_n;
            const float var = fmaxf(fmaf(-mean, mean, __uint_as_float(f.z) * inv_n), 0.f);
            const float rs = 0.5f * rsqrtf(var + 1e-5f);
            const uint2 ga = conv ? ga2 : ga1, bt = conv ? bt2 : bt1;
            float4 c0, c1;
            c0.x = rs * bf_lo(ga.x); c0.y = rs * bf_hi(ga.x); c1.x = rs * bf_lo(ga.y); c1.y = rs * bf_hi(ga.y);
            c0.z = fmaf(-mean, c0.x, 0.5f * bf_lo(bt.x)); c0.w = fmaf(-mean, c0.y, 0.5f * bf_hi(bt.x));
            c1.z = fmaf(-mean, c1.x, 0.5f * bf_lo(bt.y)); c1.w = fmaf(-mean, c1.y, 0.5f * bf_hi(bt.y));
            float4* cf = reinterpret_cast<float4*>(smem + SM_COEF + lane * 32);
            cf[0] = c0; cf[1] = c1;
            __syncwarp();
            if (lane == 0) { mbar_arrive(bars + 8 * BAR_STATS); TL(25 + conv * 4); }
        }
        if (r == 0) {
            if (lane < 16) g_s.acc[b * 32 + lane] = 0.f;
            if (lane < 2) g_s.wcnt[(lane * NB + b) * 32] = 0;
        }
    } else {
        bar_sync(0, NTHREADS);
        mbar_wait(bars + 8 * BAR_WACQ, 0);
        {
            const uint2* wsrc = reinterpret_cast<const uint2*>(w_emb + (size_t)r * 12 * C) + lane;
            uint2 wv[12];
#pragma unroll
            for (int i = 0; i < 12; i++) wv[i] = __ldg(wsrc + i * (C / 4));
            float tv = 0.f;
            if (lane < 12) tv = __bfloat162float(t_emb[b * E + r * 12 + lane]);
            weight_block(w2, smem + SM_BNC + 2304, g_s.wt + 72 * STEP_BYTES, cta, lane, false);
            const float sv = silu_half(0.5f * tv);
            float e0 = 0.f, e1 = 0.f, e2 = 0.f, e3 = 0.f;
#pragma unroll
            for (int i = 0; i < 12; i++) {
                const float sx = __shfl_sync(0xffffffffu, sv, i);
                e0 = fmaf(sx, bf_lo(wv[i].x), e0); e1 = fmaf(sx, bf_hi(wv[i].x), e1);
                e2 = fmaf(sx, bf_lo(wv[i].y), e2); e3 = fmaf(sx, bf_hi(wv[i].y), e3);
            }
            red_add4(&g_s.emb[b * C + lane * 4], e0, e1, e2, e3);
            __syncwarp();
            if (lane < 2) asm volatile("red.release.gpu.global.add.u32 [%0], 1;" ::"l"(&g_s.wcnt[(NB + lane) * 32]) : "memory");
            unsigned it = 0;
            while (ld_relaxed(&g_s.wcnt[(NB + b) * 32]) < (unsigned)NCTA && ++it < SPIN_LIMIT) __nanosleep(100);
            fence_acquire();
            *reinterpret_cast<uint4*>(smem + SM_EMB + lane * 16) = ld_relaxed_v4(&g_s.emb[b * C + lane * 4]);
            __syncwarp();
            if (lane == 0) { mbar_arrive(bars + 8 * BAR_EMB); TL(19); }
        }
        if (lane == 0) {
            mbar_wait(bars + 8 * BAR_HW, 0);
            asm volatile("st.release.gpu.global.u32 [%0], %1;" ::"l"(&g_s.hflag[cta * 32]), "r"(1) : "memory");
            TL(13);
        }
        __syncwarp();
        if (lane < 2) {
            const int irow = r - 1 + 2 * lane;
            if (irow >= 0 && irow < HW) {
                const int nb = cta - 1 + 2 * lane;
                unsigned it = 0;
                while (ld_relaxed(&g_s.hflag[nb * 32]) == 0 && ++it < SPIN_LIMIT) {}
                fence_acquire();
                fence_async_global();
                mbar_expect(bars + 8 * (BAR_HALO + lane), ROW_BYTES);
                bulk_g2s(sb + SM_ACT + 2 * lane * ROW_BYTES, g_s.h + (size_t)nb * ROW_BYTES, ROW_BYTES, bars + 8 * (BAR_HALO + lane));
                if (lane == 0) TL(14);
            }
        }
    }
}

}

extern "C" void kernel_launch(void* const* d_in, const int* in_sizes, int n_in, void* d_out, int out_size) {
    (void)in_sizes; (void)n_in; (void)out_size;
    static bool init = false;
    if (!init) {
        cudaFuncSetAttribute(resblock_kernel, cudaFuncAttributeMaxDynamicSharedMemorySize, SM_TOTAL);
        init = true;
    }
    resblock_kernel<<<NCTA, NTHREADS, SM_TOTAL>>>(
        (const __nv_bfloat16*)d_in[0], (const __nv_bfloat16*)d_in[1], (const __nv_bfloat16*)d_in[2],
        (const __nv_bfloat16*)d_in[3], (const __nv_bfloat16*)d_in[4], (const __nv_bfloat16*)d_in[5],
        (const __nv_bfloat16*)d_in[6], (const __nv_bfloat16*)d_in[7], (const __nv_bfloat16*)d_in[8],
        (__nv_bfloat16*)d_out);
}
```

```cpp
#include <cuda_runtime.h>
#include <cuda_bf16.h>
#include <stdint.h>

namespace {

constexpr int C = 128, HW = 64, NB = 2, E = 768;
constexpr int NCTA = NB * HW;
constexpr int NTHREADS = 15 * 32;
constexpr int CH_PITCH = 66 * 16;
constexpr int ROW_BYTES = 16 * CH_PITCH;
constexpr int STEP_BYTES = 4096;
constexpr int STAGE_BYTES = 3 * STEP_BYTES;
constexpr int NSTAGE = 24;
constexpr int NS = 8;

constexpr int SM_ACT = 0;
constexpr int SM_STG = SM_ACT + 3 * ROW_BYTES;
constexpr int SM_W = SM_STG + 3 * 16384;
constexpr int SM_COEF = SM_W + NS * STAGE_BYTES;
constexpr int SM_EMB = SM_COEF + 1024;
constexpr int SM_RED = SM_EMB + 512;
constexpr int SM_BNC = SM_RED + 128;
constexpr int SM_BAR = SM_BNC + 2 * 2304;
constexpr int BAR_FULL = 0, BAR_WEMPTY = NSTAGE, BAR_STATS = BAR_WEMPTY + NS, BAR_HW = BAR_STATS + 1,
              BAR_HALO = BAR_HW + 1  , BAR_EMB = BAR_HALO + 2, BAR_WACQ = BAR_EMB + 1, BAR_XH = BAR_WACQ + 1,
              NBAR = BAR_XH + 1;
constexpr int SM_TOTAL = SM_BAR + NBAR * 8;
static_assert(SM_TOTAL <= 232448, "smem");
constexpr int OUT_PITCH = 144;

constexpr unsigned SPIN_LIMIT = 1u << 16;
constexpr uint32_t SMEM_BASE = 0x400;

struct Scratch {
    float acc[2 * NB * 32];
    unsigned wcnt[2 * NB * 32];
    float emb[NB * C];
    unsigned hflag[NCTA * 32];
    unsigned char wt[2 * 72 * STEP_BYTES];
    unsigned char h[NCTA * ROW_BYTES];
};
__device__ __align__(1024) Scratch g_s;
#define TL(i) do {} while (0)
#define TLG(i) do {} while (0)

__device__ __forceinline__ uint32_t smem_u32(const void* p) { return (uint32_t)__cvta_generic_to_shared(p); }
__device__ __forceinline__ void mbar_init(uint32_t bar, int cnt) {
    asm volatile("mbarrier.init.shared::cta.b64 [%0], %1;" ::"r"(bar), "r"(cnt) : "memory");
}
__device__ __forceinline__ void mbar_arrive(uint32_t bar) {
    asm volatile("mbarrier.arrive.shared::cta.b64 _, [%0];" ::"r"(bar) : "memory");
}
__device__ __forceinline__ void mbar_expect(uint32_t bar, uint32_t bytes) {
    asm volatile("mbarrier.arrive.expect_tx.shared::cta.b64 _, [%0], %1;" ::"r"(bar), "r"(bytes) : "memory");
}
__device__ __forceinline__ bool mbar_try(uint32_t bar, uint32_t par) {
    uint32_t ok;
    asm volatile("{\n.reg .pred p;\nmbarrier.try_wait.parity.shared::cta.b64 p, [%1], %2;\nselp.u32 %0, 1, 0, p;\n}"
                 : "=r"(ok) : "r"(bar), "r"(par) : "memory");
    return ok;
}
__device__ __forceinline__ void mbar_wait(uint32_t bar, uint32_t par) {
    unsigned it = 0;
#pragma unroll 1
    while (!mbar_try(bar, par) && ++it < SPIN_LIMIT) {}
}
__device__ __forceinline__ void fence_async_smem() { asm volatile("fence.proxy.async.shared::cta;" ::: "memory"); }
__device__ __forceinline__ void fence_async_global() { asm volatile("fence.proxy.async.global;" ::: "memory"); }
__device__ __forceinline__ void bar_sync(int id, int n) { asm volatile("bar.sync %0, %1;" ::"r"(id), "r"(n) : "memory"); }
__device__ __forceinline__ void bulk_g2s(uint32_t dst, const void* src, uint32_t bytes, uint32_t bar) {
    asm volatile("cp.async.bulk.shared::cluster.global.mbarrier::complete_tx::bytes [%0], [%1], %2, [%3];"
                 ::"r"(dst), "l"(src), "r"(bytes), "r"(bar) : "memory");
}
__device__ __forceinline__ uint4 ld_relaxed_v4(const void* p) {
    uint4 v;
    asm volatile("ld.relaxed.gpu.global.v4.u32 {%0,%1,%2,%3}, [%4];" : "=r"(v.x), "=r"(v.y), "=r"(v.z), "=r"(v.w) : "l"(p) : "memory");
    return v;
}
__device__ __forceinline__ unsigned ld_acquire(const void* p) {
    unsigned v;
    asm volatile("ld.acquire.gpu.global.u32 %0, [%1];" : "=r"(v) : "l"(p) : "memory");
    return v;
}
__device__ __forceinline__ void st_relaxed(void* p, unsigned v) {
    asm volatile("st.relaxed.gpu.global.u32 [%0], %1;" ::"l"(p), "r"(v) : "memory");
}
__device__ __forceinline__ void red_add4(float* p, float a, float b, float c, float d) {
    asm volatile("red.relaxed.gpu.global.add.v4.f32 [%0], {%1,%2,%3,%4};" ::"l"(p), "f"(a), "f"(b), "f"(c), "f"(d) : "memory");
}
__device__ __forceinline__ float bf_lo(uint32_t u) { return __uint_as_float(u << 16); }
__device__ __forceinline__ float bf_hi(uint32_t u) { return __uint_as_float(u & 0xffff0000u); }
__device__ __forceinline__ uint32_t pack_bf(float lo, float hi) {
    uint32_t r;
    asm("cvt.rn.bf16x2.f32 %0, %1, %2;" : "=r"(r) : "f"(hi), "f"(lo));
    return r;
}
__device__ __forceinline__ float tanh_fast(float x) {
    float r;
    asm("tanh.approx.f32 %0, %1;" : "=f"(r) : "f"(x));
    return r;
}
__device__ __forceinline__ float silu_half(float h) { return fmaf(h, tanh_fast(h), h); }
__device__ __forceinline__ void ldsm4(uint32_t (&u)[4], uint32_t a) {
    asm volatile("ldmatrix.sync.aligned.m8n8.x4.shared.b16 {%0,%1,%2,%3}, [%4];"
                 : "=r"(u[0]), "=r"(u[1]), "=r"(u[2]), "=r"(u[3]) : "r"(a) : "memory");
}
__device__ __forceinline__ void ldsm4t(uint32_t (&u)[4], uint32_t a) {
    asm volatile("ldmatrix.sync.aligned.m8n8.x4.trans.shared.b16 {%0,%1,%2,%3}, [%4];"
                 : "=r"(u[0]), "=r"(u[1]), "=r"(u[2]), "=r"(u[3]) : "r"(a) : "memory");
}
__device__ __forceinline__ void stsm4(uint32_t a, uint32_t p0, uint32_t p1, uint32_t p2, uint32_t p3) {
    asm volatile("stmatrix.sync.aligned.m8n8.x4.shared.b16 [%0], {%1,%2,%3,%4};" ::"r"(a), "r"(p0), "r"(p1), "r"(p2), "r"(p3) : "memory");
}
__device__ __forceinline__ void stsm4t(uint32_t a, uint32_t p0, uint32_t p1, uint32_t p2, uint32_t p3) {
    asm volatile("stmatrix.sync.aligned.m8n8.x4.trans.shared.b16 [%0], {%1,%2,%3,%4};" ::"r"(a), "r"(p0), "r"(p1), "r"(p2), "r"(p3) : "memory");
}

#define R8(o) "+f"(d[o]), "+f"(d[o + 1]), "+f"(d[o + 2]), "+f"(d[o + 3]), "+f"(d[o + 4]), "+f"(d[o + 5]), "+f"(d[o + 6]), "+f"(d[o + 7])
template <uint32_t ALO, uint32_t BLO>
__device__ __forceinline__ void wgmma128(float (&d)[64]) {
    asm volatile(
        "wgmma.mma_async.sync.aligned.m64n128k16.f32.bf16.bf16 "
        "{%0,%1,%2,%3,%4,%5,%6,%7,%8,%9,%10,%11,%12,%13,%14,%15,%16,%17,%18,%19,%20,%21,%22,%23,%24,%25,%26,%27,%28,%29,%30,%31,"
        "%32,%33,%34,%35,%36,%37,%38,%39,%40,%41,%42,%43,%44,%45,%46,%47,%48,%49,%50,%51,%52,%53,%54,%55,%56,%57,%58,%59,%60,%61,%62,%63},"
        " %64, %65, 1, 1, 1, 0, 0;"
        : R8(0), R8(8), R8(16), R8(24), R8(32), R8(40), R8(48), R8(56)
        : "l"((8ull << 32) | ALO), "l"((8ull << 32) | BLO));
}
__host__ __device__ constexpr int stage_ky(int s) { return (s >> 3) == 0 ? 1 : ((s >> 3) == 1 ? 0 : 2); }
template <int S>
__device__ __forceinline__ void mma_stages(float (&d)[64], uint32_t bars, int conv, int tid) {
    constexpr uint32_t A = ((SMEM_BASE + SM_ACT + stage_ky(S) * ROW_BYTES + (S & 7) * 2 * CH_PITCH) >> 4) | ((CH_PITCH >> 4) << 16);
    constexpr uint32_t B = ((SMEM_BASE + SM_W + (S % NS) * STAGE_BYTES) >> 4) | ((2048 >> 4) << 16);
    mbar_wait(bars + 8 * (BAR_FULL + S), conv);
    if (S == 0 && tid == 0) TL(9 + conv * 8);
    asm volatile("wgmma.fence.sync.aligned;" ::: "memory");
    wgmma128<A, B>(d);
    wgmma128<A + 1, B + (STEP_BYTES >> 4)>(d);
    wgmma128<A + 2, B + 2 * (STEP_BYTES >> 4)>(d);
    asm volatile("wgmma.commit_group.sync.aligned;" ::: "memory");
    if (S > 0) {
        asm volatile("wgmma.wait_group.sync.aligned 1;" ::: "memory");
        if ((tid & 31) == 0) mbar_arrive(bars + 8 * (BAR_WEMPTY + (S + NS - 1) % NS));
    }
    if constexpr (S + 1 < NSTAGE) mma_stages<S + 1>(d, bars, conv, tid);
}
__device__ __forceinline__ void weight_block(const __nv_bfloat16* __restrict__ w, unsigned char* bounce, unsigned char* wt,
                                             int cta, int lane, bool sync_cta) {
    const int oc0 = (cta & 15) * 8, kc = cta >> 4;
    uint4 t[5];
#pragma unroll
    for (int k = 0; k < 5; k++) {
        const int i = lane + 32 * k, row = i / 18, piece = i - row * 18;
        if (i < 144) t[k] = __ldg(reinterpret_cast<const uint4*>(w + ((size_t)(oc0 + row) * C + kc * 16) * 9) + piece);
    }
    if (sync_cta) bar_sync(0, NTHREADS);
#pragma unroll
    for (int k = 0; k < 5; k++)
        if (lane + 32 * k < 144) *reinterpret_cast<uint4*>(bounce + (lane + 32 * k) * 16) = t[k];
    __syncwarp();
    if (lane < 16) {
        const int hh = lane >> 3;
        uint32_t v[36];
#pragma unroll
        for (int i = 0; i < 9; i++) {
            const uint4 q = *reinterpret_cast<const uint4*>(bounce + (lane & 7) * 288 + hh * 144 + i * 16);
            v[4 * i] = q.x; v[4 * i + 1] = q.y; v[4 * i + 2] = q.z; v[4 * i + 3] = q.w;
        }
        unsigned char* dst = wt + kc * STAGE_BYTES + hh * 2048 + (oc0 + (lane & 7)) * 16;
#pragma unroll
        for (int tap = 0; tap < 9; tap++) {
            uint32_t o[4];
#pragma unroll
            for (int m = 0; m < 4; m++) {
                const int i0 = 18 * m + tap, i1 = i0 + 9;
                const uint32_t sel = ((i0 & 1) ? 0x32u : 0x10u) | ((i1 & 1) ? 0x7600u : 0x5400u);
                o[m] = __byte_perm(v[i0 >> 1], v[i1 >> 1], sel);
            }
            const int ky = tap / 3, kx = tap % 3;
            const int kyo = (ky == 1) ? 0 : (ky == 0 ? 1 : 2);
            *reinterpret_cast<uint4*>(dst + (kyo * 24 + kx) * STEP_BYTES) = make_uint4(o[0], o[1], o[2], o[3]);
        }
    }
    __syncwarp();
}
__device__ __forceinline__ unsigned ld_relaxed(const void* p) {
    unsigned v;
    asm volatile("ld.relaxed.gpu.global.u32 %0, [%1];" : "=r"(v) : "l"(p) : "memory");
    return v;
}
__device__ __forceinline__ void fence_acquire() { asm volatile("fence.acquire.gpu;" ::: "memory"); }
template <int N>
__device__ __forceinline__ void norm_load(uint32_t (&u)[4][4], int first, int conv, uint32_t stg, uint32_t act) {
#pragma unroll
    for (int i = 0; i < N; i++) {
        if (conv == 0) ldsm4t(u[first + i], stg + (first + i) * 4096);
        else ldsm4(u[first + i], act + (first + i) * 4 * CH_PITCH);
    }
}
template <int FIRST, int N>
__device__ __forceinline__ void norm_batch(uint32_t (&u)[4][4], const float4 (&cf)[4], uint32_t act, uint32_t bar, int lane, bool valid) {
    if (valid) {
#pragma unroll
        for (int t = FIRST; t < FIRST + N; t++) {
#pragma unroll
            for (int i = 0; i < 4; i++)
                u[t][i] = pack_bf(silu_half(fmaf(bf_lo(u[t][i]), cf[t].x, cf[t].z)), silu_half(fmaf(bf_hi(u[t][i]), cf[t].y, cf[t].w)));
            stsm4(act + t * 4 * CH_PITCH, u[t][0], u[t][1], u[t][2], u[t][3]);
        }
        fence_async_smem();
    }
    __syncwarp();
    if (lane < N) mbar_arrive(bar + 16 * (FIRST + lane));
}
__device__ __forceinline__ void fence_acc(float (&d)[64]) {
#pragma unroll
    for (int i = 0; i < 64; i++) asm volatile("" : "+f"(d[i])::"memory");
}

__global__ void __launch_bounds__(NTHREADS, 1)
resblock_kernel(const __nv_bfloat16* __restrict__ x, const __nv_bfloat16* __restrict__ t_emb,
                const __nv_bfloat16* __restrict__ g1, const __nv_bfloat16* __restrict__ be1,
                const __nv_bfloat16* __restrict__ w1, const __nv_bfloat16* __restrict__ w_emb,
                const __nv_bfloat16* __restrict__ g2, const __nv_bfloat16* __restrict__ be2,
                const __nv_bfloat16* __restrict__ w2, __nv_bfloat16* __restrict__ out) {
    extern __shared__ __align__(128) unsigned char smem[];
    const uint32_t sb = smem_u32(smem);
    const uint32_t bars = sb + SM_BAR;
    const int tid = threadIdx.x, warp = tid >> 5, lane = tid & 31;
    const int cta = blockIdx.x, b = cta >> 6, r = cta & 63;
    if ((sb & 0xFFFFFFu) != SMEM_BASE) return;

    if (warp < 4) {
        const int wq = warp;
        if (wq == 0) {
            weight_block(w1, smem + SM_BNC, g_s.wt, cta, lane, true);
            if (lane == 0) g_s.hflag[cta * 32] = 0;
            if (r == 0) {
                if (lane < 16) g_s.acc[(NB + b) * 32 + lane] = 0.f;
                *reinterpret_cast<float4*>(&g_s.emb[b * C + lane * 4]) = make_float4(0.f, 0.f, 0.f, 0.f);
            }
            __syncwarp();
            if (lane == 0) TL(4);
            if (lane < 2) asm volatile("red.release.gpu.global.add.u32 [%0], 1;" ::"l"(&g_s.wcnt[lane * 32]) : "memory");
            if (lane == 0) TL(5);
        } else {
            const int t = tid - 32;
            if (t < NBAR) {
                const int cnt = t < BAR_WEMPTY ? 5 : (t < BAR_STATS || t == BAR_HW) ? 4 : (t == BAR_XH ? 256 : 1);
                mbar_init(bars + 8 * t, cnt);
            }
            *reinterpret_cast<uint4*>(smem + SM_ACT + (t >> 1) * CH_PITCH + (t & 1) * 65 * 16) = make_uint4(0, 0, 0, 0);
            fence_async_smem();
            bar_sync(0, NTHREADS);
            if (r == 0 || r == HW - 1) {
                uint4* z = reinterpret_cast<uint4*>(smem + SM_ACT + (r == 0 ? 0 : 2 * ROW_BYTES));
                for (int i = t; i < ROW_BYTES / 16; i += 96) z[i] = make_uint4(0, 0, 0, 0);
                fence_async_smem();
            }
        }
        bar_sync(2, 128);

        float d[64];
#pragma unroll
        for (int i = 0; i < 64; i++) d[i] = 0.f;
#pragma unroll 1
        for (int conv = 0; conv < 2; conv++) {
            fence_acc(d);
            mma_stages<0>(d, bars, conv, tid);
            asm volatile("wgmma.wait_group.sync.aligned 0;" ::: "memory");
            fence_acc(d);
            if (tid == 0) TL(10 + conv * 8);
            if (conv == 1) break;

            if (lane == 0) mbar_arrive(bars + 8 * (BAR_WEMPTY + (NSTAGE - 1) % NS));
            mbar_wait(bars + 8 * BAR_EMB, 0);
            const float* embs = reinterpret_cast<const float*>(smem + SM_EMB);
            float st[8];
#pragma unroll
            for (int g = 0; g < 4; g++) {
                float s = 0.f, q = 0.f, s2 = 0.f, q2 = 0.f;
#pragma unroll
                for (int jj = 0; jj < 4; jj++) {
                    const int j = g * 4 + jj;
                    const float2 e = *reinterpret_cast<const float2*>(embs + 8 * j + 2 * (lane & 3));
                    d[4 * j + 0] += e.x; d[4 * j + 1] += e.y; d[4 * j + 2] += e.x; d[4 * j + 3] += e.y;
                    s += d[4 * j + 0]; q = fmaf(d[4 * j + 0], d[4 * j + 0], q);
                    s2 += d[4 * j + 1]; q2 = fmaf(d[4 * j + 1], d[4 * j + 1], q2);
                    s += d[4 * j + 2]; q = fmaf(d[4 * j + 2], d[4 * j + 2], q);
                    s2 += d[4 * j + 3]; q2 = fmaf(d[4 * j + 3], d[4 * j + 3], q2);
                }
                st[2 * g] = s + s2; st[2 * g + 1] = q + q2;
            }
            {
                const bool h16 = lane & 16, h8 = lane & 8, h4 = lane & 4;
                float a[4];
#pragma unroll
                for (int i = 0; i < 4; i++) {
                    float give = h16 ? st[i] : st[i + 4], keep = h16 ? st[i + 4] : st[i];
                    a[i] = keep + __shfl_xor_sync(0xffffffffu, give, 16);
                }
                float c2[2];
#pragma unroll
                for (int i = 0; i < 2; i++) {
                    float give = h8 ? a[i] : a[i + 2], keep = h8 ? a[i + 2] : a[i];
                    c2[i] = keep + __shfl_xor_sync(0xffffffffu, give, 8);
                }
                float give = h4 ? c2[0] : c2[1], keep = h4 ? c2[1] : c2[0];
                float t = keep + __shfl_xor_sync(0xffffffffu, give, 4);
                t += __shfl_xor_sync(0xffffffffu, t, 2);
                t += __shfl_xor_sync(0xffffffffu, t, 1);
                float* red = reinterpret_cast<float*>(smem + SM_RED);
                if ((lane & 3) == 0) red[(lane >> 2) * 4 + wq] = t;
                bar_sync(2, 128);
                if (tid < 4) {
                    const float4 p = *reinterpret_cast<const float4*>(red + tid * 8);
                    const float4 p2 = *reinterpret_cast<const float4*>(red + tid * 8 + 4);
                    red_add4(&g_s.acc[(NB + b) * 32 + tid * 4], 1.f, (p.x + p.y) + (p.z + p.w), (p2.x + p2.y) + (p2.z + p2.w), 1.f);
                }
                if (tid == 0) TL(11);
            }
            const uint32_t hbase = sb + SM_ACT + ROW_BYTES + (lane >> 4) * CH_PITCH + (1 + wq * 16 + (lane & 15)) * 16;
            uint32_t* hg = reinterpret_cast<uint32_t*>(g_s.h + (size_t)cta * ROW_BYTES + (1 + wq * 16) * 16) + lane;
#pragma unroll
            for (int j = 0; j < 16; j += 2) {
                uint32_t p0 = pack_bf(d[4 * j + 0], d[4 * j + 1]), p1 = pack_bf(d[4 * j + 2], d[4 * j + 3]);
                uint32_t p2 = pack_bf(d[4 * j + 4], d[4 * j + 5]), p3 = pack_bf(d[4 * j + 6], d[4 * j + 7]);
                stsm4(hbase + j * CH_PITCH, p0, p1, p2, p3);
                hg[j * (CH_PITCH / 4)] = p0; hg[j * (CH_PITCH / 4) + 32] = p1;
                hg[(j + 1) * (CH_PITCH / 4)] = p2; hg[(j + 1) * (CH_PITCH / 4) + 32] = p3;
            }
            __syncwarp();
            if (lane == 0) mbar_arrive(bars + 8 * BAR_HW);
            if (tid == 0) TL(12);
            const uint32_t xbase = sb + SM_STG + 16384 + ((lane >> 4) * 8 + (lane & 7)) * 128 + (((2 * wq + ((lane >> 3) & 1)) ^ (lane & 7)) << 4);
#pragma unroll
            for (int j = 0; j < 16; j += 2) {
                uint32_t p[4];
                ldsm4t(p, xbase + j * 1024);
                d[4 * j + 0] = bf_lo(p[0]); d[4 * j + 1] = bf_hi(p[0]); d[4 * j + 2] = bf_lo(p[1]); d[4 * j + 3] = bf_hi(p[1]);
                d[4 * j + 4] = bf_lo(p[2]); d[4 * j + 5] = bf_hi(p[2]); d[4 * j + 6] = bf_lo(p[3]); d[4 * j + 7] = bf_hi(p[3]);
            }
        }
        {
            const uint32_t obase = sb + SM_STG + ((lane >> 4) * 8 + (lane & 7)) * OUT_PITCH + (wq * 16 + ((lane >> 3) & 1) * 8) * 2;
#pragma unroll
            for (int j = 0; j < 16; j += 2) {
                stsm4t(obase + j * 8 * OUT_PITCH, pack_bf(d[4 * j + 0], d[4 * j + 1]), pack_bf(d[4 * j + 2], d[4 * j + 3]),
                       pack_bf(d[4 * j + 4], d[4 * j + 5]), pack_bf(d[4 * j + 6], d[4 * j + 7]));
            }
            bar_sync(2, 128);
            const int oc0 = tid >> 3, seg = tid & 7;
            __nv_bfloat16* dst = out + ((size_t)(b * C + oc0) * HW + r) * HW + seg * 8;
#pragma unroll
            for (int i = 0; i < 8; i++) {
                const uint4 o = *reinterpret_cast<const uint4*>(smem + SM_STG + (oc0 + 16 * i) * OUT_PITCH + seg * 16);
                *reinterpret_cast<uint4*>(dst + (size_t)i * 16 * HW * HW) = o;
            }
            if (tid == 0) { TL(20); TLG(21); }
        }
    } else if (warp < 12) {
        const int nw = warp - 4;
        {
            const int c0 = nw * 16 + (lane >> 3), seg = lane & 7;
            const uint4* src = reinterpret_cast<const uint4*>(x + ((size_t)(b * C + c0) * HW + r) * HW) + seg;
            uint4 v[4];
#pragma unroll
            for (int i = 0; i < 4; i++) v[i] = __ldg(src + (size_t)i * 4 * (HW * HW / 8));
            bar_sync(0, NTHREADS);
            float s = 0.f, q = 0.f, s2 = 0.f, q2 = 0.f;
#pragma unroll
            for (int i = 0; i < 4; i++) {
                const uint32_t u[4] = {v[i].x, v[i].y, v[i].z, v[i].w};
#pragma unroll
                for (int k = 0; k < 4; k++) {
                    const float lo = bf_lo(u[k]), hi = bf_hi(u[k]);
                    s += lo; q = fmaf(lo, lo, q);
                    s2 += hi; q2 = fmaf(hi, hi, q2);
                }
            }
            s += s2; q += q2;
            float give = (lane < 16) ? q : s, keep = (lane < 16) ? s : q;
            keep += __shfl_xor_sync(0xffffffffu, give, 16);
            if (tid == 128) TL(2);
#pragma unroll
            for (int m = 8; m >= 1; m >>= 1) keep += __shfl_xor_sync(0xffffffffu, keep, m);
            float* red = reinterpret_cast<float*>(smem + SM_RED);
            if ((lane & 15) == 0) red[nw * 2 + (lane >> 4)] = keep;
            bar_sync(3, 256);
            if (tid < 128 + 4) {
                const float4 p = *reinterpret_cast<const float4*>(red + lane * 4);
                red_add4(&g_s.acc[b * 32 + lane * 4], 1.f, p.x + p.z, p.y + p.w, 1.f);
            }
            if (tid == 128) TL(3);
#pragma unroll
            for (int hrow = 0; hrow < 2; hrow++) {
                const int row = r - 1 + 2 * hrow;
                if (row >= 0 && row < HW) {
#pragma unroll
                    for (int i = 0; i < 4; i++) {
                        const int c = c0 + 4 * i;
                        const uint32_t dst = sb + SM_STG + hrow * 2 * 16384 + c * 128 + ((seg ^ (c & 7)) << 4);
                        asm volatile("cp.async.cg.shared.global [%0], [%1], 16;"
                                     ::"r"(dst), "l"(src + (ptrdiff_t)(2 * hrow - 1) * (HW / 8) + (size_t)i * 4 * (HW * HW / 8)) : "memory");
                    }
                }
            }
            asm volatile("cp.async.mbarrier.arrive.noinc.shared::cta.b64 [%0];" ::"r"(bars + 8 * BAR_XH) : "memory");
#pragma unroll
            for (int i = 0; i < 4; i++) {
                const int c = c0 + 4 * i;
                *reinterpret_cast<uint4*>(smem + SM_STG + 16384 + c * 128 + ((seg ^ (c & 7)) << 4)) = v[i];
            }
            bar_sync(3, 256);
        }
        const int par = nw >> 2;
        const int csel = (nw >> 1) & 1, half = nw & 1;
        const uint32_t act_off = sb + SM_ACT + (par * 2 + csel) * CH_PITCH + (1 + half * 32 + lane) * 16;
        const uint32_t stg_off = sb + SM_STG + ((par * 2 + csel) * 8 + (lane & 7)) * 128 + (((half * 4 + (lane >> 3)) ^ (lane & 7)) << 4);
        const unsigned char* coef = smem + SM_COEF + (par * 2 + csel) * 64 + (lane & 3) * 16;
#pragma unroll 1
        for (int conv = 0; conv < 2; conv++) {
            if (conv == 1) mbar_wait(bars + 8 * BAR_HW, 0);
            uint32_t u[4][4];
            norm_load<4>(u, 0, conv, stg_off + 16384, act_off + ROW_BYTES);
            mbar_wait(bars + 8 * BAR_STATS, conv);
            if (tid == 128) TL(22 + conv * 4);
            float4 cf[4];
#pragma unroll
            for (int i = 0; i < 4; i++) cf[i] = *reinterpret_cast<const float4*>(coef + i * 256);
            norm_batch<0, 1>(u, cf, act_off + ROW_BYTES, bars + 8 * (BAR_FULL + par), lane, true);
            if (tid == 128) TL(8 + conv * 8);
            norm_batch<1, 3>(u, cf, act_off + ROW_BYTES, bars + 8 * (BAR_FULL + par), lane, true);
            if (tid == 128) TL(24 + conv * 4);
#pragma unroll 1
            for (int o = 0; o < 2; o++) {
                const bool valid = (o == 0) ? (r != 0) : (r != HW - 1);
                if (valid) {
                    mbar_wait(bars + 8 * (conv ? BAR_HALO + o : BAR_XH), 0);
                    norm_load<4>(u, 0, conv, stg_off + o * 2 * 16384, act_off + o * 2 * ROW_BYTES);
                }
                norm_batch<0, 4>(u, cf, act_off + o * 2 * ROW_BYTES, bars + 8 * (BAR_FULL + 8 + 8 * o + par), lane, valid);
            }
            if (tid == 128) TL(23 + conv * 4);
        }
    } else if (warp == 12) {
        bar_sync(0, NTHREADS);
        if (lane == 0) {
            unsigned it = 0;
            while (ld_relaxed(&g_s.wcnt[b * 32]) < (unsigned)NCTA && ++it < SPIN_LIMIT) {}
            fence_acquire();
            fence_async_global();
            TL(6);
            int slot = 0, st = 0; uint32_t par = 1;
#pragma unroll 1
            for (int g = 0; g < 2 * NSTAGE; g++) {
                if (g == NSTAGE) { mbar_wait(bars + 8 * BAR_EMB, 0); fence_async_global(); }
                mbar_wait(bars + 8 * (BAR_WEMPTY + slot), par);
                mbar_expect(bars + 8 * (BAR_FULL + st), STAGE_BYTES);
                bulk_g2s(sb + SM_W + slot * STAGE_BYTES, g_s.wt + (size_t)g * STAGE_BYTES, STAGE_BYTES, bars + 8 * (BAR_FULL + st));
                if (g == NS - 1) mbar_arrive(bars + 8 * BAR_WACQ);
                if (++slot == NS) { slot = 0; par ^= 1; }
                if (++st == NSTAGE) st = 0;
            }
        }
    } else if (warp == 13) {
        const uint2 ga1 = __ldg(reinterpret_cast<const uint2*>(g1) + lane), bt1 = __ldg(reinterpret_cast<const uint2*>(be1) + lane);
        const uint2 ga2 = __ldg(reinterpret_cast<const uint2*>(g2) + lane), bt2 = __ldg(reinterpret_cast<const uint2*>(be2) + lane);
        bar_sync(0, NTHREADS);
#pragma unroll 1
        for (int conv = 0; conv < 2; conv++) {
            if (conv == 1) mbar_wait(bars + 8 * BAR_HW, 0);
            const float* src = &g_s.acc[(conv * NB + b) * 32 + (lane >> 3) * 4];
            uint4 f;
            unsigned it = 0;
            while (true) {
                f = ld_relaxed_v4(src);
                const bool ok = (f.x == 0x42800000u) & (f.w == 0x42800000u);
                if (__all_sync(0xffffffffu, ok) || ++it > SPIN_LIMIT) break;
            }
            if (lane == 0) TL(7 + conv * 8);
            const float inv_n = 1.0f / (32.0f * HW * HW);
            const float mean = __uint_as_float(f.y) * inv_n;
            const float var = fmaxf(fmaf(-mean, mean, __uint_as_float(f.z) * inv_n), 0.f);
            const float rs = 0.5f * rsqrtf(var + 1e-5f);
            const uint2 ga = conv ? ga2 : ga1, bt = conv ? bt2 : bt1;
            float4 c0, c1;
            c0.x = rs * bf_lo(ga.x); c0.y = rs * bf_hi(ga.x); c1.x = rs * bf_lo(ga.y); c1.y = rs * bf_hi(ga.y);
            c0.z = fmaf(-mean, c0.x, 0.5f * bf_lo(bt.x)); c0.w = fmaf(-mean, c0.y, 0.5f * bf_hi(bt.x));
            c1.z = fmaf(-mean, c1.x, 0.5f * bf_lo(bt.y)); c1.w = fmaf(-mean, c1.y, 0.5f * bf_hi(bt.y));
            float4* cf = reinterpret_cast<float4*>(smem + SM_COEF + lane * 32);
            cf[0] = c0; cf[1] = c1;
            __syncwarp();
            if (lane == 0) { mbar_arrive(bars + 8 * BAR_STATS); TL(25 + conv * 4); }
        }
        if (r == 0) {
            if (lane < 16) g_s.acc[b * 32 + lane] = 0.f;
            if (lane < 2) g_s.wcnt[(lane * NB + b) * 32] = 0;
        }
    } else {
        bar_sync(0, NTHREADS);
        mbar_wait(bars + 8 * BAR_WACQ, 0);
        {
            const uint2* wsrc = reinterpret_cast<const uint2*>(w_emb + (size_t)r * 12 * C) + lane;
            uint2 wv[12];
#pragma unroll
            for (int i = 0; i < 12; i++) wv[i] = __ldg(wsrc + i * (C / 4));
            float tv = 0.f;
            if (lane < 12) tv = __bfloat162float(t_emb[b * E + r * 12 + lane]);
            weight_block(w2, smem + SM_BNC + 2304, g_s.wt + 72 * STEP_BYTES, cta, lane, false);
            const float sv = silu_half(0.5f * tv);
            float e0 = 0.f, e1 = 0.f, e2 = 0.f, e3 = 0.f;
#pragma unroll
            for (int i = 0; i < 12; i++) {
                const float sx = __shfl_sync(0xffffffffu, sv, i);
                e0 = fmaf(sx, bf_lo(wv[i].x), e0); e1 = fmaf(sx, bf_hi(wv[i].x), e1);
                e2 = fmaf(sx, bf_lo(wv[i].y), e2); e3 = fmaf(sx, bf_hi(wv[i].y), e3);
            }
            red_add4(&g_s.emb[b * C + lane * 4], e0, e1, e2, e3);
            __syncwarp();
            if (lane < 2) asm volatile("red.release.gpu.global.add.u32 [%0], 1;" ::"l"(&g_s.wcnt[(NB + lane) * 32]) : "memory");
            unsigned it = 0;
            while (ld_relaxed(&g_s.wcnt[(NB + b) * 32]) < (unsigned)NCTA && ++it < SPIN_LIMIT) __nanosleep(100);
            fence_acquire();
            *reinterpret_cast<uint4*>(smem + SM_EMB + lane * 16) = ld_relaxed_v4(&g_s.emb[b * C + lane * 4]);
            __syncwarp();
            if (lane == 0) { mbar_arrive(bars + 8 * BAR_EMB); TL(19); }
        }
        if (lane == 0) {
            mbar_wait(bars + 8 * BAR_HW, 0);
            asm volatile("st.release.gpu.global.u32 [%0], %1;" ::"l"(&g_s.hflag[cta * 32]), "r"(1) : "memory");
            TL(13);
        }
        __syncwarp();
        if (lane < 2) {
            const int irow = r - 1 + 2 * lane;
            if (irow >= 0 && irow < HW) {
                const int nb = cta - 1 + 2 * lane;
                unsigned it = 0;
                while (ld_relaxed(&g_s.hflag[nb * 32]) == 0 && ++it < SPIN_LIMIT) {}
                fence_acquire();
                fence_async_global();
                mbar_expect(bars + 8 * (BAR_HALO + lane), ROW_BYTES);
                bulk_g2s(sb + SM_ACT + 2 * lane * ROW_BYTES, g_s.h + (size_t)nb * ROW_BYTES, ROW_BYTES, bars + 8 * (BAR_HALO + lane));
                if (lane == 0) TL(14);
            }
        }
    }
}

}

extern "C" void kernel_launch(void* const* d_in, const int* in_sizes, int n_in, void* d_out, int out_size) {
    (void)in_sizes; (void)n_in; (void)out_size;
    static bool init = false;
    if (!init) {
        cudaFuncSetAttribute(resblock_kernel, cudaFuncAttributeMaxDynamicSharedMemorySize, SM_TOTAL);
        init = true;
    }
    resblock_kernel<<<NCTA, NTHREADS, SM_TOTAL>>>(
        (const __nv_bfloat16*)d_in[0], (const __nv_bfloat16*)d_in[1], (const __nv_bfloat16*)d_in[2],
        (const __nv_bfloat16*)d_in[3], (const __nv_bfloat16*)d_in[4], (const __nv_bfloat16*)d_in[5],
        (const __nv_bfloat16*)d_in[6], (const __nv_bfloat16*)d_in[7], (const __nv_bfloat16*)d_in[8],
        (__nv_bfloat16*)d_out);
}
```

```cpp
#include <cuda_runtime.h>
#include <cuda_bf16.h>
#include <stdint.h>

namespace {

constexpr int C = 128, HW = 64, NB = 2, E = 768;
constexpr int NCTA = NB * HW;
constexpr int NTHREADS = 15 * 32;
constexpr int CH_PITCH = 66 * 16;
constexpr int ROW_BYTES = 16 * CH_PITCH;
constexpr int STEP_BYTES = 4096;
constexpr int STAGE_BYTES = 3 * STEP_BYTES;
constexpr int NSTAGE = 24;
constexpr int NS = 8;

constexpr int SM_ACT = 0;
constexpr int SM_STG = SM_ACT + 3 * ROW_BYTES;
constexpr int SM_W = SM_STG + 3 * 16384;
constexpr int SM_COEF = SM_W + NS * STAGE_BYTES;
constexpr int SM_EMB = SM_COEF + 1024;
constexpr int SM_RED = SM_EMB + 512;
constexpr int SM_BNC = SM_RED + 128;
constexpr int SM_BAR = SM_BNC + 2 * 2304;
constexpr int BAR_FULL = 0, BAR_WEMPTY = NSTAGE, BAR_STATS = BAR_WEMPTY + NS, BAR_HW = BAR_STATS + 1,
              BAR_HALO = BAR_HW + 1  , BAR_EMB = BAR_HALO + 2, BAR_WACQ = BAR_EMB + 1, BAR_XH = BAR_WACQ + 1,
              NBAR = BAR_XH + 1;
constexpr int SM_TOTAL = SM_BAR + NBAR * 8;
static_assert(SM_TOTAL <= 232448, "smem");
constexpr int OUT_PITCH = 144;

constexpr unsigned SPIN_LIMIT = 1u << 16;
constexpr uint32_t SMEM_BASE = 0x400;

struct Scratch {
    float acc[2 * NB * 32];
    unsigned wcnt[2 * NB * 32];
    float emb[NB * C];
    unsigned hflag[NCTA * 32];
    unsigned char wt[2 * 72 * STEP_BYTES];
    unsigned char h[NCTA * ROW_BYTES];
};
__device__ __align__(1024) Scratch g_scratch;
#define TL(i) do {} while (0)
#define TLG(i) do {} while (0)

__device__ __forceinline__ uint32_t smem_u32(const void* p) { return (uint32_t)__cvta_generic_to_shared(p); }
__device__ __forceinline__ void mbar_init(uint32_t bar, int cnt) {
    asm volatile("mbarrier.init.shared::cta.b64 [%0], %1;" ::"r"(bar), "r"(cnt) : "memory");
}
__device__ __forceinline__ void mbar_arrive(uint32_t bar) {
    asm volatile("mbarrier.arrive.shared::cta.b64 _, [%0];" ::"r"(bar) : "memory");
}
__device__ __forceinline__ void mbar_expect(uint32_t bar, uint32_t bytes) {
    asm volatile("mbarrier.arrive.expect_tx.shared::cta.b64 _, [%0], %1;" ::"r"(bar), "r"(bytes) : "memory");
}
__device__ __forceinline__ bool mbar_try(uint32_t bar, uint32_t par) {
    uint32_t ok;
    asm volatile("{\n.reg .pred p;\nmbarrier.try_wait.parity.shared::cta.b64 p, [%1], %2;\nselp.u32 %0, 1, 0, p;\n}"
                 : "=r"(ok) : "r"(bar), "r"(par) : "memory");
    return ok;
}
__device__ __forceinline__ void mbar_wait(uint32_t bar, uint32_t par) {
    unsigned it = 0;
#pragma unroll 1
    while (!mbar_try(bar, par) && ++it < SPIN_LIMIT) {}
}
__device__ __forceinline__ void fence_async_smem() { asm volatile("fence.proxy.async.shared::cta;" ::: "memory"); }
__device__ __forceinline__ void fence_async_global() { asm volatile("fence.proxy.async.global;" ::: "memory"); }
__device__ __forceinline__ void bar_sync(int id, int n) { asm volatile("bar.sync %0, %1;" ::"r"(id), "r"(n) : "memory"); }
__device__ __forceinline__ void bulk_g2s(uint32_t dst, const void* src, uint32_t bytes, uint32_t bar) {
    asm volatile("cp.async.bulk.shared::cluster.global.mbarrier::complete_tx::bytes [%0], [%1], %2, [%3];"
                 ::"r"(dst), "l"(src), "r"(bytes), "r"(bar) : "memory");
}
__device__ __forceinline__ uint4 ld_relaxed_v4(const void* p) {
    uint4 v;
    asm volatile("ld.relaxed.gpu.global.v4.u32 {%0,%1,%2,%3}, [%4];" : "=r"(v.x), "=r"(v.y), "=r"(v.z), "=r"(v.w) : "l"(p) : "memory");
    return v;
}
__device__ __forceinline__ unsigned ld_acquire(const void* p) {
    unsigned v;
    asm volatile("ld.acquire.gpu.global.u32 %0, [%1];" : "=r"(v) : "l"(p) : "memory");
    return v;
}
__device__ __forceinline__ void st_relaxed(void* p, unsigned v) {
    asm volatile("st.relaxed.gpu.global.u32 [%0], %1;" ::"l"(p), "r"(v) : "memory");
}
__device__ __forceinline__ void red_add4(float* p, float a, float b, float c, float d) {
    asm volatile("red.relaxed.gpu.global.add.v4.f32 [%0], {%1,%2,%3,%4};" ::"l"(p), "f"(a), "f"(b), "f"(c), "f"(d) : "memory");
}
__device__ __forceinline__ float bf_lo(uint32_t u) { return __uint_as_float(u << 16); }
__device__ __forceinline__ float bf_hi(uint32_t u) { return __uint_as_float(u & 0xffff0000u); }
__device__ __forceinline__ uint32_t pack_bf(float lo, float hi) {
    uint32_t r;
    asm("cvt.rn.bf16x2.f32 %0, %1, %2;" : "=r"(r) : "f"(hi), "f"(lo));
    return r;
}
__device__ __forceinline__ float tanh_fast(float x) {
    float r;
    asm("tanh.approx.f32 %0, %1;" : "=f"(r) : "f"(x));
    return r;
}
__device__ __forceinline__ float silu_half(float h) { return fmaf(h, tanh_fast(h), h); }
__device__ __forceinline__ void ldsm4(uint32_t (&u)[4], uint32_t a) {
    asm volatile("ldmatrix.sync.aligned.m8n8.x4.shared.b16 {%0,%1,%2,%3}, [%4];"
                 : "=r"(u[0]), "=r"(u[1]), "=r"(u[2]), "=r"(u[3]) : "r"(a) : "memory");
}
__device__ __forceinline__ void ldsm4t(uint32_t (&u)[4], uint32_t a) {
    asm volatile("ldmatrix.sync.aligned.m8n8.x4.trans.shared.b16 {%0,%1,%2,%3}, [%4];"
                 : "=r"(u[0]), "=r"(u[1]), "=r"(u[2]), "=r"(u[3]) : "r"(a) : "memory");
}
__device__ __forceinline__ void stsm4(uint32_t a, uint32_t p0, uint32_t p1, uint32_t p2, uint32_t p3) {
    asm volatile("stmatrix.sync.aligned.m8n8.x4.shared.b16 [%0], {%1,%2,%3,%4};" ::"r"(a), "r"(p0), "r"(p1), "r"(p2), "r"(p3) : "memory");
}
__device__ __forceinline__ void stsm4t(uint32_t a, uint32_t p0, uint32_t p1, uint32_t p2, uint32_t p3) {
    asm volatile("stmatrix.sync.aligned.m8n8.x4.trans.shared.b16 [%0], {%1,%2,%3,%4};" ::"r"(a), "r"(p0), "r"(p1), "r"(p2), "r"(p3) : "memory");
}

#define R8(o) "+f"(d[o]), "+f"(d[o + 1]), "+f"(d[o + 2]), "+f"(d[o + 3]), "+f"(d[o + 4]), "+f"(d[o + 5]), "+f"(d[o + 6]), "+f"(d[o + 7])
template <uint32_t ALO, uint32_t BLO>
__device__ __forceinline__ void wgmma128(float (&d)[64]) {
    asm volatile(
        "wgmma.mma_async.sync.aligned.m64n128k16.f32.bf16.bf16 "
        "{%0,%1,%2,%3,%4,%5,%6,%7,%8,%9,%10,%11,%12,%13,%14,%15,%16,%17,%18,%19,%20,%21,%22,%23,%24,%25,%26,%27,%28,%29,%30,%31,"
        "%32,%33,%34,%35,%36,%37,%38,%39,%40,%41,%42,%43,%44,%45,%46,%47,%48,%49,%50,%51,%52,%53,%54,%55,%56,%57,%58,%59,%60,%61,%62,%63},"
        " %64, %65, 1, 1, 1, 0, 0;"
        : R8(0), R8(8), R8(16), R8(24), R8(32), R8(40), R8(48), R8(56)
        : "l"((8ull << 32) | ALO), "l"((8ull << 32) | BLO));
}
__host__ __device__ constexpr int stage_ky(int s) { return (s >> 3) == 0 ? 1 : ((s >> 3) == 1 ? 0 : 2); }
template <int S>
__device__ __forceinline__ void mma_stages(float (&d)[64], uint32_t bars, int conv, int tid, Scratch& g_s) {
    constexpr uint32_t A = ((SMEM_BASE + SM_ACT + stage_ky(S) * ROW_BYTES + (S & 7) * 2 * CH_PITCH) >> 4) | ((CH_PITCH >> 4) << 16);
    constexpr uint32_t B = ((SMEM_BASE + SM_W + (S % NS) * STAGE_BYTES) >> 4) | ((2048 >> 4) << 16);
    mbar_wait(bars + 8 * (BAR_FULL + S), conv);
    if (S == 0 && tid == 0) TL(9 + conv * 8);
    asm volatile("wgmma.fence.sync.aligned;" ::: "memory");
    wgmma128<A, B>(d);
    wgmma128<A + 1, B + (STEP_BYTES >> 4)>(d);
    wgmma128<A + 2, B + 2 * (STEP_BYTES >> 4)>(d);
    asm volatile("wgmma.commit_group.sync.aligned;" ::: "memory");
    if (S > 0) {
        asm volatile("wgmma.wait_group.sync.aligned 1;" ::: "memory");
        if ((tid & 31) == 0) mbar_arrive(bars + 8 * (BAR_WEMPTY + (S + NS - 1) % NS));
    }
    if constexpr (S + 1 < NSTAGE) mma_stages<S + 1>(d, bars, conv, tid, g_s);
}
__device__ __forceinline__ void weight_block(const __nv_bfloat16* __restrict__ w, unsigned char* bounce, unsigned char* wt,
                                             int cta, int lane, bool sync_cta) {
    const int oc0 = (cta & 15) * 8, kc = cta >> 4;
    uint4 t[5];
#pragma unroll
    for (int k = 0; k < 5; k++) {
        const int i = lane + 32 * k, row = i / 18, piece = i - row * 18;
        if (i < 144) t[k] = __ldg(reinterpret_cast<const uint4*>(w + ((size_t)(oc0 + row) * C + kc * 16) * 9) + piece);
    }
    if (sync_cta) bar_sync(0, NTHREADS);
#pragma unroll
    for (int k = 0; k < 5; k++)
        if (lane + 32 * k < 144) *reinterpret_cast<uint4*>(bounce + (lane + 32 * k) * 16) = t[k];
    __syncwarp();
    if (lane < 16) {
        const int hh = lane >> 3;
        uint32_t v[36];
#pragma unroll
        for (int i = 0; i < 9; i++) {
            const uint4 q = *reinterpret_cast<const uint4*>(bounce + (lane & 7) * 288 + hh * 144 + i * 16);
            v[4 * i] = q.x; v[4 * i + 1] = q.y; v[4 * i + 2] = q.z; v[4 * i + 3] = q.w;
        }
        unsigned char* dst = wt + kc * STAGE_BYTES + hh * 2048 + (oc0 + (lane & 7)) * 16;
#pragma unroll
        for (int tap = 0; tap < 9; tap++) {
            uint32_t o[4];
#pragma unroll
            for (int m = 0; m < 4; m++) {
                const int i0 = 18 * m + tap, i1 = i0 + 9;
                const uint32_t sel = ((i0 & 1) ? 0x32u : 0x10u) | ((i1 & 1) ? 0x7600u : 0x5400u);
                o[m] = __byte_perm(v[i0 >> 1], v[i1 >> 1], sel);
            }
            const int ky = tap / 3, kx = tap % 3;
            const int kyo = (ky == 1) ? 0 : (ky == 0 ? 1 : 2);
            *reinterpret_cast<uint4*>(dst + (kyo * 24 + kx) * STEP_BYTES) = make_uint4(o[0], o[1], o[2], o[3]);
        }
    }
    __syncwarp();
}
__device__ __forceinline__ unsigned ld_relaxed(const void* p) {
    unsigned v;
    asm volatile("ld.relaxed.gpu.global.u32 %0, [%1];" : "=r"(v) : "l"(p) : "memory");
    return v;
}
__device__ __forceinline__ void fence_acquire() { asm volatile("fence.acquire.gpu;" ::: "memory"); }
template <int N>
__device__ __forceinline__ void norm_load(uint32_t (&u)[4][4], int first, int conv, uint32_t stg, uint32_t act) {
#pragma unroll
    for (int i = 0; i < N; i++) {
        if (conv == 0) ldsm4t(u[first + i], stg + (first + i) * 4096);
        else ldsm4(u[first + i], act + (first + i) * 4 * CH_PITCH);
    }
}
template <int FIRST, int N>
__device__ __forceinline__ void norm_batch(uint32_t (&u)[4][4], const float4 (&cf)[4], uint32_t act, uint32_t bar, int lane, bool valid) {
    if (valid) {
#pragma unroll
        for (int t = FIRST; t < FIRST + N; t++) {
#pragma unroll
            for (int i = 0; i < 4; i++)
                u[t][i] = pack_bf(silu_half(fmaf(bf_lo(u[t][i]), cf[t].x, cf[t].z)), silu_half(fmaf(bf_hi(u[t][i]), cf[t].y, cf[t].w)));
            stsm4(act + t * 4 * CH_PITCH, u[t][0], u[t][1], u[t][2], u[t][3]);
        }
        fence_async_smem();
    }
    __syncwarp();
    if (lane < N) mbar_arrive(bar + 16 * (FIRST + lane));
}
__device__ __forceinline__ void fence_acc(float (&d)[64]) {
#pragma unroll
    for (int i = 0; i < 64; i++) asm volatile("" : "+f"(d[i])::"memory");
}

__global__ void __launch_bounds__(NTHREADS, 1)
resblock_kernel(const __nv_bfloat16* __restrict__ x, const __nv_bfloat16* __restrict__ t_emb,
                const __nv_bfloat16* __restrict__ g1, const __nv_bfloat16* __restrict__ be1,
                const __nv_bfloat16* __restrict__ w1, const __nv_bfloat16* __restrict__ w_emb,
                const __nv_bfloat16* __restrict__ g2, const __nv_bfloat16* __restrict__ be2,
                const __nv_bfloat16* __restrict__ w2, __nv_bfloat16* __restrict__ out, Scratch* __restrict__ gs) {
    Scratch& g_s = *gs;
    extern __shared__ __align__(128) unsigned char smem[];
    const uint32_t sb = smem_u32(smem);
    const uint32_t bars = sb + SM_BAR;
    const int tid = threadIdx.x, warp = tid >> 5, lane = tid & 31;
    const int cta = blockIdx.x, b = cta >> 6, r = cta & 63;
    if ((sb & 0xFFFFFFu) != SMEM_BASE) return;

    if (warp < 4) {
        const int wq = warp;
        if (wq == 0) {
            weight_block(w1, smem + SM_BNC, g_s.wt, cta, lane, true);
            if (lane == 0) g_s.hflag[cta * 32] = 0;
            if (r == 0) {
                if (lane < 16) g_s.acc[(NB + b) * 32 + lane] = 0.f;
                *reinterpret_cast<float4*>(&g_s.emb[b * C + lane * 4]) = make_float4(0.f, 0.f, 0.f, 0.f);
            }
            __syncwarp();
            if (lane == 0) TL(4);
            if (lane < 2) asm volatile("red.release.gpu.global.add.u32 [%0], 1;" ::"l"(&g_s.wcnt[lane * 32]) : "memory");
            if (lane == 0) TL(5);
        } else {
            const int t = tid - 32;
            if (t < NBAR) {
                const int cnt = t < BAR_WEMPTY ? 5 : (t < BAR_STATS || t == BAR_HW) ? 4 : (t == BAR_XH ? 256 : 1);
                mbar_init(bars + 8 * t, cnt);
            }
            *reinterpret_cast<uint4*>(smem + SM_ACT + (t >> 1) * CH_PITCH + (t & 1) * 65 * 16) = make_uint4(0, 0, 0, 0);
            fence_async_smem();
            bar_sync(0, NTHREADS);
            if (r == 0 || r == HW - 1) {
                uint4* z = reinterpret_cast<uint4*>(smem + SM_ACT + (r == 0 ? 0 : 2 * ROW_BYTES));
                for (int i = t; i < ROW_BYTES / 16; i += 96) z[i] = make_uint4(0, 0, 0, 0);
                fence_async_smem();
            }
        }
        bar_sync(2, 128);

        float d[64];
#pragma unroll
        for (int i = 0; i < 64; i++) d[i] = 0.f;
#pragma unroll 1
        for (int conv = 0; conv < 2; conv++) {
            fence_acc(d);
            mma_stages<0>(d, bars, conv, tid, g_s);
            asm volatile("wgmma.wait_group.sync.aligned 0;" ::: "memory");
            fence_acc(d);
            if (tid == 0) TL(10 + conv * 8);
            if (conv == 1) break;

            if (lane == 0) mbar_arrive(bars + 8 * (BAR_WEMPTY + (NSTAGE - 1) % NS));
            mbar_wait(bars + 8 * BAR_EMB, 0);
            const float* embs = reinterpret_cast<const float*>(smem + SM_EMB);
            float st[8];
#pragma unroll
            for (int g = 0; g < 4; g++) {
                float s = 0.f, q = 0.f, s2 = 0.f, q2 = 0.f;
#pragma unroll
                for (int jj = 0; jj < 4; jj++) {
                    const int j = g * 4 + jj;
                    const float2 e = *reinterpret_cast<const float2*>(embs + 8 * j + 2 * (lane & 3));
                    d[4 * j + 0] += e.x; d[4 * j + 1] += e.y; d[4 * j + 2] += e.x; d[4 * j + 3] += e.y;
                    s += d[4 * j + 0]; q = fmaf(d[4 * j + 0], d[4 * j + 0], q);
                    s2 += d[4 * j + 1]; q2 = fmaf(d[4 * j + 1], d[4 * j + 1], q2);
                    s += d[4 * j + 2]; q = fmaf(d[4 * j + 2], d[4 * j + 2], q);
                    s2 += d[4 * j + 3]; q2 = fmaf(d[4 * j + 3], d[4 * j + 3], q2);
                }
                st[2 * g] = s + s2; st[2 * g + 1] = q + q2;
            }
            {
                const bool h16 = lane & 16, h8 = lane & 8, h4 = lane & 4;
                float a[4];
#pragma unroll
                for (int i = 0; i < 4; i++) {
                    float give = h16 ? st[i] : st[i + 4], keep = h16 ? st[i + 4] : st[i];
                    a[i] = keep + __shfl_xor_sync(0xffffffffu, give, 16);
                }
                float c2[2];
#pragma unroll
                for (int i = 0; i < 2; i++) {
                    float give = h8 ? a[i] : a[i + 2], keep = h8 ? a[i + 2] : a[i];
                    c2[i] = keep + __shfl_xor_sync(0xffffffffu, give, 8);
                }
                float give = h4 ? c2[0] : c2[1], keep = h4 ? c2[1] : c2[0];
                float t = keep + __shfl_xor_sync(0xffffffffu, give, 4);
                t += __shfl_xor_sync(0xffffffffu, t, 2);
                t += __shfl_xor_sync(0xffffffffu, t, 1);
                float* red = reinterpret_cast<float*>(smem + SM_RED);
                if ((lane & 3) == 0) red[(lane >> 2) * 4 + wq] = t;
                bar_sync(2, 128);
                if (tid < 4) {
                    const float4 p = *reinterpret_cast<const float4*>(red + tid * 8);
                    const float4 p2 = *reinterpret_cast<const float4*>(red + tid * 8 + 4);
                    red_add4(&g_s.acc[(NB + b) * 32 + tid * 4], 1.f, (p.x + p.y) + (p.z + p.w), (p2.x + p2.y) + (p2.z + p2.w), 1.f);
                }
                if (tid == 0) TL(11);
            }
            const uint32_t hbase = sb + SM_ACT + ROW_BYTES + (lane >> 4) * CH_PITCH + (1 + wq * 16 + (lane & 15)) * 16;
            uint32_t* hg = reinterpret_cast<uint32_t*>(g_s.h + (size_t)cta * ROW_BYTES + (1 + wq * 16) * 16) + lane;
#pragma unroll
            for (int j = 0; j < 16; j += 2) {
                uint32_t p0 = pack_bf(d[4 * j + 0], d[4 * j + 1]), p1 = pack_bf(d[4 * j + 2], d[4 * j + 3]);
                uint32_t p2 = pack_bf(d[4 * j + 4], d[4 * j + 5]), p3 = pack_bf(d[4 * j + 6], d[4 * j + 7]);
                stsm4(hbase + j * CH_PITCH, p0, p1, p2, p3);
                hg[j * (CH_PITCH / 4)] = p0; hg[j * (CH_PITCH / 4) + 32] = p1;
                hg[(j + 1) * (CH_PITCH / 4)] = p2; hg[(j + 1) * (CH_PITCH / 4) + 32] = p3;
            }
            __syncwarp();
            if (lane == 0) mbar_arrive(bars + 8 * BAR_HW);
            if (tid == 0) TL(12);
            const uint32_t xbase = sb + SM_STG + 16384 + ((lane >> 4) * 8 + (lane & 7)) * 128 + (((2 * wq + ((lane >> 3) & 1)) ^ (lane & 7)) << 4);
#pragma unroll
            for (int j = 0; j < 16; j += 2) {
                uint32_t p[4];
                ldsm4t(p, xbase + j * 1024);
                d[4 * j + 0] = bf_lo(p[0]); d[4 * j + 1] = bf_hi(p[0]); d[4 * j + 2] = bf_lo(p[1]); d[4 * j + 3] = bf_hi(p[1]);
                d[4 * j + 4] = bf_lo(p[2]); d[4 * j + 5] = bf_hi(p[2]); d[4 * j + 6] = bf_lo(p[3]); d[4 * j + 7] = bf_hi(p[3]);
            }
        }
        {
            const uint32_t obase = sb + SM_STG + ((lane >> 4) * 8 + (lane & 7)) * OUT_PITCH + (wq * 16 + ((lane >> 3) & 1) * 8) * 2;
#pragma unroll
            for (int j = 0; j < 16; j += 2) {
                stsm4t(obase + j * 8 * OUT_PITCH, pack_bf(d[4 * j + 0], d[4 * j + 1]), pack_bf(d[4 * j + 2], d[4 * j + 3]),
                       pack_bf(d[4 * j + 4], d[4 * j + 5]), pack_bf(d[4 * j + 6], d[4 * j + 7]));
            }
            bar_sync(2, 128);
            const int oc0 = tid >> 3, seg = tid & 7;
            __nv_bfloat16* dst = out + ((size_t)(b * C + oc0) * HW + r) * HW + seg * 8;
#pragma unroll
            for (int i = 0; i < 8; i++) {
                const uint4 o = *reinterpret_cast<const uint4*>(smem + SM_STG + (oc0 + 16 * i) * OUT_PITCH + seg * 16);
                *reinterpret_cast<uint4*>(dst + (size_t)i * 16 * HW * HW) = o;
            }
            if (tid == 0) { TL(20); TLG(21); }
        }
    } else if (warp < 12) {
        const int nw = warp - 4;
        {
            const int c0 = nw * 16 + (lane >> 3), seg = lane & 7;
            const uint4* src = reinterpret_cast<const uint4*>(x + ((size_t)(b * C + c0) * HW + r) * HW) + seg;
            uint4 v[4];
#pragma unroll
            for (int i = 0; i < 4; i++) v[i] = __ldg(src + (size_t)i * 4 * (HW * HW / 8));
            bar_sync(0, NTHREADS);
            float s = 0.f, q = 0.f, s2 = 0.f, q2 = 0.f;
#pragma unroll
            for (int i = 0; i < 4; i++) {
                const uint32_t u[4] = {v[i].x, v[i].y, v[i].z, v[i].w};
#pragma unroll
                for (int k = 0; k < 4; k++) {
                    const float lo = bf_lo(u[k]), hi = bf_hi(u[k]);
                    s += lo; q = fmaf(lo, lo, q);
                    s2 += hi; q2 = fmaf(hi, hi, q2);
                }
            }
            s += s2; q += q2;
            float give = (lane < 16) ? q : s, keep = (lane < 16) ? s : q;
            keep += __shfl_xor_sync(0xffffffffu, give, 16);
            if (tid == 128) TL(2);
#pragma unroll
            for (int m = 8; m >= 1; m >>= 1) keep += __shfl_xor_sync(0xffffffffu, keep, m);
            float* red = reinterpret_cast<float*>(smem + SM_RED);
            if ((lane & 15) == 0) red[nw * 2 + (lane >> 4)] = keep;
            bar_sync(3, 256);
            if (tid < 128 + 4) {
                const float4 p = *reinterpret_cast<const float4*>(red + lane * 4);
                red_add4(&g_s.acc[b * 32 + lane * 4], 1.f, p.x + p.z, p.y + p.w, 1.f);
            }
            if (tid == 128) TL(3);
#pragma unroll
            for (int hrow = 0; hrow < 2; hrow++) {
                const int row = r - 1 + 2 * hrow;
                if (row >= 0 && row < HW) {
#pragma unroll
                    for (int i = 0; i < 4; i++) {
                        const int c = c0 + 4 * i;
                        const uint32_t dst = sb + SM_STG + hrow * 2 * 16384 + c * 128 + ((seg ^ (c & 7)) << 4);
                        asm volatile("cp.async.cg.shared.global [%0], [%1], 16;"
                                     ::"r"(dst), "l"(src + (ptrdiff_t)(2 * hrow - 1) * (HW / 8) + (size_t)i * 4 * (HW * HW / 8)) : "memory");
                    }
                }
            }
            asm volatile("cp.async.mbarrier.arrive.noinc.shared::cta.b64 [%0];" ::"r"(bars + 8 * BAR_XH) : "memory");
#pragma unroll
            for (int i = 0; i < 4; i++) {
                const int c = c0 + 4 * i;
                *reinterpret_cast<uint4*>(smem + SM_STG + 16384 + c * 128 + ((seg ^ (c & 7)) << 4)) = v[i];
            }
            bar_sync(3, 256);
        }
        const int par = nw >> 2;
        const int csel = (nw >> 1) & 1, half = nw & 1;
        const uint32_t act_off = sb + SM_ACT + (par * 2 + csel) * CH_PITCH + (1 + half * 32 + lane) * 16;
        const uint32_t stg_off = sb + SM_STG + ((par * 2 + csel) * 8 + (lane & 7)) * 128 + (((half * 4 + (lane >> 3)) ^ (lane & 7)) << 4);
        const unsigned char* coef = smem + SM_COEF + (par * 2 + csel) * 64 + (lane & 3) * 16;
#pragma unroll 1
        for (int conv = 0; conv < 2; conv++) {
            if (conv == 1) mbar_wait(bars + 8 * BAR_HW, 0);
            uint32_t u[4][4];
            norm_load<4>(u, 0, conv, stg_off + 16384, act_off + ROW_BYTES);
            mbar_wait(bars + 8 * BAR_STATS, conv);
            if (tid == 128) TL(22 + conv * 4);
            float4 cf[4];
#pragma unroll
            for (int i = 0; i < 4; i++) cf[i] = *reinterpret_cast<const float4*>(coef + i * 256);
            norm_batch<0, 1>(u, cf, act_off + ROW_BYTES, bars + 8 * (BAR_FULL + par), lane, true);
            if (tid == 128) TL(8 + conv * 8);
            norm_batch<1, 3>(u, cf, act_off + ROW_BYTES, bars + 8 * (BAR_FULL + par), lane, true);
            if (tid == 128) TL(24 + conv * 4);
#pragma unroll 1
            for (int o = 0; o < 2; o++) {
                const bool valid = (o == 0) ? (r != 0) : (r != HW - 1);
                if (valid) {
                    mbar_wait(bars + 8 * (conv ? BAR_HALO + o : BAR_XH), 0);
                    norm_load<4>(u, 0, conv, stg_off + o * 2 * 16384, act_off + o * 2 * ROW_BYTES);
                }
                norm_batch<0, 4>(u, cf, act_off + o * 2 * ROW_BYTES, bars + 8 * (BAR_FULL + 8 + 8 * o + par), lane, valid);
            }
            if (tid == 128) TL(23 + conv * 4);
        }
    } else if (warp == 12) {
        bar_sync(0, NTHREADS);
        if (lane == 0) {
            unsigned it = 0;
            while (ld_relaxed(&g_s.wcnt[b * 32]) < (unsigned)NCTA && ++it < SPIN_LIMIT) {}
            fence_acquire();
            fence_async_global();
            TL(6);
            int slot = 0, st = 0; uint32_t par = 1;
#pragma unroll 1
            for (int g = 0; g < 2 * NSTAGE; g++) {
                if (g == NSTAGE) { mbar_wait(bars + 8 * BAR_EMB, 0); fence_async_global(); }
                mbar_wait(bars + 8 * (BAR_WEMPTY + slot), par);
                mbar_expect(bars + 8 * (BAR_FULL + st), STAGE_BYTES);
                bulk_g2s(sb + SM_W + slot * STAGE_BYTES, g_s.wt + (size_t)g * STAGE_BYTES, STAGE_BYTES, bars + 8 * (BAR_FULL + st));
                if (g == NS - 1) mbar_arrive(bars + 8 * BAR_WACQ);
                if (++slot == NS) { slot = 0; par ^= 1; }
                if (++st == NSTAGE) st = 0;
            }
        }
    } else if (warp == 13) {
        const uint2 ga1 = __ldg(reinterpret_cast<const uint2*>(g1) + lane), bt1 = __ldg(reinterpret_cast<const uint2*>(be1) + lane);
        const uint2 ga2 = __ldg(reinterpret_cast<const uint2*>(g2) + lane), bt2 = __ldg(reinterpret_cast<const uint2*>(be2) + lane);
        bar_sync(0, NTHREADS);
#pragma unroll 1
        for (int conv = 0; conv < 2; conv++) {
            if (conv == 1) mbar_wait(bars + 8 * BAR_HW, 0);
            const float* src = &g_s.acc[(conv * NB + b) * 32 + (lane >> 3) * 4];
            uint4 f;
            unsigned it = 0;
            while (true) {
                f = ld_relaxed_v4(src);
                const bool ok = (f.x == 0x42800000u) & (f.w == 0x42800000u);
                if (__all_sync(0xffffffffu, ok) || ++it > SPIN_LIMIT) break;
            }
            if (lane == 0) TL(7 + conv * 8);
            const float inv_n = 1.0f / (32.0f * HW * HW);
            const float mean = __uint_as_float(f.y) * inv_n;
            const float var = fmaxf(fmaf(-mean, mean, __uint_as_float(f.z) * inv_n), 0.f);
            const float rs = 0.5f * rsqrtf(var + 1e-5f);
            const uint2 ga = conv ? ga2 : ga1, bt = conv ? bt2 : bt1;
            float4 c0, c1;
            c0.x = rs * bf_lo(ga.x); c0.y = rs * bf_hi(ga.x); c1.x = rs * bf_lo(ga.y); c1.y = rs * bf_hi(ga.y);
            c0.z = fmaf(-mean, c0.x, 0.5f * bf_lo(bt.x)); c0.w = fmaf(-mean, c0.y, 0.5f * bf_hi(bt.x));
            c1.z = fmaf(-mean, c1.x, 0.5f * bf_lo(bt.y)); c1.w = fmaf(-mean, c1.y, 0.5f * bf_hi(bt.y));
            float4* cf = reinterpret_cast<float4*>(smem + SM_COEF + lane * 32);
            cf[0] = c0; cf[1] = c1;
            __syncwarp();
            if (lane == 0) { mbar_arrive(bars + 8 * BAR_STATS); TL(25 + conv * 4); }
        }
        if (r == 0) {
            if (lane < 16) g_s.acc[b * 32 + lane] = 0.f;
            if (lane < 2) g_s.wcnt[(lane * NB + b) * 32] = 0;
        }
    } else {
        bar_sync(0, NTHREADS);
        mbar_wait(bars + 8 * BAR_WACQ, 0);
        {
            const uint2* wsrc = reinterpret_cast<const uint2*>(w_emb + (size_t)r * 12 * C) + lane;
            uint2 wv[12];
#pragma unroll
            for (int i = 0; i < 12; i++) wv[i] = __ldg(wsrc + i * (C / 4));
            float tv = 0.f;
            if (lane < 12) tv = __bfloat162float(t_emb[b * E + r * 12 + lane]);
            weight_block(w2, smem + SM_BNC + 2304, g_s.wt + 72 * STEP_BYTES, cta, lane, false);
            const float sv = silu_half(0.5f * tv);
            float e0 = 0.f, e1 = 0.f, e2 = 0.f, e3 = 0.f;
#pragma unroll
            for (int i = 0; i < 12; i++) {
                const float sx = __shfl_sync(0xffffffffu, sv, i);
                e0 = fmaf(sx, bf_lo(wv[i].x), e0); e1 = fmaf(sx, bf_hi(wv[i].x), e1);
                e2 = fmaf(sx, bf_lo(wv[i].y), e2); e3 = fmaf(sx, bf_hi(wv[i].y), e3);
            }
            red_add4(&g_s.emb[b * C + lane * 4], e0, e1, e2, e3);
            __syncwarp();
            if (lane < 2) asm volatile("red.release.gpu.global.add.u32 [%0], 1;" ::"l"(&g_s.wcnt[(NB + lane) * 32]) : "memory");
            unsigned it = 0;
            while (ld_relaxed(&g_s.wcnt[(NB + b) * 32]) < (unsigned)NCTA && ++it < SPIN_LIMIT) __nanosleep(100);
            fence_acquire();
            *reinterpret_cast<uint4*>(smem + SM_EMB + lane * 16) = ld_relaxed_v4(&g_s.emb[b * C + lane * 4]);
            __syncwarp();
            if (lane == 0) { mbar_arrive(bars + 8 * BAR_EMB); TL(19); }
        }
        if (lane == 0) {
            mbar_wait(bars + 8 * BAR_HW, 0);
            asm volatile("st.release.gpu.global.u32 [%0], %1;" ::"l"(&g_s.hflag[cta * 32]), "r"(1) : "memory");
            TL(13);
        }
        __syncwarp();
        if (lane < 2) {
            const int irow = r - 1 + 2 * lane;
            if (irow >= 0 && irow < HW) {
                const int nb = cta - 1 + 2 * lane;
                unsigned it = 0;
                while (ld_relaxed(&g_s.hflag[nb * 32]) == 0 && ++it < SPIN_LIMIT) {}
                fence_acquire();
                fence_async_global();
                mbar_expect(bars + 8 * (BAR_HALO + lane), ROW_BYTES);
                bulk_g2s(sb + SM_ACT + 2 * lane * ROW_BYTES, g_s.h + (size_t)nb * ROW_BYTES, ROW_BYTES, bars + 8 * (BAR_HALO + lane));
                if (lane == 0) TL(14);
            }
        }
    }
}

}

extern "C" void kernel_launch(void* const* d_in, const int* in_sizes, int n_in, void* d_out, int out_size) {
    (void)in_sizes; (void)n_in; (void)out_size;
    static Scratch* gs = nullptr;
    if (!gs) {
        cudaFuncSetAttribute(resblock_kernel, cudaFuncAttributeMaxDynamicSharedMemorySize, SM_TOTAL);
        cudaGetSymbolAddress((void**)&gs, g_scratch);
    }
    resblock_kernel<<<NCTA, NTHREADS, SM_TOTAL>>>(
        (const __nv_bfloat16*)d_in[0], (const __nv_bfloat16*)d_in[1], (const __nv_bfloat16*)d_in[2],
        (const __nv_bfloat16*)d_in[3], (const __nv_bfloat16*)d_in[4], (const __nv_bfloat16*)d_in[5],
        (const __nv_bfloat16*)d_in[6], (const __nv_bfloat16*)d_in[7], (const __nv_bfloat16*)d_in[8],
        (__nv_bfloat16*)d_out, gs);
}
```

```cpp
#include <cuda_runtime.h>
#include <cuda_bf16.h>
#include <stdint.h>

namespace {

constexpr int C = 128, HW = 64, NB = 2, E = 768;
constexpr int NCTA = NB * HW;
constexpr int NTHREADS = 15 * 32;
constexpr int CH_PITCH = 66 * 16;
constexpr int ROW_BYTES = 16 * CH_PITCH;
constexpr int STEP_BYTES = 4096;
constexpr int STAGE_BYTES = 3 * STEP_BYTES;
constexpr int NSTAGE = 24;
constexpr int NS = 8;

constexpr uint32_t SMEM_BASE = 0x400;
constexpr uint32_t SM_ACT = SMEM_BASE;
constexpr uint32_t SM_STG = SM_ACT + 3 * ROW_BYTES + 128;
constexpr uint32_t SM_W = SM_STG + 3 * 16384;
constexpr uint32_t SM_COEF = SM_W + NS * STAGE_BYTES;
constexpr uint32_t SM_EMB = SM_COEF + 1024;
constexpr uint32_t SM_RED = SM_EMB + 512;
constexpr uint32_t SM_BNC = SM_RED + 128;
constexpr uint32_t SM_BAR = SM_BNC + 2 * 2304;
constexpr int BAR_FULL = 0, BAR_WEMPTY = NSTAGE, BAR_STATS = BAR_WEMPTY + NS, BAR_HW = BAR_STATS + 1,
              BAR_HALO = BAR_HW + 1  , BAR_EMB = BAR_HALO + 2, BAR_WACQ = BAR_EMB + 1, BAR_XH = BAR_WACQ + 1,
              NBAR = BAR_XH + 1;
constexpr int SM_TOTAL = SM_BAR + NBAR * 8 - SMEM_BASE;
static_assert(SM_TOTAL <= 232448, "smem");
constexpr int OUT_PITCH = 144;
__host__ __device__ constexpr uint32_t BAR(int i) { return SM_BAR + 8 * i; }

constexpr unsigned SPIN_LIMIT = 1u << 16;

struct Scratch {
    float acc[2 * NB * 32];
    unsigned wcnt[2 * NB * 32];
    float emb[NB * C];
    unsigned hflag[NCTA * 32];
    unsigned char wt[2 * 72 * STEP_BYTES];
    unsigned char h[NCTA * ROW_BYTES];
};
__device__ __align__(1024) Scratch g_scratch;
#define TL(i) do {} while (0)
#define TLG(i) do {} while (0)

__device__ __forceinline__ void mbar_init(uint32_t bar, int cnt) {
    asm volatile("mbarrier.init.shared::cta.b64 [%0], %1;" ::"r"(bar), "r"(cnt) : "memory");
}
__device__ __forceinline__ void mbar_arrive(uint32_t bar) {
    asm volatile("mbarrier.arrive.shared::cta.b64 _, [%0];" ::"r"(bar) : "memory");
}
__device__ __forceinline__ void mbar_expect(uint32_t bar, uint32_t bytes) {
    asm volatile("mbarrier.arrive.expect_tx.shared::cta.b64 _, [%0], %1;" ::"r"(bar), "r"(bytes) : "memory");
}
__device__ __forceinline__ bool mbar_try(uint32_t bar, uint32_t par) {
    uint32_t ok;
    asm volatile("{\n.reg .pred p;\nmbarrier.try_wait.parity.shared::cta.b64 p, [%1], %2;\nselp.u32 %0, 1, 0, p;\n}"
                 : "=r"(ok) : "r"(bar), "r"(par) : "memory");
    return ok;
}
__device__ __forceinline__ void mbar_wait(uint32_t bar, uint32_t par) {
    unsigned it = 0;
#pragma unroll 1
    while (!mbar_try(bar, par) && ++it < SPIN_LIMIT) {}
}
__device__ __forceinline__ bool elect_one() {
    uint32_t p;
    asm volatile("{\n.reg .pred p;\nelect.sync _|p, 0xffffffff;\nselp.u32 %0, 1, 0, p;\n}" : "=r"(p));
    return p;
}
__device__ __forceinline__ void fence_async_smem() { asm volatile("fence.proxy.async.shared::cta;" ::: "memory"); }
__device__ __forceinline__ void fence_async_global() { asm volatile("fence.proxy.async.global;" ::: "memory"); }
__device__ __forceinline__ void fence_acquire() { asm volatile("fence.acquire.gpu;" ::: "memory"); }
__device__ __forceinline__ void bar_sync(int id, int n) { asm volatile("bar.sync %0, %1;" ::"r"(id), "r"(n) : "memory"); }
__device__ __forceinline__ void bar_arrive(int id, int n) { asm volatile("bar.arrive %0, %1;" ::"r"(id), "r"(n) : "memory"); }
__device__ __forceinline__ void bulk_g2s(uint32_t dst, const void* src, uint32_t bytes, uint32_t bar) {
    asm volatile("cp.async.bulk.shared::cluster.global.mbarrier::complete_tx::bytes [%0], [%1], %2, [%3];"
                 ::"r"(dst), "l"(src), "r"(bytes), "r"(bar) : "memory");
}
__device__ __forceinline__ uint4 ld_relaxed_v4(const void* p) {
    uint4 v;
    asm volatile("ld.relaxed.gpu.global.v4.u32 {%0,%1,%2,%3}, [%4];" : "=r"(v.x), "=r"(v.y), "=r"(v.z), "=r"(v.w) : "l"(p) : "memory");
    return v;
}
__device__ __forceinline__ unsigned ld_relaxed(const void* p) {
    unsigned v;
    asm volatile("ld.relaxed.gpu.global.u32 %0, [%1];" : "=r"(v) : "l"(p) : "memory");
    return v;
}
__device__ __forceinline__ void red_add4(float* p, float a, float b, float c, float d) {
    asm volatile("red.relaxed.gpu.global.add.v4.f32 [%0], {%1,%2,%3,%4};" ::"l"(p), "f"(a), "f"(b), "f"(c), "f"(d) : "memory");
}
__device__ __forceinline__ void sts128(uint32_t a, uint4 v) {
    asm volatile("st.shared.v4.u32 [%0], {%1,%2,%3,%4};" ::"r"(a), "r"(v.x), "r"(v.y), "r"(v.z), "r"(v.w) : "memory");
}
__device__ __forceinline__ void sts128f(uint32_t a, float4 v) {
    asm volatile("st.shared.v4.f32 [%0], {%1,%2,%3,%4};" ::"r"(a), "f"(v.x), "f"(v.y), "f"(v.z), "f"(v.w) : "memory");
}
__device__ __forceinline__ void sts32f(uint32_t a, float v) { asm volatile("st.shared.f32 [%0], %1;" ::"r"(a), "f"(v) : "memory"); }
__device__ __forceinline__ uint4 lds128(uint32_t a) {
    uint4 v;
    asm volatile("ld.shared.v4.u32 {%0,%1,%2,%3}, [%4];" : "=r"(v.x), "=r"(v.y), "=r"(v.z), "=r"(v.w) : "r"(a) : "memory");
    return v;
}
__device__ __forceinline__ float4 lds128f(uint32_t a) {
    float4 v;
    asm volatile("ld.shared.v4.f32 {%0,%1,%2,%3}, [%4];" : "=f"(v.x), "=f"(v.y), "=f"(v.z), "=f"(v.w) : "r"(a) : "memory");
    return v;
}
__device__ __forceinline__ float2 lds64f(uint32_t a) {
    float2 v;
    asm volatile("ld.shared.v2.f32 {%0,%1}, [%2];" : "=f"(v.x), "=f"(v.y) : "r"(a) : "memory");
    return v;
}
__device__ __forceinline__ float bf_lo(uint32_t u) { return __uint_as_float(u << 16); }
__device__ __forceinline__ float bf_hi(uint32_t u) { return __uint_as_float(u & 0xffff0000u); }
__device__ __forceinline__ uint32_t pack_bf(float lo, float hi) {
    uint32_t r;
    asm("cvt.rn.bf16x2.f32 %0, %1, %2;" : "=r"(r) : "f"(hi), "f"(lo));
    return r;
}
__device__ __forceinline__ float tanh_fast(float x) {
    float r;
    asm("tanh.approx.f32 %0, %1;" : "=f"(r) : "f"(x));
    return r;
}
__device__ __forceinline__ float silu_half(float h) { return fmaf(h, tanh_fast(h), h); }
__device__ __forceinline__ void ldsm4(uint32_t (&u)[4], uint32_t a) {
    asm volatile("ldmatrix.sync.aligned.m8n8.x4.shared.b16 {%0,%1,%2,%3}, [%4];"
                 : "=r"(u[0]), "=r"(u[1]), "=r"(u[2]), "=r"(u[3]) : "r"(a) : "memory");
}
__device__ __forceinline__ void ldsm4t(uint32_t (&u)[4], uint32_t a) {
    asm volatile("ldmatrix.sync.aligned.m8n8.x4.trans.shared.b16 {%0,%1,%2,%3}, [%4];"
                 : "=r"(u[0]), "=r"(u[1]), "=r"(u[2]), "=r"(u[3]) : "r"(a) : "memory");
}
__device__ __forceinline__ void stsm4(uint32_t a, uint32_t p0, uint32_t p1, uint32_t p2, uint32_t p3) {
    asm volatile("stmatrix.sync.aligned.m8n8.x4.shared.b16 [%0], {%1,%2,%3,%4};" ::"r"(a), "r"(p0), "r"(p1), "r"(p2), "r"(p3) : "memory");
}
__device__ __forceinline__ void stsm4t(uint32_t a, uint32_t p0, uint32_t p1, uint32_t p2, uint32_t p3) {
    asm volatile("stmatrix.sync.aligned.m8n8.x4.trans.shared.b16 [%0], {%1,%2,%3,%4};" ::"r"(a), "r"(p0), "r"(p1), "r"(p2), "r"(p3) : "memory");
}

#define R8(o) "+f"(d[o]), "+f"(d[o + 1]), "+f"(d[o + 2]), "+f"(d[o + 3]), "+f"(d[o + 4]), "+f"(d[o + 5]), "+f"(d[o + 6]), "+f"(d[o + 7])
template <uint32_t ALO, uint32_t BLO>
__device__ __forceinline__ void wgmma128(float (&d)[64]) {
    asm volatile(
        "wgmma.mma_async.sync.aligned.m64n128k16.f32.bf16.bf16 "
        "{%0,%1,%2,%3,%4,%5,%6,%7,%8,%9,%10,%11,%12,%13,%14,%15,%16,%17,%18,%19,%20,%21,%22,%23,%24,%25,%26,%27,%28,%29,%30,%31,"
        "%32,%33,%34,%35,%36,%37,%38,%39,%40,%41,%42,%43,%44,%45,%46,%47,%48,%49,%50,%51,%52,%53,%54,%55,%56,%57,%58,%59,%60,%61,%62,%63},"
        " %64, %65, 1, 1, 1, 0, 0;"
        : R8(0), R8(8), R8(16), R8(24), R8(32), R8(40), R8(48), R8(56)
        : "l"((8ull << 32) | ALO), "l"((8ull << 32) | BLO));
}
__host__ __device__ constexpr int stage_ky(int s) { return (s >> 3) == 0 ? 1 : ((s >> 3) == 1 ? 0 : 2); }

template <int S>
__device__ __forceinline__ void mma_stages(float (&d)[64], int conv, int tid, Scratch* gs) {
    constexpr uint32_t A = ((SM_ACT + stage_ky(S) * ROW_BYTES + (S & 7) * 2 * CH_PITCH + 16) >> 4) | ((CH_PITCH >> 4) << 16);
    constexpr uint32_t B = ((SM_W + (S % NS) * STAGE_BYTES) >> 4) | ((2048 >> 4) << 16);
    mbar_wait(BAR(BAR_FULL + S), conv);
    if (S == 0 && tid == 0) TL(9 + conv * 8);
    asm volatile("wgmma.fence.sync.aligned;" ::: "memory");
    wgmma128<A, B>(d);
    wgmma128<A + 1, B + (STEP_BYTES >> 4)>(d);
    wgmma128<A + 2, B + 2 * (STEP_BYTES >> 4)>(d);
    asm volatile("wgmma.commit_group.sync.aligned;" ::: "memory");
    if (S > 0) {
        asm volatile("wgmma.wait_group.sync.aligned 1;" ::: "memory");
        if ((tid & 31) == 0) mbar_arrive(BAR(BAR_WEMPTY + (S + NS - 1) % NS));
    }
    if constexpr (S + 1 < NSTAGE) mma_stages<S + 1>(d, conv, tid, gs);
}

__device__ __forceinline__ void weight_block(const uint4 (&t)[5], uint32_t bounce, unsigned char* wt, int cta, int lane) {
    const uint32_t bw = bounce + (lane >> 4) * 1152 + (lane & 15) * 16;
#pragma unroll
    for (int k = 0; k < 4; k++) sts128(bw + k * 256, t[k]);
    if ((lane & 15) < 8) sts128(bw + 1024, t[4]);
    __syncwarp();
    if (lane < 16) {
        uint32_t v[36];
#pragma unroll
        for (int i = 0; i < 9; i++) {
            const uint4 q = lds128(bounce + (lane & 1) * 1152 + (lane >> 1) * 144 + i * 16);
            v[4 * i] = q.x; v[4 * i + 1] = q.y; v[4 * i + 2] = q.z; v[4 * i + 3] = q.w;
        }
        const int cc = (cta >> 6) * 8 + (lane >> 1);
        unsigned char* dst = wt + (cc >> 1) * STAGE_BYTES + (cc & 1) * 2048 + ((cta & 63) * 2 + (lane & 1)) * 16;
#pragma unroll
        for (int tap = 0; tap < 9; tap++) {
            uint32_t o[4];
#pragma unroll
            for (int m = 0; m < 4; m++) {
                const int i0 = 18 * m + tap, i1 = i0 + 9;
                const uint32_t sel = ((i0 & 1) ? 0x32u : 0x10u) | ((i1 & 1) ? 0x7600u : 0x5400u);
                o[m] = __byte_perm(v[i0 >> 1], v[i1 >> 1], sel);
            }
            const int ky = tap / 3, kx = tap % 3;
            const int kyo = (ky == 1) ? 0 : (ky == 0 ? 1 : 2);
            *reinterpret_cast<uint4*>(dst + (kyo * 24 + kx) * STEP_BYTES) = make_uint4(o[0], o[1], o[2], o[3]);
        }
    }
}
__device__ __forceinline__ void norm_load(uint32_t (&u)[4][4], int conv, uint32_t stg, uint32_t act) {
#pragma unroll
    for (int i = 0; i < 4; i++) {
        if (conv == 0) ldsm4t(u[i], stg + i * 4096);
        else ldsm4(u[i], act + i * 4 * CH_PITCH);
    }
}
template <int FIRST, int N>
__device__ __forceinline__ void norm_batch(uint32_t (&u)[4][4], const float4 (&cf)[4], uint32_t act, uint32_t bar, int lane, bool valid) {
    if (valid) {
#pragma unroll
        for (int t = FIRST; t < FIRST + N; t++) {
#pragma unroll
            for (int i = 0; i < 4; i++)
                u[t][i] = pack_bf(silu_half(fmaf(bf_lo(u[t][i]), cf[t].x, cf[t].z)), silu_half(fmaf(bf_hi(u[t][i]), cf[t].y, cf[t].w)));
            stsm4(act + t * 4 * CH_PITCH, u[t][0], u[t][1], u[t][2], u[t][3]);
        }
        fence_async_smem();
    }
    __syncwarp();
    if (lane < N) mbar_arrive(bar + 16 * (FIRST + lane));
}
__device__ __forceinline__ void fence_acc(float (&d)[64]) {
#pragma unroll
    for (int i = 0; i < 64; i++) asm volatile("" : "+f"(d[i])::"memory");
}

__global__ void __launch_bounds__(NTHREADS, 1)
resblock_kernel(const __nv_bfloat16* __restrict__ x, const __nv_bfloat16* __restrict__ w1,
                const __nv_bfloat16* __restrict__ t_emb, const __nv_bfloat16* __restrict__ g1,
                const __nv_bfloat16* __restrict__ be1, const __nv_bfloat16* __restrict__ w_emb,
                const __nv_bfloat16* __restrict__ g2, const __nv_bfloat16* __restrict__ be2,
                const __nv_bfloat16* __restrict__ w2, __nv_bfloat16* __restrict__ out, Scratch* __restrict__ gs) {
    const int tid = threadIdx.x, warp = tid >> 5, lane = tid & 31;
    const int cta = blockIdx.x, b = cta >> 6, r = cta & 63;

    const uint32_t woff = ((2 * r + (lane >> 4)) * C + b * 64) * 18 + (lane & 15) * 16;
    const int c0 = (warp - 4) * 16 + (lane >> 3), seg = lane & 7;
    const char* src = (warp == 0) ? reinterpret_cast<const char*>(w1) + woff
                                  : reinterpret_cast<const char*>(x) + (uint32_t)(((b * C + c0) * HW + r) * HW * 2 + seg * 16);
    uint4 v[5];
    if (warp == 0 || (warp >= 4 && warp < 12)) {
        const uint32_t stride = (warp == 0) ? 256 : 4 * HW * HW * 2;
#pragma unroll
        for (int k = 0; k < 4; k++) v[k] = __ldg(reinterpret_cast<const uint4*>(src + k * stride));
        if (tid < 32 && (lane & 15) < 8) v[4] = __ldg(reinterpret_cast<const uint4*>(src + 1024));
    }

    if (warp >= 4 && warp < 12) {
        const int nw = warp - 4;
        {
            float s = 0.f, q = 0.f, s2 = 0.f, q2 = 0.f;
#pragma unroll
            for (int i = 0; i < 4; i++) {
                const uint32_t u[4] = {v[i].x, v[i].y, v[i].z, v[i].w};
#pragma unroll
                for (int k = 0; k < 4; k++) {
                    const float lo = bf_lo(u[k]), hi = bf_hi(u[k]);
                    s += lo; q = fmaf(lo, lo, q);
                    s2 += hi; q2 = fmaf(hi, hi, q2);
                }
            }
            s += s2; q += q2;
            float give = (lane < 16) ? q : s, keep = (lane < 16) ? s : q;
            keep += __shfl_xor_sync(0xffffffffu, give, 16);
            if (tid == 128) TL(2);
#pragma unroll
            for (int m = 8; m >= 1; m >>= 1) keep += __shfl_xor_sync(0xffffffffu, keep, m);
            if ((lane & 15) == 0) sts32f(SM_RED + (nw * 2 + (lane >> 4)) * 4, keep);
            bar_sync(3, 384);
            if (tid < 128 + 4) {
                const float4 p = lds128f(SM_RED + lane * 16);
                red_add4(&gs->acc[b * 32 + lane * 4], 1.f, p.x + p.z, p.y + p.w, 1.f);
            }
            if (tid == 128) TL(3);
            const uint32_t sdst = SM_STG + c0 * 128;
#pragma unroll
            for (int i = 0; i < 4; i++) sts128(sdst + 16384 + i * 512 + ((seg ^ ((c0 + 4 * i) & 7)) << 4), v[i]);
#pragma unroll
            for (int hrow = 0; hrow < 2; hrow++) {
                if (hrow == 0 ? (r != 0) : (r != HW - 1)) {
#pragma unroll
                    for (int i = 0; i < 4; i++) {
                        asm volatile("cp.async.cg.shared.global [%0], [%1], 16;"
                                     ::"r"(sdst + hrow * 2 * 16384 + i * 512 + ((seg ^ ((c0 + 4 * i) & 7)) << 4)),
                                       "l"(src + (2 * hrow - 1) * (HW * 2) + i * (4 * HW * HW * 2)) : "memory");
                    }
                }
            }
            asm volatile("cp.async.mbarrier.arrive.noinc.shared::cta.b64 [%0];" ::"r"(BAR(BAR_XH)) : "memory");
            bar_sync(4, 256);
        }
        const int par = nw >> 2;
        const int ch0 = par * 2 + ((nw >> 1) & 1), half = nw & 1;
        const uint32_t act_off = SM_ACT + ch0 * CH_PITCH + (2 + half * 32 + lane) * 16;
        const uint32_t stg_off = SM_STG + (ch0 * 8 + (lane & 7)) * 128 + (((half * 4 + (lane >> 3)) ^ (lane & 7)) << 4);
        const uint32_t coef = SM_COEF + ch0 * 64 + (lane & 3) * 16;
#pragma unroll 1
        for (int conv = 0; conv < 2; conv++) {
            if (conv == 1) mbar_wait(BAR(BAR_HW), 0);
            uint32_t u[4][4];
            norm_load(u, conv, stg_off + 16384, act_off + ROW_BYTES);
            mbar_wait(BAR(BAR_STATS), conv);
            if (tid == 128) TL(22 + conv * 4);
            float4 cf[4];
#pragma unroll
            for (int i = 0; i < 4; i++) cf[i] = lds128f(coef + i * 256);
            norm_batch<0, 1>(u, cf, act_off + ROW_BYTES, BAR(BAR_FULL) + 8 * par, lane, true);
            if (tid == 128) TL(8 + conv * 8);
            norm_batch<1, 3>(u, cf, act_off + ROW_BYTES, BAR(BAR_FULL) + 8 * par, lane, true);
            if (tid == 128) TL(24 + conv * 4);
#pragma unroll 1
            for (int o = 0; o < 2; o++) {
                const bool valid = (o == 0) ? (r != 0) : (r != HW - 1);
                if (valid) {
                    mbar_wait(conv ? BAR(BAR_HALO) + 8 * o : BAR(BAR_XH), 0);
                    norm_load(u, conv, stg_off + o * 2 * 16384, act_off + o * 2 * ROW_BYTES);
                }
                norm_batch<0, 4>(u, cf, act_off + o * 2 * ROW_BYTES, BAR(BAR_FULL + 8) + 8 * (8 * o + par), lane, valid);
            }
            if (tid == 128) TL(23 + conv * 4);
        }
    } else if (warp < 4) {
        const int wq = warp;
        if (wq == 0) {
            weight_block(v, SM_BNC, gs->wt, cta, lane);
            if (lane == 0) gs->hflag[cta * 32] = 0;
            if (r == 0) {
                if (lane < 16) gs->acc[(NB + b) * 32 + lane] = 0.f;
                *reinterpret_cast<float4*>(&gs->emb[b * C + lane * 4]) = make_float4(0.f, 0.f, 0.f, 0.f);
            }
            __syncwarp();
            if (lane == 0) TL(4);
            if (lane < 2) asm volatile("red.release.gpu.global.add.u32 [%0], 1;" ::"l"(&gs->wcnt[lane * 32]) : "memory");
            if (lane == 0) TL(5);
        } else {
            const int t = tid - 32;
            if (t < NBAR) {
                const int cnt = t < BAR_WEMPTY ? 5 : (t < BAR_STATS || t == BAR_HW) ? 4 : (t == BAR_XH ? 256 : 1);
                mbar_init(BAR(0) + 8 * t, cnt);
            }
            fence_async_smem();
            bar_arrive(0, 160);
            bar_arrive(3, 384);
            const uint4 z = make_uint4(0, 0, 0, 0);
            sts128(SM_ACT + (t >> 1) * CH_PITCH + (t & 1) * 16, z);
            if (t < 2) sts128(SM_ACT + 3 * ROW_BYTES + t * 16, z);
            if (r == 0 || r == HW - 1) {
                for (int i = t; i < ROW_BYTES / 16; i += 96) sts128(SM_ACT + (r == 0 ? 0 : 2 * ROW_BYTES) + i * 16, z);
            }
            fence_async_smem();
        }
        bar_sync(2, 128);

        float d[64];
#pragma unroll
        for (int i = 0; i < 64; i++) d[i] = 0.f;
#pragma unroll 1
        for (int conv = 0; conv < 2; conv++) {
            fence_acc(d);
            mma_stages<0>(d, conv, tid, gs);
            asm volatile("wgmma.wait_group.sync.aligned 0;" ::: "memory");
            fence_acc(d);
            if (tid == 0) TL(10 + conv * 8);
            if (conv == 1) break;

            if (lane == 0) mbar_arrive(BAR(BAR_WEMPTY + (NSTAGE - 1) % NS));
            mbar_wait(BAR(BAR_EMB), 0);
            float st[8];
#pragma unroll
            for (int g = 0; g < 4; g++) {
                float s = 0.f, q = 0.f, s2 = 0.f, q2 = 0.f;
#pragma unroll
                for (int jj = 0; jj < 4; jj++) {
                    const int j = g * 4 + jj;
                    const float2 e = lds64f(SM_EMB + j * 32 + (lane & 3) * 8);
                    d[4 * j + 0] += e.x; d[4 * j + 1] += e.y; d[4 * j + 2] += e.x; d[4 * j + 3] += e.y;
                    s += d[4 * j + 0]; q = fmaf(d[4 * j + 0], d[4 * j + 0], q);
                    s2 += d[4 * j + 1]; q2 = fmaf(d[4 * j + 1], d[4 * j + 1], q2);
                    s += d[4 * j + 2]; q = fmaf(d[4 * j + 2], d[4 * j + 2], q);
                    s2 += d[4 * j + 3]; q2 = fmaf(d[4 * j + 3], d[4 * j + 3], q2);
                }
                st[2 * g] = s + s2; st[2 * g + 1] = q + q2;
            }
            {
                const bool h16 = lane & 16, h8 = lane & 8, h4 = lane & 4;
                float a[4];
#pragma unroll
                for (int i = 0; i < 4; i++) {
                    float give = h16 ? st[i] : st[i + 4], keep = h16 ? st[i + 4] : st[i];
                    a[i] = keep + __shfl_xor_sync(0xffffffffu, give, 16);
                }
                float c2[2];
#pragma unroll
                for (int i = 0; i < 2; i++) {
                    float give = h8 ? a[i] : a[i + 2], keep = h8 ? a[i + 2] : a[i];
                    c2[i] = keep + __shfl_xor_sync(0xffffffffu, give, 8);
                }
                float give = h4 ? c2[0] : c2[1], keep = h4 ? c2[1] : c2[0];
                float t = keep + __shfl_xor_sync(0xffffffffu, give, 4);
                t += __shfl_xor_sync(0xffffffffu, t, 2);
                t += __shfl_xor_sync(0xffffffffu, t, 1);
                if ((lane & 3) == 0) sts32f(SM_RED + ((lane >> 2) * 4 + wq) * 4, t);
                bar_sync(2, 128);
                if (tid < 4) {
                    const float4 p = lds128f(SM_RED + tid * 32), p2 = lds128f(SM_RED + tid * 32 + 16);
                    red_add4(&gs->acc[(NB + b) * 32 + tid * 4], 1.f, (p.x + p.y) + (p.z + p.w), (p2.x + p2.y) + (p2.z + p2.w), 1.f);
                }
                if (tid == 0) TL(11);
            }
            const uint32_t hbase = SM_ACT + ROW_BYTES + (lane >> 4) * CH_PITCH + (2 + wq * 16 + (lane & 15)) * 16;
            unsigned char* hrow = gs->h + (size_t)cta * ROW_BYTES;
            uint32_t* hg = reinterpret_cast<uint32_t*>(hrow + (2 + wq * 16) * 16) + lane;
#pragma unroll
            for (int j = 0; j < 16; j += 2) {
                uint32_t p0 = pack_bf(d[4 * j + 0], d[4 * j + 1]), p1 = pack_bf(d[4 * j + 2], d[4 * j + 3]);
                uint32_t p2 = pack_bf(d[4 * j + 4], d[4 * j + 5]), p3 = pack_bf(d[4 * j + 6], d[4 * j + 7]);
                stsm4(hbase + j * CH_PITCH, p0, p1, p2, p3);
                hg[j * (CH_PITCH / 4)] = p0; hg[j * (CH_PITCH / 4) + 32] = p1;
                hg[(j + 1) * (CH_PITCH / 4)] = p2; hg[(j + 1) * (CH_PITCH / 4) + 32] = p3;
            }
            *reinterpret_cast<uint32_t*>(hrow + (tid >> 3) * CH_PITCH + (tid & 7) * 4) = 0;
            __syncwarp();
            if (lane == 0) mbar_arrive(BAR(BAR_HW));
            if (tid == 0) TL(12);
            const uint32_t xbase = SM_STG + 16384 + ((lane >> 4) * 8 + (lane & 7)) * 128 + (((2 * wq + ((lane >> 3) & 1)) ^ (lane & 7)) << 4);
#pragma unroll
            for (int j = 0; j < 16; j += 2) {
                uint32_t p[4];
                ldsm4t(p, xbase + j * 1024);
                d[4 * j + 0] = bf_lo(p[0]); d[4 * j + 1] = bf_hi(p[0]); d[4 * j + 2] = bf_lo(p[1]); d[4 * j + 3] = bf_hi(p[1]);
                d[4 * j + 4] = bf_lo(p[2]); d[4 * j + 5] = bf_hi(p[2]); d[4 * j + 6] = bf_lo(p[3]); d[4 * j + 7] = bf_hi(p[3]);
            }
        }
        {
            const uint32_t obase = SM_STG + ((lane >> 4) * 8 + (lane & 7)) * OUT_PITCH + (wq * 16 + ((lane >> 3) & 1) * 8) * 2;
#pragma unroll
            for (int j = 0; j < 16; j += 2) {
                stsm4t(obase + j * 8 * OUT_PITCH, pack_bf(d[4 * j + 0], d[4 * j + 1]), pack_bf(d[4 * j + 2], d[4 * j + 3]),
                       pack_bf(d[4 * j + 4], d[4 * j + 5]), pack_bf(d[4 * j + 6], d[4 * j + 7]));
            }
            bar_sync(2, 128);
            const int oc0 = tid >> 3;
            __nv_bfloat16* dst = out + ((size_t)(b * C + oc0) * HW + r) * HW + seg * 8;
#pragma unroll
            for (int i = 0; i < 8; i++)
                *reinterpret_cast<uint4*>(dst + (size_t)i * 16 * HW * HW) = lds128(SM_STG + (oc0 + 16 * i) * OUT_PITCH + seg * 16);
            if (tid == 0) { TL(20); TLG(21); }
        }
    } else if (warp == 12) {
        bar_sync(0, 160);
        unsigned it = 0;
        while (ld_relaxed(&gs->wcnt[b * 32]) < (unsigned)NCTA && ++it < SPIN_LIMIT) {}
        fence_acquire();
        fence_async_global();
        if (lane == 0) TL(6);
        const unsigned char* wsrc = gs->wt;
#pragma unroll 1
        for (int round = 0; round < 2 * NSTAGE / NS; round++) {
            if (round == NSTAGE / NS) { mbar_wait(BAR(BAR_EMB), 0); fence_async_global(); }
            const uint32_t full = BAR(BAR_FULL) + 8 * NS * (round >= NSTAGE / NS ? round - NSTAGE / NS : round);
#pragma unroll
            for (int slot = 0; slot < NS; slot++) {
                mbar_wait(BAR(BAR_WEMPTY + slot), (round & 1) ^ 1);
                if (elect_one()) {
                    mbar_expect(full + 8 * slot, STAGE_BYTES);
                    bulk_g2s(SM_W + slot * STAGE_BYTES, wsrc + slot * STAGE_BYTES, STAGE_BYTES, full + 8 * slot);
                }
            }
            wsrc += NS * STAGE_BYTES;
            if (round == 0 && lane == 0) mbar_arrive(BAR(BAR_WACQ));
        }
    } else if (warp == 13) {
        const uint2 ga1 = __ldg(reinterpret_cast<const uint2*>(g1) + lane), bt1 = __ldg(reinterpret_cast<const uint2*>(be1) + lane);
        const uint2 ga2 = __ldg(reinterpret_cast<const uint2*>(g2) + lane), bt2 = __ldg(reinterpret_cast<const uint2*>(be2) + lane);
        bar_sync(0, 160);
#pragma unroll 1
        for (int conv = 0; conv < 2; conv++) {
            if (conv == 1) mbar_wait(BAR(BAR_HW), 0);
            const float* asrc = &gs->acc[(conv * NB + b) * 32 + (lane >> 3) * 4];
            uint4 f;
            unsigned it = 0;
            while (true) {
                f = ld_relaxed_v4(asrc);
                const bool ok = (f.x == 0x42800000u) & (f.w == 0x42800000u);
                if (__all_sync(0xffffffffu, ok) || ++it > SPIN_LIMIT) break;
            }
            if (lane == 0) TL(7 + conv * 8);
            const float inv_n = 1.0f / (32.0f * HW * HW);
            const float mean = __uint_as_float(f.y) * inv_n;
            const float var = fmaxf(fmaf(-mean, mean, __uint_as_float(f.z) * inv_n), 0.f);
            const float rs = 0.5f * rsqrtf(var + 1e-5f);
            const uint2 ga = conv ? ga2 : ga1, bt = conv ? bt2 : bt1;
            float4 k0, k1;
            k0.x = rs * bf_lo(ga.x); k0.y = rs * bf_hi(ga.x); k1.x = rs * bf_lo(ga.y); k1.y = rs * bf_hi(ga.y);
            k0.z = fmaf(-mean, k0.x, 0.5f * bf_lo(bt.x)); k0.w = fmaf(-mean, k0.y, 0.5f * bf_hi(bt.x));
            k1.z = fmaf(-mean, k1.x, 0.5f * bf_lo(bt.y)); k1.w = fmaf(-mean, k1.y, 0.5f * bf_hi(bt.y));
            sts128f(SM_COEF + lane * 32, k0);
            sts128f(SM_COEF + lane * 32 + 16, k1);
            __syncwarp();
            if (lane == 0) { mbar_arrive(BAR(BAR_STATS)); TL(25 + conv * 4); }
        }
        if (r == 0) {
            if (lane < 16) gs->acc[b * 32 + lane] = 0.f;
            if (lane < 2) gs->wcnt[(lane * NB + b) * 32] = 0;
        }
    } else {
        bar_sync(3, 384);
        {
            const char* w2s = reinterpret_cast<const char*>(w2) + woff;
#pragma unroll
            for (int k = 0; k < 4; k++) v[k] = __ldg(reinterpret_cast<const uint4*>(w2s + k * 256));
            if ((lane & 15) < 8) v[4] = __ldg(reinterpret_cast<const uint4*>(w2s + 1024));
            const uint2* wsrc = reinterpret_cast<const uint2*>(w_emb + (size_t)r * 12 * C) + lane;
            uint2 wv[12];
#pragma unroll
            for (int i = 0; i < 12; i++) wv[i] = __ldg(wsrc + i * (C / 4));
            float tv = 0.f;
            if (lane < 12) tv = __bfloat162float(t_emb[b * E + r * 12 + lane]);
            weight_block(v, SM_BNC + 2304, gs->wt + 72 * STEP_BYTES, cta, lane);
            const float sv = silu_half(0.5f * tv);
            float e0 = 0.f, e1 = 0.f, e2 = 0.f, e3 = 0.f;
#pragma unroll
            for (int i = 0; i < 12; i++) {
                const float sx = __shfl_sync(0xffffffffu, sv, i);
                e0 = fmaf(sx, bf_lo(wv[i].x), e0); e1 = fmaf(sx, bf_hi(wv[i].x), e1);
                e2 = fmaf(sx, bf_lo(wv[i].y), e2); e3 = fmaf(sx, bf_hi(wv[i].y), e3);
            }
            mbar_wait(BAR(BAR_WACQ), 0);
            red_add4(&gs->emb[b * C + lane * 4], e0, e1, e2, e3);
            __syncwarp();
            if (lane < 2) asm volatile("red.release.gpu.global.add.u32 [%0], 1;" ::"l"(&gs->wcnt[(NB + lane) * 32]) : "memory");
            unsigned it = 0;
            while (ld_relaxed(&gs->wcnt[(NB + b) * 32]) < (unsigned)NCTA && ++it < SPIN_LIMIT) __nanosleep(64);
            fence_acquire();
            sts128(SM_EMB + lane * 16, ld_relaxed_v4(&gs->emb[b * C + lane * 4]));
            __syncwarp();
            if (lane == 0) { mbar_arrive(BAR(BAR_EMB)); TL(19); }
        }
        mbar_wait(BAR(BAR_HW), 0);
        if (lane == 0) {
            asm volatile("st.release.gpu.global.u32 [%0], %1;" ::"l"(&gs->hflag[cta * 32]), "r"(1) : "memory");
            TL(13);
        }
        __syncwarp();
        if (lane < 2) {
            if (lane == 0 ? (r != 0) : (r != HW - 1)) {
                const int nb = cta - 1 + 2 * lane;
                unsigned it = 0;
                while (ld_relaxed(&gs->hflag[nb * 32]) == 0 && ++it < SPIN_LIMIT) {}
                fence_acquire();
                fence_async_global();
                mbar_expect(BAR(BAR_HALO) + 8 * lane, ROW_BYTES);
                bulk_g2s(SM_ACT + 2 * lane * ROW_BYTES, gs->h + (size_t)nb * ROW_BYTES, ROW_BYTES, BAR(BAR_HALO) + 8 * lane);
                if (lane == 0) TL(14);
            }
        }
    }
}

}

extern "C" void kernel_launch(void* const* d_in, const int* in_sizes, int n_in, void* d_out, int out_size) {
    (void)in_sizes; (void)n_in; (void)out_size;
    static Scratch* gs = nullptr;
    if (!gs) {
        cudaFuncSetAttribute(resblock_kernel, cudaFuncAttributeMaxDynamicSharedMemorySize, SM_TOTAL);
        cudaGetSymbolAddress((void**)&gs, g_scratch);
    }
    resblock_kernel<<<NCTA, NTHREADS, SM_TOTAL>>>(
        (const __nv_bfloat16*)d_in[0], (const __nv_bfloat16*)d_in[4], (const __nv_bfloat16*)d_in[1],
        (const __nv_bfloat16*)d_in[2], (const __nv_bfloat16*)d_in[3], (const __nv_bfloat16*)d_in[5],
        (const __nv_bfloat16*)d_in[6], (const __nv_bfloat16*)d_in[7], (const __nv_bfloat16*)d_in[8],
        (__nv_bfloat16*)d_out, gs);
}
```

```cpp
#include <cuda_runtime.h>
#include <cuda_bf16.h>
#include <stdint.h>

namespace {

constexpr int C = 128, HW = 64, NB = 2, E = 768;
constexpr int NCTA = NB * HW;
constexpr int NTHREADS = 18 * 32;
constexpr int CH_PITCH = 66 * 16;
constexpr int ROW_BYTES = 16 * CH_PITCH;
constexpr int ROW2_BYTES = 8 * CH_PITCH;
constexpr int STAGE_BYTES = 12288;
constexpr int NSEQ = 48;
constexpr int NS = 8;
#define XDELAY 250

constexpr uint32_t SMEM_BASE = 0x400;
constexpr uint32_t SM_ACT = SMEM_BASE;
constexpr uint32_t SM_ACT2 = SM_ACT + 3 * ROW_BYTES + 128;
constexpr uint32_t SM_STG = SM_ACT2 + 3 * ROW2_BYTES + 128;
constexpr uint32_t SM_W = SM_STG + 3 * 16384;
constexpr uint32_t SM_COEF = SM_W + NS * STAGE_BYTES;
constexpr uint32_t SM_EMB = SM_COEF + 1024;
constexpr uint32_t SM_RED = SM_EMB + 512;
constexpr uint32_t SM_BNC = SM_RED + 128;
constexpr uint32_t SM_BAR = SM_BNC + 2 * 2304;
constexpr int BAR_FULL = 0, BAR_WEMPTY = NSEQ, BAR_HW = BAR_WEMPTY + NS  , BAR_STATS = BAR_HW + 2  ,
              BAR_EMB = BAR_STATS + 3, BAR_WACQ = BAR_EMB + 1, BAR_XH = BAR_WACQ + 1, NBAR = BAR_XH + 1;
constexpr int SM_TOTAL = SM_BAR + NBAR * 8 - SMEM_BASE;
static_assert(SM_TOTAL <= 232448, "smem");
static_assert(NBAR <= 96, "barrier init");
constexpr int OUT_PITCH = 144;
__host__ __device__ constexpr uint32_t BAR(int i) { return SM_BAR + 8 * i; }

constexpr unsigned SPIN_LIMIT = 1u << 16;

__host__ __device__ constexpr int seq_of(int conv, int wg, int kyo, int g) {
    return conv == 0 ? wg * 12 + kyo * 4 + g
                     : 24 + (g < 2 ? wg * 6 + kyo * 2 + g : (kyo == 0 ? 12 + 2 * wg + (g & 1) : 16 + 4 * wg + (kyo - 1) * 2 + (g & 1)));
}
__host__ __device__ constexpr int ky_of(int kyo) { return kyo == 0 ? 1 : (kyo == 1 ? 0 : 2); }

struct Scratch {
    float acc[3 * NB * 32];
    unsigned wcnt[2 * NB * 32];
    float emb[NB * C];
    unsigned char wt[NSEQ * STAGE_BYTES];
    uint4 h[NCTA * 1024];
};
__device__ __align__(1024) Scratch g_scratch;
#define TL(i) do {} while (0)
#define TLG(i) do {} while (0)

__device__ __forceinline__ void mbar_init(uint32_t bar, int cnt) {
    asm volatile("mbarrier.init.shared::cta.b64 [%0], %1;" ::"r"(bar), "r"(cnt) : "memory");
}
__device__ __forceinline__ void mbar_arrive(uint32_t bar) {
    asm volatile("mbarrier.arrive.shared::cta.b64 _, [%0];" ::"r"(bar) : "memory");
}
__device__ __forceinline__ void mbar_expect(uint32_t bar, uint32_t bytes) {
    asm volatile("mbarrier.arrive.expect_tx.shared::cta.b64 _, [%0], %1;" ::"r"(bar), "r"(bytes) : "memory");
}
__device__ __forceinline__ bool mbar_try(uint32_t bar, uint32_t par) {
    uint32_t ok;
    asm volatile("{\n.reg .pred p;\nmbarrier.try_wait.parity.shared::cta.b64 p, [%1], %2;\nselp.u32 %0, 1, 0, p;\n}"
                 : "=r"(ok) : "r"(bar), "r"(par) : "memory");
    return ok;
}
__device__ __forceinline__ void mbar_wait(uint32_t bar, uint32_t par) {
    unsigned it = 0;
#pragma unroll 1
    while (!mbar_try(bar, par) && ++it < SPIN_LIMIT) {}
}
__device__ __forceinline__ bool elect_one() {
    uint32_t p;
    asm volatile("{\n.reg .pred p;\nelect.sync _|p, 0xffffffff;\nselp.u32 %0, 1, 0, p;\n}" : "=r"(p));
    return p;
}
__device__ __forceinline__ void fence_async_smem() { asm volatile("fence.proxy.async.shared::cta;" ::: "memory"); }
__device__ __forceinline__ void fence_async_global() { asm volatile("fence.proxy.async.global;" ::: "memory"); }
__device__ __forceinline__ void fence_acquire() { asm volatile("fence.acquire.gpu;" ::: "memory"); }
__device__ __forceinline__ void bar_sync(int id, int n) { asm volatile("bar.sync %0, %1;" ::"r"(id), "r"(n) : "memory"); }
__device__ __forceinline__ void bar_arrive(int id, int n) { asm volatile("bar.arrive %0, %1;" ::"r"(id), "r"(n) : "memory"); }
__device__ __forceinline__ void bulk_g2s(uint32_t dst, const void* src, uint32_t bytes, uint32_t bar) {
    asm volatile("cp.async.bulk.shared::cluster.global.mbarrier::complete_tx::bytes [%0], [%1], %2, [%3];"
                 ::"r"(dst), "l"(src), "r"(bytes), "r"(bar) : "memory");
}
__device__ __forceinline__ uint4 ld_relaxed_v4(const void* p) {
    uint4 v;
    asm volatile("ld.relaxed.gpu.global.v4.u32 {%0,%1,%2,%3}, [%4];" : "=r"(v.x), "=r"(v.y), "=r"(v.z), "=r"(v.w) : "l"(p) : "memory");
    return v;
}
__device__ __forceinline__ unsigned ld_relaxed(const void* p) {
    unsigned v;
    asm volatile("ld.relaxed.gpu.global.u32 %0, [%1];" : "=r"(v) : "l"(p) : "memory");
    return v;
}
__device__ __forceinline__ void red_add4(float* p, float a, float b, float c, float d) {
    asm volatile("red.relaxed.gpu.global.add.v4.f32 [%0], {%1,%2,%3,%4};" ::"l"(p), "f"(a), "f"(b), "f"(c), "f"(d) : "memory");
}
__device__ __forceinline__ void sts128(uint32_t a, uint4 v) {
    asm volatile("st.shared.v4.u32 [%0], {%1,%2,%3,%4};" ::"r"(a), "r"(v.x), "r"(v.y), "r"(v.z), "r"(v.w) : "memory");
}
__device__ __forceinline__ void sts128f(uint32_t a, float4 v) {
    asm volatile("st.shared.v4.f32 [%0], {%1,%2,%3,%4};" ::"r"(a), "f"(v.x), "f"(v.y), "f"(v.z), "f"(v.w) : "memory");
}
__device__ __forceinline__ void sts32f(uint32_t a, float v) { asm volatile("st.shared.f32 [%0], %1;" ::"r"(a), "f"(v) : "memory"); }
__device__ __forceinline__ uint4 lds128(uint32_t a) {
    uint4 v;
    asm volatile("ld.shared.v4.u32 {%0,%1,%2,%3}, [%4];" : "=r"(v.x), "=r"(v.y), "=r"(v.z), "=r"(v.w) : "r"(a) : "memory");
    return v;
}
__device__ __forceinline__ float4 lds128f(uint32_t a) {
    float4 v;
    asm volatile("ld.shared.v4.f32 {%0,%1,%2,%3}, [%4];" : "=f"(v.x), "=f"(v.y), "=f"(v.z), "=f"(v.w) : "r"(a) : "memory");
    return v;
}
__device__ __forceinline__ float2 lds64f(uint32_t a) {
    float2 v;
    asm volatile("ld.shared.v2.f32 {%0,%1}, [%2];" : "=f"(v.x), "=f"(v.y) : "r"(a) : "memory");
    return v;
}
__device__ __forceinline__ float bf_lo(uint32_t u) { return __uint_as_float(u << 16); }
__device__ __forceinline__ float bf_hi(uint32_t u) { return __uint_as_float(u & 0xffff0000u); }
__device__ __forceinline__ uint32_t pack_bf(float lo, float hi) {
    uint32_t r;
    asm("cvt.rn.bf16x2.f32 %0, %1, %2;" : "=r"(r) : "f"(hi), "f"(lo));
    return r;
}
__device__ __forceinline__ float tanh_fast(float x) {
    float r;
    asm("tanh.approx.f32 %0, %1;" : "=f"(r) : "f"(x));
    return r;
}
__device__ __forceinline__ float silu_half(float h) { return fmaf(h, tanh_fast(h), h); }
__device__ __forceinline__ void ldsm4(uint32_t (&u)[4], uint32_t a) {
    asm volatile("ldmatrix.sync.aligned.m8n8.x4.shared.b16 {%0,%1,%2,%3}, [%4];"
                 : "=r"(u[0]), "=r"(u[1]), "=r"(u[2]), "=r"(u[3]) : "r"(a) : "memory");
}
__device__ __forceinline__ void ldsm4t(uint32_t (&u)[4], uint32_t a) {
    asm volatile("ldmatrix.sync.aligned.m8n8.x4.trans.shared.b16 {%0,%1,%2,%3}, [%4];"
                 : "=r"(u[0]), "=r"(u[1]), "=r"(u[2]), "=r"(u[3]) : "r"(a) : "memory");
}
__device__ __forceinline__ void stsm4(uint32_t a, uint32_t p0, uint32_t p1, uint32_t p2, uint32_t p3) {
    asm volatile("stmatrix.sync.aligned.m8n8.x4.shared.b16 [%0], {%1,%2,%3,%4};" ::"r"(a), "r"(p0), "r"(p1), "r"(p2), "r"(p3) : "memory");
}
__device__ __forceinline__ void stsm4t(uint32_t a, uint32_t p0, uint32_t p1, uint32_t p2, uint32_t p3) {
    asm volatile("stmatrix.sync.aligned.m8n8.x4.trans.shared.b16 [%0], {%1,%2,%3,%4};" ::"r"(a), "r"(p0), "r"(p1), "r"(p2), "r"(p3) : "memory");
}

#define R8(o) "+f"(d[o]), "+f"(d[o + 1]), "+f"(d[o + 2]), "+f"(d[o + 3]), "+f"(d[o + 4]), "+f"(d[o + 5]), "+f"(d[o + 6]), "+f"(d[o + 7])
template <uint32_t ALO, uint32_t BLO>
__device__ __forceinline__ void wgmma64(float (&d)[32]) {
    asm volatile(
        "wgmma.mma_async.sync.aligned.m64n64k16.f32.bf16.bf16 "
        "{%0,%1,%2,%3,%4,%5,%6,%7,%8,%9,%10,%11,%12,%13,%14,%15,%16,%17,%18,%19,%20,%21,%22,%23,%24,%25,%26,%27,%28,%29,%30,%31},"
        " %32, %33, 1, 1, 1, 0, 0;"
        : R8(0), R8(8), R8(16), R8(24)
        : "l"((8ull << 32) | ALO), "l"((8ull << 32) | BLO));
}
__host__ __device__ constexpr int st_kyo(int conv, int i) { return conv == 0 ? i / 4 : (i % 6) / 2; }
__host__ __device__ constexpr int st_g(int conv, int i) { return conv == 0 ? i % 4 : (i / 6) * 2 + (i & 1); }

template <int CONV, int WG, int I>
__device__ __forceinline__ void mma_stages(float (&d)[32], int tid, Scratch* gs) {
    constexpr int kyo = st_kyo(CONV, I), g = st_g(CONV, I), seq = seq_of(CONV, WG, kyo, g);
    constexpr uint32_t abase = (CONV == 1 && g < 2) ? SM_ACT2 + ky_of(kyo) * ROW2_BYTES : SM_ACT + ky_of(kyo) * ROW_BYTES;
    constexpr uint32_t A = ((abase + g * 4 * CH_PITCH + 16) >> 4) | ((CH_PITCH >> 4) << 16);
    constexpr uint32_t A2 = A + ((2 * CH_PITCH) >> 4);
    constexpr uint32_t B = ((SM_W + (seq % NS) * STAGE_BYTES) >> 4) | ((1024 >> 4) << 16);
    mbar_wait(BAR(BAR_FULL + seq), 0);
    if (I == 0 && (tid & 127) == 0) TL(32 + seq);
    asm volatile("wgmma.fence.sync.aligned;" ::: "memory");
    wgmma64<A, B>(d);
    wgmma64<A + 1, B + 128>(d);
    wgmma64<A + 2, B + 256>(d);
    wgmma64<A2, B + 384>(d);
    wgmma64<A2 + 1, B + 512>(d);
    wgmma64<A2 + 2, B + 640>(d);
    asm volatile("wgmma.commit_group.sync.aligned;" ::: "memory");
    if constexpr (I > 0) {
        constexpr int pseq = seq_of(CONV, WG, st_kyo(CONV, I - 1), st_g(CONV, I - 1));
        if (pseq + 1 == seq) {
            asm volatile("wgmma.wait_group.sync.aligned 1;" ::: "memory");
            if (pseq + NS < NSEQ && (tid & 31) == 0) mbar_arrive(BAR(BAR_WEMPTY + pseq % NS));
        }
    }
    constexpr bool last = (I == 11);
    constexpr int nseq = last ? -1 : seq_of(CONV, WG, st_kyo(CONV, I + 1), st_g(CONV, I + 1));
    if (nseq != seq + 1) {
        asm volatile("wgmma.wait_group.sync.aligned 0;" ::: "memory");
        if (seq + NS < NSEQ && (tid & 31) == 0) mbar_arrive(BAR(BAR_WEMPTY + seq % NS));
    }
    if constexpr (!last) mma_stages<CONV, WG, I + 1>(d, tid, gs);
}

template <int CONV>
__device__ __forceinline__ void weight_block(const uint4 (&t)[5], uint32_t bounce, unsigned char* wt, int cta, int lane) {
    const uint32_t bw = bounce + (lane >> 4) * 1152 + (lane & 15) * 16;
#pragma unroll
    for (int k = 0; k < 4; k++) sts128(bw + k * 256, t[k]);
    if ((lane & 15) < 8) sts128(bw + 1024, t[4]);
    __syncwarp();
    if (lane < 16) {
        uint32_t v[36];
#pragma unroll
        for (int i = 0; i < 9; i++) {
            const uint4 q = lds128(bounce + (lane & 1) * 1152 + (lane >> 1) * 144 + i * 16);
            v[4 * i] = q.x; v[4 * i + 1] = q.y; v[4 * i + 2] = q.z; v[4 * i + 3] = q.w;
        }
        const int cc = (cta >> 6) * 8 + (lane >> 1);
        const int oc = (cta & 63) * 2 + (lane & 1);
        unsigned char* dst = wt + ((cc >> 1) & 1) * 6144 + (cc & 1) * 1024 + (oc & 63) * 16;
#pragma unroll
        for (int kyo = 0; kyo < 3; kyo++) {
            unsigned char* d2 = dst + seq_of(CONV, oc >> 6, kyo, cc >> 2) * STAGE_BYTES;
#pragma unroll
            for (int kx = 0; kx < 3; kx++) {
                const int tap = ky_of(kyo) * 3 + kx;
                uint32_t o[4];
#pragma unroll
                for (int m = 0; m < 4; m++) {
                    const int i0 = 18 * m + tap, i1 = i0 + 9;
                    const uint32_t sel = ((i0 & 1) ? 0x32u : 0x10u) | ((i1 & 1) ? 0x7600u : 0x5400u);
                    o[m] = __byte_perm(v[i0 >> 1], v[i1 >> 1], sel);
                }
                *reinterpret_cast<uint4*>(d2 + kx * 2048) = make_uint4(o[0], o[1], o[2], o[3]);
            }
        }
    }
}
__device__ __forceinline__ uint32_t act2(uint32_t u, const float4& cf) {
    return pack_bf(silu_half(fmaf(bf_lo(u), cf.x, cf.z)), silu_half(fmaf(bf_hi(u), cf.y, cf.w)));
}
template <int FIRST, int N>
__device__ __forceinline__ void norm1_batch(uint32_t (&u)[4][4], const float4 (&cf)[4], uint32_t act, int kyo, int lane, bool valid) {
    if (valid) {
#pragma unroll
        for (int t = FIRST; t < FIRST + N; t++)
            stsm4(act + t * 4 * CH_PITCH, act2(u[t][0], cf[t]), act2(u[t][1], cf[t]), act2(u[t][2], cf[t]), act2(u[t][3], cf[t]));
        fence_async_smem();
    }
    __syncwarp();
    if (lane < 2 * N) mbar_arrive(BAR(BAR_FULL) + 8 * ((lane & 1) * 12 + kyo * 4 + FIRST + (lane >> 1)));
}
__device__ __forceinline__ void fence_acc(float (&d)[32]) {
#pragma unroll
    for (int i = 0; i < 32; i++) asm volatile("" : "+f"(d[i])::"memory");
}

__global__ void __launch_bounds__(NTHREADS, 1)
resblock_kernel(const __nv_bfloat16* __restrict__ x, const __nv_bfloat16* __restrict__ w1,
                const __nv_bfloat16* __restrict__ t_emb, const __nv_bfloat16* __restrict__ g1,
                const __nv_bfloat16* __restrict__ be1, const __nv_bfloat16* __restrict__ w_emb,
                const __nv_bfloat16* __restrict__ g2, const __nv_bfloat16* __restrict__ be2,
                const __nv_bfloat16* __restrict__ w2, __nv_bfloat16* __restrict__ out, Scratch* __restrict__ gs) {
    const unsigned clk0 = clock();
    const int tid = threadIdx.x, warp = tid >> 5, lane = tid & 31;
    const int cta = blockIdx.x, b = cta >> 6, r = cta & 63;

    const uint32_t woff = ((2 * r + (lane >> 4)) * C + b * 64) * 18 + (lane & 15) * 16;
    const int c0 = (warp - 8) * 16 + (lane >> 3), seg = lane & 7;
    const char* src = (warp == 0) ? reinterpret_cast<const char*>(w1) + woff
                                  : reinterpret_cast<const char*>(x) + (uint32_t)(((b * C + c0) * HW + r) * HW * 2 + seg * 16);
    uint4 v[5];
    if (warp == 0 || (warp >= 8 && warp < 16)) {
        const uint32_t stride = (warp == 0) ? 256 : 4 * HW * HW * 2;
        if (warp != 0) { while (clock() - clk0 < XDELAY) {} }
#pragma unroll
        for (int k = 0; k < 4; k++) v[k] = __ldg(reinterpret_cast<const uint4*>(src + k * stride));
        if (tid < 32 && (lane & 15) < 8) v[4] = __ldg(reinterpret_cast<const uint4*>(src + 1024));
    }
    if (warp == 0) {
        weight_block<0>(v, SM_BNC, gs->wt, cta, lane);
        if (r == 0) {
            if (lane < 16) gs->acc[((1 + (lane >> 3)) * NB + b) * 32 + (lane & 7)] = 0.f;
            *reinterpret_cast<float4*>(&gs->emb[b * C + lane * 4]) = make_float4(0.f, 0.f, 0.f, 0.f);
        }
        __syncwarp();
        if (lane == 0) TL(4);
        if (lane < 2) asm volatile("red.release.gpu.global.add.u32 [%0], 1;" ::"l"(&gs->wcnt[lane * 32]) : "memory");
        if (lane == 0) TL(5);
    }

    if (warp >= 8 && warp < 16) {
        const int nw = warp - 8;
        {
            float s = 0.f, q = 0.f, s2 = 0.f, q2 = 0.f;
#pragma unroll
            for (int i = 0; i < 4; i++) {
                const uint32_t u[4] = {v[i].x, v[i].y, v[i].z, v[i].w};
#pragma unroll
                for (int k = 0; k < 4; k++) {
                    const float lo = bf_lo(u[k]), hi = bf_hi(u[k]);
                    s += lo; q = fmaf(lo, lo, q);
                    s2 += hi; q2 = fmaf(hi, hi, q2);
                }
            }
            s += s2; q += q2;
            float give = (lane < 16) ? q : s, keep = (lane < 16) ? s : q;
            keep += __shfl_xor_sync(0xffffffffu, give, 16);
            if (tid == 256) TL(2);
#pragma unroll
            for (int m = 8; m >= 1; m >>= 1) keep += __shfl_xor_sync(0xffffffffu, keep, m);
            if ((lane & 15) == 0) sts32f(SM_RED + (nw * 2 + (lane >> 4)) * 4, keep);
            bar_sync(3, 256 + 96 + 128);
            if (tid < 256 + 4) {
                const float4 p = lds128f(SM_RED + lane * 16);
                red_add4(&gs->acc[b * 32 + lane * 4], 1.f, p.x + p.z, p.y + p.w, 1.f);
            }
            if (tid == 256) TL(3);
#pragma unroll
            for (int i = 0; i < 4; i++) sts128(SM_STG + 16384 + c0 * 128 + i * 512 + ((seg ^ ((c0 + 4 * i) & 7)) << 4), v[i]);
            bar_sync(4, 256);
        }
        uint32_t u[4][4];
        float4 cf[4];
        {
            const int ch0 = nw >> 1, half = nw & 1;
            const uint32_t act_off = SM_ACT + ch0 * CH_PITCH + (2 + half * 32 + lane) * 16;
            const uint32_t stg_off = SM_STG + (ch0 * 8 + (lane & 7)) * 128 + (((half * 4 + (lane >> 3)) ^ (lane & 7)) << 4);
#pragma unroll
            for (int i = 0; i < 4; i++) ldsm4t(u[i], stg_off + 16384 + i * 4096);
            mbar_wait(BAR(BAR_STATS), 0);
            if (tid == 256) TL(22);
#pragma unroll
            for (int i = 0; i < 4; i++) cf[i] = lds128f(SM_COEF + ch0 * 64 + (lane & 3) * 16 + i * 256);
            norm1_batch<0, 1>(u, cf, act_off + ROW_BYTES, 0, lane, true);
            if (tid == 256) TL(8);
            norm1_batch<1, 1>(u, cf, act_off + ROW_BYTES, 0, lane, true);
            norm1_batch<2, 2>(u, cf, act_off + ROW_BYTES, 0, lane, true);
            if (tid == 256) TL(24);
            mbar_wait(BAR(BAR_XH), 0);
#pragma unroll 1
            for (int o = 0; o < 2; o++) {
                const bool valid = (o == 0) ? (r != 0) : (r != HW - 1);
#pragma unroll
                for (int i = 0; i < 4; i++) ldsm4t(u[i], stg_off + o * 2 * 16384 + i * 4096);
                norm1_batch<0, 2>(u, cf, act_off + o * 2 * ROW_BYTES, 1 + o, lane, valid);
                norm1_batch<2, 2>(u, cf, act_off + o * 2 * ROW_BYTES, 1 + o, lane, valid);
            }
            if (tid == 256) TL(23);
        }
        const int pair = nw >> 2, wq = nw & 3;
        const uint32_t unit_off = (pair * 2 + (lane >> 4)) * CH_PITCH + (2 + wq * 16 + (lane & 15)) * 16;
        const bool up = (r != 0), down = (r != HW - 1);
#pragma unroll 1
        for (int kh = 0; kh < 2; kh++) {
            const uint32_t abase = (kh ? SM_ACT + 8 * CH_PITCH : SM_ACT2) + unit_off;
            const uint32_t rowb = kh ? ROW_BYTES : ROW2_BYTES;
            mbar_wait(BAR(BAR_HW) + 8 * kh, 0);
            uint32_t o0[4], o1[4];
            ldsm4(o0, abase + rowb);
            ldsm4(o1, abase + rowb + 4 * CH_PITCH);
            const uint4* hup = gs->h + (size_t)(up ? cta - 1 : cta) * 1024 + kh * 512 + nw * 32 + lane;
            const uint4* hdn = gs->h + (size_t)(down ? cta + 1 : cta) * 1024 + kh * 512 + nw * 32 + lane;
            mbar_wait(BAR(BAR_STATS + 1) + 8 * kh, 0);
            if (tid == 256) TL(26 + kh * 2);
            uint4 hv[4];
            hv[0] = ld_relaxed_v4(hup); hv[1] = ld_relaxed_v4(hup + 256);
            hv[2] = ld_relaxed_v4(hdn); hv[3] = ld_relaxed_v4(hdn + 256);
#pragma unroll
            for (int i = 0; i < 4; i++) cf[i] = lds128f(SM_COEF + (kh * 8 + (i >> 1) * 4 + pair * 2 + (i & 1)) * 64 + (lane & 3) * 16);
            stsm4(abase + rowb, act2(o0[0], cf[0]), act2(o0[1], cf[0]), act2(o0[2], cf[1]), act2(o0[3], cf[1]));
            stsm4(abase + rowb + 4 * CH_PITCH, act2(o1[0], cf[2]), act2(o1[1], cf[2]), act2(o1[2], cf[3]), act2(o1[3], cf[3]));
            fence_async_smem();
            __syncwarp();
            if (lane < 4) mbar_arrive(BAR(BAR_FULL) + 8 * seq_of(1, lane >> 1, 0, kh * 2 + (lane & 1)));
            unsigned it = 0;
            while (true) {
                bool ok = true;
#pragma unroll
                for (int i = 0; i < 4; i++)
                    ok = ok && hv[i].x != 0xffffffffu && hv[i].y != 0xffffffffu && hv[i].z != 0xffffffffu && hv[i].w != 0xffffffffu;
                if (__all_sync(0xffffffffu, ok) || ++it > SPIN_LIMIT) break;
                hv[0] = ld_relaxed_v4(hup); hv[1] = ld_relaxed_v4(hup + 256);
                hv[2] = ld_relaxed_v4(hdn); hv[3] = ld_relaxed_v4(hdn + 256);
            }
#pragma unroll
            for (int o = 0; o < 2; o++) {
                if (o == 0 ? up : down) {
                    const uint4 a = hv[2 * o], c = hv[2 * o + 1];
                    stsm4(abase + 2 * o * rowb, act2(a.x, cf[0]), act2(a.y, cf[0]), act2(a.z, cf[1]), act2(a.w, cf[1]));
                    stsm4(abase + 2 * o * rowb + 4 * CH_PITCH, act2(c.x, cf[2]), act2(c.y, cf[2]), act2(c.z, cf[3]), act2(c.w, cf[3]));
                    fence_async_smem();
                }
                __syncwarp();
                if (lane < 4) mbar_arrive(BAR(BAR_FULL) + 8 * seq_of(1, lane >> 1, 1 + o, kh * 2 + (lane & 1)));
            }
            if (tid == 256) TL(27 + kh * 2);
        }
    } else if (warp < 8) {
        const int wg = warp >> 2, wq = warp & 3;
        if (wg == 0) {
            if (wq != 0) {
                const int t = tid - 32;
                if (t < NBAR) {
                    const int cnt = t < BAR_WEMPTY ? 9 : (t < BAR_STATS ? 4 : (t == BAR_XH ? 96 : 1));
                    mbar_init(BAR(0) + 8 * t, cnt);
                }
                fence_async_smem();
                bar_arrive(0, 160);
                bar_arrive(3, 256 + 96 + 128);
                const uint4 z = make_uint4(0, 0, 0, 0);
                sts128(SM_ACT + (t >> 1) * CH_PITCH + (t & 1) * 16, z);
                if (t < 50) sts128(SM_ACT2 + (t >> 1) * CH_PITCH + (t & 1) * 16, z);
                if (t < 2) sts128(SM_ACT + 3 * ROW_BYTES + t * 16, z);
                if (r == 0 || r == HW - 1) {
                    for (int i = t; i < ROW_BYTES / 16; i += 96) sts128(SM_ACT + (r == 0 ? 0 : 2 * ROW_BYTES) + i * 16, z);
                    for (int i = t; i < ROW2_BYTES / 16; i += 96) sts128(SM_ACT2 + (r == 0 ? 0 : 2 * ROW2_BYTES) + i * 16, z);
                }
                fence_async_smem();
            }
            bar_sync(1, 128);
            bar_arrive(5, 256);
        } else {
            bar_sync(3, 256 + 96 + 128);
            if (wq != 0) {
                const char* xs = reinterpret_cast<const char*>(x) + (uint32_t)((b * C * HW + r) * HW * 2);
                for (int i = tid - 160; i < 2048; i += 96) {
                    const int hrow = i >> 10, c = (i >> 3) & 127, sg = i & 7;
                    if (hrow == 0 ? (r != 0) : (r != HW - 1))
                        asm volatile("cp.async.cg.shared.global [%0], [%1], 16;"
                                     ::"r"(SM_STG + hrow * 2 * 16384 + c * 128 + ((sg ^ (c & 7)) << 4)),
                                       "l"(xs + c * (HW * HW * 2) + (2 * hrow - 1) * (HW * 2) + sg * 16) : "memory");
                }
                asm volatile("cp.async.mbarrier.arrive.noinc.shared::cta.b64 [%0];" ::"r"(BAR(BAR_XH)) : "memory");
                for (int i = tid - 160; i < 1024; i += 96) gs->h[cta * 1024 + i] = make_uint4(~0u, ~0u, ~0u, ~0u);
                bar_arrive(6, 128);
            } else {
                const char* w2s = reinterpret_cast<const char*>(w2) + woff;
#pragma unroll
                for (int k = 0; k < 4; k++) v[k] = __ldg(reinterpret_cast<const uint4*>(w2s + k * 256));
                if ((lane & 15) < 8) v[4] = __ldg(reinterpret_cast<const uint4*>(w2s + 1024));
                const uint2* wsrc = reinterpret_cast<const uint2*>(w_emb + (size_t)r * 12 * C) + lane;
                uint2 wv[12];
#pragma unroll
                for (int i = 0; i < 12; i++) wv[i] = __ldg(wsrc + i * (C / 4));
                float tv = 0.f;
                if (lane < 12) tv = __bfloat162float(t_emb[b * E + r * 12 + lane]);
                weight_block<1>(v, SM_BNC + 2304, gs->wt, cta, lane);
                const float sv = silu_half(0.5f * tv);
                float e0 = 0.f, e1 = 0.f, e2 = 0.f, e3 = 0.f;
#pragma unroll
                for (int i = 0; i < 12; i++) {
                    const float sx = __shfl_sync(0xffffffffu, sv, i);
                    e0 = fmaf(sx, bf_lo(wv[i].x), e0); e1 = fmaf(sx, bf_hi(wv[i].x), e1);
                    e2 = fmaf(sx, bf_lo(wv[i].y), e2); e3 = fmaf(sx, bf_hi(wv[i].y), e3);
                }
                mbar_wait(BAR(BAR_WACQ), 0);
                red_add4(&gs->emb[b * C + lane * 4], e0, e1, e2, e3);
                bar_sync(6, 128);
                if (lane < 2) asm volatile("red.release.gpu.global.add.u32 [%0], 1;" ::"l"(&gs->wcnt[(NB + lane) * 32]) : "memory");
                unsigned it = 0;
                while (ld_relaxed(&gs->wcnt[(NB + b) * 32]) < (unsigned)NCTA && ++it < SPIN_LIMIT) __nanosleep(64);
                fence_acquire();
                sts128(SM_EMB + lane * 16, ld_relaxed_v4(&gs->emb[b * C + lane * 4]));
                __syncwarp();
                if (lane == 0) { mbar_arrive(BAR(BAR_EMB)); TL(19); }
            }
            bar_sync(5, 256);
        }

        float d[32];
#pragma unroll
        for (int i = 0; i < 32; i++) d[i] = 0.f;
        fence_acc(d);
        if (wg == 0) mma_stages<0, 0, 0>(d, tid, gs); else mma_stages<0, 1, 0>(d, tid, gs);
        fence_acc(d);
        if ((tid & 127) == 0) TL(10 + wg * 4);
        {
            mbar_wait(BAR(BAR_EMB), 0);
            float st[4];
#pragma unroll
            for (int g = 0; g < 2; g++) {
                float s = 0.f, q = 0.f, s2 = 0.f, q2 = 0.f;
#pragma unroll
                for (int jj = 0; jj < 4; jj++) {
                    const int j = g * 4 + jj;
                    const float2 e = lds64f(SM_EMB + wg * 256 + j * 32 + (lane & 3) * 8);
                    d[4 * j + 0] += e.x; d[4 * j + 1] += e.y; d[4 * j + 2] += e.x; d[4 * j + 3] += e.y;
                    s += d[4 * j + 0]; q = fmaf(d[4 * j + 0], d[4 * j + 0], q);
                    s2 += d[4 * j + 1]; q2 = fmaf(d[4 * j + 1], d[4 * j + 1], q2);
                    s += d[4 * j + 2]; q = fmaf(d[4 * j + 2], d[4 * j + 2], q);
                    s2 += d[4 * j + 3]; q2 = fmaf(d[4 * j + 3], d[4 * j + 3], q2);
                }
                st[2 * g] = s + s2; st[2 * g + 1] = q + q2;
            }
            {
                const bool h16 = lane & 16, h8 = lane & 8;
                float a[2];
#pragma unroll
                for (int i = 0; i < 2; i++) {
                    float give = h16 ? st[i] : st[i + 2], keep = h16 ? st[i + 2] : st[i];
                    a[i] = keep + __shfl_xor_sync(0xffffffffu, give, 16);
                }
                float give = h8 ? a[0] : a[1], keep = h8 ? a[1] : a[0];
                float t = keep + __shfl_xor_sync(0xffffffffu, give, 8);
                t += __shfl_xor_sync(0xffffffffu, t, 4);
                t += __shfl_xor_sync(0xffffffffu, t, 2);
                t += __shfl_xor_sync(0xffffffffu, t, 1);
                if ((lane & 7) == 0) sts32f(SM_RED + wg * 64 + ((lane >> 3) * 4 + wq) * 4, t);
                bar_sync(1 + wg, 128);
                if (wq == 0 && lane < 2) {
                    const float4 p = lds128f(SM_RED + wg * 64 + lane * 32), p2 = lds128f(SM_RED + wg * 64 + lane * 32 + 16);
                    red_add4(&gs->acc[((1 + wg) * NB + b) * 32 + lane * 4], 1.f, (p.x + p.y) + (p.z + p.w), (p2.x + p2.y) + (p2.z + p2.w), 1.f);
                }
                if ((tid & 127) == 0) TL(11 + wg * 4);
            }
            const uint32_t hbase = (wg ? SM_ACT + ROW_BYTES + 8 * CH_PITCH : SM_ACT2 + ROW2_BYTES) + (lane >> 4) * CH_PITCH + (2 + wq * 16 + (lane & 15)) * 16;
            uint4* hg = gs->h + cta * 1024 + wg * 512 + wq * 32 + lane;
#pragma unroll
            for (int jj = 0; jj < 4; jj++) {
                const uint4 p = make_uint4(pack_bf(d[8 * jj + 0], d[8 * jj + 1]), pack_bf(d[8 * jj + 2], d[8 * jj + 3]),
                                           pack_bf(d[8 * jj + 4], d[8 * jj + 5]), pack_bf(d[8 * jj + 6], d[8 * jj + 7]));
                hg[jj * 128] = p;
                stsm4(hbase + jj * 2 * CH_PITCH, p.x, p.y, p.z, p.w);
            }
            __syncwarp();
            if (lane == 0) mbar_arrive(BAR(BAR_HW) + 8 * wg);
            if ((tid & 127) == 0) TL(12 + wg * 4);
            const uint32_t xbase = SM_STG + 16384 + (wg * 64 + (lane >> 4) * 8 + (lane & 7)) * 128 + (((2 * wq + ((lane >> 3) & 1)) ^ (lane & 7)) << 4);
#pragma unroll
            for (int jj = 0; jj < 4; jj++) {
                uint32_t p[4];
                ldsm4t(p, xbase + jj * 2048);
#pragma unroll
                for (int i = 0; i < 4; i++) { d[8 * jj + 2 * i] = bf_lo(p[i]); d[8 * jj + 2 * i + 1] = bf_hi(p[i]); }
            }
        }
        fence_acc(d);
        if (wg == 0) mma_stages<1, 0, 0>(d, tid, gs); else mma_stages<1, 1, 0>(d, tid, gs);
        fence_acc(d);
        if ((tid & 127) == 0) TL(13 + wg * 4);
        {
            const uint32_t ostg = SM_STG + wg * 2 * 16384;
            const uint32_t obase = ostg + ((lane >> 4) * 8 + (lane & 7)) * OUT_PITCH + (wq * 16 + ((lane >> 3) & 1) * 8) * 2;
#pragma unroll
            for (int jj = 0; jj < 4; jj++) {
                stsm4t(obase + jj * 16 * OUT_PITCH, pack_bf(d[8 * jj + 0], d[8 * jj + 1]), pack_bf(d[8 * jj + 2], d[8 * jj + 3]),
                       pack_bf(d[8 * jj + 4], d[8 * jj + 5]), pack_bf(d[8 * jj + 6], d[8 * jj + 7]));
            }
            bar_sync(1 + wg, 128);
            const int oc0 = (tid & 127) >> 3;
            __nv_bfloat16* dst = out + ((size_t)(b * C + wg * 64 + oc0) * HW + r) * HW + seg * 8;
#pragma unroll
            for (int i = 0; i < 4; i++)
                *reinterpret_cast<uint4*>(dst + (size_t)i * 16 * HW * HW) = lds128(ostg + (oc0 + 16 * i) * OUT_PITCH + seg * 16);
            if (tid == 128) { TL(20); TLG(21); }
        }
    } else if (warp == 16) {
        bar_sync(0, 160);
        unsigned it = 0;
        while (ld_relaxed(&gs->wcnt[b * 32]) < (unsigned)NCTA && ++it < SPIN_LIMIT) {}
        fence_acquire();
        fence_async_global();
        if (lane == 0) TL(6);
        const unsigned char* wsrc = gs->wt;
#pragma unroll 1
        for (int round = 0; round < NSEQ / NS; round++) {
            if (round == NSEQ / NS / 2) { mbar_wait(BAR(BAR_EMB), 0); fence_async_global(); }
            const uint32_t full = BAR(BAR_FULL) + 8 * NS * round;
#pragma unroll
            for (int slot = 0; slot < NS; slot++) {
                mbar_wait(BAR(BAR_WEMPTY + slot), (round & 1) ^ 1);
                if (elect_one()) {
                    mbar_expect(full + 8 * slot, STAGE_BYTES);
                    bulk_g2s(SM_W + slot * STAGE_BYTES, wsrc + slot * STAGE_BYTES, STAGE_BYTES, full + 8 * slot);
                }
            }
            wsrc += NS * STAGE_BYTES;
            if (round == 0 && lane == 0) mbar_arrive(BAR(BAR_WACQ));
        }
    } else {
        const uint2 ga1 = __ldg(reinterpret_cast<const uint2*>(g1) + lane), bt1 = __ldg(reinterpret_cast<const uint2*>(be1) + lane);
        const uint2 ga2 = __ldg(reinterpret_cast<const uint2*>(g2) + lane), bt2 = __ldg(reinterpret_cast<const uint2*>(be2) + lane);
        bar_sync(0, 160);
#pragma unroll 1
        for (int ph = 0; ph < 3; ph++) {
            if (ph > 0) mbar_wait(BAR(BAR_HW) + 8 * (ph - 1), 0);
            const float* asrc = &gs->acc[(ph * NB + b) * 32 + ((lane >> 3) & (ph ? 1 : 3)) * 4];
            uint4 f;
            unsigned it = 0;
            while (true) {
                f = ld_relaxed_v4(asrc);
                const bool ok = (f.x == 0x42800000u) & (f.w == 0x42800000u);
                if (__all_sync(0xffffffffu, ok) || ++it > SPIN_LIMIT) break;
            }
            if (lane == 0) TL(ph == 0 ? 7 : 29 + ph);
            const float inv_n = 1.0f / (32.0f * HW * HW);
            const float mean = __uint_as_float(f.y) * inv_n;
            const float var = fmaxf(fmaf(-mean, mean, __uint_as_float(f.z) * inv_n), 0.f);
            const float rs = 0.5f * rsqrtf(var + 1e-5f);
            const uint2 ga = ph ? ga2 : ga1, bt = ph ? bt2 : bt1;
            float4 k0, k1;
            k0.x = rs * bf_lo(ga.x); k0.y = rs * bf_hi(ga.x); k1.x = rs * bf_lo(ga.y); k1.y = rs * bf_hi(ga.y);
            k0.z = fmaf(-mean, k0.x, 0.5f * bf_lo(bt.x)); k0.w = fmaf(-mean, k0.y, 0.5f * bf_hi(bt.x));
            k1.z = fmaf(-mean, k1.x, 0.5f * bf_lo(bt.y)); k1.w = fmaf(-mean, k1.y, 0.5f * bf_hi(bt.y));
            if (ph == 0 || (lane >> 4) == ph - 1) {
                sts128f(SM_COEF + lane * 32, k0);
                sts128f(SM_COEF + lane * 32 + 16, k1);
            }
            __syncwarp();
            if (lane == 0) mbar_arrive(BAR(BAR_STATS) + 8 * ph);
        }
        if (r == 0) {
            if (lane < 16) gs->acc[b * 32 + lane] = 0.f;
            if (lane < 2) gs->wcnt[(lane * NB + b) * 32] = 0;
        }
    }
}

}

extern "C" void kernel_launch(void* const* d_in, const int* in_sizes, int n_in, void* d_out, int out_size) {
    (void)in_sizes; (void)n_in; (void)out_size;
    static Scratch* gs = nullptr;
    if (!gs) {
        cudaFuncSetAttribute(resblock_kernel, cudaFuncAttributeMaxDynamicSharedMemorySize, SM_TOTAL);
        cudaGetSymbolAddress((void**)&gs, g_scratch);
    }
    resblock_kernel<<<NCTA, NTHREADS, SM_TOTAL>>>(
        (const __nv_bfloat16*)d_in[0], (const __nv_bfloat16*)d_in[4], (const __nv_bfloat16*)d_in[1],
        (const __nv_bfloat16*)d_in[2], (const __nv_bfloat16*)d_in[3], (const __nv_bfloat16*)d_in[5],
        (const __nv_bfloat16*)d_in[6], (const __nv_bfloat16*)d_in[7], (const __nv_bfloat16*)d_in[8],
        (__nv_bfloat16*)d_out, gs);
}
```

```cpp
#include <cuda_runtime.h>
#include <cuda_bf16.h>
#include <stdint.h>

namespace {

constexpr int C = 128, HW = 64, NB = 2, E = 768;
constexpr int NCTA = NB * HW;
constexpr int NTHREADS = 16 * 32;
constexpr int CH_PITCH = 66 * 16;
constexpr int ROW_BYTES = 16 * CH_PITCH;
constexpr int STEP_BYTES = 4096;
constexpr int STAGE_BYTES = 3 * STEP_BYTES;
constexpr int NSTAGE = 24;
constexpr int NS = 8;
#define XDELAY 600

constexpr uint32_t SMEM_BASE = 0x400;
constexpr uint32_t SM_ACT = SMEM_BASE;
constexpr uint32_t SM_STG = SM_ACT + 3 * ROW_BYTES + 128;
constexpr uint32_t SM_W = SM_STG + 3 * 16384;
constexpr uint32_t SM_COEF = SM_W + NS * STAGE_BYTES;
constexpr uint32_t SM_EMB = SM_COEF + 1024;
constexpr uint32_t SM_RED = SM_EMB + 512;
constexpr uint32_t SM_BNC = SM_RED + 128;
constexpr uint32_t SM_BAR = SM_BNC + 2 * 2304;
constexpr int BAR_FULL = 0, BAR_WEMPTY = NSTAGE, BAR_HW = BAR_WEMPTY + NS, BAR_STATS = BAR_HW + 1,
              BAR_EMB = BAR_STATS + 1, BAR_WACQ = BAR_EMB + 1, BAR_XH = BAR_WACQ + 1, NBAR = BAR_XH + 1;
constexpr int SM_TOTAL = SM_BAR + NBAR * 8 - SMEM_BASE;
static_assert(SM_TOTAL <= 232448, "smem");
static_assert(NBAR <= 96, "barrier init");
constexpr int OUT_PITCH = 144;
__host__ __device__ constexpr uint32_t BAR(int i) { return SM_BAR + 8 * i; }
__host__ __device__ constexpr int ky_of(int kyo) { return kyo == 0 ? 1 : (kyo == 1 ? 0 : 2); }

constexpr unsigned SPIN_LIMIT = 1u << 16;

struct Scratch {
    float acc[2 * NB * 32];
    unsigned wcnt[2 * NB * 32];
    float emb[NB * C];
    unsigned char wt[2 * NSTAGE * STAGE_BYTES];
    uint4 h[NCTA * 1024];
};
__device__ __align__(1024) Scratch g_scratch;
#define TL(i) do {} while (0)
#define TLG(i) do {} while (0)

__device__ __forceinline__ void mbar_init(uint32_t bar, int cnt) {
    asm volatile("mbarrier.init.shared::cta.b64 [%0], %1;" ::"r"(bar), "r"(cnt) : "memory");
}
__device__ __forceinline__ void mbar_arrive(uint32_t bar) {
    asm volatile("mbarrier.arrive.shared::cta.b64 _, [%0];" ::"r"(bar) : "memory");
}
__device__ __forceinline__ void mbar_expect(uint32_t bar, uint32_t bytes) {
    asm volatile("mbarrier.arrive.expect_tx.shared::cta.b64 _, [%0], %1;" ::"r"(bar), "r"(bytes) : "memory");
}
__device__ __forceinline__ bool mbar_try(uint32_t bar, uint32_t par) {
    uint32_t ok;
    asm volatile("{\n.reg .pred p;\nmbarrier.try_wait.parity.shared::cta.b64 p, [%1], %2;\nselp.u32 %0, 1, 0, p;\n}"
                 : "=r"(ok) : "r"(bar), "r"(par) : "memory");
    return ok;
}
__device__ __forceinline__ void mbar_wait(uint32_t bar, uint32_t par) {
    unsigned it = 0;
#pragma unroll 1
    while (!mbar_try(bar, par) && ++it < SPIN_LIMIT) {}
}
__device__ __forceinline__ bool elect_one() {
    uint32_t p;
    asm volatile("{\n.reg .pred p;\nelect.sync _|p, 0xffffffff;\nselp.u32 %0, 1, 0, p;\n}" : "=r"(p));
    return p;
}
__device__ __forceinline__ void fence_async_smem() { asm volatile("fence.proxy.async.shared::cta;" ::: "memory"); }
__device__ __forceinline__ void fence_async_global() { asm volatile("fence.proxy.async.global;" ::: "memory"); }
__device__ __forceinline__ void fence_acquire() { asm volatile("fence.acquire.gpu;" ::: "memory"); }
__device__ __forceinline__ void bar_sync(int id, int n) { asm volatile("bar.sync %0, %1;" ::"r"(id), "r"(n) : "memory"); }
__device__ __forceinline__ void bar_arrive(int id, int n) { asm volatile("bar.arrive %0, %1;" ::"r"(id), "r"(n) : "memory"); }
__device__ __forceinline__ void bulk_g2s(uint32_t dst, const void* src, uint32_t bytes, uint32_t bar) {
    asm volatile("cp.async.bulk.shared::cluster.global.mbarrier::complete_tx::bytes [%0], [%1], %2, [%3];"
                 ::"r"(dst), "l"(src), "r"(bytes), "r"(bar) : "memory");
}
__device__ __forceinline__ uint4 ld_relaxed_v4(const void* p) {
    uint4 v;
    asm volatile("ld.relaxed.gpu.global.v4.u32 {%0,%1,%2,%3}, [%4];" : "=r"(v.x), "=r"(v.y), "=r"(v.z), "=r"(v.w) : "l"(p) : "memory");
    return v;
}
__device__ __forceinline__ unsigned ld_relaxed(const void* p) {
    unsigned v;
    asm volatile("ld.relaxed.gpu.global.u32 %0, [%1];" : "=r"(v) : "l"(p) : "memory");
    return v;
}
__device__ __forceinline__ void red_add4(float* p, float a, float b, float c, float d) {
    asm volatile("red.relaxed.gpu.global.add.v4.f32 [%0], {%1,%2,%3,%4};" ::"l"(p), "f"(a), "f"(b), "f"(c), "f"(d) : "memory");
}
__device__ __forceinline__ void sts128(uint32_t a, uint4 v) {
    asm volatile("st.shared.v4.u32 [%0], {%1,%2,%3,%4};" ::"r"(a), "r"(v.x), "r"(v.y), "r"(v.z), "r"(v.w) : "memory");
}
__device__ __forceinline__ void sts128f(uint32_t a, float4 v) {
    asm volatile("st.shared.v4.f32 [%0], {%1,%2,%3,%4};" ::"r"(a), "f"(v.x), "f"(v.y), "f"(v.z), "f"(v.w) : "memory");
}
__device__ __forceinline__ void sts32f(uint32_t a, float v) { asm volatile("st.shared.f32 [%0], %1;" ::"r"(a), "f"(v) : "memory"); }
__device__ __forceinline__ uint4 lds128(uint32_t a) {
    uint4 v;
    asm volatile("ld.shared.v4.u32 {%0,%1,%2,%3}, [%4];" : "=r"(v.x), "=r"(v.y), "=r"(v.z), "=r"(v.w) : "r"(a) : "memory");
    return v;
}
__device__ __forceinline__ float4 lds128f(uint32_t a) {
    float4 v;
    asm volatile("ld.shared.v4.f32 {%0,%1,%2,%3}, [%4];" : "=f"(v.x), "=f"(v.y), "=f"(v.z), "=f"(v.w) : "r"(a) : "memory");
    return v;
}
__device__ __forceinline__ float2 lds64f(uint32_t a) {
    float2 v;
    asm volatile("ld.shared.v2.f32 {%0,%1}, [%2];" : "=f"(v.x), "=f"(v.y) : "r"(a) : "memory");
    return v;
}
__device__ __forceinline__ float bf_lo(uint32_t u) { return __uint_as_float(u << 16); }
__device__ __forceinline__ float bf_hi(uint32_t u) { return __uint_as_float(u & 0xffff0000u); }
__device__ __forceinline__ uint32_t pack_bf(float lo, float hi) {
    uint32_t r;
    asm("cvt.rn.bf16x2.f32 %0, %1, %2;" : "=r"(r) : "f"(hi), "f"(lo));
    return r;
}
__device__ __forceinline__ float tanh_fast(float x) {
    float r;
    asm("tanh.approx.f32 %0, %1;" : "=f"(r) : "f"(x));
    return r;
}
__device__ __forceinline__ float silu_half(float h) { return fmaf(h, tanh_fast(h), h); }
__device__ __forceinline__ void ldsm4(uint32_t (&u)[4], uint32_t a) {
    asm volatile("ldmatrix.sync.aligned.m8n8.x4.shared.b16 {%0,%1,%2,%3}, [%4];"
                 : "=r"(u[0]), "=r"(u[1]), "=r"(u[2]), "=r"(u[3]) : "r"(a) : "memory");
}
__device__ __forceinline__ void ldsm4t(uint32_t (&u)[4], uint32_t a) {
    asm volatile("ldmatrix.sync.aligned.m8n8.x4.trans.shared.b16 {%0,%1,%2,%3}, [%4];"
                 : "=r"(u[0]), "=r"(u[1]), "=r"(u[2]), "=r"(u[3]) : "r"(a) : "memory");
}
__device__ __forceinline__ void stsm4(uint32_t a, uint32_t p0, uint32_t p1, uint32_t p2, uint32_t p3) {
    asm volatile("stmatrix.sync.aligned.m8n8.x4.shared.b16 [%0], {%1,%2,%3,%4};" ::"r"(a), "r"(p0), "r"(p1), "r"(p2), "r"(p3) : "memory");
}
__device__ __forceinline__ void stsm4t(uint32_t a, uint32_t p0, uint32_t p1, uint32_t p2, uint32_t p3) {
    asm volatile("stmatrix.sync.aligned.m8n8.x4.trans.shared.b16 [%0], {%1,%2,%3,%4};" ::"r"(a), "r"(p0), "r"(p1), "r"(p2), "r"(p3) : "memory");
}

#define R8(o) "+f"(d[o]), "+f"(d[o + 1]), "+f"(d[o + 2]), "+f"(d[o + 3]), "+f"(d[o + 4]), "+f"(d[o + 5]), "+f"(d[o + 6]), "+f"(d[o + 7])
template <uint32_t ALO, uint32_t BLO>
__device__ __forceinline__ void wgmma128(float (&d)[64]) {
    asm volatile(
        "wgmma.mma_async.sync.aligned.m64n128k16.f32.bf16.bf16 "
        "{%0,%1,%2,%3,%4,%5,%6,%7,%8,%9,%10,%11,%12,%13,%14,%15,%16,%17,%18,%19,%20,%21,%22,%23,%24,%25,%26,%27,%28,%29,%30,%31,"
        "%32,%33,%34,%35,%36,%37,%38,%39,%40,%41,%42,%43,%44,%45,%46,%47,%48,%49,%50,%51,%52,%53,%54,%55,%56,%57,%58,%59,%60,%61,%62,%63},"
        " %64, %65, 1, 1, 1, 0, 0;"
        : R8(0), R8(8), R8(16), R8(24), R8(32), R8(40), R8(48), R8(56)
        : "l"((8ull << 32) | ALO), "l"((8ull << 32) | BLO));
}
template <int S>
__device__ __forceinline__ void mma_stages(float (&d)[64], int conv, int tid, Scratch* gs) {
    constexpr uint32_t A = ((SM_ACT + ky_of(S >> 3) * ROW_BYTES + (S & 7) * 2 * CH_PITCH + 16) >> 4) | ((CH_PITCH >> 4) << 16);
    constexpr uint32_t B = ((SM_W + (S % NS) * STAGE_BYTES) >> 4) | ((2048 >> 4) << 16);
    mbar_wait(BAR(BAR_FULL + S), conv);
    if (S == 0 && tid == 0) TL(32 + conv * 24);
    asm volatile("wgmma.fence.sync.aligned;" ::: "memory");
    wgmma128<A, B>(d);
    wgmma128<A + 1, B + (STEP_BYTES >> 4)>(d);
    wgmma128<A + 2, B + 2 * (STEP_BYTES >> 4)>(d);
    asm volatile("wgmma.commit_group.sync.aligned;" ::: "memory");
    if (S > 0) {
        asm volatile("wgmma.wait_group.sync.aligned 1;" ::: "memory");
        if ((tid & 31) == 0) mbar_arrive(BAR(BAR_WEMPTY + (S + NS - 1) % NS));
    }
    if constexpr (S + 1 < NSTAGE) mma_stages<S + 1>(d, conv, tid, gs);
}

__device__ __forceinline__ void weight_block(const uint4 (&t)[5], uint32_t bounce, unsigned char* wt, int cta, int lane) {
    const uint32_t bw = bounce + (lane >> 4) * 1152 + (lane & 15) * 16;
#pragma unroll
    for (int k = 0; k < 4; k++) sts128(bw + k * 256, t[k]);
    if ((lane & 15) < 8) sts128(bw + 1024, t[4]);
    __syncwarp();
    if (lane < 16) {
        uint32_t v[36];
#pragma unroll
        for (int i = 0; i < 9; i++) {
            const uint4 q = lds128(bounce + (lane & 1) * 1152 + (lane >> 1) * 144 + i * 16);
            v[4 * i] = q.x; v[4 * i + 1] = q.y; v[4 * i + 2] = q.z; v[4 * i + 3] = q.w;
        }
        const int cc = (cta >> 6) * 8 + (lane >> 1);
        unsigned char* dst = wt + (cc >> 1) * STAGE_BYTES + (cc & 1) * 2048 + ((cta & 63) * 2 + (lane & 1)) * 16;
#pragma unroll
        for (int kyo = 0; kyo < 3; kyo++) {
#pragma unroll
            for (int kx = 0; kx < 3; kx++) {
                const int tap = ky_of(kyo) * 3 + kx;
                uint32_t o[4];
#pragma unroll
                for (int m = 0; m < 4; m++) {
                    const int i0 = 18 * m + tap, i1 = i0 + 9;
                    const uint32_t sel = ((i0 & 1) ? 0x32u : 0x10u) | ((i1 & 1) ? 0x7600u : 0x5400u);
                    o[m] = __byte_perm(v[i0 >> 1], v[i1 >> 1], sel);
                }
                *reinterpret_cast<uint4*>(dst + (kyo * 24 + kx) * STEP_BYTES) = make_uint4(o[0], o[1], o[2], o[3]);
            }
        }
    }
}
__device__ __forceinline__ uint32_t act2(uint32_t u, const float4& cf) {
    return pack_bf(silu_half(fmaf(bf_lo(u), cf.x, cf.z)), silu_half(fmaf(bf_hi(u), cf.y, cf.w)));
}
template <int FIRST, int N>
__device__ __forceinline__ void norm_batch(const uint32_t (&u)[4][4], const float4 (&cf)[8], uint32_t act, uint32_t bar, int lane, bool valid) {
    if (valid) {
#pragma unroll
        for (int t = FIRST; t < FIRST + N; t++)
            stsm4(act + t * 4 * CH_PITCH, act2(u[t][0], cf[2 * t]), act2(u[t][1], cf[2 * t]), act2(u[t][2], cf[2 * t + 1]), act2(u[t][3], cf[2 * t + 1]));
        fence_async_smem();
    }
    __syncwarp();
    if (lane < N) mbar_arrive(bar + 16 * (FIRST + lane));
}
__device__ __forceinline__ void fence_acc(float (&d)[64]) {
#pragma unroll
    for (int i = 0; i < 64; i++) asm volatile("" : "+f"(d[i])::"memory");
}
__device__ __forceinline__ void ld_unit(uint32_t (&u)[4], const uint4* p) {
    asm volatile("ld.relaxed.gpu.global.v4.u32 {%0,%1,%2,%3}, [%4];" : "=r"(u[0]), "=r"(u[1]), "=r"(u[2]), "=r"(u[3]) : "l"(p) : "memory");
}

__device__ __forceinline__ void halo_row(const char* xrow, uint32_t stg, int lane) {
    const int c = lane >> 3, sg = lane & 7;
    const char* p = xrow + c * (HW * HW * 2) + sg * 16;
    const uint32_t d0 = stg + c * 128 + ((sg ^ c) << 4), d1 = stg + (c + 4) * 128 + ((sg ^ (c + 4)) << 4);
#pragma unroll 4
    for (int i = 0; i < 16; i++) {
        asm volatile("cp.async.cg.shared.global [%0], [%1], 16;" ::"r"(d0 + i * 1024), "l"(p + i * (8 * HW * HW * 2)) : "memory");
        asm volatile("cp.async.cg.shared.global [%0], [%1], 16;" ::"r"(d1 + i * 1024), "l"(p + i * (8 * HW * HW * 2) + 4 * HW * HW * 2) : "memory");
    }
}

__global__ void __launch_bounds__(NTHREADS, 1)
resblock_kernel(const __nv_bfloat16* __restrict__ x, const __nv_bfloat16* __restrict__ w1,
                const __nv_bfloat16* __restrict__ t_emb, const __nv_bfloat16* __restrict__ g1,
                const __nv_bfloat16* __restrict__ be1, const __nv_bfloat16* __restrict__ w_emb,
                const __nv_bfloat16* __restrict__ g2, const __nv_bfloat16* __restrict__ be2,
                const __nv_bfloat16* __restrict__ w2, __nv_bfloat16* __restrict__ out, Scratch* __restrict__ gs) {
    const unsigned clk0 = clock();
    const int tid = threadIdx.x, warp = tid >> 5, lane = tid & 31;
    const int cta = blockIdx.x, b = cta >> 6, r = cta & 63;

    const uint32_t woff = ((2 * r + (lane >> 4)) * C + b * 64) * 18 + (lane & 15) * 16;
    const int c0 = (warp - 8) * 16 + (lane >> 3), seg = lane & 7;
    const char* src = (warp == 0) ? reinterpret_cast<const char*>(w1) + woff
                                  : reinterpret_cast<const char*>(x) + (uint32_t)(((b * C + c0) * HW + r) * HW * 2 + seg * 16);
    uint4 v[5];
    if (warp == 0 || warp >= 8) {
        const uint32_t stride = (warp == 0) ? 256 : 4 * HW * HW * 2;
        if (warp != 0) { while (clock() - clk0 < XDELAY) {} }
#pragma unroll
        for (int k = 0; k < 4; k++) v[k] = __ldg(reinterpret_cast<const uint4*>(src + k * stride));
        if (tid < 32 && (lane & 15) < 8) v[4] = __ldg(reinterpret_cast<const uint4*>(src + 1024));
    }
    if (warp == 0) {
        weight_block(v, SM_BNC, gs->wt, cta, lane);
        if (r == 0) {
            if (lane < 16) gs->acc[(NB + b) * 32 + lane] = 0.f;
            *reinterpret_cast<float4*>(&gs->emb[b * C + lane * 4]) = make_float4(0.f, 0.f, 0.f, 0.f);
        }
        __syncwarp();
        if (lane == 0) TL(4);
        if (lane < 2) asm volatile("red.release.gpu.global.add.u32 [%0], 1;" ::"l"(&gs->wcnt[lane * 32]) : "memory");
        if (lane == 0) TL(5);
    }

    if (warp >= 8) {
        const int nw = warp - 8;
        {
            float s = 0.f, q = 0.f, s2 = 0.f, q2 = 0.f;
#pragma unroll
            for (int i = 0; i < 4; i++) {
                const uint32_t u[4] = {v[i].x, v[i].y, v[i].z, v[i].w};
#pragma unroll
                for (int k = 0; k < 4; k++) {
                    const float lo = bf_lo(u[k]), hi = bf_hi(u[k]);
                    s += lo; q = fmaf(lo, lo, q);
                    s2 += hi; q2 = fmaf(hi, hi, q2);
                }
            }
            s += s2; q += q2;
            float give = (lane < 16) ? q : s, keep = (lane < 16) ? s : q;
            keep += __shfl_xor_sync(0xffffffffu, give, 16);
            if (tid == 256) TL(2);
#pragma unroll
            for (int m = 8; m >= 1; m >>= 1) keep += __shfl_xor_sync(0xffffffffu, keep, m);
            if ((lane & 15) == 0) sts32f(SM_RED + (nw * 2 + (lane >> 4)) * 4, keep);
            bar_sync(3, 256 + 96);
            if (tid < 256 + 4) {
                const float4 p = lds128f(SM_RED + lane * 16);
                red_add4(&gs->acc[b * 32 + lane * 4], 1.f, p.x + p.z, p.y + p.w, 1.f);
            }
            if (tid == 256) TL(3);
#pragma unroll
            for (int i = 0; i < 4; i++) sts128(SM_STG + 16384 + c0 * 128 + i * 512 + ((seg ^ ((c0 + 4 * i) & 7)) << 4), v[i]);
            bar_sync(4, 256);
        }
        const int par = nw >> 2, wq = nw & 3;
        const uint32_t act_off = SM_ACT + (par * 2 + (lane >> 4)) * CH_PITCH + (2 + wq * 16 + (lane & 15)) * 16;
        const uint32_t stg_off = SM_STG + (par * 16 + (lane >> 4) * 8 + (lane & 7)) * 128 + (((2 * wq + ((lane >> 3) & 1)) ^ (lane & 7)) << 4);
        const uint32_t fbar = BAR(BAR_FULL) + 8 * par;
#pragma unroll 1
        for (int conv = 0; conv < 2; conv++) {
            uint32_t u[4][4], hu[2][4][4];
            float4 cf[8];
            if (conv == 0) {
#pragma unroll
                for (int i = 0; i < 4; i++) ldsm4t(u[i], stg_off + 16384 + i * 4096);
            } else {
                mbar_wait(BAR(BAR_HW), 0);
#pragma unroll
                for (int i = 0; i < 4; i++) ldsm4(u[i], act_off + ROW_BYTES + i * 4 * CH_PITCH);
            }
            const uint4* hp[2];
            hp[0] = gs->h + (size_t)(r != 0 ? cta - 1 : cta) * 1024 + nw * 32 + lane;
            hp[1] = gs->h + (size_t)(r != HW - 1 ? cta + 1 : cta) * 1024 + nw * 32 + lane;
            mbar_wait(BAR(BAR_STATS), conv);
            if (tid == 256) TL(22 + conv * 4);
#pragma unroll
            for (int i = 0; i < 8; i++) cf[i] = lds128f(SM_COEF + (par * 2 + (i >> 1) * 4 + (i & 1)) * 64 + (lane & 3) * 16);
            if (conv == 1) {
#pragma unroll
                for (int i = 0; i < 8; i++) ld_unit(hu[i >> 2][i & 3], hp[i >> 2] + (i & 3) * 256);
            }
            norm_batch<0, 1>(u, cf, act_off + ROW_BYTES, fbar, lane, true);
            if (tid == 256) TL(8 + conv * 8);
            norm_batch<1, 3>(u, cf, act_off + ROW_BYTES, fbar, lane, true);
            if (tid == 256) TL(24 + conv * 4);
            if (conv == 0) {
                mbar_wait(BAR(BAR_XH), 0);
#pragma unroll
                for (int i = 0; i < 8; i++) ldsm4t(hu[i >> 2][i & 3], stg_off + (i >> 2) * 2 * 16384 + (i & 3) * 4096);
            } else {
                unsigned it = 0;
                while (true) {
                    bool ok = true;
#pragma unroll
                    for (int i = 0; i < 32; i++) ok = ok && hu[i >> 4][(i >> 2) & 3][i & 3] != 0xffffffffu;
                    if (__all_sync(0xffffffffu, ok) || ++it > SPIN_LIMIT) break;
#pragma unroll
                    for (int i = 0; i < 8; i++) ld_unit(hu[i >> 2][i & 3], hp[i >> 2] + (i & 3) * 256);
                }
            }
            norm_batch<0, 4>(hu[0], cf, act_off, fbar + 64, lane, r != 0);
            norm_batch<0, 4>(hu[1], cf, act_off + 2 * ROW_BYTES, fbar + 128, lane, r != HW - 1);
            if (tid == 256) TL(23 + conv * 4);
        }
    } else if (warp < 4) {
        const int wq = warp;
        if (wq != 0) {
            const int t = tid - 32;
            if (t == 95) TLG(1);
            if (t < NBAR) {
                const int cnt = t < BAR_WEMPTY ? 5 : (t <= BAR_HW ? 4 : (t == BAR_XH ? 64 : 1));
                mbar_init(BAR(0) + 8 * t, cnt);
            }
            fence_async_smem();
            bar_arrive(0, 96 + 128);
            bar_arrive(3, 256 + 96);
            const uint4 z = make_uint4(0, 0, 0, 0);
            sts128(SM_ACT + (t >> 1) * CH_PITCH + (t & 1) * 16, z);
            if (t < 2) sts128(SM_ACT + 3 * ROW_BYTES + t * 16, z);
            if (r == 0 || r == HW - 1) {
                for (int i = t; i < ROW_BYTES / 16; i += 96) sts128(SM_ACT + (r == 0 ? 0 : 2 * ROW_BYTES) + i * 16, z);
            }
            fence_async_smem();
        }
        bar_sync(2, 128);

        float d[64];
#pragma unroll
        for (int i = 0; i < 64; i++) d[i] = 0.f;
#pragma unroll 1
        for (int conv = 0; conv < 2; conv++) {
            fence_acc(d);
            mma_stages<0>(d, conv, tid, gs);
            asm volatile("wgmma.wait_group.sync.aligned 0;" ::: "memory");
            fence_acc(d);
            if (tid == 0) TL(10 + conv * 8);
            if (conv == 1) break;

            if (lane == 0) mbar_arrive(BAR(BAR_WEMPTY + (NSTAGE - 1) % NS));
            mbar_wait(BAR(BAR_EMB), 0);
            float st[8];
#pragma unroll
            for (int g = 0; g < 4; g++) {
                float s = 0.f, q = 0.f, s2 = 0.f, q2 = 0.f;
#pragma unroll
                for (int jj = 0; jj < 4; jj++) {
                    const int j = g * 4 + jj;
                    const float2 e = lds64f(SM_EMB + j * 32 + (lane & 3) * 8);
                    d[4 * j + 0] += e.x; d[4 * j + 1] += e.y; d[4 * j + 2] += e.x; d[4 * j + 3] += e.y;
                    s += d[4 * j + 0]; q = fmaf(d[4 * j + 0], d[4 * j + 0], q);
                    s2 += d[4 * j + 1]; q2 = fmaf(d[4 * j + 1], d[4 * j + 1], q2);
                    s += d[4 * j + 2]; q = fmaf(d[4 * j + 2], d[4 * j + 2], q);
                    s2 += d[4 * j + 3]; q2 = fmaf(d[4 * j + 3], d[4 * j + 3], q2);
                }
                st[2 * g] = s + s2; st[2 * g + 1] = q + q2;
            }
            {
                const bool h16 = lane & 16, h8 = lane & 8, h4 = lane & 4;
                float a[4];
#pragma unroll
                for (int i = 0; i < 4; i++) {
                    float give = h16 ? st[i] : st[i + 4], keep = h16 ? st[i + 4] : st[i];
                    a[i] = keep + __shfl_xor_sync(0xffffffffu, give, 16);
                }
                float c2[2];
#pragma unroll
                for (int i = 0; i < 2; i++) {
                    float give = h8 ? a[i] : a[i + 2], keep = h8 ? a[i + 2] : a[i];
                    c2[i] = keep + __shfl_xor_sync(0xffffffffu, give, 8);
                }
                float give = h4 ? c2[0] : c2[1], keep = h4 ? c2[1] : c2[0];
                float t = keep + __shfl_xor_sync(0xffffffffu, give, 4);
                t += __shfl_xor_sync(0xffffffffu, t, 2);
                t += __shfl_xor_sync(0xffffffffu, t, 1);
                if ((lane & 3) == 0) sts32f(SM_RED + ((lane >> 2) * 4 + wq) * 4, t);
                bar_sync(2, 128);
                if (tid < 4) {
                    const float4 p = lds128f(SM_RED + tid * 32), p2 = lds128f(SM_RED + tid * 32 + 16);
                    red_add4(&gs->acc[(NB + b) * 32 + tid * 4], 1.f, (p.x + p.y) + (p.z + p.w), (p2.x + p2.y) + (p2.z + p2.w), 1.f);
                }
                if (tid == 0) TL(11);
            }
            const uint32_t hbase = SM_ACT + ROW_BYTES + (lane >> 4) * CH_PITCH + (2 + wq * 16 + (lane & 15)) * 16;
            uint4* hg = gs->h + cta * 1024 + tid;
#pragma unroll
            for (int kc = 0; kc < 8; kc++) {
                const uint4 p = make_uint4(pack_bf(d[8 * kc + 0], d[8 * kc + 1]), pack_bf(d[8 * kc + 2], d[8 * kc + 3]),
                                           pack_bf(d[8 * kc + 4], d[8 * kc + 5]), pack_bf(d[8 * kc + 6], d[8 * kc + 7]));
                stsm4(hbase + kc * 2 * CH_PITCH, p.x, p.y, p.z, p.w);
                hg[kc * 128] = p;
            }
            __syncwarp();
            if (lane == 0) mbar_arrive(BAR(BAR_HW));
            if (tid == 0) TL(12);
            const uint32_t xbase = SM_STG + 16384 + ((lane >> 4) * 8 + (lane & 7)) * 128 + (((2 * wq + ((lane >> 3) & 1)) ^ (lane & 7)) << 4);
#pragma unroll
            for (int kc = 0; kc < 8; kc++) {
                uint32_t p[4];
                ldsm4t(p, xbase + kc * 2048);
#pragma unroll
                for (int i = 0; i < 4; i++) { d[8 * kc + 2 * i] = bf_lo(p[i]); d[8 * kc + 2 * i + 1] = bf_hi(p[i]); }
            }
        }
        {
            const uint32_t obase = SM_STG + ((lane >> 4) * 8 + (lane & 7)) * OUT_PITCH + (wq * 16 + ((lane >> 3) & 1) * 8) * 2;
#pragma unroll
            for (int kc = 0; kc < 8; kc++) {
                stsm4t(obase + kc * 16 * OUT_PITCH, pack_bf(d[8 * kc + 0], d[8 * kc + 1]), pack_bf(d[8 * kc + 2], d[8 * kc + 3]),
                       pack_bf(d[8 * kc + 4], d[8 * kc + 5]), pack_bf(d[8 * kc + 6], d[8 * kc + 7]));
            }
            bar_sync(2, 128);
            const int oc0 = tid >> 3;
            __nv_bfloat16* dst = out + ((size_t)(b * C + oc0) * HW + r) * HW + seg * 8;
#pragma unroll
            for (int i = 0; i < 8; i++)
                *reinterpret_cast<uint4*>(dst + (size_t)i * 16 * HW * HW) = lds128(SM_STG + (oc0 + 16 * i) * OUT_PITCH + seg * 16);
            if (tid == 0) { TL(20); TLG(21); }
        }
    } else if (warp < 6) {
        bar_sync(0, 96 + 128);
        mbar_wait(BAR(BAR_STATS), 0);
        if (warp == 5) {
            if (r != 0) halo_row(reinterpret_cast<const char*>(x) + (uint32_t)((b * C * HW + r - 1) * HW * 2), SM_STG, lane);
            asm volatile("cp.async.mbarrier.arrive.noinc.shared::cta.b64 [%0];" ::"r"(BAR(BAR_XH)) : "memory");
#pragma unroll 4
            for (int i = 0; i < 32; i++) gs->h[cta * 1024 + i * 32 + lane] = make_uint4(~0u, ~0u, ~0u, ~0u);
            bar_arrive(6, 64);
        } else {
            const char* w2s = reinterpret_cast<const char*>(w2) + woff;
#pragma unroll
            for (int k = 0; k < 4; k++) v[k] = __ldg(reinterpret_cast<const uint4*>(w2s + k * 256));
            if ((lane & 15) < 8) v[4] = __ldg(reinterpret_cast<const uint4*>(w2s + 1024));
            const uint2* wsrc = reinterpret_cast<const uint2*>(w_emb + (size_t)r * 12 * C) + lane;
            uint2 wv[12];
#pragma unroll
            for (int i = 0; i < 12; i++) wv[i] = __ldg(wsrc + i * (C / 4));
            float tv = 0.f;
            if (lane < 12) tv = __bfloat162float(t_emb[b * E + r * 12 + lane]);
            weight_block(v, SM_BNC + 2304, gs->wt + NSTAGE * STAGE_BYTES, cta, lane);
            const float sv = silu_half(0.5f * tv);
            float e0 = 0.f, e1 = 0.f, e2 = 0.f, e3 = 0.f;
#pragma unroll
            for (int i = 0; i < 12; i++) {
                const float sx = __shfl_sync(0xffffffffu, sv, i);
                e0 = fmaf(sx, bf_lo(wv[i].x), e0); e1 = fmaf(sx, bf_hi(wv[i].x), e1);
                e2 = fmaf(sx, bf_lo(wv[i].y), e2); e3 = fmaf(sx, bf_hi(wv[i].y), e3);
            }
            mbar_wait(BAR(BAR_WACQ), 0);
            red_add4(&gs->emb[b * C + lane * 4], e0, e1, e2, e3);
            bar_sync(6, 64);
            if (lane == 0) TL(13);
            if (lane < 2) asm volatile("red.release.gpu.global.add.u32 [%0], 1;" ::"l"(&gs->wcnt[(NB + lane) * 32]) : "memory");
            if (lane == 0) TL(14);
            unsigned it = 0;
            while (ld_relaxed(&gs->wcnt[(NB + b) * 32]) < (unsigned)NCTA && ++it < SPIN_LIMIT) {}
            fence_acquire();
            sts128(SM_EMB + lane * 16, ld_relaxed_v4(&gs->emb[b * C + lane * 4]));
            __syncwarp();
            if (lane == 0) { mbar_arrive(BAR(BAR_EMB)); TL(19); }
        }
    } else if (warp == 6) {
        bar_sync(0, 96 + 128);
        unsigned it = 0;
        while (ld_relaxed(&gs->wcnt[b * 32]) < (unsigned)NCTA && ++it < SPIN_LIMIT) {}
        fence_acquire();
        fence_async_global();
        if (lane == 0) TL(6);
        const unsigned char* wsrc = gs->wt;
#pragma unroll 1
        for (int round = 0; round < 2 * NSTAGE / NS; round++) {
            if (round == NSTAGE / NS) { mbar_wait(BAR(BAR_EMB), 0); fence_async_global(); }
            const uint32_t full = BAR(BAR_FULL) + 8 * NS * (round >= NSTAGE / NS ? round - NSTAGE / NS : round);
#pragma unroll
            for (int slot = 0; slot < NS; slot++) {
                mbar_wait(BAR(BAR_WEMPTY + slot), (round & 1) ^ 1);
                if (elect_one()) {
                    mbar_expect(full + 8 * slot, STAGE_BYTES);
                    bulk_g2s(SM_W + slot * STAGE_BYTES, wsrc + slot * STAGE_BYTES, STAGE_BYTES, full + 8 * slot);
                }
            }
            wsrc += NS * STAGE_BYTES;
            if (round == 0 && lane == 0) mbar_arrive(BAR(BAR_WACQ));
        }
    } else {
        const uint2 ga1 = __ldg(reinterpret_cast<const uint2*>(g1) + lane), bt1 = __ldg(reinterpret_cast<const uint2*>(be1) + lane);
        const uint2 ga2 = __ldg(reinterpret_cast<const uint2*>(g2) + lane), bt2 = __ldg(reinterpret_cast<const uint2*>(be2) + lane);
        bar_sync(0, 96 + 128);
#pragma unroll 1
        for (int conv = 0; conv < 2; conv++) {
            if (conv == 1) mbar_wait(BAR(BAR_EMB), 0);
            const float* asrc = &gs->acc[(conv * NB + b) * 32 + (lane >> 3) * 4];
            uint4 f;
            unsigned it = 0;
            while (true) {
                f = ld_relaxed_v4(asrc);
                const bool ok = (f.x == 0x42800000u) & (f.w == 0x42800000u);
                if (__all_sync(0xffffffffu, ok) || ++it > SPIN_LIMIT) break;
            }
            if (lane == 0) TL(7 + conv * 8);
            const float inv_n = 1.0f / (32.0f * HW * HW);
            const float mean = __uint_as_float(f.y) * inv_n;
            const float var = fmaxf(fmaf(-mean, mean, __uint_as_float(f.z) * inv_n), 0.f);
            const float rs = 0.5f * rsqrtf(var + 1e-5f);
            const uint2 ga = conv ? ga2 : ga1, bt = conv ? bt2 : bt1;
            float4 k0, k1;
            k0.x = rs * bf_lo(ga.x); k0.y = rs * bf_hi(ga.x); k1.x = rs * bf_lo(ga.y); k1.y = rs * bf_hi(ga.y);
            k0.z = fmaf(-mean, k0.x, 0.5f * bf_lo(bt.x)); k0.w = fmaf(-mean, k0.y, 0.5f * bf_hi(bt.x));
            k1.z = fmaf(-mean, k1.x, 0.5f * bf_lo(bt.y)); k1.w = fmaf(-mean, k1.y, 0.5f * bf_hi(bt.y));
            sts128f(SM_COEF + lane * 32, k0);
            sts128f(SM_COEF + lane * 32 + 16, k1);
            __syncwarp();
            if (lane == 0) mbar_arrive(BAR(BAR_STATS));
            if (conv == 0) {
                if (r != HW - 1) halo_row(reinterpret_cast<const char*>(x) + (uint32_t)((b * C * HW + r + 1) * HW * 2), SM_STG + 2 * 16384, lane);
                asm volatile("cp.async.mbarrier.arrive.noinc.shared::cta.b64 [%0];" ::"r"(BAR(BAR_XH)) : "memory");
            }
        }
        if (r == 0) {
            if (lane < 16) gs->acc[b * 32 + lane] = 0.f;
            if (lane < 2) gs->wcnt[(lane * NB + b) * 32] = 0;
        }
    }
}

}

extern "C" void kernel_launch(void* const* d_in, const int* in_sizes, int n_in, void* d_out, int out_size) {
    (void)in_sizes; (void)n_in; (void)out_size;
    static Scratch* gs = nullptr;
    if (!gs) {
        cudaFuncSetAttribute(resblock_kernel, cudaFuncAttributeMaxDynamicSharedMemorySize, SM_TOTAL);
        cudaGetSymbolAddress((void**)&gs, g_scratch);
    }
    resblock_kernel<<<NCTA, NTHREADS, SM_TOTAL>>>(
        (const __nv_bfloat16*)d_in[0], (const __nv_bfloat16*)d_in[4], (const __nv_bfloat16*)d_in[1],
        (const __nv_bfloat16*)d_in[2], (const __nv_bfloat16*)d_in[3], (const __nv_bfloat16*)d_in[5],
        (const __nv_bfloat16*)d_in[6], (const __nv_bfloat16*)d_in[7], (const __nv_bfloat16*)d_in[8],
        (__nv_bfloat16*)d_out, gs);
}
```

```cpp
#include <cuda_runtime.h>
#include <cuda_bf16.h>
#include <stdint.h>

namespace {

constexpr int C = 128, HW = 64, NB = 2, E = 768;
constexpr int NCTA = NB * HW;
constexpr int NTHREADS = 16 * 32;
constexpr int CH_PITCH = 66 * 16;
constexpr int ROW_BYTES = 16 * CH_PITCH;
constexpr int STEP_BYTES = 4096;
constexpr int STAGE_BYTES = 3 * STEP_BYTES;
constexpr int NSTAGE = 24;
constexpr int NS = 12;
constexpr int LAG = 2;
#define XDELAY 900
#define HDELAY 1500
#define W2DELAY 2800

constexpr uint32_t SMEM_BASE = 0x400;
constexpr uint32_t SM_ACT = SMEM_BASE;
constexpr uint32_t SM_XOWN = SM_ACT + 3 * ROW_BYTES + 128;
constexpr uint32_t SM_W = SM_XOWN + 16384;
constexpr uint32_t SM_XH = SM_W + 9 * STAGE_BYTES;
constexpr uint32_t SM_COEF = SM_W + NS * STAGE_BYTES;
constexpr uint32_t SM_EMB = SM_COEF + 1024;
constexpr uint32_t SM_RED = SM_EMB + 512;
constexpr uint32_t SM_BNC = SM_RED + 128;
constexpr uint32_t SM_BAR = SM_BNC + 2 * 2304;
constexpr int BAR_FULL = 0, BAR_WEMPTY = NSTAGE, BAR_HW = BAR_WEMPTY + NS, BAR_STATS = BAR_HW + 1,
              BAR_EMB = BAR_STATS + 1, BAR_WACQ = BAR_EMB + 1, BAR_XH = BAR_WACQ + 1, BAR_XFREE = BAR_XH + 1, NBAR = BAR_XFREE + 1;
constexpr int SM_TOTAL = SM_BAR + NBAR * 8 - SMEM_BASE;
static_assert(SM_TOTAL <= 232448, "smem");
static_assert(NBAR <= 96, "barrier init");
constexpr int OUT_PITCH = 144;
__host__ __device__ constexpr uint32_t BAR(int i) { return SM_BAR + 8 * i; }
__host__ __device__ constexpr int ky_of(int kyo) { return kyo == 0 ? 1 : (kyo == 1 ? 0 : 2); }

constexpr unsigned SPIN_LIMIT = 1u << 16;

struct Scratch {
    float acc[2 * NB * 32];
    unsigned wcnt[2 * NB * 32];
    float emb[NB * C];
    unsigned char wt[2 * NSTAGE * STAGE_BYTES];
    uint4 h[NCTA * 1024];
};
__device__ __align__(1024) Scratch g_scratch;
#define TL(i) do {} while (0)
#define TLG(i) do {} while (0)

__device__ __forceinline__ unsigned clock32() { unsigned c; asm volatile("mov.u32 %0, %%clock;" : "=r"(c)); return c; }
__device__ __forceinline__ void mbar_init(uint32_t bar, int cnt) {
    asm volatile("mbarrier.init.shared::cta.b64 [%0], %1;" ::"r"(bar), "r"(cnt) : "memory");
}
__device__ __forceinline__ void mbar_arrive(uint32_t bar) {
    asm volatile("mbarrier.arrive.shared::cta.b64 _, [%0];" ::"r"(bar) : "memory");
}
__device__ __forceinline__ void mbar_expect(uint32_t bar, uint32_t bytes) {
    asm volatile("mbarrier.arrive.expect_tx.shared::cta.b64 _, [%0], %1;" ::"r"(bar), "r"(bytes) : "memory");
}
__device__ __forceinline__ bool mbar_try(uint32_t bar, uint32_t par) {
    uint32_t ok;
    asm volatile("{\n.reg .pred p;\nmbarrier.try_wait.parity.shared::cta.b64 p, [%1], %2;\nselp.u32 %0, 1, 0, p;\n}"
                 : "=r"(ok) : "r"(bar), "r"(par) : "memory");
    return ok;
}
__device__ __forceinline__ void mbar_wait(uint32_t bar, uint32_t par) {
    unsigned it = 0;
#pragma unroll 1
    while (!mbar_try(bar, par) && ++it < SPIN_LIMIT) {}
}
__device__ __forceinline__ bool elect_one() {
    uint32_t p;
    asm volatile("{\n.reg .pred p;\nelect.sync _|p, 0xffffffff;\nselp.u32 %0, 1, 0, p;\n}" : "=r"(p));
    return p;
}
__device__ __forceinline__ void fence_async_smem() { asm volatile("fence.proxy.async.shared::cta;" ::: "memory"); }
__device__ __forceinline__ void fence_async_global() { asm volatile("fence.proxy.async.global;" ::: "memory"); }
__device__ __forceinline__ void fence_acquire() { asm volatile("fence.acquire.gpu;" ::: "memory"); }
__device__ __forceinline__ void bar_sync(int id, int n) { asm volatile("bar.sync %0, %1;" ::"r"(id), "r"(n) : "memory"); }
__device__ __forceinline__ void bar_arrive(int id, int n) { asm volatile("bar.arrive %0, %1;" ::"r"(id), "r"(n) : "memory"); }
__device__ __forceinline__ void bulk_g2s(uint32_t dst, const void* src, uint32_t bytes, uint32_t bar) {
    asm volatile("cp.async.bulk.shared::cluster.global.mbarrier::complete_tx::bytes [%0], [%1], %2, [%3];"
                 ::"r"(dst), "l"(src), "r"(bytes), "r"(bar) : "memory");
}
__device__ __forceinline__ uint4 ld_relaxed_v4(const void* p) {
    uint4 v;
    asm volatile("ld.relaxed.gpu.global.v4.u32 {%0,%1,%2,%3}, [%4];" : "=r"(v.x), "=r"(v.y), "=r"(v.z), "=r"(v.w) : "l"(p) : "memory");
    return v;
}
__device__ __forceinline__ unsigned ld_relaxed(const void* p) {
    unsigned v;
    asm volatile("ld.relaxed.gpu.global.u32 %0, [%1];" : "=r"(v) : "l"(p) : "memory");
    return v;
}
__device__ __forceinline__ void red_add4(float* p, float a, float b, float c, float d) {
    asm volatile("red.relaxed.gpu.global.add.v4.f32 [%0], {%1,%2,%3,%4};" ::"l"(p), "f"(a), "f"(b), "f"(c), "f"(d) : "memory");
}
__device__ __forceinline__ void sts128(uint32_t a, uint4 v) {
    asm volatile("st.shared.v4.u32 [%0], {%1,%2,%3,%4};" ::"r"(a), "r"(v.x), "r"(v.y), "r"(v.z), "r"(v.w) : "memory");
}
__device__ __forceinline__ void sts128f(uint32_t a, float4 v) {
    asm volatile("st.shared.v4.f32 [%0], {%1,%2,%3,%4};" ::"r"(a), "f"(v.x), "f"(v.y), "f"(v.z), "f"(v.w) : "memory");
}
__device__ __forceinline__ void sts32f(uint32_t a, float v) { asm volatile("st.shared.f32 [%0], %1;" ::"r"(a), "f"(v) : "memory"); }
__device__ __forceinline__ uint4 lds128(uint32_t a) {
    uint4 v;
    asm volatile("ld.shared.v4.u32 {%0,%1,%2,%3}, [%4];" : "=r"(v.x), "=r"(v.y), "=r"(v.z), "=r"(v.w) : "r"(a) : "memory");
    return v;
}
__device__ __forceinline__ float4 lds128f(uint32_t a) {
    float4 v;
    asm volatile("ld.shared.v4.f32 {%0,%1,%2,%3}, [%4];" : "=f"(v.x), "=f"(v.y), "=f"(v.z), "=f"(v.w) : "r"(a) : "memory");
    return v;
}
__device__ __forceinline__ float2 lds64f(uint32_t a) {
    float2 v;
    asm volatile("ld.shared.v2.f32 {%0,%1}, [%2];" : "=f"(v.x), "=f"(v.y) : "r"(a) : "memory");
    return v;
}
__device__ __forceinline__ float bf_lo(uint32_t u) { return __uint_as_float(u << 16); }
__device__ __forceinline__ float bf_hi(uint32_t u) { return __uint_as_float(u & 0xffff0000u); }
__device__ __forceinline__ uint32_t pack_bf(float lo, float hi) {
    uint32_t r;
    asm("cvt.rn.bf16x2.f32 %0, %1, %2;" : "=r"(r) : "f"(hi), "f"(lo));
    return r;
}
__device__ __forceinline__ float tanh_fast(float x) {
    float r;
    asm volatile("tanh.approx.f32 %0, %1;" : "=f"(r) : "f"(x));
    return r;
}
__device__ __forceinline__ float silu_half(float h) { return fmaf(h, tanh_fast(h), h); }
__device__ __forceinline__ void ldsm4(uint32_t (&u)[4], uint32_t a) {
    asm volatile("ldmatrix.sync.aligned.m8n8.x4.shared.b16 {%0,%1,%2,%3}, [%4];"
                 : "=r"(u[0]), "=r"(u[1]), "=r"(u[2]), "=r"(u[3]) : "r"(a) : "memory");
}
__device__ __forceinline__ void ldsm4t(uint32_t (&u)[4], uint32_t a) {
    asm volatile("ldmatrix.sync.aligned.m8n8.x4.trans.shared.b16 {%0,%1,%2,%3}, [%4];"
                 : "=r"(u[0]), "=r"(u[1]), "=r"(u[2]), "=r"(u[3]) : "r"(a) : "memory");
}
__device__ __forceinline__ void stsm4(uint32_t a, uint32_t p0, uint32_t p1, uint32_t p2, uint32_t p3) {
    asm volatile("stmatrix.sync.aligned.m8n8.x4.shared.b16 [%0], {%1,%2,%3,%4};" ::"r"(a), "r"(p0), "r"(p1), "r"(p2), "r"(p3) : "memory");
}
__device__ __forceinline__ void stsm4t(uint32_t a, uint32_t p0, uint32_t p1, uint32_t p2, uint32_t p3) {
    asm volatile("stmatrix.sync.aligned.m8n8.x4.trans.shared.b16 [%0], {%1,%2,%3,%4};" ::"r"(a), "r"(p0), "r"(p1), "r"(p2), "r"(p3) : "memory");
}

#define R8(o) "+f"(d[o]), "+f"(d[o + 1]), "+f"(d[o + 2]), "+f"(d[o + 3]), "+f"(d[o + 4]), "+f"(d[o + 5]), "+f"(d[o + 6]), "+f"(d[o + 7])
template <uint32_t ALO, uint32_t BLO>
__device__ __forceinline__ void wgmma128(float (&d)[64]) {
    asm volatile(
        "wgmma.mma_async.sync.aligned.m64n128k16.f32.bf16.bf16 "
        "{%0,%1,%2,%3,%4,%5,%6,%7,%8,%9,%10,%11,%12,%13,%14,%15,%16,%17,%18,%19,%20,%21,%22,%23,%24,%25,%26,%27,%28,%29,%30,%31,"
        "%32,%33,%34,%35,%36,%37,%38,%39,%40,%41,%42,%43,%44,%45,%46,%47,%48,%49,%50,%51,%52,%53,%54,%55,%56,%57,%58,%59,%60,%61,%62,%63},"
        " %64, %65, 1, 1, 1, 0, 0;"
        : R8(0), R8(8), R8(16), R8(24), R8(32), R8(40), R8(48), R8(56)
        : "l"((8ull << 32) | ALO), "l"((8ull << 32) | BLO));
}
template <int S>
__device__ __forceinline__ void mma_stages(float (&d)[64], float2 (&e)[16], int conv, int tid, Scratch* gs) {
    constexpr uint32_t A = ((SM_ACT + ky_of(S >> 3) * ROW_BYTES + (S & 7) * 2 * CH_PITCH + 16) >> 4) | ((CH_PITCH >> 4) << 16);
    constexpr uint32_t B = ((SM_W + (S % NS) * STAGE_BYTES) >> 4) | ((2048 >> 4) << 16);
    mbar_wait(BAR(BAR_FULL + S), conv);
    if (S == 0 && tid == 0) TL(32 + conv * 24);
    asm volatile("wgmma.fence.sync.aligned;" ::: "memory");
    wgmma128<A, B>(d);
    wgmma128<A + 1, B + (STEP_BYTES >> 4)>(d);
    wgmma128<A + 2, B + 2 * (STEP_BYTES >> 4)>(d);
    asm volatile("wgmma.commit_group.sync.aligned;" ::: "memory");
    if (S >= LAG) {
        asm volatile("wgmma.wait_group.sync.aligned %0;" ::"n"(LAG) : "memory");
        if ((tid & 31) == 0) mbar_arrive(BAR(BAR_WEMPTY + (S + NS - LAG) % NS));
    }
    if (S == NSTAGE - 3 && conv == 0) {
        mbar_wait(BAR(BAR_EMB), 0);
#pragma unroll
        for (int j = 0; j < 16; j++) e[j] = lds64f(SM_EMB + j * 32 + (tid & 3) * 8);
    }
    if constexpr (S + 1 < NSTAGE) mma_stages<S + 1>(d, e, conv, tid, gs);
}

__device__ __forceinline__ void weight_block(const uint4 (&t)[5], uint32_t bounce, unsigned char* wt, int cta, int lane) {
    const uint32_t bw = bounce + (lane >> 4) * 1152 + (lane & 15) * 16;
#pragma unroll
    for (int k = 0; k < 4; k++) sts128(bw + k * 256, t[k]);
    if ((lane & 15) < 8) sts128(bw + 1024, t[4]);
    __syncwarp();
    if (lane < 16) {
        uint32_t v[36];
#pragma unroll
        for (int i = 0; i < 9; i++) {
            const uint4 q = lds128(bounce + (lane & 1) * 1152 + (lane >> 1) * 144 + i * 16);
            v[4 * i] = q.x; v[4 * i + 1] = q.y; v[4 * i + 2] = q.z; v[4 * i + 3] = q.w;
        }
        const int cc = (cta >> 6) * 8 + (lane >> 1);
        unsigned char* dst = wt + (cc >> 1) * STAGE_BYTES + (cc & 1) * 2048 + ((cta & 63) * 2 + (lane & 1)) * 16;
#pragma unroll
        for (int kyo = 0; kyo < 3; kyo++) {
#pragma unroll
            for (int kx = 0; kx < 3; kx++) {
                const int tap = ky_of(kyo) * 3 + kx;
                uint32_t o[4];
#pragma unroll
                for (int m = 0; m < 4; m++) {
                    const int i0 = 18 * m + tap, i1 = i0 + 9;
                    const uint32_t sel = ((i0 & 1) ? 0x32u : 0x10u) | ((i1 & 1) ? 0x7600u : 0x5400u);
                    o[m] = __byte_perm(v[i0 >> 1], v[i1 >> 1], sel);
                }
                *reinterpret_cast<uint4*>(dst + (kyo * 24 + kx) * STEP_BYTES) = make_uint4(o[0], o[1], o[2], o[3]);
            }
        }
    }
}
__device__ __forceinline__ uint32_t act2(uint32_t u, const float4& cf) {
    return pack_bf(silu_half(fmaf(bf_lo(u), cf.x, cf.z)), silu_half(fmaf(bf_hi(u), cf.y, cf.w)));
}
template <int FIRST, int N>
__device__ __forceinline__ void norm_batch(const uint32_t (&u)[4][4], const float4 (&cf)[8], uint32_t act, uint32_t bar, int lane, bool valid) {
    if (valid) {
#pragma unroll
        for (int t = FIRST; t < FIRST + N; t++)
            stsm4(act + t * 4 * CH_PITCH, act2(u[t][0], cf[2 * t]), act2(u[t][1], cf[2 * t]), act2(u[t][2], cf[2 * t + 1]), act2(u[t][3], cf[2 * t + 1]));
        fence_async_smem();
    }
    __syncwarp();
    if (lane < N) mbar_arrive(bar + 16 * (FIRST + lane));
}
__device__ __forceinline__ void fence_acc(float (&d)[64]) {
#pragma unroll
    for (int i = 0; i < 64; i++) asm volatile("" : "+f"(d[i])::"memory");
}
__device__ __forceinline__ void ld_unit(uint32_t (&u)[4], const uint4* p) {
    asm volatile("ld.relaxed.gpu.global.v4.u32 {%0,%1,%2,%3}, [%4];" : "=r"(u[0]), "=r"(u[1]), "=r"(u[2]), "=r"(u[3]) : "l"(p) : "memory");
}

__device__ __forceinline__ void halo_row(const char* xrow, uint32_t stg, int lane) {
    const int c = lane >> 3, sg = lane & 7;
    const char* p = xrow + c * (HW * HW * 2) + sg * 16;
    const uint32_t d0 = stg + c * 128 + ((sg ^ c) << 4), d1 = stg + (c + 4) * 128 + ((sg ^ (c + 4)) << 4);
#pragma unroll 4
    for (int i = 0; i < 16; i++) {
        asm volatile("cp.async.cg.shared.global [%0], [%1], 16;" ::"r"(d0 + i * 1024), "l"(p + i * (8 * HW * HW * 2)) : "memory");
        asm volatile("cp.async.cg.shared.global [%0], [%1], 16;" ::"r"(d1 + i * 1024), "l"(p + i * (8 * HW * HW * 2) + 4 * HW * HW * 2) : "memory");
    }
}

__global__ void __launch_bounds__(NTHREADS, 1)
resblock_kernel(const __nv_bfloat16* __restrict__ x, const __nv_bfloat16* __restrict__ w1,
                const __nv_bfloat16* __restrict__ t_emb, const __nv_bfloat16* __restrict__ g1,
                const __nv_bfloat16* __restrict__ be1, const __nv_bfloat16* __restrict__ w_emb,
                const __nv_bfloat16* __restrict__ g2, const __nv_bfloat16* __restrict__ be2,
                const __nv_bfloat16* __restrict__ w2, __nv_bfloat16* __restrict__ out, Scratch* __restrict__ gs) {
    const unsigned clk0 = clock32();
    const int tid = threadIdx.x, warp = tid >> 5, lane = tid & 31;
    const int cta = blockIdx.x, b = cta >> 6, r = cta & 63;

    const uint32_t woff = ((2 * r + (lane >> 4)) * C + b * 64) * 18 + (lane & 15) * 16;
    const int c0 = (warp - 8) * 16 + (lane >> 3), seg = lane & 7;
    const char* src = (warp == 0) ? reinterpret_cast<const char*>(w1) + woff
                                  : reinterpret_cast<const char*>(x) + (uint32_t)(((b * C + c0) * HW + r) * HW * 2 + seg * 16);
    uint4 v[5];
    if (warp == 0 || warp >= 8) {
        const uint32_t stride = (warp == 0) ? 256 : 4 * HW * HW * 2;
        if (warp != 0) { while (clock32() - clk0 < XDELAY) {} }
#pragma unroll
        for (int k = 0; k < 4; k++) v[k] = __ldg(reinterpret_cast<const uint4*>(src + k * stride));
        if (tid < 32 && (lane & 15) < 8) v[4] = __ldg(reinterpret_cast<const uint4*>(src + 1024));
    }
    if (warp == 0) {
        weight_block(v, SM_BNC, gs->wt, cta, lane);
        if (r == 0) {
            if (lane < 16) gs->acc[(NB + b) * 32 + lane] = 0.f;
            *reinterpret_cast<float4*>(&gs->emb[b * C + lane * 4]) = make_float4(0.f, 0.f, 0.f, 0.f);
        }
        __syncwarp();
        if (lane == 0) TL(4);
        if (lane < 2) asm volatile("red.release.gpu.global.add.u32 [%0], 1;" ::"l"(&gs->wcnt[lane * 32]) : "memory");
        if (lane == 0) TL(5);
    }

    if (warp >= 8) {
        const int nw = warp - 8;
        {
            float s = 0.f, q = 0.f, s2 = 0.f, q2 = 0.f;
#pragma unroll
            for (int i = 0; i < 4; i++) {
                const uint32_t u[4] = {v[i].x, v[i].y, v[i].z, v[i].w};
#pragma unroll
                for (int k = 0; k < 4; k++) {
                    const float lo = bf_lo(u[k]), hi = bf_hi(u[k]);
                    s += lo; q = fmaf(lo, lo, q);
                    s2 += hi; q2 = fmaf(hi, hi, q2);
                }
            }
            s += s2; q += q2;
            float give = (lane < 16) ? q : s, keep = (lane < 16) ? s : q;
            keep += __shfl_xor_sync(0xffffffffu, give, 16);
            if (tid == 256) TL(2);
#pragma unroll
            for (int m = 8; m >= 1; m >>= 1) keep += __shfl_xor_sync(0xffffffffu, keep, m);
            if ((lane & 15) == 0) sts32f(SM_RED + (nw * 2 + (lane >> 4)) * 4, keep);
            bar_sync(3, 256 + 96);
            if (tid < 256 + 4) {
                const float4 p = lds128f(SM_RED + lane * 16);
                red_add4(&gs->acc[b * 32 + lane * 4], 1.f, p.x + p.z, p.y + p.w, 1.f);
            }
            if (tid == 256) TL(3);
#pragma unroll
            for (int i = 0; i < 4; i++) sts128(SM_XOWN + c0 * 128 + i * 512 + ((seg ^ ((c0 + 4 * i) & 7)) << 4), v[i]);
            bar_sync(4, 256);
        }
        const int par = nw >> 2, wq = nw & 3;
        const uint32_t act_off = SM_ACT + (par * 2 + (lane >> 4)) * CH_PITCH + (2 + wq * 16 + (lane & 15)) * 16;
        const uint32_t stg_off = (par * 16 + (lane >> 4) * 8 + (lane & 7)) * 128 + (((2 * wq + ((lane >> 3) & 1)) ^ (lane & 7)) << 4);
        const uint32_t fbar = BAR(BAR_FULL) + 8 * par;
#pragma unroll 1
        for (int conv = 0; conv < 2; conv++) {
            uint32_t u[4][4], hu[2][4][4];
            float4 cf[8];
            if (conv == 0) {
#pragma unroll
                for (int i = 0; i < 4; i++) ldsm4t(u[i], SM_XOWN + stg_off + i * 4096);
                mbar_wait(BAR(BAR_XH), 0);
#pragma unroll
                for (int i = 0; i < 8; i++) ldsm4t(hu[i >> 2][i & 3], SM_XH + stg_off + (i >> 2) * 16384 + (i & 3) * 4096);
                fence_async_smem();
                __syncwarp();
                if (lane == 0) mbar_arrive(BAR(BAR_XFREE));
            } else {
                mbar_wait(BAR(BAR_HW), 0);
#pragma unroll
                for (int i = 0; i < 4; i++) ldsm4(u[i], act_off + ROW_BYTES + i * 4 * CH_PITCH);
            }
            const uint4* hp[2];
            hp[0] = gs->h + (size_t)(r != 0 ? cta - 1 : cta) * 1024 + nw * 32 + lane;
            hp[1] = gs->h + (size_t)(r != HW - 1 ? cta + 1 : cta) * 1024 + nw * 32 + lane;
            const uint32_t cfa = SM_COEF + par * 128 + (lane & 3) * 16;
            mbar_wait(BAR(BAR_STATS), conv);
            if (tid == 256) TL(22 + conv * 4);
            cf[0] = lds128f(cfa); cf[1] = lds128f(cfa + 64);
            norm_batch<0, 1>(u, cf, act_off + ROW_BYTES, fbar, lane, true);
            if (tid == 256) TL(8 + conv * 8);
#pragma unroll
            for (int i = 2; i < 8; i++) cf[i] = lds128f(cfa + (i >> 1) * 256 + (i & 1) * 64);
            if (conv == 1) {
#pragma unroll
                for (int i = 0; i < 8; i++) ld_unit(hu[i >> 2][i & 3], hp[i >> 2] + (i & 3) * 256);
            }
            norm_batch<1, 1>(u, cf, act_off + ROW_BYTES, fbar, lane, true);
            norm_batch<2, 2>(u, cf, act_off + ROW_BYTES, fbar, lane, true);
            if (tid == 256) TL(24 + conv * 4);
            if (conv == 1) {
                unsigned it = 0;
                while (true) {
                    bool ok = true;
#pragma unroll
                    for (int i = 0; i < 32; i++) ok = ok && hu[i >> 4][(i >> 2) & 3][i & 3] != 0xffffffffu;
                    if (__all_sync(0xffffffffu, ok) || ++it > SPIN_LIMIT) break;
#pragma unroll
                    for (int i = 0; i < 8; i++) ld_unit(hu[i >> 2][i & 3], hp[i >> 2] + (i & 3) * 256);
                }
            }
            norm_batch<0, 4>(hu[0], cf, act_off, fbar + 64, lane, r != 0);
            norm_batch<0, 4>(hu[1], cf, act_off + 2 * ROW_BYTES, fbar + 128, lane, r != HW - 1);
            if (tid == 256) TL(23 + conv * 4);
        }
    } else if (warp < 4) {
        const int wq = warp;
        if (wq != 0) {
            const int t = tid - 32;
            if (t == 95) TLG(1);
            if (t < NBAR) {
                const int cnt = t < BAR_WEMPTY ? 5 : (t <= BAR_HW ? 4 : (t == BAR_XH ? 32 : (t == BAR_XFREE ? 8 : 1)));
                mbar_init(BAR(0) + 8 * t, cnt);
            }
            fence_async_smem();
            bar_arrive(0, 96 + 128);
            bar_arrive(3, 256 + 96);
            const uint4 z = make_uint4(0, 0, 0, 0);
            sts128(SM_ACT + (t >> 1) * CH_PITCH + (t & 1) * 16, z);
            if (t < 2) sts128(SM_ACT + 3 * ROW_BYTES + t * 16, z);
            if (r == 0 || r == HW - 1) {
                for (int i = t; i < ROW_BYTES / 16; i += 96) sts128(SM_ACT + (r == 0 ? 0 : 2 * ROW_BYTES) + i * 16, z);
            }
            fence_async_smem();
        }
        bar_sync(2, 128);

        float d[64];
#pragma unroll
        for (int i = 0; i < 64; i++) d[i] = 0.f;
#pragma unroll 1
        for (int conv = 0; conv < 2; conv++) {
            fence_acc(d);
            float2 ev[16];
            mma_stages<0>(d, ev, conv, tid, gs);
            asm volatile("wgmma.wait_group.sync.aligned 0;" ::: "memory");
            fence_acc(d);
            if (tid == 0) TL(10 + conv * 8);
            if (conv == 1) break;

            float st[8];
#pragma unroll
            for (int g = 0; g < 4; g++) {
                float s = 0.f, q = 0.f, s2 = 0.f, q2 = 0.f;
#pragma unroll
                for (int jj = 0; jj < 4; jj++) {
                    const int j = g * 4 + jj;
                    const float2 e = ev[j];
                    d[4 * j + 0] += e.x; d[4 * j + 1] += e.y; d[4 * j + 2] += e.x; d[4 * j + 3] += e.y;
                    s += d[4 * j + 0]; q = fmaf(d[4 * j + 0], d[4 * j + 0], q);
                    s2 += d[4 * j + 1]; q2 = fmaf(d[4 * j + 1], d[4 * j + 1], q2);
                    s += d[4 * j + 2]; q = fmaf(d[4 * j + 2], d[4 * j + 2], q);
                    s2 += d[4 * j + 3]; q2 = fmaf(d[4 * j + 3], d[4 * j + 3], q2);
                }
                st[2 * g] = s + s2; st[2 * g + 1] = q + q2;
            }
            {
                const bool h16 = lane & 16, h8 = lane & 8, h4 = lane & 4;
                float a[4];
#pragma unroll
                for (int i = 0; i < 4; i++) {
                    float give = h16 ? st[i] : st[i + 4], keep = h16 ? st[i + 4] : st[i];
                    a[i] = keep + __shfl_xor_sync(0xffffffffu, give, 16);
                }
                float c2[2];
#pragma unroll
                for (int i = 0; i < 2; i++) {
                    float give = h8 ? a[i] : a[i + 2], keep = h8 ? a[i + 2] : a[i];
                    c2[i] = keep + __shfl_xor_sync(0xffffffffu, give, 8);
                }
                float give = h4 ? c2[0] : c2[1], keep = h4 ? c2[1] : c2[0];
                float t = keep + __shfl_xor_sync(0xffffffffu, give, 4);
                t += __shfl_xor_sync(0xffffffffu, t, 2);
                t += __shfl_xor_sync(0xffffffffu, t, 1);
                if ((lane & 3) == 0) sts32f(SM_RED + ((lane >> 2) * 4 + wq) * 4, t);
                bar_sync(2, 128);
                if (tid < 4) {
                    const float4 p = lds128f(SM_RED + tid * 32), p2 = lds128f(SM_RED + tid * 32 + 16);
                    red_add4(&gs->acc[(NB + b) * 32 + tid * 4], 1.f, (p.x + p.y) + (p.z + p.w), (p2.x + p2.y) + (p2.z + p2.w), 1.f);
                }
                if (tid == 0) TL(11);
                if (lane < LAG) mbar_arrive(BAR(BAR_WEMPTY + (NSTAGE - LAG) % NS) + 8 * lane);
            }
            const uint32_t hbase = SM_ACT + ROW_BYTES + (lane >> 4) * CH_PITCH + (2 + wq * 16 + (lane & 15)) * 16;
            uint4* hg = gs->h + cta * 1024 + tid;
#pragma unroll
            for (int kc = 0; kc < 8; kc++) {
                const uint4 p = make_uint4(pack_bf(d[8 * kc + 0], d[8 * kc + 1]), pack_bf(d[8 * kc + 2], d[8 * kc + 3]),
                                           pack_bf(d[8 * kc + 4], d[8 * kc + 5]), pack_bf(d[8 * kc + 6], d[8 * kc + 7]));
                stsm4(hbase + kc * 2 * CH_PITCH, p.x, p.y, p.z, p.w);
                hg[kc * 128] = p;
            }
            __syncwarp();
            if (lane == 0) mbar_arrive(BAR(BAR_HW));
            if (tid == 0) TL(12);
            const uint32_t xbase = SM_XOWN + ((lane >> 4) * 8 + (lane & 7)) * 128 + (((2 * wq + ((lane >> 3) & 1)) ^ (lane & 7)) << 4);
#pragma unroll
            for (int kc = 0; kc < 8; kc++) {
                uint32_t p[4];
                ldsm4t(p, xbase + kc * 2048);
#pragma unroll
                for (int i = 0; i < 4; i++) { d[8 * kc + 2 * i] = bf_lo(p[i]); d[8 * kc + 2 * i + 1] = bf_hi(p[i]); }
            }
        }
        {
            const uint32_t obase = SM_W + ((lane >> 4) * 8 + (lane & 7)) * OUT_PITCH + (wq * 16 + ((lane >> 3) & 1) * 8) * 2;
#pragma unroll
            for (int kc = 0; kc < 8; kc++) {
                stsm4t(obase + kc * 16 * OUT_PITCH, pack_bf(d[8 * kc + 0], d[8 * kc + 1]), pack_bf(d[8 * kc + 2], d[8 * kc + 3]),
                       pack_bf(d[8 * kc + 4], d[8 * kc + 5]), pack_bf(d[8 * kc + 6], d[8 * kc + 7]));
            }
            bar_sync(2, 128);
            const int oc0 = tid >> 3;
            __nv_bfloat16* dst = out + ((size_t)(b * C + oc0) * HW + r) * HW + seg * 8;
#pragma unroll
            for (int i = 0; i < 8; i++)
                *reinterpret_cast<uint4*>(dst + (size_t)i * 16 * HW * HW) = lds128(SM_W + (oc0 + 16 * i) * OUT_PITCH + seg * 16);
            if (tid == 0) { TL(20); TLG(21); }
        }
    } else if (warp < 6) {
        bar_sync(0, 96 + 128);
        if (warp == 5) {
            while (clock32() - clk0 < HDELAY) {}
            const char* xr = reinterpret_cast<const char*>(x) + (uint32_t)((b * C * HW + r) * HW * 2);
            if (r != 0) halo_row(xr - HW * 2, SM_XH, lane);
            if (r != HW - 1) halo_row(xr + HW * 2, SM_XH + 16384, lane);
            asm volatile("cp.async.mbarrier.arrive.noinc.shared::cta.b64 [%0];" ::"r"(BAR(BAR_XH)) : "memory");
#pragma unroll 4
            for (int i = 0; i < 32; i++) gs->h[cta * 1024 + i * 32 + lane] = make_uint4(~0u, ~0u, ~0u, ~0u);
            bar_arrive(6, 64);
        } else {
            while (clock32() - clk0 < W2DELAY) {}
            const char* w2s = reinterpret_cast<const char*>(w2) + woff;
#pragma unroll
            for (int k = 0; k < 4; k++) v[k] = __ldg(reinterpret_cast<const uint4*>(w2s + k * 256));
            if ((lane & 15) < 8) v[4] = __ldg(reinterpret_cast<const uint4*>(w2s + 1024));
            const uint2* wsrc = reinterpret_cast<const uint2*>(w_emb + (size_t)r * 12 * C) + lane;
            uint2 wv[12];
#pragma unroll
            for (int i = 0; i < 12; i++) wv[i] = __ldg(wsrc + i * (C / 4));
            float tv = 0.f;
            if (lane < 12) tv = __bfloat162float(t_emb[b * E + r * 12 + lane]);
            weight_block(v, SM_BNC + 2304, gs->wt + NSTAGE * STAGE_BYTES, cta, lane);
            const float sv = silu_half(0.5f * tv);
            float e0 = 0.f, e1 = 0.f, e2 = 0.f, e3 = 0.f;
#pragma unroll
            for (int i = 0; i < 12; i++) {
                const float sx = __shfl_sync(0xffffffffu, sv, i);
                e0 = fmaf(sx, bf_lo(wv[i].x), e0); e1 = fmaf(sx, bf_hi(wv[i].x), e1);
                e2 = fmaf(sx, bf_lo(wv[i].y), e2); e3 = fmaf(sx, bf_hi(wv[i].y), e3);
            }
            mbar_wait(BAR(BAR_WACQ), 0);
            red_add4(&gs->emb[b * C + lane * 4], e0, e1, e2, e3);
            bar_sync(6, 64);
            if (lane == 0) TL(13);
            if (lane < 2) asm volatile("red.release.gpu.global.add.u32 [%0], 1;" ::"l"(&gs->wcnt[(NB + lane) * 32]) : "memory");
            if (lane == 0) TL(14);
            unsigned it = 0;
            while (ld_relaxed(&gs->wcnt[(NB + b) * 32]) < (unsigned)NCTA && ++it < SPIN_LIMIT) {}
            fence_acquire();
            sts128(SM_EMB + lane * 16, ld_relaxed_v4(&gs->emb[b * C + lane * 4]));
            __syncwarp();
            if (lane == 0) { mbar_arrive(BAR(BAR_EMB)); TL(19); }
        }
    } else if (warp == 6) {
        bar_sync(0, 96 + 128);
        unsigned it = 0;
        while (ld_relaxed(&gs->wcnt[b * 32]) < (unsigned)NCTA && ++it < SPIN_LIMIT) {}
        fence_acquire();
        fence_async_global();
        if (lane == 0) { mbar_arrive(BAR(BAR_WACQ)); TL(6); }
        const unsigned char* wsrc = gs->wt;
#pragma unroll 1
        for (int round = 0; round < 2 * NSTAGE / NS; round++) {
            if (round == NSTAGE / NS) { mbar_wait(BAR(BAR_EMB), 0); fence_async_global(); }
            const uint32_t full = BAR(BAR_FULL) + 8 * NS * (round >= NSTAGE / NS ? round - NSTAGE / NS : round);
#pragma unroll
            for (int slot = 0; slot < NS; slot++) {
                if (slot == 9 && round == 0) mbar_wait(BAR(BAR_XFREE), 0);
                mbar_wait(BAR(BAR_WEMPTY + slot), (round & 1) ^ 1);
                if (elect_one()) {
                    mbar_expect(full + 8 * slot, STAGE_BYTES);
                    bulk_g2s(SM_W + slot * STAGE_BYTES, wsrc + slot * STAGE_BYTES, STAGE_BYTES, full + 8 * slot);
                }
            }
            wsrc += NS * STAGE_BYTES;
        }
    } else {
        const uint2 ga1 = __ldg(reinterpret_cast<const uint2*>(g1) + lane), bt1 = __ldg(reinterpret_cast<const uint2*>(be1) + lane);
        const uint2 ga2 = __ldg(reinterpret_cast<const uint2*>(g2) + lane), bt2 = __ldg(reinterpret_cast<const uint2*>(be2) + lane);
        bar_sync(0, 96 + 128);
#pragma unroll 1
        for (int conv = 0; conv < 2; conv++) {
            if (conv == 1) mbar_wait(BAR(BAR_EMB), 0);
            const float* asrc = &gs->acc[(conv * NB + b) * 32 + (lane >> 3) * 4];
            uint4 f;
            unsigned it = 0;
            while (true) {
                f = ld_relaxed_v4(asrc);
                const bool ok = (f.x == 0x42800000u) & (f.w == 0x42800000u);
                if (__all_sync(0xffffffffu, ok) || ++it > SPIN_LIMIT) break;
            }
            if (lane == 0) TL(7 + conv * 8);
            const float inv_n = 1.0f / (32.0f * HW * HW);
            const float mean = __uint_as_float(f.y) * inv_n;
            const float var = fmaxf(fmaf(-mean, mean, __uint_as_float(f.z) * inv_n), 0.f);
            const float rs = 0.5f * rsqrtf(var + 1e-5f);
            const uint2 ga = conv ? ga2 : ga1, bt = conv ? bt2 : bt1;
            float4 k0, k1;
            k0.x = rs * bf_lo(ga.x); k0.y = rs * bf_hi(ga.x); k1.x = rs * bf_lo(ga.y); k1.y = rs * bf_hi(ga.y);
            k0.z = fmaf(-mean, k0.x, 0.5f * bf_lo(bt.x)); k0.w = fmaf(-mean, k0.y, 0.5f * bf_hi(bt.x));
            k1.z = fmaf(-mean, k1.x, 0.5f * bf_lo(bt.y)); k1.w = fmaf(-mean, k1.y, 0.5f * bf_hi(bt.y));
            sts128f(SM_COEF + lane * 32, k0);
            sts128f(SM_COEF + lane * 32 + 16, k1);
            __syncwarp();
            if (lane == 0) mbar_arrive(BAR(BAR_STATS));
        }
        if (r == 0) {
            if (lane < 16) gs->acc[b * 32 + lane] = 0.f;
            if (lane < 2) gs->wcnt[(lane * NB + b) * 32] = 0;
        }
    }
}

}

extern "C" void kernel_launch(void* const* d_in, const int* in_sizes, int n_in, void* d_out, int out_size) {
    (void)in_sizes; (void)n_in; (void)out_size;
    static Scratch* gs = nullptr;
    if (!gs) {
        cudaFuncSetAttribute(resblock_kernel, cudaFuncAttributeMaxDynamicSharedMemorySize, SM_TOTAL);
        cudaGetSymbolAddress((void**)&gs, g_scratch);
    }
    resblock_kernel<<<NCTA, NTHREADS, SM_TOTAL>>>(
        (const __nv_bfloat16*)d_in[0], (const __nv_bfloat16*)d_in[4], (const __nv_bfloat16*)d_in[1],
        (const __nv_bfloat16*)d_in[2], (const __nv_bfloat16*)d_in[3], (const __nv_bfloat16*)d_in[5],
        (const __nv_bfloat16*)d_in[6], (const __nv_bfloat16*)d_in[7], (const __nv_bfloat16*)d_in[8],
        (__nv_bfloat16*)d_out, gs);
}
```

```cpp
#include <cuda_runtime.h>
#include <cuda_bf16.h>
#include <stdint.h>

namespace {

constexpr int C = 128, HW = 64, NB = 2, E = 768;
constexpr int NCTA = NB * HW;
constexpr int NTHREADS = 16 * 32;
constexpr int CH_PITCH = 66 * 16;
constexpr int ROW_BYTES = 16 * CH_PITCH;
constexpr int STEP_BYTES = 4096;
constexpr int STAGE_BYTES = 3 * STEP_BYTES;
constexpr int NSTAGE = 24;
constexpr int NS = 12;
constexpr int LAG = 1;
#define XDELAY 900
#define HDELAY 1500
#define W2DELAY 2800

constexpr uint32_t SMEM_BASE = 0x400;
constexpr uint32_t SM_ACT = SMEM_BASE;
constexpr uint32_t SM_XOWN = SM_ACT + 3 * ROW_BYTES + 128;
constexpr uint32_t SM_W = SM_XOWN + 16384;
constexpr uint32_t SM_XH = SM_W + 9 * STAGE_BYTES;
constexpr uint32_t SM_COEF = SM_W + NS * STAGE_BYTES;
constexpr uint32_t SM_EMB = SM_COEF + 1024;
constexpr uint32_t SM_RED = SM_EMB + 512;
constexpr uint32_t SM_BNC = SM_RED + 128;
constexpr uint32_t SM_BAR = SM_BNC + 2 * 2304;
constexpr int BAR_FULL = 0, BAR_WEMPTY = NSTAGE, BAR_HW = BAR_WEMPTY + NS, BAR_STATS = BAR_HW + 1,
              BAR_EMB = BAR_STATS + 1, BAR_WACQ = BAR_EMB + 1, BAR_XH = BAR_WACQ + 1, BAR_XFREE = BAR_XH + 1, NBAR = BAR_XFREE + 1;
constexpr int SM_TOTAL = SM_BAR + NBAR * 8 - SMEM_BASE;
static_assert(SM_TOTAL <= 232448, "smem");
static_assert(NBAR <= 96, "barrier init");
constexpr int OUT_PITCH = 144;
__host__ __device__ constexpr uint32_t BAR(int i) { return SM_BAR + 8 * i; }
__host__ __device__ constexpr int ky_of(int kyo) { return kyo == 0 ? 1 : (kyo == 1 ? 0 : 2); }

constexpr unsigned SPIN_LIMIT = 1u << 16;

struct Scratch {
    float acc[2 * NB * 32];
    unsigned wcnt[2 * NB * 32];
    float emb[NB * C];
    unsigned char wt[2 * NSTAGE * STAGE_BYTES];
    uint4 h[NCTA * 1024];
};
__device__ __align__(1024) Scratch g_scratch;
#define TL(i) do {} while (0)
#define TLG(i) do {} while (0)

__device__ __forceinline__ unsigned clock32() { unsigned c; asm volatile("mov.u32 %0, %%clock;" : "=r"(c)); return c; }
__device__ __forceinline__ void mbar_init(uint32_t bar, int cnt) {
    asm volatile("mbarrier.init.shared::cta.b64 [%0], %1;" ::"r"(bar), "r"(cnt) : "memory");
}
__device__ __forceinline__ void mbar_arrive(uint32_t bar) {
    asm volatile("mbarrier.arrive.shared::cta.b64 _, [%0];" ::"r"(bar) : "memory");
}
__device__ __forceinline__ void mbar_expect(uint32_t bar, uint32_t bytes) {
    asm volatile("mbarrier.arrive.expect_tx.shared::cta.b64 _, [%0], %1;" ::"r"(bar), "r"(bytes) : "memory");
}
__device__ __forceinline__ bool mbar_try(uint32_t bar, uint32_t par) {
    uint32_t ok;
    asm volatile("{\n.reg .pred p;\nmbarrier.try_wait.parity.shared::cta.b64 p, [%1], %2;\nselp.u32 %0, 1, 0, p;\n}"
                 : "=r"(ok) : "r"(bar), "r"(par) : "memory");
    return ok;
}
__device__ __forceinline__ bool mbar_test(uint32_t bar, uint32_t par) {
    uint32_t ok;
    asm volatile("{\n.reg .pred p;\nmbarrier.test_wait.parity.shared::cta.b64 p, [%1], %2;\nselp.u32 %0, 1, 0, p;\n}"
                 : "=r"(ok) : "r"(bar), "r"(par) : "memory");
    return ok;
}
__device__ __forceinline__ void mbar_wait(uint32_t bar, uint32_t par) {
    unsigned it = 0;
#pragma unroll 1
    while (!mbar_try(bar, par) && ++it < SPIN_LIMIT) {}
}
__device__ __forceinline__ bool elect_one() {
    uint32_t p;
    asm volatile("{\n.reg .pred p;\nelect.sync _|p, 0xffffffff;\nselp.u32 %0, 1, 0, p;\n}" : "=r"(p));
    return p;
}
__device__ __forceinline__ void fence_async_smem() { asm volatile("fence.proxy.async.shared::cta;" ::: "memory"); }
__device__ __forceinline__ void fence_async_global() { asm volatile("fence.proxy.async.global;" ::: "memory"); }
__device__ __forceinline__ void fence_acquire() { asm volatile("fence.acquire.gpu;" ::: "memory"); }
__device__ __forceinline__ void bar_sync(int id, int n) { asm volatile("bar.sync %0, %1;" ::"r"(id), "r"(n) : "memory"); }
__device__ __forceinline__ void bar_arrive(int id, int n) { asm volatile("bar.arrive %0, %1;" ::"r"(id), "r"(n) : "memory"); }
__device__ __forceinline__ void bulk_g2s(uint32_t dst, const void* src, uint32_t bytes, uint32_t bar) {
    asm volatile("cp.async.bulk.shared::cluster.global.mbarrier::complete_tx::bytes [%0], [%1], %2, [%3];"
                 ::"r"(dst), "l"(src), "r"(bytes), "r"(bar) : "memory");
}
__device__ __forceinline__ uint4 ld_relaxed_v4(const void* p) {
    uint4 v;
    asm volatile("ld.relaxed.gpu.global.v4.u32 {%0,%1,%2,%3}, [%4];" : "=r"(v.x), "=r"(v.y), "=r"(v.z), "=r"(v.w) : "l"(p) : "memory");
    return v;
}
__device__ __forceinline__ unsigned ld_relaxed(const void* p) {
    unsigned v;
    asm volatile("ld.relaxed.gpu.global.u32 %0, [%1];" : "=r"(v) : "l"(p) : "memory");
    return v;
}
__device__ __forceinline__ void red_add4(float* p, float a, float b, float c, float d) {
    asm volatile("red.relaxed.gpu.global.add.v4.f32 [%0], {%1,%2,%3,%4};" ::"l"(p), "f"(a), "f"(b), "f"(c), "f"(d) : "memory");
}
__device__ __forceinline__ void sts128(uint32_t a, uint4 v) {
    asm volatile("st.shared.v4.u32 [%0], {%1,%2,%3,%4};" ::"r"(a), "r"(v.x), "r"(v.y), "r"(v.z), "r"(v.w) : "memory");
}
__device__ __forceinline__ void sts128f(uint32_t a, float4 v) {
    asm volatile("st.shared.v4.f32 [%0], {%1,%2,%3,%4};" ::"r"(a), "f"(v.x), "f"(v.y), "f"(v.z), "f"(v.w) : "memory");
}
__device__ __forceinline__ void sts32f(uint32_t a, float v) { asm volatile("st.shared.f32 [%0], %1;" ::"r"(a), "f"(v) : "memory"); }
__device__ __forceinline__ uint4 lds128(uint32_t a) {
    uint4 v;
    asm volatile("ld.shared.v4.u32 {%0,%1,%2,%3}, [%4];" : "=r"(v.x), "=r"(v.y), "=r"(v.z), "=r"(v.w) : "r"(a) : "memory");
    return v;
}
__device__ __forceinline__ float4 lds128f(uint32_t a) {
    float4 v;
    asm volatile("ld.shared.v4.f32 {%0,%1,%2,%3}, [%4];" : "=f"(v.x), "=f"(v.y), "=f"(v.z), "=f"(v.w) : "r"(a) : "memory");
    return v;
}
__device__ __forceinline__ float2 lds64f(uint32_t a) {
    float2 v;
    asm volatile("ld.shared.v2.f32 {%0,%1}, [%2];" : "=f"(v.x), "=f"(v.y) : "r"(a) : "memory");
    return v;
}
__device__ __forceinline__ float bf_lo(uint32_t u) { return __uint_as_float(u << 16); }
__device__ __forceinline__ float bf_hi(uint32_t u) { return __uint_as_float(u & 0xffff0000u); }
__device__ __forceinline__ uint32_t pack_bf(float lo, float hi) {
    uint32_t r;
    asm("cvt.rn.bf16x2.f32 %0, %1, %2;" : "=r"(r) : "f"(hi), "f"(lo));
    return r;
}
__device__ __forceinline__ float tanh_fast(float x) {
    float r;
    asm volatile("tanh.approx.f32 %0, %1;" : "=f"(r) : "f"(x));
    return r;
}
__device__ __forceinline__ float silu_half(float h) { return fmaf(h, tanh_fast(h), h); }
__device__ __forceinline__ void ldsm4(uint32_t (&u)[4], uint32_t a) {
    asm volatile("ldmatrix.sync.aligned.m8n8.x4.shared.b16 {%0,%1,%2,%3}, [%4];"
                 : "=r"(u[0]), "=r"(u[1]), "=r"(u[2]), "=r"(u[3]) : "r"(a) : "memory");
}
__device__ __forceinline__ void ldsm4t(uint32_t (&u)[4], uint32_t a) {
    asm volatile("ldmatrix.sync.aligned.m8n8.x4.trans.shared.b16 {%0,%1,%2,%3}, [%4];"
                 : "=r"(u[0]), "=r"(u[1]), "=r"(u[2]), "=r"(u[3]) : "r"(a) : "memory");
}
__device__ __forceinline__ void stsm4(uint32_t a, uint32_t p0, uint32_t p1, uint32_t p2, uint32_t p3) {
    asm volatile("stmatrix.sync.aligned.m8n8.x4.shared.b16 [%0], {%1,%2,%3,%4};" ::"r"(a), "r"(p0), "r"(p1), "r"(p2), "r"(p3) : "memory");
}
__device__ __forceinline__ void stsm4t(uint32_t a, uint32_t p0, uint32_t p1, uint32_t p2, uint32_t p3) {
    asm volatile("stmatrix.sync.aligned.m8n8.x4.trans.shared.b16 [%0], {%1,%2,%3,%4};" ::"r"(a), "r"(p0), "r"(p1), "r"(p2), "r"(p3) : "memory");
}

#define R8(o) "+f"(d[o]), "+f"(d[o + 1]), "+f"(d[o + 2]), "+f"(d[o + 3]), "+f"(d[o + 4]), "+f"(d[o + 5]), "+f"(d[o + 6]), "+f"(d[o + 7])
template <uint32_t ALO, uint32_t BLO>
__device__ __forceinline__ void wgmma128(float (&d)[64]) {
    asm volatile(
        "wgmma.mma_async.sync.aligned.m64n128k16.f32.bf16.bf16 "
        "{%0,%1,%2,%3,%4,%5,%6,%7,%8,%9,%10,%11,%12,%13,%14,%15,%16,%17,%18,%19,%20,%21,%22,%23,%24,%25,%26,%27,%28,%29,%30,%31,"
        "%32,%33,%34,%35,%36,%37,%38,%39,%40,%41,%42,%43,%44,%45,%46,%47,%48,%49,%50,%51,%52,%53,%54,%55,%56,%57,%58,%59,%60,%61,%62,%63},"
        " %64, %65, 1, 1, 1, 0, 0;"
        : R8(0), R8(8), R8(16), R8(24), R8(32), R8(40), R8(48), R8(56)
        : "l"((8ull << 32) | ALO), "l"((8ull << 32) | BLO));
}
template <int S>
__device__ __forceinline__ void mma_stages(float (&d)[64], float2 (&e)[16], int conv, int tid, Scratch* gs) {
    constexpr uint32_t A = ((SM_ACT + ky_of(S >> 3) * ROW_BYTES + (S & 7) * 2 * CH_PITCH + 16) >> 4) | ((CH_PITCH >> 4) << 16);
    constexpr uint32_t B = ((SM_W + (S % NS) * STAGE_BYTES) >> 4) | ((2048 >> 4) << 16);
    if (S == 0) mbar_wait(BAR(BAR_FULL), conv);
    bool next_ok = true;
    if (S + 1 < NSTAGE) next_ok = mbar_test(BAR(BAR_FULL + S + 1), conv);
    if (S == 0 && tid == 0) TL(32 + conv * 24);
    asm volatile("wgmma.fence.sync.aligned;" ::: "memory");
    wgmma128<A, B>(d);
    wgmma128<A + 1, B + (STEP_BYTES >> 4)>(d);
    wgmma128<A + 2, B + 2 * (STEP_BYTES >> 4)>(d);
    asm volatile("wgmma.commit_group.sync.aligned;" ::: "memory");
    if (S >= LAG) {
        asm volatile("wgmma.wait_group.sync.aligned %0;" ::"n"(LAG) : "memory");
        if ((tid & 31) == 0) mbar_arrive(BAR(BAR_WEMPTY + (S + NS - LAG) % NS));
    }
    if (!next_ok) mbar_wait(BAR(BAR_FULL + S + 1), conv);
    if (S == NSTAGE - 1 && conv == 0) {
        mbar_wait(BAR(BAR_EMB), 0);
#pragma unroll
        for (int j = 0; j < 16; j++) e[j] = lds64f(SM_EMB + j * 32 + (tid & 3) * 8);
    }
    if constexpr (S + 1 < NSTAGE) mma_stages<S + 1>(d, e, conv, tid, gs);
}

__device__ __forceinline__ void weight_block(const uint4 (&t)[5], uint32_t bounce, unsigned char* wt, int cta, int lane) {
    const uint32_t bw = bounce + (lane >> 4) * 1152 + (lane & 15) * 16;
#pragma unroll
    for (int k = 0; k < 4; k++) sts128(bw + k * 256, t[k]);
    if ((lane & 15) < 8) sts128(bw + 1024, t[4]);
    __syncwarp();
    if (lane < 16) {
        uint32_t v[36];
#pragma unroll
        for (int i = 0; i < 9; i++) {
            const uint4 q = lds128(bounce + (lane & 1) * 1152 + (lane >> 1) * 144 + i * 16);
            v[4 * i] = q.x; v[4 * i + 1] = q.y; v[4 * i + 2] = q.z; v[4 * i + 3] = q.w;
        }
        const int cc = (cta >> 6) * 8 + (lane >> 1);
        unsigned char* dst = wt + (cc >> 1) * STAGE_BYTES + (cc & 1) * 2048 + ((cta & 63) * 2 + (lane & 1)) * 16;
#pragma unroll
        for (int kyo = 0; kyo < 3; kyo++) {
#pragma unroll
            for (int kx = 0; kx < 3; kx++) {
                const int tap = ky_of(kyo) * 3 + kx;
                uint32_t o[4];
#pragma unroll
                for (int m = 0; m < 4; m++) {
                    const int i0 = 18 * m + tap, i1 = i0 + 9;
                    const uint32_t sel = ((i0 & 1) ? 0x32u : 0x10u) | ((i1 & 1) ? 0x7600u : 0x5400u);
                    o[m] = __byte_perm(v[i0 >> 1], v[i1 >> 1], sel);
                }
                *reinterpret_cast<uint4*>(dst + (kyo * 24 + kx) * STEP_BYTES) = make_uint4(o[0], o[1], o[2], o[3]);
            }
        }
    }
}
__device__ __forceinline__ uint32_t act2(uint32_t u, const float4& cf) {
    return pack_bf(silu_half(fmaf(bf_lo(u), cf.x, cf.z)), silu_half(fmaf(bf_hi(u), cf.y, cf.w)));
}
template <int FIRST, int N>
__device__ __forceinline__ void norm_batch(const uint32_t (&u)[4][4], const float4 (&cf)[8], uint32_t act, uint32_t bar, int lane, bool valid) {
    if (valid) {
#pragma unroll
        for (int t = FIRST; t < FIRST + N; t++)
            stsm4(act + t * 4 * CH_PITCH, act2(u[t][0], cf[2 * t]), act2(u[t][1], cf[2 * t]), act2(u[t][2], cf[2 * t + 1]), act2(u[t][3], cf[2 * t + 1]));
        fence_async_smem();
    }
    __syncwarp();
    if (lane < N) mbar_arrive(bar + 16 * (FIRST + lane));
}
__device__ __forceinline__ void fence_acc(float (&d)[64]) {
#pragma unroll
    for (int i = 0; i < 64; i++) asm volatile("" : "+f"(d[i])::"memory");
}
__device__ __forceinline__ void ld_unit(uint32_t (&u)[4], const uint4* p) {
    asm volatile("ld.relaxed.gpu.global.v4.u32 {%0,%1,%2,%3}, [%4];" : "=r"(u[0]), "=r"(u[1]), "=r"(u[2]), "=r"(u[3]) : "l"(p) : "memory");
}

__device__ __forceinline__ void halo_row(const char* xrow, uint32_t stg, int lane) {
    const int c = lane >> 3, sg = lane & 7;
    const char* p = xrow + c * (HW * HW * 2) + sg * 16;
    const uint32_t d0 = stg + c * 128 + ((sg ^ c) << 4), d1 = stg + (c + 4) * 128 + ((sg ^ (c + 4)) << 4);
#pragma unroll 4
    for (int i = 0; i < 16; i++) {
        asm volatile("cp.async.cg.shared.global [%0], [%1], 16;" ::"r"(d0 + i * 1024), "l"(p + i * (8 * HW * HW * 2)) : "memory");
        asm volatile("cp.async.cg.shared.global [%0], [%1], 16;" ::"r"(d1 + i * 1024), "l"(p + i * (8 * HW * HW * 2) + 4 * HW * HW * 2) : "memory");
    }
}

__global__ void __launch_bounds__(NTHREADS, 1)
resblock_kernel(const __nv_bfloat16* __restrict__ x, const __nv_bfloat16* __restrict__ w1,
                const __nv_bfloat16* __restrict__ t_emb, const __nv_bfloat16* __restrict__ g1,
                const __nv_bfloat16* __restrict__ be1, const __nv_bfloat16* __restrict__ w_emb,
                const __nv_bfloat16* __restrict__ g2, const __nv_bfloat16* __restrict__ be2,
                const __nv_bfloat16* __restrict__ w2, __nv_bfloat16* __restrict__ out, Scratch* __restrict__ gs) {
    const unsigned clk0 = clock32();
    const int tid = threadIdx.x, warp = tid >> 5, lane = tid & 31;
    const int cta = blockIdx.x, b = cta >> 6, r = cta & 63;

    const uint32_t woff = ((2 * r + (lane >> 4)) * C + b * 64) * 18 + (lane & 15) * 16;
    const int c0 = (warp - 8) * 16 + (lane >> 3), seg = lane & 7;
    const char* src = (warp == 0) ? reinterpret_cast<const char*>(w1) + woff
                                  : reinterpret_cast<const char*>(x) + (uint32_t)(((b * C + c0) * HW + r) * HW * 2 + seg * 16);
    uint4 v[5];
    if (warp == 0 || warp >= 8) {
        const uint32_t stride = (warp == 0) ? 256 : 4 * HW * HW * 2;
        if (warp != 0) { while (clock32() - clk0 < XDELAY) {} }
#pragma unroll
        for (int k = 0; k < 4; k++) v[k] = __ldg(reinterpret_cast<const uint4*>(src + k * stride));
        if (tid < 32 && (lane & 15) < 8) v[4] = __ldg(reinterpret_cast<const uint4*>(src + 1024));
    }
    if (warp == 0) {
        weight_block(v, SM_BNC, gs->wt, cta, lane);
        if (r == 0) {
            if (lane < 16) gs->acc[(NB + b) * 32 + lane] = 0.f;
            *reinterpret_cast<float4*>(&gs->emb[b * C + lane * 4]) = make_float4(0.f, 0.f, 0.f, 0.f);
        }
        __syncwarp();
        if (lane == 0) TL(4);
        if (lane < 2) asm volatile("red.release.gpu.global.add.u32 [%0], 1;" ::"l"(&gs->wcnt[lane * 32]) : "memory");
        if (lane == 0) TL(5);
    }

    if (warp >= 8) {
        const int nw = warp - 8;
        {
            float s = 0.f, q = 0.f, s2 = 0.f, q2 = 0.f;
#pragma unroll
            for (int i = 0; i < 4; i++) {
                const uint32_t u[4] = {v[i].x, v[i].y, v[i].z, v[i].w};
#pragma unroll
                for (int k = 0; k < 4; k++) {
                    const float lo = bf_lo(u[k]), hi = bf_hi(u[k]);
                    s += lo; q = fmaf(lo, lo, q);
                    s2 += hi; q2 = fmaf(hi, hi, q2);
                }
            }
            s += s2; q += q2;
            float give = (lane < 16) ? q : s, keep = (lane < 16) ? s : q;
            keep += __shfl_xor_sync(0xffffffffu, give, 16);
            if (tid == 256) TL(2);
#pragma unroll
            for (int m = 8; m >= 1; m >>= 1) keep += __shfl_xor_sync(0xffffffffu, keep, m);
            if ((lane & 15) == 0) sts32f(SM_RED + (nw * 2 + (lane >> 4)) * 4, keep);
            bar_sync(3, 256 + 96);
            if (tid < 256 + 4) {
                const float4 p = lds128f(SM_RED + lane * 16);
                red_add4(&gs->acc[b * 32 + lane * 4], 1.f, p.x + p.z, p.y + p.w, 1.f);
            }
            if (tid == 256) TL(3);
#pragma unroll
            for (int i = 0; i < 4; i++) sts128(SM_XOWN + c0 * 128 + i * 512 + ((seg ^ ((c0 + 4 * i) & 7)) << 4), v[i]);
            bar_sync(4, 256);
        }
        const int par = nw >> 2, wq = nw & 3;
        const uint32_t act_off = SM_ACT + (par * 2 + (lane >> 4)) * CH_PITCH + (2 + wq * 16 + (lane & 15)) * 16;
        const uint32_t stg_off = (par * 16 + (lane >> 4) * 8 + (lane & 7)) * 128 + (((2 * wq + ((lane >> 3) & 1)) ^ (lane & 7)) << 4);
        const uint32_t fbar = BAR(BAR_FULL) + 8 * par;
#pragma unroll 1
        for (int conv = 0; conv < 2; conv++) {
            uint32_t u[4][4], hu[2][4][4];
            float4 cf[8];
            if (conv == 0) {
#pragma unroll
                for (int i = 0; i < 4; i++) ldsm4t(u[i], SM_XOWN + stg_off + i * 4096);
                mbar_wait(BAR(BAR_XH), 0);
#pragma unroll
                for (int i = 0; i < 8; i++) ldsm4t(hu[i >> 2][i & 3], SM_XH + stg_off + (i >> 2) * 16384 + (i & 3) * 4096);
                fence_async_smem();
                __syncwarp();
                if (lane == 0) mbar_arrive(BAR(BAR_XFREE));
            } else {
                mbar_wait(BAR(BAR_HW), 0);
#pragma unroll
                for (int i = 0; i < 4; i++) ldsm4(u[i], act_off + ROW_BYTES + i * 4 * CH_PITCH);
            }
            const uint4* hp[2];
            hp[0] = gs->h + (size_t)(r != 0 ? cta - 1 : cta) * 1024 + nw * 32 + lane;
            hp[1] = gs->h + (size_t)(r != HW - 1 ? cta + 1 : cta) * 1024 + nw * 32 + lane;
            const uint32_t cfa = SM_COEF + par * 128 + (lane & 3) * 16;
            mbar_wait(BAR(BAR_STATS), conv);
            if (tid == 256) TL(22 + conv * 4);
            cf[0] = lds128f(cfa); cf[1] = lds128f(cfa + 64);
            norm_batch<0, 1>(u, cf, act_off + ROW_BYTES, fbar, lane, true);
            if (tid == 256) TL(8 + conv * 8);
#pragma unroll
            for (int i = 2; i < 8; i++) cf[i] = lds128f(cfa + (i >> 1) * 256 + (i & 1) * 64);
            if (conv == 1) {
#pragma unroll
                for (int i = 0; i < 8; i++) ld_unit(hu[i >> 2][i & 3], hp[i >> 2] + (i & 3) * 256);
            }
            norm_batch<1, 1>(u, cf, act_off + ROW_BYTES, fbar, lane, true);
            norm_batch<2, 2>(u, cf, act_off + ROW_BYTES, fbar, lane, true);
            if (tid == 256) TL(24 + conv * 4);
            if (conv == 1) {
                unsigned it = 0;
                while (true) {
                    bool ok = true;
#pragma unroll
                    for (int i = 0; i < 32; i++) ok = ok && hu[i >> 4][(i >> 2) & 3][i & 3] != 0xffffffffu;
                    if (__all_sync(0xffffffffu, ok) || ++it > SPIN_LIMIT) break;
#pragma unroll
                    for (int i = 0; i < 8; i++) ld_unit(hu[i >> 2][i & 3], hp[i >> 2] + (i & 3) * 256);
                }
            }
            norm_batch<0, 4>(hu[0], cf, act_off, fbar + 64, lane, r != 0);
            norm_batch<0, 4>(hu[1], cf, act_off + 2 * ROW_BYTES, fbar + 128, lane, r != HW - 1);
            if (tid == 256) TL(23 + conv * 4);
        }
    } else if (warp < 4) {
        const int wq = warp;
        if (wq != 0) {
            const int t = tid - 32;
            if (t == 95) TLG(1);
            if (t < NBAR) {
                const int cnt = t < BAR_WEMPTY ? 5 : (t <= BAR_HW ? 4 : (t == BAR_XH ? 32 : (t == BAR_XFREE ? 8 : 1)));
                mbar_init(BAR(0) + 8 * t, cnt);
            }
            fence_async_smem();
            bar_arrive(0, 96 + 128);
            bar_arrive(3, 256 + 96);
            const uint4 z = make_uint4(0, 0, 0, 0);
            sts128(SM_ACT + (t >> 1) * CH_PITCH + (t & 1) * 16, z);
            if (t < 2) sts128(SM_ACT + 3 * ROW_BYTES + t * 16, z);
            if (r == 0 || r == HW - 1) {
                for (int i = t; i < ROW_BYTES / 16; i += 96) sts128(SM_ACT + (r == 0 ? 0 : 2 * ROW_BYTES) + i * 16, z);
            }
            fence_async_smem();
        }
        bar_sync(2, 128);

        float d[64];
#pragma unroll
        for (int i = 0; i < 64; i++) d[i] = 0.f;
#pragma unroll 1
        for (int conv = 0; conv < 2; conv++) {
            fence_acc(d);
            float2 ev[16];
            mma_stages<0>(d, ev, conv, tid, gs);
            asm volatile("wgmma.wait_group.sync.aligned 0;" ::: "memory");
            fence_acc(d);
            if (tid == 0) TL(10 + conv * 8);
            if (conv == 1) break;

            float st[8];
#pragma unroll
            for (int g = 0; g < 4; g++) {
                float s = 0.f, q = 0.f, s2 = 0.f, q2 = 0.f;
#pragma unroll
                for (int jj = 0; jj < 4; jj++) {
                    const int j = g * 4 + jj;
                    const float2 e = ev[j];
                    d[4 * j + 0] += e.x; d[4 * j + 1] += e.y; d[4 * j + 2] += e.x; d[4 * j + 3] += e.y;
                    s += d[4 * j + 0]; q = fmaf(d[4 * j + 0], d[4 * j + 0], q);
                    s2 += d[4 * j + 1]; q2 = fmaf(d[4 * j + 1], d[4 * j + 1], q2);
                    s += d[4 * j + 2]; q = fmaf(d[4 * j + 2], d[4 * j + 2], q);
                    s2 += d[4 * j + 3]; q2 = fmaf(d[4 * j + 3], d[4 * j + 3], q2);
                }
                st[2 * g] = s + s2; st[2 * g + 1] = q + q2;
            }
            {
                const bool h16 = lane & 16, h8 = lane & 8, h4 = lane & 4;
                float a[4];
#pragma unroll
                for (int i = 0; i < 4; i++) {
                    float give = h16 ? st[i] : st[i + 4], keep = h16 ? st[i + 4] : st[i];
                    a[i] = keep + __shfl_xor_sync(0xffffffffu, give, 16);
                }
                float c2[2];
#pragma unroll
                for (int i = 0; i < 2; i++) {
                    float give = h8 ? a[i] : a[i + 2], keep = h8 ? a[i + 2] : a[i];
                    c2[i] = keep + __shfl_xor_sync(0xffffffffu, give, 8);
                }
                float give = h4 ? c2[0] : c2[1], keep = h4 ? c2[1] : c2[0];
                float t = keep + __shfl_xor_sync(0xffffffffu, give, 4);
                t += __shfl_xor_sync(0xffffffffu, t, 2);
                t += __shfl_xor_sync(0xffffffffu, t, 1);
                if ((lane & 3) == 0) sts32f(SM_RED + ((lane >> 2) * 4 + wq) * 4, t);
                bar_sync(2, 128);
                if (tid < 4) {
                    const float4 p = lds128f(SM_RED + tid * 32), p2 = lds128f(SM_RED + tid * 32 + 16);
                    red_add4(&gs->acc[(NB + b) * 32 + tid * 4], 1.f, (p.x + p.y) + (p.z + p.w), (p2.x + p2.y) + (p2.z + p2.w), 1.f);
                }
                if (tid == 0) TL(11);
                if (lane < LAG) mbar_arrive(BAR(BAR_WEMPTY + (NSTAGE - LAG) % NS) + 8 * lane);
            }
            const uint32_t hbase = SM_ACT + ROW_BYTES + (lane >> 4) * CH_PITCH + (2 + wq * 16 + (lane & 15)) * 16;
            uint4* hg = gs->h + cta * 1024 + tid;
#pragma unroll
            for (int kc = 0; kc < 8; kc++) {
                const uint4 p = make_uint4(pack_bf(d[8 * kc + 0], d[8 * kc + 1]), pack_bf(d[8 * kc + 2], d[8 * kc + 3]),
                                           pack_bf(d[8 * kc + 4], d[8 * kc + 5]), pack_bf(d[8 * kc + 6], d[8 * kc + 7]));
                stsm4(hbase + kc * 2 * CH_PITCH, p.x, p.y, p.z, p.w);
                hg[kc * 128] = p;
            }
            __syncwarp();
            if (lane == 0) mbar_arrive(BAR(BAR_HW));
            if (tid == 0) TL(12);
            const uint32_t xbase = SM_XOWN + ((lane >> 4) * 8 + (lane & 7)) * 128 + (((2 * wq + ((lane >> 3) & 1)) ^ (lane & 7)) << 4);
#pragma unroll
            for (int kc = 0; kc < 8; kc++) {
                uint32_t p[4];
                ldsm4t(p, xbase + kc * 2048);
#pragma unroll
                for (int i = 0; i < 4; i++) { d[8 * kc + 2 * i] = bf_lo(p[i]); d[8 * kc + 2 * i + 1] = bf_hi(p[i]); }
            }
        }
        {
            const uint32_t obase = SM_W + ((lane >> 4) * 8 + (lane & 7)) * OUT_PITCH + (wq * 16 + ((lane >> 3) & 1) * 8) * 2;
#pragma unroll
            for (int kc = 0; kc < 8; kc++) {
                stsm4t(obase + kc * 16 * OUT_PITCH, pack_bf(d[8 * kc + 0], d[8 * kc + 1]), pack_bf(d[8 * kc + 2], d[8 * kc + 3]),
                       pack_bf(d[8 * kc + 4], d[8 * kc + 5]), pack_bf(d[8 * kc + 6], d[8 * kc + 7]));
            }
            bar_sync(2, 128);
            const int oc0 = tid >> 3;
            __nv_bfloat16* dst = out + ((size_t)(b * C + oc0) * HW + r) * HW + seg * 8;
#pragma unroll
            for (int i = 0; i < 8; i++)
                *reinterpret_cast<uint4*>(dst + (size_t)i * 16 * HW * HW) = lds128(SM_W + (oc0 + 16 * i) * OUT_PITCH + seg * 16);
            if (tid == 0) { TL(20); TLG(21); }
        }
    } else if (warp < 6) {
        bar_sync(0, 96 + 128);
        if (warp == 5) {
            while (clock32() - clk0 < HDELAY) {}
            const char* xr = reinterpret_cast<const char*>(x) + (uint32_t)((b * C * HW + r) * HW * 2);
            if (r != 0) halo_row(xr - HW * 2, SM_XH, lane);
            if (r != HW - 1) halo_row(xr + HW * 2, SM_XH + 16384, lane);
            asm volatile("cp.async.mbarrier.arrive.noinc.shared::cta.b64 [%0];" ::"r"(BAR(BAR_XH)) : "memory");
#pragma unroll 4
            for (int i = 0; i < 32; i++) gs->h[cta * 1024 + i * 32 + lane] = make_uint4(~0u, ~0u, ~0u, ~0u);
            bar_arrive(6, 64);
        } else {
            while (clock32() - clk0 < W2DELAY) {}
            const char* w2s = reinterpret_cast<const char*>(w2) + woff;
#pragma unroll
            for (int k = 0; k < 4; k++) v[k] = __ldg(reinterpret_cast<const uint4*>(w2s + k * 256));
            if ((lane & 15) < 8) v[4] = __ldg(reinterpret_cast<const uint4*>(w2s + 1024));
            const uint2* wsrc = reinterpret_cast<const uint2*>(w_emb + (size_t)r * 12 * C) + lane;
            uint2 wv[12];
#pragma unroll
            for (int i = 0; i < 12; i++) wv[i] = __ldg(wsrc + i * (C / 4));
            float tv = 0.f;
            if (lane < 12) tv = __bfloat162float(t_emb[b * E + r * 12 + lane]);
            weight_block(v, SM_BNC + 2304, gs->wt + NSTAGE * STAGE_BYTES, cta, lane);
            const float sv = silu_half(0.5f * tv);
            float e0 = 0.f, e1 = 0.f, e2 = 0.f, e3 = 0.f;
#pragma unroll
            for (int i = 0; i < 12; i++) {
                const float sx = __shfl_sync(0xffffffffu, sv, i);
                e0 = fmaf(sx, bf_lo(wv[i].x), e0); e1 = fmaf(sx, bf_hi(wv[i].x), e1);
                e2 = fmaf(sx, bf_lo(wv[i].y), e2); e3 = fmaf(sx, bf_hi(wv[i].y), e3);
            }
            mbar_wait(BAR(BAR_WACQ), 0);
            red_add4(&gs->emb[b * C + lane * 4], e0, e1, e2, e3);
            bar_sync(6, 64);
            if (lane == 0) TL(13);
            if (lane < 2) asm volatile("red.release.gpu.global.add.u32 [%0], 1;" ::"l"(&gs->wcnt[(NB + lane) * 32]) : "memory");
            if (lane == 0) TL(14);
            unsigned it = 0;
            while (ld_relaxed(&gs->wcnt[(NB + b) * 32]) < (unsigned)NCTA && ++it < SPIN_LIMIT) {}
            fence_acquire();
            sts128(SM_EMB + lane * 16, ld_relaxed_v4(&gs->emb[b * C + lane * 4]));
            __syncwarp();
            if (lane == 0) { mbar_arrive(BAR(BAR_EMB)); TL(19); }
        }
    } else if (warp == 6) {
        bar_sync(0, 96 + 128);
        unsigned it = 0;
        while (ld_relaxed(&gs->wcnt[b * 32]) < (unsigned)NCTA && ++it < SPIN_LIMIT) {}
        fence_acquire();
        fence_async_global();
        if (lane == 0) { mbar_arrive(BAR(BAR_WACQ)); TL(6); }
        const unsigned char* wsrc = gs->wt;
#pragma unroll 1
        for (int round = 0; round < 2 * NSTAGE / NS; round++) {
            if (round == NSTAGE / NS) { mbar_wait(BAR(BAR_EMB), 0); fence_async_global(); }
            const uint32_t full = BAR(BAR_FULL) + 8 * NS * (round >= NSTAGE / NS ? round - NSTAGE / NS : round);
#pragma unroll
            for (int slot = 0; slot < NS; slot++) {
                if (slot == 9 && round == 0) mbar_wait(BAR(BAR_XFREE), 0);
                mbar_wait(BAR(BAR_WEMPTY + slot), (round & 1) ^ 1);
                if (elect_one()) {
                    mbar_expect(full + 8 * slot, STAGE_BYTES);
                    bulk_g2s(SM_W + slot * STAGE_BYTES, wsrc + slot * STAGE_BYTES, STAGE_BYTES, full + 8 * slot);
                }
            }
            wsrc += NS * STAGE_BYTES;
        }
    } else {
        const uint2 ga1 = __ldg(reinterpret_cast<const uint2*>(g1) + lane), bt1 = __ldg(reinterpret_cast<const uint2*>(be1) + lane);
        const uint2 ga2 = __ldg(reinterpret_cast<const uint2*>(g2) + lane), bt2 = __ldg(reinterpret_cast<const uint2*>(be2) + lane);
        bar_sync(0, 96 + 128);
#pragma unroll 1
        for (int conv = 0; conv < 2; conv++) {
            if (conv == 1) mbar_wait(BAR(BAR_EMB), 0);
            const float* asrc = &gs->acc[(conv * NB + b) * 32 + (lane >> 3) * 4];
            uint4 f;
            unsigned it = 0;
            while (true) {
                f = ld_relaxed_v4(asrc);
                const bool ok = (f.x == 0x42800000u) & (f.w == 0x42800000u);
                if (__all_sync(0xffffffffu, ok) || ++it > SPIN_LIMIT) break;
            }
            if (lane == 0) TL(7 + conv * 8);
            const float inv_n = 1.0f / (32.0f * HW * HW);
            const float mean = __uint_as_float(f.y) * inv_n;
            const float var = fmaxf(fmaf(-mean, mean, __uint_as_float(f.z) * inv_n), 0.f);
            const float rs = 0.5f * rsqrtf(var + 1e-5f);
            const uint2 ga = conv ? ga2 : ga1, bt = conv ? bt2 : bt1;
            float4 k0, k1;
            k0.x = rs * bf_lo(ga.x); k0.y = rs * bf_hi(ga.x); k1.x = rs * bf_lo(ga.y); k1.y = rs * bf_hi(ga.y);
            k0.z = fmaf(-mean, k0.x, 0.5f * bf_lo(bt.x)); k0.w = fmaf(-mean, k0.y, 0.5f * bf_hi(bt.x));
            k1.z = fmaf(-mean, k1.x, 0.5f * bf_lo(bt.y)); k1.w = fmaf(-mean, k1.y, 0.5f * bf_hi(bt.y));
            sts128f(SM_COEF + lane * 32, k0);
            sts128f(SM_COEF + lane * 32 + 16, k1);
            __syncwarp();
            if (lane == 0) mbar_arrive(BAR(BAR_STATS));
        }
        if (r == 0) {
            if (lane < 16) gs->acc[b * 32 + lane] = 0.f;
            if (lane < 2) gs->wcnt[(lane * NB + b) * 32] = 0;
        }
    }
}

}

extern "C" void kernel_launch(void* const* d_in, const int* in_sizes, int n_in, void* d_out, int out_size) {
    (void)in_sizes; (void)n_in; (void)out_size;
    static Scratch* gs = nullptr;
    if (!gs) {
        cudaFuncSetAttribute(resblock_kernel, cudaFuncAttributeMaxDynamicSharedMemorySize, SM_TOTAL);
        cudaGetSymbolAddress((void**)&gs, g_scratch);
    }
    resblock_kernel<<<NCTA, NTHREADS, SM_TOTAL>>>(
        (const __nv_bfloat16*)d_in[0], (const __nv_bfloat16*)d_in[4], (const __nv_bfloat16*)d_in[1],
        (const __nv_bfloat16*)d_in[2], (const __nv_bfloat16*)d_in[3], (const __nv_bfloat16*)d_in[5],
        (const __nv_bfloat16*)d_in[6], (const __nv_bfloat16*)d_in[7], (const __nv_bfloat16*)d_in[8],
        (__nv_bfloat16*)d_out, gs);
}
```

```cpp
#include <cuda_runtime.h>
#include <cuda_bf16.h>
#include <stdint.h>

namespace {

constexpr int C = 128, HW = 64, NB = 2, E = 768;
constexpr int NCTA = NB * HW;
constexpr int NTHREADS = 16 * 32;
constexpr int CH_PITCH = 66 * 16;
constexpr int ROW_BYTES = 16 * CH_PITCH;
constexpr int STEP_BYTES = 4096;
constexpr int STAGE_BYTES = 3 * STEP_BYTES;
constexpr int NSTAGE = 24;
constexpr int NS = 12;
constexpr int LAG = 1;
#define XDELAY 900
#define HDELAY 1000
#define W2DELAY 2800

constexpr uint32_t SMEM_BASE = 0x400;
constexpr uint32_t SM_ACT = SMEM_BASE;
constexpr uint32_t SM_XOWN = SM_ACT + 3 * ROW_BYTES + 128;
constexpr uint32_t SM_W = SM_XOWN + 16384;
constexpr uint32_t SM_XH = SM_W + 9 * STAGE_BYTES;
constexpr uint32_t SM_COEF = SM_W + NS * STAGE_BYTES;
constexpr uint32_t SM_EMB = SM_COEF + 1024;
constexpr uint32_t SM_RED = SM_EMB + 512;
constexpr uint32_t SM_BNC = SM_RED + 128;
constexpr uint32_t SM_BAR = SM_BNC + 2 * 2304;
constexpr int BAR_FULL = 0, BAR_WEMPTY = NSTAGE, BAR_HW = BAR_WEMPTY + NS, BAR_STATS = BAR_HW + 1,
              BAR_EMB = BAR_STATS + 1, BAR_WACQ = BAR_EMB + 1, BAR_XH = BAR_WACQ + 1, BAR_XFREE = BAR_XH + 1, NBAR = BAR_XFREE + 1;
constexpr int SM_TOTAL = SM_BAR + NBAR * 8 - SMEM_BASE;
static_assert(SM_TOTAL <= 232448, "smem");
static_assert(NBAR <= 96, "barrier init");
constexpr int OUT_PITCH = 144;
__host__ __device__ constexpr uint32_t BAR(int i) { return SM_BAR + 8 * i; }
__host__ __device__ constexpr int ky_of(int kyo) { return kyo == 0 ? 1 : (kyo == 1 ? 0 : 2); }

constexpr unsigned SPIN_LIMIT = 1u << 16;

struct Scratch {
    float acc[2 * NB * 32];
    unsigned wcnt[2 * NB * 32];
    float emb[NB * C];
    unsigned char wt[2 * NSTAGE * STAGE_BYTES];
    uint4 h[NCTA * 2048];
};
__device__ __align__(1024) Scratch g_scratch;
#define TL(i) do {} while (0)
#define TLG(i) do {} while (0)

__device__ __forceinline__ unsigned clock32() { unsigned c; asm volatile("mov.u32 %0, %%clock;" : "=r"(c)); return c; }
__device__ __forceinline__ void mbar_init(uint32_t bar, int cnt) {
    asm volatile("mbarrier.init.shared::cta.b64 [%0], %1;" ::"r"(bar), "r"(cnt) : "memory");
}
__device__ __forceinline__ void mbar_arrive(uint32_t bar) {
    asm volatile("mbarrier.arrive.shared::cta.b64 _, [%0];" ::"r"(bar) : "memory");
}
__device__ __forceinline__ void mbar_expect(uint32_t bar, uint32_t bytes) {
    asm volatile("mbarrier.arrive.expect_tx.shared::cta.b64 _, [%0], %1;" ::"r"(bar), "r"(bytes) : "memory");
}
__device__ __forceinline__ bool mbar_try(uint32_t bar, uint32_t par) {
    uint32_t ok;
    asm volatile("{\n.reg .pred p;\nmbarrier.try_wait.parity.shared::cta.b64 p, [%1], %2;\nselp.u32 %0, 1, 0, p;\n}"
                 : "=r"(ok) : "r"(bar), "r"(par) : "memory");
    return ok;
}
__device__ __forceinline__ bool mbar_test(uint32_t bar, uint32_t par) {
    uint32_t ok;
    asm volatile("{\n.reg .pred p;\nmbarrier.test_wait.parity.shared::cta.b64 p, [%1], %2;\nselp.u32 %0, 1, 0, p;\n}"
                 : "=r"(ok) : "r"(bar), "r"(par) : "memory");
    return ok;
}
__device__ __forceinline__ void mbar_wait(uint32_t bar, uint32_t par) {
    unsigned it = 0;
#pragma unroll 1
    while (!mbar_try(bar, par) && ++it < SPIN_LIMIT) {}
}
__device__ __forceinline__ bool elect_one() {
    uint32_t p;
    asm volatile("{\n.reg .pred p;\nelect.sync _|p, 0xffffffff;\nselp.u32 %0, 1, 0, p;\n}" : "=r"(p));
    return p;
}
__device__ __forceinline__ void fence_async_smem() { asm volatile("fence.proxy.async.shared::cta;" ::: "memory"); }
__device__ __forceinline__ void fence_async_global() { asm volatile("fence.proxy.async.global;" ::: "memory"); }
__device__ __forceinline__ void fence_acquire() { asm volatile("fence.acquire.gpu;" ::: "memory"); }
__device__ __forceinline__ void bar_sync(int id, int n) { asm volatile("bar.sync %0, %1;" ::"r"(id), "r"(n) : "memory"); }
__device__ __forceinline__ void bar_arrive(int id, int n) { asm volatile("bar.arrive %0, %1;" ::"r"(id), "r"(n) : "memory"); }
__device__ __forceinline__ void bulk_g2s(uint32_t dst, const void* src, uint32_t bytes, uint32_t bar) {
    asm volatile("cp.async.bulk.shared::cluster.global.mbarrier::complete_tx::bytes [%0], [%1], %2, [%3];"
                 ::"r"(dst), "l"(src), "r"(bytes), "r"(bar) : "memory");
}
__device__ __forceinline__ uint4 ld_relaxed_v4(const void* p) {
    uint4 v;
    asm volatile("ld.relaxed.gpu.global.v4.u32 {%0,%1,%2,%3}, [%4];" : "=r"(v.x), "=r"(v.y), "=r"(v.z), "=r"(v.w) : "l"(p) : "memory");
    return v;
}
__device__ __forceinline__ unsigned ld_relaxed(const void* p) {
    unsigned v;
    asm volatile("ld.relaxed.gpu.global.u32 %0, [%1];" : "=r"(v) : "l"(p) : "memory");
    return v;
}
__device__ __forceinline__ void red_add4(float* p, float a, float b, float c, float d) {
    asm volatile("red.relaxed.gpu.global.add.v4.f32 [%0], {%1,%2,%3,%4};" ::"l"(p), "f"(a), "f"(b), "f"(c), "f"(d) : "memory");
}
__device__ __forceinline__ void sts128(uint32_t a, uint4 v) {
    asm volatile("st.shared.v4.u32 [%0], {%1,%2,%3,%4};" ::"r"(a), "r"(v.x), "r"(v.y), "r"(v.z), "r"(v.w) : "memory");
}
__device__ __forceinline__ void sts128f(uint32_t a, float4 v) {
    asm volatile("st.shared.v4.f32 [%0], {%1,%2,%3,%4};" ::"r"(a), "f"(v.x), "f"(v.y), "f"(v.z), "f"(v.w) : "memory");
}
__device__ __forceinline__ void sts32f(uint32_t a, float v) { asm volatile("st.shared.f32 [%0], %1;" ::"r"(a), "f"(v) : "memory"); }
__device__ __forceinline__ uint4 lds128(uint32_t a) {
    uint4 v;
    asm volatile("ld.shared.v4.u32 {%0,%1,%2,%3}, [%4];" : "=r"(v.x), "=r"(v.y), "=r"(v.z), "=r"(v.w) : "r"(a) : "memory");
    return v;
}
__device__ __forceinline__ float4 lds128f(uint32_t a) {
    float4 v;
    asm volatile("ld.shared.v4.f32 {%0,%1,%2,%3}, [%4];" : "=f"(v.x), "=f"(v.y), "=f"(v.z), "=f"(v.w) : "r"(a) : "memory");
    return v;
}
__device__ __forceinline__ float2 lds64f(uint32_t a) {
    float2 v;
    asm volatile("ld.shared.v2.f32 {%0,%1}, [%2];" : "=f"(v.x), "=f"(v.y) : "r"(a) : "memory");
    return v;
}
__device__ __forceinline__ float bf_lo(uint32_t u) { return __uint_as_float(u << 16); }
__device__ __forceinline__ float bf_hi(uint32_t u) { return __uint_as_float(u & 0xffff0000u); }
__device__ __forceinline__ uint32_t pack_bf(float lo, float hi) {
    uint32_t r;
    asm("cvt.rn.bf16x2.f32 %0, %1, %2;" : "=r"(r) : "f"(hi), "f"(lo));
    return r;
}
__device__ __forceinline__ float tanh_fast(float x) {
    float r;
    asm volatile("tanh.approx.f32 %0, %1;" : "=f"(r) : "f"(x));
    return r;
}
__device__ __forceinline__ float silu_half(float h) { return fmaf(h, tanh_fast(h), h); }
__device__ __forceinline__ void ldsm4(uint32_t (&u)[4], uint32_t a) {
    asm volatile("ldmatrix.sync.aligned.m8n8.x4.shared.b16 {%0,%1,%2,%3}, [%4];"
                 : "=r"(u[0]), "=r"(u[1]), "=r"(u[2]), "=r"(u[3]) : "r"(a) : "memory");
}
__device__ __forceinline__ void ldsm4t(uint32_t (&u)[4], uint32_t a) {
    asm volatile("ldmatrix.sync.aligned.m8n8.x4.trans.shared.b16 {%0,%1,%2,%3}, [%4];"
                 : "=r"(u[0]), "=r"(u[1]), "=r"(u[2]), "=r"(u[3]) : "r"(a) : "memory");
}
__device__ __forceinline__ void stsm4(uint32_t a, uint32_t p0, uint32_t p1, uint32_t p2, uint32_t p3) {
    asm volatile("stmatrix.sync.aligned.m8n8.x4.shared.b16 [%0], {%1,%2,%3,%4};" ::"r"(a), "r"(p0), "r"(p1), "r"(p2), "r"(p3) : "memory");
}
__device__ __forceinline__ void stsm4t(uint32_t a, uint32_t p0, uint32_t p1, uint32_t p2, uint32_t p3) {
    asm volatile("stmatrix.sync.aligned.m8n8.x4.trans.shared.b16 [%0], {%1,%2,%3,%4};" ::"r"(a), "r"(p0), "r"(p1), "r"(p2), "r"(p3) : "memory");
}

#define R8(o) "+f"(d[o]), "+f"(d[o + 1]), "+f"(d[o + 2]), "+f"(d[o + 3]), "+f"(d[o + 4]), "+f"(d[o + 5]), "+f"(d[o + 6]), "+f"(d[o + 7])
template <uint32_t ALO, uint32_t BLO>
__device__ __forceinline__ void wgmma128(float (&d)[64]) {
    asm volatile(
        "wgmma.mma_async.sync.aligned.m64n128k16.f32.bf16.bf16 "
        "{%0,%1,%2,%3,%4,%5,%6,%7,%8,%9,%10,%11,%12,%13,%14,%15,%16,%17,%18,%19,%20,%21,%22,%23,%24,%25,%26,%27,%28,%29,%30,%31,"
        "%32,%33,%34,%35,%36,%37,%38,%39,%40,%41,%42,%43,%44,%45,%46,%47,%48,%49,%50,%51,%52,%53,%54,%55,%56,%57,%58,%59,%60,%61,%62,%63},"
        " %64, %65, 1, 1, 1, 0, 0;"
        : R8(0), R8(8), R8(16), R8(24), R8(32), R8(40), R8(48), R8(56)
        : "l"((8ull << 32) | ALO), "l"((8ull << 32) | BLO));
}
template <int S>
__device__ __forceinline__ void mma_stages(float (&d)[64], float2 (&e)[16], int conv, int tid, Scratch* gs) {
    constexpr uint32_t A = ((SM_ACT + ky_of(S >> 3) * ROW_BYTES + (S & 7) * 2 * CH_PITCH + 16) >> 4) | ((CH_PITCH >> 4) << 16);
    constexpr uint32_t B = ((SM_W + (S % NS) * STAGE_BYTES) >> 4) | ((2048 >> 4) << 16);
    if (S == 0) mbar_wait(BAR(BAR_FULL), conv);
    bool next_ok = true;
    if (S + 1 < NSTAGE) next_ok = mbar_test(BAR(BAR_FULL + S + 1), conv);
    if (S == 0 && tid == 0) TL(32 + conv * 24);
    asm volatile("wgmma.fence.sync.aligned;" ::: "memory");
    wgmma128<A, B>(d);
    wgmma128<A + 1, B + (STEP_BYTES >> 4)>(d);
    wgmma128<A + 2, B + 2 * (STEP_BYTES >> 4)>(d);
    asm volatile("wgmma.commit_group.sync.aligned;" ::: "memory");
    if (S >= LAG) {
        asm volatile("wgmma.wait_group.sync.aligned %0;" ::"n"(LAG) : "memory");
        if ((tid & 31) == 0) mbar_arrive(BAR(BAR_WEMPTY + (S + NS - LAG) % NS));
    }
    if (!next_ok) mbar_wait(BAR(BAR_FULL + S + 1), conv);
    if (S == NSTAGE - 1 && conv == 0) {
        mbar_wait(BAR(BAR_EMB), 0);
#pragma unroll
        for (int j = 0; j < 16; j++) e[j] = lds64f(SM_EMB + j * 32 + (tid & 3) * 8);
    }
    if constexpr (S + 1 < NSTAGE) mma_stages<S + 1>(d, e, conv, tid, gs);
}

__device__ __forceinline__ void weight_block(const uint4 (&t)[5], uint32_t bounce, unsigned char* wt, int cta, int lane) {
    const uint32_t bw = bounce + (lane >> 4) * 1152 + (lane & 15) * 16;
#pragma unroll
    for (int k = 0; k < 4; k++) sts128(bw + k * 256, t[k]);
    if ((lane & 15) < 8) sts128(bw + 1024, t[4]);
    __syncwarp();
    if (lane < 16) {
        uint32_t v[36];
#pragma unroll
        for (int i = 0; i < 9; i++) {
            const uint4 q = lds128(bounce + (lane & 1) * 1152 + (lane >> 1) * 144 + i * 16);
            v[4 * i] = q.x; v[4 * i + 1] = q.y; v[4 * i + 2] = q.z; v[4 * i + 3] = q.w;
        }
        const int cc = (cta >> 6) * 8 + (lane >> 1);
        unsigned char* dst = wt + (cc >> 1) * STAGE_BYTES + (cc & 1) * 2048 + ((cta & 63) * 2 + (lane & 1)) * 16;
#pragma unroll
        for (int kyo = 0; kyo < 3; kyo++) {
#pragma unroll
            for (int kx = 0; kx < 3; kx++) {
                const int tap = ky_of(kyo) * 3 + kx;
                uint32_t o[4];
#pragma unroll
                for (int m = 0; m < 4; m++) {
                    const int i0 = 18 * m + tap, i1 = i0 + 9;
                    const uint32_t sel = ((i0 & 1) ? 0x32u : 0x10u) | ((i1 & 1) ? 0x7600u : 0x5400u);
                    o[m] = __byte_perm(v[i0 >> 1], v[i1 >> 1], sel);
                }
                *reinterpret_cast<uint4*>(dst + (kyo * 24 + kx) * STEP_BYTES) = make_uint4(o[0], o[1], o[2], o[3]);
            }
        }
    }
}
__device__ __forceinline__ uint32_t act2(uint32_t u, const float4& cf) {
    return pack_bf(silu_half(fmaf(bf_lo(u), cf.x, cf.z)), silu_half(fmaf(bf_hi(u), cf.y, cf.w)));
}
__device__ __forceinline__ void norm_unit(uint32_t (&u)[4], const float4& ca, const float4& cb) {
    u[0] = act2(u[0], ca); u[1] = act2(u[1], ca); u[2] = act2(u[2], cb); u[3] = act2(u[3], cb);
}
__device__ __forceinline__ void publish(uint32_t bar, int lane) {
    fence_async_smem();
    __syncwarp();
    if (lane == 0) mbar_arrive(bar);
}
__device__ __forceinline__ void fence_acc(float (&d)[64]) {
#pragma unroll
    for (int i = 0; i < 64; i++) asm volatile("" : "+f"(d[i])::"memory");
}
__device__ __forceinline__ void ld_unit(uint32_t (&u)[4], const uint4* p) {
    asm volatile("ld.relaxed.gpu.global.v4.u32 {%0,%1,%2,%3}, [%4];" : "=r"(u[0]), "=r"(u[1]), "=r"(u[2]), "=r"(u[3]) : "l"(p) : "memory");
}

__global__ void __launch_bounds__(NTHREADS, 1)
resblock_kernel(const __nv_bfloat16* __restrict__ x, const __nv_bfloat16* __restrict__ w1,
                const __nv_bfloat16* __restrict__ t_emb, const __nv_bfloat16* __restrict__ g1,
                const __nv_bfloat16* __restrict__ be1, const __nv_bfloat16* __restrict__ w_emb,
                const __nv_bfloat16* __restrict__ g2, const __nv_bfloat16* __restrict__ be2,
                const __nv_bfloat16* __restrict__ w2, __nv_bfloat16* __restrict__ out, Scratch* __restrict__ gs) {
    const unsigned clk0 = clock32();
    const int tid = threadIdx.x, warp = tid >> 5, lane = tid & 31;
    const int cta = blockIdx.x, b = cta >> 6, r = cta & 63;

    const uint32_t woff = ((2 * r + (lane >> 4)) * C + b * 64) * 18 + (lane & 15) * 16;
    const int c0 = (warp - 8) * 16 + (lane >> 3), seg = lane & 7;
    const char* src = (warp == 0) ? reinterpret_cast<const char*>(w1) + woff
                                  : reinterpret_cast<const char*>(x) + (uint32_t)(((b * C + c0) * HW + r) * HW * 2 + seg * 16);
    uint4 v[5];
    if (warp == 0 || warp >= 8) {
        const uint32_t stride = (warp == 0) ? 256 : 4 * HW * HW * 2;
        if (warp != 0) { while (clock32() - clk0 < XDELAY) {} }
#pragma unroll
        for (int k = 0; k < 4; k++) v[k] = __ldg(reinterpret_cast<const uint4*>(src + k * stride));
        if (tid < 32 && (lane & 15) < 8) v[4] = __ldg(reinterpret_cast<const uint4*>(src + 1024));
    }
    if (warp >= 8) {
        while (clock32() - clk0 < HDELAY) {}
#pragma unroll
        for (int i = 0; i < 8; i++) {
            if (i < 4 ? (r != 0) : (r != HW - 1))
                asm volatile("cp.async.cg.shared.global [%0], [%1], 16;"
                             ::"r"(SM_XH + (i >> 2) * 16384 + c0 * 128 + (i & 3) * 512 + ((seg ^ ((c0 + 4 * i) & 7)) << 4)),
                               "l"(src + (i < 4 ? -HW * 2 : HW * 2) + (i & 3) * (4 * HW * HW * 2)) : "memory");
        }
    }
    if (warp == 0) {
        weight_block(v, SM_BNC, gs->wt, cta, lane);
        if (r == 0) {
            if (lane < 16) gs->acc[(NB + b) * 32 + lane] = 0.f;
            *reinterpret_cast<float4*>(&gs->emb[b * C + lane * 4]) = make_float4(0.f, 0.f, 0.f, 0.f);
        }
        __syncwarp();
        if (lane == 0) TL(4);
        if (lane < 2) asm volatile("red.release.gpu.global.add.u32 [%0], 1;" ::"l"(&gs->wcnt[lane * 32]) : "memory");
        if (lane == 0) TL(5);
    }

    if (warp >= 8) {
        const int nw = warp - 8;
        {
            float s = 0.f, q = 0.f, s2 = 0.f, q2 = 0.f;
#pragma unroll
            for (int i = 0; i < 4; i++) {
                const uint32_t u[4] = {v[i].x, v[i].y, v[i].z, v[i].w};
#pragma unroll
                for (int k = 0; k < 4; k++) {
                    const float lo = bf_lo(u[k]), hi = bf_hi(u[k]);
                    s += lo; q = fmaf(lo, lo, q);
                    s2 += hi; q2 = fmaf(hi, hi, q2);
                }
            }
            s += s2; q += q2;
            float give = (lane < 16) ? q : s, keep = (lane < 16) ? s : q;
            keep += __shfl_xor_sync(0xffffffffu, give, 16);
            if (tid == 256) TL(2);
#pragma unroll
            for (int m = 8; m >= 1; m >>= 1) keep += __shfl_xor_sync(0xffffffffu, keep, m);
            if ((lane & 15) == 0) sts32f(SM_RED + (nw * 2 + (lane >> 4)) * 4, keep);
            bar_sync(3, 256 + 96);
            if (tid < 256 + 4) {
                const float4 p = lds128f(SM_RED + lane * 16);
                red_add4(&gs->acc[b * 32 + lane * 4], 1.f, p.x + p.z, p.y + p.w, 1.f);
            }
            if (tid == 256) TL(3);
#pragma unroll
            for (int i = 0; i < 4; i++) sts128(SM_XOWN + c0 * 128 + i * 512 + ((seg ^ ((c0 + 4 * i) & 7)) << 4), v[i]);
            asm volatile("cp.async.wait_all;" ::: "memory");
            bar_sync(4, 256);
        }
        const int par = nw >> 2, wq = nw & 3;
        const uint32_t act_off = SM_ACT + (par * 2 + (lane >> 4)) * CH_PITCH + (2 + wq * 16 + (lane & 15)) * 16;
        const uint32_t stg_off = (par * 16 + (lane >> 4) * 8 + (lane & 7)) * 128 + (((2 * wq + ((lane >> 3) & 1)) ^ (lane & 7)) << 4);
        const uint32_t fbar = BAR(BAR_FULL) + 8 * par;
#pragma unroll 1
        for (int conv = 0; conv < 2; conv++) {
            uint32_t u[12][4];
            float4 cf[8];
            if (conv == 0) {
#pragma unroll
                for (int i = 0; i < 4; i++) ldsm4t(u[i], SM_XOWN + stg_off + i * 4096);
#pragma unroll
                for (int i = 0; i < 8; i++) ldsm4t(u[4 + i], SM_XH + stg_off + i * 4096);
                publish(BAR(BAR_XFREE), lane);
            } else {
                mbar_wait(BAR(BAR_HW), 0);
#pragma unroll
                for (int i = 0; i < 4; i++) ldsm4(u[i], act_off + ROW_BYTES + i * 4 * CH_PITCH);
            }
            uint4* hp = gs->h + (size_t)cta * 2048 + nw * 32 + lane;
            const uint32_t cfa = SM_COEF + par * 128 + (lane & 3) * 16;
            mbar_wait(BAR(BAR_STATS), conv);
            if (tid == 256) TL(22 + conv * 4);
            cf[0] = lds128f(cfa); cf[1] = lds128f(cfa + 64);
            norm_unit(u[0], cf[0], cf[1]);
            stsm4(act_off + ROW_BYTES, u[0][0], u[0][1], u[0][2], u[0][3]);
            publish(fbar, lane);
            if (tid == 256) TL(8 + conv * 8);
#pragma unroll
            for (int i = 2; i < 8; i++) cf[i] = lds128f(cfa + (i >> 1) * 256 + (i & 1) * 64);
            if (conv == 1) {
#pragma unroll
                for (int i = 0; i < 8; i++) ld_unit(u[4 + i], hp + i * 256);
            }
#pragma unroll
            for (int t = 1; t < 12; t++) {
                if (t == 4 && conv == 1) {
                    if (tid == 256) TL(24 + conv * 4);
                    unsigned it = 0;
                    while (true) {
                        bool oku = true, okd = true;
#pragma unroll
                        for (int i = 0; i < 16; i++) { oku = oku && u[4 + (i >> 2)][i & 3] != 0; okd = okd && u[8 + (i >> 2)][i & 3] != 0; }
                        if (__all_sync(0xffffffffu, (oku || r == 0) && (okd || r == HW - 1)) || ++it > SPIN_LIMIT) break;
#pragma unroll
                        for (int i = 0; i < 8; i++) ld_unit(u[4 + i], hp + i * 256);
                    }
#pragma unroll
                    for (int i = 0; i < 32; i++) u[4 + (i >> 2)][i & 3] = ~u[4 + (i >> 2)][i & 3];
                }
                norm_unit(u[t], cf[2 * (t & 3)], cf[2 * (t & 3) + 1]);
                if (t > 1) publish(fbar + 16 * (t - 1), lane);
                if (t < 4 || (t < 8 ? r != 0 : r != HW - 1))
                    stsm4(act_off + ky_of(t >> 2) * ROW_BYTES + (t & 3) * 4 * CH_PITCH, u[t][0], u[t][1], u[t][2], u[t][3]);
            }
            publish(fbar + 16 * 11, lane);
            if (conv == 1) {
#pragma unroll
                for (int i = 0; i < 8; i++) hp[i * 256] = make_uint4(0, 0, 0, 0);
            }
            if (tid == 256) TL(23 + conv * 4);
        }
    } else if (warp < 4) {
        const int wq = warp;
        if (wq != 0) {
            const int t = tid - 32;
            if (t == 95) TLG(1);
            if (t < NBAR) {
                const int cnt = t < BAR_WEMPTY ? 5 : (t <= BAR_HW ? 4 : (t == BAR_XFREE ? 8 : 1));
                mbar_init(BAR(0) + 8 * t, cnt);
            }
            fence_async_smem();
            bar_arrive(0, 96 + 128);
            bar_arrive(3, 256 + 96);
            const uint4 z = make_uint4(0, 0, 0, 0);
            sts128(SM_ACT + (t >> 1) * CH_PITCH + (t & 1) * 16, z);
            if (t < 2) sts128(SM_ACT + 3 * ROW_BYTES + t * 16, z);
            if (r == 0 || r == HW - 1) {
                for (int i = t; i < ROW_BYTES / 16; i += 96) sts128(SM_ACT + (r == 0 ? 0 : 2 * ROW_BYTES) + i * 16, z);
            }
            fence_async_smem();
        }
        bar_sync(2, 128);

        float d[64];
#pragma unroll
        for (int i = 0; i < 64; i++) d[i] = 0.f;
#pragma unroll 1
        for (int conv = 0; conv < 2; conv++) {
            fence_acc(d);
            float2 ev[16];
            mma_stages<0>(d, ev, conv, tid, gs);
            asm volatile("wgmma.wait_group.sync.aligned 0;" ::: "memory");
            fence_acc(d);
            if (tid == 0) TL(10 + conv * 8);
            if (conv == 1) break;

            float st[8];
#pragma unroll
            for (int g = 0; g < 4; g++) {
                float s = 0.f, q = 0.f, s2 = 0.f, q2 = 0.f;
#pragma unroll
                for (int jj = 0; jj < 4; jj++) {
                    const int j = g * 4 + jj;
                    const float2 e = ev[j];
                    d[4 * j + 0] += e.x; d[4 * j + 1] += e.y; d[4 * j + 2] += e.x; d[4 * j + 3] += e.y;
                    s += d[4 * j + 0]; q = fmaf(d[4 * j + 0], d[4 * j + 0], q);
                    s2 += d[4 * j + 1]; q2 = fmaf(d[4 * j + 1], d[4 * j + 1], q2);
                    s += d[4 * j + 2]; q = fmaf(d[4 * j + 2], d[4 * j + 2], q);
                    s2 += d[4 * j + 3]; q2 = fmaf(d[4 * j + 3], d[4 * j + 3], q2);
                }
                st[2 * g] = s + s2; st[2 * g + 1] = q + q2;
            }
            {
                const bool h16 = lane & 16, h8 = lane & 8, h4 = lane & 4;
                float a[4];
#pragma unroll
                for (int i = 0; i < 4; i++) {
                    float give = h16 ? st[i] : st[i + 4], keep = h16 ? st[i + 4] : st[i];
                    a[i] = keep + __shfl_xor_sync(0xffffffffu, give, 16);
                }
                float c2[2];
#pragma unroll
                for (int i = 0; i < 2; i++) {
                    float give = h8 ? a[i] : a[i + 2], keep = h8 ? a[i + 2] : a[i];
                    c2[i] = keep + __shfl_xor_sync(0xffffffffu, give, 8);
                }
                float give = h4 ? c2[0] : c2[1], keep = h4 ? c2[1] : c2[0];
                float t = keep + __shfl_xor_sync(0xffffffffu, give, 4);
                t += __shfl_xor_sync(0xffffffffu, t, 2);
                t += __shfl_xor_sync(0xffffffffu, t, 1);
                if ((lane & 3) == 0) sts32f(SM_RED + ((lane >> 2) * 4 + wq) * 4, t);
                bar_sync(2, 128);
                if (tid < 4) {
                    const float4 p = lds128f(SM_RED + tid * 32), p2 = lds128f(SM_RED + tid * 32 + 16);
                    red_add4(&gs->acc[(NB + b) * 32 + tid * 4], 1.f, (p.x + p.y) + (p.z + p.w), (p2.x + p2.y) + (p2.z + p2.w), 1.f);
                }
                if (tid == 0) TL(11);
                if (lane < LAG) mbar_arrive(BAR(BAR_WEMPTY + (NSTAGE - LAG) % NS) + 8 * lane);
            }
            const uint32_t hbase = SM_ACT + ROW_BYTES + (lane >> 4) * CH_PITCH + (2 + wq * 16 + (lane & 15)) * 16;
            uint4* hup = gs->h + (cta - 1) * 2048 + 1024 + tid;
            uint4* hdn = gs->h + (cta + 1) * 2048 + tid;
#pragma unroll
            for (int kc = 0; kc < 8; kc++) {
                const uint4 p = make_uint4(pack_bf(d[8 * kc + 0], d[8 * kc + 1]), pack_bf(d[8 * kc + 2], d[8 * kc + 3]),
                                           pack_bf(d[8 * kc + 4], d[8 * kc + 5]), pack_bf(d[8 * kc + 6], d[8 * kc + 7]));
                stsm4(hbase + kc * 2 * CH_PITCH, p.x, p.y, p.z, p.w);
                const uint4 n = make_uint4(~p.x, ~p.y, ~p.z, ~p.w);
                if (r != 0) hup[kc * 128] = n;
                if (r != HW - 1) hdn[kc * 128] = n;
            }
            __syncwarp();
            if (lane == 0) mbar_arrive(BAR(BAR_HW));
            if (tid == 0) TL(12);
            const uint32_t xbase = SM_XOWN + ((lane >> 4) * 8 + (lane & 7)) * 128 + (((2 * wq + ((lane >> 3) & 1)) ^ (lane & 7)) << 4);
#pragma unroll
            for (int kc = 0; kc < 8; kc++) {
                uint32_t p[4];
                ldsm4t(p, xbase + kc * 2048);
#pragma unroll
                for (int i = 0; i < 4; i++) { d[8 * kc + 2 * i] = bf_lo(p[i]); d[8 * kc + 2 * i + 1] = bf_hi(p[i]); }
            }
        }
        {
            const uint32_t obase = SM_W + ((lane >> 4) * 8 + (lane & 7)) * OUT_PITCH + (wq * 16 + ((lane >> 3) & 1) * 8) * 2;
#pragma unroll
            for (int kc = 0; kc < 8; kc++) {
                stsm4t(obase + kc * 16 * OUT_PITCH, pack_bf(d[8 * kc + 0], d[8 * kc + 1]), pack_bf(d[8 * kc + 2], d[8 * kc + 3]),
                       pack_bf(d[8 * kc + 4], d[8 * kc + 5]), pack_bf(d[8 * kc + 6], d[8 * kc + 7]));
            }
            bar_sync(2, 128);
            const int oc0 = tid >> 3;
            __nv_bfloat16* dst = out + ((size_t)(b * C + oc0) * HW + r) * HW + seg * 8;
#pragma unroll
            for (int i = 0; i < 8; i++)
                *reinterpret_cast<uint4*>(dst + (size_t)i * 16 * HW * HW) = lds128(SM_W + (oc0 + 16 * i) * OUT_PITCH + seg * 16);
            if (tid == 0) { TL(20); TLG(21); }
        }
    } else if (warp < 6) {
        bar_sync(0, 96 + 128);
        if (warp == 4) {
            while (clock32() - clk0 < W2DELAY) {}
            const char* w2s = reinterpret_cast<const char*>(w2) + woff;
#pragma unroll
            for (int k = 0; k < 4; k++) v[k] = __ldg(reinterpret_cast<const uint4*>(w2s + k * 256));
            if ((lane & 15) < 8) v[4] = __ldg(reinterpret_cast<const uint4*>(w2s + 1024));
            const uint2* wsrc = reinterpret_cast<const uint2*>(w_emb + (size_t)r * 12 * C) + lane;
            uint2 wv[12];
#pragma unroll
            for (int i = 0; i < 12; i++) wv[i] = __ldg(wsrc + i * (C / 4));
            float tv = 0.f;
            if (lane < 12) tv = __bfloat162float(t_emb[b * E + r * 12 + lane]);
            weight_block(v, SM_BNC + 2304, gs->wt + NSTAGE * STAGE_BYTES, cta, lane);
            const float sv = silu_half(0.5f * tv);
            float e0 = 0.f, e1 = 0.f, e2 = 0.f, e3 = 0.f;
#pragma unroll
            for (int i = 0; i < 12; i++) {
                const float sx = __shfl_sync(0xffffffffu, sv, i);
                e0 = fmaf(sx, bf_lo(wv[i].x), e0); e1 = fmaf(sx, bf_hi(wv[i].x), e1);
                e2 = fmaf(sx, bf_lo(wv[i].y), e2); e3 = fmaf(sx, bf_hi(wv[i].y), e3);
            }
            mbar_wait(BAR(BAR_WACQ), 0);
            red_add4(&gs->emb[b * C + lane * 4], e0, e1, e2, e3);
            __syncwarp();
            if (lane == 0) TL(13);
            if (lane < 2) asm volatile("red.release.gpu.global.add.u32 [%0], 1;" ::"l"(&gs->wcnt[(NB + lane) * 32]) : "memory");
            if (lane == 0) TL(14);
            unsigned it = 0;
            while (ld_relaxed(&gs->wcnt[(NB + b) * 32]) < (unsigned)NCTA && ++it < SPIN_LIMIT) {}
            fence_acquire();
            sts128(SM_EMB + lane * 16, ld_relaxed_v4(&gs->emb[b * C + lane * 4]));
            __syncwarp();
            if (lane == 0) { mbar_arrive(BAR(BAR_EMB)); TL(19); }
        }
    } else if (warp == 6) {
        bar_sync(0, 96 + 128);
        unsigned it = 0;
        while (ld_relaxed(&gs->wcnt[b * 32]) < (unsigned)NCTA && ++it < SPIN_LIMIT) {}
        fence_acquire();
        fence_async_global();
        if (lane == 0) { mbar_arrive(BAR(BAR_WACQ)); TL(6); }
        const unsigned char* wsrc = gs->wt;
#pragma unroll 1
        for (int round = 0; round < 2 * NSTAGE / NS; round++) {
            if (round == NSTAGE / NS) { mbar_wait(BAR(BAR_EMB), 0); fence_async_global(); }
            const uint32_t full = BAR(BAR_FULL) + 8 * NS * (round >= NSTAGE / NS ? round - NSTAGE / NS : round);
#pragma unroll
            for (int slot = 0; slot < NS; slot++) {
                if (slot == 9 && round == 0) mbar_wait(BAR(BAR_XFREE), 0);
                mbar_wait(BAR(BAR_WEMPTY + slot), (round & 1) ^ 1);
                if (elect_one()) {
                    mbar_expect(full + 8 * slot, STAGE_BYTES);
                    bulk_g2s(SM_W + slot * STAGE_BYTES, wsrc + slot * STAGE_BYTES, STAGE_BYTES, full + 8 * slot);
                }
            }
            wsrc += NS * STAGE_BYTES;
        }
    } else {
        const uint2 ga1 = __ldg(reinterpret_cast<const uint2*>(g1) + lane), bt1 = __ldg(reinterpret_cast<const uint2*>(be1) + lane);
        const uint2 ga2 = __ldg(reinterpret_cast<const uint2*>(g2) + lane), bt2 = __ldg(reinterpret_cast<const uint2*>(be2) + lane);
        bar_sync(0, 96 + 128);
#pragma unroll 1
        for (int conv = 0; conv < 2; conv++) {
            if (conv == 1) mbar_wait(BAR(BAR_EMB), 0);
            const float* asrc = &gs->acc[(conv * NB + b) * 32 + (lane >> 3) * 4];
            uint4 f;
            unsigned it = 0;
            while (true) {
                f = ld_relaxed_v4(asrc);
                const bool ok = (f.x == 0x42800000u) & (f.w == 0x42800000u);
                if (__all_sync(0xffffffffu, ok) || ++it > SPIN_LIMIT) break;
            }
            if (lane == 0) TL(7 + conv * 8);
            const float inv_n = 1.0f / (32.0f * HW * HW);
            const float mean = __uint_as_float(f.y) * inv_n;
            const float var = fmaxf(fmaf(-mean, mean, __uint_as_float(f.z) * inv_n), 0.f);
            const float rs = 0.5f * rsqrtf(var + 1e-5f);
            const uint2 ga = conv ? ga2 : ga1, bt = conv ? bt2 : bt1;
            float4 k0, k1;
            k0.x = rs * bf_lo(ga.x); k0.y = rs * bf_hi(ga.x); k1.x = rs * bf_lo(ga.y); k1.y = rs * bf_hi(ga.y);
            k0.z = fmaf(-mean, k0.x, 0.5f * bf_lo(bt.x)); k0.w = fmaf(-mean, k0.y, 0.5f * bf_hi(bt.x));
            k1.z = fmaf(-mean, k1.x, 0.5f * bf_lo(bt.y)); k1.w = fmaf(-mean, k1.y, 0.5f * bf_hi(bt.y));
            sts128f(SM_COEF + lane * 32, k0);
            sts128f(SM_COEF + lane * 32 + 16, k1);
            __syncwarp();
            if (lane == 0) mbar_arrive(BAR(BAR_STATS));
        }
        if (r == 0) {
            if (lane < 16) gs->acc[b * 32 + lane] = 0.f;
            if (lane < 2) gs->wcnt[(lane * NB + b) * 32] = 0;
        }
    }
}

}

extern "C" void kernel_launch(void* const* d_in, const int* in_sizes, int n_in, void* d_out, int out_size) {
    (void)in_sizes; (void)n_in; (void)out_size;
    static Scratch* gs = nullptr;
    if (!gs) {
        cudaFuncSetAttribute(resblock_kernel, cudaFuncAttributeMaxDynamicSharedMemorySize, SM_TOTAL);
        cudaGetSymbolAddress((void**)&gs, g_scratch);
    }
    resblock_kernel<<<NCTA, NTHREADS, SM_TOTAL>>>(
        (const __nv_bfloat16*)d_in[0], (const __nv_bfloat16*)d_in[4], (const __nv_bfloat16*)d_in[1],
        (const __nv_bfloat16*)d_in[2], (const __nv_bfloat16*)d_in[3], (const __nv_bfloat16*)d_in[5],
        (const __nv_bfloat16*)d_in[6], (const __nv_bfloat16*)d_in[7], (const __nv_bfloat16*)d_in[8],
        (__nv_bfloat16*)d_out, gs);
}
```

```cpp
#include <cuda_runtime.h>
#include <cuda_bf16.h>
#include <stdint.h>

namespace {

constexpr int C = 128, HW = 64, NB = 2, E = 768;
constexpr int NCTA = NB * HW;
constexpr int NTHREADS = 16 * 32;
constexpr int CH_PITCH = 66 * 16;
constexpr int ROW_BYTES = 16 * CH_PITCH;
constexpr int STEP_BYTES = 4096;
constexpr int STAGE_BYTES = 3 * STEP_BYTES;
constexpr int NSTAGE = 24;
constexpr int NS = 12;
constexpr int LAG = 1;
#define XDELAY 900
#define HDELAY 1000
#define W2DELAY 2800

constexpr uint32_t SMEM_BASE = 0x400;
constexpr uint32_t SM_ACT = SMEM_BASE;
constexpr uint32_t SM_XOWN = SM_ACT + 3 * ROW_BYTES + 128;
constexpr uint32_t SM_W = SM_XOWN + 16384;
constexpr uint32_t SM_XH = SM_W + 9 * STAGE_BYTES;
constexpr uint32_t SM_COEF = SM_W + NS * STAGE_BYTES;
constexpr uint32_t SM_EMB = SM_COEF + 1024;
constexpr uint32_t SM_ONES = SM_EMB + 2048;
constexpr uint32_t SM_RED = SM_ONES + 256;
constexpr uint32_t SM_BNC = SM_RED + 128;
constexpr uint32_t SM_BAR = SM_BNC + 2 * 2304;
constexpr int BAR_FULL = 0, BAR_WEMPTY = NSTAGE, BAR_HW = BAR_WEMPTY + NS, BAR_STATS = BAR_HW + 1,
              BAR_EMB = BAR_STATS + 1, BAR_WACQ = BAR_EMB + 1, BAR_XH = BAR_WACQ + 1, BAR_XFREE = BAR_XH + 1, NBAR = BAR_XFREE + 1;
constexpr int SM_TOTAL = SM_BAR + NBAR * 8 - SMEM_BASE;
static_assert(SM_TOTAL <= 232448, "smem");
static_assert(NBAR <= 96, "barrier init");
constexpr int OUT_PITCH = 144;
__host__ __device__ constexpr uint32_t BAR(int i) { return SM_BAR + 8 * i; }
__host__ __device__ constexpr int ky_of(int kyo) { return kyo == 0 ? 1 : (kyo == 1 ? 0 : 2); }

constexpr unsigned SPIN_LIMIT = 1u << 16;

struct Scratch {
    float acc[2 * NB * 32];
    unsigned wcnt[2 * NB * 32];
    float emb[NB * C];
    unsigned char wt[2 * NSTAGE * STAGE_BYTES];
    uint4 h[NCTA * 2048];
};
__device__ __align__(1024) Scratch g_scratch;
#define TL(i) do {} while (0)
#define TLG(i) do {} while (0)

__device__ __forceinline__ unsigned clock32() { unsigned c; asm volatile("mov.u32 %0, %%clock;" : "=r"(c)); return c; }
__device__ __forceinline__ void mbar_init(uint32_t bar, int cnt) {
    asm volatile("mbarrier.init.shared::cta.b64 [%0], %1;" ::"r"(bar), "r"(cnt) : "memory");
}
__device__ __forceinline__ void mbar_arrive(uint32_t bar) {
    asm volatile("mbarrier.arrive.shared::cta.b64 _, [%0];" ::"r"(bar) : "memory");
}
__device__ __forceinline__ void mbar_expect(uint32_t bar, uint32_t bytes) {
    asm volatile("mbarrier.arrive.expect_tx.shared::cta.b64 _, [%0], %1;" ::"r"(bar), "r"(bytes) : "memory");
}
__device__ __forceinline__ bool mbar_try(uint32_t bar, uint32_t par) {
    uint32_t ok;
    asm volatile("{\n.reg .pred p;\nmbarrier.try_wait.parity.shared::cta.b64 p, [%1], %2;\nselp.u32 %0, 1, 0, p;\n}"
                 : "=r"(ok) : "r"(bar), "r"(par) : "memory");
    return ok;
}
__device__ __forceinline__ bool mbar_test(uint32_t bar, uint32_t par) {
    uint32_t ok;
    asm volatile("{\n.reg .pred p;\nmbarrier.test_wait.parity.shared::cta.b64 p, [%1], %2;\nselp.u32 %0, 1, 0, p;\n}"
                 : "=r"(ok) : "r"(bar), "r"(par) : "memory");
    return ok;
}
__device__ __forceinline__ void mbar_wait(uint32_t bar, uint32_t par) {
    unsigned it = 0;
#pragma unroll 1
    while (!mbar_try(bar, par) && ++it < SPIN_LIMIT) {}
}
__device__ __forceinline__ bool elect_one() {
    uint32_t p;
    asm volatile("{\n.reg .pred p;\nelect.sync _|p, 0xffffffff;\nselp.u32 %0, 1, 0, p;\n}" : "=r"(p));
    return p;
}
__device__ __forceinline__ void fence_async_smem() { asm volatile("fence.proxy.async.shared::cta;" ::: "memory"); }
__device__ __forceinline__ void fence_async_global() { asm volatile("fence.proxy.async.global;" ::: "memory"); }
__device__ __forceinline__ void fence_acquire() { asm volatile("fence.acquire.gpu;" ::: "memory"); }
__device__ __forceinline__ void bar_sync(int id, int n) { asm volatile("bar.sync %0, %1;" ::"r"(id), "r"(n) : "memory"); }
__device__ __forceinline__ void bar_arrive(int id, int n) { asm volatile("bar.arrive %0, %1;" ::"r"(id), "r"(n) : "memory"); }
__device__ __forceinline__ void bulk_g2s(uint32_t dst, const void* src, uint32_t bytes, uint32_t bar) {
    asm volatile("cp.async.bulk.shared::cluster.global.mbarrier::complete_tx::bytes [%0], [%1], %2, [%3];"
                 ::"r"(dst), "l"(src), "r"(bytes), "r"(bar) : "memory");
}
__device__ __forceinline__ uint4 ld_relaxed_v4(const void* p) {
    uint4 v;
    asm volatile("ld.relaxed.gpu.global.v4.u32 {%0,%1,%2,%3}, [%4];" : "=r"(v.x), "=r"(v.y), "=r"(v.z), "=r"(v.w) : "l"(p) : "memory");
    return v;
}
__device__ __forceinline__ unsigned ld_relaxed(const void* p) {
    unsigned v;
    asm volatile("ld.relaxed.gpu.global.u32 %0, [%1];" : "=r"(v) : "l"(p) : "memory");
    return v;
}
__device__ __forceinline__ void red_add4(float* p, float a, float b, float c, float d) {
    asm volatile("red.relaxed.gpu.global.add.v4.f32 [%0], {%1,%2,%3,%4};" ::"l"(p), "f"(a), "f"(b), "f"(c), "f"(d) : "memory");
}
__device__ __forceinline__ void sts128(uint32_t a, uint4 v) {
    asm volatile("st.shared.v4.u32 [%0], {%1,%2,%3,%4};" ::"r"(a), "r"(v.x), "r"(v.y), "r"(v.z), "r"(v.w) : "memory");
}
__device__ __forceinline__ void sts128f(uint32_t a, float4 v) {
    asm volatile("st.shared.v4.f32 [%0], {%1,%2,%3,%4};" ::"r"(a), "f"(v.x), "f"(v.y), "f"(v.z), "f"(v.w) : "memory");
}
__device__ __forceinline__ void sts32f(uint32_t a, float v) { asm volatile("st.shared.f32 [%0], %1;" ::"r"(a), "f"(v) : "memory"); }
__device__ __forceinline__ uint4 lds128(uint32_t a) {
    uint4 v;
    asm volatile("ld.shared.v4.u32 {%0,%1,%2,%3}, [%4];" : "=r"(v.x), "=r"(v.y), "=r"(v.z), "=r"(v.w) : "r"(a) : "memory");
    return v;
}
__device__ __forceinline__ float4 lds128f(uint32_t a) {
    float4 v;
    asm volatile("ld.shared.v4.f32 {%0,%1,%2,%3}, [%4];" : "=f"(v.x), "=f"(v.y), "=f"(v.z), "=f"(v.w) : "r"(a) : "memory");
    return v;
}
__device__ __forceinline__ float2 lds64f(uint32_t a) {
    float2 v;
    asm volatile("ld.shared.v2.f32 {%0,%1}, [%2];" : "=f"(v.x), "=f"(v.y) : "r"(a) : "memory");
    return v;
}
__device__ __forceinline__ float bf_lo(uint32_t u) { return __uint_as_float(u << 16); }
__device__ __forceinline__ float bf_hi(uint32_t u) { return __uint_as_float(u & 0xffff0000u); }
__device__ __forceinline__ uint32_t pack_bf(float lo, float hi) {
    uint32_t r;
    asm("cvt.rn.bf16x2.f32 %0, %1, %2;" : "=r"(r) : "f"(hi), "f"(lo));
    return r;
}
__device__ __forceinline__ float tanh_fast(float x) {
    float r;
    asm volatile("tanh.approx.f32 %0, %1;" : "=f"(r) : "f"(x));
    return r;
}
__device__ __forceinline__ float silu_half(float h) { return fmaf(h, tanh_fast(h), h); }
__device__ __forceinline__ void ldsm4(uint32_t (&u)[4], uint32_t a) {
    asm volatile("ldmatrix.sync.aligned.m8n8.x4.shared.b16 {%0,%1,%2,%3}, [%4];"
                 : "=r"(u[0]), "=r"(u[1]), "=r"(u[2]), "=r"(u[3]) : "r"(a) : "memory");
}
__device__ __forceinline__ void ldsm4t(uint32_t (&u)[4], uint32_t a) {
    asm volatile("ldmatrix.sync.aligned.m8n8.x4.trans.shared.b16 {%0,%1,%2,%3}, [%4];"
                 : "=r"(u[0]), "=r"(u[1]), "=r"(u[2]), "=r"(u[3]) : "r"(a) : "memory");
}
__device__ __forceinline__ void stsm4(uint32_t a, uint32_t p0, uint32_t p1, uint32_t p2, uint32_t p3) {
    asm volatile("stmatrix.sync.aligned.m8n8.x4.shared.b16 [%0], {%1,%2,%3,%4};" ::"r"(a), "r"(p0), "r"(p1), "r"(p2), "r"(p3) : "memory");
}
__device__ __forceinline__ void stsm4t(uint32_t a, uint32_t p0, uint32_t p1, uint32_t p2, uint32_t p3) {
    asm volatile("stmatrix.sync.aligned.m8n8.x4.trans.shared.b16 [%0], {%1,%2,%3,%4};" ::"r"(a), "r"(p0), "r"(p1), "r"(p2), "r"(p3) : "memory");
}

#define R8(o) "+f"(d[o]), "+f"(d[o + 1]), "+f"(d[o + 2]), "+f"(d[o + 3]), "+f"(d[o + 4]), "+f"(d[o + 5]), "+f"(d[o + 6]), "+f"(d[o + 7])
template <uint32_t ALO, uint32_t BLO, uint64_t AHI = 8>
__device__ __forceinline__ void wgmma128(float (&d)[64]) {
    asm volatile(
        "wgmma.mma_async.sync.aligned.m64n128k16.f32.bf16.bf16 "
        "{%0,%1,%2,%3,%4,%5,%6,%7,%8,%9,%10,%11,%12,%13,%14,%15,%16,%17,%18,%19,%20,%21,%22,%23,%24,%25,%26,%27,%28,%29,%30,%31,"
        "%32,%33,%34,%35,%36,%37,%38,%39,%40,%41,%42,%43,%44,%45,%46,%47,%48,%49,%50,%51,%52,%53,%54,%55,%56,%57,%58,%59,%60,%61,%62,%63},"
        " %64, %65, 1, 1, 1, 0, 0;"
        : R8(0), R8(8), R8(16), R8(24), R8(32), R8(40), R8(48), R8(56)
        : "l"((AHI << 32) | ALO), "l"((8ull << 32) | BLO));
}
template <int S>
__device__ __forceinline__ void mma_stages(float (&d)[64], int conv, int tid, Scratch* gs) {
    constexpr uint32_t A = ((SM_ACT + ky_of(S >> 3) * ROW_BYTES + (S & 7) * 2 * CH_PITCH + 16) >> 4) | ((CH_PITCH >> 4) << 16);
    constexpr uint32_t B = ((SM_W + (S % NS) * STAGE_BYTES) >> 4) | ((2048 >> 4) << 16);
    if (S == 0) mbar_wait(BAR(BAR_FULL), conv);
    bool next_ok = true;
    constexpr uint32_t NEXT = S + 1 < NSTAGE ? BAR(BAR_FULL + S + 1) : BAR(BAR_EMB);
    const int npar = S + 1 < NSTAGE ? conv : 0;
    next_ok = mbar_test(NEXT, npar);
    if (S == 0 && tid == 0) TL(32 + conv * 24);
    asm volatile("wgmma.fence.sync.aligned;" ::: "memory");
    wgmma128<A, B>(d);
    wgmma128<A + 1, B + (STEP_BYTES >> 4)>(d);
    wgmma128<A + 2, B + 2 * (STEP_BYTES >> 4)>(d);
    asm volatile("wgmma.commit_group.sync.aligned;" ::: "memory");
    if (S >= LAG) {
        asm volatile("wgmma.wait_group.sync.aligned %0;" ::"n"(LAG) : "memory");
        if ((tid & 31) == 0) mbar_arrive(BAR(BAR_WEMPTY + (S + NS - LAG) % NS));
    }
    if (!next_ok) mbar_wait(NEXT, npar);
    if constexpr (S + 1 < NSTAGE) mma_stages<S + 1>(d, conv, tid, gs);
}

__device__ __forceinline__ void weight_block(const uint4 (&t)[5], uint32_t bounce, unsigned char* wt, int cta, int lane) {
    const uint32_t bw = bounce + (lane >> 4) * 1152 + (lane & 15) * 16;
#pragma unroll
    for (int k = 0; k < 4; k++) sts128(bw + k * 256, t[k]);
    if ((lane & 15) < 8) sts128(bw + 1024, t[4]);
    __syncwarp();
    if (lane < 16) {
        uint32_t v[36];
#pragma unroll
        for (int i = 0; i < 9; i++) {
            const uint4 q = lds128(bounce + (lane & 1) * 1152 + (lane >> 1) * 144 + i * 16);
            v[4 * i] = q.x; v[4 * i + 1] = q.y; v[4 * i + 2] = q.z; v[4 * i + 3] = q.w;
        }
        const int cc = (cta >> 6) * 8 + (lane >> 1);
        unsigned char* dst = wt + (cc >> 1) * STAGE_BYTES + (cc & 1) * 2048 + ((cta & 63) * 2 + (lane & 1)) * 16;
#pragma unroll
        for (int kyo = 0; kyo < 3; kyo++) {
#pragma unroll
            for (int kx = 0; kx < 3; kx++) {
                const int tap = ky_of(kyo) * 3 + kx;
                uint32_t o[4];
#pragma unroll
                for (int m = 0; m < 4; m++) {
                    const int i0 = 18 * m + tap, i1 = i0 + 9;
                    const uint32_t sel = ((i0 & 1) ? 0x32u : 0x10u) | ((i1 & 1) ? 0x7600u : 0x5400u);
                    o[m] = __byte_perm(v[i0 >> 1], v[i1 >> 1], sel);
                }
                *reinterpret_cast<uint4*>(dst + (kyo * 24 + kx) * STEP_BYTES) = make_uint4(o[0], o[1], o[2], o[3]);
            }
        }
    }
}
__device__ __forceinline__ uint32_t act2(uint32_t u, const float4& cf) {
    return pack_bf(silu_half(fmaf(bf_lo(u), cf.x, cf.z)), silu_half(fmaf(bf_hi(u), cf.y, cf.w)));
}
__device__ __forceinline__ void norm_unit(uint32_t (&u)[4], const float4& ca, const float4& cb) {
    u[0] = act2(u[0], ca); u[1] = act2(u[1], ca); u[2] = act2(u[2], cb); u[3] = act2(u[3], cb);
}
__device__ __forceinline__ void publish(uint32_t bar, int lane) {
    fence_async_smem();
    __syncwarp();
    if (lane == 0) mbar_arrive(bar);
}
__device__ __forceinline__ void publish2(uint32_t bar, int lane) {
    fence_async_smem();
    __syncwarp();
    if (lane < 2) mbar_arrive(bar + 16 * lane);
}
__device__ __forceinline__ void fence_acc(float (&d)[64]) {
#pragma unroll
    for (int i = 0; i < 64; i++) asm volatile("" : "+f"(d[i])::"memory");
}
__device__ __forceinline__ void ld_unit(uint32_t (&u)[4], const uint4* p) {
    asm volatile("ld.relaxed.gpu.global.v4.u32 {%0,%1,%2,%3}, [%4];" : "=r"(u[0]), "=r"(u[1]), "=r"(u[2]), "=r"(u[3]) : "l"(p) : "memory");
}

__global__ void __launch_bounds__(NTHREADS, 1)
resblock_kernel(const __nv_bfloat16* __restrict__ x, const __nv_bfloat16* __restrict__ w1,
                const __nv_bfloat16* __restrict__ t_emb, const __nv_bfloat16* __restrict__ g1,
                const __nv_bfloat16* __restrict__ be1, const __nv_bfloat16* __restrict__ w_emb,
                const __nv_bfloat16* __restrict__ g2, const __nv_bfloat16* __restrict__ be2,
                const __nv_bfloat16* __restrict__ w2, __nv_bfloat16* __restrict__ out, Scratch* __restrict__ gs) {
    const unsigned clk0 = clock32();
    const int tid = threadIdx.x, warp = tid >> 5, lane = tid & 31;
    const int cta = blockIdx.x, b = cta >> 6, r = cta & 63;

    const uint32_t woff = ((2 * r + (lane >> 4)) * C + b * 64) * 18 + (lane & 15) * 16;
    const int c0 = (warp - 8) * 16 + (lane >> 3), seg = lane & 7;
    uint4 v[5];
    if (warp == 0) {
        const char* w1s = reinterpret_cast<const char*>(w1) + woff;
#pragma unroll
        for (int k = 0; k < 4; k++) v[k] = __ldg(reinterpret_cast<const uint4*>(w1s + k * 256));
        if ((lane & 15) < 8) v[4] = __ldg(reinterpret_cast<const uint4*>(w1s + 1024));
        weight_block(v, SM_BNC, gs->wt, cta, lane);
        if (r == 0) {
            if (lane < 16) gs->acc[(NB + b) * 32 + lane] = 0.f;
            *reinterpret_cast<float4*>(&gs->emb[b * C + lane * 4]) = make_float4(0.f, 0.f, 0.f, 0.f);
        }
        __syncwarp();
        if (lane == 0) TL(4);
        if (lane < 2) asm volatile("red.release.gpu.global.add.u32 [%0], 1;" ::"l"(&gs->wcnt[lane * 32]) : "memory");
        if (lane == 0) TL(5);
    }

    if (warp >= 8) {
        const int nw = warp - 8;
        const char* src = reinterpret_cast<const char*>(x) + (uint32_t)(((b * C + c0) * HW + r) * HW * 2 + seg * 16);
#pragma unroll
        for (int k = 0; k < 4; k++) v[k] = make_uint4(0, 0, 0, 0);
#pragma unroll 1
        for (int pass = 0; pass < 2; pass++) {
            if (pass) {
                while (clock32() - clk0 < XDELAY) {}
#pragma unroll
                for (int k = 0; k < 4; k++) v[k] = __ldg(reinterpret_cast<const uint4*>(src + k * (4 * HW * HW * 2)));
#pragma unroll
                for (int i = 0; i < 8; i++) {
                    if (i < 4 ? (r != 0) : (r != HW - 1))
                        asm volatile("cp.async.cg.shared.global [%0], [%1], 16;"
                                     ::"r"(SM_XH + (i >> 2) * 16384 + c0 * 128 + (i & 3) * 512 + ((seg ^ ((c0 + 4 * i) & 7)) << 4)),
                                       "l"(src + (i < 4 ? -HW * 2 : HW * 2) + (i & 3) * (4 * HW * HW * 2)) : "memory");
                }
                if (tid == 256) TL(82);
            }
            float s = 0.f, q = 0.f, s2 = 0.f, q2 = 0.f;
#pragma unroll
            for (int i = 0; i < 4; i++) {
                const uint32_t u[4] = {v[i].x, v[i].y, v[i].z, v[i].w};
#pragma unroll
                for (int k = 0; k < 4; k++) {
                    const float lo = bf_lo(u[k]), hi = bf_hi(u[k]);
                    s += lo; q = fmaf(lo, lo, q);
                    s2 += hi; q2 = fmaf(hi, hi, q2);
                }
            }
            s += s2; q += q2;
            float give = (lane < 16) ? q : s, keep = (lane < 16) ? s : q;
            keep += __shfl_xor_sync(0xffffffffu, give, 16);
            if (tid == 256) TL(2);
#pragma unroll
            for (int m = 8; m >= 1; m >>= 1) keep += __shfl_xor_sync(0xffffffffu, keep, m);
            if ((lane & 15) == 0) sts32f(SM_RED + (nw * 2 + (lane >> 4)) * 4, keep);
            bar_sync(3 + pass, pass ? 256 : 256 + 96);
            if (pass && tid < 256 + 4) {
                const float4 p = lds128f(SM_RED + lane * 16);
                red_add4(&gs->acc[b * 32 + lane * 4], 1.f, p.x + p.z, p.y + p.w, 1.f);
            }
            if (tid == 256) TL(3);
        }
        {
#pragma unroll
            for (int i = 0; i < 4; i++) sts128(SM_XOWN + c0 * 128 + i * 512 + ((seg ^ ((c0 + 4 * i) & 7)) << 4), v[i]);
            asm volatile("cp.async.wait_all;" ::: "memory");
            bar_sync(4, 256);
        }
        const int par = nw >> 2, wq = nw & 3;
        const uint32_t act_off = SM_ACT + (par * 2 + (lane >> 4)) * CH_PITCH + (2 + wq * 16 + (lane & 15)) * 16;
        const uint32_t stg_off = (par * 16 + (lane >> 4) * 8 + (lane & 7)) * 128 + (((2 * wq + ((lane >> 3) & 1)) ^ (lane & 7)) << 4);
        const uint32_t fbar = BAR(BAR_FULL) + 8 * par;
#pragma unroll 1
        for (int conv = 0; conv < 2; conv++) {
            uint32_t u[12][4];
            float4 cf[8];
            if (conv == 0) {
#pragma unroll
                for (int i = 0; i < 4; i++) ldsm4t(u[i], SM_XOWN + stg_off + i * 4096);
#pragma unroll
                for (int i = 0; i < 8; i++) ldsm4t(u[4 + i], SM_XH + stg_off + i * 4096);
                publish(BAR(BAR_XFREE), lane);
            } else {
                mbar_wait(BAR(BAR_HW), 0);
#pragma unroll
                for (int i = 0; i < 4; i++) ldsm4(u[i], act_off + ROW_BYTES + i * 4 * CH_PITCH);
            }
            uint4* hp = gs->h + (size_t)cta * 2048 + nw * 32 + lane;
            const uint32_t cfa = SM_COEF + par * 128 + (lane & 3) * 16;
            mbar_wait(BAR(BAR_STATS), conv);
            if (tid == 256) TL(22 + conv * 4);
            cf[0] = lds128f(cfa); cf[1] = lds128f(cfa + 64);
            norm_unit(u[0], cf[0], cf[1]);
            stsm4(act_off + ROW_BYTES, u[0][0], u[0][1], u[0][2], u[0][3]);
            publish(fbar, lane);
            if (tid == 256) TL(8 + conv * 8);
#pragma unroll
            for (int i = 2; i < 8; i++) cf[i] = lds128f(cfa + (i >> 1) * 256 + (i & 1) * 64);
            if (conv == 1) {
#pragma unroll
                for (int i = 0; i < 8; i++) ld_unit(u[4 + i], hp + i * 256);
            }
#pragma unroll
            for (int t = 1; t < 12; t++) {
                if (t == 4) publish(fbar + 16 * 3, lane);
                if (t == 4 && conv == 1) {
                    if (tid == 256) TL(24 + conv * 4);
                    unsigned it = 0;
                    while (true) {
                        bool oku = true, okd = true;
#pragma unroll
                        for (int i = 0; i < 16; i++) { oku = oku && u[4 + (i >> 2)][i & 3] != 0; okd = okd && u[8 + (i >> 2)][i & 3] != 0; }
                        if (__all_sync(0xffffffffu, (oku || r == 0) && (okd || r == HW - 1)) || ++it > SPIN_LIMIT) break;
#pragma unroll
                        for (int i = 0; i < 8; i++) ld_unit(u[4 + i], hp + i * 256);
                    }
#pragma unroll
                    for (int i = 0; i < 32; i++) u[4 + (i >> 2)][i & 3] = ~u[4 + (i >> 2)][i & 3];
                }
                norm_unit(u[t], cf[2 * (t & 3)], cf[2 * (t & 3) + 1]);
                if (t == 2 || t == 3) publish(fbar + 16 * (t - 1), lane);
                if (t >= 6 && !(t & 1)) publish2(fbar + 16 * (t - 2), lane);
                if (t < 4 || (t < 8 ? r != 0 : r != HW - 1))
                    stsm4(act_off + ky_of(t >> 2) * ROW_BYTES + (t & 3) * 4 * CH_PITCH, u[t][0], u[t][1], u[t][2], u[t][3]);
            }
            publish2(fbar + 16 * 10, lane);
            if (conv == 1) {
#pragma unroll
                for (int i = 0; i < 8; i++) hp[i * 256] = make_uint4(0, 0, 0, 0);
            }
            if (tid == 256) TL(23 + conv * 4);
        }
    } else if (warp < 4) {
        const int wq = warp;
        if (wq != 0) {
            const int t = tid - 32;
            if (t == 95) TLG(1);
            if (t < NBAR) {
                const int cnt = t < BAR_WEMPTY ? 5 : (t <= BAR_HW ? 4 : (t == BAR_XFREE ? 8 : 1));
                mbar_init(BAR(0) + 8 * t, cnt);
            }
            fence_async_smem();
            bar_arrive(0, 96 + 128);
            bar_arrive(3, 256 + 96);
            const uint4 z = make_uint4(0, 0, 0, 0);
            sts128(SM_ACT + (t >> 1) * CH_PITCH + (t & 1) * 16, z);
            if (t < 2) sts128(SM_ACT + 3 * ROW_BYTES + t * 16, z);
            if (t < 16) sts128(SM_ONES + t * 16, make_uint4(t < 8 ? 0x3f803f80u : 0u, 0, 0, 0));
            if (r == 0 || r == HW - 1) {
                for (int i = t; i < ROW_BYTES / 16; i += 96) sts128(SM_ACT + (r == 0 ? 0 : 2 * ROW_BYTES) + i * 16, z);
            }
            fence_async_smem();
        }
        bar_sync(2, 128);

        float d[64];
#pragma unroll
        for (int i = 0; i < 64; i++) d[i] = 0.f;
#pragma unroll 1
        for (int conv = 0; conv < 2; conv++) {
            fence_acc(d);
            mma_stages<0>(d, conv, tid, gs);
            if (conv == 0) {
                asm volatile("wgmma.fence.sync.aligned;" ::: "memory");
                wgmma128<(SM_ONES >> 4) | (8u << 16), (SM_EMB >> 4), 0>(d);
                asm volatile("wgmma.commit_group.sync.aligned;" ::: "memory");
            }
            asm volatile("wgmma.wait_group.sync.aligned 0;" ::: "memory");
            fence_acc(d);
            if (tid == 0) TL(10 + conv * 8);
            if (conv == 1) break;

            float st[8];
#pragma unroll
            for (int g = 0; g < 4; g++) {
                float s = 0.f, q = 0.f, s2 = 0.f, q2 = 0.f;
#pragma unroll
                for (int jj = 0; jj < 4; jj++) {
                    const int j = g * 4 + jj;
                    s += d[4 * j + 0]; q = fmaf(d[4 * j + 0], d[4 * j + 0], q);
                    s2 += d[4 * j + 1]; q2 = fmaf(d[4 * j + 1], d[4 * j + 1], q2);
                    s += d[4 * j + 2]; q = fmaf(d[4 * j + 2], d[4 * j + 2], q);
                    s2 += d[4 * j + 3]; q2 = fmaf(d[4 * j + 3], d[4 * j + 3], q2);
                }
                st[2 * g] = s + s2; st[2 * g + 1] = q + q2;
            }
            {
                const bool h16 = lane & 16, h8 = lane & 8, h4 = lane & 4;
                float a[4];
#pragma unroll
                for (int i = 0; i < 4; i++) {
                    float give = h16 ? st[i] : st[i + 4], keep = h16 ? st[i + 4] : st[i];
                    a[i] = keep + __shfl_xor_sync(0xffffffffu, give, 16);
                }
                float c2[2];
#pragma unroll
                for (int i = 0; i < 2; i++) {
                    float give = h8 ? a[i] : a[i + 2], keep = h8 ? a[i + 2] : a[i];
                    c2[i] = keep + __shfl_xor_sync(0xffffffffu, give, 8);
                }
                float give = h4 ? c2[0] : c2[1], keep = h4 ? c2[1] : c2[0];
                float t = keep + __shfl_xor_sync(0xffffffffu, give, 4);
                t += __shfl_xor_sync(0xffffffffu, t, 2);
                t += __shfl_xor_sync(0xffffffffu, t, 1);
                if ((lane & 3) == 0) sts32f(SM_RED + ((lane >> 2) * 4 + wq) * 4, t);
                bar_sync(2, 128);
                if (tid < 4) {
                    const float4 p = lds128f(SM_RED + tid * 32), p2 = lds128f(SM_RED + tid * 32 + 16);
                    red_add4(&gs->acc[(NB + b) * 32 + tid * 4], 1.f, (p.x + p.y) + (p.z + p.w), (p2.x + p2.y) + (p2.z + p2.w), 1.f);
                }
                if (tid == 0) TL(11);
                if (lane < LAG) mbar_arrive(BAR(BAR_WEMPTY + (NSTAGE - LAG) % NS) + 8 * lane);
            }
            const uint32_t hbase = SM_ACT + ROW_BYTES + (lane >> 4) * CH_PITCH + (2 + wq * 16 + (lane & 15)) * 16;
            uint4* hup = gs->h + (cta - 1) * 2048 + 1024 + tid;
            uint4* hdn = gs->h + (cta + 1) * 2048 + tid;
#pragma unroll
            for (int kc = 0; kc < 8; kc++) {
                const uint4 p = make_uint4(pack_bf(d[8 * kc + 0], d[8 * kc + 1]), pack_bf(d[8 * kc + 2], d[8 * kc + 3]),
                                           pack_bf(d[8 * kc + 4], d[8 * kc + 5]), pack_bf(d[8 * kc + 6], d[8 * kc + 7]));
                stsm4(hbase + kc * 2 * CH_PITCH, p.x, p.y, p.z, p.w);
                const uint4 n = make_uint4(~p.x, ~p.y, ~p.z, ~p.w);
                if (r != 0) hup[kc * 128] = n;
                if (r != HW - 1) hdn[kc * 128] = n;
            }
            __syncwarp();
            if (lane == 0) mbar_arrive(BAR(BAR_HW));
            if (tid == 0) TL(12);
            const uint32_t xbase = SM_XOWN + ((lane >> 4) * 8 + (lane & 7)) * 128 + (((2 * wq + ((lane >> 3) & 1)) ^ (lane & 7)) << 4);
#pragma unroll
            for (int kc = 0; kc < 8; kc++) {
                uint32_t p[4];
                ldsm4t(p, xbase + kc * 2048);
#pragma unroll
                for (int i = 0; i < 4; i++) { d[8 * kc + 2 * i] = bf_lo(p[i]); d[8 * kc + 2 * i + 1] = bf_hi(p[i]); }
            }
        }
        {
            const uint32_t obase = SM_W + ((lane >> 4) * 8 + (lane & 7)) * OUT_PITCH + (wq * 16 + ((lane >> 3) & 1) * 8) * 2;
#pragma unroll
            for (int kc = 0; kc < 8; kc++) {
                stsm4t(obase + kc * 16 * OUT_PITCH, pack_bf(d[8 * kc + 0], d[8 * kc + 1]), pack_bf(d[8 * kc + 2], d[8 * kc + 3]),
                       pack_bf(d[8 * kc + 4], d[8 * kc + 5]), pack_bf(d[8 * kc + 6], d[8 * kc + 7]));
            }
            bar_sync(2, 128);
            const int oc0 = tid >> 3;
            __nv_bfloat16* dst = out + ((size_t)(b * C + oc0) * HW + r) * HW + seg * 8;
#pragma unroll
            for (int i = 0; i < 8; i++)
                *reinterpret_cast<uint4*>(dst + (size_t)i * 16 * HW * HW) = lds128(SM_W + (oc0 + 16 * i) * OUT_PITCH + seg * 16);
            if (tid == 0) { TL(20); TLG(21); }
        }
    } else if (warp < 6) {
        bar_sync(0, 96 + 128);
        if (warp == 4) {
            while (clock32() - clk0 < W2DELAY) {}
            const char* w2s = reinterpret_cast<const char*>(w2) + woff;
#pragma unroll
            for (int k = 0; k < 4; k++) v[k] = __ldg(reinterpret_cast<const uint4*>(w2s + k * 256));
            if ((lane & 15) < 8) v[4] = __ldg(reinterpret_cast<const uint4*>(w2s + 1024));
            const uint2* wsrc = reinterpret_cast<const uint2*>(w_emb + (size_t)r * 12 * C) + lane;
            uint2 wv[12];
#pragma unroll
            for (int i = 0; i < 12; i++) wv[i] = __ldg(wsrc + i * (C / 4));
            float tv = 0.f;
            if (lane < 12) tv = __bfloat162float(t_emb[b * E + r * 12 + lane]);
            weight_block(v, SM_BNC + 2304, gs->wt + NSTAGE * STAGE_BYTES, cta, lane);
            const float sv = silu_half(0.5f * tv);
            float e0 = 0.f, e1 = 0.f, e2 = 0.f, e3 = 0.f;
#pragma unroll
            for (int i = 0; i < 12; i++) {
                const float sx = __shfl_sync(0xffffffffu, sv, i);
                e0 = fmaf(sx, bf_lo(wv[i].x), e0); e1 = fmaf(sx, bf_hi(wv[i].x), e1);
                e2 = fmaf(sx, bf_lo(wv[i].y), e2); e3 = fmaf(sx, bf_hi(wv[i].y), e3);
            }
            mbar_wait(BAR(BAR_WACQ), 0);
            red_add4(&gs->emb[b * C + lane * 4], e0, e1, e2, e3);
            __syncwarp();
            if (lane == 0) TL(13);
            if (lane < 2) asm volatile("red.release.gpu.global.add.u32 [%0], 1;" ::"l"(&gs->wcnt[(NB + lane) * 32]) : "memory");
            if (lane == 0) TL(14);
            unsigned it = 0;
            while (ld_relaxed(&gs->wcnt[(NB + b) * 32]) < (unsigned)NCTA && ++it < SPIN_LIMIT) {}
            fence_acquire();
            const uint4 ef = ld_relaxed_v4(&gs->emb[b * C + lane * 4]);
            const uint32_t eu[4] = {ef.x, ef.y, ef.z, ef.w};
#pragma unroll
            for (int i = 0; i < 4; i++) {
                const float e = __uint_as_float(eu[i]);
                const float hi = bf_lo(pack_bf(e, 0.f));
                sts128(SM_EMB + (lane * 4 + i) * 16, make_uint4(pack_bf(hi, e - hi), 0, 0, 0));
            }
            fence_async_smem();
            __syncwarp();
            if (lane == 0) { mbar_arrive(BAR(BAR_EMB)); TL(19); }
        }
    } else if (warp == 6) {
        bar_sync(0, 96 + 128);
        unsigned it = 0;
        while (ld_relaxed(&gs->wcnt[b * 32]) < (unsigned)NCTA && ++it < SPIN_LIMIT) {}
        fence_acquire();
        fence_async_global();
        if (lane == 0) { mbar_arrive(BAR(BAR_WACQ)); TL(6); }
        const unsigned char* wsrc = gs->wt;
#pragma unroll 1
        for (int round = 0; round < 2 * NSTAGE / NS; round++) {
            if (round == NSTAGE / NS) { mbar_wait(BAR(BAR_EMB), 0); fence_async_global(); }
            const uint32_t full = BAR(BAR_FULL) + 8 * NS * (round >= NSTAGE / NS ? round - NSTAGE / NS : round);
#pragma unroll
            for (int slot = 0; slot < NS; slot++) {
                if (slot == 9 && round == 0) mbar_wait(BAR(BAR_XFREE), 0);
                mbar_wait(BAR(BAR_WEMPTY + slot), (round & 1) ^ 1);
                if (elect_one()) {
                    mbar_expect(full + 8 * slot, STAGE_BYTES);
                    bulk_g2s(SM_W + slot * STAGE_BYTES, wsrc + slot * STAGE_BYTES, STAGE_BYTES, full + 8 * slot);
                }
            }
            wsrc += NS * STAGE_BYTES;
        }
    } else {
        const uint2 ga1 = __ldg(reinterpret_cast<const uint2*>(g1) + lane), bt1 = __ldg(reinterpret_cast<const uint2*>(be1) + lane);
        const uint2 ga2 = __ldg(reinterpret_cast<const uint2*>(g2) + lane), bt2 = __ldg(reinterpret_cast<const uint2*>(be2) + lane);
        bar_sync(0, 96 + 128);
#pragma unroll 1
        for (int conv = 0; conv < 2; conv++) {
            if (conv == 1) mbar_wait(BAR(BAR_EMB), 0);
            const float* asrc = &gs->acc[(conv * NB + b) * 32 + (lane >> 3) * 4];
            uint4 f;
            unsigned it = 0;
            while (true) {
                f = ld_relaxed_v4(asrc);
                const bool ok = (f.x == 0x42800000u) & (f.w == 0x42800000u);
                if (__all_sync(0xffffffffu, ok) || ++it > SPIN_LIMIT) break;
            }
            if (lane == 0) TL(7 + conv * 8);
            const float inv_n = 1.0f / (32.0f * HW * HW);
            const float mean = __uint_as_float(f.y) * inv_n;
            const float var = fmaxf(fmaf(-mean, mean, __uint_as_float(f.z) * inv_n), 0.f);
            const float rs = 0.5f * rsqrtf(var + 1e-5f);
            const uint2 ga = conv ? ga2 : ga1, bt = conv ? bt2 : bt1;
            float4 k0, k1;
            k0.x = rs * bf_lo(ga.x); k0.y = rs * bf_hi(ga.x); k1.x = rs * bf_lo(ga.y); k1.y = rs * bf_hi(ga.y);
            k0.z = fmaf(-mean, k0.x, 0.5f * bf_lo(bt.x)); k0.w = fmaf(-mean, k0.y, 0.5f * bf_hi(bt.x));
            k1.z = fmaf(-mean, k1.x, 0.5f * bf_lo(bt.y)); k1.w = fmaf(-mean, k1.y, 0.5f * bf_hi(bt.y));
            sts128f(SM_COEF + lane * 32, k0);
            sts128f(SM_COEF + lane * 32 + 16, k1);
            __syncwarp();
            if (lane == 0) mbar_arrive(BAR(BAR_STATS));
        }
        if (r == 0) {
            if (lane < 16) gs->acc[b * 32 + lane] = 0.f;
            if (lane < 2) gs->wcnt[(lane * NB + b) * 32] = 0;
        }
    }
}

}

extern "C" void kernel_launch(void* const* d_in, const int* in_sizes, int n_in, void* d_out, int out_size) {
    (void)in_sizes; (void)n_in; (void)out_size;
    static Scratch* gs = nullptr;
    if (!gs) {
        cudaFuncSetAttribute(resblock_kernel, cudaFuncAttributeMaxDynamicSharedMemorySize, SM_TOTAL);
        cudaGetSymbolAddress((void**)&gs, g_scratch);
    }
    resblock_kernel<<<NCTA, NTHREADS, SM_TOTAL>>>(
        (const __nv_bfloat16*)d_in[0], (const __nv_bfloat16*)d_in[4], (const __nv_bfloat16*)d_in[1],
        (const __nv_bfloat16*)d_in[2], (const __nv_bfloat16*)d_in[3], (const __nv_bfloat16*)d_in[5],
        (const __nv_bfloat16*)d_in[6], (const __nv_bfloat16*)d_in[7], (const __nv_bfloat16*)d_in[8],
        (__nv_bfloat16*)d_out, gs);
}
```

```cpp
#include <cuda_runtime.h>
#include <cuda_bf16.h>
#include <stdint.h>

namespace {

constexpr int C = 128, HW = 64, NB = 2, E = 768;
constexpr int NCTA = NB * HW;
constexpr int NTHREADS = 16 * 32;
constexpr int CH_PITCH = 66 * 16;
constexpr int ROW_BYTES = 16 * CH_PITCH;
constexpr int STEP_BYTES = 4096;
constexpr int STAGE_BYTES = 3 * STEP_BYTES;
constexpr int NSTAGE = 24;
constexpr int NS = 12;
constexpr int LAG = 1;
#define XDELAY 900
#define HDELAY 1000
#define W2DELAY 2800

constexpr uint32_t SMEM_BASE = 0x400;
constexpr uint32_t SM_ACT = SMEM_BASE;
constexpr uint32_t SM_XOWN = SM_ACT + 3 * ROW_BYTES + 128;
constexpr uint32_t SM_W = SM_XOWN + 16384;
constexpr uint32_t SM_XH = SM_W + 9 * STAGE_BYTES;
constexpr uint32_t SM_COEF = SM_W + NS * STAGE_BYTES;
constexpr uint32_t SM_EMB = SM_COEF + 1024;
constexpr uint32_t SM_ONES = SM_EMB + 2048;
constexpr uint32_t SM_RED = SM_ONES + 256;
constexpr uint32_t SM_BNC = SM_RED + 128;
constexpr uint32_t SM_BAR = SM_BNC + 2 * 2304;
constexpr int BAR_FULL = 0, BAR_WEMPTY = NSTAGE, BAR_HW = BAR_WEMPTY + NS, BAR_STATS = BAR_HW + 1,
              BAR_EMB = BAR_STATS + 1, BAR_WACQ = BAR_EMB + 1, BAR_XH = BAR_WACQ + 1, BAR_XFREE = BAR_XH + 1, NBAR = BAR_XFREE + 1;
constexpr int SM_TOTAL = SM_BAR + NBAR * 8 - SMEM_BASE;
static_assert(SM_TOTAL <= 232448, "smem");
static_assert(NBAR <= 96, "barrier init");
constexpr int OUT_PITCH = 144;
__host__ __device__ constexpr uint32_t BAR(int i) { return SM_BAR + 8 * i; }
__host__ __device__ constexpr int ky_of(int kyo) { return kyo == 0 ? 1 : (kyo == 1 ? 0 : 2); }

constexpr unsigned SPIN_LIMIT = 1u << 16;

struct Scratch {
    float acc[2 * NB * 32];
    unsigned wcnt[2 * NB * 32];
    float emb[NB * C];
    unsigned char wt[2 * NSTAGE * STAGE_BYTES];
    uint4 h[NCTA * 2048];
};
__device__ __align__(1024) Scratch g_scratch;
#define TL(i) do {} while (0)
#define TLG(i) do {} while (0)

__device__ __forceinline__ unsigned clock32() { unsigned c; asm volatile("mov.u32 %0, %%clock;" : "=r"(c)); return c; }
__device__ __forceinline__ void mbar_init(uint32_t bar, int cnt) {
    asm volatile("mbarrier.init.shared::cta.b64 [%0], %1;" ::"r"(bar), "r"(cnt) : "memory");
}
__device__ __forceinline__ void mbar_arrive(uint32_t bar) {
    asm volatile("mbarrier.arrive.shared::cta.b64 _, [%0];" ::"r"(bar) : "memory");
}
__device__ __forceinline__ void mbar_expect(uint32_t bar, uint32_t bytes) {
    asm volatile("mbarrier.arrive.expect_tx.shared::cta.b64 _, [%0], %1;" ::"r"(bar), "r"(bytes) : "memory");
}
__device__ __forceinline__ bool mbar_try(uint32_t bar, uint32_t par) {
    uint32_t ok;
    asm volatile("{\n.reg .pred p;\nmbarrier.try_wait.parity.shared::cta.b64 p, [%1], %2;\nselp.u32 %0, 1, 0, p;\n}"
                 : "=r"(ok) : "r"(bar), "r"(par) : "memory");
    return ok;
}
__device__ __forceinline__ bool mbar_test(uint32_t bar, uint32_t par) {
    uint32_t ok;
    asm volatile("{\n.reg .pred p;\nmbarrier.test_wait.parity.shared::cta.b64 p, [%1], %2;\nselp.u32 %0, 1, 0, p;\n}"
                 : "=r"(ok) : "r"(bar), "r"(par) : "memory");
    return ok;
}
__device__ __forceinline__ void mbar_wait(uint32_t bar, uint32_t par) {
    unsigned it = 0;
#pragma unroll 1
    while (!mbar_try(bar, par) && ++it < SPIN_LIMIT) {}
}
__device__ __forceinline__ bool elect_one() {
    uint32_t p;
    asm volatile("{\n.reg .pred p;\nelect.sync _|p, 0xffffffff;\nselp.u32 %0, 1, 0, p;\n}" : "=r"(p));
    return p;
}
__device__ __forceinline__ void fence_async_smem() { asm volatile("fence.proxy.async.shared::cta;" ::: "memory"); }
__device__ __forceinline__ void fence_async_global() { asm volatile("fence.proxy.async.global;" ::: "memory"); }
__device__ __forceinline__ void fence_acquire() { asm volatile("fence.acquire.gpu;" ::: "memory"); }
__device__ __forceinline__ void bar_sync(int id, int n) { asm volatile("bar.sync %0, %1;" ::"r"(id), "r"(n) : "memory"); }
__device__ __forceinline__ void bar_arrive(int id, int n) { asm volatile("bar.arrive %0, %1;" ::"r"(id), "r"(n) : "memory"); }
__device__ __forceinline__ void bulk_g2s(uint32_t dst, const void* src, uint32_t bytes, uint32_t bar) {
    asm volatile("cp.async.bulk.shared::cluster.global.mbarrier::complete_tx::bytes [%0], [%1], %2, [%3];"
                 ::"r"(dst), "l"(src), "r"(bytes), "r"(bar) : "memory");
}
__device__ __forceinline__ uint4 ld_relaxed_v4(const void* p) {
    uint4 v;
    asm volatile("ld.relaxed.gpu.global.v4.u32 {%0,%1,%2,%3}, [%4];" : "=r"(v.x), "=r"(v.y), "=r"(v.z), "=r"(v.w) : "l"(p) : "memory");
    return v;
}
__device__ __forceinline__ unsigned ld_relaxed(const void* p) {
    unsigned v;
    asm volatile("ld.relaxed.gpu.global.u32 %0, [%1];" : "=r"(v) : "l"(p) : "memory");
    return v;
}
__device__ __forceinline__ void red_add4(float* p, float a, float b, float c, float d) {
    asm volatile("red.relaxed.gpu.global.add.v4.f32 [%0], {%1,%2,%3,%4};" ::"l"(p), "f"(a), "f"(b), "f"(c), "f"(d) : "memory");
}
__device__ __forceinline__ void sts128(uint32_t a, uint4 v) {
    asm volatile("st.shared.v4.u32 [%0], {%1,%2,%3,%4};" ::"r"(a), "r"(v.x), "r"(v.y), "r"(v.z), "r"(v.w) : "memory");
}
__device__ __forceinline__ void sts128f(uint32_t a, float4 v) {
    asm volatile("st.shared.v4.f32 [%0], {%1,%2,%3,%4};" ::"r"(a), "f"(v.x), "f"(v.y), "f"(v.z), "f"(v.w) : "memory");
}
__device__ __forceinline__ void sts32f(uint32_t a, float v) { asm volatile("st.shared.f32 [%0], %1;" ::"r"(a), "f"(v) : "memory"); }
__device__ __forceinline__ uint4 lds128(uint32_t a) {
    uint4 v;
    asm volatile("ld.shared.v4.u32 {%0,%1,%2,%3}, [%4];" : "=r"(v.x), "=r"(v.y), "=r"(v.z), "=r"(v.w) : "r"(a) : "memory");
    return v;
}
__device__ __forceinline__ float4 lds128f(uint32_t a) {
    float4 v;
    asm volatile("ld.shared.v4.f32 {%0,%1,%2,%3}, [%4];" : "=f"(v.x), "=f"(v.y), "=f"(v.z), "=f"(v.w) : "r"(a) : "memory");
    return v;
}
__device__ __forceinline__ float2 lds64f(uint32_t a) {
    float2 v;
    asm volatile("ld.shared.v2.f32 {%0,%1}, [%2];" : "=f"(v.x), "=f"(v.y) : "r"(a) : "memory");
    return v;
}
__device__ __forceinline__ float bf_lo(uint32_t u) { return __uint_as_float(u << 16); }
__device__ __forceinline__ float bf_hi(uint32_t u) { return __uint_as_float(u & 0xffff0000u); }
__device__ __forceinline__ uint32_t pack_bf(float lo, float hi) {
    uint32_t r;
    asm("cvt.rn.bf16x2.f32 %0, %1, %2;" : "=r"(r) : "f"(hi), "f"(lo));
    return r;
}
__device__ __forceinline__ float tanh_fast(float x) {
    float r;
    asm volatile("tanh.approx.f32 %0, %1;" : "=f"(r) : "f"(x));
    return r;
}
__device__ __forceinline__ float silu_half(float h) { return fmaf(h, tanh_fast(h), h); }
__device__ __forceinline__ void ldsm4(uint32_t (&u)[4], uint32_t a) {
    asm volatile("ldmatrix.sync.aligned.m8n8.x4.shared.b16 {%0,%1,%2,%3}, [%4];"
                 : "=r"(u[0]), "=r"(u[1]), "=r"(u[2]), "=r"(u[3]) : "r"(a) : "memory");
}
__device__ __forceinline__ void ldsm4t(uint32_t (&u)[4], uint32_t a) {
    asm volatile("ldmatrix.sync.aligned.m8n8.x4.trans.shared.b16 {%0,%1,%2,%3}, [%4];"
                 : "=r"(u[0]), "=r"(u[1]), "=r"(u[2]), "=r"(u[3]) : "r"(a) : "memory");
}
__device__ __forceinline__ void stsm4(uint32_t a, uint32_t p0, uint32_t p1, uint32_t p2, uint32_t p3) {
    asm volatile("stmatrix.sync.aligned.m8n8.x4.shared.b16 [%0], {%1,%2,%3,%4};" ::"r"(a), "r"(p0), "r"(p1), "r"(p2), "r"(p3) : "memory");
}
__device__ __forceinline__ void stsm4t(uint32_t a, uint32_t p0, uint32_t p1, uint32_t p2, uint32_t p3) {
    asm volatile("stmatrix.sync.aligned.m8n8.x4.trans.shared.b16 [%0], {%1,%2,%3,%4};" ::"r"(a), "r"(p0), "r"(p1), "r"(p2), "r"(p3) : "memory");
}

#define R8(o) "+f"(d[o]), "+f"(d[o + 1]), "+f"(d[o + 2]), "+f"(d[o + 3]), "+f"(d[o + 4]), "+f"(d[o + 5]), "+f"(d[o + 6]), "+f"(d[o + 7])
template <uint32_t ALO, uint32_t BLO, uint64_t AHI = 8>
__device__ __forceinline__ void wgmma128(float (&d)[64]) {
    asm volatile(
        "wgmma.mma_async.sync.aligned.m64n128k16.f32.bf16.bf16 "
        "{%0,%1,%2,%3,%4,%5,%6,%7,%8,%9,%10,%11,%12,%13,%14,%15,%16,%17,%18,%19,%20,%21,%22,%23,%24,%25,%26,%27,%28,%29,%30,%31,"
        "%32,%33,%34,%35,%36,%37,%38,%39,%40,%41,%42,%43,%44,%45,%46,%47,%48,%49,%50,%51,%52,%53,%54,%55,%56,%57,%58,%59,%60,%61,%62,%63},"
        " %64, %65, 1, 1, 1, 0, 0;"
        : R8(0), R8(8), R8(16), R8(24), R8(32), R8(40), R8(48), R8(56)
        : "l"((AHI << 32) | ALO), "l"((8ull << 32) | BLO));
}
template <int S>
__device__ __forceinline__ void mma_stages(float (&d)[64], int conv, int tid, Scratch* gs) {
    constexpr uint32_t A = ((SM_ACT + ky_of(S >> 3) * ROW_BYTES + (S & 7) * 2 * CH_PITCH + 16) >> 4) | ((CH_PITCH >> 4) << 16);
    constexpr uint32_t B = ((SM_W + (S % NS) * STAGE_BYTES) >> 4) | ((2048 >> 4) << 16);
    if (S == 0) mbar_wait(BAR(BAR_FULL), conv);
    bool next_ok = true;
    constexpr uint32_t NEXT = S + 1 < NSTAGE ? BAR(BAR_FULL + S + 1) : BAR(BAR_EMB);
    const int npar = S + 1 < NSTAGE ? conv : 0;
    next_ok = mbar_test(NEXT, npar);
    if (S == 0 && tid == 0) TL(32 + conv * 24);
    asm volatile("wgmma.fence.sync.aligned;" ::: "memory");
    wgmma128<A, B>(d);
    wgmma128<A + 1, B + (STEP_BYTES >> 4)>(d);
    wgmma128<A + 2, B + 2 * (STEP_BYTES >> 4)>(d);
    asm volatile("wgmma.commit_group.sync.aligned;" ::: "memory");
    if (S >= LAG) {
        asm volatile("wgmma.wait_group.sync.aligned %0;" ::"n"(LAG) : "memory");
        if ((tid & 31) == 0) mbar_arrive(BAR(BAR_WEMPTY + (S + NS - LAG) % NS));
    }
    if (!next_ok) mbar_wait(NEXT, npar);
    if constexpr (S + 1 < NSTAGE) mma_stages<S + 1>(d, conv, tid, gs);
}

__device__ __forceinline__ void weight_block(const uint4 (&t)[5], uint32_t bounce, unsigned char* wt, int cta, int lane) {
    const uint32_t bw = bounce + (lane >> 4) * 1152 + (lane & 15) * 16;
#pragma unroll
    for (int k = 0; k < 4; k++) sts128(bw + k * 256, t[k]);
    if ((lane & 15) < 8) sts128(bw + 1024, t[4]);
    __syncwarp();
    if (lane < 16) {
        uint32_t v[36];
#pragma unroll
        for (int i = 0; i < 9; i++) {
            const uint4 q = lds128(bounce + (lane & 1) * 1152 + (lane >> 1) * 144 + i * 16);
            v[4 * i] = q.x; v[4 * i + 1] = q.y; v[4 * i + 2] = q.z; v[4 * i + 3] = q.w;
        }
        const int cc = (cta >> 6) * 8 + (lane >> 1);
        unsigned char* dst = wt + (cc >> 1) * STAGE_BYTES + (cc & 1) * 2048 + ((cta & 63) * 2 + (lane & 1)) * 16;
#pragma unroll
        for (int kyo = 0; kyo < 3; kyo++) {
#pragma unroll
            for (int kx = 0; kx < 3; kx++) {
                const int tap = ky_of(kyo) * 3 + kx;
                uint32_t o[4];
#pragma unroll
                for (int m = 0; m < 4; m++) {
                    const int i0 = 18 * m + tap, i1 = i0 + 9;
                    const uint32_t sel = ((i0 & 1) ? 0x32u : 0x10u) | ((i1 & 1) ? 0x7600u : 0x5400u);
                    o[m] = __byte_perm(v[i0 >> 1], v[i1 >> 1], sel);
                }
                *reinterpret_cast<uint4*>(dst + (kyo * 24 + kx) * STEP_BYTES) = make_uint4(o[0], o[1], o[2], o[3]);
            }
        }
    }
}
__device__ __forceinline__ uint32_t act2(uint32_t u, const float4& cf) {
    return pack_bf(silu_half(fmaf(bf_lo(u), cf.x, cf.z)), silu_half(fmaf(bf_hi(u), cf.y, cf.w)));
}
__device__ __forceinline__ void norm_unit(uint32_t (&u)[4], const float4& ca, const float4& cb) {
    u[0] = act2(u[0], ca); u[1] = act2(u[1], ca); u[2] = act2(u[2], cb); u[3] = act2(u[3], cb);
}
__device__ __forceinline__ void publish(uint32_t bar, int lane) {
    fence_async_smem();
    __syncwarp();
    if (lane == 0) mbar_arrive(bar);
}
__device__ __forceinline__ void publish2(uint32_t bar, int lane) {
    fence_async_smem();
    __syncwarp();
    if (lane < 2) mbar_arrive(bar + 16 * lane);
}
__device__ __forceinline__ void fence_acc(float (&d)[64]) {
#pragma unroll
    for (int i = 0; i < 64; i++) asm volatile("" : "+f"(d[i])::"memory");
}
__device__ __forceinline__ void ld_unit(uint32_t (&u)[4], const uint4* p) {
    asm volatile("ld.relaxed.gpu.global.v4.u32 {%0,%1,%2,%3}, [%4];" : "=r"(u[0]), "=r"(u[1]), "=r"(u[2]), "=r"(u[3]) : "l"(p) : "memory");
}

__global__ void __launch_bounds__(NTHREADS, 1)
resblock_kernel(const __nv_bfloat16* __restrict__ x, const __nv_bfloat16* __restrict__ w1,
                const __nv_bfloat16* __restrict__ t_emb, const __nv_bfloat16* __restrict__ g1,
                const __nv_bfloat16* __restrict__ be1, const __nv_bfloat16* __restrict__ w_emb,
                const __nv_bfloat16* __restrict__ g2, const __nv_bfloat16* __restrict__ be2,
                const __nv_bfloat16* __restrict__ w2, __nv_bfloat16* __restrict__ out, Scratch* __restrict__ gs) {
    const unsigned clk0 = clock32();
    const int tid = threadIdx.x, warp = tid >> 5, lane = tid & 31;
    const int cta = blockIdx.x, b = cta >> 6, r = cta & 63;

    const uint32_t woff = ((2 * r + (lane >> 4)) * C + b * 64) * 18 + (lane & 15) * 16;
    const int c0 = (warp - 8) * 16 + (lane >> 3), seg = lane & 7;
    uint4 v[5];
    if (warp == 0) {
        const char* w1s = reinterpret_cast<const char*>(w1) + woff;
#pragma unroll
        for (int k = 0; k < 4; k++) v[k] = __ldg(reinterpret_cast<const uint4*>(w1s + k * 256));
        if ((lane & 15) < 8) v[4] = __ldg(reinterpret_cast<const uint4*>(w1s + 1024));
        weight_block(v, SM_BNC, gs->wt, cta, lane);
        if (r == 0) {
            if (lane < 16) gs->acc[(NB + b) * 32 + lane] = 0.f;
            *reinterpret_cast<float4*>(&gs->emb[b * C + lane * 4]) = make_float4(0.f, 0.f, 0.f, 0.f);
        }
        __syncwarp();
        if (lane == 0) TL(4);
        if (lane < 2) asm volatile("red.release.gpu.global.add.u32 [%0], 1;" ::"l"(&gs->wcnt[lane * 32]) : "memory");
        if (lane == 0) TL(5);
    }

    if (warp >= 8) {
        const int nw = warp - 8;
        const char* src = reinterpret_cast<const char*>(x) + (uint32_t)(((b * C + c0) * HW + r) * HW * 2 + seg * 16);
#pragma unroll
        for (int k = 0; k < 4; k++) v[k] = make_uint4(0, 0, 0, 0);
#pragma unroll 1
        for (int pass = 0; pass < 2; pass++) {
            if (pass) {
                while (clock32() - clk0 < XDELAY) {}
#pragma unroll
                for (int k = 0; k < 4; k++) v[k] = __ldg(reinterpret_cast<const uint4*>(src + k * (4 * HW * HW * 2)));
#pragma unroll
                for (int i = 0; i < 8; i++) {
                    if (i < 4 ? (r != 0) : (r != HW - 1))
                        asm volatile("cp.async.cg.shared.global [%0], [%1], 16;"
                                     ::"r"(SM_XH + (i >> 2) * 16384 + c0 * 128 + (i & 3) * 512 + ((seg ^ ((c0 + 4 * i) & 7)) << 4)),
                                       "l"(src + (i < 4 ? -HW * 2 : HW * 2) + (i & 3) * (4 * HW * HW * 2)) : "memory");
                }
                if (tid == 256) TL(82);
            }
            float s = 0.f, q = 0.f, s2 = 0.f, q2 = 0.f;
#pragma unroll
            for (int i = 0; i < 4; i++) {
                const uint32_t u[4] = {v[i].x, v[i].y, v[i].z, v[i].w};
#pragma unroll
                for (int k = 0; k < 4; k++) {
                    const float lo = bf_lo(u[k]), hi = bf_hi(u[k]);
                    s += lo; q = fmaf(lo, lo, q);
                    s2 += hi; q2 = fmaf(hi, hi, q2);
                }
            }
            s += s2; q += q2;
            float give = (lane < 16) ? q : s, keep = (lane < 16) ? s : q;
            keep += __shfl_xor_sync(0xffffffffu, give, 16);
            if (tid == 256) TL(2);
#pragma unroll
            for (int m = 8; m >= 1; m >>= 1) keep += __shfl_xor_sync(0xffffffffu, keep, m);
            if ((lane & 15) == 0) sts32f(SM_RED + (nw * 2 + (lane >> 4)) * 4, keep);
            bar_sync(3, 256);
            if (pass && tid < 256 + 4) {
                const float4 p = lds128f(SM_RED + lane * 16);
                red_add4(&gs->acc[b * 32 + lane * 4], 1.f, p.x + p.z, p.y + p.w, 1.f);
            }
            if (tid == 256) TL(3);
        }
        {
#pragma unroll
            for (int i = 0; i < 4; i++) sts128(SM_XOWN + c0 * 128 + i * 512 + ((seg ^ ((c0 + 4 * i) & 7)) << 4), v[i]);
            asm volatile("cp.async.wait_all;" ::: "memory");
            bar_sync(4, 256 + 96);
        }
        const int par = nw >> 2, wq = nw & 3;
        const uint32_t act_off = SM_ACT + (par * 2 + (lane >> 4)) * CH_PITCH + (2 + wq * 16 + (lane & 15)) * 16;
        const uint32_t stg_off = (par * 16 + (lane >> 4) * 8 + (lane & 7)) * 128 + (((2 * wq + ((lane >> 3) & 1)) ^ (lane & 7)) << 4);
        const uint32_t fbar = BAR(BAR_FULL) + 8 * par;
#pragma unroll 1
        for (int conv = 0; conv < 2; conv++) {
            uint32_t u[12][4];
            float4 cf[8];
            if (conv == 0) {
#pragma unroll
                for (int i = 0; i < 4; i++) ldsm4t(u[i], SM_XOWN + stg_off + i * 4096);
#pragma unroll
                for (int i = 0; i < 8; i++) ldsm4t(u[4 + i], SM_XH + stg_off + i * 4096);
                publish(BAR(BAR_XFREE), lane);
            } else {
                mbar_wait(BAR(BAR_HW), 0);
#pragma unroll
                for (int i = 0; i < 4; i++) ldsm4(u[i], act_off + ROW_BYTES + i * 4 * CH_PITCH);
            }
            uint4* hp = gs->h + (size_t)cta * 2048 + nw * 32 + lane;
            const uint32_t cfa = SM_COEF + par * 128 + (lane & 3) * 16;
            mbar_wait(BAR(BAR_STATS), conv);
            if (tid == 256) TL(22 + conv * 4);
            cf[0] = lds128f(cfa); cf[1] = lds128f(cfa + 64);
            norm_unit(u[0], cf[0], cf[1]);
            stsm4(act_off + ROW_BYTES, u[0][0], u[0][1], u[0][2], u[0][3]);
            publish(fbar, lane);
            if (tid == 256) TL(8 + conv * 8);
#pragma unroll
            for (int i = 2; i < 8; i++) cf[i] = lds128f(cfa + (i >> 1) * 256 + (i & 1) * 64);
            if (conv == 1) {
#pragma unroll
                for (int i = 0; i < 8; i++) ld_unit(u[4 + i], hp + i * 256);
            }
#pragma unroll
            for (int t = 1; t < 12; t++) {
                if (t == 4) publish(fbar + 16 * 3, lane);
                if (t == 4 && conv == 1) {
                    if (tid == 256) TL(24 + conv * 4);
                    unsigned it = 0;
                    while (true) {
                        bool oku = true, okd = true;
#pragma unroll
                        for (int i = 0; i < 16; i++) { oku = oku && u[4 + (i >> 2)][i & 3] != 0; okd = okd && u[8 + (i >> 2)][i & 3] != 0; }
                        if (__all_sync(0xffffffffu, (oku || r == 0) && (okd || r == HW - 1)) || ++it > SPIN_LIMIT) break;
#pragma unroll
                        for (int i = 0; i < 8; i++) ld_unit(u[4 + i], hp + i * 256);
                    }
#pragma unroll
                    for (int i = 0; i < 32; i++) u[4 + (i >> 2)][i & 3] = ~u[4 + (i >> 2)][i & 3];
                }
                norm_unit(u[t], cf[2 * (t & 3)], cf[2 * (t & 3) + 1]);
                if (t == 2 || t == 3) publish(fbar + 16 * (t - 1), lane);
                if (t >= 6 && !(t & 1)) publish2(fbar + 16 * (t - 2), lane);
                if (t < 4 || (t < 8 ? r != 0 : r != HW - 1))
                    stsm4(act_off + ky_of(t >> 2) * ROW_BYTES + (t & 3) * 4 * CH_PITCH, u[t][0], u[t][1], u[t][2], u[t][3]);
            }
            publish2(fbar + 16 * 10, lane);
            if (conv == 1) {
#pragma unroll
                for (int i = 0; i < 8; i++) hp[i * 256] = make_uint4(0, 0, 0, 0);
            }
            if (tid == 256) TL(23 + conv * 4);
        }
    } else if (warp < 4) {
        const int wq = warp;
        if (wq != 0) {
            const int t = tid - 32;
            if (lane == 0) {
                if (wq < 3) {
#pragma unroll
                    for (int i = 0; i < 12; i++) mbar_init(BAR(BAR_FULL + i) + (wq - 1) * 96, 5);
                    mbar_init(BAR(BAR_STATS) + (wq - 1) * 16, 1);
                    mbar_init(BAR(BAR_EMB) + (wq - 1) * 16, 1);
                } else {
#pragma unroll
                    for (int i = 0; i <= NS; i++) mbar_init(BAR(BAR_WEMPTY + i), 4);
                    mbar_init(BAR(BAR_XFREE), 8);
                }
            }
            fence_async_smem();
            bar_arrive(0, 96 + 128);
            bar_arrive(4, 256 + 96);
            if (t == 95) TLG(1);
            const uint4 z = make_uint4(0, 0, 0, 0);
            sts128(SM_ACT + (t >> 1) * CH_PITCH + (t & 1) * 16, z);
            if (t < 2) sts128(SM_ACT + 3 * ROW_BYTES + t * 16, z);
            if (t < 16) sts128(SM_ONES + t * 16, make_uint4(t < 8 ? 0x3f803f80u : 0u, 0, 0, 0));
            if (r == 0 || r == HW - 1) {
                for (int i = t; i < ROW_BYTES / 16; i += 96) sts128(SM_ACT + (r == 0 ? 0 : 2 * ROW_BYTES) + i * 16, z);
            }
            fence_async_smem();
        }
        bar_sync(2, 128);

        float d[64];
#pragma unroll
        for (int i = 0; i < 64; i++) d[i] = 0.f;
#pragma unroll 1
        for (int conv = 0; conv < 2; conv++) {
            fence_acc(d);
            mma_stages<0>(d, conv, tid, gs);
            if (conv == 0) {
                asm volatile("wgmma.fence.sync.aligned;" ::: "memory");
                wgmma128<(SM_ONES >> 4) | (8u << 16), (SM_EMB >> 4), 0>(d);
                asm volatile("wgmma.commit_group.sync.aligned;" ::: "memory");
            }
            asm volatile("wgmma.wait_group.sync.aligned 0;" ::: "memory");
            fence_acc(d);
            if (tid == 0) TL(10 + conv * 8);
            if (conv == 1) break;

            float st[8];
#pragma unroll
            for (int g = 0; g < 4; g++) {
                float s = 0.f, q = 0.f, s2 = 0.f, q2 = 0.f;
#pragma unroll
                for (int jj = 0; jj < 4; jj++) {
                    const int j = g * 4 + jj;
                    s += d[4 * j + 0]; q = fmaf(d[4 * j + 0], d[4 * j + 0], q);
                    s2 += d[4 * j + 1]; q2 = fmaf(d[4 * j + 1], d[4 * j + 1], q2);
                    s += d[4 * j + 2]; q = fmaf(d[4 * j + 2], d[4 * j + 2], q);
                    s2 += d[4 * j + 3]; q2 = fmaf(d[4 * j + 3], d[4 * j + 3], q2);
                }
                st[2 * g] = s + s2; st[2 * g + 1] = q + q2;
            }
            {
                const bool h16 = lane & 16, h8 = lane & 8, h4 = lane & 4;
                float a[4];
#pragma unroll
                for (int i = 0; i < 4; i++) {
                    float give = h16 ? st[i] : st[i + 4], keep = h16 ? st[i + 4] : st[i];
                    a[i] = keep + __shfl_xor_sync(0xffffffffu, give, 16);
                }
                float c2[2];
#pragma unroll
                for (int i = 0; i < 2; i++) {
                    float give = h8 ? a[i] : a[i + 2], keep = h8 ? a[i + 2] : a[i];
                    c2[i] = keep + __shfl_xor_sync(0xffffffffu, give, 8);
                }
                float give = h4 ? c2[0] : c2[1], keep = h4 ? c2[1] : c2[0];
                float t = keep + __shfl_xor_sync(0xffffffffu, give, 4);
                t += __shfl_xor_sync(0xffffffffu, t, 2);
                t += __shfl_xor_sync(0xffffffffu, t, 1);
                if ((lane & 3) == 0) sts32f(SM_RED + ((lane >> 2) * 4 + wq) * 4, t);
                bar_sync(2, 128);
                if (tid < 4) {
                    const float4 p = lds128f(SM_RED + tid * 32), p2 = lds128f(SM_RED + tid * 32 + 16);
                    red_add4(&gs->acc[(NB + b) * 32 + tid * 4], 1.f, (p.x + p.y) + (p.z + p.w), (p2.x + p2.y) + (p2.z + p2.w), 1.f);
                }
                if (tid == 0) TL(11);
                if (lane < LAG) mbar_arrive(BAR(BAR_WEMPTY + (NSTAGE - LAG) % NS) + 8 * lane);
            }
            const uint32_t hbase = SM_ACT + ROW_BYTES + (lane >> 4) * CH_PITCH + (2 + wq * 16 + (lane & 15)) * 16;
            uint4* hup = gs->h + (cta - 1) * 2048 + 1024 + tid;
            uint4* hdn = gs->h + (cta + 1) * 2048 + tid;
#pragma unroll
            for (int kc = 0; kc < 8; kc++) {
                const uint4 p = make_uint4(pack_bf(d[8 * kc + 0], d[8 * kc + 1]), pack_bf(d[8 * kc + 2], d[8 * kc + 3]),
                                           pack_bf(d[8 * kc + 4], d[8 * kc + 5]), pack_bf(d[8 * kc + 6], d[8 * kc + 7]));
                stsm4(hbase + kc * 2 * CH_PITCH, p.x, p.y, p.z, p.w);
                const uint4 n = make_uint4(~p.x, ~p.y, ~p.z, ~p.w);
                if (r != 0) hup[kc * 128] = n;
                if (r != HW - 1) hdn[kc * 128] = n;
            }
            __syncwarp();
            if (lane == 0) mbar_arrive(BAR(BAR_HW));
            if (tid == 0) TL(12);
            const uint32_t xbase = SM_XOWN + ((lane >> 4) * 8 + (lane & 7)) * 128 + (((2 * wq + ((lane >> 3) & 1)) ^ (lane & 7)) << 4);
#pragma unroll
            for (int kc = 0; kc < 8; kc++) {
                uint32_t p[4];
                ldsm4t(p, xbase + kc * 2048);
#pragma unroll
                for (int i = 0; i < 4; i++) { d[8 * kc + 2 * i] = bf_lo(p[i]); d[8 * kc + 2 * i + 1] = bf_hi(p[i]); }
            }
        }
        {
            const uint32_t obase = SM_W + ((lane >> 4) * 8 + (lane & 7)) * OUT_PITCH + (wq * 16 + ((lane >> 3) & 1) * 8) * 2;
#pragma unroll
            for (int kc = 0; kc < 8; kc++) {
                stsm4t(obase + kc * 16 * OUT_PITCH, pack_bf(d[8 * kc + 0], d[8 * kc + 1]), pack_bf(d[8 * kc + 2], d[8 * kc + 3]),
                       pack_bf(d[8 * kc + 4], d[8 * kc + 5]), pack_bf(d[8 * kc + 6], d[8 * kc + 7]));
            }
            bar_sync(2, 128);
            const int oc0 = tid >> 3;
            __nv_bfloat16* dst = out + ((size_t)(b * C + oc0) * HW + r) * HW + seg * 8;
#pragma unroll
            for (int i = 0; i < 8; i++)
                *reinterpret_cast<uint4*>(dst + (size_t)i * 16 * HW * HW) = lds128(SM_W + (oc0 + 16 * i) * OUT_PITCH + seg * 16);
            if (tid == 0) { TL(20); TLG(21); }
        }
    } else if (warp < 6) {
        bar_sync(0, 96 + 128);
        if (warp == 4) {
            while (clock32() - clk0 < W2DELAY) {}
            const char* w2s = reinterpret_cast<const char*>(w2) + woff;
#pragma unroll
            for (int k = 0; k < 4; k++) v[k] = __ldg(reinterpret_cast<const uint4*>(w2s + k * 256));
            if ((lane & 15) < 8) v[4] = __ldg(reinterpret_cast<const uint4*>(w2s + 1024));
            const uint2* wsrc = reinterpret_cast<const uint2*>(w_emb + (size_t)r * 12 * C) + lane;
            uint2 wv[12];
#pragma unroll
            for (int i = 0; i < 12; i++) wv[i] = __ldg(wsrc + i * (C / 4));
            float tv = 0.f;
            if (lane < 12) tv = __bfloat162float(t_emb[b * E + r * 12 + lane]);
            weight_block(v, SM_BNC + 2304, gs->wt + NSTAGE * STAGE_BYTES, cta, lane);
            const float sv = silu_half(0.5f * tv);
            float e0 = 0.f, e1 = 0.f, e2 = 0.f, e3 = 0.f;
#pragma unroll
            for (int i = 0; i < 12; i++) {
                const float sx = __shfl_sync(0xffffffffu, sv, i);
                e0 = fmaf(sx, bf_lo(wv[i].x), e0); e1 = fmaf(sx, bf_hi(wv[i].x), e1);
                e2 = fmaf(sx, bf_lo(wv[i].y), e2); e3 = fmaf(sx, bf_hi(wv[i].y), e3);
            }
            mbar_wait(BAR(BAR_WACQ), 0);
            red_add4(&gs->emb[b * C + lane * 4], e0, e1, e2, e3);
            __syncwarp();
            if (lane == 0) TL(13);
            if (lane < 2) asm volatile("red.release.gpu.global.add.u32 [%0], 1;" ::"l"(&gs->wcnt[(NB + lane) * 32]) : "memory");
            if (lane == 0) TL(14);
            unsigned it = 0;
            while (ld_relaxed(&gs->wcnt[(NB + b) * 32]) < (unsigned)NCTA && ++it < SPIN_LIMIT) {}
            fence_acquire();
            const uint4 ef = ld_relaxed_v4(&gs->emb[b * C + lane * 4]);
            const uint32_t eu[4] = {ef.x, ef.y, ef.z, ef.w};
#pragma unroll
            for (int i = 0; i < 4; i++) {
                const float e = __uint_as_float(eu[i]);
                const float hi = bf_lo(pack_bf(e, 0.f));
                sts128(SM_EMB + (lane * 4 + i) * 16, make_uint4(pack_bf(hi, e - hi), 0, 0, 0));
            }
            fence_async_smem();
            __syncwarp();
            if (lane == 0) { mbar_arrive(BAR(BAR_EMB)); TL(19); }
        }
    } else if (warp == 6) {
        bar_sync(0, 96 + 128);
        unsigned it = 0;
        while (ld_relaxed(&gs->wcnt[b * 32]) < (unsigned)NCTA && ++it < SPIN_LIMIT) {}
        fence_acquire();
        fence_async_global();
        if (lane == 0) { mbar_arrive(BAR(BAR_WACQ)); TL(6); }
        const unsigned char* wsrc = gs->wt;
#pragma unroll 1
        for (int round = 0; round < 2 * NSTAGE / NS; round++) {
            if (round == NSTAGE / NS) { mbar_wait(BAR(BAR_EMB), 0); fence_async_global(); }
            const uint32_t full = BAR(BAR_FULL) + 8 * NS * (round >= NSTAGE / NS ? round - NSTAGE / NS : round);
#pragma unroll
            for (int slot = 0; slot < NS; slot++) {
                if (slot == 9 && round == 0) mbar_wait(BAR(BAR_XFREE), 0);
                mbar_wait(BAR(BAR_WEMPTY + slot), (round & 1) ^ 1);
                if (elect_one()) {
                    mbar_expect(full + 8 * slot, STAGE_BYTES);
                    bulk_g2s(SM_W + slot * STAGE_BYTES, wsrc + slot * STAGE_BYTES, STAGE_BYTES, full + 8 * slot);
                }
            }
            wsrc += NS * STAGE_BYTES;
        }
    } else {
        const uint2 ga1 = __ldg(reinterpret_cast<const uint2*>(g1) + lane), bt1 = __ldg(reinterpret_cast<const uint2*>(be1) + lane);
        const uint2 ga2 = __ldg(reinterpret_cast<const uint2*>(g2) + lane), bt2 = __ldg(reinterpret_cast<const uint2*>(be2) + lane);
        bar_sync(0, 96 + 128);
#pragma unroll 1
        for (int conv = 0; conv < 2; conv++) {
            if (conv == 1) mbar_wait(BAR(BAR_EMB), 0);
            const float* asrc = &gs->acc[(conv * NB + b) * 32 + (lane >> 3) * 4];
            uint4 f;
            unsigned it = 0;
            while (true) {
                f = ld_relaxed_v4(asrc);
                const bool ok = (f.x == 0x42800000u) & (f.w == 0x42800000u);
                if (__all_sync(0xffffffffu, ok) || ++it > SPIN_LIMIT) break;
            }
            if (lane == 0) TL(7 + conv * 8);
            const float inv_n = 1.0f / (32.0f * HW * HW);
            const float mean = __uint_as_float(f.y) * inv_n;
            const float var = fmaxf(fmaf(-mean, mean, __uint_as_float(f.z) * inv_n), 0.f);
            const float rs = 0.5f * rsqrtf(var + 1e-5f);
            const uint2 ga = conv ? ga2 : ga1, bt = conv ? bt2 : bt1;
            float4 k0, k1;
            k0.x = rs * bf_lo(ga.x); k0.y = rs * bf_hi(ga.x); k1.x = rs * bf_lo(ga.y); k1.y = rs * bf_hi(ga.y);
            k0.z = fmaf(-mean, k0.x, 0.5f * bf_lo(bt.x)); k0.w = fmaf(-mean, k0.y, 0.5f * bf_hi(bt.x));
            k1.z = fmaf(-mean, k1.x, 0.5f * bf_lo(bt.y)); k1.w = fmaf(-mean, k1.y, 0.5f * bf_hi(bt.y));
            sts128f(SM_COEF + lane * 32, k0);
            sts128f(SM_COEF + lane * 32 + 16, k1);
            __syncwarp();
            if (lane == 0) mbar_arrive(BAR(BAR_STATS));
        }
        if (r == 0) {
            if (lane < 16) gs->acc[b * 32 + lane] = 0.f;
            if (lane < 2) gs->wcnt[(lane * NB + b) * 32] = 0;
        }
    }
}

}

extern "C" void kernel_launch(void* const* d_in, const int* in_sizes, int n_in, void* d_out, int out_size) {
    (void)in_sizes; (void)n_in; (void)out_size;
    static Scratch* gs = nullptr;
    if (!gs) {
        cudaFuncSetAttribute(resblock_kernel, cudaFuncAttributeMaxDynamicSharedMemorySize, SM_TOTAL);
        cudaGetSymbolAddress((void**)&gs, g_scratch);
    }
    resblock_kernel<<<NCTA, NTHREADS, SM_TOTAL>>>(
        (const __nv_bfloat16*)d_in[0], (const __nv_bfloat16*)d_in[4], (const __nv_bfloat16*)d_in[1],
        (const __nv_bfloat16*)d_in[2], (const __nv_bfloat16*)d_in[3], (const __nv_bfloat16*)d_in[5],
        (const __nv_bfloat16*)d_in[6], (const __nv_bfloat16*)d_in[7], (const __nv_bfloat16*)d_in[8],
        (__nv_bfloat16*)d_out, gs);
}
```

```cpp
#include <cuda_runtime.h>
#include <cuda_bf16.h>
#include <stdint.h>

namespace {

constexpr int C = 128, HW = 64, NB = 2, E = 768;
constexpr int NCTA = NB * HW;
constexpr int NTHREADS = 16 * 32;
constexpr int CH_PITCH = 66 * 16;
constexpr int ROW_BYTES = 16 * CH_PITCH;
constexpr int STEP_BYTES = 4096;
constexpr int STAGE_BYTES = 3 * STEP_BYTES;
constexpr int NSTAGE = 24;
constexpr int NS = 12;
constexpr int LAG = 1;
#define XDELAY 900
#define HDELAY 1000
#define W2DELAY 2800

constexpr uint32_t SMEM_BASE = 0x400;
constexpr uint32_t SM_ACT = SMEM_BASE;
constexpr uint32_t SM_XOWN = SM_ACT + 3 * ROW_BYTES + 128;
constexpr uint32_t SM_W = SM_XOWN + 16384;
constexpr uint32_t SM_XH = SM_W + 9 * STAGE_BYTES;
constexpr uint32_t SM_COEF = SM_W + NS * STAGE_BYTES;
constexpr uint32_t SM_EMB = SM_COEF + 1024;
constexpr uint32_t SM_ONES = SM_EMB + 2048;
constexpr uint32_t SM_RED = SM_ONES + 256;
constexpr uint32_t SM_BNC = SM_RED + 1024;
constexpr uint32_t SM_BAR = SM_BNC + 2 * 2304;
constexpr int BAR_FULL = 0, BAR_WEMPTY = NSTAGE, BAR_HW = BAR_WEMPTY + NS, BAR_STATS = BAR_HW + 1,
              BAR_EMB = BAR_STATS + 1, BAR_WACQ = BAR_EMB + 1, BAR_XH = BAR_WACQ + 1, BAR_XFREE = BAR_XH + 1, NBAR = BAR_XFREE + 1;
constexpr int SM_TOTAL = SM_BAR + NBAR * 8 - SMEM_BASE;
static_assert(SM_TOTAL <= 232448, "smem");
static_assert(NBAR <= 96, "barrier init");
constexpr int OUT_PITCH = 144;
__host__ __device__ constexpr uint32_t BAR(int i) { return SM_BAR + 8 * i; }
__host__ __device__ constexpr int ky_of(int kyo) { return kyo == 0 ? 1 : (kyo == 1 ? 0 : 2); }

constexpr unsigned SPIN_LIMIT = 1u << 16;

struct Scratch {
    float acc[2 * NB * 32];
    unsigned wcnt[2 * NB * 32];
    float emb[NB * C];
    unsigned char wt[2 * NSTAGE * STAGE_BYTES];
    uint4 h[NCTA * 2048];
};
__device__ __align__(1024) Scratch g_scratch;
#define TL(i) do {} while (0)
#define TLG(i) do {} while (0)

__device__ __forceinline__ unsigned clock32() { unsigned c; asm volatile("mov.u32 %0, %%clock;" : "=r"(c)); return c; }
__device__ __forceinline__ void mbar_init(uint32_t bar, int cnt) {
    asm volatile("mbarrier.init.shared::cta.b64 [%0], %1;" ::"r"(bar), "r"(cnt) : "memory");
}
__device__ __forceinline__ void mbar_arrive(uint32_t bar) {
    asm volatile("mbarrier.arrive.shared::cta.b64 _, [%0];" ::"r"(bar) : "memory");
}
__device__ __forceinline__ void mbar_expect(uint32_t bar, uint32_t bytes) {
    asm volatile("mbarrier.arrive.expect_tx.shared::cta.b64 _, [%0], %1;" ::"r"(bar), "r"(bytes) : "memory");
}
__device__ __forceinline__ bool mbar_try(uint32_t bar, uint32_t par) {
    uint32_t ok;
    asm volatile("{\n.reg .pred p;\nmbarrier.try_wait.parity.shared::cta.b64 p, [%1], %2;\nselp.u32 %0, 1, 0, p;\n}"
                 : "=r"(ok) : "r"(bar), "r"(par) : "memory");
    return ok;
}
__device__ __forceinline__ bool mbar_test(uint32_t bar, uint32_t par) {
    uint32_t ok;
    asm volatile("{\n.reg .pred p;\nmbarrier.test_wait.parity.shared::cta.b64 p, [%1], %2;\nselp.u32 %0, 1, 0, p;\n}"
                 : "=r"(ok) : "r"(bar), "r"(par) : "memory");
    return ok;
}
__device__ __forceinline__ void mbar_wait(uint32_t bar, uint32_t par) {
    unsigned it = 0;
#pragma unroll 1
    while (!mbar_try(bar, par) && ++it < SPIN_LIMIT) {}
}
__device__ __forceinline__ bool elect_one() {
    uint32_t p;
    asm volatile("{\n.reg .pred p;\nelect.sync _|p, 0xffffffff;\nselp.u32 %0, 1, 0, p;\n}" : "=r"(p));
    return p;
}
__device__ __forceinline__ void fence_async_smem() { asm volatile("fence.proxy.async.shared::cta;" ::: "memory"); }
__device__ __forceinline__ void fence_async_global() { asm volatile("fence.proxy.async.global;" ::: "memory"); }
__device__ __forceinline__ void fence_acquire() { asm volatile("fence.acquire.gpu;" ::: "memory"); }
__device__ __forceinline__ void bar_sync(int id, int n) { asm volatile("bar.sync %0, %1;" ::"r"(id), "r"(n) : "memory"); }
__device__ __forceinline__ void bar_arrive(int id, int n) { asm volatile("bar.arrive %0, %1;" ::"r"(id), "r"(n) : "memory"); }
__device__ __forceinline__ void bulk_g2s(uint32_t dst, const void* src, uint32_t bytes, uint32_t bar) {
    asm volatile("cp.async.bulk.shared::cluster.global.mbarrier::complete_tx::bytes [%0], [%1], %2, [%3];"
                 ::"r"(dst), "l"(src), "r"(bytes), "r"(bar) : "memory");
}
__device__ __forceinline__ uint4 ld_relaxed_v4(const void* p) {
    uint4 v;
    asm volatile("ld.relaxed.gpu.global.v4.u32 {%0,%1,%2,%3}, [%4];" : "=r"(v.x), "=r"(v.y), "=r"(v.z), "=r"(v.w) : "l"(p) : "memory");
    return v;
}
__device__ __forceinline__ unsigned ld_relaxed(const void* p) {
    unsigned v;
    asm volatile("ld.relaxed.gpu.global.u32 %0, [%1];" : "=r"(v) : "l"(p) : "memory");
    return v;
}
__device__ __forceinline__ void red_add4(float* p, float a, float b, float c, float d) {
    asm volatile("red.relaxed.gpu.global.add.v4.f32 [%0], {%1,%2,%3,%4};" ::"l"(p), "f"(a), "f"(b), "f"(c), "f"(d) : "memory");
}
__device__ __forceinline__ void sts128(uint32_t a, uint4 v) {
    asm volatile("st.shared.v4.u32 [%0], {%1,%2,%3,%4};" ::"r"(a), "r"(v.x), "r"(v.y), "r"(v.z), "r"(v.w) : "memory");
}
__device__ __forceinline__ void sts128f(uint32_t a, float4 v) {
    asm volatile("st.shared.v4.f32 [%0], {%1,%2,%3,%4};" ::"r"(a), "f"(v.x), "f"(v.y), "f"(v.z), "f"(v.w) : "memory");
}
__device__ __forceinline__ void sts32f(uint32_t a, float v) { asm volatile("st.shared.f32 [%0], %1;" ::"r"(a), "f"(v) : "memory"); }
__device__ __forceinline__ uint4 lds128(uint32_t a) {
    uint4 v;
    asm volatile("ld.shared.v4.u32 {%0,%1,%2,%3}, [%4];" : "=r"(v.x), "=r"(v.y), "=r"(v.z), "=r"(v.w) : "r"(a) : "memory");
    return v;
}
__device__ __forceinline__ float4 lds128f(uint32_t a) {
    float4 v;
    asm volatile("ld.shared.v4.f32 {%0,%1,%2,%3}, [%4];" : "=f"(v.x), "=f"(v.y), "=f"(v.z), "=f"(v.w) : "r"(a) : "memory");
    return v;
}
__device__ __forceinline__ float2 lds64f(uint32_t a) {
    float2 v;
    asm volatile("ld.shared.v2.f32 {%0,%1}, [%2];" : "=f"(v.x), "=f"(v.y) : "r"(a) : "memory");
    return v;
}
__device__ __forceinline__ float bf_lo(uint32_t u) { return __uint_as_float(u << 16); }
__device__ __forceinline__ float bf_hi(uint32_t u) { return __uint_as_float(u & 0xffff0000u); }
__device__ __forceinline__ uint32_t pack_bf(float lo, float hi) {
    uint32_t r;
    asm("cvt.rn.bf16x2.f32 %0, %1, %2;" : "=r"(r) : "f"(hi), "f"(lo));
    return r;
}
__device__ __forceinline__ float tanh_fast(float x) {
    float r;
    asm volatile("tanh.approx.f32 %0, %1;" : "=f"(r) : "f"(x));
    return r;
}
__device__ __forceinline__ float silu_half(float h) { return fmaf(h, tanh_fast(h), h); }
__device__ __forceinline__ void ldsm4(uint32_t (&u)[4], uint32_t a) {
    asm volatile("ldmatrix.sync.aligned.m8n8.x4.shared.b16 {%0,%1,%2,%3}, [%4];"
                 : "=r"(u[0]), "=r"(u[1]), "=r"(u[2]), "=r"(u[3]) : "r"(a) : "memory");
}
__device__ __forceinline__ void ldsm4t(uint32_t (&u)[4], uint32_t a) {
    asm volatile("ldmatrix.sync.aligned.m8n8.x4.trans.shared.b16 {%0,%1,%2,%3}, [%4];"
                 : "=r"(u[0]), "=r"(u[1]), "=r"(u[2]), "=r"(u[3]) : "r"(a) : "memory");
}
__device__ __forceinline__ void stsm4(uint32_t a, uint32_t p0, uint32_t p1, uint32_t p2, uint32_t p3) {
    asm volatile("stmatrix.sync.aligned.m8n8.x4.shared.b16 [%0], {%1,%2,%3,%4};" ::"r"(a), "r"(p0), "r"(p1), "r"(p2), "r"(p3) : "memory");
}
__device__ __forceinline__ void stsm4t(uint32_t a, uint32_t p0, uint32_t p1, uint32_t p2, uint32_t p3) {
    asm volatile("stmatrix.sync.aligned.m8n8.x4.trans.shared.b16 [%0], {%1,%2,%3,%4};" ::"r"(a), "r"(p0), "r"(p1), "r"(p2), "r"(p3) : "memory");
}

#define R8(o) "+f"(d[o]), "+f"(d[o + 1]), "+f"(d[o + 2]), "+f"(d[o + 3]), "+f"(d[o + 4]), "+f"(d[o + 5]), "+f"(d[o + 6]), "+f"(d[o + 7])
template <uint32_t ALO, uint32_t BLO, uint64_t AHI = 8>
__device__ __forceinline__ void wgmma128(float (&d)[64]) {
    asm volatile(
        "wgmma.mma_async.sync.aligned.m64n128k16.f32.bf16.bf16 "
        "{%0,%1,%2,%3,%4,%5,%6,%7,%8,%9,%10,%11,%12,%13,%14,%15,%16,%17,%18,%19,%20,%21,%22,%23,%24,%25,%26,%27,%28,%29,%30,%31,"
        "%32,%33,%34,%35,%36,%37,%38,%39,%40,%41,%42,%43,%44,%45,%46,%47,%48,%49,%50,%51,%52,%53,%54,%55,%56,%57,%58,%59,%60,%61,%62,%63},"
        " %64, %65, 1, 1, 1, 0, 0;"
        : R8(0), R8(8), R8(16), R8(24), R8(32), R8(40), R8(48), R8(56)
        : "l"((AHI << 32) | ALO), "l"((8ull << 32) | BLO));
}
template <int S>
__device__ __forceinline__ void mma_stages(float (&d)[64], int conv, int tid, Scratch* gs) {
    constexpr uint32_t A = ((SM_ACT + ky_of(S >> 3) * ROW_BYTES + (S & 7) * 2 * CH_PITCH + 16) >> 4) | ((CH_PITCH >> 4) << 16);
    constexpr uint32_t B = ((SM_W + (S % NS) * STAGE_BYTES) >> 4) | ((2048 >> 4) << 16);
    if (S == 0) mbar_wait(BAR(BAR_FULL), conv);
    bool next_ok = true;
    constexpr uint32_t NEXT = S + 1 < NSTAGE ? BAR(BAR_FULL + S + 1) : BAR(BAR_EMB);
    const int npar = S + 1 < NSTAGE ? conv : 0;
    next_ok = mbar_test(NEXT, npar);
    if (S == 0 && tid == 0) TL(32 + conv * 24);
    asm volatile("wgmma.fence.sync.aligned;" ::: "memory");
    wgmma128<A, B>(d);
    wgmma128<A + 1, B + (STEP_BYTES >> 4)>(d);
    wgmma128<A + 2, B + 2 * (STEP_BYTES >> 4)>(d);
    asm volatile("wgmma.commit_group.sync.aligned;" ::: "memory");
    if (S >= LAG) {
        asm volatile("wgmma.wait_group.sync.aligned %0;" ::"n"(LAG) : "memory");
        if ((tid & 31) == 0) mbar_arrive(BAR(BAR_WEMPTY + (S + NS - LAG) % NS));
    }
    if (!next_ok) mbar_wait(NEXT, npar);
    if constexpr (S + 1 < NSTAGE) mma_stages<S + 1>(d, conv, tid, gs);
}

__device__ __forceinline__ void weight_block(const uint4 (&t)[5], uint32_t bounce, unsigned char* wt, int cta, int lane) {
    const uint32_t bw = bounce + (lane >> 4) * 1152 + (lane & 15) * 16;
#pragma unroll
    for (int k = 0; k < 4; k++) sts128(bw + k * 256, t[k]);
    if ((lane & 15) < 8) sts128(bw + 1024, t[4]);
    __syncwarp();
    if (lane < 16) {
        uint32_t v[36];
#pragma unroll
        for (int i = 0; i < 9; i++) {
            const uint4 q = lds128(bounce + (lane & 1) * 1152 + (lane >> 1) * 144 + i * 16);
            v[4 * i] = q.x; v[4 * i + 1] = q.y; v[4 * i + 2] = q.z; v[4 * i + 3] = q.w;
        }
        const int cc = (cta >> 6) * 8 + (lane >> 1);
        unsigned char* dst = wt + (cc >> 1) * STAGE_BYTES + (cc & 1) * 2048 + ((cta & 63) * 2 + (lane & 1)) * 16;
#pragma unroll
        for (int kyo = 0; kyo < 3; kyo++) {
#pragma unroll
            for (int kx = 0; kx < 3; kx++) {
                const int tap = ky_of(kyo) * 3 + kx;
                uint32_t o[4];
#pragma unroll
                for (int m = 0; m < 4; m++) {
                    const int i0 = 18 * m + tap, i1 = i0 + 9;
                    const uint32_t sel = ((i0 & 1) ? 0x32u : 0x10u) | ((i1 & 1) ? 0x7600u : 0x5400u);
                    o[m] = __byte_perm(v[i0 >> 1], v[i1 >> 1], sel);
                }
                *reinterpret_cast<uint4*>(dst + (kyo * 24 + kx) * STEP_BYTES) = make_uint4(o[0], o[1], o[2], o[3]);
            }
        }
    }
}
__device__ __forceinline__ uint32_t act2(uint32_t u, const float4& cf) {
    return pack_bf(silu_half(fmaf(bf_lo(u), cf.x, cf.z)), silu_half(fmaf(bf_hi(u), cf.y, cf.w)));
}
__device__ __forceinline__ void norm_unit(uint32_t (&u)[4], const float4& ca, const float4& cb) {
    u[0] = act2(u[0], ca); u[1] = act2(u[1], ca); u[2] = act2(u[2], cb); u[3] = act2(u[3], cb);
}
__device__ __forceinline__ void publish(uint32_t bar, int lane) {
    fence_async_smem();
    __syncwarp();
    if (lane == 0) mbar_arrive(bar);
}
__device__ __forceinline__ void publish2(uint32_t bar, int lane) {
    fence_async_smem();
    __syncwarp();
    if (lane < 2) mbar_arrive(bar + 16 * lane);
}
__device__ __forceinline__ void stat_mma(float (&c)[4], uint32_t p, uint32_t q) {
    asm("mma.sync.aligned.m16n8k16.row.col.f32.bf16.bf16.f32 {%0,%1,%2,%3}, {%4,%5,%6,%5}, {%4,%6}, {%0,%1,%2,%3};"
        : "+f"(c[0]), "+f"(c[1]), "+f"(c[2]), "+f"(c[3]) : "r"(p), "r"(0x3f803f80u), "r"(q));
}
__device__ __forceinline__ void stat_store(const float (&c)[4], uint32_t dst, int lane) {
    const int g = lane >> 2, t = lane & 3;
    if (t == (g >> 1)) sts32f(dst + g * 4, (g & 1) ? c[1] : c[0]);
    if (g == 7) sts32f(dst + 32 + t * 4, c[2] + c[3]);
}
__device__ __forceinline__ float sum4(float4 v) { return (v.x + v.y) + (v.z + v.w); }
__device__ __forceinline__ void fence_acc(float (&d)[64]) {
#pragma unroll
    for (int i = 0; i < 64; i++) asm volatile("" : "+f"(d[i])::"memory");
}
__device__ __forceinline__ void ld_unit(uint32_t (&u)[4], const uint4* p) {
    asm volatile("ld.relaxed.gpu.global.v4.u32 {%0,%1,%2,%3}, [%4];" : "=r"(u[0]), "=r"(u[1]), "=r"(u[2]), "=r"(u[3]) : "l"(p) : "memory");
}

__global__ void __launch_bounds__(NTHREADS, 1)
resblock_kernel(const __nv_bfloat16* __restrict__ x, const __nv_bfloat16* __restrict__ w1,
                const __nv_bfloat16* __restrict__ t_emb, const __nv_bfloat16* __restrict__ g1,
                const __nv_bfloat16* __restrict__ be1, const __nv_bfloat16* __restrict__ w_emb,
                const __nv_bfloat16* __restrict__ g2, const __nv_bfloat16* __restrict__ be2,
                const __nv_bfloat16* __restrict__ w2, __nv_bfloat16* __restrict__ out, Scratch* __restrict__ gs) {
    const unsigned clk0 = clock32();
    const int tid = threadIdx.x, warp = tid >> 5, lane = tid & 31;
    const int cta = blockIdx.x, b = cta >> 6, r = cta & 63;

    const uint32_t woff = ((2 * r + (lane >> 4)) * C + b * 64) * 18 + (lane & 15) * 16;
    const int c0 = (warp - 8) * 16 + (lane >> 3), seg = lane & 7;
    uint4 v[5];
    if (warp == 0) {
        const char* w1s = reinterpret_cast<const char*>(w1) + woff;
#pragma unroll
        for (int k = 0; k < 4; k++) v[k] = __ldg(reinterpret_cast<const uint4*>(w1s + k * 256));
        if ((lane & 15) < 8) v[4] = __ldg(reinterpret_cast<const uint4*>(w1s + 1024));
    }
    if (warp >= 8 || warp == 5) {
        if (warp >= 8) {
            const char* src = reinterpret_cast<const char*>(x) + (uint32_t)(((b * C + c0) * HW + r) * HW * 2 + seg * 16);
            while (clock32() - clk0 < XDELAY) {}
#pragma unroll
            for (int k = 0; k < 4; k++) v[k] = __ldg(reinterpret_cast<const uint4*>(src + k * (4 * HW * HW * 2)));
#pragma unroll
            for (int i = 0; i < 8; i++) {
                if (i < 4 ? (r != 0) : (r != HW - 1))
                    asm volatile("cp.async.cg.shared.global [%0], [%1], 16;"
                                 ::"r"(SM_XH + (i >> 2) * 16384 + c0 * 128 + (i & 3) * 512 + ((seg ^ ((c0 + 4 * i) & 7)) << 4)),
                                   "l"(src + (i < 4 ? -HW * 2 : HW * 2) + (i & 3) * (4 * HW * HW * 2)) : "memory");
            }
        } else {
#pragma unroll
            for (int k = 0; k < 4; k++) v[k] = make_uint4(0, 0, 0, 0);
        }
        float c[4] = {0.f, 0.f, 0.f, 0.f};
#pragma unroll
        for (int k = 0; k < 4; k++) { stat_mma(c, v[k].x, v[k].y); stat_mma(c, v[k].z, v[k].w); }
        stat_store(c, SM_RED + warp * 48, lane);
        if (tid == 256) TL(2);
        if (warp >= 8) bar_sync(3, 256);
        if ((warp & 7) * 32 + lane < 4 || warp == 5) {
            const uint32_t a = SM_RED + 8 * 48 + (lane & 3) * 96;
            const float q = (sum4(lds128f(a)) + sum4(lds128f(a + 16))) + (sum4(lds128f(a + 48)) + sum4(lds128f(a + 64)));
            const float sm = sum4(lds128f(a + 32)) + sum4(lds128f(a + 80));
            if (warp == 8) red_add4(&gs->acc[b * 32 + lane * 4], 1.f, sm, q, 1.f);
        }
        if (tid == 256) TL(3);
    }
    if (warp == 0) {
        weight_block(v, SM_BNC, gs->wt, cta, lane);
        if (r == 0) {
            if (lane < 16) gs->acc[(NB + b) * 32 + lane] = 0.f;
            *reinterpret_cast<float4*>(&gs->emb[b * C + lane * 4]) = make_float4(0.f, 0.f, 0.f, 0.f);
        }
        __syncwarp();
        if (lane == 0) TL(4);
        if (lane < 2) asm volatile("red.release.gpu.global.add.u32 [%0], 1;" ::"l"(&gs->wcnt[lane * 32]) : "memory");
        if (lane == 0) TL(5);
    }

    if (warp >= 8) {
        const int nw = warp - 8;
        {
#pragma unroll
            for (int i = 0; i < 4; i++) sts128(SM_XOWN + c0 * 128 + i * 512 + ((seg ^ ((c0 + 4 * i) & 7)) << 4), v[i]);
            asm volatile("cp.async.wait_all;" ::: "memory");
            bar_sync(4, 256 + 96);
        }
        const int par = nw >> 2, wq = nw & 3;
        const uint32_t act_off = SM_ACT + (par * 2 + (lane >> 4)) * CH_PITCH + (2 + wq * 16 + (lane & 15)) * 16;
        const uint32_t stg_off = (par * 16 + (lane >> 4) * 8 + (lane & 7)) * 128 + (((2 * wq + ((lane >> 3) & 1)) ^ (lane & 7)) << 4);
        const uint32_t fbar = BAR(BAR_FULL) + 8 * par;
#pragma unroll 1
        for (int conv = 0; conv < 2; conv++) {
            uint32_t u[12][4];
            float4 cf[8];
            if (conv == 0) {
#pragma unroll
                for (int i = 0; i < 4; i++) ldsm4t(u[i], SM_XOWN + stg_off + i * 4096);
#pragma unroll
                for (int i = 0; i < 8; i++) ldsm4t(u[4 + i], SM_XH + stg_off + i * 4096);
                publish(BAR(BAR_XFREE), lane);
            } else {
                mbar_wait(BAR(BAR_HW), 0);
#pragma unroll
                for (int i = 0; i < 4; i++) ldsm4(u[i], act_off + ROW_BYTES + i * 4 * CH_PITCH);
            }
            uint4* hp = gs->h + (size_t)cta * 2048 + nw * 32 + lane;
            const uint32_t cfa = SM_COEF + par * 128 + (lane & 3) * 16;
            mbar_wait(BAR(BAR_STATS), conv);
            if (tid == 256) TL(22 + conv * 4);
            cf[0] = lds128f(cfa); cf[1] = lds128f(cfa + 64);
            norm_unit(u[0], cf[0], cf[1]);
            stsm4(act_off + ROW_BYTES, u[0][0], u[0][1], u[0][2], u[0][3]);
            publish(fbar, lane);
            if (tid == 256) TL(8 + conv * 8);
#pragma unroll
            for (int i = 2; i < 8; i++) cf[i] = lds128f(cfa + (i >> 1) * 256 + (i & 1) * 64);
            if (conv == 1) {
#pragma unroll
                for (int i = 0; i < 8; i++) ld_unit(u[4 + i], hp + i * 256);
            }
#pragma unroll
            for (int t = 1; t < 12; t++) {
                if (t == 4) publish(fbar + 16 * 3, lane);
                if (t == 4 && conv == 1) {
                    if (tid == 256) TL(24 + conv * 4);
                    unsigned it = 0;
                    while (true) {
                        bool oku = true, okd = true;
#pragma unroll
                        for (int i = 0; i < 16; i++) { oku = oku && u[4 + (i >> 2)][i & 3] != 0; okd = okd && u[8 + (i >> 2)][i & 3] != 0; }
                        if (__all_sync(0xffffffffu, (oku || r == 0) && (okd || r == HW - 1)) || ++it > SPIN_LIMIT) break;
#pragma unroll
                        for (int i = 0; i < 8; i++) ld_unit(u[4 + i], hp + i * 256);
                    }
#pragma unroll
                    for (int i = 0; i < 32; i++) u[4 + (i >> 2)][i & 3] = ~u[4 + (i >> 2)][i & 3];
                }
                norm_unit(u[t], cf[2 * (t & 3)], cf[2 * (t & 3) + 1]);
                if (t == 2 || t == 3) publish(fbar + 16 * (t - 1), lane);
                if (t >= 6 && !(t & 1)) publish2(fbar + 16 * (t - 2), lane);
                if (t < 4 || (t < 8 ? r != 0 : r != HW - 1))
                    stsm4(act_off + ky_of(t >> 2) * ROW_BYTES + (t & 3) * 4 * CH_PITCH, u[t][0], u[t][1], u[t][2], u[t][3]);
            }
            publish2(fbar + 16 * 10, lane);
            if (conv == 1) {
#pragma unroll
                for (int i = 0; i < 8; i++) hp[i * 256] = make_uint4(0, 0, 0, 0);
            }
            if (tid == 256) TL(23 + conv * 4);
        }
    } else if (warp < 4) {
        const int wq = warp;
        if (wq != 0) {
            const int t = tid - 32;
            if (lane == 0) {
                if (wq < 3) {
#pragma unroll
                    for (int i = 0; i < 12; i++) mbar_init(BAR(BAR_FULL + i) + (wq - 1) * 96, 5);
                    mbar_init(BAR(BAR_STATS) + (wq - 1) * 16, 1);
                    mbar_init(BAR(BAR_EMB) + (wq - 1) * 16, 1);
                } else {
#pragma unroll
                    for (int i = 0; i <= NS; i++) mbar_init(BAR(BAR_WEMPTY + i), 4);
                    mbar_init(BAR(BAR_XFREE), 8);
                }
            }
            fence_async_smem();
            bar_arrive(0, 96 + 128);
            bar_arrive(4, 256 + 96);
            if (t == 95) TLG(1);
            const uint4 z = make_uint4(0, 0, 0, 0);
            sts128(SM_ACT + (t >> 1) * CH_PITCH + (t & 1) * 16, z);
            if (t < 2) sts128(SM_ACT + 3 * ROW_BYTES + t * 16, z);
            if (t < 16) sts128(SM_ONES + t * 16, make_uint4(t < 8 ? 0x3f803f80u : 0u, 0, 0, 0));
            if (r == 0 || r == HW - 1) {
#pragma unroll 1
                for (int i = t; i < ROW_BYTES / 16; i += 96) sts128(SM_ACT + (r == 0 ? 0 : 2 * ROW_BYTES) + i * 16, z);
            }
            fence_async_smem();
        }
        bar_sync(2, 128);

        float d[64];
#pragma unroll
        for (int i = 0; i < 64; i++) d[i] = 0.f;
#pragma unroll 1
        for (int conv = 0; conv < 2; conv++) {
            fence_acc(d);
            mma_stages<0>(d, conv, tid, gs);
            if (conv == 0) {
                asm volatile("wgmma.fence.sync.aligned;" ::: "memory");
                wgmma128<(SM_ONES >> 4) | (8u << 16), (SM_EMB >> 4), 0>(d);
                asm volatile("wgmma.commit_group.sync.aligned;" ::: "memory");
            }
            asm volatile("wgmma.wait_group.sync.aligned 0;" ::: "memory");
            fence_acc(d);
            if (tid == 0) TL(10 + conv * 8);
            if (conv == 1) break;

            uint32_t hp[32];
#pragma unroll
            for (int g = 0; g < 4; g++) {
                float c[4] = {0.f, 0.f, 0.f, 0.f};
#pragma unroll
                for (int i = 0; i < 8; i++) hp[8 * g + i] = pack_bf(d[16 * g + 2 * i], d[16 * g + 2 * i + 1]);
#pragma unroll
                for (int i = 0; i < 4; i++) stat_mma(c, hp[8 * g + 2 * i], hp[8 * g + 2 * i + 1]);
                stat_store(c, SM_RED + (g * 4 + wq) * 48, lane);
            }
            bar_sync(2, 128);
            if (tid < 16) {
                const uint32_t a = SM_RED + tid * 48;
                float q = sum4(lds128f(a)) + sum4(lds128f(a + 16)), sm = sum4(lds128f(a + 32));
                q += __shfl_xor_sync(0xffffu, q, 1); sm += __shfl_xor_sync(0xffffu, sm, 1);
                q += __shfl_xor_sync(0xffffu, q, 2); sm += __shfl_xor_sync(0xffffu, sm, 2);
                if ((tid & 3) == 0) red_add4(&gs->acc[(NB + b) * 32 + tid], 1.f, sm, q, 1.f);
            }
            if (tid == 0) TL(11);
            const uint32_t hbase = SM_ACT + ROW_BYTES + (lane >> 4) * CH_PITCH + (2 + wq * 16 + (lane & 15)) * 16;
#pragma unroll
            for (int kc = 0; kc < 8; kc++) stsm4(hbase + kc * 2 * CH_PITCH, hp[4 * kc], hp[4 * kc + 1], hp[4 * kc + 2], hp[4 * kc + 3]);
            __syncwarp();
            if (lane == 0) mbar_arrive(BAR(BAR_HW));
            if (lane < LAG) mbar_arrive(BAR(BAR_WEMPTY + (NSTAGE - LAG) % NS) + 8 * lane);
            uint4* hup = gs->h + (cta - 1) * 2048 + 1024 + tid;
            uint4* hdn = gs->h + (cta + 1) * 2048 + tid;
            if (r != HW - 1) {
#pragma unroll
                for (int kc = 0; kc < 8; kc++) hdn[kc * 128] = make_uint4(~hp[4 * kc], ~hp[4 * kc + 1], ~hp[4 * kc + 2], ~hp[4 * kc + 3]);
            }
            if (r != 0) {
#pragma unroll
                for (int kc = 0; kc < 8; kc++) hup[kc * 128] = make_uint4(~hp[4 * kc], ~hp[4 * kc + 1], ~hp[4 * kc + 2], ~hp[4 * kc + 3]);
            }
            if (tid == 0) TL(12);
            const uint32_t xbase = SM_XOWN + ((lane >> 4) * 8 + (lane & 7)) * 128 + (((2 * wq + ((lane >> 3) & 1)) ^ (lane & 7)) << 4);
#pragma unroll
            for (int kc = 0; kc < 8; kc++) {
                uint32_t p[4];
                ldsm4t(p, xbase + kc * 2048);
#pragma unroll
                for (int i = 0; i < 4; i++) { d[8 * kc + 2 * i] = bf_lo(p[i]); d[8 * kc + 2 * i + 1] = bf_hi(p[i]); }
            }
        }
        {
            const uint32_t obase = SM_W + ((lane >> 4) * 8 + (lane & 7)) * OUT_PITCH + (wq * 16 + ((lane >> 3) & 1) * 8) * 2;
#pragma unroll
            for (int kc = 0; kc < 8; kc++) {
                stsm4t(obase + kc * 16 * OUT_PITCH, pack_bf(d[8 * kc + 0], d[8 * kc + 1]), pack_bf(d[8 * kc + 2], d[8 * kc + 3]),
                       pack_bf(d[8 * kc + 4], d[8 * kc + 5]), pack_bf(d[8 * kc + 6], d[8 * kc + 7]));
            }
            bar_sync(2, 128);
            const int oc0 = tid >> 3;
            __nv_bfloat16* dst = out + ((size_t)(b * C + oc0) * HW + r) * HW + seg * 8;
#pragma unroll
            for (int i = 0; i < 8; i++)
                *reinterpret_cast<uint4*>(dst + (size_t)i * 16 * HW * HW) = lds128(SM_W + (oc0 + 16 * i) * OUT_PITCH + seg * 16);
            if (tid == 0) { TL(20); TLG(21); }
        }
    } else if (warp < 6) {
        bar_sync(0, 96 + 128);
        if (warp == 4) {
            while (clock32() - clk0 < W2DELAY) {}
            const char* w2s = reinterpret_cast<const char*>(w2) + woff;
#pragma unroll
            for (int k = 0; k < 4; k++) v[k] = __ldg(reinterpret_cast<const uint4*>(w2s + k * 256));
            if ((lane & 15) < 8) v[4] = __ldg(reinterpret_cast<const uint4*>(w2s + 1024));
            const uint2* wsrc = reinterpret_cast<const uint2*>(w_emb + (size_t)r * 12 * C) + lane;
            uint2 wv[12];
#pragma unroll
            for (int i = 0; i < 12; i++) wv[i] = __ldg(wsrc + i * (C / 4));
            float tv = 0.f;
            if (lane < 12) tv = __bfloat162float(t_emb[b * E + r * 12 + lane]);
            weight_block(v, SM_BNC + 2304, gs->wt + NSTAGE * STAGE_BYTES, cta, lane);
            const float sv = silu_half(0.5f * tv);
            float e0 = 0.f, e1 = 0.f, e2 = 0.f, e3 = 0.f;
#pragma unroll
            for (int i = 0; i < 12; i++) {
                const float sx = __shfl_sync(0xffffffffu, sv, i);
                e0 = fmaf(sx, bf_lo(wv[i].x), e0); e1 = fmaf(sx, bf_hi(wv[i].x), e1);
                e2 = fmaf(sx, bf_lo(wv[i].y), e2); e3 = fmaf(sx, bf_hi(wv[i].y), e3);
            }
            mbar_wait(BAR(BAR_WACQ), 0);
            red_add4(&gs->emb[b * C + lane * 4], e0, e1, e2, e3);
            __syncwarp();
            if (lane == 0) TL(13);
            if (lane < 2) asm volatile("red.release.gpu.global.add.u32 [%0], 1;" ::"l"(&gs->wcnt[(NB + lane) * 32]) : "memory");
            if (lane == 0) TL(14);
            unsigned it = 0;
            while (ld_relaxed(&gs->wcnt[(NB + b) * 32]) < (unsigned)NCTA && ++it < SPIN_LIMIT) {}
            fence_acquire();
            const uint4 ef = ld_relaxed_v4(&gs->emb[b * C + lane * 4]);
            const uint32_t eu[4] = {ef.x, ef.y, ef.z, ef.w};
#pragma unroll
            for (int i = 0; i < 4; i++) {
                const float e = __uint_as_float(eu[i]);
                const float hi = bf_lo(pack_bf(e, 0.f));
                sts128(SM_EMB + (lane * 4 + i) * 16, make_uint4(pack_bf(hi, e - hi), 0, 0, 0));
            }
            fence_async_smem();
            __syncwarp();
            if (lane == 0) { mbar_arrive(BAR(BAR_EMB)); TL(19); }
        }
    } else if (warp == 6) {
        bar_sync(0, 96 + 128);
        unsigned it = 0;
        while (ld_relaxed(&gs->wcnt[b * 32]) < (unsigned)NCTA && ++it < SPIN_LIMIT) {}
        fence_acquire();
        fence_async_global();
        if (lane == 0) { mbar_arrive(BAR(BAR_WACQ)); TL(6); }
        const unsigned char* wsrc = gs->wt;
#pragma unroll 1
        for (int round = 0; round < 2 * NSTAGE / NS; round++) {
            if (round == NSTAGE / NS) { mbar_wait(BAR(BAR_EMB), 0); fence_async_global(); }
            const uint32_t full = BAR(BAR_FULL) + 8 * NS * (round >= NSTAGE / NS ? round - NSTAGE / NS : round);
#pragma unroll
            for (int slot = 0; slot < NS; slot++) {
                if (slot == 9 && round == 0) mbar_wait(BAR(BAR_XFREE), 0);
                mbar_wait(BAR(BAR_WEMPTY + slot), (round & 1) ^ 1);
                if (elect_one()) {
                    mbar_expect(full + 8 * slot, STAGE_BYTES);
                    bulk_g2s(SM_W + slot * STAGE_BYTES, wsrc + slot * STAGE_BYTES, STAGE_BYTES, full + 8 * slot);
                }
            }
            wsrc += NS * STAGE_BYTES;
        }
    } else {
        const uint2 ga1 = __ldg(reinterpret_cast<const uint2*>(g1) + lane), bt1 = __ldg(reinterpret_cast<const uint2*>(be1) + lane);
        const uint2 ga2 = __ldg(reinterpret_cast<const uint2*>(g2) + lane), bt2 = __ldg(reinterpret_cast<const uint2*>(be2) + lane);
        bar_sync(0, 96 + 128);
#pragma unroll 1
        for (int conv = 0; conv < 2; conv++) {
            if (conv == 1) mbar_wait(BAR(BAR_EMB), 0);
            const float* asrc = &gs->acc[(conv * NB + b) * 32 + (lane >> 3) * 4];
            uint4 f;
            unsigned it = 0;
            while (true) {
                f = ld_relaxed_v4(asrc);
                const bool ok = (f.x == 0x42800000u) & (f.w == 0x42800000u);
                if (__all_sync(0xffffffffu, ok) || ++it > SPIN_LIMIT) break;
            }
            if (lane == 0) TL(7 + conv * 8);
            const float inv_n = 1.0f / (32.0f * HW * HW);
            const float mean = __uint_as_float(f.y) * inv_n;
            const float var = fmaxf(fmaf(-mean, mean, __uint_as_float(f.z) * inv_n), 0.f);
            const float rs = 0.5f * rsqrtf(var + 1e-5f);
            const uint2 ga = conv ? ga2 : ga1, bt = conv ? bt2 : bt1;
            float4 k0, k1;
            k0.x = rs * bf_lo(ga.x); k0.y = rs * bf_hi(ga.x); k1.x = rs * bf_lo(ga.y); k1.y = rs * bf_hi(ga.y);
            k0.z = fmaf(-mean, k0.x, 0.5f * bf_lo(bt.x)); k0.w = fmaf(-mean, k0.y, 0.5f * bf_hi(bt.x));
            k1.z = fmaf(-mean, k1.x, 0.5f * bf_lo(bt.y)); k1.w = fmaf(-mean, k1.y, 0.5f * bf_hi(bt.y));
            sts128f(SM_COEF + lane * 32, k0);
            sts128f(SM_COEF + lane * 32 + 16, k1);
            __syncwarp();
            if (lane == 0) mbar_arrive(BAR(BAR_STATS));
        }
        if (r == 0) {
            if (lane < 16) gs->acc[b * 32 + lane] = 0.f;
            if (lane < 2) gs->wcnt[(lane * NB + b) * 32] = 0;
        }
    }
}

}

extern "C" void kernel_launch(void* const* d_in, const int* in_sizes, int n_in, void* d_out, int out_size) {
    (void)in_sizes; (void)n_in; (void)out_size;
    static Scratch* gs = nullptr;
    if (!gs) {
        cudaFuncSetAttribute(resblock_kernel, cudaFuncAttributeMaxDynamicSharedMemorySize, SM_TOTAL);
        cudaGetSymbolAddress((void**)&gs, g_scratch);
    }
    resblock_kernel<<<NCTA, NTHREADS, SM_TOTAL>>>(
        (const __nv_bfloat16*)d_in[0], (const __nv_bfloat16*)d_in[4], (const __nv_bfloat16*)d_in[1],
        (const __nv_bfloat16*)d_in[2], (const __nv_bfloat16*)d_in[3], (const __nv_bfloat16*)d_in[5],
        (const __nv_bfloat16*)d_in[6], (const __nv_bfloat16*)d_in[7], (const __nv_bfloat16*)d_in[8],
        (__nv_bfloat16*)d_out, gs);
}
```

```cpp
#include <cuda_runtime.h>
#include <cuda_bf16.h>
#include <stdint.h>

namespace {

constexpr int C = 128, HW = 64, NB = 2, E = 768;
constexpr int NCTA = NB * HW;
constexpr int NTHREADS = 16 * 32;
constexpr int CH_PITCH = 66 * 16;
constexpr int ROW_BYTES = 16 * CH_PITCH;
constexpr int STEP_BYTES = 4096;
constexpr int STAGE_BYTES = 3 * STEP_BYTES;
constexpr int NSTAGE = 24;
constexpr int NS = 12;
constexpr int LAG = 1;
#define XDELAY 600
#define HDELAY 500
#define PUBMODE 0
#define W2DELAY 2800

constexpr uint32_t SMEM_BASE = 0x400;
constexpr uint32_t SM_ACT = SMEM_BASE;
constexpr uint32_t SM_XOWN = SM_ACT + 3 * ROW_BYTES + 128;
constexpr uint32_t SM_W = SM_XOWN + 16384;
constexpr uint32_t SM_XH = SM_W + 9 * STAGE_BYTES;
constexpr uint32_t SM_COEF = SM_W + NS * STAGE_BYTES;
constexpr uint32_t SM_EMB = SM_COEF + 1024;
constexpr uint32_t SM_ONES = SM_EMB + 2048;
constexpr uint32_t SM_RED = SM_ONES + 256;
constexpr uint32_t SM_BNC = SM_RED + 1024;
constexpr uint32_t SM_BAR = SM_BNC + 2 * 2304;
constexpr int BAR_FULL = 0, BAR_WEMPTY = NSTAGE, BAR_HW = BAR_WEMPTY + NS, BAR_STATS = BAR_HW + 1,
              BAR_EMB = BAR_STATS + 1, BAR_WACQ = BAR_EMB + 1, BAR_XH = BAR_WACQ + 1, BAR_XFREE = BAR_XH + 1, NBAR = BAR_XFREE + 1;
constexpr int SM_TOTAL = SM_BAR + NBAR * 8 - SMEM_BASE;
static_assert(SM_TOTAL <= 232448, "smem");
static_assert(NBAR <= 96, "barrier init");
constexpr int OUT_PITCH = 144;
__host__ __device__ constexpr uint32_t BAR(int i) { return SM_BAR + 8 * i; }
__host__ __device__ constexpr int ky_of(int kyo) { return kyo == 0 ? 1 : (kyo == 1 ? 0 : 2); }

constexpr unsigned SPIN_LIMIT = 1u << 16;

struct Scratch {
    float acc[2 * NB * 32];
    unsigned wcnt[2 * NB * 32];
    float emb[NB * C];
    unsigned char wt[2 * NSTAGE * STAGE_BYTES];
    uint4 h[NCTA * 1024];
};
__device__ __align__(1024) Scratch g_scratch;
#define TL(i) do {} while (0)
#define TLG(i) do {} while (0)

__device__ __forceinline__ unsigned clock32() { unsigned c; asm volatile("mov.u32 %0, %%clock;" : "=r"(c)); return c; }
__device__ __forceinline__ void mbar_init(uint32_t bar, int cnt) {
    asm volatile("mbarrier.init.shared::cta.b64 [%0], %1;" ::"r"(bar), "r"(cnt) : "memory");
}
__device__ __forceinline__ void mbar_arrive(uint32_t bar) {
    asm volatile("mbarrier.arrive.shared::cta.b64 _, [%0];" ::"r"(bar) : "memory");
}
__device__ __forceinline__ void mbar_expect(uint32_t bar, uint32_t bytes) {
    asm volatile("mbarrier.arrive.expect_tx.shared::cta.b64 _, [%0], %1;" ::"r"(bar), "r"(bytes) : "memory");
}
__device__ __forceinline__ bool mbar_try(uint32_t bar, uint32_t par) {
    uint32_t ok;
    asm volatile("{\n.reg .pred p;\nmbarrier.try_wait.parity.shared::cta.b64 p, [%1], %2;\nselp.u32 %0, 1, 0, p;\n}"
                 : "=r"(ok) : "r"(bar), "r"(par) : "memory");
    return ok;
}
__device__ __forceinline__ bool mbar_test(uint32_t bar, uint32_t par) {
    uint32_t ok;
    asm volatile("{\n.reg .pred p;\nmbarrier.test_wait.parity.shared::cta.b64 p, [%1], %2;\nselp.u32 %0, 1, 0, p;\n}"
                 : "=r"(ok) : "r"(bar), "r"(par) : "memory");
    return ok;
}
__device__ __forceinline__ void mbar_wait(uint32_t bar, uint32_t par) {
    unsigned it = 0;
#pragma unroll 1
    while (!mbar_try(bar, par) && ++it < SPIN_LIMIT) {}
}
__device__ __forceinline__ bool elect_one() {
    uint32_t p;
    asm volatile("{\n.reg .pred p;\nelect.sync _|p, 0xffffffff;\nselp.u32 %0, 1, 0, p;\n}" : "=r"(p));
    return p;
}
__device__ __forceinline__ void fence_async_smem() { asm volatile("fence.proxy.async.shared::cta;" ::: "memory"); }
__device__ __forceinline__ void fence_async_global() { asm volatile("fence.proxy.async.global;" ::: "memory"); }
__device__ __forceinline__ void fence_acquire() { asm volatile("fence.acquire.gpu;" ::: "memory"); }
__device__ __forceinline__ void bar_sync(int id, int n) { asm volatile("bar.sync %0, %1;" ::"r"(id), "r"(n) : "memory"); }
__device__ __forceinline__ void bar_arrive(int id, int n) { asm volatile("bar.arrive %0, %1;" ::"r"(id), "r"(n) : "memory"); }
__device__ __forceinline__ void bulk_g2s(uint32_t dst, const void* src, uint32_t bytes, uint32_t bar) {
    asm volatile("cp.async.bulk.shared::cluster.global.mbarrier::complete_tx::bytes [%0], [%1], %2, [%3];"
                 ::"r"(dst), "l"(src), "r"(bytes), "r"(bar) : "memory");
}
__device__ __forceinline__ uint4 ld_relaxed_v4(const void* p) {
    uint4 v;
    asm volatile("ld.relaxed.gpu.global.v4.u32 {%0,%1,%2,%3}, [%4];" : "=r"(v.x), "=r"(v.y), "=r"(v.z), "=r"(v.w) : "l"(p) : "memory");
    return v;
}
__device__ __forceinline__ unsigned ld_relaxed(const void* p) {
    unsigned v;
    asm volatile("ld.relaxed.gpu.global.u32 %0, [%1];" : "=r"(v) : "l"(p) : "memory");
    return v;
}
__device__ __forceinline__ void red_add4(float* p, float a, float b, float c, float d) {
    asm volatile("red.relaxed.gpu.global.add.v4.f32 [%0], {%1,%2,%3,%4};" ::"l"(p), "f"(a), "f"(b), "f"(c), "f"(d) : "memory");
}
__device__ __forceinline__ void sts128(uint32_t a, uint4 v) {
    asm volatile("st.shared.v4.u32 [%0], {%1,%2,%3,%4};" ::"r"(a), "r"(v.x), "r"(v.y), "r"(v.z), "r"(v.w) : "memory");
}
__device__ __forceinline__ void sts128f(uint32_t a, float4 v) {
    asm volatile("st.shared.v4.f32 [%0], {%1,%2,%3,%4};" ::"r"(a), "f"(v.x), "f"(v.y), "f"(v.z), "f"(v.w) : "memory");
}
__device__ __forceinline__ void sts32f(uint32_t a, float v) { asm volatile("st.shared.f32 [%0], %1;" ::"r"(a), "f"(v) : "memory"); }
__device__ __forceinline__ uint4 lds128(uint32_t a) {
    uint4 v;
    asm volatile("ld.shared.v4.u32 {%0,%1,%2,%3}, [%4];" : "=r"(v.x), "=r"(v.y), "=r"(v.z), "=r"(v.w) : "r"(a) : "memory");
    return v;
}
__device__ __forceinline__ float4 lds128f(uint32_t a) {
    float4 v;
    asm volatile("ld.shared.v4.f32 {%0,%1,%2,%3}, [%4];" : "=f"(v.x), "=f"(v.y), "=f"(v.z), "=f"(v.w) : "r"(a) : "memory");
    return v;
}
__device__ __forceinline__ float2 lds64f(uint32_t a) {
    float2 v;
    asm volatile("ld.shared.v2.f32 {%0,%1}, [%2];" : "=f"(v.x), "=f"(v.y) : "r"(a) : "memory");
    return v;
}
__device__ __forceinline__ float bf_lo(uint32_t u) { return __uint_as_float(u << 16); }
__device__ __forceinline__ float bf_hi(uint32_t u) { return __uint_as_float(u & 0xffff0000u); }
__device__ __forceinline__ uint32_t pack_bf(float lo, float hi) {
    uint32_t r;
    asm("cvt.rn.bf16x2.f32 %0, %1, %2;" : "=r"(r) : "f"(hi), "f"(lo));
    return r;
}
__device__ __forceinline__ float tanh_fast(float x) {
    float r;
    asm volatile("tanh.approx.f32 %0, %1;" : "=f"(r) : "f"(x));
    return r;
}
__device__ __forceinline__ float silu_half(float h) { return fmaf(h, tanh_fast(h), h); }
__device__ __forceinline__ void ldsm4(uint32_t (&u)[4], uint32_t a) {
    asm volatile("ldmatrix.sync.aligned.m8n8.x4.shared.b16 {%0,%1,%2,%3}, [%4];"
                 : "=r"(u[0]), "=r"(u[1]), "=r"(u[2]), "=r"(u[3]) : "r"(a) : "memory");
}
__device__ __forceinline__ void ldsm4t(uint32_t (&u)[4], uint32_t a) {
    asm volatile("ldmatrix.sync.aligned.m8n8.x4.trans.shared.b16 {%0,%1,%2,%3}, [%4];"
                 : "=r"(u[0]), "=r"(u[1]), "=r"(u[2]), "=r"(u[3]) : "r"(a) : "memory");
}
__device__ __forceinline__ void stsm4(uint32_t a, uint32_t p0, uint32_t p1, uint32_t p2, uint32_t p3) {
    asm volatile("stmatrix.sync.aligned.m8n8.x4.shared.b16 [%0], {%1,%2,%3,%4};" ::"r"(a), "r"(p0), "r"(p1), "r"(p2), "r"(p3) : "memory");
}
__device__ __forceinline__ void stsm4t(uint32_t a, uint32_t p0, uint32_t p1, uint32_t p2, uint32_t p3) {
    asm volatile("stmatrix.sync.aligned.m8n8.x4.trans.shared.b16 [%0], {%1,%2,%3,%4};" ::"r"(a), "r"(p0), "r"(p1), "r"(p2), "r"(p3) : "memory");
}

#define R8(o) "+f"(d[o]), "+f"(d[o + 1]), "+f"(d[o + 2]), "+f"(d[o + 3]), "+f"(d[o + 4]), "+f"(d[o + 5]), "+f"(d[o + 6]), "+f"(d[o + 7])
template <uint32_t ALO, uint32_t BLO, uint64_t AHI = 8>
__device__ __forceinline__ void wgmma128(float (&d)[64]) {
    asm volatile(
        "wgmma.mma_async.sync.aligned.m64n128k16.f32.bf16.bf16 "
        "{%0,%1,%2,%3,%4,%5,%6,%7,%8,%9,%10,%11,%12,%13,%14,%15,%16,%17,%18,%19,%20,%21,%22,%23,%24,%25,%26,%27,%28,%29,%30,%31,"
        "%32,%33,%34,%35,%36,%37,%38,%39,%40,%41,%42,%43,%44,%45,%46,%47,%48,%49,%50,%51,%52,%53,%54,%55,%56,%57,%58,%59,%60,%61,%62,%63},"
        " %64, %65, 1, 1, 1, 0, 0;"
        : R8(0), R8(8), R8(16), R8(24), R8(32), R8(40), R8(48), R8(56)
        : "l"((AHI << 32) | ALO), "l"((8ull << 32) | BLO));
}
template <int S>
__device__ __forceinline__ void mma_stages(float (&d)[64], int conv, int tid, Scratch* gs) {
    constexpr uint32_t A = ((SM_ACT + ky_of(S >> 3) * ROW_BYTES + (S & 7) * 2 * CH_PITCH + 16) >> 4) | ((CH_PITCH >> 4) << 16);
    constexpr uint32_t B = ((SM_W + (S % NS) * STAGE_BYTES) >> 4) | ((2048 >> 4) << 16);
    if (S == 0) mbar_wait(BAR(BAR_FULL), conv);
    bool next_ok = true;
    constexpr uint32_t NEXT = S + 1 < NSTAGE ? BAR(BAR_FULL + S + 1) : BAR(BAR_EMB);
    const int npar = S + 1 < NSTAGE ? conv : 0;
    next_ok = mbar_test(NEXT, npar);
    if (S == 0 && tid == 0) TL(32 + conv * 24);
    asm volatile("wgmma.fence.sync.aligned;" ::: "memory");
    wgmma128<A, B>(d);
    wgmma128<A + 1, B + (STEP_BYTES >> 4)>(d);
    wgmma128<A + 2, B + 2 * (STEP_BYTES >> 4)>(d);
    asm volatile("wgmma.commit_group.sync.aligned;" ::: "memory");
    if (S >= LAG) {
        asm volatile("wgmma.wait_group.sync.aligned %0;" ::"n"(LAG) : "memory");
        if ((tid & 31) == 0) mbar_arrive(BAR(BAR_WEMPTY + (S + NS - LAG) % NS));
    }
    if (!next_ok) mbar_wait(NEXT, npar);
    if constexpr (S + 1 < NSTAGE) mma_stages<S + 1>(d, conv, tid, gs);
}

__device__ __forceinline__ void weight_block(const uint4 (&t)[5], uint32_t bounce, unsigned char* wt, int cta, int lane) {
    const uint32_t bw = bounce + (lane >> 4) * 1152 + (lane & 15) * 16;
#pragma unroll
    for (int k = 0; k < 4; k++) sts128(bw + k * 256, t[k]);
    if ((lane & 15) < 8) sts128(bw + 1024, t[4]);
    __syncwarp();
    if (lane < 16) {
        uint32_t v[36];
#pragma unroll
        for (int i = 0; i < 9; i++) {
            const uint4 q = lds128(bounce + (lane & 1) * 1152 + (lane >> 1) * 144 + i * 16);
            v[4 * i] = q.x; v[4 * i + 1] = q.y; v[4 * i + 2] = q.z; v[4 * i + 3] = q.w;
        }
        const int cc = (cta >> 6) * 8 + (lane >> 1);
        unsigned char* dst = wt + (cc >> 1) * STAGE_BYTES + (cc & 1) * 2048 + ((cta & 63) * 2 + (lane & 1)) * 16;
#pragma unroll
        for (int kyo = 0; kyo < 3; kyo++) {
#pragma unroll
            for (int kx = 0; kx < 3; kx++) {
                const int tap = ky_of(kyo) * 3 + kx;
                uint32_t o[4];
#pragma unroll
                for (int m = 0; m < 4; m++) {
                    const int i0 = 18 * m + tap, i1 = i0 + 9;
                    const uint32_t sel = ((i0 & 1) ? 0x32u : 0x10u) | ((i1 & 1) ? 0x7600u : 0x5400u);
                    o[m] = __byte_perm(v[i0 >> 1], v[i1 >> 1], sel);
                }
                *reinterpret_cast<uint4*>(dst + (kyo * 24 + kx) * STEP_BYTES) = make_uint4(o[0], o[1], o[2], o[3]);
            }
        }
    }
}
__device__ __forceinline__ uint32_t act2(uint32_t u, const float4& cf) {
    return pack_bf(silu_half(fmaf(bf_lo(u), cf.x, cf.z)), silu_half(fmaf(bf_hi(u), cf.y, cf.w)));
}
__device__ __forceinline__ void norm_unit(uint32_t (&u)[4], const float4& ca, const float4& cb) {
    u[0] = act2(u[0], ca); u[1] = act2(u[1], ca); u[2] = act2(u[2], cb); u[3] = act2(u[3], cb);
}
__device__ __forceinline__ void publish(uint32_t bar, int lane) {
    fence_async_smem();
    __syncwarp();
    if (lane == 0) mbar_arrive(bar);
}
__device__ __forceinline__ void publish2(uint32_t bar, int lane) {
    fence_async_smem();
    __syncwarp();
    if (lane < 2) mbar_arrive(bar + 16 * lane);
}
__device__ __forceinline__ void stat_mma(float (&c)[4], uint32_t p, uint32_t q) {
    asm("mma.sync.aligned.m16n8k16.row.col.f32.bf16.bf16.f32 {%0,%1,%2,%3}, {%4,%5,%6,%5}, {%4,%6}, {%0,%1,%2,%3};"
        : "+f"(c[0]), "+f"(c[1]), "+f"(c[2]), "+f"(c[3]) : "r"(p), "r"(0x3f803f80u), "r"(q));
}
__device__ __forceinline__ void stat_store(const float (&c)[4], uint32_t dst, int lane) {
    const int g = lane >> 2, t = lane & 3;
    if (t == (g >> 1)) sts32f(dst + g * 4, (g & 1) ? c[1] : c[0]);
    if (g == 7) sts32f(dst + 32 + t * 4, c[2] + c[3]);
}
__device__ __forceinline__ float sum4(float4 v) { return (v.x + v.y) + (v.z + v.w); }
__device__ __forceinline__ void fence_acc(float (&d)[64]) {
#pragma unroll
    for (int i = 0; i < 64; i++) asm volatile("" : "+f"(d[i])::"memory");
}
__device__ __forceinline__ void ld_unit(uint32_t (&u)[4], const uint4* p) {
    asm volatile("ld.relaxed.gpu.global.v4.u32 {%0,%1,%2,%3}, [%4];" : "=r"(u[0]), "=r"(u[1]), "=r"(u[2]), "=r"(u[3]) : "l"(p) : "memory");
}

__global__ void __launch_bounds__(NTHREADS, 1)
resblock_kernel(const __nv_bfloat16* __restrict__ x, const __nv_bfloat16* __restrict__ w1,
                const __nv_bfloat16* __restrict__ t_emb, const __nv_bfloat16* __restrict__ g1,
                const __nv_bfloat16* __restrict__ be1, const __nv_bfloat16* __restrict__ w_emb,
                const __nv_bfloat16* __restrict__ g2, const __nv_bfloat16* __restrict__ be2,
                const __nv_bfloat16* __restrict__ w2, __nv_bfloat16* __restrict__ out, Scratch* __restrict__ gs) {
    const unsigned clk0 = clock32();
    const int tid = threadIdx.x, warp = tid >> 5, lane = tid & 31;
    const int cta = blockIdx.x, b = cta >> 6, r = cta & 63;

    const uint32_t woff = ((2 * r + (lane >> 4)) * C + b * 64) * 18 + (lane & 15) * 16;
    const int c0 = (warp - 8) * 16 + (lane >> 3), seg = lane & 7;
    uint4 v[5];
    if (warp == 0) {
        const char* w1s = reinterpret_cast<const char*>(w1) + woff;
#pragma unroll
        for (int k = 0; k < 4; k++) v[k] = __ldg(reinterpret_cast<const uint4*>(w1s + k * 256));
        if ((lane & 15) < 8) v[4] = __ldg(reinterpret_cast<const uint4*>(w1s + 1024));
    }
    if (warp >= 8 || warp == 5) {
        if (warp >= 8) {
            const char* src = reinterpret_cast<const char*>(x) + (uint32_t)(((b * C + c0) * HW + r) * HW * 2 + seg * 16);
            while (clock32() - clk0 < XDELAY) {}
#pragma unroll
            for (int k = 0; k < 4; k++) v[k] = __ldg(reinterpret_cast<const uint4*>(src + k * (4 * HW * HW * 2)));
#pragma unroll
            for (int i = 0; i < 8; i++) {
                if (i < 4 ? (r != 0) : (r != HW - 1))
                    asm volatile("cp.async.cg.shared.global [%0], [%1], 16;"
                                 ::"r"(SM_XH + (i >> 2) * 16384 + c0 * 128 + (i & 3) * 512 + ((seg ^ ((c0 + 4 * i) & 7)) << 4)),
                                   "l"(src + (i < 4 ? -HW * 2 : HW * 2) + (i & 3) * (4 * HW * HW * 2)) : "memory");
            }
        } else {
#pragma unroll
            for (int k = 0; k < 4; k++) v[k] = make_uint4(0, 0, 0, 0);
        }
        float c[4] = {0.f, 0.f, 0.f, 0.f};
#pragma unroll
        for (int k = 0; k < 4; k++) { stat_mma(c, v[k].x, v[k].y); stat_mma(c, v[k].z, v[k].w); }
        stat_store(c, SM_RED + warp * 48, lane);
        if (tid == 256) TL(2);
        if (warp >= 8) bar_sync(3, 256);
        if ((warp & 7) * 32 + lane < 4 || warp == 5) {
            const uint32_t a = SM_RED + 8 * 48 + (lane & 3) * 96;
            const float q = (sum4(lds128f(a)) + sum4(lds128f(a + 16))) + (sum4(lds128f(a + 48)) + sum4(lds128f(a + 64)));
            const float sm = sum4(lds128f(a + 32)) + sum4(lds128f(a + 80));
            if (warp == 8) red_add4(&gs->acc[b * 32 + lane * 4], 1.f, sm, q, 1.f);
        }
        if (tid == 256) TL(3);
    }
    if (warp == 0) {
        weight_block(v, SM_BNC, gs->wt, cta, lane);
        if (r == 0) {
            if (lane < 16) gs->acc[(NB + b) * 32 + lane] = 0.f;
            *reinterpret_cast<float4*>(&gs->emb[b * C + lane * 4]) = make_float4(0.f, 0.f, 0.f, 0.f);
        }
        __syncwarp();
        if (lane == 0) TL(4);
        if (lane < 2) asm volatile("red.release.gpu.global.add.u32 [%0], 1;" ::"l"(&gs->wcnt[lane * 32]) : "memory");
        if (lane == 0) TL(5);
    }

    if (warp >= 8) {
        const int nw = warp - 8;
        {
#pragma unroll
            for (int i = 0; i < 4; i++) sts128(SM_XOWN + c0 * 128 + i * 512 + ((seg ^ ((c0 + 4 * i) & 7)) << 4), v[i]);
            asm volatile("cp.async.wait_all;" ::: "memory");
            bar_sync(4, 256 + 96);
        }
        const int par = nw >> 2, wq = nw & 3;
        const uint32_t act_off = SM_ACT + (par * 2 + (lane >> 4)) * CH_PITCH + (2 + wq * 16 + (lane & 15)) * 16;
        const uint32_t stg_off = (par * 16 + (lane >> 4) * 8 + (lane & 7)) * 128 + (((2 * wq + ((lane >> 3) & 1)) ^ (lane & 7)) << 4);
        const uint32_t fbar = BAR(BAR_FULL) + 8 * par;
#pragma unroll 1
        for (int conv = 0; conv < 2; conv++) {
            uint32_t u[12][4];
            float4 cf[8];
            if (conv == 0) {
#pragma unroll
                for (int i = 0; i < 4; i++) ldsm4t(u[i], SM_XOWN + stg_off + i * 4096);
#pragma unroll
                for (int i = 0; i < 8; i++) ldsm4t(u[4 + i], SM_XH + stg_off + i * 4096);
                publish(BAR(BAR_XFREE), lane);
            } else {
                mbar_wait(BAR(BAR_HW), 0);
#pragma unroll
                for (int i = 0; i < 4; i++) ldsm4(u[i], act_off + ROW_BYTES + i * 4 * CH_PITCH);
            }
            if (conv == 1) {
                const uint4* hu = gs->h + (size_t)(r != 0 ? cta - 1 : cta) * 1024 + nw * 32 + lane;
                const uint4* hd = gs->h + (size_t)(r != HW - 1 ? cta + 1 : cta) * 1024 + nw * 32 + lane;
                const unsigned c1 = clock32();
                while (clock32() - c1 < HDELAY) {}
                unsigned it = 0;
                while (true) {
#pragma unroll
                    for (int i = 0; i < 4; i++) { ld_unit(u[4 + i], hu + i * 256); ld_unit(u[8 + i], hd + i * 256); }
                    bool ok = true;
#pragma unroll
                    for (int i = 0; i < 32; i++) ok = ok && u[4 + (i >> 2)][i & 3] != 0xffffffffu;
                    if (__all_sync(0xffffffffu, ok) || ++it > SPIN_LIMIT) break;
                }
                if (tid == 256) TL(28);
            }
            const uint32_t cfa = SM_COEF + par * 128 + (lane & 3) * 16;
            mbar_wait(BAR(BAR_STATS), conv);
            if (tid == 256) TL(22 + conv * 4);
#pragma unroll
            for (int i = 0; i < 8; i++) cf[i] = lds128f(cfa + (i >> 1) * 256 + (i & 1) * 64);
#pragma unroll
            for (int t = 0; t < 12; t++) {
                norm_unit(u[t], cf[2 * (t & 3)], cf[2 * (t & 3) + 1]);
                if (t >= 4 && !(t & 1)) publish2(fbar + 16 * (t - 2), lane);
                if (t < 4 || (t < 8 ? r != 0 : r != HW - 1))
                    stsm4(act_off + ky_of(t >> 2) * ROW_BYTES + (t & 3) * 4 * CH_PITCH, u[t][0], u[t][1], u[t][2], u[t][3]);
                if (t == 1) publish2(fbar, lane);
                if (t == 1 && tid == 256) TL(8 + conv * 8);
            }
            publish2(fbar + 16 * 10, lane);
            if (tid == 256) TL(23 + conv * 4);
        }
    } else if (warp < 4) {
        const int wq = warp;
        if (wq != 0) {
            const int t = tid - 32;
            if (lane == 0) {
                if (wq < 3) {
#pragma unroll
                    for (int i = 0; i < 12; i++) mbar_init(BAR(BAR_FULL + i) + (wq - 1) * 96, 5);
                    mbar_init(BAR(BAR_STATS) + (wq - 1) * 16, 1);
                    mbar_init(BAR(BAR_EMB) + (wq - 1) * 16, 1);
                } else {
#pragma unroll
                    for (int i = 0; i <= NS; i++) mbar_init(BAR(BAR_WEMPTY + i), 4);
                    mbar_init(BAR(BAR_XFREE), 8);
                }
            }
#pragma unroll 1
            for (int i = t; i < 1024; i += 96) gs->h[cta * 1024 + i] = make_uint4(~0u, ~0u, ~0u, ~0u);
            fence_async_smem();
            bar_arrive(0, 96 + 128);
            bar_arrive(4, 256 + 96);
            if (t == 95) TLG(1);
            const uint4 z = make_uint4(0, 0, 0, 0);
            sts128(SM_ACT + (t >> 1) * CH_PITCH + (t & 1) * 16, z);
            if (t < 2) sts128(SM_ACT + 3 * ROW_BYTES + t * 16, z);
            if (t < 16) sts128(SM_ONES + t * 16, make_uint4(t < 8 ? 0x3f803f80u : 0u, 0, 0, 0));
            if (r == 0 || r == HW - 1) {
#pragma unroll 1
                for (int i = t; i < ROW_BYTES / 16; i += 96) sts128(SM_ACT + (r == 0 ? 0 : 2 * ROW_BYTES) + i * 16, z);
            }
            fence_async_smem();
        }
        bar_sync(2, 128);

        float d[64];
#pragma unroll
        for (int i = 0; i < 64; i++) d[i] = 0.f;
#pragma unroll 1
        for (int conv = 0; conv < 2; conv++) {
            fence_acc(d);
            mma_stages<0>(d, conv, tid, gs);
            if (conv == 0) {
                asm volatile("wgmma.fence.sync.aligned;" ::: "memory");
                wgmma128<(SM_ONES >> 4) | (8u << 16), (SM_EMB >> 4), 0>(d);
                asm volatile("wgmma.commit_group.sync.aligned;" ::: "memory");
            }
            asm volatile("wgmma.wait_group.sync.aligned 0;" ::: "memory");
            fence_acc(d);
            if (tid == 0) TL(10 + conv * 8);
            if (conv == 1) break;

            uint32_t hp[32];
#pragma unroll
            for (int g = 0; g < 4; g++) {
                float c[4] = {0.f, 0.f, 0.f, 0.f};
#pragma unroll
                for (int i = 0; i < 8; i++) hp[8 * g + i] = pack_bf(d[16 * g + 2 * i], d[16 * g + 2 * i + 1]);
#pragma unroll
                for (int i = 0; i < 4; i++) stat_mma(c, hp[8 * g + 2 * i], hp[8 * g + 2 * i + 1]);
                stat_store(c, SM_RED + (g * 4 + wq) * 48, lane);
            }
            bar_sync(2, 128);
            if (tid < 16) {
                const uint32_t a = SM_RED + tid * 48;
                float q = sum4(lds128f(a)) + sum4(lds128f(a + 16)), sm = sum4(lds128f(a + 32));
                q += __shfl_xor_sync(0xffffu, q, 1); sm += __shfl_xor_sync(0xffffu, sm, 1);
                q += __shfl_xor_sync(0xffffu, q, 2); sm += __shfl_xor_sync(0xffffu, sm, 2);
                if ((tid & 3) == 0) red_add4(&gs->acc[(NB + b) * 32 + tid], 1.f, sm, q, 1.f);
            }
            if (tid == 0) TL(11);
            const uint32_t hbase = SM_ACT + ROW_BYTES + (lane >> 4) * CH_PITCH + (2 + wq * 16 + (lane & 15)) * 16;
#pragma unroll
            for (int kc = 0; kc < 8; kc++) stsm4(hbase + kc * 2 * CH_PITCH, hp[4 * kc], hp[4 * kc + 1], hp[4 * kc + 2], hp[4 * kc + 3]);
            __syncwarp();
            if (lane == 0) mbar_arrive(BAR(BAR_HW));
            if (lane < LAG) mbar_arrive(BAR(BAR_WEMPTY + (NSTAGE - LAG) % NS) + 8 * lane);
            uint4* hg = gs->h + cta * 1024 + tid;
#pragma unroll
            for (int kc = 0; kc < 8; kc++) hg[kc * 128] = make_uint4(hp[4 * kc], hp[4 * kc + 1], hp[4 * kc + 2], hp[4 * kc + 3]);
            if (tid == 0) TL(12);
            const uint32_t xbase = SM_XOWN + ((lane >> 4) * 8 + (lane & 7)) * 128 + (((2 * wq + ((lane >> 3) & 1)) ^ (lane & 7)) << 4);
#pragma unroll
            for (int kc = 0; kc < 8; kc++) {
                uint32_t p[4];
                ldsm4t(p, xbase + kc * 2048);
#pragma unroll
                for (int i = 0; i < 4; i++) { d[8 * kc + 2 * i] = bf_lo(p[i]); d[8 * kc + 2 * i + 1] = bf_hi(p[i]); }
            }
        }
        {
            const uint32_t obase = SM_W + ((lane >> 4) * 8 + (lane & 7)) * OUT_PITCH + (wq * 16 + ((lane >> 3) & 1) * 8) * 2;
#pragma unroll
            for (int kc = 0; kc < 8; kc++) {
                stsm4t(obase + kc * 16 * OUT_PITCH, pack_bf(d[8 * kc + 0], d[8 * kc + 1]), pack_bf(d[8 * kc + 2], d[8 * kc + 3]),
                       pack_bf(d[8 * kc + 4], d[8 * kc + 5]), pack_bf(d[8 * kc + 6], d[8 * kc + 7]));
            }
            bar_sync(2, 128);
            const int oc0 = tid >> 3;
            __nv_bfloat16* dst = out + ((size_t)(b * C + oc0) * HW + r) * HW + seg * 8;
#pragma unroll
            for (int i = 0; i < 8; i++)
                *reinterpret_cast<uint4*>(dst + (size_t)i * 16 * HW * HW) = lds128(SM_W + (oc0 + 16 * i) * OUT_PITCH + seg * 16);
            if (tid == 0) { TL(20); TLG(21); }
        }
    } else if (warp < 6) {
        bar_sync(0, 96 + 128);
        if (warp == 4) {
            while (clock32() - clk0 < W2DELAY) {}
            const char* w2s = reinterpret_cast<const char*>(w2) + woff;
#pragma unroll
            for (int k = 0; k < 4; k++) v[k] = __ldg(reinterpret_cast<const uint4*>(w2s + k * 256));
            if ((lane & 15) < 8) v[4] = __ldg(reinterpret_cast<const uint4*>(w2s + 1024));
            const uint2* wsrc = reinterpret_cast<const uint2*>(w_emb + (size_t)r * 12 * C) + lane;
            uint2 wv[12];
#pragma unroll
            for (int i = 0; i < 12; i++) wv[i] = __ldg(wsrc + i * (C / 4));
            float tv = 0.f;
            if (lane < 12) tv = __bfloat162float(t_emb[b * E + r * 12 + lane]);
            weight_block(v, SM_BNC + 2304, gs->wt + NSTAGE * STAGE_BYTES, cta, lane);
            const float sv = silu_half(0.5f * tv);
            float e0 = 0.f, e1 = 0.f, e2 = 0.f, e3 = 0.f;
#pragma unroll
            for (int i = 0; i < 12; i++) {
                const float sx = __shfl_sync(0xffffffffu, sv, i);
                e0 = fmaf(sx, bf_lo(wv[i].x), e0); e1 = fmaf(sx, bf_hi(wv[i].x), e1);
                e2 = fmaf(sx, bf_lo(wv[i].y), e2); e3 = fmaf(sx, bf_hi(wv[i].y), e3);
            }
            mbar_wait(BAR(BAR_WACQ), 0);
            red_add4(&gs->emb[b * C + lane * 4], e0, e1, e2, e3);
            __syncwarp();
            if (lane == 0) TL(13);
            if (lane < 2) asm volatile("red.release.gpu.global.add.u32 [%0], 1;" ::"l"(&gs->wcnt[(NB + lane) * 32]) : "memory");
            if (lane == 0) TL(14);
            unsigned it = 0;
            while (ld_relaxed(&gs->wcnt[(NB + b) * 32]) < (unsigned)NCTA && ++it < SPIN_LIMIT) {}
            fence_acquire();
            const uint4 ef = ld_relaxed_v4(&gs->emb[b * C + lane * 4]);
            const uint32_t eu[4] = {ef.x, ef.y, ef.z, ef.w};
#pragma unroll
            for (int i = 0; i < 4; i++) {
                const float e = __uint_as_float(eu[i]);
                const float hi = bf_lo(pack_bf(e, 0.f));
                sts128(SM_EMB + (lane * 4 + i) * 16, make_uint4(pack_bf(hi, e - hi), 0, 0, 0));
            }
            fence_async_smem();
            __syncwarp();
            if (lane == 0) { mbar_arrive(BAR(BAR_EMB)); TL(19); }
        }
    } else if (warp == 6) {
        bar_sync(0, 96 + 128);
        unsigned it = 0;
        while (ld_relaxed(&gs->wcnt[b * 32]) < (unsigned)NCTA && ++it < SPIN_LIMIT) {}
        fence_acquire();
        fence_async_global();
        if (lane == 0) { mbar_arrive(BAR(BAR_WACQ)); TL(6); }
        const unsigned char* wsrc = gs->wt;
#pragma unroll 1
        for (int round = 0; round < 2 * NSTAGE / NS; round++) {
            if (round == NSTAGE / NS) { mbar_wait(BAR(BAR_EMB), 0); fence_async_global(); }
            const uint32_t full = BAR(BAR_FULL) + 8 * NS * (round >= NSTAGE / NS ? round - NSTAGE / NS : round);
#pragma unroll
            for (int slot = 0; slot < NS; slot++) {
                if (slot == 9 && round == 0) mbar_wait(BAR(BAR_XFREE), 0);
                mbar_wait(BAR(BAR_WEMPTY + slot), (round & 1) ^ 1);
                if (elect_one()) {
                    mbar_expect(full + 8 * slot, STAGE_BYTES);
                    bulk_g2s(SM_W + slot * STAGE_BYTES, wsrc + slot * STAGE_BYTES, STAGE_BYTES, full + 8 * slot);
                }
            }
            wsrc += NS * STAGE_BYTES;
        }
    } else {
        const uint2 ga1 = __ldg(reinterpret_cast<const uint2*>(g1) + lane), bt1 = __ldg(reinterpret_cast<const uint2*>(be1) + lane);
        const uint2 ga2 = __ldg(reinterpret_cast<const uint2*>(g2) + lane), bt2 = __ldg(reinterpret_cast<const uint2*>(be2) + lane);
        bar_sync(0, 96 + 128);
#pragma unroll 1
        for (int conv = 0; conv < 2; conv++) {
            if (conv == 1) mbar_wait(BAR(BAR_EMB), 0);
            const float* asrc = &gs->acc[(conv * NB + b) * 32 + (lane >> 3) * 4];
            uint4 f;
            unsigned it = 0;
            while (true) {
                f = ld_relaxed_v4(asrc);
                const bool ok = (f.x == 0x42800000u) & (f.w == 0x42800000u);
                if (__all_sync(0xffffffffu, ok) || ++it > SPIN_LIMIT) break;
            }
            if (lane == 0) TL(7 + conv * 8);
            const float inv_n = 1.0f / (32.0f * HW * HW);
            const float mean = __uint_as_float(f.y) * inv_n;
            const float var = fmaxf(fmaf(-mean, mean, __uint_as_float(f.z) * inv_n), 0.f);
            const float rs = 0.5f * rsqrtf(var + 1e-5f);
            const uint2 ga = conv ? ga2 : ga1, bt = conv ? bt2 : bt1;
            float4 k0, k1;
            k0.x = rs * bf_lo(ga.x); k0.y = rs * bf_hi(ga.x); k1.x = rs * bf_lo(ga.y); k1.y = rs * bf_hi(ga.y);
            k0.z = fmaf(-mean, k0.x, 0.5f * bf_lo(bt.x)); k0.w = fmaf(-mean, k0.y, 0.5f * bf_hi(bt.x));
            k1.z = fmaf(-mean, k1.x, 0.5f * bf_lo(bt.y)); k1.w = fmaf(-mean, k1.y, 0.5f * bf_hi(bt.y));
            sts128f(SM_COEF + lane * 32, k0);
            sts128f(SM_COEF + lane * 32 + 16, k1);
            __syncwarp();
            if (lane == 0) mbar_arrive(BAR(BAR_STATS));
        }
        if (r == 0) {
            if (lane < 16) gs->acc[b * 32 + lane] = 0.f;
            if (lane < 2) gs->wcnt[(lane * NB + b) * 32] = 0;
        }
    }
}

}

extern "C" void kernel_launch(void* const* d_in, const int* in_sizes, int n_in, void* d_out, int out_size) {
    (void)in_sizes; (void)n_in; (void)out_size;
    static Scratch* gs = nullptr;
    if (!gs) {
        cudaFuncSetAttribute(resblock_kernel, cudaFuncAttributeMaxDynamicSharedMemorySize, SM_TOTAL);
        cudaGetSymbolAddress((void**)&gs, g_scratch);
    }
    resblock_kernel<<<NCTA, NTHREADS, SM_TOTAL>>>(
        (const __nv_bfloat16*)d_in[0], (const __nv_bfloat16*)d_in[4], (const __nv_bfloat16*)d_in[1],
        (const __nv_bfloat16*)d_in[2], (const __nv_bfloat16*)d_in[3], (const __nv_bfloat16*)d_in[5],
        (const __nv_bfloat16*)d_in[6], (const __nv_bfloat16*)d_in[7], (const __nv_bfloat16*)d_in[8],
        (__nv_bfloat16*)d_out, gs);
}
```

```cpp
#include <cuda_runtime.h>
#include <cuda_bf16.h>
#include <stdint.h>

namespace {

constexpr int C = 128, HW = 64, NB = 2, E = 768;
constexpr int NCTA = NB * HW;
constexpr int NTHREADS = 16 * 32;
constexpr int CH_PITCH = 66 * 16;
constexpr int ROW_BYTES = 16 * CH_PITCH;
constexpr int STEP_BYTES = 4096;
constexpr int STAGE_BYTES = 3 * STEP_BYTES;
constexpr int NSTAGE = 24;
constexpr int NS = 12;
constexpr int LAG = 1;
#define XDELAY 600
#define HDELAY 500
#define PUB1 2
#define HOLD 3
#define W2DELAY 2800

constexpr uint32_t SMEM_BASE = 0x400;
constexpr uint32_t SM_ACT = SMEM_BASE;
constexpr uint32_t SM_XOWN = SM_ACT + 3 * ROW_BYTES + 128;
constexpr uint32_t SM_W = SM_XOWN + 16384;
constexpr uint32_t SM_XH = SM_W + 9 * STAGE_BYTES;
constexpr uint32_t SM_COEF = SM_W + NS * STAGE_BYTES;
constexpr uint32_t SM_EMB = SM_COEF + 1024;
constexpr uint32_t SM_ONES = SM_EMB + 2048;
constexpr uint32_t SM_RED = SM_ONES + 256;
constexpr uint32_t SM_BNC = SM_RED + 1024;
constexpr uint32_t SM_BAR = SM_BNC + 2 * 2304;
constexpr int BAR_FULL = 0, BAR_WEMPTY = NSTAGE, BAR_HW = BAR_WEMPTY + NS, BAR_STATS = BAR_HW + 1,
              BAR_EMB = BAR_STATS + 1, BAR_WACQ = BAR_EMB + 1, BAR_XH = BAR_WACQ + 1, BAR_XFREE = BAR_XH + 1, NBAR = BAR_XFREE + 1;
constexpr int SM_TOTAL = SM_BAR + NBAR * 8 - SMEM_BASE;
static_assert(SM_TOTAL <= 232448, "smem");
static_assert(NBAR <= 96, "barrier init");
constexpr int OUT_PITCH = 144;
__host__ __device__ constexpr uint32_t BAR(int i) { return SM_BAR + 8 * i; }
__host__ __device__ constexpr int ky_of(int kyo) { return kyo == 0 ? 1 : (kyo == 1 ? 0 : 2); }

constexpr unsigned SPIN_LIMIT = 1u << 16;

struct Scratch {
    float acc[2 * NB * 32];
    unsigned wcnt[2 * NB * 32];
    float emb[NB * C];
    unsigned char wt[2 * NSTAGE * STAGE_BYTES];
    unsigned epoch[NCTA * 32];
    uint4 h[2 * NCTA * 1024];
};
__device__ __align__(1024) Scratch g_scratch;
#define TL(i) do {} while (0)
#define TLG(i) do {} while (0)

__device__ __forceinline__ unsigned clock32() { unsigned c; asm volatile("mov.u32 %0, %%clock;" : "=r"(c)); return c; }
__device__ __forceinline__ void mbar_init(uint32_t bar, int cnt) {
    asm volatile("mbarrier.init.shared::cta.b64 [%0], %1;" ::"r"(bar), "r"(cnt) : "memory");
}
__device__ __forceinline__ void mbar_arrive(uint32_t bar) {
    asm volatile("mbarrier.arrive.shared::cta.b64 _, [%0];" ::"r"(bar) : "memory");
}
__device__ __forceinline__ void mbar_expect(uint32_t bar, uint32_t bytes) {
    asm volatile("mbarrier.arrive.expect_tx.shared::cta.b64 _, [%0], %1;" ::"r"(bar), "r"(bytes) : "memory");
}
__device__ __forceinline__ bool mbar_try(uint32_t bar, uint32_t par) {
    uint32_t ok;
    asm volatile("{\n.reg .pred p;\nmbarrier.try_wait.parity.shared::cta.b64 p, [%1], %2;\nselp.u32 %0, 1, 0, p;\n}"
                 : "=r"(ok) : "r"(bar), "r"(par) : "memory");
    return ok;
}
__device__ __forceinline__ bool mbar_test(uint32_t bar, uint32_t par) {
    uint32_t ok;
    asm volatile("{\n.reg .pred p;\nmbarrier.test_wait.parity.shared::cta.b64 p, [%1], %2;\nselp.u32 %0, 1, 0, p;\n}"
                 : "=r"(ok) : "r"(bar), "r"(par) : "memory");
    return ok;
}
__device__ __forceinline__ void mbar_wait(uint32_t bar, uint32_t par) {
    unsigned it = 0;
#pragma unroll 1
    while (!mbar_try(bar, par) && ++it < SPIN_LIMIT) {}
}
__device__ __forceinline__ bool elect_one() {
    uint32_t p;
    asm volatile("{\n.reg .pred p;\nelect.sync _|p, 0xffffffff;\nselp.u32 %0, 1, 0, p;\n}" : "=r"(p));
    return p;
}
__device__ __forceinline__ void fence_async_smem() { asm volatile("fence.proxy.async.shared::cta;" ::: "memory"); }
__device__ __forceinline__ void fence_async_global() { asm volatile("fence.proxy.async.global;" ::: "memory"); }
__device__ __forceinline__ void fence_acquire() { asm volatile("fence.acquire.gpu;" ::: "memory"); }
__device__ __forceinline__ void bar_sync(int id, int n) { asm volatile("bar.sync %0, %1;" ::"r"(id), "r"(n) : "memory"); }
__device__ __forceinline__ void bar_arrive(int id, int n) { asm volatile("bar.arrive %0, %1;" ::"r"(id), "r"(n) : "memory"); }
__device__ __forceinline__ void bulk_g2s(uint32_t dst, const void* src, uint32_t bytes, uint32_t bar) {
    asm volatile("cp.async.bulk.shared::cluster.global.mbarrier::complete_tx::bytes [%0], [%1], %2, [%3];"
                 ::"r"(dst), "l"(src), "r"(bytes), "r"(bar) : "memory");
}
__device__ __forceinline__ uint4 ld_relaxed_v4(const void* p) {
    uint4 v;
    asm volatile("ld.relaxed.gpu.global.v4.u32 {%0,%1,%2,%3}, [%4];" : "=r"(v.x), "=r"(v.y), "=r"(v.z), "=r"(v.w) : "l"(p) : "memory");
    return v;
}
__device__ __forceinline__ unsigned ld_relaxed(const void* p) {
    unsigned v;
    asm volatile("ld.relaxed.gpu.global.u32 %0, [%1];" : "=r"(v) : "l"(p) : "memory");
    return v;
}
__device__ __forceinline__ void red_add4(float* p, float a, float b, float c, float d) {
    asm volatile("red.relaxed.gpu.global.add.v4.f32 [%0], {%1,%2,%3,%4};" ::"l"(p), "f"(a), "f"(b), "f"(c), "f"(d) : "memory");
}
__device__ __forceinline__ void sts128(uint32_t a, uint4 v) {
    asm volatile("st.shared.v4.u32 [%0], {%1,%2,%3,%4};" ::"r"(a), "r"(v.x), "r"(v.y), "r"(v.z), "r"(v.w) : "memory");
}
__device__ __forceinline__ void sts128f(uint32_t a, float4 v) {
    asm volatile("st.shared.v4.f32 [%0], {%1,%2,%3,%4};" ::"r"(a), "f"(v.x), "f"(v.y), "f"(v.z), "f"(v.w) : "memory");
}
__device__ __forceinline__ void sts32f(uint32_t a, float v) { asm volatile("st.shared.f32 [%0], %1;" ::"r"(a), "f"(v) : "memory"); }
__device__ __forceinline__ uint4 lds128(uint32_t a) {
    uint4 v;
    asm volatile("ld.shared.v4.u32 {%0,%1,%2,%3}, [%4];" : "=r"(v.x), "=r"(v.y), "=r"(v.z), "=r"(v.w) : "r"(a) : "memory");
    return v;
}
__device__ __forceinline__ float4 lds128f(uint32_t a) {
    float4 v;
    asm volatile("ld.shared.v4.f32 {%0,%1,%2,%3}, [%4];" : "=f"(v.x), "=f"(v.y), "=f"(v.z), "=f"(v.w) : "r"(a) : "memory");
    return v;
}
__device__ __forceinline__ float2 lds64f(uint32_t a) {
    float2 v;
    asm volatile("ld.shared.v2.f32 {%0,%1}, [%2];" : "=f"(v.x), "=f"(v.y) : "r"(a) : "memory");
    return v;
}
__device__ __forceinline__ float bf_lo(uint32_t u) { return __uint_as_float(u << 16); }
__device__ __forceinline__ float bf_hi(uint32_t u) { return __uint_as_float(u & 0xffff0000u); }
__device__ __forceinline__ uint32_t pack_bf(float lo, float hi) {
    uint32_t r;
    asm("cvt.rn.bf16x2.f32 %0, %1, %2;" : "=r"(r) : "f"(hi), "f"(lo));
    return r;
}
__device__ __forceinline__ float tanh_fast(float x) {
    float r;
    asm volatile("tanh.approx.f32 %0, %1;" : "=f"(r) : "f"(x));
    return r;
}
__device__ __forceinline__ float silu_half(float h) { return fmaf(h, tanh_fast(h), h); }
__device__ __forceinline__ void ldsm4(uint32_t (&u)[4], uint32_t a) {
    asm volatile("ldmatrix.sync.aligned.m8n8.x4.shared.b16 {%0,%1,%2,%3}, [%4];"
                 : "=r"(u[0]), "=r"(u[1]), "=r"(u[2]), "=r"(u[3]) : "r"(a) : "memory");
}
__device__ __forceinline__ void ldsm4t(uint32_t (&u)[4], uint32_t a) {
    asm volatile("ldmatrix.sync.aligned.m8n8.x4.trans.shared.b16 {%0,%1,%2,%3}, [%4];"
                 : "=r"(u[0]), "=r"(u[1]), "=r"(u[2]), "=r"(u[3]) : "r"(a) : "memory");
}
__device__ __forceinline__ void stsm4(uint32_t a, uint32_t p0, uint32_t p1, uint32_t p2, uint32_t p3) {
    asm volatile("stmatrix.sync.aligned.m8n8.x4.shared.b16 [%0], {%1,%2,%3,%4};" ::"r"(a), "r"(p0), "r"(p1), "r"(p2), "r"(p3) : "memory");
}
__device__ __forceinline__ void stsm4t(uint32_t a, uint32_t p0, uint32_t p1, uint32_t p2, uint32_t p3) {
    asm volatile("stmatrix.sync.aligned.m8n8.x4.trans.shared.b16 [%0], {%1,%2,%3,%4};" ::"r"(a), "r"(p0), "r"(p1), "r"(p2), "r"(p3) : "memory");
}

#define R8(o) "+f"(d[o]), "+f"(d[o + 1]), "+f"(d[o + 2]), "+f"(d[o + 3]), "+f"(d[o + 4]), "+f"(d[o + 5]), "+f"(d[o + 6]), "+f"(d[o + 7])
template <uint32_t ALO, uint32_t BLO, uint64_t AHI = 8>
__device__ __forceinline__ void wgmma128(float (&d)[64]) {
    asm volatile(
        "wgmma.mma_async.sync.aligned.m64n128k16.f32.bf16.bf16 "
        "{%0,%1,%2,%3,%4,%5,%6,%7,%8,%9,%10,%11,%12,%13,%14,%15,%16,%17,%18,%19,%20,%21,%22,%23,%24,%25,%26,%27,%28,%29,%30,%31,"
        "%32,%33,%34,%35,%36,%37,%38,%39,%40,%41,%42,%43,%44,%45,%46,%47,%48,%49,%50,%51,%52,%53,%54,%55,%56,%57,%58,%59,%60,%61,%62,%63},"
        " %64, %65, 1, 1, 1, 0, 0;"
        : R8(0), R8(8), R8(16), R8(24), R8(32), R8(40), R8(48), R8(56)
        : "l"((AHI << 32) | ALO), "l"((8ull << 32) | BLO));
}
template <int S>
__device__ __forceinline__ void mma_stages(float (&d)[64], int conv, int tid, Scratch* gs) {
    constexpr uint32_t A = ((SM_ACT + ky_of(S >> 3) * ROW_BYTES + (S & 7) * 2 * CH_PITCH + 16) >> 4) | ((CH_PITCH >> 4) << 16);
    constexpr uint32_t B = ((SM_W + (S % NS) * STAGE_BYTES) >> 4) | ((2048 >> 4) << 16);
    if (S == 0) mbar_wait(BAR(BAR_FULL), conv);
    bool next_ok = true;
    constexpr uint32_t NEXT = S + 1 < NSTAGE ? BAR(BAR_FULL + S + 1) : BAR(BAR_EMB);
    const int npar = S + 1 < NSTAGE ? conv : 0;
    next_ok = mbar_test(NEXT, npar);
    if (S == 0 && tid == 0) TL(32 + conv * 24);
    asm volatile("wgmma.fence.sync.aligned;" ::: "memory");
    wgmma128<A, B>(d);
    wgmma128<A + 1, B + (STEP_BYTES >> 4)>(d);
    wgmma128<A + 2, B + 2 * (STEP_BYTES >> 4)>(d);
    asm volatile("wgmma.commit_group.sync.aligned;" ::: "memory");
    if (S >= LAG) {
        asm volatile("wgmma.wait_group.sync.aligned %0;" ::"n"(LAG) : "memory");
        if ((tid & 31) == 0) mbar_arrive(BAR(BAR_WEMPTY + (S + NS - LAG) % NS));
    }
    if (!next_ok) mbar_wait(NEXT, npar);
    if constexpr (S + 1 < NSTAGE) mma_stages<S + 1>(d, conv, tid, gs);
}

__device__ __forceinline__ void weight_block(const uint4 (&t)[5], uint32_t bounce, unsigned char* wt, int cta, int lane) {
    const uint32_t bw = bounce + (lane >> 4) * 1152 + (lane & 15) * 16;
#pragma unroll
    for (int k = 0; k < 4; k++) sts128(bw + k * 256, t[k]);
    if ((lane & 15) < 8) sts128(bw + 1024, t[4]);
    __syncwarp();
    if (lane < 16) {
        uint32_t v[36];
#pragma unroll
        for (int i = 0; i < 9; i++) {
            const uint4 q = lds128(bounce + (lane & 1) * 1152 + (lane >> 1) * 144 + i * 16);
            v[4 * i] = q.x; v[4 * i + 1] = q.y; v[4 * i + 2] = q.z; v[4 * i + 3] = q.w;
        }
        const int cc = (cta >> 6) * 8 + (lane >> 1);
        unsigned char* dst = wt + (cc >> 1) * STAGE_BYTES + (cc & 1) * 2048 + ((cta & 63) * 2 + (lane & 1)) * 16;
#pragma unroll
        for (int kyo = 0; kyo < 3; kyo++) {
#pragma unroll
            for (int kx = 0; kx < 3; kx++) {
                const int tap = ky_of(kyo) * 3 + kx;
                uint32_t o[4];
#pragma unroll
                for (int m = 0; m < 4; m++) {
                    const int i0 = 18 * m + tap, i1 = i0 + 9;
                    const uint32_t sel = ((i0 & 1) ? 0x32u : 0x10u) | ((i1 & 1) ? 0x7600u : 0x5400u);
                    o[m] = __byte_perm(v[i0 >> 1], v[i1 >> 1], sel);
                }
                *reinterpret_cast<uint4*>(dst + (kyo * 24 + kx) * STEP_BYTES) = make_uint4(o[0], o[1], o[2], o[3]);
            }
        }
    }
}
__device__ __forceinline__ uint32_t act2(uint32_t u, const float4& cf) {
    return pack_bf(silu_half(fmaf(bf_lo(u), cf.x, cf.z)), silu_half(fmaf(bf_hi(u), cf.y, cf.w)));
}
__device__ __forceinline__ void norm_unit(uint32_t (&u)[4], const float4& ca, const float4& cb) {
    u[0] = act2(u[0], ca); u[1] = act2(u[1], ca); u[2] = act2(u[2], cb); u[3] = act2(u[3], cb);
}
__device__ __forceinline__ void publish(uint32_t bar, int lane) {
    fence_async_smem();
    __syncwarp();
    if (lane == 0) mbar_arrive(bar);
}
__device__ __forceinline__ void publish2(uint32_t bar, int lane) {
    fence_async_smem();
    __syncwarp();
    if (lane < 2) mbar_arrive(bar + 8 * lane);
}
__device__ __forceinline__ void stat_mma(float (&c)[4], uint32_t p, uint32_t q) {
    asm("mma.sync.aligned.m16n8k16.row.col.f32.bf16.bf16.f32 {%0,%1,%2,%3}, {%4,%5,%6,%5}, {%4,%6}, {%0,%1,%2,%3};"
        : "+f"(c[0]), "+f"(c[1]), "+f"(c[2]), "+f"(c[3]) : "r"(p), "r"(0x3f803f80u), "r"(q));
}
__device__ __forceinline__ void stat_store(const float (&c)[4], uint32_t dst, int lane) {
    const int g = lane >> 2, t = lane & 3;
    if (t == (g >> 1)) sts32f(dst + g * 4, (g & 1) ? c[1] : c[0]);
    if (g == 7) sts32f(dst + 32 + t * 4, c[2] + c[3]);
}
__device__ __forceinline__ float sum4(float4 v) { return (v.x + v.y) + (v.z + v.w); }
__device__ __forceinline__ void fence_acc(float (&d)[64]) {
#pragma unroll
    for (int i = 0; i < 64; i++) asm volatile("" : "+f"(d[i])::"memory");
}
__device__ __forceinline__ void ld_unit(uint32_t (&u)[4], const uint4* p) {
    asm volatile("ld.relaxed.gpu.global.v4.u32 {%0,%1,%2,%3}, [%4];" : "=r"(u[0]), "=r"(u[1]), "=r"(u[2]), "=r"(u[3]) : "l"(p) : "memory");
}

template <int FIRST, int N>
__device__ __forceinline__ void fetch_units(uint32_t (&u)[12][4], const uint4* p) {
    unsigned it = 0;
    while (true) {
#pragma unroll
        for (int i = 0; i < N; i++) ld_unit(u[FIRST + i], p + i * 128);
        bool ok = true;
#pragma unroll
        for (int i = 0; i < 4 * N; i++) ok = ok && u[FIRST + (i >> 2)][i & 3] != 0;
        if (__all_sync(0xffffffffu, ok) || ++it > SPIN_LIMIT) break;
    }
#pragma unroll
    for (int i = 0; i < 4 * N; i++) u[FIRST + (i >> 2)][i & 3] = ~u[FIRST + (i >> 2)][i & 3];
}

__global__ void __launch_bounds__(NTHREADS, 1)
resblock_kernel(const __nv_bfloat16* __restrict__ x, const __nv_bfloat16* __restrict__ w1,
                const __nv_bfloat16* __restrict__ t_emb, const __nv_bfloat16* __restrict__ g1,
                const __nv_bfloat16* __restrict__ be1, const __nv_bfloat16* __restrict__ w_emb,
                const __nv_bfloat16* __restrict__ g2, const __nv_bfloat16* __restrict__ be2,
                const __nv_bfloat16* __restrict__ w2, __nv_bfloat16* __restrict__ out, Scratch* __restrict__ gs) {
    const unsigned clk0 = clock32();
    const int tid = threadIdx.x, warp = tid >> 5, lane = tid & 31;
    const int cta = blockIdx.x, b = cta >> 6, r = cta & 63;

    const uint32_t woff = ((2 * r + (lane >> 4)) * C + b * 64) * 18 + (lane & 15) * 16;
    const int c0 = (warp - 8) * 16 + (lane >> 3), seg = lane & 7;
    uint4 v[5];
    if (warp == 0) {
        const char* w1s = reinterpret_cast<const char*>(w1) + woff;
#pragma unroll
        for (int k = 0; k < 4; k++) v[k] = __ldg(reinterpret_cast<const uint4*>(w1s + k * 256));
        if ((lane & 15) < 8) v[4] = __ldg(reinterpret_cast<const uint4*>(w1s + 1024));
    }
    if (warp >= 8 || warp == 5) {
        if (warp >= 8) {
            const char* src = reinterpret_cast<const char*>(x) + (uint32_t)(((b * C + c0) * HW + r) * HW * 2 + seg * 16);
            while (clock32() - clk0 < XDELAY) {}
#pragma unroll
            for (int k = 0; k < 4; k++) v[k] = __ldg(reinterpret_cast<const uint4*>(src + k * (4 * HW * HW * 2)));
#pragma unroll
            for (int i = 0; i < 8; i++) {
                if (i < 4 ? (r != 0) : (r != HW - 1))
                    asm volatile("cp.async.cg.shared.global [%0], [%1], 16;"
                                 ::"r"(SM_XH + (i >> 2) * 16384 + c0 * 128 + (i & 3) * 512 + ((seg ^ ((c0 + 4 * i) & 7)) << 4)),
                                   "l"(src + (i < 4 ? -HW * 2 : HW * 2) + (i & 3) * (4 * HW * HW * 2)) : "memory");
            }
        } else {
#pragma unroll
            for (int k = 0; k < 4; k++) v[k] = make_uint4(0, 0, 0, 0);
        }
        float c[4] = {0.f, 0.f, 0.f, 0.f};
#pragma unroll
        for (int k = 0; k < 4; k++) { stat_mma(c, v[k].x, v[k].y); stat_mma(c, v[k].z, v[k].w); }
        stat_store(c, SM_RED + warp * 48, lane);
        if (tid == 256) TL(2);
        if (warp >= 8) bar_sync(3, 256);
        if ((warp & 7) * 32 + lane < 4 || warp == 5) {
            const uint32_t a = SM_RED + 8 * 48 + (lane & 3) * 96;
            const float q = (sum4(lds128f(a)) + sum4(lds128f(a + 16))) + (sum4(lds128f(a + 48)) + sum4(lds128f(a + 64)));
            const float sm = sum4(lds128f(a + 32)) + sum4(lds128f(a + 80));
            if (warp == 8) red_add4(&gs->acc[b * 32 + lane * 4], 1.f, sm, q, 1.f);
        }
        if (tid == 256) TL(3);
    }
    if (warp == 0) {
        weight_block(v, SM_BNC, gs->wt, cta, lane);
        if (r == 0) {
            if (lane < 16) gs->acc[(NB + b) * 32 + lane] = 0.f;
            *reinterpret_cast<float4*>(&gs->emb[b * C + lane * 4]) = make_float4(0.f, 0.f, 0.f, 0.f);
        }
        __syncwarp();
        if (lane == 0) TL(4);
        if (lane < 2) asm volatile("red.release.gpu.global.add.u32 [%0], 1;" ::"l"(&gs->wcnt[lane * 32]) : "memory");
        if (lane == 0) TL(5);
    }

    if (warp >= 8) {
        const int nw = warp - 8;
        {
#pragma unroll
            for (int i = 0; i < 4; i++) sts128(SM_XOWN + c0 * 128 + i * 512 + ((seg ^ ((c0 + 4 * i) & 7)) << 4), v[i]);
            asm volatile("cp.async.wait_all;" ::: "memory");
            bar_sync(4, 256 + 96);
        }
        const int hi = nw >> 2, wq = nw & 3;
        const unsigned epoch = gs->epoch[cta * 32];
        const uint32_t act_off = SM_ACT + (lane >> 4) * CH_PITCH + (2 + wq * 16 + (lane & 15)) * 16;
        const uint32_t act1 = act_off + (hi ? 0 : ROW_BYTES), act2b = act_off + 2 * ROW_BYTES + hi * 8 * CH_PITCH;
        const uint32_t stg_off = ((lane >> 4) * 8 + (lane & 7)) * 128 + (((2 * wq + ((lane >> 3) & 1)) ^ (lane & 7)) << 4);
        const uint32_t bar1 = BAR(BAR_FULL) + hi * 64, bar2 = BAR(BAR_FULL + 16) + hi * 32;
        const uint32_t cfa = SM_COEF + (lane & 3) * 16;
        const bool v1 = !hi || r != 0, v2 = r != HW - 1;
        const uint4* hrow = gs->h + ((epoch & 1) * NCTA + cta) * 1024 + wq * 32 + lane;
#pragma unroll 1
        for (int conv = 0; conv < 2; conv++) {
            uint32_t u[12][4];
            if (conv == 0) {
#pragma unroll
                for (int i = 0; i < 8; i++) ldsm4t(u[i], (hi ? SM_XH : SM_XOWN) + stg_off + i * 2048);
#pragma unroll
                for (int i = 0; i < 4; i++) ldsm4t(u[8 + i], SM_XH + 16384 + hi * 8192 + stg_off + i * 2048);
                publish(BAR(BAR_XFREE), lane);
            } else if (!hi) {
                mbar_wait(BAR(BAR_HW), 0);
#pragma unroll
                for (int i = 0; i < 8; i++) ldsm4(u[i], act1 + i * 2 * CH_PITCH);
            }
            mbar_wait(BAR(BAR_STATS), conv);
            if (tid == 256) TL(22 + conv * 4);
            float4 ca = lds128f(cfa), cb = lds128f(cfa + 64);
            if (hi) {
                if (conv == 0) mbar_wait(BAR(BAR_FULL + HOLD), 0);
                else if (v1) fetch_units<0, 8>(u, hrow - 1024);
                if (tid == 384) TL(24 + conv * 4);
            }
#pragma unroll
            for (int t = 0; t < 12; t++) {
                if (t == 8 && conv == 1 && v2) fetch_units<8, 4>(u, hrow + 1024 + hi * 512);
                const float4 c0 = ca, c1 = cb;
                if (t < 11) {
                    const uint32_t nc = cfa + (t < 7 ? (t + 1) * 128 : (t - 7) * 128 + hi * 512);
                    ca = lds128f(nc); cb = lds128f(nc + 64);
                }
                norm_unit(u[t], c0, c1);
                if (t < 8 ? v1 : v2) stsm4(t < 8 ? act1 + t * 2 * CH_PITCH : act2b + (t - 8) * 2 * CH_PITCH, u[t][0], u[t][1], u[t][2], u[t][3]);
                if (t < PUB1) publish(bar1 + 8 * t, lane);
                else if (t & 1) publish2(t < 8 ? bar1 + 8 * (t - 1) : bar2 + 8 * (t - 9), lane);
                if (t == 0 && tid == 256) TL(8 + conv * 8);
                if (t == 7 && tid == 256) TL(84 + conv);
            }
            if (tid == 256) TL(23 + conv * 4);
        }
        uint4* hz = gs->h + (((epoch + 1) & 1) * NCTA + cta) * 1024 + (tid - 256);
#pragma unroll
        for (int i = 0; i < 4; i++) hz[i * 256] = make_uint4(0, 0, 0, 0);
    } else if (warp < 4) {
        const int wq = warp;
        if (wq != 0) {
            const int t = tid - 32;
            if (lane == 0) {
                if (wq < 3) {
#pragma unroll
                    for (int i = 0; i < 12; i++) mbar_init(BAR(BAR_FULL + i) + (wq - 1) * 96, 5);
                    mbar_init(BAR(BAR_STATS) + (wq - 1) * 16, 1);
                    mbar_init(BAR(BAR_EMB) + (wq - 1) * 16, 1);
                } else {
#pragma unroll
                    for (int i = 0; i <= NS; i++) mbar_init(BAR(BAR_WEMPTY + i), 4);
                    mbar_init(BAR(BAR_XFREE), 8);
                }
            }
            fence_async_smem();
            bar_arrive(0, 96 + 128);
            bar_arrive(4, 256 + 96);
            if (t == 95) TLG(1);
            const uint4 z = make_uint4(0, 0, 0, 0);
            sts128(SM_ACT + (t >> 1) * CH_PITCH + (t & 1) * 16, z);
            if (t < 2) sts128(SM_ACT + 3 * ROW_BYTES + t * 16, z);
            if (t < 16) sts128(SM_ONES + t * 16, make_uint4(t < 8 ? 0x3f803f80u : 0u, 0, 0, 0));
            if (r == 0 || r == HW - 1) {
#pragma unroll 1
                for (int i = t; i < ROW_BYTES / 16; i += 96) sts128(SM_ACT + (r == 0 ? 0 : 2 * ROW_BYTES) + i * 16, z);
            }
            fence_async_smem();
        }
        bar_sync(2, 128);
        const unsigned epoch = gs->epoch[cta * 32];

        float d[64];
#pragma unroll
        for (int i = 0; i < 64; i++) d[i] = 0.f;
#pragma unroll 1
        for (int conv = 0; conv < 2; conv++) {
            fence_acc(d);
            mma_stages<0>(d, conv, tid, gs);
            if (conv == 0) {
                asm volatile("wgmma.fence.sync.aligned;" ::: "memory");
                wgmma128<(SM_ONES >> 4) | (8u << 16), (SM_EMB >> 4), 0>(d);
                asm volatile("wgmma.commit_group.sync.aligned;" ::: "memory");
            }
            asm volatile("wgmma.wait_group.sync.aligned 0;" ::: "memory");
            fence_acc(d);
            if (tid == 0) TL(10 + conv * 8);
            if (conv == 1) break;

            uint32_t hp[32];
#pragma unroll
            for (int g = 0; g < 4; g++) {
                float c[4] = {0.f, 0.f, 0.f, 0.f};
#pragma unroll
                for (int i = 0; i < 8; i++) hp[8 * g + i] = pack_bf(d[16 * g + 2 * i], d[16 * g + 2 * i + 1]);
#pragma unroll
                for (int i = 0; i < 4; i++) stat_mma(c, hp[8 * g + 2 * i], hp[8 * g + 2 * i + 1]);
                stat_store(c, SM_RED + (g * 4 + wq) * 48, lane);
            }
            bar_sync(2, 128);
            if (tid < 16) {
                const uint32_t a = SM_RED + tid * 48;
                float q = sum4(lds128f(a)) + sum4(lds128f(a + 16)), sm = sum4(lds128f(a + 32));
                q += __shfl_xor_sync(0xffffu, q, 1); sm += __shfl_xor_sync(0xffffu, sm, 1);
                q += __shfl_xor_sync(0xffffu, q, 2); sm += __shfl_xor_sync(0xffffu, sm, 2);
                if ((tid & 3) == 0) red_add4(&gs->acc[(NB + b) * 32 + tid], 1.f, sm, q, 1.f);
            }
            if (tid == 0) TL(11);
            const uint32_t hbase = SM_ACT + ROW_BYTES + (lane >> 4) * CH_PITCH + (2 + wq * 16 + (lane & 15)) * 16;
#pragma unroll
            for (int kc = 0; kc < 8; kc++) stsm4(hbase + kc * 2 * CH_PITCH, hp[4 * kc], hp[4 * kc + 1], hp[4 * kc + 2], hp[4 * kc + 3]);
            __syncwarp();
            if (lane == 0) mbar_arrive(BAR(BAR_HW));
            if (lane < LAG) mbar_arrive(BAR(BAR_WEMPTY + (NSTAGE - LAG) % NS) + 8 * lane);
            uint4* hg = gs->h + ((epoch & 1) * NCTA + cta) * 1024 + tid;
#pragma unroll
            for (int kc = 0; kc < 8; kc++) hg[kc * 128] = make_uint4(~hp[4 * kc], ~hp[4 * kc + 1], ~hp[4 * kc + 2], ~hp[4 * kc + 3]);
            if (tid == 0) TL(12);
            const uint32_t xbase = SM_XOWN + ((lane >> 4) * 8 + (lane & 7)) * 128 + (((2 * wq + ((lane >> 3) & 1)) ^ (lane & 7)) << 4);
#pragma unroll
            for (int kc = 0; kc < 8; kc++) {
                uint32_t p[4];
                ldsm4t(p, xbase + kc * 2048);
#pragma unroll
                for (int i = 0; i < 4; i++) { d[8 * kc + 2 * i] = bf_lo(p[i]); d[8 * kc + 2 * i + 1] = bf_hi(p[i]); }
            }
        }
        {
            const uint32_t obase = SM_W + ((lane >> 4) * 8 + (lane & 7)) * OUT_PITCH + (wq * 16 + ((lane >> 3) & 1) * 8) * 2;
#pragma unroll
            for (int kc = 0; kc < 8; kc++) {
                stsm4t(obase + kc * 16 * OUT_PITCH, pack_bf(d[8 * kc + 0], d[8 * kc + 1]), pack_bf(d[8 * kc + 2], d[8 * kc + 3]),
                       pack_bf(d[8 * kc + 4], d[8 * kc + 5]), pack_bf(d[8 * kc + 6], d[8 * kc + 7]));
            }
            bar_sync(2, 128);
            const int oc0 = tid >> 3;
            __nv_bfloat16* dst = out + ((size_t)(b * C + oc0) * HW + r) * HW + seg * 8;
#pragma unroll
            for (int i = 0; i < 8; i++)
                *reinterpret_cast<uint4*>(dst + (size_t)i * 16 * HW * HW) = lds128(SM_W + (oc0 + 16 * i) * OUT_PITCH + seg * 16);
            if (tid == 0) gs->epoch[cta * 32] = epoch + 1;
            if (tid == 0) { TL(20); TLG(21); }
        }
    } else if (warp < 6) {
        bar_sync(0, 96 + 128);
        if (warp == 4) {
            while (clock32() - clk0 < W2DELAY) {}
            const char* w2s = reinterpret_cast<const char*>(w2) + woff;
#pragma unroll
            for (int k = 0; k < 4; k++) v[k] = __ldg(reinterpret_cast<const uint4*>(w2s + k * 256));
            if ((lane & 15) < 8) v[4] = __ldg(reinterpret_cast<const uint4*>(w2s + 1024));
            const uint2* wsrc = reinterpret_cast<const uint2*>(w_emb + (size_t)r * 12 * C) + lane;
            uint2 wv[12];
#pragma unroll
            for (int i = 0; i < 12; i++) wv[i] = __ldg(wsrc + i * (C / 4));
            float tv = 0.f;
            if (lane < 12) tv = __bfloat162float(t_emb[b * E + r * 12 + lane]);
            weight_block(v, SM_BNC + 2304, gs->wt + NSTAGE * STAGE_BYTES, cta, lane);
            const float sv = silu_half(0.5f * tv);
            float e0 = 0.f, e1 = 0.f, e2 = 0.f, e3 = 0.f;
#pragma unroll
            for (int i = 0; i < 12; i++) {
                const float sx = __shfl_sync(0xffffffffu, sv, i);
                e0 = fmaf(sx, bf_lo(wv[i].x), e0); e1 = fmaf(sx, bf_hi(wv[i].x), e1);
                e2 = fmaf(sx, bf_lo(wv[i].y), e2); e3 = fmaf(sx, bf_hi(wv[i].y), e3);
            }
            mbar_wait(BAR(BAR_WACQ), 0);
            red_add4(&gs->emb[b * C + lane * 4], e0, e1, e2, e3);
            __syncwarp();
            if (lane == 0) TL(13);
            if (lane < 2) asm volatile("red.release.gpu.global.add.u32 [%0], 1;" ::"l"(&gs->wcnt[(NB + lane) * 32]) : "memory");
            if (lane == 0) TL(14);
            unsigned it = 0;
            while (ld_relaxed(&gs->wcnt[(NB + b) * 32]) < (unsigned)NCTA && ++it < SPIN_LIMIT) {}
            fence_acquire();
            const uint4 ef = ld_relaxed_v4(&gs->emb[b * C + lane * 4]);
            const uint32_t eu[4] = {ef.x, ef.y, ef.z, ef.w};
#pragma unroll
            for (int i = 0; i < 4; i++) {
                const float e = __uint_as_float(eu[i]);
                const float hi = bf_lo(pack_bf(e, 0.f));
                sts128(SM_EMB + (lane * 4 + i) * 16, make_uint4(pack_bf(hi, e - hi), 0, 0, 0));
            }
            fence_async_smem();
            __syncwarp();
            if (lane == 0) { mbar_arrive(BAR(BAR_EMB)); TL(19); }
        }
    } else if (warp == 6) {
        bar_sync(0, 96 + 128);
        unsigned it = 0;
        while (ld_relaxed(&gs->wcnt[b * 32]) < (unsigned)NCTA && ++it < SPIN_LIMIT) {}
        fence_acquire();
        fence_async_global();
        if (lane == 0) { mbar_arrive(BAR(BAR_WACQ)); TL(6); }
        const unsigned char* wsrc = gs->wt;
#pragma unroll 1
        for (int round = 0; round < 2 * NSTAGE / NS; round++) {
            if (round == NSTAGE / NS) { mbar_wait(BAR(BAR_EMB), 0); fence_async_global(); }
            const uint32_t full = BAR(BAR_FULL) + 8 * NS * (round >= NSTAGE / NS ? round - NSTAGE / NS : round);
#pragma unroll
            for (int slot = 0; slot < NS; slot++) {
                if (slot == 9 && round == 0) mbar_wait(BAR(BAR_XFREE), 0);
                mbar_wait(BAR(BAR_WEMPTY + slot), (round & 1) ^ 1);
                if (elect_one()) {
                    mbar_expect(full + 8 * slot, STAGE_BYTES);
                    bulk_g2s(SM_W + slot * STAGE_BYTES, wsrc + slot * STAGE_BYTES, STAGE_BYTES, full + 8 * slot);
                }
            }
            wsrc += NS * STAGE_BYTES;
        }
    } else {
        const uint2 ga1 = __ldg(reinterpret_cast<const uint2*>(g1) + lane), bt1 = __ldg(reinterpret_cast<const uint2*>(be1) + lane);
        const uint2 ga2 = __ldg(reinterpret_cast<const uint2*>(g2) + lane), bt2 = __ldg(reinterpret_cast<const uint2*>(be2) + lane);
        bar_sync(0, 96 + 128);
#pragma unroll 1
        for (int conv = 0; conv < 2; conv++) {
            if (conv == 1) mbar_wait(BAR(BAR_EMB), 0);
            const float* asrc = &gs->acc[(conv * NB + b) * 32 + (lane >> 3) * 4];
            uint4 f;
            unsigned it = 0;
            while (true) {
                f = ld_relaxed_v4(asrc);
                const bool ok = (f.x == 0x42800000u) & (f.w == 0x42800000u);
                if (__all_sync(0xffffffffu, ok) || ++it > SPIN_LIMIT) break;
            }
            if (lane == 0) TL(7 + conv * 8);
            const float inv_n = 1.0f / (32.0f * HW * HW);
            const float mean = __uint_as_float(f.y) * inv_n;
            const float var = fmaxf(fmaf(-mean, mean, __uint_as_float(f.z) * inv_n), 0.f);
            const float rs = 0.5f * rsqrtf(var + 1e-5f);
            const uint2 ga = conv ? ga2 : ga1, bt = conv ? bt2 : bt1;
            float4 k0, k1;
            k0.x = rs * bf_lo(ga.x); k0.y = rs * bf_hi(ga.x); k1.x = rs * bf_lo(ga.y); k1.y = rs * bf_hi(ga.y);
            k0.z = fmaf(-mean, k0.x, 0.5f * bf_lo(bt.x)); k0.w = fmaf(-mean, k0.y, 0.5f * bf_hi(bt.x));
            k1.z = fmaf(-mean, k1.x, 0.5f * bf_lo(bt.y)); k1.w = fmaf(-mean, k1.y, 0.5f * bf_hi(bt.y));
            sts128f(SM_COEF + lane * 32, k0);
            sts128f(SM_COEF + lane * 32 + 16, k1);
            __syncwarp();
            if (lane == 0) mbar_arrive(BAR(BAR_STATS));
        }
        if (r == 0) {
            if (lane < 16) gs->acc[b * 32 + lane] = 0.f;
            if (lane < 2) gs->wcnt[(lane * NB + b) * 32] = 0;
        }
    }
}

}

extern "C" void kernel_launch(void* const* d_in, const int* in_sizes, int n_in, void* d_out, int out_size) {
    (void)in_sizes; (void)n_in; (void)out_size;
    static Scratch* gs = nullptr;
    if (!gs) {
        cudaFuncSetAttribute(resblock_kernel, cudaFuncAttributeMaxDynamicSharedMemorySize, SM_TOTAL);
        cudaGetSymbolAddress((void**)&gs, g_scratch);
    }
    resblock_kernel<<<NCTA, NTHREADS, SM_TOTAL>>>(
        (const __nv_bfloat16*)d_in[0], (const __nv_bfloat16*)d_in[4], (const __nv_bfloat16*)d_in[1],
        (const __nv_bfloat16*)d_in[2], (const __nv_bfloat16*)d_in[3], (const __nv_bfloat16*)d_in[5],
        (const __nv_bfloat16*)d_in[6], (const __nv_bfloat16*)d_in[7], (const __nv_bfloat16*)d_in[8],
        (__nv_bfloat16*)d_out, gs);
}
```

```cpp
#include <cuda_runtime.h>
#include <cuda_bf16.h>
#include <stdint.h>

namespace {

constexpr int C = 128, HW = 64, NB = 2, E = 768;
constexpr int NCTA = NB * HW;
constexpr int NTHREADS = 20 * 32;
constexpr int CH_PITCH = 66 * 16;
constexpr int ROW_BYTES = 16 * CH_PITCH;
constexpr int STEP_BYTES = 4096;
constexpr int STAGE_BYTES = 3 * STEP_BYTES;
constexpr int NSTAGE = 24;
constexpr int NS = 12;
constexpr int LAG = 1;
#define XDELAY 600
#define HDELAY 500
#define PUB1 2
#define FETCH_AT 2
#define W2DELAY 2800

constexpr uint32_t SMEM_BASE = 0x400;
constexpr uint32_t SM_ACT = SMEM_BASE;
constexpr uint32_t SM_XOWN = SM_ACT + 3 * ROW_BYTES + 128;
constexpr uint32_t SM_W = SM_XOWN + 16384;
constexpr uint32_t SM_XH = SM_W;
__host__ __device__ constexpr uint32_t slot_addr(int slot) { return SM_W + ((slot + 3) % NS) * STAGE_BYTES; }
constexpr uint32_t SM_COEF = SM_W + NS * STAGE_BYTES;
constexpr uint32_t SM_EMB = SM_COEF + 1024;
constexpr uint32_t SM_ONES = SM_EMB + 2048;
constexpr uint32_t SM_RED = SM_ONES + 256;
constexpr uint32_t SM_BNC = SM_RED + 1280;
constexpr uint32_t SM_BAR = SM_BNC + 2 * 2304;
constexpr int BAR_FULL = 0, BAR_WEMPTY = NSTAGE, BAR_HW = BAR_WEMPTY + NS, BAR_STATS = BAR_HW + 1,
              BAR_EMB = BAR_STATS + 1, BAR_WACQ = BAR_EMB + 1, BAR_XH = BAR_WACQ + 1, BAR_XFREE = BAR_XH + 1, NBAR = BAR_XFREE + 1;
constexpr int SM_TOTAL = SM_BAR + NBAR * 8 - SMEM_BASE;
static_assert(SM_TOTAL <= 232448, "smem");
static_assert(NBAR <= 96, "barrier init");
constexpr int OUT_PITCH = 144;
__host__ __device__ constexpr uint32_t BAR(int i) { return SM_BAR + 8 * i; }
__host__ __device__ constexpr int ky_of(int kyo) { return kyo == 0 ? 1 : (kyo == 1 ? 0 : 2); }

constexpr unsigned SPIN_LIMIT = 1u << 16;

struct Scratch {
    float acc[2 * NB * 32];
    unsigned wcnt[2 * NB * 32];
    float emb[NB * C];
    unsigned char wt[2 * NSTAGE * STAGE_BYTES];
    unsigned epoch[NCTA * 32];
    uint4 h[2 * NCTA * 1024];
};
__device__ __align__(1024) Scratch g_scratch;
#define TL(i) do {} while (0)
#define TLG(i) do {} while (0)

__device__ __forceinline__ unsigned clock32() { unsigned c; asm volatile("mov.u32 %0, %%clock;" : "=r"(c)); return c; }
__device__ __forceinline__ void mbar_init(uint32_t bar, int cnt) {
    asm volatile("mbarrier.init.shared::cta.b64 [%0], %1;" ::"r"(bar), "r"(cnt) : "memory");
}
__device__ __forceinline__ void mbar_arrive(uint32_t bar) {
    asm volatile("mbarrier.arrive.shared::cta.b64 _, [%0];" ::"r"(bar) : "memory");
}
__device__ __forceinline__ void mbar_expect(uint32_t bar, uint32_t bytes) {
    asm volatile("mbarrier.arrive.expect_tx.shared::cta.b64 _, [%0], %1;" ::"r"(bar), "r"(bytes) : "memory");
}
__device__ __forceinline__ bool mbar_try(uint32_t bar, uint32_t par) {
    uint32_t ok;
    asm volatile("{\n.reg .pred p;\nmbarrier.try_wait.parity.shared::cta.b64 p, [%1], %2;\nselp.u32 %0, 1, 0, p;\n}"
                 : "=r"(ok) : "r"(bar), "r"(par) : "memory");
    return ok;
}
__device__ __forceinline__ bool mbar_test(uint32_t bar, uint32_t par) {
    uint32_t ok;
    asm volatile("{\n.reg .pred p;\nmbarrier.test_wait.parity.shared::cta.b64 p, [%1], %2;\nselp.u32 %0, 1, 0, p;\n}"
                 : "=r"(ok) : "r"(bar), "r"(par) : "memory");
    return ok;
}
__device__ __forceinline__ void mbar_wait(uint32_t bar, uint32_t par) {
    unsigned it = 0;
#pragma unroll 1
    while (!mbar_try(bar, par) && ++it < SPIN_LIMIT) {}
}
__device__ __forceinline__ bool elect_one() {
    uint32_t p;
    asm volatile("{\n.reg .pred p;\nelect.sync _|p, 0xffffffff;\nselp.u32 %0, 1, 0, p;\n}" : "=r"(p));
    return p;
}
__device__ __forceinline__ void fence_async_smem() { asm volatile("fence.proxy.async.shared::cta;" ::: "memory"); }
__device__ __forceinline__ void fence_async_global() { asm volatile("fence.proxy.async.global;" ::: "memory"); }
__device__ __forceinline__ void fence_acquire() { asm volatile("fence.acquire.gpu;" ::: "memory"); }
__device__ __forceinline__ void bar_sync(int id, int n) { asm volatile("bar.sync %0, %1;" ::"r"(id), "r"(n) : "memory"); }
__device__ __forceinline__ void bar_arrive(int id, int n) { asm volatile("bar.arrive %0, %1;" ::"r"(id), "r"(n) : "memory"); }
__device__ __forceinline__ void bulk_g2s(uint32_t dst, const void* src, uint32_t bytes, uint32_t bar) {
    asm volatile("cp.async.bulk.shared::cluster.global.mbarrier::complete_tx::bytes [%0], [%1], %2, [%3];"
                 ::"r"(dst), "l"(src), "r"(bytes), "r"(bar) : "memory");
}
__device__ __forceinline__ uint4 ld_relaxed_v4(const void* p) {
    uint4 v;
    asm volatile("ld.relaxed.gpu.global.v4.u32 {%0,%1,%2,%3}, [%4];" : "=r"(v.x), "=r"(v.y), "=r"(v.z), "=r"(v.w) : "l"(p) : "memory");
    return v;
}
__device__ __forceinline__ unsigned ld_relaxed(const void* p) {
    unsigned v;
    asm volatile("ld.relaxed.gpu.global.u32 %0, [%1];" : "=r"(v) : "l"(p) : "memory");
    return v;
}
__device__ __forceinline__ void red_add4(float* p, float a, float b, float c, float d) {
    asm volatile("red.relaxed.gpu.global.add.v4.f32 [%0], {%1,%2,%3,%4};" ::"l"(p), "f"(a), "f"(b), "f"(c), "f"(d) : "memory");
}
__device__ __forceinline__ void sts128(uint32_t a, uint4 v) {
    asm volatile("st.shared.v4.u32 [%0], {%1,%2,%3,%4};" ::"r"(a), "r"(v.x), "r"(v.y), "r"(v.z), "r"(v.w) : "memory");
}
__device__ __forceinline__ void sts128f(uint32_t a, float4 v) {
    asm volatile("st.shared.v4.f32 [%0], {%1,%2,%3,%4};" ::"r"(a), "f"(v.x), "f"(v.y), "f"(v.z), "f"(v.w) : "memory");
}
__device__ __forceinline__ void sts32f(uint32_t a, float v) { asm volatile("st.shared.f32 [%0], %1;" ::"r"(a), "f"(v) : "memory"); }
__device__ __forceinline__ uint4 lds128(uint32_t a) {
    uint4 v;
    asm volatile("ld.shared.v4.u32 {%0,%1,%2,%3}, [%4];" : "=r"(v.x), "=r"(v.y), "=r"(v.z), "=r"(v.w) : "r"(a) : "memory");
    return v;
}
__device__ __forceinline__ float4 lds128f(uint32_t a) {
    float4 v;
    asm volatile("ld.shared.v4.f32 {%0,%1,%2,%3}, [%4];" : "=f"(v.x), "=f"(v.y), "=f"(v.z), "=f"(v.w) : "r"(a) : "memory");
    return v;
}
__device__ __forceinline__ float2 lds64f(uint32_t a) {
    float2 v;
    asm volatile("ld.shared.v2.f32 {%0,%1}, [%2];" : "=f"(v.x), "=f"(v.y) : "r"(a) : "memory");
    return v;
}
__device__ __forceinline__ float bf_lo(uint32_t u) { return __uint_as_float(u << 16); }
__device__ __forceinline__ float bf_hi(uint32_t u) { return __uint_as_float(u & 0xffff0000u); }
__device__ __forceinline__ uint32_t pack_bf(float lo, float hi) {
    uint32_t r;
    asm("cvt.rn.bf16x2.f32 %0, %1, %2;" : "=r"(r) : "f"(hi), "f"(lo));
    return r;
}
__device__ __forceinline__ float tanh_fast(float x) {
    float r;
    asm volatile("tanh.approx.f32 %0, %1;" : "=f"(r) : "f"(x));
    return r;
}
__device__ __forceinline__ float silu_half(float h) { return fmaf(h, tanh_fast(h), h); }
__device__ __forceinline__ void ldsm4(uint32_t (&u)[4], uint32_t a) {
    asm volatile("ldmatrix.sync.aligned.m8n8.x4.shared.b16 {%0,%1,%2,%3}, [%4];"
                 : "=r"(u[0]), "=r"(u[1]), "=r"(u[2]), "=r"(u[3]) : "r"(a) : "memory");
}
__device__ __forceinline__ void ldsm4t(uint32_t (&u)[4], uint32_t a) {
    asm volatile("ldmatrix.sync.aligned.m8n8.x4.trans.shared.b16 {%0,%1,%2,%3}, [%4];"
                 : "=r"(u[0]), "=r"(u[1]), "=r"(u[2]), "=r"(u[3]) : "r"(a) : "memory");
}
__device__ __forceinline__ void stsm4(uint32_t a, uint32_t p0, uint32_t p1, uint32_t p2, uint32_t p3) {
    asm volatile("stmatrix.sync.aligned.m8n8.x4.shared.b16 [%0], {%1,%2,%3,%4};" ::"r"(a), "r"(p0), "r"(p1), "r"(p2), "r"(p3) : "memory");
}
__device__ __forceinline__ void stsm4t(uint32_t a, uint32_t p0, uint32_t p1, uint32_t p2, uint32_t p3) {
    asm volatile("stmatrix.sync.aligned.m8n8.x4.trans.shared.b16 [%0], {%1,%2,%3,%4};" ::"r"(a), "r"(p0), "r"(p1), "r"(p2), "r"(p3) : "memory");
}

#define R8(o) "+f"(d[o]), "+f"(d[o + 1]), "+f"(d[o + 2]), "+f"(d[o + 3]), "+f"(d[o + 4]), "+f"(d[o + 5]), "+f"(d[o + 6]), "+f"(d[o + 7])
template <uint32_t ALO, uint32_t BLO, uint64_t AHI = 8>
__device__ __forceinline__ void wgmma128(float (&d)[64]) {
    asm volatile(
        "wgmma.mma_async.sync.aligned.m64n128k16.f32.bf16.bf16 "
        "{%0,%1,%2,%3,%4,%5,%6,%7,%8,%9,%10,%11,%12,%13,%14,%15,%16,%17,%18,%19,%20,%21,%22,%23,%24,%25,%26,%27,%28,%29,%30,%31,"
        "%32,%33,%34,%35,%36,%37,%38,%39,%40,%41,%42,%43,%44,%45,%46,%47,%48,%49,%50,%51,%52,%53,%54,%55,%56,%57,%58,%59,%60,%61,%62,%63},"
        " %64, %65, 1, 1, 1, 0, 0;"
        : R8(0), R8(8), R8(16), R8(24), R8(32), R8(40), R8(48), R8(56)
        : "l"((AHI << 32) | ALO), "l"((8ull << 32) | BLO));
}
template <int S>
__device__ __forceinline__ void mma_stages(float (&d)[64], int conv, int tid, Scratch* gs) {
    constexpr uint32_t A = ((SM_ACT + S * 2 * CH_PITCH + 16) >> 4) | ((CH_PITCH >> 4) << 16);
    constexpr uint32_t B = (slot_addr(S % NS) >> 4) | ((2048 >> 4) << 16);
    if (S == 0) mbar_wait(BAR(BAR_FULL), conv);
    bool next_ok = true;
    constexpr uint32_t NEXT = S + 1 < NSTAGE ? BAR(BAR_FULL + S + 1) : BAR(BAR_EMB);
    const int npar = S + 1 < NSTAGE ? conv : 0;
    next_ok = mbar_test(NEXT, npar);
    if (S == 0 && tid == 0) TL(32 + conv * 24);
    asm volatile("wgmma.fence.sync.aligned;" ::: "memory");
    wgmma128<A, B>(d);
    wgmma128<A + 1, B + (STEP_BYTES >> 4)>(d);
    wgmma128<A + 2, B + 2 * (STEP_BYTES >> 4)>(d);
    asm volatile("wgmma.commit_group.sync.aligned;" ::: "memory");
    if (S >= LAG) {
        asm volatile("wgmma.wait_group.sync.aligned %0;" ::"n"(LAG) : "memory");
        if ((tid & 31) == 0) mbar_arrive(BAR(BAR_WEMPTY + (S + NS - LAG) % NS));
    }
    if (!next_ok) mbar_wait(NEXT, npar);
    if constexpr (S + 1 < NSTAGE) mma_stages<S + 1>(d, conv, tid, gs);
}

__device__ __forceinline__ void weight_block(const uint4 (&t)[5], uint32_t bounce, unsigned char* wt, int cta, int lane) {
    const uint32_t bw = bounce + (lane >> 4) * 1152 + (lane & 15) * 16;
#pragma unroll
    for (int k = 0; k < 4; k++) sts128(bw + k * 256, t[k]);
    if ((lane & 15) < 8) sts128(bw + 1024, t[4]);
    __syncwarp();
    if (lane < 16) {
        uint32_t v[36];
#pragma unroll
        for (int i = 0; i < 9; i++) {
            const uint4 q = lds128(bounce + (lane & 1) * 1152 + (lane >> 1) * 144 + i * 16);
            v[4 * i] = q.x; v[4 * i + 1] = q.y; v[4 * i + 2] = q.z; v[4 * i + 3] = q.w;
        }
        const int cc = (cta >> 6) * 8 + (lane >> 1);
        unsigned char* dst = wt + (cc >> 1) * STAGE_BYTES + (cc & 1) * 2048 + ((cta & 63) * 2 + (lane & 1)) * 16;
#pragma unroll
        for (int kyo = 0; kyo < 3; kyo++) {
#pragma unroll
            for (int kx = 0; kx < 3; kx++) {
                const int tap = ky_of(kyo) * 3 + kx;
                uint32_t o[4];
#pragma unroll
                for (int m = 0; m < 4; m++) {
                    const int i0 = 18 * m + tap, i1 = i0 + 9;
                    const uint32_t sel = ((i0 & 1) ? 0x32u : 0x10u) | ((i1 & 1) ? 0x7600u : 0x5400u);
                    o[m] = __byte_perm(v[i0 >> 1], v[i1 >> 1], sel);
                }
                *reinterpret_cast<uint4*>(dst + (kyo * 24 + kx) * STEP_BYTES) = make_uint4(o[0], o[1], o[2], o[3]);
            }
        }
    }
}
__device__ __forceinline__ uint32_t act2(uint32_t u, const float4& cf) {
    return pack_bf(silu_half(fmaf(bf_lo(u), cf.x, cf.z)), silu_half(fmaf(bf_hi(u), cf.y, cf.w)));
}
__device__ __forceinline__ void norm_unit(uint32_t (&u)[4], const float4& ca, const float4& cb) {
    u[0] = act2(u[0], ca); u[1] = act2(u[1], ca); u[2] = act2(u[2], cb); u[3] = act2(u[3], cb);
}
__device__ __forceinline__ void publish(uint32_t bar, int lane) {
    fence_async_smem();
    __syncwarp();
    if (lane == 0) mbar_arrive(bar);
}
__device__ __forceinline__ void publish2(uint32_t bar, int lane) {
    fence_async_smem();
    __syncwarp();
    if (lane < 2) mbar_arrive(bar + 8 * lane);
}
__device__ __forceinline__ void stat_mma(float (&c)[4], uint32_t p, uint32_t q) {
    asm("mma.sync.aligned.m16n8k16.row.col.f32.bf16.bf16.f32 {%0,%1,%2,%3}, {%4,%5,%6,%5}, {%4,%6}, {%0,%1,%2,%3};"
        : "+f"(c[0]), "+f"(c[1]), "+f"(c[2]), "+f"(c[3]) : "r"(p), "r"(0x3f803f80u), "r"(q));
}
__device__ __forceinline__ void stat_store(const float (&c)[4], uint32_t dst, int lane) {
    const int g = lane >> 2, t = lane & 3;
    if (t == (g >> 1)) sts32f(dst + g * 4, (g & 1) ? c[1] : c[0]);
    if (g == 7) sts32f(dst + 32 + t * 4, c[2] + c[3]);
}
__device__ __forceinline__ float sum4(float4 v) { return (v.x + v.y) + (v.z + v.w); }
__device__ __forceinline__ void stat_publish(uint32_t src, float* acc, int lane, bool real) {
    const uint32_t a = src + (lane & 15) * 48;
    float q = sum4(lds128f(a)) + sum4(lds128f(a + 16)), sm = sum4(lds128f(a + 32));
    q += __shfl_xor_sync(0xffffffffu, q, 1); sm += __shfl_xor_sync(0xffffffffu, sm, 1);
    q += __shfl_xor_sync(0xffffffffu, q, 2); sm += __shfl_xor_sync(0xffffffffu, sm, 2);
    if (real && (lane & 19) == 0) red_add4(acc + lane, 1.f, sm, q, 1.f);
}
__device__ __forceinline__ void fence_acc(float (&d)[64]) {
#pragma unroll
    for (int i = 0; i < 64; i++) asm volatile("" : "+f"(d[i])::"memory");
}
__device__ __forceinline__ void ld_unit(uint32_t (&u)[4], const uint4* p) {
    asm volatile("ld.relaxed.gpu.global.v4.u32 {%0,%1,%2,%3}, [%4];" : "=r"(u[0]), "=r"(u[1]), "=r"(u[2]), "=r"(u[3]) : "l"(p) : "memory");
}

__global__ void __launch_bounds__(NTHREADS, 1)
resblock_kernel(const __nv_bfloat16* __restrict__ x, const __nv_bfloat16* __restrict__ w1,
                const __nv_bfloat16* __restrict__ t_emb, const __nv_bfloat16* __restrict__ g1,
                const __nv_bfloat16* __restrict__ be1, const __nv_bfloat16* __restrict__ w_emb,
                const __nv_bfloat16* __restrict__ g2, const __nv_bfloat16* __restrict__ be2,
                const __nv_bfloat16* __restrict__ w2, __nv_bfloat16* __restrict__ out, Scratch* __restrict__ gs) {
    const unsigned clk0 = clock32();
    const int tid = threadIdx.x, warp = tid >> 5, lane = tid & 31;
    const int cta = blockIdx.x, b = cta >> 6, r = cta & 63;

    const uint32_t woff = ((2 * r + (lane >> 4)) * C + b * 64) * 18 + (lane & 15) * 16;
    const int c0 = (warp - 8) * 16 + (lane >> 3), seg = lane & 7;
    uint4 v[5];
    if (warp == 0) {
        const char* w1s = reinterpret_cast<const char*>(w1) + woff;
#pragma unroll
        for (int k = 0; k < 4; k++) v[k] = __ldg(reinterpret_cast<const uint4*>(w1s + k * 256));
        if ((lane & 15) < 8) v[4] = __ldg(reinterpret_cast<const uint4*>(w1s + 1024));
    }
    const bool loader = (warp >= 8 && warp < 16);
    if (loader || warp == 5) {
        if (loader) {
            const char* src = reinterpret_cast<const char*>(x) + (uint32_t)(((b * C + c0) * HW + r) * HW * 2 + seg * 16);
            while (clock32() - clk0 < XDELAY) {}
#pragma unroll
            for (int k = 0; k < 4; k++) v[k] = __ldg(reinterpret_cast<const uint4*>(src + k * (4 * HW * HW * 2)));
#pragma unroll
            for (int i = 0; i < 8; i++) {
                if (i < 4 ? (r != 0) : (r != HW - 1))
                    asm volatile("cp.async.cg.shared.global [%0], [%1], 16;"
                                 ::"r"(SM_XH + (i >> 2) * 16384 + c0 * 128 + (i & 3) * 512 + ((seg ^ ((c0 + 4 * i) & 7)) << 4)),
                                   "l"(src + (i < 4 ? -HW * 2 : HW * 2) + (i & 3) * (4 * HW * HW * 2)) : "memory");
            }
        } else {
#pragma unroll
            for (int k = 0; k < 4; k++) v[k] = make_uint4(0, 0, 0, 0);
        }
        float c[2][4] = {{0.f, 0.f, 0.f, 0.f}, {0.f, 0.f, 0.f, 0.f}};
#pragma unroll
        for (int k = 0; k < 4; k++) { stat_mma(c[0], v[k].x, v[k].y); stat_mma(c[1], v[k].z, v[k].w); }
        stat_store(c[0], SM_RED + (warp & 7) * 96 + (loader ? 0 : 384), lane);
        stat_store(c[1], SM_RED + (warp & 7) * 96 + 48 + (loader ? 0 : 384), lane);
        if (tid == 256) TL(2);
        if (loader) bar_sync(3, 256);
        if (warp <= 8) stat_publish(SM_RED, &gs->acc[b * 32], lane, warp == 8);
        if (tid == 256) TL(3);
        if (loader) {
#pragma unroll
            for (int i = 0; i < 4; i++) sts128(SM_XOWN + c0 * 128 + i * 512 + ((seg ^ ((c0 + 4 * i) & 7)) << 4), v[i]);
        }
    }
    if (warp == 0) {
        weight_block(v, SM_BNC, gs->wt, cta, lane);
        if (r == 0) {
            if (lane < 16) gs->acc[(NB + b) * 32 + lane] = 0.f;
            *reinterpret_cast<float4*>(&gs->emb[b * C + lane * 4]) = make_float4(0.f, 0.f, 0.f, 0.f);
        }
        __syncwarp();
        if (lane == 0) TL(4);
        if (lane < 2) asm volatile("red.release.gpu.global.add.u32 [%0], 1;" ::"l"(&gs->wcnt[lane * 32]) : "memory");
        if (lane == 0) TL(5);
    }

    if (warp >= 8) {
        asm volatile("setmaxnreg.dec.sync.aligned.u32 80;");
        const int nw = warp - 8;
        asm volatile("cp.async.wait_all;" ::: "memory");
        bar_sync(4, 384 + 96);
        const int w3 = nw >> 2, wq = nw & 3;
        const unsigned epoch = gs->epoch[cta * 32];
        const uint32_t act_off = SM_ACT + (w3 * 2 + (lane >> 4)) * CH_PITCH + (2 + wq * 16 + (lane & 15)) * 16;
        const uint32_t stg_off = SM_XOWN + (w3 * 16 + (lane >> 4) * 8 + (lane & 7)) * 128 + (((2 * wq + ((lane >> 3) & 1)) ^ (lane & 7)) << 4);
        const uint32_t fbar = BAR(BAR_FULL) + 8 * w3;
        const uint32_t cfa = SM_COEF + (lane & 3) * 16;
        const uint4* hrow = gs->h + ((epoch & 1) * NCTA + cta) * 1024 + wq * 32 + lane;
#pragma unroll 1
        for (int conv = 0; conv < 2; conv++) {
            uint32_t u[8][4];
            if (conv == 0) {
#pragma unroll
                for (int i = 0; i < 8; i++) ldsm4t(u[i], stg_off + i * 6144);
                publish(BAR(BAR_XFREE), lane);
            } else {
                mbar_wait(BAR(BAR_HW), 0);
#pragma unroll
                for (int i = 0; i < 3; i++) ldsm4(u[i], act_off + i * 6 * CH_PITCH);
            }
            mbar_wait(BAR(BAR_STATS), conv);
            if (tid == 256) TL(22 + conv * 4);
            float4 ca = lds128f(cfa + w3 * 128), cb = lds128f(cfa + w3 * 128 + 64);
#pragma unroll
            for (int i = 0; i < 8; i++) {
                const int st = w3 + 3 * i;
                if (conv == 1 && i == FETCH_AT) {
                    unsigned it = 0;
                    while (true) {
                        bool ok = true;
#pragma unroll
                        for (int j = 2; j < 8; j++) {
                            const int sj = w3 + 3 * j;
                            if (sj >= 8) {
                                const int ro = sj < 16 ? (r != 0 ? -1024 : 0) : (r != HW - 1 ? 1024 : 0);
                                ld_unit(u[j], hrow + ro + (sj & 7) * 128);
                            }
                        }
#pragma unroll
                        for (int j = 0; j < 24; j++) ok = ok && (u[2 + (j >> 2)][j & 3] != 0 || (j < 4 && w3 < 2));
                        if (__all_sync(0xffffffffu, ok) || ++it > SPIN_LIMIT) break;
                    }
#pragma unroll
                    for (int j = 0; j < 24; j++) u[2 + (j >> 2)][j & 3] ^= (j < 4 && w3 < 2) ? 0u : ~0u;
                    if (tid == 256) TL(28);
                }
                const float4 c0f = ca, c1f = cb;
                if (i < 7) { ca = lds128f(cfa + ((st + 3) & 7) * 128); cb = lds128f(cfa + ((st + 3) & 7) * 128 + 64); }
                norm_unit(u[i], c0f, c1f);
                if (st < 8 || (st < 16 ? r != 0 : r != HW - 1)) stsm4(act_off + i * 6 * CH_PITCH, u[i][0], u[i][1], u[i][2], u[i][3]);
                publish(fbar + 24 * i, lane);
                if (i == 0 && tid == 256) TL(8 + conv * 8);
                if (i == 1 && tid == 256) TL(84 + conv);
            }
            if (tid == 256) TL(23 + conv * 4);
        }
        if (loader) {
            uint4* hz = gs->h + (((epoch + 1) & 1) * NCTA + cta) * 1024 + (tid - 256);
#pragma unroll
            for (int i = 0; i < 4; i++) hz[i * 256] = make_uint4(0, 0, 0, 0);
        }
    } else if (warp < 4) {
        const int wq = warp;
        if (wq != 0) {
            const int t = tid - 32;
            if (lane == 0) {
                if (wq < 3) {
#pragma unroll
                    for (int i = 0; i < 12; i++) mbar_init(BAR(BAR_FULL + i) + (wq - 1) * 96, 5);
                    mbar_init(BAR(BAR_STATS) + (wq - 1) * 16, 1);
                    mbar_init(BAR(BAR_EMB) + (wq - 1) * 16, 1);
                } else {
#pragma unroll
                    for (int i = 0; i <= NS; i++) mbar_init(BAR(BAR_WEMPTY + i), 4);
                    mbar_init(BAR(BAR_XFREE), 12);
                }
            }
            fence_async_smem();
            bar_arrive(0, 96 + 128);
            bar_arrive(4, 384 + 96);
            if (t == 95) TLG(1);
            const uint4 z = make_uint4(0, 0, 0, 0);
            sts128(SM_ACT + (t >> 1) * CH_PITCH + (t & 1) * 16, z);
            if (t < 2) sts128(SM_ACT + 3 * ROW_BYTES + t * 16, z);
            if (t < 16) sts128(SM_ONES + t * 16, make_uint4(t < 8 ? 0x3f803f80u : 0u, 0, 0, 0));
            if (r == 0 || r == HW - 1) {
#pragma unroll 1
                for (int i = t; i < ROW_BYTES / 16; i += 96) sts128(SM_ACT + (r == 0 ? 1 : 2) * ROW_BYTES + i * 16, z);
            }
            fence_async_smem();
        }
        bar_sync(2, 128);
        asm volatile("setmaxnreg.inc.sync.aligned.u32 136;");
        const unsigned epoch = gs->epoch[cta * 32];

        float d[64];
#pragma unroll
        for (int i = 0; i < 64; i++) d[i] = 0.f;
#pragma unroll 1
        for (int conv = 0; conv < 2; conv++) {
            fence_acc(d);
            mma_stages<0>(d, conv, tid, gs);
            if (conv == 0) {
                asm volatile("wgmma.fence.sync.aligned;" ::: "memory");
                wgmma128<(SM_ONES >> 4) | (8u << 16), (SM_EMB >> 4), 0>(d);
                asm volatile("wgmma.commit_group.sync.aligned;" ::: "memory");
            }
            asm volatile("wgmma.wait_group.sync.aligned 0;" ::: "memory");
            fence_acc(d);
            if (tid == 0) TL(10 + conv * 8);
            if (conv == 1) break;

            uint32_t hp[32];
#pragma unroll
            for (int g = 0; g < 4; g++) {
                float c[4] = {0.f, 0.f, 0.f, 0.f};
#pragma unroll
                for (int i = 0; i < 8; i++) hp[8 * g + i] = pack_bf(d[16 * g + 2 * i], d[16 * g + 2 * i + 1]);
#pragma unroll
                for (int i = 0; i < 4; i++) stat_mma(c, hp[8 * g + 2 * i], hp[8 * g + 2 * i + 1]);
                stat_store(c, SM_RED + (g * 4 + wq) * 48, lane);
            }
            bar_sync(2, 128);
            if (wq == 0) stat_publish(SM_RED, &gs->acc[(NB + b) * 32], lane, true);
            if (tid == 0) TL(11);
            const uint32_t hbase = SM_ACT + (lane >> 4) * CH_PITCH + (2 + wq * 16 + (lane & 15)) * 16;
#pragma unroll
            for (int kc = 0; kc < 8; kc++) stsm4(hbase + kc * 2 * CH_PITCH, hp[4 * kc], hp[4 * kc + 1], hp[4 * kc + 2], hp[4 * kc + 3]);
            __syncwarp();
            if (lane == 0) mbar_arrive(BAR(BAR_HW));
            if (lane < LAG) mbar_arrive(BAR(BAR_WEMPTY + (NSTAGE - LAG) % NS) + 8 * lane);
            uint4* hg = gs->h + ((epoch & 1) * NCTA + cta) * 1024 + tid;
#pragma unroll
            for (int kc = 0; kc < 8; kc++) hg[kc * 128] = make_uint4(~hp[4 * kc], ~hp[4 * kc + 1], ~hp[4 * kc + 2], ~hp[4 * kc + 3]);
            if (tid == 0) TL(12);
            const uint32_t xbase = SM_XOWN + ((lane >> 4) * 8 + (lane & 7)) * 128 + (((2 * wq + ((lane >> 3) & 1)) ^ (lane & 7)) << 4);
#pragma unroll
            for (int kc = 0; kc < 8; kc++) {
                uint32_t p[4];
                ldsm4t(p, xbase + kc * 2048);
#pragma unroll
                for (int i = 0; i < 4; i++) { d[8 * kc + 2 * i] = bf_lo(p[i]); d[8 * kc + 2 * i + 1] = bf_hi(p[i]); }
            }
        }
        {
            const uint32_t obase = slot_addr(0) + ((lane >> 4) * 8 + (lane & 7)) * OUT_PITCH + (wq * 16 + ((lane >> 3) & 1) * 8) * 2;
#pragma unroll
            for (int kc = 0; kc < 8; kc++) {
                stsm4t(obase + kc * 16 * OUT_PITCH, pack_bf(d[8 * kc + 0], d[8 * kc + 1]), pack_bf(d[8 * kc + 2], d[8 * kc + 3]),
                       pack_bf(d[8 * kc + 4], d[8 * kc + 5]), pack_bf(d[8 * kc + 6], d[8 * kc + 7]));
            }
            bar_sync(2, 128);
            const int oc0 = tid >> 3;
            __nv_bfloat16* dst = out + ((size_t)(b * C + oc0) * HW + r) * HW + seg * 8;
#pragma unroll
            for (int i = 0; i < 8; i++)
                *reinterpret_cast<uint4*>(dst + (size_t)i * 16 * HW * HW) = lds128(slot_addr(0) + (oc0 + 16 * i) * OUT_PITCH + seg * 16);
            if (tid == 0) gs->epoch[cta * 32] = epoch + 1;
            if (tid == 0) { TL(20); TLG(21); }
        }
    } else if (warp < 6) {
        bar_sync(0, 96 + 128);
        if (warp == 4) {
            while (clock32() - clk0 < W2DELAY) {}
            const char* w2s = reinterpret_cast<const char*>(w2) + woff;
#pragma unroll
            for (int k = 0; k < 4; k++) v[k] = __ldg(reinterpret_cast<const uint4*>(w2s + k * 256));
            if ((lane & 15) < 8) v[4] = __ldg(reinterpret_cast<const uint4*>(w2s + 1024));
            const uint2* wsrc = reinterpret_cast<const uint2*>(w_emb + (size_t)r * 12 * C) + lane;
            uint2 wv[12];
#pragma unroll
            for (int i = 0; i < 12; i++) wv[i] = __ldg(wsrc + i * (C / 4));
            float tv = 0.f;
            if (lane < 12) tv = __bfloat162float(t_emb[b * E + r * 12 + lane]);
            weight_block(v, SM_BNC + 2304, gs->wt + NSTAGE * STAGE_BYTES, cta, lane);
            const float sv = silu_half(0.5f * tv);
            float e0 = 0.f, e1 = 0.f, e2 = 0.f, e3 = 0.f;
#pragma unroll
            for (int i = 0; i < 12; i++) {
                const float sx = __shfl_sync(0xffffffffu, sv, i);
                e0 = fmaf(sx, bf_lo(wv[i].x), e0); e1 = fmaf(sx, bf_hi(wv[i].x), e1);
                e2 = fmaf(sx, bf_lo(wv[i].y), e2); e3 = fmaf(sx, bf_hi(wv[i].y), e3);
            }
            mbar_wait(BAR(BAR_WACQ), 0);
            red_add4(&gs->emb[b * C + lane * 4], e0, e1, e2, e3);
            __syncwarp();
            if (lane == 0) TL(13);
            if (lane < 2) asm volatile("red.release.gpu.global.add.u32 [%0], 1;" ::"l"(&gs->wcnt[(NB + lane) * 32]) : "memory");
            if (lane == 0) TL(14);
            unsigned it = 0;
            while (ld_relaxed(&gs->wcnt[(NB + b) * 32]) < (unsigned)NCTA && ++it < SPIN_LIMIT) {}
            fence_acquire();
            const uint4 ef = ld_relaxed_v4(&gs->emb[b * C + lane * 4]);
            const uint32_t eu[4] = {ef.x, ef.y, ef.z, ef.w};
#pragma unroll
            for (int i = 0; i < 4; i++) {
                const float e = __uint_as_float(eu[i]);
                const float hi = bf_lo(pack_bf(e, 0.f));
                sts128(SM_EMB + (lane * 4 + i) * 16, make_uint4(pack_bf(hi, e - hi), 0, 0, 0));
            }
            fence_async_smem();
            __syncwarp();
            if (lane == 0) { mbar_arrive(BAR(BAR_EMB)); TL(19); }
        }
    } else if (warp == 6) {
        bar_sync(0, 96 + 128);
        unsigned it = 0;
        while (ld_relaxed(&gs->wcnt[b * 32]) < (unsigned)NCTA && ++it < SPIN_LIMIT) {}
        fence_acquire();
        fence_async_global();
        if (lane == 0) { mbar_arrive(BAR(BAR_WACQ)); TL(6); }
        const unsigned char* wsrc = gs->wt;
#pragma unroll 1
        for (int round = 0; round < 2 * NSTAGE / NS; round++) {
            if (round == NSTAGE / NS) { mbar_wait(BAR(BAR_EMB), 0); fence_async_global(); }
            const uint32_t full = BAR(BAR_FULL) + 8 * NS * (round >= NSTAGE / NS ? round - NSTAGE / NS : round);
#pragma unroll
            for (int slot = 0; slot < NS; slot++) {
                if (slot == 9 && round == 0) mbar_wait(BAR(BAR_XFREE), 0);
                mbar_wait(BAR(BAR_WEMPTY + slot), (round & 1) ^ 1);
                if (elect_one()) {
                    mbar_expect(full + 8 * slot, STAGE_BYTES);
                    bulk_g2s(slot_addr(slot), wsrc + slot * STAGE_BYTES, STAGE_BYTES, full + 8 * slot);
                }
            }
            wsrc += NS * STAGE_BYTES;
        }
    } else {
        const uint2 ga1 = __ldg(reinterpret_cast<const uint2*>(g1) + lane), bt1 = __ldg(reinterpret_cast<const uint2*>(be1) + lane);
        const uint2 ga2 = __ldg(reinterpret_cast<const uint2*>(g2) + lane), bt2 = __ldg(reinterpret_cast<const uint2*>(be2) + lane);
        bar_sync(0, 96 + 128);
#pragma unroll 1
        for (int conv = 0; conv < 2; conv++) {
            if (conv == 1) mbar_wait(BAR(BAR_EMB), 0);
            const float* asrc = &gs->acc[(conv * NB + b) * 32 + (lane >> 3) * 4];
            uint4 f;
            unsigned it = 0;
            while (true) {
                f = ld_relaxed_v4(asrc);
                const bool ok = (f.x == 0x42800000u) & (f.w == 0x42800000u);
                if (__all_sync(0xffffffffu, ok) || ++it > SPIN_LIMIT) break;
            }
            if (lane == 0) TL(7 + conv * 8);
            const float inv_n = 1.0f / (32.0f * HW * HW);
            const float mean = __uint_as_float(f.y) * inv_n;
            const float var = fmaxf(fmaf(-mean, mean, __uint_as_float(f.z) * inv_n), 0.f);
            const float rs = 0.5f * rsqrtf(var + 1e-5f);
            const uint2 ga = conv ? ga2 : ga1, bt = conv ? bt2 : bt1;
            float4 k0, k1;
            k0.x = rs * bf_lo(ga.x); k0.y = rs * bf_hi(ga.x); k1.x = rs * bf_lo(ga.y); k1.y = rs * bf_hi(ga.y);
            k0.z = fmaf(-mean, k0.x, 0.5f * bf_lo(bt.x)); k0.w = fmaf(-mean, k0.y, 0.5f * bf_hi(bt.x));
            k1.z = fmaf(-mean, k1.x, 0.5f * bf_lo(bt.y)); k1.w = fmaf(-mean, k1.y, 0.5f * bf_hi(bt.y));
            sts128f(SM_COEF + lane * 32, k0);
            sts128f(SM_COEF + lane * 32 + 16, k1);
            __syncwarp();
            if (lane == 0) mbar_arrive(BAR(BAR_STATS));
        }
        if (r == 0) {
            if (lane < 16) gs->acc[b * 32 + lane] = 0.f;
            if (lane < 2) gs->wcnt[(lane * NB + b) * 32] = 0;
        }
    }
}

}

extern "C" void kernel_launch(void* const* d_in, const int* in_sizes, int n_in, void* d_out, int out_size) {
    (void)in_sizes; (void)n_in; (void)out_size;
    static Scratch* gs = nullptr;
    if (!gs) {
        cudaFuncSetAttribute(resblock_kernel, cudaFuncAttributeMaxDynamicSharedMemorySize, SM_TOTAL);
        cudaGetSymbolAddress((void**)&gs, g_scratch);
    }
    resblock_kernel<<<NCTA, NTHREADS, SM_TOTAL>>>(
        (const __nv_bfloat16*)d_in[0], (const __nv_bfloat16*)d_in[4], (const __nv_bfloat16*)d_in[1],
        (const __nv_bfloat16*)d_in[2], (const __nv_bfloat16*)d_in[3], (const __nv_bfloat16*)d_in[5],
        (const __nv_bfloat16*)d_in[6], (const __nv_bfloat16*)d_in[7], (const __nv_bfloat16*)d_in[8],
        (__nv_bfloat16*)d_out, gs);
}
```

```cpp
#include <cuda_runtime.h>
#include <cuda_bf16.h>
#include <stdint.h>

namespace {

constexpr int C = 128, HW = 64, NB = 2, E = 768;
constexpr int NCTA = NB * HW;
constexpr int NTHREADS = 16 * 32;
constexpr int CH_PITCH = 66 * 16;
constexpr int ROW_BYTES = 16 * CH_PITCH;
constexpr int STEP_BYTES = 4096;
constexpr int STAGE_BYTES = 3 * STEP_BYTES;
constexpr int NSTAGE = 24;
constexpr int NS = 12;
constexpr int LAG = 1;
#define XDELAY 600
#define HDELAY 500
#define PUB1 2
#define FETCH_AT 2
#define W2DELAY 2800

constexpr uint32_t SMEM_BASE = 0x400;
constexpr uint32_t SM_ACT = SMEM_BASE;
constexpr uint32_t SM_XOWN = SM_ACT + 3 * ROW_BYTES + 128;
constexpr uint32_t SM_W = SM_XOWN + 16384;
constexpr uint32_t SM_XH = SM_W;
__host__ __device__ constexpr uint32_t slot_addr(int slot) { return SM_W + ((slot + 3) % NS) * STAGE_BYTES; }
constexpr uint32_t SM_COEF = SM_W + NS * STAGE_BYTES;
constexpr uint32_t SM_EMB = SM_COEF + 1024;
constexpr uint32_t SM_ONES = SM_EMB + 2048;
constexpr uint32_t SM_RED = SM_ONES + 256;
constexpr uint32_t SM_BNC = SM_RED + 1280;
constexpr uint32_t SM_BAR = SM_BNC + 2 * 2304;
constexpr int BAR_FULL = 0, BAR_WEMPTY = NSTAGE, BAR_HW = BAR_WEMPTY + NS, BAR_STATS = BAR_HW + 1,
              BAR_EMB = BAR_STATS + 1, BAR_WACQ = BAR_EMB + 1, BAR_XH = BAR_WACQ + 1, BAR_XFREE = BAR_XH + 1,
              BAR_ACT = BAR_XFREE + 1  , NBAR = BAR_ACT + 12;
constexpr int SM_TOTAL = SM_BAR + NBAR * 8 - SMEM_BASE;
static_assert(SM_TOTAL <= 232448, "smem");
static_assert(NBAR <= 96, "barrier init");
constexpr int OUT_PITCH = 144;
__host__ __device__ constexpr uint32_t BAR(int i) { return SM_BAR + 8 * i; }
__host__ __device__ constexpr int ky_of(int kyo) { return kyo == 0 ? 1 : (kyo == 1 ? 0 : 2); }

constexpr unsigned SPIN_LIMIT = 1u << 16;

struct Scratch {
    float acc[2 * NB * 32];
    unsigned wcnt[2 * NB * 32];
    float emb[NB * C];
    unsigned char wt[2 * NSTAGE * STAGE_BYTES];
    unsigned epoch[NCTA * 32];
    uint4 h[2 * NCTA * 1024];
};
__device__ __align__(1024) Scratch g_scratch;
#define TL(i) do {} while (0)
#define TLG(i) do {} while (0)

__device__ __forceinline__ unsigned clock32() { unsigned c; asm volatile("mov.u32 %0, %%clock;" : "=r"(c)); return c; }
__device__ __forceinline__ void mbar_init(uint32_t bar, int cnt) {
    asm volatile("mbarrier.init.shared::cta.b64 [%0], %1;" ::"r"(bar), "r"(cnt) : "memory");
}
__device__ __forceinline__ void mbar_arrive(uint32_t bar) {
    asm volatile("mbarrier.arrive.shared::cta.b64 _, [%0];" ::"r"(bar) : "memory");
}
__device__ __forceinline__ void mbar_expect(uint32_t bar, uint32_t bytes) {
    asm volatile("mbarrier.arrive.expect_tx.shared::cta.b64 _, [%0], %1;" ::"r"(bar), "r"(bytes) : "memory");
}
__device__ __forceinline__ bool mbar_try(uint32_t bar, uint32_t par) {
    uint32_t ok;
    asm volatile("{\n.reg .pred p;\nmbarrier.try_wait.parity.shared::cta.b64 p, [%1], %2;\nselp.u32 %0, 1, 0, p;\n}"
                 : "=r"(ok) : "r"(bar), "r"(par) : "memory");
    return ok;
}
__device__ __forceinline__ bool mbar_test(uint32_t bar, uint32_t par) {
    uint32_t ok;
    asm volatile("{\n.reg .pred p;\nmbarrier.test_wait.parity.shared::cta.b64 p, [%1], %2;\nselp.u32 %0, 1, 0, p;\n}"
                 : "=r"(ok) : "r"(bar), "r"(par) : "memory");
    return ok;
}
__device__ __forceinline__ void mbar_wait(uint32_t bar, uint32_t par) {
    unsigned it = 0;
#pragma unroll 1
    while (!mbar_try(bar, par) && ++it < SPIN_LIMIT) {}
}
__device__ __forceinline__ bool elect_one() {
    uint32_t p;
    asm volatile("{\n.reg .pred p;\nelect.sync _|p, 0xffffffff;\nselp.u32 %0, 1, 0, p;\n}" : "=r"(p));
    return p;
}
__device__ __forceinline__ void fence_async_smem() { asm volatile("fence.proxy.async.shared::cta;" ::: "memory"); }
__device__ __forceinline__ void fence_async_global() { asm volatile("fence.proxy.async.global;" ::: "memory"); }
__device__ __forceinline__ void fence_acquire() { asm volatile("fence.acquire.gpu;" ::: "memory"); }
__device__ __forceinline__ void bar_sync(int id, int n) { asm volatile("bar.sync %0, %1;" ::"r"(id), "r"(n) : "memory"); }
__device__ __forceinline__ void bar_arrive(int id, int n) { asm volatile("bar.arrive %0, %1;" ::"r"(id), "r"(n) : "memory"); }
__device__ __forceinline__ void bulk_g2s(uint32_t dst, const void* src, uint32_t bytes, uint32_t bar) {
    asm volatile("cp.async.bulk.shared::cluster.global.mbarrier::complete_tx::bytes [%0], [%1], %2, [%3];"
                 ::"r"(dst), "l"(src), "r"(bytes), "r"(bar) : "memory");
}
__device__ __forceinline__ uint4 ld_relaxed_v4(const void* p) {
    uint4 v;
    asm volatile("ld.relaxed.gpu.global.v4.u32 {%0,%1,%2,%3}, [%4];" : "=r"(v.x), "=r"(v.y), "=r"(v.z), "=r"(v.w) : "l"(p) : "memory");
    return v;
}
__device__ __forceinline__ unsigned ld_relaxed(const void* p) {
    unsigned v;
    asm volatile("ld.relaxed.gpu.global.u32 %0, [%1];" : "=r"(v) : "l"(p) : "memory");
    return v;
}
__device__ __forceinline__ void red_add4(float* p, float a, float b, float c, float d) {
    asm volatile("red.relaxed.gpu.global.add.v4.f32 [%0], {%1,%2,%3,%4};" ::"l"(p), "f"(a), "f"(b), "f"(c), "f"(d) : "memory");
}
__device__ __forceinline__ void sts128(uint32_t a, uint4 v) {
    asm volatile("st.shared.v4.u32 [%0], {%1,%2,%3,%4};" ::"r"(a), "r"(v.x), "r"(v.y), "r"(v.z), "r"(v.w) : "memory");
}
__device__ __forceinline__ void sts128f(uint32_t a, float4 v) {
    asm volatile("st.shared.v4.f32 [%0], {%1,%2,%3,%4};" ::"r"(a), "f"(v.x), "f"(v.y), "f"(v.z), "f"(v.w) : "memory");
}
__device__ __forceinline__ void sts32f(uint32_t a, float v) { asm volatile("st.shared.f32 [%0], %1;" ::"r"(a), "f"(v) : "memory"); }
__device__ __forceinline__ uint4 lds128(uint32_t a) {
    uint4 v;
    asm volatile("ld.shared.v4.u32 {%0,%1,%2,%3}, [%4];" : "=r"(v.x), "=r"(v.y), "=r"(v.z), "=r"(v.w) : "r"(a) : "memory");
    return v;
}
__device__ __forceinline__ float4 lds128f(uint32_t a) {
    float4 v;
    asm volatile("ld.shared.v4.f32 {%0,%1,%2,%3}, [%4];" : "=f"(v.x), "=f"(v.y), "=f"(v.z), "=f"(v.w) : "r"(a) : "memory");
    return v;
}
__device__ __forceinline__ float2 lds64f(uint32_t a) {
    float2 v;
    asm volatile("ld.shared.v2.f32 {%0,%1}, [%2];" : "=f"(v.x), "=f"(v.y) : "r"(a) : "memory");
    return v;
}
__device__ __forceinline__ float bf_lo(uint32_t u) { return __uint_as_float(u << 16); }
__device__ __forceinline__ float bf_hi(uint32_t u) { return __uint_as_float(u & 0xffff0000u); }
__device__ __forceinline__ uint32_t pack_bf(float lo, float hi) {
    uint32_t r;
    asm("cvt.rn.bf16x2.f32 %0, %1, %2;" : "=r"(r) : "f"(hi), "f"(lo));
    return r;
}
__device__ __forceinline__ float tanh_fast(float x) {
    float r;
    asm volatile("tanh.approx.f32 %0, %1;" : "=f"(r) : "f"(x));
    return r;
}
__device__ __forceinline__ float silu_half(float h) { return fmaf(h, tanh_fast(h), h); }
__device__ __forceinline__ void ldsm4(uint32_t (&u)[4], uint32_t a) {
    asm volatile("ldmatrix.sync.aligned.m8n8.x4.shared.b16 {%0,%1,%2,%3}, [%4];"
                 : "=r"(u[0]), "=r"(u[1]), "=r"(u[2]), "=r"(u[3]) : "r"(a) : "memory");
}
__device__ __forceinline__ void ldsm4t(uint32_t (&u)[4], uint32_t a) {
    asm volatile("ldmatrix.sync.aligned.m8n8.x4.trans.shared.b16 {%0,%1,%2,%3}, [%4];"
                 : "=r"(u[0]), "=r"(u[1]), "=r"(u[2]), "=r"(u[3]) : "r"(a) : "memory");
}
__device__ __forceinline__ void stsm4(uint32_t a, uint32_t p0, uint32_t p1, uint32_t p2, uint32_t p3) {
    asm volatile("stmatrix.sync.aligned.m8n8.x4.shared.b16 [%0], {%1,%2,%3,%4};" ::"r"(a), "r"(p0), "r"(p1), "r"(p2), "r"(p3) : "memory");
}
__device__ __forceinline__ void stsm4t(uint32_t a, uint32_t p0, uint32_t p1, uint32_t p2, uint32_t p3) {
    asm volatile("stmatrix.sync.aligned.m8n8.x4.trans.shared.b16 [%0], {%1,%2,%3,%4};" ::"r"(a), "r"(p0), "r"(p1), "r"(p2), "r"(p3) : "memory");
}

#define R8(o) "+f"(d[o]), "+f"(d[o + 1]), "+f"(d[o + 2]), "+f"(d[o + 3]), "+f"(d[o + 4]), "+f"(d[o + 5]), "+f"(d[o + 6]), "+f"(d[o + 7])
template <uint32_t ALO, uint32_t BLO, uint64_t AHI = 8>
__device__ __forceinline__ void wgmma128(float (&d)[64]) {
    asm volatile(
        "wgmma.mma_async.sync.aligned.m64n128k16.f32.bf16.bf16 "
        "{%0,%1,%2,%3,%4,%5,%6,%7,%8,%9,%10,%11,%12,%13,%14,%15,%16,%17,%18,%19,%20,%21,%22,%23,%24,%25,%26,%27,%28,%29,%30,%31,"
        "%32,%33,%34,%35,%36,%37,%38,%39,%40,%41,%42,%43,%44,%45,%46,%47,%48,%49,%50,%51,%52,%53,%54,%55,%56,%57,%58,%59,%60,%61,%62,%63},"
        " %64, %65, 1, 1, 1, 0, 0;"
        : R8(0), R8(8), R8(16), R8(24), R8(32), R8(40), R8(48), R8(56)
        : "l"((AHI << 32) | ALO), "l"((8ull << 32) | BLO));
}
template <int S>
__device__ __forceinline__ void mma_stages(float (&d)[64], int conv, int tid, Scratch* gs) {
    constexpr uint32_t A = ((SM_ACT + S * 2 * CH_PITCH + 16) >> 4) | ((CH_PITCH >> 4) << 16);
    constexpr uint32_t B = (slot_addr(S % NS) >> 4) | ((2048 >> 4) << 16);
    if (S == 0) mbar_wait(BAR(BAR_FULL), conv);
    bool next_ok = true;
    constexpr uint32_t NEXT = S + 1 < NSTAGE ? BAR(BAR_FULL + S + 1) : BAR(BAR_EMB);
    const int npar = S + 1 < NSTAGE ? conv : 0;
    next_ok = mbar_test(NEXT, npar);
    if (S == 0 && tid == 0) TL(32 + conv * 24);
    asm volatile("wgmma.fence.sync.aligned;" ::: "memory");
    wgmma128<A, B>(d);
    wgmma128<A + 1, B + (STEP_BYTES >> 4)>(d);
    wgmma128<A + 2, B + 2 * (STEP_BYTES >> 4)>(d);
    asm volatile("wgmma.commit_group.sync.aligned;" ::: "memory");
    if (S >= LAG) {
        asm volatile("wgmma.wait_group.sync.aligned %0;" ::"n"(LAG) : "memory");
        if ((tid & 31) == 0) mbar_arrive(BAR(BAR_WEMPTY + (S + NS - LAG) % NS));
    }
    if (!next_ok) mbar_wait(NEXT, npar);
    if constexpr (S + 1 < NSTAGE) mma_stages<S + 1>(d, conv, tid, gs);
}

__device__ __forceinline__ void weight_block(const uint4 (&t)[5], uint32_t bounce, unsigned char* wt, int cta, int lane) {
    const uint32_t bw = bounce + (lane >> 4) * 1152 + (lane & 15) * 16;
#pragma unroll
    for (int k = 0; k < 4; k++) sts128(bw + k * 256, t[k]);
    if ((lane & 15) < 8) sts128(bw + 1024, t[4]);
    __syncwarp();
    if (lane < 16) {
        uint32_t v[36];
#pragma unroll
        for (int i = 0; i < 9; i++) {
            const uint4 q = lds128(bounce + (lane & 1) * 1152 + (lane >> 1) * 144 + i * 16);
            v[4 * i] = q.x; v[4 * i + 1] = q.y; v[4 * i + 2] = q.z; v[4 * i + 3] = q.w;
        }
        const int cc = (cta >> 6) * 8 + (lane >> 1);
        unsigned char* dst = wt + (cc >> 1) * STAGE_BYTES + (cc & 1) * 2048 + ((cta & 63) * 2 + (lane & 1)) * 16;
#pragma unroll
        for (int kyo = 0; kyo < 3; kyo++) {
#pragma unroll
            for (int kx = 0; kx < 3; kx++) {
                const int tap = ky_of(kyo) * 3 + kx;
                uint32_t o[4];
#pragma unroll
                for (int m = 0; m < 4; m++) {
                    const int i0 = 18 * m + tap, i1 = i0 + 9;
                    const uint32_t sel = ((i0 & 1) ? 0x32u : 0x10u) | ((i1 & 1) ? 0x7600u : 0x5400u);
                    o[m] = __byte_perm(v[i0 >> 1], v[i1 >> 1], sel);
                }
                *reinterpret_cast<uint4*>(dst + (kyo * 24 + kx) * STEP_BYTES) = make_uint4(o[0], o[1], o[2], o[3]);
            }
        }
    }
}
__device__ __forceinline__ uint32_t act2(uint32_t u, const float4& cf) {
    return pack_bf(silu_half(fmaf(bf_lo(u), cf.x, cf.z)), silu_half(fmaf(bf_hi(u), cf.y, cf.w)));
}
__device__ __forceinline__ void norm_unit(uint32_t (&u)[4], const float4& ca, const float4& cb) {
    u[0] = act2(u[0], ca); u[1] = act2(u[1], ca); u[2] = act2(u[2], cb); u[3] = act2(u[3], cb);
}
__device__ __forceinline__ void publish(uint32_t bar, int lane) {
    fence_async_smem();
    __syncwarp();
    if (lane == 0) mbar_arrive(bar);
}
__device__ __forceinline__ void publish2(uint32_t bar, int lane) {
    fence_async_smem();
    __syncwarp();
    if (lane < 2) mbar_arrive(bar + 8 * lane);
}
__device__ __forceinline__ void stat_mma(float (&c)[4], uint32_t p, uint32_t q) {
    asm("mma.sync.aligned.m16n8k16.row.col.f32.bf16.bf16.f32 {%0,%1,%2,%3}, {%4,%5,%6,%5}, {%4,%6}, {%0,%1,%2,%3};"
        : "+f"(c[0]), "+f"(c[1]), "+f"(c[2]), "+f"(c[3]) : "r"(p), "r"(0x3f803f80u), "r"(q));
}
__device__ __forceinline__ void stat_store(const float (&c)[4], uint32_t dst, int lane) {
    const int g = lane >> 2, t = lane & 3;
    if (t == (g >> 1)) sts32f(dst + g * 4, (g & 1) ? c[1] : c[0]);
    if (g == 7) sts32f(dst + 32 + t * 4, c[2] + c[3]);
}
__device__ __forceinline__ float sum4(float4 v) { return (v.x + v.y) + (v.z + v.w); }
__device__ __forceinline__ void stat_publish(uint32_t src, float* acc, int lane, bool real) {
    const uint32_t a = src + (lane & 15) * 48;
    float q = sum4(lds128f(a)) + sum4(lds128f(a + 16)), sm = sum4(lds128f(a + 32));
    q += __shfl_xor_sync(0xffffffffu, q, 1); sm += __shfl_xor_sync(0xffffffffu, sm, 1);
    q += __shfl_xor_sync(0xffffffffu, q, 2); sm += __shfl_xor_sync(0xffffffffu, sm, 2);
    if (real && (lane & 19) == 0) red_add4(acc + lane, 1.f, sm, q, 1.f);
}
__device__ __forceinline__ void fence_acc(float (&d)[64]) {
#pragma unroll
    for (int i = 0; i < 64; i++) asm volatile("" : "+f"(d[i])::"memory");
}
__device__ __forceinline__ void ld_unit(uint32_t (&u)[4], const uint4* p) {
    asm volatile("ld.relaxed.gpu.global.v4.u32 {%0,%1,%2,%3}, [%4];" : "=r"(u[0]), "=r"(u[1]), "=r"(u[2]), "=r"(u[3]) : "l"(p) : "memory");
}

__global__ void __launch_bounds__(NTHREADS, 1)
resblock_kernel(const __nv_bfloat16* __restrict__ x, const __nv_bfloat16* __restrict__ w1,
                const __nv_bfloat16* __restrict__ t_emb, const __nv_bfloat16* __restrict__ g1,
                const __nv_bfloat16* __restrict__ be1, const __nv_bfloat16* __restrict__ w_emb,
                const __nv_bfloat16* __restrict__ g2, const __nv_bfloat16* __restrict__ be2,
                const __nv_bfloat16* __restrict__ w2, __nv_bfloat16* __restrict__ out, Scratch* __restrict__ gs) {
    const unsigned clk0 = clock32();
    const int tid = threadIdx.x, warp = tid >> 5, lane = tid & 31;
    const int cta = blockIdx.x, b = cta >> 6, r = cta & 63;

    const uint32_t woff = ((2 * r + (lane >> 4)) * C + b * 64) * 18 + (lane & 15) * 16;
    const int c0 = (warp - 8) * 16 + (lane >> 3), seg = lane & 7;
    uint4 v[5];
    if (warp == 0) {
        const char* w1s = reinterpret_cast<const char*>(w1) + woff;
#pragma unroll
        for (int k = 0; k < 4; k++) v[k] = __ldg(reinterpret_cast<const uint4*>(w1s + k * 256));
        if ((lane & 15) < 8) v[4] = __ldg(reinterpret_cast<const uint4*>(w1s + 1024));
    }
    const bool loader = warp >= 8;
    if (loader || warp == 5) {
        if (loader) {
            const char* src = reinterpret_cast<const char*>(x) + (uint32_t)(((b * C + c0) * HW + r) * HW * 2 + seg * 16);
            while (clock32() - clk0 < XDELAY) {}
#pragma unroll
            for (int k = 0; k < 4; k++) v[k] = __ldg(reinterpret_cast<const uint4*>(src + k * (4 * HW * HW * 2)));
#pragma unroll
            for (int i = 0; i < 8; i++) {
                if (i < 4 ? (r != 0) : (r != HW - 1))
                    asm volatile("cp.async.cg.shared.global [%0], [%1], 16;"
                                 ::"r"(SM_XH + (i >> 2) * 16384 + c0 * 128 + (i & 3) * 512 + ((seg ^ ((c0 + 4 * i) & 7)) << 4)),
                                   "l"(src + (i < 4 ? -HW * 2 : HW * 2) + (i & 3) * (4 * HW * HW * 2)) : "memory");
            }
        } else {
#pragma unroll
            for (int k = 0; k < 4; k++) v[k] = make_uint4(0, 0, 0, 0);
        }
        float c[2][4] = {{0.f, 0.f, 0.f, 0.f}, {0.f, 0.f, 0.f, 0.f}};
#pragma unroll
        for (int k = 0; k < 4; k++) { stat_mma(c[0], v[k].x, v[k].y); stat_mma(c[1], v[k].z, v[k].w); }
        stat_store(c[0], SM_RED + (warp & 7) * 96 + (loader ? 0 : 384), lane);
        stat_store(c[1], SM_RED + (warp & 7) * 96 + 48 + (loader ? 0 : 384), lane);
        if (tid == 256) TL(2);
        if (loader) bar_sync(3, 256);
        if (warp <= 8) stat_publish(SM_RED, &gs->acc[b * 32], lane, warp == 8);
        if (tid == 256) TL(3);
        if (loader) {
#pragma unroll
            for (int i = 0; i < 4; i++) sts128(SM_XOWN + c0 * 128 + i * 512 + ((seg ^ ((c0 + 4 * i) & 7)) << 4), v[i]);
        }
    }
    if (warp == 0) {
        weight_block(v, SM_BNC, gs->wt, cta, lane);
        if (r == 0) {
            if (lane < 16) gs->acc[(NB + b) * 32 + lane] = 0.f;
            *reinterpret_cast<float4*>(&gs->emb[b * C + lane * 4]) = make_float4(0.f, 0.f, 0.f, 0.f);
        }
        __syncwarp();
        if (lane == 0) TL(4);
        if (lane < 2) asm volatile("red.release.gpu.global.add.u32 [%0], 1;" ::"l"(&gs->wcnt[lane * 32]) : "memory");
        if (lane == 0) TL(5);
    }

    if (warp >= 8) {
        const int nw = warp - 8;
        asm volatile("cp.async.wait_all;" ::: "memory");
        bar_sync(4, 256 + 96);
        const int par = nw >> 2, wq = nw & 3;
        const unsigned epoch = gs->epoch[cta * 32];
        const uint32_t act_off = SM_ACT + (par * 2 + (lane >> 4)) * CH_PITCH + (2 + wq * 16 + (lane & 15)) * 16;
        const uint32_t stg_off = SM_XOWN + (par * 16 + (lane >> 4) * 8 + (lane & 7)) * 128 + (((2 * wq + ((lane >> 3) & 1)) ^ (lane & 7)) << 4);
        const uint32_t cfa = SM_COEF + par * 128 + (lane & 3) * 16;
        const uint4* hrow = gs->h + ((epoch & 1) * NCTA + cta) * 1024 + nw * 32 + lane;
        const uint4* hu = hrow - (r != 0 ? 1024 : 0);
        const uint4* hd = hrow + (r != HW - 1 ? 1024 : 0);
#pragma unroll 1
        for (int conv = 0; conv < 2; conv++) {
            uint32_t u[12][4];
            float4 cf[8];
            if (conv == 0) {
#pragma unroll
                for (int i = 0; i < 12; i++) ldsm4t(u[i], stg_off + i * 4096);
                publish(BAR(BAR_XFREE), lane);
            } else {
                mbar_wait(BAR(BAR_HW), 0);
#pragma unroll
                for (int i = 0; i < 4; i++) ldsm4(u[i], act_off + i * 4 * CH_PITCH);
            }
            mbar_wait(BAR(BAR_STATS), conv);
            if (tid == 256) TL(22 + conv * 4);
            cf[0] = lds128f(cfa); cf[1] = lds128f(cfa + 64);
#pragma unroll 1
            for (int row = 0; row < 3; row++) {
                const bool valid = row == 0 || (row == 1 ? r != 0 : r != HW - 1);
                const uint32_t dst = act_off + row * ROW_BYTES;
                norm_unit(u[0], cf[0], cf[1]);
                if (valid) stsm4(dst, u[0][0], u[0][1], u[0][2], u[0][3]);
                if (row == 0) {
                    publish(BAR(BAR_FULL) + 8 * par, lane);
                    if (tid == 256) TL(8 + conv * 8);
#pragma unroll
                    for (int i = 2; i < 8; i++) cf[i] = lds128f(cfa + (i >> 1) * 256 + (i & 1) * 64);
                    if (conv == 1) {
#pragma unroll
                        for (int i = 0; i < 4; i++) { ld_unit(u[4 + i], hu + i * 256); ld_unit(u[8 + i], hd + i * 256); }
                    }
                } else {
                    __syncwarp();
                    if (lane == 0) mbar_arrive(BAR(BAR_ACT) + 32 * row);
                }
#pragma unroll
                for (int t = 1; t < 4; t++) {
                    norm_unit(u[t], cf[2 * t], cf[2 * t + 1]);
                    if (valid) stsm4(dst + t * 4 * CH_PITCH, u[t][0], u[t][1], u[t][2], u[t][3]);
                    __syncwarp();
                    if (lane == 0) mbar_arrive(BAR(BAR_ACT + t) + 32 * row);
                }
                if (row == 0 && tid == 256) TL(84 + conv);
                if (row == 0 && conv == 1) {
                    unsigned it = 0;
                    while (true) {
                        bool ok = true;
#pragma unroll
                        for (int i = 0; i < 32; i++) ok = ok && u[4 + (i >> 2)][i & 3] != 0;
                        if (__all_sync(0xffffffffu, ok) || ++it > SPIN_LIMIT) break;
#pragma unroll
                        for (int i = 0; i < 4; i++) { ld_unit(u[4 + i], hu + i * 256); ld_unit(u[8 + i], hd + i * 256); }
                    }
#pragma unroll
                    for (int i = 0; i < 32; i++) u[4 + (i >> 2)][i & 3] = ~u[4 + (i >> 2)][i & 3];
                    if (tid == 256) TL(28);
                }
#pragma unroll
                for (int i = 0; i < 32; i++) u[i >> 2][i & 3] = u[4 + (i >> 2)][i & 3];
            }
            if (tid == 256) TL(23 + conv * 4);
        }
        uint4* hz = gs->h + (((epoch + 1) & 1) * NCTA + cta) * 1024 + (tid - 256);
#pragma unroll
        for (int i = 0; i < 4; i++) hz[i * 256] = make_uint4(0, 0, 0, 0);
    } else if (warp < 4) {
        const int wq = warp;
        if (wq != 0) {
            const int t = tid - 32;
            if (lane == 0) {
                if (wq == 1) {
#pragma unroll
                    for (int i = 0; i < 18; i++) mbar_init(BAR(BAR_FULL + i), i < 2 ? 5 : 2);
                } else if (wq == 2) {
#pragma unroll
                    for (int i = 18; i < NSTAGE; i++) mbar_init(BAR(BAR_FULL + i), 2);
#pragma unroll
                    for (int i = 0; i < 12; i++) mbar_init(BAR(BAR_ACT + i), 8);
                } else {
#pragma unroll
                    for (int i = 0; i <= NS; i++) mbar_init(BAR(BAR_WEMPTY + i), 4);
#pragma unroll
                    for (int i = BAR_STATS; i < BAR_XFREE; i++) mbar_init(BAR(i), 1);
                    mbar_init(BAR(BAR_XFREE), 8);
                }
            }
            fence_async_smem();
            bar_arrive(0, 96 + 128);
            bar_arrive(4, 256 + 96);
            if (t == 95) TLG(1);
            const uint4 z = make_uint4(0, 0, 0, 0);
            sts128(SM_ACT + (t >> 1) * CH_PITCH + (t & 1) * 16, z);
            if (t < 2) sts128(SM_ACT + 3 * ROW_BYTES + t * 16, z);
            if (t < 16) sts128(SM_ONES + t * 16, make_uint4(t < 8 ? 0x3f803f80u : 0u, 0, 0, 0));
            if (r == 0 || r == HW - 1) {
#pragma unroll 1
                for (int i = t; i < ROW_BYTES / 16; i += 96) sts128(SM_ACT + (r == 0 ? 1 : 2) * ROW_BYTES + i * 16, z);
            }
            fence_async_smem();
        }
        bar_sync(2, 128);
        const unsigned epoch = gs->epoch[cta * 32];

        float d[64];
#pragma unroll
        for (int i = 0; i < 64; i++) d[i] = 0.f;
#pragma unroll 1
        for (int conv = 0; conv < 2; conv++) {
            fence_acc(d);
            mma_stages<0>(d, conv, tid, gs);
            if (conv == 0) {
                asm volatile("wgmma.fence.sync.aligned;" ::: "memory");
                wgmma128<(SM_ONES >> 4) | (8u << 16), (SM_EMB >> 4), 0>(d);
                asm volatile("wgmma.commit_group.sync.aligned;" ::: "memory");
            }
            asm volatile("wgmma.wait_group.sync.aligned 0;" ::: "memory");
            fence_acc(d);
            if (tid == 0) TL(10 + conv * 8);
            if (conv == 1) break;

            uint32_t hp[32];
#pragma unroll
            for (int g = 0; g < 4; g++) {
                float c[4] = {0.f, 0.f, 0.f, 0.f};
#pragma unroll
                for (int i = 0; i < 8; i++) hp[8 * g + i] = pack_bf(d[16 * g + 2 * i], d[16 * g + 2 * i + 1]);
#pragma unroll
                for (int i = 0; i < 4; i++) stat_mma(c, hp[8 * g + 2 * i], hp[8 * g + 2 * i + 1]);
                stat_store(c, SM_RED + (g * 4 + wq) * 48, lane);
            }
            bar_sync(2, 128);
            if (wq == 0) stat_publish(SM_RED, &gs->acc[(NB + b) * 32], lane, true);
            if (tid == 0) TL(11);
            const uint32_t hbase = SM_ACT + (lane >> 4) * CH_PITCH + (2 + wq * 16 + (lane & 15)) * 16;
#pragma unroll
            for (int kc = 0; kc < 8; kc++) stsm4(hbase + kc * 2 * CH_PITCH, hp[4 * kc], hp[4 * kc + 1], hp[4 * kc + 2], hp[4 * kc + 3]);
            __syncwarp();
            if (lane == 0) mbar_arrive(BAR(BAR_HW));
            if (lane < LAG) mbar_arrive(BAR(BAR_WEMPTY + (NSTAGE - LAG) % NS) + 8 * lane);
            uint4* hg = gs->h + ((epoch & 1) * NCTA + cta) * 1024 + tid;
#pragma unroll
            for (int kc = 0; kc < 8; kc++) hg[kc * 128] = make_uint4(~hp[4 * kc], ~hp[4 * kc + 1], ~hp[4 * kc + 2], ~hp[4 * kc + 3]);
            if (tid == 0) TL(12);
            const uint32_t xbase = SM_XOWN + ((lane >> 4) * 8 + (lane & 7)) * 128 + (((2 * wq + ((lane >> 3) & 1)) ^ (lane & 7)) << 4);
#pragma unroll
            for (int kc = 0; kc < 8; kc++) {
                uint32_t p[4];
                ldsm4t(p, xbase + kc * 2048);
#pragma unroll
                for (int i = 0; i < 4; i++) { d[8 * kc + 2 * i] = bf_lo(p[i]); d[8 * kc + 2 * i + 1] = bf_hi(p[i]); }
            }
        }
        {
            const uint32_t obase = slot_addr(0) + ((lane >> 4) * 8 + (lane & 7)) * OUT_PITCH + (wq * 16 + ((lane >> 3) & 1) * 8) * 2;
#pragma unroll
            for (int kc = 0; kc < 8; kc++) {
                stsm4t(obase + kc * 16 * OUT_PITCH, pack_bf(d[8 * kc + 0], d[8 * kc + 1]), pack_bf(d[8 * kc + 2], d[8 * kc + 3]),
                       pack_bf(d[8 * kc + 4], d[8 * kc + 5]), pack_bf(d[8 * kc + 6], d[8 * kc + 7]));
            }
            bar_sync(2, 128);
            const int oc0 = tid >> 3;
            __nv_bfloat16* dst = out + ((size_t)(b * C + oc0) * HW + r) * HW + seg * 8;
#pragma unroll
            for (int i = 0; i < 8; i++)
                *reinterpret_cast<uint4*>(dst + (size_t)i * 16 * HW * HW) = lds128(slot_addr(0) + (oc0 + 16 * i) * OUT_PITCH + seg * 16);
            if (tid == 0) gs->epoch[cta * 32] = epoch + 1;
            if (tid == 0) { TL(20); TLG(21); }
        }
    } else if (warp < 6) {
        bar_sync(0, 96 + 128);
        if (warp == 5) {
#pragma unroll 1
            for (int i = 0; i < 24; i++) {
                const int pr = i < 12 ? i : i - 12;
                if (pr == 0) continue;
                mbar_wait(BAR(BAR_ACT) + 8 * pr, i >= 12);
                fence_async_smem();
                if (lane < 2) mbar_arrive(BAR(BAR_FULL) + 16 * pr + 8 * lane);
            }
        } else {
            while (clock32() - clk0 < W2DELAY) {}
            const char* w2s = reinterpret_cast<const char*>(w2) + woff;
#pragma unroll
            for (int k = 0; k < 4; k++) v[k] = __ldg(reinterpret_cast<const uint4*>(w2s + k * 256));
            if ((lane & 15) < 8) v[4] = __ldg(reinterpret_cast<const uint4*>(w2s + 1024));
            const uint2* wsrc = reinterpret_cast<const uint2*>(w_emb + (size_t)r * 12 * C) + lane;
            uint2 wv[12];
#pragma unroll
            for (int i = 0; i < 12; i++) wv[i] = __ldg(wsrc + i * (C / 4));
            float tv = 0.f;
            if (lane < 12) tv = __bfloat162float(t_emb[b * E + r * 12 + lane]);
            weight_block(v, SM_BNC + 2304, gs->wt + NSTAGE * STAGE_BYTES, cta, lane);
            const float sv = silu_half(0.5f * tv);
            float e0 = 0.f, e1 = 0.f, e2 = 0.f, e3 = 0.f;
#pragma unroll
            for (int i = 0; i < 12; i++) {
                const float sx = __shfl_sync(0xffffffffu, sv, i);
                e0 = fmaf(sx, bf_lo(wv[i].x), e0); e1 = fmaf(sx, bf_hi(wv[i].x), e1);
                e2 = fmaf(sx, bf_lo(wv[i].y), e2); e3 = fmaf(sx, bf_hi(wv[i].y), e3);
            }
            mbar_wait(BAR(BAR_WACQ), 0);
            red_add4(&gs->emb[b * C + lane * 4], e0, e1, e2, e3);
            __syncwarp();
            if (lane == 0) TL(13);
            if (lane < 2) asm volatile("red.release.gpu.global.add.u32 [%0], 1;" ::"l"(&gs->wcnt[(NB + lane) * 32]) : "memory");
            if (lane == 0) TL(14);
            unsigned it = 0;
            while (ld_relaxed(&gs->wcnt[(NB + b) * 32]) < (unsigned)NCTA && ++it < SPIN_LIMIT) {}
            fence_acquire();
            const uint4 ef = ld_relaxed_v4(&gs->emb[b * C + lane * 4]);
            const uint32_t eu[4] = {ef.x, ef.y, ef.z, ef.w};
#pragma unroll
            for (int i = 0; i < 4; i++) {
                const float e = __uint_as_float(eu[i]);
                const float hi = bf_lo(pack_bf(e, 0.f));
                sts128(SM_EMB + (lane * 4 + i) * 16, make_uint4(pack_bf(hi, e - hi), 0, 0, 0));
            }
            fence_async_smem();
            __syncwarp();
            if (lane == 0) { mbar_arrive(BAR(BAR_EMB)); TL(19); }
        }
    } else if (warp == 6) {
        bar_sync(0, 96 + 128);
        unsigned it = 0;
        while (ld_relaxed(&gs->wcnt[b * 32]) < (unsigned)NCTA && ++it < SPIN_LIMIT) {}
        fence_acquire();
        fence_async_global();
        if (lane == 0) { mbar_arrive(BAR(BAR_WACQ)); TL(6); }
        const unsigned char* wsrc = gs->wt;
#pragma unroll 1
        for (int round = 0; round < 2 * NSTAGE / NS; round++) {
            if (round == NSTAGE / NS) { mbar_wait(BAR(BAR_EMB), 0); fence_async_global(); }
            const uint32_t full = BAR(BAR_FULL) + 8 * NS * (round >= NSTAGE / NS ? round - NSTAGE / NS : round);
#pragma unroll
            for (int slot = 0; slot < NS; slot++) {
                if (slot == 9 && round == 0) mbar_wait(BAR(BAR_XFREE), 0);
                mbar_wait(BAR(BAR_WEMPTY + slot), (round & 1) ^ 1);
                if (elect_one()) {
                    mbar_expect(full + 8 * slot, STAGE_BYTES);
                    bulk_g2s(slot_addr(slot), wsrc + slot * STAGE_BYTES, STAGE_BYTES, full + 8 * slot);
                }
            }
            wsrc += NS * STAGE_BYTES;
        }
    } else {
        const uint2 ga1 = __ldg(reinterpret_cast<const uint2*>(g1) + lane), bt1 = __ldg(reinterpret_cast<const uint2*>(be1) + lane);
        const uint2 ga2 = __ldg(reinterpret_cast<const uint2*>(g2) + lane), bt2 = __ldg(reinterpret_cast<const uint2*>(be2) + lane);
        bar_sync(0, 96 + 128);
#pragma unroll 1
        for (int conv = 0; conv < 2; conv++) {
            if (conv == 1) mbar_wait(BAR(BAR_EMB), 0);
            const float* asrc = &gs->acc[(conv * NB + b) * 32 + (lane >> 3) * 4];
            uint4 f;
            unsigned it = 0;
            while (true) {
                f = ld_relaxed_v4(asrc);
                const bool ok = (f.x == 0x42800000u) & (f.w == 0x42800000u);
                if (__all_sync(0xffffffffu, ok) || ++it > SPIN_LIMIT) break;
            }
            if (lane == 0) TL(7 + conv * 8);
            const float inv_n = 1.0f / (32.0f * HW * HW);
            const float mean = __uint_as_float(f.y) * inv_n;
            const float var = fmaxf(fmaf(-mean, mean, __uint_as_float(f.z) * inv_n), 0.f);
            const float rs = 0.5f * rsqrtf(var + 1e-5f);
            const uint2 ga = conv ? ga2 : ga1, bt = conv ? bt2 : bt1;
            float4 k0, k1;
            k0.x = rs * bf_lo(ga.x); k0.y = rs * bf_hi(ga.x); k1.x = rs * bf_lo(ga.y); k1.y = rs * bf_hi(ga.y);
            k0.z = fmaf(-mean, k0.x, 0.5f * bf_lo(bt.x)); k0.w = fmaf(-mean, k0.y, 0.5f * bf_hi(bt.x));
            k1.z = fmaf(-mean, k1.x, 0.5f * bf_lo(bt.y)); k1.w = fmaf(-mean, k1.y, 0.5f * bf_hi(bt.y));
            sts128f(SM_COEF + lane * 32, k0);
            sts128f(SM_COEF + lane * 32 + 16, k1);
            __syncwarp();
            if (lane == 0) mbar_arrive(BAR(BAR_STATS));
        }
        if (r == 0) {
            if (lane < 16) gs->acc[b * 32 + lane] = 0.f;
            if (lane < 2) gs->wcnt[(lane * NB + b) * 32] = 0;
        }
    }
}

}

extern "C" void kernel_launch(void* const* d_in, const int* in_sizes, int n_in, void* d_out, int out_size) {
    (void)in_sizes; (void)n_in; (void)out_size;
    static Scratch* gs = nullptr;
    if (!gs) {
        cudaFuncSetAttribute(resblock_kernel, cudaFuncAttributeMaxDynamicSharedMemorySize, SM_TOTAL);
        cudaGetSymbolAddress((void**)&gs, g_scratch);
    }
    resblock_kernel<<<NCTA, NTHREADS, SM_TOTAL>>>(
        (const __nv_bfloat16*)d_in[0], (const __nv_bfloat16*)d_in[4], (const __nv_bfloat16*)d_in[1],
        (const __nv_bfloat16*)d_in[2], (const __nv_bfloat16*)d_in[3], (const __nv_bfloat16*)d_in[5],
        (const __nv_bfloat16*)d_in[6], (const __nv_bfloat16*)d_in[7], (const __nv_bfloat16*)d_in[8],
        (__nv_bfloat16*)d_out, gs);
}
```

```cpp
#include <cuda_runtime.h>
#include <cuda_bf16.h>
#include <stdint.h>

namespace {

constexpr int C = 128, HW = 64, NB = 2, E = 768;
constexpr int NCTA = NB * HW;
constexpr int NTHREADS = 16 * 32;
constexpr int CH_PITCH = 66 * 16;
constexpr int ROW_BYTES = 16 * CH_PITCH;
constexpr int STEP_BYTES = 4096;
constexpr int STAGE_BYTES = 3 * STEP_BYTES;
constexpr int NSTAGE = 24;
constexpr int NS = 12;
constexpr int LAG = 1;
#define XDELAY 600
#define HDELAY 500
#define PUB1 2
#define FETCH_AT 2
#define W2DELAY 2800

constexpr uint32_t SMEM_BASE = 0x400;
constexpr uint32_t SM_ACT = SMEM_BASE;
constexpr uint32_t SM_XOWN = SM_ACT + 3 * ROW_BYTES + 128;
constexpr uint32_t SM_W = SM_XOWN + 16384;
constexpr uint32_t SM_XH = SM_W;
__host__ __device__ constexpr uint32_t slot_addr(int slot) { return SM_W + ((slot + 3) % NS) * STAGE_BYTES; }
constexpr uint32_t SM_COEF = SM_W + NS * STAGE_BYTES;
constexpr uint32_t SM_EMB = SM_COEF + 1024;
constexpr uint32_t SM_ONES = SM_EMB + 2048;
constexpr uint32_t SM_RED = SM_ONES + 256;
constexpr uint32_t SM_BNC = SM_RED + 1280;
constexpr uint32_t SM_BAR = SM_BNC + 2 * 2304;
constexpr int BAR_FULL = 0, BAR_WEMPTY = NSTAGE, BAR_HW = BAR_WEMPTY + NS, BAR_STATS = BAR_HW + 1,
              BAR_EMB = BAR_STATS + 1, BAR_WACQ = BAR_EMB + 1, BAR_XH = BAR_WACQ + 1, BAR_XFREE = BAR_XH + 1,
              BAR_ACT = BAR_XFREE + 1  , NBAR = BAR_ACT + 12;
constexpr int SM_TOTAL = SM_BAR + NBAR * 8 - SMEM_BASE;
static_assert(SM_TOTAL <= 232448, "smem");
static_assert(NBAR <= 96, "barrier init");
constexpr int OUT_PITCH = 144;
__host__ __device__ constexpr uint32_t BAR(int i) { return SM_BAR + 8 * i; }
__host__ __device__ constexpr int ky_of(int kyo) { return kyo == 0 ? 1 : (kyo == 1 ? 0 : 2); }

constexpr unsigned SPIN_LIMIT = 1u << 16;

struct Scratch {
    float acc[2 * NB * 32];
    unsigned wcnt[2 * NB * 32];
    float emb[NB * C];
    unsigned char wt[2 * NSTAGE * STAGE_BYTES];
    unsigned epoch[NCTA * 32];
    uint4 h[2 * NCTA * 1024];
};
__device__ __align__(1024) Scratch g_scratch;
#define TL(i) do {} while (0)
#define TLG(i) do {} while (0)

__device__ __forceinline__ unsigned clock32() { unsigned c; asm volatile("mov.u32 %0, %%clock;" : "=r"(c)); return c; }
__device__ __forceinline__ void mbar_init(uint32_t bar, int cnt) {
    asm volatile("mbarrier.init.shared::cta.b64 [%0], %1;" ::"r"(bar), "r"(cnt) : "memory");
}
__device__ __forceinline__ void mbar_arrive(uint32_t bar) {
    asm volatile("mbarrier.arrive.shared::cta.b64 _, [%0];" ::"r"(bar) : "memory");
}
__device__ __forceinline__ void mbar_expect(uint32_t bar, uint32_t bytes) {
    asm volatile("mbarrier.arrive.expect_tx.shared::cta.b64 _, [%0], %1;" ::"r"(bar), "r"(bytes) : "memory");
}
__device__ __forceinline__ bool mbar_try(uint32_t bar, uint32_t par) {
    uint32_t ok;
    asm volatile("{\n.reg .pred p;\nmbarrier.try_wait.parity.shared::cta.b64 p, [%1], %2;\nselp.u32 %0, 1, 0, p;\n}"
                 : "=r"(ok) : "r"(bar), "r"(par) : "memory");
    return ok;
}
__device__ __forceinline__ bool mbar_test(uint32_t bar, uint32_t par) {
    uint32_t ok;
    asm volatile("{\n.reg .pred p;\nmbarrier.test_wait.parity.shared::cta.b64 p, [%1], %2;\nselp.u32 %0, 1, 0, p;\n}"
                 : "=r"(ok) : "r"(bar), "r"(par) : "memory");
    return ok;
}
__device__ __forceinline__ void mbar_wait(uint32_t bar, uint32_t par) {
    unsigned it = 0;
#pragma unroll 1
    while (!mbar_try(bar, par) && ++it < SPIN_LIMIT) {}
}
__device__ __forceinline__ bool elect_one() {
    uint32_t p;
    asm volatile("{\n.reg .pred p;\nelect.sync _|p, 0xffffffff;\nselp.u32 %0, 1, 0, p;\n}" : "=r"(p));
    return p;
}
__device__ __forceinline__ void fence_async_smem() { asm volatile("fence.proxy.async.shared::cta;" ::: "memory"); }
__device__ __forceinline__ void fence_async_global() { asm volatile("fence.proxy.async.global;" ::: "memory"); }
__device__ __forceinline__ void fence_acquire() { asm volatile("fence.acquire.gpu;" ::: "memory"); }
__device__ __forceinline__ void bar_sync(int id, int n) { asm volatile("bar.sync %0, %1;" ::"r"(id), "r"(n) : "memory"); }
__device__ __forceinline__ void bar_arrive(int id, int n) { asm volatile("bar.arrive %0, %1;" ::"r"(id), "r"(n) : "memory"); }
__device__ __forceinline__ void bulk_g2s(uint32_t dst, const void* src, uint32_t bytes, uint32_t bar) {
    asm volatile("cp.async.bulk.shared::cluster.global.mbarrier::complete_tx::bytes [%0], [%1], %2, [%3];"
                 ::"r"(dst), "l"(src), "r"(bytes), "r"(bar) : "memory");
}
__device__ __forceinline__ uint4 ld_relaxed_v4(const void* p) {
    uint4 v;
    asm volatile("ld.relaxed.gpu.global.v4.u32 {%0,%1,%2,%3}, [%4];" : "=r"(v.x), "=r"(v.y), "=r"(v.z), "=r"(v.w) : "l"(p) : "memory");
    return v;
}
__device__ __forceinline__ unsigned ld_relaxed(const void* p) {
    unsigned v;
    asm volatile("ld.relaxed.gpu.global.u32 %0, [%1];" : "=r"(v) : "l"(p) : "memory");
    return v;
}
__device__ __forceinline__ void red_add4(float* p, float a, float b, float c, float d) {
    asm volatile("red.relaxed.gpu.global.add.v4.f32 [%0], {%1,%2,%3,%4};" ::"l"(p), "f"(a), "f"(b), "f"(c), "f"(d) : "memory");
}
__device__ __forceinline__ void sts128(uint32_t a, uint4 v) {
    asm volatile("st.shared.v4.u32 [%0], {%1,%2,%3,%4};" ::"r"(a), "r"(v.x), "r"(v.y), "r"(v.z), "r"(v.w) : "memory");
}
__device__ __forceinline__ void sts128f(uint32_t a, float4 v) {
    asm volatile("st.shared.v4.f32 [%0], {%1,%2,%3,%4};" ::"r"(a), "f"(v.x), "f"(v.y), "f"(v.z), "f"(v.w) : "memory");
}
__device__ __forceinline__ void sts32f(uint32_t a, float v) { asm volatile("st.shared.f32 [%0], %1;" ::"r"(a), "f"(v) : "memory"); }
__device__ __forceinline__ uint4 lds128(uint32_t a) {
    uint4 v;
    asm volatile("ld.shared.v4.u32 {%0,%1,%2,%3}, [%4];" : "=r"(v.x), "=r"(v.y), "=r"(v.z), "=r"(v.w) : "r"(a) : "memory");
    return v;
}
__device__ __forceinline__ float4 lds128f(uint32_t a) {
    float4 v;
    asm volatile("ld.shared.v4.f32 {%0,%1,%2,%3}, [%4];" : "=f"(v.x), "=f"(v.y), "=f"(v.z), "=f"(v.w) : "r"(a) : "memory");
    return v;
}
__device__ __forceinline__ float2 lds64f(uint32_t a) {
    float2 v;
    asm volatile("ld.shared.v2.f32 {%0,%1}, [%2];" : "=f"(v.x), "=f"(v.y) : "r"(a) : "memory");
    return v;
}
__device__ __forceinline__ float bf_lo(uint32_t u) { return __uint_as_float(u << 16); }
__device__ __forceinline__ float bf_hi(uint32_t u) { return __uint_as_float(u & 0xffff0000u); }
__device__ __forceinline__ uint32_t pack_bf(float lo, float hi) {
    uint32_t r;
    asm("cvt.rn.bf16x2.f32 %0, %1, %2;" : "=r"(r) : "f"(hi), "f"(lo));
    return r;
}
__device__ __forceinline__ float tanh_fast(float x) {
    float r;
    asm("tanh.approx.f32 %0, %1;" : "=f"(r) : "f"(x));
    return r;
}
__device__ __forceinline__ float silu_half(float h) { return fmaf(h, tanh_fast(h), h); }
__device__ __forceinline__ void ldsm4(uint32_t (&u)[4], uint32_t a) {
    asm volatile("ldmatrix.sync.aligned.m8n8.x4.shared.b16 {%0,%1,%2,%3}, [%4];"
                 : "=r"(u[0]), "=r"(u[1]), "=r"(u[2]), "=r"(u[3]) : "r"(a) : "memory");
}
__device__ __forceinline__ void ldsm4t(uint32_t (&u)[4], uint32_t a) {
    asm volatile("ldmatrix.sync.aligned.m8n8.x4.trans.shared.b16 {%0,%1,%2,%3}, [%4];"
                 : "=r"(u[0]), "=r"(u[1]), "=r"(u[2]), "=r"(u[3]) : "r"(a) : "memory");
}
__device__ __forceinline__ void stsm4(uint32_t a, uint32_t p0, uint32_t p1, uint32_t p2, uint32_t p3) {
    asm volatile("stmatrix.sync.aligned.m8n8.x4.shared.b16 [%0], {%1,%2,%3,%4};" ::"r"(a), "r"(p0), "r"(p1), "r"(p2), "r"(p3) : "memory");
}
__device__ __forceinline__ void stsm4t(uint32_t a, uint32_t p0, uint32_t p1, uint32_t p2, uint32_t p3) {
    asm volatile("stmatrix.sync.aligned.m8n8.x4.trans.shared.b16 [%0], {%1,%2,%3,%4};" ::"r"(a), "r"(p0), "r"(p1), "r"(p2), "r"(p3) : "memory");
}

#define R8(o) "+f"(d[o]), "+f"(d[o + 1]), "+f"(d[o + 2]), "+f"(d[o + 3]), "+f"(d[o + 4]), "+f"(d[o + 5]), "+f"(d[o + 6]), "+f"(d[o + 7])
template <uint32_t ALO, uint32_t BLO, uint64_t AHI = 8>
__device__ __forceinline__ void wgmma128(float (&d)[64]) {
    asm volatile(
        "wgmma.mma_async.sync.aligned.m64n128k16.f32.bf16.bf16 "
        "{%0,%1,%2,%3,%4,%5,%6,%7,%8,%9,%10,%11,%12,%13,%14,%15,%16,%17,%18,%19,%20,%21,%22,%23,%24,%25,%26,%27,%28,%29,%30,%31,"
        "%32,%33,%34,%35,%36,%37,%38,%39,%40,%41,%42,%43,%44,%45,%46,%47,%48,%49,%50,%51,%52,%53,%54,%55,%56,%57,%58,%59,%60,%61,%62,%63},"
        " %64, %65, 1, 1, 1, 0, 0;"
        : R8(0), R8(8), R8(16), R8(24), R8(32), R8(40), R8(48), R8(56)
        : "l"((AHI << 32) | ALO), "l"((8ull << 32) | BLO));
}
template <int S>
__device__ __forceinline__ void mma_stages(float (&d)[64], int conv, int tid, Scratch* gs) {
    constexpr uint32_t A = ((SM_ACT + S * 2 * CH_PITCH + 16) >> 4) | ((CH_PITCH >> 4) << 16);
    constexpr uint32_t B = (slot_addr(S % NS) >> 4) | ((2048 >> 4) << 16);
    if (S == 0) mbar_wait(BAR(BAR_FULL), conv);
    bool next_ok = true;
    constexpr uint32_t NEXT = S + 1 < NSTAGE ? BAR(BAR_FULL + S + 1) : BAR(BAR_EMB);
    const int npar = S + 1 < NSTAGE ? conv : 0;
    next_ok = mbar_test(NEXT, npar);
    if (S == 0 && tid == 0) TL(32 + conv * 24);
    asm volatile("wgmma.fence.sync.aligned;" ::: "memory");
    wgmma128<A, B>(d);
    wgmma128<A + 1, B + (STEP_BYTES >> 4)>(d);
    wgmma128<A + 2, B + 2 * (STEP_BYTES >> 4)>(d);
    asm volatile("wgmma.commit_group.sync.aligned;" ::: "memory");
    if (S >= LAG) {
        asm volatile("wgmma.wait_group.sync.aligned %0;" ::"n"(LAG) : "memory");
        if ((tid & 31) == 0) mbar_arrive(BAR(BAR_WEMPTY + (S + NS - LAG) % NS));
    }
    if (!next_ok) mbar_wait(NEXT, npar);
    if constexpr (S + 1 < NSTAGE) mma_stages<S + 1>(d, conv, tid, gs);
}

__device__ __forceinline__ void weight_block(const uint4 (&t)[5], uint32_t bounce, unsigned char* wt, int cta, int lane) {
    const uint32_t bw = bounce + (lane >> 4) * 1152 + (lane & 15) * 16;
#pragma unroll
    for (int k = 0; k < 4; k++) sts128(bw + k * 256, t[k]);
    if ((lane & 15) < 8) sts128(bw + 1024, t[4]);
    __syncwarp();
    if (lane < 16) {
        uint32_t v[36];
#pragma unroll
        for (int i = 0; i < 9; i++) {
            const uint4 q = lds128(bounce + (lane & 1) * 1152 + (lane >> 1) * 144 + i * 16);
            v[4 * i] = q.x; v[4 * i + 1] = q.y; v[4 * i + 2] = q.z; v[4 * i + 3] = q.w;
        }
        const int cc = (cta >> 6) * 8 + (lane >> 1);
        unsigned char* dst = wt + (cc >> 1) * STAGE_BYTES + (cc & 1) * 2048 + ((cta & 63) * 2 + (lane & 1)) * 16;
#pragma unroll
        for (int kyo = 0; kyo < 3; kyo++) {
#pragma unroll
            for (int kx = 0; kx < 3; kx++) {
                const int tap = ky_of(kyo) * 3 + kx;
                uint32_t o[4];
#pragma unroll
                for (int m = 0; m < 4; m++) {
                    const int i0 = 18 * m + tap, i1 = i0 + 9;
                    const uint32_t sel = ((i0 & 1) ? 0x32u : 0x10u) | ((i1 & 1) ? 0x7600u : 0x5400u);
                    o[m] = __byte_perm(v[i0 >> 1], v[i1 >> 1], sel);
                }
                *reinterpret_cast<uint4*>(dst + (kyo * 24 + kx) * STEP_BYTES) = make_uint4(o[0], o[1], o[2], o[3]);
            }
        }
    }
}
__device__ __forceinline__ uint32_t act2(uint32_t u, const float4& cf) {
    return pack_bf(silu_half(fmaf(bf_lo(u), cf.x, cf.z)), silu_half(fmaf(bf_hi(u), cf.y, cf.w)));
}
__device__ __forceinline__ void norm_unit(uint32_t (&u)[4], const float4& ca, const float4& cb) {
    u[0] = act2(u[0], ca); u[1] = act2(u[1], ca); u[2] = act2(u[2], cb); u[3] = act2(u[3], cb);
}
__device__ __forceinline__ void stsm4_arrive(uint32_t a, const uint32_t (&u)[4], uint32_t mask, uint32_t bar, int lane) {
    asm volatile("{\n.reg .pred p;\nsetp.eq.s32 p, %6, 0;\n"
                 "stmatrix.sync.aligned.m8n8.x4.shared.b16 [%0], {%1,%2,%3,%4};\n"
                 "@p mbarrier.arrive.shared::cta.b64 _, [%5];\n}"
                 ::"r"(a), "r"(u[0] & mask), "r"(u[1] & mask), "r"(u[2] & mask), "r"(u[3] & mask), "r"(bar), "r"(lane) : "memory");
}
__device__ __forceinline__ void publish(uint32_t bar, int lane) {
    fence_async_smem();
    __syncwarp();
    if (lane == 0) mbar_arrive(bar);
}
__device__ __forceinline__ void publish2(uint32_t bar, int lane) {
    fence_async_smem();
    __syncwarp();
    if (lane < 2) mbar_arrive(bar + 8 * lane);
}
__device__ __forceinline__ void stat_mma(float (&c)[4], uint32_t p, uint32_t q) {
    asm("mma.sync.aligned.m16n8k16.row.col.f32.bf16.bf16.f32 {%0,%1,%2,%3}, {%4,%5,%6,%5}, {%4,%6}, {%0,%1,%2,%3};"
        : "+f"(c[0]), "+f"(c[1]), "+f"(c[2]), "+f"(c[3]) : "r"(p), "r"(0x3f803f80u), "r"(q));
}
__device__ __forceinline__ void stat_store(const float (&c)[4], uint32_t dst, int lane) {
    const int g = lane >> 2, t = lane & 3;
    if (t == (g >> 1)) sts32f(dst + g * 4, (g & 1) ? c[1] : c[0]);
    if (g == 7) sts32f(dst + 32 + t * 4, c[2] + c[3]);
}
__device__ __forceinline__ float sum4(float4 v) { return (v.x + v.y) + (v.z + v.w); }
__device__ __forceinline__ void stat_publish(uint32_t src, float* acc, int lane, bool real) {
    const uint32_t a = src + (lane & 15) * 48;
    float q = sum4(lds128f(a)) + sum4(lds128f(a + 16)), sm = sum4(lds128f(a + 32));
    q += __shfl_xor_sync(0xffffffffu, q, 1); sm += __shfl_xor_sync(0xffffffffu, sm, 1);
    q += __shfl_xor_sync(0xffffffffu, q, 2); sm += __shfl_xor_sync(0xffffffffu, sm, 2);
    if (real && (lane & 19) == 0) red_add4(acc + lane, 1.f, sm, q, 1.f);
}
__device__ __forceinline__ void fence_acc(float (&d)[64]) {
#pragma unroll
    for (int i = 0; i < 64; i++) asm volatile("" : "+f"(d[i])::"memory");
}
__device__ __forceinline__ void ld_unit(uint32_t (&u)[4], const uint4* p) {
    asm volatile("ld.relaxed.gpu.global.v4.u32 {%0,%1,%2,%3}, [%4];" : "=r"(u[0]), "=r"(u[1]), "=r"(u[2]), "=r"(u[3]) : "l"(p) : "memory");
}

__global__ void __launch_bounds__(NTHREADS, 1)
resblock_kernel(const __nv_bfloat16* __restrict__ x, const __nv_bfloat16* __restrict__ w1,
                const __nv_bfloat16* __restrict__ t_emb, const __nv_bfloat16* __restrict__ g1,
                const __nv_bfloat16* __restrict__ be1, const __nv_bfloat16* __restrict__ w_emb,
                const __nv_bfloat16* __restrict__ g2, const __nv_bfloat16* __restrict__ be2,
                const __nv_bfloat16* __restrict__ w2, __nv_bfloat16* __restrict__ out, Scratch* __restrict__ gs) {
    const unsigned clk0 = clock32();
    const int tid = threadIdx.x, warp = tid >> 5, lane = tid & 31;
    const int cta = blockIdx.x, b = cta >> 6, r = cta & 63;

    const uint32_t woff = ((2 * r + (lane >> 4)) * C + b * 64) * 18 + (lane & 15) * 16;
    const int c0 = (warp - 8) * 16 + (lane >> 3), seg = lane & 7;
    uint4 v[5];
    if (warp == 0) {
        const char* w1s = reinterpret_cast<const char*>(w1) + woff;
#pragma unroll
        for (int k = 0; k < 4; k++) v[k] = __ldg(reinterpret_cast<const uint4*>(w1s + k * 256));
        if ((lane & 15) < 8) v[4] = __ldg(reinterpret_cast<const uint4*>(w1s + 1024));
    }
    const bool loader = warp >= 8;
    if (loader || warp == 5) {
        if (loader) {
            const char* src = reinterpret_cast<const char*>(x) + (uint32_t)(((b * C + c0) * HW + r) * HW * 2 + seg * 16);
            while (clock32() - clk0 < XDELAY) {}
#pragma unroll
            for (int k = 0; k < 4; k++) v[k] = __ldg(reinterpret_cast<const uint4*>(src + k * (4 * HW * HW * 2)));
#pragma unroll
            for (int i = 0; i < 8; i++) {
                if (i < 4 ? (r != 0) : (r != HW - 1))
                    asm volatile("cp.async.cg.shared.global [%0], [%1], 16;"
                                 ::"r"(SM_XH + (i >> 2) * 16384 + c0 * 128 + (i & 3) * 512 + ((seg ^ ((c0 + 4 * i) & 7)) << 4)),
                                   "l"(src + (i < 4 ? -HW * 2 : HW * 2) + (i & 3) * (4 * HW * HW * 2)) : "memory");
            }
        } else {
#pragma unroll
            for (int k = 0; k < 4; k++) v[k] = make_uint4(0, 0, 0, 0);
        }
        float c[2][4] = {{0.f, 0.f, 0.f, 0.f}, {0.f, 0.f, 0.f, 0.f}};
#pragma unroll
        for (int k = 0; k < 4; k++) { stat_mma(c[0], v[k].x, v[k].y); stat_mma(c[1], v[k].z, v[k].w); }
        stat_store(c[0], SM_RED + (warp & 7) * 96 + (loader ? 0 : 384), lane);
        stat_store(c[1], SM_RED + (warp & 7) * 96 + 48 + (loader ? 0 : 384), lane);
        if (tid == 256) TL(2);
        if (loader) bar_sync(3, 256);
        if (warp <= 8) stat_publish(SM_RED, &gs->acc[b * 32], lane, warp == 8);
        if (tid == 256) TL(3);
        if (loader) {
#pragma unroll
            for (int i = 0; i < 4; i++) sts128(SM_XOWN + c0 * 128 + i * 512 + ((seg ^ ((c0 + 4 * i) & 7)) << 4), v[i]);
        }
    }
    if (warp == 0) {
        weight_block(v, SM_BNC, gs->wt, cta, lane);
        if (r == 0) {
            if (lane < 16) gs->acc[(NB + b) * 32 + lane] = 0.f;
            *reinterpret_cast<float4*>(&gs->emb[b * C + lane * 4]) = make_float4(0.f, 0.f, 0.f, 0.f);
        }
        __syncwarp();
        if (lane == 0) TL(4);
        if (lane < 2) asm volatile("red.release.gpu.global.add.u32 [%0], 1;" ::"l"(&gs->wcnt[lane * 32]) : "memory");
        if (lane == 0) TL(5);
    }

    if (warp >= 8) {
        const int nw = warp - 8;
        asm volatile("cp.async.wait_all;" ::: "memory");
        bar_sync(4, 256 + 96);
        const int par = nw >> 2, wq = nw & 3;
        const unsigned epoch = gs->epoch[cta * 32];
        const uint32_t act_off = SM_ACT + (par * 2 + (lane >> 4)) * CH_PITCH + (2 + wq * 16 + (lane & 15)) * 16;
        const uint32_t stg_off = SM_XOWN + (par * 16 + (lane >> 4) * 8 + (lane & 7)) * 128 + (((2 * wq + ((lane >> 3) & 1)) ^ (lane & 7)) << 4);
        const uint32_t cfa = SM_COEF + par * 128 + (lane & 3) * 16;
        const uint4* hrow = gs->h + ((epoch & 1) * NCTA + cta) * 1024 + nw * 32 + lane;
        const uint32_t mask_up = r != 0 ? ~0u : 0u, mask_dn = r != HW - 1 ? ~0u : 0u;
        const uint4* hu = hrow - (r != 0 ? 1024 : 0);
        const uint4* hd = hrow + (r != HW - 1 ? 1024 : 0);
#pragma unroll 1
        for (int conv = 0; conv < 2; conv++) {
            uint32_t u[12][4];
            float4 cf[8];
            if (conv == 0) {
#pragma unroll
                for (int i = 0; i < 12; i++) ldsm4t(u[i], stg_off + i * 4096);
                publish(BAR(BAR_XFREE), lane);
            } else {
                mbar_wait(BAR(BAR_HW), 0);
#pragma unroll
                for (int i = 0; i < 4; i++) ldsm4(u[i], act_off + i * 4 * CH_PITCH);
            }
            mbar_wait(BAR(BAR_STATS), conv);
            if (tid == 256) TL(22 + conv * 4);
            cf[0] = lds128f(cfa); cf[1] = lds128f(cfa + 64);
            norm_unit(u[0], cf[0], cf[1]);
            stsm4(act_off, u[0][0], u[0][1], u[0][2], u[0][3]);
            publish(BAR(BAR_FULL) + 8 * par, lane);
            if (tid == 256) TL(8 + conv * 8);
#pragma unroll
            for (int i = 2; i < 8; i++) cf[i] = lds128f(cfa + (i >> 1) * 256 + (i & 1) * 64);
            if (conv == 1) {
#pragma unroll
                for (int i = 0; i < 4; i++) { ld_unit(u[4 + i], hu + i * 256); ld_unit(u[8 + i], hd + i * 256); }
            }
#pragma unroll
            for (int t = 1; t < 4; t++) {
                norm_unit(u[t], cf[2 * t], cf[2 * t + 1]);
                stsm4_arrive(act_off + t * 4 * CH_PITCH, u[t], ~0u, BAR(BAR_ACT + t), lane);
            }
            if (tid == 256) TL(84 + conv);
            if (conv == 1) {
                unsigned it = 0;
                while (true) {
                    bool ok = true;
#pragma unroll
                    for (int i = 0; i < 32; i++) ok = ok && u[4 + (i >> 2)][i & 3] != 0;
                    if (__all_sync(0xffffffffu, ok) || ++it > SPIN_LIMIT) break;
#pragma unroll
                    for (int i = 0; i < 4; i++) { ld_unit(u[4 + i], hu + i * 256); ld_unit(u[8 + i], hd + i * 256); }
                }
#pragma unroll
                for (int i = 0; i < 32; i++) u[4 + (i >> 2)][i & 3] = ~u[4 + (i >> 2)][i & 3];
                if (tid == 256) TL(28);
            }
#pragma unroll
            for (int t = 4; t < 12; t++) {
                norm_unit(u[t], cf[2 * (t & 3)], cf[2 * (t & 3) + 1]);
                stsm4_arrive(act_off + t * 4 * CH_PITCH, u[t], t < 8 ? mask_up : mask_dn, BAR(BAR_ACT + t), lane);
            }
            if (tid == 256) TL(23 + conv * 4);
        }
        uint4* hz = gs->h + (((epoch + 1) & 1) * NCTA + cta) * 1024 + (tid - 256);
#pragma unroll
        for (int i = 0; i < 4; i++) hz[i * 256] = make_uint4(0, 0, 0, 0);
    } else if (warp < 4) {
        const int wq = warp;
        if (wq != 0) {
            const int t = tid - 32;
            if (lane == 0) {
                if (wq == 1) {
#pragma unroll
                    for (int i = 0; i < 18; i++) mbar_init(BAR(BAR_FULL + i), i < 2 ? 5 : 2);
                } else if (wq == 2) {
#pragma unroll
                    for (int i = 18; i < NSTAGE; i++) mbar_init(BAR(BAR_FULL + i), 2);
#pragma unroll
                    for (int i = 0; i < 12; i++) mbar_init(BAR(BAR_ACT + i), 8);
                } else {
#pragma unroll
                    for (int i = 0; i <= NS; i++) mbar_init(BAR(BAR_WEMPTY + i), 4);
#pragma unroll
                    for (int i = BAR_STATS; i < BAR_XFREE; i++) mbar_init(BAR(i), 1);
                    mbar_init(BAR(BAR_XFREE), 8);
                }
            }
            fence_async_smem();
            bar_arrive(0, 96 + 128);
            bar_arrive(4, 256 + 96);
            if (t == 95) TLG(1);
            const uint4 z = make_uint4(0, 0, 0, 0);
            sts128(SM_ACT + (t >> 1) * CH_PITCH + (t & 1) * 16, z);
            if (t < 2) sts128(SM_ACT + 3 * ROW_BYTES + t * 16, z);
            if (t < 16) sts128(SM_ONES + t * 16, make_uint4(t < 8 ? 0x3f803f80u : 0u, 0, 0, 0));
            fence_async_smem();
        }
        bar_sync(2, 128);
        const unsigned epoch = gs->epoch[cta * 32];

        float d[64];
#pragma unroll
        for (int i = 0; i < 64; i++) d[i] = 0.f;
#pragma unroll 1
        for (int conv = 0; conv < 2; conv++) {
            fence_acc(d);
            mma_stages<0>(d, conv, tid, gs);
            if (conv == 0) {
                asm volatile("wgmma.fence.sync.aligned;" ::: "memory");
                wgmma128<(SM_ONES >> 4) | (8u << 16), (SM_EMB >> 4), 0>(d);
                asm volatile("wgmma.commit_group.sync.aligned;" ::: "memory");
            }
            asm volatile("wgmma.wait_group.sync.aligned 0;" ::: "memory");
            fence_acc(d);
            if (tid == 0) TL(10 + conv * 8);
            if (conv == 1) break;

            uint32_t hp[32];
#pragma unroll
            for (int g = 0; g < 4; g++) {
                float c[4] = {0.f, 0.f, 0.f, 0.f};
#pragma unroll
                for (int i = 0; i < 8; i++) hp[8 * g + i] = pack_bf(d[16 * g + 2 * i], d[16 * g + 2 * i + 1]);
#pragma unroll
                for (int i = 0; i < 4; i++) stat_mma(c, hp[8 * g + 2 * i], hp[8 * g + 2 * i + 1]);
                stat_store(c, SM_RED + (g * 4 + wq) * 48, lane);
            }
            bar_sync(2, 128);
            if (wq == 0) stat_publish(SM_RED, &gs->acc[(NB + b) * 32], lane, true);
            if (tid == 0) TL(11);
            const uint32_t hbase = SM_ACT + (lane >> 4) * CH_PITCH + (2 + wq * 16 + (lane & 15)) * 16;
#pragma unroll
            for (int kc = 0; kc < 8; kc++) stsm4(hbase + kc * 2 * CH_PITCH, hp[4 * kc], hp[4 * kc + 1], hp[4 * kc + 2], hp[4 * kc + 3]);
            __syncwarp();
            if (lane == 0) mbar_arrive(BAR(BAR_HW));
            if (lane < LAG) mbar_arrive(BAR(BAR_WEMPTY + (NSTAGE - LAG) % NS) + 8 * lane);
            uint4* hg = gs->h + ((epoch & 1) * NCTA + cta) * 1024 + tid;
#pragma unroll
            for (int kc = 0; kc < 8; kc++) hg[kc * 128] = make_uint4(~hp[4 * kc], ~hp[4 * kc + 1], ~hp[4 * kc + 2], ~hp[4 * kc + 3]);
            if (tid == 0) TL(12);
            const uint32_t xbase = SM_XOWN + ((lane >> 4) * 8 + (lane & 7)) * 128 + (((2 * wq + ((lane >> 3) & 1)) ^ (lane & 7)) << 4);
#pragma unroll
            for (int kc = 0; kc < 8; kc++) {
                uint32_t p[4];
                ldsm4t(p, xbase + kc * 2048);
#pragma unroll
                for (int i = 0; i < 4; i++) { d[8 * kc + 2 * i] = bf_lo(p[i]); d[8 * kc + 2 * i + 1] = bf_hi(p[i]); }
            }
        }
        {
            const uint32_t obase = slot_addr(0) + ((lane >> 4) * 8 + (lane & 7)) * OUT_PITCH + (wq * 16 + ((lane >> 3) & 1) * 8) * 2;
#pragma unroll
            for (int kc = 0; kc < 8; kc++) {
                stsm4t(obase + kc * 16 * OUT_PITCH, pack_bf(d[8 * kc + 0], d[8 * kc + 1]), pack_bf(d[8 * kc + 2], d[8 * kc + 3]),
                       pack_bf(d[8 * kc + 4], d[8 * kc + 5]), pack_bf(d[8 * kc + 6], d[8 * kc + 7]));
            }
            bar_sync(2, 128);
            const int oc0 = tid >> 3;
            __nv_bfloat16* dst = out + ((size_t)(b * C + oc0) * HW + r) * HW + seg * 8;
#pragma unroll
            for (int i = 0; i < 8; i++)
                *reinterpret_cast<uint4*>(dst + (size_t)i * 16 * HW * HW) = lds128(slot_addr(0) + (oc0 + 16 * i) * OUT_PITCH + seg * 16);
            if (tid == 0) gs->epoch[cta * 32] = epoch + 1;
            if (tid == 0) { TL(20); TLG(21); }
        }
    } else if (warp < 6) {
        bar_sync(0, 96 + 128);
        if (warp == 5) {
#pragma unroll 1
            for (int i = 0; i < 24; i++) {
                const int pr = i < 12 ? i : i - 12;
                if (pr == 0) continue;
                mbar_wait(BAR(BAR_ACT) + 8 * pr, i >= 12);
                fence_async_smem();
                if (lane < 2) mbar_arrive(BAR(BAR_FULL) + 16 * pr + 8 * lane);
            }
        } else {
            while (clock32() - clk0 < W2DELAY) {}
            const char* w2s = reinterpret_cast<const char*>(w2) + woff;
#pragma unroll
            for (int k = 0; k < 4; k++) v[k] = __ldg(reinterpret_cast<const uint4*>(w2s + k * 256));
            if ((lane & 15) < 8) v[4] = __ldg(reinterpret_cast<const uint4*>(w2s + 1024));
            const uint2* wsrc = reinterpret_cast<const uint2*>(w_emb + (size_t)r * 12 * C) + lane;
            uint2 wv[12];
#pragma unroll
            for (int i = 0; i < 12; i++) wv[i] = __ldg(wsrc + i * (C / 4));
            float tv = 0.f;
            if (lane < 12) tv = __bfloat162float(t_emb[b * E + r * 12 + lane]);
            weight_block(v, SM_BNC + 2304, gs->wt + NSTAGE * STAGE_BYTES, cta, lane);
            const float sv = silu_half(0.5f * tv);
            float e0 = 0.f, e1 = 0.f, e2 = 0.f, e3 = 0.f;
#pragma unroll
            for (int i = 0; i < 12; i++) {
                const float sx = __shfl_sync(0xffffffffu, sv, i);
                e0 = fmaf(sx, bf_lo(wv[i].x), e0); e1 = fmaf(sx, bf_hi(wv[i].x), e1);
                e2 = fmaf(sx, bf_lo(wv[i].y), e2); e3 = fmaf(sx, bf_hi(wv[i].y), e3);
            }
            mbar_wait(BAR(BAR_WACQ), 0);
            red_add4(&gs->emb[b * C + lane * 4], e0, e1, e2, e3);
            __syncwarp();
            if (lane == 0) TL(13);
            if (lane < 2) asm volatile("red.release.gpu.global.add.u32 [%0], 1;" ::"l"(&gs->wcnt[(NB + lane) * 32]) : "memory");
            if (lane == 0) TL(14);
            unsigned it = 0;
            while (ld_relaxed(&gs->wcnt[(NB + b) * 32]) < (unsigned)NCTA && ++it < SPIN_LIMIT) {}
            fence_acquire();
            const uint4 ef = ld_relaxed_v4(&gs->emb[b * C + lane * 4]);
            const uint32_t eu[4] = {ef.x, ef.y, ef.z, ef.w};
#pragma unroll
            for (int i = 0; i < 4; i++) {
                const float e = __uint_as_float(eu[i]);
                const float hi = bf_lo(pack_bf(e, 0.f));
                sts128(SM_EMB + (lane * 4 + i) * 16, make_uint4(pack_bf(hi, e - hi), 0, 0, 0));
            }
            fence_async_smem();
            __syncwarp();
            if (lane == 0) { mbar_arrive(BAR(BAR_EMB)); TL(19); }
        }
    } else if (warp == 6) {
        bar_sync(0, 96 + 128);
        unsigned it = 0;
        while (ld_relaxed(&gs->wcnt[b * 32]) < (unsigned)NCTA && ++it < SPIN_LIMIT) {}
        fence_acquire();
        fence_async_global();
        if (lane == 0) { mbar_arrive(BAR(BAR_WACQ)); TL(6); }
        const unsigned char* wsrc = gs->wt;
#pragma unroll 1
        for (int round = 0; round < 2 * NSTAGE / NS; round++) {
            if (round == NSTAGE / NS) { mbar_wait(BAR(BAR_EMB), 0); fence_async_global(); }
            const uint32_t full = BAR(BAR_FULL) + 8 * NS * (round >= NSTAGE / NS ? round - NSTAGE / NS : round);
#pragma unroll
            for (int slot = 0; slot < NS; slot++) {
                if (slot == 9 && round == 0) mbar_wait(BAR(BAR_XFREE), 0);
                mbar_wait(BAR(BAR_WEMPTY + slot), (round & 1) ^ 1);
                if (elect_one()) {
                    mbar_expect(full + 8 * slot, STAGE_BYTES);
                    bulk_g2s(slot_addr(slot), wsrc + slot * STAGE_BYTES, STAGE_BYTES, full + 8 * slot);
                }
            }
            wsrc += NS * STAGE_BYTES;
        }
    } else {
        const uint2 ga1 = __ldg(reinterpret_cast<const uint2*>(g1) + lane), bt1 = __ldg(reinterpret_cast<const uint2*>(be1) + lane);
        const uint2 ga2 = __ldg(reinterpret_cast<const uint2*>(g2) + lane), bt2 = __ldg(reinterpret_cast<const uint2*>(be2) + lane);
        bar_sync(0, 96 + 128);
#pragma unroll 1
        for (int conv = 0; conv < 2; conv++) {
            if (conv == 1) mbar_wait(BAR(BAR_EMB), 0);
            const float* asrc = &gs->acc[(conv * NB + b) * 32 + (lane >> 3) * 4];
            uint4 f;
            unsigned it = 0;
            while (true) {
                f = ld_relaxed_v4(asrc);
                const bool ok = (f.x == 0x42800000u) & (f.w == 0x42800000u);
                if (__all_sync(0xffffffffu, ok) || ++it > SPIN_LIMIT) break;
            }
            if (lane == 0) TL(7 + conv * 8);
            const float inv_n = 1.0f / (32.0f * HW * HW);
            const float mean = __uint_as_float(f.y) * inv_n;
            const float var = fmaxf(fmaf(-mean, mean, __uint_as_float(f.z) * inv_n), 0.f);
            const float rs = 0.5f * rsqrtf(var + 1e-5f);
            const uint2 ga = conv ? ga2 : ga1, bt = conv ? bt2 : bt1;
            float4 k0, k1;
            k0.x = rs * bf_lo(ga.x); k0.y = rs * bf_hi(ga.x); k1.x = rs * bf_lo(ga.y); k1.y = rs * bf_hi(ga.y);
            k0.z = fmaf(-mean, k0.x, 0.5f * bf_lo(bt.x)); k0.w = fmaf(-mean, k0.y, 0.5f * bf_hi(bt.x));
            k1.z = fmaf(-mean, k1.x, 0.5f * bf_lo(bt.y)); k1.w = fmaf(-mean, k1.y, 0.5f * bf_hi(bt.y));
            sts128f(SM_COEF + lane * 32, k0);
            sts128f(SM_COEF + lane * 32 + 16, k1);
            __syncwarp();
            if (lane == 0) mbar_arrive(BAR(BAR_STATS));
        }
        if (r == 0) {
            if (lane < 16) gs->acc[b * 32 + lane] = 0.f;
            if (lane < 2) gs->wcnt[(lane * NB + b) * 32] = 0;
        }
    }
}

}

extern "C" void kernel_launch(void* const* d_in, const int* in_sizes, int n_in, void* d_out, int out_size) {
    (void)in_sizes; (void)n_in; (void)out_size;
    static Scratch* gs = nullptr;
    if (!gs) {
        cudaFuncSetAttribute(resblock_kernel, cudaFuncAttributeMaxDynamicSharedMemorySize, SM_TOTAL);
        cudaGetSymbolAddress((void**)&gs, g_scratch);
    }
    resblock_kernel<<<NCTA, NTHREADS, SM_TOTAL>>>(
        (const __nv_bfloat16*)d_in[0], (const __nv_bfloat16*)d_in[4], (const __nv_bfloat16*)d_in[1],
        (const __nv_bfloat16*)d_in[2], (const __nv_bfloat16*)d_in[3], (const __nv_bfloat16*)d_in[5],
        (const __nv_bfloat16*)d_in[6], (const __nv_bfloat16*)d_in[7], (const __nv_bfloat16*)d_in[8],
        (__nv_bfloat16*)d_out, gs);
}
```

```cpp
#include <cuda_runtime.h>
#include <cuda_bf16.h>
#include <stdint.h>

namespace {

constexpr int C = 128, HW = 64, NB = 2, E = 768;
constexpr int NCTA = NB * HW;
constexpr int NTHREADS = 16 * 32;
constexpr int CH_PITCH = 66 * 16;
constexpr int ROW_BYTES = 16 * CH_PITCH;
constexpr int STEP_BYTES = 4096;
constexpr int STAGE_BYTES = 3 * STEP_BYTES;
constexpr int NSTAGE = 24;
constexpr int NS = 12;
constexpr int LAG = 1;
#define XDELAY 600
#define HDELAY 500
#define NA 2
#define FETCH_AT 0
#define W2DELAY 2800

constexpr uint32_t SMEM_BASE = 0x400;
constexpr uint32_t SM_ACT = SMEM_BASE;
constexpr uint32_t SM_XOWN = SM_ACT + 3 * ROW_BYTES + 128;
constexpr uint32_t SM_W = SM_XOWN + 16384;
constexpr uint32_t SM_XH = SM_W;
__host__ __device__ constexpr uint32_t slot_addr(int slot) { return SM_W + ((slot + 3) % NS) * STAGE_BYTES; }
constexpr uint32_t SM_COEF = SM_W + NS * STAGE_BYTES;
constexpr uint32_t SM_EMB = SM_COEF + 1024;
constexpr uint32_t SM_ONES = SM_EMB + 2048;
constexpr uint32_t SM_RED = SM_ONES + 256;
constexpr uint32_t SM_BNC = SM_RED + 1280;
constexpr uint32_t SM_BAR = SM_BNC + 2 * 2304;
constexpr int BAR_FULL = 0, BAR_WEMPTY = NSTAGE, BAR_HW = BAR_WEMPTY + NS, BAR_STATS = BAR_HW + 1,
              BAR_EMB = BAR_STATS + 1, BAR_WACQ = BAR_EMB + 1, BAR_XH = BAR_WACQ + 1, BAR_XFREE = BAR_XH + 1, NBAR = BAR_XFREE + 1;
constexpr int SM_TOTAL = SM_BAR + NBAR * 8 - SMEM_BASE;
static_assert(SM_TOTAL <= 232448, "smem");
static_assert(NBAR <= 96, "barrier init");
constexpr int OUT_PITCH = 144;
__host__ __device__ constexpr uint32_t BAR(int i) { return SM_BAR + 8 * i; }
__host__ __device__ constexpr int ky_of(int kyo) { return kyo == 0 ? 1 : (kyo == 1 ? 0 : 2); }

constexpr unsigned SPIN_LIMIT = 1u << 16;

struct Scratch {
    float acc[2 * NB * 32];
    unsigned wcnt[2 * NB * 32];
    float emb[NB * C];
    unsigned char wt[2 * NSTAGE * STAGE_BYTES];
    unsigned epoch[NCTA * 32];
    uint4 h[2 * NCTA * 1024];
};
__device__ __align__(1024) Scratch g_scratch;
#define TL(i) do {} while (0)
#define TLG(i) do {} while (0)

__device__ __forceinline__ unsigned clock32() { unsigned c; asm volatile("mov.u32 %0, %%clock;" : "=r"(c)); return c; }
__device__ __forceinline__ void mbar_init(uint32_t bar, int cnt) {
    asm volatile("mbarrier.init.shared::cta.b64 [%0], %1;" ::"r"(bar), "r"(cnt) : "memory");
}
__device__ __forceinline__ void mbar_arrive(uint32_t bar) {
    asm volatile("mbarrier.arrive.shared::cta.b64 _, [%0];" ::"r"(bar) : "memory");
}
__device__ __forceinline__ void mbar_expect(uint32_t bar, uint32_t bytes) {
    asm volatile("mbarrier.arrive.expect_tx.shared::cta.b64 _, [%0], %1;" ::"r"(bar), "r"(bytes) : "memory");
}
__device__ __forceinline__ bool mbar_try(uint32_t bar, uint32_t par) {
    uint32_t ok;
    asm volatile("{\n.reg .pred p;\nmbarrier.try_wait.parity.shared::cta.b64 p, [%1], %2;\nselp.u32 %0, 1, 0, p;\n}"
                 : "=r"(ok) : "r"(bar), "r"(par) : "memory");
    return ok;
}
__device__ __forceinline__ bool mbar_test(uint32_t bar, uint32_t par) {
    uint32_t ok;
    asm volatile("{\n.reg .pred p;\nmbarrier.test_wait.parity.shared::cta.b64 p, [%1], %2;\nselp.u32 %0, 1, 0, p;\n}"
                 : "=r"(ok) : "r"(bar), "r"(par) : "memory");
    return ok;
}
__device__ __forceinline__ void mbar_wait(uint32_t bar, uint32_t par) {
    unsigned it = 0;
#pragma unroll 1
    while (!mbar_try(bar, par) && ++it < SPIN_LIMIT) {}
}
__device__ __forceinline__ bool elect_one() {
    uint32_t p;
    asm volatile("{\n.reg .pred p;\nelect.sync _|p, 0xffffffff;\nselp.u32 %0, 1, 0, p;\n}" : "=r"(p));
    return p;
}
__device__ __forceinline__ void fence_async_smem() { asm volatile("fence.proxy.async.shared::cta;" ::: "memory"); }
__device__ __forceinline__ void fence_async_global() { asm volatile("fence.proxy.async.global;" ::: "memory"); }
__device__ __forceinline__ void fence_acquire() { asm volatile("fence.acquire.gpu;" ::: "memory"); }
__device__ __forceinline__ void bar_sync(int id, int n) { asm volatile("bar.sync %0, %1;" ::"r"(id), "r"(n) : "memory"); }
__device__ __forceinline__ void bar_arrive(int id, int n) { asm volatile("bar.arrive %0, %1;" ::"r"(id), "r"(n) : "memory"); }
__device__ __forceinline__ void bulk_g2s(uint32_t dst, const void* src, uint32_t bytes, uint32_t bar) {
    asm volatile("cp.async.bulk.shared::cluster.global.mbarrier::complete_tx::bytes [%0], [%1], %2, [%3];"
                 ::"r"(dst), "l"(src), "r"(bytes), "r"(bar) : "memory");
}
__device__ __forceinline__ uint4 ld_relaxed_v4(const void* p) {
    uint4 v;
    asm volatile("ld.relaxed.gpu.global.v4.u32 {%0,%1,%2,%3}, [%4];" : "=r"(v.x), "=r"(v.y), "=r"(v.z), "=r"(v.w) : "l"(p) : "memory");
    return v;
}
__device__ __forceinline__ unsigned ld_relaxed(const void* p) {
    unsigned v;
    asm volatile("ld.relaxed.gpu.global.u32 %0, [%1];" : "=r"(v) : "l"(p) : "memory");
    return v;
}
__device__ __forceinline__ void red_add4(float* p, float a, float b, float c, float d) {
    asm volatile("red.relaxed.gpu.global.add.v4.f32 [%0], {%1,%2,%3,%4};" ::"l"(p), "f"(a), "f"(b), "f"(c), "f"(d) : "memory");
}
__device__ __forceinline__ void sts128(uint32_t a, uint4 v) {
    asm volatile("st.shared.v4.u32 [%0], {%1,%2,%3,%4};" ::"r"(a), "r"(v.x), "r"(v.y), "r"(v.z), "r"(v.w) : "memory");
}
__device__ __forceinline__ void sts128f(uint32_t a, float4 v) {
    asm volatile("st.shared.v4.f32 [%0], {%1,%2,%3,%4};" ::"r"(a), "f"(v.x), "f"(v.y), "f"(v.z), "f"(v.w) : "memory");
}
__device__ __forceinline__ void sts32f(uint32_t a, float v) { asm volatile("st.shared.f32 [%0], %1;" ::"r"(a), "f"(v) : "memory"); }
__device__ __forceinline__ uint4 lds128(uint32_t a) {
    uint4 v;
    asm volatile("ld.shared.v4.u32 {%0,%1,%2,%3}, [%4];" : "=r"(v.x), "=r"(v.y), "=r"(v.z), "=r"(v.w) : "r"(a) : "memory");
    return v;
}
__device__ __forceinline__ float4 lds128f(uint32_t a) {
    float4 v;
    asm volatile("ld.shared.v4.f32 {%0,%1,%2,%3}, [%4];" : "=f"(v.x), "=f"(v.y), "=f"(v.z), "=f"(v.w) : "r"(a) : "memory");
    return v;
}
__device__ __forceinline__ float2 lds64f(uint32_t a) {
    float2 v;
    asm volatile("ld.shared.v2.f32 {%0,%1}, [%2];" : "=f"(v.x), "=f"(v.y) : "r"(a) : "memory");
    return v;
}
__device__ __forceinline__ float bf_lo(uint32_t u) { return __uint_as_float(u << 16); }
__device__ __forceinline__ float bf_hi(uint32_t u) { return __uint_as_float(u & 0xffff0000u); }
__device__ __forceinline__ uint32_t pack_bf(float lo, float hi) {
    uint32_t r;
    asm("cvt.rn.bf16x2.f32 %0, %1, %2;" : "=r"(r) : "f"(hi), "f"(lo));
    return r;
}
__device__ __forceinline__ float tanh_fast(float x) {
    float r;
    asm("tanh.approx.f32 %0, %1;" : "=f"(r) : "f"(x));
    return r;
}
__device__ __forceinline__ float silu_half(float h) { return fmaf(h, tanh_fast(h), h); }
__device__ __forceinline__ void ldsm4(uint32_t (&u)[4], uint32_t a) {
    asm volatile("ldmatrix.sync.aligned.m8n8.x4.shared.b16 {%0,%1,%2,%3}, [%4];"
                 : "=r"(u[0]), "=r"(u[1]), "=r"(u[2]), "=r"(u[3]) : "r"(a) : "memory");
}
__device__ __forceinline__ void ldsm4t(uint32_t (&u)[4], uint32_t a) {
    asm volatile("ldmatrix.sync.aligned.m8n8.x4.trans.shared.b16 {%0,%1,%2,%3}, [%4];"
                 : "=r"(u[0]), "=r"(u[1]), "=r"(u[2]), "=r"(u[3]) : "r"(a) : "memory");
}
__device__ __forceinline__ void stsm4(uint32_t a, uint32_t p0, uint32_t p1, uint32_t p2, uint32_t p3) {
    asm volatile("stmatrix.sync.aligned.m8n8.x4.shared.b16 [%0], {%1,%2,%3,%4};" ::"r"(a), "r"(p0), "r"(p1), "r"(p2), "r"(p3) : "memory");
}
__device__ __forceinline__ void stsm4t(uint32_t a, uint32_t p0, uint32_t p1, uint32_t p2, uint32_t p3) {
    asm volatile("stmatrix.sync.aligned.m8n8.x4.trans.shared.b16 [%0], {%1,%2,%3,%4};" ::"r"(a), "r"(p0), "r"(p1), "r"(p2), "r"(p3) : "memory");
}

#define R8(o) "+f"(d[o]), "+f"(d[o + 1]), "+f"(d[o + 2]), "+f"(d[o + 3]), "+f"(d[o + 4]), "+f"(d[o + 5]), "+f"(d[o + 6]), "+f"(d[o + 7])
template <uint32_t ALO, uint32_t BLO, uint64_t AHI = 8>
__device__ __forceinline__ void wgmma128(float (&d)[64]) {
    asm volatile(
        "wgmma.mma_async.sync.aligned.m64n128k16.f32.bf16.bf16 "
        "{%0,%1,%2,%3,%4,%5,%6,%7,%8,%9,%10,%11,%12,%13,%14,%15,%16,%17,%18,%19,%20,%21,%22,%23,%24,%25,%26,%27,%28,%29,%30,%31,"
        "%32,%33,%34,%35,%36,%37,%38,%39,%40,%41,%42,%43,%44,%45,%46,%47,%48,%49,%50,%51,%52,%53,%54,%55,%56,%57,%58,%59,%60,%61,%62,%63},"
        " %64, %65, 1, 1, 1, 0, 0;"
        : R8(0), R8(8), R8(16), R8(24), R8(32), R8(40), R8(48), R8(56)
        : "l"((AHI << 32) | ALO), "l"((8ull << 32) | BLO));
}
template <int S>
__device__ __forceinline__ void mma_stages(float (&d)[64], int conv, int tid, Scratch* gs) {
    constexpr uint32_t A = ((SM_ACT + S * 2 * CH_PITCH + 16) >> 4) | ((CH_PITCH >> 4) << 16);
    constexpr uint32_t B = (slot_addr(S % NS) >> 4) | ((2048 >> 4) << 16);
    if (S == 0) mbar_wait(BAR(BAR_FULL), conv);
    bool next_ok = true;
    constexpr uint32_t NEXT = S + 1 < NSTAGE ? BAR(BAR_FULL + S + 1) : BAR(BAR_EMB);
    const int npar = S + 1 < NSTAGE ? conv : 0;
    next_ok = mbar_test(NEXT, npar);
    if (S == 0 && tid == 0) TL(32 + conv * 24);
    asm volatile("wgmma.fence.sync.aligned;" ::: "memory");
    wgmma128<A, B>(d);
    wgmma128<A + 1, B + (STEP_BYTES >> 4)>(d);
    wgmma128<A + 2, B + 2 * (STEP_BYTES >> 4)>(d);
    asm volatile("wgmma.commit_group.sync.aligned;" ::: "memory");
    if (S >= LAG) {
        asm volatile("wgmma.wait_group.sync.aligned %0;" ::"n"(LAG) : "memory");
        if ((tid & 31) == 0) mbar_arrive(BAR(BAR_WEMPTY + (S + NS - LAG) % NS));
    }
    if (!next_ok) mbar_wait(NEXT, npar);
    if constexpr (S + 1 < NSTAGE) mma_stages<S + 1>(d, conv, tid, gs);
}

__device__ __forceinline__ void weight_block(const uint4 (&t)[5], uint32_t bounce, unsigned char* wt, int cta, int lane) {
    const uint32_t bw = bounce + (lane >> 4) * 1152 + (lane & 15) * 16;
#pragma unroll
    for (int k = 0; k < 4; k++) sts128(bw + k * 256, t[k]);
    if ((lane & 15) < 8) sts128(bw + 1024, t[4]);
    __syncwarp();
    if (lane < 16) {
        uint32_t v[36];
#pragma unroll
        for (int i = 0; i < 9; i++) {
            const uint4 q = lds128(bounce + (lane & 1) * 1152 + (lane >> 1) * 144 + i * 16);
            v[4 * i] = q.x; v[4 * i + 1] = q.y; v[4 * i + 2] = q.z; v[4 * i + 3] = q.w;
        }
        const int cc = (cta >> 6) * 8 + (lane >> 1);
        unsigned char* dst = wt + (cc >> 1) * STAGE_BYTES + (cc & 1) * 2048 + ((cta & 63) * 2 + (lane & 1)) * 16;
#pragma unroll
        for (int kyo = 0; kyo < 3; kyo++) {
#pragma unroll
            for (int kx = 0; kx < 3; kx++) {
                const int tap = ky_of(kyo) * 3 + kx;
                uint32_t o[4];
#pragma unroll
                for (int m = 0; m < 4; m++) {
                    const int i0 = 18 * m + tap, i1 = i0 + 9;
                    const uint32_t sel = ((i0 & 1) ? 0x32u : 0x10u) | ((i1 & 1) ? 0x7600u : 0x5400u);
                    o[m] = __byte_perm(v[i0 >> 1], v[i1 >> 1], sel);
                }
                *reinterpret_cast<uint4*>(dst + (kyo * 24 + kx) * STEP_BYTES) = make_uint4(o[0], o[1], o[2], o[3]);
            }
        }
    }
}
__device__ __forceinline__ uint32_t act2(uint32_t u, const float4& cf) {
    return pack_bf(silu_half(fmaf(bf_lo(u), cf.x, cf.z)), silu_half(fmaf(bf_hi(u), cf.y, cf.w)));
}
__device__ __forceinline__ void norm_unit(uint32_t (&u)[4], const float4& ca, const float4& cb) {
    u[0] = act2(u[0], ca); u[1] = act2(u[1], ca); u[2] = act2(u[2], cb); u[3] = act2(u[3], cb);
}
template <int FIRST, int N>
__device__ __forceinline__ void norm_block(uint32_t (&u)[12][4], const float4 (&cf)[8], uint32_t act, uint32_t mask, uint32_t fbar, int lane) {
#pragma unroll
    for (int t = FIRST; t < FIRST + N; t++) {
        norm_unit(u[t], cf[2 * (t & 3)], cf[2 * (t & 3) + 1]);
        stsm4(act + t * 4 * CH_PITCH, u[t][0] & mask, u[t][1] & mask, u[t][2] & mask, u[t][3] & mask);
    }
    fence_async_smem();
    __syncwarp();
    if (lane < N) mbar_arrive(fbar + 16 * (FIRST + lane));
}
__device__ __forceinline__ void publish(uint32_t bar, int lane) {
    fence_async_smem();
    __syncwarp();
    if (lane == 0) mbar_arrive(bar);
}
__device__ __forceinline__ void stat_mma(float (&c)[4], uint32_t p, uint32_t q) {
    asm("mma.sync.aligned.m16n8k16.row.col.f32.bf16.bf16.f32 {%0,%1,%2,%3}, {%4,%5,%6,%5}, {%4,%6}, {%0,%1,%2,%3};"
        : "+f"(c[0]), "+f"(c[1]), "+f"(c[2]), "+f"(c[3]) : "r"(p), "r"(0x3f803f80u), "r"(q));
}
__device__ __forceinline__ void stat_store(const float (&c)[4], uint32_t dst, int lane) {
    const int g = lane >> 2, t = lane & 3;
    if (t == (g >> 1)) sts32f(dst + g * 4, (g & 1) ? c[1] : c[0]);
    if (g == 7) sts32f(dst + 32 + t * 4, c[2] + c[3]);
}
__device__ __forceinline__ float sum4(float4 v) { return (v.x + v.y) + (v.z + v.w); }
__device__ __forceinline__ void stat_publish(uint32_t src, float* acc, int lane, bool real) {
    const uint32_t a = src + (lane & 15) * 48;
    float q = sum4(lds128f(a)) + sum4(lds128f(a + 16)), sm = sum4(lds128f(a + 32));
    q += __shfl_xor_sync(0xffffffffu, q, 1); sm += __shfl_xor_sync(0xffffffffu, sm, 1);
    q += __shfl_xor_sync(0xffffffffu, q, 2); sm += __shfl_xor_sync(0xffffffffu, sm, 2);
    if (real && (lane & 19) == 0) red_add4(acc + lane, 1.f, sm, q, 1.f);
}
__device__ __forceinline__ void fence_acc(float (&d)[64]) {
#pragma unroll
    for (int i = 0; i < 64; i++) asm volatile("" : "+f"(d[i])::"memory");
}
__device__ __forceinline__ void ld_unit(uint32_t (&u)[4], const uint4* p) {
    asm volatile("ld.relaxed.gpu.global.v4.u32 {%0,%1,%2,%3}, [%4];" : "=r"(u[0]), "=r"(u[1]), "=r"(u[2]), "=r"(u[3]) : "l"(p) : "memory");
}

template <int FIRST>
__device__ __forceinline__ void settle_row(uint32_t (&u)[12][4], const uint4* p) {
    unsigned it = 0;
    while (true) {
        bool ok = true;
#pragma unroll
        for (int i = 0; i < 16; i++) ok = ok && u[FIRST + (i >> 2)][i & 3] != 0;
        if (__all_sync(0xffffffffu, ok) || ++it > SPIN_LIMIT) break;
#pragma unroll
        for (int i = 0; i < 4; i++) ld_unit(u[FIRST + i], p + i * 256);
    }
#pragma unroll
    for (int i = 0; i < 16; i++) u[FIRST + (i >> 2)][i & 3] = ~u[FIRST + (i >> 2)][i & 3];
}

__global__ void __launch_bounds__(NTHREADS, 1)
resblock_kernel(const __nv_bfloat16* __restrict__ x, const __nv_bfloat16* __restrict__ w1,
                const __nv_bfloat16* __restrict__ t_emb, const __nv_bfloat16* __restrict__ g1,
                const __nv_bfloat16* __restrict__ be1, const __nv_bfloat16* __restrict__ w_emb,
                const __nv_bfloat16* __restrict__ g2, const __nv_bfloat16* __restrict__ be2,
                const __nv_bfloat16* __restrict__ w2, __nv_bfloat16* __restrict__ out, Scratch* __restrict__ gs) {
    const unsigned clk0 = clock32();
    const int tid = threadIdx.x, warp = tid >> 5, lane = tid & 31;
    const int cta = blockIdx.x, b = cta >> 6, r = cta & 63;

    const uint32_t woff = ((2 * r + (lane >> 4)) * C + b * 64) * 18 + (lane & 15) * 16;
    const int c0 = (warp - 8) * 16 + (lane >> 3), seg = lane & 7;
    uint4 v[5];
    if (warp == 0) {
        const char* w1s = reinterpret_cast<const char*>(w1) + woff;
#pragma unroll
        for (int k = 0; k < 4; k++) v[k] = __ldg(reinterpret_cast<const uint4*>(w1s + k * 256));
        if ((lane & 15) < 8) v[4] = __ldg(reinterpret_cast<const uint4*>(w1s + 1024));
    }
    const bool loader = warp >= 8;
    if (loader || warp == 5) {
        if (loader) {
            const char* src = reinterpret_cast<const char*>(x) + (uint32_t)(((b * C + c0) * HW + r) * HW * 2 + seg * 16);
            while (clock32() - clk0 < XDELAY) {}
#pragma unroll
            for (int k = 0; k < 4; k++) v[k] = __ldg(reinterpret_cast<const uint4*>(src + k * (4 * HW * HW * 2)));
#pragma unroll
            for (int i = 0; i < 8; i++) {
                if (i < 4 ? (r != 0) : (r != HW - 1))
                    asm volatile("cp.async.cg.shared.global [%0], [%1], 16;"
                                 ::"r"(SM_XH + (i >> 2) * 16384 + c0 * 128 + (i & 3) * 512 + ((seg ^ ((c0 + 4 * i) & 7)) << 4)),
                                   "l"(src + (i < 4 ? -HW * 2 : HW * 2) + (i & 3) * (4 * HW * HW * 2)) : "memory");
            }
        } else {
#pragma unroll
            for (int k = 0; k < 4; k++) v[k] = make_uint4(0, 0, 0, 0);
        }
        float c[2][4] = {{0.f, 0.f, 0.f, 0.f}, {0.f, 0.f, 0.f, 0.f}};
#pragma unroll
        for (int k = 0; k < 4; k++) { stat_mma(c[0], v[k].x, v[k].y); stat_mma(c[1], v[k].z, v[k].w); }
        stat_store(c[0], SM_RED + (warp & 7) * 96 + (loader ? 0 : 384), lane);
        stat_store(c[1], SM_RED + (warp & 7) * 96 + 48 + (loader ? 0 : 384), lane);
        if (tid == 256) TL(2);
        if (loader) bar_sync(3, 256);
        if (warp <= 8) stat_publish(SM_RED, &gs->acc[b * 32], lane, warp == 8);
        if (tid == 256) TL(3);
        if (loader) {
#pragma unroll
            for (int i = 0; i < 4; i++) sts128(SM_XOWN + c0 * 128 + i * 512 + ((seg ^ ((c0 + 4 * i) & 7)) << 4), v[i]);
        }
    }
    if (warp == 0) {
        weight_block(v, SM_BNC, gs->wt, cta, lane);
        if (r == 0) {
            if (lane < 16) gs->acc[(NB + b) * 32 + lane] = 0.f;
            *reinterpret_cast<float4*>(&gs->emb[b * C + lane * 4]) = make_float4(0.f, 0.f, 0.f, 0.f);
        }
        __syncwarp();
        if (lane == 0) TL(4);
        if (lane < 2) asm volatile("red.release.gpu.global.add.u32 [%0], 1;" ::"l"(&gs->wcnt[lane * 32]) : "memory");
        if (lane == 0) TL(5);
    }

    if (warp >= 8) {
        const int nw = warp - 8;
        asm volatile("cp.async.wait_all;" ::: "memory");
        bar_sync(4, 256 + 96);
        const int par = nw >> 2, wq = nw & 3;
        const unsigned epoch = gs->epoch[cta * 32];
        const uint32_t act_off = SM_ACT + (par * 2 + (lane >> 4)) * CH_PITCH + (2 + wq * 16 + (lane & 15)) * 16;
        const uint32_t stg_off = SM_XOWN + (par * 16 + (lane >> 4) * 8 + (lane & 7)) * 128 + (((2 * wq + ((lane >> 3) & 1)) ^ (lane & 7)) << 4);
        const uint32_t cfa = SM_COEF + par * 128 + (lane & 3) * 16;
        const uint32_t fbar = BAR(BAR_FULL) + 8 * par;
        const uint4* hrow = gs->h + ((epoch & 1) * NCTA + cta) * 1024 + nw * 32 + lane;
        const uint32_t mask_up = r != 0 ? ~0u : 0u, mask_dn = r != HW - 1 ? ~0u : 0u;
        const uint4* hu = hrow - (r != 0 ? 1024 : 0);
        const uint4* hd = hrow + (r != HW - 1 ? 1024 : 0);
#pragma unroll 1
        for (int conv = 0; conv < 2; conv++) {
            uint32_t u[12][4];
            float4 cf[8];
            if (conv == 0) {
#pragma unroll
                for (int i = 0; i < 12; i++) ldsm4t(u[i], stg_off + i * 4096);
                publish(BAR(BAR_XFREE), lane);
            } else {
                mbar_wait(BAR(BAR_HW), 0);
#pragma unroll
                for (int i = 0; i < 4; i++) ldsm4(u[i], act_off + i * 4 * CH_PITCH);
            }
            mbar_wait(BAR(BAR_STATS), conv);
            if (tid == 256) TL(22 + conv * 4);
#pragma unroll
            for (int i = 0; i < 2 * NA; i++) cf[i] = lds128f(cfa + (i >> 1) * 256 + (i & 1) * 64);
            norm_block<0, NA>(u, cf, act_off, ~0u, fbar, lane);
            if (tid == 256) TL(8 + conv * 8);
#pragma unroll
            for (int i = 2 * NA; i < 8; i++) cf[i] = lds128f(cfa + (i >> 1) * 256 + (i & 1) * 64);
            if (conv == 1) {
#pragma unroll
                for (int i = 0; i < 4; i++) { ld_unit(u[4 + i], hu + i * 256); ld_unit(u[8 + i], hd + i * 256); }
            }
            norm_block<2, 2>(u, cf, act_off, ~0u, fbar, lane);
            if (tid == 256) TL(84 + conv);
            if (conv == 1) settle_row<4>(u, hu);
            if (tid == 256) TL(28);
            norm_block<4, 2>(u, cf, act_off, mask_up, fbar, lane);
            norm_block<6, 2>(u, cf, act_off, mask_up, fbar, lane);
            if (conv == 1) settle_row<8>(u, hd);
            norm_block<8, 4>(u, cf, act_off, mask_dn, fbar, lane);
            if (tid == 256) TL(23 + conv * 4);
        }
        uint4* hz = gs->h + (((epoch + 1) & 1) * NCTA + cta) * 1024 + (tid - 256);
#pragma unroll
        for (int i = 0; i < 4; i++) hz[i * 256] = make_uint4(0, 0, 0, 0);
    } else if (warp < 4) {
        const int wq = warp;
        if (wq != 0) {
            const int t = tid - 32;
            if (lane == 0) {
                if (wq == 1) {
#pragma unroll
                    for (int i = 0; i < 12; i++) mbar_init(BAR(BAR_FULL + i), 5);
                } else if (wq == 2) {
#pragma unroll
                    for (int i = 12; i < NSTAGE; i++) mbar_init(BAR(BAR_FULL + i), 5);
                } else {
#pragma unroll
                    for (int i = 0; i <= NS; i++) mbar_init(BAR(BAR_WEMPTY + i), 4);
#pragma unroll
                    for (int i = BAR_STATS; i < BAR_XFREE; i++) mbar_init(BAR(i), 1);
                    mbar_init(BAR(BAR_XFREE), 8);
                }
            }
            fence_async_smem();
            bar_arrive(0, 96 + 128);
            bar_arrive(4, 256 + 96);
            if (t == 95) TLG(1);
            const uint4 z = make_uint4(0, 0, 0, 0);
            sts128(SM_ACT + (t >> 1) * CH_PITCH + (t & 1) * 16, z);
            if (t < 2) sts128(SM_ACT + 3 * ROW_BYTES + t * 16, z);
            if (t < 16) sts128(SM_ONES + t * 16, make_uint4(t < 8 ? 0x3f803f80u : 0u, 0, 0, 0));
            fence_async_smem();
        }
        bar_sync(2, 128);
        const unsigned epoch = gs->epoch[cta * 32];

        float d[64];
#pragma unroll
        for (int i = 0; i < 64; i++) d[i] = 0.f;
#pragma unroll 1
        for (int conv = 0; conv < 2; conv++) {
            fence_acc(d);
            mma_stages<0>(d, conv, tid, gs);
            if (conv == 0) {
                asm volatile("wgmma.fence.sync.aligned;" ::: "memory");
                wgmma128<(SM_ONES >> 4) | (8u << 16), (SM_EMB >> 4), 0>(d);
                asm volatile("wgmma.commit_group.sync.aligned;" ::: "memory");
            }
            asm volatile("wgmma.wait_group.sync.aligned 0;" ::: "memory");
            fence_acc(d);
            if (tid == 0) TL(10 + conv * 8);
            if (conv == 1) break;

            uint32_t hp[32];
#pragma unroll
            for (int g = 0; g < 4; g++) {
                float c[4] = {0.f, 0.f, 0.f, 0.f};
#pragma unroll
                for (int i = 0; i < 8; i++) hp[8 * g + i] = pack_bf(d[16 * g + 2 * i], d[16 * g + 2 * i + 1]);
#pragma unroll
                for (int i = 0; i < 4; i++) stat_mma(c, hp[8 * g + 2 * i], hp[8 * g + 2 * i + 1]);
                stat_store(c, SM_RED + (g * 4 + wq) * 48, lane);
            }
            bar_sync(2, 128);
            if (wq == 0) stat_publish(SM_RED, &gs->acc[(NB + b) * 32], lane, true);
            if (tid == 0) TL(11);
            const uint32_t hbase = SM_ACT + (lane >> 4) * CH_PITCH + (2 + wq * 16 + (lane & 15)) * 16;
#pragma unroll
            for (int kc = 0; kc < 8; kc++) stsm4(hbase + kc * 2 * CH_PITCH, hp[4 * kc], hp[4 * kc + 1], hp[4 * kc + 2], hp[4 * kc + 3]);
            __syncwarp();
            if (lane == 0) mbar_arrive(BAR(BAR_HW));
            if (lane < LAG) mbar_arrive(BAR(BAR_WEMPTY + (NSTAGE - LAG) % NS) + 8 * lane);
            uint4* hg = gs->h + ((epoch & 1) * NCTA + cta) * 1024 + tid;
#pragma unroll
            for (int kc = 0; kc < 8; kc++) hg[kc * 128] = make_uint4(~hp[4 * kc], ~hp[4 * kc + 1], ~hp[4 * kc + 2], ~hp[4 * kc + 3]);
            if (tid == 0) TL(12);
            const uint32_t xbase = SM_XOWN + ((lane >> 4) * 8 + (lane & 7)) * 128 + (((2 * wq + ((lane >> 3) & 1)) ^ (lane & 7)) << 4);
#pragma unroll
            for (int kc = 0; kc < 8; kc++) {
                uint32_t p[4];
                ldsm4t(p, xbase + kc * 2048);
#pragma unroll
                for (int i = 0; i < 4; i++) { d[8 * kc + 2 * i] = bf_lo(p[i]); d[8 * kc + 2 * i + 1] = bf_hi(p[i]); }
            }
        }
        {
            const uint32_t obase = slot_addr(0) + ((lane >> 4) * 8 + (lane & 7)) * OUT_PITCH + (wq * 16 + ((lane >> 3) & 1) * 8) * 2;
#pragma unroll
            for (int kc = 0; kc < 8; kc++) {
                stsm4t(obase + kc * 16 * OUT_PITCH, pack_bf(d[8 * kc + 0], d[8 * kc + 1]), pack_bf(d[8 * kc + 2], d[8 * kc + 3]),
                       pack_bf(d[8 * kc + 4], d[8 * kc + 5]), pack_bf(d[8 * kc + 6], d[8 * kc + 7]));
            }
            bar_sync(2, 128);
            const int oc0 = tid >> 3;
            __nv_bfloat16* dst = out + ((size_t)(b * C + oc0) * HW + r) * HW + seg * 8;
#pragma unroll
            for (int i = 0; i < 8; i++)
                *reinterpret_cast<uint4*>(dst + (size_t)i * 16 * HW * HW) = lds128(slot_addr(0) + (oc0 + 16 * i) * OUT_PITCH + seg * 16);
            if (tid == 0) gs->epoch[cta * 32] = epoch + 1;
            if (tid == 0) { TL(20); TLG(21); }
        }
    } else if (warp < 6) {
        bar_sync(0, 96 + 128);
        if (warp == 4) {
            while (clock32() - clk0 < W2DELAY) {}
            const char* w2s = reinterpret_cast<const char*>(w2) + woff;
#pragma unroll
            for (int k = 0; k < 4; k++) v[k] = __ldg(reinterpret_cast<const uint4*>(w2s + k * 256));
            if ((lane & 15) < 8) v[4] = __ldg(reinterpret_cast<const uint4*>(w2s + 1024));
            const uint2* wsrc = reinterpret_cast<const uint2*>(w_emb + (size_t)r * 12 * C) + lane;
            uint2 wv[12];
#pragma unroll
            for (int i = 0; i < 12; i++) wv[i] = __ldg(wsrc + i * (C / 4));
            float tv = 0.f;
            if (lane < 12) tv = __bfloat162float(t_emb[b * E + r * 12 + lane]);
            weight_block(v, SM_BNC + 2304, gs->wt + NSTAGE * STAGE_BYTES, cta, lane);
            const float sv = silu_half(0.5f * tv);
            float e0 = 0.f, e1 = 0.f, e2 = 0.f, e3 = 0.f;
#pragma unroll
            for (int i = 0; i < 12; i++) {
                const float sx = __shfl_sync(0xffffffffu, sv, i);
                e0 = fmaf(sx, bf_lo(wv[i].x), e0); e1 = fmaf(sx, bf_hi(wv[i].x), e1);
                e2 = fmaf(sx, bf_lo(wv[i].y), e2); e3 = fmaf(sx, bf_hi(wv[i].y), e3);
            }
            mbar_wait(BAR(BAR_WACQ), 0);
            red_add4(&gs->emb[b * C + lane * 4], e0, e1, e2, e3);
            __syncwarp();
            if (lane == 0) TL(13);
            if (lane < 2) asm volatile("red.release.gpu.global.add.u32 [%0], 1;" ::"l"(&gs->wcnt[(NB + lane) * 32]) : "memory");
            if (lane == 0) TL(14);
            unsigned it = 0;
            while (ld_relaxed(&gs->wcnt[(NB + b) * 32]) < (unsigned)NCTA && ++it < SPIN_LIMIT) {}
            fence_acquire();
            const uint4 ef = ld_relaxed_v4(&gs->emb[b * C + lane * 4]);
            const uint32_t eu[4] = {ef.x, ef.y, ef.z, ef.w};
#pragma unroll
            for (int i = 0; i < 4; i++) {
                const float e = __uint_as_float(eu[i]);
                const float hi = bf_lo(pack_bf(e, 0.f));
                sts128(SM_EMB + (lane * 4 + i) * 16, make_uint4(pack_bf(hi, e - hi), 0, 0, 0));
            }
            fence_async_smem();
            __syncwarp();
            if (lane == 0) { mbar_arrive(BAR(BAR_EMB)); TL(19); }
        }
    } else if (warp == 6) {
        bar_sync(0, 96 + 128);
        unsigned it = 0;
        while (ld_relaxed(&gs->wcnt[b * 32]) < (unsigned)NCTA && ++it < SPIN_LIMIT) {}
        fence_acquire();
        fence_async_global();
        if (lane == 0) { mbar_arrive(BAR(BAR_WACQ)); TL(6); }
        const unsigned char* wsrc = gs->wt;
#pragma unroll 1
        for (int round = 0; round < 2 * NSTAGE / NS; round++) {
            if (round == NSTAGE / NS) { mbar_wait(BAR(BAR_EMB), 0); fence_async_global(); }
            const uint32_t full = BAR(BAR_FULL) + 8 * NS * (round >= NSTAGE / NS ? round - NSTAGE / NS : round);
#pragma unroll
            for (int slot = 0; slot < NS; slot++) {
                if (slot == 9 && round == 0) mbar_wait(BAR(BAR_XFREE), 0);
                mbar_wait(BAR(BAR_WEMPTY + slot), (round & 1) ^ 1);
                if (elect_one()) {
                    mbar_expect(full + 8 * slot, STAGE_BYTES);
                    bulk_g2s(slot_addr(slot), wsrc + slot * STAGE_BYTES, STAGE_BYTES, full + 8 * slot);
                }
            }
            wsrc += NS * STAGE_BYTES;
        }
    } else {
        const uint2 ga1 = __ldg(reinterpret_cast<const uint2*>(g1) + lane), bt1 = __ldg(reinterpret_cast<const uint2*>(be1) + lane);
        const uint2 ga2 = __ldg(reinterpret_cast<const uint2*>(g2) + lane), bt2 = __ldg(reinterpret_cast<const uint2*>(be2) + lane);
        bar_sync(0, 96 + 128);
#pragma unroll 1
        for (int conv = 0; conv < 2; conv++) {
            if (conv == 1) mbar_wait(BAR(BAR_EMB), 0);
            const float* asrc = &gs->acc[(conv * NB + b) * 32 + (lane >> 3) * 4];
            uint4 f;
            unsigned it = 0;
            while (true) {
                f = ld_relaxed_v4(asrc);
                const bool ok = (f.x == 0x42800000u) & (f.w == 0x42800000u);
                if (__all_sync(0xffffffffu, ok) || ++it > SPIN_LIMIT) break;
            }
            if (lane == 0) TL(7 + conv * 8);
            const float inv_n = 1.0f / (32.0f * HW * HW);
            const float mean = __uint_as_float(f.y) * inv_n;
            const float var = fmaxf(fmaf(-mean, mean, __uint_as_float(f.z) * inv_n), 0.f);
            const float rs = 0.5f * rsqrtf(var + 1e-5f);
            const uint2 ga = conv ? ga2 : ga1, bt = conv ? bt2 : bt1;
            float4 k0, k1;
            k0.x = rs * bf_lo(ga.x); k0.y = rs * bf_hi(ga.x); k1.x = rs * bf_lo(ga.y); k1.y = rs * bf_hi(ga.y);
            k0.z = fmaf(-mean, k0.x, 0.5f * bf_lo(bt.x)); k0.w = fmaf(-mean, k0.y, 0.5f * bf_hi(bt.x));
            k1.z = fmaf(-mean, k1.x, 0.5f * bf_lo(bt.y)); k1.w = fmaf(-mean, k1.y, 0.5f * bf_hi(bt.y));
            sts128f(SM_COEF + lane * 32, k0);
            sts128f(SM_COEF + lane * 32 + 16, k1);
            __syncwarp();
            if (lane == 0) mbar_arrive(BAR(BAR_STATS));
        }
        if (r == 0) {
            if (lane < 16) gs->acc[b * 32 + lane] = 0.f;
            if (lane < 2) gs->wcnt[(lane * NB + b) * 32] = 0;
        }
    }
}

}

extern "C" void kernel_launch(void* const* d_in, const int* in_sizes, int n_in, void* d_out, int out_size) {
    (void)in_sizes; (void)n_in; (void)out_size;
    static Scratch* gs = nullptr;
    if (!gs) {
        cudaFuncSetAttribute(resblock_kernel, cudaFuncAttributeMaxDynamicSharedMemorySize, SM_TOTAL);
        cudaGetSymbolAddress((void**)&gs, g_scratch);
    }
    resblock_kernel<<<NCTA, NTHREADS, SM_TOTAL>>>(
        (const __nv_bfloat16*)d_in[0], (const __nv_bfloat16*)d_in[4], (const __nv_bfloat16*)d_in[1],
        (const __nv_bfloat16*)d_in[2], (const __nv_bfloat16*)d_in[3], (const __nv_bfloat16*)d_in[5],
        (const __nv_bfloat16*)d_in[6], (const __nv_bfloat16*)d_in[7], (const __nv_bfloat16*)d_in[8],
        (__nv_bfloat16*)d_out, gs);
}
```

```cpp
#include <cuda_runtime.h>
#include <cuda_bf16.h>
#include <stdint.h>

namespace {

constexpr int C = 128, HW = 64, NB = 2, E = 768;
constexpr int NCTA = NB * HW;
constexpr int NTHREADS = 16 * 32;
constexpr int CH_PITCH = 66 * 16;
constexpr int ROW_BYTES = 16 * CH_PITCH;
constexpr int STEP_BYTES = 4096;
constexpr int STAGE_BYTES = 3 * STEP_BYTES;
constexpr int NSTAGE = 24;
constexpr int KC_BYTES = 2 * CH_PITCH;
constexpr int NS = 12;
constexpr int LAG = 1;
#define XDELAY 600
#define HDELAY 600
#define NA 2
#define W2DELAY 2800

constexpr uint32_t SMEM_BASE = 0x400;
constexpr uint32_t SM_ACT = SMEM_BASE;
constexpr uint32_t SM_XOWN = SM_ACT + 3 * ROW_BYTES + 128;
constexpr uint32_t SM_W = SM_XOWN + 16384;
__host__ __device__ constexpr uint32_t slot_addr(int slot) { return SM_W + slot * STAGE_BYTES; }
constexpr uint32_t SM_COEF = SM_W + NS * STAGE_BYTES;
constexpr uint32_t SM_EMB = SM_COEF + 1024;
constexpr uint32_t SM_ONES = SM_EMB + 2048;
constexpr uint32_t SM_RED = SM_ONES + 256;
constexpr uint32_t SM_BNC = SM_RED + 1280;
constexpr uint32_t SM_BAR = SM_BNC + 2 * 2304;
constexpr int BAR_FULL = 0, BAR_WEMPTY = NSTAGE, BAR_HW = BAR_WEMPTY + NS, BAR_STATS = BAR_HW + 1,
              BAR_EMB = BAR_STATS + 1, BAR_WACQ = BAR_EMB + 1, BAR_ACK = BAR_WACQ + 1, NBAR = BAR_ACK + 1;
constexpr int SM_TOTAL = SM_BAR + NBAR * 8 - SMEM_BASE;
static_assert(SM_TOTAL <= 232448, "smem");
static_assert(NBAR <= 96, "barrier init");
constexpr int OUT_PITCH = 144;
__host__ __device__ constexpr uint32_t BAR(int i) { return SM_BAR + 8 * i; }
__host__ __device__ constexpr int ky_of(int kyo) { return kyo == 0 ? 1 : (kyo == 1 ? 0 : 2); }

constexpr unsigned SPIN_LIMIT = 1u << 16;

struct Scratch {
    float acc[2 * NB * 32];
    unsigned wcnt[2 * NB * 32];
    float emb[NB * C];
    unsigned char wt[2 * NSTAGE * STAGE_BYTES];
    uint4 box[2 * NCTA * 1024];
};
__device__ __align__(1024) Scratch g_scratch;
#define TL(i) do {} while (0)
#define TLG(i) do {} while (0)

__device__ __forceinline__ unsigned clock32() { unsigned c; asm volatile("mov.u32 %0, %%clock;" : "=r"(c)); return c; }
__device__ __forceinline__ uint32_t mapa(uint32_t a, uint32_t rank) {
    uint32_t d;
    asm("mapa.shared::cluster.u32 %0, %1, %2;" : "=r"(d) : "r"(a), "r"(rank));
    return d;
}
#define S0 mapa(0, blockIdx.x & 1)
__device__ __forceinline__ void mbar_init(uint32_t bar, int cnt) {
    asm volatile("mbarrier.init.shared::cta.b64 [%0], %1;" ::"r"(bar + S0), "r"(cnt) : "memory");
}
__device__ __forceinline__ void mbar_arrive(uint32_t bar) {
    asm volatile("mbarrier.arrive.shared::cta.b64 _, [%0];" ::"r"(bar + S0) : "memory");
}
__device__ __forceinline__ void mbar_expect(uint32_t bar, uint32_t bytes) {
    asm volatile("mbarrier.arrive.expect_tx.shared::cta.b64 _, [%0], %1;" ::"r"(bar + S0), "r"(bytes) : "memory");
}
__device__ __forceinline__ bool mbar_try(uint32_t bar, uint32_t par) {
    uint32_t ok;
    asm volatile("{\n.reg .pred p;\nmbarrier.try_wait.parity.shared::cta.b64 p, [%1], %2;\nselp.u32 %0, 1, 0, p;\n}"
                 : "=r"(ok) : "r"(bar + S0), "r"(par) : "memory");
    return ok;
}
__device__ __forceinline__ bool mbar_test(uint32_t bar, uint32_t par) {
    uint32_t ok;
    asm volatile("{\n.reg .pred p;\nmbarrier.test_wait.parity.shared::cta.b64 p, [%1], %2;\nselp.u32 %0, 1, 0, p;\n}"
                 : "=r"(ok) : "r"(bar + S0), "r"(par) : "memory");
    return ok;
}
__device__ __forceinline__ void mbar_wait(uint32_t bar, uint32_t par) {
    unsigned it = 0;
#pragma unroll 1
    while (!mbar_try(bar, par) && ++it < SPIN_LIMIT) {}
}
__device__ __forceinline__ bool elect_one() {
    uint32_t p;
    asm volatile("{\n.reg .pred p;\nelect.sync _|p, 0xffffffff;\nselp.u32 %0, 1, 0, p;\n}" : "=r"(p));
    return p;
}
__device__ __forceinline__ void fence_async_smem() { asm volatile("fence.proxy.async.shared::cta;" ::: "memory"); }
__device__ __forceinline__ void fence_async_global() { asm volatile("fence.proxy.async.global;" ::: "memory"); }
__device__ __forceinline__ void fence_acquire() { asm volatile("fence.acquire.gpu;" ::: "memory"); }
__device__ __forceinline__ void bar_sync(int id, int n) { asm volatile("bar.sync %0, %1;" ::"r"(id), "r"(n) : "memory"); }
__device__ __forceinline__ void bar_arrive(int id, int n) { asm volatile("bar.arrive %0, %1;" ::"r"(id), "r"(n) : "memory"); }
__device__ __forceinline__ void bulk_g2s(uint32_t dst, const void* src, uint32_t bytes, uint32_t bar) {
    asm volatile("cp.async.bulk.shared::cluster.global.mbarrier::complete_tx::bytes [%0], [%1], %2, [%3];"
                 ::"r"(dst), "l"(src), "r"(bytes), "r"(bar) : "memory");
}
__device__ __forceinline__ uint4 ld_relaxed_v4(const void* p) {
    uint4 v;
    asm volatile("ld.relaxed.gpu.global.v4.u32 {%0,%1,%2,%3}, [%4];" : "=r"(v.x), "=r"(v.y), "=r"(v.z), "=r"(v.w) : "l"(p) : "memory");
    return v;
}
__device__ __forceinline__ unsigned ld_relaxed(const void* p) {
    unsigned v;
    asm volatile("ld.relaxed.gpu.global.u32 %0, [%1];" : "=r"(v) : "l"(p) : "memory");
    return v;
}
__device__ __forceinline__ void red_add4(float* p, float a, float b, float c, float d) {
    asm volatile("red.relaxed.gpu.global.add.v4.f32 [%0], {%1,%2,%3,%4};" ::"l"(p), "f"(a), "f"(b), "f"(c), "f"(d) : "memory");
}
__device__ __forceinline__ void sts128(uint32_t a, uint4 v) {
    asm volatile("st.shared.v4.u32 [%0], {%1,%2,%3,%4};" ::"r"(a + S0), "r"(v.x), "r"(v.y), "r"(v.z), "r"(v.w) : "memory");
}
__device__ __forceinline__ void sts128f(uint32_t a, float4 v) {
    asm volatile("st.shared.v4.f32 [%0], {%1,%2,%3,%4};" ::"r"(a + S0), "f"(v.x), "f"(v.y), "f"(v.z), "f"(v.w) : "memory");
}
__device__ __forceinline__ void sts32f(uint32_t a, float v) { asm volatile("st.shared.f32 [%0], %1;" ::"r"(a + S0), "f"(v) : "memory"); }
__device__ __forceinline__ uint4 lds128(uint32_t a) {
    uint4 v;
    asm volatile("ld.shared.v4.u32 {%0,%1,%2,%3}, [%4];" : "=r"(v.x), "=r"(v.y), "=r"(v.z), "=r"(v.w) : "r"(a + S0) : "memory");
    return v;
}
__device__ __forceinline__ float4 lds128f(uint32_t a) {
    float4 v;
    asm volatile("ld.shared.v4.f32 {%0,%1,%2,%3}, [%4];" : "=f"(v.x), "=f"(v.y), "=f"(v.z), "=f"(v.w) : "r"(a + S0) : "memory");
    return v;
}
__device__ __forceinline__ float2 lds64f(uint32_t a) {
    float2 v;
    asm volatile("ld.shared.v2.f32 {%0,%1}, [%2];" : "=f"(v.x), "=f"(v.y) : "r"(a + S0) : "memory");
    return v;
}
__device__ __forceinline__ float bf_lo(uint32_t u) { return __uint_as_float(u << 16); }
__device__ __forceinline__ float bf_hi(uint32_t u) { return __uint_as_float(u & 0xffff0000u); }
__device__ __forceinline__ uint32_t pack_bf(float lo, float hi) {
    uint32_t r;
    asm("cvt.rn.bf16x2.f32 %0, %1, %2;" : "=r"(r) : "f"(hi), "f"(lo));
    return r;
}
__device__ __forceinline__ float tanh_fast(float x) {
    float r;
    asm("tanh.approx.f32 %0, %1;" : "=f"(r) : "f"(x));
    return r;
}
__device__ __forceinline__ float silu_half(float h) { return fmaf(h, tanh_fast(h), h); }
__device__ __forceinline__ void ldsm4(uint32_t (&u)[4], uint32_t a) {
    asm volatile("ldmatrix.sync.aligned.m8n8.x4.shared.b16 {%0,%1,%2,%3}, [%4];"
                 : "=r"(u[0]), "=r"(u[1]), "=r"(u[2]), "=r"(u[3]) : "r"(a + S0) : "memory");
}
__device__ __forceinline__ void ldsm4t(uint32_t (&u)[4], uint32_t a) {
    asm volatile("ldmatrix.sync.aligned.m8n8.x4.trans.shared.b16 {%0,%1,%2,%3}, [%4];"
                 : "=r"(u[0]), "=r"(u[1]), "=r"(u[2]), "=r"(u[3]) : "r"(a + S0) : "memory");
}
__device__ __forceinline__ void stsm4(uint32_t a, uint32_t p0, uint32_t p1, uint32_t p2, uint32_t p3) {
    asm volatile("stmatrix.sync.aligned.m8n8.x4.shared.b16 [%0], {%1,%2,%3,%4};" ::"r"(a + S0), "r"(p0), "r"(p1), "r"(p2), "r"(p3) : "memory");
}
__device__ __forceinline__ void stsm4t(uint32_t a, uint32_t p0, uint32_t p1, uint32_t p2, uint32_t p3) {
    asm volatile("stmatrix.sync.aligned.m8n8.x4.trans.shared.b16 [%0], {%1,%2,%3,%4};" ::"r"(a + S0), "r"(p0), "r"(p1), "r"(p2), "r"(p3) : "memory");
}

#define R8(o) "+f"(d[o]), "+f"(d[o + 1]), "+f"(d[o + 2]), "+f"(d[o + 3]), "+f"(d[o + 4]), "+f"(d[o + 5]), "+f"(d[o + 6]), "+f"(d[o + 7])
template <uint32_t ALO, uint32_t BLO, uint64_t AHI = 8>
__device__ __forceinline__ void wgmma128(float (&d)[64]) {
    asm volatile(
        "wgmma.mma_async.sync.aligned.m64n128k16.f32.bf16.bf16 "
        "{%0,%1,%2,%3,%4,%5,%6,%7,%8,%9,%10,%11,%12,%13,%14,%15,%16,%17,%18,%19,%20,%21,%22,%23,%24,%25,%26,%27,%28,%29,%30,%31,"
        "%32,%33,%34,%35,%36,%37,%38,%39,%40,%41,%42,%43,%44,%45,%46,%47,%48,%49,%50,%51,%52,%53,%54,%55,%56,%57,%58,%59,%60,%61,%62,%63},"
        " %64, %65, 1, 1, 1, 0, 0;"
        : R8(0), R8(8), R8(16), R8(24), R8(32), R8(40), R8(48), R8(56)
        : "l"((AHI << 32) | ALO), "l"((8ull << 32) | BLO));
}
template <int S>
__device__ __forceinline__ void mma_stages(float (&d)[64], int conv, int tid, Scratch* gs) {
    constexpr uint32_t A = ((SM_ACT + S * 2 * CH_PITCH + 16) >> 4) | ((CH_PITCH >> 4) << 16);
    constexpr uint32_t B = (slot_addr(S % NS) >> 4) | ((2048 >> 4) << 16);
    if (S == 0) mbar_wait(BAR(BAR_FULL), conv);
    bool next_ok = true;
    constexpr uint32_t NEXT = S + 1 < NSTAGE ? BAR(BAR_FULL + S + 1) : BAR(BAR_EMB);
    const int npar = S + 1 < NSTAGE ? conv : 0;
    next_ok = mbar_test(NEXT, npar);
    if (S == 0 && tid == 0) TL(32 + conv * 24);
    asm volatile("wgmma.fence.sync.aligned;" ::: "memory");
    wgmma128<A, B>(d);
    wgmma128<A + 1, B + (STEP_BYTES >> 4)>(d);
    wgmma128<A + 2, B + 2 * (STEP_BYTES >> 4)>(d);
    asm volatile("wgmma.commit_group.sync.aligned;" ::: "memory");
    if (S >= LAG) {
        asm volatile("wgmma.wait_group.sync.aligned %0;" ::"n"(LAG) : "memory");
        if ((tid & 31) == 0) mbar_arrive(BAR(BAR_WEMPTY + (S + NS - LAG) % NS));
    }
    if (!next_ok) mbar_wait(NEXT, npar);
    if constexpr (S + 1 < NSTAGE) mma_stages<S + 1>(d, conv, tid, gs);
}

__device__ __forceinline__ void weight_block(const uint4 (&t)[5], uint32_t bounce, unsigned char* wt, int cta, int lane) {
    const uint32_t bw = bounce + (lane >> 4) * 1152 + (lane & 15) * 16;
#pragma unroll
    for (int k = 0; k < 4; k++) sts128(bw + k * 256, t[k]);
    if ((lane & 15) < 8) sts128(bw + 1024, t[4]);
    __syncwarp();
    if (lane < 16) {
        uint32_t v[36];
#pragma unroll
        for (int i = 0; i < 9; i++) {
            const uint4 q = lds128(bounce + (lane & 1) * 1152 + (lane >> 1) * 144 + i * 16);
            v[4 * i] = q.x; v[4 * i + 1] = q.y; v[4 * i + 2] = q.z; v[4 * i + 3] = q.w;
        }
        const int cc = (cta >> 6) * 8 + (lane >> 1);
        unsigned char* dst = wt + (cc >> 1) * STAGE_BYTES + (cc & 1) * 2048 + ((cta & 63) * 2 + (lane & 1)) * 16;
#pragma unroll
        for (int kyo = 0; kyo < 3; kyo++) {
#pragma unroll
            for (int kx = 0; kx < 3; kx++) {
                const int tap = ky_of(kyo) * 3 + kx;
                uint32_t o[4];
#pragma unroll
                for (int m = 0; m < 4; m++) {
                    const int i0 = 18 * m + tap, i1 = i0 + 9;
                    const uint32_t sel = ((i0 & 1) ? 0x32u : 0x10u) | ((i1 & 1) ? 0x7600u : 0x5400u);
                    o[m] = __byte_perm(v[i0 >> 1], v[i1 >> 1], sel);
                }
                *reinterpret_cast<uint4*>(dst + (kyo * 24 + kx) * STEP_BYTES) = make_uint4(o[0], o[1], o[2], o[3]);
            }
        }
    }
}
__device__ __forceinline__ uint32_t act2(uint32_t u, const float4& cf) {
    return pack_bf(silu_half(fmaf(bf_lo(u), cf.x, cf.z)), silu_half(fmaf(bf_hi(u), cf.y, cf.w)));
}
__device__ __forceinline__ void norm_unit(uint32_t (&u)[4], const float4& ca, const float4& cb) {
    u[0] = act2(u[0], ca); u[1] = act2(u[1], ca); u[2] = act2(u[2], cb); u[3] = act2(u[3], cb);
}
template <int FIRST, int N>
__device__ __forceinline__ void norm_block(uint32_t (&u)[4][4], uint32_t cfa, uint32_t act, uint32_t fbar, int lane) {
    float4 cf[2 * N];
#pragma unroll
    for (int i = 0; i < 2 * N; i++) cf[i] = lds128f(cfa + (FIRST + (i >> 1)) * 256 + (i & 1) * 64);
#pragma unroll
    for (int t = 0; t < N; t++) {
        norm_unit(u[FIRST + t], cf[2 * t], cf[2 * t + 1]);
        stsm4(act + (FIRST + t) * 2 * KC_BYTES, u[FIRST + t][0], u[FIRST + t][1], u[FIRST + t][2], u[FIRST + t][3]);
    }
    fence_async_smem();
    __syncwarp();
    if (lane < N) mbar_arrive(fbar + 16 * (FIRST + lane));
}
__device__ __forceinline__ void stat_mma(float (&c)[4], uint32_t p, uint32_t q) {
    asm("mma.sync.aligned.m16n8k16.row.col.f32.bf16.bf16.f32 {%0,%1,%2,%3}, {%4,%5,%6,%5}, {%4,%6}, {%0,%1,%2,%3};"
        : "+f"(c[0]), "+f"(c[1]), "+f"(c[2]), "+f"(c[3]) : "r"(p), "r"(0x3f803f80u), "r"(q));
}
__device__ __forceinline__ void stat_store(const float (&c)[4], uint32_t dst, int lane) {
    const int g = lane >> 2, t = lane & 3;
    if (t == (g >> 1)) sts32f(dst + g * 4, (g & 1) ? c[1] : c[0]);
    if (g == 7) sts32f(dst + 32 + t * 4, c[2] + c[3]);
}
__device__ __forceinline__ float sum4(float4 v) { return (v.x + v.y) + (v.z + v.w); }
__device__ __forceinline__ void stat_publish(uint32_t src, float* acc, int lane, bool real) {
    const uint32_t a = src + (lane & 15) * 48;
    float q = sum4(lds128f(a)) + sum4(lds128f(a + 16)), sm = sum4(lds128f(a + 32));
    q += __shfl_xor_sync(0xffffffffu, q, 1); sm += __shfl_xor_sync(0xffffffffu, sm, 1);
    q += __shfl_xor_sync(0xffffffffu, q, 2); sm += __shfl_xor_sync(0xffffffffu, sm, 2);
    if (real && (lane & 19) == 0) red_add4(acc + lane, 1.f, sm, q, 1.f);
}
__device__ __forceinline__ void fence_acc(float (&d)[64]) {
#pragma unroll
    for (int i = 0; i < 64; i++) asm volatile("" : "+f"(d[i])::"memory");
}
__device__ __forceinline__ void ld_unit(uint32_t (&u)[4], const uint4* p) {
    asm volatile("ld.relaxed.gpu.global.v4.u32 {%0,%1,%2,%3}, [%4];" : "=r"(u[0]), "=r"(u[1]), "=r"(u[2]), "=r"(u[3]) : "l"(p) : "memory");
}

__global__ void __cluster_dims__(2, 1, 1) __launch_bounds__(NTHREADS, 1)
resblock_kernel(const __nv_bfloat16* __restrict__ x, const __nv_bfloat16* __restrict__ w1,
                const __nv_bfloat16* __restrict__ t_emb, const __nv_bfloat16* __restrict__ g1,
                const __nv_bfloat16* __restrict__ be1, const __nv_bfloat16* __restrict__ w_emb,
                const __nv_bfloat16* __restrict__ g2, const __nv_bfloat16* __restrict__ be2,
                const __nv_bfloat16* __restrict__ w2, __nv_bfloat16* __restrict__ out, Scratch* __restrict__ gs) {
    const unsigned clk0 = clock32();
    const int tid = threadIdx.x, warp = tid >> 5, lane = tid & 31;
    const int cta = blockIdx.x, b = cta >> 6, r = cta & 63;

    const uint32_t woff = ((2 * r + (lane >> 4)) * C + b * 64) * 18 + (lane & 15) * 16;
    const int c0 = (warp - 8) * 16 + (lane >> 3), seg = lane & 7;
    uint4 v[5];
    if (warp == 0) {
        const char* w1s = reinterpret_cast<const char*>(w1) + woff;
#pragma unroll
        for (int k = 0; k < 4; k++) v[k] = __ldg(reinterpret_cast<const uint4*>(w1s + k * 256));
        if ((lane & 15) < 8) v[4] = __ldg(reinterpret_cast<const uint4*>(w1s + 1024));
    }
    if (warp == 0 || warp > 3) asm volatile("barrier.cluster.arrive.relaxed.aligned;" ::: "memory");
    const bool loader = warp >= 8;
    if (loader || warp == 5) {
        if (loader) {
            const char* src = reinterpret_cast<const char*>(x) + (uint32_t)(((b * C + c0) * HW + r) * HW * 2 + seg * 16);
            while (clock32() - clk0 < XDELAY) {}
#pragma unroll
            for (int k = 0; k < 4; k++) v[k] = __ldg(reinterpret_cast<const uint4*>(src + k * (4 * HW * HW * 2)));
        } else {
#pragma unroll
            for (int k = 0; k < 4; k++) v[k] = make_uint4(0, 0, 0, 0);
        }
        float c[2][4] = {{0.f, 0.f, 0.f, 0.f}, {0.f, 0.f, 0.f, 0.f}};
#pragma unroll
        for (int k = 0; k < 4; k++) { stat_mma(c[0], v[k].x, v[k].y); stat_mma(c[1], v[k].z, v[k].w); }
        stat_store(c[0], SM_RED + (warp & 7) * 96 + (loader ? 0 : 384), lane);
        stat_store(c[1], SM_RED + (warp & 7) * 96 + 48 + (loader ? 0 : 384), lane);
        if (tid == 256) TL(2);
        if (loader) bar_sync(3, 256);
        if (warp <= 8) stat_publish(SM_RED, &gs->acc[b * 32], lane, warp == 8);
        if (tid == 256) TL(3);
        if (loader) {
#pragma unroll
            for (int i = 0; i < 4; i++) sts128(SM_XOWN + c0 * 128 + i * 512 + ((seg ^ ((c0 + 4 * i) & 7)) << 4), v[i]);
        }
    }
    if (warp == 0) {
        weight_block(v, SM_BNC, gs->wt, cta, lane);
        if (r == 0) {
            if (lane < 16) gs->acc[(NB + b) * 32 + lane] = 0.f;
            *reinterpret_cast<float4*>(&gs->emb[b * C + lane * 4]) = make_float4(0.f, 0.f, 0.f, 0.f);
        }
        __syncwarp();
        if (lane == 0) TL(4);
        if (lane < 2) asm volatile("red.release.gpu.global.add.u32 [%0], 1;" ::"l"(&gs->wcnt[lane * 32]) : "memory");
        if (lane == 0) TL(5);
    }

    if (warp >= 8) {
        const int nw = warp - 8;
        bar_sync(4, 256 + 96);
        const int par = nw >> 2, wq = nw & 3;
        const uint32_t act_off = SM_ACT + (par * 2 + (lane >> 4)) * CH_PITCH + (2 + wq * 16 + (lane & 15)) * 16;
        const uint32_t stg_off = SM_XOWN + (par * 16 + (lane >> 4) * 8 + (lane & 7)) * 128 + (((2 * wq + ((lane >> 3) & 1)) ^ (lane & 7)) << 4);
        const uint32_t cfa = SM_COEF + par * 128 + (lane & 3) * 16;
        const uint32_t fbar = BAR(BAR_FULL) + 8 * par;
        const bool has_outer = (r != 0) && (r != HW - 1);
#pragma unroll 1
        for (int conv = 0; conv < 2; conv++) {
            uint32_t u[4][4];
            if (conv == 0) {
#pragma unroll
                for (int i = 0; i < 4; i++) ldsm4t(u[i], stg_off + i * 4096);
            } else {
                mbar_wait(BAR(BAR_HW), 0);
#pragma unroll
                for (int i = 0; i < 4; i++) ldsm4(u[i], act_off + i * 2 * KC_BYTES);
            }
            uint4* inbox = gs->box + (conv * NCTA + cta) * 1024 + nw * 32 + lane;
            mbar_wait(BAR(BAR_STATS), conv);
            if (tid == 256) TL(22 + conv * 4);
            norm_block<0, NA>(u, cfa, act_off, fbar, lane);
            if (tid == 256) TL(8 + conv * 8);
            norm_block<2, 2>(u, cfa, act_off, fbar, lane);
            if (tid == 256) TL(84 + conv);
            if (has_outer) {
                uint4* outbox = inbox + ((r & 1) ? 1024 : -1024);
#pragma unroll
                for (int i = 0; i < 4; i++) outbox[i * 256] = make_uint4(~u[i][0], ~u[i][1], ~u[i][2], ~u[i][3]);
                const unsigned c1 = clock32();
                while (clock32() - c1 < HDELAY) {}
                unsigned it = 0;
                while (ld_relaxed(inbox + 3 * 256 + 31 - lane) == 0 && ++it < SPIN_LIMIT) {}
                if (tid == 256) TL(88 + conv);
                while (true) {
#pragma unroll
                    for (int i = 0; i < 4; i++) ld_unit(u[i], inbox + i * 256);
                    bool ok = true;
#pragma unroll
                    for (int i = 0; i < 16; i++) ok = ok && u[i >> 2][i & 3] != 0;
                    if (__all_sync(0xffffffffu, ok) || ++it > SPIN_LIMIT) break;
                }
            } else {
#pragma unroll
                for (int i = 0; i < 16; i++) u[i >> 2][i & 3] = ~0u;
            }
            if (tid == 256) TL(24 + conv * 4);
#pragma unroll
            for (int i = 0; i < 4; i++) stsm4(act_off + 2 * ROW_BYTES + i * 2 * KC_BYTES, ~u[i][0], ~u[i][1], ~u[i][2], ~u[i][3]);
            fence_async_smem();
            __syncwarp();
            if (lane < 4) mbar_arrive(fbar + 128 + 16 * lane);
            if (tid == 256) TL(23 + conv * 4);
            if (has_outer) {
#pragma unroll
                for (int i = 0; i < 4; i++) inbox[i * 256] = make_uint4(0, 0, 0, 0);
            }
        }
    } else if (warp < 4) {
        const int wq = warp;
        if (wq != 0) {
            const int t = tid - 32;
            if (lane == 0) {
                if (wq == 1) {
#pragma unroll
                    for (int i = 0; i < 12; i++) mbar_init(BAR(BAR_FULL + i), i < 8 ? 5 : 1);
                } else if (wq == 2) {
#pragma unroll
                    for (int i = 12; i < NSTAGE; i++) mbar_init(BAR(BAR_FULL + i), i < 16 ? 1 : 5);
                    mbar_init(BAR(BAR_EMB), 2);
                    mbar_init(BAR(BAR_ACK), 1);
                } else {
#pragma unroll
                    for (int i = 0; i <= NS; i++) mbar_init(BAR(BAR_WEMPTY + i), 4);
                    mbar_init(BAR(BAR_STATS), 1);
                    mbar_init(BAR(BAR_WACQ), 1);
                }
                asm volatile("fence.mbarrier_init.release.cluster;" ::: "memory");
            }
            fence_async_smem();
            bar_arrive(0, 96 + 128);
            bar_arrive(4, 256 + 96);
            if (t == 95) TLG(1);
            const uint4 z = make_uint4(0, 0, 0, 0);
            sts128(SM_ACT + (t >> 1) * CH_PITCH + (t & 1) * 16, z);
            if (t < 2) sts128(SM_ACT + 3 * ROW_BYTES + t * 16, z);
            if (t < 16) sts128(SM_ONES + t * 16, make_uint4(t < 8 ? 0x3f803f80u : 0u, 0, 0, 0));
            fence_async_smem();
            asm volatile("barrier.cluster.arrive.release.aligned;" ::: "memory");
        }
        bar_sync(2, 128);

        float d[64];
#pragma unroll
        for (int i = 0; i < 64; i++) d[i] = 0.f;
#pragma unroll 1
        for (int conv = 0; conv < 2; conv++) {
            fence_acc(d);
            mma_stages<0>(d, conv, tid, gs);
            if (conv == 0) {
                asm volatile("wgmma.fence.sync.aligned;" ::: "memory");
                wgmma128<(SM_ONES >> 4) | (8u << 16), (SM_EMB >> 4), 0>(d);
                asm volatile("wgmma.commit_group.sync.aligned;" ::: "memory");
            }
            asm volatile("wgmma.wait_group.sync.aligned 0;" ::: "memory");
            fence_acc(d);
            if (tid == 0) TL(10 + conv * 8);
            if (conv == 1) break;

            uint32_t hp[32];
#pragma unroll
            for (int g = 0; g < 4; g++) {
                float c[4] = {0.f, 0.f, 0.f, 0.f};
#pragma unroll
                for (int i = 0; i < 8; i++) hp[8 * g + i] = pack_bf(d[16 * g + 2 * i], d[16 * g + 2 * i + 1]);
#pragma unroll
                for (int i = 0; i < 4; i++) stat_mma(c, hp[8 * g + 2 * i], hp[8 * g + 2 * i + 1]);
                stat_store(c, SM_RED + (g * 4 + wq) * 48, lane);
            }
            bar_sync(2, 128);
            if (wq == 0) stat_publish(SM_RED, &gs->acc[(NB + b) * 32], lane, true);
            if (tid == 0) TL(11);
            const uint32_t hbase = SM_ACT + (lane >> 4) * CH_PITCH + (2 + wq * 16 + (lane & 15)) * 16;
#pragma unroll
            for (int kc = 0; kc < 8; kc++) stsm4(hbase + kc * 2 * CH_PITCH, hp[4 * kc], hp[4 * kc + 1], hp[4 * kc + 2], hp[4 * kc + 3]);
            __syncwarp();
            if (lane == 0) mbar_arrive(BAR(BAR_HW));
            if (lane < LAG) mbar_arrive(BAR(BAR_WEMPTY + (NSTAGE - LAG) % NS) + 8 * lane);
            if (tid == 0) TL(12);
            const uint32_t xbase = SM_XOWN + ((lane >> 4) * 8 + (lane & 7)) * 128 + (((2 * wq + ((lane >> 3) & 1)) ^ (lane & 7)) << 4);
#pragma unroll
            for (int kc = 0; kc < 8; kc++) {
                uint32_t p[4];
                ldsm4t(p, xbase + kc * 2048);
#pragma unroll
                for (int i = 0; i < 4; i++) { d[8 * kc + 2 * i] = bf_lo(p[i]); d[8 * kc + 2 * i + 1] = bf_hi(p[i]); }
            }
        }
        {
            const uint32_t obase = slot_addr(0) + ((lane >> 4) * 8 + (lane & 7)) * OUT_PITCH + (wq * 16 + ((lane >> 3) & 1) * 8) * 2;
#pragma unroll
            for (int kc = 0; kc < 8; kc++) {
                stsm4t(obase + kc * 16 * OUT_PITCH, pack_bf(d[8 * kc + 0], d[8 * kc + 1]), pack_bf(d[8 * kc + 2], d[8 * kc + 3]),
                       pack_bf(d[8 * kc + 4], d[8 * kc + 5]), pack_bf(d[8 * kc + 6], d[8 * kc + 7]));
            }
            bar_sync(2, 128);
            const int oc0 = tid >> 3;
            __nv_bfloat16* dst = out + ((size_t)(b * C + oc0) * HW + r) * HW + seg * 8;
#pragma unroll
            for (int i = 0; i < 8; i++)
                *reinterpret_cast<uint4*>(dst + (size_t)i * 16 * HW * HW) = lds128(slot_addr(0) + (oc0 + 16 * i) * OUT_PITCH + seg * 16);
            if (tid == 0) { TL(20); TLG(21); }
        }
    } else if (warp < 6) {
        bar_sync(0, 96 + 128);
        if (warp == 5) {
            asm volatile("barrier.cluster.wait.acquire.aligned;" ::: "memory");
            const uint32_t peer = (r & 1) ^ 1;
            const uint32_t self0 = mapa(0, r & 1), peer0 = mapa(0, peer);
#pragma unroll 1
            for (int conv = 0; conv < 2; conv++) {
#pragma unroll 1
                for (int kc = 0; kc < 8; kc++) {
                    mbar_wait(BAR(BAR_FULL) + 8 * kc, conv);
                    if (elect_one())
                        asm volatile("cp.async.bulk.shared::cluster.shared::cta.mbarrier::complete_tx::bytes [%0], [%1], %2, [%3];"
                                     ::"r"(peer0 + SM_ACT + ROW_BYTES + kc * KC_BYTES), "r"(self0 + SM_ACT + kc * KC_BYTES), "r"(KC_BYTES),
                                       "r"(peer0 + BAR(BAR_FULL + 8) + 8 * kc) : "memory");
                }
                if (lane == 0) TL(86 + conv);
#pragma unroll 1
                for (int kc = 0; kc < 8; kc++) mbar_wait(BAR(BAR_FULL + 8) + 8 * kc, conv);
                if (lane == 0)
                    asm volatile("mbarrier.arrive.release.cluster.shared::cluster.b64 _, [%0];" ::"r"(peer0 + (conv ? BAR(BAR_ACK) : BAR(BAR_EMB))) : "memory");
            }
            mbar_wait(BAR(BAR_ACK), 0);
        } else {
            while (clock32() - clk0 < W2DELAY) {}
            const char* w2s = reinterpret_cast<const char*>(w2) + woff;
#pragma unroll
            for (int k = 0; k < 4; k++) v[k] = __ldg(reinterpret_cast<const uint4*>(w2s + k * 256));
            if ((lane & 15) < 8) v[4] = __ldg(reinterpret_cast<const uint4*>(w2s + 1024));
            const uint2* wsrc = reinterpret_cast<const uint2*>(w_emb + (size_t)r * 12 * C) + lane;
            uint2 wv[12];
#pragma unroll
            for (int i = 0; i < 12; i++) wv[i] = __ldg(wsrc + i * (C / 4));
            float tv = 0.f;
            if (lane < 12) tv = __bfloat162float(t_emb[b * E + r * 12 + lane]);
            weight_block(v, SM_BNC + 2304, gs->wt + NSTAGE * STAGE_BYTES, cta, lane);
            const float sv = silu_half(0.5f * tv);
            float e0 = 0.f, e1 = 0.f, e2 = 0.f, e3 = 0.f;
#pragma unroll
            for (int i = 0; i < 12; i++) {
                const float sx = __shfl_sync(0xffffffffu, sv, i);
                e0 = fmaf(sx, bf_lo(wv[i].x), e0); e1 = fmaf(sx, bf_hi(wv[i].x), e1);
                e2 = fmaf(sx, bf_lo(wv[i].y), e2); e3 = fmaf(sx, bf_hi(wv[i].y), e3);
            }
            mbar_wait(BAR(BAR_WACQ), 0);
            red_add4(&gs->emb[b * C + lane * 4], e0, e1, e2, e3);
            __syncwarp();
            if (lane == 0) TL(13);
            if (lane < 2) asm volatile("red.release.gpu.global.add.u32 [%0], 1;" ::"l"(&gs->wcnt[(NB + lane) * 32]) : "memory");
            if (lane == 0) TL(14);
            unsigned it = 0;
            while (ld_relaxed(&gs->wcnt[(NB + b) * 32]) < (unsigned)NCTA && ++it < SPIN_LIMIT) {}
            fence_acquire();
            const uint4 ef = ld_relaxed_v4(&gs->emb[b * C + lane * 4]);
            const uint32_t eu[4] = {ef.x, ef.y, ef.z, ef.w};
#pragma unroll
            for (int i = 0; i < 4; i++) {
                const float e = __uint_as_float(eu[i]);
                const float hi = bf_lo(pack_bf(e, 0.f));
                sts128(SM_EMB + (lane * 4 + i) * 16, make_uint4(pack_bf(hi, e - hi), 0, 0, 0));
            }
            fence_async_smem();
            __syncwarp();
            if (lane == 0) { mbar_arrive(BAR(BAR_EMB)); TL(19); }
        }
    } else if (warp == 6) {
        bar_sync(0, 96 + 128);
        unsigned it = 0;
        while (ld_relaxed(&gs->wcnt[b * 32]) < (unsigned)NCTA && ++it < SPIN_LIMIT) {}
        fence_acquire();
        fence_async_global();
        if (lane == 0) { mbar_arrive(BAR(BAR_WACQ)); TL(6); }
        const uint32_t self0 = mapa(0, r & 1);
        const int swap = (r & 1) ? 0 : 8;
#pragma unroll 1
        for (int round = 0; round < 2 * NSTAGE / NS; round++) {
            if (round == NSTAGE / NS) { mbar_wait(BAR(BAR_EMB), 0); fence_async_global(); }
            const int s0 = (round & 1) * NS;
            const unsigned char* wsrc = gs->wt + (round >> 1) * NSTAGE * STAGE_BYTES;
#pragma unroll
            for (int slot = 0; slot < NS; slot++) {
                const int st = s0 + slot;
                const bool prow = st >= 8 && st < 16;
                mbar_wait(BAR(BAR_WEMPTY + slot), (round & 1) ^ 1);
                if (elect_one()) {
                    mbar_expect(BAR(BAR_FULL) + 8 * st, STAGE_BYTES + (prow ? KC_BYTES : 0));
                    bulk_g2s(self0 + slot_addr(slot), wsrc + (st < 8 ? st : (prow ? st + swap : st - swap)) * STAGE_BYTES, STAGE_BYTES,
                             self0 + BAR(BAR_FULL) + 8 * st);
                }
            }
        }
    } else {
        const uint2 ga1 = __ldg(reinterpret_cast<const uint2*>(g1) + lane), bt1 = __ldg(reinterpret_cast<const uint2*>(be1) + lane);
        const uint2 ga2 = __ldg(reinterpret_cast<const uint2*>(g2) + lane), bt2 = __ldg(reinterpret_cast<const uint2*>(be2) + lane);
        bar_sync(0, 96 + 128);
#pragma unroll 1
        for (int conv = 0; conv < 2; conv++) {
            if (conv == 1) mbar_wait(BAR(BAR_EMB), 0);
            const float* asrc = &gs->acc[(conv * NB + b) * 32 + (lane >> 3) * 4];
            uint4 f;
            unsigned it = 0;
            while (true) {
                f = ld_relaxed_v4(asrc);
                const bool ok = (f.x == 0x42800000u) & (f.w == 0x42800000u);
                if (__all_sync(0xffffffffu, ok) || ++it > SPIN_LIMIT) break;
            }
            if (lane == 0) TL(7 + conv * 8);
            const float inv_n = 1.0f / (32.0f * HW * HW);
            const float mean = __uint_as_float(f.y) * inv_n;
            const float var = fmaxf(fmaf(-mean, mean, __uint_as_float(f.z) * inv_n), 0.f);
            const float rs = 0.5f * rsqrtf(var + 1e-5f);
            const uint2 ga = conv ? ga2 : ga1, bt = conv ? bt2 : bt1;
            float4 k0, k1;
            k0.x = rs * bf_lo(ga.x); k0.y = rs * bf_hi(ga.x); k1.x = rs * bf_lo(ga.y); k1.y = rs * bf_hi(ga.y);
            k0.z = fmaf(-mean, k0.x, 0.5f * bf_lo(bt.x)); k0.w = fmaf(-mean, k0.y, 0.5f * bf_hi(bt.x));
            k1.z = fmaf(-mean, k1.x, 0.5f * bf_lo(bt.y)); k1.w = fmaf(-mean, k1.y, 0.5f * bf_hi(bt.y));
            sts128f(SM_COEF + lane * 32, k0);
            sts128f(SM_COEF + lane * 32 + 16, k1);
            __syncwarp();
            if (lane == 0) mbar_arrive(BAR(BAR_STATS));
        }
        if (r == 0) {
            if (lane < 16) gs->acc[b * 32 + lane] = 0.f;
            if (lane < 2) gs->wcnt[(lane * NB + b) * 32] = 0;
        }
    }
}

}

extern "C" void kernel_launch(void* const* d_in, const int* in_sizes, int n_in, void* d_out, int out_size) {
    (void)in_sizes; (void)n_in; (void)out_size;
    static Scratch* gs = nullptr;
    if (!gs) {
        cudaFuncSetAttribute(resblock_kernel, cudaFuncAttributeMaxDynamicSharedMemorySize, SM_TOTAL);
        cudaGetSymbolAddress((void**)&gs, g_scratch);
    }
    resblock_kernel<<<NCTA, NTHREADS, SM_TOTAL>>>(
        (const __nv_bfloat16*)d_in[0], (const __nv_bfloat16*)d_in[4], (const __nv_bfloat16*)d_in[1],
        (const __nv_bfloat16*)d_in[2], (const __nv_bfloat16*)d_in[3], (const __nv_bfloat16*)d_in[5],
        (const __nv_bfloat16*)d_in[6], (const __nv_bfloat16*)d_in[7], (const __nv_bfloat16*)d_in[8],
        (__nv_bfloat16*)d_out, gs);
}
```

```cpp
#include <cuda_runtime.h>
#include <cuda_bf16.h>
#include <stdint.h>

namespace {

constexpr int C = 128, HW = 64, NB = 2, E = 768;
constexpr int NCTA = NB * HW;
constexpr int NTHREADS = 16 * 32;
constexpr int CH_PITCH = 66 * 16;
constexpr int ROW_BYTES = 16 * CH_PITCH;
constexpr int STEP_BYTES = 4096;
constexpr int STAGE_BYTES = 3 * STEP_BYTES;
constexpr int NSTAGE = 24;
constexpr int KC_BYTES = 2 * CH_PITCH;
constexpr int NS = 12;
constexpr int LAG = 1;
#define XDELAY 600
#define HDELAY 600
#define NA 2
#define HSEND 0
#define W2DELAY 2800

constexpr uint32_t SMEM_BASE = 0x400;
constexpr uint32_t SM_ACT = SMEM_BASE;
constexpr uint32_t SM_XOWN = SM_ACT + 3 * ROW_BYTES + 128;
constexpr uint32_t SM_XOUT = SM_ACT + 2 * ROW_BYTES + 32;
constexpr uint32_t SM_W = SM_XOWN + 16384;
__host__ __device__ constexpr uint32_t slot_addr(int slot) { return SM_W + slot * STAGE_BYTES; }
constexpr uint32_t SM_COEF = SM_W + NS * STAGE_BYTES;
constexpr uint32_t SM_EMB = SM_COEF + 1024;
constexpr uint32_t SM_ONES = SM_EMB + 2048;
constexpr uint32_t SM_RED = SM_ONES + 256;
constexpr uint32_t SM_BNC = SM_RED + 1280;
constexpr uint32_t SM_BAR = SM_BNC + 2 * 2304;
constexpr int BAR_FULL = 0, BAR_WEMPTY = NSTAGE, BAR_HW = BAR_WEMPTY + NS, BAR_STATS = BAR_HW + 1,
              BAR_EMB = BAR_STATS + 1, BAR_WACQ = BAR_EMB + 1, BAR_ACK = BAR_WACQ + 1, NBAR = BAR_ACK + 1;
constexpr int SM_TOTAL = SM_BAR + NBAR * 8 - SMEM_BASE;
static_assert(SM_TOTAL <= 232448, "smem");
static_assert(NBAR <= 96, "barrier init");
constexpr int OUT_PITCH = 144;
__host__ __device__ constexpr uint32_t BAR(int i) { return SM_BAR + 8 * i; }
__host__ __device__ constexpr int ky_of(int kyo) { return kyo == 0 ? 1 : (kyo == 1 ? 0 : 2); }

constexpr unsigned SPIN_LIMIT = 1u << 16;

struct Scratch {
    float acc[2 * NB * 32];
    unsigned wcnt[2 * NB * 32];
    float emb[NB * C];
    unsigned char wt[2 * NSTAGE * STAGE_BYTES];
    uint4 box[NCTA * 1024];
};
__device__ __align__(1024) Scratch g_scratch;
#define TL(i) do {} while (0)
#define TLG(i) do {} while (0)

__device__ __forceinline__ unsigned clock32() { unsigned c; asm volatile("mov.u32 %0, %%clock;" : "=r"(c)); return c; }
__device__ __forceinline__ uint32_t mapa(uint32_t a, uint32_t rank) {
    uint32_t d;
    asm("mapa.shared::cluster.u32 %0, %1, %2;" : "=r"(d) : "r"(a), "r"(rank));
    return d;
}
#define S0 mapa(0, blockIdx.x & 1)
__device__ __forceinline__ void mbar_init(uint32_t bar, int cnt) {
    asm volatile("mbarrier.init.shared::cta.b64 [%0], %1;" ::"r"(bar + S0), "r"(cnt) : "memory");
}
__device__ __forceinline__ void mbar_arrive(uint32_t bar) {
    asm volatile("mbarrier.arrive.shared::cta.b64 _, [%0];" ::"r"(bar + S0) : "memory");
}
__device__ __forceinline__ void mbar_expect(uint32_t bar, uint32_t bytes) {
    asm volatile("mbarrier.arrive.expect_tx.shared::cta.b64 _, [%0], %1;" ::"r"(bar + S0), "r"(bytes) : "memory");
}
__device__ __forceinline__ bool mbar_try(uint32_t bar, uint32_t par) {
    uint32_t ok;
    asm volatile("{\n.reg .pred p;\nmbarrier.try_wait.parity.shared::cta.b64 p, [%1], %2;\nselp.u32 %0, 1, 0, p;\n}"
                 : "=r"(ok) : "r"(bar + S0), "r"(par) : "memory");
    return ok;
}
__device__ __forceinline__ bool mbar_test(uint32_t bar, uint32_t par) {
    uint32_t ok;
    asm volatile("{\n.reg .pred p;\nmbarrier.test_wait.parity.shared::cta.b64 p, [%1], %2;\nselp.u32 %0, 1, 0, p;\n}"
                 : "=r"(ok) : "r"(bar + S0), "r"(par) : "memory");
    return ok;
}
__device__ __forceinline__ void mbar_wait(uint32_t bar, uint32_t par) {
    unsigned it = 0;
#pragma unroll 1
    while (!mbar_try(bar, par) && ++it < SPIN_LIMIT) {}
}
__device__ __forceinline__ bool elect_one() {
    uint32_t p;
    asm volatile("{\n.reg .pred p;\nelect.sync _|p, 0xffffffff;\nselp.u32 %0, 1, 0, p;\n}" : "=r"(p));
    return p;
}
__device__ __forceinline__ void fence_async_smem() { asm volatile("fence.proxy.async.shared::cta;" ::: "memory"); }
__device__ __forceinline__ void fence_async_global() { asm volatile("fence.proxy.async.global;" ::: "memory"); }
__device__ __forceinline__ void fence_acquire() { asm volatile("fence.acquire.gpu;" ::: "memory"); }
__device__ __forceinline__ void bar_sync(int id, int n) { asm volatile("bar.sync %0, %1;" ::"r"(id), "r"(n) : "memory"); }
__device__ __forceinline__ void bar_arrive(int id, int n) { asm volatile("bar.arrive %0, %1;" ::"r"(id), "r"(n) : "memory"); }
__device__ __forceinline__ void bulk_g2s(uint32_t dst, const void* src, uint32_t bytes, uint32_t bar) {
    asm volatile("cp.async.bulk.shared::cluster.global.mbarrier::complete_tx::bytes [%0], [%1], %2, [%3];"
                 ::"r"(dst), "l"(src), "r"(bytes), "r"(bar) : "memory");
}
__device__ __forceinline__ uint4 ld_relaxed_v4(const void* p) {
    uint4 v;
    asm volatile("ld.relaxed.gpu.global.v4.u32 {%0,%1,%2,%3}, [%4];" : "=r"(v.x), "=r"(v.y), "=r"(v.z), "=r"(v.w) : "l"(p) : "memory");
    return v;
}
__device__ __forceinline__ unsigned ld_relaxed(const void* p) {
    unsigned v;
    asm volatile("ld.relaxed.gpu.global.u32 %0, [%1];" : "=r"(v) : "l"(p) : "memory");
    return v;
}
__device__ __forceinline__ void red_add4(float* p, float a, float b, float c, float d) {
    asm volatile("red.relaxed.gpu.global.add.v4.f32 [%0], {%1,%2,%3,%4};" ::"l"(p), "f"(a), "f"(b), "f"(c), "f"(d) : "memory");
}
__device__ __forceinline__ void sts128(uint32_t a, uint4 v) {
    asm volatile("st.shared.v4.u32 [%0], {%1,%2,%3,%4};" ::"r"(a + S0), "r"(v.x), "r"(v.y), "r"(v.z), "r"(v.w) : "memory");
}
__device__ __forceinline__ void sts128f(uint32_t a, float4 v) {
    asm volatile("st.shared.v4.f32 [%0], {%1,%2,%3,%4};" ::"r"(a + S0), "f"(v.x), "f"(v.y), "f"(v.z), "f"(v.w) : "memory");
}
__device__ __forceinline__ void sts32f(uint32_t a, float v) { asm volatile("st.shared.f32 [%0], %1;" ::"r"(a + S0), "f"(v) : "memory"); }
__device__ __forceinline__ uint4 lds128(uint32_t a) {
    uint4 v;
    asm volatile("ld.shared.v4.u32 {%0,%1,%2,%3}, [%4];" : "=r"(v.x), "=r"(v.y), "=r"(v.z), "=r"(v.w) : "r"(a + S0) : "memory");
    return v;
}
__device__ __forceinline__ float4 lds128f(uint32_t a) {
    float4 v;
    asm volatile("ld.shared.v4.f32 {%0,%1,%2,%3}, [%4];" : "=f"(v.x), "=f"(v.y), "=f"(v.z), "=f"(v.w) : "r"(a + S0) : "memory");
    return v;
}
__device__ __forceinline__ float2 lds64f(uint32_t a) {
    float2 v;
    asm volatile("ld.shared.v2.f32 {%0,%1}, [%2];" : "=f"(v.x), "=f"(v.y) : "r"(a + S0) : "memory");
    return v;
}
__device__ __forceinline__ float bf_lo(uint32_t u) { return __uint_as_float(u << 16); }
__device__ __forceinline__ float bf_hi(uint32_t u) { return __uint_as_float(u & 0xffff0000u); }
__device__ __forceinline__ uint32_t pack_bf(float lo, float hi) {
    uint32_t r;
    asm("cvt.rn.bf16x2.f32 %0, %1, %2;" : "=r"(r) : "f"(hi), "f"(lo));
    return r;
}
__device__ __forceinline__ float tanh_fast(float x) {
    float r;
    asm("tanh.approx.f32 %0, %1;" : "=f"(r) : "f"(x));
    return r;
}
__device__ __forceinline__ float silu_half(float h) { return fmaf(h, tanh_fast(h), h); }
__device__ __forceinline__ void ldsm4(uint32_t (&u)[4], uint32_t a) {
    asm volatile("ldmatrix.sync.aligned.m8n8.x4.shared.b16 {%0,%1,%2,%3}, [%4];"
                 : "=r"(u[0]), "=r"(u[1]), "=r"(u[2]), "=r"(u[3]) : "r"(a + S0) : "memory");
}
__device__ __forceinline__ void ldsm4t(uint32_t (&u)[4], uint32_t a) {
    asm volatile("ldmatrix.sync.aligned.m8n8.x4.trans.shared.b16 {%0,%1,%2,%3}, [%4];"
                 : "=r"(u[0]), "=r"(u[1]), "=r"(u[2]), "=r"(u[3]) : "r"(a + S0) : "memory");
}
__device__ __forceinline__ void stsm4(uint32_t a, uint32_t p0, uint32_t p1, uint32_t p2, uint32_t p3) {
    asm volatile("stmatrix.sync.aligned.m8n8.x4.shared.b16 [%0], {%1,%2,%3,%4};" ::"r"(a + S0), "r"(p0), "r"(p1), "r"(p2), "r"(p3) : "memory");
}
__device__ __forceinline__ void stsm4t(uint32_t a, uint32_t p0, uint32_t p1, uint32_t p2, uint32_t p3) {
    asm volatile("stmatrix.sync.aligned.m8n8.x4.trans.shared.b16 [%0], {%1,%2,%3,%4};" ::"r"(a + S0), "r"(p0), "r"(p1), "r"(p2), "r"(p3) : "memory");
}

#define R8(o) "+f"(d[o]), "+f"(d[o + 1]), "+f"(d[o + 2]), "+f"(d[o + 3]), "+f"(d[o + 4]), "+f"(d[o + 5]), "+f"(d[o + 6]), "+f"(d[o + 7])
template <uint32_t ALO, uint32_t BLO, uint64_t AHI = 8>
__device__ __forceinline__ void wgmma128(float (&d)[64]) {
    asm volatile(
        "wgmma.mma_async.sync.aligned.m64n128k16.f32.bf16.bf16 "
        "{%0,%1,%2,%3,%4,%5,%6,%7,%8,%9,%10,%11,%12,%13,%14,%15,%16,%17,%18,%19,%20,%21,%22,%23,%24,%25,%26,%27,%28,%29,%30,%31,"
        "%32,%33,%34,%35,%36,%37,%38,%39,%40,%41,%42,%43,%44,%45,%46,%47,%48,%49,%50,%51,%52,%53,%54,%55,%56,%57,%58,%59,%60,%61,%62,%63},"
        " %64, %65, 1, 1, 1, 0, 0;"
        : R8(0), R8(8), R8(16), R8(24), R8(32), R8(40), R8(48), R8(56)
        : "l"((AHI << 32) | ALO), "l"((8ull << 32) | BLO));
}
template <int S>
__device__ __forceinline__ void mma_stages(float (&d)[64], int conv, int tid, Scratch* gs) {
    constexpr uint32_t A = ((SM_ACT + S * 2 * CH_PITCH + 16) >> 4) | ((CH_PITCH >> 4) << 16);
    constexpr uint32_t B = (slot_addr(S % NS) >> 4) | ((2048 >> 4) << 16);
    if (S == 0) mbar_wait(BAR(BAR_FULL), conv);
    bool next_ok = true;
    constexpr uint32_t NEXT = S + 1 < NSTAGE ? BAR(BAR_FULL + S + 1) : BAR(BAR_EMB);
    const int npar = S + 1 < NSTAGE ? conv : 0;
    next_ok = mbar_test(NEXT, npar);
    if (S == 0 && tid == 0) TL(32 + conv * 24);
    asm volatile("wgmma.fence.sync.aligned;" ::: "memory");
    wgmma128<A, B>(d);
    wgmma128<A + 1, B + (STEP_BYTES >> 4)>(d);
    wgmma128<A + 2, B + 2 * (STEP_BYTES >> 4)>(d);
    asm volatile("wgmma.commit_group.sync.aligned;" ::: "memory");
    if (S >= LAG) {
        asm volatile("wgmma.wait_group.sync.aligned %0;" ::"n"(LAG) : "memory");
        if ((tid & 31) == 0) mbar_arrive(BAR(BAR_WEMPTY + (S + NS - LAG) % NS));
    }
    if (!next_ok) mbar_wait(NEXT, npar);
    if constexpr (S + 1 < NSTAGE) mma_stages<S + 1>(d, conv, tid, gs);
}

__device__ __forceinline__ void weight_block(const uint4 (&t)[5], uint32_t bounce, unsigned char* wt, int cta, int lane) {
    const uint32_t bw = bounce + (lane >> 4) * 1152 + (lane & 15) * 16;
#pragma unroll
    for (int k = 0; k < 4; k++) sts128(bw + k * 256, t[k]);
    if ((lane & 15) < 8) sts128(bw + 1024, t[4]);
    __syncwarp();
    if (lane < 16) {
        uint32_t v[36];
#pragma unroll
        for (int i = 0; i < 9; i++) {
            const uint4 q = lds128(bounce + (lane & 1) * 1152 + (lane >> 1) * 144 + i * 16);
            v[4 * i] = q.x; v[4 * i + 1] = q.y; v[4 * i + 2] = q.z; v[4 * i + 3] = q.w;
        }
        const int cc = (cta >> 6) * 8 + (lane >> 1);
        unsigned char* dst = wt + (cc >> 1) * STAGE_BYTES + (cc & 1) * 2048 + ((cta & 63) * 2 + (lane & 1)) * 16;
#pragma unroll
        for (int kyo = 0; kyo < 3; kyo++) {
#pragma unroll
            for (int kx = 0; kx < 3; kx++) {
                const int tap = ky_of(kyo) * 3 + kx;
                uint32_t o[4];
#pragma unroll
                for (int m = 0; m < 4; m++) {
                    const int i0 = 18 * m + tap, i1 = i0 + 9;
                    const uint32_t sel = ((i0 & 1) ? 0x32u : 0x10u) | ((i1 & 1) ? 0x7600u : 0x5400u);
                    o[m] = __byte_perm(v[i0 >> 1], v[i1 >> 1], sel);
                }
                *reinterpret_cast<uint4*>(dst + (kyo * 24 + kx) * STEP_BYTES) = make_uint4(o[0], o[1], o[2], o[3]);
            }
        }
    }
}
__device__ __forceinline__ uint32_t act2(uint32_t u, const float4& cf) {
    return pack_bf(silu_half(fmaf(bf_lo(u), cf.x, cf.z)), silu_half(fmaf(bf_hi(u), cf.y, cf.w)));
}
__device__ __forceinline__ void norm_unit(uint32_t (&u)[4], const float4& ca, const float4& cb) {
    u[0] = act2(u[0], ca); u[1] = act2(u[1], ca); u[2] = act2(u[2], cb); u[3] = act2(u[3], cb);
}
template <int FIRST, int N>
__device__ __forceinline__ void norm_block(uint32_t (&u)[4][4], float4 (&cf)[8], bool load_cf, uint32_t cfa, uint32_t act, uint32_t mask, uint32_t fbar, int lane) {
    if (load_cf) {
#pragma unroll
        for (int i = 2 * FIRST; i < 2 * (FIRST + N); i++) cf[i] = lds128f(cfa + (i >> 1) * 256 + (i & 1) * 64);
    }
#pragma unroll
    for (int t = FIRST; t < FIRST + N; t++) {
        norm_unit(u[t], cf[2 * t], cf[2 * t + 1]);
        stsm4(act + t * 2 * KC_BYTES, u[t][0] & mask, u[t][1] & mask, u[t][2] & mask, u[t][3] & mask);
    }
    fence_async_smem();
    __syncwarp();
    if (lane < N) mbar_arrive(fbar + 16 * (FIRST + lane));
}
__device__ __forceinline__ void stat_mma(float (&c)[4], uint32_t p, uint32_t q) {
    asm("mma.sync.aligned.m16n8k16.row.col.f32.bf16.bf16.f32 {%0,%1,%2,%3}, {%4,%5,%6,%5}, {%4,%6}, {%0,%1,%2,%3};"
        : "+f"(c[0]), "+f"(c[1]), "+f"(c[2]), "+f"(c[3]) : "r"(p), "r"(0x3f803f80u), "r"(q));
}
__device__ __forceinline__ void stat_store(const float (&c)[4], uint32_t dst, int lane) {
    const int g = lane >> 2, t = lane & 3;
    if (t == (g >> 1)) sts32f(dst + g * 4, (g & 1) ? c[1] : c[0]);
    if (g == 7) sts32f(dst + 32 + t * 4, c[2] + c[3]);
}
__device__ __forceinline__ float sum4(float4 v) { return (v.x + v.y) + (v.z + v.w); }
__device__ __forceinline__ void stat_publish(uint32_t src, float* acc, int lane, bool real) {
    const uint32_t a = src + (lane & 15) * 48;
    float q = sum4(lds128f(a)) + sum4(lds128f(a + 16)), sm = sum4(lds128f(a + 32));
    q += __shfl_xor_sync(0xffffffffu, q, 1); sm += __shfl_xor_sync(0xffffffffu, sm, 1);
    q += __shfl_xor_sync(0xffffffffu, q, 2); sm += __shfl_xor_sync(0xffffffffu, sm, 2);
    if (real && (lane & 19) == 0) red_add4(acc + lane, 1.f, sm, q, 1.f);
}
__device__ __forceinline__ void fence_acc(float (&d)[64]) {
#pragma unroll
    for (int i = 0; i < 64; i++) asm volatile("" : "+f"(d[i])::"memory");
}
__device__ __forceinline__ void ld_unit(uint32_t (&u)[4], const uint4* p) {
    asm volatile("ld.relaxed.gpu.global.v4.u32 {%0,%1,%2,%3}, [%4];" : "=r"(u[0]), "=r"(u[1]), "=r"(u[2]), "=r"(u[3]) : "l"(p) : "memory");
}

__global__ void __cluster_dims__(2, 1, 1) __launch_bounds__(NTHREADS, 1)
resblock_kernel(const __nv_bfloat16* __restrict__ x, const __nv_bfloat16* __restrict__ w1,
                const __nv_bfloat16* __restrict__ t_emb, const __nv_bfloat16* __restrict__ g1,
                const __nv_bfloat16* __restrict__ be1, const __nv_bfloat16* __restrict__ w_emb,
                const __nv_bfloat16* __restrict__ g2, const __nv_bfloat16* __restrict__ be2,
                const __nv_bfloat16* __restrict__ w2, __nv_bfloat16* __restrict__ out, Scratch* __restrict__ gs) {
    const unsigned clk0 = clock32();
    const int tid = threadIdx.x, warp = tid >> 5, lane = tid & 31;
    const int cta = blockIdx.x, b = cta >> 6, r = cta & 63;

    const uint32_t woff = ((2 * r + (lane >> 4)) * C + b * 64) * 18 + (lane & 15) * 16;
    const int c0 = (warp - 8) * 16 + (lane >> 3), seg = lane & 7;
    uint4 v[5];
    if (warp == 0) {
        const char* w1s = reinterpret_cast<const char*>(w1) + woff;
#pragma unroll
        for (int k = 0; k < 4; k++) v[k] = __ldg(reinterpret_cast<const uint4*>(w1s + k * 256));
        if ((lane & 15) < 8) v[4] = __ldg(reinterpret_cast<const uint4*>(w1s + 1024));
    }
    if (warp == 0 || warp > 3) asm volatile("barrier.cluster.arrive.relaxed.aligned;" ::: "memory");
    const bool loader = warp >= 8;
    const bool has_outer = (r != 0) && (r != HW - 1);
    if (loader || warp == 5) {
        if (loader) {
            const char* src = reinterpret_cast<const char*>(x) + (uint32_t)(((b * C + c0) * HW + r) * HW * 2 + seg * 16);
            while (clock32() - clk0 < XDELAY) {}
#pragma unroll
            for (int k = 0; k < 4; k++) v[k] = __ldg(reinterpret_cast<const uint4*>(src + k * (4 * HW * HW * 2)));
            if (has_outer) {
#pragma unroll
                for (int i = 0; i < 4; i++)
                    asm volatile("cp.async.cg.shared.global [%0], [%1], 16;"
                                 ::"r"(S0 + SM_XOUT + c0 * 128 + i * 512 + ((seg ^ ((c0 + 4 * i) & 7)) << 4)),
                                   "l"(src + ((r & 1) ? HW * 2 : -HW * 2) + i * (4 * HW * HW * 2)) : "memory");
            }
        } else {
#pragma unroll
            for (int k = 0; k < 4; k++) v[k] = make_uint4(0, 0, 0, 0);
        }
        float c[2][4] = {{0.f, 0.f, 0.f, 0.f}, {0.f, 0.f, 0.f, 0.f}};
#pragma unroll
        for (int k = 0; k < 4; k++) { stat_mma(c[0], v[k].x, v[k].y); stat_mma(c[1], v[k].z, v[k].w); }
        stat_store(c[0], SM_RED + (warp & 7) * 96 + (loader ? 0 : 384), lane);
        stat_store(c[1], SM_RED + (warp & 7) * 96 + 48 + (loader ? 0 : 384), lane);
        if (tid == 256) TL(2);
        if (loader) bar_sync(3, 256);
        if (warp <= 8) stat_publish(SM_RED, &gs->acc[b * 32], lane, warp == 8);
        if (tid == 256) TL(3);
        if (loader) {
#pragma unroll
            for (int i = 0; i < 4; i++) sts128(SM_XOWN + c0 * 128 + i * 512 + ((seg ^ ((c0 + 4 * i) & 7)) << 4), v[i]);
        }
    }
    if (warp == 0) {
        weight_block(v, SM_BNC, gs->wt, cta, lane);
        if (r == 0) {
            if (lane < 16) gs->acc[(NB + b) * 32 + lane] = 0.f;
            *reinterpret_cast<float4*>(&gs->emb[b * C + lane * 4]) = make_float4(0.f, 0.f, 0.f, 0.f);
        }
        __syncwarp();
        if (lane == 0) TL(4);
        if (lane < 2) asm volatile("red.release.gpu.global.add.u32 [%0], 1;" ::"l"(&gs->wcnt[lane * 32]) : "memory");
        if (lane == 0) TL(5);
    }

    if (warp >= 8) {
        const int nw = warp - 8;
        asm volatile("cp.async.wait_all;" ::: "memory");
        bar_sync(4, 256 + 96);
        const int par = nw >> 2, wq = nw & 3;
        const uint32_t act_off = SM_ACT + (par * 2 + (lane >> 4)) * CH_PITCH + (2 + wq * 16 + (lane & 15)) * 16;
        const uint32_t stg_off = (par * 16 + (lane >> 4) * 8 + (lane & 7)) * 128 + (((2 * wq + ((lane >> 3) & 1)) ^ (lane & 7)) << 4);
        const uint32_t cfa = SM_COEF + par * 128 + (lane & 3) * 16;
        const uint32_t fbar = BAR(BAR_FULL) + 8 * par;
        uint4* inbox = gs->box + cta * 1024 + nw * 32 + lane;
#pragma unroll 1
        for (int conv = 0; conv < 2; conv++) {
            uint32_t u[4][4], w[4][4];
            float4 cf[8];
            if (conv == 0) {
#pragma unroll
                for (int i = 0; i < 4; i++) { ldsm4t(u[i], SM_XOWN + stg_off + i * 4096); ldsm4t(w[i], SM_XOUT + stg_off + i * 4096); }
                bar_sync(3, 256);
                if (nw == 0) sts128(SM_ACT + 2 * ROW_BYTES + (lane >> 1) * CH_PITCH + (lane & 1) * 16, make_uint4(0, 0, 0, 0));
            } else {
                mbar_wait(BAR(BAR_HW), 0);
#pragma unroll
                for (int i = 0; i < 4; i++) ldsm4(u[i], act_off + i * 2 * KC_BYTES);
            }
            mbar_wait(BAR(BAR_STATS), conv);
            if (tid == 256) TL(22 + conv * 4);
            norm_block<0, NA>(u, cf, true, cfa, act_off, ~0u, fbar, lane);
            if (tid == 256) TL(8 + conv * 8);
            norm_block<2, 2>(u, cf, true, cfa, act_off, ~0u, fbar, lane);
            if (tid == 256) TL(84 + conv);
            if (conv == 1 && has_outer) {
                unsigned it = 0;
                while (ld_relaxed(inbox + 3 * 256 + 31 - lane) == 0 && ++it < SPIN_LIMIT) {}
                if (tid == 256) TL(89);
                while (true) {
#pragma unroll
                    for (int i = 0; i < 4; i++) ld_unit(w[i], inbox + i * 256);
                    bool ok = true;
#pragma unroll
                    for (int i = 0; i < 16; i++) ok = ok && w[i >> 2][i & 3] != 0;
                    if (__all_sync(0xffffffffu, ok) || ++it > SPIN_LIMIT) break;
                }
#pragma unroll
                for (int i = 0; i < 16; i++) w[i >> 2][i & 3] = ~w[i >> 2][i & 3];
            }
            if (tid == 256) TL(24 + conv * 4);
            norm_block<0, 4>(w, cf, false, cfa, act_off + 2 * ROW_BYTES, has_outer ? ~0u : 0u, fbar + 128, lane);
            if (tid == 256) TL(23 + conv * 4);
        }
        if (has_outer) {
            mbar_wait(BAR(BAR_FULL + NSTAGE - 1), 1);
#pragma unroll
            for (int i = 0; i < 4; i++) inbox[i * 256] = make_uint4(0, 0, 0, 0);
        }
    } else if (warp < 4) {
        const int wq = warp;
        if (wq != 0) {
            const int t = tid - 32;
            if (lane == 0) {
                if (wq == 1) {
#pragma unroll
                    for (int i = 0; i < 12; i++) mbar_init(BAR(BAR_FULL + i), i < 8 ? 5 : 1);
                } else if (wq == 2) {
#pragma unroll
                    for (int i = 12; i < NSTAGE; i++) mbar_init(BAR(BAR_FULL + i), i < 16 ? 1 : 5);
                    mbar_init(BAR(BAR_EMB), 2);
                    mbar_init(BAR(BAR_ACK), 1);
                } else {
#pragma unroll
                    for (int i = 0; i <= NS; i++) mbar_init(BAR(BAR_WEMPTY + i), 4);
                    mbar_init(BAR(BAR_STATS), 1);
                    mbar_init(BAR(BAR_WACQ), 1);
                }
                asm volatile("fence.mbarrier_init.release.cluster;" ::: "memory");
            }
            fence_async_smem();
            bar_arrive(0, 96 + 128);
            bar_arrive(4, 256 + 96);
            if (t == 95) TLG(1);
            const uint4 z = make_uint4(0, 0, 0, 0);
            if (t < 66) sts128(SM_ACT + (t >> 1) * CH_PITCH + (t & 1) * 16, z);
            if (t < 2) sts128(SM_ACT + 3 * ROW_BYTES + t * 16, z);
            if (t < 16) sts128(SM_ONES + t * 16, make_uint4(t < 8 ? 0x3f803f80u : 0u, 0, 0, 0));
            fence_async_smem();
            asm volatile("barrier.cluster.arrive.release.aligned;" ::: "memory");
        }
        bar_sync(2, 128);

        float d[64];
#pragma unroll
        for (int i = 0; i < 64; i++) d[i] = 0.f;
#pragma unroll 1
        for (int conv = 0; conv < 2; conv++) {
            fence_acc(d);
            mma_stages<0>(d, conv, tid, gs);
            if (conv == 0) {
                asm volatile("wgmma.fence.sync.aligned;" ::: "memory");
                wgmma128<(SM_ONES >> 4) | (8u << 16), (SM_EMB >> 4), 0>(d);
                asm volatile("wgmma.commit_group.sync.aligned;" ::: "memory");
            }
            asm volatile("wgmma.wait_group.sync.aligned 0;" ::: "memory");
            fence_acc(d);
            if (tid == 0) TL(10 + conv * 8);
            if (conv == 1) break;

            uint32_t hp[32];
#pragma unroll
            for (int g = 0; g < 4; g++) {
                float c[4] = {0.f, 0.f, 0.f, 0.f};
#pragma unroll
                for (int i = 0; i < 8; i++) hp[8 * g + i] = pack_bf(d[16 * g + 2 * i], d[16 * g + 2 * i + 1]);
#pragma unroll
                for (int i = 0; i < 4; i++) stat_mma(c, hp[8 * g + 2 * i], hp[8 * g + 2 * i + 1]);
                stat_store(c, SM_RED + (g * 4 + wq) * 48, lane);
            }
            bar_sync(2, 128);
            if (wq == 0) stat_publish(SM_RED, &gs->acc[(NB + b) * 32], lane, true);
            if (tid == 0) TL(11);
            const uint32_t hbase = SM_ACT + (lane >> 4) * CH_PITCH + (2 + wq * 16 + (lane & 15)) * 16;
#pragma unroll
            for (int kc = 0; kc < 8; kc++) stsm4(hbase + kc * 2 * CH_PITCH, hp[4 * kc], hp[4 * kc + 1], hp[4 * kc + 2], hp[4 * kc + 3]);
            __syncwarp();
            if (lane == 0) mbar_arrive(BAR(BAR_HW));
            if (lane < LAG) mbar_arrive(BAR(BAR_WEMPTY + (NSTAGE - LAG) % NS) + 8 * lane);
            if (has_outer) {
                uint4* outbox = gs->box + (cta + ((r & 1) ? 1 : -1)) * 1024 + tid;
#pragma unroll
                for (int kc = 0; kc < 8; kc++) outbox[kc * 128] = make_uint4(~hp[4 * kc], ~hp[4 * kc + 1], ~hp[4 * kc + 2], ~hp[4 * kc + 3]);
            }
            if (tid == 0) TL(12);
            const uint32_t xbase = SM_XOWN + ((lane >> 4) * 8 + (lane & 7)) * 128 + (((2 * wq + ((lane >> 3) & 1)) ^ (lane & 7)) << 4);
#pragma unroll
            for (int kc = 0; kc < 8; kc++) {
                uint32_t p[4];
                ldsm4t(p, xbase + kc * 2048);
#pragma unroll
                for (int i = 0; i < 4; i++) { d[8 * kc + 2 * i] = bf_lo(p[i]); d[8 * kc + 2 * i + 1] = bf_hi(p[i]); }
            }
        }
        {
            const uint32_t obase = slot_addr(0) + ((lane >> 4) * 8 + (lane & 7)) * OUT_PITCH + (wq * 16 + ((lane >> 3) & 1) * 8) * 2;
#pragma unroll
            for (int kc = 0; kc < 8; kc++) {
                stsm4t(obase + kc * 16 * OUT_PITCH, pack_bf(d[8 * kc + 0], d[8 * kc + 1]), pack_bf(d[8 * kc + 2], d[8 * kc + 3]),
                       pack_bf(d[8 * kc + 4], d[8 * kc + 5]), pack_bf(d[8 * kc + 6], d[8 * kc + 7]));
            }
            bar_sync(2, 128);
            const int oc0 = tid >> 3;
            __nv_bfloat16* dst = out + ((size_t)(b * C + oc0) * HW + r) * HW + seg * 8;
#pragma unroll
            for (int i = 0; i < 8; i++)
                *reinterpret_cast<uint4*>(dst + (size_t)i * 16 * HW * HW) = lds128(slot_addr(0) + (oc0 + 16 * i) * OUT_PITCH + seg * 16);
            if (tid == 0) { TL(20); TLG(21); }
        }
    } else if (warp < 6) {
        bar_sync(0, 96 + 128);
        if (warp == 5) {
            asm volatile("barrier.cluster.wait.acquire.aligned;" ::: "memory");
            const uint32_t peer = (r & 1) ^ 1;
            const uint32_t self0 = mapa(0, r & 1), peer0 = mapa(0, peer);
#pragma unroll 1
            for (int conv = 0; conv < 2; conv++) {
#pragma unroll 1
                for (int kc = 0; kc < 8; kc++) {
                    mbar_wait(BAR(BAR_FULL) + 8 * kc, conv);
                    if (elect_one())
                        asm volatile("cp.async.bulk.shared::cluster.shared::cta.mbarrier::complete_tx::bytes [%0], [%1], %2, [%3];"
                                     ::"r"(peer0 + SM_ACT + ROW_BYTES + kc * KC_BYTES), "r"(self0 + SM_ACT + kc * KC_BYTES), "r"(KC_BYTES),
                                       "r"(peer0 + BAR(BAR_FULL + 8) + 8 * kc) : "memory");
                }
                if (lane == 0) TL(86 + conv);
#pragma unroll 1
                for (int kc = 0; kc < 8; kc++) mbar_wait(BAR(BAR_FULL + 8) + 8 * kc, conv);
                if (lane == 0)
                    asm volatile("mbarrier.arrive.release.cluster.shared::cluster.b64 _, [%0];" ::"r"(peer0 + (conv ? BAR(BAR_ACK) : BAR(BAR_EMB))) : "memory");
            }
            mbar_wait(BAR(BAR_ACK), 0);
        } else {
            while (clock32() - clk0 < W2DELAY) {}
            const char* w2s = reinterpret_cast<const char*>(w2) + woff;
#pragma unroll
            for (int k = 0; k < 4; k++) v[k] = __ldg(reinterpret_cast<const uint4*>(w2s + k * 256));
            if ((lane & 15) < 8) v[4] = __ldg(reinterpret_cast<const uint4*>(w2s + 1024));
            const uint2* wsrc = reinterpret_cast<const uint2*>(w_emb + (size_t)r * 12 * C) + lane;
            uint2 wv[12];
#pragma unroll
            for (int i = 0; i < 12; i++) wv[i] = __ldg(wsrc + i * (C / 4));
            float tv = 0.f;
            if (lane < 12) tv = __bfloat162float(t_emb[b * E + r * 12 + lane]);
            weight_block(v, SM_BNC + 2304, gs->wt + NSTAGE * STAGE_BYTES, cta, lane);
            const float sv = silu_half(0.5f * tv);
            float e0 = 0.f, e1 = 0.f, e2 = 0.f, e3 = 0.f;
#pragma unroll
            for (int i = 0; i < 12; i++) {
                const float sx = __shfl_sync(0xffffffffu, sv, i);
                e0 = fmaf(sx, bf_lo(wv[i].x), e0); e1 = fmaf(sx, bf_hi(wv[i].x), e1);
                e2 = fmaf(sx, bf_lo(wv[i].y), e2); e3 = fmaf(sx, bf_hi(wv[i].y), e3);
            }
            mbar_wait(BAR(BAR_WACQ), 0);
            red_add4(&gs->emb[b * C + lane * 4], e0, e1, e2, e3);
            __syncwarp();
            if (lane == 0) TL(13);
            if (lane < 2) asm volatile("red.release.gpu.global.add.u32 [%0], 1;" ::"l"(&gs->wcnt[(NB + lane) * 32]) : "memory");
            if (lane == 0) TL(14);
            unsigned it = 0;
            while (ld_relaxed(&gs->wcnt[(NB + b) * 32]) < (unsigned)NCTA && ++it < SPIN_LIMIT) {}
            fence_acquire();
            const uint4 ef = ld_relaxed_v4(&gs->emb[b * C + lane * 4]);
            const uint32_t eu[4] = {ef.x, ef.y, ef.z, ef.w};
#pragma unroll
            for (int i = 0; i < 4; i++) {
                const float e = __uint_as_float(eu[i]);
                const float hi = bf_lo(pack_bf(e, 0.f));
                sts128(SM_EMB + (lane * 4 + i) * 16, make_uint4(pack_bf(hi, e - hi), 0, 0, 0));
            }
            fence_async_smem();
            __syncwarp();
            if (lane == 0) { mbar_arrive(BAR(BAR_EMB)); TL(19); }
        }
    } else if (warp == 6) {
        bar_sync(0, 96 + 128);
        unsigned it = 0;
        while (ld_relaxed(&gs->wcnt[b * 32]) < (unsigned)NCTA && ++it < SPIN_LIMIT) {}
        fence_acquire();
        fence_async_global();
        if (lane == 0) { mbar_arrive(BAR(BAR_WACQ)); TL(6); }
        const uint32_t self0 = mapa(0, r & 1);
        const int swap = (r & 1) ? 0 : 8;
#pragma unroll 1
        for (int round = 0; round < 2 * NSTAGE / NS; round++) {
            if (round == NSTAGE / NS) { mbar_wait(BAR(BAR_EMB), 0); fence_async_global(); }
            const int s0 = (round & 1) * NS;
            const unsigned char* wsrc = gs->wt + (round >> 1) * NSTAGE * STAGE_BYTES;
#pragma unroll
            for (int slot = 0; slot < NS; slot++) {
                const int st = s0 + slot;
                const bool prow = st >= 8 && st < 16;
                mbar_wait(BAR(BAR_WEMPTY + slot), (round & 1) ^ 1);
                if (elect_one()) {
                    mbar_expect(BAR(BAR_FULL) + 8 * st, STAGE_BYTES + (prow ? KC_BYTES : 0));
                    bulk_g2s(self0 + slot_addr(slot), wsrc + (st < 8 ? st : (prow ? st + swap : st - swap)) * STAGE_BYTES, STAGE_BYTES,
                             self0 + BAR(BAR_FULL) + 8 * st);
                }
            }
        }
    } else {
        const uint2 ga1 = __ldg(reinterpret_cast<const uint2*>(g1) + lane), bt1 = __ldg(reinterpret_cast<const uint2*>(be1) + lane);
        const uint2 ga2 = __ldg(reinterpret_cast<const uint2*>(g2) + lane), bt2 = __ldg(reinterpret_cast<const uint2*>(be2) + lane);
        bar_sync(0, 96 + 128);
#pragma unroll 1
        for (int conv = 0; conv < 2; conv++) {
            if (conv == 1) mbar_wait(BAR(BAR_EMB), 0);
            const float* asrc = &gs->acc[(conv * NB + b) * 32 + (lane >> 3) * 4];
            uint4 f;
            unsigned it = 0;
            while (true) {
                f = ld_relaxed_v4(asrc);
                const bool ok = (f.x == 0x42800000u) & (f.w == 0x42800000u);
                if (__all_sync(0xffffffffu, ok) || ++it > SPIN_LIMIT) break;
            }
            if (lane == 0) TL(7 + conv * 8);
            const float inv_n = 1.0f / (32.0f * HW * HW);
            const float mean = __uint_as_float(f.y) * inv_n;
            const float var = fmaxf(fmaf(-mean, mean, __uint_as_float(f.z) * inv_n), 0.f);
            const float rs = 0.5f * rsqrtf(var + 1e-5f);
            const uint2 ga = conv ? ga2 : ga1, bt = conv ? bt2 : bt1;
            float4 k0, k1;
            k0.x = rs * bf_lo(ga.x); k0.y = rs * bf_hi(ga.x); k1.x = rs * bf_lo(ga.y); k1.y = rs * bf_hi(ga.y);
            k0.z = fmaf(-mean, k0.x, 0.5f * bf_lo(bt.x)); k0.w = fmaf(-mean, k0.y, 0.5f * bf_hi(bt.x));
            k1.z = fmaf(-mean, k1.x, 0.5f * bf_lo(bt.y)); k1.w = fmaf(-mean, k1.y, 0.5f * bf_hi(bt.y));
            sts128f(SM_COEF + lane * 32, k0);
            sts128f(SM_COEF + lane * 32 + 16, k1);
            __syncwarp();
            if (lane == 0) mbar_arrive(BAR(BAR_STATS));
        }
        if (r == 0) {
            if (lane < 16) gs->acc[b * 32 + lane] = 0.f;
            if (lane < 2) gs->wcnt[(lane * NB + b) * 32] = 0;
        }
    }
}

}

extern "C" void kernel_launch(void* const* d_in, const int* in_sizes, int n_in, void* d_out, int out_size) {
    (void)in_sizes; (void)n_in; (void)out_size;
    static Scratch* gs = nullptr;
    if (!gs) {
        cudaFuncSetAttribute(resblock_kernel, cudaFuncAttributeMaxDynamicSharedMemorySize, SM_TOTAL);
        cudaGetSymbolAddress((void**)&gs, g_scratch);
    }
    resblock_kernel<<<NCTA, NTHREADS, SM_TOTAL>>>(
        (const __nv_bfloat16*)d_in[0], (const __nv_bfloat16*)d_in[4], (const __nv_bfloat16*)d_in[1],
        (const __nv_bfloat16*)d_in[2], (const __nv_bfloat16*)d_in[3], (const __nv_bfloat16*)d_in[5],
        (const __nv_bfloat16*)d_in[6], (const __nv_bfloat16*)d_in[7], (const __nv_bfloat16*)d_in[8],
        (__nv_bfloat16*)d_out, gs);
}
```

```cpp
#include <cuda_runtime.h>
#include <cuda_bf16.h>
#include <stdint.h>

namespace {

constexpr int C = 128, HW = 64, NB = 2, E = 768;
constexpr int NCTA = NB * HW;
constexpr int NTHREADS = 16 * 32;
constexpr int CH_PITCH = 66 * 16;
constexpr int ROW_BYTES = 16 * CH_PITCH;
constexpr int STEP_BYTES = 4096;
constexpr int STAGE_BYTES = 3 * STEP_BYTES;
constexpr int NSTAGE = 24;
constexpr int KC_BYTES = 2 * CH_PITCH;
constexpr int NS = 12;
constexpr int LAG = 1;
#define XDELAY 600
#define HDELAY 600
#define NA 2
#define HSEND 0
#define W2DELAY 2800

constexpr uint32_t SMEM_BASE = 0x400;
constexpr uint32_t SM_ACT = SMEM_BASE;
constexpr uint32_t SM_XOWN = SM_ACT + 3 * ROW_BYTES + 128;
constexpr uint32_t SM_XOUT = SM_ACT + 2 * ROW_BYTES + 32;
constexpr uint32_t SM_W = SM_XOWN + 16384;
__host__ __device__ constexpr uint32_t slot_addr(int slot) { return SM_W + slot * STAGE_BYTES; }
constexpr uint32_t SM_COEF = SM_W + NS * STAGE_BYTES;
constexpr uint32_t SM_EMB = SM_COEF + 1024;
constexpr uint32_t SM_ONES = SM_EMB + 2048;
constexpr uint32_t SM_RED = SM_ONES + 256;
constexpr uint32_t SM_BNC = SM_RED + 1280;
constexpr uint32_t SM_BAR = SM_BNC + 2 * 2304;
constexpr int BAR_FULL = 0, BAR_WEMPTY = NSTAGE, BAR_HW = BAR_WEMPTY + NS, BAR_STATS = BAR_HW + 1,
              BAR_EMB = BAR_STATS + 1, BAR_WACQ = BAR_EMB + 1, BAR_ACK = BAR_WACQ + 1, NBAR = BAR_ACK + 1;
constexpr int SM_TOTAL = SM_BAR + NBAR * 8 - SMEM_BASE;
static_assert(SM_TOTAL <= 232448, "smem");
static_assert(NBAR <= 96, "barrier init");
constexpr int OUT_PITCH = 144;
__host__ __device__ constexpr uint32_t BAR(int i) { return SM_BAR + 8 * i; }
__host__ __device__ constexpr int ky_of(int kyo) { return kyo == 0 ? 1 : (kyo == 1 ? 0 : 2); }

constexpr unsigned SPIN_LIMIT = 1u << 16;

struct Scratch {
    float acc[2 * NB * 32];
    unsigned wcnt[2 * NB * 32];
    float emb[NB * C];
    unsigned char wt[2 * NSTAGE * STAGE_BYTES];
    uint4 box[NCTA * 1024];
};
__device__ __align__(1024) Scratch g_scratch;
#define TL(i) do {} while (0)
#define TLG(i) do {} while (0)

__device__ __forceinline__ unsigned clock32() { unsigned c; asm volatile("mov.u32 %0, %%clock;" : "=r"(c)); return c; }
__device__ __forceinline__ uint32_t mapa(uint32_t a, uint32_t rank) {
    uint32_t d;
    asm("mapa.shared::cluster.u32 %0, %1, %2;" : "=r"(d) : "r"(a), "r"(rank));
    return d;
}
#define S0 mapa(0, blockIdx.x & 1)
__device__ __forceinline__ void mbar_init(uint32_t bar, int cnt) {
    asm volatile("mbarrier.init.shared::cta.b64 [%0], %1;" ::"r"(bar + S0), "r"(cnt) : "memory");
}
__device__ __forceinline__ void mbar_arrive(uint32_t bar) {
    asm volatile("mbarrier.arrive.shared::cta.b64 _, [%0];" ::"r"(bar + S0) : "memory");
}
__device__ __forceinline__ void mbar_expect(uint32_t bar, uint32_t bytes) {
    asm volatile("mbarrier.arrive.expect_tx.shared::cta.b64 _, [%0], %1;" ::"r"(bar + S0), "r"(bytes) : "memory");
}
__device__ __forceinline__ bool mbar_try(uint32_t bar, uint32_t par) {
    uint32_t ok;
    asm volatile("{\n.reg .pred p;\nmbarrier.try_wait.parity.shared::cta.b64 p, [%1], %2;\nselp.u32 %0, 1, 0, p;\n}"
                 : "=r"(ok) : "r"(bar + S0), "r"(par) : "memory");
    return ok;
}
__device__ __forceinline__ bool mbar_test(uint32_t bar, uint32_t par) {
    uint32_t ok;
    asm volatile("{\n.reg .pred p;\nmbarrier.test_wait.parity.shared::cta.b64 p, [%1], %2;\nselp.u32 %0, 1, 0, p;\n}"
                 : "=r"(ok) : "r"(bar + S0), "r"(par) : "memory");
    return ok;
}
__device__ __forceinline__ void mbar_wait(uint32_t bar, uint32_t par) {
    unsigned it = 0;
#pragma unroll 1
    while (!mbar_try(bar, par) && ++it < SPIN_LIMIT) {}
}
__device__ __forceinline__ bool elect_one() {
    uint32_t p;
    asm volatile("{\n.reg .pred p;\nelect.sync _|p, 0xffffffff;\nselp.u32 %0, 1, 0, p;\n}" : "=r"(p));
    return p;
}
__device__ __forceinline__ void fence_async_smem() { asm volatile("fence.proxy.async.shared::cta;" ::: "memory"); }
__device__ __forceinline__ void fence_async_global() { asm volatile("fence.proxy.async.global;" ::: "memory"); }
__device__ __forceinline__ void fence_acquire() { asm volatile("fence.acquire.gpu;" ::: "memory"); }
__device__ __forceinline__ void bar_sync(int id, int n) { asm volatile("bar.sync %0, %1;" ::"r"(id), "r"(n) : "memory"); }
__device__ __forceinline__ void bar_arrive(int id, int n) { asm volatile("bar.arrive %0, %1;" ::"r"(id), "r"(n) : "memory"); }
__device__ __forceinline__ void bulk_g2s(uint32_t dst, const void* src, uint32_t bytes, uint32_t bar) {
    asm volatile("cp.async.bulk.shared::cluster.global.mbarrier::complete_tx::bytes [%0], [%1], %2, [%3];"
                 ::"r"(dst), "l"(src), "r"(bytes), "r"(bar) : "memory");
}
__device__ __forceinline__ uint4 ld_relaxed_v4(const void* p) {
    uint4 v;
    asm volatile("ld.relaxed.gpu.global.v4.u32 {%0,%1,%2,%3}, [%4];" : "=r"(v.x), "=r"(v.y), "=r"(v.z), "=r"(v.w) : "l"(p) : "memory");
    return v;
}
__device__ __forceinline__ unsigned ld_relaxed(const void* p) {
    unsigned v;
    asm volatile("ld.relaxed.gpu.global.u32 %0, [%1];" : "=r"(v) : "l"(p) : "memory");
    return v;
}
__device__ __forceinline__ void red_add4(float* p, float a, float b, float c, float d) {
    asm volatile("red.relaxed.gpu.global.add.v4.f32 [%0], {%1,%2,%3,%4};" ::"l"(p), "f"(a), "f"(b), "f"(c), "f"(d) : "memory");
}
__device__ __forceinline__ void sts128(uint32_t a, uint4 v) {
    asm volatile("st.shared.v4.u32 [%0], {%1,%2,%3,%4};" ::"r"(a + S0), "r"(v.x), "r"(v.y), "r"(v.z), "r"(v.w) : "memory");
}
__device__ __forceinline__ void sts128f(uint32_t a, float4 v) {
    asm volatile("st.shared.v4.f32 [%0], {%1,%2,%3,%4};" ::"r"(a + S0), "f"(v.x), "f"(v.y), "f"(v.z), "f"(v.w) : "memory");
}
__device__ __forceinline__ void sts32f(uint32_t a, float v) { asm volatile("st.shared.f32 [%0], %1;" ::"r"(a + S0), "f"(v) : "memory"); }
__device__ __forceinline__ uint4 lds128(uint32_t a) {
    uint4 v;
    asm volatile("ld.shared.v4.u32 {%0,%1,%2,%3}, [%4];" : "=r"(v.x), "=r"(v.y), "=r"(v.z), "=r"(v.w) : "r"(a + S0) : "memory");
    return v;
}
__device__ __forceinline__ float4 lds128f(uint32_t a) {
    float4 v;
    asm volatile("ld.shared.v4.f32 {%0,%1,%2,%3}, [%4];" : "=f"(v.x), "=f"(v.y), "=f"(v.z), "=f"(v.w) : "r"(a + S0) : "memory");
    return v;
}
__device__ __forceinline__ float2 lds64f(uint32_t a) {
    float2 v;
    asm volatile("ld.shared.v2.f32 {%0,%1}, [%2];" : "=f"(v.x), "=f"(v.y) : "r"(a + S0) : "memory");
    return v;
}
__device__ __forceinline__ float bf_lo(uint32_t u) { return __uint_as_float(u << 16); }
__device__ __forceinline__ float bf_hi(uint32_t u) { return __uint_as_float(u & 0xffff0000u); }
__device__ __forceinline__ uint32_t pack_bf(float lo, float hi) {
    uint32_t r;
    asm("cvt.rn.bf16x2.f32 %0, %1, %2;" : "=r"(r) : "f"(hi), "f"(lo));
    return r;
}
__device__ __forceinline__ float tanh_fast(float x) {
    float r;
    asm("tanh.approx.f32 %0, %1;" : "=f"(r) : "f"(x));
    return r;
}
__device__ __forceinline__ float silu_half(float h) { return fmaf(h, tanh_fast(h), h); }
__device__ __forceinline__ void ldsm4(uint32_t (&u)[4], uint32_t a) {
    asm volatile("ldmatrix.sync.aligned.m8n8.x4.shared.b16 {%0,%1,%2,%3}, [%4];"
                 : "=r"(u[0]), "=r"(u[1]), "=r"(u[2]), "=r"(u[3]) : "r"(a + S0) : "memory");
}
__device__ __forceinline__ void ldsm4t(uint32_t (&u)[4], uint32_t a) {
    asm volatile("ldmatrix.sync.aligned.m8n8.x4.trans.shared.b16 {%0,%1,%2,%3}, [%4];"
                 : "=r"(u[0]), "=r"(u[1]), "=r"(u[2]), "=r"(u[3]) : "r"(a + S0) : "memory");
}
__device__ __forceinline__ void stsm4(uint32_t a, uint32_t p0, uint32_t p1, uint32_t p2, uint32_t p3) {
    asm volatile("stmatrix.sync.aligned.m8n8.x4.shared.b16 [%0], {%1,%2,%3,%4};" ::"r"(a + S0), "r"(p0), "r"(p1), "r"(p2), "r"(p3) : "memory");
}
__device__ __forceinline__ void stsm4t(uint32_t a, uint32_t p0, uint32_t p1, uint32_t p2, uint32_t p3) {
    asm volatile("stmatrix.sync.aligned.m8n8.x4.trans.shared.b16 [%0], {%1,%2,%3,%4};" ::"r"(a + S0), "r"(p0), "r"(p1), "r"(p2), "r"(p3) : "memory");
}

#define R8(o) "+f"(d[o]), "+f"(d[o + 1]), "+f"(d[o + 2]), "+f"(d[o + 3]), "+f"(d[o + 4]), "+f"(d[o + 5]), "+f"(d[o + 6]), "+f"(d[o + 7])
template <uint32_t ALO, uint32_t BLO, uint64_t AHI = 8>
__device__ __forceinline__ void wgmma128(float (&d)[64]) {
    asm volatile(
        "wgmma.mma_async.sync.aligned.m64n128k16.f32.bf16.bf16 "
        "{%0,%1,%2,%3,%4,%5,%6,%7,%8,%9,%10,%11,%12,%13,%14,%15,%16,%17,%18,%19,%20,%21,%22,%23,%24,%25,%26,%27,%28,%29,%30,%31,"
        "%32,%33,%34,%35,%36,%37,%38,%39,%40,%41,%42,%43,%44,%45,%46,%47,%48,%49,%50,%51,%52,%53,%54,%55,%56,%57,%58,%59,%60,%61,%62,%63},"
        " %64, %65, 1, 1, 1, 0, 0;"
        : R8(0), R8(8), R8(16), R8(24), R8(32), R8(40), R8(48), R8(56)
        : "l"((AHI << 32) | ALO), "l"((8ull << 32) | BLO));
}
template <int S>
__device__ __forceinline__ void mma_stages(float (&d)[64], int conv, int tid, Scratch* gs) {
    constexpr uint32_t A = ((SM_ACT + S * 2 * CH_PITCH + 16) >> 4) | ((CH_PITCH >> 4) << 16);
    constexpr uint32_t B = (slot_addr(S % NS) >> 4) | ((2048 >> 4) << 16);
    if (S == 0) mbar_wait(BAR(BAR_FULL), conv);
    bool next_ok = true;
    constexpr uint32_t NEXT = S + 1 < NSTAGE ? BAR(BAR_FULL + S + 1) : BAR(BAR_EMB);
    const int npar = S + 1 < NSTAGE ? conv : 0;
    next_ok = mbar_test(NEXT, npar);
    if (S == 0 && tid == 0) TL(32 + conv * 24);
    asm volatile("wgmma.fence.sync.aligned;" ::: "memory");
    wgmma128<A, B>(d);
    wgmma128<A + 1, B + (STEP_BYTES >> 4)>(d);
    wgmma128<A + 2, B + 2 * (STEP_BYTES >> 4)>(d);
    asm volatile("wgmma.commit_group.sync.aligned;" ::: "memory");
    if (S >= LAG) {
        asm volatile("wgmma.wait_group.sync.aligned %0;" ::"n"(LAG) : "memory");
        if ((tid & 31) == 0) mbar_arrive(BAR(BAR_WEMPTY + (S + NS - LAG) % NS));
    }
    if (!next_ok) mbar_wait(NEXT, npar);
    if constexpr (S + 1 < NSTAGE) mma_stages<S + 1>(d, conv, tid, gs);
}

__device__ __forceinline__ void weight_block(const uint4 (&t)[5], uint32_t bounce, unsigned char* wt, int cta, int lane) {
    const uint32_t bw = bounce + (lane >> 4) * 1152 + (lane & 15) * 16;
#pragma unroll
    for (int k = 0; k < 4; k++) sts128(bw + k * 256, t[k]);
    if ((lane & 15) < 8) sts128(bw + 1024, t[4]);
    __syncwarp();
    if (lane < 16) {
        uint32_t v[36];
#pragma unroll
        for (int i = 0; i < 9; i++) {
            const uint4 q = lds128(bounce + (lane & 1) * 1152 + (lane >> 1) * 144 + i * 16);
            v[4 * i] = q.x; v[4 * i + 1] = q.y; v[4 * i + 2] = q.z; v[4 * i + 3] = q.w;
        }
        const int cc = (cta >> 6) * 8 + (lane >> 1);
        unsigned char* dst = wt + (cc >> 1) * STAGE_BYTES + (cc & 1) * 2048 + ((cta & 63) * 2 + (lane & 1)) * 16;
#pragma unroll
        for (int kyo = 0; kyo < 3; kyo++) {
#pragma unroll
            for (int kx = 0; kx < 3; kx++) {
                const int tap = ky_of(kyo) * 3 + kx;
                uint32_t o[4];
#pragma unroll
                for (int m = 0; m < 4; m++) {
                    const int i0 = 18 * m + tap, i1 = i0 + 9;
                    const uint32_t sel = ((i0 & 1) ? 0x32u : 0x10u) | ((i1 & 1) ? 0x7600u : 0x5400u);
                    o[m] = __byte_perm(v[i0 >> 1], v[i1 >> 1], sel);
                }
                *reinterpret_cast<uint4*>(dst + (kyo * 24 + kx) * STEP_BYTES) = make_uint4(o[0], o[1], o[2], o[3]);
            }
        }
    }
}
__device__ __forceinline__ uint32_t act2(uint32_t u, const float4& cf) {
    return pack_bf(silu_half(fmaf(bf_lo(u), cf.x, cf.z)), silu_half(fmaf(bf_hi(u), cf.y, cf.w)));
}
__device__ __forceinline__ void norm_unit(uint32_t (&u)[4], const float4& ca, const float4& cb) {
    u[0] = act2(u[0], ca); u[1] = act2(u[1], ca); u[2] = act2(u[2], cb); u[3] = act2(u[3], cb);
}
template <int FIRST, int N>
__device__ __forceinline__ void norm_block(uint32_t (&u)[4][4], float4 (&cf)[8], bool load_cf, uint32_t cfa, uint32_t act, uint32_t mask, uint32_t fbar, int lane) {
    if (load_cf) {
#pragma unroll
        for (int i = 2 * FIRST; i < 2 * (FIRST + N); i++) cf[i] = lds128f(cfa + (i >> 1) * 256 + (i & 1) * 64);
    }
#pragma unroll
    for (int t = FIRST; t < FIRST + N; t++) {
        norm_unit(u[t], cf[2 * t], cf[2 * t + 1]);
        stsm4(act + t * 2 * KC_BYTES, u[t][0] & mask, u[t][1] & mask, u[t][2] & mask, u[t][3] & mask);
    }
    fence_async_smem();
    __syncwarp();
    if (lane < N) mbar_arrive(fbar + 16 * (FIRST + lane));
}
__device__ __forceinline__ void stat_mma(float (&c)[4], uint32_t p, uint32_t q) {
    asm("mma.sync.aligned.m16n8k16.row.col.f32.bf16.bf16.f32 {%0,%1,%2,%3}, {%4,%5,%6,%5}, {%4,%6}, {%0,%1,%2,%3};"
        : "+f"(c[0]), "+f"(c[1]), "+f"(c[2]), "+f"(c[3]) : "r"(p), "r"(0x3f803f80u), "r"(q));
}
__device__ __forceinline__ void stat_store(const float (&c)[4], uint32_t dst, int lane) {
    const int g = lane >> 2, t = lane & 3;
    if (t == (g >> 1)) sts32f(dst + g * 4, (g & 1) ? c[1] : c[0]);
    if (g == 7) sts32f(dst + 32 + t * 4, c[2] + c[3]);
}
__device__ __forceinline__ float sum4(float4 v) { return (v.x + v.y) + (v.z + v.w); }
__device__ __forceinline__ void stat_publish(uint32_t src, float* acc, int lane, bool real) {
    const uint32_t a = src + (lane & 15) * 48;
    float q = sum4(lds128f(a)) + sum4(lds128f(a + 16)), sm = sum4(lds128f(a + 32));
    q += __shfl_xor_sync(0xffffffffu, q, 1); sm += __shfl_xor_sync(0xffffffffu, sm, 1);
    q += __shfl_xor_sync(0xffffffffu, q, 2); sm += __shfl_xor_sync(0xffffffffu, sm, 2);
    if (real && (lane & 19) == 0) red_add4(acc + lane, 1.f, sm, q, 1.f);
}
__device__ __forceinline__ void fence_acc(float (&d)[64]) {
#pragma unroll
    for (int i = 0; i < 64; i++) asm volatile("" : "+f"(d[i])::"memory");
}
__device__ __forceinline__ void ld_unit(uint32_t (&u)[4], const uint4* p) {
    asm volatile("ld.relaxed.gpu.global.v4.u32 {%0,%1,%2,%3}, [%4];" : "=r"(u[0]), "=r"(u[1]), "=r"(u[2]), "=r"(u[3]) : "l"(p) : "memory");
}

__global__ void __cluster_dims__(2, 1, 1) __launch_bounds__(NTHREADS, 1)
resblock_kernel(const __nv_bfloat16* __restrict__ x, const __nv_bfloat16* __restrict__ w1,
                const __nv_bfloat16* __restrict__ t_emb, const __nv_bfloat16* __restrict__ g1,
                const __nv_bfloat16* __restrict__ be1, const __nv_bfloat16* __restrict__ w_emb,
                const __nv_bfloat16* __restrict__ g2, const __nv_bfloat16* __restrict__ be2,
                const __nv_bfloat16* __restrict__ w2, __nv_bfloat16* __restrict__ out, Scratch* __restrict__ gs) {
    const unsigned clk0 = clock32();
    const int tid = threadIdx.x, warp = __shfl_sync(0xffffffffu, tid >> 5, 0), lane = tid & 31;
    const int cta = blockIdx.x, b = cta >> 6, r = cta & 63;

    const uint32_t woff = ((2 * r + (lane >> 4)) * C + b * 64) * 18 + (lane & 15) * 16;
    const int c0 = (warp - 8) * 16 + (lane >> 3), seg = lane & 7;
    uint4 v[5];
    if (warp == 0) {
        const char* w1s = reinterpret_cast<const char*>(w1) + woff;
#pragma unroll
        for (int k = 0; k < 4; k++) v[k] = __ldg(reinterpret_cast<const uint4*>(w1s + k * 256));
        if ((lane & 15) < 8) v[4] = __ldg(reinterpret_cast<const uint4*>(w1s + 1024));
    }
    if (warp == 0 || warp > 3) asm volatile("barrier.cluster.arrive.relaxed.aligned;" ::: "memory");
    const bool loader = warp >= 8;
    const bool has_outer = (r != 0) && (r != HW - 1);
    if (loader || warp == 5) {
        if (loader) {
            const char* src = reinterpret_cast<const char*>(x) + (uint32_t)(((b * C + c0) * HW + r) * HW * 2 + seg * 16);
            while (clock32() - clk0 < XDELAY) {}
#pragma unroll
            for (int k = 0; k < 4; k++) v[k] = __ldg(reinterpret_cast<const uint4*>(src + k * (4 * HW * HW * 2)));
            if (has_outer) {
#pragma unroll
                for (int i = 0; i < 4; i++)
                    asm volatile("cp.async.cg.shared.global [%0], [%1], 16;"
                                 ::"r"(S0 + SM_XOUT + c0 * 128 + i * 512 + ((seg ^ ((c0 + 4 * i) & 7)) << 4)),
                                   "l"(src + ((r & 1) ? HW * 2 : -HW * 2) + i * (4 * HW * HW * 2)) : "memory");
            }
        } else {
#pragma unroll
            for (int k = 0; k < 4; k++) v[k] = make_uint4(0, 0, 0, 0);
        }
        float c[2][4] = {{0.f, 0.f, 0.f, 0.f}, {0.f, 0.f, 0.f, 0.f}};
#pragma unroll
        for (int k = 0; k < 4; k++) { stat_mma(c[0], v[k].x, v[k].y); stat_mma(c[1], v[k].z, v[k].w); }
        stat_store(c[0], SM_RED + (warp & 7) * 96 + (loader ? 0 : 384), lane);
        stat_store(c[1], SM_RED + (warp & 7) * 96 + 48 + (loader ? 0 : 384), lane);
        if (tid == 256) TL(2);
        if (loader) bar_sync(3, 256);
        if (warp <= 8) stat_publish(SM_RED, &gs->acc[b * 32], lane, warp == 8);
        if (tid == 256) TL(3);
        if (loader) {
#pragma unroll
            for (int i = 0; i < 4; i++) sts128(SM_XOWN + c0 * 128 + i * 512 + ((seg ^ ((c0 + 4 * i) & 7)) << 4), v[i]);
        }
    }
    if (warp == 0) {
        weight_block(v, SM_BNC, gs->wt, cta, lane);
        if (r == 0) {
            if (lane < 16) gs->acc[(NB + b) * 32 + lane] = 0.f;
            *reinterpret_cast<float4*>(&gs->emb[b * C + lane * 4]) = make_float4(0.f, 0.f, 0.f, 0.f);
        }
        __syncwarp();
        if (lane == 0) TL(4);
        if (lane < 2) asm volatile("red.release.gpu.global.add.u32 [%0], 1;" ::"l"(&gs->wcnt[lane * 32]) : "memory");
        if (lane == 0) TL(5);
    }

    if (warp >= 8) {
        const int nw = warp - 8;
        asm volatile("cp.async.wait_all;" ::: "memory");
        bar_sync(4, 256 + 96);
        const int par = nw >> 2, wq = nw & 3;
        const uint32_t act_off = SM_ACT + (par * 2 + (lane >> 4)) * CH_PITCH + (2 + wq * 16 + (lane & 15)) * 16;
        const uint32_t stg_off = (par * 16 + (lane >> 4) * 8 + (lane & 7)) * 128 + (((2 * wq + ((lane >> 3) & 1)) ^ (lane & 7)) << 4);
        const uint32_t cfa = SM_COEF + par * 128 + (lane & 3) * 16;
        const uint32_t fbar = BAR(BAR_FULL) + 8 * par;
        uint4* inbox = gs->box + cta * 1024 + nw * 32 + lane;
#pragma unroll 1
        for (int conv = 0; conv < 2; conv++) {
            uint32_t u[4][4], w[4][4];
            float4 cf[8];
            if (conv == 0) {
#pragma unroll
                for (int i = 0; i < 4; i++) { ldsm4t(u[i], SM_XOWN + stg_off + i * 4096); ldsm4t(w[i], SM_XOUT + stg_off + i * 4096); }
                bar_sync(3, 256);
                if (nw == 0) sts128(SM_ACT + 2 * ROW_BYTES + (lane >> 1) * CH_PITCH + (lane & 1) * 16, make_uint4(0, 0, 0, 0));
            } else {
                mbar_wait(BAR(BAR_HW), 0);
#pragma unroll
                for (int i = 0; i < 4; i++) ldsm4(u[i], act_off + i * 2 * KC_BYTES);
            }
            mbar_wait(BAR(BAR_STATS), conv);
            if (tid == 256) TL(22 + conv * 4);
            norm_block<0, NA>(u, cf, true, cfa, act_off, ~0u, fbar, lane);
            if (tid == 256) TL(8 + conv * 8);
            norm_block<2, 2>(u, cf, true, cfa, act_off, ~0u, fbar, lane);
            if (tid == 256) TL(84 + conv);
            if (conv == 1 && has_outer) {
                unsigned it = 0;
                while (ld_relaxed(inbox + 3 * 256 + 31 - lane) == 0 && ++it < SPIN_LIMIT) {}
                if (tid == 256) TL(89);
                while (true) {
#pragma unroll
                    for (int i = 0; i < 4; i++) ld_unit(w[i], inbox + i * 256);
                    bool ok = true;
#pragma unroll
                    for (int i = 0; i < 16; i++) ok = ok && w[i >> 2][i & 3] != 0;
                    if (__all_sync(0xffffffffu, ok) || ++it > SPIN_LIMIT) break;
                }
#pragma unroll
                for (int i = 0; i < 16; i++) w[i >> 2][i & 3] = ~w[i >> 2][i & 3];
            }
            if (tid == 256) TL(24 + conv * 4);
            norm_block<0, 4>(w, cf, false, cfa, act_off + 2 * ROW_BYTES, has_outer ? ~0u : 0u, fbar + 128, lane);
            if (tid == 256) TL(23 + conv * 4);
        }
        if (has_outer) {
            mbar_wait(BAR(BAR_FULL + NSTAGE - 1), 1);
#pragma unroll
            for (int i = 0; i < 4; i++) inbox[i * 256] = make_uint4(0, 0, 0, 0);
        }
    } else if (warp < 4) {
        const int wq = warp;
        if (wq != 0) {
            const int t = tid - 32;
            if (lane == 0) {
                if (wq == 1) {
#pragma unroll
                    for (int i = 0; i < 12; i++) mbar_init(BAR(BAR_FULL + i), i < 8 ? 5 : 1);
                } else if (wq == 2) {
#pragma unroll
                    for (int i = 12; i < NSTAGE; i++) mbar_init(BAR(BAR_FULL + i), i < 16 ? 1 : 5);
                    mbar_init(BAR(BAR_EMB), 2);
                    mbar_init(BAR(BAR_ACK), 1);
                } else {
#pragma unroll
                    for (int i = 0; i <= NS; i++) mbar_init(BAR(BAR_WEMPTY + i), 4);
                    mbar_init(BAR(BAR_STATS), 1);
                    mbar_init(BAR(BAR_WACQ), 1);
                }
                asm volatile("fence.mbarrier_init.release.cluster;" ::: "memory");
            }
            fence_async_smem();
            bar_arrive(0, 96 + 128);
            bar_arrive(4, 256 + 96);
            if (t == 95) TLG(1);
            const uint4 z = make_uint4(0, 0, 0, 0);
            if (t < 66) sts128(SM_ACT + (t >> 1) * CH_PITCH + (t & 1) * 16, z);
            if (t < 2) sts128(SM_ACT + 3 * ROW_BYTES + t * 16, z);
            if (t < 16) sts128(SM_ONES + t * 16, make_uint4(t < 8 ? 0x3f803f80u : 0u, 0, 0, 0));
            fence_async_smem();
            asm volatile("barrier.cluster.arrive.release.aligned;" ::: "memory");
        }
        bar_sync(2, 128);

        float d[64];
#pragma unroll
        for (int i = 0; i < 64; i++) d[i] = 0.f;
#pragma unroll 1
        for (int conv = 0; conv < 2; conv++) {
            fence_acc(d);
            mma_stages<0>(d, conv, tid, gs);
            if (conv == 0) {
                asm volatile("wgmma.fence.sync.aligned;" ::: "memory");
                wgmma128<(SM_ONES >> 4) | (8u << 16), (SM_EMB >> 4), 0>(d);
                asm volatile("wgmma.commit_group.sync.aligned;" ::: "memory");
            }
            asm volatile("wgmma.wait_group.sync.aligned 0;" ::: "memory");
            fence_acc(d);
            if (tid == 0) TL(10 + conv * 8);
            if (conv == 1) break;

            uint32_t hp[32];
#pragma unroll
            for (int g = 0; g < 4; g++) {
                float c[4] = {0.f, 0.f, 0.f, 0.f};
#pragma unroll
                for (int i = 0; i < 8; i++) hp[8 * g + i] = pack_bf(d[16 * g + 2 * i], d[16 * g + 2 * i + 1]);
#pragma unroll
                for (int i = 0; i < 4; i++) stat_mma(c, hp[8 * g + 2 * i], hp[8 * g + 2 * i + 1]);
                stat_store(c, SM_RED + (g * 4 + wq) * 48, lane);
            }
            bar_sync(2, 128);
            if (wq == 0) stat_publish(SM_RED, &gs->acc[(NB + b) * 32], lane, true);
            if (tid == 0) TL(11);
            const uint32_t hbase = SM_ACT + (lane >> 4) * CH_PITCH + (2 + wq * 16 + (lane & 15)) * 16;
#pragma unroll
            for (int kc = 0; kc < 8; kc++) stsm4(hbase + kc * 2 * CH_PITCH, hp[4 * kc], hp[4 * kc + 1], hp[4 * kc + 2], hp[4 * kc + 3]);
            __syncwarp();
            if (lane == 0) mbar_arrive(BAR(BAR_HW));
            if (lane < LAG) mbar_arrive(BAR(BAR_WEMPTY + (NSTAGE - LAG) % NS) + 8 * lane);
            if (has_outer) {
                uint4* outbox = gs->box + (cta + ((r & 1) ? 1 : -1)) * 1024 + tid;
#pragma unroll
                for (int kc = 0; kc < 8; kc++) outbox[kc * 128] = make_uint4(~hp[4 * kc], ~hp[4 * kc + 1], ~hp[4 * kc + 2], ~hp[4 * kc + 3]);
            }
            if (tid == 0) TL(12);
            const uint32_t xbase = SM_XOWN + ((lane >> 4) * 8 + (lane & 7)) * 128 + (((2 * wq + ((lane >> 3) & 1)) ^ (lane & 7)) << 4);
#pragma unroll
            for (int kc = 0; kc < 8; kc++) {
                uint32_t p[4];
                ldsm4t(p, xbase + kc * 2048);
#pragma unroll
                for (int i = 0; i < 4; i++) { d[8 * kc + 2 * i] = bf_lo(p[i]); d[8 * kc + 2 * i + 1] = bf_hi(p[i]); }
            }
        }
        {
            const uint32_t obase = slot_addr(0) + ((lane >> 4) * 8 + (lane & 7)) * OUT_PITCH + (wq * 16 + ((lane >> 3) & 1) * 8) * 2;
#pragma unroll
            for (int kc = 0; kc < 8; kc++) {
                stsm4t(obase + kc * 16 * OUT_PITCH, pack_bf(d[8 * kc + 0], d[8 * kc + 1]), pack_bf(d[8 * kc + 2], d[8 * kc + 3]),
                       pack_bf(d[8 * kc + 4], d[8 * kc + 5]), pack_bf(d[8 * kc + 6], d[8 * kc + 7]));
            }
            bar_sync(2, 128);
            const int oc0 = tid >> 3;
            __nv_bfloat16* dst = out + ((size_t)(b * C + oc0) * HW + r) * HW + seg * 8;
#pragma unroll
            for (int i = 0; i < 8; i++)
                *reinterpret_cast<uint4*>(dst + (size_t)i * 16 * HW * HW) = lds128(slot_addr(0) + (oc0 + 16 * i) * OUT_PITCH + seg * 16);
            if (tid == 0) { TL(20); TLG(21); }
        }
    } else if (warp < 6) {
        bar_sync(0, 96 + 128);
        if (warp == 5) {
            asm volatile("barrier.cluster.wait.acquire.aligned;" ::: "memory");
            const uint32_t peer = (r & 1) ^ 1;
            const uint32_t self0 = mapa(0, r & 1), peer0 = mapa(0, peer);
#pragma unroll 1
            for (int conv = 0; conv < 2; conv++) {
#pragma unroll 1
                for (int kc = 0; kc < 8; kc++) {
                    mbar_wait(BAR(BAR_FULL) + 8 * kc, conv);
                    if (elect_one())
                        asm volatile("cp.async.bulk.shared::cluster.shared::cta.mbarrier::complete_tx::bytes [%0], [%1], %2, [%3];"
                                     ::"r"(peer0 + SM_ACT + ROW_BYTES + kc * KC_BYTES), "r"(self0 + SM_ACT + kc * KC_BYTES), "r"(KC_BYTES),
                                       "r"(peer0 + BAR(BAR_FULL + 8) + 8 * kc) : "memory");
                }
                if (lane == 0) TL(86 + conv);
#pragma unroll 1
                for (int kc = 0; kc < 8; kc++) mbar_wait(BAR(BAR_FULL + 8) + 8 * kc, conv);
                if (lane == 0)
                    asm volatile("mbarrier.arrive.release.cluster.shared::cluster.b64 _, [%0];" ::"r"(peer0 + (conv ? BAR(BAR_ACK) : BAR(BAR_EMB))) : "memory");
            }
            mbar_wait(BAR(BAR_ACK), 0);
        } else {
            while (clock32() - clk0 < W2DELAY) {}
            const char* w2s = reinterpret_cast<const char*>(w2) + woff;
#pragma unroll
            for (int k = 0; k < 4; k++) v[k] = __ldg(reinterpret_cast<const uint4*>(w2s + k * 256));
            if ((lane & 15) < 8) v[4] = __ldg(reinterpret_cast<const uint4*>(w2s + 1024));
            const uint2* wsrc = reinterpret_cast<const uint2*>(w_emb + (size_t)r * 12 * C) + lane;
            uint2 wv[12];
#pragma unroll
            for (int i = 0; i < 12; i++) wv[i] = __ldg(wsrc + i * (C / 4));
            float tv = 0.f;
            if (lane < 12) tv = __bfloat162float(t_emb[b * E + r * 12 + lane]);
            weight_block(v, SM_BNC + 2304, gs->wt + NSTAGE * STAGE_BYTES, cta, lane);
            const float sv = silu_half(0.5f * tv);
            float e0 = 0.f, e1 = 0.f, e2 = 0.f, e3 = 0.f;
#pragma unroll
            for (int i = 0; i < 12; i++) {
                const float sx = __shfl_sync(0xffffffffu, sv, i);
                e0 = fmaf(sx, bf_lo(wv[i].x), e0); e1 = fmaf(sx, bf_hi(wv[i].x), e1);
                e2 = fmaf(sx, bf_lo(wv[i].y), e2); e3 = fmaf(sx, bf_hi(wv[i].y), e3);
            }
            mbar_wait(BAR(BAR_WACQ), 0);
            red_add4(&gs->emb[b * C + lane * 4], e0, e1, e2, e3);
            __syncwarp();
            if (lane == 0) TL(13);
            if (lane < 2) asm volatile("red.release.gpu.global.add.u32 [%0], 1;" ::"l"(&gs->wcnt[(NB + lane) * 32]) : "memory");
            if (lane == 0) TL(14);
            unsigned it = 0;
            while (ld_relaxed(&gs->wcnt[(NB + b) * 32]) < (unsigned)NCTA && ++it < SPIN_LIMIT) {}
            fence_acquire();
            const uint4 ef = ld_relaxed_v4(&gs->emb[b * C + lane * 4]);
            const uint32_t eu[4] = {ef.x, ef.y, ef.z, ef.w};
#pragma unroll
            for (int i = 0; i < 4; i++) {
                const float e = __uint_as_float(eu[i]);
                const float hi = bf_lo(pack_bf(e, 0.f));
                sts128(SM_EMB + (lane * 4 + i) * 16, make_uint4(pack_bf(hi, e - hi), 0, 0, 0));
            }
            fence_async_smem();
            __syncwarp();
            if (lane == 0) { mbar_arrive(BAR(BAR_EMB)); TL(19); }
        }
    } else if (warp == 6) {
        bar_sync(0, 96 + 128);
        const uint32_t ebytes = STAGE_BYTES + ((lane >> 3) == 1 ? KC_BYTES : 0);
        if (lane < NSTAGE) mbar_expect(BAR(BAR_FULL) + 8 * lane, ebytes);
        const int swap = (r & 1) ? 0 : 8 * STAGE_BYTES;
        const unsigned char* wsrc = gs->wt;
        uint32_t dst = S0 + SM_W, full = S0 + BAR(BAR_FULL), empty = BAR(BAR_WEMPTY);
        unsigned it = 0;
        while (ld_relaxed(&gs->wcnt[b * 32]) < (unsigned)NCTA && ++it < SPIN_LIMIT) {}
        fence_acquire();
        fence_async_global();
        if (lane == 0) TL(6);
#pragma unroll 1
        for (int g = 0; g < 2 * NSTAGE; g++) {
            if (g >= NS) {
                mbar_wait(empty, ((g - NS) / NS) & 1);
                if (g == NSTAGE) { mbar_wait(BAR(BAR_EMB), 0); fence_async_global(); }
                if (g == NSTAGE || g == NSTAGE + NS) {
                    if (lane >= g - NSTAGE && lane < g - NSTAGE + NS) mbar_expect(BAR(BAR_FULL) + 8 * lane, ebytes);
                    __syncwarp();
                }
            }
            if (elect_one()) bulk_g2s(dst, wsrc, STAGE_BYTES, full);
            if (g == 3 && lane == 0) mbar_arrive(BAR(BAR_WACQ));
            wsrc += STAGE_BYTES; dst += STAGE_BYTES; full += 8; empty += 8;
            const int st = (g >= NSTAGE ? g - NSTAGE : g) + 1;
            if (st == 8 || st == NSTAGE) wsrc += swap;
            if (st == 16) wsrc -= 2 * swap;
            if (st == NS || st == NSTAGE) { dst -= NS * STAGE_BYTES; empty -= 8 * NS; }
            if (st == NSTAGE) full -= 8 * NSTAGE;
        }
    } else {
        const uint2 ga1 = __ldg(reinterpret_cast<const uint2*>(g1) + lane), bt1 = __ldg(reinterpret_cast<const uint2*>(be1) + lane);
        const uint2 ga2 = __ldg(reinterpret_cast<const uint2*>(g2) + lane), bt2 = __ldg(reinterpret_cast<const uint2*>(be2) + lane);
        bar_sync(0, 96 + 128);
#pragma unroll 1
        for (int conv = 0; conv < 2; conv++) {
            if (conv == 1) mbar_wait(BAR(BAR_EMB), 0);
            const float* asrc = &gs->acc[(conv * NB + b) * 32 + (lane >> 3) * 4];
            uint4 f;
            unsigned it = 0;
            while (true) {
                f = ld_relaxed_v4(asrc);
                const bool ok = (f.x == 0x42800000u) & (f.w == 0x42800000u);
                if (__all_sync(0xffffffffu, ok) || ++it > SPIN_LIMIT) break;
            }
            if (lane == 0) TL(7 + conv * 8);
            const float inv_n = 1.0f / (32.0f * HW * HW);
            const float mean = __uint_as_float(f.y) * inv_n;
            const float var = fmaxf(fmaf(-mean, mean, __uint_as_float(f.z) * inv_n), 0.f);
            const float rs = 0.5f * rsqrtf(var + 1e-5f);
            const uint2 ga = conv ? ga2 : ga1, bt = conv ? bt2 : bt1;
            float4 k0, k1;
            k0.x = rs * bf_lo(ga.x); k0.y = rs * bf_hi(ga.x); k1.x = rs * bf_lo(ga.y); k1.y = rs * bf_hi(ga.y);
            k0.z = fmaf(-mean, k0.x, 0.5f * bf_lo(bt.x)); k0.w = fmaf(-mean, k0.y, 0.5f * bf_hi(bt.x));
            k1.z = fmaf(-mean, k1.x, 0.5f * bf_lo(bt.y)); k1.w = fmaf(-mean, k1.y, 0.5f * bf_hi(bt.y));
            sts128f(SM_COEF + lane * 32, k0);
            sts128f(SM_COEF + lane * 32 + 16, k1);
            __syncwarp();
            if (lane == 0) mbar_arrive(BAR(BAR_STATS));
        }
        if (r == 0) {
            if (lane < 16) gs->acc[b * 32 + lane] = 0.f;
            if (lane < 2) gs->wcnt[(lane * NB + b) * 32] = 0;
        }
    }
}

}

extern "C" void kernel_launch(void* const* d_in, const int* in_sizes, int n_in, void* d_out, int out_size) {
    (void)in_sizes; (void)n_in; (void)out_size;
    static Scratch* gs = nullptr;
    if (!gs) {
        cudaFuncSetAttribute(resblock_kernel, cudaFuncAttributeMaxDynamicSharedMemorySize, SM_TOTAL);
        cudaGetSymbolAddress((void**)&gs, g_scratch);
    }
    resblock_kernel<<<NCTA, NTHREADS, SM_TOTAL>>>(
        (const __nv_bfloat16*)d_in[0], (const __nv_bfloat16*)d_in[4], (const __nv_bfloat16*)d_in[1],
        (const __nv_bfloat16*)d_in[2], (const __nv_bfloat16*)d_in[3], (const __nv_bfloat16*)d_in[5],
        (const __nv_bfloat16*)d_in[6], (const __nv_bfloat16*)d_in[7], (const __nv_bfloat16*)d_in[8],
        (__nv_bfloat16*)d_out, gs);
}
```

```cpp
#include <cuda_runtime.h>
#include <cuda.h>
#include <cuda_bf16.h>
#include <stdint.h>

namespace {

constexpr int C = 128, HW = 64, NB = 2, E = 768;
constexpr int NCTA = NB * HW;
constexpr int NTHREADS = 16 * 32;
constexpr int CH_PITCH = 66 * 16;
constexpr int ROW_BYTES = 16 * CH_PITCH;
constexpr int STEP_BYTES = 4096;
constexpr int STAGE_BYTES = 3 * STEP_BYTES;
constexpr int NSTAGE = 24;
constexpr int KC_BYTES = 2 * CH_PITCH;
constexpr int NS = 12;
constexpr int LAG = 1;
#define XDELAY 600
#define HDELAY 600
#define NA 2
#define XSTAG 300
#define HSEND 0
#define W2DELAY 2800

constexpr uint32_t SMEM_BASE = 0x400;
constexpr uint32_t SM_XOWN = SMEM_BASE;
constexpr uint32_t SM_ACT = SM_XOWN + 16384 + 512;
constexpr uint32_t SM_XOUT = SM_ACT + 2 * ROW_BYTES + 512;
static_assert(SM_XOUT % 1024 == 0, "swizzle atom alignment");
constexpr uint32_t SM_W = SM_ACT + 3 * ROW_BYTES + 128;
__host__ __device__ constexpr uint32_t slot_addr(int slot) { return SM_W + slot * STAGE_BYTES; }
constexpr uint32_t SM_COEF = SM_W + NS * STAGE_BYTES;
constexpr uint32_t SM_EMB = SM_COEF + 1024;
constexpr uint32_t SM_ONES = SM_EMB + 2048;
constexpr uint32_t SM_RED = SM_ONES + 256;
constexpr uint32_t SM_BNC = SM_RED + 1280;
constexpr uint32_t SM_BAR = SM_BNC + 2 * 2304;
constexpr int BAR_FULL = 0, BAR_WEMPTY = NSTAGE, BAR_HW = BAR_WEMPTY + NS, BAR_STATS = BAR_HW + 1  ,
              BAR_EMB = BAR_STATS + 4, BAR_WACQ = BAR_EMB + 1, BAR_ACK = BAR_WACQ + 1, BAR_X = BAR_ACK + 1  , NBAR = BAR_X + 5;
constexpr int SM_TOTAL = SM_BAR + NBAR * 8 - SMEM_BASE;
static_assert(SM_TOTAL <= 232448, "smem");
static_assert(NBAR <= 96, "barrier init");
constexpr int OUT_PITCH = 144;
__host__ __device__ constexpr uint32_t BAR(int i) { return SM_BAR + 8 * i; }
__host__ __device__ constexpr int ky_of(int kyo) { return kyo == 0 ? 1 : (kyo == 1 ? 0 : 2); }

constexpr unsigned SPIN_LIMIT = 1u << 16;

struct Scratch {
    float acc[2 * NB * 32];
    unsigned wcnt[2 * NB * 32];
    float emb[NB * C];
    unsigned char wt[2 * NSTAGE * STAGE_BYTES];
    uint4 box[NCTA * 1024];
};
__device__ __align__(1024) Scratch g_scratch;
#define TL(i) do {} while (0)
#define TLG(i) do {} while (0)

__device__ __forceinline__ unsigned clock32() { unsigned c; asm volatile("mov.u32 %0, %%clock;" : "=r"(c)); return c; }
__device__ __forceinline__ uint32_t mapa(uint32_t a, uint32_t rank) {
    uint32_t d;
    asm("mapa.shared::cluster.u32 %0, %1, %2;" : "=r"(d) : "r"(a), "r"(rank));
    return d;
}
#define S0 mapa(0, blockIdx.x & 1)
__device__ __forceinline__ void mbar_init(uint32_t bar, int cnt) {
    asm volatile("mbarrier.init.shared::cta.b64 [%0], %1;" ::"r"(bar + S0), "r"(cnt) : "memory");
}
__device__ __forceinline__ void mbar_arrive(uint32_t bar) {
    asm volatile("mbarrier.arrive.shared::cta.b64 _, [%0];" ::"r"(bar + S0) : "memory");
}
__device__ __forceinline__ void mbar_expect(uint32_t bar, uint32_t bytes) {
    asm volatile("mbarrier.arrive.expect_tx.shared::cta.b64 _, [%0], %1;" ::"r"(bar + S0), "r"(bytes) : "memory");
}
__device__ __forceinline__ bool mbar_try(uint32_t bar, uint32_t par) {
    uint32_t ok;
    asm volatile("{\n.reg .pred p;\nmbarrier.try_wait.parity.shared::cta.b64 p, [%1], %2;\nselp.u32 %0, 1, 0, p;\n}"
                 : "=r"(ok) : "r"(bar + S0), "r"(par) : "memory");
    return ok;
}
__device__ __forceinline__ bool mbar_test(uint32_t bar, uint32_t par) {
    uint32_t ok;
    asm volatile("{\n.reg .pred p;\nmbarrier.test_wait.parity.shared::cta.b64 p, [%1], %2;\nselp.u32 %0, 1, 0, p;\n}"
                 : "=r"(ok) : "r"(bar + S0), "r"(par) : "memory");
    return ok;
}
__device__ __forceinline__ void mbar_wait(uint32_t bar, uint32_t par) {
    unsigned it = 0;
#pragma unroll 1
    while (!mbar_try(bar, par) && ++it < SPIN_LIMIT) {}
}
__device__ __forceinline__ bool elect_one() {
    uint32_t p;
    asm volatile("{\n.reg .pred p;\nelect.sync _|p, 0xffffffff;\nselp.u32 %0, 1, 0, p;\n}" : "=r"(p));
    return p;
}
__device__ __forceinline__ void fence_async_smem() { asm volatile("fence.proxy.async.shared::cta;" ::: "memory"); }
__device__ __forceinline__ void fence_async_global() { asm volatile("fence.proxy.async.global;" ::: "memory"); }
__device__ __forceinline__ void fence_acquire() { asm volatile("fence.acquire.gpu;" ::: "memory"); }
__device__ __forceinline__ void bar_sync(int id, int n) { asm volatile("bar.sync %0, %1;" ::"r"(id), "r"(n) : "memory"); }
__device__ __forceinline__ void bar_arrive(int id, int n) { asm volatile("bar.arrive %0, %1;" ::"r"(id), "r"(n) : "memory"); }
__device__ __forceinline__ void bulk_g2s(uint32_t dst, const void* src, uint32_t bytes, uint32_t bar) {
    asm volatile("cp.async.bulk.shared::cluster.global.mbarrier::complete_tx::bytes [%0], [%1], %2, [%3];"
                 ::"r"(dst), "l"(src), "r"(bytes), "r"(bar) : "memory");
}
__device__ __forceinline__ void tma_x(uint32_t dst, const CUtensorMap* tm, int row, int ch, uint32_t bar) {
    asm volatile("cp.async.bulk.tensor.3d.shared::cluster.global.mbarrier::complete_tx::bytes [%0], [%1, {%2, %3, %4}], [%5];"
                 ::"r"(dst + S0), "l"(tm), "r"(0), "r"(row), "r"(ch), "r"(bar + S0) : "memory");
}
__device__ __forceinline__ uint4 ld_relaxed_v4(const void* p) {
    uint4 v;
    asm volatile("ld.relaxed.gpu.global.v4.u32 {%0,%1,%2,%3}, [%4];" : "=r"(v.x), "=r"(v.y), "=r"(v.z), "=r"(v.w) : "l"(p) : "memory");
    return v;
}
__device__ __forceinline__ unsigned ld_relaxed(const void* p) {
    unsigned v;
    asm volatile("ld.relaxed.gpu.global.u32 %0, [%1];" : "=r"(v) : "l"(p) : "memory");
    return v;
}
__device__ __forceinline__ void red_add4(float* p, float a, float b, float c, float d) {
    asm volatile("red.relaxed.gpu.global.add.v4.f32 [%0], {%1,%2,%3,%4};" ::"l"(p), "f"(a), "f"(b), "f"(c), "f"(d) : "memory");
}
__device__ __forceinline__ void sts128(uint32_t a, uint4 v) {
    asm volatile("st.shared.v4.u32 [%0], {%1,%2,%3,%4};" ::"r"(a + S0), "r"(v.x), "r"(v.y), "r"(v.z), "r"(v.w) : "memory");
}
__device__ __forceinline__ void sts128f(uint32_t a, float4 v) {
    asm volatile("st.shared.v4.f32 [%0], {%1,%2,%3,%4};" ::"r"(a + S0), "f"(v.x), "f"(v.y), "f"(v.z), "f"(v.w) : "memory");
}
__device__ __forceinline__ void sts32f(uint32_t a, float v) { asm volatile("st.shared.f32 [%0], %1;" ::"r"(a + S0), "f"(v) : "memory"); }
__device__ __forceinline__ uint4 lds128(uint32_t a) {
    uint4 v;
    asm volatile("ld.shared.v4.u32 {%0,%1,%2,%3}, [%4];" : "=r"(v.x), "=r"(v.y), "=r"(v.z), "=r"(v.w) : "r"(a + S0) : "memory");
    return v;
}
__device__ __forceinline__ float4 lds128f(uint32_t a) {
    float4 v;
    asm volatile("ld.shared.v4.f32 {%0,%1,%2,%3}, [%4];" : "=f"(v.x), "=f"(v.y), "=f"(v.z), "=f"(v.w) : "r"(a + S0) : "memory");
    return v;
}
__device__ __forceinline__ float2 lds64f(uint32_t a) {
    float2 v;
    asm volatile("ld.shared.v2.f32 {%0,%1}, [%2];" : "=f"(v.x), "=f"(v.y) : "r"(a + S0) : "memory");
    return v;
}
__device__ __forceinline__ float bf_lo(uint32_t u) { return __uint_as_float(u << 16); }
__device__ __forceinline__ float bf_hi(uint32_t u) { return __uint_as_float(u & 0xffff0000u); }
__device__ __forceinline__ uint32_t pack_bf(float lo, float hi) {
    uint32_t r;
    asm("cvt.rn.bf16x2.f32 %0, %1, %2;" : "=r"(r) : "f"(hi), "f"(lo));
    return r;
}
__device__ __forceinline__ float tanh_fast(float x) {
    float r;
    asm("tanh.approx.f32 %0, %1;" : "=f"(r) : "f"(x));
    return r;
}
__device__ __forceinline__ float silu_half(float h) { return fmaf(h, tanh_fast(h), h); }
__device__ __forceinline__ void ldsm4(uint32_t (&u)[4], uint32_t a) {
    asm volatile("ldmatrix.sync.aligned.m8n8.x4.shared.b16 {%0,%1,%2,%3}, [%4];"
                 : "=r"(u[0]), "=r"(u[1]), "=r"(u[2]), "=r"(u[3]) : "r"(a + S0) : "memory");
}
__device__ __forceinline__ void ldsm4t(uint32_t (&u)[4], uint32_t a) {
    asm volatile("ldmatrix.sync.aligned.m8n8.x4.trans.shared.b16 {%0,%1,%2,%3}, [%4];"
                 : "=r"(u[0]), "=r"(u[1]), "=r"(u[2]), "=r"(u[3]) : "r"(a + S0) : "memory");
}
__device__ __forceinline__ void stsm4(uint32_t a, uint32_t p0, uint32_t p1, uint32_t p2, uint32_t p3) {
    asm volatile("stmatrix.sync.aligned.m8n8.x4.shared.b16 [%0], {%1,%2,%3,%4};" ::"r"(a + S0), "r"(p0), "r"(p1), "r"(p2), "r"(p3) : "memory");
}
__device__ __forceinline__ void stsm4t(uint32_t a, uint32_t p0, uint32_t p1, uint32_t p2, uint32_t p3) {
    asm volatile("stmatrix.sync.aligned.m8n8.x4.trans.shared.b16 [%0], {%1,%2,%3,%4};" ::"r"(a + S0), "r"(p0), "r"(p1), "r"(p2), "r"(p3) : "memory");
}

#define R8(o) "+f"(d[o]), "+f"(d[o + 1]), "+f"(d[o + 2]), "+f"(d[o + 3]), "+f"(d[o + 4]), "+f"(d[o + 5]), "+f"(d[o + 6]), "+f"(d[o + 7])
template <uint32_t ALO, uint32_t BLO, uint64_t AHI = 8>
__device__ __forceinline__ void wgmma128(float (&d)[64]) {
    asm volatile(
        "wgmma.mma_async.sync.aligned.m64n128k16.f32.bf16.bf16 "
        "{%0,%1,%2,%3,%4,%5,%6,%7,%8,%9,%10,%11,%12,%13,%14,%15,%16,%17,%18,%19,%20,%21,%22,%23,%24,%25,%26,%27,%28,%29,%30,%31,"
        "%32,%33,%34,%35,%36,%37,%38,%39,%40,%41,%42,%43,%44,%45,%46,%47,%48,%49,%50,%51,%52,%53,%54,%55,%56,%57,%58,%59,%60,%61,%62,%63},"
        " %64, %65, 1, 1, 1, 0, 0;"
        : R8(0), R8(8), R8(16), R8(24), R8(32), R8(40), R8(48), R8(56)
        : "l"((AHI << 32) | ALO), "l"((8ull << 32) | BLO));
}
template <int S>
__device__ __forceinline__ void mma_stages(float (&d)[64], int conv, int tid, Scratch* gs) {
    constexpr uint32_t A = ((SM_ACT + S * 2 * CH_PITCH + 16) >> 4) | ((CH_PITCH >> 4) << 16);
    constexpr uint32_t B = (slot_addr(S % NS) >> 4) | ((2048 >> 4) << 16);
    if (S == 0) mbar_wait(BAR(BAR_FULL), conv);
    bool next_ok = true;
    constexpr uint32_t NEXT = S + 1 < NSTAGE ? BAR(BAR_FULL + S + 1) : BAR(BAR_EMB);
    const int npar = S + 1 < NSTAGE ? conv : 0;
    next_ok = mbar_test(NEXT, npar);
    if (S == 0 && tid == 0) TL(32 + conv * 24);
    asm volatile("wgmma.fence.sync.aligned;" ::: "memory");
    wgmma128<A, B>(d);
    wgmma128<A + 1, B + (STEP_BYTES >> 4)>(d);
    wgmma128<A + 2, B + 2 * (STEP_BYTES >> 4)>(d);
    asm volatile("wgmma.commit_group.sync.aligned;" ::: "memory");
    if (S >= LAG) {
        asm volatile("wgmma.wait_group.sync.aligned %0;" ::"n"(LAG) : "memory");
        if ((tid & 31) == 0) mbar_arrive(BAR(BAR_WEMPTY + (S + NS - LAG) % NS));
    }
    if (!next_ok) mbar_wait(NEXT, npar);
    if constexpr (S + 1 < NSTAGE) mma_stages<S + 1>(d, conv, tid, gs);
}

__device__ __forceinline__ void weight_block(const uint4 (&t)[5], uint32_t bounce, unsigned char* wt, int cta, int lane) {
    const uint32_t bw = bounce + (lane >> 4) * 1152 + (lane & 15) * 16;
#pragma unroll
    for (int k = 0; k < 4; k++) sts128(bw + k * 256, t[k]);
    if ((lane & 15) < 8) sts128(bw + 1024, t[4]);
    __syncwarp();
    if (lane < 16) {
        uint32_t v[36];
#pragma unroll
        for (int i = 0; i < 9; i++) {
            const uint4 q = lds128(bounce + (lane & 1) * 1152 + (lane >> 1) * 144 + i * 16);
            v[4 * i] = q.x; v[4 * i + 1] = q.y; v[4 * i + 2] = q.z; v[4 * i + 3] = q.w;
        }
        const int cc = (cta >> 6) * 8 + (lane >> 1);
        unsigned char* dst = wt + (cc >> 1) * STAGE_BYTES + (cc & 1) * 2048 + ((cta & 63) * 2 + (lane & 1)) * 16;
#pragma unroll
        for (int kyo = 0; kyo < 3; kyo++) {
#pragma unroll
            for (int kx = 0; kx < 3; kx++) {
                const int tap = ky_of(kyo) * 3 + kx;
                uint32_t o[4];
#pragma unroll
                for (int m = 0; m < 4; m++) {
                    const int i0 = 18 * m + tap, i1 = i0 + 9;
                    const uint32_t sel = ((i0 & 1) ? 0x32u : 0x10u) | ((i1 & 1) ? 0x7600u : 0x5400u);
                    o[m] = __byte_perm(v[i0 >> 1], v[i1 >> 1], sel);
                }
                *reinterpret_cast<uint4*>(dst + (kyo * 24 + kx) * STEP_BYTES) = make_uint4(o[0], o[1], o[2], o[3]);
            }
        }
    }
}
__device__ __forceinline__ uint32_t act2(uint32_t u, const float4& cf) {
    return pack_bf(silu_half(fmaf(bf_lo(u), cf.x, cf.z)), silu_half(fmaf(bf_hi(u), cf.y, cf.w)));
}
__device__ __forceinline__ void norm_unit(uint32_t (&u)[4], const float4& ca, const float4& cb) {
    u[0] = act2(u[0], ca); u[1] = act2(u[1], ca); u[2] = act2(u[2], cb); u[3] = act2(u[3], cb);
}
template <int FIRST, int N>
__device__ __forceinline__ void norm_block(uint32_t (&u)[4][4], float4 (&cf)[8], bool load_cf, uint32_t cfa, uint32_t act, uint32_t mask, uint32_t fbar, int lane) {
    if (load_cf) {
#pragma unroll
        for (int i = 2 * FIRST; i < 2 * (FIRST + N); i++) cf[i] = lds128f(cfa + (i >> 1) * 256 + (i & 1) * 64);
    }
#pragma unroll
    for (int t = FIRST; t < FIRST + N; t++) {
        norm_unit(u[t], cf[2 * t], cf[2 * t + 1]);
        stsm4(act + t * 2 * KC_BYTES, u[t][0] & mask, u[t][1] & mask, u[t][2] & mask, u[t][3] & mask);
    }
    fence_async_smem();
    __syncwarp();
    if (lane < N) mbar_arrive(fbar + 16 * (FIRST + lane));
}
__device__ __forceinline__ void stat_mma(float (&c)[4], uint32_t p, uint32_t q) {
    asm("mma.sync.aligned.m16n8k16.row.col.f32.bf16.bf16.f32 {%0,%1,%2,%3}, {%4,%5,%6,%5}, {%4,%6}, {%0,%1,%2,%3};"
        : "+f"(c[0]), "+f"(c[1]), "+f"(c[2]), "+f"(c[3]) : "r"(p), "r"(0x3f803f80u), "r"(q));
}
__device__ __forceinline__ void stat_store(const float (&c)[4], uint32_t dst, int lane) {
    const int g = lane >> 2, t = lane & 3;
    if (t == (g >> 1)) sts32f(dst + g * 4, (g & 1) ? c[1] : c[0]);
    if (g == 7) sts32f(dst + 32 + t * 4, c[2] + c[3]);
}
__device__ __forceinline__ float sum4(float4 v) { return (v.x + v.y) + (v.z + v.w); }
__device__ __forceinline__ void stat_publish(uint32_t src, float* acc, int lane, bool real) {
    const uint32_t a = src + (lane & 15) * 48;
    float q = sum4(lds128f(a)) + sum4(lds128f(a + 16)), sm = sum4(lds128f(a + 32));
    q += __shfl_xor_sync(0xffffffffu, q, 1); sm += __shfl_xor_sync(0xffffffffu, sm, 1);
    q += __shfl_xor_sync(0xffffffffu, q, 2); sm += __shfl_xor_sync(0xffffffffu, sm, 2);
    if (real && (lane & 19) == 0) red_add4(acc + lane, 1.f, sm, q, 1.f);
}
__device__ __forceinline__ void fence_acc(float (&d)[64]) {
#pragma unroll
    for (int i = 0; i < 64; i++) asm volatile("" : "+f"(d[i])::"memory");
}
__device__ __forceinline__ void ld_unit(uint32_t (&u)[4], const uint4* p) {
    asm volatile("ld.relaxed.gpu.global.v4.u32 {%0,%1,%2,%3}, [%4];" : "=r"(u[0]), "=r"(u[1]), "=r"(u[2]), "=r"(u[3]) : "l"(p) : "memory");
}

__global__ void __cluster_dims__(2, 1, 1) __launch_bounds__(NTHREADS, 1)
resblock_kernel(const __nv_bfloat16* __restrict__ w1,
                const __nv_bfloat16* __restrict__ t_emb, const __nv_bfloat16* __restrict__ g1,
                const __nv_bfloat16* __restrict__ be1, const __nv_bfloat16* __restrict__ w_emb,
                const __nv_bfloat16* __restrict__ g2, const __nv_bfloat16* __restrict__ be2,
                const __nv_bfloat16* __restrict__ w2, __nv_bfloat16* __restrict__ out, Scratch* __restrict__ gs,
                const __grid_constant__ CUtensorMap xmap) {
    const unsigned clk0 = clock32();
    const int tid = threadIdx.x, warp = __shfl_sync(0xffffffffu, tid >> 5, 0), lane = tid & 31;
    const int cta = blockIdx.x, b = cta >> 6, r = cta & 63;

    const uint32_t woff = ((2 * r + (lane >> 4)) * C + b * 64) * 18 + (lane & 15) * 16;
    const int seg = lane & 7;
    uint4 v[5];
    if (warp == 0) {
        const char* w1s = reinterpret_cast<const char*>(w1) + woff;
#pragma unroll
        for (int k = 0; k < 4; k++) v[k] = __ldg(reinterpret_cast<const uint4*>(w1s + k * 256));
        if ((lane & 15) < 8) v[4] = __ldg(reinterpret_cast<const uint4*>(w1s + 1024));
    }
    if (warp != 3) asm volatile("barrier.cluster.arrive.relaxed.aligned;" ::: "memory");
    const bool has_outer = (r != 0) && (r != HW - 1);
    if (warp == 1 || warp == 2 || warp == 4 || warp == 5) {
        const int g = warp < 3 ? warp - 1 : 7 - warp;
        if (elect_one()) {
            asm volatile("prefetch.tensormap [%0];" ::"l"(&xmap) : "memory");
            mbar_init(BAR(BAR_X) + 8 * g, 1);
            if (g == 3) mbar_init(BAR(BAR_X + 4), 1);
            mbar_expect(BAR(BAR_X) + 8 * g, 4096);
            fence_async_smem();
            while (clock32() - clk0 < XDELAY + g * XSTAG) {}
            tma_x(SM_XOWN + g * 4096, &xmap, r, b * C + g * 32, BAR(BAR_X) + 8 * g);
            if (g == 3 && has_outer) {
                mbar_expect(BAR(BAR_X + 4), 16384);
#pragma unroll
                for (int i = 0; i < 4; i++) tma_x(SM_XOUT + i * 4096, &xmap, r + ((r & 1) ? 1 : -1), b * C + i * 32, BAR(BAR_X + 4));
            }
        }
        __syncwarp();
        bar_arrive(4, 256 + 32 + 128);
        mbar_wait(BAR(BAR_X) + 8 * g, 0);
        if (lane == 0) TL(70 + g);
        float c[2][4] = {{0.f, 0.f, 0.f, 0.f}, {0.f, 0.f, 0.f, 0.f}};
#pragma unroll
        for (int k = 0; k < 8; k++) {
            const uint4 q = lds128(SM_XOWN + g * 4096 + k * 512 + lane * 16);
            stat_mma(c[0], q.x, q.y); stat_mma(c[1], q.z, q.w);
        }
#pragma unroll
        for (int i = 0; i < 4; i++) c[0][i] += c[1][i];
        stat_store(c[0], SM_RED + g * 48, lane);
        __syncwarp();
        if (lane == 0) {
            const uint32_t a = SM_RED + g * 48;
            red_add4(&gs->acc[b * 32 + g * 4], 1.f, sum4(lds128f(a + 32)), sum4(lds128f(a)) + sum4(lds128f(a + 16)), 1.f);
            TL(74 + g);
        }
    }
    if (warp == 0) {
        weight_block(v, SM_BNC, gs->wt, cta, lane);
        if (r == 0) {
            if (lane < 16) gs->acc[(NB + b) * 32 + lane] = 0.f;
            *reinterpret_cast<float4*>(&gs->emb[b * C + lane * 4]) = make_float4(0.f, 0.f, 0.f, 0.f);
        }
        __syncwarp();
        if (lane == 0) TL(4);
        if (lane < 2) asm volatile("red.release.gpu.global.add.u32 [%0], 1;" ::"l"(&gs->wcnt[lane * 32]) : "memory");
        if (lane == 0) TL(5);
    }

    if (warp >= 8) {
        const int nw = warp - 8;
        bar_sync(4, 256 + 32 + 128);
        const int par = nw >> 2, wq = nw & 3;
        const uint32_t act_off = SM_ACT + (par * 2 + (lane >> 4)) * CH_PITCH + (2 + wq * 16 + (lane & 15)) * 16;
        const uint32_t stg_off = (par * 16 + (lane >> 4) * 8 + (lane & 7)) * 128 + (((2 * wq + ((lane >> 3) & 1)) ^ (lane & 7)) << 4);
        const uint32_t cfa = SM_COEF + par * 128 + (lane & 3) * 16;
        const uint32_t fbar = BAR(BAR_FULL) + 8 * par;
        uint4* inbox = gs->box + cta * 1024 + nw * 32 + lane;
#pragma unroll 1
        for (int conv = 0; conv < 2; conv++) {
            uint32_t u[4][4], w[4][4];
            float4 cf[8];
            if (conv == 0) {
                mbar_wait(BAR(BAR_X), 0); ldsm4t(u[0], SM_XOWN + stg_off);
                mbar_wait(BAR(BAR_X + 1), 0); ldsm4t(u[1], SM_XOWN + stg_off + 4096);
                mbar_wait(BAR(BAR_STATS), 0);
                if (tid == 256) TL(22);
                norm_block<0, 1>(u, cf, true, cfa, act_off, ~0u, fbar, lane);
                if (tid == 256) TL(8);
                mbar_wait(BAR(BAR_X + 2), 0); ldsm4t(u[2], SM_XOWN + stg_off + 8192);
                mbar_wait(BAR(BAR_STATS + 1), 0);
                norm_block<1, 1>(u, cf, true, cfa, act_off, ~0u, fbar, lane);
                mbar_wait(BAR(BAR_X + 3), 0); ldsm4t(u[3], SM_XOWN + stg_off + 12288);
                mbar_wait(BAR(BAR_STATS + 2), 0);
                norm_block<2, 1>(u, cf, true, cfa, act_off, ~0u, fbar, lane);
                mbar_wait(BAR(BAR_STATS + 3), 0);
                norm_block<3, 1>(u, cf, true, cfa, act_off, ~0u, fbar, lane);
                if (has_outer) {
                    mbar_wait(BAR(BAR_X + 4), 0);
#pragma unroll
                    for (int i = 0; i < 4; i++) ldsm4t(w[i], SM_XOUT + stg_off + i * 4096);
                }
                bar_sync(3, 256);
                if (nw == 0) sts128(SM_ACT + 2 * ROW_BYTES + (lane >> 1) * CH_PITCH + (lane & 1) * 16, make_uint4(0, 0, 0, 0));
            } else {
                mbar_wait(BAR(BAR_HW), 0);
#pragma unroll
                for (int i = 0; i < 4; i++) ldsm4(u[i], act_off + i * 2 * KC_BYTES);
                mbar_wait(BAR(BAR_STATS + 1), 1);
                mbar_wait(BAR(BAR_STATS), 1);
                if (tid == 256) TL(26);
                norm_block<0, 2>(u, cf, true, cfa, act_off, ~0u, fbar, lane);
                if (tid == 256) TL(16);
                mbar_wait(BAR(BAR_STATS + 2), 1);
                mbar_wait(BAR(BAR_STATS + 3), 1);
                norm_block<2, 2>(u, cf, true, cfa, act_off, ~0u, fbar, lane);
            }
            if (tid == 256) TL(84 + conv);
            if (conv == 1 && has_outer) {
                unsigned it = 0;
                while (ld_relaxed(inbox + 3 * 256 + 31 - lane) == 0 && ++it < SPIN_LIMIT) {}
                if (tid == 256) TL(89);
                while (true) {
#pragma unroll
                    for (int i = 0; i < 4; i++) ld_unit(w[i], inbox + i * 256);
                    bool ok = true;
#pragma unroll
                    for (int i = 0; i < 16; i++) ok = ok && w[i >> 2][i & 3] != 0;
                    if (__all_sync(0xffffffffu, ok) || ++it > SPIN_LIMIT) break;
                }
#pragma unroll
                for (int i = 0; i < 16; i++) w[i >> 2][i & 3] = ~w[i >> 2][i & 3];
            }
            if (tid == 256) TL(24 + conv * 4);
            norm_block<0, 4>(w, cf, false, cfa, act_off + 2 * ROW_BYTES, has_outer ? ~0u : 0u, fbar + 128, lane);
            if (tid == 256) TL(23 + conv * 4);
        }
        if (has_outer) {
            mbar_wait(BAR(BAR_FULL + NSTAGE - 1), 1);
#pragma unroll
            for (int i = 0; i < 4; i++) inbox[i * 256] = make_uint4(0, 0, 0, 0);
        }
    } else if (warp < 4) {
        const int wq = warp;
        if (wq == 3) {
            if (elect_one()) {
#pragma unroll
                for (int i = 0; i < NSTAGE; i++) mbar_init(BAR(BAR_FULL + i), (i >> 3) == 1 ? 1 : 5);
#pragma unroll
                for (int i = 0; i <= NS; i++) mbar_init(BAR(BAR_WEMPTY + i), 4);
#pragma unroll
                for (int i = BAR_STATS; i < BAR_X; i++) mbar_init(BAR(i), i == BAR_EMB ? 2 : 1);
                asm volatile("fence.mbarrier_init.release.cluster;" ::: "memory");
            }
            __syncwarp();
            fence_async_smem();
            bar_arrive(0, 96);
            bar_arrive(5, 96);
            bar_arrive(4, 256 + 32 + 128);
            if (lane == 0) TLG(1);
            const uint4 z = make_uint4(0, 0, 0, 0);
#pragma unroll
            for (int i = 0; i < 2; i++) sts128(SM_ACT + (i * 16 + (lane >> 1)) * CH_PITCH + (lane & 1) * 16, z);
            if (lane < 4) sts128(SM_ACT + (2 + (lane >> 1)) * ROW_BYTES + (lane & 1) * 16, z);
            if (lane < 16) sts128(SM_ONES + lane * 16, make_uint4(lane < 8 ? 0x3f803f80u : 0u, 0, 0, 0));
            fence_async_smem();
            asm volatile("barrier.cluster.arrive.release.aligned;" ::: "memory");
        }
        bar_sync(2, 128);

        float d[64];
#pragma unroll
        for (int i = 0; i < 64; i++) d[i] = 0.f;
#pragma unroll 1
        for (int conv = 0; conv < 2; conv++) {
            fence_acc(d);
            mma_stages<0>(d, conv, tid, gs);
            if (conv == 0) {
                asm volatile("wgmma.fence.sync.aligned;" ::: "memory");
                wgmma128<(SM_ONES >> 4) | (8u << 16), (SM_EMB >> 4), 0>(d);
                asm volatile("wgmma.commit_group.sync.aligned;" ::: "memory");
            }
            asm volatile("wgmma.wait_group.sync.aligned 0;" ::: "memory");
            fence_acc(d);
            if (tid == 0) TL(10 + conv * 8);
            if (conv == 1) break;

            uint32_t hp[32];
#pragma unroll
            for (int g = 0; g < 4; g++) {
                float c[4] = {0.f, 0.f, 0.f, 0.f};
#pragma unroll
                for (int i = 0; i < 8; i++) hp[8 * g + i] = pack_bf(d[16 * g + 2 * i], d[16 * g + 2 * i + 1]);
#pragma unroll
                for (int i = 0; i < 4; i++) stat_mma(c, hp[8 * g + 2 * i], hp[8 * g + 2 * i + 1]);
                stat_store(c, SM_RED + (g * 4 + wq) * 48, lane);
            }
            bar_sync(2, 128);
            if (wq == 0) stat_publish(SM_RED, &gs->acc[(NB + b) * 32], lane, true);
            if (tid == 0) TL(11);
            const uint32_t hbase = SM_ACT + (lane >> 4) * CH_PITCH + (2 + wq * 16 + (lane & 15)) * 16;
#pragma unroll
            for (int kc = 0; kc < 8; kc++) stsm4(hbase + kc * 2 * CH_PITCH, hp[4 * kc], hp[4 * kc + 1], hp[4 * kc + 2], hp[4 * kc + 3]);
            __syncwarp();
            if (lane == 0) mbar_arrive(BAR(BAR_HW));
            if (lane < LAG) mbar_arrive(BAR(BAR_WEMPTY + (NSTAGE - LAG) % NS) + 8 * lane);
            if (has_outer) {
                uint4* outbox = gs->box + (cta + ((r & 1) ? 1 : -1)) * 1024 + tid;
#pragma unroll
                for (int kc = 0; kc < 8; kc++) outbox[kc * 128] = make_uint4(~hp[4 * kc], ~hp[4 * kc + 1], ~hp[4 * kc + 2], ~hp[4 * kc + 3]);
            }
            if (tid == 0) TL(12);
            const uint32_t xbase = SM_XOWN + ((lane >> 4) * 8 + (lane & 7)) * 128 + (((2 * wq + ((lane >> 3) & 1)) ^ (lane & 7)) << 4);
#pragma unroll
            for (int kc = 0; kc < 8; kc++) {
                uint32_t p[4];
                ldsm4t(p, xbase + kc * 2048);
#pragma unroll
                for (int i = 0; i < 4; i++) { d[8 * kc + 2 * i] = bf_lo(p[i]); d[8 * kc + 2 * i + 1] = bf_hi(p[i]); }
            }
        }
        {
            const uint32_t obase = slot_addr(0) + ((lane >> 4) * 8 + (lane & 7)) * OUT_PITCH + (wq * 16 + ((lane >> 3) & 1) * 8) * 2;
#pragma unroll
            for (int kc = 0; kc < 8; kc++) {
                stsm4t(obase + kc * 16 * OUT_PITCH, pack_bf(d[8 * kc + 0], d[8 * kc + 1]), pack_bf(d[8 * kc + 2], d[8 * kc + 3]),
                       pack_bf(d[8 * kc + 4], d[8 * kc + 5]), pack_bf(d[8 * kc + 6], d[8 * kc + 7]));
            }
            bar_sync(2, 128);
            const int oc0 = tid >> 3;
            __nv_bfloat16* dst = out + ((size_t)(b * C + oc0) * HW + r) * HW + seg * 8;
#pragma unroll
            for (int i = 0; i < 8; i++)
                *reinterpret_cast<uint4*>(dst + (size_t)i * 16 * HW * HW) = lds128(slot_addr(0) + (oc0 + 16 * i) * OUT_PITCH + seg * 16);
            if (tid == 0) { TL(20); TLG(21); }
        }
    } else if (warp < 6) {
        bar_sync(5, 96);
        if (warp == 5) {
            asm volatile("barrier.cluster.wait.acquire.aligned;" ::: "memory");
            const uint32_t peer = (r & 1) ^ 1;
            const uint32_t self0 = mapa(0, r & 1), peer0 = mapa(0, peer);
#pragma unroll 1
            for (int conv = 0; conv < 2; conv++) {
#pragma unroll 1
                for (int kc = 0; kc < 8; kc++) {
                    mbar_wait(BAR(BAR_FULL) + 8 * kc, conv);
                    if (elect_one())
                        asm volatile("cp.async.bulk.shared::cluster.shared::cta.mbarrier::complete_tx::bytes [%0], [%1], %2, [%3];"
                                     ::"r"(peer0 + SM_ACT + ROW_BYTES + kc * KC_BYTES), "r"(self0 + SM_ACT + kc * KC_BYTES), "r"(KC_BYTES),
                                       "r"(peer0 + BAR(BAR_FULL + 8) + 8 * kc) : "memory");
                }
                if (lane == 0) TL(86 + conv);
#pragma unroll 1
                for (int kc = 0; kc < 8; kc++) mbar_wait(BAR(BAR_FULL + 8) + 8 * kc, conv);
                if (lane == 0)
                    asm volatile("mbarrier.arrive.release.cluster.shared::cluster.b64 _, [%0];" ::"r"(peer0 + (conv ? BAR(BAR_ACK) : BAR(BAR_EMB))) : "memory");
            }
            mbar_wait(BAR(BAR_ACK), 0);
        } else {
            while (clock32() - clk0 < W2DELAY) {}
            const char* w2s = reinterpret_cast<const char*>(w2) + woff;
#pragma unroll
            for (int k = 0; k < 4; k++) v[k] = __ldg(reinterpret_cast<const uint4*>(w2s + k * 256));
            if ((lane & 15) < 8) v[4] = __ldg(reinterpret_cast<const uint4*>(w2s + 1024));
            const uint2* wsrc = reinterpret_cast<const uint2*>(w_emb + (size_t)r * 12 * C) + lane;
            uint2 wv[12];
#pragma unroll
            for (int i = 0; i < 12; i++) wv[i] = __ldg(wsrc + i * (C / 4));
            float tv = 0.f;
            if (lane < 12) tv = __bfloat162float(t_emb[b * E + r * 12 + lane]);
            weight_block(v, SM_BNC + 2304, gs->wt + NSTAGE * STAGE_BYTES, cta, lane);
            const float sv = silu_half(0.5f * tv);
            float e0 = 0.f, e1 = 0.f, e2 = 0.f, e3 = 0.f;
#pragma unroll
            for (int i = 0; i < 12; i++) {
                const float sx = __shfl_sync(0xffffffffu, sv, i);
                e0 = fmaf(sx, bf_lo(wv[i].x), e0); e1 = fmaf(sx, bf_hi(wv[i].x), e1);
                e2 = fmaf(sx, bf_lo(wv[i].y), e2); e3 = fmaf(sx, bf_hi(wv[i].y), e3);
            }
            mbar_wait(BAR(BAR_WACQ), 0);
            red_add4(&gs->emb[b * C + lane * 4], e0, e1, e2, e3);
            __syncwarp();
            if (lane == 0) TL(13);
            if (lane < 2) asm volatile("red.release.gpu.global.add.u32 [%0], 1;" ::"l"(&gs->wcnt[(NB + lane) * 32]) : "memory");
            if (lane == 0) TL(14);
            unsigned it = 0;
            while (ld_relaxed(&gs->wcnt[(NB + b) * 32]) < (unsigned)NCTA && ++it < SPIN_LIMIT) {}
            fence_acquire();
            const uint4 ef = ld_relaxed_v4(&gs->emb[b * C + lane * 4]);
            const uint32_t eu[4] = {ef.x, ef.y, ef.z, ef.w};
#pragma unroll
            for (int i = 0; i < 4; i++) {
                const float e = __uint_as_float(eu[i]);
                const float hi = bf_lo(pack_bf(e, 0.f));
                sts128(SM_EMB + (lane * 4 + i) * 16, make_uint4(pack_bf(hi, e - hi), 0, 0, 0));
            }
            fence_async_smem();
            __syncwarp();
            if (lane == 0) { mbar_arrive(BAR(BAR_EMB)); TL(19); }
        }
    } else if (warp == 6) {
        bar_sync(0, 96);
        const uint32_t ebytes = STAGE_BYTES + ((lane >> 3) == 1 ? KC_BYTES : 0);
        if (lane < NSTAGE) mbar_expect(BAR(BAR_FULL) + 8 * lane, ebytes);
        const int swap = (r & 1) ? 0 : 8 * STAGE_BYTES;
        const unsigned char* wsrc = gs->wt;
        uint32_t dst = S0 + SM_W, full = S0 + BAR(BAR_FULL), empty = BAR(BAR_WEMPTY);
        unsigned it = 0;
        while (ld_relaxed(&gs->wcnt[b * 32]) < (unsigned)NCTA && ++it < SPIN_LIMIT) {}
        fence_acquire();
        fence_async_global();
        if (lane == 0) TL(6);
#pragma unroll 1
        for (int g = 0; g < 2 * NSTAGE; g++) {
            if (g >= NS) {
                mbar_wait(empty, ((g - NS) / NS) & 1);
                if (g == NSTAGE) { mbar_wait(BAR(BAR_EMB), 0); fence_async_global(); }
                if (g == NSTAGE || g == NSTAGE + NS) {
                    if (lane >= g - NSTAGE && lane < g - NSTAGE + NS) mbar_expect(BAR(BAR_FULL) + 8 * lane, ebytes);
                    __syncwarp();
                }
            }
            if (elect_one()) bulk_g2s(dst, wsrc, STAGE_BYTES, full);
            if (g == 3 && lane == 0) mbar_arrive(BAR(BAR_WACQ));
            wsrc += STAGE_BYTES; dst += STAGE_BYTES; full += 8; empty += 8;
            const int st = (g >= NSTAGE ? g - NSTAGE : g) + 1;
            if (st == 8 || st == NSTAGE) wsrc += swap;
            if (st == 16) wsrc -= 2 * swap;
            if (st == NS || st == NSTAGE) { dst -= NS * STAGE_BYTES; empty -= 8 * NS; }
            if (st == NSTAGE) full -= 8 * NSTAGE;
        }
    } else {
        const uint2 ga1 = __ldg(reinterpret_cast<const uint2*>(g1) + lane), bt1 = __ldg(reinterpret_cast<const uint2*>(be1) + lane);
        const uint2 ga2 = __ldg(reinterpret_cast<const uint2*>(g2) + lane), bt2 = __ldg(reinterpret_cast<const uint2*>(be2) + lane);
        bar_sync(0, 96);
#pragma unroll 1
        for (int conv = 0; conv < 2; conv++) {
            if (conv == 1) mbar_wait(BAR(BAR_EMB), 0);
            const float* asrc = &gs->acc[(conv * NB + b) * 32 + (lane >> 3) * 4];
            const uint2 ga = conv ? ga2 : ga1, bt = conv ? bt2 : bt1;
            bool done = false;
            unsigned it = 0;
#pragma unroll 1
            while (true) {
                const uint4 f = ld_relaxed_v4(asrc);
                const bool fresh = !done && (((f.x == 0x42800000u) & (f.w == 0x42800000u)) || it > SPIN_LIMIT);
                it++;
                if (!__any_sync(0xffffffffu, fresh)) continue;
                if (lane == 0 && fresh) TL(7 + conv * 8);
                if (lane == 24 && fresh) TL(90 + conv);
                const float inv_n = 1.0f / (32.0f * HW * HW);
                const float mean = __uint_as_float(f.y) * inv_n;
                const float var = fmaxf(fmaf(-mean, mean, __uint_as_float(f.z) * inv_n), 0.f);
                const float rs = 0.5f * rsqrtf(var + 1e-5f);
                float4 k0, k1;
                k0.x = rs * bf_lo(ga.x); k0.y = rs * bf_hi(ga.x); k1.x = rs * bf_lo(ga.y); k1.y = rs * bf_hi(ga.y);
                k0.z = fmaf(-mean, k0.x, 0.5f * bf_lo(bt.x)); k0.w = fmaf(-mean, k0.y, 0.5f * bf_hi(bt.x));
                k1.z = fmaf(-mean, k1.x, 0.5f * bf_lo(bt.y)); k1.w = fmaf(-mean, k1.y, 0.5f * bf_hi(bt.y));
                if (fresh) {
                    sts128f(SM_COEF + lane * 32, k0);
                    sts128f(SM_COEF + lane * 32 + 16, k1);
                }
                __syncwarp();
                if (fresh && (lane & 7) == 0) mbar_arrive(BAR(BAR_STATS) + lane);
                done = done || fresh;
                if (__all_sync(0xffffffffu, done)) break;
            }
        }
        if (r == 0) {
            if (lane < 16) gs->acc[b * 32 + lane] = 0.f;
            if (lane < 2) gs->wcnt[(lane * NB + b) * 32] = 0;
        }
    }
}

}

extern "C" void kernel_launch(void* const* d_in, const int* in_sizes, int n_in, void* d_out, int out_size) {
    (void)in_sizes; (void)n_in; (void)out_size;
    typedef CUresult (*EncodeFn)(CUtensorMap*, CUtensorMapDataType, cuuint32_t, void*, const cuuint64_t*, const cuuint64_t*,
                                 const cuuint32_t*, const cuuint32_t*, CUtensorMapInterleave, CUtensorMapSwizzle,
                                 CUtensorMapL2promotion, CUtensorMapFloatOOBfill);
    static Scratch* gs = nullptr;
    static EncodeFn encode = nullptr;
    if (!gs) {
        cudaFuncSetAttribute(resblock_kernel, cudaFuncAttributeMaxDynamicSharedMemorySize, SM_TOTAL);
        cudaGetSymbolAddress((void**)&gs, g_scratch);
        cudaDriverEntryPointQueryResult qr;
        cudaGetDriverEntryPoint("cuTensorMapEncodeTiled", (void**)&encode, cudaEnableDefault, &qr);
    }
    CUtensorMap xmap;
    const cuuint64_t dims[3] = {HW, HW, NB * C}, strides[2] = {HW * 2, HW * HW * 2};
    const cuuint32_t box[3] = {HW, 1, 32}, es[3] = {1, 1, 1};
    encode(&xmap, CU_TENSOR_MAP_DATA_TYPE_BFLOAT16, 3, d_in[0], dims, strides, box, es, CU_TENSOR_MAP_INTERLEAVE_NONE,
           CU_TENSOR_MAP_SWIZZLE_128B, CU_TENSOR_MAP_L2_PROMOTION_NONE, CU_TENSOR_MAP_FLOAT_OOB_FILL_NONE);
    resblock_kernel<<<NCTA, NTHREADS, SM_TOTAL>>>(
        (const __nv_bfloat16*)d_in[4], (const __nv_bfloat16*)d_in[1],
        (const __nv_bfloat16*)d_in[2], (const __nv_bfloat16*)d_in[3], (const __nv_bfloat16*)d_in[5],
        (const __nv_bfloat16*)d_in[6], (const __nv_bfloat16*)d_in[7], (const __nv_bfloat16*)d_in[8],
        (__nv_bfloat16*)d_out, gs, xmap);
}
```

```cpp
#include <cuda_runtime.h>
#include <cuda.h>
#include <cuda_bf16.h>
#include <stdint.h>

namespace {

constexpr int C = 128, HW = 64, NB = 2, E = 768;
constexpr int NCTA = NB * HW;
constexpr int NTHREADS = 16 * 32;
constexpr int CH_PITCH = 66 * 16;
constexpr int ROW_BYTES = 16 * CH_PITCH;
constexpr int STEP_BYTES = 4096;
constexpr int STAGE_BYTES = 3 * STEP_BYTES;
constexpr int NSTAGE = 24;
constexpr int KC_BYTES = 2 * CH_PITCH;
constexpr int NS = 12;
constexpr int LAG = 1;
#define XDELAY 500
#define HDELAY 600
#define NA 2
#define XSTAG 400
#define HSEND 0
#define W2DELAY 2800

constexpr uint32_t SMEM_BASE = 0x400;
constexpr uint32_t SM_XOWN = SMEM_BASE;
constexpr uint32_t SM_ACT = SM_XOWN + 16384 + 512;
constexpr uint32_t SM_XOUT = SM_ACT + 2 * ROW_BYTES + 512;
static_assert(SM_XOUT % 1024 == 0, "swizzle atom alignment");
constexpr uint32_t SM_W = SM_ACT + 3 * ROW_BYTES + 128;
__host__ __device__ constexpr uint32_t slot_addr(int slot) { return SM_W + slot * STAGE_BYTES; }
constexpr uint32_t SM_COEF = SM_W + NS * STAGE_BYTES;
constexpr uint32_t SM_EMB = SM_COEF + 1024;
constexpr uint32_t SM_ONES = SM_EMB + 2048;
constexpr uint32_t SM_RED = SM_ONES + 256;
constexpr uint32_t SM_BNC = SM_RED + 1280;
constexpr uint32_t SM_BAR = SM_BNC + 2 * 2304;
constexpr int BAR_FULL = 0, BAR_WEMPTY = NSTAGE, BAR_HW = BAR_WEMPTY + NS, BAR_STATS = BAR_HW + 1  ,
              BAR_EMB = BAR_STATS + 4, BAR_ACK = BAR_EMB + 1, BAR_X = BAR_ACK + 1  , NBAR = BAR_X + 5;
constexpr int SM_TOTAL = SM_BAR + NBAR * 8 - SMEM_BASE;
static_assert(SM_TOTAL <= 232448, "smem");
static_assert(NBAR <= 96, "barrier init");
constexpr int OUT_PITCH = 144;
__host__ __device__ constexpr uint32_t BAR(int i) { return SM_BAR + 8 * i; }
__host__ __device__ constexpr int ky_of(int kyo) { return kyo == 0 ? 1 : (kyo == 1 ? 0 : 2); }

constexpr unsigned SPIN_LIMIT = 1u << 16;

struct Scratch {
    float acc[2 * NB * 32];
    unsigned wcnt[2 * NB * 32];
    float emb[NB * C];
    unsigned char wt[2 * NSTAGE * STAGE_BYTES];
    uint4 box[NCTA * 1024];
};
__device__ __align__(1024) Scratch g_scratch;
#define TL(i) do {} while (0)
#define TLG(i) do {} while (0)

__device__ __forceinline__ unsigned clock32() { unsigned c; asm volatile("mov.u32 %0, %%clock;" : "=r"(c)); return c; }
__device__ __forceinline__ uint32_t mapa(uint32_t a, uint32_t rank) {
    uint32_t d;
    asm("mapa.shared::cluster.u32 %0, %1, %2;" : "=r"(d) : "r"(a), "r"(rank));
    return d;
}
#define S0 mapa(0, blockIdx.x & 1)
__device__ __forceinline__ void mbar_init(uint32_t bar, int cnt) {
    asm volatile("mbarrier.init.shared::cta.b64 [%0], %1;" ::"r"(bar + S0), "r"(cnt) : "memory");
}
__device__ __forceinline__ void mbar_arrive(uint32_t bar) {
    asm volatile("mbarrier.arrive.shared::cta.b64 _, [%0];" ::"r"(bar + S0) : "memory");
}
__device__ __forceinline__ void mbar_expect(uint32_t bar, uint32_t bytes) {
    asm volatile("mbarrier.arrive.expect_tx.shared::cta.b64 _, [%0], %1;" ::"r"(bar + S0), "r"(bytes) : "memory");
}
__device__ __forceinline__ bool mbar_try(uint32_t bar, uint32_t par) {
    uint32_t ok;
    asm volatile("{\n.reg .pred p;\nmbarrier.try_wait.parity.shared::cta.b64 p, [%1], %2;\nselp.u32 %0, 1, 0, p;\n}"
                 : "=r"(ok) : "r"(bar + S0), "r"(par) : "memory");
    return ok;
}
__device__ __forceinline__ bool mbar_test(uint32_t bar, uint32_t par) {
    uint32_t ok;
    asm volatile("{\n.reg .pred p;\nmbarrier.test_wait.parity.shared::cta.b64 p, [%1], %2;\nselp.u32 %0, 1, 0, p;\n}"
                 : "=r"(ok) : "r"(bar + S0), "r"(par) : "memory");
    return ok;
}
__device__ __forceinline__ void mbar_wait(uint32_t bar, uint32_t par) {
    unsigned it = 0;
#pragma unroll 1
    while (!mbar_try(bar, par) && ++it < SPIN_LIMIT) {}
}
__device__ __forceinline__ bool elect_one() {
    uint32_t p;
    asm volatile("{\n.reg .pred p;\nelect.sync _|p, 0xffffffff;\nselp.u32 %0, 1, 0, p;\n}" : "=r"(p));
    return p;
}
__device__ __forceinline__ void fence_async_smem() { asm volatile("fence.proxy.async.shared::cta;" ::: "memory"); }
__device__ __forceinline__ void fence_async_global() { asm volatile("fence.proxy.async.global;" ::: "memory"); }
__device__ __forceinline__ void fence_acquire() { asm volatile("fence.acquire.gpu;" ::: "memory"); }
__device__ __forceinline__ void bar_sync(int id, int n) { asm volatile("bar.sync %0, %1;" ::"r"(id), "r"(n) : "memory"); }
__device__ __forceinline__ void bar_arrive(int id, int n) { asm volatile("bar.arrive %0, %1;" ::"r"(id), "r"(n) : "memory"); }
__device__ __forceinline__ void bulk_g2s(uint32_t dst, const void* src, uint32_t bytes, uint32_t bar) {
    asm volatile("cp.async.bulk.shared::cluster.global.mbarrier::complete_tx::bytes [%0], [%1], %2, [%3];"
                 ::"r"(dst), "l"(src), "r"(bytes), "r"(bar) : "memory");
}
__device__ __forceinline__ void tma_x(uint32_t dst, const CUtensorMap* tm, int row, int ch, uint32_t bar) {
    asm volatile("cp.async.bulk.tensor.3d.shared::cluster.global.mbarrier::complete_tx::bytes [%0], [%1, {%2, %3, %4}], [%5];"
                 ::"r"(dst + S0), "l"(tm), "r"(0), "r"(row), "r"(ch), "r"(bar + S0) : "memory");
}
__device__ __forceinline__ uint4 ld_relaxed_v4(const void* p) {
    uint4 v;
    asm volatile("ld.relaxed.gpu.global.v4.u32 {%0,%1,%2,%3}, [%4];" : "=r"(v.x), "=r"(v.y), "=r"(v.z), "=r"(v.w) : "l"(p) : "memory");
    return v;
}
__device__ __forceinline__ unsigned ld_relaxed(const void* p) {
    unsigned v;
    asm volatile("ld.relaxed.gpu.global.u32 %0, [%1];" : "=r"(v) : "l"(p) : "memory");
    return v;
}
__device__ __forceinline__ void red_add4(float* p, float a, float b, float c, float d) {
    asm volatile("red.relaxed.gpu.global.add.v4.f32 [%0], {%1,%2,%3,%4};" ::"l"(p), "f"(a), "f"(b), "f"(c), "f"(d) : "memory");
}
__device__ __forceinline__ void sts128(uint32_t a, uint4 v) {
    asm volatile("st.shared.v4.u32 [%0], {%1,%2,%3,%4};" ::"r"(a + S0), "r"(v.x), "r"(v.y), "r"(v.z), "r"(v.w) : "memory");
}
__device__ __forceinline__ void sts128f(uint32_t a, float4 v) {
    asm volatile("st.shared.v4.f32 [%0], {%1,%2,%3,%4};" ::"r"(a + S0), "f"(v.x), "f"(v.y), "f"(v.z), "f"(v.w) : "memory");
}
__device__ __forceinline__ void sts32f(uint32_t a, float v) { asm volatile("st.shared.f32 [%0], %1;" ::"r"(a + S0), "f"(v) : "memory"); }
__device__ __forceinline__ uint4 lds128(uint32_t a) {
    uint4 v;
    asm volatile("ld.shared.v4.u32 {%0,%1,%2,%3}, [%4];" : "=r"(v.x), "=r"(v.y), "=r"(v.z), "=r"(v.w) : "r"(a + S0) : "memory");
    return v;
}
__device__ __forceinline__ float4 lds128f(uint32_t a) {
    float4 v;
    asm volatile("ld.shared.v4.f32 {%0,%1,%2,%3}, [%4];" : "=f"(v.x), "=f"(v.y), "=f"(v.z), "=f"(v.w) : "r"(a + S0) : "memory");
    return v;
}
__device__ __forceinline__ float2 lds64f(uint32_t a) {
    float2 v;
    asm volatile("ld.shared.v2.f32 {%0,%1}, [%2];" : "=f"(v.x), "=f"(v.y) : "r"(a + S0) : "memory");
    return v;
}
__device__ __forceinline__ float bf_lo(uint32_t u) { return __uint_as_float(u << 16); }
__device__ __forceinline__ float bf_hi(uint32_t u) { return __uint_as_float(u & 0xffff0000u); }
__device__ __forceinline__ uint32_t pack_bf(float lo, float hi) {
    uint32_t r;
    asm("cvt.rn.bf16x2.f32 %0, %1, %2;" : "=r"(r) : "f"(hi), "f"(lo));
    return r;
}
__device__ __forceinline__ float tanh_fast(float x) {
    float r;
    asm("tanh.approx.f32 %0, %1;" : "=f"(r) : "f"(x));
    return r;
}
__device__ __forceinline__ float silu_half(float h) { return fmaf(h, tanh_fast(h), h); }
__device__ __forceinline__ void ldsm4(uint32_t (&u)[4], uint32_t a) {
    asm volatile("ldmatrix.sync.aligned.m8n8.x4.shared.b16 {%0,%1,%2,%3}, [%4];"
                 : "=r"(u[0]), "=r"(u[1]), "=r"(u[2]), "=r"(u[3]) : "r"(a + S0) : "memory");
}
__device__ __forceinline__ void ldsm4t(uint32_t (&u)[4], uint32_t a) {
    asm volatile("ldmatrix.sync.aligned.m8n8.x4.trans.shared.b16 {%0,%1,%2,%3}, [%4];"
                 : "=r"(u[0]), "=r"(u[1]), "=r"(u[2]), "=r"(u[3]) : "r"(a + S0) : "memory");
}
__device__ __forceinline__ void stsm4(uint32_t a, uint32_t p0, uint32_t p1, uint32_t p2, uint32_t p3) {
    asm volatile("stmatrix.sync.aligned.m8n8.x4.shared.b16 [%0], {%1,%2,%3,%4};" ::"r"(a + S0), "r"(p0), "r"(p1), "r"(p2), "r"(p3) : "memory");
}
__device__ __forceinline__ void stsm4t(uint32_t a, uint32_t p0, uint32_t p1, uint32_t p2, uint32_t p3) {
    asm volatile("stmatrix.sync.aligned.m8n8.x4.trans.shared.b16 [%0], {%1,%2,%3,%4};" ::"r"(a + S0), "r"(p0), "r"(p1), "r"(p2), "r"(p3) : "memory");
}

#define R8(o) "+f"(d[o]), "+f"(d[o + 1]), "+f"(d[o + 2]), "+f"(d[o + 3]), "+f"(d[o + 4]), "+f"(d[o + 5]), "+f"(d[o + 6]), "+f"(d[o + 7])
template <uint32_t ALO, uint32_t BLO, uint64_t AHI = 8>
__device__ __forceinline__ void wgmma128(float (&d)[64]) {
    asm volatile(
        "wgmma.mma_async.sync.aligned.m64n128k16.f32.bf16.bf16 "
        "{%0,%1,%2,%3,%4,%5,%6,%7,%8,%9,%10,%11,%12,%13,%14,%15,%16,%17,%18,%19,%20,%21,%22,%23,%24,%25,%26,%27,%28,%29,%30,%31,"
        "%32,%33,%34,%35,%36,%37,%38,%39,%40,%41,%42,%43,%44,%45,%46,%47,%48,%49,%50,%51,%52,%53,%54,%55,%56,%57,%58,%59,%60,%61,%62,%63},"
        " %64, %65, 1, 1, 1, 0, 0;"
        : R8(0), R8(8), R8(16), R8(24), R8(32), R8(40), R8(48), R8(56)
        : "l"((AHI << 32) | ALO), "l"((8ull << 32) | BLO));
}
template <int S>
__device__ __forceinline__ void mma_stages(float (&d)[64], int conv, int tid, Scratch* gs) {
    constexpr uint32_t A = ((SM_ACT + S * 2 * CH_PITCH + 16) >> 4) | ((CH_PITCH >> 4) << 16);
    constexpr uint32_t B = (slot_addr(S % NS) >> 4) | ((2048 >> 4) << 16);
    if (S == 0) mbar_wait(BAR(BAR_FULL), conv);
    bool next_ok = true;
    constexpr uint32_t NEXT = S + 1 < NSTAGE ? BAR(BAR_FULL + S + 1) : BAR(BAR_EMB);
    const int npar = S + 1 < NSTAGE ? conv : 0;
    next_ok = mbar_test(NEXT, npar);
    if (S == 0 && tid == 0) TL(32 + conv * 24);
    asm volatile("wgmma.fence.sync.aligned;" ::: "memory");
    wgmma128<A, B>(d);
    wgmma128<A + 1, B + (STEP_BYTES >> 4)>(d);
    wgmma128<A + 2, B + 2 * (STEP_BYTES >> 4)>(d);
    asm volatile("wgmma.commit_group.sync.aligned;" ::: "memory");
    if (S >= LAG) {
        asm volatile("wgmma.wait_group.sync.aligned %0;" ::"n"(LAG) : "memory");
        if ((tid & 31) == 0) mbar_arrive(BAR(BAR_WEMPTY + (S + NS - LAG) % NS));
    }
    if (!next_ok) mbar_wait(NEXT, npar);
    if constexpr (S + 1 < NSTAGE) mma_stages<S + 1>(d, conv, tid, gs);
}

template <bool READBACK>
__device__ __forceinline__ void weight_block(const uint4 (&t)[5], uint32_t bounce, unsigned char* wt, int cta, int lane) {
    const uint32_t bw = bounce + (lane >> 4) * 1152 + (lane & 15) * 16;
#pragma unroll
    for (int k = 0; k < 4; k++) sts128(bw + k * 256, t[k]);
    if ((lane & 15) < 8) sts128(bw + 1024, t[4]);
    __syncwarp();
    if (lane < 16) {
        uint32_t v[36];
#pragma unroll
        for (int i = 0; i < 9; i++) {
            const uint4 q = lds128(bounce + (lane & 1) * 1152 + (lane >> 1) * 144 + i * 16);
            v[4 * i] = q.x; v[4 * i + 1] = q.y; v[4 * i + 2] = q.z; v[4 * i + 3] = q.w;
        }
        const int cc = (cta >> 6) * 8 + (lane >> 1);
        unsigned char* dst = wt + (cc >> 1) * STAGE_BYTES + (cc & 1) * 2048 + ((cta & 63) * 2 + (lane & 1)) * 16;
#pragma unroll
        for (int kyo = 0; kyo < 3; kyo++) {
#pragma unroll
            for (int kx = 0; kx < 3; kx++) {
                const int tap = ky_of(kyo) * 3 + kx;
                uint32_t o[4];
#pragma unroll
                for (int m = 0; m < 4; m++) {
                    const int i0 = 18 * m + tap, i1 = i0 + 9;
                    const uint32_t sel = ((i0 & 1) ? 0x32u : 0x10u) | ((i1 & 1) ? 0x7600u : 0x5400u);
                    o[m] = __byte_perm(v[i0 >> 1], v[i1 >> 1], sel);
                }
                *reinterpret_cast<uint4*>(dst + (kyo * 24 + kx) * STEP_BYTES) = make_uint4(o[0], o[1], o[2], o[3]);
            }
        }
        if (READBACK) {
            unsigned acc = 0;
#pragma unroll
            for (int i = 0; i < 9; i++) acc |= ld_relaxed(dst + ((i / 3) * 24 + i % 3) * STEP_BYTES);
            asm volatile("{\n.reg .pred p;\nsetp.eq.u32 p, %0, 0x9e3779b9;\n@p st.shared.u32 [%1], %0;\n}" ::"r"(acc), "r"(bounce + S0) : "memory");
        }
    }
}
__device__ __forceinline__ uint32_t act2(uint32_t u, const float4& cf) {
    return pack_bf(silu_half(fmaf(bf_lo(u), cf.x, cf.z)), silu_half(fmaf(bf_hi(u), cf.y, cf.w)));
}
__device__ __forceinline__ void norm_unit(uint32_t (&u)[4], const float4& ca, const float4& cb) {
    u[0] = act2(u[0], ca); u[1] = act2(u[1], ca); u[2] = act2(u[2], cb); u[3] = act2(u[3], cb);
}
template <int FIRST, int N>
__device__ __forceinline__ void norm_block(uint32_t (&u)[4][4], float4 (&cf)[8], bool load_cf, uint32_t cfa, uint32_t act, uint32_t mask, uint32_t fbar, int lane) {
    if (load_cf) {
#pragma unroll
        for (int i = 2 * FIRST; i < 2 * (FIRST + N); i++) cf[i] = lds128f(cfa + (i >> 1) * 256 + (i & 1) * 64);
    }
#pragma unroll
    for (int t = FIRST; t < FIRST + N; t++) {
        norm_unit(u[t], cf[2 * t], cf[2 * t + 1]);
        stsm4(act + t * 2 * KC_BYTES, u[t][0] & mask, u[t][1] & mask, u[t][2] & mask, u[t][3] & mask);
    }
    fence_async_smem();
    __syncwarp();
    if (lane < N) mbar_arrive(fbar + 16 * (FIRST + lane));
}
__device__ __forceinline__ void stat_mma(float (&c)[4], uint32_t p, uint32_t q) {
    asm("mma.sync.aligned.m16n8k16.row.col.f32.bf16.bf16.f32 {%0,%1,%2,%3}, {%4,%5,%6,%5}, {%4,%6}, {%0,%1,%2,%3};"
        : "+f"(c[0]), "+f"(c[1]), "+f"(c[2]), "+f"(c[3]) : "r"(p), "r"(0x3f803f80u), "r"(q));
}
__device__ __forceinline__ void stat_store(const float (&c)[4], uint32_t dst, int lane) {
    const int g = lane >> 2, t = lane & 3;
    if (t == (g >> 1)) sts32f(dst + g * 4, (g & 1) ? c[1] : c[0]);
    if (g == 7) sts32f(dst + 32 + t * 4, c[2] + c[3]);
}
__device__ __forceinline__ float sum4(float4 v) { return (v.x + v.y) + (v.z + v.w); }
__device__ __forceinline__ void stat_publish(uint32_t src, float* acc, int lane, bool real) {
    const uint32_t a = src + (lane & 15) * 48;
    float q = sum4(lds128f(a)) + sum4(lds128f(a + 16)), sm = sum4(lds128f(a + 32));
    q += __shfl_xor_sync(0xffffffffu, q, 1); sm += __shfl_xor_sync(0xffffffffu, sm, 1);
    q += __shfl_xor_sync(0xffffffffu, q, 2); sm += __shfl_xor_sync(0xffffffffu, sm, 2);
    if (real && (lane & 19) == 0) red_add4(acc + lane, 1.f, sm, q, 1.f);
}
__device__ __forceinline__ void fence_acc(float (&d)[64]) {
#pragma unroll
    for (int i = 0; i < 64; i++) asm volatile("" : "+f"(d[i])::"memory");
}
__device__ __forceinline__ void ld_unit(uint32_t (&u)[4], const uint4* p) {
    asm volatile("ld.relaxed.gpu.global.v4.u32 {%0,%1,%2,%3}, [%4];" : "=r"(u[0]), "=r"(u[1]), "=r"(u[2]), "=r"(u[3]) : "l"(p) : "memory");
}

__global__ void __cluster_dims__(2, 1, 1) __launch_bounds__(NTHREADS, 1)
resblock_kernel(const __nv_bfloat16* __restrict__ w1,
                const __nv_bfloat16* __restrict__ t_emb, const __nv_bfloat16* __restrict__ g1,
                const __nv_bfloat16* __restrict__ be1, const __nv_bfloat16* __restrict__ w_emb,
                const __nv_bfloat16* __restrict__ g2, const __nv_bfloat16* __restrict__ be2,
                const __nv_bfloat16* __restrict__ w2, __nv_bfloat16* __restrict__ out, Scratch* __restrict__ gs,
                const __grid_constant__ CUtensorMap xmap) {
    const unsigned clk0 = clock32();
    if (threadIdx.x == 480) TLG(1);
    const int tid = threadIdx.x, warp = __shfl_sync(0xffffffffu, tid >> 5, 0), lane = tid & 31;
    const int cta = blockIdx.x, b = cta >> 6, r = cta & 63;

    const uint32_t woff = ((2 * r + (lane >> 4)) * C + b * 64) * 18 + (lane & 15) * 16;
    const int seg = lane & 7;
    uint4 v[5];
    if (warp == 0) {
        const char* w1s = reinterpret_cast<const char*>(w1) + woff;
#pragma unroll
        for (int k = 0; k < 4; k++) v[k] = __ldg(reinterpret_cast<const uint4*>(w1s + k * 256));
        if ((lane & 15) < 8) v[4] = __ldg(reinterpret_cast<const uint4*>(w1s + 1024));
    }
    if (warp != 3) asm volatile("barrier.cluster.arrive.relaxed.aligned;" ::: "memory");
    const bool has_outer = (r != 0) && (r != HW - 1);
    if (warp == 1 || warp == 2 || warp == 4 || warp == 5) {
        const int g = warp < 3 ? warp - 1 : 7 - warp;
        if (elect_one()) {
            asm volatile("prefetch.tensormap [%0];" ::"l"(&xmap) : "memory");
            mbar_init(BAR(BAR_X) + 8 * g, 1);
            if (g == 3) mbar_init(BAR(BAR_X + 4), 1);
            mbar_expect(BAR(BAR_X) + 8 * g, 4096);
            fence_async_smem();
            while (clock32() - clk0 < XDELAY + g * XSTAG) {}
            tma_x(SM_XOWN + g * 4096, &xmap, r, b * C + g * 32, BAR(BAR_X) + 8 * g);
            if (g == 3 && has_outer) {
                mbar_expect(BAR(BAR_X + 4), 16384);
#pragma unroll
                for (int i = 0; i < 4; i++) tma_x(SM_XOUT + i * 4096, &xmap, r + ((r & 1) ? 1 : -1), b * C + i * 32, BAR(BAR_X + 4));
            }
        }
        __syncwarp();
        bar_arrive(4, 256 + 32 + 128);
        mbar_wait(BAR(BAR_X) + 8 * g, 0);
        if (lane == 0) TL(70 + g);
        float c[2][4] = {{0.f, 0.f, 0.f, 0.f}, {0.f, 0.f, 0.f, 0.f}};
#pragma unroll
        for (int k = 0; k < 8; k++) {
            const uint4 q = lds128(SM_XOWN + g * 4096 + k * 512 + lane * 16);
            stat_mma(c[0], q.x, q.y); stat_mma(c[1], q.z, q.w);
        }
#pragma unroll
        for (int i = 0; i < 4; i++) c[0][i] += c[1][i];
        stat_store(c[0], SM_RED + g * 48, lane);
        __syncwarp();
        if (lane == 0) {
            const uint32_t a = SM_RED + g * 48;
            red_add4(&gs->acc[b * 32 + g * 4], 1.f, sum4(lds128f(a + 32)), sum4(lds128f(a)) + sum4(lds128f(a + 16)), 1.f);
            TL(74 + g);
        }
    }
    if (warp == 0) {
        weight_block<true>(v, SM_BNC, gs->wt, cta, lane);
        __syncwarp();
        if (lane == 0) TL(4);
        if (lane < 2) asm volatile("red.relaxed.gpu.global.add.u32 [%0], 1;" ::"l"(&gs->wcnt[lane * 32]) : "memory");
        if (lane == 0) TL(5);
    }

    if (warp >= 8) {
        const int nw = warp - 8;
        bar_sync(4, 256 + 32 + 128);
        const int par = nw >> 2, wq = nw & 3;
        const uint32_t act_off = SM_ACT + (par * 2 + (lane >> 4)) * CH_PITCH + (2 + wq * 16 + (lane & 15)) * 16;
        const uint32_t stg_off = (par * 16 + (lane >> 4) * 8 + (lane & 7)) * 128 + (((2 * wq + ((lane >> 3) & 1)) ^ (lane & 7)) << 4);
        const uint32_t cfa = SM_COEF + par * 128 + (lane & 3) * 16;
        const uint32_t fbar = BAR(BAR_FULL) + 8 * par;
        uint4* inbox = gs->box + cta * 1024 + nw * 32 + lane;
#pragma unroll 1
        for (int conv = 0; conv < 2; conv++) {
            uint32_t u[4][4], w[4][4];
            float4 cf[8];
            if (conv == 0) {
                mbar_wait(BAR(BAR_X), 0); ldsm4t(u[0], SM_XOWN + stg_off);
                mbar_wait(BAR(BAR_X + 1), 0); ldsm4t(u[1], SM_XOWN + stg_off + 4096);
                mbar_wait(BAR(BAR_STATS), 0);
                if (tid == 256) TL(22);
                norm_block<0, 1>(u, cf, true, cfa, act_off, ~0u, fbar, lane);
                if (tid == 256) TL(8);
                mbar_wait(BAR(BAR_X + 2), 0); ldsm4t(u[2], SM_XOWN + stg_off + 8192);
                mbar_wait(BAR(BAR_STATS + 1), 0);
                norm_block<1, 1>(u, cf, true, cfa, act_off, ~0u, fbar, lane);
                mbar_wait(BAR(BAR_X + 3), 0); ldsm4t(u[3], SM_XOWN + stg_off + 12288);
                mbar_wait(BAR(BAR_STATS + 2), 0);
                norm_block<2, 1>(u, cf, true, cfa, act_off, ~0u, fbar, lane);
                mbar_wait(BAR(BAR_STATS + 3), 0);
                norm_block<3, 1>(u, cf, true, cfa, act_off, ~0u, fbar, lane);
                if (has_outer) {
                    mbar_wait(BAR(BAR_X + 4), 0);
#pragma unroll
                    for (int i = 0; i < 4; i++) ldsm4t(w[i], SM_XOUT + stg_off + i * 4096);
                }
                bar_sync(3, 256);
                if (nw == 0) sts128(SM_ACT + 2 * ROW_BYTES + (lane >> 1) * CH_PITCH + (lane & 1) * 16, make_uint4(0, 0, 0, 0));
            } else {
                mbar_wait(BAR(BAR_HW), 0);
#pragma unroll
                for (int i = 0; i < 4; i++) ldsm4(u[i], act_off + i * 2 * KC_BYTES);
                mbar_wait(BAR(BAR_STATS + 1), 1);
                mbar_wait(BAR(BAR_STATS), 1);
                if (tid == 256) TL(26);
                norm_block<0, 2>(u, cf, true, cfa, act_off, ~0u, fbar, lane);
                if (tid == 256) TL(16);
                mbar_wait(BAR(BAR_STATS + 2), 1);
                mbar_wait(BAR(BAR_STATS + 3), 1);
                norm_block<2, 2>(u, cf, true, cfa, act_off, ~0u, fbar, lane);
            }
            if (tid == 256) TL(84 + conv);
            if (conv == 1 && has_outer) {
                unsigned it = 0;
                while (ld_relaxed(inbox + 3 * 256 + 31 - lane) == 0 && ++it < SPIN_LIMIT) {}
                if (tid == 256) TL(89);
                while (true) {
#pragma unroll
                    for (int i = 0; i < 4; i++) ld_unit(w[i], inbox + i * 256);
                    bool ok = true;
#pragma unroll
                    for (int i = 0; i < 16; i++) ok = ok && w[i >> 2][i & 3] != 0;
                    if (__all_sync(0xffffffffu, ok) || ++it > SPIN_LIMIT) break;
                }
#pragma unroll
                for (int i = 0; i < 16; i++) w[i >> 2][i & 3] = ~w[i >> 2][i & 3];
            }
            if (tid == 256) TL(24 + conv * 4);
            norm_block<0, 4>(w, cf, false, cfa, act_off + 2 * ROW_BYTES, has_outer ? ~0u : 0u, fbar + 128, lane);
            if (tid == 256) TL(23 + conv * 4);
        }
        if (has_outer) {
            mbar_wait(BAR(BAR_FULL + NSTAGE - 1), 1);
#pragma unroll
            for (int i = 0; i < 4; i++) inbox[i * 256] = make_uint4(0, 0, 0, 0);
        }
    } else if (warp < 4) {
        const int wq = warp;
        if (wq == 3) {
            if (elect_one()) {
#pragma unroll
                for (int i = 0; i < NSTAGE; i++) mbar_init(BAR(BAR_FULL + i), (i >> 3) == 1 ? 1 : 5);
#pragma unroll
                for (int i = 0; i <= NS; i++) mbar_init(BAR(BAR_WEMPTY + i), 4);
#pragma unroll
                for (int i = BAR_STATS; i < BAR_X; i++) mbar_init(BAR(i), i == BAR_EMB ? 2 : 1);
                asm volatile("fence.mbarrier_init.release.cluster;" ::: "memory");
            }
            __syncwarp();
            fence_async_smem();
            bar_arrive(0, 96);
            bar_arrive(5, 96);
            bar_arrive(4, 256 + 32 + 128);
            const uint4 z = make_uint4(0, 0, 0, 0);
#pragma unroll
            for (int i = 0; i < 2; i++) sts128(SM_ACT + (i * 16 + (lane >> 1)) * CH_PITCH + (lane & 1) * 16, z);
            if (lane < 4) sts128(SM_ACT + (2 + (lane >> 1)) * ROW_BYTES + (lane & 1) * 16, z);
            if (lane < 16) sts128(SM_ONES + lane * 16, make_uint4(lane < 8 ? 0x3f803f80u : 0u, 0, 0, 0));
            fence_async_smem();
            asm volatile("barrier.cluster.arrive.release.aligned;" ::: "memory");
        }
        bar_sync(2, 128);

        float d[64];
#pragma unroll
        for (int i = 0; i < 64; i++) d[i] = 0.f;
#pragma unroll 1
        for (int conv = 0; conv < 2; conv++) {
            fence_acc(d);
            mma_stages<0>(d, conv, tid, gs);
            if (conv == 0) {
                asm volatile("wgmma.fence.sync.aligned;" ::: "memory");
                wgmma128<(SM_ONES >> 4) | (8u << 16), (SM_EMB >> 4), 0>(d);
                asm volatile("wgmma.commit_group.sync.aligned;" ::: "memory");
            }
            asm volatile("wgmma.wait_group.sync.aligned 0;" ::: "memory");
            fence_acc(d);
            if (tid == 0) TL(10 + conv * 8);
            if (conv == 1) break;

            uint32_t hp[32];
#pragma unroll
            for (int g = 0; g < 4; g++) {
                float c[4] = {0.f, 0.f, 0.f, 0.f};
#pragma unroll
                for (int i = 0; i < 8; i++) hp[8 * g + i] = pack_bf(d[16 * g + 2 * i], d[16 * g + 2 * i + 1]);
#pragma unroll
                for (int i = 0; i < 4; i++) stat_mma(c, hp[8 * g + 2 * i], hp[8 * g + 2 * i + 1]);
                stat_store(c, SM_RED + (g * 4 + wq) * 48, lane);
            }
            bar_sync(2, 128);
            if (wq == 0) stat_publish(SM_RED, &gs->acc[(NB + b) * 32], lane, true);
            if (tid == 0) TL(11);
            const uint32_t hbase = SM_ACT + (lane >> 4) * CH_PITCH + (2 + wq * 16 + (lane & 15)) * 16;
#pragma unroll
            for (int kc = 0; kc < 8; kc++) stsm4(hbase + kc * 2 * CH_PITCH, hp[4 * kc], hp[4 * kc + 1], hp[4 * kc + 2], hp[4 * kc + 3]);
            __syncwarp();
            if (lane == 0) mbar_arrive(BAR(BAR_HW));
            if (lane < LAG) mbar_arrive(BAR(BAR_WEMPTY + (NSTAGE - LAG) % NS) + 8 * lane);
            if (has_outer) {
                uint4* outbox = gs->box + (cta + ((r & 1) ? 1 : -1)) * 1024 + tid;
#pragma unroll
                for (int kc = 0; kc < 8; kc++) outbox[kc * 128] = make_uint4(~hp[4 * kc], ~hp[4 * kc + 1], ~hp[4 * kc + 2], ~hp[4 * kc + 3]);
            }
            if (tid == 0) TL(12);
            const uint32_t xbase = SM_XOWN + ((lane >> 4) * 8 + (lane & 7)) * 128 + (((2 * wq + ((lane >> 3) & 1)) ^ (lane & 7)) << 4);
#pragma unroll
            for (int kc = 0; kc < 8; kc++) {
                uint32_t p[4];
                ldsm4t(p, xbase + kc * 2048);
#pragma unroll
                for (int i = 0; i < 4; i++) { d[8 * kc + 2 * i] = bf_lo(p[i]); d[8 * kc + 2 * i + 1] = bf_hi(p[i]); }
            }
        }
        {
            const uint32_t obase = slot_addr(0) + ((lane >> 4) * 8 + (lane & 7)) * OUT_PITCH + (wq * 16 + ((lane >> 3) & 1) * 8) * 2;
#pragma unroll
            for (int kc = 0; kc < 8; kc++) {
                stsm4t(obase + kc * 16 * OUT_PITCH, pack_bf(d[8 * kc + 0], d[8 * kc + 1]), pack_bf(d[8 * kc + 2], d[8 * kc + 3]),
                       pack_bf(d[8 * kc + 4], d[8 * kc + 5]), pack_bf(d[8 * kc + 6], d[8 * kc + 7]));
            }
            bar_sync(2, 128);
            const int oc0 = tid >> 3;
            __nv_bfloat16* dst = out + ((size_t)(b * C + oc0) * HW + r) * HW + seg * 8;
#pragma unroll
            for (int i = 0; i < 8; i++)
                *reinterpret_cast<uint4*>(dst + (size_t)i * 16 * HW * HW) = lds128(slot_addr(0) + (oc0 + 16 * i) * OUT_PITCH + seg * 16);
            if (tid == 0) { TL(20); TLG(21); }
        }
    } else if (warp < 6) {
        bar_sync(5, 96);
        if (warp == 5) {
            asm volatile("barrier.cluster.wait.acquire.aligned;" ::: "memory");
            const uint32_t peer = (r & 1) ^ 1;
            const uint32_t self0 = mapa(0, r & 1), peer0 = mapa(0, peer);
#pragma unroll 1
            for (int conv = 0; conv < 2; conv++) {
#pragma unroll 1
                for (int kc = 0; kc < 8; kc++) {
                    mbar_wait(BAR(BAR_FULL) + 8 * kc, conv);
                    if (elect_one())
                        asm volatile("cp.async.bulk.shared::cluster.shared::cta.mbarrier::complete_tx::bytes [%0], [%1], %2, [%3];"
                                     ::"r"(peer0 + SM_ACT + ROW_BYTES + kc * KC_BYTES), "r"(self0 + SM_ACT + kc * KC_BYTES), "r"(KC_BYTES),
                                       "r"(peer0 + BAR(BAR_FULL + 8) + 8 * kc) : "memory");
                }
                if (lane == 0) TL(86 + conv);
#pragma unroll 1
                for (int kc = 0; kc < 8; kc++) mbar_wait(BAR(BAR_FULL + 8) + 8 * kc, conv);
                if (lane == 0)
                    asm volatile("mbarrier.arrive.release.cluster.shared::cluster.b64 _, [%0];" ::"r"(peer0 + (conv ? BAR(BAR_ACK) : BAR(BAR_EMB))) : "memory");
            }
            mbar_wait(BAR(BAR_ACK), 0);
        } else {
            while (clock32() - clk0 < W2DELAY) {}
            const char* w2s = reinterpret_cast<const char*>(w2) + woff;
#pragma unroll
            for (int k = 0; k < 4; k++) v[k] = __ldg(reinterpret_cast<const uint4*>(w2s + k * 256));
            if ((lane & 15) < 8) v[4] = __ldg(reinterpret_cast<const uint4*>(w2s + 1024));
            const uint2* wsrc = reinterpret_cast<const uint2*>(w_emb + (size_t)r * 12 * C) + lane;
            uint2 wv[12];
#pragma unroll
            for (int i = 0; i < 12; i++) wv[i] = __ldg(wsrc + i * (C / 4));
            float tv = 0.f;
            if (lane < 12) tv = __bfloat162float(t_emb[b * E + r * 12 + lane]);
            weight_block<false>(v, SM_BNC + 2304, gs->wt + NSTAGE * STAGE_BYTES, cta, lane);
            const float sv = silu_half(0.5f * tv);
            float e0 = 0.f, e1 = 0.f, e2 = 0.f, e3 = 0.f;
#pragma unroll
            for (int i = 0; i < 12; i++) {
                const float sx = __shfl_sync(0xffffffffu, sv, i);
                e0 = fmaf(sx, bf_lo(wv[i].x), e0); e1 = fmaf(sx, bf_hi(wv[i].x), e1);
                e2 = fmaf(sx, bf_lo(wv[i].y), e2); e3 = fmaf(sx, bf_hi(wv[i].y), e3);
            }
            if (r == 0 && lane < 16) gs->acc[(NB + b) * 32 + lane] = 0.f;
            red_add4(&gs->emb[b * C + lane * 4], e0, e1, e2, e3);
            __syncwarp();
            if (lane == 0) TL(13);
            if (lane < 2) asm volatile("red.release.gpu.global.add.u32 [%0], 1;" ::"l"(&gs->wcnt[(NB + lane) * 32]) : "memory");
            if (lane == 0) TL(14);
            unsigned it = 0;
            while (ld_relaxed(&gs->wcnt[(NB + b) * 32]) < (unsigned)NCTA && ++it < SPIN_LIMIT) {}
            fence_acquire();
            const uint4 ef = ld_relaxed_v4(&gs->emb[b * C + lane * 4]);
            const uint32_t eu[4] = {ef.x, ef.y, ef.z, ef.w};
#pragma unroll
            for (int i = 0; i < 4; i++) {
                const float e = __uint_as_float(eu[i]);
                const float hi = bf_lo(pack_bf(e, 0.f));
                sts128(SM_EMB + (lane * 4 + i) * 16, make_uint4(pack_bf(hi, e - hi), 0, 0, 0));
            }
            fence_async_smem();
            __syncwarp();
            if (lane == 0) { mbar_arrive(BAR(BAR_EMB)); TL(19); }
        }
    } else if (warp == 6) {
        bar_sync(0, 96);
        const uint32_t ebytes = STAGE_BYTES + ((lane >> 3) == 1 ? KC_BYTES : 0);
        if (lane < NSTAGE) mbar_expect(BAR(BAR_FULL) + 8 * lane, ebytes);
        const int swap = (r & 1) ? 0 : 8 * STAGE_BYTES;
        const unsigned char* wsrc = gs->wt;
        uint32_t dst = S0 + SM_W, full = S0 + BAR(BAR_FULL), empty = BAR(BAR_WEMPTY);
        unsigned it = 0;
        while (ld_relaxed(&gs->wcnt[b * 32]) < (unsigned)NCTA && ++it < SPIN_LIMIT) {}
        fence_acquire();
        fence_async_global();
        if (lane == 0) TL(6);
#pragma unroll 1
        for (int g = 0; g < 2 * NSTAGE; g++) {
            if (g >= NS) {
                mbar_wait(empty, ((g - NS) / NS) & 1);
                if (g == NSTAGE) { mbar_wait(BAR(BAR_EMB), 0); fence_async_global(); }
                if (g == NSTAGE || g == NSTAGE + NS) {
                    if (lane >= g - NSTAGE && lane < g - NSTAGE + NS) mbar_expect(BAR(BAR_FULL) + 8 * lane, ebytes);
                    __syncwarp();
                }
            }
            if (elect_one()) bulk_g2s(dst, wsrc, STAGE_BYTES, full);
            wsrc += STAGE_BYTES; dst += STAGE_BYTES; full += 8; empty += 8;
            const int st = (g >= NSTAGE ? g - NSTAGE : g) + 1;
            if (st == 8 || st == NSTAGE) wsrc += swap;
            if (st == 16) wsrc -= 2 * swap;
            if (st == NS || st == NSTAGE) { dst -= NS * STAGE_BYTES; empty -= 8 * NS; }
            if (st == NSTAGE) full -= 8 * NSTAGE;
        }
    } else {
        const uint2 ga1 = __ldg(reinterpret_cast<const uint2*>(g1) + lane), bt1 = __ldg(reinterpret_cast<const uint2*>(be1) + lane);
        const uint2 ga2 = __ldg(reinterpret_cast<const uint2*>(g2) + lane), bt2 = __ldg(reinterpret_cast<const uint2*>(be2) + lane);
        bar_sync(0, 96);
#pragma unroll 1
        for (int conv = 0; conv < 2; conv++) {
            if (conv == 1) mbar_wait(BAR(BAR_EMB), 0);
            const float* asrc = &gs->acc[(conv * NB + b) * 32 + (lane >> 3) * 4];
            const uint2 ga = conv ? ga2 : ga1, bt = conv ? bt2 : bt1;
            bool done = false;
            unsigned it = 0;
#pragma unroll 1
            while (true) {
                const uint4 f = ld_relaxed_v4(asrc);
                const bool fresh = !done && (((f.x == 0x42800000u) & (f.w == 0x42800000u)) || it > SPIN_LIMIT);
                it++;
                if (!__any_sync(0xffffffffu, fresh)) continue;
                if (lane == 0 && fresh) TL(7 + conv * 8);
                if (lane == 24 && fresh) TL(90 + conv);
                const float inv_n = 1.0f / (32.0f * HW * HW);
                const float mean = __uint_as_float(f.y) * inv_n;
                const float var = fmaxf(fmaf(-mean, mean, __uint_as_float(f.z) * inv_n), 0.f);
                const float rs = 0.5f * rsqrtf(var + 1e-5f);
                float4 k0, k1;
                k0.x = rs * bf_lo(ga.x); k0.y = rs * bf_hi(ga.x); k1.x = rs * bf_lo(ga.y); k1.y = rs * bf_hi(ga.y);
                k0.z = fmaf(-mean, k0.x, 0.5f * bf_lo(bt.x)); k0.w = fmaf(-mean, k0.y, 0.5f * bf_hi(bt.x));
                k1.z = fmaf(-mean, k1.x, 0.5f * bf_lo(bt.y)); k1.w = fmaf(-mean, k1.y, 0.5f * bf_hi(bt.y));
                if (fresh) {
                    sts128f(SM_COEF + lane * 32, k0);
                    sts128f(SM_COEF + lane * 32 + 16, k1);
                }
                __syncwarp();
                if (fresh && (lane & 7) == 0) mbar_arrive(BAR(BAR_STATS) + lane);
                done = done || fresh;
                if (__all_sync(0xffffffffu, done)) break;
            }
        }
        if (r == 0) {
            if (lane < 16) gs->acc[b * 32 + lane] = 0.f;
            if (lane < 2) gs->wcnt[(lane * NB + b) * 32] = 0;
            *reinterpret_cast<float4*>(&gs->emb[b * C + lane * 4]) = make_float4(0.f, 0.f, 0.f, 0.f);
        }
    }
}

}

extern "C" void kernel_launch(void* const* d_in, const int* in_sizes, int n_in, void* d_out, int out_size) {
    (void)in_sizes; (void)n_in; (void)out_size;
    typedef CUresult (*EncodeFn)(CUtensorMap*, CUtensorMapDataType, cuuint32_t, void*, const cuuint64_t*, const cuuint64_t*,
                                 const cuuint32_t*, const cuuint32_t*, CUtensorMapInterleave, CUtensorMapSwizzle,
                                 CUtensorMapL2promotion, CUtensorMapFloatOOBfill);
    static Scratch* gs = nullptr;
    static EncodeFn encode = nullptr;
    if (!gs) {
        cudaFuncSetAttribute(resblock_kernel, cudaFuncAttributeMaxDynamicSharedMemorySize, SM_TOTAL);
        cudaGetSymbolAddress((void**)&gs, g_scratch);
        cudaDriverEntryPointQueryResult qr;
        cudaGetDriverEntryPoint("cuTensorMapEncodeTiled", (void**)&encode, cudaEnableDefault, &qr);
    }
    CUtensorMap xmap;
    const cuuint64_t dims[3] = {HW, HW, NB * C}, strides[2] = {HW * 2, HW * HW * 2};
    const cuuint32_t box[3] = {HW, 1, 32}, es[3] = {1, 1, 1};
    encode(&xmap, CU_TENSOR_MAP_DATA_TYPE_BFLOAT16, 3, d_in[0], dims, strides, box, es, CU_TENSOR_MAP_INTERLEAVE_NONE,
           CU_TENSOR_MAP_SWIZZLE_128B, CU_TENSOR_MAP_L2_PROMOTION_NONE, CU_TENSOR_MAP_FLOAT_OOB_FILL_NONE);
    resblock_kernel<<<NCTA, NTHREADS, SM_TOTAL>>>(
        (const __nv_bfloat16*)d_in[4], (const __nv_bfloat16*)d_in[1],
        (const __nv_bfloat16*)d_in[2], (const __nv_bfloat16*)d_in[3], (const __nv_bfloat16*)d_in[5],
        (const __nv_bfloat16*)d_in[6], (const __nv_bfloat16*)d_in[7], (const __nv_bfloat16*)d_in[8],
        (__nv_bfloat16*)d_out, gs, xmap);
}
```

```cpp
#include <cuda_runtime.h>
#include <cuda.h>
#include <cuda_bf16.h>
#include <stdint.h>

namespace {

constexpr int C = 128, HW = 64, NB = 2, E = 768;
constexpr int NCTA = NB * HW;
constexpr int NTHREADS = 16 * 32;
constexpr int CH_PITCH = 66 * 16;
constexpr int ROW_BYTES = 16 * CH_PITCH;
constexpr int STEP_BYTES = 4096;
constexpr int STAGE_BYTES = 3 * STEP_BYTES;
constexpr int NSTAGE = 24;
constexpr int KC_BYTES = 2 * CH_PITCH;
constexpr int NS = 12;
constexpr int LAG = 1;
#define XDELAY 500
#define HDELAY 600
#define NA 2
#define RB 1
#define XSTAG 400
#define HSEND 0
#define W2DELAY 2800

constexpr uint32_t SMEM_BASE = 0x400;
constexpr uint32_t SM_XOWN = SMEM_BASE;
constexpr uint32_t SM_ACT = SM_XOWN + 16384 + 512;
constexpr uint32_t SM_XOUT = SM_ACT + 2 * ROW_BYTES + 512;
static_assert(SM_XOUT % 1024 == 0, "swizzle atom alignment");
constexpr uint32_t SM_W = SM_ACT + 3 * ROW_BYTES + 128;
__host__ __device__ constexpr uint32_t slot_addr(int slot) { return SM_W + slot * STAGE_BYTES; }
constexpr uint32_t SM_COEF = SM_W + NS * STAGE_BYTES;
constexpr uint32_t SM_EMB = SM_COEF + 1024;
constexpr uint32_t SM_ONES = SM_EMB + 2048;
constexpr uint32_t SM_RED = SM_ONES + 256;
constexpr uint32_t SM_BNC = SM_RED + 1280;
constexpr uint32_t SM_BAR = SM_BNC + 2 * 2304;
constexpr int BAR_FULL = 0, BAR_WEMPTY = NSTAGE, BAR_HW = BAR_WEMPTY + NS, BAR_STATS = BAR_HW + 1  ,
              BAR_EMB = BAR_STATS + 4, BAR_ACK = BAR_EMB + 1, BAR_X = BAR_ACK + 1  , NBAR = BAR_X + 5;
constexpr int SM_TOTAL = SM_BAR + NBAR * 8 - SMEM_BASE;
static_assert(SM_TOTAL <= 232448, "smem");
static_assert(NBAR <= 96, "barrier init");
constexpr int OUT_PITCH = 144;
__host__ __device__ constexpr uint32_t BAR(int i) { return SM_BAR + 8 * i; }
__host__ __device__ constexpr int ky_of(int kyo) { return kyo == 0 ? 1 : (kyo == 1 ? 0 : 2); }

constexpr unsigned SPIN_LIMIT = 1u << 16;

struct Scratch {
    float acc[2 * NB * 32];
    unsigned wcnt[2 * NB * 32];
    float emb[NB * C];
    unsigned char wt[2 * NSTAGE * STAGE_BYTES];
    uint4 box[NCTA * 1024];
};
__device__ __align__(1024) Scratch g_scratch;
#define TL(i) do {} while (0)
#define TLG(i) do {} while (0)

__device__ __forceinline__ unsigned clock32() { unsigned c; asm volatile("mov.u32 %0, %%clock;" : "=r"(c)); return c; }
__device__ __forceinline__ uint32_t mapa(uint32_t a, uint32_t rank) {
    uint32_t d;
    asm("mapa.shared::cluster.u32 %0, %1, %2;" : "=r"(d) : "r"(a), "r"(rank));
    return d;
}
#define S0 mapa(0, blockIdx.x & 1)
__device__ __forceinline__ void mbar_init(uint32_t bar, int cnt) {
    asm volatile("mbarrier.init.shared::cta.b64 [%0], %1;" ::"r"(bar + S0), "r"(cnt) : "memory");
}
__device__ __forceinline__ void mbar_arrive(uint32_t bar) {
    asm volatile("mbarrier.arrive.shared::cta.b64 _, [%0];" ::"r"(bar + S0) : "memory");
}
__device__ __forceinline__ void mbar_expect(uint32_t bar, uint32_t bytes) {
    asm volatile("mbarrier.arrive.expect_tx.shared::cta.b64 _, [%0], %1;" ::"r"(bar + S0), "r"(bytes) : "memory");
}
__device__ __forceinline__ bool mbar_try(uint32_t bar, uint32_t par) {
    uint32_t ok;
    asm volatile("{\n.reg .pred p;\nmbarrier.try_wait.parity.shared::cta.b64 p, [%1], %2;\nselp.u32 %0, 1, 0, p;\n}"
                 : "=r"(ok) : "r"(bar + S0), "r"(par) : "memory");
    return ok;
}
__device__ __forceinline__ bool mbar_test(uint32_t bar, uint32_t par) {
    uint32_t ok;
    asm volatile("{\n.reg .pred p;\nmbarrier.test_wait.parity.shared::cta.b64 p, [%1], %2;\nselp.u32 %0, 1, 0, p;\n}"
                 : "=r"(ok) : "r"(bar + S0), "r"(par) : "memory");
    return ok;
}
__device__ __forceinline__ void mbar_wait(uint32_t bar, uint32_t par) {
    unsigned it = 0;
#pragma unroll 1
    while (!mbar_try(bar, par) && ++it < SPIN_LIMIT) {}
}
__device__ __forceinline__ bool elect_one() {
    uint32_t p;
    asm volatile("{\n.reg .pred p;\nelect.sync _|p, 0xffffffff;\nselp.u32 %0, 1, 0, p;\n}" : "=r"(p));
    return p;
}
__device__ __forceinline__ void fence_async_smem() { asm volatile("fence.proxy.async.shared::cta;" ::: "memory"); }
__device__ __forceinline__ void fence_async_global() { asm volatile("fence.proxy.async.global;" ::: "memory"); }
__device__ __forceinline__ void fence_acquire() { asm volatile("fence.acquire.gpu;" ::: "memory"); }
__device__ __forceinline__ void bar_sync(int id, int n) { asm volatile("bar.sync %0, %1;" ::"r"(id), "r"(n) : "memory"); }
__device__ __forceinline__ void bar_arrive(int id, int n) { asm volatile("bar.arrive %0, %1;" ::"r"(id), "r"(n) : "memory"); }
__device__ __forceinline__ void bulk_g2s(uint32_t dst, const void* src, uint32_t bytes, uint32_t bar) {
    asm volatile("cp.async.bulk.shared::cluster.global.mbarrier::complete_tx::bytes [%0], [%1], %2, [%3];"
                 ::"r"(dst), "l"(src), "r"(bytes), "r"(bar) : "memory");
}
__device__ __forceinline__ void tma_x(uint32_t dst, const CUtensorMap* tm, int row, int ch, uint32_t bar) {
    asm volatile("cp.async.bulk.tensor.3d.shared::cluster.global.mbarrier::complete_tx::bytes [%0], [%1, {%2, %3, %4}], [%5];"
                 ::"r"(dst + S0), "l"(tm), "r"(0), "r"(row), "r"(ch), "r"(bar + S0) : "memory");
}
__device__ __forceinline__ uint4 ld_relaxed_v4(const void* p) {
    uint4 v;
    asm volatile("ld.relaxed.gpu.global.v4.u32 {%0,%1,%2,%3}, [%4];" : "=r"(v.x), "=r"(v.y), "=r"(v.z), "=r"(v.w) : "l"(p) : "memory");
    return v;
}
__device__ __forceinline__ unsigned ld_relaxed(const void* p) {
    unsigned v;
    asm volatile("ld.relaxed.gpu.global.u32 %0, [%1];" : "=r"(v) : "l"(p) : "memory");
    return v;
}
__device__ __forceinline__ void red_add4(float* p, float a, float b, float c, float d) {
    asm volatile("red.relaxed.gpu.global.add.v4.f32 [%0], {%1,%2,%3,%4};" ::"l"(p), "f"(a), "f"(b), "f"(c), "f"(d) : "memory");
}
__device__ __forceinline__ void sts128(uint32_t a, uint4 v) {
    asm volatile("st.shared.v4.u32 [%0], {%1,%2,%3,%4};" ::"r"(a + S0), "r"(v.x), "r"(v.y), "r"(v.z), "r"(v.w) : "memory");
}
__device__ __forceinline__ void sts128f(uint32_t a, float4 v) {
    asm volatile("st.shared.v4.f32 [%0], {%1,%2,%3,%4};" ::"r"(a + S0), "f"(v.x), "f"(v.y), "f"(v.z), "f"(v.w) : "memory");
}
__device__ __forceinline__ void sts32f(uint32_t a, float v) { asm volatile("st.shared.f32 [%0], %1;" ::"r"(a + S0), "f"(v) : "memory"); }
__device__ __forceinline__ uint4 lds128(uint32_t a) {
    uint4 v;
    asm volatile("ld.shared.v4.u32 {%0,%1,%2,%3}, [%4];" : "=r"(v.x), "=r"(v.y), "=r"(v.z), "=r"(v.w) : "r"(a + S0) : "memory");
    return v;
}
__device__ __forceinline__ float4 lds128f(uint32_t a) {
    float4 v;
    asm volatile("ld.shared.v4.f32 {%0,%1,%2,%3}, [%4];" : "=f"(v.x), "=f"(v.y), "=f"(v.z), "=f"(v.w) : "r"(a + S0) : "memory");
    return v;
}
__device__ __forceinline__ float2 lds64f(uint32_t a) {
    float2 v;
    asm volatile("ld.shared.v2.f32 {%0,%1}, [%2];" : "=f"(v.x), "=f"(v.y) : "r"(a + S0) : "memory");
    return v;
}
__device__ __forceinline__ float bf_lo(uint32_t u) { return __uint_as_float(u << 16); }
__device__ __forceinline__ float bf_hi(uint32_t u) { return __uint_as_float(u & 0xffff0000u); }
__device__ __forceinline__ uint32_t pack_bf(float lo, float hi) {
    uint32_t r;
    asm("cvt.rn.bf16x2.f32 %0, %1, %2;" : "=r"(r) : "f"(hi), "f"(lo));
    return r;
}
__device__ __forceinline__ float tanh_fast(float x) {
    float r;
    asm("tanh.approx.f32 %0, %1;" : "=f"(r) : "f"(x));
    return r;
}
__device__ __forceinline__ float silu_half(float h) { return fmaf(h, tanh_fast(h), h); }
__device__ __forceinline__ void ldsm4(uint32_t (&u)[4], uint32_t a) {
    asm volatile("ldmatrix.sync.aligned.m8n8.x4.shared.b16 {%0,%1,%2,%3}, [%4];"
                 : "=r"(u[0]), "=r"(u[1]), "=r"(u[2]), "=r"(u[3]) : "r"(a + S0) : "memory");
}
__device__ __forceinline__ void ldsm4t(uint32_t (&u)[4], uint32_t a) {
    asm volatile("ldmatrix.sync.aligned.m8n8.x4.trans.shared.b16 {%0,%1,%2,%3}, [%4];"
                 : "=r"(u[0]), "=r"(u[1]), "=r"(u[2]), "=r"(u[3]) : "r"(a + S0) : "memory");
}
__device__ __forceinline__ void stsm4(uint32_t a, uint32_t p0, uint32_t p1, uint32_t p2, uint32_t p3) {
    asm volatile("stmatrix.sync.aligned.m8n8.x4.shared.b16 [%0], {%1,%2,%3,%4};" ::"r"(a + S0), "r"(p0), "r"(p1), "r"(p2), "r"(p3) : "memory");
}
__device__ __forceinline__ void stsm4t(uint32_t a, uint32_t p0, uint32_t p1, uint32_t p2, uint32_t p3) {
    asm volatile("stmatrix.sync.aligned.m8n8.x4.trans.shared.b16 [%0], {%1,%2,%3,%4};" ::"r"(a + S0), "r"(p0), "r"(p1), "r"(p2), "r"(p3) : "memory");
}

#define R8(o) "+f"(d[o]), "+f"(d[o + 1]), "+f"(d[o + 2]), "+f"(d[o + 3]), "+f"(d[o + 4]), "+f"(d[o + 5]), "+f"(d[o + 6]), "+f"(d[o + 7])
template <uint32_t ALO, uint32_t BLO, uint64_t AHI = 8, uint64_t BHI = 48>
__device__ __forceinline__ void wgmma128(float (&d)[64]) {
    asm volatile(
        "wgmma.mma_async.sync.aligned.m64n128k16.f32.bf16.bf16 "
        "{%0,%1,%2,%3,%4,%5,%6,%7,%8,%9,%10,%11,%12,%13,%14,%15,%16,%17,%18,%19,%20,%21,%22,%23,%24,%25,%26,%27,%28,%29,%30,%31,"
        "%32,%33,%34,%35,%36,%37,%38,%39,%40,%41,%42,%43,%44,%45,%46,%47,%48,%49,%50,%51,%52,%53,%54,%55,%56,%57,%58,%59,%60,%61,%62,%63},"
        " %64, %65, 1, 1, 1, 0, 0;"
        : R8(0), R8(8), R8(16), R8(24), R8(32), R8(40), R8(48), R8(56)
        : "l"((AHI << 32) | ALO), "l"((BHI << 32) | BLO));
}
template <int S>
__device__ __forceinline__ void mma_stages(float (&d)[64], int conv, int tid, Scratch* gs) {
    constexpr uint32_t A = ((SM_ACT + S * 2 * CH_PITCH + 16) >> 4) | ((CH_PITCH >> 4) << 16);
    constexpr uint32_t B = (slot_addr(S % NS) >> 4) | (8u << 16);
    if (S == 0) mbar_wait(BAR(BAR_FULL), conv);
    bool next_ok = true;
    constexpr uint32_t NEXT = S + 1 < NSTAGE ? BAR(BAR_FULL + S + 1) : BAR(BAR_EMB);
    const int npar = S + 1 < NSTAGE ? conv : 0;
    next_ok = mbar_test(NEXT, npar);
    if (S == 0 && tid == 0) TL(32 + conv * 24);
    asm volatile("wgmma.fence.sync.aligned;" ::: "memory");
    wgmma128<A, B>(d);
    wgmma128<A + 1, B + 16>(d);
    wgmma128<A + 2, B + 32>(d);
    asm volatile("wgmma.commit_group.sync.aligned;" ::: "memory");
    if (S >= LAG) {
        asm volatile("wgmma.wait_group.sync.aligned %0;" ::"n"(LAG) : "memory");
        if ((tid & 31) == 0) mbar_arrive(BAR(BAR_WEMPTY + (S + NS - LAG) % NS));
    }
    if (!next_ok) mbar_wait(NEXT, npar);
    if constexpr (S + 1 < NSTAGE) mma_stages<S + 1>(d, conv, tid, gs);
}

__device__ __forceinline__ void weight_load(uint4 (&t)[5], const __nv_bfloat16* w, int cta, int lane) {
    const char* base = reinterpret_cast<const char*>(w) + ((cta & 15) * 8 * C + (cta >> 4) * 16) * 18;
#pragma unroll
    for (int k = 0; k < 5; k++) {
        const int i = lane + 32 * k, row = (i * 57) >> 10;
        if (k < 4 || lane < 16) t[k] = __ldg(reinterpret_cast<const uint4*>(base + row * (C * 18 - 288) + i * 16));
    }
}
template <bool READBACK>
__device__ __forceinline__ void weight_block(const uint4 (&t)[5], uint32_t bounce, unsigned char* wt, int cta, int lane) {
#pragma unroll
    for (int k = 0; k < 5; k++)
        if (k < 4 || lane < 16) sts128(bounce + (lane + 32 * k) * 16, t[k]);
    __syncwarp();
    unsigned char* dst = wt + (cta >> 4) * STAGE_BYTES + (cta & 15) * 768;
    if (lane < 16) {
        uint32_t v[36];
#pragma unroll
        for (int i = 0; i < 9; i++) {
            const uint4 q = lds128(bounce + (lane & 7) * 288 + (lane >> 3) * 144 + i * 16);
            v[4 * i] = q.x; v[4 * i + 1] = q.y; v[4 * i + 2] = q.z; v[4 * i + 3] = q.w;
        }
#pragma unroll
        for (int kyo = 0; kyo < 3; kyo++) {
#pragma unroll
            for (int kx = 0; kx < 3; kx++) {
                const int tap = ky_of(kyo) * 3 + kx;
                uint32_t o[4];
#pragma unroll
                for (int m = 0; m < 4; m++) {
                    const int i0 = 18 * m + tap, i1 = i0 + 9;
                    const uint32_t sel = ((i0 & 1) ? 0x32u : 0x10u) | ((i1 & 1) ? 0x7600u : 0x5400u);
                    o[m] = __byte_perm(v[i0 >> 1], v[i1 >> 1], sel);
                }
                *reinterpret_cast<uint4*>(dst + kyo * 8 * STAGE_BYTES + kx * 256 + lane * 16) = make_uint4(o[0], o[1], o[2], o[3]);
            }
        }
    }
    if (READBACK) {
        __syncwarp();
        unsigned acc = 0;
        if (lane < 24) {
#pragma unroll
            for (int i = 0; i < 3; i++) acc |= ld_relaxed(dst + i * 8 * STAGE_BYTES + lane * 32);
        }
        asm volatile("{\n.reg .pred p;\nsetp.eq.u32 p, %0, 0x9e3779b9;\n@p st.shared.u32 [%1], %0;\n}" ::"r"(acc), "r"(bounce + S0) : "memory");
    }
}
__device__ __forceinline__ uint32_t act2(uint32_t u, const float4& cf) {
    return pack_bf(silu_half(fmaf(bf_lo(u), cf.x, cf.z)), silu_half(fmaf(bf_hi(u), cf.y, cf.w)));
}
__device__ __forceinline__ void norm_unit(uint32_t (&u)[4], const float4& ca, const float4& cb) {
    u[0] = act2(u[0], ca); u[1] = act2(u[1], ca); u[2] = act2(u[2], cb); u[3] = act2(u[3], cb);
}
template <int FIRST, int N>
__device__ __forceinline__ void norm_block(uint32_t (&u)[4][4], float4 (&cf)[8], bool load_cf, uint32_t cfa, uint32_t act, uint32_t mask, uint32_t fbar, int lane) {
    if (load_cf) {
#pragma unroll
        for (int i = 2 * FIRST; i < 2 * (FIRST + N); i++) cf[i] = lds128f(cfa + (i >> 1) * 256 + (i & 1) * 64);
    }
#pragma unroll
    for (int t = FIRST; t < FIRST + N; t++) {
        norm_unit(u[t], cf[2 * t], cf[2 * t + 1]);
        stsm4(act + t * 2 * KC_BYTES, u[t][0] & mask, u[t][1] & mask, u[t][2] & mask, u[t][3] & mask);
    }
    fence_async_smem();
    __syncwarp();
    if (lane < N) mbar_arrive(fbar + 16 * (FIRST + lane));
}
__device__ __forceinline__ void stat_mma(float (&c)[4], uint32_t p, uint32_t q) {
    asm("mma.sync.aligned.m16n8k16.row.col.f32.bf16.bf16.f32 {%0,%1,%2,%3}, {%4,%5,%6,%5}, {%4,%6}, {%0,%1,%2,%3};"
        : "+f"(c[0]), "+f"(c[1]), "+f"(c[2]), "+f"(c[3]) : "r"(p), "r"(0x3f803f80u), "r"(q));
}
__device__ __forceinline__ void stat_store(const float (&c)[4], uint32_t dst, int lane) {
    const int g = lane >> 2, t = lane & 3;
    if (t == (g >> 1)) sts32f(dst + g * 4, (g & 1) ? c[1] : c[0]);
    if (g == 7) sts32f(dst + 32 + t * 4, c[2] + c[3]);
}
__device__ __forceinline__ float sum4(float4 v) { return (v.x + v.y) + (v.z + v.w); }
__device__ __forceinline__ void stat_publish(uint32_t src, float* acc, int lane, bool real) {
    const uint32_t a = src + (lane & 15) * 48;
    float q = sum4(lds128f(a)) + sum4(lds128f(a + 16)), sm = sum4(lds128f(a + 32));
    q += __shfl_xor_sync(0xffffffffu, q, 1); sm += __shfl_xor_sync(0xffffffffu, sm, 1);
    q += __shfl_xor_sync(0xffffffffu, q, 2); sm += __shfl_xor_sync(0xffffffffu, sm, 2);
    if (real && (lane & 19) == 0) red_add4(acc + lane, 1.f, sm, q, 1.f);
}
__device__ __forceinline__ void fence_acc(float (&d)[64]) {
#pragma unroll
    for (int i = 0; i < 64; i++) asm volatile("" : "+f"(d[i])::"memory");
}
__device__ __forceinline__ void ld_unit(uint32_t (&u)[4], const uint4* p) {
    asm volatile("ld.relaxed.gpu.global.v4.u32 {%0,%1,%2,%3}, [%4];" : "=r"(u[0]), "=r"(u[1]), "=r"(u[2]), "=r"(u[3]) : "l"(p) : "memory");
}

__global__ void __cluster_dims__(2, 1, 1) __launch_bounds__(NTHREADS, 1)
resblock_kernel(const __nv_bfloat16* __restrict__ w1,
                const __nv_bfloat16* __restrict__ t_emb, const __nv_bfloat16* __restrict__ g1,
                const __nv_bfloat16* __restrict__ be1, const __nv_bfloat16* __restrict__ w_emb,
                const __nv_bfloat16* __restrict__ g2, const __nv_bfloat16* __restrict__ be2,
                const __nv_bfloat16* __restrict__ w2, __nv_bfloat16* __restrict__ out, Scratch* __restrict__ gs,
                const __grid_constant__ CUtensorMap xmap) {
    const unsigned clk0 = clock32();
    if (threadIdx.x == 480) TLG(1);
    const int tid = threadIdx.x, warp = __shfl_sync(0xffffffffu, tid >> 5, 0), lane = tid & 31;
    const int cta = blockIdx.x, b = cta >> 6, r = cta & 63;

    const int seg = lane & 7;
    uint4 v[5];
    if (warp == 0) {
        weight_load(v, w1, cta, lane);
    }
    if (warp != 3) asm volatile("barrier.cluster.arrive.relaxed.aligned;" ::: "memory");
    const bool has_outer = (r != 0) && (r != HW - 1);
    if (warp == 1 || warp == 2 || warp == 4 || warp == 5) {
        const int g = warp < 3 ? warp - 1 : 7 - warp;
        if (elect_one()) {
            asm volatile("prefetch.tensormap [%0];" ::"l"(&xmap) : "memory");
            mbar_init(BAR(BAR_X) + 8 * g, 1);
            if (g == 3) mbar_init(BAR(BAR_X + 4), 1);
            mbar_expect(BAR(BAR_X) + 8 * g, 4096);
            fence_async_smem();
            while (clock32() - clk0 < XDELAY + g * XSTAG) {}
            tma_x(SM_XOWN + g * 4096, &xmap, r, b * C + g * 32, BAR(BAR_X) + 8 * g);
            if (g == 3 && has_outer) {
                mbar_expect(BAR(BAR_X + 4), 16384);
#pragma unroll
                for (int i = 0; i < 4; i++) tma_x(SM_XOUT + i * 4096, &xmap, r + ((r & 1) ? 1 : -1), b * C + i * 32, BAR(BAR_X + 4));
            }
        }
        __syncwarp();
        bar_arrive(4, 256 + 32 + 128);
        mbar_wait(BAR(BAR_X) + 8 * g, 0);
        if (lane == 0) TL(70 + g);
        float c[2][4] = {{0.f, 0.f, 0.f, 0.f}, {0.f, 0.f, 0.f, 0.f}};
#pragma unroll
        for (int k = 0; k < 8; k++) {
            const uint4 q = lds128(SM_XOWN + g * 4096 + k * 512 + lane * 16);
            stat_mma(c[0], q.x, q.y); stat_mma(c[1], q.z, q.w);
        }
#pragma unroll
        for (int i = 0; i < 4; i++) c[0][i] += c[1][i];
        stat_store(c[0], SM_RED + g * 48, lane);
        __syncwarp();
        if (lane == 0) {
            const uint32_t a = SM_RED + g * 48;
            red_add4(&gs->acc[b * 32 + g * 4], 1.f, sum4(lds128f(a + 32)), sum4(lds128f(a)) + sum4(lds128f(a + 16)), 1.f);
            TL(74 + g);
        }
    }
    if (warp == 0) {
        weight_block<RB>(v, SM_BNC, gs->wt, cta, lane);
        __syncwarp();
        if (lane == 0) TL(4);
        if (lane < 2) asm volatile("red.relaxed.gpu.global.add.u32 [%0], 1;" ::"l"(&gs->wcnt[lane * 32]) : "memory");
        if (lane == 0) TL(5);
    }

    if (warp >= 8) {
        const int nw = warp - 8;
        bar_sync(4, 256 + 32 + 128);
        const int par = nw >> 2, wq = nw & 3;
        const uint32_t act_off = SM_ACT + (par * 2 + (lane >> 4)) * CH_PITCH + (2 + wq * 16 + (lane & 15)) * 16;
        const uint32_t stg_off = (par * 16 + (lane >> 4) * 8 + (lane & 7)) * 128 + (((2 * wq + ((lane >> 3) & 1)) ^ (lane & 7)) << 4);
        const uint32_t cfa = SM_COEF + par * 128 + (lane & 3) * 16;
        const uint32_t fbar = BAR(BAR_FULL) + 8 * par;
        uint4* inbox = gs->box + cta * 1024 + nw * 32 + lane;
#pragma unroll 1
        for (int conv = 0; conv < 2; conv++) {
            uint32_t u[4][4], w[4][4];
            float4 cf[8];
            if (conv == 0) {
                mbar_wait(BAR(BAR_X), 0); ldsm4t(u[0], SM_XOWN + stg_off);
                mbar_wait(BAR(BAR_X + 1), 0); ldsm4t(u[1], SM_XOWN + stg_off + 4096);
                mbar_wait(BAR(BAR_STATS), 0);
                if (tid == 256) TL(22);
                norm_block<0, 1>(u, cf, true, cfa, act_off, ~0u, fbar, lane);
                if (tid == 256) TL(8);
                mbar_wait(BAR(BAR_X + 2), 0); ldsm4t(u[2], SM_XOWN + stg_off + 8192);
                mbar_wait(BAR(BAR_STATS + 1), 0);
                norm_block<1, 1>(u, cf, true, cfa, act_off, ~0u, fbar, lane);
                mbar_wait(BAR(BAR_X + 3), 0); ldsm4t(u[3], SM_XOWN + stg_off + 12288);
                mbar_wait(BAR(BAR_STATS + 2), 0);
                norm_block<2, 1>(u, cf, true, cfa, act_off, ~0u, fbar, lane);
                mbar_wait(BAR(BAR_STATS + 3), 0);
                norm_block<3, 1>(u, cf, true, cfa, act_off, ~0u, fbar, lane);
                if (has_outer) {
                    mbar_wait(BAR(BAR_X + 4), 0);
#pragma unroll
                    for (int i = 0; i < 4; i++) ldsm4t(w[i], SM_XOUT + stg_off + i * 4096);
                }
                bar_sync(3, 256);
                if (nw == 0) sts128(SM_ACT + 2 * ROW_BYTES + (lane >> 1) * CH_PITCH + (lane & 1) * 16, make_uint4(0, 0, 0, 0));
            } else {
                mbar_wait(BAR(BAR_HW), 0);
#pragma unroll
                for (int i = 0; i < 4; i++) ldsm4(u[i], act_off + i * 2 * KC_BYTES);
                mbar_wait(BAR(BAR_STATS + 1), 1);
                mbar_wait(BAR(BAR_STATS), 1);
                if (tid == 256) TL(26);
                norm_block<0, 2>(u, cf, true, cfa, act_off, ~0u, fbar, lane);
                if (tid == 256) TL(16);
                mbar_wait(BAR(BAR_STATS + 2), 1);
                mbar_wait(BAR(BAR_STATS + 3), 1);
                norm_block<2, 2>(u, cf, true, cfa, act_off, ~0u, fbar, lane);
            }
            if (tid == 256) TL(84 + conv);
            if (conv == 1 && has_outer) {
                unsigned it = 0;
                while (ld_relaxed(inbox + 3 * 256 + 31 - lane) == 0 && ++it < SPIN_LIMIT) {}
                if (tid == 256) TL(89);
                while (true) {
#pragma unroll
                    for (int i = 0; i < 4; i++) ld_unit(w[i], inbox + i * 256);
                    bool ok = true;
#pragma unroll
                    for (int i = 0; i < 16; i++) ok = ok && w[i >> 2][i & 3] != 0;
                    if (__all_sync(0xffffffffu, ok) || ++it > SPIN_LIMIT) break;
                }
#pragma unroll
                for (int i = 0; i < 16; i++) w[i >> 2][i & 3] = ~w[i >> 2][i & 3];
            }
            if (tid == 256) TL(24 + conv * 4);
            norm_block<0, 4>(w, cf, false, cfa, act_off + 2 * ROW_BYTES, has_outer ? ~0u : 0u, fbar + 128, lane);
            if (tid == 256) TL(23 + conv * 4);
        }
        if (has_outer) {
            mbar_wait(BAR(BAR_FULL + NSTAGE - 1), 1);
#pragma unroll
            for (int i = 0; i < 4; i++) inbox[i * 256] = make_uint4(0, 0, 0, 0);
        }
    } else if (warp < 4) {
        const int wq = warp;
        if (wq == 3) {
            if (elect_one()) {
#pragma unroll
                for (int i = 0; i < NSTAGE; i++) mbar_init(BAR(BAR_FULL + i), (i >> 3) == 1 ? 1 : 5);
#pragma unroll
                for (int i = 0; i <= NS; i++) mbar_init(BAR(BAR_WEMPTY + i), 4);
#pragma unroll
                for (int i = BAR_STATS; i < BAR_X; i++) mbar_init(BAR(i), i == BAR_EMB ? 2 : 1);
                asm volatile("fence.mbarrier_init.release.cluster;" ::: "memory");
            }
            __syncwarp();
            fence_async_smem();
            bar_arrive(0, 96);
            bar_arrive(5, 96);
            bar_arrive(4, 256 + 32 + 128);
            const uint4 z = make_uint4(0, 0, 0, 0);
#pragma unroll
            for (int i = 0; i < 2; i++) sts128(SM_ACT + (i * 16 + (lane >> 1)) * CH_PITCH + (lane & 1) * 16, z);
            if (lane < 4) sts128(SM_ACT + (2 + (lane >> 1)) * ROW_BYTES + (lane & 1) * 16, z);
            if (lane < 16) sts128(SM_ONES + lane * 16, make_uint4(lane < 8 ? 0x3f803f80u : 0u, 0, 0, 0));
            fence_async_smem();
            asm volatile("barrier.cluster.arrive.release.aligned;" ::: "memory");
        }
        bar_sync(2, 128);

        float d[64];
#pragma unroll
        for (int i = 0; i < 64; i++) d[i] = 0.f;
#pragma unroll 1
        for (int conv = 0; conv < 2; conv++) {
            fence_acc(d);
            mma_stages<0>(d, conv, tid, gs);
            if (conv == 0) {
                asm volatile("wgmma.fence.sync.aligned;" ::: "memory");
                wgmma128<(SM_ONES >> 4) | (8u << 16), (SM_EMB >> 4), 0, 8>(d);
                asm volatile("wgmma.commit_group.sync.aligned;" ::: "memory");
            }
            asm volatile("wgmma.wait_group.sync.aligned 0;" ::: "memory");
            fence_acc(d);
            if (tid == 0) TL(10 + conv * 8);
            if (conv == 1) break;

            uint32_t hp[32];
#pragma unroll
            for (int g = 0; g < 4; g++) {
                float c[4] = {0.f, 0.f, 0.f, 0.f};
#pragma unroll
                for (int i = 0; i < 8; i++) hp[8 * g + i] = pack_bf(d[16 * g + 2 * i], d[16 * g + 2 * i + 1]);
#pragma unroll
                for (int i = 0; i < 4; i++) stat_mma(c, hp[8 * g + 2 * i], hp[8 * g + 2 * i + 1]);
                stat_store(c, SM_RED + (g * 4 + wq) * 48, lane);
            }
            bar_sync(2, 128);
            if (wq == 0) stat_publish(SM_RED, &gs->acc[(NB + b) * 32], lane, true);
            if (tid == 0) TL(11);
            const uint32_t hbase = SM_ACT + (lane >> 4) * CH_PITCH + (2 + wq * 16 + (lane & 15)) * 16;
#pragma unroll
            for (int kc = 0; kc < 8; kc++) stsm4(hbase + kc * 2 * CH_PITCH, hp[4 * kc], hp[4 * kc + 1], hp[4 * kc + 2], hp[4 * kc + 3]);
            __syncwarp();
            if (lane == 0) mbar_arrive(BAR(BAR_HW));
            if (lane < LAG) mbar_arrive(BAR(BAR_WEMPTY + (NSTAGE - LAG) % NS) + 8 * lane);
            if (has_outer) {
                uint4* outbox = gs->box + (cta + ((r & 1) ? 1 : -1)) * 1024 + tid;
#pragma unroll
                for (int kc = 0; kc < 8; kc++) outbox[kc * 128] = make_uint4(~hp[4 * kc], ~hp[4 * kc + 1], ~hp[4 * kc + 2], ~hp[4 * kc + 3]);
            }
            if (tid == 0) TL(12);
            const uint32_t xbase = SM_XOWN + ((lane >> 4) * 8 + (lane & 7)) * 128 + (((2 * wq + ((lane >> 3) & 1)) ^ (lane & 7)) << 4);
#pragma unroll
            for (int kc = 0; kc < 8; kc++) {
                uint32_t p[4];
                ldsm4t(p, xbase + kc * 2048);
#pragma unroll
                for (int i = 0; i < 4; i++) { d[8 * kc + 2 * i] = bf_lo(p[i]); d[8 * kc + 2 * i + 1] = bf_hi(p[i]); }
            }
        }
        {
            const uint32_t obase = slot_addr(0) + ((lane >> 4) * 8 + (lane & 7)) * OUT_PITCH + (wq * 16 + ((lane >> 3) & 1) * 8) * 2;
#pragma unroll
            for (int kc = 0; kc < 8; kc++) {
                stsm4t(obase + kc * 16 * OUT_PITCH, pack_bf(d[8 * kc + 0], d[8 * kc + 1]), pack_bf(d[8 * kc + 2], d[8 * kc + 3]),
                       pack_bf(d[8 * kc + 4], d[8 * kc + 5]), pack_bf(d[8 * kc + 6], d[8 * kc + 7]));
            }
            bar_sync(2, 128);
            const int oc0 = tid >> 3;
            __nv_bfloat16* dst = out + ((size_t)(b * C + oc0) * HW + r) * HW + seg * 8;
#pragma unroll
            for (int i = 0; i < 8; i++)
                *reinterpret_cast<uint4*>(dst + (size_t)i * 16 * HW * HW) = lds128(slot_addr(0) + (oc0 + 16 * i) * OUT_PITCH + seg * 16);
            if (tid == 0) { TL(20); TLG(21); }
        }
    } else if (warp < 6) {
        bar_sync(5, 96);
        if (warp == 5) {
            asm volatile("barrier.cluster.wait.acquire.aligned;" ::: "memory");
            const uint32_t peer = (r & 1) ^ 1;
            const uint32_t self0 = mapa(0, r & 1), peer0 = mapa(0, peer);
#pragma unroll 1
            for (int conv = 0; conv < 2; conv++) {
#pragma unroll 1
                for (int kc = 0; kc < 8; kc++) {
                    mbar_wait(BAR(BAR_FULL) + 8 * kc, conv);
                    if (elect_one())
                        asm volatile("cp.async.bulk.shared::cluster.shared::cta.mbarrier::complete_tx::bytes [%0], [%1], %2, [%3];"
                                     ::"r"(peer0 + SM_ACT + ROW_BYTES + kc * KC_BYTES), "r"(self0 + SM_ACT + kc * KC_BYTES), "r"(KC_BYTES),
                                       "r"(peer0 + BAR(BAR_FULL + 8) + 8 * kc) : "memory");
                }
                if (lane == 0) TL(86 + conv);
#pragma unroll 1
                for (int kc = 0; kc < 8; kc++) mbar_wait(BAR(BAR_FULL + 8) + 8 * kc, conv);
                if (lane == 0)
                    asm volatile("mbarrier.arrive.release.cluster.shared::cluster.b64 _, [%0];" ::"r"(peer0 + (conv ? BAR(BAR_ACK) : BAR(BAR_EMB))) : "memory");
            }
            mbar_wait(BAR(BAR_ACK), 0);
        } else {
            while (clock32() - clk0 < W2DELAY) {}
            weight_load(v, w2, cta, lane);
            const uint2* wsrc = reinterpret_cast<const uint2*>(w_emb + (size_t)r * 12 * C) + lane;
            uint2 wv[12];
#pragma unroll
            for (int i = 0; i < 12; i++) wv[i] = __ldg(wsrc + i * (C / 4));
            float tv = 0.f;
            if (lane < 12) tv = __bfloat162float(t_emb[b * E + r * 12 + lane]);
            weight_block<false>(v, SM_BNC + 2304, gs->wt + NSTAGE * STAGE_BYTES, cta, lane);
            const float sv = silu_half(0.5f * tv);
            float e0 = 0.f, e1 = 0.f, e2 = 0.f, e3 = 0.f;
#pragma unroll
            for (int i = 0; i < 12; i++) {
                const float sx = __shfl_sync(0xffffffffu, sv, i);
                e0 = fmaf(sx, bf_lo(wv[i].x), e0); e1 = fmaf(sx, bf_hi(wv[i].x), e1);
                e2 = fmaf(sx, bf_lo(wv[i].y), e2); e3 = fmaf(sx, bf_hi(wv[i].y), e3);
            }
            if (r == 0 && lane < 16) gs->acc[(NB + b) * 32 + lane] = 0.f;
            red_add4(&gs->emb[b * C + lane * 4], e0, e1, e2, e3);
            __syncwarp();
            if (lane == 0) TL(13);
            if (lane < 2) asm volatile("red.release.gpu.global.add.u32 [%0], 1;" ::"l"(&gs->wcnt[(NB + lane) * 32]) : "memory");
            if (lane == 0) TL(14);
            unsigned it = 0;
            while (ld_relaxed(&gs->wcnt[(NB + b) * 32]) < (unsigned)NCTA && ++it < SPIN_LIMIT) {}
            fence_acquire();
            const uint4 ef = ld_relaxed_v4(&gs->emb[b * C + lane * 4]);
            const uint32_t eu[4] = {ef.x, ef.y, ef.z, ef.w};
#pragma unroll
            for (int i = 0; i < 4; i++) {
                const float e = __uint_as_float(eu[i]);
                const float hi = bf_lo(pack_bf(e, 0.f));
                sts128(SM_EMB + (lane * 4 + i) * 16, make_uint4(pack_bf(hi, e - hi), 0, 0, 0));
            }
            fence_async_smem();
            __syncwarp();
            if (lane == 0) { mbar_arrive(BAR(BAR_EMB)); TL(19); }
        }
    } else if (warp == 6) {
        bar_sync(0, 96);
        const uint32_t ebytes = STAGE_BYTES + ((lane >> 3) == 1 ? KC_BYTES : 0);
        if (lane < NSTAGE) mbar_expect(BAR(BAR_FULL) + 8 * lane, ebytes);
        const int swap = (r & 1) ? 0 : 8 * STAGE_BYTES;
        const unsigned char* wsrc = gs->wt;
        uint32_t dst = S0 + SM_W, full = S0 + BAR(BAR_FULL), empty = BAR(BAR_WEMPTY);
        unsigned it = 0;
        while (ld_relaxed(&gs->wcnt[b * 32]) < (unsigned)NCTA && ++it < SPIN_LIMIT) {}
        fence_acquire();
        fence_async_global();
        if (lane == 0) TL(6);
#pragma unroll 1
        for (int g = 0; g < 2 * NSTAGE; g++) {
            if (g >= NS) {
                mbar_wait(empty, ((g - NS) / NS) & 1);
                if (g == NSTAGE) { mbar_wait(BAR(BAR_EMB), 0); fence_async_global(); }
                if (g == NSTAGE || g == NSTAGE + NS) {
                    if (lane >= g - NSTAGE && lane < g - NSTAGE + NS) mbar_expect(BAR(BAR_FULL) + 8 * lane, ebytes);
                    __syncwarp();
                }
            }
            if (elect_one()) bulk_g2s(dst, wsrc, STAGE_BYTES, full);
            wsrc += STAGE_BYTES; dst += STAGE_BYTES; full += 8; empty += 8;
            const int st = (g >= NSTAGE ? g - NSTAGE : g) + 1;
            if (st == 8 || st == NSTAGE) wsrc += swap;
            if (st == 16) wsrc -= 2 * swap;
            if (st == NS || st == NSTAGE) { dst -= NS * STAGE_BYTES; empty -= 8 * NS; }
            if (st == NSTAGE) full -= 8 * NSTAGE;
        }
    } else {
        const uint2 ga1 = __ldg(reinterpret_cast<const uint2*>(g1) + lane), bt1 = __ldg(reinterpret_cast<const uint2*>(be1) + lane);
        const uint2 ga2 = __ldg(reinterpret_cast<const uint2*>(g2) + lane), bt2 = __ldg(reinterpret_cast<const uint2*>(be2) + lane);
        bar_sync(0, 96);
#pragma unroll 1
        for (int conv = 0; conv < 2; conv++) {
            if (conv == 1) mbar_wait(BAR(BAR_EMB), 0);
            const float* asrc = &gs->acc[(conv * NB + b) * 32 + (lane >> 3) * 4];
            const uint2 ga = conv ? ga2 : ga1, bt = conv ? bt2 : bt1;
            bool done = false;
            unsigned it = 0;
#pragma unroll 1
            while (true) {
                const uint4 f = ld_relaxed_v4(asrc);
                const bool fresh = !done && (((f.x == 0x42800000u) & (f.w == 0x42800000u)) || it > SPIN_LIMIT);
                it++;
                if (!__any_sync(0xffffffffu, fresh)) continue;
                if (lane == 0 && fresh) TL(7 + conv * 8);
                if (lane == 24 && fresh) TL(90 + conv);
                const float inv_n = 1.0f / (32.0f * HW * HW);
                const float mean = __uint_as_float(f.y) * inv_n;
                const float var = fmaxf(fmaf(-mean, mean, __uint_as_float(f.z) * inv_n), 0.f);
                const float rs = 0.5f * rsqrtf(var + 1e-5f);
                float4 k0, k1;
                k0.x = rs * bf_lo(ga.x); k0.y = rs * bf_hi(ga.x); k1.x = rs * bf_lo(ga.y); k1.y = rs * bf_hi(ga.y);
                k0.z = fmaf(-mean, k0.x, 0.5f * bf_lo(bt.x)); k0.w = fmaf(-mean, k0.y, 0.5f * bf_hi(bt.x));
                k1.z = fmaf(-mean, k1.x, 0.5f * bf_lo(bt.y)); k1.w = fmaf(-mean, k1.y, 0.5f * bf_hi(bt.y));
                if (fresh) {
                    sts128f(SM_COEF + lane * 32, k0);
                    sts128f(SM_COEF + lane * 32 + 16, k1);
                }
                __syncwarp();
                if (fresh && (lane & 7) == 0) mbar_arrive(BAR(BAR_STATS) + lane);
                done = done || fresh;
                if (__all_sync(0xffffffffu, done)) break;
            }
        }
        if (r == 0) {
            if (lane < 16) gs->acc[b * 32 + lane] = 0.f;
            if (lane < 2) gs->wcnt[(lane * NB + b) * 32] = 0;
            *reinterpret_cast<float4*>(&gs->emb[b * C + lane * 4]) = make_float4(0.f, 0.f, 0.f, 0.f);
        }
    }
}

}

extern "C" void kernel_launch(void* const* d_in, const int* in_sizes, int n_in, void* d_out, int out_size) {
    (void)in_sizes; (void)n_in; (void)out_size;
    typedef CUresult (*EncodeFn)(CUtensorMap*, CUtensorMapDataType, cuuint32_t, void*, const cuuint64_t*, const cuuint64_t*,
                                 const cuuint32_t*, const cuuint32_t*, CUtensorMapInterleave, CUtensorMapSwizzle,
                                 CUtensorMapL2promotion, CUtensorMapFloatOOBfill);
    static Scratch* gs = nullptr;
    static EncodeFn encode = nullptr;
    if (!gs) {
        cudaFuncSetAttribute(resblock_kernel, cudaFuncAttributeMaxDynamicSharedMemorySize, SM_TOTAL);
        cudaGetSymbolAddress((void**)&gs, g_scratch);
        cudaDriverEntryPointQueryResult qr;
        cudaGetDriverEntryPoint("cuTensorMapEncodeTiled", (void**)&encode, cudaEnableDefault, &qr);
    }
    CUtensorMap xmap;
    const cuuint64_t dims[3] = {HW, HW, NB * C}, strides[2] = {HW * 2, HW * HW * 2};
    const cuuint32_t box[3] = {HW, 1, 32}, es[3] = {1, 1, 1};
    encode(&xmap, CU_TENSOR_MAP_DATA_TYPE_BFLOAT16, 3, d_in[0], dims, strides, box, es, CU_TENSOR_MAP_INTERLEAVE_NONE,
           CU_TENSOR_MAP_SWIZZLE_128B, CU_TENSOR_MAP_L2_PROMOTION_NONE, CU_TENSOR_MAP_FLOAT_OOB_FILL_NONE);
    resblock_kernel<<<NCTA, NTHREADS, SM_TOTAL>>>(
        (const __nv_bfloat16*)d_in[4], (const __nv_bfloat16*)d_in[1],
        (const __nv_bfloat16*)d_in[2], (const __nv_bfloat16*)d_in[3], (const __nv_bfloat16*)d_in[5],
        (const __nv_bfloat16*)d_in[6], (const __nv_bfloat16*)d_in[7], (const __nv_bfloat16*)d_in[8],
        (__nv_bfloat16*)d_out, gs, xmap);
}
```

```cpp
#include <cuda_runtime.h>
#include <cuda.h>
#include <cuda_bf16.h>
#include <stdint.h>

namespace {

constexpr int C = 128, HW = 64, NB = 2, E = 768;
constexpr int NCTA = NB * HW;
constexpr int NTHREADS = 16 * 32;
constexpr int CH_PITCH = 66 * 16;
constexpr int ROW_BYTES = 16 * CH_PITCH;
constexpr int STEP_BYTES = 4096;
constexpr int STAGE_BYTES = 3 * STEP_BYTES;
constexpr int NSTAGE = 24;
constexpr int KC_BYTES = 2 * CH_PITCH;
constexpr int NS = 12;
constexpr int LAG = 1;
#define XDELAY 500
#define HDELAY 600
#define NA 2
#define RB 1
#define XSTAG 400
#define HSEND 0
#define W2DELAY 2200

constexpr uint32_t SMEM_BASE = 0x400;
constexpr uint32_t SM_XOWN = SMEM_BASE;
constexpr uint32_t SM_ACT = SM_XOWN + 16384 + 512;
constexpr uint32_t SM_XOUT = SM_ACT + 2 * ROW_BYTES + 512;
static_assert(SM_XOUT % 1024 == 0, "swizzle atom alignment");
constexpr uint32_t SM_W = SM_ACT + 3 * ROW_BYTES + 128;
__host__ __device__ constexpr uint32_t slot_addr(int slot) { return SM_W + slot * STAGE_BYTES; }
constexpr uint32_t SM_COEF = SM_W + NS * STAGE_BYTES;
constexpr uint32_t SM_EMB = SM_COEF + 1024;
constexpr uint32_t SM_ONES = SM_EMB + 2048;
constexpr uint32_t SM_RED = SM_ONES + 256;
constexpr uint32_t SM_BNC = SM_RED + 1280;
constexpr uint32_t SM_BAR = SM_BNC + 2 * 2304;
constexpr int BAR_FULL = 0, BAR_WEMPTY = NSTAGE, BAR_HW = BAR_WEMPTY + NS, BAR_STATS = BAR_HW + 1  ,
              BAR_EMB = BAR_STATS + 4, BAR_ACK = BAR_EMB + 1, BAR_X = BAR_ACK + 1  , NBAR = BAR_X + 5;
constexpr int SM_TOTAL = SM_BAR + NBAR * 8 - SMEM_BASE;
static_assert(SM_TOTAL <= 232448, "smem");
static_assert(NBAR <= 96, "barrier init");
constexpr int OUT_PITCH = 144;
__host__ __device__ constexpr uint32_t BAR(int i) { return SM_BAR + 8 * i; }
__host__ __device__ constexpr int ky_of(int kyo) { return kyo == 0 ? 1 : (kyo == 1 ? 0 : 2); }

constexpr unsigned SPIN_LIMIT = 1u << 16;

struct Scratch {
    float acc[2 * NB * 32];
    unsigned wcnt[2 * NB * 32];
    float emb[NB * C * 2];
    unsigned char wt[2 * NSTAGE * STAGE_BYTES];
    uint4 box[NCTA * 1024];
};
__device__ __align__(1024) Scratch g_scratch;
#define TL(i) do {} while (0)
#define TLG(i) do {} while (0)

__device__ __forceinline__ unsigned clock32() { unsigned c; asm volatile("mov.u32 %0, %%clock;" : "=r"(c)); return c; }
__device__ __forceinline__ uint32_t mapa(uint32_t a, uint32_t rank) {
    uint32_t d;
    asm("mapa.shared::cluster.u32 %0, %1, %2;" : "=r"(d) : "r"(a), "r"(rank));
    return d;
}
#define S0 mapa(0, blockIdx.x & 1)
__device__ __forceinline__ void mbar_init(uint32_t bar, int cnt) {
    asm volatile("mbarrier.init.shared::cta.b64 [%0], %1;" ::"r"(bar + S0), "r"(cnt) : "memory");
}
__device__ __forceinline__ void mbar_arrive(uint32_t bar) {
    asm volatile("mbarrier.arrive.shared::cta.b64 _, [%0];" ::"r"(bar + S0) : "memory");
}
__device__ __forceinline__ void mbar_expect(uint32_t bar, uint32_t bytes) {
    asm volatile("mbarrier.arrive.expect_tx.shared::cta.b64 _, [%0], %1;" ::"r"(bar + S0), "r"(bytes) : "memory");
}
__device__ __forceinline__ bool mbar_try(uint32_t bar, uint32_t par) {
    uint32_t ok;
    asm volatile("{\n.reg .pred p;\nmbarrier.try_wait.parity.shared::cta.b64 p, [%1], %2;\nselp.u32 %0, 1, 0, p;\n}"
                 : "=r"(ok) : "r"(bar + S0), "r"(par) : "memory");
    return ok;
}
__device__ __forceinline__ bool mbar_test(uint32_t bar, uint32_t par) {
    uint32_t ok;
    asm volatile("{\n.reg .pred p;\nmbarrier.test_wait.parity.shared::cta.b64 p, [%1], %2;\nselp.u32 %0, 1, 0, p;\n}"
                 : "=r"(ok) : "r"(bar + S0), "r"(par) : "memory");
    return ok;
}
__device__ __forceinline__ void mbar_wait(uint32_t bar, uint32_t par) {
    unsigned it = 0;
#pragma unroll 1
    while (!mbar_try(bar, par) && ++it < SPIN_LIMIT) {}
}
__device__ __forceinline__ bool elect_one() {
    uint32_t p;
    asm volatile("{\n.reg .pred p;\nelect.sync _|p, 0xffffffff;\nselp.u32 %0, 1, 0, p;\n}" : "=r"(p));
    return p;
}
__device__ __forceinline__ void fence_async_smem() { asm volatile("fence.proxy.async.shared::cta;" ::: "memory"); }
__device__ __forceinline__ void fence_async_global() { asm volatile("fence.proxy.async.global;" ::: "memory"); }
__device__ __forceinline__ void fence_acquire() { asm volatile("fence.acquire.gpu;" ::: "memory"); }
__device__ __forceinline__ void bar_sync(int id, int n) { asm volatile("bar.sync %0, %1;" ::"r"(id), "r"(n) : "memory"); }
__device__ __forceinline__ void bar_arrive(int id, int n) { asm volatile("bar.arrive %0, %1;" ::"r"(id), "r"(n) : "memory"); }
__device__ __forceinline__ void bulk_g2s(uint32_t dst, const void* src, uint32_t bytes, uint32_t bar) {
    asm volatile("cp.async.bulk.shared::cluster.global.mbarrier::complete_tx::bytes [%0], [%1], %2, [%3];"
                 ::"r"(dst), "l"(src), "r"(bytes), "r"(bar) : "memory");
}
__device__ __forceinline__ void tma_x(uint32_t dst, const CUtensorMap* tm, int row, int ch, uint32_t bar) {
    asm volatile("cp.async.bulk.tensor.3d.shared::cluster.global.mbarrier::complete_tx::bytes [%0], [%1, {%2, %3, %4}], [%5];"
                 ::"r"(dst + S0), "l"(tm), "r"(0), "r"(row), "r"(ch), "r"(bar + S0) : "memory");
}
__device__ __forceinline__ uint4 ld_relaxed_v4(const void* p) {
    uint4 v;
    asm volatile("ld.relaxed.gpu.global.v4.u32 {%0,%1,%2,%3}, [%4];" : "=r"(v.x), "=r"(v.y), "=r"(v.z), "=r"(v.w) : "l"(p) : "memory");
    return v;
}
__device__ __forceinline__ unsigned ld_relaxed(const void* p) {
    unsigned v;
    asm volatile("ld.relaxed.gpu.global.u32 %0, [%1];" : "=r"(v) : "l"(p) : "memory");
    return v;
}
__device__ __forceinline__ void red_add4(float* p, float a, float b, float c, float d) {
    asm volatile("red.relaxed.gpu.global.add.v4.f32 [%0], {%1,%2,%3,%4};" ::"l"(p), "f"(a), "f"(b), "f"(c), "f"(d) : "memory");
}
__device__ __forceinline__ void sts128(uint32_t a, uint4 v) {
    asm volatile("st.shared.v4.u32 [%0], {%1,%2,%3,%4};" ::"r"(a + S0), "r"(v.x), "r"(v.y), "r"(v.z), "r"(v.w) : "memory");
}
__device__ __forceinline__ void sts128f(uint32_t a, float4 v) {
    asm volatile("st.shared.v4.f32 [%0], {%1,%2,%3,%4};" ::"r"(a + S0), "f"(v.x), "f"(v.y), "f"(v.z), "f"(v.w) : "memory");
}
__device__ __forceinline__ void sts32f(uint32_t a, float v) { asm volatile("st.shared.f32 [%0], %1;" ::"r"(a + S0), "f"(v) : "memory"); }
__device__ __forceinline__ uint4 lds128(uint32_t a) {
    uint4 v;
    asm volatile("ld.shared.v4.u32 {%0,%1,%2,%3}, [%4];" : "=r"(v.x), "=r"(v.y), "=r"(v.z), "=r"(v.w) : "r"(a + S0) : "memory");
    return v;
}
__device__ __forceinline__ float4 lds128f(uint32_t a) {
    float4 v;
    asm volatile("ld.shared.v4.f32 {%0,%1,%2,%3}, [%4];" : "=f"(v.x), "=f"(v.y), "=f"(v.z), "=f"(v.w) : "r"(a + S0) : "memory");
    return v;
}
__device__ __forceinline__ float2 lds64f(uint32_t a) {
    float2 v;
    asm volatile("ld.shared.v2.f32 {%0,%1}, [%2];" : "=f"(v.x), "=f"(v.y) : "r"(a + S0) : "memory");
    return v;
}
__device__ __forceinline__ float bf_lo(uint32_t u) { return __uint_as_float(u << 16); }
__device__ __forceinline__ float bf_hi(uint32_t u) { return __uint_as_float(u & 0xffff0000u); }
__device__ __forceinline__ uint32_t pack_bf(float lo, float hi) {
    uint32_t r;
    asm("cvt.rn.bf16x2.f32 %0, %1, %2;" : "=r"(r) : "f"(hi), "f"(lo));
    return r;
}
__device__ __forceinline__ float tanh_fast(float x) {
    float r;
    asm("tanh.approx.f32 %0, %1;" : "=f"(r) : "f"(x));
    return r;
}
__device__ __forceinline__ float silu_half(float h) { return fmaf(h, tanh_fast(h), h); }
__device__ __forceinline__ void ldsm4(uint32_t (&u)[4], uint32_t a) {
    asm volatile("ldmatrix.sync.aligned.m8n8.x4.shared.b16 {%0,%1,%2,%3}, [%4];"
                 : "=r"(u[0]), "=r"(u[1]), "=r"(u[2]), "=r"(u[3]) : "r"(a + S0) : "memory");
}
__device__ __forceinline__ void ldsm4t(uint32_t (&u)[4], uint32_t a) {
    asm volatile("ldmatrix.sync.aligned.m8n8.x4.trans.shared.b16 {%0,%1,%2,%3}, [%4];"
                 : "=r"(u[0]), "=r"(u[1]), "=r"(u[2]), "=r"(u[3]) : "r"(a + S0) : "memory");
}
__device__ __forceinline__ void stsm4(uint32_t a, uint32_t p0, uint32_t p1, uint32_t p2, uint32_t p3) {
    asm volatile("stmatrix.sync.aligned.m8n8.x4.shared.b16 [%0], {%1,%2,%3,%4};" ::"r"(a + S0), "r"(p0), "r"(p1), "r"(p2), "r"(p3) : "memory");
}
__device__ __forceinline__ void stsm4t(uint32_t a, uint32_t p0, uint32_t p1, uint32_t p2, uint32_t p3) {
    asm volatile("stmatrix.sync.aligned.m8n8.x4.trans.shared.b16 [%0], {%1,%2,%3,%4};" ::"r"(a + S0), "r"(p0), "r"(p1), "r"(p2), "r"(p3) : "memory");
}

#define R8(o) "+f"(d[o]), "+f"(d[o + 1]), "+f"(d[o + 2]), "+f"(d[o + 3]), "+f"(d[o + 4]), "+f"(d[o + 5]), "+f"(d[o + 6]), "+f"(d[o + 7])
template <uint32_t ALO, uint32_t BLO, uint64_t AHI = 8, uint64_t BHI = 48>
__device__ __forceinline__ void wgmma128(float (&d)[64]) {
    asm volatile(
        "wgmma.mma_async.sync.aligned.m64n128k16.f32.bf16.bf16 "
        "{%0,%1,%2,%3,%4,%5,%6,%7,%8,%9,%10,%11,%12,%13,%14,%15,%16,%17,%18,%19,%20,%21,%22,%23,%24,%25,%26,%27,%28,%29,%30,%31,"
        "%32,%33,%34,%35,%36,%37,%38,%39,%40,%41,%42,%43,%44,%45,%46,%47,%48,%49,%50,%51,%52,%53,%54,%55,%56,%57,%58,%59,%60,%61,%62,%63},"
        " %64, %65, 1, 1, 1, 0, 0;"
        : R8(0), R8(8), R8(16), R8(24), R8(32), R8(40), R8(48), R8(56)
        : "l"((AHI << 32) | ALO), "l"((BHI << 32) | BLO));
}
template <int S>
__device__ __forceinline__ void mma_stages(float (&d)[64], int conv, int tid, Scratch* gs) {
    constexpr uint32_t A = ((SM_ACT + S * 2 * CH_PITCH + 16) >> 4) | ((CH_PITCH >> 4) << 16);
    constexpr uint32_t B = (slot_addr(S % NS) >> 4) | (8u << 16);
    if (S == 0) mbar_wait(BAR(BAR_FULL), conv);
    bool next_ok = true;
    constexpr uint32_t NEXT = S + 1 < NSTAGE ? BAR(BAR_FULL + S + 1) : BAR(BAR_EMB);
    const int npar = S + 1 < NSTAGE ? conv : 0;
    next_ok = mbar_test(NEXT, npar);
    if (S == 0 && tid == 0) TL(32 + conv * 24);
    asm volatile("wgmma.fence.sync.aligned;" ::: "memory");
    wgmma128<A, B>(d);
    wgmma128<A + 1, B + 16>(d);
    wgmma128<A + 2, B + 32>(d);
    asm volatile("wgmma.commit_group.sync.aligned;" ::: "memory");
    if (S >= LAG) {
        asm volatile("wgmma.wait_group.sync.aligned %0;" ::"n"(LAG) : "memory");
        if ((tid & 31) == 0) mbar_arrive(BAR(BAR_WEMPTY + (S + NS - LAG) % NS));
    }
    if (!next_ok) mbar_wait(NEXT, npar);
    if constexpr (S + 1 < NSTAGE) mma_stages<S + 1>(d, conv, tid, gs);
}

__device__ __forceinline__ void weight_load(uint4 (&t)[5], const __nv_bfloat16* w, int cta, int lane) {
    const char* base = reinterpret_cast<const char*>(w) + ((cta & 15) * 8 * C + (cta >> 4) * 16) * 18;
#pragma unroll
    for (int k = 0; k < 5; k++) {
        const int i = lane + 32 * k, row = (i * 57) >> 10;
        if (k < 4 || lane < 16) t[k] = __ldg(reinterpret_cast<const uint4*>(base + row * (C * 18 - 288) + i * 16));
    }
}
template <bool READBACK>
__device__ __forceinline__ void weight_block(const uint4 (&t)[5], uint32_t bounce, unsigned char* wt, int cta, int lane) {
#pragma unroll
    for (int k = 0; k < 5; k++)
        if (k < 4 || lane < 16) sts128(bounce + (lane + 32 * k) * 16, t[k]);
    __syncwarp();
    unsigned char* dst = wt + (cta >> 4) * STAGE_BYTES + (cta & 15) * 768;
    if (lane < 16) {
        uint32_t v[36];
#pragma unroll
        for (int i = 0; i < 9; i++) {
            const uint4 q = lds128(bounce + (lane & 7) * 288 + (lane >> 3) * 144 + i * 16);
            v[4 * i] = q.x; v[4 * i + 1] = q.y; v[4 * i + 2] = q.z; v[4 * i + 3] = q.w;
        }
#pragma unroll
        for (int kyo = 0; kyo < 3; kyo++) {
#pragma unroll
            for (int kx = 0; kx < 3; kx++) {
                const int tap = ky_of(kyo) * 3 + kx;
                uint32_t o[4];
#pragma unroll
                for (int m = 0; m < 4; m++) {
                    const int i0 = 18 * m + tap, i1 = i0 + 9;
                    const uint32_t sel = ((i0 & 1) ? 0x32u : 0x10u) | ((i1 & 1) ? 0x7600u : 0x5400u);
                    o[m] = __byte_perm(v[i0 >> 1], v[i1 >> 1], sel);
                }
                *reinterpret_cast<uint4*>(dst + kyo * 8 * STAGE_BYTES + kx * 256 + lane * 16) = make_uint4(o[0], o[1], o[2], o[3]);
            }
        }
    }
    if (READBACK) {
        __syncwarp();
        unsigned acc = 0;
        if (lane < 24) {
#pragma unroll
            for (int i = 0; i < 3; i++) acc |= ld_relaxed(dst + i * 8 * STAGE_BYTES + lane * 32);
        }
        asm volatile("{\n.reg .pred p;\nsetp.eq.u32 p, %0, 0x9e3779b9;\n@p st.shared.u32 [%1], %0;\n}" ::"r"(acc), "r"(bounce + S0) : "memory");
    }
}
__device__ __forceinline__ uint32_t act2(uint32_t u, const float4& cf) {
    return pack_bf(silu_half(fmaf(bf_lo(u), cf.x, cf.z)), silu_half(fmaf(bf_hi(u), cf.y, cf.w)));
}
__device__ __forceinline__ void norm_unit(uint32_t (&u)[4], const float4& ca, const float4& cb) {
    u[0] = act2(u[0], ca); u[1] = act2(u[1], ca); u[2] = act2(u[2], cb); u[3] = act2(u[3], cb);
}
template <int FIRST, int N>
__device__ __forceinline__ void norm_block(uint32_t (&u)[4][4], float4 (&cf)[8], bool load_cf, uint32_t cfa, uint32_t act, uint32_t mask, uint32_t fbar, int lane) {
    if (load_cf) {
#pragma unroll
        for (int i = 2 * FIRST; i < 2 * (FIRST + N); i++) cf[i] = lds128f(cfa + (i >> 1) * 256 + (i & 1) * 64);
    }
#pragma unroll
    for (int t = FIRST; t < FIRST + N; t++) {
        norm_unit(u[t], cf[2 * t], cf[2 * t + 1]);
        stsm4(act + t * 2 * KC_BYTES, u[t][0] & mask, u[t][1] & mask, u[t][2] & mask, u[t][3] & mask);
    }
    fence_async_smem();
    __syncwarp();
    if (lane < N) mbar_arrive(fbar + 16 * (FIRST + lane));
}
__device__ __forceinline__ void stat_mma(float (&c)[4], uint32_t p, uint32_t q) {
    asm("mma.sync.aligned.m16n8k16.row.col.f32.bf16.bf16.f32 {%0,%1,%2,%3}, {%4,%5,%6,%5}, {%4,%6}, {%0,%1,%2,%3};"
        : "+f"(c[0]), "+f"(c[1]), "+f"(c[2]), "+f"(c[3]) : "r"(p), "r"(0x3f803f80u), "r"(q));
}
__device__ __forceinline__ void stat_store(const float (&c)[4], uint32_t dst, int lane) {
    const int g = lane >> 2, t = lane & 3;
    if (t == (g >> 1)) sts32f(dst + g * 4, (g & 1) ? c[1] : c[0]);
    if (g == 7) sts32f(dst + 32 + t * 4, c[2] + c[3]);
}
__device__ __forceinline__ float sum4(float4 v) { return (v.x + v.y) + (v.z + v.w); }
__device__ __forceinline__ void stat_publish(uint32_t src, float* acc, int lane, bool real) {
    const uint32_t a = src + (lane & 15) * 48;
    float q = sum4(lds128f(a)) + sum4(lds128f(a + 16)), sm = sum4(lds128f(a + 32));
    q += __shfl_xor_sync(0xffffffffu, q, 1); sm += __shfl_xor_sync(0xffffffffu, sm, 1);
    q += __shfl_xor_sync(0xffffffffu, q, 2); sm += __shfl_xor_sync(0xffffffffu, sm, 2);
    if (real && (lane & 19) == 0) red_add4(acc + lane, 1.f, sm, q, 1.f);
}
__device__ __forceinline__ void fence_acc(float (&d)[64]) {
#pragma unroll
    for (int i = 0; i < 64; i++) asm volatile("" : "+f"(d[i])::"memory");
}
__device__ __forceinline__ void ld_unit(uint32_t (&u)[4], const uint4* p) {
    asm volatile("ld.relaxed.gpu.global.v4.u32 {%0,%1,%2,%3}, [%4];" : "=r"(u[0]), "=r"(u[1]), "=r"(u[2]), "=r"(u[3]) : "l"(p) : "memory");
}

__global__ void __cluster_dims__(2, 1, 1) __launch_bounds__(NTHREADS, 1)
resblock_kernel(const __nv_bfloat16* __restrict__ w1,
                const __nv_bfloat16* __restrict__ t_emb, const __nv_bfloat16* __restrict__ g1,
                const __nv_bfloat16* __restrict__ be1, const __nv_bfloat16* __restrict__ w_emb,
                const __nv_bfloat16* __restrict__ g2, const __nv_bfloat16* __restrict__ be2,
                const __nv_bfloat16* __restrict__ w2, __nv_bfloat16* __restrict__ out, Scratch* __restrict__ gs,
                const __grid_constant__ CUtensorMap xmap) {
    const unsigned clk0 = clock32();
    if (threadIdx.x == 480) TLG(1);
    const int tid = threadIdx.x, warp = __shfl_sync(0xffffffffu, tid >> 5, 0), lane = tid & 31;
    const int cta = blockIdx.x, b = cta >> 6, r = cta & 63;

    const int seg = lane & 7;
    uint4 v[5];
    if (warp == 0) {
        weight_load(v, w1, cta, lane);
    }
    if (warp != 3) asm volatile("barrier.cluster.arrive.relaxed.aligned;" ::: "memory");
    const bool has_outer = (r != 0) && (r != HW - 1);
    float tv = 0.f;
    if (warp == 4 && lane < 12) tv = __bfloat162float(t_emb[b * E + r * 12 + lane]);
    if (warp == 1 || warp == 2 || warp == 4 || warp == 5) {
        const int g = warp < 3 ? warp - 1 : 7 - warp;
        if (elect_one()) {
            asm volatile("prefetch.tensormap [%0];" ::"l"(&xmap) : "memory");
            mbar_init(BAR(BAR_X) + 8 * g, 1);
            if (g == 3) mbar_init(BAR(BAR_X + 4), 1);
            mbar_expect(BAR(BAR_X) + 8 * g, 4096);
            fence_async_smem();
            while (clock32() - clk0 < XDELAY + g * XSTAG) {}
            tma_x(SM_XOWN + g * 4096, &xmap, r, b * C + g * 32, BAR(BAR_X) + 8 * g);
            if (g == 3 && has_outer) {
                mbar_expect(BAR(BAR_X + 4), 16384);
#pragma unroll
                for (int i = 0; i < 4; i++) tma_x(SM_XOUT + i * 4096, &xmap, r + ((r & 1) ? 1 : -1), b * C + i * 32, BAR(BAR_X + 4));
            }
            if (g == 3) {
                while (clock32() - clk0 < W2DELAY) {}
                asm volatile("cp.async.bulk.prefetch.L2.global [%0], 2304;" ::"l"(reinterpret_cast<const char*>(w2) + cta * 2304) : "memory");
                asm volatile("cp.async.bulk.prefetch.L2.global [%0], 1536;" ::"l"(reinterpret_cast<const char*>(w_emb) + cta * 1536) : "memory");
            }
        }
        __syncwarp();
        bar_arrive(4, 256 + 32 + 128);
        mbar_wait(BAR(BAR_X) + 8 * g, 0);
        if (lane == 0) TL(70 + g);
        float c[2][4] = {{0.f, 0.f, 0.f, 0.f}, {0.f, 0.f, 0.f, 0.f}};
#pragma unroll
        for (int k = 0; k < 8; k++) {
            const uint4 q = lds128(SM_XOWN + g * 4096 + k * 512 + lane * 16);
            stat_mma(c[0], q.x, q.y); stat_mma(c[1], q.z, q.w);
        }
#pragma unroll
        for (int i = 0; i < 4; i++) c[0][i] += c[1][i];
        stat_store(c[0], SM_RED + g * 48, lane);
        __syncwarp();
        if (lane == 0) {
            const uint32_t a = SM_RED + g * 48;
            red_add4(&gs->acc[b * 32 + g * 4], 1.f, sum4(lds128f(a + 32)), sum4(lds128f(a)) + sum4(lds128f(a + 16)), 1.f);
            TL(74 + g);
        }
    }
    if (warp == 0) {
        weight_block<RB>(v, SM_BNC, gs->wt, cta, lane);
        __syncwarp();
        if (lane == 0) TL(4);
        if (lane < 2) asm volatile("red.relaxed.gpu.global.add.u32 [%0], 1;" ::"l"(&gs->wcnt[lane * 32]) : "memory");
        if (lane == 0) TL(5);
    }

    if (warp >= 8) {
        const int nw = warp - 8;
        bar_sync(4, 256 + 32 + 128);
        const int par = nw >> 2, wq = nw & 3;
        const uint32_t act_off = SM_ACT + (par * 2 + (lane >> 4)) * CH_PITCH + (2 + wq * 16 + (lane & 15)) * 16;
        const uint32_t stg_off = (par * 16 + (lane >> 4) * 8 + (lane & 7)) * 128 + (((2 * wq + ((lane >> 3) & 1)) ^ (lane & 7)) << 4);
        const uint32_t cfa = SM_COEF + par * 128 + (lane & 3) * 16;
        const uint32_t fbar = BAR(BAR_FULL) + 8 * par;
        uint4* inbox = gs->box + cta * 1024 + nw * 32 + lane;
#pragma unroll 1
        for (int conv = 0; conv < 2; conv++) {
            uint32_t u[4][4], w[4][4];
            float4 cf[8];
            if (conv == 0) {
                mbar_wait(BAR(BAR_X), 0); ldsm4t(u[0], SM_XOWN + stg_off);
                mbar_wait(BAR(BAR_X + 1), 0); ldsm4t(u[1], SM_XOWN + stg_off + 4096);
                mbar_wait(BAR(BAR_STATS), 0);
                if (tid == 256) TL(22);
                norm_block<0, 1>(u, cf, true, cfa, act_off, ~0u, fbar, lane);
                if (tid == 256) TL(8);
                mbar_wait(BAR(BAR_X + 2), 0); ldsm4t(u[2], SM_XOWN + stg_off + 8192);
                mbar_wait(BAR(BAR_STATS + 1), 0);
                norm_block<1, 1>(u, cf, true, cfa, act_off, ~0u, fbar, lane);
                mbar_wait(BAR(BAR_X + 3), 0); ldsm4t(u[3], SM_XOWN + stg_off + 12288);
                mbar_wait(BAR(BAR_STATS + 2), 0);
                norm_block<2, 1>(u, cf, true, cfa, act_off, ~0u, fbar, lane);
                mbar_wait(BAR(BAR_STATS + 3), 0);
                norm_block<3, 1>(u, cf, true, cfa, act_off, ~0u, fbar, lane);
                if (has_outer) {
                    mbar_wait(BAR(BAR_X + 4), 0);
#pragma unroll
                    for (int i = 0; i < 4; i++) ldsm4t(w[i], SM_XOUT + stg_off + i * 4096);
                }
                bar_sync(3, 256);
                if (nw == 0) sts128(SM_ACT + 2 * ROW_BYTES + (lane >> 1) * CH_PITCH + (lane & 1) * 16, make_uint4(0, 0, 0, 0));
            } else {
                mbar_wait(BAR(BAR_HW), 0);
#pragma unroll
                for (int i = 0; i < 4; i++) ldsm4(u[i], act_off + i * 2 * KC_BYTES);
                mbar_wait(BAR(BAR_STATS + 1), 1);
                mbar_wait(BAR(BAR_STATS), 1);
                if (tid == 256) TL(26);
                norm_block<0, 2>(u, cf, true, cfa, act_off, ~0u, fbar, lane);
                if (tid == 256) TL(16);
                mbar_wait(BAR(BAR_STATS + 2), 1);
                mbar_wait(BAR(BAR_STATS + 3), 1);
                norm_block<2, 2>(u, cf, true, cfa, act_off, ~0u, fbar, lane);
            }
            if (tid == 256) TL(84 + conv);
            if (conv == 1 && has_outer) {
                unsigned it = 0;
                while (ld_relaxed(inbox + 3 * 256 + 31 - lane) == 0 && ++it < SPIN_LIMIT) {}
                if (tid == 256) TL(89);
                while (true) {
#pragma unroll
                    for (int i = 0; i < 4; i++) ld_unit(w[i], inbox + i * 256);
                    bool ok = true;
#pragma unroll
                    for (int i = 0; i < 16; i++) ok = ok && w[i >> 2][i & 3] != 0;
                    if (__all_sync(0xffffffffu, ok) || ++it > SPIN_LIMIT) break;
                }
#pragma unroll
                for (int i = 0; i < 16; i++) w[i >> 2][i & 3] = ~w[i >> 2][i & 3];
            }
            if (tid == 256) TL(24 + conv * 4);
            norm_block<0, 4>(w, cf, false, cfa, act_off + 2 * ROW_BYTES, has_outer ? ~0u : 0u, fbar + 128, lane);
            if (tid == 256) TL(23 + conv * 4);
        }
        if (has_outer) {
            mbar_wait(BAR(BAR_FULL + NSTAGE - 1), 1);
#pragma unroll
            for (int i = 0; i < 4; i++) inbox[i * 256] = make_uint4(0, 0, 0, 0);
        }
    } else if (warp < 4) {
        const int wq = warp;
        if (wq == 3) {
            if (elect_one()) {
#pragma unroll
                for (int i = 0; i < NSTAGE; i++) mbar_init(BAR(BAR_FULL + i), (i >> 3) == 1 ? 1 : 5);
#pragma unroll
                for (int i = 0; i <= NS; i++) mbar_init(BAR(BAR_WEMPTY + i), 4);
#pragma unroll
                for (int i = BAR_STATS; i < BAR_X; i++) mbar_init(BAR(i), i == BAR_EMB ? 2 : 1);
                asm volatile("fence.mbarrier_init.release.cluster;" ::: "memory");
            }
            __syncwarp();
            fence_async_smem();
            bar_arrive(0, 96);
            bar_arrive(5, 96);
            bar_arrive(4, 256 + 32 + 128);
            const uint4 z = make_uint4(0, 0, 0, 0);
#pragma unroll
            for (int i = 0; i < 2; i++) sts128(SM_ACT + (i * 16 + (lane >> 1)) * CH_PITCH + (lane & 1) * 16, z);
            if (lane < 4) sts128(SM_ACT + (2 + (lane >> 1)) * ROW_BYTES + (lane & 1) * 16, z);
            if (lane < 16) sts128(SM_ONES + lane * 16, make_uint4(lane < 8 ? 0x3f803f80u : 0u, 0, 0, 0));
            fence_async_smem();
            asm volatile("barrier.cluster.arrive.release.aligned;" ::: "memory");
        }
        bar_sync(2, 128);

        float d[64];
#pragma unroll
        for (int i = 0; i < 64; i++) d[i] = 0.f;
#pragma unroll 1
        for (int conv = 0; conv < 2; conv++) {
            fence_acc(d);
            mma_stages<0>(d, conv, tid, gs);
            if (conv == 0) {
                asm volatile("wgmma.fence.sync.aligned;" ::: "memory");
                wgmma128<(SM_ONES >> 4) | (8u << 16), (SM_EMB >> 4), 0, 8>(d);
                asm volatile("wgmma.commit_group.sync.aligned;" ::: "memory");
            }
            asm volatile("wgmma.wait_group.sync.aligned 0;" ::: "memory");
            fence_acc(d);
            if (tid == 0) TL(10 + conv * 8);
            if (conv == 1) break;

            uint32_t hp[32];
#pragma unroll
            for (int g = 0; g < 4; g++) {
                float c[4] = {0.f, 0.f, 0.f, 0.f};
#pragma unroll
                for (int i = 0; i < 8; i++) hp[8 * g + i] = pack_bf(d[16 * g + 2 * i], d[16 * g + 2 * i + 1]);
#pragma unroll
                for (int i = 0; i < 4; i++) stat_mma(c, hp[8 * g + 2 * i], hp[8 * g + 2 * i + 1]);
                stat_store(c, SM_RED + (g * 4 + wq) * 48, lane);
            }
            bar_sync(2, 128);
            if (wq == 0) stat_publish(SM_RED, &gs->acc[(NB + b) * 32], lane, true);
            if (tid == 0) TL(11);
            const uint32_t hbase = SM_ACT + (lane >> 4) * CH_PITCH + (2 + wq * 16 + (lane & 15)) * 16;
#pragma unroll
            for (int kc = 0; kc < 8; kc++) stsm4(hbase + kc * 2 * CH_PITCH, hp[4 * kc], hp[4 * kc + 1], hp[4 * kc + 2], hp[4 * kc + 3]);
            __syncwarp();
            if (lane == 0) mbar_arrive(BAR(BAR_HW));
            if (lane < LAG) mbar_arrive(BAR(BAR_WEMPTY + (NSTAGE - LAG) % NS) + 8 * lane);
            if (has_outer) {
                uint4* outbox = gs->box + (cta + ((r & 1) ? 1 : -1)) * 1024 + tid;
#pragma unroll
                for (int kc = 0; kc < 8; kc++) outbox[kc * 128] = make_uint4(~hp[4 * kc], ~hp[4 * kc + 1], ~hp[4 * kc + 2], ~hp[4 * kc + 3]);
            }
            if (tid == 0) TL(12);
            const uint32_t xbase = SM_XOWN + ((lane >> 4) * 8 + (lane & 7)) * 128 + (((2 * wq + ((lane >> 3) & 1)) ^ (lane & 7)) << 4);
#pragma unroll
            for (int kc = 0; kc < 8; kc++) {
                uint32_t p[4];
                ldsm4t(p, xbase + kc * 2048);
#pragma unroll
                for (int i = 0; i < 4; i++) { d[8 * kc + 2 * i] = bf_lo(p[i]); d[8 * kc + 2 * i + 1] = bf_hi(p[i]); }
            }
        }
        {
            const uint32_t obase = slot_addr(0) + ((lane >> 4) * 8 + (lane & 7)) * OUT_PITCH + (wq * 16 + ((lane >> 3) & 1) * 8) * 2;
#pragma unroll
            for (int kc = 0; kc < 8; kc++) {
                stsm4t(obase + kc * 16 * OUT_PITCH, pack_bf(d[8 * kc + 0], d[8 * kc + 1]), pack_bf(d[8 * kc + 2], d[8 * kc + 3]),
                       pack_bf(d[8 * kc + 4], d[8 * kc + 5]), pack_bf(d[8 * kc + 6], d[8 * kc + 7]));
            }
            bar_sync(2, 128);
            const int oc0 = tid >> 3;
            __nv_bfloat16* dst = out + ((size_t)(b * C + oc0) * HW + r) * HW + seg * 8;
#pragma unroll
            for (int i = 0; i < 8; i++)
                *reinterpret_cast<uint4*>(dst + (size_t)i * 16 * HW * HW) = lds128(slot_addr(0) + (oc0 + 16 * i) * OUT_PITCH + seg * 16);
            if (tid == 0) { TL(20); TLG(21); }
        }
    } else if (warp < 6) {
        bar_sync(5, 96);
        if (warp == 5) {
            asm volatile("barrier.cluster.wait.acquire.aligned;" ::: "memory");
            const uint32_t peer = (r & 1) ^ 1;
            const uint32_t self0 = mapa(0, r & 1), peer0 = mapa(0, peer);
#pragma unroll 1
            for (int conv = 0; conv < 2; conv++) {
#pragma unroll 1
                for (int kc = 0; kc < 8; kc++) {
                    mbar_wait(BAR(BAR_FULL) + 8 * kc, conv);
                    if (elect_one())
                        asm volatile("cp.async.bulk.shared::cluster.shared::cta.mbarrier::complete_tx::bytes [%0], [%1], %2, [%3];"
                                     ::"r"(peer0 + SM_ACT + ROW_BYTES + kc * KC_BYTES), "r"(self0 + SM_ACT + kc * KC_BYTES), "r"(KC_BYTES),
                                       "r"(peer0 + BAR(BAR_FULL + 8) + 8 * kc) : "memory");
                }
                if (lane == 0) TL(86 + conv);
#pragma unroll 1
                for (int kc = 0; kc < 8; kc++) mbar_wait(BAR(BAR_FULL + 8) + 8 * kc, conv);
                if (lane == 0)
                    asm volatile("mbarrier.arrive.release.cluster.shared::cluster.b64 _, [%0];" ::"r"(peer0 + (conv ? BAR(BAR_ACK) : BAR(BAR_EMB))) : "memory");
            }
            mbar_wait(BAR(BAR_ACK), 0);
        } else {
            mbar_wait(BAR(BAR_STATS + 3), 0);
            weight_load(v, w2, cta, lane);
            const uint2* wsrc = reinterpret_cast<const uint2*>(w_emb + (size_t)r * 12 * C) + lane;
            uint2 wv[12];
#pragma unroll
            for (int i = 0; i < 12; i++) wv[i] = __ldg(wsrc + i * (C / 4));
            if (r == 0 && lane < 16) gs->acc[(NB + b) * 32 + lane] = 0.f;
            const float sv = silu_half(0.5f * tv);
            float e0 = 0.f, e1 = 0.f, e2 = 0.f, e3 = 0.f;
#pragma unroll
            for (int i = 0; i < 12; i++) {
                const float sx = __shfl_sync(0xffffffffu, sv, i);
                e0 = fmaf(sx, bf_lo(wv[i].x), e0); e1 = fmaf(sx, bf_hi(wv[i].x), e1);
                e2 = fmaf(sx, bf_lo(wv[i].y), e2); e3 = fmaf(sx, bf_hi(wv[i].y), e3);
            }
            float* eacc = &gs->emb[(b * C + lane * 4) * 2];
            red_add4(eacc, 1.f, e0, e1, 1.f);
            red_add4(eacc + 4, 1.f, e2, e3, 1.f);
            if (lane == 0) TL(13);
            weight_block<true>(v, SM_BNC + 2304, gs->wt + NSTAGE * STAGE_BYTES, cta, lane);
            if (r == 0) asm volatile("fence.acq_rel.gpu;" ::: "memory");
            __syncwarp();
            if (lane < 2) asm volatile("red.relaxed.gpu.global.add.u32 [%0], 1;" ::"l"(&gs->wcnt[(NB + lane) * 32]) : "memory");
            if (lane == 0) TL(14);
            unsigned it = 0;
            uint4 f0, f1;
            while (true) {
                const unsigned cw = ld_relaxed(&gs->wcnt[(NB + b) * 32]);
                f0 = ld_relaxed_v4(eacc); f1 = ld_relaxed_v4(eacc + 4);
                const bool ok = cw >= (unsigned)NCTA && f0.x == 0x42800000u && f0.w == 0x42800000u && f1.x == 0x42800000u && f1.w == 0x42800000u;
                if (__all_sync(0xffffffffu, ok) || ++it > SPIN_LIMIT) break;
            }
            fence_acquire();
            const uint32_t eu[4] = {f0.y, f0.z, f1.y, f1.z};
#pragma unroll
            for (int i = 0; i < 4; i++) {
                const float e = __uint_as_float(eu[i]);
                const float hi = bf_lo(pack_bf(e, 0.f));
                sts128(SM_EMB + (lane * 4 + i) * 16, make_uint4(pack_bf(hi, e - hi), 0, 0, 0));
            }
            fence_async_smem();
            __syncwarp();
            if (lane == 0) { mbar_arrive(BAR(BAR_EMB)); TL(19); }
        }
    } else if (warp == 6) {
        bar_sync(0, 96);
        const uint32_t ebytes = STAGE_BYTES + ((lane >> 3) == 1 ? KC_BYTES : 0);
        if (lane < NSTAGE) mbar_expect(BAR(BAR_FULL) + 8 * lane, ebytes);
        const int swap = (r & 1) ? 0 : 8 * STAGE_BYTES;
        const unsigned char* wsrc = gs->wt;
        uint32_t dst = S0 + SM_W, full = S0 + BAR(BAR_FULL), empty = BAR(BAR_WEMPTY);
        unsigned it = 0;
        while (ld_relaxed(&gs->wcnt[b * 32]) < (unsigned)NCTA && ++it < SPIN_LIMIT) {}
        fence_acquire();
        fence_async_global();
        if (lane == 0) TL(6);
#pragma unroll 1
        for (int g = 0; g < 2 * NSTAGE; g++) {
            if (g >= NS) {
                mbar_wait(empty, ((g - NS) / NS) & 1);
                if (g == NSTAGE) { mbar_wait(BAR(BAR_EMB), 0); fence_async_global(); }
                if (g == NSTAGE || g == NSTAGE + NS) {
                    if (lane >= g - NSTAGE && lane < g - NSTAGE + NS) mbar_expect(BAR(BAR_FULL) + 8 * lane, ebytes);
                    __syncwarp();
                }
            }
            if (elect_one()) bulk_g2s(dst, wsrc, STAGE_BYTES, full);
            wsrc += STAGE_BYTES; dst += STAGE_BYTES; full += 8; empty += 8;
            const int st = (g >= NSTAGE ? g - NSTAGE : g) + 1;
            if (st == 8 || st == NSTAGE) wsrc += swap;
            if (st == 16) wsrc -= 2 * swap;
            if (st == NS || st == NSTAGE) { dst -= NS * STAGE_BYTES; empty -= 8 * NS; }
            if (st == NSTAGE) full -= 8 * NSTAGE;
        }
    } else {
        const uint2 ga1 = __ldg(reinterpret_cast<const uint2*>(g1) + lane), bt1 = __ldg(reinterpret_cast<const uint2*>(be1) + lane);
        const uint2 ga2 = __ldg(reinterpret_cast<const uint2*>(g2) + lane), bt2 = __ldg(reinterpret_cast<const uint2*>(be2) + lane);
        bar_sync(0, 96);
#pragma unroll 1
        for (int conv = 0; conv < 2; conv++) {
            if (conv == 1) mbar_wait(BAR(BAR_EMB), 0);
            const float* asrc = &gs->acc[(conv * NB + b) * 32 + (lane >> 3) * 4];
            const uint2 ga = conv ? ga2 : ga1, bt = conv ? bt2 : bt1;
            bool done = false;
            unsigned it = 0;
#pragma unroll 1
            while (true) {
                const uint4 f = ld_relaxed_v4(asrc);
                const bool fresh = !done && (((f.x == 0x42800000u) & (f.w == 0x42800000u)) || it > SPIN_LIMIT);
                it++;
                if (!__any_sync(0xffffffffu, fresh)) continue;
                if (lane == 0 && fresh) TL(7 + conv * 8);
                if (lane == 24 && fresh) TL(90 + conv);
                const float inv_n = 1.0f / (32.0f * HW * HW);
                const float mean = __uint_as_float(f.y) * inv_n;
                const float var = fmaxf(fmaf(-mean, mean, __uint_as_float(f.z) * inv_n), 0.f);
                const float rs = 0.5f * rsqrtf(var + 1e-5f);
                float4 k0, k1;
                k0.x = rs * bf_lo(ga.x); k0.y = rs * bf_hi(ga.x); k1.x = rs * bf_lo(ga.y); k1.y = rs * bf_hi(ga.y);
                k0.z = fmaf(-mean, k0.x, 0.5f * bf_lo(bt.x)); k0.w = fmaf(-mean, k0.y, 0.5f * bf_hi(bt.x));
                k1.z = fmaf(-mean, k1.x, 0.5f * bf_lo(bt.y)); k1.w = fmaf(-mean, k1.y, 0.5f * bf_hi(bt.y));
                if (fresh) {
                    sts128f(SM_COEF + lane * 32, k0);
                    sts128f(SM_COEF + lane * 32 + 16, k1);
                }
                __syncwarp();
                if (fresh && (lane & 7) == 0) mbar_arrive(BAR(BAR_STATS) + lane);
                done = done || fresh;
                if (__all_sync(0xffffffffu, done)) break;
            }
        }
        if (r == 0) {
            if (lane < 16) gs->acc[b * 32 + lane] = 0.f;
            if (lane < 2) gs->wcnt[(lane * NB + b) * 32] = 0;
            *reinterpret_cast<float4*>(&gs->emb[(b * C + lane * 4) * 2]) = make_float4(0.f, 0.f, 0.f, 0.f);
            *reinterpret_cast<float4*>(&gs->emb[(b * C + lane * 4) * 2 + 4]) = make_float4(0.f, 0.f, 0.f, 0.f);
        }
    }
}

}

extern "C" void kernel_launch(void* const* d_in, const int* in_sizes, int n_in, void* d_out, int out_size) {
    (void)in_sizes; (void)n_in; (void)out_size;
    typedef CUresult (*EncodeFn)(CUtensorMap*, CUtensorMapDataType, cuuint32_t, void*, const cuuint64_t*, const cuuint64_t*,
                                 const cuuint32_t*, const cuuint32_t*, CUtensorMapInterleave, CUtensorMapSwizzle,
                                 CUtensorMapL2promotion, CUtensorMapFloatOOBfill);
    static Scratch* gs = nullptr;
    static EncodeFn encode = nullptr;
    if (!gs) {
        cudaFuncSetAttribute(resblock_kernel, cudaFuncAttributeMaxDynamicSharedMemorySize, SM_TOTAL);
        cudaGetSymbolAddress((void**)&gs, g_scratch);
        cudaDriverEntryPointQueryResult qr;
        cudaGetDriverEntryPoint("cuTensorMapEncodeTiled", (void**)&encode, cudaEnableDefault, &qr);
    }
    CUtensorMap xmap;
    const cuuint64_t dims[3] = {HW, HW, NB * C}, strides[2] = {HW * 2, HW * HW * 2};
    const cuuint32_t box[3] = {HW, 1, 32}, es[3] = {1, 1, 1};
    encode(&xmap, CU_TENSOR_MAP_DATA_TYPE_BFLOAT16, 3, d_in[0], dims, strides, box, es, CU_TENSOR_MAP_INTERLEAVE_NONE,
           CU_TENSOR_MAP_SWIZZLE_128B, CU_TENSOR_MAP_L2_PROMOTION_NONE, CU_TENSOR_MAP_FLOAT_OOB_FILL_NONE);
    resblock_kernel<<<NCTA, NTHREADS, SM_TOTAL>>>(
        (const __nv_bfloat16*)d_in[4], (const __nv_bfloat16*)d_in[1],
        (const __nv_bfloat16*)d_in[2], (const __nv_bfloat16*)d_in[3], (const __nv_bfloat16*)d_in[5],
        (const __nv_bfloat16*)d_in[6], (const __nv_bfloat16*)d_in[7], (const __nv_bfloat16*)d_in[8],
        (__nv_bfloat16*)d_out, gs, xmap);
}
```

```cpp
#include <cuda_runtime.h>
#include <cuda.h>
#include <cuda_bf16.h>
#include <stdint.h>

namespace {

constexpr int C = 128, HW = 64, NB = 2, E = 768;
constexpr int NCTA = NB * HW;
constexpr int NXTRA = 4;
constexpr int NTHREADS = 16 * 32;
constexpr int CH_PITCH = 66 * 16;
constexpr int ROW_BYTES = 16 * CH_PITCH;
constexpr int STEP_BYTES = 4096;
constexpr int STAGE_BYTES = 3 * STEP_BYTES;
constexpr int NSTAGE = 24;
constexpr int KC_BYTES = 2 * CH_PITCH;
constexpr int NS = 12;
constexpr int LAG = 1;
#define XDELAY 500
#define HDELAY 600
#define NA 2
#define RB 1
#define XSTAG 400
#define HSEND 0
#define W2DELAY 2200

constexpr uint32_t SMEM_BASE = 0x400;
constexpr uint32_t SM_XOWN = SMEM_BASE;
constexpr uint32_t SM_ACT = SM_XOWN + 16384 + 512;
constexpr uint32_t SM_XOUT = SM_ACT + 2 * ROW_BYTES + 512;
static_assert(SM_XOUT % 1024 == 0, "swizzle atom alignment");
constexpr uint32_t SM_W = SM_ACT + 3 * ROW_BYTES + 128;
__host__ __device__ constexpr uint32_t slot_addr(int slot) { return SM_W + slot * STAGE_BYTES; }
constexpr uint32_t SM_COEF = SM_W + NS * STAGE_BYTES;
constexpr uint32_t SM_EMB = SM_COEF + 1024;
constexpr uint32_t SM_ONES = SM_EMB + 2048;
constexpr uint32_t SM_RED = SM_ONES + 256;
constexpr uint32_t SM_BNC = SM_RED + 1280;
constexpr uint32_t SM_BAR = SM_BNC + 2304;
constexpr int BAR_FULL = 0, BAR_WEMPTY = NSTAGE, BAR_HW = BAR_WEMPTY + NS, BAR_STATS = BAR_HW + 1  ,
              BAR_EMB = BAR_STATS + 4, BAR_ACK = BAR_EMB + 1, BAR_X = BAR_ACK + 1  , NBAR = BAR_X + 5;
constexpr int SM_TOTAL = SM_BAR + NBAR * 8 - SMEM_BASE;
static_assert(SM_TOTAL <= 232448, "smem");
static_assert(NBAR <= 96, "barrier init");
constexpr int OUT_PITCH = 144;
__host__ __device__ constexpr uint32_t BAR(int i) { return SM_BAR + 8 * i; }
__host__ __device__ constexpr int ky_of(int kyo) { return kyo == 0 ? 1 : (kyo == 1 ? 0 : 2); }

constexpr unsigned SPIN_LIMIT = 1u << 16;

#define LS 1056
#define GS1 4
#define PD 0
struct Scratch {
    float acc1[NB * 4 * LS];
    float acc2[NB * LS];
    unsigned wcnt[2 * NB * LS];
    float emb[NB * C];
    unsigned char wt[2 * NSTAGE * STAGE_BYTES];
    uint4 box[NCTA * 1024];
};
__device__ __align__(1024) Scratch g_scratch;
#define TL(i) do {} while (0)
#define TLG(i) do {} while (0)

__device__ __forceinline__ unsigned clock32() { unsigned c; asm volatile("mov.u32 %0, %%clock;" : "=r"(c)); return c; }
__device__ __forceinline__ uint32_t mapa(uint32_t a, uint32_t rank) {
    uint32_t d;
    asm("mapa.shared::cluster.u32 %0, %1, %2;" : "=r"(d) : "r"(a), "r"(rank));
    return d;
}
#define S0 mapa(0, blockIdx.x & 1)
__device__ __forceinline__ void mbar_init(uint32_t bar, int cnt) {
    asm volatile("mbarrier.init.shared::cta.b64 [%0], %1;" ::"r"(bar + S0), "r"(cnt) : "memory");
}
__device__ __forceinline__ void mbar_arrive(uint32_t bar) {
    asm volatile("mbarrier.arrive.shared::cta.b64 _, [%0];" ::"r"(bar + S0) : "memory");
}
__device__ __forceinline__ void mbar_expect(uint32_t bar, uint32_t bytes) {
    asm volatile("mbarrier.arrive.expect_tx.shared::cta.b64 _, [%0], %1;" ::"r"(bar + S0), "r"(bytes) : "memory");
}
__device__ __forceinline__ bool mbar_try(uint32_t bar, uint32_t par) {
    uint32_t ok;
    asm volatile("{\n.reg .pred p;\nmbarrier.try_wait.parity.shared::cta.b64 p, [%1], %2;\nselp.u32 %0, 1, 0, p;\n}"
                 : "=r"(ok) : "r"(bar + S0), "r"(par) : "memory");
    return ok;
}
__device__ __forceinline__ bool mbar_test(uint32_t bar, uint32_t par) {
    uint32_t ok;
    asm volatile("{\n.reg .pred p;\nmbarrier.test_wait.parity.shared::cta.b64 p, [%1], %2;\nselp.u32 %0, 1, 0, p;\n}"
                 : "=r"(ok) : "r"(bar + S0), "r"(par) : "memory");
    return ok;
}
__device__ __forceinline__ void mbar_wait(uint32_t bar, uint32_t par) {
    unsigned it = 0;
#pragma unroll 1
    while (!mbar_try(bar, par) && ++it < SPIN_LIMIT) {}
}
__device__ __forceinline__ bool elect_one() {
    uint32_t p;
    asm volatile("{\n.reg .pred p;\nelect.sync _|p, 0xffffffff;\nselp.u32 %0, 1, 0, p;\n}" : "=r"(p));
    return p;
}
__device__ __forceinline__ void fence_async_smem() { asm volatile("fence.proxy.async.shared::cta;" ::: "memory"); }
__device__ __forceinline__ void fence_async_global() { asm volatile("fence.proxy.async.global;" ::: "memory"); }
__device__ __forceinline__ void fence_acquire() { asm volatile("fence.acquire.gpu;" ::: "memory"); }
__device__ __forceinline__ void bar_sync(int id, int n) { asm volatile("bar.sync %0, %1;" ::"r"(id), "r"(n) : "memory"); }
__device__ __forceinline__ void bar_arrive(int id, int n) { asm volatile("bar.arrive %0, %1;" ::"r"(id), "r"(n) : "memory"); }
__device__ __forceinline__ void bulk_g2s(uint32_t dst, const void* src, uint32_t bytes, uint32_t bar) {
    asm volatile("cp.async.bulk.shared::cluster.global.mbarrier::complete_tx::bytes [%0], [%1], %2, [%3];"
                 ::"r"(dst), "l"(src), "r"(bytes), "r"(bar) : "memory");
}
__device__ __forceinline__ void tma_x(uint32_t dst, const CUtensorMap* tm, int row, int ch, uint32_t bar) {
    asm volatile("cp.async.bulk.tensor.3d.shared::cluster.global.mbarrier::complete_tx::bytes [%0], [%1, {%2, %3, %4}], [%5];"
                 ::"r"(dst + S0), "l"(tm), "r"(0), "r"(row), "r"(ch), "r"(bar + S0) : "memory");
}
__device__ __forceinline__ uint4 ld_relaxed_v4(const void* p) {
    uint4 v;
    asm volatile("ld.relaxed.gpu.global.v4.u32 {%0,%1,%2,%3}, [%4];" : "=r"(v.x), "=r"(v.y), "=r"(v.z), "=r"(v.w) : "l"(p) : "memory");
    return v;
}
__device__ __forceinline__ unsigned ld_relaxed(const void* p) {
    unsigned v;
    asm volatile("ld.relaxed.gpu.global.u32 %0, [%1];" : "=r"(v) : "l"(p) : "memory");
    return v;
}
__device__ __forceinline__ void red_add4(float* p, float a, float b, float c, float d) {
    asm volatile("red.relaxed.gpu.global.add.v4.f32 [%0], {%1,%2,%3,%4};" ::"l"(p), "f"(a), "f"(b), "f"(c), "f"(d) : "memory");
}
__device__ __forceinline__ void sts128(uint32_t a, uint4 v) {
    asm volatile("st.shared.v4.u32 [%0], {%1,%2,%3,%4};" ::"r"(a + S0), "r"(v.x), "r"(v.y), "r"(v.z), "r"(v.w) : "memory");
}
__device__ __forceinline__ void sts128f(uint32_t a, float4 v) {
    asm volatile("st.shared.v4.f32 [%0], {%1,%2,%3,%4};" ::"r"(a + S0), "f"(v.x), "f"(v.y), "f"(v.z), "f"(v.w) : "memory");
}
__device__ __forceinline__ void sts32f(uint32_t a, float v) { asm volatile("st.shared.f32 [%0], %1;" ::"r"(a + S0), "f"(v) : "memory"); }
__device__ __forceinline__ uint4 lds128(uint32_t a) {
    uint4 v;
    asm volatile("ld.shared.v4.u32 {%0,%1,%2,%3}, [%4];" : "=r"(v.x), "=r"(v.y), "=r"(v.z), "=r"(v.w) : "r"(a + S0) : "memory");
    return v;
}
__device__ __forceinline__ float4 lds128f(uint32_t a) {
    float4 v;
    asm volatile("ld.shared.v4.f32 {%0,%1,%2,%3}, [%4];" : "=f"(v.x), "=f"(v.y), "=f"(v.z), "=f"(v.w) : "r"(a + S0) : "memory");
    return v;
}
__device__ __forceinline__ float2 lds64f(uint32_t a) {
    float2 v;
    asm volatile("ld.shared.v2.f32 {%0,%1}, [%2];" : "=f"(v.x), "=f"(v.y) : "r"(a + S0) : "memory");
    return v;
}
__device__ __forceinline__ float bf_lo(uint32_t u) { return __uint_as_float(u << 16); }
__device__ __forceinline__ float bf_hi(uint32_t u) { return __uint_as_float(u & 0xffff0000u); }
__device__ __forceinline__ uint32_t pack_bf(float lo, float hi) {
    uint32_t r;
    asm("cvt.rn.bf16x2.f32 %0, %1, %2;" : "=r"(r) : "f"(hi), "f"(lo));
    return r;
}
__device__ __forceinline__ float tanh_fast(float x) {
    float r;
    asm("tanh.approx.f32 %0, %1;" : "=f"(r) : "f"(x));
    return r;
}
__device__ __forceinline__ float silu_half(float h) { return fmaf(h, tanh_fast(h), h); }
__device__ __forceinline__ void ldsm4(uint32_t (&u)[4], uint32_t a) {
    asm volatile("ldmatrix.sync.aligned.m8n8.x4.shared.b16 {%0,%1,%2,%3}, [%4];"
                 : "=r"(u[0]), "=r"(u[1]), "=r"(u[2]), "=r"(u[3]) : "r"(a + S0) : "memory");
}
__device__ __forceinline__ void ldsm4t(uint32_t (&u)[4], uint32_t a) {
    asm volatile("ldmatrix.sync.aligned.m8n8.x4.trans.shared.b16 {%0,%1,%2,%3}, [%4];"
                 : "=r"(u[0]), "=r"(u[1]), "=r"(u[2]), "=r"(u[3]) : "r"(a + S0) : "memory");
}
__device__ __forceinline__ void stsm4(uint32_t a, uint32_t p0, uint32_t p1, uint32_t p2, uint32_t p3) {
    asm volatile("stmatrix.sync.aligned.m8n8.x4.shared.b16 [%0], {%1,%2,%3,%4};" ::"r"(a + S0), "r"(p0), "r"(p1), "r"(p2), "r"(p3) : "memory");
}
__device__ __forceinline__ void stsm4t(uint32_t a, uint32_t p0, uint32_t p1, uint32_t p2, uint32_t p3) {
    asm volatile("stmatrix.sync.aligned.m8n8.x4.trans.shared.b16 [%0], {%1,%2,%3,%4};" ::"r"(a + S0), "r"(p0), "r"(p1), "r"(p2), "r"(p3) : "memory");
}

#define R8(o) "+f"(d[o]), "+f"(d[o + 1]), "+f"(d[o + 2]), "+f"(d[o + 3]), "+f"(d[o + 4]), "+f"(d[o + 5]), "+f"(d[o + 6]), "+f"(d[o + 7])
template <uint32_t ALO, uint32_t BLO, uint64_t AHI = 8, uint64_t BHI = 48>
__device__ __forceinline__ void wgmma128(float (&d)[64]) {
    asm volatile(
        "wgmma.mma_async.sync.aligned.m64n128k16.f32.bf16.bf16 "
        "{%0,%1,%2,%3,%4,%5,%6,%7,%8,%9,%10,%11,%12,%13,%14,%15,%16,%17,%18,%19,%20,%21,%22,%23,%24,%25,%26,%27,%28,%29,%30,%31,"
        "%32,%33,%34,%35,%36,%37,%38,%39,%40,%41,%42,%43,%44,%45,%46,%47,%48,%49,%50,%51,%52,%53,%54,%55,%56,%57,%58,%59,%60,%61,%62,%63},"
        " %64, %65, 1, 1, 1, 0, 0;"
        : R8(0), R8(8), R8(16), R8(24), R8(32), R8(40), R8(48), R8(56)
        : "l"((AHI << 32) | ALO), "l"((BHI << 32) | BLO));
}
template <int S>
__device__ __forceinline__ void mma_stages(float (&d)[64], int conv, int tid, Scratch* gs) {
    constexpr uint32_t A = ((SM_ACT + S * 2 * CH_PITCH + 16) >> 4) | ((CH_PITCH >> 4) << 16);
    constexpr uint32_t B = (slot_addr(S % NS) >> 4) | (8u << 16);
    if (S == 0) mbar_wait(BAR(BAR_FULL), conv);
    bool next_ok = true;
    constexpr uint32_t NEXT = S + 1 < NSTAGE ? BAR(BAR_FULL + S + 1) : BAR(BAR_EMB);
    const int npar = S + 1 < NSTAGE ? conv : 0;
    next_ok = mbar_test(NEXT, npar);
    if (S == 0 && tid == 0) TL(32 + conv * 24);
    asm volatile("wgmma.fence.sync.aligned;" ::: "memory");
    wgmma128<A, B>(d);
    wgmma128<A + 1, B + 16>(d);
    wgmma128<A + 2, B + 32>(d);
    asm volatile("wgmma.commit_group.sync.aligned;" ::: "memory");
    if (S >= LAG) {
        asm volatile("wgmma.wait_group.sync.aligned %0;" ::"n"(LAG) : "memory");
        if ((tid & 31) == 0) mbar_arrive(BAR(BAR_WEMPTY + (S + NS - LAG) % NS));
    }
    if (!next_ok) mbar_wait(NEXT, npar);
    if constexpr (S + 1 < NSTAGE) mma_stages<S + 1>(d, conv, tid, gs);
}

__device__ __forceinline__ void weight_load(uint4 (&t)[5], const __nv_bfloat16* w, int cta, int lane) {
    const char* base = reinterpret_cast<const char*>(w) + ((cta & 15) * 8 * C + (cta >> 4) * 16) * 18;
#pragma unroll
    for (int k = 0; k < 5; k++) {
        const int i = lane + 32 * k, row = (i * 57) >> 10;
        if (k < 4 || lane < 16) t[k] = __ldg(reinterpret_cast<const uint4*>(base + row * (C * 18 - 288) + i * 16));
    }
}
template <bool READBACK>
__device__ __forceinline__ void weight_block(const uint4 (&t)[5], uint32_t bounce, unsigned char* wt, int cta, int lane) {
#pragma unroll
    for (int k = 0; k < 5; k++)
        if (k < 4 || lane < 16) sts128(bounce + (lane + 32 * k) * 16, t[k]);
    __syncwarp();
    unsigned char* dst = wt + (cta >> 4) * STAGE_BYTES + (cta & 15) * 768;
    if (lane < 16) {
        uint32_t v[36];
#pragma unroll
        for (int i = 0; i < 9; i++) {
            const uint4 q = lds128(bounce + (lane & 7) * 288 + (lane >> 3) * 144 + i * 16);
            v[4 * i] = q.x; v[4 * i + 1] = q.y; v[4 * i + 2] = q.z; v[4 * i + 3] = q.w;
        }
#pragma unroll
        for (int kyo = 0; kyo < 3; kyo++) {
#pragma unroll
            for (int kx = 0; kx < 3; kx++) {
                const int tap = ky_of(kyo) * 3 + kx;
                uint32_t o[4];
#pragma unroll
                for (int m = 0; m < 4; m++) {
                    const int i0 = 18 * m + tap, i1 = i0 + 9;
                    const uint32_t sel = ((i0 & 1) ? 0x32u : 0x10u) | ((i1 & 1) ? 0x7600u : 0x5400u);
                    o[m] = __byte_perm(v[i0 >> 1], v[i1 >> 1], sel);
                }
                *reinterpret_cast<uint4*>(dst + kyo * 8 * STAGE_BYTES + kx * 256 + lane * 16) = make_uint4(o[0], o[1], o[2], o[3]);
            }
        }
    }
    if (READBACK) {
        __syncwarp();
        unsigned acc = 0;
        if (lane < 24) {
#pragma unroll
            for (int i = 0; i < 3; i++) acc |= ld_relaxed(dst + i * 8 * STAGE_BYTES + lane * 32);
        }
        asm volatile("{\n.reg .pred p;\nsetp.eq.u32 p, %0, 0x9e3779b9;\n@p st.shared.u32 [%1], %0;\n}" ::"r"(acc), "r"(bounce + S0) : "memory");
    }
}
__device__ __forceinline__ uint32_t act2(uint32_t u, const float4& cf) {
    return pack_bf(silu_half(fmaf(bf_lo(u), cf.x, cf.z)), silu_half(fmaf(bf_hi(u), cf.y, cf.w)));
}
__device__ __forceinline__ void norm_unit(uint32_t (&u)[4], const float4& ca, const float4& cb) {
    u[0] = act2(u[0], ca); u[1] = act2(u[1], ca); u[2] = act2(u[2], cb); u[3] = act2(u[3], cb);
}
template <int FIRST, int N>
__device__ __forceinline__ void norm_block(uint32_t (&u)[4][4], float4 (&cf)[8], bool load_cf, uint32_t cfa, uint32_t act, uint32_t mask, uint32_t fbar, int lane) {
    if (load_cf) {
#pragma unroll
        for (int i = 2 * FIRST; i < 2 * (FIRST + N); i++) cf[i] = lds128f(cfa + (i >> 1) * 256 + (i & 1) * 64);
    }
#pragma unroll
    for (int t = FIRST; t < FIRST + N; t++) {
        norm_unit(u[t], cf[2 * t], cf[2 * t + 1]);
        stsm4(act + t * 2 * KC_BYTES, u[t][0] & mask, u[t][1] & mask, u[t][2] & mask, u[t][3] & mask);
    }
    fence_async_smem();
    __syncwarp();
    if (lane < N) mbar_arrive(fbar + 16 * (FIRST + lane));
}
__device__ __forceinline__ void stat_mma(float (&c)[4], uint32_t p, uint32_t q) {
    asm("mma.sync.aligned.m16n8k16.row.col.f32.bf16.bf16.f32 {%0,%1,%2,%3}, {%4,%5,%6,%5}, {%4,%6}, {%0,%1,%2,%3};"
        : "+f"(c[0]), "+f"(c[1]), "+f"(c[2]), "+f"(c[3]) : "r"(p), "r"(0x3f803f80u), "r"(q));
}
__device__ __forceinline__ void stat_store(const float (&c)[4], uint32_t dst, int lane) {
    const int g = lane >> 2, t = lane & 3;
    if (t == (g >> 1)) sts32f(dst + g * 4, (g & 1) ? c[1] : c[0]);
    if (g == 7) sts32f(dst + 32 + t * 4, c[2] + c[3]);
}
__device__ __forceinline__ float sum4(float4 v) { return (v.x + v.y) + (v.z + v.w); }
__device__ __forceinline__ void stat_publish(uint32_t src, float* acc, int lane, bool real) {
    const uint32_t a = src + (lane & 15) * 48;
    float q = sum4(lds128f(a)) + sum4(lds128f(a + 16)), sm = sum4(lds128f(a + 32));
    q += __shfl_xor_sync(0xffffffffu, q, 1); sm += __shfl_xor_sync(0xffffffffu, sm, 1);
    q += __shfl_xor_sync(0xffffffffu, q, 2); sm += __shfl_xor_sync(0xffffffffu, sm, 2);
    if (real && (lane & 19) == 0) red_add4(acc + lane, 1.f, sm, q, 1.f);
}
__device__ __forceinline__ void fence_acc(float (&d)[64]) {
#pragma unroll
    for (int i = 0; i < 64; i++) asm volatile("" : "+f"(d[i])::"memory");
}
__device__ __forceinline__ void ld_unit(uint32_t (&u)[4], const uint4* p) {
    asm volatile("ld.relaxed.gpu.global.v4.u32 {%0,%1,%2,%3}, [%4];" : "=r"(u[0]), "=r"(u[1]), "=r"(u[2]), "=r"(u[3]) : "l"(p) : "memory");
}

__device__ __noinline__ void side_jobs(const __nv_bfloat16* __restrict__ t_emb, const __nv_bfloat16* __restrict__ w_emb,
                                       const __nv_bfloat16* __restrict__ w2, Scratch* __restrict__ gs, unsigned clk0) {
    const int tid = threadIdx.x, warp = tid >> 5, lane = tid & 31, j = blockIdx.x;
    while (clock32() - clk0 < W2DELAY) {}
    uint4 v[2][5];
    weight_load(v[0], w2, j * 32 + warp, lane);
    weight_load(v[1], w2, j * 32 + 16 + warp, lane);
    const int e0 = (tid >> 3) * 12;
    uint2 wv[12];
#pragma unroll
    for (int i = 0; i < 12; i++) wv[i] = __ldg(reinterpret_cast<const uint2*>(w_emb + (e0 + i) * C + j * 32) + (tid & 7));
    uint2 tv[2][3];
#pragma unroll
    for (int i = 0; i < 6; i++) tv[i / 3][i % 3] = __ldg(reinterpret_cast<const uint2*>(t_emb + (i / 3) * E + e0) + i % 3);
    if (j == 0 && tid < 32) gs->acc2[(tid >> 4) * LS + (tid & 15)] = 0.f;
#pragma unroll 1
    for (int k = 0; k < 2; k++) {
        weight_block<false>(v[0], SM_W + warp * 2304, gs->wt + NSTAGE * STAGE_BYTES, j * 32 + k * 16 + warp, lane);
        __syncwarp();
#pragma unroll
        for (int i = 0; i < 5; i++) v[0][i] = v[1][i];
    }
    float acc[8] = {0.f, 0.f, 0.f, 0.f, 0.f, 0.f, 0.f, 0.f};
#pragma unroll
    for (int i = 0; i < 12; i++) {
#pragma unroll
        for (int bb = 0; bb < 2; bb++) {
            const uint2 t2 = tv[bb][i >> 2];
            const uint32_t tw = (i & 2) ? t2.y : t2.x;
            const float sv = silu_half(0.5f * ((i & 1) ? bf_hi(tw) : bf_lo(tw)));
            acc[4 * bb + 0] = fmaf(sv, bf_lo(wv[i].x), acc[4 * bb + 0]); acc[4 * bb + 1] = fmaf(sv, bf_hi(wv[i].x), acc[4 * bb + 1]);
            acc[4 * bb + 2] = fmaf(sv, bf_lo(wv[i].y), acc[4 * bb + 2]); acc[4 * bb + 3] = fmaf(sv, bf_hi(wv[i].y), acc[4 * bb + 3]);
        }
    }
#pragma unroll
    for (int i = 0; i < 8; i++) {
        acc[i] += __shfl_xor_sync(0xffffffffu, acc[i], 8);
        acc[i] += __shfl_xor_sync(0xffffffffu, acc[i], 16);
    }
    if (lane < 8) {
        sts128f(SM_ACT + warp * 256 + lane * 16, make_float4(acc[0], acc[1], acc[2], acc[3]));
        sts128f(SM_ACT + warp * 256 + 128 + lane * 16, make_float4(acc[4], acc[5], acc[6], acc[7]));
    }
    __syncthreads();
    if (tid < 32) {
        float2 sum = make_float2(0.f, 0.f);
#pragma unroll
        for (int w = 0; w < 16; w++) { const float2 p = lds64f(SM_ACT + w * 256 + tid * 8); sum.x += p.x; sum.y += p.y; }
        *reinterpret_cast<float2*>(&gs->emb[(tid >> 4) * C + j * 32 + (tid & 15) * 2]) = sum;
        __syncwarp();
        if (tid < 2) asm volatile("red.release.gpu.global.add.u32 [%0], 1;" ::"l"(&gs->wcnt[(NB + tid) * LS]) : "memory");
    }
}

__global__ void __cluster_dims__(2, 1, 1) __launch_bounds__(NTHREADS, 1)
resblock_kernel(const __nv_bfloat16* __restrict__ w1,
                const __nv_bfloat16* __restrict__ t_emb, const __nv_bfloat16* __restrict__ g1,
                const __nv_bfloat16* __restrict__ be1, const __nv_bfloat16* __restrict__ w_emb,
                const __nv_bfloat16* __restrict__ g2, const __nv_bfloat16* __restrict__ be2,
                const __nv_bfloat16* __restrict__ w2, __nv_bfloat16* __restrict__ out, Scratch* __restrict__ gs,
                const __grid_constant__ CUtensorMap xmap) {
    const unsigned clk0 = clock32();
    if (threadIdx.x == 480 && blockIdx.x >= NXTRA) TLG(1);
    const int tid = threadIdx.x, warp = __shfl_sync(0xffffffffu, tid >> 5, 0), lane = tid & 31;
    const int cta = blockIdx.x - NXTRA, b = cta >> 6, r = cta & 63;
    if (cta < 0) { side_jobs(t_emb, w_emb, w2, gs, clk0); return; }

    const int seg = lane & 7;
    uint4 v[5];
    if (warp == 0) {
        weight_load(v, w1, cta, lane);
    }
    if (warp != 3) asm volatile("barrier.cluster.arrive.relaxed.aligned;" ::: "memory");
    const bool has_outer = (r != 0) && (r != HW - 1);
    if (warp == 1 || warp == 2 || warp == 4 || warp == 5) {
        const int g = warp < 3 ? warp - 1 : 7 - warp;
        if (elect_one()) {
            asm volatile("prefetch.tensormap [%0];" ::"l"(&xmap) : "memory");
            mbar_init(BAR(BAR_X) + 8 * g, 1);
            if (g == 3) mbar_init(BAR(BAR_X + 4), 1);
            mbar_expect(BAR(BAR_X) + 8 * g, 4096);
            fence_async_smem();
            while (clock32() - clk0 < XDELAY + g * XSTAG) {}
            tma_x(SM_XOWN + g * 4096, &xmap, r, b * C + g * 32, BAR(BAR_X) + 8 * g);
            if (g == 3 && has_outer) {
                mbar_expect(BAR(BAR_X + 4), 16384);
#pragma unroll
                for (int i = 0; i < 4; i++) tma_x(SM_XOUT + i * 4096, &xmap, r + ((r & 1) ? 1 : -1), b * C + i * 32, BAR(BAR_X + 4));
            }
        }
        __syncwarp();
        bar_arrive(4, 256 + 32 + 128);
        mbar_wait(BAR(BAR_X) + 8 * g, 0);
        if (lane == 0) TL(70 + g);
        float c[2][4] = {{0.f, 0.f, 0.f, 0.f}, {0.f, 0.f, 0.f, 0.f}};
#pragma unroll
        for (int k = 0; k < 8; k++) {
            const uint4 q = lds128(SM_XOWN + g * 4096 + k * 512 + lane * 16);
            stat_mma(c[0], q.x, q.y); stat_mma(c[1], q.z, q.w);
        }
#pragma unroll
        for (int i = 0; i < 4; i++) c[0][i] += c[1][i];
        stat_store(c[0], SM_RED + g * 48, lane);
        __syncwarp();
        if (lane == 0) {
            const uint32_t a = SM_RED + g * 48;
            red_add4(&gs->acc1[b * 4 * LS + g * GS1], 1.f, sum4(lds128f(a + 32)), sum4(lds128f(a)) + sum4(lds128f(a + 16)), 1.f);
            TL(74 + g);
        }
    }
    if (warp == 0) {
        weight_block<RB>(v, SM_BNC, gs->wt, cta, lane);
        __syncwarp();
        if (lane == 0) TL(4);
        if (lane < 2) asm volatile("red.relaxed.gpu.global.add.u32 [%0], 1;" ::"l"(&gs->wcnt[lane * LS]) : "memory");
        if (lane == 0) TL(5);
    }

    if (warp >= 8) {
        const int nw = warp - 8;
        bar_sync(4, 256 + 32 + 128);
        const int par = nw >> 2, wq = nw & 3;
        const uint32_t act_off = SM_ACT + (par * 2 + (lane >> 4)) * CH_PITCH + (2 + wq * 16 + (lane & 15)) * 16;
        const uint32_t stg_off = (par * 16 + (lane >> 4) * 8 + (lane & 7)) * 128 + (((2 * wq + ((lane >> 3) & 1)) ^ (lane & 7)) << 4);
        const uint32_t cfa = SM_COEF + par * 128 + (lane & 3) * 16;
        const uint32_t fbar = BAR(BAR_FULL) + 8 * par;
        uint4* inbox = gs->box + cta * 1024 + nw * 32 + lane;
#pragma unroll 1
        for (int conv = 0; conv < 2; conv++) {
            uint32_t u[4][4], w[4][4];
            float4 cf[8];
            if (conv == 0) {
                mbar_wait(BAR(BAR_X), 0); ldsm4t(u[0], SM_XOWN + stg_off);
                mbar_wait(BAR(BAR_X + 1), 0); ldsm4t(u[1], SM_XOWN + stg_off + 4096);
                mbar_wait(BAR(BAR_STATS), 0);
                if (tid == 256) TL(22);
                norm_block<0, 1>(u, cf, true, cfa, act_off, ~0u, fbar, lane);
                if (tid == 256) TL(8);
                mbar_wait(BAR(BAR_X + 2), 0); ldsm4t(u[2], SM_XOWN + stg_off + 8192);
                mbar_wait(BAR(BAR_STATS + 1), 0);
                norm_block<1, 1>(u, cf, true, cfa, act_off, ~0u, fbar, lane);
                mbar_wait(BAR(BAR_X + 3), 0); ldsm4t(u[3], SM_XOWN + stg_off + 12288);
                mbar_wait(BAR(BAR_STATS + 2), 0);
                norm_block<2, 1>(u, cf, true, cfa, act_off, ~0u, fbar, lane);
                mbar_wait(BAR(BAR_STATS + 3), 0);
                norm_block<3, 1>(u, cf, true, cfa, act_off, ~0u, fbar, lane);
                if (has_outer) {
                    mbar_wait(BAR(BAR_X + 4), 0);
#pragma unroll
                    for (int i = 0; i < 4; i++) ldsm4t(w[i], SM_XOUT + stg_off + i * 4096);
                }
                bar_sync(3, 256);
                if (nw == 0) sts128(SM_ACT + 2 * ROW_BYTES + (lane >> 1) * CH_PITCH + (lane & 1) * 16, make_uint4(0, 0, 0, 0));
            } else {
                mbar_wait(BAR(BAR_HW), 0);
#pragma unroll
                for (int i = 0; i < 4; i++) ldsm4(u[i], act_off + i * 2 * KC_BYTES);
                mbar_wait(BAR(BAR_STATS + 1), 1);
                mbar_wait(BAR(BAR_STATS), 1);
                if (tid == 256) TL(26);
                norm_block<0, 2>(u, cf, true, cfa, act_off, ~0u, fbar, lane);
                if (tid == 256) TL(16);
                mbar_wait(BAR(BAR_STATS + 2), 1);
                mbar_wait(BAR(BAR_STATS + 3), 1);
                norm_block<2, 2>(u, cf, true, cfa, act_off, ~0u, fbar, lane);
            }
            if (tid == 256) TL(84 + conv);
            if (conv == 1 && has_outer) {
                unsigned it = 0;
                while (ld_relaxed(inbox + 3 * 256 + 31 - lane) == 0 && ++it < SPIN_LIMIT) {}
                if (tid == 256) TL(89);
                while (true) {
#pragma unroll
                    for (int i = 0; i < 4; i++) ld_unit(w[i], inbox + i * 256);
                    bool ok = true;
#pragma unroll
                    for (int i = 0; i < 16; i++) ok = ok && w[i >> 2][i & 3] != 0;
                    if (__all_sync(0xffffffffu, ok) || ++it > SPIN_LIMIT) break;
                }
#pragma unroll
                for (int i = 0; i < 16; i++) w[i >> 2][i & 3] = ~w[i >> 2][i & 3];
            }
            if (tid == 256) TL(24 + conv * 4);
            norm_block<0, 4>(w, cf, false, cfa, act_off + 2 * ROW_BYTES, has_outer ? ~0u : 0u, fbar + 128, lane);
            if (tid == 256) TL(23 + conv * 4);
        }
        if (has_outer) {
            mbar_wait(BAR(BAR_FULL + NSTAGE - 1), 1);
#pragma unroll
            for (int i = 0; i < 4; i++) inbox[i * 256] = make_uint4(0, 0, 0, 0);
        }
    } else if (warp < 4) {
        const int wq = warp;
        if (wq == 3) {
            if (elect_one()) {
#pragma unroll
                for (int i = 0; i < NSTAGE; i++) mbar_init(BAR(BAR_FULL + i), (i >> 3) == 1 ? 1 : 5);
#pragma unroll
                for (int i = 0; i <= NS; i++) mbar_init(BAR(BAR_WEMPTY + i), 4);
#pragma unroll
                for (int i = BAR_STATS; i < BAR_X; i++) mbar_init(BAR(i), i == BAR_EMB ? 2 : 1);
                asm volatile("fence.mbarrier_init.release.cluster;" ::: "memory");
            }
            __syncwarp();
            fence_async_smem();
            bar_arrive(0, 96);
            bar_arrive(5, 96);
            bar_arrive(4, 256 + 32 + 128);
            const uint4 z = make_uint4(0, 0, 0, 0);
#pragma unroll
            for (int i = 0; i < 2; i++) sts128(SM_ACT + (i * 16 + (lane >> 1)) * CH_PITCH + (lane & 1) * 16, z);
            if (lane < 4) sts128(SM_ACT + (2 + (lane >> 1)) * ROW_BYTES + (lane & 1) * 16, z);
            if (lane < 16) sts128(SM_ONES + lane * 16, make_uint4(lane < 8 ? 0x3f803f80u : 0u, 0, 0, 0));
            fence_async_smem();
            asm volatile("barrier.cluster.arrive.release.aligned;" ::: "memory");
        }
        bar_sync(2, 128);

        float d[64];
#pragma unroll
        for (int i = 0; i < 64; i++) d[i] = 0.f;
#pragma unroll 1
        for (int conv = 0; conv < 2; conv++) {
            fence_acc(d);
            mma_stages<0>(d, conv, tid, gs);
            if (conv == 0) {
                asm volatile("wgmma.fence.sync.aligned;" ::: "memory");
                wgmma128<(SM_ONES >> 4) | (8u << 16), (SM_EMB >> 4), 0, 8>(d);
                asm volatile("wgmma.commit_group.sync.aligned;" ::: "memory");
            }
            asm volatile("wgmma.wait_group.sync.aligned 0;" ::: "memory");
            fence_acc(d);
            if (tid == 0) TL(10 + conv * 8);
            if (conv == 1) break;

            uint32_t hp[32];
#pragma unroll
            for (int g = 0; g < 4; g++) {
                float c[4] = {0.f, 0.f, 0.f, 0.f};
#pragma unroll
                for (int i = 0; i < 8; i++) hp[8 * g + i] = pack_bf(d[16 * g + 2 * i], d[16 * g + 2 * i + 1]);
#pragma unroll
                for (int i = 0; i < 4; i++) stat_mma(c, hp[8 * g + 2 * i], hp[8 * g + 2 * i + 1]);
                stat_store(c, SM_RED + (g * 4 + wq) * 48, lane);
            }
            bar_sync(2, 128);
            if (wq == 0) stat_publish(SM_RED, &gs->acc2[b * LS], lane, true);
            if (tid == 0) TL(11);
            const uint32_t hbase = SM_ACT + (lane >> 4) * CH_PITCH + (2 + wq * 16 + (lane & 15)) * 16;
#pragma unroll
            for (int kc = 0; kc < 8; kc++) stsm4(hbase + kc * 2 * CH_PITCH, hp[4 * kc], hp[4 * kc + 1], hp[4 * kc + 2], hp[4 * kc + 3]);
            __syncwarp();
            if (lane == 0) mbar_arrive(BAR(BAR_HW));
            if (lane < LAG) mbar_arrive(BAR(BAR_WEMPTY + (NSTAGE - LAG) % NS) + 8 * lane);
            if (has_outer) {
                uint4* outbox = gs->box + (cta + ((r & 1) ? 1 : -1)) * 1024 + tid;
#pragma unroll
                for (int kc = 0; kc < 8; kc++) outbox[kc * 128] = make_uint4(~hp[4 * kc], ~hp[4 * kc + 1], ~hp[4 * kc + 2], ~hp[4 * kc + 3]);
            }
            if (tid == 0) TL(12);
            const uint32_t xbase = SM_XOWN + ((lane >> 4) * 8 + (lane & 7)) * 128 + (((2 * wq + ((lane >> 3) & 1)) ^ (lane & 7)) << 4);
#pragma unroll
            for (int kc = 0; kc < 8; kc++) {
                uint32_t p[4];
                ldsm4t(p, xbase + kc * 2048);
#pragma unroll
                for (int i = 0; i < 4; i++) { d[8 * kc + 2 * i] = bf_lo(p[i]); d[8 * kc + 2 * i + 1] = bf_hi(p[i]); }
            }
        }
        {
            const uint32_t obase = slot_addr(0) + ((lane >> 4) * 8 + (lane & 7)) * OUT_PITCH + (wq * 16 + ((lane >> 3) & 1) * 8) * 2;
#pragma unroll
            for (int kc = 0; kc < 8; kc++) {
                stsm4t(obase + kc * 16 * OUT_PITCH, pack_bf(d[8 * kc + 0], d[8 * kc + 1]), pack_bf(d[8 * kc + 2], d[8 * kc + 3]),
                       pack_bf(d[8 * kc + 4], d[8 * kc + 5]), pack_bf(d[8 * kc + 6], d[8 * kc + 7]));
            }
            bar_sync(2, 128);
            const int oc0 = tid >> 3;
            __nv_bfloat16* dst = out + ((size_t)(b * C + oc0) * HW + r) * HW + seg * 8;
#pragma unroll
            for (int i = 0; i < 8; i++)
                *reinterpret_cast<uint4*>(dst + (size_t)i * 16 * HW * HW) = lds128(slot_addr(0) + (oc0 + 16 * i) * OUT_PITCH + seg * 16);
            if (tid == 0) { TL(20); TLG(21); }
        }
    } else if (warp < 6) {
        bar_sync(5, 96);
        if (warp == 5) {
            asm volatile("barrier.cluster.wait.acquire.aligned;" ::: "memory");
            const uint32_t peer = (r & 1) ^ 1;
            const uint32_t self0 = mapa(0, r & 1), peer0 = mapa(0, peer);
#pragma unroll 1
            for (int conv = 0; conv < 2; conv++) {
#pragma unroll 1
                for (int kc = 0; kc < 8; kc++) {
                    mbar_wait(BAR(BAR_FULL) + 8 * kc, conv);
                    if (elect_one())
                        asm volatile("cp.async.bulk.shared::cluster.shared::cta.mbarrier::complete_tx::bytes [%0], [%1], %2, [%3];"
                                     ::"r"(peer0 + SM_ACT + ROW_BYTES + kc * KC_BYTES), "r"(self0 + SM_ACT + kc * KC_BYTES), "r"(KC_BYTES),
                                       "r"(peer0 + BAR(BAR_FULL + 8) + 8 * kc) : "memory");
                }
                if (lane == 0) TL(86 + conv);
#pragma unroll 1
                for (int kc = 0; kc < 8; kc++) mbar_wait(BAR(BAR_FULL + 8) + 8 * kc, conv);
                if (lane == 0)
                    asm volatile("mbarrier.arrive.release.cluster.shared::cluster.b64 _, [%0];" ::"r"(peer0 + (conv ? BAR(BAR_ACK) : BAR(BAR_EMB))) : "memory");
            }
            mbar_wait(BAR(BAR_ACK), 0);
        } else {
            mbar_wait(BAR(BAR_STATS + 3), 0);
            unsigned it = 0;
            while (ld_relaxed(&gs->wcnt[(NB + b) * LS]) < (unsigned)NXTRA && ++it < SPIN_LIMIT) __nanosleep(100);
            fence_acquire();
            if (lane == 0) TL(14);
            const uint4 ef = ld_relaxed_v4(&gs->emb[b * C + lane * 4]);
            const uint32_t eu[4] = {ef.x, ef.y, ef.z, ef.w};
#pragma unroll
            for (int i = 0; i < 4; i++) {
                const float e = __uint_as_float(eu[i]);
                const float hi = bf_lo(pack_bf(e, 0.f));
                sts128(SM_EMB + (lane * 4 + i) * 16, make_uint4(pack_bf(hi, e - hi), 0, 0, 0));
            }
            fence_async_smem();
            __syncwarp();
            if (lane == 0) { mbar_arrive(BAR(BAR_EMB)); TL(19); }
        }
    } else if (warp == 6) {
        bar_sync(0, 96);
        const uint32_t ebytes = STAGE_BYTES + ((lane >> 3) == 1 ? KC_BYTES : 0);
        if (lane < NSTAGE) mbar_expect(BAR(BAR_FULL) + 8 * lane, ebytes);
        const int swap = (r & 1) ? 0 : 8 * STAGE_BYTES;
        const unsigned char* wsrc = gs->wt;
        uint32_t dst = S0 + SM_W, full = S0 + BAR(BAR_FULL), empty = BAR(BAR_WEMPTY);
        unsigned it = 0;
        while (clock32() - clk0 < PD) {}
        while (ld_relaxed(&gs->wcnt[b * LS]) < (unsigned)NCTA && ++it < SPIN_LIMIT) {}
        fence_acquire();
        fence_async_global();
        if (lane == 0) TL(6);
#pragma unroll 1
        for (int g = 0; g < 2 * NSTAGE; g++) {
            if (g >= NS) {
                mbar_wait(empty, ((g - NS) / NS) & 1);
                if (g == NSTAGE) { mbar_wait(BAR(BAR_EMB), 0); fence_async_global(); }
                if (g == NSTAGE || g == NSTAGE + NS) {
                    if (lane >= g - NSTAGE && lane < g - NSTAGE + NS) mbar_expect(BAR(BAR_FULL) + 8 * lane, ebytes);
                    __syncwarp();
                }
            }
            if (elect_one()) bulk_g2s(dst, wsrc, STAGE_BYTES, full);
            wsrc += STAGE_BYTES; dst += STAGE_BYTES; full += 8; empty += 8;
            const int st = (g >= NSTAGE ? g - NSTAGE : g) + 1;
            if (st == 8 || st == NSTAGE) wsrc += swap;
            if (st == 16) wsrc -= 2 * swap;
            if (st == NS || st == NSTAGE) { dst -= NS * STAGE_BYTES; empty -= 8 * NS; }
            if (st == NSTAGE) full -= 8 * NSTAGE;
        }
    } else {
        const uint2 ga1 = __ldg(reinterpret_cast<const uint2*>(g1) + lane), bt1 = __ldg(reinterpret_cast<const uint2*>(be1) + lane);
        const uint2 ga2 = __ldg(reinterpret_cast<const uint2*>(g2) + lane), bt2 = __ldg(reinterpret_cast<const uint2*>(be2) + lane);
        bar_sync(0, 96);
#pragma unroll 1
        for (int conv = 0; conv < 2; conv++) {
            if (conv == 1) mbar_wait(BAR(BAR_EMB), 0);
            const float* asrc = conv ? &gs->acc2[b * LS + (lane >> 3) * 4] : &gs->acc1[b * 4 * LS + (lane >> 3) * GS1];
            while (clock32() - clk0 < PD) {}
            const uint2 ga = conv ? ga2 : ga1, bt = conv ? bt2 : bt1;
            bool done = false;
            unsigned it = 0;
#pragma unroll 1
            while (true) {
                const uint4 f = ld_relaxed_v4(asrc);
                const bool fresh = !done && (((f.x == 0x42800000u) & (f.w == 0x42800000u)) || it > SPIN_LIMIT);
                it++;
                if (!__any_sync(0xffffffffu, fresh)) continue;
                if (lane == 0 && fresh) TL(7 + conv * 8);
                if (lane == 24 && fresh) TL(90 + conv);
                const float inv_n = 1.0f / (32.0f * HW * HW);
                const float mean = __uint_as_float(f.y) * inv_n;
                const float var = fmaxf(fmaf(-mean, mean, __uint_as_float(f.z) * inv_n), 0.f);
                const float rs = 0.5f * rsqrtf(var + 1e-5f);
                float4 k0, k1;
                k0.x = rs * bf_lo(ga.x); k0.y = rs * bf_hi(ga.x); k1.x = rs * bf_lo(ga.y); k1.y = rs * bf_hi(ga.y);
                k0.z = fmaf(-mean, k0.x, 0.5f * bf_lo(bt.x)); k0.w = fmaf(-mean, k0.y, 0.5f * bf_hi(bt.x));
                k1.z = fmaf(-mean, k1.x, 0.5f * bf_lo(bt.y)); k1.w = fmaf(-mean, k1.y, 0.5f * bf_hi(bt.y));
                if (fresh) {
                    sts128f(SM_COEF + lane * 32, k0);
                    sts128f(SM_COEF + lane * 32 + 16, k1);
                }
                __syncwarp();
                if (fresh && (lane & 7) == 0) mbar_arrive(BAR(BAR_STATS) + lane);
                done = done || fresh;
                if (__all_sync(0xffffffffu, done)) break;
            }
        }
        if (r == 0) {
            if (lane < 16) gs->acc1[b * 4 * LS + (lane >> 2) * GS1 + (lane & 3)] = 0.f;
            if (lane < 2) gs->wcnt[(lane * NB + b) * LS] = 0;
        }
    }
}

}

extern "C" void kernel_launch(void* const* d_in, const int* in_sizes, int n_in, void* d_out, int out_size) {
    (void)in_sizes; (void)n_in; (void)out_size;
    typedef CUresult (*EncodeFn)(CUtensorMap*, CUtensorMapDataType, cuuint32_t, void*, const cuuint64_t*, const cuuint64_t*,
                                 const cuuint32_t*, const cuuint32_t*, CUtensorMapInterleave, CUtensorMapSwizzle,
                                 CUtensorMapL2promotion, CUtensorMapFloatOOBfill);
    static Scratch* gs = nullptr;
    static EncodeFn encode = nullptr;
    if (!gs) {
        cudaFuncSetAttribute(resblock_kernel, cudaFuncAttributeMaxDynamicSharedMemorySize, SM_TOTAL);
        cudaGetSymbolAddress((void**)&gs, g_scratch);
        cudaDriverEntryPointQueryResult qr;
        cudaGetDriverEntryPoint("cuTensorMapEncodeTiled", (void**)&encode, cudaEnableDefault, &qr);
    }
    CUtensorMap xmap;
    const cuuint64_t dims[3] = {HW, HW, NB * C}, strides[2] = {HW * 2, HW * HW * 2};
    const cuuint32_t box[3] = {HW, 1, 32}, es[3] = {1, 1, 1};
    encode(&xmap, CU_TENSOR_MAP_DATA_TYPE_BFLOAT16, 3, d_in[0], dims, strides, box, es, CU_TENSOR_MAP_INTERLEAVE_NONE,
           CU_TENSOR_MAP_SWIZZLE_128B, CU_TENSOR_MAP_L2_PROMOTION_NONE, CU_TENSOR_MAP_FLOAT_OOB_FILL_NONE);
    resblock_kernel<<<NCTA + NXTRA, NTHREADS, SM_TOTAL>>>(
        (const __nv_bfloat16*)d_in[4], (const __nv_bfloat16*)d_in[1],
        (const __nv_bfloat16*)d_in[2], (const __nv_bfloat16*)d_in[3], (const __nv_bfloat16*)d_in[5],
        (const __nv_bfloat16*)d_in[6], (const __nv_bfloat16*)d_in[7], (const __nv_bfloat16*)d_in[8],
        (__nv_bfloat16*)d_out, gs, xmap);
}
```

```cpp
#include <cuda_runtime.h>
#include <cuda.h>
#include <cuda_bf16.h>
#include <stdint.h>

namespace {

constexpr int C = 128, HW = 64, NB = 2, E = 768;
constexpr int NCTA = NB * HW;
constexpr int NXTRA = 4;
constexpr int NTHREADS = 16 * 32;
constexpr int CH_PITCH = 66 * 16;
constexpr int ROW_BYTES = 16 * CH_PITCH;
constexpr int STEP_BYTES = 4096;
constexpr int STAGE_BYTES = 3 * STEP_BYTES;
constexpr int NSTAGE = 24;
constexpr int KC_BYTES = 2 * CH_PITCH;
constexpr int NS = 12;
constexpr int LAG = 1;
#define XDELAY 500
#define HDELAY 600
#define NA 2
#define RB 1
#define XSTAG 400
#define HSEND 0
#define W2DELAY 2200

constexpr uint32_t SMEM_BASE = 0x400;
constexpr uint32_t SM_XOWN = SMEM_BASE;
constexpr uint32_t SM_ACT = SM_XOWN + 16384 + 512;
constexpr uint32_t SM_XOUT = SM_ACT + 2 * ROW_BYTES + 512;
static_assert(SM_XOUT % 1024 == 0, "swizzle atom alignment");
constexpr uint32_t SM_W = SM_ACT + 3 * ROW_BYTES + 128;
__host__ __device__ constexpr uint32_t slot_addr(int slot) { return SM_W + slot * STAGE_BYTES; }
constexpr uint32_t SM_COEF = SM_W + NS * STAGE_BYTES;
constexpr uint32_t SM_EMB = SM_COEF + 1024;
constexpr uint32_t SM_ONES = SM_EMB + 2048;
constexpr uint32_t SM_RED = SM_ONES + 256;
constexpr uint32_t SM_BNC = SM_RED + 1280;
constexpr uint32_t SM_BAR = SM_BNC + 2304;
constexpr int BAR_FULL = 0, BAR_WEMPTY = NSTAGE, BAR_HW = BAR_WEMPTY + NS, BAR_STATS = BAR_HW + 1  ,
              BAR_EMB = BAR_STATS + 4, BAR_ACK = BAR_EMB + 1, BAR_X = BAR_ACK + 1  , NBAR = BAR_X + 5;
constexpr int SM_TOTAL = SM_BAR + NBAR * 8 - SMEM_BASE;
static_assert(SM_TOTAL <= 232448, "smem");
static_assert(NBAR <= 96, "barrier init");
constexpr int OUT_PITCH = 144;
__host__ __device__ constexpr uint32_t BAR(int i) { return SM_BAR + 8 * i; }
__host__ __device__ constexpr int ky_of(int kyo) { return kyo == 0 ? 1 : (kyo == 1 ? 0 : 2); }

constexpr unsigned SPIN_LIMIT = 1u << 16;

#define LS 1056
#define GS1 4
#define PD 0
struct Scratch {
    float acc1[NB * 4 * LS];
    float acc2[NB * LS];
    unsigned wcnt[3 * NB * LS];
    float emb[NXTRA * NB * C];
    unsigned char wt[2 * NSTAGE * STAGE_BYTES];
    uint4 box[NCTA * 1024];
};
__device__ __align__(1024) Scratch g_scratch;
#define TL(i) do {} while (0)
#define TLG(i) do {} while (0)

__device__ __forceinline__ unsigned clock32() { unsigned c; asm volatile("mov.u32 %0, %%clock;" : "=r"(c)); return c; }
__device__ __forceinline__ uint32_t mapa(uint32_t a, uint32_t rank) {
    uint32_t d;
    asm("mapa.shared::cluster.u32 %0, %1, %2;" : "=r"(d) : "r"(a), "r"(rank));
    return d;
}
#define S0 mapa(0, blockIdx.x & 1)
__device__ __forceinline__ void mbar_init(uint32_t bar, int cnt) {
    asm volatile("mbarrier.init.shared::cta.b64 [%0], %1;" ::"r"(bar + S0), "r"(cnt) : "memory");
}
__device__ __forceinline__ void mbar_arrive(uint32_t bar) {
    asm volatile("mbarrier.arrive.shared::cta.b64 _, [%0];" ::"r"(bar + S0) : "memory");
}
__device__ __forceinline__ void mbar_expect(uint32_t bar, uint32_t bytes) {
    asm volatile("mbarrier.arrive.expect_tx.shared::cta.b64 _, [%0], %1;" ::"r"(bar + S0), "r"(bytes) : "memory");
}
__device__ __forceinline__ bool mbar_try(uint32_t bar, uint32_t par) {
    uint32_t ok;
    asm volatile("{\n.reg .pred p;\nmbarrier.try_wait.parity.shared::cta.b64 p, [%1], %2;\nselp.u32 %0, 1, 0, p;\n}"
                 : "=r"(ok) : "r"(bar + S0), "r"(par) : "memory");
    return ok;
}
__device__ __forceinline__ bool mbar_test(uint32_t bar, uint32_t par) {
    uint32_t ok;
    asm volatile("{\n.reg .pred p;\nmbarrier.test_wait.parity.shared::cta.b64 p, [%1], %2;\nselp.u32 %0, 1, 0, p;\n}"
                 : "=r"(ok) : "r"(bar + S0), "r"(par) : "memory");
    return ok;
}
__device__ __forceinline__ void mbar_wait(uint32_t bar, uint32_t par) {
    unsigned it = 0;
#pragma unroll 1
    while (!mbar_try(bar, par) && ++it < SPIN_LIMIT) {}
}
__device__ __forceinline__ bool elect_one() {
    uint32_t p;
    asm volatile("{\n.reg .pred p;\nelect.sync _|p, 0xffffffff;\nselp.u32 %0, 1, 0, p;\n}" : "=r"(p));
    return p;
}
__device__ __forceinline__ void fence_async_smem() { asm volatile("fence.proxy.async.shared::cta;" ::: "memory"); }
__device__ __forceinline__ void fence_async_global() { asm volatile("fence.proxy.async.global;" ::: "memory"); }
__device__ __forceinline__ void fence_acquire() { asm volatile("fence.acquire.gpu;" ::: "memory"); }
__device__ __forceinline__ void bar_sync(int id, int n) { asm volatile("bar.sync %0, %1;" ::"r"(id), "r"(n) : "memory"); }
__device__ __forceinline__ void bar_arrive(int id, int n) { asm volatile("bar.arrive %0, %1;" ::"r"(id), "r"(n) : "memory"); }
__device__ __forceinline__ void bulk_g2s(uint32_t dst, const void* src, uint32_t bytes, uint32_t bar) {
    asm volatile("cp.async.bulk.shared::cluster.global.mbarrier::complete_tx::bytes [%0], [%1], %2, [%3];"
                 ::"r"(dst), "l"(src), "r"(bytes), "r"(bar) : "memory");
}
__device__ __forceinline__ void tma_x(uint32_t dst, const CUtensorMap* tm, int row, int ch, uint32_t bar) {
    asm volatile("cp.async.bulk.tensor.3d.shared::cluster.global.mbarrier::complete_tx::bytes [%0], [%1, {%2, %3, %4}], [%5];"
                 ::"r"(dst + S0), "l"(tm), "r"(0), "r"(row), "r"(ch), "r"(bar + S0) : "memory");
}
__device__ __forceinline__ uint4 ld_relaxed_v4(const void* p) {
    uint4 v;
    asm volatile("ld.relaxed.gpu.global.v4.u32 {%0,%1,%2,%3}, [%4];" : "=r"(v.x), "=r"(v.y), "=r"(v.z), "=r"(v.w) : "l"(p) : "memory");
    return v;
}
__device__ __forceinline__ unsigned ld_relaxed(const void* p) {
    unsigned v;
    asm volatile("ld.relaxed.gpu.global.u32 %0, [%1];" : "=r"(v) : "l"(p) : "memory");
    return v;
}
__device__ __forceinline__ void red_add4(float* p, float a, float b, float c, float d) {
    asm volatile("red.relaxed.gpu.global.add.v4.f32 [%0], {%1,%2,%3,%4};" ::"l"(p), "f"(a), "f"(b), "f"(c), "f"(d) : "memory");
}
__device__ __forceinline__ void sts128(uint32_t a, uint4 v) {
    asm volatile("st.shared.v4.u32 [%0], {%1,%2,%3,%4};" ::"r"(a + S0), "r"(v.x), "r"(v.y), "r"(v.z), "r"(v.w) : "memory");
}
__device__ __forceinline__ void sts128f(uint32_t a, float4 v) {
    asm volatile("st.shared.v4.f32 [%0], {%1,%2,%3,%4};" ::"r"(a + S0), "f"(v.x), "f"(v.y), "f"(v.z), "f"(v.w) : "memory");
}
__device__ __forceinline__ void sts32f(uint32_t a, float v) { asm volatile("st.shared.f32 [%0], %1;" ::"r"(a + S0), "f"(v) : "memory"); }
__device__ __forceinline__ uint4 lds128(uint32_t a) {
    uint4 v;
    asm volatile("ld.shared.v4.u32 {%0,%1,%2,%3}, [%4];" : "=r"(v.x), "=r"(v.y), "=r"(v.z), "=r"(v.w) : "r"(a + S0) : "memory");
    return v;
}
__device__ __forceinline__ float4 lds128f(uint32_t a) {
    float4 v;
    asm volatile("ld.shared.v4.f32 {%0,%1,%2,%3}, [%4];" : "=f"(v.x), "=f"(v.y), "=f"(v.z), "=f"(v.w) : "r"(a + S0) : "memory");
    return v;
}
__device__ __forceinline__ float2 lds64f(uint32_t a) {
    float2 v;
    asm volatile("ld.shared.v2.f32 {%0,%1}, [%2];" : "=f"(v.x), "=f"(v.y) : "r"(a + S0) : "memory");
    return v;
}
__device__ __forceinline__ float bf_lo(uint32_t u) { return __uint_as_float(u << 16); }
__device__ __forceinline__ float bf_hi(uint32_t u) { return __uint_as_float(u & 0xffff0000u); }
__device__ __forceinline__ uint32_t pack_bf(float lo, float hi) {
    uint32_t r;
    asm("cvt.rn.bf16x2.f32 %0, %1, %2;" : "=r"(r) : "f"(hi), "f"(lo));
    return r;
}
__device__ __forceinline__ float tanh_fast(float x) {
    float r;
    asm("tanh.approx.f32 %0, %1;" : "=f"(r) : "f"(x));
    return r;
}
__device__ __forceinline__ float silu_half(float h) { return fmaf(h, tanh_fast(h), h); }
__device__ __forceinline__ void ldsm4(uint32_t (&u)[4], uint32_t a) {
    asm volatile("ldmatrix.sync.aligned.m8n8.x4.shared.b16 {%0,%1,%2,%3}, [%4];"
                 : "=r"(u[0]), "=r"(u[1]), "=r"(u[2]), "=r"(u[3]) : "r"(a + S0) : "memory");
}
__device__ __forceinline__ void ldsm4t(uint32_t (&u)[4], uint32_t a) {
    asm volatile("ldmatrix.sync.aligned.m8n8.x4.trans.shared.b16 {%0,%1,%2,%3}, [%4];"
                 : "=r"(u[0]), "=r"(u[1]), "=r"(u[2]), "=r"(u[3]) : "r"(a + S0) : "memory");
}
__device__ __forceinline__ void stsm4(uint32_t a, uint32_t p0, uint32_t p1, uint32_t p2, uint32_t p3) {
    asm volatile("stmatrix.sync.aligned.m8n8.x4.shared.b16 [%0], {%1,%2,%3,%4};" ::"r"(a + S0), "r"(p0), "r"(p1), "r"(p2), "r"(p3) : "memory");
}
__device__ __forceinline__ void stsm4t(uint32_t a, uint32_t p0, uint32_t p1, uint32_t p2, uint32_t p3) {
    asm volatile("stmatrix.sync.aligned.m8n8.x4.trans.shared.b16 [%0], {%1,%2,%3,%4};" ::"r"(a + S0), "r"(p0), "r"(p1), "r"(p2), "r"(p3) : "memory");
}

#define R8(o) "+f"(d[o]), "+f"(d[o + 1]), "+f"(d[o + 2]), "+f"(d[o + 3]), "+f"(d[o + 4]), "+f"(d[o + 5]), "+f"(d[o + 6]), "+f"(d[o + 7])
template <uint32_t ALO, uint32_t BLO, uint64_t AHI = 8, uint64_t BHI = 48>
__device__ __forceinline__ void wgmma128(float (&d)[64]) {
    asm volatile(
        "wgmma.mma_async.sync.aligned.m64n128k16.f32.bf16.bf16 "
        "{%0,%1,%2,%3,%4,%5,%6,%7,%8,%9,%10,%11,%12,%13,%14,%15,%16,%17,%18,%19,%20,%21,%22,%23,%24,%25,%26,%27,%28,%29,%30,%31,"
        "%32,%33,%34,%35,%36,%37,%38,%39,%40,%41,%42,%43,%44,%45,%46,%47,%48,%49,%50,%51,%52,%53,%54,%55,%56,%57,%58,%59,%60,%61,%62,%63},"
        " %64, %65, 1, 1, 1, 0, 0;"
        : R8(0), R8(8), R8(16), R8(24), R8(32), R8(40), R8(48), R8(56)
        : "l"((AHI << 32) | ALO), "l"((BHI << 32) | BLO));
}
template <int S>
__device__ __forceinline__ void mma_stages(float (&d)[64], int conv, int tid, Scratch* gs) {
    constexpr uint32_t A = ((SM_ACT + S * 2 * CH_PITCH + 16) >> 4) | ((CH_PITCH >> 4) << 16);
    constexpr uint32_t B = (slot_addr(S % NS) >> 4) | (8u << 16);
    if (S == 0) mbar_wait(BAR(BAR_FULL), conv);
    bool next_ok = true;
    constexpr uint32_t NEXT = S + 1 < NSTAGE ? BAR(BAR_FULL + S + 1) : BAR(BAR_EMB);
    const int npar = S + 1 < NSTAGE ? conv : 0;
    next_ok = mbar_test(NEXT, npar);
    if (S == 0 && tid == 0) TL(32 + conv * 24);
    asm volatile("wgmma.fence.sync.aligned;" ::: "memory");
    wgmma128<A, B>(d);
    wgmma128<A + 1, B + 16>(d);
    wgmma128<A + 2, B + 32>(d);
    asm volatile("wgmma.commit_group.sync.aligned;" ::: "memory");
    if (S >= LAG) {
        asm volatile("wgmma.wait_group.sync.aligned %0;" ::"n"(LAG) : "memory");
        if ((tid & 31) == 0) mbar_arrive(BAR(BAR_WEMPTY + (S + NS - LAG) % NS));
    }
    if (!next_ok) mbar_wait(NEXT, npar);
    if constexpr (S + 1 < NSTAGE) mma_stages<S + 1>(d, conv, tid, gs);
}

__device__ __forceinline__ void weight_load(uint4 (&t)[5], const __nv_bfloat16* w, int cta, int lane) {
    const char* base = reinterpret_cast<const char*>(w) + ((cta & 15) * 8 * C + (cta >> 4) * 16) * 18;
#pragma unroll
    for (int k = 0; k < 5; k++) {
        const int i = lane + 32 * k, row = (i * 57) >> 10;
        if (k < 4 || lane < 16) t[k] = __ldg(reinterpret_cast<const uint4*>(base + row * (C * 18 - 288) + i * 16));
    }
}
template <bool READBACK>
__device__ __forceinline__ void weight_block(const uint4 (&t)[5], uint32_t bounce, unsigned char* wt, int cta, int lane) {
#pragma unroll
    for (int k = 0; k < 5; k++)
        if (k < 4 || lane < 16) sts128(bounce + (lane + 32 * k) * 16, t[k]);
    __syncwarp();
    unsigned char* dst = wt + (cta >> 4) * STAGE_BYTES + (cta & 15) * 768;
    if (lane < 16) {
        uint32_t v[36];
#pragma unroll
        for (int i = 0; i < 9; i++) {
            const uint4 q = lds128(bounce + (lane & 7) * 288 + (lane >> 3) * 144 + i * 16);
            v[4 * i] = q.x; v[4 * i + 1] = q.y; v[4 * i + 2] = q.z; v[4 * i + 3] = q.w;
        }
#pragma unroll
        for (int kyo = 0; kyo < 3; kyo++) {
#pragma unroll
            for (int kx = 0; kx < 3; kx++) {
                const int tap = ky_of(kyo) * 3 + kx;
                uint32_t o[4];
#pragma unroll
                for (int m = 0; m < 4; m++) {
                    const int i0 = 18 * m + tap, i1 = i0 + 9;
                    const uint32_t sel = ((i0 & 1) ? 0x32u : 0x10u) | ((i1 & 1) ? 0x7600u : 0x5400u);
                    o[m] = __byte_perm(v[i0 >> 1], v[i1 >> 1], sel);
                }
                *reinterpret_cast<uint4*>(dst + kyo * 8 * STAGE_BYTES + kx * 256 + lane * 16) = make_uint4(o[0], o[1], o[2], o[3]);
            }
        }
    }
    if (READBACK) {
        __syncwarp();
        unsigned acc = 0;
        if (lane < 24) {
#pragma unroll
            for (int i = 0; i < 3; i++) acc |= ld_relaxed(dst + i * 8 * STAGE_BYTES + lane * 32);
        }
        asm volatile("{\n.reg .pred p;\nsetp.eq.u32 p, %0, 0x9e3779b9;\n@p st.shared.u32 [%1], %0;\n}" ::"r"(acc), "r"(bounce + S0) : "memory");
    }
}
__device__ __forceinline__ uint32_t act2(uint32_t u, const float4& cf) {
    return pack_bf(silu_half(fmaf(bf_lo(u), cf.x, cf.z)), silu_half(fmaf(bf_hi(u), cf.y, cf.w)));
}
__device__ __forceinline__ void norm_unit(uint32_t (&u)[4], const float4& ca, const float4& cb) {
    u[0] = act2(u[0], ca); u[1] = act2(u[1], ca); u[2] = act2(u[2], cb); u[3] = act2(u[3], cb);
}
template <int FIRST, int N>
__device__ __forceinline__ void norm_block(uint32_t (&u)[4][4], float4 (&cf)[8], bool load_cf, uint32_t cfa, uint32_t act, uint32_t mask, uint32_t fbar, int lane) {
    if (load_cf) {
#pragma unroll
        for (int i = 2 * FIRST; i < 2 * (FIRST + N); i++) cf[i] = lds128f(cfa + (i >> 1) * 256 + (i & 1) * 64);
    }
#pragma unroll
    for (int t = FIRST; t < FIRST + N; t++) {
        norm_unit(u[t], cf[2 * t], cf[2 * t + 1]);
        stsm4(act + t * 2 * KC_BYTES, u[t][0] & mask, u[t][1] & mask, u[t][2] & mask, u[t][3] & mask);
    }
    fence_async_smem();
    __syncwarp();
    if (lane < N) mbar_arrive(fbar + 16 * (FIRST + lane));
}
__device__ __forceinline__ void stat_mma(float (&c)[4], uint32_t p, uint32_t q) {
    asm("mma.sync.aligned.m16n8k16.row.col.f32.bf16.bf16.f32 {%0,%1,%2,%3}, {%4,%5,%6,%5}, {%4,%6}, {%0,%1,%2,%3};"
        : "+f"(c[0]), "+f"(c[1]), "+f"(c[2]), "+f"(c[3]) : "r"(p), "r"(0x3f803f80u), "r"(q));
}
__device__ __forceinline__ void stat_store(const float (&c)[4], uint32_t dst, int lane) {
    const int g = lane >> 2, t = lane & 3;
    if (t == (g >> 1)) sts32f(dst + g * 4, (g & 1) ? c[1] : c[0]);
    if (g == 7) sts32f(dst + 32 + t * 4, c[2] + c[3]);
}
__device__ __forceinline__ float sum4(float4 v) { return (v.x + v.y) + (v.z + v.w); }
__device__ __forceinline__ void stat_publish(uint32_t src, float* acc, int lane, bool real) {
    const uint32_t a = src + (lane & 15) * 48;
    float q = sum4(lds128f(a)) + sum4(lds128f(a + 16)), sm = sum4(lds128f(a + 32));
    q += __shfl_xor_sync(0xffffffffu, q, 1); sm += __shfl_xor_sync(0xffffffffu, sm, 1);
    q += __shfl_xor_sync(0xffffffffu, q, 2); sm += __shfl_xor_sync(0xffffffffu, sm, 2);
    if (real && (lane & 19) == 0) red_add4(acc + lane, 1.f, sm, q, 1.f);
}
__device__ __forceinline__ void fence_acc(float (&d)[64]) {
#pragma unroll
    for (int i = 0; i < 64; i++) asm volatile("" : "+f"(d[i])::"memory");
}
__device__ __forceinline__ void ld_unit(uint32_t (&u)[4], const uint4* p) {
    asm volatile("ld.relaxed.gpu.global.v4.u32 {%0,%1,%2,%3}, [%4];" : "=r"(u[0]), "=r"(u[1]), "=r"(u[2]), "=r"(u[3]) : "l"(p) : "memory");
}

__device__ __noinline__ void side_jobs(const __nv_bfloat16* __restrict__ t_emb, const __nv_bfloat16* __restrict__ w_emb,
                                       const __nv_bfloat16* __restrict__ w2, Scratch* __restrict__ gs, unsigned clk0) {
    const int tid = threadIdx.x, warp = tid >> 5, lane = tid & 31, j = blockIdx.x;
    float tv = 0.f;
    if (lane < 24) tv = __bfloat162float(t_emb[(lane / 12) * E + j * 192 + warp * 12 + lane % 12]);
    if (tid == 0) {
        mbar_init(BAR(0), 1);
        mbar_expect(BAR(0), 192 * C * 2);
        fence_async_smem();
        while (clock32() - clk0 < W2DELAY) {}
#pragma unroll
        for (int i = 0; i < 4; i++) bulk_g2s(S0 + SM_W + i * 12288, w_emb + (j * 192 + i * 48) * C, 12288, S0 + BAR(0));
#pragma unroll
        for (int i = 0; i < 4; i++)
            asm volatile("cp.async.bulk.prefetch.L2.global [%0], 18432;" ::"l"(reinterpret_cast<const char*>(w2) + (j * 4 + i) * 18432) : "memory");
    }
    if (j == 0 && tid < 32) gs->acc2[(tid >> 4) * LS + (tid & 15)] = 0.f;
    const float sv = silu_half(0.5f * tv);
    __syncthreads();
    mbar_wait(BAR(0), 0);
    float acc[8] = {0.f, 0.f, 0.f, 0.f, 0.f, 0.f, 0.f, 0.f};
#pragma unroll
    for (int i = 0; i < 12; i++) {
        const float2 wq = lds64f(SM_W + (warp * 12 + i) * 256 + lane * 8);
        const uint32_t wx = __float_as_uint(wq.x), wy = __float_as_uint(wq.y);
#pragma unroll
        for (int bb = 0; bb < 2; bb++) {
            const float sx = __shfl_sync(0xffffffffu, sv, bb * 12 + i);
            acc[4 * bb + 0] = fmaf(sx, bf_lo(wx), acc[4 * bb + 0]); acc[4 * bb + 1] = fmaf(sx, bf_hi(wx), acc[4 * bb + 1]);
            acc[4 * bb + 2] = fmaf(sx, bf_lo(wy), acc[4 * bb + 2]); acc[4 * bb + 3] = fmaf(sx, bf_hi(wy), acc[4 * bb + 3]);
        }
    }
    sts128f(SM_ACT + warp * 1024 + lane * 16, make_float4(acc[0], acc[1], acc[2], acc[3]));
    sts128f(SM_ACT + warp * 1024 + 512 + lane * 16, make_float4(acc[4], acc[5], acc[6], acc[7]));
    __syncthreads();
    if (tid < 128) {
        float2 sum = make_float2(0.f, 0.f);
#pragma unroll
        for (int w = 0; w < 16; w++) { const float2 p = lds64f(SM_ACT + w * 1024 + tid * 8); sum.x += p.x; sum.y += p.y; }
        *reinterpret_cast<float2*>(&gs->emb[j * NB * C + tid * 2]) = sum;
        bar_sync(1, 128);
        if (tid < 2) asm volatile("red.release.gpu.global.add.u32 [%0], 1;" ::"l"(&gs->wcnt[(2 * NB + tid) * LS]) : "memory");
    }
}

__global__ void __cluster_dims__(2, 1, 1) __launch_bounds__(NTHREADS, 1)
resblock_kernel(const __nv_bfloat16* __restrict__ w1,
                const __nv_bfloat16* __restrict__ t_emb, const __nv_bfloat16* __restrict__ g1,
                const __nv_bfloat16* __restrict__ be1, const __nv_bfloat16* __restrict__ w_emb,
                const __nv_bfloat16* __restrict__ g2, const __nv_bfloat16* __restrict__ be2,
                const __nv_bfloat16* __restrict__ w2, __nv_bfloat16* __restrict__ out, Scratch* __restrict__ gs,
                const __grid_constant__ CUtensorMap xmap) {
    const unsigned clk0 = clock32();
    if (threadIdx.x == 480 && blockIdx.x >= NXTRA) TLG(1);
    const int tid = threadIdx.x, warp = __shfl_sync(0xffffffffu, tid >> 5, 0), lane = tid & 31;
    const int cta = blockIdx.x - NXTRA, b = cta >> 6, r = cta & 63;
    if (cta < 0) { side_jobs(t_emb, w_emb, w2, gs, clk0); return; }

    const int seg = lane & 7;
    uint4 v[5];
    if (warp == 0) {
        weight_load(v, w1, cta, lane);
    }
    if (warp != 3) asm volatile("barrier.cluster.arrive.relaxed.aligned;" ::: "memory");
    const bool has_outer = (r != 0) && (r != HW - 1);
    if (warp == 1 || warp == 2 || warp == 4 || warp == 5) {
        const int g = warp < 3 ? warp - 1 : 7 - warp;
        if (elect_one()) {
            asm volatile("prefetch.tensormap [%0];" ::"l"(&xmap) : "memory");
            mbar_init(BAR(BAR_X) + 8 * g, 1);
            if (g == 3) mbar_init(BAR(BAR_X + 4), 1);
            mbar_expect(BAR(BAR_X) + 8 * g, 4096);
            fence_async_smem();
            while (clock32() - clk0 < XDELAY + g * XSTAG) {}
            tma_x(SM_XOWN + g * 4096, &xmap, r, b * C + g * 32, BAR(BAR_X) + 8 * g);
            if (g == 3 && has_outer) {
                mbar_expect(BAR(BAR_X + 4), 16384);
#pragma unroll
                for (int i = 0; i < 4; i++) tma_x(SM_XOUT + i * 4096, &xmap, r + ((r & 1) ? 1 : -1), b * C + i * 32, BAR(BAR_X + 4));
            }
        }
        __syncwarp();
        bar_arrive(4, 256 + 32 + 128);
        mbar_wait(BAR(BAR_X) + 8 * g, 0);
        if (lane == 0) TL(70 + g);
        float c[2][4] = {{0.f, 0.f, 0.f, 0.f}, {0.f, 0.f, 0.f, 0.f}};
#pragma unroll
        for (int k = 0; k < 8; k++) {
            const uint4 q = lds128(SM_XOWN + g * 4096 + k * 512 + lane * 16);
            stat_mma(c[0], q.x, q.y); stat_mma(c[1], q.z, q.w);
        }
#pragma unroll
        for (int i = 0; i < 4; i++) c[0][i] += c[1][i];
        stat_store(c[0], SM_RED + g * 48, lane);
        __syncwarp();
        if (lane == 0) {
            const uint32_t a = SM_RED + g * 48;
            red_add4(&gs->acc1[b * 4 * LS + g * GS1], 1.f, sum4(lds128f(a + 32)), sum4(lds128f(a)) + sum4(lds128f(a + 16)), 1.f);
            TL(74 + g);
        }
    }
    if (warp == 0) {
        weight_block<RB>(v, SM_BNC, gs->wt, cta, lane);
        __syncwarp();
        if (lane == 0) TL(4);
        if (lane < 2) asm volatile("red.relaxed.gpu.global.add.u32 [%0], 1;" ::"l"(&gs->wcnt[lane * LS]) : "memory");
        if (lane == 0) TL(5);
    }

    if (warp >= 8) {
        const int nw = warp - 8;
        bar_sync(4, 256 + 32 + 128);
        const int par = nw >> 2, wq = nw & 3;
        const uint32_t act_off = SM_ACT + (par * 2 + (lane >> 4)) * CH_PITCH + (2 + wq * 16 + (lane & 15)) * 16;
        const uint32_t stg_off = (par * 16 + (lane >> 4) * 8 + (lane & 7)) * 128 + (((2 * wq + ((lane >> 3) & 1)) ^ (lane & 7)) << 4);
        const uint32_t cfa = SM_COEF + par * 128 + (lane & 3) * 16;
        const uint32_t fbar = BAR(BAR_FULL) + 8 * par;
        uint4* inbox = gs->box + cta * 1024 + nw * 32 + lane;
#pragma unroll 1
        for (int conv = 0; conv < 2; conv++) {
            uint32_t u[4][4], w[4][4];
            float4 cf[8];
            if (conv == 0) {
                mbar_wait(BAR(BAR_X), 0); ldsm4t(u[0], SM_XOWN + stg_off);
                mbar_wait(BAR(BAR_X + 1), 0); ldsm4t(u[1], SM_XOWN + stg_off + 4096);
                mbar_wait(BAR(BAR_STATS), 0);
                if (tid == 256) TL(22);
                norm_block<0, 1>(u, cf, true, cfa, act_off, ~0u, fbar, lane);
                if (tid == 256) TL(8);
                mbar_wait(BAR(BAR_X + 2), 0); ldsm4t(u[2], SM_XOWN + stg_off + 8192);
                mbar_wait(BAR(BAR_STATS + 1), 0);
                norm_block<1, 1>(u, cf, true, cfa, act_off, ~0u, fbar, lane);
                mbar_wait(BAR(BAR_X + 3), 0); ldsm4t(u[3], SM_XOWN + stg_off + 12288);
                mbar_wait(BAR(BAR_STATS + 2), 0);
                norm_block<2, 1>(u, cf, true, cfa, act_off, ~0u, fbar, lane);
                mbar_wait(BAR(BAR_STATS + 3), 0);
                norm_block<3, 1>(u, cf, true, cfa, act_off, ~0u, fbar, lane);
                if (has_outer) {
                    mbar_wait(BAR(BAR_X + 4), 0);
#pragma unroll
                    for (int i = 0; i < 4; i++) ldsm4t(w[i], SM_XOUT + stg_off + i * 4096);
                }
                bar_sync(3, 256);
                if (nw == 0) sts128(SM_ACT + 2 * ROW_BYTES + (lane >> 1) * CH_PITCH + (lane & 1) * 16, make_uint4(0, 0, 0, 0));
            } else {
                mbar_wait(BAR(BAR_HW), 0);
#pragma unroll
                for (int i = 0; i < 4; i++) ldsm4(u[i], act_off + i * 2 * KC_BYTES);
                mbar_wait(BAR(BAR_STATS + 1), 1);
                mbar_wait(BAR(BAR_STATS), 1);
                if (tid == 256) TL(26);
                norm_block<0, 2>(u, cf, true, cfa, act_off, ~0u, fbar, lane);
                if (tid == 256) TL(16);
                mbar_wait(BAR(BAR_STATS + 2), 1);
                mbar_wait(BAR(BAR_STATS + 3), 1);
                norm_block<2, 2>(u, cf, true, cfa, act_off, ~0u, fbar, lane);
            }
            if (tid == 256) TL(84 + conv);
            if (conv == 1 && has_outer) {
                unsigned it = 0;
                while (ld_relaxed(inbox + 3 * 256 + 31 - lane) == 0 && ++it < SPIN_LIMIT) {}
                if (tid == 256) TL(89);
                while (true) {
#pragma unroll
                    for (int i = 0; i < 4; i++) ld_unit(w[i], inbox + i * 256);
                    bool ok = true;
#pragma unroll
                    for (int i = 0; i < 16; i++) ok = ok && w[i >> 2][i & 3] != 0;
                    if (__all_sync(0xffffffffu, ok) || ++it > SPIN_LIMIT) break;
                }
#pragma unroll
                for (int i = 0; i < 16; i++) w[i >> 2][i & 3] = ~w[i >> 2][i & 3];
            }
            if (tid == 256) TL(24 + conv * 4);
            norm_block<0, 4>(w, cf, false, cfa, act_off + 2 * ROW_BYTES, has_outer ? ~0u : 0u, fbar + 128, lane);
            if (tid == 256) TL(23 + conv * 4);
        }
        if (has_outer) {
            mbar_wait(BAR(BAR_FULL + NSTAGE - 1), 1);
#pragma unroll
            for (int i = 0; i < 4; i++) inbox[i * 256] = make_uint4(0, 0, 0, 0);
        }
    } else if (warp < 4) {
        const int wq = warp;
        if (wq == 3) {
            if (elect_one()) {
#pragma unroll
                for (int i = 0; i < NSTAGE; i++) mbar_init(BAR(BAR_FULL + i), (i >> 3) == 1 ? 1 : 5);
#pragma unroll
                for (int i = 0; i <= NS; i++) mbar_init(BAR(BAR_WEMPTY + i), 4);
#pragma unroll
                for (int i = BAR_STATS; i < BAR_X; i++) mbar_init(BAR(i), i == BAR_EMB ? 3 : 1);
                asm volatile("fence.mbarrier_init.release.cluster;" ::: "memory");
            }
            __syncwarp();
            fence_async_smem();
            bar_arrive(0, 96);
            bar_arrive(5, 96);
            bar_arrive(4, 256 + 32 + 128);
            const uint4 z = make_uint4(0, 0, 0, 0);
#pragma unroll
            for (int i = 0; i < 2; i++) sts128(SM_ACT + (i * 16 + (lane >> 1)) * CH_PITCH + (lane & 1) * 16, z);
            if (lane < 4) sts128(SM_ACT + (2 + (lane >> 1)) * ROW_BYTES + (lane & 1) * 16, z);
            if (lane < 16) sts128(SM_ONES + lane * 16, make_uint4(lane < 8 ? 0x3f803f80u : 0u, 0, 0, 0));
            fence_async_smem();
            asm volatile("barrier.cluster.arrive.release.aligned;" ::: "memory");
        }
        bar_sync(2, 128);

        float d[64];
#pragma unroll
        for (int i = 0; i < 64; i++) d[i] = 0.f;
#pragma unroll 1
        for (int conv = 0; conv < 2; conv++) {
            fence_acc(d);
            mma_stages<0>(d, conv, tid, gs);
            if (conv == 0) {
                asm volatile("wgmma.fence.sync.aligned;" ::: "memory");
                wgmma128<(SM_ONES >> 4) | (8u << 16), (SM_EMB >> 4), 0, 8>(d);
                asm volatile("wgmma.commit_group.sync.aligned;" ::: "memory");
            }
            asm volatile("wgmma.wait_group.sync.aligned 0;" ::: "memory");
            fence_acc(d);
            if (tid == 0) TL(10 + conv * 8);
            if (conv == 1) break;

            uint32_t hp[32];
#pragma unroll
            for (int g = 0; g < 4; g++) {
                float c[4] = {0.f, 0.f, 0.f, 0.f};
#pragma unroll
                for (int i = 0; i < 8; i++) hp[8 * g + i] = pack_bf(d[16 * g + 2 * i], d[16 * g + 2 * i + 1]);
#pragma unroll
                for (int i = 0; i < 4; i++) stat_mma(c, hp[8 * g + 2 * i], hp[8 * g + 2 * i + 1]);
                stat_store(c, SM_RED + (g * 4 + wq) * 48, lane);
            }
            bar_sync(2, 128);
            if (wq == 0) stat_publish(SM_RED, &gs->acc2[b * LS], lane, true);
            if (tid == 0) TL(11);
            const uint32_t hbase = SM_ACT + (lane >> 4) * CH_PITCH + (2 + wq * 16 + (lane & 15)) * 16;
#pragma unroll
            for (int kc = 0; kc < 8; kc++) stsm4(hbase + kc * 2 * CH_PITCH, hp[4 * kc], hp[4 * kc + 1], hp[4 * kc + 2], hp[4 * kc + 3]);
            __syncwarp();
            if (lane == 0) mbar_arrive(BAR(BAR_HW));
            if (lane < LAG) mbar_arrive(BAR(BAR_WEMPTY + (NSTAGE - LAG) % NS) + 8 * lane);
            if (has_outer) {
                uint4* outbox = gs->box + (cta + ((r & 1) ? 1 : -1)) * 1024 + tid;
#pragma unroll
                for (int kc = 0; kc < 8; kc++) outbox[kc * 128] = make_uint4(~hp[4 * kc], ~hp[4 * kc + 1], ~hp[4 * kc + 2], ~hp[4 * kc + 3]);
            }
            if (tid == 0) TL(12);
            const uint32_t xbase = SM_XOWN + ((lane >> 4) * 8 + (lane & 7)) * 128 + (((2 * wq + ((lane >> 3) & 1)) ^ (lane & 7)) << 4);
#pragma unroll
            for (int kc = 0; kc < 8; kc++) {
                uint32_t p[4];
                ldsm4t(p, xbase + kc * 2048);
#pragma unroll
                for (int i = 0; i < 4; i++) { d[8 * kc + 2 * i] = bf_lo(p[i]); d[8 * kc + 2 * i + 1] = bf_hi(p[i]); }
            }
        }
        {
            const uint32_t obase = slot_addr(0) + ((lane >> 4) * 8 + (lane & 7)) * OUT_PITCH + (wq * 16 + ((lane >> 3) & 1) * 8) * 2;
#pragma unroll
            for (int kc = 0; kc < 8; kc++) {
                stsm4t(obase + kc * 16 * OUT_PITCH, pack_bf(d[8 * kc + 0], d[8 * kc + 1]), pack_bf(d[8 * kc + 2], d[8 * kc + 3]),
                       pack_bf(d[8 * kc + 4], d[8 * kc + 5]), pack_bf(d[8 * kc + 6], d[8 * kc + 7]));
            }
            bar_sync(2, 128);
            const int oc0 = tid >> 3;
            __nv_bfloat16* dst = out + ((size_t)(b * C + oc0) * HW + r) * HW + seg * 8;
#pragma unroll
            for (int i = 0; i < 8; i++)
                *reinterpret_cast<uint4*>(dst + (size_t)i * 16 * HW * HW) = lds128(slot_addr(0) + (oc0 + 16 * i) * OUT_PITCH + seg * 16);
            if (tid == 0) { TL(20); TLG(21); }
        }
    } else if (warp < 6) {
        bar_sync(5, 96);
        if (warp == 5) {
            asm volatile("barrier.cluster.wait.acquire.aligned;" ::: "memory");
            const uint32_t peer = (r & 1) ^ 1;
            const uint32_t self0 = mapa(0, r & 1), peer0 = mapa(0, peer);
#pragma unroll 1
            for (int conv = 0; conv < 2; conv++) {
#pragma unroll 1
                for (int kc = 0; kc < 8; kc++) {
                    mbar_wait(BAR(BAR_FULL) + 8 * kc, conv);
                    if (elect_one())
                        asm volatile("cp.async.bulk.shared::cluster.shared::cta.mbarrier::complete_tx::bytes [%0], [%1], %2, [%3];"
                                     ::"r"(peer0 + SM_ACT + ROW_BYTES + kc * KC_BYTES), "r"(self0 + SM_ACT + kc * KC_BYTES), "r"(KC_BYTES),
                                       "r"(peer0 + BAR(BAR_FULL + 8) + 8 * kc) : "memory");
                }
                if (lane == 0) TL(86 + conv);
#pragma unroll 1
                for (int kc = 0; kc < 8; kc++) mbar_wait(BAR(BAR_FULL + 8) + 8 * kc, conv);
                if (lane == 0)
                    asm volatile("mbarrier.arrive.release.cluster.shared::cluster.b64 _, [%0];" ::"r"(peer0 + (conv ? BAR(BAR_ACK) : BAR(BAR_EMB))) : "memory");
            }
            mbar_wait(BAR(BAR_ACK), 0);
        } else {
            mbar_wait(BAR(BAR_STATS + 3), 0);
            weight_load(v, w2, cta, lane);
            weight_block<false>(v, SM_BNC, gs->wt + NSTAGE * STAGE_BYTES, cta, lane);
            __syncwarp();
            if (lane == 0) TL(13);
            if (lane < 2) asm volatile("red.release.gpu.global.add.u32 [%0], 1;" ::"l"(&gs->wcnt[(NB + lane) * LS]) : "memory");
            if (lane == 0) TL(14);
            unsigned it = 0;
            while (ld_relaxed(&gs->wcnt[(2 * NB + b) * LS]) < (unsigned)NXTRA && ++it < SPIN_LIMIT) __nanosleep(100);
            fence_acquire();
            float ev[4] = {0.f, 0.f, 0.f, 0.f};
#pragma unroll
            for (int j = 0; j < NXTRA; j++) {
                const uint4 ef = ld_relaxed_v4(&gs->emb[(j * NB + b) * C + lane * 4]);
                ev[0] += __uint_as_float(ef.x); ev[1] += __uint_as_float(ef.y); ev[2] += __uint_as_float(ef.z); ev[3] += __uint_as_float(ef.w);
            }
#pragma unroll
            for (int i = 0; i < 4; i++) {
                const float hi = bf_lo(pack_bf(ev[i], 0.f));
                sts128(SM_EMB + (lane * 4 + i) * 16, make_uint4(pack_bf(hi, ev[i] - hi), 0, 0, 0));
            }
            fence_async_smem();
            __syncwarp();
            if (lane == 0) { mbar_arrive(BAR(BAR_EMB)); TL(19); }
        }
    } else if (warp == 6) {
        bar_sync(0, 96);
        const uint32_t ebytes = STAGE_BYTES + ((lane >> 3) == 1 ? KC_BYTES : 0);
        if (lane < NSTAGE) mbar_expect(BAR(BAR_FULL) + 8 * lane, ebytes);
        const int swap = (r & 1) ? 0 : 8 * STAGE_BYTES;
        const unsigned char* wsrc = gs->wt;
        uint32_t dst = S0 + SM_W, full = S0 + BAR(BAR_FULL), empty = BAR(BAR_WEMPTY);
        unsigned it = 0;
        while (clock32() - clk0 < PD) {}
        while (ld_relaxed(&gs->wcnt[b * LS]) < (unsigned)NCTA && ++it < SPIN_LIMIT) {}
        fence_acquire();
        fence_async_global();
        if (lane == 0) TL(6);
#pragma unroll 1
        for (int g = 0; g < 2 * NSTAGE; g++) {
            if (g >= NS) {
                mbar_wait(empty, ((g - NS) / NS) & 1);
                if (g == NSTAGE) {
                    it = 0;
                    while (ld_relaxed(&gs->wcnt[(NB + b) * LS]) < (unsigned)NCTA && ++it < SPIN_LIMIT) {}
                    fence_acquire();
                    fence_async_global();
                    if (lane == 0) { mbar_arrive(BAR(BAR_EMB)); TL(2); }
                }
                if (g == NSTAGE || g == NSTAGE + NS) {
                    if (lane >= g - NSTAGE && lane < g - NSTAGE + NS) mbar_expect(BAR(BAR_FULL) + 8 * lane, ebytes);
                    __syncwarp();
                }
            }
            if (elect_one()) bulk_g2s(dst, wsrc, STAGE_BYTES, full);
            wsrc += STAGE_BYTES; dst += STAGE_BYTES; full += 8; empty += 8;
            const int st = (g >= NSTAGE ? g - NSTAGE : g) + 1;
            if (st == 8 || st == NSTAGE) wsrc += swap;
            if (st == 16) wsrc -= 2 * swap;
            if (st == NS || st == NSTAGE) { dst -= NS * STAGE_BYTES; empty -= 8 * NS; }
            if (st == NSTAGE) full -= 8 * NSTAGE;
        }
    } else {
        const uint2 ga1 = __ldg(reinterpret_cast<const uint2*>(g1) + lane), bt1 = __ldg(reinterpret_cast<const uint2*>(be1) + lane);
        const uint2 ga2 = __ldg(reinterpret_cast<const uint2*>(g2) + lane), bt2 = __ldg(reinterpret_cast<const uint2*>(be2) + lane);
        bar_sync(0, 96);
#pragma unroll 1
        for (int conv = 0; conv < 2; conv++) {
            if (conv == 1) mbar_wait(BAR(BAR_EMB), 0);
            const float* asrc = conv ? &gs->acc2[b * LS + (lane >> 3) * 4] : &gs->acc1[b * 4 * LS + (lane >> 3) * GS1];
            while (clock32() - clk0 < PD) {}
            const uint2 ga = conv ? ga2 : ga1, bt = conv ? bt2 : bt1;
            bool done = false;
            unsigned it = 0;
#pragma unroll 1
            while (true) {
                const uint4 f = ld_relaxed_v4(asrc);
                const bool fresh = !done && (((f.x == 0x42800000u) & (f.w == 0x42800000u)) || it > SPIN_LIMIT);
                it++;
                if (!__any_sync(0xffffffffu, fresh)) continue;
                if (lane == 0 && fresh) TL(7 + conv * 8);
                if (lane == 24 && fresh) TL(90 + conv);
                const float inv_n = 1.0f / (32.0f * HW * HW);
                const float mean = __uint_as_float(f.y) * inv_n;
                const float var = fmaxf(fmaf(-mean, mean, __uint_as_float(f.z) * inv_n), 0.f);
                const float rs = 0.5f * rsqrtf(var + 1e-5f);
                float4 k0, k1;
                k0.x = rs * bf_lo(ga.x); k0.y = rs * bf_hi(ga.x); k1.x = rs * bf_lo(ga.y); k1.y = rs * bf_hi(ga.y);
                k0.z = fmaf(-mean, k0.x, 0.5f * bf_lo(bt.x)); k0.w = fmaf(-mean, k0.y, 0.5f * bf_hi(bt.x));
                k1.z = fmaf(-mean, k1.x, 0.5f * bf_lo(bt.y)); k1.w = fmaf(-mean, k1.y, 0.5f * bf_hi(bt.y));
                if (fresh) {
                    sts128f(SM_COEF + lane * 32, k0);
                    sts128f(SM_COEF + lane * 32 + 16, k1);
                }
                __syncwarp();
                if (fresh && (lane & 7) == 0) mbar_arrive(BAR(BAR_STATS) + lane);
                done = done || fresh;
                if (__all_sync(0xffffffffu, done)) break;
            }
        }
        if (r == 0) {
            if (lane < 16) gs->acc1[b * 4 * LS + (lane >> 2) * GS1 + (lane & 3)] = 0.f;
            if (lane < 3) gs->wcnt[(lane * NB + b) * LS] = 0;
        }
    }
}

}

extern "C" void kernel_launch(void* const* d_in, const int* in_sizes, int n_in, void* d_out, int out_size) {
    (void)in_sizes; (void)n_in; (void)out_size;
    typedef CUresult (*EncodeFn)(CUtensorMap*, CUtensorMapDataType, cuuint32_t, void*, const cuuint64_t*, const cuuint64_t*,
                                 const cuuint32_t*, const cuuint32_t*, CUtensorMapInterleave, CUtensorMapSwizzle,
                                 CUtensorMapL2promotion, CUtensorMapFloatOOBfill);
    static Scratch* gs = nullptr;
    static EncodeFn encode = nullptr;
    if (!gs) {
        cudaFuncSetAttribute(resblock_kernel, cudaFuncAttributeMaxDynamicSharedMemorySize, SM_TOTAL);
        cudaGetSymbolAddress((void**)&gs, g_scratch);
        cudaDriverEntryPointQueryResult qr;
        cudaGetDriverEntryPoint("cuTensorMapEncodeTiled", (void**)&encode, cudaEnableDefault, &qr);
    }
    CUtensorMap xmap;
    const cuuint64_t dims[3] = {HW, HW, NB * C}, strides[2] = {HW * 2, HW * HW * 2};
    const cuuint32_t box[3] = {HW, 1, 32}, es[3] = {1, 1, 1};
    encode(&xmap, CU_TENSOR_MAP_DATA_TYPE_BFLOAT16, 3, d_in[0], dims, strides, box, es, CU_TENSOR_MAP_INTERLEAVE_NONE,
           CU_TENSOR_MAP_SWIZZLE_128B, CU_TENSOR_MAP_L2_PROMOTION_NONE, CU_TENSOR_MAP_FLOAT_OOB_FILL_NONE);
    resblock_kernel<<<NCTA + NXTRA, NTHREADS, SM_TOTAL>>>(
        (const __nv_bfloat16*)d_in[4], (const __nv_bfloat16*)d_in[1],
        (const __nv_bfloat16*)d_in[2], (const __nv_bfloat16*)d_in[3], (const __nv_bfloat16*)d_in[5],
        (const __nv_bfloat16*)d_in[6], (const __nv_bfloat16*)d_in[7], (const __nv_bfloat16*)d_in[8],
        (__nv_bfloat16*)d_out, gs, xmap);
}
```

```cpp
#include <cuda_runtime.h>
#include <cuda.h>
#include <cuda_bf16.h>
#include <stdint.h>

namespace {

constexpr int C = 128, HW = 64, NB = 2, E = 768;
constexpr int NCTA = NB * HW;
constexpr int NXTRA = 4;
constexpr int NTHREADS = 16 * 32;
constexpr int CH_PITCH = 66 * 16;
constexpr int ROW_BYTES = 16 * CH_PITCH;
constexpr int STEP_BYTES = 4096;
constexpr int STAGE_BYTES = 3 * STEP_BYTES;
constexpr int NSTAGE = 24;
constexpr int KC_BYTES = 2 * CH_PITCH;
constexpr int NS = 12;
constexpr int LAG = 1;
#define XDELAY 500
#define HDELAY 600
#define NA 2
#define RB 1
#define XSTAG 400
#define HSEND 0
#define W2DELAY 2000

constexpr uint32_t SMEM_BASE = 0x400;
constexpr uint32_t SM_XOWN = SMEM_BASE;
constexpr uint32_t SM_ACT = SM_XOWN + 16384 + 512;
constexpr uint32_t SM_XOUT = SM_ACT + 2 * ROW_BYTES + 512;
static_assert(SM_XOUT % 1024 == 0, "swizzle atom alignment");
constexpr uint32_t SM_W = SM_ACT + 3 * ROW_BYTES + 128;
__host__ __device__ constexpr uint32_t slot_addr(int slot) { return SM_W + slot * STAGE_BYTES; }
constexpr uint32_t SM_COEF = SM_W + NS * STAGE_BYTES;
constexpr uint32_t SM_EMB = SM_COEF + 1024;
constexpr uint32_t SM_ONES = SM_EMB + 2048;
constexpr uint32_t SM_RED = SM_ONES + 256;
constexpr uint32_t SM_BNC = SM_RED + 1280;
constexpr uint32_t SM_BAR = SM_BNC + 2 * 2304;
constexpr int BAR_FULL = 0, BAR_WEMPTY = NSTAGE, BAR_HW = BAR_WEMPTY + NS, BAR_STATS = BAR_HW + 1  ,
              BAR_EMB = BAR_STATS + 4, BAR_ACK = BAR_EMB + 1, BAR_W2 = BAR_ACK + 1, BAR_X = BAR_W2 + 1  , NBAR = BAR_X + 5;
constexpr int SM_TOTAL = SM_BAR + NBAR * 8 - SMEM_BASE;
static_assert(SM_TOTAL <= 232448, "smem");
static_assert(NBAR <= 96, "barrier init");
constexpr int OUT_PITCH = 144;
__host__ __device__ constexpr uint32_t BAR(int i) { return SM_BAR + 8 * i; }
__host__ __device__ constexpr int ky_of(int kyo) { return kyo == 0 ? 1 : (kyo == 1 ? 0 : 2); }

constexpr unsigned SPIN_LIMIT = 1u << 16;

#define LS 1056
#define GS1 4
#define PD 0
struct Scratch {
    float acc1[NB * 4 * LS];
    float acc2[NB * LS];
    unsigned wcnt[3 * NB * LS];
    float emb[NXTRA * NB * C];
    unsigned char wt[2 * NSTAGE * STAGE_BYTES];
    uint4 box[NCTA * 1024];
};
__device__ __align__(1024) Scratch g_scratch;
#define TL(i) do {} while (0)
#define TLG(i) do {} while (0)

__device__ __forceinline__ unsigned clock32() { unsigned c; asm volatile("mov.u32 %0, %%clock;" : "=r"(c)); return c; }
__device__ __forceinline__ uint32_t mapa(uint32_t a, uint32_t rank) {
    uint32_t d;
    asm("mapa.shared::cluster.u32 %0, %1, %2;" : "=r"(d) : "r"(a), "r"(rank));
    return d;
}
#define S0 mapa(0, blockIdx.x & 1)
__device__ __forceinline__ void mbar_init(uint32_t bar, int cnt) {
    asm volatile("mbarrier.init.shared::cta.b64 [%0], %1;" ::"r"(bar + S0), "r"(cnt) : "memory");
}
__device__ __forceinline__ void mbar_arrive(uint32_t bar) {
    asm volatile("mbarrier.arrive.shared::cta.b64 _, [%0];" ::"r"(bar + S0) : "memory");
}
__device__ __forceinline__ void mbar_expect(uint32_t bar, uint32_t bytes) {
    asm volatile("mbarrier.arrive.expect_tx.shared::cta.b64 _, [%0], %1;" ::"r"(bar + S0), "r"(bytes) : "memory");
}
__device__ __forceinline__ bool mbar_try(uint32_t bar, uint32_t par) {
    uint32_t ok;
    asm volatile("{\n.reg .pred p;\nmbarrier.try_wait.parity.shared::cta.b64 p, [%1], %2;\nselp.u32 %0, 1, 0, p;\n}"
                 : "=r"(ok) : "r"(bar + S0), "r"(par) : "memory");
    return ok;
}
__device__ __forceinline__ bool mbar_test(uint32_t bar, uint32_t par) {
    uint32_t ok;
    asm volatile("{\n.reg .pred p;\nmbarrier.test_wait.parity.shared::cta.b64 p, [%1], %2;\nselp.u32 %0, 1, 0, p;\n}"
                 : "=r"(ok) : "r"(bar + S0), "r"(par) : "memory");
    return ok;
}
__device__ __forceinline__ void mbar_wait(uint32_t bar, uint32_t par) {
    unsigned it = 0;
#pragma unroll 1
    while (!mbar_try(bar, par) && ++it < SPIN_LIMIT) {}
}
__device__ __forceinline__ bool elect_one() {
    uint32_t p;
    asm volatile("{\n.reg .pred p;\nelect.sync _|p, 0xffffffff;\nselp.u32 %0, 1, 0, p;\n}" : "=r"(p));
    return p;
}
__device__ __forceinline__ void fence_async_smem() { asm volatile("fence.proxy.async.shared::cta;" ::: "memory"); }
__device__ __forceinline__ void fence_async_global() { asm volatile("fence.proxy.async.global;" ::: "memory"); }
__device__ __forceinline__ void fence_acquire() { asm volatile("fence.acquire.gpu;" ::: "memory"); }
__device__ __forceinline__ void bar_sync(int id, int n) { asm volatile("bar.sync %0, %1;" ::"r"(id), "r"(n) : "memory"); }
__device__ __forceinline__ void bar_arrive(int id, int n) { asm volatile("bar.arrive %0, %1;" ::"r"(id), "r"(n) : "memory"); }
__device__ __forceinline__ void bulk_g2s(uint32_t dst, const void* src, uint32_t bytes, uint32_t bar) {
    asm volatile("cp.async.bulk.shared::cluster.global.mbarrier::complete_tx::bytes [%0], [%1], %2, [%3];"
                 ::"r"(dst), "l"(src), "r"(bytes), "r"(bar) : "memory");
}
__device__ __forceinline__ void tma_x(uint32_t dst, const CUtensorMap* tm, int row, int ch, uint32_t bar) {
    asm volatile("cp.async.bulk.tensor.3d.shared::cluster.global.mbarrier::complete_tx::bytes [%0], [%1, {%2, %3, %4}], [%5];"
                 ::"r"(dst + S0), "l"(tm), "r"(0), "r"(row), "r"(ch), "r"(bar + S0) : "memory");
}
__device__ __forceinline__ uint4 ld_relaxed_v4(const void* p) {
    uint4 v;
    asm volatile("ld.relaxed.gpu.global.v4.u32 {%0,%1,%2,%3}, [%4];" : "=r"(v.x), "=r"(v.y), "=r"(v.z), "=r"(v.w) : "l"(p) : "memory");
    return v;
}
__device__ __forceinline__ unsigned ld_relaxed(const void* p) {
    unsigned v;
    asm volatile("ld.relaxed.gpu.global.u32 %0, [%1];" : "=r"(v) : "l"(p) : "memory");
    return v;
}
__device__ __forceinline__ void red_add4(float* p, float a, float b, float c, float d) {
    asm volatile("red.relaxed.gpu.global.add.v4.f32 [%0], {%1,%2,%3,%4};" ::"l"(p), "f"(a), "f"(b), "f"(c), "f"(d) : "memory");
}
__device__ __forceinline__ void sts128(uint32_t a, uint4 v) {
    asm volatile("st.shared.v4.u32 [%0], {%1,%2,%3,%4};" ::"r"(a + S0), "r"(v.x), "r"(v.y), "r"(v.z), "r"(v.w) : "memory");
}
__device__ __forceinline__ void sts128f(uint32_t a, float4 v) {
    asm volatile("st.shared.v4.f32 [%0], {%1,%2,%3,%4};" ::"r"(a + S0), "f"(v.x), "f"(v.y), "f"(v.z), "f"(v.w) : "memory");
}
__device__ __forceinline__ void sts32f(uint32_t a, float v) { asm volatile("st.shared.f32 [%0], %1;" ::"r"(a + S0), "f"(v) : "memory"); }
__device__ __forceinline__ uint4 lds128(uint32_t a) {
    uint4 v;
    asm volatile("ld.shared.v4.u32 {%0,%1,%2,%3}, [%4];" : "=r"(v.x), "=r"(v.y), "=r"(v.z), "=r"(v.w) : "r"(a + S0) : "memory");
    return v;
}
__device__ __forceinline__ float4 lds128f(uint32_t a) {
    float4 v;
    asm volatile("ld.shared.v4.f32 {%0,%1,%2,%3}, [%4];" : "=f"(v.x), "=f"(v.y), "=f"(v.z), "=f"(v.w) : "r"(a + S0) : "memory");
    return v;
}
__device__ __forceinline__ float2 lds64f(uint32_t a) {
    float2 v;
    asm volatile("ld.shared.v2.f32 {%0,%1}, [%2];" : "=f"(v.x), "=f"(v.y) : "r"(a + S0) : "memory");
    return v;
}
__device__ __forceinline__ float bf_lo(uint32_t u) { return __uint_as_float(u << 16); }
__device__ __forceinline__ float bf_hi(uint32_t u) { return __uint_as_float(u & 0xffff0000u); }
__device__ __forceinline__ uint32_t pack_bf(float lo, float hi) {
    uint32_t r;
    asm("cvt.rn.bf16x2.f32 %0, %1, %2;" : "=r"(r) : "f"(hi), "f"(lo));
    return r;
}
__device__ __forceinline__ float tanh_fast(float x) {
    float r;
    asm("tanh.approx.f32 %0, %1;" : "=f"(r) : "f"(x));
    return r;
}
__device__ __forceinline__ float silu_half(float h) { return fmaf(h, tanh_fast(h), h); }
__device__ __forceinline__ void ldsm4(uint32_t (&u)[4], uint32_t a) {
    asm volatile("ldmatrix.sync.aligned.m8n8.x4.shared.b16 {%0,%1,%2,%3}, [%4];"
                 : "=r"(u[0]), "=r"(u[1]), "=r"(u[2]), "=r"(u[3]) : "r"(a + S0) : "memory");
}
__device__ __forceinline__ void ldsm4t(uint32_t (&u)[4], uint32_t a) {
    asm volatile("ldmatrix.sync.aligned.m8n8.x4.trans.shared.b16 {%0,%1,%2,%3}, [%4];"
                 : "=r"(u[0]), "=r"(u[1]), "=r"(u[2]), "=r"(u[3]) : "r"(a + S0) : "memory");
}
__device__ __forceinline__ void stsm4(uint32_t a, uint32_t p0, uint32_t p1, uint32_t p2, uint32_t p3) {
    asm volatile("stmatrix.sync.aligned.m8n8.x4.shared.b16 [%0], {%1,%2,%3,%4};" ::"r"(a + S0), "r"(p0), "r"(p1), "r"(p2), "r"(p3) : "memory");
}
__device__ __forceinline__ void stsm4t(uint32_t a, uint32_t p0, uint32_t p1, uint32_t p2, uint32_t p3) {
    asm volatile("stmatrix.sync.aligned.m8n8.x4.trans.shared.b16 [%0], {%1,%2,%3,%4};" ::"r"(a + S0), "r"(p0), "r"(p1), "r"(p2), "r"(p3) : "memory");
}

#define R8(o) "+f"(d[o]), "+f"(d[o + 1]), "+f"(d[o + 2]), "+f"(d[o + 3]), "+f"(d[o + 4]), "+f"(d[o + 5]), "+f"(d[o + 6]), "+f"(d[o + 7])
template <uint32_t ALO, uint32_t BLO, uint64_t AHI = 8, uint64_t BHI = 48>
__device__ __forceinline__ void wgmma128(float (&d)[64]) {
    asm volatile(
        "wgmma.mma_async.sync.aligned.m64n128k16.f32.bf16.bf16 "
        "{%0,%1,%2,%3,%4,%5,%6,%7,%8,%9,%10,%11,%12,%13,%14,%15,%16,%17,%18,%19,%20,%21,%22,%23,%24,%25,%26,%27,%28,%29,%30,%31,"
        "%32,%33,%34,%35,%36,%37,%38,%39,%40,%41,%42,%43,%44,%45,%46,%47,%48,%49,%50,%51,%52,%53,%54,%55,%56,%57,%58,%59,%60,%61,%62,%63},"
        " %64, %65, 1, 1, 1, 0, 0;"
        : R8(0), R8(8), R8(16), R8(24), R8(32), R8(40), R8(48), R8(56)
        : "l"((AHI << 32) | ALO), "l"((BHI << 32) | BLO));
}
template <int S>
__device__ __forceinline__ void mma_stages(float (&d)[64], int conv, int tid, Scratch* gs) {
    constexpr uint32_t A = ((SM_ACT + S * 2 * CH_PITCH + 16) >> 4) | ((CH_PITCH >> 4) << 16);
    constexpr uint32_t B = (slot_addr(S % NS) >> 4) | (8u << 16);
    if (S == 0) mbar_wait(BAR(BAR_FULL), conv);
    bool next_ok = true;
    constexpr uint32_t NEXT = S + 1 < NSTAGE ? BAR(BAR_FULL + S + 1) : BAR(BAR_EMB);
    const int npar = S + 1 < NSTAGE ? conv : 0;
    next_ok = mbar_test(NEXT, npar);
    if (S == 0 && tid == 0) TL(32 + conv * 24);
    asm volatile("wgmma.fence.sync.aligned;" ::: "memory");
    wgmma128<A, B>(d);
    wgmma128<A + 1, B + 16>(d);
    wgmma128<A + 2, B + 32>(d);
    asm volatile("wgmma.commit_group.sync.aligned;" ::: "memory");
    if (S >= LAG) {
        asm volatile("wgmma.wait_group.sync.aligned %0;" ::"n"(LAG) : "memory");
        if ((tid & 31) == 0) mbar_arrive(BAR(BAR_WEMPTY + (S + NS - LAG) % NS));
    }
    if (!next_ok) mbar_wait(NEXT, npar);
    if constexpr (S + 1 < NSTAGE) mma_stages<S + 1>(d, conv, tid, gs);
}

__device__ __forceinline__ void weight_load(uint4 (&t)[5], const __nv_bfloat16* w, int cta, int lane) {
    const char* base = reinterpret_cast<const char*>(w) + ((cta & 15) * 8 * C + (cta >> 4) * 16) * 18;
#pragma unroll
    for (int k = 0; k < 5; k++) {
        const int i = lane + 32 * k, row = (i * 57) >> 10;
        if (k < 4 || lane < 16) t[k] = __ldg(reinterpret_cast<const uint4*>(base + row * (C * 18 - 288) + i * 16));
    }
}
__device__ __forceinline__ void weight_block(uint32_t bounce, unsigned char* wt, int cta, int lane, bool readback) {
    unsigned char* dst = wt + (cta >> 4) * STAGE_BYTES + (cta & 15) * 768;
    if (lane < 16) {
        uint32_t v[36];
#pragma unroll
        for (int i = 0; i < 9; i++) {
            const uint4 q = lds128(bounce + (lane & 7) * 288 + (lane >> 3) * 144 + i * 16);
            v[4 * i] = q.x; v[4 * i + 1] = q.y; v[4 * i + 2] = q.z; v[4 * i + 3] = q.w;
        }
#pragma unroll
        for (int kyo = 0; kyo < 3; kyo++) {
#pragma unroll
            for (int kx = 0; kx < 3; kx++) {
                const int tap = ky_of(kyo) * 3 + kx;
                uint32_t o[4];
#pragma unroll
                for (int m = 0; m < 4; m++) {
                    const int i0 = 18 * m + tap, i1 = i0 + 9;
                    const uint32_t sel = ((i0 & 1) ? 0x32u : 0x10u) | ((i1 & 1) ? 0x7600u : 0x5400u);
                    o[m] = __byte_perm(v[i0 >> 1], v[i1 >> 1], sel);
                }
                *reinterpret_cast<uint4*>(dst + kyo * 8 * STAGE_BYTES + kx * 256 + lane * 16) = make_uint4(o[0], o[1], o[2], o[3]);
            }
        }
    }
    if (readback) {
        __syncwarp();
        unsigned acc = 0;
        if (lane < 24) {
#pragma unroll
            for (int i = 0; i < 3; i++) acc |= ld_relaxed(dst + i * 8 * STAGE_BYTES + lane * 32);
        }
        asm volatile("{\n.reg .pred p;\nsetp.eq.u32 p, %0, 0x9e3779b9;\n@p st.shared.u32 [%1], %0;\n}" ::"r"(acc), "r"(bounce + S0) : "memory");
    }
}
__device__ __forceinline__ uint32_t act2(uint32_t u, const float4& cf) {
    return pack_bf(silu_half(fmaf(bf_lo(u), cf.x, cf.z)), silu_half(fmaf(bf_hi(u), cf.y, cf.w)));
}
__device__ __forceinline__ void norm_unit(uint32_t (&u)[4], const float4& ca, const float4& cb) {
    u[0] = act2(u[0], ca); u[1] = act2(u[1], ca); u[2] = act2(u[2], cb); u[3] = act2(u[3], cb);
}
template <int FIRST, int N>
__device__ __forceinline__ void norm_block(uint32_t (&u)[4][4], float4 (&cf)[8], bool load_cf, uint32_t cfa, uint32_t act, uint32_t mask, uint32_t fbar, int lane) {
    if (load_cf) {
#pragma unroll
        for (int i = 2 * FIRST; i < 2 * (FIRST + N); i++) cf[i] = lds128f(cfa + (i >> 1) * 256 + (i & 1) * 64);
    }
#pragma unroll
    for (int t = FIRST; t < FIRST + N; t++) {
        norm_unit(u[t], cf[2 * t], cf[2 * t + 1]);
        stsm4(act + t * 2 * KC_BYTES, u[t][0] & mask, u[t][1] & mask, u[t][2] & mask, u[t][3] & mask);
    }
    fence_async_smem();
    __syncwarp();
    if (lane < N) mbar_arrive(fbar + 16 * (FIRST + lane));
}
__device__ __forceinline__ void stat_mma(float (&c)[4], uint32_t p, uint32_t q) {
    asm("mma.sync.aligned.m16n8k16.row.col.f32.bf16.bf16.f32 {%0,%1,%2,%3}, {%4,%5,%6,%5}, {%4,%6}, {%0,%1,%2,%3};"
        : "+f"(c[0]), "+f"(c[1]), "+f"(c[2]), "+f"(c[3]) : "r"(p), "r"(0x3f803f80u), "r"(q));
}
__device__ __forceinline__ void stat_store(const float (&c)[4], uint32_t dst, int lane) {
    const int g = lane >> 2, t = lane & 3;
    if (t == (g >> 1)) sts32f(dst + g * 4, (g & 1) ? c[1] : c[0]);
    if (g == 7) sts32f(dst + 32 + t * 4, c[2] + c[3]);
}
__device__ __forceinline__ float sum4(float4 v) { return (v.x + v.y) + (v.z + v.w); }
__device__ __forceinline__ void stat_publish(uint32_t src, float* acc, int lane, bool real) {
    const uint32_t a = src + (lane & 15) * 48;
    float q = sum4(lds128f(a)) + sum4(lds128f(a + 16)), sm = sum4(lds128f(a + 32));
    q += __shfl_xor_sync(0xffffffffu, q, 1); sm += __shfl_xor_sync(0xffffffffu, sm, 1);
    q += __shfl_xor_sync(0xffffffffu, q, 2); sm += __shfl_xor_sync(0xffffffffu, sm, 2);
    if (real && (lane & 19) == 0) red_add4(acc + lane, 1.f, sm, q, 1.f);
}
__device__ __forceinline__ void fence_acc(float (&d)[64]) {
#pragma unroll
    for (int i = 0; i < 64; i++) asm volatile("" : "+f"(d[i])::"memory");
}
__device__ __forceinline__ void ld_unit(uint32_t (&u)[4], const uint4* p) {
    asm volatile("ld.relaxed.gpu.global.v4.u32 {%0,%1,%2,%3}, [%4];" : "=r"(u[0]), "=r"(u[1]), "=r"(u[2]), "=r"(u[3]) : "l"(p) : "memory");
}

__device__ __noinline__ void side_jobs(const __nv_bfloat16* __restrict__ t_emb, const __nv_bfloat16* __restrict__ w_emb,
                                       const __nv_bfloat16* __restrict__ w2, Scratch* __restrict__ gs, unsigned clk0) {
    const int tid = threadIdx.x, warp = tid >> 5, lane = tid & 31, j = blockIdx.x;
    float tv = 0.f;
    if (lane < 24) tv = __bfloat162float(t_emb[(lane / 12) * E + j * 192 + warp * 12 + lane % 12]);
    if (tid == 0) {
        mbar_init(BAR(0), 1);
        mbar_expect(BAR(0), 192 * C * 2);
        fence_async_smem();
        while (clock32() - clk0 < W2DELAY) {}
#pragma unroll
        for (int i = 0; i < 4; i++) bulk_g2s(S0 + SM_W + i * 12288, w_emb + (j * 192 + i * 48) * C, 12288, S0 + BAR(0));
    }
    if (j == 0 && tid < 32) gs->acc2[(tid >> 4) * LS + (tid & 15)] = 0.f;
    const float sv = silu_half(0.5f * tv);
    __syncthreads();
    mbar_wait(BAR(0), 0);
    float acc[8] = {0.f, 0.f, 0.f, 0.f, 0.f, 0.f, 0.f, 0.f};
#pragma unroll
    for (int i = 0; i < 12; i++) {
        const float2 wq = lds64f(SM_W + (warp * 12 + i) * 256 + lane * 8);
        const uint32_t wx = __float_as_uint(wq.x), wy = __float_as_uint(wq.y);
#pragma unroll
        for (int bb = 0; bb < 2; bb++) {
            const float sx = __shfl_sync(0xffffffffu, sv, bb * 12 + i);
            acc[4 * bb + 0] = fmaf(sx, bf_lo(wx), acc[4 * bb + 0]); acc[4 * bb + 1] = fmaf(sx, bf_hi(wx), acc[4 * bb + 1]);
            acc[4 * bb + 2] = fmaf(sx, bf_lo(wy), acc[4 * bb + 2]); acc[4 * bb + 3] = fmaf(sx, bf_hi(wy), acc[4 * bb + 3]);
        }
    }
    sts128f(SM_ACT + warp * 1024 + lane * 16, make_float4(acc[0], acc[1], acc[2], acc[3]));
    sts128f(SM_ACT + warp * 1024 + 512 + lane * 16, make_float4(acc[4], acc[5], acc[6], acc[7]));
    __syncthreads();
    if (tid < 128) {
        float2 sum = make_float2(0.f, 0.f);
#pragma unroll
        for (int w = 0; w < 16; w++) { const float2 p = lds64f(SM_ACT + w * 1024 + tid * 8); sum.x += p.x; sum.y += p.y; }
        *reinterpret_cast<float2*>(&gs->emb[j * NB * C + tid * 2]) = sum;
        bar_sync(1, 128);
        if (tid < 2) asm volatile("red.release.gpu.global.add.u32 [%0], 1;" ::"l"(&gs->wcnt[(2 * NB + tid) * LS]) : "memory");
    }
}

__global__ void __cluster_dims__(2, 1, 1) __launch_bounds__(NTHREADS, 1)
resblock_kernel(const __nv_bfloat16* __restrict__ w1,
                const __nv_bfloat16* __restrict__ t_emb, const __nv_bfloat16* __restrict__ g1,
                const __nv_bfloat16* __restrict__ be1, const __nv_bfloat16* __restrict__ w_emb,
                const __nv_bfloat16* __restrict__ g2, const __nv_bfloat16* __restrict__ be2,
                const __nv_bfloat16* __restrict__ w2, __nv_bfloat16* __restrict__ out, Scratch* __restrict__ gs,
                const __grid_constant__ CUtensorMap xmap) {
    const unsigned clk0 = clock32();
    if (threadIdx.x == 480 && blockIdx.x >= NXTRA) TLG(1);
    const int tid = threadIdx.x, lane = tid & 31;
    const int cta = blockIdx.x - NXTRA, b = cta >> 6, r = cta & 63;
    uint4 v[5];
    if (tid < 32) weight_load(v, w1, cta & (NCTA - 1), lane);
    const int warp = __shfl_sync(0xffffffffu, tid >> 5, 0);
    if (cta < 0) { side_jobs(t_emb, w_emb, w2, gs, clk0); return; }

    const int seg = lane & 7;
    if (warp != 3) asm volatile("barrier.cluster.arrive.relaxed.aligned;" ::: "memory");
    const bool has_outer = (r != 0) && (r != HW - 1);
    if (warp == 1 || warp == 2 || warp == 4 || warp == 5) {
        const int g = warp < 3 ? warp - 1 : 7 - warp;
        if (elect_one()) {
            asm volatile("prefetch.tensormap [%0];" ::"l"(&xmap) : "memory");
            mbar_init(BAR(BAR_X) + 8 * g, 1);
            if (g == 3) mbar_init(BAR(BAR_X + 4), 1);
            mbar_expect(BAR(BAR_X) + 8 * g, 4096);
            fence_async_smem();
            while (clock32() - clk0 < XDELAY + g * XSTAG) {}
            tma_x(SM_XOWN + g * 4096, &xmap, r, b * C + g * 32, BAR(BAR_X) + 8 * g);
            if (g == 3 && has_outer) {
                mbar_expect(BAR(BAR_X + 4), 16384);
#pragma unroll
                for (int i = 0; i < 4; i++) tma_x(SM_XOUT + i * 4096, &xmap, r + ((r & 1) ? 1 : -1), b * C + i * 32, BAR(BAR_X + 4));
            }
        }
        __syncwarp();
        bar_arrive(4, 256 + 32 + 128);
        mbar_wait(BAR(BAR_X) + 8 * g, 0);
        if (lane == 0) TL(70 + g);
        float c[2][4] = {{0.f, 0.f, 0.f, 0.f}, {0.f, 0.f, 0.f, 0.f}};
#pragma unroll
        for (int k = 0; k < 8; k++) {
            const uint4 q = lds128(SM_XOWN + g * 4096 + k * 512 + lane * 16);
            stat_mma(c[0], q.x, q.y); stat_mma(c[1], q.z, q.w);
        }
#pragma unroll
        for (int i = 0; i < 4; i++) c[0][i] += c[1][i];
        stat_store(c[0], SM_RED + g * 48, lane);
        __syncwarp();
        if (lane == 0) {
            const uint32_t a = SM_RED + g * 48;
            red_add4(&gs->acc1[b * 4 * LS + g * GS1], 1.f, sum4(lds128f(a + 32)), sum4(lds128f(a)) + sum4(lds128f(a + 16)), 1.f);
            TL(74 + g);
        }
    }
    if (warp == 0) {
#pragma unroll
        for (int k = 0; k < 5; k++)
            if (k < 4 || lane < 16) sts128(SM_BNC + (lane + 32 * k) * 16, v[k]);
        __syncwarp();
#pragma unroll 1
        for (int k = 0; k < 2; k++) {
            if (k) { bar_sync(6, 64); mbar_wait(BAR(BAR_W2), 0); }
            weight_block(SM_BNC + k * 2304, gs->wt + k * NSTAGE * STAGE_BYTES, cta, lane, k == 0);
            __syncwarp();
            if (lane == 0) TL(k ? 13 : 4);
            if (k == 0 && lane < 2) asm volatile("red.relaxed.gpu.global.add.u32 [%0], 1;" ::"l"(&gs->wcnt[lane * LS + (cta >> 4)]) : "memory");
        }
        bar_arrive(7, 64);
    }

    if (warp >= 8) {
        const int nw = warp - 8;
        bar_sync(4, 256 + 32 + 128);
        const int par = nw >> 2, wq = nw & 3;
        const uint32_t act_off = SM_ACT + (par * 2 + (lane >> 4)) * CH_PITCH + (2 + wq * 16 + (lane & 15)) * 16;
        const uint32_t stg_off = (par * 16 + (lane >> 4) * 8 + (lane & 7)) * 128 + (((2 * wq + ((lane >> 3) & 1)) ^ (lane & 7)) << 4);
        const uint32_t cfa = SM_COEF + par * 128 + (lane & 3) * 16;
        const uint32_t fbar = BAR(BAR_FULL) + 8 * par;
        uint4* inbox = gs->box + cta * 1024 + nw * 32 + lane;
#pragma unroll 1
        for (int conv = 0; conv < 2; conv++) {
            uint32_t u[4][4], w[4][4];
            float4 cf[8];
            if (conv == 0) {
                mbar_wait(BAR(BAR_X), 0); ldsm4t(u[0], SM_XOWN + stg_off);
                mbar_wait(BAR(BAR_X + 1), 0); ldsm4t(u[1], SM_XOWN + stg_off + 4096);
                mbar_wait(BAR(BAR_STATS), 0);
                if (tid == 256) TL(22);
                norm_block<0, 1>(u, cf, true, cfa, act_off, ~0u, fbar, lane);
                if (tid == 256) TL(8);
                mbar_wait(BAR(BAR_X + 2), 0); ldsm4t(u[2], SM_XOWN + stg_off + 8192);
                mbar_wait(BAR(BAR_STATS + 1), 0);
                norm_block<1, 1>(u, cf, true, cfa, act_off, ~0u, fbar, lane);
                mbar_wait(BAR(BAR_X + 3), 0); ldsm4t(u[3], SM_XOWN + stg_off + 12288);
                mbar_wait(BAR(BAR_STATS + 2), 0);
                norm_block<2, 1>(u, cf, true, cfa, act_off, ~0u, fbar, lane);
                mbar_wait(BAR(BAR_STATS + 3), 0);
                norm_block<3, 1>(u, cf, true, cfa, act_off, ~0u, fbar, lane);
            } else {
                mbar_wait(BAR(BAR_HW), 0);
#pragma unroll
                for (int i = 0; i < 4; i++) ldsm4(u[i], act_off + i * 2 * KC_BYTES);
                mbar_wait(BAR(BAR_STATS + 1), 1);
                mbar_wait(BAR(BAR_STATS), 1);
                if (tid == 256) TL(26);
                norm_block<0, 2>(u, cf, true, cfa, act_off, ~0u, fbar, lane);
                if (tid == 256) TL(16);
                mbar_wait(BAR(BAR_STATS + 2), 1);
                mbar_wait(BAR(BAR_STATS + 3), 1);
                norm_block<2, 2>(u, cf, true, cfa, act_off, ~0u, fbar, lane);
            }
            if (tid == 256) TL(84 + conv);
            if (has_outer) {
                mbar_wait(BAR(BAR_X + 4), conv);
                if (conv == 0) {
#pragma unroll
                    for (int i = 0; i < 4; i++) ldsm4t(w[i], SM_XOUT + stg_off + i * 4096);
                } else {
#pragma unroll
                    for (int i = 0; i < 4; i++) {
                        const uint4 q = lds128(SM_XOUT + (tid - 256) * 16 + i * 4096);
                        w[i][0] = q.x; w[i][1] = q.y; w[i][2] = q.z; w[i][3] = q.w;
                    }
                    unsigned it = 0;
                    while (true) {
                        bool ok = true;
#pragma unroll
                        for (int i = 0; i < 16; i++) ok = ok && w[i >> 2][i & 3] != 0;
                        if (__all_sync(0xffffffffu, ok) || ++it > SPIN_LIMIT) break;
#pragma unroll
                        for (int i = 0; i < 4; i++) ld_unit(w[i], inbox + i * 256);
                    }
#pragma unroll
                    for (int i = 0; i < 16; i++) w[i >> 2][i & 3] = ~w[i >> 2][i & 3];
                }
            }
            bar_sync(3, 256);
            if (nw == 0) sts128(SM_ACT + 2 * ROW_BYTES + (lane >> 1) * CH_PITCH + (lane & 1) * 16, make_uint4(0, 0, 0, 0));
            if (tid == 256) TL(24 + conv * 4);
            norm_block<0, 4>(w, cf, false, cfa, act_off + 2 * ROW_BYTES, has_outer ? ~0u : 0u, fbar + 128, lane);
            if (tid == 256) TL(23 + conv * 4);
        }
        if (has_outer) {
            mbar_wait(BAR(BAR_FULL + NSTAGE - 1), 1);
#pragma unroll
            for (int i = 0; i < 4; i++) inbox[i * 256] = make_uint4(0, 0, 0, 0);
        }
    } else if (warp < 4) {
        const int wq = warp;
        if (wq == 3) {
            if (elect_one()) {
#pragma unroll
                for (int i = 0; i < NSTAGE; i++) mbar_init(BAR(BAR_FULL + i), (i >> 3) == 1 ? 1 : 5);
#pragma unroll
                for (int i = 0; i <= NS; i++) mbar_init(BAR(BAR_WEMPTY + i), 4);
#pragma unroll
                for (int i = BAR_STATS; i < BAR_X; i++) mbar_init(BAR(i), i == BAR_EMB ? 3 : 1);
                asm volatile("fence.mbarrier_init.release.cluster;" ::: "memory");
            }
            __syncwarp();
            fence_async_smem();
            bar_arrive(0, 96);
            bar_arrive(5, 96);
            bar_arrive(4, 256 + 32 + 128);
            const uint4 z = make_uint4(0, 0, 0, 0);
#pragma unroll
            for (int i = 0; i < 2; i++) sts128(SM_ACT + (i * 16 + (lane >> 1)) * CH_PITCH + (lane & 1) * 16, z);
            if (lane < 4) sts128(SM_ACT + (2 + (lane >> 1)) * ROW_BYTES + (lane & 1) * 16, z);
            if (lane < 16) sts128(SM_ONES + lane * 16, make_uint4(lane < 8 ? 0x3f803f80u : 0u, 0, 0, 0));
            fence_async_smem();
            asm volatile("barrier.cluster.arrive.release.aligned;" ::: "memory");
            bar_arrive(6, 64);
            if (elect_one()) {
                mbar_expect(BAR(BAR_W2), 2304);
                while (clock32() - clk0 < W2DELAY) {}
                const char* base = reinterpret_cast<const char*>(w2) + ((cta & 15) * 8 * C + (cta >> 4) * 16) * 18;
#pragma unroll 1
                for (int i = 0; i < 8; i++) bulk_g2s(S0 + SM_BNC + 2304 + i * 288, base + i * (C * 18), 288, S0 + BAR(BAR_W2));
            }
            __syncwarp();
        }
        bar_sync(2, 128);

        float d[64];
#pragma unroll
        for (int i = 0; i < 64; i++) d[i] = 0.f;
#pragma unroll 1
        for (int conv = 0; conv < 2; conv++) {
            fence_acc(d);
            mma_stages<0>(d, conv, tid, gs);
            if (conv == 0) {
                asm volatile("wgmma.fence.sync.aligned;" ::: "memory");
                wgmma128<(SM_ONES >> 4) | (8u << 16), (SM_EMB >> 4), 0, 8>(d);
                asm volatile("wgmma.commit_group.sync.aligned;" ::: "memory");
            }
            asm volatile("wgmma.wait_group.sync.aligned 0;" ::: "memory");
            fence_acc(d);
            if (tid == 0) TL(10 + conv * 8);
            if (conv == 1) break;

            uint32_t hp[32];
#pragma unroll
            for (int g = 0; g < 4; g++) {
                float c[4] = {0.f, 0.f, 0.f, 0.f};
#pragma unroll
                for (int i = 0; i < 8; i++) hp[8 * g + i] = pack_bf(d[16 * g + 2 * i], d[16 * g + 2 * i + 1]);
#pragma unroll
                for (int i = 0; i < 4; i++) stat_mma(c, hp[8 * g + 2 * i], hp[8 * g + 2 * i + 1]);
                stat_store(c, SM_RED + (g * 4 + wq) * 48, lane);
            }
            bar_sync(2, 128);
            if (wq == 0) stat_publish(SM_RED, &gs->acc2[b * LS], lane, true);
            if (tid == 0) TL(11);
            const uint32_t hbase = SM_ACT + (lane >> 4) * CH_PITCH + (2 + wq * 16 + (lane & 15)) * 16;
#pragma unroll
            for (int kc = 0; kc < 8; kc++) stsm4(hbase + kc * 2 * CH_PITCH, hp[4 * kc], hp[4 * kc + 1], hp[4 * kc + 2], hp[4 * kc + 3]);
            __syncwarp();
            if (lane == 0) mbar_arrive(BAR(BAR_HW));
            if (lane < LAG) mbar_arrive(BAR(BAR_WEMPTY + (NSTAGE - LAG) % NS) + 8 * lane);
            if (has_outer) {
                uint4* outbox = gs->box + (cta + ((r & 1) ? 1 : -1)) * 1024 + tid;
#pragma unroll
                for (int kc = 0; kc < 8; kc++) outbox[kc * 128] = make_uint4(~hp[4 * kc], ~hp[4 * kc + 1], ~hp[4 * kc + 2], ~hp[4 * kc + 3]);
            }
            if (tid == 0) TL(12);
            const uint32_t xbase = SM_XOWN + ((lane >> 4) * 8 + (lane & 7)) * 128 + (((2 * wq + ((lane >> 3) & 1)) ^ (lane & 7)) << 4);
#pragma unroll
            for (int kc = 0; kc < 8; kc++) {
                uint32_t p[4];
                ldsm4t(p, xbase + kc * 2048);
#pragma unroll
                for (int i = 0; i < 4; i++) { d[8 * kc + 2 * i] = bf_lo(p[i]); d[8 * kc + 2 * i + 1] = bf_hi(p[i]); }
            }
        }
        {
            const uint32_t obase = slot_addr(0) + ((lane >> 4) * 8 + (lane & 7)) * OUT_PITCH + (wq * 16 + ((lane >> 3) & 1) * 8) * 2;
#pragma unroll
            for (int kc = 0; kc < 8; kc++) {
                stsm4t(obase + kc * 16 * OUT_PITCH, pack_bf(d[8 * kc + 0], d[8 * kc + 1]), pack_bf(d[8 * kc + 2], d[8 * kc + 3]),
                       pack_bf(d[8 * kc + 4], d[8 * kc + 5]), pack_bf(d[8 * kc + 6], d[8 * kc + 7]));
            }
            bar_sync(2, 128);
            const int oc0 = tid >> 3;
            __nv_bfloat16* dst = out + ((size_t)(b * C + oc0) * HW + r) * HW + seg * 8;
#pragma unroll
            for (int i = 0; i < 8; i++)
                *reinterpret_cast<uint4*>(dst + (size_t)i * 16 * HW * HW) = lds128(slot_addr(0) + (oc0 + 16 * i) * OUT_PITCH + seg * 16);
            if (tid == 0) { TL(20); TLG(21); }
        }
    } else if (warp < 6) {
        bar_sync(5, 96);
        if (warp == 5) {
            asm volatile("barrier.cluster.wait.acquire.aligned;" ::: "memory");
            const uint32_t peer = (r & 1) ^ 1;
            const uint32_t self0 = mapa(0, r & 1), peer0 = mapa(0, peer);
#pragma unroll 1
            for (int conv = 0; conv < 2; conv++) {
#pragma unroll 1
                for (int kc = 0; kc < 8; kc++) {
                    mbar_wait(BAR(BAR_FULL) + 8 * kc, conv);
                    if (elect_one())
                        asm volatile("cp.async.bulk.shared::cluster.shared::cta.mbarrier::complete_tx::bytes [%0], [%1], %2, [%3];"
                                     ::"r"(peer0 + SM_ACT + ROW_BYTES + kc * KC_BYTES), "r"(self0 + SM_ACT + kc * KC_BYTES), "r"(KC_BYTES),
                                       "r"(peer0 + BAR(BAR_FULL + 8) + 8 * kc) : "memory");
                }
                if (lane == 0) TL(86 + conv);
#pragma unroll 1
                for (int kc = 0; kc < 8; kc++) mbar_wait(BAR(BAR_FULL + 8) + 8 * kc, conv);
                if (lane == 0)
                    asm volatile("mbarrier.arrive.release.cluster.shared::cluster.b64 _, [%0];" ::"r"(peer0 + (conv ? BAR(BAR_ACK) : BAR(BAR_EMB))) : "memory");
            }
            mbar_wait(BAR(BAR_ACK), 0);
        } else {
            bar_sync(7, 64);
            if (lane < 2) asm volatile("red.release.gpu.global.add.u32 [%0], 1;" ::"l"(&gs->wcnt[(NB + lane) * LS]) : "memory");
            if (lane == 0) TL(14);
            mbar_wait(BAR(BAR_STATS + 3), 0);
            unsigned it = 0;
            while (ld_relaxed(&gs->wcnt[(2 * NB + b) * LS]) < (unsigned)NXTRA && ++it < SPIN_LIMIT) __nanosleep(100);
            fence_acquire();
            float ev[4] = {0.f, 0.f, 0.f, 0.f};
#pragma unroll
            for (int j = 0; j < NXTRA; j++) {
                const uint4 ef = ld_relaxed_v4(&gs->emb[(j * NB + b) * C + lane * 4]);
                ev[0] += __uint_as_float(ef.x); ev[1] += __uint_as_float(ef.y); ev[2] += __uint_as_float(ef.z); ev[3] += __uint_as_float(ef.w);
            }
#pragma unroll
            for (int i = 0; i < 4; i++) {
                const float hi = bf_lo(pack_bf(ev[i], 0.f));
                sts128(SM_EMB + (lane * 4 + i) * 16, make_uint4(pack_bf(hi, ev[i] - hi), 0, 0, 0));
            }
            fence_async_smem();
            __syncwarp();
            if (lane == 0) { mbar_arrive(BAR(BAR_EMB)); TL(19); }
        }
    } else if (warp == 6) {
        bar_sync(0, 96);
        const uint32_t ebytes = STAGE_BYTES + ((lane >> 3) == 1 ? KC_BYTES : 0);
        if (lane < NSTAGE) mbar_expect(BAR(BAR_FULL) + 8 * lane, ebytes);
        const int swap = (r & 1) ? 0 : 8 * STAGE_BYTES;
        const unsigned char* wsrc = gs->wt;
        uint32_t dst = S0 + SM_W, full = S0 + BAR(BAR_FULL), empty = BAR(BAR_WEMPTY);
        unsigned it = 0;
        unsigned ready = 0;
#pragma unroll 1
        for (int g = 0; g < 2 * NSTAGE; g++) {
            if (g < 8 && !((ready >> g) & 1)) {
                do {
                    ready = __ballot_sync(0xffffffffu, ld_relaxed(&gs->wcnt[b * LS + (lane & 7)]) >= 16u);
                } while (!((ready >> g) & 1) && ++it < SPIN_LIMIT);
                fence_acquire();
                fence_async_global();
                if (lane == 0) TL(g ? 3 : 6);
            }
            if (g >= NS) {
                mbar_wait(empty, ((g - NS) / NS) & 1);
                if (g == NSTAGE) {
                    it = 0;
                    while (ld_relaxed(&gs->wcnt[(NB + b) * LS]) < (unsigned)NCTA && ++it < SPIN_LIMIT) {}
                    fence_acquire();
                    fence_async_global();
                    if (lane == 0) { mbar_arrive(BAR(BAR_EMB)); TL(2); }
                }
                if (g == NSTAGE || g == NSTAGE + NS) {
                    if (lane >= g - NSTAGE && lane < g - NSTAGE + NS) mbar_expect(BAR(BAR_FULL) + 8 * lane, ebytes);
                    __syncwarp();
                }
            }
            if (elect_one()) bulk_g2s(dst, wsrc, STAGE_BYTES, full);
            wsrc += STAGE_BYTES; dst += STAGE_BYTES; full += 8; empty += 8;
            const int st = (g >= NSTAGE ? g - NSTAGE : g) + 1;
            if (st == 8 || st == NSTAGE) wsrc += swap;
            if (st == 16) wsrc -= 2 * swap;
            if (st == NS || st == NSTAGE) { dst -= NS * STAGE_BYTES; empty -= 8 * NS; }
            if (st == NSTAGE) full -= 8 * NSTAGE;
        }
    } else {
        const uint2 ga1 = __ldg(reinterpret_cast<const uint2*>(g1) + lane), bt1 = __ldg(reinterpret_cast<const uint2*>(be1) + lane);
        const uint2 ga2 = __ldg(reinterpret_cast<const uint2*>(g2) + lane), bt2 = __ldg(reinterpret_cast<const uint2*>(be2) + lane);
        bar_sync(0, 96);
#pragma unroll 1
        for (int conv = 0; conv < 2; conv++) {
            if (conv == 1) mbar_wait(BAR(BAR_EMB), 0);
            const float* asrc = conv ? &gs->acc2[b * LS + (lane >> 3) * 4] : &gs->acc1[b * 4 * LS + (lane >> 3) * GS1];
            while (clock32() - clk0 < PD) {}
            const uint2 ga = conv ? ga2 : ga1, bt = conv ? bt2 : bt1;
            bool done = false;
            unsigned it = 0;
#pragma unroll 1
            while (true) {
                const uint4 f = ld_relaxed_v4(asrc);
                const bool fresh = !done && (((f.x == 0x42800000u) & (f.w == 0x42800000u)) || it > SPIN_LIMIT);
                it++;
                if (!__any_sync(0xffffffffu, fresh)) continue;
                if (lane == 0 && fresh) TL(7 + conv * 8);
                if (lane == 24 && fresh) TL(90 + conv);
                const float inv_n = 1.0f / (32.0f * HW * HW);
                const float mean = __uint_as_float(f.y) * inv_n;
                const float var = fmaxf(fmaf(-mean, mean, __uint_as_float(f.z) * inv_n), 0.f);
                const float rs = 0.5f * rsqrtf(var + 1e-5f);
                float4 k0, k1;
                k0.x = rs * bf_lo(ga.x); k0.y = rs * bf_hi(ga.x); k1.x = rs * bf_lo(ga.y); k1.y = rs * bf_hi(ga.y);
                k0.z = fmaf(-mean, k0.x, 0.5f * bf_lo(bt.x)); k0.w = fmaf(-mean, k0.y, 0.5f * bf_hi(bt.x));
                k1.z = fmaf(-mean, k1.x, 0.5f * bf_lo(bt.y)); k1.w = fmaf(-mean, k1.y, 0.5f * bf_hi(bt.y));
                if (fresh) {
                    sts128f(SM_COEF + lane * 32, k0);
                    sts128f(SM_COEF + lane * 32 + 16, k1);
                }
                __syncwarp();
                if (fresh && (lane & 7) == 0) mbar_arrive(BAR(BAR_STATS) + lane);
                done = done || fresh;
                if (__all_sync(0xffffffffu, done)) break;
            }
        }
        if (has_outer && elect_one()) {
            mbar_expect(BAR(BAR_X + 4), 16384);
            bulk_g2s(S0 + SM_XOUT, gs->box + cta * 1024, 16384, S0 + BAR(BAR_X + 4));
        }
        if (r == 0) {
            if (lane < 16) gs->acc1[b * 4 * LS + (lane >> 2) * GS1 + (lane & 3)] = 0.f;
            if (lane < 24) gs->wcnt[((lane >> 3) * NB + b) * LS + (lane & 7)] = 0;
        }
    }
}

}

extern "C" void kernel_launch(void* const* d_in, const int* in_sizes, int n_in, void* d_out, int out_size) {
    (void)in_sizes; (void)n_in; (void)out_size;
    typedef CUresult (*EncodeFn)(CUtensorMap*, CUtensorMapDataType, cuuint32_t, void*, const cuuint64_t*, const cuuint64_t*,
                                 const cuuint32_t*, const cuuint32_t*, CUtensorMapInterleave, CUtensorMapSwizzle,
                                 CUtensorMapL2promotion, CUtensorMapFloatOOBfill);
    static Scratch* gs = nullptr;
    static EncodeFn encode = nullptr;
    if (!gs) {
        cudaFuncSetAttribute(resblock_kernel, cudaFuncAttributeMaxDynamicSharedMemorySize, SM_TOTAL);
        cudaGetSymbolAddress((void**)&gs, g_scratch);
        cudaDriverEntryPointQueryResult qr;
        cudaGetDriverEntryPoint("cuTensorMapEncodeTiled", (void**)&encode, cudaEnableDefault, &qr);
    }
    CUtensorMap xmap;
    const cuuint64_t dims[3] = {HW, HW, NB * C}, strides[2] = {HW * 2, HW * HW * 2};
    const cuuint32_t box[3] = {HW, 1, 32}, es[3] = {1, 1, 1};
    encode(&xmap, CU_TENSOR_MAP_DATA_TYPE_BFLOAT16, 3, d_in[0], dims, strides, box, es, CU_TENSOR_MAP_INTERLEAVE_NONE,
           CU_TENSOR_MAP_SWIZZLE_128B, CU_TENSOR_MAP_L2_PROMOTION_NONE, CU_TENSOR_MAP_FLOAT_OOB_FILL_NONE);
    resblock_kernel<<<NCTA + NXTRA, NTHREADS, SM_TOTAL>>>(
        (const __nv_bfloat16*)d_in[4], (const __nv_bfloat16*)d_in[1],
        (const __nv_bfloat16*)d_in[2], (const __nv_bfloat16*)d_in[3], (const __nv_bfloat16*)d_in[5],
        (const __nv_bfloat16*)d_in[6], (const __nv_bfloat16*)d_in[7], (const __nv_bfloat16*)d_in[8],
        (__nv_bfloat16*)d_out, gs, xmap);
}
```

```cpp
#include <cuda_runtime.h>
#include <cuda.h>
#include <cuda_bf16.h>
#include <stdint.h>

namespace {

constexpr int C = 128, HW = 64, NB = 2, E = 768;
constexpr int NCTA = NB * HW;
constexpr int NXTRA = 4;
constexpr int NTHREADS = 16 * 32;
constexpr int CH_PITCH = 66 * 16;
constexpr int ROW_BYTES = 16 * CH_PITCH;
constexpr int STEP_BYTES = 4096;
constexpr int STAGE_BYTES = 3 * STEP_BYTES;
constexpr int NSTAGE = 24;
constexpr int KC_BYTES = 2 * CH_PITCH;
constexpr int NS = 12;
constexpr int LAG = 1;
#define XDELAY 500
#define HDELAY 600
#define NA 2
#define RB 1
#define XSTAG 400
#define HSEND 0
#define W2DELAY 2000

constexpr uint32_t SMEM_BASE = 0x400;
constexpr uint32_t SM_XOWN = SMEM_BASE;
constexpr uint32_t SM_ACT = SM_XOWN + 16384 + 512;
constexpr uint32_t SM_XOUT = SM_ACT + 2 * ROW_BYTES + 512;
static_assert(SM_XOUT % 1024 == 0, "swizzle atom alignment");
constexpr uint32_t SM_W = SM_ACT + 3 * ROW_BYTES + 128;
__host__ __device__ constexpr uint32_t slot_addr(int slot) { return SM_W + slot * STAGE_BYTES; }
constexpr uint32_t SM_COEF = SM_W + NS * STAGE_BYTES;
constexpr uint32_t SM_EMB = SM_COEF + 1024;
constexpr uint32_t SM_ONES = SM_EMB + 2048;
constexpr uint32_t SM_RED = SM_ONES + 256;
constexpr uint32_t SM_BNC = SM_RED + 1280;
constexpr uint32_t SM_BAR = SM_BNC + 2 * 2304;
constexpr int BAR_FULL = 0, BAR_WEMPTY = NSTAGE, BAR_HW = BAR_WEMPTY + NS, BAR_STATS = BAR_HW + 1  ,
              BAR_EMB = BAR_STATS + 4, BAR_ACK = BAR_EMB + 1, BAR_W2 = BAR_ACK + 1, BAR_X = BAR_W2 + 1  , NBAR = BAR_X + 5;
constexpr int SM_TOTAL = SM_BAR + NBAR * 8 - SMEM_BASE;
static_assert(SM_TOTAL <= 232448, "smem");
static_assert(NBAR <= 96, "barrier init");
constexpr int OUT_PITCH = 144;
__host__ __device__ constexpr uint32_t BAR(int i) { return SM_BAR + 8 * i; }
__host__ __device__ constexpr int ky_of(int kyo) { return kyo == 0 ? 1 : (kyo == 1 ? 0 : 2); }

constexpr unsigned SPIN_LIMIT = 1u << 16;

#define LS 1056
#define GS1 4
#define PD 0
struct Scratch {
    float acc1[NB * 4 * LS];
    float acc2[NB * LS];
    unsigned wcnt[3 * NB * LS];
    float emb[NXTRA * NB * C];
    unsigned char wt[2 * NSTAGE * STAGE_BYTES];
    uint4 box[NCTA * 1024];
};
__device__ __align__(1024) Scratch g_scratch;
#define TL(i) do {} while (0)
#define TLG(i) do {} while (0)

__device__ __forceinline__ unsigned clock32() { unsigned c; asm volatile("mov.u32 %0, %%clock;" : "=r"(c)); return c; }
__device__ __forceinline__ uint32_t mapa(uint32_t a, uint32_t rank) {
    uint32_t d;
    asm("mapa.shared::cluster.u32 %0, %1, %2;" : "=r"(d) : "r"(a), "r"(rank));
    return d;
}
#define S0 mapa(0, blockIdx.x & 1)
__device__ __forceinline__ void mbar_init(uint32_t bar, int cnt) {
    asm volatile("mbarrier.init.shared::cta.b64 [%0], %1;" ::"r"(bar + S0), "r"(cnt) : "memory");
}
__device__ __forceinline__ void mbar_arrive(uint32_t bar) {
    asm volatile("mbarrier.arrive.shared::cta.b64 _, [%0];" ::"r"(bar + S0) : "memory");
}
__device__ __forceinline__ void mbar_expect(uint32_t bar, uint32_t bytes) {
    asm volatile("mbarrier.arrive.expect_tx.shared::cta.b64 _, [%0], %1;" ::"r"(bar + S0), "r"(bytes) : "memory");
}
__device__ __forceinline__ bool mbar_try(uint32_t bar, uint32_t par) {
    uint32_t ok;
    asm volatile("{\n.reg .pred p;\nmbarrier.try_wait.parity.shared::cta.b64 p, [%1], %2;\nselp.u32 %0, 1, 0, p;\n}"
                 : "=r"(ok) : "r"(bar + S0), "r"(par) : "memory");
    return ok;
}
__device__ __forceinline__ bool mbar_test(uint32_t bar, uint32_t par) {
    uint32_t ok;
    asm volatile("{\n.reg .pred p;\nmbarrier.test_wait.parity.shared::cta.b64 p, [%1], %2;\nselp.u32 %0, 1, 0, p;\n}"
                 : "=r"(ok) : "r"(bar + S0), "r"(par) : "memory");
    return ok;
}
__device__ __forceinline__ void mbar_wait(uint32_t bar, uint32_t par) {
    unsigned it = 0;
#pragma unroll 1
    while (!mbar_try(bar, par) && ++it < SPIN_LIMIT) {}
}
__device__ __forceinline__ bool elect_one() {
    uint32_t p;
    asm volatile("{\n.reg .pred p;\nelect.sync _|p, 0xffffffff;\nselp.u32 %0, 1, 0, p;\n}" : "=r"(p));
    return p;
}
__device__ __forceinline__ void fence_async_smem() { asm volatile("fence.proxy.async.shared::cta;" ::: "memory"); }
__device__ __forceinline__ void fence_async_global() { asm volatile("fence.proxy.async.global;" ::: "memory"); }
__device__ __forceinline__ void fence_acquire() { asm volatile("fence.acquire.gpu;" ::: "memory"); }
__device__ __forceinline__ void bar_sync(int id, int n) { asm volatile("bar.sync %0, %1;" ::"r"(id), "r"(n) : "memory"); }
__device__ __forceinline__ void bar_arrive(int id, int n) { asm volatile("bar.arrive %0, %1;" ::"r"(id), "r"(n) : "memory"); }
__device__ __forceinline__ void bulk_g2s(uint32_t dst, const void* src, uint32_t bytes, uint32_t bar) {
    asm volatile("cp.async.bulk.shared::cluster.global.mbarrier::complete_tx::bytes [%0], [%1], %2, [%3];"
                 ::"r"(dst), "l"(src), "r"(bytes), "r"(bar) : "memory");
}
__device__ __forceinline__ void tma_x(uint32_t dst, const CUtensorMap* tm, int row, int ch, uint32_t bar) {
    asm volatile("cp.async.bulk.tensor.3d.shared::cluster.global.mbarrier::complete_tx::bytes [%0], [%1, {%2, %3, %4}], [%5];"
                 ::"r"(dst + S0), "l"(tm), "r"(0), "r"(row), "r"(ch), "r"(bar + S0) : "memory");
}
__device__ __forceinline__ uint4 ld_relaxed_v4(const void* p) {
    uint4 v;
    asm volatile("ld.relaxed.gpu.global.v4.u32 {%0,%1,%2,%3}, [%4];" : "=r"(v.x), "=r"(v.y), "=r"(v.z), "=r"(v.w) : "l"(p) : "memory");
    return v;
}
__device__ __forceinline__ unsigned ld_relaxed(const void* p) {
    unsigned v;
    asm volatile("ld.relaxed.gpu.global.u32 %0, [%1];" : "=r"(v) : "l"(p) : "memory");
    return v;
}
__device__ __forceinline__ void red_add4(float* p, float a, float b, float c, float d) {
    asm volatile("red.relaxed.gpu.global.add.v4.f32 [%0], {%1,%2,%3,%4};" ::"l"(p), "f"(a), "f"(b), "f"(c), "f"(d) : "memory");
}
__device__ __forceinline__ void sts128(uint32_t a, uint4 v) {
    asm volatile("st.shared.v4.u32 [%0], {%1,%2,%3,%4};" ::"r"(a + S0), "r"(v.x), "r"(v.y), "r"(v.z), "r"(v.w) : "memory");
}
__device__ __forceinline__ void sts128f(uint32_t a, float4 v) {
    asm volatile("st.shared.v4.f32 [%0], {%1,%2,%3,%4};" ::"r"(a + S0), "f"(v.x), "f"(v.y), "f"(v.z), "f"(v.w) : "memory");
}
__device__ __forceinline__ void sts32f(uint32_t a, float v) { asm volatile("st.shared.f32 [%0], %1;" ::"r"(a + S0), "f"(v) : "memory"); }
__device__ __forceinline__ uint4 lds128(uint32_t a) {
    uint4 v;
    asm volatile("ld.shared.v4.u32 {%0,%1,%2,%3}, [%4];" : "=r"(v.x), "=r"(v.y), "=r"(v.z), "=r"(v.w) : "r"(a + S0) : "memory");
    return v;
}
__device__ __forceinline__ float4 lds128f(uint32_t a) {
    float4 v;
    asm volatile("ld.shared.v4.f32 {%0,%1,%2,%3}, [%4];" : "=f"(v.x), "=f"(v.y), "=f"(v.z), "=f"(v.w) : "r"(a + S0) : "memory");
    return v;
}
__device__ __forceinline__ float2 lds64f(uint32_t a) {
    float2 v;
    asm volatile("ld.shared.v2.f32 {%0,%1}, [%2];" : "=f"(v.x), "=f"(v.y) : "r"(a + S0) : "memory");
    return v;
}
__device__ __forceinline__ float bf_lo(uint32_t u) { return __uint_as_float(u << 16); }
__device__ __forceinline__ float bf_hi(uint32_t u) { return __uint_as_float(u & 0xffff0000u); }
__device__ __forceinline__ uint32_t pack_bf(float lo, float hi) {
    uint32_t r;
    asm("cvt.rn.bf16x2.f32 %0, %1, %2;" : "=r"(r) : "f"(hi), "f"(lo));
    return r;
}
__device__ __forceinline__ float tanh_fast(float x) {
    float r;
    asm("tanh.approx.f32 %0, %1;" : "=f"(r) : "f"(x));
    return r;
}
__device__ __forceinline__ float silu_half(float h) { return fmaf(h, tanh_fast(h), h); }
__device__ __forceinline__ void ldsm4(uint32_t (&u)[4], uint32_t a) {
    asm volatile("ldmatrix.sync.aligned.m8n8.x4.shared.b16 {%0,%1,%2,%3}, [%4];"
                 : "=r"(u[0]), "=r"(u[1]), "=r"(u[2]), "=r"(u[3]) : "r"(a + S0) : "memory");
}
__device__ __forceinline__ void ldsm4t(uint32_t (&u)[4], uint32_t a) {
    asm volatile("ldmatrix.sync.aligned.m8n8.x4.trans.shared.b16 {%0,%1,%2,%3}, [%4];"
                 : "=r"(u[0]), "=r"(u[1]), "=r"(u[2]), "=r"(u[3]) : "r"(a + S0) : "memory");
}
__device__ __forceinline__ void stsm4(uint32_t a, uint32_t p0, uint32_t p1, uint32_t p2, uint32_t p3) {
    asm volatile("stmatrix.sync.aligned.m8n8.x4.shared.b16 [%0], {%1,%2,%3,%4};" ::"r"(a + S0), "r"(p0), "r"(p1), "r"(p2), "r"(p3) : "memory");
}
__device__ __forceinline__ void stsm4t(uint32_t a, uint32_t p0, uint32_t p1, uint32_t p2, uint32_t p3) {
    asm volatile("stmatrix.sync.aligned.m8n8.x4.trans.shared.b16 [%0], {%1,%2,%3,%4};" ::"r"(a + S0), "r"(p0), "r"(p1), "r"(p2), "r"(p3) : "memory");
}

#define R8(o) "+f"(d[o]), "+f"(d[o + 1]), "+f"(d[o + 2]), "+f"(d[o + 3]), "+f"(d[o + 4]), "+f"(d[o + 5]), "+f"(d[o + 6]), "+f"(d[o + 7])
template <uint32_t ALO, uint32_t BLO, uint64_t AHI = 8, uint64_t BHI = 48>
__device__ __forceinline__ void wgmma128(float (&d)[64]) {
    asm volatile(
        "wgmma.mma_async.sync.aligned.m64n128k16.f32.bf16.bf16 "
        "{%0,%1,%2,%3,%4,%5,%6,%7,%8,%9,%10,%11,%12,%13,%14,%15,%16,%17,%18,%19,%20,%21,%22,%23,%24,%25,%26,%27,%28,%29,%30,%31,"
        "%32,%33,%34,%35,%36,%37,%38,%39,%40,%41,%42,%43,%44,%45,%46,%47,%48,%49,%50,%51,%52,%53,%54,%55,%56,%57,%58,%59,%60,%61,%62,%63},"
        " %64, %65, 1, 1, 1, 0, 0;"
        : R8(0), R8(8), R8(16), R8(24), R8(32), R8(40), R8(48), R8(56)
        : "l"((AHI << 32) | ALO), "l"((BHI << 32) | BLO));
}
template <int S>
__device__ __forceinline__ void mma_stages(float (&d)[64], int conv, int tid, Scratch* gs) {
    constexpr uint32_t A = ((SM_ACT + S * 2 * CH_PITCH + 16) >> 4) | ((CH_PITCH >> 4) << 16);
    constexpr uint32_t B = (slot_addr(S % NS) >> 4) | (8u << 16);
    if (S == 0) mbar_wait(BAR(BAR_FULL), conv);
    bool next_ok = true;
    constexpr uint32_t NEXT = S + 1 < NSTAGE ? BAR(BAR_FULL + S + 1) : BAR(BAR_EMB);
    const int npar = S + 1 < NSTAGE ? conv : 0;
    next_ok = mbar_test(NEXT, npar);
    if (S == 0 && tid == 0) TL(32 + conv * 24);
    asm volatile("wgmma.fence.sync.aligned;" ::: "memory");
    wgmma128<A, B>(d);
    wgmma128<A + 1, B + 16>(d);
    wgmma128<A + 2, B + 32>(d);
    asm volatile("wgmma.commit_group.sync.aligned;" ::: "memory");
    if (S >= LAG) {
        asm volatile("wgmma.wait_group.sync.aligned %0;" ::"n"(LAG) : "memory");
        if ((tid & 31) == 0) mbar_arrive(BAR(BAR_WEMPTY + (S + NS - LAG) % NS));
    }
    if (!next_ok) mbar_wait(NEXT, npar);
    if constexpr (S + 1 < NSTAGE) mma_stages<S + 1>(d, conv, tid, gs);
}

__device__ __forceinline__ void weight_load(uint4 (&t)[5], const __nv_bfloat16* w, int cta, int lane) {
    const char* base = reinterpret_cast<const char*>(w) + ((cta & 15) * 8 * C + (cta >> 4) * 16) * 18;
#pragma unroll
    for (int k = 0; k < 5; k++) {
        const int i = lane + 32 * k, row = (i * 57) >> 10;
        if (k < 4 || lane < 16) t[k] = __ldg(reinterpret_cast<const uint4*>(base + row * (C * 18 - 288) + i * 16));
    }
}
__device__ __forceinline__ void weight_block(uint32_t bounce, unsigned char* wt, int cta, int lane, bool readback) {
    unsigned char* dst = wt + (cta >> 4) * STAGE_BYTES + (cta & 15) * 768;
    if (lane < 16) {
        uint32_t v[36];
#pragma unroll
        for (int i = 0; i < 9; i++) {
            const uint4 q = lds128(bounce + (lane & 7) * 288 + (lane >> 3) * 144 + i * 16);
            v[4 * i] = q.x; v[4 * i + 1] = q.y; v[4 * i + 2] = q.z; v[4 * i + 3] = q.w;
        }
#pragma unroll
        for (int kyo = 0; kyo < 3; kyo++) {
#pragma unroll
            for (int kx = 0; kx < 3; kx++) {
                const int tap = ky_of(kyo) * 3 + kx;
                uint32_t o[4];
#pragma unroll
                for (int m = 0; m < 4; m++) {
                    const int i0 = 18 * m + tap, i1 = i0 + 9;
                    const uint32_t sel = ((i0 & 1) ? 0x32u : 0x10u) | ((i1 & 1) ? 0x7600u : 0x5400u);
                    o[m] = __byte_perm(v[i0 >> 1], v[i1 >> 1], sel);
                }
                *reinterpret_cast<uint4*>(dst + kyo * 8 * STAGE_BYTES + kx * 256 + lane * 16) = make_uint4(o[0], o[1], o[2], o[3]);
            }
        }
    }
    if (readback) {
        __syncwarp();
        unsigned acc = 0;
        if (lane < 24) {
#pragma unroll
            for (int i = 0; i < 3; i++) acc |= ld_relaxed(dst + i * 8 * STAGE_BYTES + lane * 32);
        }
        asm volatile("{\n.reg .pred p;\nsetp.eq.u32 p, %0, 0x9e3779b9;\n@p st.shared.u32 [%1], %0;\n}" ::"r"(acc), "r"(bounce + S0) : "memory");
    }
}
__device__ __forceinline__ uint32_t act2(uint32_t u, const float4& cf) {
    return pack_bf(silu_half(fmaf(bf_lo(u), cf.x, cf.z)), silu_half(fmaf(bf_hi(u), cf.y, cf.w)));
}
__device__ __forceinline__ void norm_unit(uint32_t (&u)[4], const float4& ca, const float4& cb) {
    u[0] = act2(u[0], ca); u[1] = act2(u[1], ca); u[2] = act2(u[2], cb); u[3] = act2(u[3], cb);
}
template <int FIRST, int N>
__device__ __forceinline__ void norm_block(uint32_t (&u)[4][4], float4 (&cf)[8], bool load_cf, uint32_t cfa, uint32_t act, uint32_t mask, uint32_t fbar, int lane) {
    if (load_cf) {
#pragma unroll
        for (int i = 2 * FIRST; i < 2 * (FIRST + N); i++) cf[i] = lds128f(cfa + (i >> 1) * 256 + (i & 1) * 64);
    }
#pragma unroll
    for (int t = FIRST; t < FIRST + N; t++) {
        norm_unit(u[t], cf[2 * t], cf[2 * t + 1]);
        stsm4(act + t * 2 * KC_BYTES, u[t][0] & mask, u[t][1] & mask, u[t][2] & mask, u[t][3] & mask);
    }
    fence_async_smem();
    __syncwarp();
    if (lane < N) mbar_arrive(fbar + 16 * (FIRST + lane));
}
__device__ __forceinline__ void stat_mma(float (&c)[4], uint32_t p, uint32_t q) {
    asm("mma.sync.aligned.m16n8k16.row.col.f32.bf16.bf16.f32 {%0,%1,%2,%3}, {%4,%5,%6,%5}, {%4,%6}, {%0,%1,%2,%3};"
        : "+f"(c[0]), "+f"(c[1]), "+f"(c[2]), "+f"(c[3]) : "r"(p), "r"(0x3f803f80u), "r"(q));
}
__device__ __forceinline__ void stat_store(const float (&c)[4], uint32_t dst, int lane) {
    const int g = lane >> 2, t = lane & 3;
    if (t == (g >> 1)) sts32f(dst + g * 4, (g & 1) ? c[1] : c[0]);
    if (g == 7) sts32f(dst + 32 + t * 4, c[2] + c[3]);
}
__device__ __forceinline__ float sum4(float4 v) { return (v.x + v.y) + (v.z + v.w); }
__device__ __forceinline__ void stat_publish(uint32_t src, float* acc, int lane, bool real) {
    const uint32_t a = src + (lane & 15) * 48;
    float q = sum4(lds128f(a)) + sum4(lds128f(a + 16)), sm = sum4(lds128f(a + 32));
    q += __shfl_xor_sync(0xffffffffu, q, 1); sm += __shfl_xor_sync(0xffffffffu, sm, 1);
    q += __shfl_xor_sync(0xffffffffu, q, 2); sm += __shfl_xor_sync(0xffffffffu, sm, 2);
    if (real && (lane & 19) == 0) red_add4(acc + lane, 1.f, sm, q, 1.f);
}
__device__ __forceinline__ void fence_acc(float (&d)[64]) {
#pragma unroll
    for (int i = 0; i < 64; i++) asm volatile("" : "+f"(d[i])::"memory");
}
__device__ __forceinline__ void ld_unit(uint32_t (&u)[4], const uint4* p) {
    asm volatile("ld.relaxed.gpu.global.v4.u32 {%0,%1,%2,%3}, [%4];" : "=r"(u[0]), "=r"(u[1]), "=r"(u[2]), "=r"(u[3]) : "l"(p) : "memory");
}

__device__ __noinline__ void side_jobs(const __nv_bfloat16* __restrict__ t_emb, const __nv_bfloat16* __restrict__ w_emb,
                                       const __nv_bfloat16* __restrict__ w2, Scratch* __restrict__ gs, unsigned clk0) {
    const int tid = threadIdx.x, warp = tid >> 5, lane = tid & 31, j = blockIdx.x;
    float tv = 0.f;
    if (lane < 24) tv = __bfloat162float(t_emb[(lane / 12) * E + j * 192 + warp * 12 + lane % 12]);
    if (tid == 0) {
        mbar_init(BAR(0), 1);
        mbar_expect(BAR(0), 192 * C * 2);
        fence_async_smem();
        while (clock32() - clk0 < W2DELAY) {}
#pragma unroll
        for (int i = 0; i < 4; i++) bulk_g2s(S0 + SM_W + i * 12288, w_emb + (j * 192 + i * 48) * C, 12288, S0 + BAR(0));
    }
    if (j == 0 && tid < 32) gs->acc2[(tid >> 4) * LS + (tid & 15)] = 0.f;
    const float sv = silu_half(0.5f * tv);
    __syncthreads();
    mbar_wait(BAR(0), 0);
    float acc[8] = {0.f, 0.f, 0.f, 0.f, 0.f, 0.f, 0.f, 0.f};
#pragma unroll
    for (int i = 0; i < 12; i++) {
        const float2 wq = lds64f(SM_W + (warp * 12 + i) * 256 + lane * 8);
        const uint32_t wx = __float_as_uint(wq.x), wy = __float_as_uint(wq.y);
#pragma unroll
        for (int bb = 0; bb < 2; bb++) {
            const float sx = __shfl_sync(0xffffffffu, sv, bb * 12 + i);
            acc[4 * bb + 0] = fmaf(sx, bf_lo(wx), acc[4 * bb + 0]); acc[4 * bb + 1] = fmaf(sx, bf_hi(wx), acc[4 * bb + 1]);
            acc[4 * bb + 2] = fmaf(sx, bf_lo(wy), acc[4 * bb + 2]); acc[4 * bb + 3] = fmaf(sx, bf_hi(wy), acc[4 * bb + 3]);
        }
    }
    sts128f(SM_ACT + warp * 1024 + lane * 16, make_float4(acc[0], acc[1], acc[2], acc[3]));
    sts128f(SM_ACT + warp * 1024 + 512 + lane * 16, make_float4(acc[4], acc[5], acc[6], acc[7]));
    __syncthreads();
    if (tid < 128) {
        float2 sum = make_float2(0.f, 0.f);
#pragma unroll
        for (int w = 0; w < 16; w++) { const float2 p = lds64f(SM_ACT + w * 1024 + tid * 8); sum.x += p.x; sum.y += p.y; }
        *reinterpret_cast<float2*>(&gs->emb[j * NB * C + tid * 2]) = sum;
        bar_sync(1, 128);
        if (tid < 2) asm volatile("red.release.gpu.global.add.u32 [%0], 1;" ::"l"(&gs->wcnt[(2 * NB + tid) * LS]) : "memory");
    }
}

__global__ void __cluster_dims__(2, 1, 1) __launch_bounds__(NTHREADS, 1)
resblock_kernel(const __nv_bfloat16* __restrict__ w1,
                const __nv_bfloat16* __restrict__ t_emb, const __nv_bfloat16* __restrict__ g1,
                const __nv_bfloat16* __restrict__ be1, const __nv_bfloat16* __restrict__ w_emb,
                const __nv_bfloat16* __restrict__ g2, const __nv_bfloat16* __restrict__ be2,
                const __nv_bfloat16* __restrict__ w2, __nv_bfloat16* __restrict__ out, Scratch* __restrict__ gs,
                const __grid_constant__ CUtensorMap xmap) {
    const unsigned clk0 = clock32();
    if (threadIdx.x == 480 && blockIdx.x >= NXTRA) TLG(1);
    const int tid = threadIdx.x, lane = tid & 31;
    const int cta = blockIdx.x - NXTRA, b = cta >> 6, r = cta & 63;
    uint4 v[5];
    if (tid < 32) weight_load(v, w1, cta & (NCTA - 1), lane);
    const int warp = __shfl_sync(0xffffffffu, tid >> 5, 0);
    if (cta < 0) { side_jobs(t_emb, w_emb, w2, gs, clk0); return; }

    const int seg = lane & 7;
    if (warp != 3) asm volatile("barrier.cluster.arrive.relaxed.aligned;" ::: "memory");
    const bool has_outer = (r != 0) && (r != HW - 1);
    if (warp == 1 || warp == 2 || warp == 4 || warp == 5) {
        const int g = warp < 3 ? warp - 1 : 7 - warp;
        if (elect_one()) {
            asm volatile("prefetch.tensormap [%0];" ::"l"(&xmap) : "memory");
            mbar_init(BAR(BAR_X) + 8 * g, 1);
            if (g == 3) mbar_init(BAR(BAR_X + 4), 1);
            mbar_expect(BAR(BAR_X) + 8 * g, 4096);
            fence_async_smem();
            while (clock32() - clk0 < XDELAY + g * XSTAG) {}
            tma_x(SM_XOWN + g * 4096, &xmap, r, b * C + g * 32, BAR(BAR_X) + 8 * g);
            if (g == 3 && has_outer) {
                mbar_expect(BAR(BAR_X + 4), 16384);
#pragma unroll
                for (int i = 0; i < 4; i++) tma_x(SM_XOUT + i * 4096, &xmap, r + ((r & 1) ? 1 : -1), b * C + i * 32, BAR(BAR_X + 4));
            }
        }
        __syncwarp();
        bar_arrive(4, 256 + 32 + 128);
        mbar_wait(BAR(BAR_X) + 8 * g, 0);
        if (lane == 0) TL(70 + g);
        float c[2][4] = {{0.f, 0.f, 0.f, 0.f}, {0.f, 0.f, 0.f, 0.f}};
#pragma unroll
        for (int k = 0; k < 8; k++) {
            const uint4 q = lds128(SM_XOWN + g * 4096 + k * 512 + lane * 16);
            stat_mma(c[0], q.x, q.y); stat_mma(c[1], q.z, q.w);
        }
#pragma unroll
        for (int i = 0; i < 4; i++) c[0][i] += c[1][i];
        stat_store(c[0], SM_RED + g * 48, lane);
        __syncwarp();
        if (lane == 0) {
            const uint32_t a = SM_RED + g * 48;
            red_add4(&gs->acc1[b * 4 * LS + g * GS1], 1.f, sum4(lds128f(a + 32)), sum4(lds128f(a)) + sum4(lds128f(a + 16)), 1.f);
            TL(74 + g);
        }
    }
    if (warp == 0 || warp == 4) {
        const int k = warp >> 2;
        if (k == 0) {
#pragma unroll
            for (int i = 0; i < 5; i++)
                if (i < 4 || lane < 16) sts128(SM_BNC + (lane + 32 * i) * 16, v[i]);
            if (lane == 0) TL(81);
            __syncwarp();
        } else {
            bar_sync(6, 64);
            mbar_wait(BAR(BAR_W2), 0);
        }
        weight_block(SM_BNC + k * 2304, gs->wt + k * NSTAGE * STAGE_BYTES, cta, lane, k == 0);
        __syncwarp();
        if (lane == 0) TL(k ? 13 : 4);
        if (k == 0 && lane < 2) asm volatile("red.relaxed.gpu.global.add.u32 [%0], 1;" ::"l"(&gs->wcnt[lane * LS + (cta >> 4)]) : "memory");
    }

    if (warp >= 8) {
        const int nw = warp - 8;
        bar_sync(4, 256 + 32 + 128);
        const int par = nw >> 2, wq = nw & 3;
        const uint32_t act_off = SM_ACT + (par * 2 + (lane >> 4)) * CH_PITCH + (2 + wq * 16 + (lane & 15)) * 16;
        const uint32_t stg_off = (par * 16 + (lane >> 4) * 8 + (lane & 7)) * 128 + (((2 * wq + ((lane >> 3) & 1)) ^ (lane & 7)) << 4);
        const uint32_t cfa = SM_COEF + par * 128 + (lane & 3) * 16;
        const uint32_t fbar = BAR(BAR_FULL) + 8 * par;
        uint4* inbox = gs->box + cta * 1024 + nw * 32 + lane;
#pragma unroll 1
        for (int conv = 0; conv < 2; conv++) {
            uint32_t u[4][4], w[4][4];
            float4 cf[8];
            if (conv == 0) {
                mbar_wait(BAR(BAR_X), 0); ldsm4t(u[0], SM_XOWN + stg_off);
                mbar_wait(BAR(BAR_X + 1), 0); ldsm4t(u[1], SM_XOWN + stg_off + 4096);
                mbar_wait(BAR(BAR_STATS), 0);
                if (tid == 256) TL(22);
                norm_block<0, 1>(u, cf, true, cfa, act_off, ~0u, fbar, lane);
                if (tid == 256) TL(8);
                mbar_wait(BAR(BAR_X + 2), 0); ldsm4t(u[2], SM_XOWN + stg_off + 8192);
                mbar_wait(BAR(BAR_STATS + 1), 0);
                norm_block<1, 1>(u, cf, true, cfa, act_off, ~0u, fbar, lane);
                mbar_wait(BAR(BAR_X + 3), 0); ldsm4t(u[3], SM_XOWN + stg_off + 12288);
                mbar_wait(BAR(BAR_STATS + 2), 0);
                norm_block<2, 1>(u, cf, true, cfa, act_off, ~0u, fbar, lane);
                mbar_wait(BAR(BAR_STATS + 3), 0);
                norm_block<3, 1>(u, cf, true, cfa, act_off, ~0u, fbar, lane);
            } else {
                mbar_wait(BAR(BAR_HW), 0);
#pragma unroll
                for (int i = 0; i < 4; i++) ldsm4(u[i], act_off + i * 2 * KC_BYTES);
                mbar_wait(BAR(BAR_STATS + 1), 1);
                mbar_wait(BAR(BAR_STATS), 1);
                if (tid == 256) TL(26);
                norm_block<0, 2>(u, cf, true, cfa, act_off, ~0u, fbar, lane);
                if (tid == 256) TL(16);
                mbar_wait(BAR(BAR_STATS + 2), 1);
                mbar_wait(BAR(BAR_STATS + 3), 1);
                norm_block<2, 2>(u, cf, true, cfa, act_off, ~0u, fbar, lane);
            }
            if (tid == 256) TL(84 + conv);
            if (has_outer) {
                mbar_wait(BAR(BAR_X + 4), conv);
                if (conv == 0) {
#pragma unroll
                    for (int i = 0; i < 4; i++) ldsm4t(w[i], SM_XOUT + stg_off + i * 4096);
                } else {
#pragma unroll
                    for (int i = 0; i < 4; i++) {
                        const uint4 q = lds128(SM_XOUT + (tid - 256) * 16 + i * 4096);
                        w[i][0] = q.x; w[i][1] = q.y; w[i][2] = q.z; w[i][3] = q.w;
                    }
                    unsigned it = 0;
                    while (true) {
                        bool ok = true;
#pragma unroll
                        for (int i = 0; i < 16; i++) ok = ok && w[i >> 2][i & 3] != 0;
                        if (__all_sync(0xffffffffu, ok) || ++it > SPIN_LIMIT) break;
#pragma unroll
                        for (int i = 0; i < 4; i++) ld_unit(w[i], inbox + i * 256);
                    }
#pragma unroll
                    for (int i = 0; i < 16; i++) w[i >> 2][i & 3] = ~w[i >> 2][i & 3];
                }
            }
            bar_sync(3, 256);
            if (nw == 0) sts128(SM_ACT + 2 * ROW_BYTES + (lane >> 1) * CH_PITCH + (lane & 1) * 16, make_uint4(0, 0, 0, 0));
            if (tid == 256) TL(24 + conv * 4);
            norm_block<0, 4>(w, cf, false, cfa, act_off + 2 * ROW_BYTES, has_outer ? ~0u : 0u, fbar + 128, lane);
            if (tid == 256) TL(23 + conv * 4);
        }
        if (has_outer) {
            mbar_wait(BAR(BAR_FULL + NSTAGE - 1), 1);
#pragma unroll
            for (int i = 0; i < 4; i++) inbox[i * 256] = make_uint4(0, 0, 0, 0);
        }
    } else if (warp < 4) {
        const int wq = warp;
        if (wq == 3) {
            if (elect_one()) {
#pragma unroll
                for (int i = 0; i < NSTAGE; i++) mbar_init(BAR(BAR_FULL + i), (i >> 3) == 1 ? 1 : 5);
#pragma unroll
                for (int i = 0; i <= NS; i++) mbar_init(BAR(BAR_WEMPTY + i), 4);
#pragma unroll
                for (int i = BAR_STATS; i < BAR_X; i++) mbar_init(BAR(i), i == BAR_EMB ? 3 : 1);
                asm volatile("fence.mbarrier_init.release.cluster;" ::: "memory");
            }
            __syncwarp();
            fence_async_smem();
            bar_arrive(0, 96);
            bar_arrive(5, 96);
            bar_arrive(4, 256 + 32 + 128);
            const uint4 z = make_uint4(0, 0, 0, 0);
#pragma unroll
            for (int i = 0; i < 2; i++) sts128(SM_ACT + (i * 16 + (lane >> 1)) * CH_PITCH + (lane & 1) * 16, z);
            if (lane < 4) sts128(SM_ACT + (2 + (lane >> 1)) * ROW_BYTES + (lane & 1) * 16, z);
            if (lane < 16) sts128(SM_ONES + lane * 16, make_uint4(lane < 8 ? 0x3f803f80u : 0u, 0, 0, 0));
            fence_async_smem();
            asm volatile("barrier.cluster.arrive.release.aligned;" ::: "memory");
            bar_arrive(6, 64);
            if (elect_one()) {
                mbar_expect(BAR(BAR_W2), 2304);
                while (clock32() - clk0 < W2DELAY) {}
                const char* base = reinterpret_cast<const char*>(w2) + ((cta & 15) * 8 * C + (cta >> 4) * 16) * 18;
#pragma unroll 1
                for (int i = 0; i < 8; i++) bulk_g2s(S0 + SM_BNC + 2304 + i * 288, base + i * (C * 18), 288, S0 + BAR(BAR_W2));
            }
            __syncwarp();
        }
        bar_sync(2, 128);

        float d[64];
#pragma unroll
        for (int i = 0; i < 64; i++) d[i] = 0.f;
#pragma unroll 1
        for (int conv = 0; conv < 2; conv++) {
            fence_acc(d);
            mma_stages<0>(d, conv, tid, gs);
            if (conv == 0) {
                asm volatile("wgmma.fence.sync.aligned;" ::: "memory");
                wgmma128<(SM_ONES >> 4) | (8u << 16), (SM_EMB >> 4), 0, 8>(d);
                asm volatile("wgmma.commit_group.sync.aligned;" ::: "memory");
            }
            asm volatile("wgmma.wait_group.sync.aligned 0;" ::: "memory");
            fence_acc(d);
            if (tid == 0) TL(10 + conv * 8);
            if (conv == 1) break;

            uint32_t hp[32];
#pragma unroll
            for (int g = 0; g < 4; g++) {
                float c[4] = {0.f, 0.f, 0.f, 0.f};
#pragma unroll
                for (int i = 0; i < 8; i++) hp[8 * g + i] = pack_bf(d[16 * g + 2 * i], d[16 * g + 2 * i + 1]);
#pragma unroll
                for (int i = 0; i < 4; i++) stat_mma(c, hp[8 * g + 2 * i], hp[8 * g + 2 * i + 1]);
                stat_store(c, SM_RED + (g * 4 + wq) * 48, lane);
            }
            bar_sync(2, 128);
            if (wq == 0) stat_publish(SM_RED, &gs->acc2[b * LS], lane, true);
            if (tid == 0) TL(11);
            const uint32_t hbase = SM_ACT + (lane >> 4) * CH_PITCH + (2 + wq * 16 + (lane & 15)) * 16;
#pragma unroll
            for (int kc = 0; kc < 8; kc++) stsm4(hbase + kc * 2 * CH_PITCH, hp[4 * kc], hp[4 * kc + 1], hp[4 * kc + 2], hp[4 * kc + 3]);
            __syncwarp();
            if (lane == 0) mbar_arrive(BAR(BAR_HW));
            if (lane < LAG) mbar_arrive(BAR(BAR_WEMPTY + (NSTAGE - LAG) % NS) + 8 * lane);
            if (has_outer) {
                uint4* outbox = gs->box + (cta + ((r & 1) ? 1 : -1)) * 1024 + tid;
#pragma unroll
                for (int kc = 0; kc < 8; kc++) outbox[kc * 128] = make_uint4(~hp[4 * kc], ~hp[4 * kc + 1], ~hp[4 * kc + 2], ~hp[4 * kc + 3]);
            }
            if (tid == 0) TL(12);
            const uint32_t xbase = SM_XOWN + ((lane >> 4) * 8 + (lane & 7)) * 128 + (((2 * wq + ((lane >> 3) & 1)) ^ (lane & 7)) << 4);
#pragma unroll
            for (int kc = 0; kc < 8; kc++) {
                uint32_t p[4];
                ldsm4t(p, xbase + kc * 2048);
#pragma unroll
                for (int i = 0; i < 4; i++) { d[8 * kc + 2 * i] = bf_lo(p[i]); d[8 * kc + 2 * i + 1] = bf_hi(p[i]); }
            }
        }
        {
            const uint32_t obase = slot_addr(0) + ((lane >> 4) * 8 + (lane & 7)) * OUT_PITCH + (wq * 16 + ((lane >> 3) & 1) * 8) * 2;
#pragma unroll
            for (int kc = 0; kc < 8; kc++) {
                stsm4t(obase + kc * 16 * OUT_PITCH, pack_bf(d[8 * kc + 0], d[8 * kc + 1]), pack_bf(d[8 * kc + 2], d[8 * kc + 3]),
                       pack_bf(d[8 * kc + 4], d[8 * kc + 5]), pack_bf(d[8 * kc + 6], d[8 * kc + 7]));
            }
            bar_sync(2, 128);
            const int oc0 = tid >> 3;
            __nv_bfloat16* dst = out + ((size_t)(b * C + oc0) * HW + r) * HW + seg * 8;
#pragma unroll
            for (int i = 0; i < 8; i++)
                *reinterpret_cast<uint4*>(dst + (size_t)i * 16 * HW * HW) = lds128(slot_addr(0) + (oc0 + 16 * i) * OUT_PITCH + seg * 16);
            if (tid == 0) { TL(20); TLG(21); }
        }
    } else if (warp < 6) {
        bar_sync(5, 96);
        if (warp == 5) {
            asm volatile("barrier.cluster.wait.acquire.aligned;" ::: "memory");
            const uint32_t peer = (r & 1) ^ 1;
            const uint32_t self0 = mapa(0, r & 1), peer0 = mapa(0, peer);
#pragma unroll 1
            for (int conv = 0; conv < 2; conv++) {
#pragma unroll 1
                for (int kc = 0; kc < 8; kc++) {
                    mbar_wait(BAR(BAR_FULL) + 8 * kc, conv);
                    if (elect_one())
                        asm volatile("cp.async.bulk.shared::cluster.shared::cta.mbarrier::complete_tx::bytes [%0], [%1], %2, [%3];"
                                     ::"r"(peer0 + SM_ACT + ROW_BYTES + kc * KC_BYTES), "r"(self0 + SM_ACT + kc * KC_BYTES), "r"(KC_BYTES),
                                       "r"(peer0 + BAR(BAR_FULL + 8) + 8 * kc) : "memory");
                }
                if (lane == 0) TL(86 + conv);
#pragma unroll 1
                for (int kc = 0; kc < 8; kc++) mbar_wait(BAR(BAR_FULL + 8) + 8 * kc, conv);
                if (lane == 0)
                    asm volatile("mbarrier.arrive.release.cluster.shared::cluster.b64 _, [%0];" ::"r"(peer0 + (conv ? BAR(BAR_ACK) : BAR(BAR_EMB))) : "memory");
            }
            mbar_wait(BAR(BAR_ACK), 0);
        } else {
            if (lane < 2) asm volatile("red.release.gpu.global.add.u32 [%0], 1;" ::"l"(&gs->wcnt[(NB + lane) * LS]) : "memory");
            if (lane == 0) TL(14);
            mbar_wait(BAR(BAR_STATS + 3), 0);
            unsigned it = 0;
            while (ld_relaxed(&gs->wcnt[(2 * NB + b) * LS]) < (unsigned)NXTRA && ++it < SPIN_LIMIT) __nanosleep(100);
            fence_acquire();
            float ev[4] = {0.f, 0.f, 0.f, 0.f};
#pragma unroll
            for (int j = 0; j < NXTRA; j++) {
                const uint4 ef = ld_relaxed_v4(&gs->emb[(j * NB + b) * C + lane * 4]);
                ev[0] += __uint_as_float(ef.x); ev[1] += __uint_as_float(ef.y); ev[2] += __uint_as_float(ef.z); ev[3] += __uint_as_float(ef.w);
            }
#pragma unroll
            for (int i = 0; i < 4; i++) {
                const float hi = bf_lo(pack_bf(ev[i], 0.f));
                sts128(SM_EMB + (lane * 4 + i) * 16, make_uint4(pack_bf(hi, ev[i] - hi), 0, 0, 0));
            }
            fence_async_smem();
            __syncwarp();
            if (lane == 0) { mbar_arrive(BAR(BAR_EMB)); TL(19); }
        }
    } else if (warp == 6) {
        bar_sync(0, 96);
        const uint32_t ebytes = STAGE_BYTES + ((lane >> 3) == 1 ? KC_BYTES : 0);
        if (lane < NSTAGE) mbar_expect(BAR(BAR_FULL) + 8 * lane, ebytes);
        const int swap = (r & 1) ? 0 : 8 * STAGE_BYTES;
        unsigned it = 0;
        {
            int g = 0;
#pragma unroll 1
            while (g < NS) {
                unsigned ready = __ballot_sync(0xffffffffu, ld_relaxed(&gs->wcnt[b * LS + (lane & 7)]) >= 16u) >> g;
                if (++it > SPIN_LIMIT) ready = ~0u;
                if (!(ready & 1)) continue;
                fence_acquire();
                fence_async_global();
                if (lane == 0) TL(g ? 3 : 6);
#pragma unroll 1
                for (; (ready & 1) && g < NS; g++, ready >>= 1)
                    if (elect_one())
                        bulk_g2s(S0 + SM_W + g * STAGE_BYTES, gs->wt + g * STAGE_BYTES + (g >= 8 ? swap : 0), STAGE_BYTES, S0 + BAR(BAR_FULL) + 8 * g);
            }
        }
#pragma unroll 1
        for (int q = 3; q < 12; q++) {
            const int conv = q >= 6, qs = conv ? q - 6 : q, sl = q % 3;
            const unsigned char* wsrc = gs->wt + q * 4 * STAGE_BYTES + (qs < 2 ? 0 : (qs < 4 ? swap : -swap));
            const uint32_t par = (q / 3 - 1) & 1;
            if (q == 6) {
                it = 0;
                while (ld_relaxed(&gs->wcnt[(NB + b) * LS]) < (unsigned)NCTA && ++it < SPIN_LIMIT) {}
                fence_acquire();
                fence_async_global();
                if (lane == 0) { mbar_arrive(BAR(BAR_EMB)); TL(2); }
            }
#pragma unroll
            for (int i = 0; i < 4; i++) {
                mbar_wait(BAR(BAR_WEMPTY + i) + 32 * sl, par);
                if (i == 0 && (q == 6 || q == 9)) {
                    if ((lane >= NS) == (q == 9) && lane < NSTAGE) mbar_expect(BAR(BAR_FULL) + 8 * lane, ebytes);
                    __syncwarp();
                }
                if (elect_one())
                    bulk_g2s(S0 + SM_W + (sl * 4 + i) * STAGE_BYTES, wsrc + i * STAGE_BYTES, STAGE_BYTES, S0 + BAR(BAR_FULL + i) + 32 * qs);
            }
        }
    } else {
        const uint2 ga1 = __ldg(reinterpret_cast<const uint2*>(g1) + lane), bt1 = __ldg(reinterpret_cast<const uint2*>(be1) + lane);
        const uint2 ga2 = __ldg(reinterpret_cast<const uint2*>(g2) + lane), bt2 = __ldg(reinterpret_cast<const uint2*>(be2) + lane);
        bar_sync(0, 96);
#pragma unroll 1
        for (int conv = 0; conv < 2; conv++) {
            if (conv == 1) mbar_wait(BAR(BAR_EMB), 0);
            const float* asrc = conv ? &gs->acc2[b * LS + (lane >> 3) * 4] : &gs->acc1[b * 4 * LS + (lane >> 3) * GS1];
            while (clock32() - clk0 < PD) {}
            const uint2 ga = conv ? ga2 : ga1, bt = conv ? bt2 : bt1;
            bool done = false;
            unsigned it = 0;
#pragma unroll 1
            while (true) {
                const uint4 f = ld_relaxed_v4(asrc);
                const bool fresh = !done && (((f.x == 0x42800000u) & (f.w == 0x42800000u)) || it > SPIN_LIMIT);
                it++;
                if (!__any_sync(0xffffffffu, fresh)) continue;
                if (lane == 0 && fresh) TL(7 + conv * 8);
                if (lane == 24 && fresh) TL(90 + conv);
                const float inv_n = 1.0f / (32.0f * HW * HW);
                const float mean = __uint_as_float(f.y) * inv_n;
                const float var = fmaxf(fmaf(-mean, mean, __uint_as_float(f.z) * inv_n), 0.f);
                const float rs = 0.5f * rsqrtf(var + 1e-5f);
                float4 k0, k1;
                k0.x = rs * bf_lo(ga.x); k0.y = rs * bf_hi(ga.x); k1.x = rs * bf_lo(ga.y); k1.y = rs * bf_hi(ga.y);
                k0.z = fmaf(-mean, k0.x, 0.5f * bf_lo(bt.x)); k0.w = fmaf(-mean, k0.y, 0.5f * bf_hi(bt.x));
                k1.z = fmaf(-mean, k1.x, 0.5f * bf_lo(bt.y)); k1.w = fmaf(-mean, k1.y, 0.5f * bf_hi(bt.y));
                if (fresh) {
                    sts128f(SM_COEF + lane * 32, k0);
                    sts128f(SM_COEF + lane * 32 + 16, k1);
                }
                __syncwarp();
                if (fresh && (lane & 7) == 0) mbar_arrive(BAR(BAR_STATS) + lane);
                done = done || fresh;
                if (__all_sync(0xffffffffu, done)) break;
            }
        }
        if (has_outer && elect_one()) {
            mbar_expect(BAR(BAR_X + 4), 16384);
            bulk_g2s(S0 + SM_XOUT, gs->box + cta * 1024, 16384, S0 + BAR(BAR_X + 4));
        }
        if (r == 0) {
            if (lane < 16) gs->acc1[b * 4 * LS + (lane >> 2) * GS1 + (lane & 3)] = 0.f;
            if (lane < 24) gs->wcnt[((lane >> 3) * NB + b) * LS + (lane & 7)] = 0;
        }
    }
}

}

extern "C" void kernel_launch(void* const* d_in, const int* in_sizes, int n_in, void* d_out, int out_size) {
    (void)in_sizes; (void)n_in; (void)out_size;
    typedef CUresult (*EncodeFn)(CUtensorMap*, CUtensorMapDataType, cuuint32_t, void*, const cuuint64_t*, const cuuint64_t*,
                                 const cuuint32_t*, const cuuint32_t*, CUtensorMapInterleave, CUtensorMapSwizzle,
                                 CUtensorMapL2promotion, CUtensorMapFloatOOBfill);
    static Scratch* gs = nullptr;
    static EncodeFn encode = nullptr;
    if (!gs) {
        cudaFuncSetAttribute(resblock_kernel, cudaFuncAttributeMaxDynamicSharedMemorySize, SM_TOTAL);
        cudaGetSymbolAddress((void**)&gs, g_scratch);
        cudaDriverEntryPointQueryResult qr;
        cudaGetDriverEntryPoint("cuTensorMapEncodeTiled", (void**)&encode, cudaEnableDefault, &qr);
    }
    CUtensorMap xmap;
    const cuuint64_t dims[3] = {HW, HW, NB * C}, strides[2] = {HW * 2, HW * HW * 2};
    const cuuint32_t box[3] = {HW, 1, 32}, es[3] = {1, 1, 1};
    encode(&xmap, CU_TENSOR_MAP_DATA_TYPE_BFLOAT16, 3, d_in[0], dims, strides, box, es, CU_TENSOR_MAP_INTERLEAVE_NONE,
           CU_TENSOR_MAP_SWIZZLE_128B, CU_TENSOR_MAP_L2_PROMOTION_NONE, CU_TENSOR_MAP_FLOAT_OOB_FILL_NONE);
    resblock_kernel<<<NCTA + NXTRA, NTHREADS, SM_TOTAL>>>(
        (const __nv_bfloat16*)d_in[4], (const __nv_bfloat16*)d_in[1],
        (const __nv_bfloat16*)d_in[2], (const __nv_bfloat16*)d_in[3], (const __nv_bfloat16*)d_in[5],
        (const __nv_bfloat16*)d_in[6], (const __nv_bfloat16*)d_in[7], (const __nv_bfloat16*)d_in[8],
        (__nv_bfloat16*)d_out, gs, xmap);
}
```

```cpp
#include <cuda_runtime.h>
#include <cuda.h>
#include <cuda_bf16.h>
#include <stdint.h>

namespace {

constexpr int C = 128, HW = 64, NB = 2, E = 768;
constexpr int NCTA = NB * HW;
constexpr int NXTRA = 4;
constexpr int NTHREADS = 16 * 32;
constexpr int CH_PITCH = 66 * 16;
constexpr int ROW_BYTES = 16 * CH_PITCH;
constexpr int STEP_BYTES = 4096;
constexpr int STAGE_BYTES = 3 * STEP_BYTES;
constexpr int NSTAGE = 24;
constexpr int KC_BYTES = 2 * CH_PITCH;
constexpr int NS = 12;
constexpr int LAG = 1;
#define XDELAY 700
#define HDELAY 600
#define NA 3
#define RB 1
#define XSTAG2 100
#define XSTAG 600
#define HSEND 0
#define W2DELAY 2000

constexpr uint32_t SMEM_BASE = 0x400;
constexpr uint32_t SM_XOWN = SMEM_BASE;
constexpr uint32_t SM_ACT = SM_XOWN + 16384 + 512;
constexpr uint32_t SM_XOUT = SM_ACT + 2 * ROW_BYTES + 512;
static_assert(SM_XOUT % 1024 == 0, "swizzle atom alignment");
constexpr uint32_t SM_W = SM_ACT + 3 * ROW_BYTES + 128;
__host__ __device__ constexpr uint32_t slot_addr(int slot) { return SM_W + slot * STAGE_BYTES; }
constexpr uint32_t SM_COEF = SM_W + NS * STAGE_BYTES;
constexpr uint32_t SM_EMB = SM_COEF + 1024;
constexpr uint32_t SM_ONES = SM_EMB + 2048;
constexpr uint32_t SM_RED = SM_ONES + 256;
constexpr uint32_t SM_BNC = SM_RED + 1280;
constexpr uint32_t SM_BAR = SM_BNC + 2 * 2304;
constexpr int BAR_FULL = 0, BAR_WEMPTY = NSTAGE, BAR_HW = BAR_WEMPTY + NS, BAR_STATS = BAR_HW + 1  ,
              BAR_EMB = BAR_STATS + 3, BAR_ACK = BAR_EMB + 1, BAR_W2 = BAR_ACK + 1, BAR_X = BAR_W2 + 1  , NBAR = BAR_X + 5;
constexpr int SM_TOTAL = SM_BAR + NBAR * 8 - SMEM_BASE;
static_assert(SM_TOTAL <= 232448, "smem");
static_assert(NBAR <= 96, "barrier init");
constexpr int OUT_PITCH = 144;
__host__ __device__ constexpr uint32_t BAR(int i) { return SM_BAR + 8 * i; }
__host__ __device__ constexpr int ky_of(int kyo) { return kyo == 0 ? 1 : (kyo == 1 ? 0 : 2); }

constexpr unsigned SPIN_LIMIT = 1u << 16;

#define LS 1056
#define GS1 4
#define PD 0
struct Scratch {
    float acc1[NB * 4 * LS];
    float acc2[NB * LS];
    unsigned wcnt[3 * NB * LS];
    float emb[NXTRA * NB * C];
    unsigned char wt[2 * NSTAGE * STAGE_BYTES];
    uint4 box[NCTA * 1024];
};
__device__ __align__(1024) Scratch g_scratch;
#define TL(i) do {} while (0)
#define TLG(i) do {} while (0)

__device__ __forceinline__ unsigned clock32() { unsigned c; asm volatile("mov.u32 %0, %%clock;" : "=r"(c)); return c; }
__device__ __forceinline__ uint32_t mapa(uint32_t a, uint32_t rank) {
    uint32_t d;
    asm("mapa.shared::cluster.u32 %0, %1, %2;" : "=r"(d) : "r"(a), "r"(rank));
    return d;
}
#define S0 mapa(0, blockIdx.x & 1)
__device__ __forceinline__ void mbar_init(uint32_t bar, int cnt) {
    asm volatile("mbarrier.init.shared::cta.b64 [%0], %1;" ::"r"(bar + S0), "r"(cnt) : "memory");
}
__device__ __forceinline__ void mbar_arrive(uint32_t bar) {
    asm volatile("mbarrier.arrive.shared::cta.b64 _, [%0];" ::"r"(bar + S0) : "memory");
}
__device__ __forceinline__ void mbar_expect(uint32_t bar, uint32_t bytes) {
    asm volatile("mbarrier.arrive.expect_tx.shared::cta.b64 _, [%0], %1;" ::"r"(bar + S0), "r"(bytes) : "memory");
}
__device__ __forceinline__ bool mbar_try(uint32_t bar, uint32_t par) {
    uint32_t ok;
    asm volatile("{\n.reg .pred p;\nmbarrier.try_wait.parity.shared::cta.b64 p, [%1], %2;\nselp.u32 %0, 1, 0, p;\n}"
                 : "=r"(ok) : "r"(bar + S0), "r"(par) : "memory");
    return ok;
}
__device__ __forceinline__ bool mbar_test(uint32_t bar, uint32_t par) {
    uint32_t ok;
    asm volatile("{\n.reg .pred p;\nmbarrier.test_wait.parity.shared::cta.b64 p, [%1], %2;\nselp.u32 %0, 1, 0, p;\n}"
                 : "=r"(ok) : "r"(bar + S0), "r"(par) : "memory");
    return ok;
}
__device__ __forceinline__ void mbar_wait(uint32_t bar, uint32_t par) {
    unsigned it = 0;
#pragma unroll 1
    while (!mbar_try(bar, par) && ++it < SPIN_LIMIT) {}
}
__device__ __forceinline__ bool elect_one() {
    uint32_t p;
    asm volatile("{\n.reg .pred p;\nelect.sync _|p, 0xffffffff;\nselp.u32 %0, 1, 0, p;\n}" : "=r"(p));
    return p;
}
__device__ __forceinline__ void fence_async_smem() { asm volatile("fence.proxy.async.shared::cta;" ::: "memory"); }
__device__ __forceinline__ void fence_async_global() { asm volatile("fence.proxy.async.global;" ::: "memory"); }
__device__ __forceinline__ void fence_acquire() { asm volatile("fence.acquire.gpu;" ::: "memory"); }
__device__ __forceinline__ void bar_sync(int id, int n) { asm volatile("bar.sync %0, %1;" ::"r"(id), "r"(n) : "memory"); }
__device__ __forceinline__ void bar_arrive(int id, int n) { asm volatile("bar.arrive %0, %1;" ::"r"(id), "r"(n) : "memory"); }
__device__ __forceinline__ void bulk_g2s(uint32_t dst, const void* src, uint32_t bytes, uint32_t bar) {
    asm volatile("cp.async.bulk.shared::cluster.global.mbarrier::complete_tx::bytes [%0], [%1], %2, [%3];"
                 ::"r"(dst), "l"(src), "r"(bytes), "r"(bar) : "memory");
}
__device__ __forceinline__ void tma_x(uint32_t dst, const CUtensorMap* tm, int row, int ch, uint32_t bar) {
    asm volatile("cp.async.bulk.tensor.3d.shared::cluster.global.mbarrier::complete_tx::bytes [%0], [%1, {%2, %3, %4}], [%5];"
                 ::"r"(dst + S0), "l"(tm), "r"(0), "r"(row), "r"(ch), "r"(bar + S0) : "memory");
}
__device__ __forceinline__ uint4 ld_relaxed_v4(const void* p) {
    uint4 v;
    asm volatile("ld.relaxed.gpu.global.v4.u32 {%0,%1,%2,%3}, [%4];" : "=r"(v.x), "=r"(v.y), "=r"(v.z), "=r"(v.w) : "l"(p) : "memory");
    return v;
}
__device__ __forceinline__ unsigned ld_relaxed(const void* p) {
    unsigned v;
    asm volatile("ld.relaxed.gpu.global.u32 %0, [%1];" : "=r"(v) : "l"(p) : "memory");
    return v;
}
__device__ __forceinline__ void red_add4(float* p, float a, float b, float c, float d) {
    asm volatile("red.relaxed.gpu.global.add.v4.f32 [%0], {%1,%2,%3,%4};" ::"l"(p), "f"(a), "f"(b), "f"(c), "f"(d) : "memory");
}
__device__ __forceinline__ void sts128(uint32_t a, uint4 v) {
    asm volatile("st.shared.v4.u32 [%0], {%1,%2,%3,%4};" ::"r"(a + S0), "r"(v.x), "r"(v.y), "r"(v.z), "r"(v.w) : "memory");
}
__device__ __forceinline__ void sts128f(uint32_t a, float4 v) {
    asm volatile("st.shared.v4.f32 [%0], {%1,%2,%3,%4};" ::"r"(a + S0), "f"(v.x), "f"(v.y), "f"(v.z), "f"(v.w) : "memory");
}
__device__ __forceinline__ void sts32f(uint32_t a, float v) { asm volatile("st.shared.f32 [%0], %1;" ::"r"(a + S0), "f"(v) : "memory"); }
__device__ __forceinline__ uint4 lds128(uint32_t a) {
    uint4 v;
    asm volatile("ld.shared.v4.u32 {%0,%1,%2,%3}, [%4];" : "=r"(v.x), "=r"(v.y), "=r"(v.z), "=r"(v.w) : "r"(a + S0) : "memory");
    return v;
}
__device__ __forceinline__ float4 lds128f(uint32_t a) {
    float4 v;
    asm volatile("ld.shared.v4.f32 {%0,%1,%2,%3}, [%4];" : "=f"(v.x), "=f"(v.y), "=f"(v.z), "=f"(v.w) : "r"(a + S0) : "memory");
    return v;
}
__device__ __forceinline__ float2 lds64f(uint32_t a) {
    float2 v;
    asm volatile("ld.shared.v2.f32 {%0,%1}, [%2];" : "=f"(v.x), "=f"(v.y) : "r"(a + S0) : "memory");
    return v;
}
__device__ __forceinline__ float bf_lo(uint32_t u) { return __uint_as_float(u << 16); }
__device__ __forceinline__ float bf_hi(uint32_t u) { return __uint_as_float(u & 0xffff0000u); }
__device__ __forceinline__ uint32_t pack_bf(float lo, float hi) {
    uint32_t r;
    asm("cvt.rn.bf16x2.f32 %0, %1, %2;" : "=r"(r) : "f"(hi), "f"(lo));
    return r;
}
__device__ __forceinline__ float tanh_fast(float x) {
    float r;
    asm("tanh.approx.f32 %0, %1;" : "=f"(r) : "f"(x));
    return r;
}
__device__ __forceinline__ float silu_half(float h) { return fmaf(h, tanh_fast(h), h); }
__device__ __forceinline__ void ldsm4(uint32_t (&u)[4], uint32_t a) {
    asm volatile("ldmatrix.sync.aligned.m8n8.x4.shared.b16 {%0,%1,%2,%3}, [%4];"
                 : "=r"(u[0]), "=r"(u[1]), "=r"(u[2]), "=r"(u[3]) : "r"(a + S0) : "memory");
}
__device__ __forceinline__ void ldsm4t(uint32_t (&u)[4], uint32_t a) {
    asm volatile("ldmatrix.sync.aligned.m8n8.x4.trans.shared.b16 {%0,%1,%2,%3}, [%4];"
                 : "=r"(u[0]), "=r"(u[1]), "=r"(u[2]), "=r"(u[3]) : "r"(a + S0) : "memory");
}
__device__ __forceinline__ void stsm4(uint32_t a, uint32_t p0, uint32_t p1, uint32_t p2, uint32_t p3) {
    asm volatile("stmatrix.sync.aligned.m8n8.x4.shared.b16 [%0], {%1,%2,%3,%4};" ::"r"(a + S0), "r"(p0), "r"(p1), "r"(p2), "r"(p3) : "memory");
}
__device__ __forceinline__ void stsm4t(uint32_t a, uint32_t p0, uint32_t p1, uint32_t p2, uint32_t p3) {
    asm volatile("stmatrix.sync.aligned.m8n8.x4.trans.shared.b16 [%0], {%1,%2,%3,%4};" ::"r"(a + S0), "r"(p0), "r"(p1), "r"(p2), "r"(p3) : "memory");
}

#define R8(o) "+f"(d[o]), "+f"(d[o + 1]), "+f"(d[o + 2]), "+f"(d[o + 3]), "+f"(d[o + 4]), "+f"(d[o + 5]), "+f"(d[o + 6]), "+f"(d[o + 7])
template <uint32_t ALO, uint32_t BLO, uint64_t AHI = 8, uint64_t BHI = 48>
__device__ __forceinline__ void wgmma128(float (&d)[64]) {
    asm volatile(
        "wgmma.mma_async.sync.aligned.m64n128k16.f32.bf16.bf16 "
        "{%0,%1,%2,%3,%4,%5,%6,%7,%8,%9,%10,%11,%12,%13,%14,%15,%16,%17,%18,%19,%20,%21,%22,%23,%24,%25,%26,%27,%28,%29,%30,%31,"
        "%32,%33,%34,%35,%36,%37,%38,%39,%40,%41,%42,%43,%44,%45,%46,%47,%48,%49,%50,%51,%52,%53,%54,%55,%56,%57,%58,%59,%60,%61,%62,%63},"
        " %64, %65, 1, 1, 1, 0, 0;"
        : R8(0), R8(8), R8(16), R8(24), R8(32), R8(40), R8(48), R8(56)
        : "l"((AHI << 32) | ALO), "l"((BHI << 32) | BLO));
}
template <int S>
__device__ __forceinline__ void mma_stages(float (&d)[64], int conv, int tid, Scratch* gs) {
    constexpr uint32_t A = ((SM_ACT + S * 2 * CH_PITCH + 16) >> 4) | ((CH_PITCH >> 4) << 16);
    constexpr uint32_t B = (slot_addr(S % NS) >> 4) | (8u << 16);
    if (S == 0) mbar_wait(BAR(BAR_FULL), conv);
    bool next_ok = true;
    constexpr uint32_t NEXT = S + 1 < NSTAGE ? BAR(BAR_FULL + S + 1) : BAR(BAR_EMB);
    const int npar = S + 1 < NSTAGE ? conv : 0;
    next_ok = mbar_test(NEXT, npar);
    if (S == 0 && tid == 0) TL(32 + conv * 24);
    asm volatile("wgmma.fence.sync.aligned;" ::: "memory");
    wgmma128<A, B>(d);
    wgmma128<A + 1, B + 16>(d);
    wgmma128<A + 2, B + 32>(d);
    asm volatile("wgmma.commit_group.sync.aligned;" ::: "memory");
    if (S >= LAG) {
        asm volatile("wgmma.wait_group.sync.aligned %0;" ::"n"(LAG) : "memory");
        if ((tid & 31) == 0) mbar_arrive(BAR(BAR_WEMPTY + (S + NS - LAG) % NS));
    }
    if (!next_ok) mbar_wait(NEXT, npar);
    if constexpr (S + 1 < NSTAGE) mma_stages<S + 1>(d, conv, tid, gs);
}

__device__ __forceinline__ void weight_load(uint4 (&t)[5], const __nv_bfloat16* w, int cta, int lane) {
    const char* base = reinterpret_cast<const char*>(w) + ((cta & 15) * 8 * C + (cta >> 4) * 16) * 18;
#pragma unroll
    for (int k = 0; k < 5; k++) {
        const int i = lane + 32 * k, row = (i * 57) >> 10;
        if (k < 4 || lane < 16) t[k] = __ldg(reinterpret_cast<const uint4*>(base + row * (C * 18 - 288) + i * 16));
    }
}
__device__ __forceinline__ void weight_block(uint32_t bounce, unsigned char* wt, int cta, int lane, bool readback) {
    unsigned char* dst = wt + (cta >> 4) * STAGE_BYTES + (cta & 15) * 768;
    if (lane < 16) {
        uint32_t v[36];
#pragma unroll
        for (int i = 0; i < 9; i++) {
            const uint4 q = lds128(bounce + (lane & 7) * 288 + (lane >> 3) * 144 + i * 16);
            v[4 * i] = q.x; v[4 * i + 1] = q.y; v[4 * i + 2] = q.z; v[4 * i + 3] = q.w;
        }
#pragma unroll
        for (int kyo = 0; kyo < 3; kyo++) {
#pragma unroll
            for (int kx = 0; kx < 3; kx++) {
                const int tap = ky_of(kyo) * 3 + kx;
                uint32_t o[4];
#pragma unroll
                for (int m = 0; m < 4; m++) {
                    const int i0 = 18 * m + tap, i1 = i0 + 9;
                    const uint32_t sel = ((i0 & 1) ? 0x32u : 0x10u) | ((i1 & 1) ? 0x7600u : 0x5400u);
                    o[m] = __byte_perm(v[i0 >> 1], v[i1 >> 1], sel);
                }
                *reinterpret_cast<uint4*>(dst + kyo * 8 * STAGE_BYTES + kx * 256 + lane * 16) = make_uint4(o[0], o[1], o[2], o[3]);
            }
        }
    }
    if (readback) {
        __syncwarp();
        unsigned acc = 0;
        if (lane < 24) {
#pragma unroll
            for (int i = 0; i < 3; i++) acc |= ld_relaxed(dst + i * 8 * STAGE_BYTES + lane * 32);
        }
        asm volatile("{\n.reg .pred p;\nsetp.eq.u32 p, %0, 0x9e3779b9;\n@p st.shared.u32 [%1], %0;\n}" ::"r"(acc), "r"(bounce + S0) : "memory");
    }
}
__device__ __forceinline__ uint32_t act2(uint32_t u, const float4& cf) {
    return pack_bf(silu_half(fmaf(bf_lo(u), cf.x, cf.z)), silu_half(fmaf(bf_hi(u), cf.y, cf.w)));
}
__device__ __forceinline__ void norm_unit(uint32_t (&u)[4], const float4& ca, const float4& cb) {
    u[0] = act2(u[0], ca); u[1] = act2(u[1], ca); u[2] = act2(u[2], cb); u[3] = act2(u[3], cb);
}
template <int FIRST, int N>
__device__ __forceinline__ void norm_block(uint32_t (&u)[4][4], float4 (&cf)[8], bool load_cf, uint32_t cfa, uint32_t act, uint32_t mask, uint32_t fbar, int lane) {
    if (load_cf) {
#pragma unroll
        for (int i = 2 * FIRST; i < 2 * (FIRST + N); i++) cf[i] = lds128f(cfa + (i >> 1) * 256 + (i & 1) * 64);
    }
#pragma unroll
    for (int t = FIRST; t < FIRST + N; t++) {
        norm_unit(u[t], cf[2 * t], cf[2 * t + 1]);
        stsm4(act + t * 2 * KC_BYTES, u[t][0] & mask, u[t][1] & mask, u[t][2] & mask, u[t][3] & mask);
    }
    fence_async_smem();
    __syncwarp();
    if (lane < N) mbar_arrive(fbar + 16 * (FIRST + lane));
}
__device__ __forceinline__ void stat_mma(float (&c)[4], uint32_t p, uint32_t q) {
    asm("mma.sync.aligned.m16n8k16.row.col.f32.bf16.bf16.f32 {%0,%1,%2,%3}, {%4,%5,%6,%5}, {%4,%6}, {%0,%1,%2,%3};"
        : "+f"(c[0]), "+f"(c[1]), "+f"(c[2]), "+f"(c[3]) : "r"(p), "r"(0x3f803f80u), "r"(q));
}
__device__ __forceinline__ void stat_store(const float (&c)[4], uint32_t dst, int lane) {
    const int g = lane >> 2, t = lane & 3;
    if (t == (g >> 1)) sts32f(dst + g * 4, (g & 1) ? c[1] : c[0]);
    if (g == 7) sts32f(dst + 32 + t * 4, c[2] + c[3]);
}
__device__ __forceinline__ float sum4(float4 v) { return (v.x + v.y) + (v.z + v.w); }
__device__ __forceinline__ void stat_publish(uint32_t src, float* acc, int lane, bool real) {
    const uint32_t a = src + (lane & 15) * 48;
    float q = sum4(lds128f(a)) + sum4(lds128f(a + 16)), sm = sum4(lds128f(a + 32));
    q += __shfl_xor_sync(0xffffffffu, q, 1); sm += __shfl_xor_sync(0xffffffffu, sm, 1);
    q += __shfl_xor_sync(0xffffffffu, q, 2); sm += __shfl_xor_sync(0xffffffffu, sm, 2);
    if (real && (lane & 19) == 0) red_add4(acc + lane, 1.f, sm, q, 1.f);
}
__device__ __forceinline__ void fence_acc(float (&d)[64]) {
#pragma unroll
    for (int i = 0; i < 64; i++) asm volatile("" : "+f"(d[i])::"memory");
}
__device__ __forceinline__ void ld_unit(uint32_t (&u)[4], const uint4* p) {
    asm volatile("ld.relaxed.gpu.global.v4.u32 {%0,%1,%2,%3}, [%4];" : "=r"(u[0]), "=r"(u[1]), "=r"(u[2]), "=r"(u[3]) : "l"(p) : "memory");
}

__device__ __noinline__ void side_jobs(const __nv_bfloat16* __restrict__ t_emb, const __nv_bfloat16* __restrict__ w_emb,
                                       const __nv_bfloat16* __restrict__ w2, Scratch* __restrict__ gs, unsigned clk0) {
    const int tid = threadIdx.x, warp = tid >> 5, lane = tid & 31, j = blockIdx.x;
    float tv = 0.f;
    if (lane < 24) tv = __bfloat162float(t_emb[(lane / 12) * E + j * 192 + warp * 12 + lane % 12]);
    if (tid == 0) {
        mbar_init(BAR(0), 1);
        mbar_expect(BAR(0), 192 * C * 2);
        fence_async_smem();
        while (clock32() - clk0 < W2DELAY) {}
#pragma unroll
        for (int i = 0; i < 4; i++) bulk_g2s(S0 + SM_W + i * 12288, w_emb + (j * 192 + i * 48) * C, 12288, S0 + BAR(0));
    }
    if (j == 0 && tid < 32) gs->acc2[(tid >> 4) * LS + (tid & 15)] = 0.f;
    const float sv = silu_half(0.5f * tv);
    __syncthreads();
    mbar_wait(BAR(0), 0);
    float acc[8] = {0.f, 0.f, 0.f, 0.f, 0.f, 0.f, 0.f, 0.f};
#pragma unroll
    for (int i = 0; i < 12; i++) {
        const float2 wq = lds64f(SM_W + (warp * 12 + i) * 256 + lane * 8);
        const uint32_t wx = __float_as_uint(wq.x), wy = __float_as_uint(wq.y);
#pragma unroll
        for (int bb = 0; bb < 2; bb++) {
            const float sx = __shfl_sync(0xffffffffu, sv, bb * 12 + i);
            acc[4 * bb + 0] = fmaf(sx, bf_lo(wx), acc[4 * bb + 0]); acc[4 * bb + 1] = fmaf(sx, bf_hi(wx), acc[4 * bb + 1]);
            acc[4 * bb + 2] = fmaf(sx, bf_lo(wy), acc[4 * bb + 2]); acc[4 * bb + 3] = fmaf(sx, bf_hi(wy), acc[4 * bb + 3]);
        }
    }
    sts128f(SM_ACT + warp * 1024 + lane * 16, make_float4(acc[0], acc[1], acc[2], acc[3]));
    sts128f(SM_ACT + warp * 1024 + 512 + lane * 16, make_float4(acc[4], acc[5], acc[6], acc[7]));
    __syncthreads();
    if (tid < 128) {
        float2 sum = make_float2(0.f, 0.f);
#pragma unroll
        for (int w = 0; w < 16; w++) { const float2 p = lds64f(SM_ACT + w * 1024 + tid * 8); sum.x += p.x; sum.y += p.y; }
        *reinterpret_cast<float2*>(&gs->emb[j * NB * C + tid * 2]) = sum;
        bar_sync(1, 128);
        if (tid < 2) asm volatile("red.release.gpu.global.add.u32 [%0], 1;" ::"l"(&gs->wcnt[(2 * NB + tid) * LS]) : "memory");
    }
}

__global__ void __cluster_dims__(2, 1, 1) __launch_bounds__(NTHREADS, 1)
resblock_kernel(const __nv_bfloat16* __restrict__ w1,
                const __nv_bfloat16* __restrict__ t_emb, const __nv_bfloat16* __restrict__ g1,
                const __nv_bfloat16* __restrict__ be1, const __nv_bfloat16* __restrict__ w_emb,
                const __nv_bfloat16* __restrict__ g2, const __nv_bfloat16* __restrict__ be2,
                const __nv_bfloat16* __restrict__ w2, __nv_bfloat16* __restrict__ out, Scratch* __restrict__ gs,
                const __grid_constant__ CUtensorMap xmap) {
    const unsigned clk0 = clock32();
    if (threadIdx.x == 480 && blockIdx.x >= NXTRA) TLG(1);
    const int tid = threadIdx.x, lane = tid & 31;
    const int cta = blockIdx.x - NXTRA, b = cta >> 6, r = cta & 63;
    uint4 v[5];
    if (tid < 32) weight_load(v, w1, cta & (NCTA - 1), lane);
    const int warp = __shfl_sync(0xffffffffu, tid >> 5, 0);
    if (cta < 0) { side_jobs(t_emb, w_emb, w2, gs, clk0); return; }

    const int seg = lane & 7;
    if (warp != 3) asm volatile("barrier.cluster.arrive.relaxed.aligned;" ::: "memory");
    const bool has_outer = (r != 0) && (r != HW - 1);
    if (warp == 1 || warp == 2 || warp == 4 || warp == 5) {
        const int g = warp < 3 ? warp - 1 : 7 - warp;
        if (elect_one()) {
            asm volatile("prefetch.tensormap [%0];" ::"l"(&xmap) : "memory");
            mbar_init(BAR(BAR_X) + 8 * g, 1);
            if (g == 3) mbar_init(BAR(BAR_X + 4), 1);
            mbar_expect(BAR(BAR_X) + 8 * g, 4096);
            fence_async_smem();
            while (clock32() - clk0 < XDELAY + (g >> 1) * XSTAG + (g & 1) * XSTAG2) {}
            tma_x(SM_XOWN + g * 4096, &xmap, r, b * C + g * 32, BAR(BAR_X) + 8 * g);
            if (g == 3 && has_outer) {
                mbar_expect(BAR(BAR_X + 4), 16384);
#pragma unroll
                for (int i = 0; i < 4; i++) tma_x(SM_XOUT + i * 4096, &xmap, r + ((r & 1) ? 1 : -1), b * C + i * 32, BAR(BAR_X + 4));
            }
        }
        __syncwarp();
        bar_arrive(4, 256 + 32 + 128);
        mbar_wait(BAR(BAR_X) + 8 * g, 0);
        if (lane == 0) TL(70 + g);
        float c[2][4] = {{0.f, 0.f, 0.f, 0.f}, {0.f, 0.f, 0.f, 0.f}};
#pragma unroll
        for (int k = 0; k < 8; k++) {
            const uint4 q = lds128(SM_XOWN + g * 4096 + k * 512 + lane * 16);
            stat_mma(c[0], q.x, q.y); stat_mma(c[1], q.z, q.w);
        }
#pragma unroll
        for (int i = 0; i < 4; i++) c[0][i] += c[1][i];
        stat_store(c[0], SM_RED + g * 48, lane);
        __syncwarp();
        if (lane == 0) {
            const uint32_t a = SM_RED + g * 48;
            red_add4(&gs->acc1[b * 4 * LS + g * GS1], 1.f, sum4(lds128f(a + 32)), sum4(lds128f(a)) + sum4(lds128f(a + 16)), 1.f);
            TL(74 + g);
        }
    }
    if (warp == 0 || warp == 4) {
        const int k = warp >> 2;
        if (k == 0) {
#pragma unroll
            for (int i = 0; i < 5; i++)
                if (i < 4 || lane < 16) sts128(SM_BNC + (lane + 32 * i) * 16, v[i]);
            if (lane == 0) TL(81);
            __syncwarp();
        } else {
            bar_sync(6, 64);
            mbar_wait(BAR(BAR_W2), 0);
        }
        weight_block(SM_BNC + k * 2304, gs->wt + k * NSTAGE * STAGE_BYTES, cta, lane, k == 0);
        __syncwarp();
        if (lane == 0) TL(k ? 13 : 4);
        if (k == 0 && lane < 2) asm volatile("red.relaxed.gpu.global.add.u32 [%0], 1;" ::"l"(&gs->wcnt[lane * LS + (cta >> 4)]) : "memory");
    }

    if (warp >= 8) {
        const int nw = warp - 8;
        bar_sync(4, 256 + 32 + 128);
        const int par = nw >> 2, wq = nw & 3;
        const uint32_t act_off = SM_ACT + (par * 2 + (lane >> 4)) * CH_PITCH + (2 + wq * 16 + (lane & 15)) * 16;
        const uint32_t stg_off = (par * 16 + (lane >> 4) * 8 + (lane & 7)) * 128 + (((2 * wq + ((lane >> 3) & 1)) ^ (lane & 7)) << 4);
        const uint32_t cfa = SM_COEF + par * 128 + (lane & 3) * 16;
        const uint32_t fbar = BAR(BAR_FULL) + 8 * par;
        uint4* inbox = gs->box + cta * 1024 + nw * 32 + lane;
#pragma unroll 1
        for (int conv = 0; conv < 2; conv++) {
            uint32_t u[4][4], w[4][4];
            float4 cf[8];
            if (conv == 0) {
#pragma unroll
                for (int i = 0; i < 4; i++) { mbar_wait(BAR(BAR_X + i), 0); ldsm4t(u[i], SM_XOWN + stg_off + i * 4096); }
                mbar_wait(BAR(BAR_STATS), 0);
                if (tid == 256) TL(22);
                norm_block<0, 2>(u, cf, true, cfa, act_off, ~0u, fbar, lane);
                if (tid == 256) TL(8);
                mbar_wait(BAR(BAR_STATS + 1), 0);
                norm_block<2, 2>(u, cf, true, cfa, act_off, ~0u, fbar, lane);
            } else {
                mbar_wait(BAR(BAR_HW), 0);
#pragma unroll
                for (int i = 0; i < 4; i++) ldsm4(u[i], act_off + i * 2 * KC_BYTES);
                mbar_wait(BAR(BAR_STATS + 2), 0);
                if (tid == 256) TL(26);
                norm_block<0, NA>(u, cf, true, cfa, act_off, ~0u, fbar, lane);
                if (tid == 256) TL(16);
                norm_block<NA, 4 - NA>(u, cf, true, cfa, act_off, ~0u, fbar, lane);
            }
            if (tid == 256) TL(84 + conv);
            if (has_outer) {
                mbar_wait(BAR(BAR_X + 4), conv);
                if (conv == 0) {
#pragma unroll
                    for (int i = 0; i < 4; i++) ldsm4t(w[i], SM_XOUT + stg_off + i * 4096);
                } else {
#pragma unroll
                    for (int i = 0; i < 4; i++) {
                        const uint4 q = lds128(SM_XOUT + (tid - 256) * 16 + i * 4096);
                        w[i][0] = q.x; w[i][1] = q.y; w[i][2] = q.z; w[i][3] = q.w;
                    }
                    unsigned it = 0;
                    while (true) {
                        bool ok = true;
#pragma unroll
                        for (int i = 0; i < 16; i++) ok = ok && w[i >> 2][i & 3] != 0;
                        if (__all_sync(0xffffffffu, ok) || ++it > SPIN_LIMIT) break;
#pragma unroll
                        for (int i = 0; i < 4; i++) ld_unit(w[i], inbox + i * 256);
                    }
#pragma unroll
                    for (int i = 0; i < 16; i++) w[i >> 2][i & 3] = ~w[i >> 2][i & 3];
                }
            }
            bar_sync(3, 256);
            if (nw == 0) sts128(SM_ACT + 2 * ROW_BYTES + (lane >> 1) * CH_PITCH + (lane & 1) * 16, make_uint4(0, 0, 0, 0));
            if (tid == 256) TL(24 + conv * 4);
            norm_block<0, 4>(w, cf, false, cfa, act_off + 2 * ROW_BYTES, has_outer ? ~0u : 0u, fbar + 128, lane);
            if (tid == 256) TL(23 + conv * 4);
        }
        if (has_outer) {
            mbar_wait(BAR(BAR_FULL + NSTAGE - 1), 1);
#pragma unroll
            for (int i = 0; i < 4; i++) inbox[i * 256] = make_uint4(0, 0, 0, 0);
        }
    } else if (warp < 4) {
        const int wq = warp;
        if (wq == 3) {
            if (elect_one()) {
#pragma unroll
                for (int i = 0; i < NSTAGE; i++) mbar_init(BAR(BAR_FULL + i), (i >> 3) == 1 ? 1 : 5);
#pragma unroll
                for (int i = 0; i <= NS; i++) mbar_init(BAR(BAR_WEMPTY + i), 4);
#pragma unroll
                for (int i = BAR_STATS; i < BAR_X; i++) mbar_init(BAR(i), i == BAR_EMB ? 3 : (i < BAR_STATS + 2 ? 2 : (i == BAR_STATS + 2 ? 4 : 1)));
                asm volatile("fence.mbarrier_init.release.cluster;" ::: "memory");
            }
            __syncwarp();
            fence_async_smem();
            bar_arrive(0, 96);
            bar_arrive(5, 96);
            bar_arrive(4, 256 + 32 + 128);
            const uint4 z = make_uint4(0, 0, 0, 0);
#pragma unroll
            for (int i = 0; i < 2; i++) sts128(SM_ACT + (i * 16 + (lane >> 1)) * CH_PITCH + (lane & 1) * 16, z);
            if (lane < 4) sts128(SM_ACT + (2 + (lane >> 1)) * ROW_BYTES + (lane & 1) * 16, z);
            if (lane < 16) sts128(SM_ONES + lane * 16, make_uint4(lane < 8 ? 0x3f803f80u : 0u, 0, 0, 0));
            fence_async_smem();
            asm volatile("barrier.cluster.arrive.release.aligned;" ::: "memory");
            bar_arrive(6, 64);
            if (elect_one()) {
                mbar_expect(BAR(BAR_W2), 2304);
                while (clock32() - clk0 < W2DELAY) {}
                const char* base = reinterpret_cast<const char*>(w2) + ((cta & 15) * 8 * C + (cta >> 4) * 16) * 18;
#pragma unroll 1
                for (int i = 0; i < 8; i++) bulk_g2s(S0 + SM_BNC + 2304 + i * 288, base + i * (C * 18), 288, S0 + BAR(BAR_W2));
            }
            __syncwarp();
        }
        bar_sync(2, 128);

        float d[64];
#pragma unroll
        for (int i = 0; i < 64; i++) d[i] = 0.f;
#pragma unroll 1
        for (int conv = 0; conv < 2; conv++) {
            fence_acc(d);
            mma_stages<0>(d, conv, tid, gs);
            if (conv == 0) {
                asm volatile("wgmma.fence.sync.aligned;" ::: "memory");
                wgmma128<(SM_ONES >> 4) | (8u << 16), (SM_EMB >> 4), 0, 8>(d);
                asm volatile("wgmma.commit_group.sync.aligned;" ::: "memory");
            }
            asm volatile("wgmma.wait_group.sync.aligned 0;" ::: "memory");
            fence_acc(d);
            if (tid == 0) TL(10 + conv * 8);
            if (conv == 1) break;

            uint32_t hp[32];
#pragma unroll
            for (int g = 0; g < 4; g++) {
                float c[4] = {0.f, 0.f, 0.f, 0.f};
#pragma unroll
                for (int i = 0; i < 8; i++) hp[8 * g + i] = pack_bf(d[16 * g + 2 * i], d[16 * g + 2 * i + 1]);
#pragma unroll
                for (int i = 0; i < 4; i++) stat_mma(c, hp[8 * g + 2 * i], hp[8 * g + 2 * i + 1]);
                stat_store(c, SM_RED + (g * 4 + wq) * 48, lane);
            }
            bar_sync(2, 128);
            if (wq == 0) stat_publish(SM_RED, &gs->acc2[b * LS], lane, true);
            if (tid == 0) TL(11);
            const uint32_t hbase = SM_ACT + (lane >> 4) * CH_PITCH + (2 + wq * 16 + (lane & 15)) * 16;
#pragma unroll
            for (int kc = 0; kc < 8; kc++) stsm4(hbase + kc * 2 * CH_PITCH, hp[4 * kc], hp[4 * kc + 1], hp[4 * kc + 2], hp[4 * kc + 3]);
            __syncwarp();
            if (lane == 0) mbar_arrive(BAR(BAR_HW));
            if (lane < LAG) mbar_arrive(BAR(BAR_WEMPTY + (NSTAGE - LAG) % NS) + 8 * lane);
            if (has_outer) {
                uint4* outbox = gs->box + (cta + ((r & 1) ? 1 : -1)) * 1024 + tid;
#pragma unroll
                for (int kc = 0; kc < 8; kc++) outbox[kc * 128] = make_uint4(~hp[4 * kc], ~hp[4 * kc + 1], ~hp[4 * kc + 2], ~hp[4 * kc + 3]);
            }
            if (tid == 0) TL(12);
            const uint32_t xbase = SM_XOWN + ((lane >> 4) * 8 + (lane & 7)) * 128 + (((2 * wq + ((lane >> 3) & 1)) ^ (lane & 7)) << 4);
#pragma unroll
            for (int kc = 0; kc < 8; kc++) {
                uint32_t p[4];
                ldsm4t(p, xbase + kc * 2048);
#pragma unroll
                for (int i = 0; i < 4; i++) { d[8 * kc + 2 * i] = bf_lo(p[i]); d[8 * kc + 2 * i + 1] = bf_hi(p[i]); }
            }
        }
        {
            const uint32_t obase = slot_addr(0) + ((lane >> 4) * 8 + (lane & 7)) * OUT_PITCH + (wq * 16 + ((lane >> 3) & 1) * 8) * 2;
#pragma unroll
            for (int kc = 0; kc < 8; kc++) {
                stsm4t(obase + kc * 16 * OUT_PITCH, pack_bf(d[8 * kc + 0], d[8 * kc + 1]), pack_bf(d[8 * kc + 2], d[8 * kc + 3]),
                       pack_bf(d[8 * kc + 4], d[8 * kc + 5]), pack_bf(d[8 * kc + 6], d[8 * kc + 7]));
            }
            bar_sync(2, 128);
            const int oc0 = tid >> 3;
            __nv_bfloat16* dst = out + ((size_t)(b * C + oc0) * HW + r) * HW + seg * 8;
#pragma unroll
            for (int i = 0; i < 8; i++)
                *reinterpret_cast<uint4*>(dst + (size_t)i * 16 * HW * HW) = lds128(slot_addr(0) + (oc0 + 16 * i) * OUT_PITCH + seg * 16);
            if (tid == 0) { TL(20); TLG(21); }
        }
    } else if (warp < 6) {
        bar_sync(5, 96);
        if (warp == 5) {
            asm volatile("barrier.cluster.wait.acquire.aligned;" ::: "memory");
            const uint32_t peer = (r & 1) ^ 1;
            const uint32_t self0 = mapa(0, r & 1), peer0 = mapa(0, peer);
#pragma unroll 1
            for (int conv = 0; conv < 2; conv++) {
#pragma unroll 1
                for (int kc = 0; kc < 8; kc++) {
                    mbar_wait(BAR(BAR_FULL) + 8 * kc, conv);
                    if (elect_one())
                        asm volatile("cp.async.bulk.shared::cluster.shared::cta.mbarrier::complete_tx::bytes [%0], [%1], %2, [%3];"
                                     ::"r"(peer0 + SM_ACT + ROW_BYTES + kc * KC_BYTES), "r"(self0 + SM_ACT + kc * KC_BYTES), "r"(KC_BYTES),
                                       "r"(peer0 + BAR(BAR_FULL + 8) + 8 * kc) : "memory");
                }
                if (lane == 0) TL(86 + conv);
#pragma unroll 1
                for (int kc = 0; kc < 8; kc++) mbar_wait(BAR(BAR_FULL + 8) + 8 * kc, conv);
                if (lane == 0)
                    asm volatile("mbarrier.arrive.release.cluster.shared::cluster.b64 _, [%0];" ::"r"(peer0 + (conv ? BAR(BAR_ACK) : BAR(BAR_EMB))) : "memory");
            }
            mbar_wait(BAR(BAR_ACK), 0);
        } else {
            if (lane < 2) asm volatile("red.release.gpu.global.add.u32 [%0], 1;" ::"l"(&gs->wcnt[(NB + lane) * LS]) : "memory");
            if (lane == 0) TL(14);
            mbar_wait(BAR(BAR_STATS + 1), 0);
            unsigned it = 0;
            while (ld_relaxed(&gs->wcnt[(2 * NB + b) * LS]) < (unsigned)NXTRA && ++it < SPIN_LIMIT) __nanosleep(100);
            fence_acquire();
            float ev[4] = {0.f, 0.f, 0.f, 0.f};
#pragma unroll
            for (int j = 0; j < NXTRA; j++) {
                const uint4 ef = ld_relaxed_v4(&gs->emb[(j * NB + b) * C + lane * 4]);
                ev[0] += __uint_as_float(ef.x); ev[1] += __uint_as_float(ef.y); ev[2] += __uint_as_float(ef.z); ev[3] += __uint_as_float(ef.w);
            }
#pragma unroll
            for (int i = 0; i < 4; i++) {
                const float hi = bf_lo(pack_bf(ev[i], 0.f));
                sts128(SM_EMB + (lane * 4 + i) * 16, make_uint4(pack_bf(hi, ev[i] - hi), 0, 0, 0));
            }
            fence_async_smem();
            __syncwarp();
            if (lane == 0) { mbar_arrive(BAR(BAR_EMB)); TL(19); }
        }
    } else if (warp == 6) {
        bar_sync(0, 96);
        const uint32_t ebytes = STAGE_BYTES + ((lane >> 3) == 1 ? KC_BYTES : 0);
        if (lane < NSTAGE) mbar_expect(BAR(BAR_FULL) + 8 * lane, ebytes);
        const int swap = (r & 1) ? 0 : 8 * STAGE_BYTES;
        unsigned it = 0;
        {
            int g = 0;
#pragma unroll 1
            while (g < NS) {
                unsigned ready = __ballot_sync(0xffffffffu, ld_relaxed(&gs->wcnt[b * LS + (lane & 7)]) >= 16u) >> g;
                if (++it > SPIN_LIMIT) ready = ~0u;
                if (!(ready & 1)) continue;
                fence_acquire();
                fence_async_global();
                if (lane == 0) TL(g ? 3 : 6);
#pragma unroll 1
                for (; (ready & 1) && g < NS; g++, ready >>= 1)
                    if (elect_one())
                        bulk_g2s(S0 + SM_W + g * STAGE_BYTES, gs->wt + g * STAGE_BYTES + (g >= 8 ? swap : 0), STAGE_BYTES, S0 + BAR(BAR_FULL) + 8 * g);
            }
        }
#pragma unroll 1
        for (int q = 3; q < 12; q++) {
            const int conv = q >= 6, qs = conv ? q - 6 : q, sl = q % 3;
            const unsigned char* wsrc = gs->wt + q * 4 * STAGE_BYTES + (qs < 2 ? 0 : (qs < 4 ? swap : -swap));
            const uint32_t par = (q / 3 - 1) & 1;
            if (q == 6) {
                it = 0;
                while (ld_relaxed(&gs->wcnt[(NB + b) * LS]) < (unsigned)NCTA && ++it < SPIN_LIMIT) {}
                fence_acquire();
                fence_async_global();
                if (lane == 0) { mbar_arrive(BAR(BAR_EMB)); TL(2); }
            }
#pragma unroll
            for (int i = 0; i < 4; i++) {
                mbar_wait(BAR(BAR_WEMPTY + i) + 32 * sl, par);
                if (i == 0 && (q == 6 || q == 9)) {
                    if ((lane >= NS) == (q == 9) && lane < NSTAGE) mbar_expect(BAR(BAR_FULL) + 8 * lane, ebytes);
                    __syncwarp();
                }
                if (elect_one())
                    bulk_g2s(S0 + SM_W + (sl * 4 + i) * STAGE_BYTES, wsrc + i * STAGE_BYTES, STAGE_BYTES, S0 + BAR(BAR_FULL + i) + 32 * qs);
            }
        }
    } else {
        const uint2 ga1 = __ldg(reinterpret_cast<const uint2*>(g1) + lane), bt1 = __ldg(reinterpret_cast<const uint2*>(be1) + lane);
        const uint2 ga2 = __ldg(reinterpret_cast<const uint2*>(g2) + lane), bt2 = __ldg(reinterpret_cast<const uint2*>(be2) + lane);
        bar_sync(0, 96);
#pragma unroll 1
        for (int conv = 0; conv < 2; conv++) {
            if (conv == 1) mbar_wait(BAR(BAR_EMB), 0);
            const float* asrc = conv ? &gs->acc2[b * LS + (lane >> 3) * 4] : &gs->acc1[b * 4 * LS + (lane >> 3) * GS1];
            while (clock32() - clk0 < PD) {}
            const uint2 ga = conv ? ga2 : ga1, bt = conv ? bt2 : bt1;
            bool done = false;
            unsigned it = 0;
#pragma unroll 1
            while (true) {
                const uint4 f = ld_relaxed_v4(asrc);
                const bool fresh = !done && (((f.x == 0x42800000u) & (f.w == 0x42800000u)) || it > SPIN_LIMIT);
                it++;
                if (!__any_sync(0xffffffffu, fresh)) continue;
                if (lane == 0 && fresh) TL(7 + conv * 8);
                if (lane == 24 && fresh) TL(90 + conv);
                const float inv_n = 1.0f / (32.0f * HW * HW);
                const float mean = __uint_as_float(f.y) * inv_n;
                const float var = fmaxf(fmaf(-mean, mean, __uint_as_float(f.z) * inv_n), 0.f);
                const float rs = 0.5f * rsqrtf(var + 1e-5f);
                float4 k0, k1;
                k0.x = rs * bf_lo(ga.x); k0.y = rs * bf_hi(ga.x); k1.x = rs * bf_lo(ga.y); k1.y = rs * bf_hi(ga.y);
                k0.z = fmaf(-mean, k0.x, 0.5f * bf_lo(bt.x)); k0.w = fmaf(-mean, k0.y, 0.5f * bf_hi(bt.x));
                k1.z = fmaf(-mean, k1.x, 0.5f * bf_lo(bt.y)); k1.w = fmaf(-mean, k1.y, 0.5f * bf_hi(bt.y));
                if (fresh) {
                    sts128f(SM_COEF + lane * 32, k0);
                    sts128f(SM_COEF + lane * 32 + 16, k1);
                }
                __syncwarp();
                if (fresh && (lane & 7) == 0) mbar_arrive(BAR(BAR_STATS) + (conv ? 16 : (lane >> 4) * 8));
                done = done || fresh;
                if (__all_sync(0xffffffffu, done)) break;
            }
        }
        if (has_outer && elect_one()) {
            mbar_expect(BAR(BAR_X + 4), 16384);
            bulk_g2s(S0 + SM_XOUT, gs->box + cta * 1024, 16384, S0 + BAR(BAR_X + 4));
        }
        if (r == 0) {
            if (lane < 16) gs->acc1[b * 4 * LS + (lane >> 2) * GS1 + (lane & 3)] = 0.f;
            if (lane < 24) gs->wcnt[((lane >> 3) * NB + b) * LS + (lane & 7)] = 0;
        }
    }
}

}

extern "C" void kernel_launch(void* const* d_in, const int* in_sizes, int n_in, void* d_out, int out_size) {
    (void)in_sizes; (void)n_in; (void)out_size;
    typedef CUresult (*EncodeFn)(CUtensorMap*, CUtensorMapDataType, cuuint32_t, void*, const cuuint64_t*, const cuuint64_t*,
                                 const cuuint32_t*, const cuuint32_t*, CUtensorMapInterleave, CUtensorMapSwizzle,
                                 CUtensorMapL2promotion, CUtensorMapFloatOOBfill);
    static Scratch* gs = nullptr;
    static EncodeFn encode = nullptr;
    if (!gs) {
        cudaFuncSetAttribute(resblock_kernel, cudaFuncAttributeMaxDynamicSharedMemorySize, SM_TOTAL);
        cudaGetSymbolAddress((void**)&gs, g_scratch);
        cudaDriverEntryPointQueryResult qr;
        cudaGetDriverEntryPoint("cuTensorMapEncodeTiled", (void**)&encode, cudaEnableDefault, &qr);
    }
    CUtensorMap xmap;
    const cuuint64_t dims[3] = {HW, HW, NB * C}, strides[2] = {HW * 2, HW * HW * 2};
    const cuuint32_t box[3] = {HW, 1, 32}, es[3] = {1, 1, 1};
    encode(&xmap, CU_TENSOR_MAP_DATA_TYPE_BFLOAT16, 3, d_in[0], dims, strides, box, es, CU_TENSOR_MAP_INTERLEAVE_NONE,
           CU_TENSOR_MAP_SWIZZLE_128B, CU_TENSOR_MAP_L2_PROMOTION_NONE, CU_TENSOR_MAP_FLOAT_OOB_FILL_NONE);
    resblock_kernel<<<NCTA + NXTRA, NTHREADS, SM_TOTAL>>>(
        (const __nv_bfloat16*)d_in[4], (const __nv_bfloat16*)d_in[1],
        (const __nv_bfloat16*)d_in[2], (const __nv_bfloat16*)d_in[3], (const __nv_bfloat16*)d_in[5],
        (const __nv_bfloat16*)d_in[6], (const __nv_bfloat16*)d_in[7], (const __nv_bfloat16*)d_in[8],
        (__nv_bfloat16*)d_out, gs, xmap);
}
```

```cpp
#include <cuda_runtime.h>
#include <cuda.h>
#include <cuda_bf16.h>
#include <stdint.h>

namespace {

constexpr int C = 128, HW = 64, NB = 2, E = 768;
constexpr int NCTA = NB * HW;
constexpr int NXTRA = 4;
constexpr int NTHREADS = 16 * 32;
constexpr int CH_PITCH = 66 * 16;
constexpr int ROW_BYTES = 16 * CH_PITCH;
constexpr int STEP_BYTES = 4096;
constexpr int STAGE_BYTES = 3 * STEP_BYTES;
constexpr int NSTAGE = 24;
constexpr int KC_BYTES = 2 * CH_PITCH;
constexpr int NS = 12;
constexpr int LAG = 1;
#define XDELAY 600
#define HDELAY 600
#define SEQ 0
#define MMA0_WAIT mbar_try
#define PDELAY 60
#define RB 1
#define XSTAG2 200
#define XSTAG 800
#define HSEND 0
#define W2DELAY 2000

constexpr uint32_t SMEM_BASE = 0x400;
constexpr uint32_t SM_XOWN = SMEM_BASE;
constexpr uint32_t SM_ACT = SM_XOWN + 16384 + 512;
constexpr uint32_t SM_XOUT = SM_ACT + 2 * ROW_BYTES + 512;
static_assert(SM_XOUT % 1024 == 0, "swizzle atom alignment");
constexpr uint32_t SM_W = SM_ACT + 3 * ROW_BYTES + 128;
__host__ __device__ constexpr uint32_t slot_addr(int slot) { return SM_W + slot * STAGE_BYTES; }
constexpr uint32_t SM_COEF = SM_W + NS * STAGE_BYTES;
constexpr uint32_t SM_GST = SM_COEF + 2048;
constexpr uint32_t SM_EMB = SM_GST + 128;
constexpr uint32_t SM_ONES = SM_EMB + 2048;
constexpr uint32_t SM_RED = SM_ONES + 256;
constexpr uint32_t SM_BNC = SM_RED + 1280;
constexpr uint32_t SM_BAR = SM_BNC + 2 * 2304;
constexpr int BAR_FULL = 0, BAR_WEMPTY = NSTAGE, BAR_HW = BAR_WEMPTY + NS, BAR_STATS = BAR_HW + 1,
              BAR_EMB = BAR_STATS + 1, BAR_ACK = BAR_EMB + 1, BAR_W2 = BAR_ACK + 1, BAR_X = BAR_W2 + 1  , NBAR = BAR_X + 5;
constexpr int SM_TOTAL = SM_BAR + NBAR * 8 - SMEM_BASE;
static_assert(SM_TOTAL <= 232448, "smem");
static_assert(NBAR <= 96, "barrier init");
constexpr int OUT_PITCH = 144;
__host__ __device__ constexpr uint32_t BAR(int i) { return SM_BAR + 8 * i; }
__host__ __device__ constexpr int ky_of(int kyo) { return kyo == 0 ? 1 : (kyo == 1 ? 0 : 2); }

constexpr unsigned SPIN_LIMIT = 1u << 16;

#define LS 1056
#define GS1 4
#define PD 0
struct Scratch {
    float acc1[NB * 4 * LS];
    float acc2[NB * LS];
    unsigned wcnt[3 * NB * LS];
    float emb[NXTRA * NB * C];
    unsigned char wt[2 * NSTAGE * STAGE_BYTES];
    uint4 box[NCTA * 1024];
};
__device__ __align__(1024) Scratch g_scratch;
#define TL(i) do {} while (0)
#define TLG(i) do {} while (0)

__device__ __forceinline__ unsigned clock32() { unsigned c; asm volatile("mov.u32 %0, %%clock;" : "=r"(c)); return c; }
__device__ __forceinline__ uint32_t mapa(uint32_t a, uint32_t rank) {
    uint32_t d;
    asm("mapa.shared::cluster.u32 %0, %1, %2;" : "=r"(d) : "r"(a), "r"(rank));
    return d;
}
#define S0 mapa(0, blockIdx.x & 1)
__device__ __forceinline__ void mbar_init(uint32_t bar, int cnt) {
    asm volatile("mbarrier.init.shared::cta.b64 [%0], %1;" ::"r"(bar + S0), "r"(cnt) : "memory");
}
__device__ __forceinline__ void mbar_arrive(uint32_t bar) {
    asm volatile("mbarrier.arrive.shared::cta.b64 _, [%0];" ::"r"(bar + S0) : "memory");
}
__device__ __forceinline__ void mbar_expect(uint32_t bar, uint32_t bytes) {
    asm volatile("mbarrier.arrive.expect_tx.shared::cta.b64 _, [%0], %1;" ::"r"(bar + S0), "r"(bytes) : "memory");
}
__device__ __forceinline__ bool mbar_try(uint32_t bar, uint32_t par) {
    uint32_t ok;
    asm volatile("{\n.reg .pred p;\nmbarrier.try_wait.parity.shared::cta.b64 p, [%1], %2;\nselp.u32 %0, 1, 0, p;\n}"
                 : "=r"(ok) : "r"(bar + S0), "r"(par) : "memory");
    return ok;
}
__device__ __forceinline__ bool mbar_test(uint32_t bar, uint32_t par) {
    uint32_t ok;
    asm volatile("{\n.reg .pred p;\nmbarrier.test_wait.parity.shared::cta.b64 p, [%1], %2;\nselp.u32 %0, 1, 0, p;\n}"
                 : "=r"(ok) : "r"(bar + S0), "r"(par) : "memory");
    return ok;
}
__device__ __forceinline__ void mbar_wait(uint32_t bar, uint32_t par) {
    unsigned it = 0;
#pragma unroll 1
    while (!mbar_try(bar, par) && ++it < SPIN_LIMIT) {}
}
__device__ __forceinline__ bool elect_one() {
    uint32_t p;
    asm volatile("{\n.reg .pred p;\nelect.sync _|p, 0xffffffff;\nselp.u32 %0, 1, 0, p;\n}" : "=r"(p));
    return p;
}
__device__ __forceinline__ void fence_async_smem() { asm volatile("fence.proxy.async.shared::cta;" ::: "memory"); }
__device__ __forceinline__ void fence_async_global() { asm volatile("fence.proxy.async.global;" ::: "memory"); }
__device__ __forceinline__ void fence_acquire() { asm volatile("fence.acquire.gpu;" ::: "memory"); }
__device__ __forceinline__ void bar_sync(int id, int n) { asm volatile("bar.sync %0, %1;" ::"r"(id), "r"(n) : "memory"); }
__device__ __forceinline__ void bar_arrive(int id, int n) { asm volatile("bar.arrive %0, %1;" ::"r"(id), "r"(n) : "memory"); }
__device__ __forceinline__ void bulk_g2s(uint32_t dst, const void* src, uint32_t bytes, uint32_t bar) {
    asm volatile("cp.async.bulk.shared::cluster.global.mbarrier::complete_tx::bytes [%0], [%1], %2, [%3];"
                 ::"r"(dst), "l"(src), "r"(bytes), "r"(bar) : "memory");
}
__device__ __forceinline__ void tma_x(uint32_t dst, const CUtensorMap* tm, int row, int ch, uint32_t bar) {
    asm volatile("cp.async.bulk.tensor.3d.shared::cluster.global.mbarrier::complete_tx::bytes [%0], [%1, {%2, %3, %4}], [%5];"
                 ::"r"(dst + S0), "l"(tm), "r"(0), "r"(row), "r"(ch), "r"(bar + S0) : "memory");
}
__device__ __forceinline__ uint4 ld_relaxed_v4(const void* p) {
    uint4 v;
    asm volatile("ld.relaxed.gpu.global.v4.u32 {%0,%1,%2,%3}, [%4];" : "=r"(v.x), "=r"(v.y), "=r"(v.z), "=r"(v.w) : "l"(p) : "memory");
    return v;
}
__device__ __forceinline__ unsigned ld_relaxed(const void* p) {
    unsigned v;
    asm volatile("ld.relaxed.gpu.global.u32 %0, [%1];" : "=r"(v) : "l"(p) : "memory");
    return v;
}
__device__ __forceinline__ void red_add4(float* p, float a, float b, float c, float d) {
    asm volatile("red.relaxed.gpu.global.add.v4.f32 [%0], {%1,%2,%3,%4};" ::"l"(p), "f"(a), "f"(b), "f"(c), "f"(d) : "memory");
}
__device__ __forceinline__ void sts128(uint32_t a, uint4 v) {
    asm volatile("st.shared.v4.u32 [%0], {%1,%2,%3,%4};" ::"r"(a + S0), "r"(v.x), "r"(v.y), "r"(v.z), "r"(v.w) : "memory");
}
__device__ __forceinline__ void sts128f(uint32_t a, float4 v) {
    asm volatile("st.shared.v4.f32 [%0], {%1,%2,%3,%4};" ::"r"(a + S0), "f"(v.x), "f"(v.y), "f"(v.z), "f"(v.w) : "memory");
}
__device__ __forceinline__ void sts32f(uint32_t a, float v) { asm volatile("st.shared.f32 [%0], %1;" ::"r"(a + S0), "f"(v) : "memory"); }
__device__ __forceinline__ uint4 lds128(uint32_t a) {
    uint4 v;
    asm volatile("ld.shared.v4.u32 {%0,%1,%2,%3}, [%4];" : "=r"(v.x), "=r"(v.y), "=r"(v.z), "=r"(v.w) : "r"(a + S0) : "memory");
    return v;
}
__device__ __forceinline__ float4 lds128f(uint32_t a) {
    float4 v;
    asm volatile("ld.shared.v4.f32 {%0,%1,%2,%3}, [%4];" : "=f"(v.x), "=f"(v.y), "=f"(v.z), "=f"(v.w) : "r"(a + S0) : "memory");
    return v;
}
__device__ __forceinline__ float2 lds64f(uint32_t a) {
    float2 v;
    asm volatile("ld.shared.v2.f32 {%0,%1}, [%2];" : "=f"(v.x), "=f"(v.y) : "r"(a + S0) : "memory");
    return v;
}
__device__ __forceinline__ float bf_lo(uint32_t u) { return __uint_as_float(u << 16); }
__device__ __forceinline__ float bf_hi(uint32_t u) { return __uint_as_float(u & 0xffff0000u); }
__device__ __forceinline__ uint32_t pack_bf(float lo, float hi) {
    uint32_t r;
    asm("cvt.rn.bf16x2.f32 %0, %1, %2;" : "=r"(r) : "f"(hi), "f"(lo));
    return r;
}
__device__ __forceinline__ float tanh_fast(float x) {
    float r;
    asm("tanh.approx.f32 %0, %1;" : "=f"(r) : "f"(x));
    return r;
}
__device__ __forceinline__ float silu_half(float h) { return fmaf(h, tanh_fast(h), h); }
__device__ __forceinline__ void ldsm4(uint32_t (&u)[4], uint32_t a) {
    asm volatile("ldmatrix.sync.aligned.m8n8.x4.shared.b16 {%0,%1,%2,%3}, [%4];"
                 : "=r"(u[0]), "=r"(u[1]), "=r"(u[2]), "=r"(u[3]) : "r"(a + S0) : "memory");
}
__device__ __forceinline__ void ldsm4t(uint32_t (&u)[4], uint32_t a) {
    asm volatile("ldmatrix.sync.aligned.m8n8.x4.trans.shared.b16 {%0,%1,%2,%3}, [%4];"
                 : "=r"(u[0]), "=r"(u[1]), "=r"(u[2]), "=r"(u[3]) : "r"(a + S0) : "memory");
}
__device__ __forceinline__ void stsm4(uint32_t a, uint32_t p0, uint32_t p1, uint32_t p2, uint32_t p3) {
    asm volatile("stmatrix.sync.aligned.m8n8.x4.shared.b16 [%0], {%1,%2,%3,%4};" ::"r"(a + S0), "r"(p0), "r"(p1), "r"(p2), "r"(p3) : "memory");
}
__device__ __forceinline__ void stsm4t(uint32_t a, uint32_t p0, uint32_t p1, uint32_t p2, uint32_t p3) {
    asm volatile("stmatrix.sync.aligned.m8n8.x4.trans.shared.b16 [%0], {%1,%2,%3,%4};" ::"r"(a + S0), "r"(p0), "r"(p1), "r"(p2), "r"(p3) : "memory");
}

#define R8(o) "+f"(d[o]), "+f"(d[o + 1]), "+f"(d[o + 2]), "+f"(d[o + 3]), "+f"(d[o + 4]), "+f"(d[o + 5]), "+f"(d[o + 6]), "+f"(d[o + 7])
template <uint32_t ALO, uint32_t BLO, uint64_t AHI = 8, uint64_t BHI = 48>
__device__ __forceinline__ void wgmma128(float (&d)[64]) {
    asm volatile(
        "wgmma.mma_async.sync.aligned.m64n128k16.f32.bf16.bf16 "
        "{%0,%1,%2,%3,%4,%5,%6,%7,%8,%9,%10,%11,%12,%13,%14,%15,%16,%17,%18,%19,%20,%21,%22,%23,%24,%25,%26,%27,%28,%29,%30,%31,"
        "%32,%33,%34,%35,%36,%37,%38,%39,%40,%41,%42,%43,%44,%45,%46,%47,%48,%49,%50,%51,%52,%53,%54,%55,%56,%57,%58,%59,%60,%61,%62,%63},"
        " %64, %65, 1, 1, 1, 0, 0;"
        : R8(0), R8(8), R8(16), R8(24), R8(32), R8(40), R8(48), R8(56)
        : "l"((AHI << 32) | ALO), "l"((BHI << 32) | BLO));
}
template <int S>
__device__ __forceinline__ void mma_stages(float (&d)[64], int conv, int tid, Scratch* gs) {
    constexpr uint32_t A = ((SM_ACT + S * 2 * CH_PITCH + 16) >> 4) | ((CH_PITCH >> 4) << 16);
    constexpr uint32_t B = (slot_addr(S % NS) >> 4) | (8u << 16);
    if (S == 0) {
        unsigned it = 0;
#pragma unroll 1
        while (!MMA0_WAIT(BAR(BAR_FULL), conv) && ++it < SPIN_LIMIT) {}
    }
    bool next_ok = true;
    constexpr uint32_t NEXT = S + 1 < NSTAGE ? BAR(BAR_FULL + S + 1) : BAR(BAR_EMB);
    const int npar = S + 1 < NSTAGE ? conv : 0;
    next_ok = mbar_test(NEXT, npar);
    if (S == 0 && tid == 0) TL(32 + conv * 24);
    asm volatile("wgmma.fence.sync.aligned;" ::: "memory");
    wgmma128<A, B>(d);
    wgmma128<A + 1, B + 16>(d);
    wgmma128<A + 2, B + 32>(d);
    asm volatile("wgmma.commit_group.sync.aligned;" ::: "memory");
    if (S >= LAG) {
        asm volatile("wgmma.wait_group.sync.aligned %0;" ::"n"(LAG) : "memory");
        if ((tid & 31) == 0) mbar_arrive(BAR(BAR_WEMPTY + (S + NS - LAG) % NS));
    }
    if (!next_ok) mbar_wait(NEXT, npar);
    if constexpr (S + 1 < NSTAGE) mma_stages<S + 1>(d, conv, tid, gs);
}

__device__ __forceinline__ void weight_load(uint4 (&t)[5], const __nv_bfloat16* w, int cta, int lane) {
    const char* base = reinterpret_cast<const char*>(w) + ((cta & 15) * 8 * C + (cta >> 4) * 16) * 18;
#pragma unroll
    for (int k = 0; k < 5; k++) {
        const int i = lane + 32 * k, row = (i * 57) >> 10;
        if (k < 4 || lane < 16) t[k] = __ldg(reinterpret_cast<const uint4*>(base + row * (C * 18 - 288) + i * 16));
    }
}
__device__ __forceinline__ void weight_block(uint32_t bounce, unsigned char* wt, int cta, int lane, bool readback) {
    unsigned char* dst = wt + (cta >> 4) * STAGE_BYTES + (cta & 15) * 768;
    if (lane < 16) {
        uint32_t v[36];
#pragma unroll
        for (int i = 0; i < 9; i++) {
            const uint4 q = lds128(bounce + (lane & 7) * 288 + (lane >> 3) * 144 + i * 16);
            v[4 * i] = q.x; v[4 * i + 1] = q.y; v[4 * i + 2] = q.z; v[4 * i + 3] = q.w;
        }
#pragma unroll
        for (int kyo = 0; kyo < 3; kyo++) {
#pragma unroll
            for (int kx = 0; kx < 3; kx++) {
                const int tap = ky_of(kyo) * 3 + kx;
                uint32_t o[4];
#pragma unroll
                for (int m = 0; m < 4; m++) {
                    const int i0 = 18 * m + tap, i1 = i0 + 9;
                    const uint32_t sel = ((i0 & 1) ? 0x32u : 0x10u) | ((i1 & 1) ? 0x7600u : 0x5400u);
                    o[m] = __byte_perm(v[i0 >> 1], v[i1 >> 1], sel);
                }
                *reinterpret_cast<uint4*>(dst + kyo * 8 * STAGE_BYTES + kx * 256 + lane * 16) = make_uint4(o[0], o[1], o[2], o[3]);
            }
        }
    }
    if (readback) {
        __syncwarp();
        unsigned acc = 0;
        if (lane < 24) {
#pragma unroll
            for (int i = 0; i < 3; i++) acc |= ld_relaxed(dst + i * 8 * STAGE_BYTES + lane * 32);
        }
        asm volatile("{\n.reg .pred p;\nsetp.eq.u32 p, %0, 0x9e3779b9;\n@p st.shared.u32 [%1], %0;\n}" ::"r"(acc), "r"(bounce + S0) : "memory");
    }
}
__device__ __forceinline__ uint32_t act2(uint32_t u, const float4& cf) {
    return pack_bf(silu_half(fmaf(bf_lo(u), cf.x, cf.z)), silu_half(fmaf(bf_hi(u), cf.y, cf.w)));
}
__device__ __forceinline__ void norm_unit(uint32_t (&u)[4], const float4& ca, const float4& cb) {
    u[0] = act2(u[0], ca); u[1] = act2(u[1], ca); u[2] = act2(u[2], cb); u[3] = act2(u[3], cb);
}
__device__ __forceinline__ void group_coefs(uint32_t slot, float4& ca, float4& cb) {
    float4 gsv;
    unsigned it = 0;
#pragma unroll 1
    do {
        asm volatile("ld.volatile.shared.v4.f32 {%0,%1,%2,%3}, [%4];" : "=f"(gsv.x), "=f"(gsv.y), "=f"(gsv.z), "=f"(gsv.w) : "r"(slot + S0) : "memory");
    } while (!__all_sync(0xffffffffu, gsv.z != 0.f) && ++it < 8 * SPIN_LIMIT);
    ca.z = fmaf(-gsv.y, ca.x, ca.z); ca.w = fmaf(-gsv.y, ca.y, ca.w); ca.x *= gsv.x; ca.y *= gsv.x;
    cb.z = fmaf(-gsv.y, cb.x, cb.z); cb.w = fmaf(-gsv.y, cb.y, cb.w); cb.x *= gsv.x; cb.y *= gsv.x;
}
template <int FIRST, int N>
__device__ __forceinline__ void norm_block(uint32_t (&u)[4][4], float4 (&cf)[8], bool fold, uint32_t gst, uint32_t act, uint32_t mask, uint32_t fbar, int lane) {
    if (fold) {
#pragma unroll
        for (int t = FIRST; t < FIRST + N; t++) group_coefs(gst + 16 * t, cf[2 * t], cf[2 * t + 1]);
    }
#pragma unroll
    for (int t = FIRST; t < FIRST + N; t++) {
        norm_unit(u[t], cf[2 * t], cf[2 * t + 1]);
        stsm4(act + t * 2 * KC_BYTES, u[t][0] & mask, u[t][1] & mask, u[t][2] & mask, u[t][3] & mask);
    }
    fence_async_smem();
    __syncwarp();
    if (lane < N) mbar_arrive(fbar + 16 * (FIRST + lane));
}
__device__ __forceinline__ void stat_mma(float (&c)[4], uint32_t p, uint32_t q) {
    asm("mma.sync.aligned.m16n8k16.row.col.f32.bf16.bf16.f32 {%0,%1,%2,%3}, {%4,%5,%6,%5}, {%4,%6}, {%0,%1,%2,%3};"
        : "+f"(c[0]), "+f"(c[1]), "+f"(c[2]), "+f"(c[3]) : "r"(p), "r"(0x3f803f80u), "r"(q));
}
__device__ __forceinline__ void stat_store(const float (&c)[4], uint32_t dst, int lane) {
    const int g = lane >> 2, t = lane & 3;
    if (t == (g >> 1)) sts32f(dst + g * 4, (g & 1) ? c[1] : c[0]);
    if (g == 7) sts32f(dst + 32 + t * 4, c[2] + c[3]);
}
__device__ __forceinline__ float sum4(float4 v) { return (v.x + v.y) + (v.z + v.w); }
__device__ __forceinline__ void stat_publish(uint32_t src, float* acc, int lane, bool real) {
    const uint32_t a = src + (lane & 15) * 48;
    float q = sum4(lds128f(a)) + sum4(lds128f(a + 16)), sm = sum4(lds128f(a + 32));
    q += __shfl_xor_sync(0xffffffffu, q, 1); sm += __shfl_xor_sync(0xffffffffu, sm, 1);
    q += __shfl_xor_sync(0xffffffffu, q, 2); sm += __shfl_xor_sync(0xffffffffu, sm, 2);
    if (real && (lane & 19) == 0) red_add4(acc + lane, 1.f, sm, q, 1.f);
}
__device__ __forceinline__ void fence_acc(float (&d)[64]) {
#pragma unroll
    for (int i = 0; i < 64; i++) asm volatile("" : "+f"(d[i])::"memory");
}
__device__ __forceinline__ void ld_unit(uint32_t (&u)[4], const uint4* p) {
    asm volatile("ld.relaxed.gpu.global.v4.u32 {%0,%1,%2,%3}, [%4];" : "=r"(u[0]), "=r"(u[1]), "=r"(u[2]), "=r"(u[3]) : "l"(p) : "memory");
}

__device__ __noinline__ void side_jobs(const __nv_bfloat16* __restrict__ t_emb, const __nv_bfloat16* __restrict__ w_emb,
                                       const __nv_bfloat16* __restrict__ w2, Scratch* __restrict__ gs, unsigned clk0) {
    const int tid = threadIdx.x, warp = tid >> 5, lane = tid & 31, j = blockIdx.x;
    float tv = 0.f;
    if (lane < 24) tv = __bfloat162float(t_emb[(lane / 12) * E + j * 192 + warp * 12 + lane % 12]);
    if (tid == 0) {
        mbar_init(BAR(0), 1);
        mbar_expect(BAR(0), 192 * C * 2);
        fence_async_smem();
        while (clock32() - clk0 < W2DELAY) {}
#pragma unroll
        for (int i = 0; i < 4; i++) bulk_g2s(S0 + SM_W + i * 12288, w_emb + (j * 192 + i * 48) * C, 12288, S0 + BAR(0));
    }
    if (j == 0 && tid < 32) gs->acc2[(tid >> 4) * LS + (tid & 15)] = 0.f;
    const float sv = silu_half(0.5f * tv);
    __syncthreads();
    mbar_wait(BAR(0), 0);
    float acc[8] = {0.f, 0.f, 0.f, 0.f, 0.f, 0.f, 0.f, 0.f};
#pragma unroll
    for (int i = 0; i < 12; i++) {
        const float2 wq = lds64f(SM_W + (warp * 12 + i) * 256 + lane * 8);
        const uint32_t wx = __float_as_uint(wq.x), wy = __float_as_uint(wq.y);
#pragma unroll
        for (int bb = 0; bb < 2; bb++) {
            const float sx = __shfl_sync(0xffffffffu, sv, bb * 12 + i);
            acc[4 * bb + 0] = fmaf(sx, bf_lo(wx), acc[4 * bb + 0]); acc[4 * bb + 1] = fmaf(sx, bf_hi(wx), acc[4 * bb + 1]);
            acc[4 * bb + 2] = fmaf(sx, bf_lo(wy), acc[4 * bb + 2]); acc[4 * bb + 3] = fmaf(sx, bf_hi(wy), acc[4 * bb + 3]);
        }
    }
    sts128f(SM_ACT + warp * 1024 + lane * 16, make_float4(acc[0], acc[1], acc[2], acc[3]));
    sts128f(SM_ACT + warp * 1024 + 512 + lane * 16, make_float4(acc[4], acc[5], acc[6], acc[7]));
    __syncthreads();
    if (tid < 128) {
        float2 sum = make_float2(0.f, 0.f);
#pragma unroll
        for (int w = 0; w < 16; w++) { const float2 p = lds64f(SM_ACT + w * 1024 + tid * 8); sum.x += p.x; sum.y += p.y; }
        *reinterpret_cast<float2*>(&gs->emb[j * NB * C + tid * 2]) = sum;
        bar_sync(1, 128);
        if (tid < 2) asm volatile("red.release.gpu.global.add.u32 [%0], 1;" ::"l"(&gs->wcnt[(2 * NB + tid) * LS]) : "memory");
    }
}

__global__ void __cluster_dims__(2, 1, 1) __launch_bounds__(NTHREADS, 1)
resblock_kernel(const __nv_bfloat16* __restrict__ w1,
                const __nv_bfloat16* __restrict__ t_emb, const __nv_bfloat16* __restrict__ g1,
                const __nv_bfloat16* __restrict__ be1, const __nv_bfloat16* __restrict__ w_emb,
                const __nv_bfloat16* __restrict__ g2, const __nv_bfloat16* __restrict__ be2,
                const __nv_bfloat16* __restrict__ w2, __nv_bfloat16* __restrict__ out, Scratch* __restrict__ gs,
                const __grid_constant__ CUtensorMap xmap) {
    const unsigned clk0 = clock32();
    if (threadIdx.x == 480 && blockIdx.x >= NXTRA) TLG(1);
    const int tid = threadIdx.x, lane = tid & 31;
    const int cta = blockIdx.x - NXTRA, b = cta >> 6, r = cta & 63;
    uint4 v[5];
    if (tid < 32) weight_load(v, w1, cta & (NCTA - 1), lane);
    const int warp = __shfl_sync(0xffffffffu, tid >> 5, 0);
    if (cta < 0) { side_jobs(t_emb, w_emb, w2, gs, clk0); return; }

    const int seg = lane & 7;
    if (warp != 3) asm volatile("barrier.cluster.arrive.relaxed.aligned;" ::: "memory");
    const bool has_outer = (r != 0) && (r != HW - 1);
    if (warp == 1 || warp == 2 || warp == 4 || warp == 5) {
        const int g = warp < 3 ? warp - 1 : 7 - warp;
        if (elect_one()) {
            asm volatile("prefetch.tensormap [%0];" ::"l"(&xmap) : "memory");
            mbar_init(BAR(BAR_X) + 8 * g, 1);
            if (g == 3) mbar_init(BAR(BAR_X + 4), 1);
            mbar_expect(BAR(BAR_X) + 8 * g, 4096);
            fence_async_smem();
            while (clock32() - clk0 < XDELAY + (g >> 1) * XSTAG + (g & 1) * XSTAG2) {}
            tma_x(SM_XOWN + g * 4096, &xmap, r, b * C + g * 32, BAR(BAR_X) + 8 * g);
            if (g == 3 && has_outer) {
                mbar_expect(BAR(BAR_X + 4), 16384);
#pragma unroll
                for (int i = 0; i < 4; i++) tma_x(SM_XOUT + i * 4096, &xmap, r + ((r & 1) ? 1 : -1), b * C + i * 32, BAR(BAR_X + 4));
            }
        }
        __syncwarp();
        bar_arrive(4, 256 + 64 + 128);
        mbar_wait(BAR(BAR_X) + 8 * g, 0);
        if (lane == 0) TL(70 + g);
        float c[8][4];
#pragma unroll
        for (int k = 0; k < 8; k++) {
            const uint4 q = lds128(SM_XOWN + g * 4096 + k * 512 + lane * 16);
            c[k][0] = c[k][1] = c[k][2] = c[k][3] = 0.f;
            stat_mma(c[k], q.x, q.y); stat_mma(c[k], q.z, q.w);
        }
#pragma unroll
        for (int i = 0; i < 4; i++) c[0][i] = ((c[0][i] + c[1][i]) + (c[2][i] + c[3][i])) + ((c[4][i] + c[5][i]) + (c[6][i] + c[7][i]));
        stat_store(c[0], SM_RED + g * 48, lane);
        __syncwarp();
        if (lane == 0) {
            const uint32_t a = SM_RED + g * 48;
            red_add4(&gs->acc1[b * 4 * LS + g * GS1], 1.f, sum4(lds128f(a + 32)), sum4(lds128f(a)) + sum4(lds128f(a + 16)), 1.f);
            TL(74 + g);
        }
    }
    if (warp == 0 || warp == 4) {
        const int k = warp >> 2;
        if (k == 0) {
#pragma unroll
            for (int i = 0; i < 5; i++)
                if (i < 4 || lane < 16) sts128(SM_BNC + (lane + 32 * i) * 16, v[i]);
            if (lane == 0) TL(81);
            __syncwarp();
        } else {
            bar_sync(6, 64);
            mbar_wait(BAR(BAR_W2), 0);
        }
        weight_block(SM_BNC + k * 2304, gs->wt + k * NSTAGE * STAGE_BYTES, cta, lane, k == 0);
        __syncwarp();
        if (lane == 0) TL(k ? 13 : 4);
        if (k == 0 && lane < 2) asm volatile("red.relaxed.gpu.global.add.u32 [%0], 1;" ::"l"(&gs->wcnt[lane * LS + (cta >> 4)]) : "memory");
    }

    if (warp >= 8) {
        const int nw = warp - 8;
        bar_sync(4, 256 + 64 + 128);
        const int par = nw >> 2, wq = nw & 3;
        const uint32_t act_off = SM_ACT + (par * 2 + (lane >> 4)) * CH_PITCH + (2 + wq * 16 + (lane & 15)) * 16;
        const uint32_t stg_off = (par * 16 + (lane >> 4) * 8 + (lane & 7)) * 128 + (((2 * wq + ((lane >> 3) & 1)) ^ (lane & 7)) << 4);
        const uint32_t cfa = SM_COEF + par * 128 + (lane & 3) * 16;
        const uint32_t fbar = BAR(BAR_FULL) + 8 * par;
        uint4* inbox = gs->box + cta * 1024 + nw * 32 + lane;
#pragma unroll 1
        for (int conv = 0; conv < 2; conv++) {
            uint32_t u[4][4], w[4][4];
            float4 cf[8];
            if (conv == 0) {
#pragma unroll
                for (int i = 0; i < 4; i++) { mbar_wait(BAR(BAR_X + i), 0); ldsm4t(u[i], SM_XOWN + stg_off + i * 4096); }
            } else {
                mbar_wait(BAR(BAR_HW), 0);
#pragma unroll
                for (int i = 0; i < 4; i++) ldsm4(u[i], act_off + i * 2 * KC_BYTES);
            }
#pragma unroll
            for (int i = 0; i < 8; i++) cf[i] = lds128f(cfa + conv * 1024 + (i >> 1) * 256 + (i & 1) * 64);
            const uint32_t gst = SM_GST + conv * 64;
            group_coefs(gst, cf[0], cf[1]);
            if (tid == 256) TL(22 + conv * 4);
            if (par) { const unsigned c1 = clock32(); while (clock32() - c1 < PDELAY) {} }
            norm_block<0, 1>(u, cf, false, gst, act_off, ~0u, fbar, lane);
            if (tid == 256) TL(8 + conv * 8);
            norm_block<1, 1>(u, cf, true, gst, act_off, ~0u, fbar, lane);
            norm_block<2, 1>(u, cf, true, gst, act_off, ~0u, fbar, lane);
            norm_block<3, 1>(u, cf, true, gst, act_off, ~0u, fbar, lane);
            if (tid == 256) TL(84 + conv);
            if (has_outer) {
                mbar_wait(BAR(BAR_X + 4), conv);
                if (conv == 0) {
#pragma unroll
                    for (int i = 0; i < 4; i++) ldsm4t(w[i], SM_XOUT + stg_off + i * 4096);
                } else {
#pragma unroll
                    for (int i = 0; i < 4; i++) {
                        const uint4 q = lds128(SM_XOUT + (tid - 256) * 16 + i * 4096);
                        w[i][0] = q.x; w[i][1] = q.y; w[i][2] = q.z; w[i][3] = q.w;
                    }
                    unsigned it = 0;
                    while (true) {
                        bool ok = true;
#pragma unroll
                        for (int i = 0; i < 16; i++) ok = ok && w[i >> 2][i & 3] != 0;
                        if (__all_sync(0xffffffffu, ok) || ++it > SPIN_LIMIT) break;
#pragma unroll
                        for (int i = 0; i < 4; i++) ld_unit(w[i], inbox + i * 256);
                    }
#pragma unroll
                    for (int i = 0; i < 16; i++) w[i >> 2][i & 3] = ~w[i >> 2][i & 3];
                }
            }
            bar_sync(3, 256);
            if (nw == 0) sts128(SM_ACT + 2 * ROW_BYTES + (lane >> 1) * CH_PITCH + (lane & 1) * 16, make_uint4(0, 0, 0, 0));
            if (tid == 256) TL(24 + conv * 4);
            norm_block<0, 4>(w, cf, false, 0, act_off + 2 * ROW_BYTES, has_outer ? ~0u : 0u, fbar + 128, lane);
            if (tid == 256) TL(23 + conv * 4);
        }
        if (has_outer) {
            mbar_wait(BAR(BAR_FULL + NSTAGE - 1), 1);
#pragma unroll
            for (int i = 0; i < 4; i++) inbox[i * 256] = make_uint4(0, 0, 0, 0);
        }
    } else if (warp < 4) {
        const int wq = warp;
        if (wq == 3) {
            if (elect_one()) {
#pragma unroll
                for (int i = 0; i < NSTAGE; i++) mbar_init(BAR(BAR_FULL + i), (i >> 3) == 1 ? 1 : 5);
#pragma unroll
                for (int i = 0; i <= NS; i++) mbar_init(BAR(BAR_WEMPTY + i), 4);
#pragma unroll
                for (int i = BAR_STATS; i < BAR_X; i++) mbar_init(BAR(i), i == BAR_EMB ? 3 : 1);
                asm volatile("fence.mbarrier_init.release.cluster;" ::: "memory");
            }
            __syncwarp();
            fence_async_smem();
            bar_arrive(0, 96);
            bar_arrive(5, 96);
            bar_arrive(4, 256 + 64 + 128);
            const uint4 z = make_uint4(0, 0, 0, 0);
#pragma unroll
            for (int i = 0; i < 2; i++) sts128(SM_ACT + (i * 16 + (lane >> 1)) * CH_PITCH + (lane & 1) * 16, z);
            if (lane < 4) sts128(SM_ACT + (2 + (lane >> 1)) * ROW_BYTES + (lane & 1) * 16, z);
            if (lane < 16) sts128(SM_ONES + lane * 16, make_uint4(lane < 8 ? 0x3f803f80u : 0u, 0, 0, 0));
            fence_async_smem();
            asm volatile("barrier.cluster.arrive.release.aligned;" ::: "memory");
            bar_arrive(6, 64);
            if (elect_one()) {
                mbar_expect(BAR(BAR_W2), 2304);
                while (clock32() - clk0 < W2DELAY) {}
                const char* base = reinterpret_cast<const char*>(w2) + ((cta & 15) * 8 * C + (cta >> 4) * 16) * 18;
#pragma unroll 1
                for (int i = 0; i < 8; i++) bulk_g2s(S0 + SM_BNC + 2304 + i * 288, base + i * (C * 18), 288, S0 + BAR(BAR_W2));
            }
            __syncwarp();
        }
        bar_sync(2, 128);

        float d[64];
#pragma unroll
        for (int i = 0; i < 64; i++) d[i] = 0.f;
#pragma unroll 1
        for (int conv = 0; conv < 2; conv++) {
            fence_acc(d);
            mma_stages<0>(d, conv, tid, gs);
            if (conv == 0) {
                asm volatile("wgmma.fence.sync.aligned;" ::: "memory");
                wgmma128<(SM_ONES >> 4) | (8u << 16), (SM_EMB >> 4), 0, 8>(d);
                asm volatile("wgmma.commit_group.sync.aligned;" ::: "memory");
            }
            asm volatile("wgmma.wait_group.sync.aligned 0;" ::: "memory");
            fence_acc(d);
            if (tid == 0) TL(10 + conv * 8);
            if (conv == 1) break;

            uint32_t hp[32];
#pragma unroll
            for (int g = 0; g < 4; g++) {
                float c[4] = {0.f, 0.f, 0.f, 0.f};
#pragma unroll
                for (int i = 0; i < 8; i++) hp[8 * g + i] = pack_bf(d[16 * g + 2 * i], d[16 * g + 2 * i + 1]);
#pragma unroll
                for (int i = 0; i < 4; i++) stat_mma(c, hp[8 * g + 2 * i], hp[8 * g + 2 * i + 1]);
                stat_store(c, SM_RED + (g * 4 + wq) * 48, lane);
            }
            bar_sync(2, 128);
            if (wq == 0) stat_publish(SM_RED, &gs->acc2[b * LS], lane, true);
            if (tid == 0) TL(11);
            const uint32_t hbase = SM_ACT + (lane >> 4) * CH_PITCH + (2 + wq * 16 + (lane & 15)) * 16;
#pragma unroll
            for (int kc = 0; kc < 8; kc++) stsm4(hbase + kc * 2 * CH_PITCH, hp[4 * kc], hp[4 * kc + 1], hp[4 * kc + 2], hp[4 * kc + 3]);
            __syncwarp();
            if (lane == 0) mbar_arrive(BAR(BAR_HW));
            if (lane < LAG) mbar_arrive(BAR(BAR_WEMPTY + (NSTAGE - LAG) % NS) + 8 * lane);
            if (has_outer) {
                uint4* outbox = gs->box + (cta + ((r & 1) ? 1 : -1)) * 1024 + tid;
#pragma unroll
                for (int kc = 0; kc < 8; kc++) outbox[kc * 128] = make_uint4(~hp[4 * kc], ~hp[4 * kc + 1], ~hp[4 * kc + 2], ~hp[4 * kc + 3]);
            }
            if (tid == 0) TL(12);
            const uint32_t xbase = SM_XOWN + ((lane >> 4) * 8 + (lane & 7)) * 128 + (((2 * wq + ((lane >> 3) & 1)) ^ (lane & 7)) << 4);
#pragma unroll
            for (int kc = 0; kc < 8; kc++) {
                uint32_t p[4];
                ldsm4t(p, xbase + kc * 2048);
#pragma unroll
                for (int i = 0; i < 4; i++) { d[8 * kc + 2 * i] = bf_lo(p[i]); d[8 * kc + 2 * i + 1] = bf_hi(p[i]); }
            }
        }
        {
            const uint32_t obase = slot_addr(0) + ((lane >> 4) * 8 + (lane & 7)) * OUT_PITCH + (wq * 16 + ((lane >> 3) & 1) * 8) * 2;
#pragma unroll
            for (int kc = 0; kc < 8; kc++) {
                stsm4t(obase + kc * 16 * OUT_PITCH, pack_bf(d[8 * kc + 0], d[8 * kc + 1]), pack_bf(d[8 * kc + 2], d[8 * kc + 3]),
                       pack_bf(d[8 * kc + 4], d[8 * kc + 5]), pack_bf(d[8 * kc + 6], d[8 * kc + 7]));
            }
            bar_sync(2, 128);
            const int oc0 = tid >> 3;
            __nv_bfloat16* dst = out + ((size_t)(b * C + oc0) * HW + r) * HW + seg * 8;
#pragma unroll
            for (int i = 0; i < 8; i++)
                *reinterpret_cast<uint4*>(dst + (size_t)i * 16 * HW * HW) = lds128(slot_addr(0) + (oc0 + 16 * i) * OUT_PITCH + seg * 16);
            if (tid == 0) { TL(20); TLG(21); }
        }
    } else if (warp < 6) {
        bar_sync(5, 96);
        if (warp == 5) {
            asm volatile("barrier.cluster.wait.acquire.aligned;" ::: "memory");
            const uint32_t peer = (r & 1) ^ 1;
            const uint32_t self0 = mapa(0, r & 1), peer0 = mapa(0, peer);
#pragma unroll 1
            for (int conv = 0; conv < 2; conv++) {
#pragma unroll 1
                for (int kc = 0; kc < 8; kc++) {
                    mbar_wait(BAR(BAR_FULL) + 8 * kc, conv);
                    if (elect_one())
                        asm volatile("cp.async.bulk.shared::cluster.shared::cta.mbarrier::complete_tx::bytes [%0], [%1], %2, [%3];"
                                     ::"r"(peer0 + SM_ACT + ROW_BYTES + kc * KC_BYTES), "r"(self0 + SM_ACT + kc * KC_BYTES), "r"(KC_BYTES),
                                       "r"(peer0 + BAR(BAR_FULL + 8) + 8 * kc) : "memory");
                }
                if (lane == 0) TL(86 + conv);
#pragma unroll 1
                for (int kc = 0; kc < 8; kc++) mbar_wait(BAR(BAR_FULL + 8) + 8 * kc, conv);
                if (lane == 0)
                    asm volatile("mbarrier.arrive.release.cluster.shared::cluster.b64 _, [%0];" ::"r"(peer0 + (conv ? BAR(BAR_ACK) : BAR(BAR_EMB))) : "memory");
            }
            mbar_wait(BAR(BAR_ACK), 0);
        } else {
            if (lane < 2) asm volatile("red.release.gpu.global.add.u32 [%0], 1;" ::"l"(&gs->wcnt[(NB + lane) * LS]) : "memory");
            if (lane == 0) TL(14);
            mbar_wait(BAR(BAR_STATS), 0);
            unsigned it = 0;
            while (ld_relaxed(&gs->wcnt[(2 * NB + b) * LS]) < (unsigned)NXTRA && ++it < SPIN_LIMIT) __nanosleep(100);
            fence_acquire();
            float ev[4] = {0.f, 0.f, 0.f, 0.f};
#pragma unroll
            for (int j = 0; j < NXTRA; j++) {
                const uint4 ef = ld_relaxed_v4(&gs->emb[(j * NB + b) * C + lane * 4]);
                ev[0] += __uint_as_float(ef.x); ev[1] += __uint_as_float(ef.y); ev[2] += __uint_as_float(ef.z); ev[3] += __uint_as_float(ef.w);
            }
#pragma unroll
            for (int i = 0; i < 4; i++) {
                const float hi = bf_lo(pack_bf(ev[i], 0.f));
                sts128(SM_EMB + (lane * 4 + i) * 16, make_uint4(pack_bf(hi, ev[i] - hi), 0, 0, 0));
            }
            fence_async_smem();
            __syncwarp();
            if (lane == 0) { mbar_arrive(BAR(BAR_EMB)); TL(19); }
        }
    } else if (warp == 6) {
        bar_sync(0, 96);
        const uint32_t ebytes = STAGE_BYTES + ((lane >> 3) == 1 ? KC_BYTES : 0);
        if (lane < NSTAGE) mbar_expect(BAR(BAR_FULL) + 8 * lane, ebytes);
        const int swap = (r & 1) ? 0 : 8 * STAGE_BYTES;
        unsigned it = 0;
        {
            int g = 0;
#pragma unroll 1
            while (g < NS) {
                unsigned ready = __ballot_sync(0xffffffffu, ld_relaxed(&gs->wcnt[b * LS + (lane & 7)]) >= 16u) >> g;
                if (++it > SPIN_LIMIT) ready = ~0u;
                if (!(ready & 1)) continue;
                fence_acquire();
                fence_async_global();
                if (lane == 0) TL(g ? 3 : 6);
#pragma unroll 1
                for (; (ready & 1) && g < NS; g++, ready >>= 1)
                    if (elect_one())
                        bulk_g2s(S0 + SM_W + g * STAGE_BYTES, gs->wt + g * STAGE_BYTES + (g >= 8 ? swap : 0), STAGE_BYTES, S0 + BAR(BAR_FULL) + 8 * g);
            }
        }
#pragma unroll 1
        for (int q = 3; q < 12; q++) {
            const int conv = q >= 6, qs = conv ? q - 6 : q, sl = q % 3;
            const unsigned char* wsrc = gs->wt + q * 4 * STAGE_BYTES + (qs < 2 ? 0 : (qs < 4 ? swap : -swap));
            const uint32_t par = (q / 3 - 1) & 1;
            if (q == 6) {
                it = 0;
                while (ld_relaxed(&gs->wcnt[(NB + b) * LS]) < (unsigned)NCTA && ++it < SPIN_LIMIT) {}
                fence_acquire();
                fence_async_global();
                if (lane == 0) { mbar_arrive(BAR(BAR_EMB)); TL(2); }
            }
#pragma unroll
            for (int i = 0; i < 4; i++) {
                mbar_wait(BAR(BAR_WEMPTY + i) + 32 * sl, par);
                if (i == 0 && (q == 6 || q == 9)) {
                    if ((lane >= NS) == (q == 9) && lane < NSTAGE) mbar_expect(BAR(BAR_FULL) + 8 * lane, ebytes);
                    __syncwarp();
                }
                if (elect_one())
                    bulk_g2s(S0 + SM_W + (sl * 4 + i) * STAGE_BYTES, wsrc + i * STAGE_BYTES, STAGE_BYTES, S0 + BAR(BAR_FULL + i) + 32 * qs);
            }
        }
    } else {
        const uint2 ga1 = __ldg(reinterpret_cast<const uint2*>(g1) + lane), bt1 = __ldg(reinterpret_cast<const uint2*>(be1) + lane);
        const uint2 ga2 = __ldg(reinterpret_cast<const uint2*>(g2) + lane), bt2 = __ldg(reinterpret_cast<const uint2*>(be2) + lane);
        if (lane < 8) sts128(SM_GST + lane * 16, make_uint4(0, 0, 0, 0));
        sts128f(SM_COEF + lane * 32, make_float4(0.5f * bf_lo(ga1.x), 0.5f * bf_hi(ga1.x), 0.5f * bf_lo(bt1.x), 0.5f * bf_hi(bt1.x)));
        sts128f(SM_COEF + lane * 32 + 16, make_float4(0.5f * bf_lo(ga1.y), 0.5f * bf_hi(ga1.y), 0.5f * bf_lo(bt1.y), 0.5f * bf_hi(bt1.y)));
        sts128f(SM_COEF + 1024 + lane * 32, make_float4(0.5f * bf_lo(ga2.x), 0.5f * bf_hi(ga2.x), 0.5f * bf_lo(bt2.x), 0.5f * bf_hi(bt2.x)));
        sts128f(SM_COEF + 1024 + lane * 32 + 16, make_float4(0.5f * bf_lo(ga2.y), 0.5f * bf_hi(ga2.y), 0.5f * bf_lo(bt2.y), 0.5f * bf_hi(bt2.y)));
        bar_arrive(4, 256 + 64 + 128);
        bar_sync(0, 96);
#pragma unroll 1
        for (int conv = 0; conv < 2; conv++) {
            if (conv == 1) mbar_wait(BAR(BAR_EMB), 0);
            const float* asrc = conv ? &gs->acc2[b * LS + (lane & 3) * 4] : &gs->acc1[b * 4 * LS + (lane & 3) * GS1];
            unsigned it = 0;
#pragma unroll 1
            while (true) {
                const uint4 f = ld_relaxed_v4(asrc);
                const bool ok = ((f.x == 0x42800000u) & (f.w == 0x42800000u)) || ++it > SPIN_LIMIT;
                const float inv_n = 1.0f / (32.0f * HW * HW);
                const float mean = __uint_as_float(f.y) * inv_n;
                const float rs = rsqrtf(fmaxf(fmaf(-mean, mean, __uint_as_float(f.z) * inv_n), 0.f) + 1e-5f);
                if (ok && lane < 4) sts128f(SM_GST + conv * 64 + lane * 16, make_float4(rs, mean * rs, 1.f, 0.f));
                if (__all_sync(0xffffffffu, ok)) break;
            }
            if (lane == 0) { mbar_arrive(BAR(BAR_STATS)); TL(7 + conv * 8); }
        }
        if (has_outer && elect_one()) {
            mbar_expect(BAR(BAR_X + 4), 16384);
            bulk_g2s(S0 + SM_XOUT, gs->box + cta * 1024, 16384, S0 + BAR(BAR_X + 4));
        }
        if (r == 0) {
            if (lane < 16) gs->acc1[b * 4 * LS + (lane >> 2) * GS1 + (lane & 3)] = 0.f;
            if (lane < 24) gs->wcnt[((lane >> 3) * NB + b) * LS + (lane & 7)] = 0;
        }
    }
}

}

extern "C" void kernel_launch(void* const* d_in, const int* in_sizes, int n_in, void* d_out, int out_size) {
    (void)in_sizes; (void)n_in; (void)out_size;
    typedef CUresult (*EncodeFn)(CUtensorMap*, CUtensorMapDataType, cuuint32_t, void*, const cuuint64_t*, const cuuint64_t*,
                                 const cuuint32_t*, const cuuint32_t*, CUtensorMapInterleave, CUtensorMapSwizzle,
                                 CUtensorMapL2promotion, CUtensorMapFloatOOBfill);
    static Scratch* gs = nullptr;
    static EncodeFn encode = nullptr;
    if (!gs) {
        cudaFuncSetAttribute(resblock_kernel, cudaFuncAttributeMaxDynamicSharedMemorySize, SM_TOTAL);
        cudaGetSymbolAddress((void**)&gs, g_scratch);
        cudaDriverEntryPointQueryResult qr;
        cudaGetDriverEntryPoint("cuTensorMapEncodeTiled", (void**)&encode, cudaEnableDefault, &qr);
    }
    CUtensorMap xmap;
    const cuuint64_t dims[3] = {HW, HW, NB * C}, strides[2] = {HW * 2, HW * HW * 2};
    const cuuint32_t box[3] = {HW, 1, 32}, es[3] = {1, 1, 1};
    encode(&xmap, CU_TENSOR_MAP_DATA_TYPE_BFLOAT16, 3, d_in[0], dims, strides, box, es, CU_TENSOR_MAP_INTERLEAVE_NONE,
           CU_TENSOR_MAP_SWIZZLE_128B, CU_TENSOR_MAP_L2_PROMOTION_NONE, CU_TENSOR_MAP_FLOAT_OOB_FILL_NONE);
    resblock_kernel<<<NCTA + NXTRA, NTHREADS, SM_TOTAL>>>(
        (const __nv_bfloat16*)d_in[4], (const __nv_bfloat16*)d_in[1],
        (const __nv_bfloat16*)d_in[2], (const __nv_bfloat16*)d_in[3], (const __nv_bfloat16*)d_in[5],
        (const __nv_bfloat16*)d_in[6], (const __nv_bfloat16*)d_in[7], (const __nv_bfloat16*)d_in[8],
        (__nv_bfloat16*)d_out, gs, xmap);
}
```

```cpp
#include <cuda_runtime.h>
#include <cuda.h>
#include <cuda_bf16.h>
#include <stdint.h>

namespace {

constexpr int C = 128, HW = 64, NB = 2, E = 768;
constexpr int NCTA = NB * HW;
constexpr int NXTRA = 4;
constexpr int NTHREADS = 16 * 32;
constexpr int CH_PITCH = 66 * 16;
constexpr int ROW_BYTES = 16 * CH_PITCH;
constexpr int STEP_BYTES = 4096;
constexpr int STAGE_BYTES = 3 * STEP_BYTES;
constexpr int NSTAGE = 24;
constexpr int KC_BYTES = 2 * CH_PITCH;
constexpr int NS = 12;
constexpr int LAG = 1;
#define XDELAY 600
#define HDELAY 600
#define SEQ 0
#define MMA0_WAIT mbar_try
#define PDELAY 60
#define RB 1
#define XSTAG2 200
#define XSTAG 800
#define HSEND 0
#define W2DELAY 2000

constexpr uint32_t SMEM_BASE = 0x400;
constexpr uint32_t SM_XOWN = SMEM_BASE;
constexpr uint32_t SM_ACT = SM_XOWN + 16384 + 512;
constexpr uint32_t SM_XOUT = SM_ACT + 2 * ROW_BYTES + 512;
static_assert(SM_XOUT % 1024 == 0, "swizzle atom alignment");
constexpr uint32_t SM_W = SM_ACT + 3 * ROW_BYTES + 128;
__host__ __device__ constexpr uint32_t slot_addr(int slot) { return SM_W + slot * STAGE_BYTES; }
constexpr uint32_t SM_COEF = SM_W + NS * STAGE_BYTES;
constexpr uint32_t SM_GST = SM_COEF + 2048;
constexpr uint32_t SM_EMB = SM_GST + 128;
constexpr uint32_t SM_ONES = SM_EMB + 2048;
constexpr uint32_t SM_RED = SM_ONES + 256;
constexpr uint32_t SM_BNC = SM_RED + 1280;
constexpr uint32_t SM_BAR = SM_BNC + 2 * 2304;
constexpr int BAR_FULL = 0, BAR_WEMPTY = NSTAGE, BAR_HW = BAR_WEMPTY + NS, BAR_XFREE = BAR_HW + 1, BAR_STATS = BAR_XFREE + 1,
              BAR_EMB = BAR_STATS + 1, BAR_ACK = BAR_EMB + 1, BAR_W2 = BAR_ACK + 1, BAR_X = BAR_W2 + 1  , NBAR = BAR_X + 5;
constexpr int SM_TOTAL = SM_BAR + NBAR * 8 - SMEM_BASE;
static_assert(SM_TOTAL <= 232448, "smem");
static_assert(NBAR <= 96, "barrier init");
constexpr int OUT_PITCH = 144;
__host__ __device__ constexpr uint32_t BAR(int i) { return SM_BAR + 8 * i; }
__host__ __device__ constexpr int ky_of(int kyo) { return kyo == 0 ? 1 : (kyo == 1 ? 0 : 2); }

constexpr unsigned SPIN_LIMIT = 1u << 16;

#define LS 1056
#define GS1 4
#define PD 0
struct Scratch {
    float acc1[NB * 4 * LS];
    float acc2[NB * LS];
    unsigned wcnt[3 * NB * LS];
    float emb[NXTRA * NB * C];
    unsigned char wt[2 * NSTAGE * STAGE_BYTES];
    uint4 box[NCTA * 1024];
};
__device__ __align__(1024) Scratch g_scratch;
#define TL(i) do {} while (0)
#define TLG(i) do {} while (0)

__device__ __forceinline__ unsigned clock32() { unsigned c; asm volatile("mov.u32 %0, %%clock;" : "=r"(c)); return c; }
__device__ __forceinline__ uint32_t mapa(uint32_t a, uint32_t rank) {
    uint32_t d;
    asm("mapa.shared::cluster.u32 %0, %1, %2;" : "=r"(d) : "r"(a), "r"(rank));
    return d;
}
#define S0 mapa(0, blockIdx.x & 1)
__device__ __forceinline__ void mbar_init(uint32_t bar, int cnt) {
    asm volatile("mbarrier.init.shared::cta.b64 [%0], %1;" ::"r"(bar + S0), "r"(cnt) : "memory");
}
__device__ __forceinline__ void mbar_arrive(uint32_t bar) {
    asm volatile("mbarrier.arrive.shared::cta.b64 _, [%0];" ::"r"(bar + S0) : "memory");
}
__device__ __forceinline__ void mbar_expect(uint32_t bar, uint32_t bytes) {
    asm volatile("mbarrier.arrive.expect_tx.shared::cta.b64 _, [%0], %1;" ::"r"(bar + S0), "r"(bytes) : "memory");
}
__device__ __forceinline__ bool mbar_try(uint32_t bar, uint32_t par) {
    uint32_t ok;
    asm volatile("{\n.reg .pred p;\nmbarrier.try_wait.parity.shared::cta.b64 p, [%1], %2;\nselp.u32 %0, 1, 0, p;\n}"
                 : "=r"(ok) : "r"(bar + S0), "r"(par) : "memory");
    return ok;
}
__device__ __forceinline__ bool mbar_test(uint32_t bar, uint32_t par) {
    uint32_t ok;
    asm volatile("{\n.reg .pred p;\nmbarrier.test_wait.parity.shared::cta.b64 p, [%1], %2;\nselp.u32 %0, 1, 0, p;\n}"
                 : "=r"(ok) : "r"(bar + S0), "r"(par) : "memory");
    return ok;
}
__device__ __forceinline__ void mbar_wait(uint32_t bar, uint32_t par) {
    unsigned it = 0;
#pragma unroll 1
    while (!mbar_try(bar, par) && ++it < SPIN_LIMIT) {}
}
__device__ __forceinline__ bool elect_one() {
    uint32_t p;
    asm volatile("{\n.reg .pred p;\nelect.sync _|p, 0xffffffff;\nselp.u32 %0, 1, 0, p;\n}" : "=r"(p));
    return p;
}
__device__ __forceinline__ void fence_async_smem() { asm volatile("fence.proxy.async.shared::cta;" ::: "memory"); }
__device__ __forceinline__ void fence_async_global() { asm volatile("fence.proxy.async.global;" ::: "memory"); }
__device__ __forceinline__ void fence_acquire() { asm volatile("fence.acquire.gpu;" ::: "memory"); }
__device__ __forceinline__ void bar_sync(int id, int n) { asm volatile("bar.sync %0, %1;" ::"r"(id), "r"(n) : "memory"); }
__device__ __forceinline__ void bar_arrive(int id, int n) { asm volatile("bar.arrive %0, %1;" ::"r"(id), "r"(n) : "memory"); }
__device__ __forceinline__ void bulk_g2s(uint32_t dst, const void* src, uint32_t bytes, uint32_t bar) {
    asm volatile("cp.async.bulk.shared::cluster.global.mbarrier::complete_tx::bytes [%0], [%1], %2, [%3];"
                 ::"r"(dst), "l"(src), "r"(bytes), "r"(bar) : "memory");
}
__device__ __forceinline__ void tma_x(uint32_t dst, const CUtensorMap* tm, int row, int ch, uint32_t bar) {
    asm volatile("cp.async.bulk.tensor.3d.shared::cluster.global.mbarrier::complete_tx::bytes [%0], [%1, {%2, %3, %4}], [%5];"
                 ::"r"(dst + S0), "l"(tm), "r"(0), "r"(row), "r"(ch), "r"(bar + S0) : "memory");
}
__device__ __forceinline__ uint4 ld_relaxed_v4(const void* p) {
    uint4 v;
    asm volatile("ld.relaxed.gpu.global.v4.u32 {%0,%1,%2,%3}, [%4];" : "=r"(v.x), "=r"(v.y), "=r"(v.z), "=r"(v.w) : "l"(p) : "memory");
    return v;
}
__device__ __forceinline__ unsigned ld_relaxed(const void* p) {
    unsigned v;
    asm volatile("ld.relaxed.gpu.global.u32 %0, [%1];" : "=r"(v) : "l"(p) : "memory");
    return v;
}
__device__ __forceinline__ void red_add4(float* p, float a, float b, float c, float d) {
    asm volatile("red.relaxed.gpu.global.add.v4.f32 [%0], {%1,%2,%3,%4};" ::"l"(p), "f"(a), "f"(b), "f"(c), "f"(d) : "memory");
}
__device__ __forceinline__ void sts128(uint32_t a, uint4 v) {
    asm volatile("st.shared.v4.u32 [%0], {%1,%2,%3,%4};" ::"r"(a + S0), "r"(v.x), "r"(v.y), "r"(v.z), "r"(v.w) : "memory");
}
__device__ __forceinline__ void sts128f(uint32_t a, float4 v) {
    asm volatile("st.shared.v4.f32 [%0], {%1,%2,%3,%4};" ::"r"(a + S0), "f"(v.x), "f"(v.y), "f"(v.z), "f"(v.w) : "memory");
}
__device__ __forceinline__ void sts32f(uint32_t a, float v) { asm volatile("st.shared.f32 [%0], %1;" ::"r"(a + S0), "f"(v) : "memory"); }
__device__ __forceinline__ uint4 lds128(uint32_t a) {
    uint4 v;
    asm volatile("ld.shared.v4.u32 {%0,%1,%2,%3}, [%4];" : "=r"(v.x), "=r"(v.y), "=r"(v.z), "=r"(v.w) : "r"(a + S0) : "memory");
    return v;
}
__device__ __forceinline__ float4 lds128f(uint32_t a) {
    float4 v;
    asm volatile("ld.shared.v4.f32 {%0,%1,%2,%3}, [%4];" : "=f"(v.x), "=f"(v.y), "=f"(v.z), "=f"(v.w) : "r"(a + S0) : "memory");
    return v;
}
__device__ __forceinline__ float2 lds64f(uint32_t a) {
    float2 v;
    asm volatile("ld.shared.v2.f32 {%0,%1}, [%2];" : "=f"(v.x), "=f"(v.y) : "r"(a + S0) : "memory");
    return v;
}
__device__ __forceinline__ float bf_lo(uint32_t u) { return __uint_as_float(u << 16); }
__device__ __forceinline__ float bf_hi(uint32_t u) { return __uint_as_float(u & 0xffff0000u); }
__device__ __forceinline__ uint32_t pack_bf(float lo, float hi) {
    uint32_t r;
    asm("cvt.rn.bf16x2.f32 %0, %1, %2;" : "=r"(r) : "f"(hi), "f"(lo));
    return r;
}
__device__ __forceinline__ float tanh_fast(float x) {
    float r;
    asm("tanh.approx.f32 %0, %1;" : "=f"(r) : "f"(x));
    return r;
}
__device__ __forceinline__ float silu_half(float h) { return fmaf(h, tanh_fast(h), h); }
__device__ __forceinline__ void ldsm4(uint32_t (&u)[4], uint32_t a) {
    asm volatile("ldmatrix.sync.aligned.m8n8.x4.shared.b16 {%0,%1,%2,%3}, [%4];"
                 : "=r"(u[0]), "=r"(u[1]), "=r"(u[2]), "=r"(u[3]) : "r"(a + S0) : "memory");
}
__device__ __forceinline__ void ldsm4t(uint32_t (&u)[4], uint32_t a) {
    asm volatile("ldmatrix.sync.aligned.m8n8.x4.trans.shared.b16 {%0,%1,%2,%3}, [%4];"
                 : "=r"(u[0]), "=r"(u[1]), "=r"(u[2]), "=r"(u[3]) : "r"(a + S0) : "memory");
}
__device__ __forceinline__ void stsm4(uint32_t a, uint32_t p0, uint32_t p1, uint32_t p2, uint32_t p3) {
    asm volatile("stmatrix.sync.aligned.m8n8.x4.shared.b16 [%0], {%1,%2,%3,%4};" ::"r"(a + S0), "r"(p0), "r"(p1), "r"(p2), "r"(p3) : "memory");
}
__device__ __forceinline__ void stsm4t(uint32_t a, uint32_t p0, uint32_t p1, uint32_t p2, uint32_t p3) {
    asm volatile("stmatrix.sync.aligned.m8n8.x4.trans.shared.b16 [%0], {%1,%2,%3,%4};" ::"r"(a + S0), "r"(p0), "r"(p1), "r"(p2), "r"(p3) : "memory");
}

#define R8(o) "+f"(d[o]), "+f"(d[o + 1]), "+f"(d[o + 2]), "+f"(d[o + 3]), "+f"(d[o + 4]), "+f"(d[o + 5]), "+f"(d[o + 6]), "+f"(d[o + 7])
template <uint32_t ALO, uint32_t BLO, uint64_t AHI = 8, uint64_t BHI = 48>
__device__ __forceinline__ void wgmma128(float (&d)[64]) {
    asm volatile(
        "wgmma.mma_async.sync.aligned.m64n128k16.f32.bf16.bf16 "
        "{%0,%1,%2,%3,%4,%5,%6,%7,%8,%9,%10,%11,%12,%13,%14,%15,%16,%17,%18,%19,%20,%21,%22,%23,%24,%25,%26,%27,%28,%29,%30,%31,"
        "%32,%33,%34,%35,%36,%37,%38,%39,%40,%41,%42,%43,%44,%45,%46,%47,%48,%49,%50,%51,%52,%53,%54,%55,%56,%57,%58,%59,%60,%61,%62,%63},"
        " %64, %65, 1, 1, 1, 0, 0;"
        : R8(0), R8(8), R8(16), R8(24), R8(32), R8(40), R8(48), R8(56)
        : "l"((AHI << 32) | ALO), "l"((BHI << 32) | BLO));
}
template <int S>
__device__ __forceinline__ void mma_stages(float (&d)[64], int conv, int tid, Scratch* gs) {
    constexpr uint32_t A = ((SM_ACT + S * 2 * CH_PITCH + 16) >> 4) | ((CH_PITCH >> 4) << 16);
    constexpr uint32_t B = (slot_addr(S % NS) >> 4) | (8u << 16);
    if (S == 0) {
        unsigned it = 0;
#pragma unroll 1
        while (!MMA0_WAIT(BAR(BAR_FULL), conv) && ++it < SPIN_LIMIT) {}
    }
    bool next_ok = true;
    constexpr uint32_t NEXT = S + 1 < NSTAGE ? BAR(BAR_FULL + S + 1) : BAR(BAR_EMB);
    const int npar = S + 1 < NSTAGE ? conv : 0;
    next_ok = mbar_test(NEXT, npar);
    if (S == 0 && tid == 0) TL(32 + conv * 24);
    asm volatile("wgmma.fence.sync.aligned;" ::: "memory");
    wgmma128<A, B>(d);
    wgmma128<A + 1, B + 16>(d);
    wgmma128<A + 2, B + 32>(d);
    asm volatile("wgmma.commit_group.sync.aligned;" ::: "memory");
    if (S >= LAG) {
        asm volatile("wgmma.wait_group.sync.aligned %0;" ::"n"(LAG) : "memory");
        if ((tid & 31) == 0) mbar_arrive(BAR(BAR_WEMPTY + (S + NS - LAG) % NS));
    }
    if (!next_ok) mbar_wait(NEXT, npar);
    if constexpr (S + 1 < NSTAGE) mma_stages<S + 1>(d, conv, tid, gs);
}

__device__ __forceinline__ void weight_load(uint4 (&t)[5], const __nv_bfloat16* w, int cta, int lane) {
    const char* base = reinterpret_cast<const char*>(w) + ((cta & 15) * 8 * C + (cta >> 4) * 16) * 18;
#pragma unroll
    for (int k = 0; k < 5; k++) {
        const int i = lane + 32 * k, row = (i * 57) >> 10;
        if (k < 4 || lane < 16) t[k] = __ldg(reinterpret_cast<const uint4*>(base + row * (C * 18 - 288) + i * 16));
    }
}
__device__ __forceinline__ void weight_block(uint32_t bounce, unsigned char* wt, int cta, int lane, bool readback) {
    unsigned char* dst = wt + (cta >> 4) * STAGE_BYTES + (cta & 15) * 768;
    if (lane < 16) {
        uint32_t v[36];
#pragma unroll
        for (int i = 0; i < 9; i++) {
            const uint4 q = lds128(bounce + (lane & 7) * 288 + (lane >> 3) * 144 + i * 16);
            v[4 * i] = q.x; v[4 * i + 1] = q.y; v[4 * i + 2] = q.z; v[4 * i + 3] = q.w;
        }
#pragma unroll
        for (int kyo = 0; kyo < 3; kyo++) {
#pragma unroll
            for (int kx = 0; kx < 3; kx++) {
                const int tap = ky_of(kyo) * 3 + kx;
                uint32_t o[4];
#pragma unroll
                for (int m = 0; m < 4; m++) {
                    const int i0 = 18 * m + tap, i1 = i0 + 9;
                    const uint32_t sel = ((i0 & 1) ? 0x32u : 0x10u) | ((i1 & 1) ? 0x7600u : 0x5400u);
                    o[m] = __byte_perm(v[i0 >> 1], v[i1 >> 1], sel);
                }
                *reinterpret_cast<uint4*>(dst + kyo * 8 * STAGE_BYTES + kx * 256 + lane * 16) = make_uint4(o[0], o[1], o[2], o[3]);
            }
        }
    }
    if (readback) {
        __syncwarp();
        unsigned acc = 0;
        if (lane < 24) {
#pragma unroll
            for (int i = 0; i < 3; i++) acc |= ld_relaxed(dst + i * 8 * STAGE_BYTES + lane * 32);
        }
        asm volatile("{\n.reg .pred p;\nsetp.eq.u32 p, %0, 0x9e3779b9;\n@p st.shared.u32 [%1], %0;\n}" ::"r"(acc), "r"(bounce + S0) : "memory");
    }
}
__device__ __forceinline__ uint32_t act2(uint32_t u, const float4& cf) {
    return pack_bf(silu_half(fmaf(bf_lo(u), cf.x, cf.z)), silu_half(fmaf(bf_hi(u), cf.y, cf.w)));
}
__device__ __forceinline__ void norm_unit(uint32_t (&u)[4], const float4& ca, const float4& cb) {
    u[0] = act2(u[0], ca); u[1] = act2(u[1], ca); u[2] = act2(u[2], cb); u[3] = act2(u[3], cb);
}
__device__ __forceinline__ void group_coefs(uint32_t slot, float4& ca, float4& cb) {
    float4 gsv;
    unsigned it = 0;
#pragma unroll 1
    do {
        asm volatile("ld.volatile.shared.v4.f32 {%0,%1,%2,%3}, [%4];" : "=f"(gsv.x), "=f"(gsv.y), "=f"(gsv.z), "=f"(gsv.w) : "r"(slot + S0) : "memory");
    } while (!__all_sync(0xffffffffu, gsv.z != 0.f) && ++it < 8 * SPIN_LIMIT);
    ca.z = fmaf(-gsv.y, ca.x, ca.z); ca.w = fmaf(-gsv.y, ca.y, ca.w); ca.x *= gsv.x; ca.y *= gsv.x;
    cb.z = fmaf(-gsv.y, cb.x, cb.z); cb.w = fmaf(-gsv.y, cb.y, cb.w); cb.x *= gsv.x; cb.y *= gsv.x;
}
template <int FIRST, int N>
__device__ __forceinline__ void norm_block(uint32_t (&u)[4][4], float4 (&cf)[8], bool fold, uint32_t gst, uint32_t act, uint32_t mask, uint32_t fbar, int lane) {
    if (fold) {
#pragma unroll
        for (int t = FIRST; t < FIRST + N; t++) group_coefs(gst + 16 * t, cf[2 * t], cf[2 * t + 1]);
    }
#pragma unroll
    for (int t = FIRST; t < FIRST + N; t++) {
        norm_unit(u[t], cf[2 * t], cf[2 * t + 1]);
        stsm4(act + t * 2 * KC_BYTES, u[t][0] & mask, u[t][1] & mask, u[t][2] & mask, u[t][3] & mask);
    }
    fence_async_smem();
    __syncwarp();
    if (lane < N) mbar_arrive(fbar + 16 * (FIRST + lane));
}
__device__ __forceinline__ void stat_mma(float (&c)[4], uint32_t p, uint32_t q) {
    asm("mma.sync.aligned.m16n8k16.row.col.f32.bf16.bf16.f32 {%0,%1,%2,%3}, {%4,%5,%6,%5}, {%4,%6}, {%0,%1,%2,%3};"
        : "+f"(c[0]), "+f"(c[1]), "+f"(c[2]), "+f"(c[3]) : "r"(p), "r"(0x3f803f80u), "r"(q));
}
__device__ __forceinline__ void stat_store(const float (&c)[4], uint32_t dst, int lane) {
    const int g = lane >> 2, t = lane & 3;
    if (t == (g >> 1)) sts32f(dst + g * 4, (g & 1) ? c[1] : c[0]);
    if (g == 7) sts32f(dst + 32 + t * 4, c[2] + c[3]);
}
__device__ __forceinline__ float sum4(float4 v) { return (v.x + v.y) + (v.z + v.w); }
__device__ __forceinline__ void stat_publish(uint32_t src, float* acc, int lane, bool real) {
    const uint32_t a = src + (lane & 15) * 48;
    float q = sum4(lds128f(a)) + sum4(lds128f(a + 16)), sm = sum4(lds128f(a + 32));
    q += __shfl_xor_sync(0xffffffffu, q, 1); sm += __shfl_xor_sync(0xffffffffu, sm, 1);
    q += __shfl_xor_sync(0xffffffffu, q, 2); sm += __shfl_xor_sync(0xffffffffu, sm, 2);
    if (real && (lane & 19) == 0) red_add4(acc + lane, 1.f, sm, q, 1.f);
}
__device__ __forceinline__ void fence_acc(float (&d)[64]) {
#pragma unroll
    for (int i = 0; i < 64; i++) asm volatile("" : "+f"(d[i])::"memory");
}
__device__ __forceinline__ void ld_unit(uint32_t (&u)[4], const uint4* p) {
    asm volatile("ld.relaxed.gpu.global.v4.u32 {%0,%1,%2,%3}, [%4];" : "=r"(u[0]), "=r"(u[1]), "=r"(u[2]), "=r"(u[3]) : "l"(p) : "memory");
}

__device__ __noinline__ void side_jobs(const __nv_bfloat16* __restrict__ t_emb, const __nv_bfloat16* __restrict__ w_emb,
                                       const __nv_bfloat16* __restrict__ w2, Scratch* __restrict__ gs, unsigned clk0) {
    const int tid = threadIdx.x, warp = tid >> 5, lane = tid & 31, j = blockIdx.x;
    float tv = 0.f;
    if (lane < 24) tv = __bfloat162float(t_emb[(lane / 12) * E + j * 192 + warp * 12 + lane % 12]);
    if (tid == 0) {
        mbar_init(BAR(0), 1);
        mbar_expect(BAR(0), 192 * C * 2);
        fence_async_smem();
        while (clock32() - clk0 < W2DELAY) {}
#pragma unroll
        for (int i = 0; i < 4; i++) bulk_g2s(S0 + SM_W + i * 12288, w_emb + (j * 192 + i * 48) * C, 12288, S0 + BAR(0));
    }
    if (j == 0 && tid < 32) gs->acc2[(tid >> 4) * LS + (tid & 15)] = 0.f;
    const float sv = silu_half(0.5f * tv);
    __syncthreads();
    mbar_wait(BAR(0), 0);
    float acc[8] = {0.f, 0.f, 0.f, 0.f, 0.f, 0.f, 0.f, 0.f};
#pragma unroll
    for (int i = 0; i < 12; i++) {
        const float2 wq = lds64f(SM_W + (warp * 12 + i) * 256 + lane * 8);
        const uint32_t wx = __float_as_uint(wq.x), wy = __float_as_uint(wq.y);
#pragma unroll
        for (int bb = 0; bb < 2; bb++) {
            const float sx = __shfl_sync(0xffffffffu, sv, bb * 12 + i);
            acc[4 * bb + 0] = fmaf(sx, bf_lo(wx), acc[4 * bb + 0]); acc[4 * bb + 1] = fmaf(sx, bf_hi(wx), acc[4 * bb + 1]);
            acc[4 * bb + 2] = fmaf(sx, bf_lo(wy), acc[4 * bb + 2]); acc[4 * bb + 3] = fmaf(sx, bf_hi(wy), acc[4 * bb + 3]);
        }
    }
    sts128f(SM_ACT + warp * 1024 + lane * 16, make_float4(acc[0], acc[1], acc[2], acc[3]));
    sts128f(SM_ACT + warp * 1024 + 512 + lane * 16, make_float4(acc[4], acc[5], acc[6], acc[7]));
    __syncthreads();
    if (tid < 128) {
        float2 sum = make_float2(0.f, 0.f);
#pragma unroll
        for (int w = 0; w < 16; w++) { const float2 p = lds64f(SM_ACT + w * 1024 + tid * 8); sum.x += p.x; sum.y += p.y; }
        *reinterpret_cast<float2*>(&gs->emb[j * NB * C + tid * 2]) = sum;
        bar_sync(1, 128);
        if (tid < 2) asm volatile("red.release.gpu.global.add.u32 [%0], 1;" ::"l"(&gs->wcnt[(2 * NB + tid) * LS]) : "memory");
    }
}

__global__ void __cluster_dims__(2, 1, 1) __launch_bounds__(NTHREADS, 1)
resblock_kernel(const __nv_bfloat16* __restrict__ w1,
                const __nv_bfloat16* __restrict__ t_emb, const __nv_bfloat16* __restrict__ g1,
                const __nv_bfloat16* __restrict__ be1, const __nv_bfloat16* __restrict__ w_emb,
                const __nv_bfloat16* __restrict__ g2, const __nv_bfloat16* __restrict__ be2,
                const __nv_bfloat16* __restrict__ w2, __nv_bfloat16* __restrict__ out, Scratch* __restrict__ gs,
                const __grid_constant__ CUtensorMap xmap) {
    const unsigned clk0 = clock32();
    if (threadIdx.x == 480 && blockIdx.x >= NXTRA) TLG(1);
    const int tid = threadIdx.x, lane = tid & 31;
    const int cta = blockIdx.x - NXTRA, b = cta >> 6, r = cta & 63;
    uint4 v[5];
    if (tid < 32) weight_load(v, w1, cta & (NCTA - 1), lane);
    const int warp = __shfl_sync(0xffffffffu, tid >> 5, 0);
    if (cta < 0) { side_jobs(t_emb, w_emb, w2, gs, clk0); return; }

    const int seg = lane & 7;
    if (warp != 3) asm volatile("barrier.cluster.arrive.relaxed.aligned;" ::: "memory");
    const bool has_outer = (r != 0) && (r != HW - 1);
    if (warp == 1 || warp == 2 || warp == 4 || warp == 5) {
        const int g = warp < 3 ? warp - 1 : 7 - warp;
        if (elect_one()) {
            asm volatile("prefetch.tensormap [%0];" ::"l"(&xmap) : "memory");
            mbar_init(BAR(BAR_X) + 8 * g, 1);
            if (g == 3) mbar_init(BAR(BAR_X + 4), 1);
            mbar_expect(BAR(BAR_X) + 8 * g, 4096);
            fence_async_smem();
            while (clock32() - clk0 < XDELAY + (g >> 1) * XSTAG + (g & 1) * XSTAG2) {}
            tma_x(SM_XOWN + g * 4096, &xmap, r, b * C + g * 32, BAR(BAR_X) + 8 * g);
            if (g == 3 && has_outer) {
                mbar_expect(BAR(BAR_X + 4), 16384);
#pragma unroll
                for (int i = 0; i < 4; i++) tma_x(SM_XOUT + i * 4096, &xmap, r + ((r & 1) ? 1 : -1), b * C + i * 32, BAR(BAR_X + 4));
            }
        }
        __syncwarp();
        bar_arrive(4, 256 + 64 + 128);
        mbar_wait(BAR(BAR_X) + 8 * g, 0);
        if (lane == 0) TL(70 + g);
        float c[8][4];
#pragma unroll
        for (int k = 0; k < 8; k++) {
            const uint4 q = lds128(SM_XOWN + g * 4096 + k * 512 + lane * 16);
            c[k][0] = c[k][1] = c[k][2] = c[k][3] = 0.f;
            stat_mma(c[k], q.x, q.y); stat_mma(c[k], q.z, q.w);
        }
#pragma unroll
        for (int i = 0; i < 4; i++) c[0][i] = ((c[0][i] + c[1][i]) + (c[2][i] + c[3][i])) + ((c[4][i] + c[5][i]) + (c[6][i] + c[7][i]));
        stat_store(c[0], SM_RED + g * 48, lane);
        __syncwarp();
        if (lane == 0) {
            const uint32_t a = SM_RED + g * 48;
            red_add4(&gs->acc1[b * 4 * LS + g * GS1], 1.f, sum4(lds128f(a + 32)), sum4(lds128f(a)) + sum4(lds128f(a + 16)), 1.f);
            TL(74 + g);
        }
    }
    if (warp == 0 || warp == 4) {
        const int k = warp >> 2;
        if (k == 0) {
#pragma unroll
            for (int i = 0; i < 5; i++)
                if (i < 4 || lane < 16) sts128(SM_BNC + (lane + 32 * i) * 16, v[i]);
            if (lane == 0) TL(81);
            __syncwarp();
        } else {
            bar_sync(6, 64);
            mbar_wait(BAR(BAR_W2), 0);
        }
        weight_block(SM_BNC + k * 2304, gs->wt + k * NSTAGE * STAGE_BYTES, cta, lane, k == 0);
        __syncwarp();
        if (lane == 0) TL(k ? 13 : 4);
        if (k == 0 && lane < 2) asm volatile("red.relaxed.gpu.global.add.u32 [%0], 1;" ::"l"(&gs->wcnt[lane * LS + (cta >> 4)]) : "memory");
    }

    if (warp >= 8) {
        const int nw = warp - 8;
        bar_sync(4, 256 + 64 + 128);
        const int par = nw >> 2, wq = nw & 3;
        const uint32_t act_off = SM_ACT + (par * 2 + (lane >> 4)) * CH_PITCH + (2 + wq * 16 + (lane & 15)) * 16;
        const uint32_t stg_off = (par * 16 + (lane >> 4) * 8 + (lane & 7)) * 128 + (((2 * wq + ((lane >> 3) & 1)) ^ (lane & 7)) << 4);
        const uint32_t cfa = SM_COEF + par * 128 + (lane & 3) * 16;
        const uint32_t fbar = BAR(BAR_FULL) + 8 * par;
        uint4* inbox = gs->box + cta * 1024 + nw * 32 + lane;
#pragma unroll 1
        for (int conv = 0; conv < 2; conv++) {
            uint32_t u[4][4], w[4][4];
            float4 cf[8];
            if (conv == 0) {
#pragma unroll
                for (int i = 0; i < 4; i++) { mbar_wait(BAR(BAR_X + i), 0); ldsm4t(u[i], SM_XOWN + stg_off + i * 4096); }
            } else {
                mbar_wait(BAR(BAR_HW), 0);
#pragma unroll
                for (int i = 0; i < 4; i++) ldsm4(u[i], act_off + i * 2 * KC_BYTES);
            }
#pragma unroll
            for (int i = 0; i < 8; i++) cf[i] = lds128f(cfa + conv * 1024 + (i >> 1) * 256 + (i & 1) * 64);
            const uint32_t gst = SM_GST + conv * 64;
            group_coefs(gst, cf[0], cf[1]);
            if (tid == 256) TL(22 + conv * 4);
            if (par) { const unsigned c1 = clock32(); while (clock32() - c1 < PDELAY) {} }
            norm_block<0, 1>(u, cf, false, gst, act_off, ~0u, fbar, lane);
            if (tid == 256) TL(8 + conv * 8);
            norm_block<1, 1>(u, cf, true, gst, act_off, ~0u, fbar, lane);
            norm_block<2, 1>(u, cf, true, gst, act_off, ~0u, fbar, lane);
            norm_block<3, 1>(u, cf, true, gst, act_off, ~0u, fbar, lane);
            if (tid == 256) TL(84 + conv);
            if (has_outer) {
                mbar_wait(BAR(BAR_X + 4), conv);
                if (conv == 0) {
#pragma unroll
                    for (int i = 0; i < 4; i++) ldsm4t(w[i], SM_XOUT + stg_off + i * 4096);
                } else {
#pragma unroll
                    for (int i = 0; i < 4; i++) {
                        const uint4 q = lds128(SM_XOWN + (tid - 256) * 16 + i * 4096);
                        w[i][0] = q.x; w[i][1] = q.y; w[i][2] = q.z; w[i][3] = q.w;
                    }
                    unsigned it = 0;
                    while (true) {
                        bool ok = true;
#pragma unroll
                        for (int i = 0; i < 16; i++) ok = ok && w[i >> 2][i & 3] != 0;
                        if (__all_sync(0xffffffffu, ok) || ++it > SPIN_LIMIT) break;
#pragma unroll
                        for (int i = 0; i < 4; i++) ld_unit(w[i], inbox + i * 256);
                    }
#pragma unroll
                    for (int i = 0; i < 16; i++) w[i >> 2][i & 3] = ~w[i >> 2][i & 3];
                }
            }
            if (conv == 0) {
                bar_sync(3, 256);
                if (nw == 0) sts128(SM_ACT + 2 * ROW_BYTES + (lane >> 1) * CH_PITCH + (lane & 1) * 16, make_uint4(0, 0, 0, 0));
            }
            if (tid == 256) TL(24 + conv * 4);
            norm_block<0, 2>(w, cf, false, 0, act_off + 2 * ROW_BYTES, has_outer ? ~0u : 0u, fbar + 128, lane);
            if (tid == 256) TL(88 + conv);
            norm_block<2, 2>(w, cf, false, 0, act_off + 2 * ROW_BYTES, has_outer ? ~0u : 0u, fbar + 128, lane);
            if (tid == 256) TL(23 + conv * 4);
        }
        if (has_outer) {
            mbar_wait(BAR(BAR_FULL + NSTAGE - 1), 1);
#pragma unroll
            for (int i = 0; i < 4; i++) inbox[i * 256] = make_uint4(0, 0, 0, 0);
        }
    } else if (warp < 4) {
        const int wq = warp;
        if (wq == 3) {
            if (elect_one()) {
#pragma unroll
                for (int i = 0; i < NSTAGE; i++) mbar_init(BAR(BAR_FULL + i), (i >> 3) == 1 ? 1 : 5);
#pragma unroll
                for (int i = 0; i < NS + 2; i++) mbar_init(BAR(BAR_WEMPTY + i), 4);
#pragma unroll
                for (int i = BAR_STATS; i < BAR_X; i++) mbar_init(BAR(i), i == BAR_EMB ? 3 : 1);
                asm volatile("fence.mbarrier_init.release.cluster;" ::: "memory");
            }
            __syncwarp();
            fence_async_smem();
            bar_arrive(0, 96);
            bar_arrive(5, 96);
            bar_arrive(4, 256 + 64 + 128);
            const uint4 z = make_uint4(0, 0, 0, 0);
#pragma unroll
            for (int i = 0; i < 2; i++) sts128(SM_ACT + (i * 16 + (lane >> 1)) * CH_PITCH + (lane & 1) * 16, z);
            if (lane < 4) sts128(SM_ACT + (2 + (lane >> 1)) * ROW_BYTES + (lane & 1) * 16, z);
            if (lane < 16) sts128(SM_ONES + lane * 16, make_uint4(lane < 8 ? 0x3f803f80u : 0u, 0, 0, 0));
            fence_async_smem();
            asm volatile("barrier.cluster.arrive.release.aligned;" ::: "memory");
            bar_arrive(6, 64);
            if (elect_one()) {
                mbar_expect(BAR(BAR_W2), 2304);
                while (clock32() - clk0 < W2DELAY) {}
                const char* base = reinterpret_cast<const char*>(w2) + ((cta & 15) * 8 * C + (cta >> 4) * 16) * 18;
#pragma unroll 1
                for (int i = 0; i < 8; i++) bulk_g2s(S0 + SM_BNC + 2304 + i * 288, base + i * (C * 18), 288, S0 + BAR(BAR_W2));
            }
            __syncwarp();
        }
        bar_sync(2, 128);

        float d[64];
#pragma unroll
        for (int i = 0; i < 64; i++) d[i] = 0.f;
#pragma unroll 1
        for (int conv = 0; conv < 2; conv++) {
            fence_acc(d);
            mma_stages<0>(d, conv, tid, gs);
            if (conv == 0) {
                asm volatile("wgmma.fence.sync.aligned;" ::: "memory");
                wgmma128<(SM_ONES >> 4) | (8u << 16), (SM_EMB >> 4), 0, 8>(d);
                asm volatile("wgmma.commit_group.sync.aligned;" ::: "memory");
            }
            asm volatile("wgmma.wait_group.sync.aligned 0;" ::: "memory");
            fence_acc(d);
            if (tid == 0) TL(10 + conv * 8);
            if (conv == 1) break;

            uint32_t hp[32];
#pragma unroll
            for (int g = 0; g < 4; g++) {
                float c[4] = {0.f, 0.f, 0.f, 0.f};
#pragma unroll
                for (int i = 0; i < 8; i++) hp[8 * g + i] = pack_bf(d[16 * g + 2 * i], d[16 * g + 2 * i + 1]);
#pragma unroll
                for (int i = 0; i < 4; i++) stat_mma(c, hp[8 * g + 2 * i], hp[8 * g + 2 * i + 1]);
                stat_store(c, SM_RED + (g * 4 + wq) * 48, lane);
            }
            bar_sync(2, 128);
            if (wq == 0) stat_publish(SM_RED, &gs->acc2[b * LS], lane, true);
            if (tid == 0) TL(11);
            const uint32_t hbase = SM_ACT + (lane >> 4) * CH_PITCH + (2 + wq * 16 + (lane & 15)) * 16;
#pragma unroll
            for (int kc = 0; kc < 8; kc++) stsm4(hbase + kc * 2 * CH_PITCH, hp[4 * kc], hp[4 * kc + 1], hp[4 * kc + 2], hp[4 * kc + 3]);
            __syncwarp();
            if (lane == 0) mbar_arrive(BAR(BAR_HW));
            if (lane < LAG) mbar_arrive(BAR(BAR_WEMPTY + (NSTAGE - LAG) % NS) + 8 * lane);
            if (has_outer) {
                uint4* outbox = gs->box + (cta + ((r & 1) ? 1 : -1)) * 1024 + tid;
#pragma unroll
                for (int kc = 0; kc < 8; kc++) outbox[kc * 128] = make_uint4(~hp[4 * kc], ~hp[4 * kc + 1], ~hp[4 * kc + 2], ~hp[4 * kc + 3]);
            }
            if (tid == 0) TL(12);
            const uint32_t xbase = SM_XOWN + ((lane >> 4) * 8 + (lane & 7)) * 128 + (((2 * wq + ((lane >> 3) & 1)) ^ (lane & 7)) << 4);
#pragma unroll
            for (int kc = 0; kc < 8; kc++) {
                uint32_t p[4];
                ldsm4t(p, xbase + kc * 2048);
#pragma unroll
                for (int i = 0; i < 4; i++) { d[8 * kc + 2 * i] = bf_lo(p[i]); d[8 * kc + 2 * i + 1] = bf_hi(p[i]); }
            }
            fence_async_smem();
            __syncwarp();
            if (lane == 0) mbar_arrive(BAR(BAR_XFREE));
        }
        {
            const uint32_t obase = slot_addr(0) + ((lane >> 4) * 8 + (lane & 7)) * OUT_PITCH + (wq * 16 + ((lane >> 3) & 1) * 8) * 2;
#pragma unroll
            for (int kc = 0; kc < 8; kc++) {
                stsm4t(obase + kc * 16 * OUT_PITCH, pack_bf(d[8 * kc + 0], d[8 * kc + 1]), pack_bf(d[8 * kc + 2], d[8 * kc + 3]),
                       pack_bf(d[8 * kc + 4], d[8 * kc + 5]), pack_bf(d[8 * kc + 6], d[8 * kc + 7]));
            }
            bar_sync(2, 128);
            const int oc0 = tid >> 3;
            __nv_bfloat16* dst = out + ((size_t)(b * C + oc0) * HW + r) * HW + seg * 8;
#pragma unroll
            for (int i = 0; i < 8; i++)
                *reinterpret_cast<uint4*>(dst + (size_t)i * 16 * HW * HW) = lds128(slot_addr(0) + (oc0 + 16 * i) * OUT_PITCH + seg * 16);
            if (tid == 0) { TL(20); TLG(21); }
        }
    } else if (warp < 6) {
        bar_sync(5, 96);
        if (warp == 5) {
            asm volatile("barrier.cluster.wait.acquire.aligned;" ::: "memory");
            const uint32_t peer = (r & 1) ^ 1;
            const uint32_t self0 = mapa(0, r & 1), peer0 = mapa(0, peer);
#pragma unroll 1
            for (int conv = 0; conv < 2; conv++) {
#pragma unroll 1
                for (int kc = 0; kc < 8; kc++) {
                    mbar_wait(BAR(BAR_FULL) + 8 * kc, conv);
                    if (elect_one())
                        asm volatile("cp.async.bulk.shared::cluster.shared::cta.mbarrier::complete_tx::bytes [%0], [%1], %2, [%3];"
                                     ::"r"(peer0 + SM_ACT + ROW_BYTES + kc * KC_BYTES), "r"(self0 + SM_ACT + kc * KC_BYTES), "r"(KC_BYTES),
                                       "r"(peer0 + BAR(BAR_FULL + 8) + 8 * kc) : "memory");
                }
                if (lane == 0) TL(86 + conv);
#pragma unroll 1
                for (int kc = 0; kc < 8; kc++) mbar_wait(BAR(BAR_FULL + 8) + 8 * kc, conv);
                if (lane == 0)
                    asm volatile("mbarrier.arrive.release.cluster.shared::cluster.b64 _, [%0];" ::"r"(peer0 + (conv ? BAR(BAR_ACK) : BAR(BAR_EMB))) : "memory");
            }
            mbar_wait(BAR(BAR_ACK), 0);
        } else {
            if (lane < 2) asm volatile("red.release.gpu.global.add.u32 [%0], 1;" ::"l"(&gs->wcnt[(NB + lane) * LS]) : "memory");
            if (lane == 0) TL(14);
            mbar_wait(BAR(BAR_STATS), 0);
            unsigned it = 0;
            while (ld_relaxed(&gs->wcnt[(2 * NB + b) * LS]) < (unsigned)NXTRA && ++it < SPIN_LIMIT) __nanosleep(100);
            fence_acquire();
            float ev[4] = {0.f, 0.f, 0.f, 0.f};
#pragma unroll
            for (int j = 0; j < NXTRA; j++) {
                const uint4 ef = ld_relaxed_v4(&gs->emb[(j * NB + b) * C + lane * 4]);
                ev[0] += __uint_as_float(ef.x); ev[1] += __uint_as_float(ef.y); ev[2] += __uint_as_float(ef.z); ev[3] += __uint_as_float(ef.w);
            }
#pragma unroll
            for (int i = 0; i < 4; i++) {
                const float hi = bf_lo(pack_bf(ev[i], 0.f));
                sts128(SM_EMB + (lane * 4 + i) * 16, make_uint4(pack_bf(hi, ev[i] - hi), 0, 0, 0));
            }
            fence_async_smem();
            __syncwarp();
            if (lane == 0) { mbar_arrive(BAR(BAR_EMB)); TL(19); }
        }
    } else if (warp == 6) {
        bar_sync(0, 96);
        const uint32_t ebytes = STAGE_BYTES + ((lane >> 3) == 1 ? KC_BYTES : 0);
        if (lane < NSTAGE) mbar_expect(BAR(BAR_FULL) + 8 * lane, ebytes);
        const int swap = (r & 1) ? 0 : 8 * STAGE_BYTES;
        unsigned it = 0;
        {
            int g = 0;
#pragma unroll 1
            while (g < NS) {
                unsigned ready = __ballot_sync(0xffffffffu, ld_relaxed(&gs->wcnt[b * LS + (lane & 7)]) >= 16u) >> g;
                if (++it > SPIN_LIMIT) ready = ~0u;
                if (!(ready & 1)) continue;
                fence_acquire();
                fence_async_global();
                if (lane == 0) TL(g ? 3 : 6);
#pragma unroll 1
                for (; (ready & 1) && g < NS; g++, ready >>= 1)
                    if (elect_one())
                        bulk_g2s(S0 + SM_W + g * STAGE_BYTES, gs->wt + g * STAGE_BYTES + (g >= 8 ? swap : 0), STAGE_BYTES, S0 + BAR(BAR_FULL) + 8 * g);
            }
        }
#pragma unroll 1
        for (int q = 3; q < 12; q++) {
            const int conv = q >= 6, qs = conv ? q - 6 : q, sl = q % 3;
            const unsigned char* wsrc = gs->wt + q * 4 * STAGE_BYTES + (qs < 2 ? 0 : (qs < 4 ? swap : -swap));
            const uint32_t par = (q / 3 - 1) & 1;
            if (q == 6) {
                it = 0;
                while (ld_relaxed(&gs->wcnt[(NB + b) * LS]) < (unsigned)NCTA && ++it < SPIN_LIMIT) {}
                fence_acquire();
                fence_async_global();
                if (lane == 0) { mbar_arrive(BAR(BAR_EMB)); TL(2); }
            }
#pragma unroll
            for (int i = 0; i < 4; i++) {
                mbar_wait(BAR(BAR_WEMPTY + i) + 32 * sl, par);
                if (i == 0 && (q == 6 || q == 9)) {
                    if ((lane >= NS) == (q == 9) && lane < NSTAGE) mbar_expect(BAR(BAR_FULL) + 8 * lane, ebytes);
                    __syncwarp();
                }
                if (elect_one())
                    bulk_g2s(S0 + SM_W + (sl * 4 + i) * STAGE_BYTES, wsrc + i * STAGE_BYTES, STAGE_BYTES, S0 + BAR(BAR_FULL + i) + 32 * qs);
            }
        }
    } else {
        const uint2 ga1 = __ldg(reinterpret_cast<const uint2*>(g1) + lane), bt1 = __ldg(reinterpret_cast<const uint2*>(be1) + lane);
        const uint2 ga2 = __ldg(reinterpret_cast<const uint2*>(g2) + lane), bt2 = __ldg(reinterpret_cast<const uint2*>(be2) + lane);
        if (lane < 8) sts128(SM_GST + lane * 16, make_uint4(0, 0, 0, 0));
        sts128f(SM_COEF + lane * 32, make_float4(0.5f * bf_lo(ga1.x), 0.5f * bf_hi(ga1.x), 0.5f * bf_lo(bt1.x), 0.5f * bf_hi(bt1.x)));
        sts128f(SM_COEF + lane * 32 + 16, make_float4(0.5f * bf_lo(ga1.y), 0.5f * bf_hi(ga1.y), 0.5f * bf_lo(bt1.y), 0.5f * bf_hi(bt1.y)));
        sts128f(SM_COEF + 1024 + lane * 32, make_float4(0.5f * bf_lo(ga2.x), 0.5f * bf_hi(ga2.x), 0.5f * bf_lo(bt2.x), 0.5f * bf_hi(bt2.x)));
        sts128f(SM_COEF + 1024 + lane * 32 + 16, make_float4(0.5f * bf_lo(ga2.y), 0.5f * bf_hi(ga2.y), 0.5f * bf_lo(bt2.y), 0.5f * bf_hi(bt2.y)));
        bar_arrive(4, 256 + 64 + 128);
        bar_sync(0, 96);
#pragma unroll 1
        for (int conv = 0; conv < 2; conv++) {
            if (conv == 1) mbar_wait(BAR(BAR_EMB), 0);
            const float* asrc = conv ? &gs->acc2[b * LS + (lane & 3) * 4] : &gs->acc1[b * 4 * LS + (lane & 3) * GS1];
            unsigned it = 0;
#pragma unroll 1
            while (true) {
                const uint4 f = ld_relaxed_v4(asrc);
                const bool ok = ((f.x == 0x42800000u) & (f.w == 0x42800000u)) || ++it > SPIN_LIMIT;
                const float inv_n = 1.0f / (32.0f * HW * HW);
                const float mean = __uint_as_float(f.y) * inv_n;
                const float rs = rsqrtf(fmaxf(fmaf(-mean, mean, __uint_as_float(f.z) * inv_n), 0.f) + 1e-5f);
                if (ok && lane < 4) sts128f(SM_GST + conv * 64 + lane * 16, make_float4(rs, mean * rs, 1.f, 0.f));
                if (__all_sync(0xffffffffu, ok)) break;
            }
            if (lane == 0) { mbar_arrive(BAR(BAR_STATS)); TL(7 + conv * 8); }
        }
        mbar_wait(BAR(BAR_XFREE), 0);
        if (has_outer && elect_one()) {
            mbar_expect(BAR(BAR_X + 4), 16384);
            bulk_g2s(S0 + SM_XOWN, gs->box + cta * 1024, 16384, S0 + BAR(BAR_X + 4));
        }
        if (r == 0) {
            if (lane < 16) gs->acc1[b * 4 * LS + (lane >> 2) * GS1 + (lane & 3)] = 0.f;
            if (lane < 24) gs->wcnt[((lane >> 3) * NB + b) * LS + (lane & 7)] = 0;
        }
    }
}

}

extern "C" void kernel_launch(void* const* d_in, const int* in_sizes, int n_in, void* d_out, int out_size) {
    (void)in_sizes; (void)n_in; (void)out_size;
    typedef CUresult (*EncodeFn)(CUtensorMap*, CUtensorMapDataType, cuuint32_t, void*, const cuuint64_t*, const cuuint64_t*,
                                 const cuuint32_t*, const cuuint32_t*, CUtensorMapInterleave, CUtensorMapSwizzle,
                                 CUtensorMapL2promotion, CUtensorMapFloatOOBfill);
    static Scratch* gs = nullptr;
    static EncodeFn encode = nullptr;
    if (!gs) {
        cudaFuncSetAttribute(resblock_kernel, cudaFuncAttributeMaxDynamicSharedMemorySize, SM_TOTAL);
        cudaGetSymbolAddress((void**)&gs, g_scratch);
        cudaDriverEntryPointQueryResult qr;
        cudaGetDriverEntryPoint("cuTensorMapEncodeTiled", (void**)&encode, cudaEnableDefault, &qr);
    }
    CUtensorMap xmap;
    const cuuint64_t dims[3] = {HW, HW, NB * C}, strides[2] = {HW * 2, HW * HW * 2};
    const cuuint32_t box[3] = {HW, 1, 32}, es[3] = {1, 1, 1};
    encode(&xmap, CU_TENSOR_MAP_DATA_TYPE_BFLOAT16, 3, d_in[0], dims, strides, box, es, CU_TENSOR_MAP_INTERLEAVE_NONE,
           CU_TENSOR_MAP_SWIZZLE_128B, CU_TENSOR_MAP_L2_PROMOTION_NONE, CU_TENSOR_MAP_FLOAT_OOB_FILL_NONE);
    resblock_kernel<<<NCTA + NXTRA, NTHREADS, SM_TOTAL>>>(
        (const __nv_bfloat16*)d_in[4], (const __nv_bfloat16*)d_in[1],
        (const __nv_bfloat16*)d_in[2], (const __nv_bfloat16*)d_in[3], (const __nv_bfloat16*)d_in[5],
        (const __nv_bfloat16*)d_in[6], (const __nv_bfloat16*)d_in[7], (const __nv_bfloat16*)d_in[8],
        (__nv_bfloat16*)d_out, gs, xmap);
}
```

```cpp
#include <cuda_runtime.h>
#include <cuda.h>
#include <cuda_bf16.h>
#include <stdint.h>

namespace {

constexpr int C = 128, HW = 64, NB = 2, E = 768;
constexpr int NCTA = NB * HW;
constexpr int NXTRA = 4;
constexpr int NTHREADS = 16 * 32;
constexpr int CH_PITCH = 66 * 16;
constexpr int ROW_BYTES = 16 * CH_PITCH;
constexpr int STEP_BYTES = 4096;
constexpr int STAGE_BYTES = 3 * STEP_BYTES;
constexpr int NSTAGE = 24;
constexpr int KC_BYTES = 2 * CH_PITCH;
constexpr int NS = 12;
constexpr int LAG = 1;
#define XDELAY 600
#define HDELAY 600
#define SEQ 0
#define MMA0_WAIT mbar_try
#define PDELAY 60
#define RB 1
#define XSTAG2 200
#define XSTAG 800
#define HSEND 0
#define W2DELAY 2000

constexpr uint32_t SMEM_BASE = 0x400;
constexpr uint32_t SM_XOWN = SMEM_BASE;
constexpr uint32_t SM_ACT = SM_XOWN + 16384 + 512;
constexpr uint32_t SM_XOUT = SM_ACT + 2 * ROW_BYTES + 512;
static_assert(SM_XOUT % 1024 == 0, "swizzle atom alignment");
constexpr uint32_t SM_W = SM_ACT + 3 * ROW_BYTES + 128;
__host__ __device__ constexpr uint32_t slot_addr(int slot) { return SM_W + slot * STAGE_BYTES; }
constexpr uint32_t SM_COEF = SM_W + NS * STAGE_BYTES;
constexpr uint32_t SM_GST = SM_COEF + 2048;
constexpr uint32_t SM_EMB = SM_GST + 128;
constexpr uint32_t SM_ONES = SM_EMB + 2048;
constexpr uint32_t SM_RED = SM_ONES + 256;
constexpr uint32_t SM_BNC = SM_RED + 1280;
constexpr uint32_t SM_BAR = SM_BNC + 2 * 2304;
constexpr int BAR_FULL = 0, BAR_WEMPTY = NSTAGE, BAR_HW = BAR_WEMPTY + NS, BAR_XFREE = BAR_HW + 1, BAR_STATS = BAR_XFREE + 1,
              BAR_EMB = BAR_STATS + 1, BAR_ACK = BAR_EMB + 1, BAR_W2 = BAR_ACK + 1, BAR_X = BAR_W2 + 1  , NBAR = BAR_X + 5;
constexpr int SM_TOTAL = SM_BAR + NBAR * 8 - SMEM_BASE;
static_assert(SM_TOTAL <= 232448, "smem");
static_assert(NBAR <= 96, "barrier init");
constexpr int OUT_PITCH = 144;
__host__ __device__ constexpr uint32_t BAR(int i) { return SM_BAR + 8 * i; }
__host__ __device__ constexpr int ky_of(int kyo) { return kyo == 0 ? 1 : (kyo == 1 ? 0 : 2); }

constexpr unsigned SPIN_LIMIT = 1u << 16;

#define LS 1056
#define GS1 4
#define PD 0
struct Scratch {
    float acc1[NB * 4 * LS];
    float acc2[NB * LS];
    unsigned wcnt[3 * NB * LS];
    float emb[NXTRA * NB * C];
    unsigned char wt[2 * NSTAGE * STAGE_BYTES];
    uint4 box[NCTA * 1024];
};
__device__ __align__(1024) Scratch g_scratch;
#define TL(i) do {} while (0)
#define TLG(i) do {} while (0)

__device__ __forceinline__ unsigned clock32() { unsigned c; asm volatile("mov.u32 %0, %%clock;" : "=r"(c)); return c; }
__device__ __forceinline__ uint32_t mapa(uint32_t a, uint32_t rank) {
    uint32_t d;
    asm("mapa.shared::cluster.u32 %0, %1, %2;" : "=r"(d) : "r"(a), "r"(rank));
    return d;
}
#define S0 mapa(0, blockIdx.x & 1)
__device__ __forceinline__ void mbar_init(uint32_t bar, int cnt) {
    asm volatile("mbarrier.init.shared::cta.b64 [%0], %1;" ::"r"(bar + S0), "r"(cnt) : "memory");
}
__device__ __forceinline__ void mbar_arrive(uint32_t bar) {
    asm volatile("mbarrier.arrive.shared::cta.b64 _, [%0];" ::"r"(bar + S0) : "memory");
}
__device__ __forceinline__ void mbar_expect(uint32_t bar, uint32_t bytes) {
    asm volatile("mbarrier.arrive.expect_tx.shared::cta.b64 _, [%0], %1;" ::"r"(bar + S0), "r"(bytes) : "memory");
}
__device__ __forceinline__ bool mbar_try(uint32_t bar, uint32_t par) {
    uint32_t ok;
    asm volatile("{\n.reg .pred p;\nmbarrier.try_wait.parity.shared::cta.b64 p, [%1], %2;\nselp.u32 %0, 1, 0, p;\n}"
                 : "=r"(ok) : "r"(bar + S0), "r"(par) : "memory");
    return ok;
}
__device__ __forceinline__ bool mbar_test(uint32_t bar, uint32_t par) {
    uint32_t ok;
    asm volatile("{\n.reg .pred p;\nmbarrier.test_wait.parity.shared::cta.b64 p, [%1], %2;\nselp.u32 %0, 1, 0, p;\n}"
                 : "=r"(ok) : "r"(bar + S0), "r"(par) : "memory");
    return ok;
}
__device__ __forceinline__ void mbar_wait(uint32_t bar, uint32_t par) {
    unsigned it = 0;
#pragma unroll 1
    while (!mbar_try(bar, par) && ++it < SPIN_LIMIT) {}
}
__device__ __forceinline__ bool elect_one() {
    uint32_t p;
    asm volatile("{\n.reg .pred p;\nelect.sync _|p, 0xffffffff;\nselp.u32 %0, 1, 0, p;\n}" : "=r"(p));
    return p;
}
__device__ __forceinline__ void fence_async_smem() { asm volatile("fence.proxy.async.shared::cta;" ::: "memory"); }
__device__ __forceinline__ void fence_async_global() { asm volatile("fence.proxy.async.global;" ::: "memory"); }
__device__ __forceinline__ void fence_acquire() { asm volatile("fence.acquire.gpu;" ::: "memory"); }
__device__ __forceinline__ void bar_sync(int id, int n) { asm volatile("bar.sync %0, %1;" ::"r"(id), "r"(n) : "memory"); }
__device__ __forceinline__ void bar_arrive(int id, int n) { asm volatile("bar.arrive %0, %1;" ::"r"(id), "r"(n) : "memory"); }
__device__ __forceinline__ void bulk_g2s(uint32_t dst, const void* src, uint32_t bytes, uint32_t bar) {
    asm volatile("cp.async.bulk.shared::cluster.global.mbarrier::complete_tx::bytes [%0], [%1], %2, [%3];"
                 ::"r"(dst), "l"(src), "r"(bytes), "r"(bar) : "memory");
}
__device__ __forceinline__ void tma_x(uint32_t dst, const CUtensorMap* tm, int row, int ch, uint32_t bar) {
    asm volatile("cp.async.bulk.tensor.3d.shared::cluster.global.mbarrier::complete_tx::bytes [%0], [%1, {%2, %3, %4}], [%5];"
                 ::"r"(dst + S0), "l"(tm), "r"(0), "r"(row), "r"(ch), "r"(bar + S0) : "memory");
}
__device__ __forceinline__ uint4 ld_relaxed_v4(const void* p) {
    uint4 v;
    asm volatile("ld.relaxed.gpu.global.v4.u32 {%0,%1,%2,%3}, [%4];" : "=r"(v.x), "=r"(v.y), "=r"(v.z), "=r"(v.w) : "l"(p) : "memory");
    return v;
}
__device__ __forceinline__ unsigned ld_relaxed(const void* p) {
    unsigned v;
    asm volatile("ld.relaxed.gpu.global.u32 %0, [%1];" : "=r"(v) : "l"(p) : "memory");
    return v;
}
__device__ __forceinline__ void red_add4(float* p, float a, float b, float c, float d) {
    asm volatile("red.relaxed.gpu.global.add.v4.f32 [%0], {%1,%2,%3,%4};" ::"l"(p), "f"(a), "f"(b), "f"(c), "f"(d) : "memory");
}
__device__ __forceinline__ void sts128(uint32_t a, uint4 v) {
    asm volatile("st.shared.v4.u32 [%0], {%1,%2,%3,%4};" ::"r"(a + S0), "r"(v.x), "r"(v.y), "r"(v.z), "r"(v.w) : "memory");
}
__device__ __forceinline__ void sts128f(uint32_t a, float4 v) {
    asm volatile("st.shared.v4.f32 [%0], {%1,%2,%3,%4};" ::"r"(a + S0), "f"(v.x), "f"(v.y), "f"(v.z), "f"(v.w) : "memory");
}
__device__ __forceinline__ void sts32f(uint32_t a, float v) { asm volatile("st.shared.f32 [%0], %1;" ::"r"(a + S0), "f"(v) : "memory"); }
__device__ __forceinline__ uint4 lds128(uint32_t a) {
    uint4 v;
    asm volatile("ld.shared.v4.u32 {%0,%1,%2,%3}, [%4];" : "=r"(v.x), "=r"(v.y), "=r"(v.z), "=r"(v.w) : "r"(a + S0) : "memory");
    return v;
}
__device__ __forceinline__ float4 lds128f(uint32_t a) {
    float4 v;
    asm volatile("ld.shared.v4.f32 {%0,%1,%2,%3}, [%4];" : "=f"(v.x), "=f"(v.y), "=f"(v.z), "=f"(v.w) : "r"(a + S0) : "memory");
    return v;
}
__device__ __forceinline__ float2 lds64f(uint32_t a) {
    float2 v;
    asm volatile("ld.shared.v2.f32 {%0,%1}, [%2];" : "=f"(v.x), "=f"(v.y) : "r"(a + S0) : "memory");
    return v;
}
__device__ __forceinline__ float bf_lo(uint32_t u) { return __uint_as_float(u << 16); }
__device__ __forceinline__ float bf_hi(uint32_t u) { return __uint_as_float(u & 0xffff0000u); }
__device__ __forceinline__ uint32_t pack_bf(float lo, float hi) {
    uint32_t r;
    asm("cvt.rn.bf16x2.f32 %0, %1, %2;" : "=r"(r) : "f"(hi), "f"(lo));
    return r;
}
__device__ __forceinline__ float tanh_fast(float x) {
    float r;
    asm("tanh.approx.f32 %0, %1;" : "=f"(r) : "f"(x));
    return r;
}
__device__ __forceinline__ float silu_half(float h) { return fmaf(h, tanh_fast(h), h); }
__device__ __forceinline__ void ldsm4(uint32_t (&u)[4], uint32_t a) {
    asm volatile("ldmatrix.sync.aligned.m8n8.x4.shared.b16 {%0,%1,%2,%3}, [%4];"
                 : "=r"(u[0]), "=r"(u[1]), "=r"(u[2]), "=r"(u[3]) : "r"(a + S0) : "memory");
}
__device__ __forceinline__ void ldsm4t(uint32_t (&u)[4], uint32_t a) {
    asm volatile("ldmatrix.sync.aligned.m8n8.x4.trans.shared.b16 {%0,%1,%2,%3}, [%4];"
                 : "=r"(u[0]), "=r"(u[1]), "=r"(u[2]), "=r"(u[3]) : "r"(a + S0) : "memory");
}
__device__ __forceinline__ void stsm4(uint32_t a, uint32_t p0, uint32_t p1, uint32_t p2, uint32_t p3) {
    asm volatile("stmatrix.sync.aligned.m8n8.x4.shared.b16 [%0], {%1,%2,%3,%4};" ::"r"(a + S0), "r"(p0), "r"(p1), "r"(p2), "r"(p3) : "memory");
}
__device__ __forceinline__ void stsm4t(uint32_t a, uint32_t p0, uint32_t p1, uint32_t p2, uint32_t p3) {
    asm volatile("stmatrix.sync.aligned.m8n8.x4.trans.shared.b16 [%0], {%1,%2,%3,%4};" ::"r"(a + S0), "r"(p0), "r"(p1), "r"(p2), "r"(p3) : "memory");
}

#define R8(o) "+f"(d[o]), "+f"(d[o + 1]), "+f"(d[o + 2]), "+f"(d[o + 3]), "+f"(d[o + 4]), "+f"(d[o + 5]), "+f"(d[o + 6]), "+f"(d[o + 7])
template <uint32_t ALO, uint32_t BLO, uint64_t AHI = 8, uint64_t BHI = 48>
__device__ __forceinline__ void wgmma128(float (&d)[64]) {
    asm volatile(
        "wgmma.mma_async.sync.aligned.m64n128k16.f32.bf16.bf16 "
        "{%0,%1,%2,%3,%4,%5,%6,%7,%8,%9,%10,%11,%12,%13,%14,%15,%16,%17,%18,%19,%20,%21,%22,%23,%24,%25,%26,%27,%28,%29,%30,%31,"
        "%32,%33,%34,%35,%36,%37,%38,%39,%40,%41,%42,%43,%44,%45,%46,%47,%48,%49,%50,%51,%52,%53,%54,%55,%56,%57,%58,%59,%60,%61,%62,%63},"
        " %64, %65, 1, 1, 1, 0, 0;"
        : R8(0), R8(8), R8(16), R8(24), R8(32), R8(40), R8(48), R8(56)
        : "l"((AHI << 32) | ALO), "l"((BHI << 32) | BLO));
}
template <int S>
__device__ __forceinline__ void mma_stages(float (&d)[64], int conv, int tid, Scratch* gs) {
    constexpr uint32_t A = ((SM_ACT + S * 2 * CH_PITCH + 16) >> 4) | ((CH_PITCH >> 4) << 16);
    constexpr uint32_t B = (slot_addr(S % NS) >> 4) | (8u << 16);
    if (S == 0) {
        unsigned it = 0;
#pragma unroll 1
        while (!MMA0_WAIT(BAR(BAR_FULL), conv) && ++it < SPIN_LIMIT) {}
    }
    bool next_ok = true;
    constexpr uint32_t NEXT = S + 1 < NSTAGE ? BAR(BAR_FULL + S + 1) : BAR(BAR_EMB);
    const int npar = S + 1 < NSTAGE ? conv : 0;
    next_ok = mbar_test(NEXT, npar);
    if (S == 0 && tid == 0) TL(32 + conv * 24);
    asm volatile("wgmma.fence.sync.aligned;" ::: "memory");
    wgmma128<A, B>(d);
    wgmma128<A + 1, B + 16>(d);
    wgmma128<A + 2, B + 32>(d);
    asm volatile("wgmma.commit_group.sync.aligned;" ::: "memory");
    if (S >= LAG) {
        asm volatile("wgmma.wait_group.sync.aligned %0;" ::"n"(LAG) : "memory");
        if ((tid & 31) == 0) mbar_arrive(BAR(BAR_WEMPTY + (S + NS - LAG) % NS));
    }
    if (!next_ok) mbar_wait(NEXT, npar);
    if constexpr (S + 1 < NSTAGE) mma_stages<S + 1>(d, conv, tid, gs);
}

__device__ __forceinline__ void weight_load(uint4 (&t)[5], const __nv_bfloat16* w, int cta, int lane) {
    const char* base = reinterpret_cast<const char*>(w) + ((cta & 15) * 8 * C + (cta >> 4) * 16) * 18;
#pragma unroll
    for (int k = 0; k < 5; k++) {
        const int i = lane + 32 * k, row = (i * 57) >> 10;
        if (k < 4 || lane < 16) t[k] = __ldg(reinterpret_cast<const uint4*>(base + row * (C * 18 - 288) + i * 16));
    }
}
__device__ __forceinline__ void weight_block(uint32_t bounce, unsigned char* wt, int cta, int lane, bool readback) {
    unsigned char* dst = wt + (cta >> 4) * STAGE_BYTES + (cta & 15) * 768;
    if (lane < 16) {
        uint32_t v[36];
#pragma unroll
        for (int i = 0; i < 9; i++) {
            const uint4 q = lds128(bounce + (lane & 7) * 288 + (lane >> 3) * 144 + i * 16);
            v[4 * i] = q.x; v[4 * i + 1] = q.y; v[4 * i + 2] = q.z; v[4 * i + 3] = q.w;
        }
#pragma unroll
        for (int kyo = 0; kyo < 3; kyo++) {
#pragma unroll
            for (int kx = 0; kx < 3; kx++) {
                const int tap = ky_of(kyo) * 3 + kx;
                uint32_t o[4];
#pragma unroll
                for (int m = 0; m < 4; m++) {
                    const int i0 = 18 * m + tap, i1 = i0 + 9;
                    const uint32_t sel = ((i0 & 1) ? 0x32u : 0x10u) | ((i1 & 1) ? 0x7600u : 0x5400u);
                    o[m] = __byte_perm(v[i0 >> 1], v[i1 >> 1], sel);
                }
                *reinterpret_cast<uint4*>(dst + kyo * 8 * STAGE_BYTES + kx * 256 + lane * 16) = make_uint4(o[0], o[1], o[2], o[3]);
            }
        }
    }
    if (readback) {
        __syncwarp();
        unsigned acc = 0;
        if (lane < 24) {
#pragma unroll
            for (int i = 0; i < 3; i++) acc |= ld_relaxed(dst + i * 8 * STAGE_BYTES + lane * 32);
        }
        asm volatile("{\n.reg .pred p;\nsetp.eq.u32 p, %0, 0x9e3779b9;\n@p st.shared.u32 [%1], %0;\n}" ::"r"(acc), "r"(bounce + S0) : "memory");
    }
}
__device__ __forceinline__ uint32_t act2(uint32_t u, const float4& cf) {
    return pack_bf(silu_half(fmaf(bf_lo(u), cf.x, cf.z)), silu_half(fmaf(bf_hi(u), cf.y, cf.w)));
}
__device__ __forceinline__ void norm_unit(uint32_t (&u)[4], const float4& ca, const float4& cb) {
    u[0] = act2(u[0], ca); u[1] = act2(u[1], ca); u[2] = act2(u[2], cb); u[3] = act2(u[3], cb);
}
__device__ __forceinline__ void read_stats(uint32_t gst, float (&g)[8]) {
    asm volatile("ld.volatile.shared.v4.f32 {%0,%1,%2,%3}, [%4];" : "=f"(g[0]), "=f"(g[1]), "=f"(g[2]), "=f"(g[3]) : "r"(gst + S0) : "memory");
    asm volatile("ld.volatile.shared.v4.f32 {%0,%1,%2,%3}, [%4];" : "=f"(g[4]), "=f"(g[5]), "=f"(g[6]), "=f"(g[7]) : "r"(gst + 16 + S0) : "memory");
}
template <int T>
__device__ __forceinline__ void group_coefs(uint32_t gst, float (&g)[8], float4 (&cf)[8]) {
    unsigned it = 0;
#pragma unroll 1
    while (!__all_sync(0xffffffffu, g[2 * T] != 0.f) && ++it < 8 * SPIN_LIMIT) read_stats(gst, g);
    float4 &ca = cf[2 * T], &cb = cf[2 * T + 1];
    const float rs = g[2 * T], mr = g[2 * T + 1];
    ca.z = fmaf(-mr, ca.x, ca.z); ca.w = fmaf(-mr, ca.y, ca.w); ca.x *= rs; ca.y *= rs;
    cb.z = fmaf(-mr, cb.x, cb.z); cb.w = fmaf(-mr, cb.y, cb.w); cb.x *= rs; cb.y *= rs;
}
template <int FIRST, int N>
__device__ __forceinline__ void norm_block(uint32_t (&u)[4][4], float4 (&cf)[8], uint32_t act, uint32_t mask, uint32_t fbar, int lane) {
#pragma unroll
    for (int t = FIRST; t < FIRST + N; t++) {
        norm_unit(u[t], cf[2 * t], cf[2 * t + 1]);
        stsm4(act + t * 2 * KC_BYTES, u[t][0] & mask, u[t][1] & mask, u[t][2] & mask, u[t][3] & mask);
    }
    fence_async_smem();
    __syncwarp();
    if (lane < N) mbar_arrive(fbar + 16 * (FIRST + lane));
}
__device__ __forceinline__ void stat_mma(float (&c)[4], uint32_t p, uint32_t q) {
    asm("mma.sync.aligned.m16n8k16.row.col.f32.bf16.bf16.f32 {%0,%1,%2,%3}, {%4,%5,%6,%5}, {%4,%6}, {%0,%1,%2,%3};"
        : "+f"(c[0]), "+f"(c[1]), "+f"(c[2]), "+f"(c[3]) : "r"(p), "r"(0x3f803f80u), "r"(q));
}
__device__ __forceinline__ void stat_store(const float (&c)[4], uint32_t dst, int lane) {
    const int g = lane >> 2, t = lane & 3;
    if (t == (g >> 1)) sts32f(dst + g * 4, (g & 1) ? c[1] : c[0]);
    if (g == 7) sts32f(dst + 32 + t * 4, c[2] + c[3]);
}
__device__ __forceinline__ float sum4(float4 v) { return (v.x + v.y) + (v.z + v.w); }
__device__ __forceinline__ void stat_publish(uint32_t src, float* acc, int lane, bool real) {
    const uint32_t a = src + (lane & 15) * 48;
    float q = sum4(lds128f(a)) + sum4(lds128f(a + 16)), sm = sum4(lds128f(a + 32));
    q += __shfl_xor_sync(0xffffffffu, q, 1); sm += __shfl_xor_sync(0xffffffffu, sm, 1);
    q += __shfl_xor_sync(0xffffffffu, q, 2); sm += __shfl_xor_sync(0xffffffffu, sm, 2);
    if (real && (lane & 19) == 0) red_add4(acc + lane, 1.f, sm, q, 1.f);
}
__device__ __forceinline__ void fence_acc(float (&d)[64]) {
#pragma unroll
    for (int i = 0; i < 64; i++) asm volatile("" : "+f"(d[i])::"memory");
}
__device__ __forceinline__ void ld_unit(uint32_t (&u)[4], const uint4* p) {
    asm volatile("ld.relaxed.gpu.global.v4.u32 {%0,%1,%2,%3}, [%4];" : "=r"(u[0]), "=r"(u[1]), "=r"(u[2]), "=r"(u[3]) : "l"(p) : "memory");
}

__device__ __noinline__ void side_jobs(const __nv_bfloat16* __restrict__ t_emb, const __nv_bfloat16* __restrict__ w_emb,
                                       const __nv_bfloat16* __restrict__ w2, Scratch* __restrict__ gs, unsigned clk0) {
    const int tid = threadIdx.x, warp = tid >> 5, lane = tid & 31, j = blockIdx.x;
    float tv = 0.f;
    if (lane < 24) tv = __bfloat162float(t_emb[(lane / 12) * E + j * 192 + warp * 12 + lane % 12]);
    if (tid == 0) {
        mbar_init(BAR(0), 1);
        mbar_expect(BAR(0), 192 * C * 2);
        fence_async_smem();
        while (clock32() - clk0 < W2DELAY) {}
#pragma unroll
        for (int i = 0; i < 4; i++) bulk_g2s(S0 + SM_W + i * 12288, w_emb + (j * 192 + i * 48) * C, 12288, S0 + BAR(0));
    }
    if (j == 0 && tid < 32) gs->acc2[(tid >> 4) * LS + (tid & 15)] = 0.f;
    const float sv = silu_half(0.5f * tv);
    __syncthreads();
    mbar_wait(BAR(0), 0);
    float acc[8] = {0.f, 0.f, 0.f, 0.f, 0.f, 0.f, 0.f, 0.f};
#pragma unroll
    for (int i = 0; i < 12; i++) {
        const float2 wq = lds64f(SM_W + (warp * 12 + i) * 256 + lane * 8);
        const uint32_t wx = __float_as_uint(wq.x), wy = __float_as_uint(wq.y);
#pragma unroll
        for (int bb = 0; bb < 2; bb++) {
            const float sx = __shfl_sync(0xffffffffu, sv, bb * 12 + i);
            acc[4 * bb + 0] = fmaf(sx, bf_lo(wx), acc[4 * bb + 0]); acc[4 * bb + 1] = fmaf(sx, bf_hi(wx), acc[4 * bb + 1]);
            acc[4 * bb + 2] = fmaf(sx, bf_lo(wy), acc[4 * bb + 2]); acc[4 * bb + 3] = fmaf(sx, bf_hi(wy), acc[4 * bb + 3]);
        }
    }
    sts128f(SM_ACT + warp * 1024 + lane * 16, make_float4(acc[0], acc[1], acc[2], acc[3]));
    sts128f(SM_ACT + warp * 1024 + 512 + lane * 16, make_float4(acc[4], acc[5], acc[6], acc[7]));
    __syncthreads();
    if (tid < 128) {
        float2 sum = make_float2(0.f, 0.f);
#pragma unroll
        for (int w = 0; w < 16; w++) { const float2 p = lds64f(SM_ACT + w * 1024 + tid * 8); sum.x += p.x; sum.y += p.y; }
        *reinterpret_cast<float2*>(&gs->emb[j * NB * C + tid * 2]) = sum;
        bar_sync(1, 128);
        if (tid < 2) asm volatile("red.release.gpu.global.add.u32 [%0], 1;" ::"l"(&gs->wcnt[(2 * NB + tid) * LS]) : "memory");
    }
}

__global__ void __cluster_dims__(2, 1, 1) __launch_bounds__(NTHREADS, 1)
resblock_kernel(const __nv_bfloat16* __restrict__ w1,
                const __nv_bfloat16* __restrict__ t_emb, const __nv_bfloat16* __restrict__ g1,
                const __nv_bfloat16* __restrict__ be1, const __nv_bfloat16* __restrict__ w_emb,
                const __nv_bfloat16* __restrict__ g2, const __nv_bfloat16* __restrict__ be2,
                const __nv_bfloat16* __restrict__ w2, __nv_bfloat16* __restrict__ out, Scratch* __restrict__ gs,
                const __grid_constant__ CUtensorMap xmap) {
    const unsigned clk0 = clock32();
    if (threadIdx.x == 480 && blockIdx.x >= NXTRA) TLG(1);
    const int tid = threadIdx.x, lane = tid & 31;
    const int cta = blockIdx.x - NXTRA, b = cta >> 6, r = cta & 63;
    uint4 v[5];
    if (tid < 32) weight_load(v, w1, cta & (NCTA - 1), lane);
    const int warp = __shfl_sync(0xffffffffu, tid >> 5, 0);
    if (cta < 0) { side_jobs(t_emb, w_emb, w2, gs, clk0); return; }

    const int seg = lane & 7;
    if (warp != 3) asm volatile("barrier.cluster.arrive.relaxed.aligned;" ::: "memory");
    const bool has_outer = (r != 0) && (r != HW - 1);
    if (warp == 1 || warp == 2 || warp == 4 || warp == 5) {
        const int g = warp < 3 ? warp - 1 : 7 - warp;
        if (elect_one()) {
            asm volatile("prefetch.tensormap [%0];" ::"l"(&xmap) : "memory");
            mbar_init(BAR(BAR_X) + 8 * g, 1);
            if (g == 3) mbar_init(BAR(BAR_X + 4), 1);
            mbar_expect(BAR(BAR_X) + 8 * g, 4096);
            fence_async_smem();
            while (clock32() - clk0 < XDELAY + (g >> 1) * XSTAG + (g & 1) * XSTAG2) {}
            tma_x(SM_XOWN + g * 4096, &xmap, r, b * C + g * 32, BAR(BAR_X) + 8 * g);
            if (g == 3 && has_outer) {
                mbar_expect(BAR(BAR_X + 4), 16384);
#pragma unroll
                for (int i = 0; i < 4; i++) tma_x(SM_XOUT + i * 4096, &xmap, r + ((r & 1) ? 1 : -1), b * C + i * 32, BAR(BAR_X + 4));
            }
        }
        __syncwarp();
        bar_arrive(4, 256 + 64 + 128);
        mbar_wait(BAR(BAR_X) + 8 * g, 0);
        if (lane == 0) TL(70 + g);
        float c[8][4];
#pragma unroll
        for (int k = 0; k < 8; k++) {
            const uint4 q = lds128(SM_XOWN + g * 4096 + k * 512 + lane * 16);
            c[k][0] = c[k][1] = c[k][2] = c[k][3] = 0.f;
            stat_mma(c[k], q.x, q.y); stat_mma(c[k], q.z, q.w);
        }
#pragma unroll
        for (int i = 0; i < 4; i++) c[0][i] = ((c[0][i] + c[1][i]) + (c[2][i] + c[3][i])) + ((c[4][i] + c[5][i]) + (c[6][i] + c[7][i]));
        stat_store(c[0], SM_RED + g * 48, lane);
        __syncwarp();
        if (lane == 0) {
            const uint32_t a = SM_RED + g * 48;
            red_add4(&gs->acc1[b * 4 * LS + g * GS1], 1.f, sum4(lds128f(a + 32)), sum4(lds128f(a)) + sum4(lds128f(a + 16)), 1.f);
            TL(74 + g);
        }
    }
    if (warp == 0 || warp == 4) {
        const int k = warp >> 2;
        if (k == 0) {
#pragma unroll
            for (int i = 0; i < 5; i++)
                if (i < 4 || lane < 16) sts128(SM_BNC + (lane + 32 * i) * 16, v[i]);
            if (lane == 0) TL(81);
            __syncwarp();
        } else {
            bar_sync(6, 64);
            mbar_wait(BAR(BAR_W2), 0);
        }
        weight_block(SM_BNC + k * 2304, gs->wt + k * NSTAGE * STAGE_BYTES, cta, lane, k == 0);
        __syncwarp();
        if (lane == 0) TL(k ? 13 : 4);
        if (k == 0 && lane < 2) asm volatile("red.relaxed.gpu.global.add.u32 [%0], 1;" ::"l"(&gs->wcnt[lane * LS + (cta >> 4)]) : "memory");
    }

    if (warp >= 8) {
        const int nw = warp - 8;
        bar_sync(4, 256 + 64 + 128);
        const int par = nw >> 2, wq = nw & 3;
        const uint32_t act_off = SM_ACT + (par * 2 + (lane >> 4)) * CH_PITCH + (2 + wq * 16 + (lane & 15)) * 16;
        const uint32_t stg_off = (par * 16 + (lane >> 4) * 8 + (lane & 7)) * 128 + (((2 * wq + ((lane >> 3) & 1)) ^ (lane & 7)) << 4);
        const uint32_t cfa = SM_COEF + par * 128 + (lane & 3) * 16;
        const uint32_t fbar = BAR(BAR_FULL) + 8 * par;
        uint4* inbox = gs->box + cta * 1024 + nw * 32 + lane;
#pragma unroll 1
        for (int conv = 0; conv < 2; conv++) {
            uint32_t u[4][4], w[4][4];
            float4 cf[8];
            if (conv == 0) {
#pragma unroll
                for (int i = 0; i < 4; i++) { mbar_wait(BAR(BAR_X + i), 0); ldsm4t(u[i], SM_XOWN + stg_off + i * 4096); }
            } else {
                mbar_wait(BAR(BAR_HW), 0);
#pragma unroll
                for (int i = 0; i < 4; i++) ldsm4(u[i], act_off + i * 2 * KC_BYTES);
            }
#pragma unroll
            for (int i = 0; i < 8; i++) cf[i] = lds128f(cfa + conv * 1024 + (i >> 1) * 256 + (i & 1) * 64);
            const uint32_t gst = SM_GST + conv * 32;
            float gv[8];
            read_stats(gst, gv);
            group_coefs<0>(gst, gv, cf);
            if (tid == 256) TL(22 + conv * 4);
            if (par) { const unsigned c1 = clock32(); while (clock32() - c1 < PDELAY) {} }
            norm_block<0, 1>(u, cf, act_off, ~0u, fbar, lane);
            if (tid == 256) TL(8 + conv * 8);
            group_coefs<1>(gst, gv, cf);
            norm_block<1, 1>(u, cf, act_off, ~0u, fbar, lane);
            group_coefs<2>(gst, gv, cf);
            norm_block<2, 1>(u, cf, act_off, ~0u, fbar, lane);
            group_coefs<3>(gst, gv, cf);
            norm_block<3, 1>(u, cf, act_off, ~0u, fbar, lane);
            if (tid == 256) TL(84 + conv);
            if (has_outer) {
                mbar_wait(BAR(BAR_X + 4), conv);
                if (conv == 0) {
#pragma unroll
                    for (int i = 0; i < 4; i++) ldsm4t(w[i], SM_XOUT + stg_off + i * 4096);
                } else {
#pragma unroll
                    for (int i = 0; i < 4; i++) {
                        const uint4 q = lds128(SM_XOWN + (tid - 256) * 16 + i * 4096);
                        w[i][0] = q.x; w[i][1] = q.y; w[i][2] = q.z; w[i][3] = q.w;
                    }
                    unsigned it = 0;
                    while (true) {
                        bool ok = true;
#pragma unroll
                        for (int i = 0; i < 16; i++) ok = ok && w[i >> 2][i & 3] != 0;
                        if (__all_sync(0xffffffffu, ok) || ++it > SPIN_LIMIT) break;
#pragma unroll
                        for (int i = 0; i < 4; i++) ld_unit(w[i], inbox + i * 256);
                    }
#pragma unroll
                    for (int i = 0; i < 16; i++) w[i >> 2][i & 3] = ~w[i >> 2][i & 3];
                }
            }
            if (conv == 0) {
                bar_sync(3, 256);
                if (nw == 0) sts128(SM_ACT + 2 * ROW_BYTES + (lane >> 1) * CH_PITCH + (lane & 1) * 16, make_uint4(0, 0, 0, 0));
            }
            if (tid == 256) TL(24 + conv * 4);
            norm_block<0, 2>(w, cf, act_off + 2 * ROW_BYTES, has_outer ? ~0u : 0u, fbar + 128, lane);
            if (tid == 256) TL(88 + conv);
            norm_block<2, 2>(w, cf, act_off + 2 * ROW_BYTES, has_outer ? ~0u : 0u, fbar + 128, lane);
            if (tid == 256) TL(23 + conv * 4);
        }
        if (has_outer) {
            mbar_wait(BAR(BAR_FULL + NSTAGE - 1), 1);
#pragma unroll
            for (int i = 0; i < 4; i++) inbox[i * 256] = make_uint4(0, 0, 0, 0);
        }
    } else if (warp < 4) {
        const int wq = warp;
        if (wq == 3) {
            if (elect_one()) {
#pragma unroll
                for (int i = 0; i < NSTAGE; i++) mbar_init(BAR(BAR_FULL + i), (i >> 3) == 1 ? 1 : 5);
#pragma unroll
                for (int i = 0; i < NS + 2; i++) mbar_init(BAR(BAR_WEMPTY + i), 4);
#pragma unroll
                for (int i = BAR_STATS; i < BAR_X; i++) mbar_init(BAR(i), i == BAR_EMB ? 3 : 1);
                asm volatile("fence.mbarrier_init.release.cluster;" ::: "memory");
            }
            __syncwarp();
            fence_async_smem();
            bar_arrive(0, 96);
            bar_arrive(5, 96);
            bar_arrive(4, 256 + 64 + 128);
            const uint4 z = make_uint4(0, 0, 0, 0);
#pragma unroll
            for (int i = 0; i < 2; i++) sts128(SM_ACT + (i * 16 + (lane >> 1)) * CH_PITCH + (lane & 1) * 16, z);
            if (lane < 4) sts128(SM_ACT + (2 + (lane >> 1)) * ROW_BYTES + (lane & 1) * 16, z);
            if (lane < 16) sts128(SM_ONES + lane * 16, make_uint4(lane < 8 ? 0x3f803f80u : 0u, 0, 0, 0));
            fence_async_smem();
            asm volatile("barrier.cluster.arrive.release.aligned;" ::: "memory");
            bar_arrive(6, 64);
            if (elect_one()) {
                mbar_expect(BAR(BAR_W2), 2304);
                while (clock32() - clk0 < W2DELAY) {}
                const char* base = reinterpret_cast<const char*>(w2) + ((cta & 15) * 8 * C + (cta >> 4) * 16) * 18;
#pragma unroll 1
                for (int i = 0; i < 8; i++) bulk_g2s(S0 + SM_BNC + 2304 + i * 288, base + i * (C * 18), 288, S0 + BAR(BAR_W2));
            }
            __syncwarp();
        }
        bar_sync(2, 128);

        float d[64];
#pragma unroll
        for (int i = 0; i < 64; i++) d[i] = 0.f;
#pragma unroll 1
        for (int conv = 0; conv < 2; conv++) {
            fence_acc(d);
            mma_stages<0>(d, conv, tid, gs);
            if (conv == 0) {
                asm volatile("wgmma.fence.sync.aligned;" ::: "memory");
                wgmma128<(SM_ONES >> 4) | (8u << 16), (SM_EMB >> 4), 0, 8>(d);
                asm volatile("wgmma.commit_group.sync.aligned;" ::: "memory");
            }
            asm volatile("wgmma.wait_group.sync.aligned 0;" ::: "memory");
            fence_acc(d);
            if (tid == 0) TL(10 + conv * 8);
            if (conv == 1) break;

            uint32_t hp[32];
#pragma unroll
            for (int g = 0; g < 4; g++) {
                float c[4] = {0.f, 0.f, 0.f, 0.f};
#pragma unroll
                for (int i = 0; i < 8; i++) hp[8 * g + i] = pack_bf(d[16 * g + 2 * i], d[16 * g + 2 * i + 1]);
#pragma unroll
                for (int i = 0; i < 4; i++) stat_mma(c, hp[8 * g + 2 * i], hp[8 * g + 2 * i + 1]);
                stat_store(c, SM_RED + (g * 4 + wq) * 48, lane);
            }
            bar_sync(2, 128);
            if (wq == 0) stat_publish(SM_RED, &gs->acc2[b * LS], lane, true);
            if (tid == 0) TL(11);
            const uint32_t hbase = SM_ACT + (lane >> 4) * CH_PITCH + (2 + wq * 16 + (lane & 15)) * 16;
#pragma unroll
            for (int kc = 0; kc < 8; kc++) stsm4(hbase + kc * 2 * CH_PITCH, hp[4 * kc], hp[4 * kc + 1], hp[4 * kc + 2], hp[4 * kc + 3]);
            __syncwarp();
            if (lane == 0) mbar_arrive(BAR(BAR_HW));
            if (lane < LAG) mbar_arrive(BAR(BAR_WEMPTY + (NSTAGE - LAG) % NS) + 8 * lane);
            if (has_outer) {
                uint4* outbox = gs->box + (cta + ((r & 1) ? 1 : -1)) * 1024 + tid;
#pragma unroll
                for (int kc = 0; kc < 8; kc++) outbox[kc * 128] = make_uint4(~hp[4 * kc], ~hp[4 * kc + 1], ~hp[4 * kc + 2], ~hp[4 * kc + 3]);
            }
            if (tid == 0) TL(12);
            const uint32_t xbase = SM_XOWN + ((lane >> 4) * 8 + (lane & 7)) * 128 + (((2 * wq + ((lane >> 3) & 1)) ^ (lane & 7)) << 4);
#pragma unroll
            for (int kc = 0; kc < 8; kc++) {
                uint32_t p[4];
                ldsm4t(p, xbase + kc * 2048);
#pragma unroll
                for (int i = 0; i < 4; i++) { d[8 * kc + 2 * i] = bf_lo(p[i]); d[8 * kc + 2 * i + 1] = bf_hi(p[i]); }
            }
            fence_async_smem();
            __syncwarp();
            if (lane == 0) mbar_arrive(BAR(BAR_XFREE));
        }
        {
            const uint32_t obase = slot_addr(0) + ((lane >> 4) * 8 + (lane & 7)) * OUT_PITCH + (wq * 16 + ((lane >> 3) & 1) * 8) * 2;
#pragma unroll
            for (int kc = 0; kc < 8; kc++) {
                stsm4t(obase + kc * 16 * OUT_PITCH, pack_bf(d[8 * kc + 0], d[8 * kc + 1]), pack_bf(d[8 * kc + 2], d[8 * kc + 3]),
                       pack_bf(d[8 * kc + 4], d[8 * kc + 5]), pack_bf(d[8 * kc + 6], d[8 * kc + 7]));
            }
            bar_sync(2, 128);
            const int oc0 = tid >> 3;
            __nv_bfloat16* dst = out + ((size_t)(b * C + oc0) * HW + r) * HW + seg * 8;
#pragma unroll
            for (int i = 0; i < 8; i++)
                *reinterpret_cast<uint4*>(dst + (size_t)i * 16 * HW * HW) = lds128(slot_addr(0) + (oc0 + 16 * i) * OUT_PITCH + seg * 16);
            if (tid == 0) { TL(20); TLG(21); }
        }
    } else if (warp < 6) {
        bar_sync(5, 96);
        if (warp == 5) {
            asm volatile("barrier.cluster.wait.acquire.aligned;" ::: "memory");
            const uint32_t peer = (r & 1) ^ 1;
            const uint32_t self0 = mapa(0, r & 1), peer0 = mapa(0, peer);
#pragma unroll 1
            for (int conv = 0; conv < 2; conv++) {
#pragma unroll 1
                for (int kc = 0; kc < 8; kc++) {
                    mbar_wait(BAR(BAR_FULL) + 8 * kc, conv);
                    if (elect_one())
                        asm volatile("cp.async.bulk.shared::cluster.shared::cta.mbarrier::complete_tx::bytes [%0], [%1], %2, [%3];"
                                     ::"r"(peer0 + SM_ACT + ROW_BYTES + kc * KC_BYTES), "r"(self0 + SM_ACT + kc * KC_BYTES), "r"(KC_BYTES),
                                       "r"(peer0 + BAR(BAR_FULL + 8) + 8 * kc) : "memory");
                }
                if (lane == 0) TL(86 + conv);
#pragma unroll 1
                for (int kc = 0; kc < 8; kc++) mbar_wait(BAR(BAR_FULL + 8) + 8 * kc, conv);
                if (lane == 0)
                    asm volatile("mbarrier.arrive.release.cluster.shared::cluster.b64 _, [%0];" ::"r"(peer0 + (conv ? BAR(BAR_ACK) : BAR(BAR_EMB))) : "memory");
            }
            mbar_wait(BAR(BAR_ACK), 0);
        } else {
            if (lane < 2) asm volatile("red.release.gpu.global.add.u32 [%0], 1;" ::"l"(&gs->wcnt[(NB + lane) * LS]) : "memory");
            if (lane == 0) TL(14);
            mbar_wait(BAR(BAR_STATS), 0);
            unsigned it = 0;
            while (ld_relaxed(&gs->wcnt[(2 * NB + b) * LS]) < (unsigned)NXTRA && ++it < SPIN_LIMIT) __nanosleep(100);
            fence_acquire();
            float ev[4] = {0.f, 0.f, 0.f, 0.f};
#pragma unroll
            for (int j = 0; j < NXTRA; j++) {
                const uint4 ef = ld_relaxed_v4(&gs->emb[(j * NB + b) * C + lane * 4]);
                ev[0] += __uint_as_float(ef.x); ev[1] += __uint_as_float(ef.y); ev[2] += __uint_as_float(ef.z); ev[3] += __uint_as_float(ef.w);
            }
#pragma unroll
            for (int i = 0; i < 4; i++) {
                const float hi = bf_lo(pack_bf(ev[i], 0.f));
                sts128(SM_EMB + (lane * 4 + i) * 16, make_uint4(pack_bf(hi, ev[i] - hi), 0, 0, 0));
            }
            fence_async_smem();
            __syncwarp();
            if (lane == 0) { mbar_arrive(BAR(BAR_EMB)); TL(19); }
        }
    } else if (warp == 6) {
        bar_sync(0, 96);
        const uint32_t ebytes = STAGE_BYTES + ((lane >> 3) == 1 ? KC_BYTES : 0);
        if (lane < NSTAGE) mbar_expect(BAR(BAR_FULL) + 8 * lane, ebytes);
        const int swap = (r & 1) ? 0 : 8 * STAGE_BYTES;
        unsigned it = 0;
        {
            int g = 0;
#pragma unroll 1
            while (g < NS) {
                unsigned ready = __ballot_sync(0xffffffffu, ld_relaxed(&gs->wcnt[b * LS + (lane & 7)]) >= 16u) >> g;
                if (++it > SPIN_LIMIT) ready = ~0u;
                if (!(ready & 1)) continue;
                fence_acquire();
                fence_async_global();
                if (lane == 0) TL(g ? 3 : 6);
#pragma unroll 1
                for (; (ready & 1) && g < NS; g++, ready >>= 1)
                    if (elect_one())
                        bulk_g2s(S0 + SM_W + g * STAGE_BYTES, gs->wt + g * STAGE_BYTES + (g >= 8 ? swap : 0), STAGE_BYTES, S0 + BAR(BAR_FULL) + 8 * g);
            }
        }
#pragma unroll 1
        for (int q = 3; q < 12; q++) {
            const int conv = q >= 6, qs = conv ? q - 6 : q, sl = q % 3;
            const unsigned char* wsrc = gs->wt + q * 4 * STAGE_BYTES + (qs < 2 ? 0 : (qs < 4 ? swap : -swap));
            const uint32_t par = (q / 3 - 1) & 1;
            if (q == 6) {
                it = 0;
                while (ld_relaxed(&gs->wcnt[(NB + b) * LS]) < (unsigned)NCTA && ++it < SPIN_LIMIT) {}
                fence_acquire();
                fence_async_global();
                if (lane == 0) { mbar_arrive(BAR(BAR_EMB)); TL(2); }
            }
#pragma unroll
            for (int i = 0; i < 4; i++) {
                mbar_wait(BAR(BAR_WEMPTY + i) + 32 * sl, par);
                if (i == 0 && (q == 6 || q == 9)) {
                    if ((lane >= NS) == (q == 9) && lane < NSTAGE) mbar_expect(BAR(BAR_FULL) + 8 * lane, ebytes);
                    __syncwarp();
                }
                if (elect_one())
                    bulk_g2s(S0 + SM_W + (sl * 4 + i) * STAGE_BYTES, wsrc + i * STAGE_BYTES, STAGE_BYTES, S0 + BAR(BAR_FULL + i) + 32 * qs);
            }
        }
    } else {
        const uint2 ga1 = __ldg(reinterpret_cast<const uint2*>(g1) + lane), bt1 = __ldg(reinterpret_cast<const uint2*>(be1) + lane);
        const uint2 ga2 = __ldg(reinterpret_cast<const uint2*>(g2) + lane), bt2 = __ldg(reinterpret_cast<const uint2*>(be2) + lane);
        if (lane < 8) sts128(SM_GST + lane * 16, make_uint4(0, 0, 0, 0));
        sts128f(SM_COEF + lane * 32, make_float4(0.5f * bf_lo(ga1.x), 0.5f * bf_hi(ga1.x), 0.5f * bf_lo(bt1.x), 0.5f * bf_hi(bt1.x)));
        sts128f(SM_COEF + lane * 32 + 16, make_float4(0.5f * bf_lo(ga1.y), 0.5f * bf_hi(ga1.y), 0.5f * bf_lo(bt1.y), 0.5f * bf_hi(bt1.y)));
        sts128f(SM_COEF + 1024 + lane * 32, make_float4(0.5f * bf_lo(ga2.x), 0.5f * bf_hi(ga2.x), 0.5f * bf_lo(bt2.x), 0.5f * bf_hi(bt2.x)));
        sts128f(SM_COEF + 1024 + lane * 32 + 16, make_float4(0.5f * bf_lo(ga2.y), 0.5f * bf_hi(ga2.y), 0.5f * bf_lo(bt2.y), 0.5f * bf_hi(bt2.y)));
        bar_arrive(4, 256 + 64 + 128);
        bar_sync(0, 96);
#pragma unroll 1
        for (int conv = 0; conv < 2; conv++) {
            if (conv == 1) mbar_wait(BAR(BAR_EMB), 0);
            const float* asrc = conv ? &gs->acc2[b * LS + (lane & 3) * 4] : &gs->acc1[b * 4 * LS + (lane & 3) * GS1];
            unsigned it = 0;
#pragma unroll 1
            while (true) {
                const uint4 f = ld_relaxed_v4(asrc);
                const bool ok = ((f.x == 0x42800000u) & (f.w == 0x42800000u)) || ++it > SPIN_LIMIT;
                const float inv_n = 1.0f / (32.0f * HW * HW);
                const float mean = __uint_as_float(f.y) * inv_n;
                const float rs = rsqrtf(fmaxf(fmaf(-mean, mean, __uint_as_float(f.z) * inv_n), 0.f) + 1e-5f);
                if (ok && lane < 4)
                    asm volatile("st.shared.v2.f32 [%0], {%1,%2};" ::"r"(S0 + SM_GST + conv * 32 + lane * 8), "f"(rs == 0.f ? 1e-38f : rs), "f"(mean * rs) : "memory");
                if (__all_sync(0xffffffffu, ok)) break;
            }
            if (lane == 0) { mbar_arrive(BAR(BAR_STATS)); TL(7 + conv * 8); }
        }
        mbar_wait(BAR(BAR_XFREE), 0);
        if (has_outer && elect_one()) {
            mbar_expect(BAR(BAR_X + 4), 16384);
            bulk_g2s(S0 + SM_XOWN, gs->box + cta * 1024, 16384, S0 + BAR(BAR_X + 4));
        }
        if (r == 0) {
            if (lane < 16) gs->acc1[b * 4 * LS + (lane >> 2) * GS1 + (lane & 3)] = 0.f;
            if (lane < 24) gs->wcnt[((lane >> 3) * NB + b) * LS + (lane & 7)] = 0;
        }
    }
}

}

extern "C" void kernel_launch(void* const* d_in, const int* in_sizes, int n_in, void* d_out, int out_size) {
    (void)in_sizes; (void)n_in; (void)out_size;
    typedef CUresult (*EncodeFn)(CUtensorMap*, CUtensorMapDataType, cuuint32_t, void*, const cuuint64_t*, const cuuint64_t*,
                                 const cuuint32_t*, const cuuint32_t*, CUtensorMapInterleave, CUtensorMapSwizzle,
                                 CUtensorMapL2promotion, CUtensorMapFloatOOBfill);
    static Scratch* gs = nullptr;
    static EncodeFn encode = nullptr;
    if (!gs) {
        cudaFuncSetAttribute(resblock_kernel, cudaFuncAttributeMaxDynamicSharedMemorySize, SM_TOTAL);
        cudaGetSymbolAddress((void**)&gs, g_scratch);
        cudaDriverEntryPointQueryResult qr;
        cudaGetDriverEntryPoint("cuTensorMapEncodeTiled", (void**)&encode, cudaEnableDefault, &qr);
    }
    CUtensorMap xmap;
    const cuuint64_t dims[3] = {HW, HW, NB * C}, strides[2] = {HW * 2, HW * HW * 2};
    const cuuint32_t box[3] = {HW, 1, 32}, es[3] = {1, 1, 1};
    encode(&xmap, CU_TENSOR_MAP_DATA_TYPE_BFLOAT16, 3, d_in[0], dims, strides, box, es, CU_TENSOR_MAP_INTERLEAVE_NONE,
           CU_TENSOR_MAP_SWIZZLE_128B, CU_TENSOR_MAP_L2_PROMOTION_NONE, CU_TENSOR_MAP_FLOAT_OOB_FILL_NONE);
    resblock_kernel<<<NCTA + NXTRA, NTHREADS, SM_TOTAL>>>(
        (const __nv_bfloat16*)d_in[4], (const __nv_bfloat16*)d_in[1],
        (const __nv_bfloat16*)d_in[2], (const __nv_bfloat16*)d_in[3], (const __nv_bfloat16*)d_in[5],
        (const __nv_bfloat16*)d_in[6], (const __nv_bfloat16*)d_in[7], (const __nv_bfloat16*)d_in[8],
        (__nv_bfloat16*)d_out, gs, xmap);
}
```

```cpp
#include <cuda_runtime.h>
#include <cuda.h>
#include <cuda_bf16.h>
#include <stdint.h>

namespace {

constexpr int C = 128, HW = 64, NB = 2, E = 768;
constexpr int NCTA = NB * HW;
constexpr int NXTRA = 4;
constexpr int NTHREADS = 16 * 32;
constexpr int CH_PITCH = 66 * 16;
constexpr int ROW_BYTES = 16 * CH_PITCH;
constexpr int STEP_BYTES = 4096;
constexpr int STAGE_BYTES = 3 * STEP_BYTES;
constexpr int NSTAGE = 24;
constexpr int KC_BYTES = 2 * CH_PITCH;
constexpr int NS = 12;
constexpr int LAG = 1;
#define XDELAY 600
#define HDELAY 600
#define SEQ 0
#define MMA0_WAIT mbar_try
#define SPINPAUSE
#define NPOLL 1
#define PD2 0
#define PDELAY 60
#define RB 1
#define XSTAG2 200
#define XSTAG 800
#define HSEND 0
#define W2DELAY 2000

constexpr uint32_t SMEM_BASE = 0x400;
constexpr uint32_t SM_XOWN = SMEM_BASE;
constexpr uint32_t SM_ACT = SM_XOWN + 16384 + 512;
constexpr uint32_t SM_XOUT = SM_ACT + 2 * ROW_BYTES + 512;
static_assert(SM_XOUT % 1024 == 0, "swizzle atom alignment");
constexpr uint32_t SM_W = SM_ACT + 3 * ROW_BYTES + 128;
__host__ __device__ constexpr uint32_t slot_addr(int slot) { return SM_W + slot * STAGE_BYTES; }
constexpr uint32_t SM_COEF = SM_W + NS * STAGE_BYTES;
constexpr uint32_t SM_GST = SM_COEF + 2048;
constexpr uint32_t SM_EMB = SM_GST + 128;
constexpr uint32_t SM_ONES = SM_EMB + 2048;
constexpr uint32_t SM_RED = SM_ONES + 256;
constexpr uint32_t SM_BNC = SM_RED + 1280;
constexpr uint32_t SM_BAR = SM_BNC + 2 * 2304;
constexpr int BAR_FULL = 0, BAR_WEMPTY = NSTAGE, BAR_HW = BAR_WEMPTY + NS, BAR_XFREE = BAR_HW + 1, BAR_STATS = BAR_XFREE + 1,
              BAR_EMB = BAR_STATS + 1, BAR_ACK = BAR_EMB + 1, BAR_W2 = BAR_ACK + 1, BAR_X = BAR_W2 + 1  , NBAR = BAR_X + 5;
constexpr int SM_TOTAL = SM_BAR + NBAR * 8 - SMEM_BASE;
static_assert(SM_TOTAL <= 232448, "smem");
static_assert(NBAR <= 96, "barrier init");
constexpr int OUT_PITCH = 144;
__host__ __device__ constexpr uint32_t BAR(int i) { return SM_BAR + 8 * i; }
__host__ __device__ constexpr int ky_of(int kyo) { return kyo == 0 ? 1 : (kyo == 1 ? 0 : 2); }

constexpr unsigned SPIN_LIMIT = 1u << 16;

#define LS 1056
#define GS1 4
#define PD 0
struct Scratch {
    float acc1[NB * 4 * LS];
    float acc2[NB * LS];
    unsigned wcnt[3 * NB * LS];
    float emb[NXTRA * NB * C];
    unsigned char wt[2 * NSTAGE * STAGE_BYTES];
    uint4 box[NCTA * 1024];
};
__device__ __align__(1024) Scratch g_scratch;
#define TL(i) do {} while (0)
#define TLG(i) do {} while (0)

__device__ __forceinline__ unsigned clock32() { unsigned c; asm volatile("mov.u32 %0, %%clock;" : "=r"(c)); return c; }
__device__ __forceinline__ uint32_t mapa(uint32_t a, uint32_t rank) {
    uint32_t d;
    asm("mapa.shared::cluster.u32 %0, %1, %2;" : "=r"(d) : "r"(a), "r"(rank));
    return d;
}
#define S0 mapa(0, blockIdx.x & 1)
__device__ __forceinline__ void mbar_init(uint32_t bar, int cnt) {
    asm volatile("mbarrier.init.shared::cta.b64 [%0], %1;" ::"r"(bar + S0), "r"(cnt) : "memory");
}
__device__ __forceinline__ void mbar_arrive(uint32_t bar) {
    asm volatile("mbarrier.arrive.shared::cta.b64 _, [%0];" ::"r"(bar + S0) : "memory");
}
__device__ __forceinline__ void mbar_expect(uint32_t bar, uint32_t bytes) {
    asm volatile("mbarrier.arrive.expect_tx.shared::cta.b64 _, [%0], %1;" ::"r"(bar + S0), "r"(bytes) : "memory");
}
__device__ __forceinline__ bool mbar_try(uint32_t bar, uint32_t par) {
    uint32_t ok;
    asm volatile("{\n.reg .pred p;\nmbarrier.try_wait.parity.shared::cta.b64 p, [%1], %2;\nselp.u32 %0, 1, 0, p;\n}"
                 : "=r"(ok) : "r"(bar + S0), "r"(par) : "memory");
    return ok;
}
__device__ __forceinline__ bool mbar_test(uint32_t bar, uint32_t par) {
    uint32_t ok;
    asm volatile("{\n.reg .pred p;\nmbarrier.test_wait.parity.shared::cta.b64 p, [%1], %2;\nselp.u32 %0, 1, 0, p;\n}"
                 : "=r"(ok) : "r"(bar + S0), "r"(par) : "memory");
    return ok;
}
__device__ __forceinline__ void mbar_wait(uint32_t bar, uint32_t par) {
    unsigned it = 0;
#pragma unroll 1
    while (!mbar_try(bar, par) && ++it < SPIN_LIMIT) {}
}
__device__ __forceinline__ bool elect_one() {
    uint32_t p;
    asm volatile("{\n.reg .pred p;\nelect.sync _|p, 0xffffffff;\nselp.u32 %0, 1, 0, p;\n}" : "=r"(p));
    return p;
}
__device__ __forceinline__ void fence_async_smem() { asm volatile("fence.proxy.async.shared::cta;" ::: "memory"); }
__device__ __forceinline__ void fence_async_global() { asm volatile("fence.proxy.async.global;" ::: "memory"); }
__device__ __forceinline__ void fence_acquire() { asm volatile("fence.acquire.gpu;" ::: "memory"); }
__device__ __forceinline__ void bar_sync(int id, int n) { asm volatile("bar.sync %0, %1;" ::"r"(id), "r"(n) : "memory"); }
__device__ __forceinline__ void bar_arrive(int id, int n) { asm volatile("bar.arrive %0, %1;" ::"r"(id), "r"(n) : "memory"); }
__device__ __forceinline__ void bulk_g2s(uint32_t dst, const void* src, uint32_t bytes, uint32_t bar) {
    asm volatile("cp.async.bulk.shared::cluster.global.mbarrier::complete_tx::bytes [%0], [%1], %2, [%3];"
                 ::"r"(dst), "l"(src), "r"(bytes), "r"(bar) : "memory");
}
__device__ __forceinline__ void tma_x(uint32_t dst, const CUtensorMap* tm, int row, int ch, uint32_t bar) {
    asm volatile("cp.async.bulk.tensor.3d.shared::cluster.global.mbarrier::complete_tx::bytes [%0], [%1, {%2, %3, %4}], [%5];"
                 ::"r"(dst + S0), "l"(tm), "r"(0), "r"(row), "r"(ch), "r"(bar + S0) : "memory");
}
__device__ __forceinline__ uint4 ld_relaxed_v4(const void* p) {
    uint4 v;
    asm volatile("ld.relaxed.gpu.global.v4.u32 {%0,%1,%2,%3}, [%4];" : "=r"(v.x), "=r"(v.y), "=r"(v.z), "=r"(v.w) : "l"(p) : "memory");
    return v;
}
__device__ __forceinline__ unsigned ld_relaxed(const void* p) {
    unsigned v;
    asm volatile("ld.relaxed.gpu.global.u32 %0, [%1];" : "=r"(v) : "l"(p) : "memory");
    return v;
}
__device__ __forceinline__ void red_add4(float* p, float a, float b, float c, float d) {
    asm volatile("red.relaxed.gpu.global.add.v4.f32 [%0], {%1,%2,%3,%4};" ::"l"(p), "f"(a), "f"(b), "f"(c), "f"(d) : "memory");
}
__device__ __forceinline__ void sts128(uint32_t a, uint4 v) {
    asm volatile("st.shared.v4.u32 [%0], {%1,%2,%3,%4};" ::"r"(a + S0), "r"(v.x), "r"(v.y), "r"(v.z), "r"(v.w) : "memory");
}
__device__ __forceinline__ void sts128f(uint32_t a, float4 v) {
    asm volatile("st.shared.v4.f32 [%0], {%1,%2,%3,%4};" ::"r"(a + S0), "f"(v.x), "f"(v.y), "f"(v.z), "f"(v.w) : "memory");
}
__device__ __forceinline__ void sts32f(uint32_t a, float v) { asm volatile("st.shared.f32 [%0], %1;" ::"r"(a + S0), "f"(v) : "memory"); }
__device__ __forceinline__ uint4 lds128(uint32_t a) {
    uint4 v;
    asm volatile("ld.shared.v4.u32 {%0,%1,%2,%3}, [%4];" : "=r"(v.x), "=r"(v.y), "=r"(v.z), "=r"(v.w) : "r"(a + S0) : "memory");
    return v;
}
__device__ __forceinline__ float4 lds128f(uint32_t a) {
    float4 v;
    asm volatile("ld.shared.v4.f32 {%0,%1,%2,%3}, [%4];" : "=f"(v.x), "=f"(v.y), "=f"(v.z), "=f"(v.w) : "r"(a + S0) : "memory");
    return v;
}
__device__ __forceinline__ float2 lds64f(uint32_t a) {
    float2 v;
    asm volatile("ld.shared.v2.f32 {%0,%1}, [%2];" : "=f"(v.x), "=f"(v.y) : "r"(a + S0) : "memory");
    return v;
}
__device__ __forceinline__ float bf_lo(uint32_t u) { return __uint_as_float(u << 16); }
__device__ __forceinline__ float bf_hi(uint32_t u) { return __uint_as_float(u & 0xffff0000u); }
__device__ __forceinline__ uint32_t pack_bf(float lo, float hi) {
    uint32_t r;
    asm("cvt.rn.bf16x2.f32 %0, %1, %2;" : "=r"(r) : "f"(hi), "f"(lo));
    return r;
}
__device__ __forceinline__ float tanh_fast(float x) {
    float r;
    asm("tanh.approx.f32 %0, %1;" : "=f"(r) : "f"(x));
    return r;
}
__device__ __forceinline__ float silu_half(float h) { return fmaf(h, tanh_fast(h), h); }
__device__ __forceinline__ void ldsm4(uint32_t (&u)[4], uint32_t a) {
    asm volatile("ldmatrix.sync.aligned.m8n8.x4.shared.b16 {%0,%1,%2,%3}, [%4];"
                 : "=r"(u[0]), "=r"(u[1]), "=r"(u[2]), "=r"(u[3]) : "r"(a + S0) : "memory");
}
__device__ __forceinline__ void ldsm4t(uint32_t (&u)[4], uint32_t a) {
    asm volatile("ldmatrix.sync.aligned.m8n8.x4.trans.shared.b16 {%0,%1,%2,%3}, [%4];"
                 : "=r"(u[0]), "=r"(u[1]), "=r"(u[2]), "=r"(u[3]) : "r"(a + S0) : "memory");
}
__device__ __forceinline__ void stsm4(uint32_t a, uint32_t p0, uint32_t p1, uint32_t p2, uint32_t p3) {
    asm volatile("stmatrix.sync.aligned.m8n8.x4.shared.b16 [%0], {%1,%2,%3,%4};" ::"r"(a + S0), "r"(p0), "r"(p1), "r"(p2), "r"(p3) : "memory");
}
__device__ __forceinline__ void stsm4t(uint32_t a, uint32_t p0, uint32_t p1, uint32_t p2, uint32_t p3) {
    asm volatile("stmatrix.sync.aligned.m8n8.x4.trans.shared.b16 [%0], {%1,%2,%3,%4};" ::"r"(a + S0), "r"(p0), "r"(p1), "r"(p2), "r"(p3) : "memory");
}

#define R8(o) "+f"(d[o]), "+f"(d[o + 1]), "+f"(d[o + 2]), "+f"(d[o + 3]), "+f"(d[o + 4]), "+f"(d[o + 5]), "+f"(d[o + 6]), "+f"(d[o + 7])
template <uint32_t ALO, uint32_t BLO, uint64_t AHI = 8, uint64_t BHI = 48>
__device__ __forceinline__ void wgmma128(float (&d)[64]) {
    asm volatile(
        "wgmma.mma_async.sync.aligned.m64n128k16.f32.bf16.bf16 "
        "{%0,%1,%2,%3,%4,%5,%6,%7,%8,%9,%10,%11,%12,%13,%14,%15,%16,%17,%18,%19,%20,%21,%22,%23,%24,%25,%26,%27,%28,%29,%30,%31,"
        "%32,%33,%34,%35,%36,%37,%38,%39,%40,%41,%42,%43,%44,%45,%46,%47,%48,%49,%50,%51,%52,%53,%54,%55,%56,%57,%58,%59,%60,%61,%62,%63},"
        " %64, %65, 1, 1, 1, 0, 0;"
        : R8(0), R8(8), R8(16), R8(24), R8(32), R8(40), R8(48), R8(56)
        : "l"((AHI << 32) | ALO), "l"((BHI << 32) | BLO));
}
template <int S>
__device__ __forceinline__ void mma_stages(float (&d)[64], int conv, int tid, Scratch* gs) {
    constexpr uint32_t A = ((SM_ACT + S * 2 * CH_PITCH + 16) >> 4) | ((CH_PITCH >> 4) << 16);
    constexpr uint32_t B = (slot_addr(S % NS) >> 4) | (8u << 16);
    if (S == 0) {
        unsigned it = 0;
#pragma unroll 1
        while (!MMA0_WAIT(BAR(BAR_FULL), conv) && ++it < SPIN_LIMIT) {}
    }
    bool next_ok = true;
    constexpr uint32_t NEXT = S + 1 < NSTAGE ? BAR(BAR_FULL + S + 1) : BAR(BAR_EMB);
    const int npar = S + 1 < NSTAGE ? conv : 0;
    next_ok = mbar_test(NEXT, npar);
    if (S == 0 && tid == 0) TL(32 + conv * 24);
    asm volatile("wgmma.fence.sync.aligned;" ::: "memory");
    wgmma128<A, B>(d);
    wgmma128<A + 1, B + 16>(d);
    wgmma128<A + 2, B + 32>(d);
    asm volatile("wgmma.commit_group.sync.aligned;" ::: "memory");
    if (S >= LAG) {
        asm volatile("wgmma.wait_group.sync.aligned %0;" ::"n"(LAG) : "memory");
        if ((tid & 31) == 0) mbar_arrive(BAR(BAR_WEMPTY + (S + NS - LAG) % NS));
    }
    if (!next_ok) mbar_wait(NEXT, npar);
    if constexpr (S + 1 < NSTAGE) mma_stages<S + 1>(d, conv, tid, gs);
}

__device__ __forceinline__ void weight_load(uint4 (&t)[5], const __nv_bfloat16* w, int cta, int lane) {
    const char* base = reinterpret_cast<const char*>(w) + ((cta & 15) * 8 * C + (cta >> 4) * 16) * 18;
#pragma unroll
    for (int k = 0; k < 5; k++) {
        const int i = lane + 32 * k, row = (i * 57) >> 10;
        if (k < 4 || lane < 16) t[k] = __ldg(reinterpret_cast<const uint4*>(base + row * (C * 18 - 288) + i * 16));
    }
}
__device__ __forceinline__ void weight_block(uint32_t bounce, unsigned char* wt, int cta, int lane, bool readback, Scratch* gs) {
    unsigned char* dst = wt + (cta >> 4) * STAGE_BYTES + (cta & 15) * 768;
    if (lane < 16) {
        uint32_t v[36];
#pragma unroll
        for (int i = 0; i < 9; i++) {
            const uint4 q = lds128(bounce + (lane & 7) * 288 + (lane >> 3) * 144 + i * 16);
            v[4 * i] = q.x; v[4 * i + 1] = q.y; v[4 * i + 2] = q.z; v[4 * i + 3] = q.w;
        }
#pragma unroll
        for (int kyo = 0; kyo < 3; kyo++) {
#pragma unroll
            for (int kx = 0; kx < 3; kx++) {
                const int tap = ky_of(kyo) * 3 + kx;
                uint32_t o[4];
#pragma unroll
                for (int m = 0; m < 4; m++) {
                    const int i0 = 18 * m + tap, i1 = i0 + 9;
                    const uint32_t sel = ((i0 & 1) ? 0x32u : 0x10u) | ((i1 & 1) ? 0x7600u : 0x5400u);
                    o[m] = __byte_perm(v[i0 >> 1], v[i1 >> 1], sel);
                }
                *reinterpret_cast<uint4*>(dst + kyo * 8 * STAGE_BYTES + kx * 256 + lane * 16) = make_uint4(o[0], o[1], o[2], o[3]);
            }
        }
    }
    if (readback) {
        __syncwarp();
        if (lane == 0) TL(5);
        unsigned acc = 0;
        if (lane < 24) {
#pragma unroll
            for (int i = 0; i < 3; i++) acc |= ld_relaxed(dst + i * 8 * STAGE_BYTES + lane * 32);
        }
        asm volatile("{\n.reg .pred p;\nsetp.eq.u32 p, %0, 0x9e3779b9;\n@p st.shared.u32 [%1], %0;\n}" ::"r"(acc), "r"(bounce + S0) : "memory");
    }
}
__device__ __forceinline__ uint32_t act2(uint32_t u, const float4& cf) {
    return pack_bf(silu_half(fmaf(bf_lo(u), cf.x, cf.z)), silu_half(fmaf(bf_hi(u), cf.y, cf.w)));
}
__device__ __forceinline__ void norm_unit(uint32_t (&u)[4], const float4& ca, const float4& cb) {
    u[0] = act2(u[0], ca); u[1] = act2(u[1], ca); u[2] = act2(u[2], cb); u[3] = act2(u[3], cb);
}
__device__ __forceinline__ void read_stats(uint32_t gst, float (&g)[8]) {
    asm volatile("ld.volatile.shared.v4.f32 {%0,%1,%2,%3}, [%4];" : "=f"(g[0]), "=f"(g[1]), "=f"(g[2]), "=f"(g[3]) : "r"(gst + S0) : "memory");
    asm volatile("ld.volatile.shared.v4.f32 {%0,%1,%2,%3}, [%4];" : "=f"(g[4]), "=f"(g[5]), "=f"(g[6]), "=f"(g[7]) : "r"(gst + 16 + S0) : "memory");
}
template <int T>
__device__ __forceinline__ void group_coefs(uint32_t gst, float (&g)[8], float4 (&cf)[8]) {
    unsigned it = 0;
#pragma unroll 1
    while (!__all_sync(0xffffffffu, g[2 * T] != 0.f) && ++it < 8 * SPIN_LIMIT) { SPINPAUSE; read_stats(gst, g); }
    float4 &ca = cf[2 * T], &cb = cf[2 * T + 1];
    const float rs = g[2 * T], mr = g[2 * T + 1];
    ca.z = fmaf(-mr, ca.x, ca.z); ca.w = fmaf(-mr, ca.y, ca.w); ca.x *= rs; ca.y *= rs;
    cb.z = fmaf(-mr, cb.x, cb.z); cb.w = fmaf(-mr, cb.y, cb.w); cb.x *= rs; cb.y *= rs;
}
template <int FIRST, int N>
__device__ __forceinline__ void norm_block(uint32_t (&u)[4][4], float4 (&cf)[8], uint32_t act, uint32_t mask, uint32_t fbar, int lane) {
#pragma unroll
    for (int t = FIRST; t < FIRST + N; t++) {
        norm_unit(u[t], cf[2 * t], cf[2 * t + 1]);
        stsm4(act + t * 2 * KC_BYTES, u[t][0] & mask, u[t][1] & mask, u[t][2] & mask, u[t][3] & mask);
    }
    fence_async_smem();
    __syncwarp();
    if (lane < N) mbar_arrive(fbar + 16 * (FIRST + lane));
}
__device__ __forceinline__ void stat_mma(float (&c)[4], uint32_t p, uint32_t q) {
    asm("mma.sync.aligned.m16n8k16.row.col.f32.bf16.bf16.f32 {%0,%1,%2,%3}, {%4,%5,%6,%5}, {%4,%6}, {%0,%1,%2,%3};"
        : "+f"(c[0]), "+f"(c[1]), "+f"(c[2]), "+f"(c[3]) : "r"(p), "r"(0x3f803f80u), "r"(q));
}
__device__ __forceinline__ void stat_store(const float (&c)[4], uint32_t dst, int lane) {
    const int g = lane >> 2, t = lane & 3;
    if (t == (g >> 1)) sts32f(dst + g * 4, (g & 1) ? c[1] : c[0]);
    if (g == 7) sts32f(dst + 32 + t * 4, c[2] + c[3]);
}
__device__ __forceinline__ float sum4(float4 v) { return (v.x + v.y) + (v.z + v.w); }
__device__ __forceinline__ void stat_publish(uint32_t src, float* acc, int lane, bool real) {
    const uint32_t a = src + (lane & 15) * 48;
    float q = sum4(lds128f(a)) + sum4(lds128f(a + 16)), sm = sum4(lds128f(a + 32));
    q += __shfl_xor_sync(0xffffffffu, q, 1); sm += __shfl_xor_sync(0xffffffffu, sm, 1);
    q += __shfl_xor_sync(0xffffffffu, q, 2); sm += __shfl_xor_sync(0xffffffffu, sm, 2);
    if (real && (lane & 19) == 0) red_add4(acc + lane, 1.f, sm, q, 1.f);
}
__device__ __forceinline__ void fence_acc(float (&d)[64]) {
#pragma unroll
    for (int i = 0; i < 64; i++) asm volatile("" : "+f"(d[i])::"memory");
}
__device__ __forceinline__ void ld_unit(uint32_t (&u)[4], const uint4* p) {
    asm volatile("ld.relaxed.gpu.global.v4.u32 {%0,%1,%2,%3}, [%4];" : "=r"(u[0]), "=r"(u[1]), "=r"(u[2]), "=r"(u[3]) : "l"(p) : "memory");
}

__device__ __noinline__ void side_jobs(const __nv_bfloat16* __restrict__ t_emb, const __nv_bfloat16* __restrict__ w_emb,
                                       const __nv_bfloat16* __restrict__ w2, Scratch* __restrict__ gs, unsigned clk0) {
    const int tid = threadIdx.x, warp = tid >> 5, lane = tid & 31, j = blockIdx.x;
    float tv = 0.f;
    if (lane < 24) tv = __bfloat162float(t_emb[(lane / 12) * E + j * 192 + warp * 12 + lane % 12]);
    if (tid == 0) {
        mbar_init(BAR(0), 1);
        mbar_expect(BAR(0), 192 * C * 2);
        fence_async_smem();
        while (clock32() - clk0 < W2DELAY) {}
#pragma unroll
        for (int i = 0; i < 4; i++) bulk_g2s(S0 + SM_W + i * 12288, w_emb + (j * 192 + i * 48) * C, 12288, S0 + BAR(0));
    }
    if (j == 0 && tid < 32) gs->acc2[(tid >> 4) * LS + (tid & 15)] = 0.f;
    const float sv = silu_half(0.5f * tv);
    __syncthreads();
    mbar_wait(BAR(0), 0);
    float acc[8] = {0.f, 0.f, 0.f, 0.f, 0.f, 0.f, 0.f, 0.f};
#pragma unroll
    for (int i = 0; i < 12; i++) {
        const float2 wq = lds64f(SM_W + (warp * 12 + i) * 256 + lane * 8);
        const uint32_t wx = __float_as_uint(wq.x), wy = __float_as_uint(wq.y);
#pragma unroll
        for (int bb = 0; bb < 2; bb++) {
            const float sx = __shfl_sync(0xffffffffu, sv, bb * 12 + i);
            acc[4 * bb + 0] = fmaf(sx, bf_lo(wx), acc[4 * bb + 0]); acc[4 * bb + 1] = fmaf(sx, bf_hi(wx), acc[4 * bb + 1]);
            acc[4 * bb + 2] = fmaf(sx, bf_lo(wy), acc[4 * bb + 2]); acc[4 * bb + 3] = fmaf(sx, bf_hi(wy), acc[4 * bb + 3]);
        }
    }
    sts128f(SM_ACT + warp * 1024 + lane * 16, make_float4(acc[0], acc[1], acc[2], acc[3]));
    sts128f(SM_ACT + warp * 1024 + 512 + lane * 16, make_float4(acc[4], acc[5], acc[6], acc[7]));
    __syncthreads();
    if (tid < 128) {
        float2 sum = make_float2(0.f, 0.f);
#pragma unroll
        for (int w = 0; w < 16; w++) { const float2 p = lds64f(SM_ACT + w * 1024 + tid * 8); sum.x += p.x; sum.y += p.y; }
        *reinterpret_cast<float2*>(&gs->emb[j * NB * C + tid * 2]) = sum;
        bar_sync(1, 128);
        if (tid < 2) asm volatile("red.release.gpu.global.add.u32 [%0], 1;" ::"l"(&gs->wcnt[(2 * NB + tid) * LS]) : "memory");
    }
}

__global__ void __cluster_dims__(2, 1, 1) __launch_bounds__(NTHREADS, 1)
resblock_kernel(const __nv_bfloat16* __restrict__ w1,
                const __nv_bfloat16* __restrict__ t_emb, const __nv_bfloat16* __restrict__ g1,
                const __nv_bfloat16* __restrict__ be1, const __nv_bfloat16* __restrict__ w_emb,
                const __nv_bfloat16* __restrict__ g2, const __nv_bfloat16* __restrict__ be2,
                const __nv_bfloat16* __restrict__ w2, __nv_bfloat16* __restrict__ out, Scratch* __restrict__ gs,
                const __grid_constant__ CUtensorMap xmap) {
    const unsigned clk0 = clock32();
    if (threadIdx.x == 480 && blockIdx.x >= NXTRA) TLG(1);
    const int tid = threadIdx.x, lane = tid & 31;
    const int cta = blockIdx.x - NXTRA, b = cta >> 6, r = cta & 63;
    uint4 v[5];
    if (tid < 32) weight_load(v, w1, cta & (NCTA - 1), lane);
    const int warp = __shfl_sync(0xffffffffu, tid >> 5, 0);
    if (cta < 0) { side_jobs(t_emb, w_emb, w2, gs, clk0); return; }

    const int seg = lane & 7;
    if (warp != 3) asm volatile("barrier.cluster.arrive.relaxed.aligned;" ::: "memory");
    const bool has_outer = (r != 0) && (r != HW - 1);
    if (warp == 1 || warp == 2 || warp == 4 || warp == 5) {
        const int g = warp < 3 ? warp - 1 : 7 - warp;
        if (elect_one()) {
            asm volatile("prefetch.tensormap [%0];" ::"l"(&xmap) : "memory");
            mbar_init(BAR(BAR_X) + 8 * g, 1);
            if (g == 3) mbar_init(BAR(BAR_X + 4), 1);
            mbar_expect(BAR(BAR_X) + 8 * g, 4096);
            fence_async_smem();
            while (clock32() - clk0 < XDELAY + (g >> 1) * XSTAG + (g & 1) * XSTAG2) {}
            tma_x(SM_XOWN + g * 4096, &xmap, r, b * C + g * 32, BAR(BAR_X) + 8 * g);
            if (g == 3 && has_outer) {
                mbar_expect(BAR(BAR_X + 4), 16384);
#pragma unroll
                for (int i = 0; i < 4; i++) tma_x(SM_XOUT + i * 4096, &xmap, r + ((r & 1) ? 1 : -1), b * C + i * 32, BAR(BAR_X + 4));
            }
        }
        __syncwarp();
        bar_arrive(4, 256 + 64 + 128);
        mbar_wait(BAR(BAR_X) + 8 * g, 0);
        if (lane == 0) TL(70 + g);
        float c[8][4];
#pragma unroll
        for (int k = 0; k < 8; k++) {
            const uint4 q = lds128(SM_XOWN + g * 4096 + k * 512 + lane * 16);
            c[k][0] = c[k][1] = c[k][2] = c[k][3] = 0.f;
            stat_mma(c[k], q.x, q.y); stat_mma(c[k], q.z, q.w);
        }
#pragma unroll
        for (int i = 0; i < 4; i++) c[0][i] = ((c[0][i] + c[1][i]) + (c[2][i] + c[3][i])) + ((c[4][i] + c[5][i]) + (c[6][i] + c[7][i]));
        if (lane == 0 && g == 0) { if (c[0][0] == 1.2345f) sts32f(SM_RED, 0.f); TL(92); }
        stat_store(c[0], SM_RED + g * 48, lane);
        __syncwarp();
        if (lane == 0) {
            const uint32_t a = SM_RED + g * 48;
            red_add4(&gs->acc1[b * 4 * LS + g * GS1], 1.f, sum4(lds128f(a + 32)), sum4(lds128f(a)) + sum4(lds128f(a + 16)), 1.f);
            TL(74 + g);
        }
    }
    if (warp == 0 || warp == 4) {
        const int k = warp >> 2;
        if (k == 0) {
#pragma unroll
            for (int i = 0; i < 5; i++)
                if (i < 4 || lane < 16) sts128(SM_BNC + (lane + 32 * i) * 16, v[i]);
            if (lane == 0) TL(81);
            __syncwarp();
        } else {
            bar_sync(6, 64);
            mbar_wait(BAR(BAR_W2), 0);
        }
        weight_block(SM_BNC + k * 2304, gs->wt + k * NSTAGE * STAGE_BYTES, cta, lane, k == 0, gs);
        __syncwarp();
        if (lane == 0) TL(k ? 13 : 4);
        if (k == 0 && lane < 2) asm volatile("red.relaxed.gpu.global.add.u32 [%0], 1;" ::"l"(&gs->wcnt[lane * LS + (cta >> 4)]) : "memory");
    }

    if (warp >= 8) {
        const int nw = warp - 8;
        bar_sync(4, 256 + 64 + 128);
        const int par = nw >> 2, wq = nw & 3;
        const uint32_t act_off = SM_ACT + (par * 2 + (lane >> 4)) * CH_PITCH + (2 + wq * 16 + (lane & 15)) * 16;
        const uint32_t stg_off = (par * 16 + (lane >> 4) * 8 + (lane & 7)) * 128 + (((2 * wq + ((lane >> 3) & 1)) ^ (lane & 7)) << 4);
        const uint32_t cfa = SM_COEF + par * 128 + (lane & 3) * 16;
        const uint32_t fbar = BAR(BAR_FULL) + 8 * par;
        uint4* inbox = gs->box + cta * 1024 + nw * 32 + lane;
#pragma unroll 1
        for (int conv = 0; conv < 2; conv++) {
            uint32_t u[4][4], w[4][4];
            float4 cf[8];
            if (conv == 0) {
#pragma unroll
                for (int i = 0; i < 4; i++) { mbar_wait(BAR(BAR_X + i), 0); ldsm4t(u[i], SM_XOWN + stg_off + i * 4096); }
            } else {
                mbar_wait(BAR(BAR_HW), 0);
#pragma unroll
                for (int i = 0; i < 4; i++) ldsm4(u[i], act_off + i * 2 * KC_BYTES);
            }
#pragma unroll
            for (int i = 0; i < 8; i++) cf[i] = lds128f(cfa + conv * 1024 + (i >> 1) * 256 + (i & 1) * 64);
            const uint32_t gst = SM_GST + conv * 32;
            float gv[8];
            read_stats(gst, gv);
            group_coefs<0>(gst, gv, cf);
            if (tid == 256) TL(22 + conv * 4);
            if (par) { const unsigned c1 = clock32(); while (clock32() - c1 < PDELAY) {} }
            norm_block<0, 1>(u, cf, act_off, ~0u, fbar, lane);
            if (tid == 256) TL(8 + conv * 8);
            group_coefs<1>(gst, gv, cf);
            norm_block<1, 1>(u, cf, act_off, ~0u, fbar, lane);
            group_coefs<2>(gst, gv, cf);
            norm_block<2, 1>(u, cf, act_off, ~0u, fbar, lane);
            group_coefs<3>(gst, gv, cf);
            norm_block<3, 1>(u, cf, act_off, ~0u, fbar, lane);
            if (tid == 256) TL(84 + conv);
            if (has_outer) {
                mbar_wait(BAR(BAR_X + 4), conv);
                if (conv == 0) {
#pragma unroll
                    for (int i = 0; i < 4; i++) ldsm4t(w[i], SM_XOUT + stg_off + i * 4096);
                } else {
#pragma unroll
                    for (int i = 0; i < 4; i++) {
                        const uint4 q = lds128(SM_XOWN + (tid - 256) * 16 + i * 4096);
                        w[i][0] = q.x; w[i][1] = q.y; w[i][2] = q.z; w[i][3] = q.w;
                    }
                    unsigned it = 0;
                    while (true) {
                        bool ok = true;
#pragma unroll
                        for (int i = 0; i < 16; i++) ok = ok && w[i >> 2][i & 3] != 0;
                        if (__all_sync(0xffffffffu, ok) || ++it > SPIN_LIMIT) break;
#pragma unroll
                        for (int i = 0; i < 4; i++) ld_unit(w[i], inbox + i * 256);
                    }
#pragma unroll
                    for (int i = 0; i < 16; i++) w[i >> 2][i & 3] = ~w[i >> 2][i & 3];
                }
            }
            if (conv == 0) {
                bar_sync(3, 256);
                if (nw == 0) sts128(SM_ACT + 2 * ROW_BYTES + (lane >> 1) * CH_PITCH + (lane & 1) * 16, make_uint4(0, 0, 0, 0));
            }
            if (tid == 256) TL(24 + conv * 4);
            norm_block<0, 2>(w, cf, act_off + 2 * ROW_BYTES, has_outer ? ~0u : 0u, fbar + 128, lane);
            if (tid == 256) TL(88 + conv);
            norm_block<2, 2>(w, cf, act_off + 2 * ROW_BYTES, has_outer ? ~0u : 0u, fbar + 128, lane);
            if (tid == 256) TL(23 + conv * 4);
        }
        if (has_outer) {
            mbar_wait(BAR(BAR_FULL + NSTAGE - 1), 1);
#pragma unroll
            for (int i = 0; i < 4; i++) inbox[i * 256] = make_uint4(0, 0, 0, 0);
        }
    } else if (warp < 4) {
        const int wq = warp;
        if (wq == 3) {
            if (elect_one()) {
#pragma unroll
                for (int i = 0; i < NSTAGE; i++) mbar_init(BAR(BAR_FULL + i), (i >> 3) == 1 ? 1 : 5);
#pragma unroll
                for (int i = 0; i < NS + 2; i++) mbar_init(BAR(BAR_WEMPTY + i), 4);
#pragma unroll
                for (int i = BAR_STATS; i < BAR_X; i++) mbar_init(BAR(i), i == BAR_EMB ? 3 : 1);
                asm volatile("fence.mbarrier_init.release.cluster;" ::: "memory");
            }
            __syncwarp();
            fence_async_smem();
            bar_arrive(0, 96);
            bar_arrive(5, 96);
            bar_arrive(4, 256 + 64 + 128);
            const uint4 z = make_uint4(0, 0, 0, 0);
#pragma unroll
            for (int i = 0; i < 2; i++) sts128(SM_ACT + (i * 16 + (lane >> 1)) * CH_PITCH + (lane & 1) * 16, z);
            if (lane < 4) sts128(SM_ACT + (2 + (lane >> 1)) * ROW_BYTES + (lane & 1) * 16, z);
            if (lane < 16) sts128(SM_ONES + lane * 16, make_uint4(lane < 8 ? 0x3f803f80u : 0u, 0, 0, 0));
            fence_async_smem();
            asm volatile("barrier.cluster.arrive.release.aligned;" ::: "memory");
            bar_arrive(6, 64);
            if (elect_one()) {
                mbar_expect(BAR(BAR_W2), 2304);
                while (clock32() - clk0 < W2DELAY) {}
                const char* base = reinterpret_cast<const char*>(w2) + ((cta & 15) * 8 * C + (cta >> 4) * 16) * 18;
#pragma unroll 1
                for (int i = 0; i < 8; i++) bulk_g2s(S0 + SM_BNC + 2304 + i * 288, base + i * (C * 18), 288, S0 + BAR(BAR_W2));
            }
            __syncwarp();
        }
        bar_sync(2, 128);

        float d[64];
#pragma unroll
        for (int i = 0; i < 64; i++) d[i] = 0.f;
#pragma unroll 1
        for (int conv = 0; conv < 2; conv++) {
            fence_acc(d);
            mma_stages<0>(d, conv, tid, gs);
            if (conv == 0) {
                asm volatile("wgmma.fence.sync.aligned;" ::: "memory");
                wgmma128<(SM_ONES >> 4) | (8u << 16), (SM_EMB >> 4), 0, 8>(d);
                asm volatile("wgmma.commit_group.sync.aligned;" ::: "memory");
            }
            asm volatile("wgmma.wait_group.sync.aligned 0;" ::: "memory");
            fence_acc(d);
            if (tid == 0) TL(10 + conv * 8);
            if (conv == 1) break;

            uint32_t hp[32];
#pragma unroll
            for (int g = 0; g < 4; g++) {
                float c[4] = {0.f, 0.f, 0.f, 0.f};
#pragma unroll
                for (int i = 0; i < 8; i++) hp[8 * g + i] = pack_bf(d[16 * g + 2 * i], d[16 * g + 2 * i + 1]);
#pragma unroll
                for (int i = 0; i < 4; i++) stat_mma(c, hp[8 * g + 2 * i], hp[8 * g + 2 * i + 1]);
                stat_store(c, SM_RED + (g * 4 + wq) * 48, lane);
            }
            bar_sync(2, 128);
            if (wq == 0) stat_publish(SM_RED, &gs->acc2[b * LS], lane, true);
            if (tid == 0) TL(11);
            const uint32_t hbase = SM_ACT + (lane >> 4) * CH_PITCH + (2 + wq * 16 + (lane & 15)) * 16;
#pragma unroll
            for (int kc = 0; kc < 8; kc++) stsm4(hbase + kc * 2 * CH_PITCH, hp[4 * kc], hp[4 * kc + 1], hp[4 * kc + 2], hp[4 * kc + 3]);
            __syncwarp();
            if (lane == 0) mbar_arrive(BAR(BAR_HW));
            if (lane < LAG) mbar_arrive(BAR(BAR_WEMPTY + (NSTAGE - LAG) % NS) + 8 * lane);
            if (has_outer) {
                uint4* outbox = gs->box + (cta + ((r & 1) ? 1 : -1)) * 1024 + tid;
#pragma unroll
                for (int kc = 0; kc < 8; kc++) outbox[kc * 128] = make_uint4(~hp[4 * kc], ~hp[4 * kc + 1], ~hp[4 * kc + 2], ~hp[4 * kc + 3]);
            }
            if (tid == 0) TL(12);
            const uint32_t xbase = SM_XOWN + ((lane >> 4) * 8 + (lane & 7)) * 128 + (((2 * wq + ((lane >> 3) & 1)) ^ (lane & 7)) << 4);
#pragma unroll
            for (int kc = 0; kc < 8; kc++) {
                uint32_t p[4];
                ldsm4t(p, xbase + kc * 2048);
#pragma unroll
                for (int i = 0; i < 4; i++) { d[8 * kc + 2 * i] = bf_lo(p[i]); d[8 * kc + 2 * i + 1] = bf_hi(p[i]); }
            }
            fence_async_smem();
            __syncwarp();
            if (lane == 0) mbar_arrive(BAR(BAR_XFREE));
        }
        {
            const uint32_t obase = slot_addr(0) + ((lane >> 4) * 8 + (lane & 7)) * OUT_PITCH + (wq * 16 + ((lane >> 3) & 1) * 8) * 2;
#pragma unroll
            for (int kc = 0; kc < 8; kc++) {
                stsm4t(obase + kc * 16 * OUT_PITCH, pack_bf(d[8 * kc + 0], d[8 * kc + 1]), pack_bf(d[8 * kc + 2], d[8 * kc + 3]),
                       pack_bf(d[8 * kc + 4], d[8 * kc + 5]), pack_bf(d[8 * kc + 6], d[8 * kc + 7]));
            }
            bar_sync(2, 128);
            const int oc0 = tid >> 3;
            __nv_bfloat16* dst = out + ((size_t)(b * C + oc0) * HW + r) * HW + seg * 8;
#pragma unroll
            for (int i = 0; i < 8; i++)
                *reinterpret_cast<uint4*>(dst + (size_t)i * 16 * HW * HW) = lds128(slot_addr(0) + (oc0 + 16 * i) * OUT_PITCH + seg * 16);
            if (tid == 0) { TL(20); TLG(21); }
        }
    } else if (warp < 6) {
        bar_sync(5, 96);
        if (warp == 5) {
            asm volatile("barrier.cluster.wait.acquire.aligned;" ::: "memory");
            const uint32_t peer = (r & 1) ^ 1;
            const uint32_t self0 = mapa(0, r & 1), peer0 = mapa(0, peer);
#pragma unroll 1
            for (int conv = 0; conv < 2; conv++) {
#pragma unroll 1
                for (int kc = 0; kc < 8; kc++) {
                    mbar_wait(BAR(BAR_FULL) + 8 * kc, conv);
                    if (elect_one())
                        asm volatile("cp.async.bulk.shared::cluster.shared::cta.mbarrier::complete_tx::bytes [%0], [%1], %2, [%3];"
                                     ::"r"(peer0 + SM_ACT + ROW_BYTES + kc * KC_BYTES), "r"(self0 + SM_ACT + kc * KC_BYTES), "r"(KC_BYTES),
                                       "r"(peer0 + BAR(BAR_FULL + 8) + 8 * kc) : "memory");
                }
                if (lane == 0) TL(86 + conv);
#pragma unroll 1
                for (int kc = 0; kc < 8; kc++) mbar_wait(BAR(BAR_FULL + 8) + 8 * kc, conv);
                if (lane == 0)
                    asm volatile("mbarrier.arrive.release.cluster.shared::cluster.b64 _, [%0];" ::"r"(peer0 + (conv ? BAR(BAR_ACK) : BAR(BAR_EMB))) : "memory");
            }
            mbar_wait(BAR(BAR_ACK), 0);
        } else {
            if (lane < 2) asm volatile("red.release.gpu.global.add.u32 [%0], 1;" ::"l"(&gs->wcnt[(NB + lane) * LS]) : "memory");
            if (lane == 0) TL(14);
            mbar_wait(BAR(BAR_STATS), 0);
            unsigned it = 0;
            while (ld_relaxed(&gs->wcnt[(2 * NB + b) * LS]) < (unsigned)NXTRA && ++it < SPIN_LIMIT) __nanosleep(100);
            fence_acquire();
            float ev[4] = {0.f, 0.f, 0.f, 0.f};
#pragma unroll
            for (int j = 0; j < NXTRA; j++) {
                const uint4 ef = ld_relaxed_v4(&gs->emb[(j * NB + b) * C + lane * 4]);
                ev[0] += __uint_as_float(ef.x); ev[1] += __uint_as_float(ef.y); ev[2] += __uint_as_float(ef.z); ev[3] += __uint_as_float(ef.w);
            }
#pragma unroll
            for (int i = 0; i < 4; i++) {
                const float hi = bf_lo(pack_bf(ev[i], 0.f));
                sts128(SM_EMB + (lane * 4 + i) * 16, make_uint4(pack_bf(hi, ev[i] - hi), 0, 0, 0));
            }
            fence_async_smem();
            __syncwarp();
            if (lane == 0) { mbar_arrive(BAR(BAR_EMB)); TL(19); }
        }
    } else if (warp == 6) {
        bar_sync(0, 96);
        const uint32_t ebytes = STAGE_BYTES + ((lane >> 3) == 1 ? KC_BYTES : 0);
        if (lane < NSTAGE) mbar_expect(BAR(BAR_FULL) + 8 * lane, ebytes);
        const int swap = (r & 1) ? 0 : 8 * STAGE_BYTES;
        unsigned it = 0;
        {
            int g = 0;
#pragma unroll 1
            while (g < NS) {
                unsigned ready = __ballot_sync(0xffffffffu, ld_relaxed(&gs->wcnt[b * LS + (lane & 7)]) >= 16u) >> g;
                if (++it > SPIN_LIMIT) ready = ~0u;
                if (!(ready & 1)) continue;
                fence_acquire();
                fence_async_global();
                if (lane == 0) TL(g ? 3 : 6);
#pragma unroll 1
                for (; (ready & 1) && g < NS; g++, ready >>= 1)
                    if (elect_one())
                        bulk_g2s(S0 + SM_W + g * STAGE_BYTES, gs->wt + g * STAGE_BYTES + (g >= 8 ? swap : 0), STAGE_BYTES, S0 + BAR(BAR_FULL) + 8 * g);
            }
        }
#pragma unroll 1
        for (int q = 3; q < 12; q++) {
            const int conv = q >= 6, qs = conv ? q - 6 : q, sl = q % 3;
            const unsigned char* wsrc = gs->wt + q * 4 * STAGE_BYTES + (qs < 2 ? 0 : (qs < 4 ? swap : -swap));
            const uint32_t par = (q / 3 - 1) & 1;
            if (q == 6) {
                it = 0;
                while (ld_relaxed(&gs->wcnt[(NB + b) * LS]) < (unsigned)NCTA && ++it < SPIN_LIMIT) {}
                fence_acquire();
                fence_async_global();
                if (lane == 0) { mbar_arrive(BAR(BAR_EMB)); TL(2); }
            }
#pragma unroll
            for (int i = 0; i < 4; i++) {
                mbar_wait(BAR(BAR_WEMPTY + i) + 32 * sl, par);
                if (i == 0 && (q == 6 || q == 9)) {
                    if ((lane >= NS) == (q == 9) && lane < NSTAGE) mbar_expect(BAR(BAR_FULL) + 8 * lane, ebytes);
                    __syncwarp();
                }
                if (elect_one())
                    bulk_g2s(S0 + SM_W + (sl * 4 + i) * STAGE_BYTES, wsrc + i * STAGE_BYTES, STAGE_BYTES, S0 + BAR(BAR_FULL + i) + 32 * qs);
            }
        }
    } else {
        const uint2 ga1 = __ldg(reinterpret_cast<const uint2*>(g1) + lane), bt1 = __ldg(reinterpret_cast<const uint2*>(be1) + lane);
        const uint2 ga2 = __ldg(reinterpret_cast<const uint2*>(g2) + lane), bt2 = __ldg(reinterpret_cast<const uint2*>(be2) + lane);
        if (lane < 8) sts128(SM_GST + lane * 16, make_uint4(0, 0, 0, 0));
        sts128f(SM_COEF + lane * 32, make_float4(0.5f * bf_lo(ga1.x), 0.5f * bf_hi(ga1.x), 0.5f * bf_lo(bt1.x), 0.5f * bf_hi(bt1.x)));
        sts128f(SM_COEF + lane * 32 + 16, make_float4(0.5f * bf_lo(ga1.y), 0.5f * bf_hi(ga1.y), 0.5f * bf_lo(bt1.y), 0.5f * bf_hi(bt1.y)));
        sts128f(SM_COEF + 1024 + lane * 32, make_float4(0.5f * bf_lo(ga2.x), 0.5f * bf_hi(ga2.x), 0.5f * bf_lo(bt2.x), 0.5f * bf_hi(bt2.x)));
        sts128f(SM_COEF + 1024 + lane * 32 + 16, make_float4(0.5f * bf_lo(ga2.y), 0.5f * bf_hi(ga2.y), 0.5f * bf_lo(bt2.y), 0.5f * bf_hi(bt2.y)));
        bar_arrive(4, 256 + 64 + 128);
        bar_sync(0, 96);
#pragma unroll 1
        for (int conv = 0; conv < 2; conv++) {
            if (conv == 1) {
                mbar_wait(BAR(BAR_HW), 0);
                const unsigned c1 = clock32();
                while (clock32() - c1 < PD2) {}
            } else {
                while (clock32() - clk0 < PD) {}
            }
            const float* asrc = conv ? &gs->acc2[b * LS + (lane & 3) * 4] : &gs->acc1[b * 4 * LS + (lane & 3) * GS1];
            unsigned it = 0;
            uint4 fq[NPOLL];
#pragma unroll
            for (int i = 0; i < NPOLL; i++) {
                fq[i] = ld_relaxed_v4(asrc);
                if (i + 1 < NPOLL) { const unsigned c1 = clock32(); while (clock32() - c1 < 450 / NPOLL) {} }
            }
            bool all = false;
#pragma unroll 1
            while (!all) {
#pragma unroll
                for (int i = 0; i < NPOLL; i++) {
                    const uint4 f = fq[i];
                    const bool ok = ((f.x == 0x42800000u) & (f.w == 0x42800000u)) || it > SPIN_LIMIT;
                    if (ok && lane < 4) {
                        const float inv_n = 1.0f / (32.0f * HW * HW);
                        const float mean = __uint_as_float(f.y) * inv_n;
                        const float rs = rsqrtf(fmaxf(fmaf(-mean, mean, __uint_as_float(f.z) * inv_n), 0.f) + 1e-5f);
                        asm volatile("st.shared.v2.f32 [%0], {%1,%2};" ::"r"(S0 + SM_GST + conv * 32 + lane * 8), "f"(rs == 0.f ? 1e-38f : rs), "f"(mean * rs) : "memory");
                    }
                    if (__all_sync(0xffffffffu, ok)) { all = true; break; }
                    fq[i] = ld_relaxed_v4(asrc);
                }
                it++;
            }
            if (lane == 0) { mbar_arrive(BAR(BAR_STATS)); TL(7 + conv * 8); }
        }
        mbar_wait(BAR(BAR_XFREE), 0);
        if (has_outer && elect_one()) {
            mbar_expect(BAR(BAR_X + 4), 16384);
            bulk_g2s(S0 + SM_XOWN, gs->box + cta * 1024, 16384, S0 + BAR(BAR_X + 4));
        }
        if (r == 0) {
            if (lane < 16) gs->acc1[b * 4 * LS + (lane >> 2) * GS1 + (lane & 3)] = 0.f;
            if (lane < 24) gs->wcnt[((lane >> 3) * NB + b) * LS + (lane & 7)] = 0;
        }
    }
}

}

extern "C" void kernel_launch(void* const* d_in, const int* in_sizes, int n_in, void* d_out, int out_size) {
    (void)in_sizes; (void)n_in; (void)out_size;
    typedef CUresult (*EncodeFn)(CUtensorMap*, CUtensorMapDataType, cuuint32_t, void*, const cuuint64_t*, const cuuint64_t*,
                                 const cuuint32_t*, const cuuint32_t*, CUtensorMapInterleave, CUtensorMapSwizzle,
                                 CUtensorMapL2promotion, CUtensorMapFloatOOBfill);
    static Scratch* gs = nullptr;
    static EncodeFn encode = nullptr;
    if (!gs) {
        cudaFuncSetAttribute(resblock_kernel, cudaFuncAttributeMaxDynamicSharedMemorySize, SM_TOTAL);
        cudaGetSymbolAddress((void**)&gs, g_scratch);
        cudaDriverEntryPointQueryResult qr;
        cudaGetDriverEntryPoint("cuTensorMapEncodeTiled", (void**)&encode, cudaEnableDefault, &qr);
    }
    CUtensorMap xmap;
    const cuuint64_t dims[3] = {HW, HW, NB * C}, strides[2] = {HW * 2, HW * HW * 2};
    const cuuint32_t box[3] = {HW, 1, 32}, es[3] = {1, 1, 1};
    encode(&xmap, CU_TENSOR_MAP_DATA_TYPE_BFLOAT16, 3, d_in[0], dims, strides, box, es, CU_TENSOR_MAP_INTERLEAVE_NONE,
           CU_TENSOR_MAP_SWIZZLE_128B, CU_TENSOR_MAP_L2_PROMOTION_NONE, CU_TENSOR_MAP_FLOAT_OOB_FILL_NONE);
    resblock_kernel<<<NCTA + NXTRA, NTHREADS, SM_TOTAL>>>(
        (const __nv_bfloat16*)d_in[4], (const __nv_bfloat16*)d_in[1],
        (const __nv_bfloat16*)d_in[2], (const __nv_bfloat16*)d_in[3], (const __nv_bfloat16*)d_in[5],
        (const __nv_bfloat16*)d_in[6], (const __nv_bfloat16*)d_in[7], (const __nv_bfloat16*)d_in[8],
        (__nv_bfloat16*)d_out, gs, xmap);
}
```

```cpp
#include <cuda_runtime.h>
#include <cuda.h>
#include <cuda_bf16.h>
#include <stdint.h>

namespace {

constexpr int C = 128, HW = 64, NB = 2, E = 768;
constexpr int NCTA = NB * HW;
constexpr int NXTRA = 4;
constexpr int NTHREADS = 16 * 32;
constexpr int CH_PITCH = 66 * 16;
constexpr int ROW_BYTES = 16 * CH_PITCH;
constexpr int STEP_BYTES = 4096;
constexpr int STAGE_BYTES = 3 * STEP_BYTES;
constexpr int NSTAGE = 24;
constexpr int KC_BYTES = 2 * CH_PITCH;
constexpr int NS = 12;
constexpr int LAG = 1;
#define XDELAY 600
#define HDELAY 600
#define SEQ 0
#define MMA0_WAIT mbar_try
#define SPINPAUSE
#define NPOLL 1
#define PD2 0
#define PDELAY 60
#define RB 1
#define XSTAG2 200
#define XSTAG 800
#define HSEND 0
#define W2DELAY 2000

constexpr uint32_t SMEM_BASE = 0x400;
constexpr uint32_t SM_XOWN = SMEM_BASE;
constexpr uint32_t SM_ACT = SM_XOWN + 16384 + 512;
constexpr uint32_t SM_XOUT = SM_ACT + 2 * ROW_BYTES + 512;
static_assert(SM_XOUT % 1024 == 0, "swizzle atom alignment");
constexpr uint32_t SM_W = SM_ACT + 3 * ROW_BYTES + 128;
__host__ __device__ constexpr uint32_t slot_addr(int slot) { return SM_W + slot * STAGE_BYTES; }
constexpr uint32_t SM_COEF = SM_W + NS * STAGE_BYTES;
constexpr uint32_t SM_GST = SM_COEF + 2048;
constexpr uint32_t SM_EMB = SM_GST + 128;
constexpr uint32_t SM_ONES = SM_EMB + 2048;
constexpr uint32_t SM_RED = SM_ONES + 256;
constexpr uint32_t SM_BNC = SM_RED + 1280;
constexpr uint32_t SM_BAR = SM_BNC + 2 * 2304;
constexpr int BAR_FULL = 0, BAR_WEMPTY = NSTAGE, BAR_HW = BAR_WEMPTY + NS, BAR_XFREE = BAR_HW + 1, BAR_STATS = BAR_XFREE + 1,
              BAR_EMB = BAR_STATS + 1, BAR_ACK = BAR_EMB + 1, BAR_W2 = BAR_ACK + 1, BAR_X = BAR_W2 + 1  , NBAR = BAR_X + 5;
constexpr int SM_TOTAL = SM_BAR + NBAR * 8 - SMEM_BASE;
static_assert(SM_TOTAL <= 232448, "smem");
static_assert(NBAR <= 96, "barrier init");
constexpr int OUT_PITCH = 144;
__host__ __device__ constexpr uint32_t BAR(int i) { return SM_BAR + 8 * i; }
__host__ __device__ constexpr int ky_of(int kyo) { return kyo == 0 ? 1 : (kyo == 1 ? 0 : 2); }

constexpr unsigned SPIN_LIMIT = 1u << 16;

#define LS 1056
#define GS1 4
#define PD 0
struct Scratch {
    float acc1[NB * 4 * LS];
    float acc2[NB * LS];
    unsigned wcnt[3 * NB * LS];
    float emb[NXTRA * NB * C];
    unsigned char wt[2 * NSTAGE * STAGE_BYTES];
    uint4 box[NCTA * 1024];
};
__device__ __align__(1024) Scratch g_scratch;
#define TL(i) do {} while (0)
#define TLG(i) do {} while (0)

__device__ __forceinline__ unsigned clock32() { unsigned c; asm volatile("mov.u32 %0, %%clock;" : "=r"(c)); return c; }
__device__ __forceinline__ uint32_t mapa(uint32_t a, uint32_t rank) {
    uint32_t d;
    asm("mapa.shared::cluster.u32 %0, %1, %2;" : "=r"(d) : "r"(a), "r"(rank));
    return d;
}
#define S0 mapa(0, blockIdx.x & 1)
__device__ __forceinline__ void mbar_init(uint32_t bar, int cnt) {
    asm volatile("mbarrier.init.shared::cta.b64 [%0], %1;" ::"r"(bar + S0), "r"(cnt) : "memory");
}
__device__ __forceinline__ void mbar_arrive(uint32_t bar) {
    asm volatile("mbarrier.arrive.shared::cta.b64 _, [%0];" ::"r"(bar + S0) : "memory");
}
__device__ __forceinline__ void mbar_expect(uint32_t bar, uint32_t bytes) {
    asm volatile("mbarrier.arrive.expect_tx.shared::cta.b64 _, [%0], %1;" ::"r"(bar + S0), "r"(bytes) : "memory");
}
__device__ __forceinline__ bool mbar_try(uint32_t bar, uint32_t par) {
    uint32_t ok;
    asm volatile("{\n.reg .pred p;\nmbarrier.try_wait.parity.shared::cta.b64 p, [%1], %2;\nselp.u32 %0, 1, 0, p;\n}"
                 : "=r"(ok) : "r"(bar + S0), "r"(par) : "memory");
    return ok;
}
__device__ __forceinline__ bool mbar_test(uint32_t bar, uint32_t par) {
    uint32_t ok;
    asm volatile("{\n.reg .pred p;\nmbarrier.test_wait.parity.shared::cta.b64 p, [%1], %2;\nselp.u32 %0, 1, 0, p;\n}"
                 : "=r"(ok) : "r"(bar + S0), "r"(par) : "memory");
    return ok;
}
__device__ __forceinline__ void mbar_wait(uint32_t bar, uint32_t par) {
    unsigned it = 0;
#pragma unroll 1
    while (!mbar_try(bar, par) && ++it < SPIN_LIMIT) {}
}
__device__ __forceinline__ bool elect_one() {
    uint32_t p;
    asm volatile("{\n.reg .pred p;\nelect.sync _|p, 0xffffffff;\nselp.u32 %0, 1, 0, p;\n}" : "=r"(p));
    return p;
}
__device__ __forceinline__ void fence_async_smem() { asm volatile("fence.proxy.async.shared::cta;" ::: "memory"); }
__device__ __forceinline__ void fence_async_global() { asm volatile("fence.proxy.async.global;" ::: "memory"); }
__device__ __forceinline__ void fence_acquire() { asm volatile("fence.acquire.gpu;" ::: "memory"); }
__device__ __forceinline__ void bar_sync(int id, int n) { asm volatile("bar.sync %0, %1;" ::"r"(id), "r"(n) : "memory"); }
__device__ __forceinline__ void bar_arrive(int id, int n) { asm volatile("bar.arrive %0, %1;" ::"r"(id), "r"(n) : "memory"); }
__device__ __forceinline__ void bulk_g2s(uint32_t dst, const void* src, uint32_t bytes, uint32_t bar) {
    asm volatile("cp.async.bulk.shared::cluster.global.mbarrier::complete_tx::bytes [%0], [%1], %2, [%3];"
                 ::"r"(dst), "l"(src), "r"(bytes), "r"(bar) : "memory");
}
__device__ __forceinline__ void tma_x(uint32_t dst, const CUtensorMap* tm, int row, int ch, uint32_t bar) {
    asm volatile("cp.async.bulk.tensor.3d.shared::cluster.global.mbarrier::complete_tx::bytes [%0], [%1, {%2, %3, %4}], [%5];"
                 ::"r"(dst + S0), "l"(tm), "r"(0), "r"(row), "r"(ch), "r"(bar + S0) : "memory");
}
__device__ __forceinline__ uint4 ld_relaxed_v4(const void* p) {
    uint4 v;
    asm volatile("ld.relaxed.gpu.global.v4.u32 {%0,%1,%2,%3}, [%4];" : "=r"(v.x), "=r"(v.y), "=r"(v.z), "=r"(v.w) : "l"(p) : "memory");
    return v;
}
__device__ __forceinline__ unsigned ld_relaxed(const void* p) {
    unsigned v;
    asm volatile("ld.relaxed.gpu.global.u32 %0, [%1];" : "=r"(v) : "l"(p) : "memory");
    return v;
}
__device__ __forceinline__ void red_add4(float* p, float a, float b, float c, float d) {
    asm volatile("red.relaxed.gpu.global.add.v4.f32 [%0], {%1,%2,%3,%4};" ::"l"(p), "f"(a), "f"(b), "f"(c), "f"(d) : "memory");
}
__device__ __forceinline__ void sts128(uint32_t a, uint4 v) {
    asm volatile("st.shared.v4.u32 [%0], {%1,%2,%3,%4};" ::"r"(a + S0), "r"(v.x), "r"(v.y), "r"(v.z), "r"(v.w) : "memory");
}
__device__ __forceinline__ void sts128f(uint32_t a, float4 v) {
    asm volatile("st.shared.v4.f32 [%0], {%1,%2,%3,%4};" ::"r"(a + S0), "f"(v.x), "f"(v.y), "f"(v.z), "f"(v.w) : "memory");
}
__device__ __forceinline__ void sts32f(uint32_t a, float v) { asm volatile("st.shared.f32 [%0], %1;" ::"r"(a + S0), "f"(v) : "memory"); }
__device__ __forceinline__ uint4 lds128(uint32_t a) {
    uint4 v;
    asm volatile("ld.shared.v4.u32 {%0,%1,%2,%3}, [%4];" : "=r"(v.x), "=r"(v.y), "=r"(v.z), "=r"(v.w) : "r"(a + S0) : "memory");
    return v;
}
__device__ __forceinline__ float4 lds128f(uint32_t a) {
    float4 v;
    asm volatile("ld.shared.v4.f32 {%0,%1,%2,%3}, [%4];" : "=f"(v.x), "=f"(v.y), "=f"(v.z), "=f"(v.w) : "r"(a + S0) : "memory");
    return v;
}
__device__ __forceinline__ float2 lds64f(uint32_t a) {
    float2 v;
    asm volatile("ld.shared.v2.f32 {%0,%1}, [%2];" : "=f"(v.x), "=f"(v.y) : "r"(a + S0) : "memory");
    return v;
}
__device__ __forceinline__ float bf_lo(uint32_t u) { return __uint_as_float(u << 16); }
__device__ __forceinline__ float bf_hi(uint32_t u) { return __uint_as_float(u & 0xffff0000u); }
__device__ __forceinline__ uint32_t pack_bf(float lo, float hi) {
    uint32_t r;
    asm("cvt.rn.bf16x2.f32 %0, %1, %2;" : "=r"(r) : "f"(hi), "f"(lo));
    return r;
}
__device__ __forceinline__ float tanh_fast(float x) {
    float r;
    asm("tanh.approx.f32 %0, %1;" : "=f"(r) : "f"(x));
    return r;
}
__device__ __forceinline__ float silu_half(float h) { return fmaf(h, tanh_fast(h), h); }
__device__ __forceinline__ void ldsm4(uint32_t (&u)[4], uint32_t a) {
    asm volatile("ldmatrix.sync.aligned.m8n8.x4.shared.b16 {%0,%1,%2,%3}, [%4];"
                 : "=r"(u[0]), "=r"(u[1]), "=r"(u[2]), "=r"(u[3]) : "r"(a + S0) : "memory");
}
__device__ __forceinline__ void ldsm4t(uint32_t (&u)[4], uint32_t a) {
    asm volatile("ldmatrix.sync.aligned.m8n8.x4.trans.shared.b16 {%0,%1,%2,%3}, [%4];"
                 : "=r"(u[0]), "=r"(u[1]), "=r"(u[2]), "=r"(u[3]) : "r"(a + S0) : "memory");
}
__device__ __forceinline__ void stsm4(uint32_t a, uint32_t p0, uint32_t p1, uint32_t p2, uint32_t p3) {
    asm volatile("stmatrix.sync.aligned.m8n8.x4.shared.b16 [%0], {%1,%2,%3,%4};" ::"r"(a + S0), "r"(p0), "r"(p1), "r"(p2), "r"(p3) : "memory");
}
__device__ __forceinline__ void stsm4t(uint32_t a, uint32_t p0, uint32_t p1, uint32_t p2, uint32_t p3) {
    asm volatile("stmatrix.sync.aligned.m8n8.x4.trans.shared.b16 [%0], {%1,%2,%3,%4};" ::"r"(a + S0), "r"(p0), "r"(p1), "r"(p2), "r"(p3) : "memory");
}

#define R8(o) "+f"(d[o]), "+f"(d[o + 1]), "+f"(d[o + 2]), "+f"(d[o + 3]), "+f"(d[o + 4]), "+f"(d[o + 5]), "+f"(d[o + 6]), "+f"(d[o + 7])
template <uint32_t ALO, uint32_t BLO, uint64_t AHI = 8, uint64_t BHI = 48>
__device__ __forceinline__ void wgmma128(float (&d)[64]) {
    asm volatile(
        "wgmma.mma_async.sync.aligned.m64n128k16.f32.bf16.bf16 "
        "{%0,%1,%2,%3,%4,%5,%6,%7,%8,%9,%10,%11,%12,%13,%14,%15,%16,%17,%18,%19,%20,%21,%22,%23,%24,%25,%26,%27,%28,%29,%30,%31,"
        "%32,%33,%34,%35,%36,%37,%38,%39,%40,%41,%42,%43,%44,%45,%46,%47,%48,%49,%50,%51,%52,%53,%54,%55,%56,%57,%58,%59,%60,%61,%62,%63},"
        " %64, %65, 1, 1, 1, 0, 0;"
        : R8(0), R8(8), R8(16), R8(24), R8(32), R8(40), R8(48), R8(56)
        : "l"((AHI << 32) | ALO), "l"((BHI << 32) | BLO));
}
template <int S>
__device__ __forceinline__ void mma_stages(float (&d)[64], int conv, int tid, Scratch* gs) {
    constexpr uint32_t A = ((SM_ACT + S * 2 * CH_PITCH + 16) >> 4) | ((CH_PITCH >> 4) << 16);
    constexpr uint32_t B = (slot_addr(S % NS) >> 4) | (8u << 16);
    if (S == 0) {
        unsigned it = 0;
#pragma unroll 1
        while (!MMA0_WAIT(BAR(BAR_FULL), conv) && ++it < SPIN_LIMIT) {}
    }
    bool next_ok = true;
    constexpr uint32_t NEXT = S + 1 < NSTAGE ? BAR(BAR_FULL + S + 1) : BAR(BAR_EMB);
    const int npar = S + 1 < NSTAGE ? conv : 0;
    next_ok = mbar_test(NEXT, npar);
    if (S == 0 && tid == 0) TL(32 + conv * 24);
    asm volatile("wgmma.fence.sync.aligned;" ::: "memory");
    wgmma128<A, B>(d);
    wgmma128<A + 1, B + 16>(d);
    wgmma128<A + 2, B + 32>(d);
    asm volatile("wgmma.commit_group.sync.aligned;" ::: "memory");
    if (S >= LAG) {
        asm volatile("wgmma.wait_group.sync.aligned %0;" ::"n"(LAG) : "memory");
        if ((tid & 31) == 0) mbar_arrive(BAR(BAR_WEMPTY + (S + NS - LAG) % NS));
    }
    if (!next_ok) mbar_wait(NEXT, npar);
    if constexpr (S + 1 < NSTAGE) mma_stages<S + 1>(d, conv, tid, gs);
}

__device__ __forceinline__ void weight_load(uint4 (&t)[5], const __nv_bfloat16* w, int cta, int lane) {
    const char* base = reinterpret_cast<const char*>(w) + ((cta & 15) * 8 * C + (cta >> 4) * 16) * 18;
#pragma unroll
    for (int k = 0; k < 5; k++) {
        const int i = lane + 32 * k, row = (i * 57) >> 10;
        if (k < 4 || lane < 16) t[k] = __ldg(reinterpret_cast<const uint4*>(base + row * (C * 18 - 288) + i * 16));
    }
}
__device__ __forceinline__ void weight_block(uint32_t bounce, unsigned char* wt, int cta, int lane, bool readback, Scratch* gs) {
    unsigned char* dst = wt + (cta >> 4) * STAGE_BYTES + (cta & 15) * 768;
    if (lane < 16) {
        uint32_t v[36];
#pragma unroll
        for (int i = 0; i < 9; i++) {
            const uint4 q = lds128(bounce + (lane & 7) * 288 + (lane >> 3) * 144 + i * 16);
            v[4 * i] = q.x; v[4 * i + 1] = q.y; v[4 * i + 2] = q.z; v[4 * i + 3] = q.w;
        }
#pragma unroll
        for (int kyo = 0; kyo < 3; kyo++) {
#pragma unroll
            for (int kx = 0; kx < 3; kx++) {
                const int tap = ky_of(kyo) * 3 + kx;
                uint32_t o[4];
#pragma unroll
                for (int m = 0; m < 4; m++) {
                    const int i0 = 18 * m + tap, i1 = i0 + 9;
                    const uint32_t sel = ((i0 & 1) ? 0x32u : 0x10u) | ((i1 & 1) ? 0x7600u : 0x5400u);
                    o[m] = __byte_perm(v[i0 >> 1], v[i1 >> 1], sel);
                }
                *reinterpret_cast<uint4*>(dst + kyo * 8 * STAGE_BYTES + kx * 256 + lane * 16) = make_uint4(o[0], o[1], o[2], o[3]);
            }
        }
    }
    if (readback) {
        __syncwarp();
        if (lane == 0) TL(5);
        unsigned acc = 0;
        if (lane < 24) {
#pragma unroll
            for (int i = 0; i < 3; i++) acc |= ld_relaxed(dst + i * 8 * STAGE_BYTES + lane * 32);
        }
        asm volatile("{\n.reg .pred p;\nsetp.eq.u32 p, %0, 0x9e3779b9;\n@p st.shared.u32 [%1], %0;\n}" ::"r"(acc), "r"(bounce + S0) : "memory");
    }
}
__device__ __forceinline__ uint32_t act2(uint32_t u, const float4& cf) {
    return pack_bf(silu_half(fmaf(bf_lo(u), cf.x, cf.z)), silu_half(fmaf(bf_hi(u), cf.y, cf.w)));
}
__device__ __forceinline__ void norm_unit(uint32_t (&u)[4], const float4& ca, const float4& cb) {
    u[0] = act2(u[0], ca); u[1] = act2(u[1], ca); u[2] = act2(u[2], cb); u[3] = act2(u[3], cb);
}
__device__ __forceinline__ void read_stats(uint32_t gst, float (&g)[8]) {
    asm volatile("ld.volatile.shared.v4.f32 {%0,%1,%2,%3}, [%4];" : "=f"(g[0]), "=f"(g[1]), "=f"(g[2]), "=f"(g[3]) : "r"(gst + S0) : "memory");
    asm volatile("ld.volatile.shared.v4.f32 {%0,%1,%2,%3}, [%4];" : "=f"(g[4]), "=f"(g[5]), "=f"(g[6]), "=f"(g[7]) : "r"(gst + 16 + S0) : "memory");
}
template <int T>
__device__ __forceinline__ void group_coefs(uint32_t gst, float (&g)[8], float4 (&cf)[8]) {
    unsigned it = 0;
#pragma unroll 1
    while (!__all_sync(0xffffffffu, g[2 * T] != 0.f) && ++it < 8 * SPIN_LIMIT) { SPINPAUSE; read_stats(gst, g); }
    float4 &ca = cf[2 * T], &cb = cf[2 * T + 1];
    const float rs = g[2 * T], mr = g[2 * T + 1];
    ca.z = fmaf(-mr, ca.x, ca.z); ca.w = fmaf(-mr, ca.y, ca.w); ca.x *= rs; ca.y *= rs;
    cb.z = fmaf(-mr, cb.x, cb.z); cb.w = fmaf(-mr, cb.y, cb.w); cb.x *= rs; cb.y *= rs;
}
template <int FIRST, int N>
__device__ __forceinline__ void norm_block(uint32_t (&u)[4][4], float4 (&cf)[8], uint32_t act, uint32_t mask, uint32_t fbar, int lane) {
#pragma unroll
    for (int t = FIRST; t < FIRST + N; t++) {
        norm_unit(u[t], cf[2 * t], cf[2 * t + 1]);
        stsm4(act + t * 2 * KC_BYTES, u[t][0] & mask, u[t][1] & mask, u[t][2] & mask, u[t][3] & mask);
    }
    fence_async_smem();
    __syncwarp();
    if (lane < N) mbar_arrive(fbar + 16 * (FIRST + lane));
}
__device__ __forceinline__ void publish(uint32_t bar, int lane) {
    fence_async_smem();
    __syncwarp();
    if (lane == 0) mbar_arrive(bar);
}
template <int T>
__device__ __forceinline__ void next_unit(uint32_t (&u)[4][4], float4 (&cf)[8], uint32_t gst, float (&g)[8], uint32_t act, uint32_t fbar, int lane) {
    const bool have = __all_sync(0xffffffffu, g[2 * T] != 0.f);
    if (!have) publish(fbar + 16 * (T - 1), lane);
    group_coefs<T>(gst, g, cf);
    norm_unit(u[T], cf[2 * T], cf[2 * T + 1]);
    if (have) publish(fbar + 16 * (T - 1), lane);
    stsm4(act + T * 2 * KC_BYTES, u[T][0], u[T][1], u[T][2], u[T][3]);
}
__device__ __forceinline__ void stat_mma(float (&c)[4], uint32_t p, uint32_t q) {
    asm("mma.sync.aligned.m16n8k16.row.col.f32.bf16.bf16.f32 {%0,%1,%2,%3}, {%4,%5,%6,%5}, {%4,%6}, {%0,%1,%2,%3};"
        : "+f"(c[0]), "+f"(c[1]), "+f"(c[2]), "+f"(c[3]) : "r"(p), "r"(0x3f803f80u), "r"(q));
}
__device__ __forceinline__ void stat_store(const float (&c)[4], uint32_t dst, int lane) {
    const int g = lane >> 2, t = lane & 3;
    if (t == (g >> 1)) sts32f(dst + g * 4, (g & 1) ? c[1] : c[0]);
    if (g == 7) sts32f(dst + 32 + t * 4, c[2] + c[3]);
}
__device__ __forceinline__ float sum4(float4 v) { return (v.x + v.y) + (v.z + v.w); }
__device__ __forceinline__ void stat_publish(uint32_t src, float* acc, int lane, bool real) {
    const uint32_t a = src + (lane & 15) * 48;
    float q = sum4(lds128f(a)) + sum4(lds128f(a + 16)), sm = sum4(lds128f(a + 32));
    q += __shfl_xor_sync(0xffffffffu, q, 1); sm += __shfl_xor_sync(0xffffffffu, sm, 1);
    q += __shfl_xor_sync(0xffffffffu, q, 2); sm += __shfl_xor_sync(0xffffffffu, sm, 2);
    if (real && (lane & 19) == 0) red_add4(acc + lane, 1.f, sm, q, 1.f);
}
__device__ __forceinline__ void fence_acc(float (&d)[64]) {
#pragma unroll
    for (int i = 0; i < 64; i++) asm volatile("" : "+f"(d[i])::"memory");
}
__device__ __forceinline__ void ld_unit(uint32_t (&u)[4], const uint4* p) {
    asm volatile("ld.relaxed.gpu.global.v4.u32 {%0,%1,%2,%3}, [%4];" : "=r"(u[0]), "=r"(u[1]), "=r"(u[2]), "=r"(u[3]) : "l"(p) : "memory");
}

__device__ __noinline__ void side_jobs(const __nv_bfloat16* __restrict__ t_emb, const __nv_bfloat16* __restrict__ w_emb,
                                       const __nv_bfloat16* __restrict__ w2, Scratch* __restrict__ gs, unsigned clk0) {
    const int tid = threadIdx.x, warp = tid >> 5, lane = tid & 31, j = blockIdx.x;
    float tv = 0.f;
    if (lane < 24) tv = __bfloat162float(t_emb[(lane / 12) * E + j * 192 + warp * 12 + lane % 12]);
    if (tid == 0) {
        mbar_init(BAR(0), 1);
        mbar_expect(BAR(0), 192 * C * 2);
        fence_async_smem();
        while (clock32() - clk0 < W2DELAY) {}
#pragma unroll
        for (int i = 0; i < 4; i++) bulk_g2s(S0 + SM_W + i * 12288, w_emb + (j * 192 + i * 48) * C, 12288, S0 + BAR(0));
    }
    if (j == 0 && tid < 32) gs->acc2[(tid >> 4) * LS + (tid & 15)] = 0.f;
    const float sv = silu_half(0.5f * tv);
    __syncthreads();
    mbar_wait(BAR(0), 0);
    float acc[8] = {0.f, 0.f, 0.f, 0.f, 0.f, 0.f, 0.f, 0.f};
#pragma unroll
    for (int i = 0; i < 12; i++) {
        const float2 wq = lds64f(SM_W + (warp * 12 + i) * 256 + lane * 8);
        const uint32_t wx = __float_as_uint(wq.x), wy = __float_as_uint(wq.y);
#pragma unroll
        for (int bb = 0; bb < 2; bb++) {
            const float sx = __shfl_sync(0xffffffffu, sv, bb * 12 + i);
            acc[4 * bb + 0] = fmaf(sx, bf_lo(wx), acc[4 * bb + 0]); acc[4 * bb + 1] = fmaf(sx, bf_hi(wx), acc[4 * bb + 1]);
            acc[4 * bb + 2] = fmaf(sx, bf_lo(wy), acc[4 * bb + 2]); acc[4 * bb + 3] = fmaf(sx, bf_hi(wy), acc[4 * bb + 3]);
        }
    }
    sts128f(SM_ACT + warp * 1024 + lane * 16, make_float4(acc[0], acc[1], acc[2], acc[3]));
    sts128f(SM_ACT + warp * 1024 + 512 + lane * 16, make_float4(acc[4], acc[5], acc[6], acc[7]));
    __syncthreads();
    if (tid < 128) {
        float2 sum = make_float2(0.f, 0.f);
#pragma unroll
        for (int w = 0; w < 16; w++) { const float2 p = lds64f(SM_ACT + w * 1024 + tid * 8); sum.x += p.x; sum.y += p.y; }
        *reinterpret_cast<float2*>(&gs->emb[j * NB * C + tid * 2]) = sum;
        bar_sync(1, 128);
        if (tid < 2) asm volatile("red.release.gpu.global.add.u32 [%0], 1;" ::"l"(&gs->wcnt[(2 * NB + tid) * LS]) : "memory");
    }
}

__global__ void __cluster_dims__(2, 1, 1) __launch_bounds__(NTHREADS, 1)
resblock_kernel(const __nv_bfloat16* __restrict__ w1,
                const __nv_bfloat16* __restrict__ t_emb, const __nv_bfloat16* __restrict__ g1,
                const __nv_bfloat16* __restrict__ be1, const __nv_bfloat16* __restrict__ w_emb,
                const __nv_bfloat16* __restrict__ g2, const __nv_bfloat16* __restrict__ be2,
                const __nv_bfloat16* __restrict__ w2, __nv_bfloat16* __restrict__ out, Scratch* __restrict__ gs,
                const __grid_constant__ CUtensorMap xmap) {
    const unsigned clk0 = clock32();
    if (threadIdx.x == 480 && blockIdx.x >= NXTRA) TLG(1);
    const int tid = threadIdx.x, lane = tid & 31;
    const int cta = blockIdx.x - NXTRA, b = cta >> 6, r = cta & 63;
    uint4 v[5];
    if (tid < 32) weight_load(v, w1, cta & (NCTA - 1), lane);
    const int warp = __shfl_sync(0xffffffffu, tid >> 5, 0);
    if (cta < 0) { side_jobs(t_emb, w_emb, w2, gs, clk0); return; }

    const int seg = lane & 7;
    if (warp != 3) asm volatile("barrier.cluster.arrive.relaxed.aligned;" ::: "memory");
    const bool has_outer = (r != 0) && (r != HW - 1);
    if (warp == 1 || warp == 2 || warp == 4 || warp == 5) {
        const int g = warp < 3 ? warp - 1 : 7 - warp;
        if (elect_one()) {
            asm volatile("prefetch.tensormap [%0];" ::"l"(&xmap) : "memory");
            mbar_init(BAR(BAR_X) + 8 * g, 1);
            if (g == 3) mbar_init(BAR(BAR_X + 4), 1);
            mbar_expect(BAR(BAR_X) + 8 * g, 4096);
            fence_async_smem();
            while (clock32() - clk0 < XDELAY + (g >> 1) * XSTAG + (g & 1) * XSTAG2) {}
            tma_x(SM_XOWN + g * 4096, &xmap, r, b * C + g * 32, BAR(BAR_X) + 8 * g);
            if (g == 3 && has_outer) {
                mbar_expect(BAR(BAR_X + 4), 16384);
#pragma unroll
                for (int i = 0; i < 4; i++) tma_x(SM_XOUT + i * 4096, &xmap, r + ((r & 1) ? 1 : -1), b * C + i * 32, BAR(BAR_X + 4));
            }
        }
        __syncwarp();
        bar_arrive(4, 256 + 64 + 128);
        mbar_wait(BAR(BAR_X) + 8 * g, 0);
        if (lane == 0) TL(70 + g);
        float c[8][4];
#pragma unroll
        for (int k = 0; k < 8; k++) {
            const uint4 q = lds128(SM_XOWN + g * 4096 + k * 512 + lane * 16);
            c[k][0] = c[k][1] = c[k][2] = c[k][3] = 0.f;
            stat_mma(c[k], q.x, q.y); stat_mma(c[k], q.z, q.w);
        }
#pragma unroll
        for (int i = 0; i < 4; i++) c[0][i] = ((c[0][i] + c[1][i]) + (c[2][i] + c[3][i])) + ((c[4][i] + c[5][i]) + (c[6][i] + c[7][i]));
        if (lane == 0 && g == 0) { if (c[0][0] == 1.2345f) sts32f(SM_RED, 0.f); TL(92); }
        stat_store(c[0], SM_RED + g * 48, lane);
        __syncwarp();
        if (lane == 0) {
            const uint32_t a = SM_RED + g * 48;
            red_add4(&gs->acc1[b * 4 * LS + g * GS1], 1.f, sum4(lds128f(a + 32)), sum4(lds128f(a)) + sum4(lds128f(a + 16)), 1.f);
            TL(74 + g);
        }
    }
    if (warp == 0 || warp == 4) {
        const int k = warp >> 2;
        if (k == 0) {
#pragma unroll
            for (int i = 0; i < 5; i++)
                if (i < 4 || lane < 16) sts128(SM_BNC + (lane + 32 * i) * 16, v[i]);
            if (lane == 0) TL(81);
            __syncwarp();
        } else {
            bar_sync(6, 64);
            mbar_wait(BAR(BAR_W2), 0);
        }
        weight_block(SM_BNC + k * 2304, gs->wt + k * NSTAGE * STAGE_BYTES, cta, lane, k == 0, gs);
        __syncwarp();
        if (lane == 0) TL(k ? 13 : 4);
        if (k == 0 && lane < 2) asm volatile("red.relaxed.gpu.global.add.u32 [%0], 1;" ::"l"(&gs->wcnt[lane * LS + (cta >> 4)]) : "memory");
    }

    if (warp >= 8) {
        const int nw = warp - 8;
        bar_sync(4, 256 + 64 + 128);
        const int par = nw >> 2, wq = nw & 3;
        const uint32_t act_off = SM_ACT + (par * 2 + (lane >> 4)) * CH_PITCH + (2 + wq * 16 + (lane & 15)) * 16;
        const uint32_t stg_off = (par * 16 + (lane >> 4) * 8 + (lane & 7)) * 128 + (((2 * wq + ((lane >> 3) & 1)) ^ (lane & 7)) << 4);
        const uint32_t cfa = SM_COEF + par * 128 + (lane & 3) * 16;
        const uint32_t fbar = BAR(BAR_FULL) + 8 * par;
        uint4* inbox = gs->box + cta * 1024 + nw * 32 + lane;
#pragma unroll 1
        for (int conv = 0; conv < 2; conv++) {
            uint32_t u[4][4], w[4][4];
            float4 cf[8];
            if (conv == 0) {
#pragma unroll
                for (int i = 0; i < 4; i++) { mbar_wait(BAR(BAR_X + i), 0); ldsm4t(u[i], SM_XOWN + stg_off + i * 4096); }
            } else {
                mbar_wait(BAR(BAR_HW), 0);
#pragma unroll
                for (int i = 0; i < 4; i++) ldsm4(u[i], act_off + i * 2 * KC_BYTES);
            }
#pragma unroll
            for (int i = 0; i < 8; i++) cf[i] = lds128f(cfa + conv * 1024 + (i >> 1) * 256 + (i & 1) * 64);
            const uint32_t gst = SM_GST + conv * 32;
            float gv[8];
            read_stats(gst, gv);
            group_coefs<0>(gst, gv, cf);
            if (tid == 256) TL(22 + conv * 4);
            if (par) { const unsigned c1 = clock32(); while (clock32() - c1 < PDELAY) {} }
            norm_block<0, 1>(u, cf, act_off, ~0u, fbar, lane);
            if (tid == 256) TL(8 + conv * 8);
            group_coefs<1>(gst, gv, cf);
            norm_unit(u[1], cf[2], cf[3]);
            stsm4(act_off + 2 * KC_BYTES, u[1][0], u[1][1], u[1][2], u[1][3]);
            next_unit<2>(u, cf, gst, gv, act_off, fbar, lane);
            next_unit<3>(u, cf, gst, gv, act_off, fbar, lane);
            publish(fbar + 48, lane);
            if (tid == 256) TL(84 + conv);
            if (has_outer) {
                mbar_wait(BAR(BAR_X + 4), conv);
                if (conv == 0) {
#pragma unroll
                    for (int i = 0; i < 4; i++) ldsm4t(w[i], SM_XOUT + stg_off + i * 4096);
                } else {
#pragma unroll
                    for (int i = 0; i < 4; i++) {
                        const uint4 q = lds128(SM_XOWN + (tid - 256) * 16 + i * 4096);
                        w[i][0] = q.x; w[i][1] = q.y; w[i][2] = q.z; w[i][3] = q.w;
                    }
                    unsigned it = 0;
                    while (true) {
                        bool ok = true;
#pragma unroll
                        for (int i = 0; i < 16; i++) ok = ok && w[i >> 2][i & 3] != 0;
                        if (__all_sync(0xffffffffu, ok) || ++it > SPIN_LIMIT) break;
#pragma unroll
                        for (int i = 0; i < 4; i++) ld_unit(w[i], inbox + i * 256);
                    }
#pragma unroll
                    for (int i = 0; i < 16; i++) w[i >> 2][i & 3] = ~w[i >> 2][i & 3];
                }
            }
            if (conv == 0) {
                bar_sync(3, 256);
                if (nw == 0) sts128(SM_ACT + 2 * ROW_BYTES + (lane >> 1) * CH_PITCH + (lane & 1) * 16, make_uint4(0, 0, 0, 0));
            }
            if (tid == 256) TL(24 + conv * 4);
            norm_block<0, 2>(w, cf, act_off + 2 * ROW_BYTES, has_outer ? ~0u : 0u, fbar + 128, lane);
            if (tid == 256) TL(88 + conv);
            norm_block<2, 2>(w, cf, act_off + 2 * ROW_BYTES, has_outer ? ~0u : 0u, fbar + 128, lane);
            if (tid == 256) TL(23 + conv * 4);
        }
        if (has_outer) {
            mbar_wait(BAR(BAR_FULL + NSTAGE - 1), 1);
#pragma unroll
            for (int i = 0; i < 4; i++) inbox[i * 256] = make_uint4(0, 0, 0, 0);
        }
    } else if (warp < 4) {
        const int wq = warp;
        if (wq == 3) {
            if (elect_one()) {
#pragma unroll
                for (int i = 0; i < NSTAGE; i++) mbar_init(BAR(BAR_FULL + i), (i >> 3) == 1 ? 1 : 5);
#pragma unroll
                for (int i = 0; i < NS + 2; i++) mbar_init(BAR(BAR_WEMPTY + i), 4);
#pragma unroll
                for (int i = BAR_STATS; i < BAR_X; i++) mbar_init(BAR(i), i == BAR_EMB ? 3 : 1);
                asm volatile("fence.mbarrier_init.release.cluster;" ::: "memory");
            }
            __syncwarp();
            fence_async_smem();
            bar_arrive(0, 96);
            bar_arrive(5, 96);
            bar_arrive(4, 256 + 64 + 128);
            const uint4 z = make_uint4(0, 0, 0, 0);
#pragma unroll
            for (int i = 0; i < 2; i++) sts128(SM_ACT + (i * 16 + (lane >> 1)) * CH_PITCH + (lane & 1) * 16, z);
            if (lane < 4) sts128(SM_ACT + (2 + (lane >> 1)) * ROW_BYTES + (lane & 1) * 16, z);
            if (lane < 16) sts128(SM_ONES + lane * 16, make_uint4(lane < 8 ? 0x3f803f80u : 0u, 0, 0, 0));
            fence_async_smem();
            asm volatile("barrier.cluster.arrive.release.aligned;" ::: "memory");
            bar_arrive(6, 64);
            if (elect_one()) {
                mbar_expect(BAR(BAR_W2), 2304);
                while (clock32() - clk0 < W2DELAY) {}
                const char* base = reinterpret_cast<const char*>(w2) + ((cta & 15) * 8 * C + (cta >> 4) * 16) * 18;
#pragma unroll 1
                for (int i = 0; i < 8; i++) bulk_g2s(S0 + SM_BNC + 2304 + i * 288, base + i * (C * 18), 288, S0 + BAR(BAR_W2));
            }
            __syncwarp();
        }
        bar_sync(2, 128);

        float d[64];
#pragma unroll
        for (int i = 0; i < 64; i++) d[i] = 0.f;
#pragma unroll 1
        for (int conv = 0; conv < 2; conv++) {
            fence_acc(d);
            mma_stages<0>(d, conv, tid, gs);
            if (conv == 0) {
                asm volatile("wgmma.fence.sync.aligned;" ::: "memory");
                wgmma128<(SM_ONES >> 4) | (8u << 16), (SM_EMB >> 4), 0, 8>(d);
                asm volatile("wgmma.commit_group.sync.aligned;" ::: "memory");
            }
            asm volatile("wgmma.wait_group.sync.aligned 0;" ::: "memory");
            fence_acc(d);
            if (tid == 0) TL(10 + conv * 8);
            if (conv == 1) break;

            uint32_t hp[32];
#pragma unroll
            for (int g = 0; g < 4; g++) {
                float c[4] = {0.f, 0.f, 0.f, 0.f};
#pragma unroll
                for (int i = 0; i < 8; i++) hp[8 * g + i] = pack_bf(d[16 * g + 2 * i], d[16 * g + 2 * i + 1]);
#pragma unroll
                for (int i = 0; i < 4; i++) stat_mma(c, hp[8 * g + 2 * i], hp[8 * g + 2 * i + 1]);
                stat_store(c, SM_RED + (g * 4 + wq) * 48, lane);
            }
            bar_sync(2, 128);
            if (wq == 0) stat_publish(SM_RED, &gs->acc2[b * LS], lane, true);
            if (tid == 0) TL(11);
            const uint32_t hbase = SM_ACT + (lane >> 4) * CH_PITCH + (2 + wq * 16 + (lane & 15)) * 16;
#pragma unroll
            for (int kc = 0; kc < 8; kc++) stsm4(hbase + kc * 2 * CH_PITCH, hp[4 * kc], hp[4 * kc + 1], hp[4 * kc + 2], hp[4 * kc + 3]);
            __syncwarp();
            if (lane == 0) mbar_arrive(BAR(BAR_HW));
            if (lane < LAG) mbar_arrive(BAR(BAR_WEMPTY + (NSTAGE - LAG) % NS) + 8 * lane);
            if (has_outer) {
                uint4* outbox = gs->box + (cta + ((r & 1) ? 1 : -1)) * 1024 + tid;
#pragma unroll
                for (int kc = 0; kc < 8; kc++) outbox[kc * 128] = make_uint4(~hp[4 * kc], ~hp[4 * kc + 1], ~hp[4 * kc + 2], ~hp[4 * kc + 3]);
            }
            if (tid == 0) TL(12);
            const uint32_t xbase = SM_XOWN + ((lane >> 4) * 8 + (lane & 7)) * 128 + (((2 * wq + ((lane >> 3) & 1)) ^ (lane & 7)) << 4);
#pragma unroll
            for (int kc = 0; kc < 8; kc++) {
                uint32_t p[4];
                ldsm4t(p, xbase + kc * 2048);
#pragma unroll
                for (int i = 0; i < 4; i++) { d[8 * kc + 2 * i] = bf_lo(p[i]); d[8 * kc + 2 * i + 1] = bf_hi(p[i]); }
            }
            fence_async_smem();
            __syncwarp();
            if (lane == 0) mbar_arrive(BAR(BAR_XFREE));
        }
        {
            const uint32_t obase = slot_addr(0) + ((lane >> 4) * 8 + (lane & 7)) * OUT_PITCH + (wq * 16 + ((lane >> 3) & 1) * 8) * 2;
#pragma unroll
            for (int kc = 0; kc < 8; kc++) {
                stsm4t(obase + kc * 16 * OUT_PITCH, pack_bf(d[8 * kc + 0], d[8 * kc + 1]), pack_bf(d[8 * kc + 2], d[8 * kc + 3]),
                       pack_bf(d[8 * kc + 4], d[8 * kc + 5]), pack_bf(d[8 * kc + 6], d[8 * kc + 7]));
            }
            bar_sync(2, 128);
            const int oc0 = tid >> 3;
            __nv_bfloat16* dst = out + ((size_t)(b * C + oc0) * HW + r) * HW + seg * 8;
#pragma unroll
            for (int i = 0; i < 8; i++)
                *reinterpret_cast<uint4*>(dst + (size_t)i * 16 * HW * HW) = lds128(slot_addr(0) + (oc0 + 16 * i) * OUT_PITCH + seg * 16);
            if (tid == 0) { TL(20); TLG(21); }
        }
    } else if (warp < 6) {
        bar_sync(5, 96);
        if (warp == 5) {
            asm volatile("barrier.cluster.wait.acquire.aligned;" ::: "memory");
            const uint32_t peer = (r & 1) ^ 1;
            const uint32_t self0 = mapa(0, r & 1), peer0 = mapa(0, peer);
#pragma unroll 1
            for (int conv = 0; conv < 2; conv++) {
#pragma unroll 1
                for (int kc = 0; kc < 8; kc++) {
                    mbar_wait(BAR(BAR_FULL) + 8 * kc, conv);
                    if (elect_one())
                        asm volatile("cp.async.bulk.shared::cluster.shared::cta.mbarrier::complete_tx::bytes [%0], [%1], %2, [%3];"
                                     ::"r"(peer0 + SM_ACT + ROW_BYTES + kc * KC_BYTES), "r"(self0 + SM_ACT + kc * KC_BYTES), "r"(KC_BYTES),
                                       "r"(peer0 + BAR(BAR_FULL + 8) + 8 * kc) : "memory");
                }
                if (lane == 0) TL(86 + conv);
#pragma unroll 1
                for (int kc = 0; kc < 8; kc++) mbar_wait(BAR(BAR_FULL + 8) + 8 * kc, conv);
                if (lane == 0)
                    asm volatile("mbarrier.arrive.release.cluster.shared::cluster.b64 _, [%0];" ::"r"(peer0 + (conv ? BAR(BAR_ACK) : BAR(BAR_EMB))) : "memory");
            }
            mbar_wait(BAR(BAR_ACK), 0);
        } else {
            if (lane < 2) asm volatile("red.release.gpu.global.add.u32 [%0], 1;" ::"l"(&gs->wcnt[(NB + lane) * LS]) : "memory");
            if (lane == 0) TL(14);
            mbar_wait(BAR(BAR_STATS), 0);
            unsigned it = 0;
            while (ld_relaxed(&gs->wcnt[(2 * NB + b) * LS]) < (unsigned)NXTRA && ++it < SPIN_LIMIT) __nanosleep(100);
            fence_acquire();
            float ev[4] = {0.f, 0.f, 0.f, 0.f};
#pragma unroll
            for (int j = 0; j < NXTRA; j++) {
                const uint4 ef = ld_relaxed_v4(&gs->emb[(j * NB + b) * C + lane * 4]);
                ev[0] += __uint_as_float(ef.x); ev[1] += __uint_as_float(ef.y); ev[2] += __uint_as_float(ef.z); ev[3] += __uint_as_float(ef.w);
            }
#pragma unroll
            for (int i = 0; i < 4; i++) {
                const float hi = bf_lo(pack_bf(ev[i], 0.f));
                sts128(SM_EMB + (lane * 4 + i) * 16, make_uint4(pack_bf(hi, ev[i] - hi), 0, 0, 0));
            }
            fence_async_smem();
            __syncwarp();
            if (lane == 0) { mbar_arrive(BAR(BAR_EMB)); TL(19); }
        }
    } else if (warp == 6) {
        bar_sync(0, 96);
        const uint32_t ebytes = STAGE_BYTES + ((lane >> 3) == 1 ? KC_BYTES : 0);
        if (lane < NSTAGE) mbar_expect(BAR(BAR_FULL) + 8 * lane, ebytes);
        const int swap = (r & 1) ? 0 : 8 * STAGE_BYTES;
        unsigned it = 0;
        {
            int g = 0;
#pragma unroll 1
            while (g < NS) {
                unsigned ready = __ballot_sync(0xffffffffu, ld_relaxed(&gs->wcnt[b * LS + (lane & 7)]) >= 16u) >> g;
                if (++it > SPIN_LIMIT) ready = ~0u;
                if (!(ready & 1)) continue;
                fence_acquire();
                fence_async_global();
                if (lane == 0) TL(g ? 3 : 6);
#pragma unroll 1
                for (; (ready & 1) && g < NS; g++, ready >>= 1)
                    if (elect_one())
                        bulk_g2s(S0 + SM_W + g * STAGE_BYTES, gs->wt + g * STAGE_BYTES + (g >= 8 ? swap : 0), STAGE_BYTES, S0 + BAR(BAR_FULL) + 8 * g);
            }
        }
#pragma unroll 1
        for (int q = 3; q < 12; q++) {
            const int conv = q >= 6, qs = conv ? q - 6 : q, sl = q % 3;
            const unsigned char* wsrc = gs->wt + q * 4 * STAGE_BYTES + (qs < 2 ? 0 : (qs < 4 ? swap : -swap));
            const uint32_t par = (q / 3 - 1) & 1;
            if (q == 6) {
                it = 0;
                while (ld_relaxed(&gs->wcnt[(NB + b) * LS]) < (unsigned)NCTA && ++it < SPIN_LIMIT) {}
                fence_acquire();
                fence_async_global();
                if (lane == 0) { mbar_arrive(BAR(BAR_EMB)); TL(2); }
            }
#pragma unroll
            for (int i = 0; i < 4; i++) {
                mbar_wait(BAR(BAR_WEMPTY + i) + 32 * sl, par);
                if (i == 0 && (q == 6 || q == 9)) {
                    if ((lane >= NS) == (q == 9) && lane < NSTAGE) mbar_expect(BAR(BAR_FULL) + 8 * lane, ebytes);
                    __syncwarp();
                }
                if (elect_one())
                    bulk_g2s(S0 + SM_W + (sl * 4 + i) * STAGE_BYTES, wsrc + i * STAGE_BYTES, STAGE_BYTES, S0 + BAR(BAR_FULL + i) + 32 * qs);
            }
        }
    } else {
        const uint2 ga1 = __ldg(reinterpret_cast<const uint2*>(g1) + lane), bt1 = __ldg(reinterpret_cast<const uint2*>(be1) + lane);
        const uint2 ga2 = __ldg(reinterpret_cast<const uint2*>(g2) + lane), bt2 = __ldg(reinterpret_cast<const uint2*>(be2) + lane);
        if (lane < 8) sts128(SM_GST + lane * 16, make_uint4(0, 0, 0, 0));
        sts128f(SM_COEF + lane * 32, make_float4(0.5f * bf_lo(ga1.x), 0.5f * bf_hi(ga1.x), 0.5f * bf_lo(bt1.x), 0.5f * bf_hi(bt1.x)));
        sts128f(SM_COEF + lane * 32 + 16, make_float4(0.5f * bf_lo(ga1.y), 0.5f * bf_hi(ga1.y), 0.5f * bf_lo(bt1.y), 0.5f * bf_hi(bt1.y)));
        sts128f(SM_COEF + 1024 + lane * 32, make_float4(0.5f * bf_lo(ga2.x), 0.5f * bf_hi(ga2.x), 0.5f * bf_lo(bt2.x), 0.5f * bf_hi(bt2.x)));
        sts128f(SM_COEF + 1024 + lane * 32 + 16, make_float4(0.5f * bf_lo(ga2.y), 0.5f * bf_hi(ga2.y), 0.5f * bf_lo(bt2.y), 0.5f * bf_hi(bt2.y)));
        bar_arrive(4, 256 + 64 + 128);
        bar_sync(0, 96);
#pragma unroll 1
        for (int conv = 0; conv < 2; conv++) {
            if (conv == 1) {
                mbar_wait(BAR(BAR_HW), 0);
                const unsigned c1 = clock32();
                while (clock32() - c1 < PD2) {}
            } else {
                while (clock32() - clk0 < PD) {}
            }
            const float* asrc = conv ? &gs->acc2[b * LS + (lane & 3) * 4] : &gs->acc1[b * 4 * LS + (lane & 3) * GS1];
            unsigned it = 0;
            uint4 fq[NPOLL];
#pragma unroll
            for (int i = 0; i < NPOLL; i++) {
                fq[i] = ld_relaxed_v4(asrc);
                if (i + 1 < NPOLL) { const unsigned c1 = clock32(); while (clock32() - c1 < 450 / NPOLL) {} }
            }
            bool all = false;
#pragma unroll 1
            while (!all) {
#pragma unroll
                for (int i = 0; i < NPOLL; i++) {
                    const uint4 f = fq[i];
                    const bool ok = ((f.x == 0x42800000u) & (f.w == 0x42800000u)) || it > SPIN_LIMIT;
                    if (ok && lane < 4) {
                        const float inv_n = 1.0f / (32.0f * HW * HW);
                        const float mean = __uint_as_float(f.y) * inv_n;
                        const float rs = rsqrtf(fmaxf(fmaf(-mean, mean, __uint_as_float(f.z) * inv_n), 0.f) + 1e-5f);
                        asm volatile("st.shared.v2.f32 [%0], {%1,%2};" ::"r"(S0 + SM_GST + conv * 32 + lane * 8), "f"(rs == 0.f ? 1e-38f : rs), "f"(mean * rs) : "memory");
                    }
                    if (__all_sync(0xffffffffu, ok)) { all = true; break; }
                    fq[i] = ld_relaxed_v4(asrc);
                }
                it++;
            }
            if (lane == 0) { mbar_arrive(BAR(BAR_STATS)); TL(7 + conv * 8); }
        }
        mbar_wait(BAR(BAR_XFREE), 0);
        if (has_outer && elect_one()) {
            mbar_expect(BAR(BAR_X + 4), 16384);
            bulk_g2s(S0 + SM_XOWN, gs->box + cta * 1024, 16384, S0 + BAR(BAR_X + 4));
        }
        if (r == 0) {
            if (lane < 16) gs->acc1[b * 4 * LS + (lane >> 2) * GS1 + (lane & 3)] = 0.f;
            if (lane < 24) gs->wcnt[((lane >> 3) * NB + b) * LS + (lane & 7)] = 0;
        }
    }
}

}

extern "C" void kernel_launch(void* const* d_in, const int* in_sizes, int n_in, void* d_out, int out_size) {
    (void)in_sizes; (void)n_in; (void)out_size;
    typedef CUresult (*EncodeFn)(CUtensorMap*, CUtensorMapDataType, cuuint32_t, void*, const cuuint64_t*, const cuuint64_t*,
                                 const cuuint32_t*, const cuuint32_t*, CUtensorMapInterleave, CUtensorMapSwizzle,
                                 CUtensorMapL2promotion, CUtensorMapFloatOOBfill);
    static Scratch* gs = nullptr;
    static EncodeFn encode = nullptr;
    if (!gs) {
        cudaFuncSetAttribute(resblock_kernel, cudaFuncAttributeMaxDynamicSharedMemorySize, SM_TOTAL);
        cudaGetSymbolAddress((void**)&gs, g_scratch);
        cudaDriverEntryPointQueryResult qr;
        cudaGetDriverEntryPoint("cuTensorMapEncodeTiled", (void**)&encode, cudaEnableDefault, &qr);
    }
    CUtensorMap xmap;
    const cuuint64_t dims[3] = {HW, HW, NB * C}, strides[2] = {HW * 2, HW * HW * 2};
    const cuuint32_t box[3] = {HW, 1, 32}, es[3] = {1, 1, 1};
    encode(&xmap, CU_TENSOR_MAP_DATA_TYPE_BFLOAT16, 3, d_in[0], dims, strides, box, es, CU_TENSOR_MAP_INTERLEAVE_NONE,
           CU_TENSOR_MAP_SWIZZLE_128B, CU_TENSOR_MAP_L2_PROMOTION_NONE, CU_TENSOR_MAP_FLOAT_OOB_FILL_NONE);
    resblock_kernel<<<NCTA + NXTRA, NTHREADS, SM_TOTAL>>>(
        (const __nv_bfloat16*)d_in[4], (const __nv_bfloat16*)d_in[1],
        (const __nv_bfloat16*)d_in[2], (const __nv_bfloat16*)d_in[3], (const __nv_bfloat16*)d_in[5],
        (const __nv_bfloat16*)d_in[6], (const __nv_bfloat16*)d_in[7], (const __nv_bfloat16*)d_in[8],
        (__nv_bfloat16*)d_out, gs, xmap);
}
```

```cpp
#include <cuda_runtime.h>
#include <cuda.h>
#include <cuda_bf16.h>
#include <stdint.h>

namespace {

constexpr int C = 128, HW = 64, NB = 2, E = 768;
constexpr int NCTA = NB * HW;
constexpr int NXTRA = 4;
constexpr int NTHREADS = 16 * 32;
constexpr int CH_PITCH = 66 * 16;
constexpr int ROW_BYTES = 16 * CH_PITCH;
constexpr int STEP_BYTES = 4096;
constexpr int STAGE_BYTES = 3 * STEP_BYTES;
constexpr int NSTAGE = 24;
constexpr int KC_BYTES = 2 * CH_PITCH;
constexpr int NS = 12;
constexpr int LAG = 1;
#define XDELAY 400
#define HDELAY 600
#define SEQ 0
#define MMA0_WAIT mbar_try
#define SPINPAUSE
#define NPOLL 1
#define PD2 0
#define PDELAY 60
#define RB 1
#define XSTAG2 400
#define XSTAG 800
#define HSEND 0
#define W2DELAY 1400

constexpr uint32_t SMEM_BASE = 0x400;
constexpr uint32_t SM_XOWN = SMEM_BASE;
constexpr uint32_t SM_ACT = SM_XOWN + 16384 + 512;
constexpr uint32_t SM_XOUT = SM_ACT + 2 * ROW_BYTES + 512;
static_assert(SM_XOUT % 1024 == 0, "swizzle atom alignment");
constexpr uint32_t SM_W = SM_ACT + 3 * ROW_BYTES + 128;
__host__ __device__ constexpr uint32_t slot_addr(int slot) { return SM_W + slot * STAGE_BYTES; }
constexpr uint32_t SM_COEF = SM_W + NS * STAGE_BYTES;
constexpr uint32_t SM_GST = SM_COEF + 2048;
constexpr uint32_t SM_EMB = SM_GST + 128;
constexpr uint32_t SM_ONES = SM_EMB + 2048;
constexpr uint32_t SM_RED = SM_ONES + 256;
constexpr uint32_t SM_BNC = SM_RED + 1280;
constexpr uint32_t SM_BAR = SM_BNC + 2 * 2304;
constexpr int BAR_FULL = 0, BAR_WEMPTY = NSTAGE, BAR_HW = BAR_WEMPTY + NS, BAR_XFREE = BAR_HW + 1, BAR_STATS = BAR_XFREE + 1,
              BAR_EMB = BAR_STATS + 1, BAR_ACK = BAR_EMB + 1, BAR_W2 = BAR_ACK + 1, BAR_X = BAR_W2 + 1  , NBAR = BAR_X + 5;
constexpr int SM_TOTAL = SM_BAR + NBAR * 8 - SMEM_BASE;
static_assert(SM_TOTAL <= 232448, "smem");
static_assert(NBAR <= 96, "barrier init");
constexpr int OUT_PITCH = 144;
__host__ __device__ constexpr uint32_t BAR(int i) { return SM_BAR + 8 * i; }
__host__ __device__ constexpr int ky_of(int kyo) { return kyo == 0 ? 1 : (kyo == 1 ? 0 : 2); }

constexpr unsigned SPIN_LIMIT = 1u << 16;

#define LS 1056
#define GS1 4
#define PD 0
struct Scratch {
    float acc1[NB * 4 * LS];
    float acc2[NB * LS];
    unsigned wcnt[3 * NB * LS];
    float emb[NXTRA * NB * C];
    unsigned char wt[2 * NSTAGE * STAGE_BYTES];
    uint4 box[NCTA * 1024];
};
__device__ __align__(1024) Scratch g_scratch;
#define TL(i) do {} while (0)
#define TLG(i) do {} while (0)

__device__ __forceinline__ unsigned clock32() { unsigned c; asm volatile("mov.u32 %0, %%clock;" : "=r"(c)); return c; }
__device__ __forceinline__ uint32_t mapa(uint32_t a, uint32_t rank) {
    uint32_t d;
    asm("mapa.shared::cluster.u32 %0, %1, %2;" : "=r"(d) : "r"(a), "r"(rank));
    return d;
}
#define S0 mapa(0, blockIdx.x & 1)
__device__ __forceinline__ void mbar_init(uint32_t bar, int cnt) {
    asm volatile("mbarrier.init.shared::cta.b64 [%0], %1;" ::"r"(bar + S0), "r"(cnt) : "memory");
}
__device__ __forceinline__ void mbar_arrive(uint32_t bar) {
    asm volatile("mbarrier.arrive.shared::cta.b64 _, [%0];" ::"r"(bar + S0) : "memory");
}
__device__ __forceinline__ void mbar_expect(uint32_t bar, uint32_t bytes) {
    asm volatile("mbarrier.arrive.expect_tx.shared::cta.b64 _, [%0], %1;" ::"r"(bar + S0), "r"(bytes) : "memory");
}
__device__ __forceinline__ bool mbar_try(uint32_t bar, uint32_t par) {
    uint32_t ok;
    asm volatile("{\n.reg .pred p;\nmbarrier.try_wait.parity.shared::cta.b64 p, [%1], %2;\nselp.u32 %0, 1, 0, p;\n}"
                 : "=r"(ok) : "r"(bar + S0), "r"(par) : "memory");
    return ok;
}
__device__ __forceinline__ bool mbar_test(uint32_t bar, uint32_t par) {
    uint32_t ok;
    asm volatile("{\n.reg .pred p;\nmbarrier.test_wait.parity.shared::cta.b64 p, [%1], %2;\nselp.u32 %0, 1, 0, p;\n}"
                 : "=r"(ok) : "r"(bar + S0), "r"(par) : "memory");
    return ok;
}
__device__ __forceinline__ void mbar_wait(uint32_t bar, uint32_t par) {
    unsigned it = 0;
#pragma unroll 1
    while (!mbar_try(bar, par) && ++it < SPIN_LIMIT) {}
}
__device__ __forceinline__ bool elect_one() {
    uint32_t p;
    asm volatile("{\n.reg .pred p;\nelect.sync _|p, 0xffffffff;\nselp.u32 %0, 1, 0, p;\n}" : "=r"(p));
    return p;
}
__device__ __forceinline__ void fence_async_smem() { asm volatile("fence.proxy.async.shared::cta;" ::: "memory"); }
__device__ __forceinline__ void fence_async_global() { asm volatile("fence.proxy.async.global;" ::: "memory"); }
__device__ __forceinline__ void fence_acquire() { asm volatile("fence.acquire.gpu;" ::: "memory"); }
__device__ __forceinline__ void bar_sync(int id, int n) { asm volatile("bar.sync %0, %1;" ::"r"(id), "r"(n) : "memory"); }
__device__ __forceinline__ void bar_arrive(int id, int n) { asm volatile("bar.arrive %0, %1;" ::"r"(id), "r"(n) : "memory"); }
__device__ __forceinline__ void bulk_g2s(uint32_t dst, const void* src, uint32_t bytes, uint32_t bar) {
    asm volatile("cp.async.bulk.shared::cluster.global.mbarrier::complete_tx::bytes [%0], [%1], %2, [%3];"
                 ::"r"(dst), "l"(src), "r"(bytes), "r"(bar) : "memory");
}
__device__ __forceinline__ void tma_x(uint32_t dst, const CUtensorMap* tm, int row, int ch, uint32_t bar) {
    asm volatile("cp.async.bulk.tensor.3d.shared::cluster.global.mbarrier::complete_tx::bytes [%0], [%1, {%2, %3, %4}], [%5];"
                 ::"r"(dst + S0), "l"(tm), "r"(0), "r"(row), "r"(ch), "r"(bar + S0) : "memory");
}
__device__ __forceinline__ uint4 ld_relaxed_v4(const void* p) {
    uint4 v;
    asm volatile("ld.relaxed.gpu.global.v4.u32 {%0,%1,%2,%3}, [%4];" : "=r"(v.x), "=r"(v.y), "=r"(v.z), "=r"(v.w) : "l"(p) : "memory");
    return v;
}
__device__ __forceinline__ unsigned ld_relaxed(const void* p) {
    unsigned v;
    asm volatile("ld.relaxed.gpu.global.u32 %0, [%1];" : "=r"(v) : "l"(p) : "memory");
    return v;
}
__device__ __forceinline__ void red_add4(float* p, float a, float b, float c, float d) {
    asm volatile("red.relaxed.gpu.global.add.v4.f32 [%0], {%1,%2,%3,%4};" ::"l"(p), "f"(a), "f"(b), "f"(c), "f"(d) : "memory");
}
__device__ __forceinline__ void sts128(uint32_t a, uint4 v) {
    asm volatile("st.shared.v4.u32 [%0], {%1,%2,%3,%4};" ::"r"(a + S0), "r"(v.x), "r"(v.y), "r"(v.z), "r"(v.w) : "memory");
}
__device__ __forceinline__ void sts128f(uint32_t a, float4 v) {
    asm volatile("st.shared.v4.f32 [%0], {%1,%2,%3,%4};" ::"r"(a + S0), "f"(v.x), "f"(v.y), "f"(v.z), "f"(v.w) : "memory");
}
__device__ __forceinline__ void sts32f(uint32_t a, float v) { asm volatile("st.shared.f32 [%0], %1;" ::"r"(a + S0), "f"(v) : "memory"); }
__device__ __forceinline__ uint4 lds128(uint32_t a) {
    uint4 v;
    asm volatile("ld.shared.v4.u32 {%0,%1,%2,%3}, [%4];" : "=r"(v.x), "=r"(v.y), "=r"(v.z), "=r"(v.w) : "r"(a + S0) : "memory");
    return v;
}
__device__ __forceinline__ float4 lds128f(uint32_t a) {
    float4 v;
    asm volatile("ld.shared.v4.f32 {%0,%1,%2,%3}, [%4];" : "=f"(v.x), "=f"(v.y), "=f"(v.z), "=f"(v.w) : "r"(a + S0) : "memory");
    return v;
}
__device__ __forceinline__ float2 lds64f(uint32_t a) {
    float2 v;
    asm volatile("ld.shared.v2.f32 {%0,%1}, [%2];" : "=f"(v.x), "=f"(v.y) : "r"(a + S0) : "memory");
    return v;
}
__device__ __forceinline__ float bf_lo(uint32_t u) { return __uint_as_float(u << 16); }
__device__ __forceinline__ float bf_hi(uint32_t u) { return __uint_as_float(u & 0xffff0000u); }
__device__ __forceinline__ uint32_t pack_bf(float lo, float hi) {
    uint32_t r;
    asm("cvt.rn.bf16x2.f32 %0, %1, %2;" : "=r"(r) : "f"(hi), "f"(lo));
    return r;
}
__device__ __forceinline__ float tanh_fast(float x) {
    float r;
    asm("tanh.approx.f32 %0, %1;" : "=f"(r) : "f"(x));
    return r;
}
__device__ __forceinline__ float silu_half(float h) { return fmaf(h, tanh_fast(h), h); }
__device__ __forceinline__ void ldsm4(uint32_t (&u)[4], uint32_t a) {
    asm volatile("ldmatrix.sync.aligned.m8n8.x4.shared.b16 {%0,%1,%2,%3}, [%4];"
                 : "=r"(u[0]), "=r"(u[1]), "=r"(u[2]), "=r"(u[3]) : "r"(a + S0) : "memory");
}
__device__ __forceinline__ void ldsm4t(uint32_t (&u)[4], uint32_t a) {
    asm volatile("ldmatrix.sync.aligned.m8n8.x4.trans.shared.b16 {%0,%1,%2,%3}, [%4];"
                 : "=r"(u[0]), "=r"(u[1]), "=r"(u[2]), "=r"(u[3]) : "r"(a + S0) : "memory");
}
__device__ __forceinline__ void stsm4(uint32_t a, uint32_t p0, uint32_t p1, uint32_t p2, uint32_t p3) {
    asm volatile("stmatrix.sync.aligned.m8n8.x4.shared.b16 [%0], {%1,%2,%3,%4};" ::"r"(a + S0), "r"(p0), "r"(p1), "r"(p2), "r"(p3) : "memory");
}
__device__ __forceinline__ void stsm4t(uint32_t a, uint32_t p0, uint32_t p1, uint32_t p2, uint32_t p3) {
    asm volatile("stmatrix.sync.aligned.m8n8.x4.trans.shared.b16 [%0], {%1,%2,%3,%4};" ::"r"(a + S0), "r"(p0), "r"(p1), "r"(p2), "r"(p3) : "memory");
}

#define R8(o) "+f"(d[o]), "+f"(d[o + 1]), "+f"(d[o + 2]), "+f"(d[o + 3]), "+f"(d[o + 4]), "+f"(d[o + 5]), "+f"(d[o + 6]), "+f"(d[o + 7])
template <uint32_t ALO, uint32_t BLO, uint64_t AHI = 8, uint64_t BHI = 48>
__device__ __forceinline__ void wgmma128(float (&d)[64]) {
    asm volatile(
        "wgmma.mma_async.sync.aligned.m64n128k16.f32.bf16.bf16 "
        "{%0,%1,%2,%3,%4,%5,%6,%7,%8,%9,%10,%11,%12,%13,%14,%15,%16,%17,%18,%19,%20,%21,%22,%23,%24,%25,%26,%27,%28,%29,%30,%31,"
        "%32,%33,%34,%35,%36,%37,%38,%39,%40,%41,%42,%43,%44,%45,%46,%47,%48,%49,%50,%51,%52,%53,%54,%55,%56,%57,%58,%59,%60,%61,%62,%63},"
        " %64, %65, 1, 1, 1, 0, 0;"
        : R8(0), R8(8), R8(16), R8(24), R8(32), R8(40), R8(48), R8(56)
        : "l"((AHI << 32) | ALO), "l"((BHI << 32) | BLO));
}
template <int S>
__device__ __forceinline__ void mma_stages(float (&d)[64], int conv, int tid, Scratch* gs) {
    constexpr uint32_t A = ((SM_ACT + S * 2 * CH_PITCH + 16) >> 4) | ((CH_PITCH >> 4) << 16);
    constexpr uint32_t B = (slot_addr(S % NS) >> 4) | (8u << 16);
    if (S == 0) {
        unsigned it = 0;
#pragma unroll 1
        while (!MMA0_WAIT(BAR(BAR_FULL), conv) && ++it < SPIN_LIMIT) {}
    }
    bool next_ok = true;
    constexpr uint32_t NEXT = S + 1 < NSTAGE ? BAR(BAR_FULL + S + 1) : BAR(BAR_EMB);
    const int npar = S + 1 < NSTAGE ? conv : 0;
    next_ok = mbar_test(NEXT, npar);
    if (S == 0 && tid == 0) TL(32 + conv * 24);
    asm volatile("wgmma.fence.sync.aligned;" ::: "memory");
    wgmma128<A, B>(d);
    wgmma128<A + 1, B + 16>(d);
    wgmma128<A + 2, B + 32>(d);
    asm volatile("wgmma.commit_group.sync.aligned;" ::: "memory");
    if (S >= LAG) {
        asm volatile("wgmma.wait_group.sync.aligned %0;" ::"n"(LAG) : "memory");
        if ((tid & 31) == 0) mbar_arrive(BAR(BAR_WEMPTY + (S + NS - LAG) % NS));
    }
    if (!next_ok) mbar_wait(NEXT, npar);
    if constexpr (S + 1 < NSTAGE) mma_stages<S + 1>(d, conv, tid, gs);
}

__device__ __forceinline__ void weight_load(uint4 (&t)[5], const __nv_bfloat16* w, int cta, int lane) {
    const char* base = reinterpret_cast<const char*>(w) + ((cta & 15) * 8 * C + (cta >> 4) * 16) * 18;
#pragma unroll
    for (int k = 0; k < 5; k++) {
        const int i = lane + 32 * k, row = (i * 57) >> 10;
        if (k < 4 || lane < 16) t[k] = __ldg(reinterpret_cast<const uint4*>(base + row * (C * 18 - 288) + i * 16));
    }
}
__device__ __forceinline__ void weight_block(uint32_t bounce, unsigned char* wt, int cta, int lane, bool readback, Scratch* gs) {
    unsigned char* dst = wt + (cta >> 4) * STAGE_BYTES + (cta & 15) * 768;
    if (lane < 16) {
        uint32_t v[36];
#pragma unroll
        for (int i = 0; i < 9; i++) {
            const uint4 q = lds128(bounce + (lane & 7) * 288 + (lane >> 3) * 144 + i * 16);
            v[4 * i] = q.x; v[4 * i + 1] = q.y; v[4 * i + 2] = q.z; v[4 * i + 3] = q.w;
        }
#pragma unroll
        for (int kyo = 0; kyo < 3; kyo++) {
#pragma unroll
            for (int kx = 0; kx < 3; kx++) {
                const int tap = ky_of(kyo) * 3 + kx;
                uint32_t o[4];
#pragma unroll
                for (int m = 0; m < 4; m++) {
                    const int i0 = 18 * m + tap, i1 = i0 + 9;
                    const uint32_t sel = ((i0 & 1) ? 0x32u : 0x10u) | ((i1 & 1) ? 0x7600u : 0x5400u);
                    o[m] = __byte_perm(v[i0 >> 1], v[i1 >> 1], sel);
                }
                *reinterpret_cast<uint4*>(dst + kyo * 8 * STAGE_BYTES + kx * 256 + lane * 16) = make_uint4(o[0], o[1], o[2], o[3]);
            }
        }
    }
    if (readback) {
        __syncwarp();
        unsigned acc = 0;
        if (lane < 24) {
#pragma unroll
            for (int i = 0; i < 3; i++) acc |= ld_relaxed(dst + i * 8 * STAGE_BYTES + lane * 32);
        }
        asm volatile("{\n.reg .pred p;\nsetp.eq.u32 p, %0, 0x9e3779b9;\n@p st.shared.u32 [%1], %0;\n}" ::"r"(acc), "r"(bounce + S0) : "memory");
    }
}
__device__ __forceinline__ uint32_t act2(uint32_t u, const float4& cf) {
    return pack_bf(silu_half(fmaf(bf_lo(u), cf.x, cf.z)), silu_half(fmaf(bf_hi(u), cf.y, cf.w)));
}
__device__ __forceinline__ void norm_unit(uint32_t (&u)[4], const float4& ca, const float4& cb) {
    u[0] = act2(u[0], ca); u[1] = act2(u[1], ca); u[2] = act2(u[2], cb); u[3] = act2(u[3], cb);
}
__device__ __forceinline__ void read_stats(uint32_t gst, float (&g)[8]) {
    asm volatile("ld.volatile.shared.v4.f32 {%0,%1,%2,%3}, [%4];" : "=f"(g[0]), "=f"(g[1]), "=f"(g[2]), "=f"(g[3]) : "r"(gst + S0) : "memory");
    asm volatile("ld.volatile.shared.v4.f32 {%0,%1,%2,%3}, [%4];" : "=f"(g[4]), "=f"(g[5]), "=f"(g[6]), "=f"(g[7]) : "r"(gst + 16 + S0) : "memory");
}
template <int T>
__device__ __forceinline__ void group_coefs(uint32_t gst, float (&g)[8], float4 (&cf)[8]) {
    unsigned it = 0;
#pragma unroll 1
    while (!__all_sync(0xffffffffu, g[2 * T] != 0.f) && ++it < 8 * SPIN_LIMIT) { SPINPAUSE; read_stats(gst, g); }
    float4 &ca = cf[2 * T], &cb = cf[2 * T + 1];
    const float rs = g[2 * T], mr = g[2 * T + 1];
    ca.z = fmaf(-mr, ca.x, ca.z); ca.w = fmaf(-mr, ca.y, ca.w); ca.x *= rs; ca.y *= rs;
    cb.z = fmaf(-mr, cb.x, cb.z); cb.w = fmaf(-mr, cb.y, cb.w); cb.x *= rs; cb.y *= rs;
}
template <int FIRST, int N>
__device__ __forceinline__ void norm_block(uint32_t (&u)[4][4], float4 (&cf)[8], uint32_t act, uint32_t mask, uint32_t fbar, int lane) {
#pragma unroll
    for (int t = FIRST; t < FIRST + N; t++) {
        norm_unit(u[t], cf[2 * t], cf[2 * t + 1]);
        stsm4(act + t * 2 * KC_BYTES, u[t][0] & mask, u[t][1] & mask, u[t][2] & mask, u[t][3] & mask);
    }
    fence_async_smem();
    __syncwarp();
    if (lane < N) mbar_arrive(fbar + 16 * (FIRST + lane));
}
__device__ __forceinline__ void publish(uint32_t bar, int lane) {
    fence_async_smem();
    __syncwarp();
    if (lane == 0) mbar_arrive(bar);
}
template <int T>
__device__ __forceinline__ void next_unit(uint32_t (&u)[4][4], float4 (&cf)[8], uint32_t gst, float (&g)[8], uint32_t act, uint32_t fbar, int lane) {
    const bool have = __all_sync(0xffffffffu, g[2 * T] != 0.f);
    if (!have) publish(fbar + 16 * (T - 1), lane);
    group_coefs<T>(gst, g, cf);
    norm_unit(u[T], cf[2 * T], cf[2 * T + 1]);
    if (have) publish(fbar + 16 * (T - 1), lane);
    stsm4(act + T * 2 * KC_BYTES, u[T][0], u[T][1], u[T][2], u[T][3]);
}
__device__ __forceinline__ void stat_mma(float (&c)[4], uint32_t p, uint32_t q) {
    asm("mma.sync.aligned.m16n8k16.row.col.f32.bf16.bf16.f32 {%0,%1,%2,%3}, {%4,%5,%6,%5}, {%4,%6}, {%0,%1,%2,%3};"
        : "+f"(c[0]), "+f"(c[1]), "+f"(c[2]), "+f"(c[3]) : "r"(p), "r"(0x3f803f80u), "r"(q));
}
__device__ __forceinline__ void stat_store(const float (&c)[4], uint32_t dst, int lane) {
    const int g = lane >> 2, t = lane & 3;
    if (t == (g >> 1)) sts32f(dst + g * 4, (g & 1) ? c[1] : c[0]);
    if (g == 7) sts32f(dst + 32 + t * 4, c[2] + c[3]);
}
__device__ __forceinline__ float sum4(float4 v) { return (v.x + v.y) + (v.z + v.w); }
__device__ __forceinline__ void stat_publish(uint32_t src, float* acc, int lane, bool real) {
    const uint32_t a = src + (lane & 15) * 48;
    float q = sum4(lds128f(a)) + sum4(lds128f(a + 16)), sm = sum4(lds128f(a + 32));
    q += __shfl_xor_sync(0xffffffffu, q, 1); sm += __shfl_xor_sync(0xffffffffu, sm, 1);
    q += __shfl_xor_sync(0xffffffffu, q, 2); sm += __shfl_xor_sync(0xffffffffu, sm, 2);
    if (real && (lane & 19) == 0) red_add4(acc + lane, 1.f, sm, q, 1.f);
}
__device__ __forceinline__ void fence_acc(float (&d)[64]) {
#pragma unroll
    for (int i = 0; i < 64; i++) asm volatile("" : "+f"(d[i])::"memory");
}
__device__ __forceinline__ void ld_unit(uint32_t (&u)[4], const uint4* p) {
    asm volatile("ld.relaxed.gpu.global.v4.u32 {%0,%1,%2,%3}, [%4];" : "=r"(u[0]), "=r"(u[1]), "=r"(u[2]), "=r"(u[3]) : "l"(p) : "memory");
}

__device__ __noinline__ void side_jobs(const __nv_bfloat16* __restrict__ t_emb, const __nv_bfloat16* __restrict__ w_emb,
                                       const __nv_bfloat16* __restrict__ w2, Scratch* __restrict__ gs, unsigned clk0) {
    const int tid = threadIdx.x, warp = tid >> 5, lane = tid & 31, j = blockIdx.x;
    float tv = 0.f;
    if (lane < 24) tv = __bfloat162float(t_emb[(lane / 12) * E + j * 192 + warp * 12 + lane % 12]);
    if (tid == 0) {
        mbar_init(BAR(0), 1);
        mbar_expect(BAR(0), 192 * C * 2);
        fence_async_smem();
        while (clock32() - clk0 < W2DELAY) {}
#pragma unroll
        for (int i = 0; i < 4; i++) bulk_g2s(S0 + SM_W + i * 12288, w_emb + (j * 192 + i * 48) * C, 12288, S0 + BAR(0));
    }
    if (j == 0 && tid < 32) gs->acc2[(tid >> 4) * LS + (tid & 15)] = 0.f;
    const float sv = silu_half(0.5f * tv);
    __syncthreads();
    mbar_wait(BAR(0), 0);
    float acc[8] = {0.f, 0.f, 0.f, 0.f, 0.f, 0.f, 0.f, 0.f};
#pragma unroll
    for (int i = 0; i < 12; i++) {
        const float2 wq = lds64f(SM_W + (warp * 12 + i) * 256 + lane * 8);
        const uint32_t wx = __float_as_uint(wq.x), wy = __float_as_uint(wq.y);
#pragma unroll
        for (int bb = 0; bb < 2; bb++) {
            const float sx = __shfl_sync(0xffffffffu, sv, bb * 12 + i);
            acc[4 * bb + 0] = fmaf(sx, bf_lo(wx), acc[4 * bb + 0]); acc[4 * bb + 1] = fmaf(sx, bf_hi(wx), acc[4 * bb + 1]);
            acc[4 * bb + 2] = fmaf(sx, bf_lo(wy), acc[4 * bb + 2]); acc[4 * bb + 3] = fmaf(sx, bf_hi(wy), acc[4 * bb + 3]);
        }
    }
    sts128f(SM_ACT + warp * 1024 + lane * 16, make_float4(acc[0], acc[1], acc[2], acc[3]));
    sts128f(SM_ACT + warp * 1024 + 512 + lane * 16, make_float4(acc[4], acc[5], acc[6], acc[7]));
    __syncthreads();
    if (tid < 128) {
        float2 sum = make_float2(0.f, 0.f);
#pragma unroll
        for (int w = 0; w < 16; w++) { const float2 p = lds64f(SM_ACT + w * 1024 + tid * 8); sum.x += p.x; sum.y += p.y; }
        *reinterpret_cast<float2*>(&gs->emb[j * NB * C + tid * 2]) = sum;
        bar_sync(1, 128);
        if (tid < 2) asm volatile("red.release.gpu.global.add.u32 [%0], 1;" ::"l"(&gs->wcnt[(2 * NB + tid) * LS]) : "memory");
    }
}

__global__ void __cluster_dims__(2, 1, 1) __launch_bounds__(NTHREADS, 1)
resblock_kernel(const __nv_bfloat16* __restrict__ w1,
                const __nv_bfloat16* __restrict__ t_emb, const __nv_bfloat16* __restrict__ g1,
                const __nv_bfloat16* __restrict__ be1, const __nv_bfloat16* __restrict__ w_emb,
                const __nv_bfloat16* __restrict__ g2, const __nv_bfloat16* __restrict__ be2,
                const __nv_bfloat16* __restrict__ w2, __nv_bfloat16* __restrict__ out, Scratch* __restrict__ gs,
                const __grid_constant__ CUtensorMap xmap) {
    const unsigned clk0 = clock32();
    if (threadIdx.x == 480 && blockIdx.x >= NXTRA) TLG(1);
    const int tid = threadIdx.x, lane = tid & 31;
    const int cta = blockIdx.x - NXTRA, b = cta >> 6, r = cta & 63;
    uint4 v[5];
    if (tid < 32) weight_load(v, w1, cta & (NCTA - 1), lane);
    const int warp = __shfl_sync(0xffffffffu, tid >> 5, 0);
    if (cta < 0) { side_jobs(t_emb, w_emb, w2, gs, clk0); return; }

    const int seg = lane & 7;
    if (warp != 3) asm volatile("barrier.cluster.arrive.relaxed.aligned;" ::: "memory");
    const bool has_outer = (r != 0) && (r != HW - 1);
    if (warp == 1 || warp == 2 || warp == 4 || warp == 5) {
        const int g = warp < 3 ? warp - 1 : 7 - warp;
        if (elect_one()) {
            asm volatile("prefetch.tensormap [%0];" ::"l"(&xmap) : "memory");
            mbar_init(BAR(BAR_X) + 8 * g, 1);
            if (g == 3) mbar_init(BAR(BAR_X + 4), 1);
            mbar_expect(BAR(BAR_X) + 8 * g, 4096);
            fence_async_smem();
            while (clock32() - clk0 < XDELAY + (g >> 1) * XSTAG + (g & 1) * XSTAG2) {}
            tma_x(SM_XOWN + g * 4096, &xmap, r, b * C + g * 32, BAR(BAR_X) + 8 * g);
            if (g == 3 && has_outer) {
                mbar_expect(BAR(BAR_X + 4), 16384);
#pragma unroll
                for (int i = 0; i < 4; i++) tma_x(SM_XOUT + i * 4096, &xmap, r + ((r & 1) ? 1 : -1), b * C + i * 32, BAR(BAR_X + 4));
            }
        }
        __syncwarp();
        bar_arrive(4, 256 + 64 + 128);
        mbar_wait(BAR(BAR_X) + 8 * g, 0);
        if (lane == 0) TL(70 + g);
        float c[8][4];
#pragma unroll
        for (int k = 0; k < 8; k++) {
            const uint4 q = lds128(SM_XOWN + g * 4096 + k * 512 + lane * 16);
            c[k][0] = c[k][1] = c[k][2] = c[k][3] = 0.f;
            stat_mma(c[k], q.x, q.y); stat_mma(c[k], q.z, q.w);
        }
#pragma unroll
        for (int i = 0; i < 4; i++) c[0][i] = ((c[0][i] + c[1][i]) + (c[2][i] + c[3][i])) + ((c[4][i] + c[5][i]) + (c[6][i] + c[7][i]));
        if (lane == 0 && g == 0) { if (c[0][0] == 1.2345f) sts32f(SM_RED, 0.f); TL(92); }
        stat_store(c[0], SM_RED + g * 48, lane);
        __syncwarp();
        if (lane == 0) {
            const uint32_t a = SM_RED + g * 48;
            red_add4(&gs->acc1[b * 4 * LS + g * GS1], 1.f, sum4(lds128f(a + 32)), sum4(lds128f(a)) + sum4(lds128f(a + 16)), 1.f);
            TL(74 + g);
        }
    }
    if (warp == 3) {
            if (elect_one()) {
#pragma unroll
                for (int i = 0; i < NSTAGE; i++) mbar_init(BAR(BAR_FULL + i), (i >> 3) == 1 ? 1 : 5);
#pragma unroll
                for (int i = 0; i < NS + 2; i++) mbar_init(BAR(BAR_WEMPTY + i), 4);
#pragma unroll
                for (int i = BAR_STATS; i < BAR_X; i++) mbar_init(BAR(i), i == BAR_EMB ? 3 : 1);
                asm volatile("fence.mbarrier_init.release.cluster;" ::: "memory");
            }
            __syncwarp();
            fence_async_smem();
            bar_arrive(0, 96);
            bar_arrive(5, 96);
            bar_arrive(4, 256 + 64 + 128);
            const uint4 z = make_uint4(0, 0, 0, 0);
#pragma unroll
            for (int i = 0; i < 2; i++) sts128(SM_ACT + (i * 16 + (lane >> 1)) * CH_PITCH + (lane & 1) * 16, z);
            if (lane < 4) sts128(SM_ACT + (2 + (lane >> 1)) * ROW_BYTES + (lane & 1) * 16, z);
            if (lane < 16) sts128(SM_ONES + lane * 16, make_uint4(lane < 8 ? 0x3f803f80u : 0u, 0, 0, 0));
            fence_async_smem();
            asm volatile("barrier.cluster.arrive.release.aligned;" ::: "memory");
            if (elect_one()) {
                mbar_expect(BAR(BAR_W2), 2304);
                while (clock32() - clk0 < W2DELAY) {}
                const char* base = reinterpret_cast<const char*>(w2) + ((cta & 15) * 8 * C + (cta >> 4) * 16) * 18;
#pragma unroll 1
                for (int i = 0; i < 8; i++) bulk_g2s(S0 + SM_BNC + 2304 + i * 288, base + i * (C * 18), 288, S0 + BAR(BAR_W2));
            }
            __syncwarp();
        }
    if (warp == 0 || warp == 3) {
        const int k = warp & 1;
        if (k == 0) {
#pragma unroll
            for (int i = 0; i < 5; i++)
                if (i < 4 || lane < 16) sts128(SM_BNC + (lane + 32 * i) * 16, v[i]);
            if (lane == 0) TL(81);
            __syncwarp();
        } else {
            mbar_wait(BAR(BAR_W2), 0);
            if (lane == 0) TL(14);
        }
        weight_block(SM_BNC + k * 2304, gs->wt + k * NSTAGE * STAGE_BYTES, cta, lane, true, gs);
        __syncwarp();
        if (lane == 0) TL(k ? 13 : 4);
        if (lane < 2) asm volatile("red.relaxed.gpu.global.add.u32 [%0], 1;" ::"l"(&gs->wcnt[(k * NB + lane) * LS + (k ? 0 : cta >> 4)]) : "memory");
    }

    if (warp >= 8) {
        const int nw = warp - 8;
        bar_sync(4, 256 + 64 + 128);
        const int par = nw >> 2, wq = nw & 3;
        const uint32_t act_off = SM_ACT + (par * 2 + (lane >> 4)) * CH_PITCH + (2 + wq * 16 + (lane & 15)) * 16;
        const uint32_t stg_off = (par * 16 + (lane >> 4) * 8 + (lane & 7)) * 128 + (((2 * wq + ((lane >> 3) & 1)) ^ (lane & 7)) << 4);
        const uint32_t cfa = SM_COEF + par * 128 + (lane & 3) * 16;
        const uint32_t fbar = BAR(BAR_FULL) + 8 * par;
        uint4* inbox = gs->box + cta * 1024 + nw * 32 + lane;
#pragma unroll 1
        for (int conv = 0; conv < 2; conv++) {
            uint32_t u[4][4], w[4][4];
            float4 cf[8];
            if (conv == 0) {
#pragma unroll
                for (int i = 0; i < 4; i++) { mbar_wait(BAR(BAR_X + i), 0); ldsm4t(u[i], SM_XOWN + stg_off + i * 4096); }
            } else {
                mbar_wait(BAR(BAR_HW), 0);
#pragma unroll
                for (int i = 0; i < 4; i++) ldsm4(u[i], act_off + i * 2 * KC_BYTES);
            }
#pragma unroll
            for (int i = 0; i < 8; i++) cf[i] = lds128f(cfa + conv * 1024 + (i >> 1) * 256 + (i & 1) * 64);
            const uint32_t gst = SM_GST + conv * 32;
            float gv[8];
            read_stats(gst, gv);
            group_coefs<0>(gst, gv, cf);
            if (tid == 256) TL(22 + conv * 4);
            if (par) { const unsigned c1 = clock32(); while (clock32() - c1 < PDELAY) {} }
            norm_block<0, 1>(u, cf, act_off, ~0u, fbar, lane);
            if (tid == 256) TL(8 + conv * 8);
            group_coefs<1>(gst, gv, cf);
            norm_unit(u[1], cf[2], cf[3]);
            stsm4(act_off + 2 * KC_BYTES, u[1][0], u[1][1], u[1][2], u[1][3]);
            next_unit<2>(u, cf, gst, gv, act_off, fbar, lane);
            next_unit<3>(u, cf, gst, gv, act_off, fbar, lane);
            publish(fbar + 48, lane);
            if (tid == 256) TL(84 + conv);
            if (has_outer) {
                mbar_wait(BAR(BAR_X + 4), conv);
                if (conv == 0) {
#pragma unroll
                    for (int i = 0; i < 4; i++) ldsm4t(w[i], SM_XOUT + stg_off + i * 4096);
                } else {
#pragma unroll
                    for (int i = 0; i < 4; i++) {
                        const uint4 q = lds128(SM_XOWN + (tid - 256) * 16 + i * 4096);
                        w[i][0] = q.x; w[i][1] = q.y; w[i][2] = q.z; w[i][3] = q.w;
                    }
                    unsigned it = 0;
                    while (true) {
                        bool ok = true;
#pragma unroll
                        for (int i = 0; i < 16; i++) ok = ok && w[i >> 2][i & 3] != 0;
                        if (__all_sync(0xffffffffu, ok) || ++it > SPIN_LIMIT) break;
#pragma unroll
                        for (int i = 0; i < 4; i++) ld_unit(w[i], inbox + i * 256);
                    }
#pragma unroll
                    for (int i = 0; i < 16; i++) w[i >> 2][i & 3] = ~w[i >> 2][i & 3];
                }
            }
            if (conv == 0) {
                bar_sync(3, 256);
                if (nw == 0) sts128(SM_ACT + 2 * ROW_BYTES + (lane >> 1) * CH_PITCH + (lane & 1) * 16, make_uint4(0, 0, 0, 0));
            }
            if (tid == 256) TL(24 + conv * 4);
            norm_block<0, 2>(w, cf, act_off + 2 * ROW_BYTES, has_outer ? ~0u : 0u, fbar + 128, lane);
            if (tid == 256) TL(88 + conv);
            norm_block<2, 2>(w, cf, act_off + 2 * ROW_BYTES, has_outer ? ~0u : 0u, fbar + 128, lane);
            if (tid == 256) TL(23 + conv * 4);
        }
        if (has_outer) {
            mbar_wait(BAR(BAR_FULL + NSTAGE - 1), 1);
#pragma unroll
            for (int i = 0; i < 4; i++) inbox[i * 256] = make_uint4(0, 0, 0, 0);
        }
    } else if (warp < 4) {
        const int wq = warp;
        bar_sync(2, 128);

        float d[64];
#pragma unroll
        for (int i = 0; i < 64; i++) d[i] = 0.f;
#pragma unroll 1
        for (int conv = 0; conv < 2; conv++) {
            fence_acc(d);
            mma_stages<0>(d, conv, tid, gs);
            if (conv == 0) {
                asm volatile("wgmma.fence.sync.aligned;" ::: "memory");
                wgmma128<(SM_ONES >> 4) | (8u << 16), (SM_EMB >> 4), 0, 8>(d);
                asm volatile("wgmma.commit_group.sync.aligned;" ::: "memory");
            }
            asm volatile("wgmma.wait_group.sync.aligned 0;" ::: "memory");
            fence_acc(d);
            if (tid == 0) TL(10 + conv * 8);
            if (conv == 1) break;

            uint32_t hp[32];
#pragma unroll
            for (int g = 0; g < 4; g++) {
                float c[4] = {0.f, 0.f, 0.f, 0.f};
#pragma unroll
                for (int i = 0; i < 8; i++) hp[8 * g + i] = pack_bf(d[16 * g + 2 * i], d[16 * g + 2 * i + 1]);
#pragma unroll
                for (int i = 0; i < 4; i++) stat_mma(c, hp[8 * g + 2 * i], hp[8 * g + 2 * i + 1]);
                stat_store(c, SM_RED + (g * 4 + wq) * 48, lane);
            }
            bar_sync(2, 128);
            if (wq == 0) stat_publish(SM_RED, &gs->acc2[b * LS], lane, true);
            if (tid == 0) TL(11);
            const uint32_t hbase = SM_ACT + (lane >> 4) * CH_PITCH + (2 + wq * 16 + (lane & 15)) * 16;
#pragma unroll
            for (int kc = 0; kc < 8; kc++) stsm4(hbase + kc * 2 * CH_PITCH, hp[4 * kc], hp[4 * kc + 1], hp[4 * kc + 2], hp[4 * kc + 3]);
            __syncwarp();
            if (lane == 0) mbar_arrive(BAR(BAR_HW));
            if (lane < LAG) mbar_arrive(BAR(BAR_WEMPTY + (NSTAGE - LAG) % NS) + 8 * lane);
            if (has_outer) {
                uint4* outbox = gs->box + (cta + ((r & 1) ? 1 : -1)) * 1024 + tid;
#pragma unroll
                for (int kc = 0; kc < 8; kc++) outbox[kc * 128] = make_uint4(~hp[4 * kc], ~hp[4 * kc + 1], ~hp[4 * kc + 2], ~hp[4 * kc + 3]);
            }
            if (tid == 0) TL(12);
            const uint32_t xbase = SM_XOWN + ((lane >> 4) * 8 + (lane & 7)) * 128 + (((2 * wq + ((lane >> 3) & 1)) ^ (lane & 7)) << 4);
#pragma unroll
            for (int kc = 0; kc < 8; kc++) {
                uint32_t p[4];
                ldsm4t(p, xbase + kc * 2048);
#pragma unroll
                for (int i = 0; i < 4; i++) { d[8 * kc + 2 * i] = bf_lo(p[i]); d[8 * kc + 2 * i + 1] = bf_hi(p[i]); }
            }
            fence_async_smem();
            __syncwarp();
            if (lane == 0) mbar_arrive(BAR(BAR_XFREE));
        }
        {
            const uint32_t obase = slot_addr(0) + ((lane >> 4) * 8 + (lane & 7)) * OUT_PITCH + (wq * 16 + ((lane >> 3) & 1) * 8) * 2;
#pragma unroll
            for (int kc = 0; kc < 8; kc++) {
                stsm4t(obase + kc * 16 * OUT_PITCH, pack_bf(d[8 * kc + 0], d[8 * kc + 1]), pack_bf(d[8 * kc + 2], d[8 * kc + 3]),
                       pack_bf(d[8 * kc + 4], d[8 * kc + 5]), pack_bf(d[8 * kc + 6], d[8 * kc + 7]));
            }
            bar_sync(2, 128);
            const int oc0 = tid >> 3;
            __nv_bfloat16* dst = out + ((size_t)(b * C + oc0) * HW + r) * HW + seg * 8;
#pragma unroll
            for (int i = 0; i < 8; i++)
                *reinterpret_cast<uint4*>(dst + (size_t)i * 16 * HW * HW) = lds128(slot_addr(0) + (oc0 + 16 * i) * OUT_PITCH + seg * 16);
            if (tid == 0) { TL(20); TLG(21); }
        }
    } else if (warp < 6) {
        bar_sync(5, 96);
        if (warp == 5) {
            asm volatile("barrier.cluster.wait.acquire.aligned;" ::: "memory");
            const uint32_t peer = (r & 1) ^ 1;
            const uint32_t self0 = mapa(0, r & 1), peer0 = mapa(0, peer);
#pragma unroll 1
            for (int conv = 0; conv < 2; conv++) {
#pragma unroll 1
                for (int kc = 0; kc < 8; kc++) {
                    mbar_wait(BAR(BAR_FULL) + 8 * kc, conv);
                    if (elect_one())
                        asm volatile("cp.async.bulk.shared::cluster.shared::cta.mbarrier::complete_tx::bytes [%0], [%1], %2, [%3];"
                                     ::"r"(peer0 + SM_ACT + ROW_BYTES + kc * KC_BYTES), "r"(self0 + SM_ACT + kc * KC_BYTES), "r"(KC_BYTES),
                                       "r"(peer0 + BAR(BAR_FULL + 8) + 8 * kc) : "memory");
                }
                if (lane == 0) TL(86 + conv);
#pragma unroll 1
                for (int kc = 0; kc < 8; kc++) mbar_wait(BAR(BAR_FULL + 8) + 8 * kc, conv);
                if (lane == 0)
                    asm volatile("mbarrier.arrive.release.cluster.shared::cluster.b64 _, [%0];" ::"r"(peer0 + (conv ? BAR(BAR_ACK) : BAR(BAR_EMB))) : "memory");
            }
            mbar_wait(BAR(BAR_ACK), 0);
        } else {
            mbar_wait(BAR(BAR_STATS), 0);
            unsigned it = 0;
            while (ld_relaxed(&gs->wcnt[(2 * NB + b) * LS]) < (unsigned)NXTRA && ++it < SPIN_LIMIT) __nanosleep(100);
            fence_acquire();
            float ev[4] = {0.f, 0.f, 0.f, 0.f};
#pragma unroll
            for (int j = 0; j < NXTRA; j++) {
                const uint4 ef = ld_relaxed_v4(&gs->emb[(j * NB + b) * C + lane * 4]);
                ev[0] += __uint_as_float(ef.x); ev[1] += __uint_as_float(ef.y); ev[2] += __uint_as_float(ef.z); ev[3] += __uint_as_float(ef.w);
            }
#pragma unroll
            for (int i = 0; i < 4; i++) {
                const float hi = bf_lo(pack_bf(ev[i], 0.f));
                sts128(SM_EMB + (lane * 4 + i) * 16, make_uint4(pack_bf(hi, ev[i] - hi), 0, 0, 0));
            }
            fence_async_smem();
            __syncwarp();
            if (lane == 0) { mbar_arrive(BAR(BAR_EMB)); TL(19); }
        }
    } else if (warp == 6) {
        bar_sync(0, 96);
        const uint32_t ebytes = STAGE_BYTES + ((lane >> 3) == 1 ? KC_BYTES : 0);
        if (lane < NSTAGE) mbar_expect(BAR(BAR_FULL) + 8 * lane, ebytes);
        const int swap = (r & 1) ? 0 : 8 * STAGE_BYTES;
        unsigned it = 0;
        {
            int g = 0;
#pragma unroll 1
            while (g < NS) {
                unsigned ready = __ballot_sync(0xffffffffu, ld_relaxed(&gs->wcnt[b * LS + (lane & 7)]) >= 16u) >> g;
                if (++it > SPIN_LIMIT) ready = ~0u;
                if (!(ready & 1)) continue;
                fence_acquire();
                fence_async_global();
                if (lane == 0) TL(g ? 3 : 6);
#pragma unroll 1
                for (; (ready & 1) && g < NS; g++, ready >>= 1)
                    if (elect_one())
                        bulk_g2s(S0 + SM_W + g * STAGE_BYTES, gs->wt + g * STAGE_BYTES + (g >= 8 ? swap : 0), STAGE_BYTES, S0 + BAR(BAR_FULL) + 8 * g);
            }
        }
#pragma unroll 1
        for (int q = 3; q < 12; q++) {
            const int conv = q >= 6, qs = conv ? q - 6 : q, sl = q % 3;
            const unsigned char* wsrc = gs->wt + q * 4 * STAGE_BYTES + (qs < 2 ? 0 : (qs < 4 ? swap : -swap));
            const uint32_t par = (q / 3 - 1) & 1;
            if (q == 6) {
                it = 0;
                while (ld_relaxed(&gs->wcnt[(NB + b) * LS]) < (unsigned)NCTA && ++it < SPIN_LIMIT) {}
                fence_acquire();
                fence_async_global();
                if (lane == 0) { mbar_arrive(BAR(BAR_EMB)); TL(2); }
            }
#pragma unroll
            for (int i = 0; i < 4; i++) {
                mbar_wait(BAR(BAR_WEMPTY + i) + 32 * sl, par);
                if (i == 0 && (q == 6 || q == 9)) {
                    if ((lane >= NS) == (q == 9) && lane < NSTAGE) mbar_expect(BAR(BAR_FULL) + 8 * lane, ebytes);
                    __syncwarp();
                }
                if (elect_one())
                    bulk_g2s(S0 + SM_W + (sl * 4 + i) * STAGE_BYTES, wsrc + i * STAGE_BYTES, STAGE_BYTES, S0 + BAR(BAR_FULL + i) + 32 * qs);
            }
        }
    } else {
        const uint2 ga1 = __ldg(reinterpret_cast<const uint2*>(g1) + lane), bt1 = __ldg(reinterpret_cast<const uint2*>(be1) + lane);
        const uint2 ga2 = __ldg(reinterpret_cast<const uint2*>(g2) + lane), bt2 = __ldg(reinterpret_cast<const uint2*>(be2) + lane);
        if (lane < 8) sts128(SM_GST + lane * 16, make_uint4(0, 0, 0, 0));
        sts128f(SM_COEF + lane * 32, make_float4(0.5f * bf_lo(ga1.x), 0.5f * bf_hi(ga1.x), 0.5f * bf_lo(bt1.x), 0.5f * bf_hi(bt1.x)));
        sts128f(SM_COEF + lane * 32 + 16, make_float4(0.5f * bf_lo(ga1.y), 0.5f * bf_hi(ga1.y), 0.5f * bf_lo(bt1.y), 0.5f * bf_hi(bt1.y)));
        sts128f(SM_COEF + 1024 + lane * 32, make_float4(0.5f * bf_lo(ga2.x), 0.5f * bf_hi(ga2.x), 0.5f * bf_lo(bt2.x), 0.5f * bf_hi(bt2.x)));
        sts128f(SM_COEF + 1024 + lane * 32 + 16, make_float4(0.5f * bf_lo(ga2.y), 0.5f * bf_hi(ga2.y), 0.5f * bf_lo(bt2.y), 0.5f * bf_hi(bt2.y)));
        bar_arrive(4, 256 + 64 + 128);
        bar_sync(0, 96);
#pragma unroll 1
        for (int conv = 0; conv < 2; conv++) {
            if (conv == 1) {
                mbar_wait(BAR(BAR_HW), 0);
                const unsigned c1 = clock32();
                while (clock32() - c1 < PD2) {}
            } else {
                while (clock32() - clk0 < PD) {}
            }
            const float* asrc = conv ? &gs->acc2[b * LS + (lane & 3) * 4] : &gs->acc1[b * 4 * LS + (lane & 3) * GS1];
            unsigned it = 0;
            uint4 fq[NPOLL];
#pragma unroll
            for (int i = 0; i < NPOLL; i++) {
                fq[i] = ld_relaxed_v4(asrc);
                if (i + 1 < NPOLL) { const unsigned c1 = clock32(); while (clock32() - c1 < 450 / NPOLL) {} }
            }
            bool all = false;
#pragma unroll 1
            while (!all) {
#pragma unroll
                for (int i = 0; i < NPOLL; i++) {
                    const uint4 f = fq[i];
                    const bool ok = ((f.x == 0x42800000u) & (f.w == 0x42800000u)) || it > SPIN_LIMIT;
                    if (ok && lane < 4) {
                        const float inv_n = 1.0f / (32.0f * HW * HW);
                        const float mean = __uint_as_float(f.y) * inv_n;
                        const float rs = rsqrtf(fmaxf(fmaf(-mean, mean, __uint_as_float(f.z) * inv_n), 0.f) + 1e-5f);
                        asm volatile("st.shared.v2.f32 [%0], {%1,%2};" ::"r"(S0 + SM_GST + conv * 32 + lane * 8), "f"(rs == 0.f ? 1e-38f : rs), "f"(mean * rs) : "memory");
                    }
                    if (__all_sync(0xffffffffu, ok)) { all = true; break; }
                    fq[i] = ld_relaxed_v4(asrc);
                }
                it++;
            }
            if (lane == 0) { mbar_arrive(BAR(BAR_STATS)); TL(7 + conv * 8); }
        }
        mbar_wait(BAR(BAR_XFREE), 0);
        if (has_outer && elect_one()) {
            mbar_expect(BAR(BAR_X + 4), 16384);
            bulk_g2s(S0 + SM_XOWN, gs->box + cta * 1024, 16384, S0 + BAR(BAR_X + 4));
        }
        if (r == 0) {
            if (lane < 16) gs->acc1[b * 4 * LS + (lane >> 2) * GS1 + (lane & 3)] = 0.f;
            if (lane < 24) gs->wcnt[((lane >> 3) * NB + b) * LS + (lane & 7)] = 0;
        }
    }
}

}

extern "C" void kernel_launch(void* const* d_in, const int* in_sizes, int n_in, void* d_out, int out_size) {
    (void)in_sizes; (void)n_in; (void)out_size;
    typedef CUresult (*EncodeFn)(CUtensorMap*, CUtensorMapDataType, cuuint32_t, void*, const cuuint64_t*, const cuuint64_t*,
                                 const cuuint32_t*, const cuuint32_t*, CUtensorMapInterleave, CUtensorMapSwizzle,
                                 CUtensorMapL2promotion, CUtensorMapFloatOOBfill);
    static Scratch* gs = nullptr;
    static EncodeFn encode = nullptr;
    if (!gs) {
        cudaFuncSetAttribute(resblock_kernel, cudaFuncAttributeMaxDynamicSharedMemorySize, SM_TOTAL);
        cudaGetSymbolAddress((void**)&gs, g_scratch);
        cudaDriverEntryPointQueryResult qr;
        cudaGetDriverEntryPoint("cuTensorMapEncodeTiled", (void**)&encode, cudaEnableDefault, &qr);
    }
    CUtensorMap xmap;
    const cuuint64_t dims[3] = {HW, HW, NB * C}, strides[2] = {HW * 2, HW * HW * 2};
    const cuuint32_t box[3] = {HW, 1, 32}, es[3] = {1, 1, 1};
    encode(&xmap, CU_TENSOR_MAP_DATA_TYPE_BFLOAT16, 3, d_in[0], dims, strides, box, es, CU_TENSOR_MAP_INTERLEAVE_NONE,
           CU_TENSOR_MAP_SWIZZLE_128B, CU_TENSOR_MAP_L2_PROMOTION_NONE, CU_TENSOR_MAP_FLOAT_OOB_FILL_NONE);
    resblock_kernel<<<NCTA + NXTRA, NTHREADS, SM_TOTAL>>>(
        (const __nv_bfloat16*)d_in[4], (const __nv_bfloat16*)d_in[1],
        (const __nv_bfloat16*)d_in[2], (const __nv_bfloat16*)d_in[3], (const __nv_bfloat16*)d_in[5],
        (const __nv_bfloat16*)d_in[6], (const __nv_bfloat16*)d_in[7], (const __nv_bfloat16*)d_in[8],
        (__nv_bfloat16*)d_out, gs, xmap);
}
```

```cpp
#include <cuda_runtime.h>
#include <cuda.h>
#include <cuda_bf16.h>
#include <stdint.h>

namespace {

constexpr int C = 128, HW = 64, NB = 2, E = 768;
constexpr int NCTA = NB * HW;
constexpr int NXTRA = 4;
constexpr int NTHREADS = 16 * 32;
constexpr int CH_PITCH = 66 * 16;
constexpr int ROW_BYTES = 16 * CH_PITCH;
constexpr int STEP_BYTES = 4096;
constexpr int STAGE_BYTES = 3 * STEP_BYTES;
constexpr int NSTAGE = 24;
constexpr int KC_BYTES = 2 * CH_PITCH;
constexpr int NS = 12;
constexpr int LAG = 1;
#define XDELAY 400
#define HDELAY 600
#define SEQ 0
#define MMA0_WAIT mbar_try
#define SPINPAUSE
#define NPOLL 1
#define PD2 0
#define PDELAY 60
#define RB 1
#define XSTAG2 400
#define XSTAG 800
#define HSEND 0
#define W2DELAY 1400

constexpr uint32_t SMEM_BASE = 0x400;
constexpr uint32_t SM_XOWN = SMEM_BASE;
constexpr uint32_t SM_ACT = SM_XOWN + 16384 + 512;
constexpr uint32_t SM_XOUT = SM_ACT + 2 * ROW_BYTES + 512;
static_assert(SM_XOUT % 1024 == 0, "swizzle atom alignment");
constexpr uint32_t SM_W = SM_ACT + 3 * ROW_BYTES + 128;
__host__ __device__ constexpr uint32_t slot_addr(int slot) { return SM_W + slot * STAGE_BYTES; }
constexpr uint32_t SM_COEF = SM_W + NS * STAGE_BYTES;
constexpr uint32_t SM_GST = SM_COEF + 2048;
constexpr uint32_t SM_EMB = SM_GST + 128;
constexpr uint32_t SM_ONES = SM_EMB + 2048;
constexpr uint32_t SM_RED = SM_ONES + 256;
constexpr uint32_t SM_BNC = SM_RED + 1280;
constexpr uint32_t SM_BAR = SM_BNC + 2 * 2304;
constexpr int BAR_FULL = 0, BAR_WEMPTY = NSTAGE, BAR_HW = BAR_WEMPTY + NS, BAR_XFREE = BAR_HW + 1, BAR_STATS = BAR_XFREE + 1,
              BAR_EMB = BAR_STATS + 1, BAR_ACK = BAR_EMB + 1, BAR_X = BAR_ACK + 1  , NBAR = BAR_X + 5;
constexpr int SM_TOTAL = SM_BAR + NBAR * 8 - SMEM_BASE;
static_assert(SM_TOTAL <= 232448, "smem");
static_assert(NBAR <= 96, "barrier init");
constexpr int OUT_PITCH = 144;
__host__ __device__ constexpr uint32_t BAR(int i) { return SM_BAR + 8 * i; }
__host__ __device__ constexpr int ky_of(int kyo) { return kyo == 0 ? 1 : (kyo == 1 ? 0 : 2); }

constexpr unsigned SPIN_LIMIT = 1u << 16;

#define LS 1056
#define GS1 4
#define PD 0
struct Scratch {
    float acc1[NB * 4 * LS];
    float acc2[NB * LS];
    unsigned wcnt[3 * NB * LS];
    float emb[NXTRA * NB * C];
    unsigned char wt[2 * NSTAGE * STAGE_BYTES];
    uint4 box[NCTA * 1024];
};
__device__ __align__(1024) Scratch g_scratch;
#define TL(i) do {} while (0)
#define TLG(i) do {} while (0)

__device__ __forceinline__ unsigned clock32() { unsigned c; asm volatile("mov.u32 %0, %%clock;" : "=r"(c)); return c; }
__device__ __forceinline__ uint32_t mapa(uint32_t a, uint32_t rank) {
    uint32_t d;
    asm("mapa.shared::cluster.u32 %0, %1, %2;" : "=r"(d) : "r"(a), "r"(rank));
    return d;
}
#define S0 mapa(0, blockIdx.x & 1)
__device__ __forceinline__ void mbar_init(uint32_t bar, int cnt) {
    asm volatile("mbarrier.init.shared::cta.b64 [%0], %1;" ::"r"(bar + S0), "r"(cnt) : "memory");
}
__device__ __forceinline__ void mbar_arrive(uint32_t bar) {
    asm volatile("mbarrier.arrive.shared::cta.b64 _, [%0];" ::"r"(bar + S0) : "memory");
}
__device__ __forceinline__ void mbar_expect(uint32_t bar, uint32_t bytes) {
    asm volatile("mbarrier.arrive.expect_tx.shared::cta.b64 _, [%0], %1;" ::"r"(bar + S0), "r"(bytes) : "memory");
}
__device__ __forceinline__ bool mbar_try(uint32_t bar, uint32_t par) {
    uint32_t ok;
    asm volatile("{\n.reg .pred p;\nmbarrier.try_wait.parity.shared::cta.b64 p, [%1], %2;\nselp.u32 %0, 1, 0, p;\n}"
                 : "=r"(ok) : "r"(bar + S0), "r"(par) : "memory");
    return ok;
}
__device__ __forceinline__ bool mbar_test(uint32_t bar, uint32_t par) {
    uint32_t ok;
    asm volatile("{\n.reg .pred p;\nmbarrier.test_wait.parity.shared::cta.b64 p, [%1], %2;\nselp.u32 %0, 1, 0, p;\n}"
                 : "=r"(ok) : "r"(bar + S0), "r"(par) : "memory");
    return ok;
}
__device__ __forceinline__ void mbar_wait(uint32_t bar, uint32_t par) {
    unsigned it = 0;
#pragma unroll 1
    while (!mbar_try(bar, par) && ++it < SPIN_LIMIT) {}
}
__device__ __forceinline__ bool elect_one() {
    uint32_t p;
    asm volatile("{\n.reg .pred p;\nelect.sync _|p, 0xffffffff;\nselp.u32 %0, 1, 0, p;\n}" : "=r"(p));
    return p;
}
__device__ __forceinline__ void fence_async_smem() { asm volatile("fence.proxy.async.shared::cta;" ::: "memory"); }
__device__ __forceinline__ void fence_async_global() { asm volatile("fence.proxy.async.global;" ::: "memory"); }
__device__ __forceinline__ void fence_acquire() { asm volatile("fence.acquire.gpu;" ::: "memory"); }
__device__ __forceinline__ void bar_sync(int id, int n) { asm volatile("bar.sync %0, %1;" ::"r"(id), "r"(n) : "memory"); }
__device__ __forceinline__ void bar_arrive(int id, int n) { asm volatile("bar.arrive %0, %1;" ::"r"(id), "r"(n) : "memory"); }
__device__ __forceinline__ void bulk_g2s(uint32_t dst, const void* src, uint32_t bytes, uint32_t bar) {
    asm volatile("cp.async.bulk.shared::cluster.global.mbarrier::complete_tx::bytes [%0], [%1], %2, [%3];"
                 ::"r"(dst), "l"(src), "r"(bytes), "r"(bar) : "memory");
}
__device__ __forceinline__ void tma_x(uint32_t dst, const CUtensorMap* tm, int row, int ch, uint32_t bar) {
    asm volatile("cp.async.bulk.tensor.3d.shared::cluster.global.mbarrier::complete_tx::bytes [%0], [%1, {%2, %3, %4}], [%5];"
                 ::"r"(dst + S0), "l"(tm), "r"(0), "r"(row), "r"(ch), "r"(bar + S0) : "memory");
}
__device__ __forceinline__ uint4 ld_relaxed_v4(const void* p) {
    uint4 v;
    asm volatile("ld.relaxed.gpu.global.v4.u32 {%0,%1,%2,%3}, [%4];" : "=r"(v.x), "=r"(v.y), "=r"(v.z), "=r"(v.w) : "l"(p) : "memory");
    return v;
}
__device__ __forceinline__ unsigned ld_relaxed(const void* p) {
    unsigned v;
    asm volatile("ld.relaxed.gpu.global.u32 %0, [%1];" : "=r"(v) : "l"(p) : "memory");
    return v;
}
__device__ __forceinline__ void red_add4(float* p, float a, float b, float c, float d) {
    asm volatile("red.relaxed.gpu.global.add.v4.f32 [%0], {%1,%2,%3,%4};" ::"l"(p), "f"(a), "f"(b), "f"(c), "f"(d) : "memory");
}
__device__ __forceinline__ void sts128(uint32_t a, uint4 v) {
    asm volatile("st.shared.v4.u32 [%0], {%1,%2,%3,%4};" ::"r"(a + S0), "r"(v.x), "r"(v.y), "r"(v.z), "r"(v.w) : "memory");
}
__device__ __forceinline__ void sts128f(uint32_t a, float4 v) {
    asm volatile("st.shared.v4.f32 [%0], {%1,%2,%3,%4};" ::"r"(a + S0), "f"(v.x), "f"(v.y), "f"(v.z), "f"(v.w) : "memory");
}
__device__ __forceinline__ void sts32f(uint32_t a, float v) { asm volatile("st.shared.f32 [%0], %1;" ::"r"(a + S0), "f"(v) : "memory"); }
__device__ __forceinline__ uint4 lds128(uint32_t a) {
    uint4 v;
    asm volatile("ld.shared.v4.u32 {%0,%1,%2,%3}, [%4];" : "=r"(v.x), "=r"(v.y), "=r"(v.z), "=r"(v.w) : "r"(a + S0) : "memory");
    return v;
}
__device__ __forceinline__ float4 lds128f(uint32_t a) {
    float4 v;
    asm volatile("ld.shared.v4.f32 {%0,%1,%2,%3}, [%4];" : "=f"(v.x), "=f"(v.y), "=f"(v.z), "=f"(v.w) : "r"(a + S0) : "memory");
    return v;
}
__device__ __forceinline__ float2 lds64f(uint32_t a) {
    float2 v;
    asm volatile("ld.shared.v2.f32 {%0,%1}, [%2];" : "=f"(v.x), "=f"(v.y) : "r"(a + S0) : "memory");
    return v;
}
__device__ __forceinline__ float bf_lo(uint32_t u) { return __uint_as_float(u << 16); }
__device__ __forceinline__ float bf_hi(uint32_t u) { return __uint_as_float(u & 0xffff0000u); }
__device__ __forceinline__ uint32_t pack_bf(float lo, float hi) {
    uint32_t r;
    asm("cvt.rn.bf16x2.f32 %0, %1, %2;" : "=r"(r) : "f"(hi), "f"(lo));
    return r;
}
__device__ __forceinline__ float tanh_fast(float x) {
    float r;
    asm("tanh.approx.f32 %0, %1;" : "=f"(r) : "f"(x));
    return r;
}
__device__ __forceinline__ float silu_half(float h) { return fmaf(h, tanh_fast(h), h); }
__device__ __forceinline__ void ldsm4(uint32_t (&u)[4], uint32_t a) {
    asm volatile("ldmatrix.sync.aligned.m8n8.x4.shared.b16 {%0,%1,%2,%3}, [%4];"
                 : "=r"(u[0]), "=r"(u[1]), "=r"(u[2]), "=r"(u[3]) : "r"(a + S0) : "memory");
}
__device__ __forceinline__ void ldsm4t(uint32_t (&u)[4], uint32_t a) {
    asm volatile("ldmatrix.sync.aligned.m8n8.x4.trans.shared.b16 {%0,%1,%2,%3}, [%4];"
                 : "=r"(u[0]), "=r"(u[1]), "=r"(u[2]), "=r"(u[3]) : "r"(a + S0) : "memory");
}
__device__ __forceinline__ void stsm4(uint32_t a, uint32_t p0, uint32_t p1, uint32_t p2, uint32_t p3) {
    asm volatile("stmatrix.sync.aligned.m8n8.x4.shared.b16 [%0], {%1,%2,%3,%4};" ::"r"(a + S0), "r"(p0), "r"(p1), "r"(p2), "r"(p3) : "memory");
}
__device__ __forceinline__ void stsm4t(uint32_t a, uint32_t p0, uint32_t p1, uint32_t p2, uint32_t p3) {
    asm volatile("stmatrix.sync.aligned.m8n8.x4.trans.shared.b16 [%0], {%1,%2,%3,%4};" ::"r"(a + S0), "r"(p0), "r"(p1), "r"(p2), "r"(p3) : "memory");
}

#define R8(o) "+f"(d[o]), "+f"(d[o + 1]), "+f"(d[o + 2]), "+f"(d[o + 3]), "+f"(d[o + 4]), "+f"(d[o + 5]), "+f"(d[o + 6]), "+f"(d[o + 7])
template <uint32_t ALO, uint32_t BLO, uint64_t AHI = 8, uint64_t BHI = 48>
__device__ __forceinline__ void wgmma128(float (&d)[64]) {
    asm volatile(
        "wgmma.mma_async.sync.aligned.m64n128k16.f32.bf16.bf16 "
        "{%0,%1,%2,%3,%4,%5,%6,%7,%8,%9,%10,%11,%12,%13,%14,%15,%16,%17,%18,%19,%20,%21,%22,%23,%24,%25,%26,%27,%28,%29,%30,%31,"
        "%32,%33,%34,%35,%36,%37,%38,%39,%40,%41,%42,%43,%44,%45,%46,%47,%48,%49,%50,%51,%52,%53,%54,%55,%56,%57,%58,%59,%60,%61,%62,%63},"
        " %64, %65, 1, 1, 1, 0, 0;"
        : R8(0), R8(8), R8(16), R8(24), R8(32), R8(40), R8(48), R8(56)
        : "l"((AHI << 32) | ALO), "l"((BHI << 32) | BLO));
}
template <int S>
__device__ __forceinline__ void mma_stages(float (&d)[64], int conv, int tid, Scratch* gs) {
    constexpr uint32_t A = ((SM_ACT + S * 2 * CH_PITCH + 16) >> 4) | ((CH_PITCH >> 4) << 16);
    constexpr uint32_t B = (slot_addr(S % NS) >> 4) | (8u << 16);
    if (S == 0) {
        unsigned it = 0;
#pragma unroll 1
        while (!MMA0_WAIT(BAR(BAR_FULL), conv) && ++it < SPIN_LIMIT) {}
    }
    bool next_ok = true;
    constexpr uint32_t NEXT = S + 1 < NSTAGE ? BAR(BAR_FULL + S + 1) : BAR(BAR_EMB);
    const int npar = S + 1 < NSTAGE ? conv : 0;
    next_ok = mbar_test(NEXT, npar);
    if (S == 0 && tid == 0) TL(32 + conv * 24);
    asm volatile("wgmma.fence.sync.aligned;" ::: "memory");
    wgmma128<A, B>(d);
    wgmma128<A + 1, B + 16>(d);
    wgmma128<A + 2, B + 32>(d);
    asm volatile("wgmma.commit_group.sync.aligned;" ::: "memory");
    if (S >= LAG) {
        asm volatile("wgmma.wait_group.sync.aligned %0;" ::"n"(LAG) : "memory");
        if ((tid & 31) == 0) mbar_arrive(BAR(BAR_WEMPTY + (S + NS - LAG) % NS));
    }
    if (!next_ok) mbar_wait(NEXT, npar);
    if constexpr (S + 1 < NSTAGE) mma_stages<S + 1>(d, conv, tid, gs);
}

__device__ __forceinline__ void weight_load(uint4 (&t)[5], const __nv_bfloat16* w, int cta, int lane) {
    const char* base = reinterpret_cast<const char*>(w) + ((cta & 15) * 8 * C + (cta >> 4) * 16) * 18;
#pragma unroll
    for (int k = 0; k < 5; k++) {
        const int i = lane + 32 * k, row = (i * 57) >> 10;
        if (k < 4 || lane < 16) t[k] = __ldg(reinterpret_cast<const uint4*>(base + row * (C * 18 - 288) + i * 16));
    }
}
__device__ __forceinline__ void weight_block(uint32_t bounce, unsigned char* wt, int cta, int lane, bool readback, Scratch* gs) {
    unsigned char* dst = wt + (cta >> 4) * STAGE_BYTES + (cta & 15) * 768;
    if (lane < 16) {
        uint32_t v[36];
#pragma unroll
        for (int i = 0; i < 9; i++) {
            const uint4 q = lds128(bounce + (lane & 7) * 288 + (lane >> 3) * 144 + i * 16);
            v[4 * i] = q.x; v[4 * i + 1] = q.y; v[4 * i + 2] = q.z; v[4 * i + 3] = q.w;
        }
#pragma unroll
        for (int kyo = 0; kyo < 3; kyo++) {
#pragma unroll
            for (int kx = 0; kx < 3; kx++) {
                const int tap = ky_of(kyo) * 3 + kx;
                uint32_t o[4];
#pragma unroll
                for (int m = 0; m < 4; m++) {
                    const int i0 = 18 * m + tap, i1 = i0 + 9;
                    const uint32_t sel = ((i0 & 1) ? 0x32u : 0x10u) | ((i1 & 1) ? 0x7600u : 0x5400u);
                    o[m] = __byte_perm(v[i0 >> 1], v[i1 >> 1], sel);
                }
                *reinterpret_cast<uint4*>(dst + kyo * 8 * STAGE_BYTES + kx * 256 + lane * 16) = make_uint4(o[0], o[1], o[2], o[3]);
            }
        }
    }
    if (readback) {
        __syncwarp();
        unsigned acc = 0;
        if (lane < 24) {
#pragma unroll
            for (int i = 0; i < 3; i++) acc |= ld_relaxed(dst + i * 8 * STAGE_BYTES + lane * 32);
        }
        asm volatile("{\n.reg .pred p;\nsetp.eq.u32 p, %0, 0x9e3779b9;\n@p st.shared.u32 [%1], %0;\n}" ::"r"(acc), "r"(bounce + S0) : "memory");
    }
}
__device__ __forceinline__ uint32_t act2(uint32_t u, const float4& cf) {
    return pack_bf(silu_half(fmaf(bf_lo(u), cf.x, cf.z)), silu_half(fmaf(bf_hi(u), cf.y, cf.w)));
}
__device__ __forceinline__ void norm_unit(uint32_t (&u)[4], const float4& ca, const float4& cb) {
    u[0] = act2(u[0], ca); u[1] = act2(u[1], ca); u[2] = act2(u[2], cb); u[3] = act2(u[3], cb);
}
__device__ __forceinline__ void read_stats(uint32_t gst, float (&g)[8]) {
    asm volatile("ld.volatile.shared.v4.f32 {%0,%1,%2,%3}, [%4];" : "=f"(g[0]), "=f"(g[1]), "=f"(g[2]), "=f"(g[3]) : "r"(gst + S0) : "memory");
    asm volatile("ld.volatile.shared.v4.f32 {%0,%1,%2,%3}, [%4];" : "=f"(g[4]), "=f"(g[5]), "=f"(g[6]), "=f"(g[7]) : "r"(gst + 16 + S0) : "memory");
}
template <int T>
__device__ __forceinline__ void group_coefs(uint32_t gst, float (&g)[8], float4 (&cf)[8]) {
    unsigned it = 0;
#pragma unroll 1
    while (!__all_sync(0xffffffffu, g[2 * T] != 0.f) && ++it < 8 * SPIN_LIMIT) { SPINPAUSE; read_stats(gst, g); }
    float4 &ca = cf[2 * T], &cb = cf[2 * T + 1];
    const float rs = g[2 * T], mr = g[2 * T + 1];
    ca.z = fmaf(-mr, ca.x, ca.z); ca.w = fmaf(-mr, ca.y, ca.w); ca.x *= rs; ca.y *= rs;
    cb.z = fmaf(-mr, cb.x, cb.z); cb.w = fmaf(-mr, cb.y, cb.w); cb.x *= rs; cb.y *= rs;
}
template <int FIRST, int N>
__device__ __forceinline__ void norm_block(uint32_t (&u)[4][4], float4 (&cf)[8], uint32_t act, uint32_t mask, uint32_t fbar, int lane) {
#pragma unroll
    for (int t = FIRST; t < FIRST + N; t++) {
        norm_unit(u[t], cf[2 * t], cf[2 * t + 1]);
        stsm4(act + t * 2 * KC_BYTES, u[t][0] & mask, u[t][1] & mask, u[t][2] & mask, u[t][3] & mask);
    }
    fence_async_smem();
    __syncwarp();
    if (lane < N) mbar_arrive(fbar + 16 * (FIRST + lane));
}
__device__ __forceinline__ void publish(uint32_t bar, int lane) {
    fence_async_smem();
    __syncwarp();
    if (lane == 0) mbar_arrive(bar);
}
template <int T>
__device__ __forceinline__ void next_unit(uint32_t (&u)[4][4], float4 (&cf)[8], uint32_t gst, float (&g)[8], uint32_t act, uint32_t fbar, int lane) {
    const bool have = __all_sync(0xffffffffu, g[2 * T] != 0.f);
    if (!have) publish(fbar + 16 * (T - 1), lane);
    group_coefs<T>(gst, g, cf);
    norm_unit(u[T], cf[2 * T], cf[2 * T + 1]);
    if (have) publish(fbar + 16 * (T - 1), lane);
    stsm4(act + T * 2 * KC_BYTES, u[T][0], u[T][1], u[T][2], u[T][3]);
}
__device__ __forceinline__ void stat_mma(float (&c)[4], uint32_t p, uint32_t q) {
    asm("mma.sync.aligned.m16n8k16.row.col.f32.bf16.bf16.f32 {%0,%1,%2,%3}, {%4,%5,%6,%5}, {%4,%6}, {%0,%1,%2,%3};"
        : "+f"(c[0]), "+f"(c[1]), "+f"(c[2]), "+f"(c[3]) : "r"(p), "r"(0x3f803f80u), "r"(q));
}
__device__ __forceinline__ void stat_store(const float (&c)[4], uint32_t dst, int lane) {
    const int g = lane >> 2, t = lane & 3;
    if (t == (g >> 1)) sts32f(dst + g * 4, (g & 1) ? c[1] : c[0]);
    if (g == 7) sts32f(dst + 32 + t * 4, c[2] + c[3]);
}
__device__ __forceinline__ float sum4(float4 v) { return (v.x + v.y) + (v.z + v.w); }
__device__ __forceinline__ void stat_publish(uint32_t src, float* acc, int lane, bool real) {
    const uint32_t a = src + (lane & 15) * 48;
    float q = sum4(lds128f(a)) + sum4(lds128f(a + 16)), sm = sum4(lds128f(a + 32));
    q += __shfl_xor_sync(0xffffffffu, q, 1); sm += __shfl_xor_sync(0xffffffffu, sm, 1);
    q += __shfl_xor_sync(0xffffffffu, q, 2); sm += __shfl_xor_sync(0xffffffffu, sm, 2);
    if (real && (lane & 19) == 0) red_add4(acc + lane, 1.f, sm, q, 1.f);
}
__device__ __forceinline__ void fence_acc(float (&d)[64]) {
#pragma unroll
    for (int i = 0; i < 64; i++) asm volatile("" : "+f"(d[i])::"memory");
}
__device__ __forceinline__ void ld_unit(uint32_t (&u)[4], const uint4* p) {
    asm volatile("ld.relaxed.gpu.global.v4.u32 {%0,%1,%2,%3}, [%4];" : "=r"(u[0]), "=r"(u[1]), "=r"(u[2]), "=r"(u[3]) : "l"(p) : "memory");
}

__device__ __noinline__ void side_jobs(const __nv_bfloat16* __restrict__ t_emb, const __nv_bfloat16* __restrict__ w_emb,
                                       const __nv_bfloat16* __restrict__ w2, Scratch* __restrict__ gs, unsigned clk0) {
    const int tid = threadIdx.x, warp = tid >> 5, lane = tid & 31, j = blockIdx.x;
    float tv = 0.f;
    if (lane < 24) tv = __bfloat162float(t_emb[(lane / 12) * E + j * 192 + warp * 12 + lane % 12]);
    if (tid == 0) {
        mbar_init(BAR(0), 1);
        mbar_expect(BAR(0), 192 * C * 2);
        fence_async_smem();
        while (clock32() - clk0 < W2DELAY) {}
#pragma unroll
        for (int i = 0; i < 4; i++) bulk_g2s(S0 + SM_W + i * 12288, w_emb + (j * 192 + i * 48) * C, 12288, S0 + BAR(0));
    }
    if (j == 0 && tid < 32) gs->acc2[(tid >> 4) * LS + (tid & 15)] = 0.f;
    const float sv = silu_half(0.5f * tv);
    __syncthreads();
    mbar_wait(BAR(0), 0);
    float acc[8] = {0.f, 0.f, 0.f, 0.f, 0.f, 0.f, 0.f, 0.f};
#pragma unroll
    for (int i = 0; i < 12; i++) {
        const float2 wq = lds64f(SM_W + (warp * 12 + i) * 256 + lane * 8);
        const uint32_t wx = __float_as_uint(wq.x), wy = __float_as_uint(wq.y);
#pragma unroll
        for (int bb = 0; bb < 2; bb++) {
            const float sx = __shfl_sync(0xffffffffu, sv, bb * 12 + i);
            acc[4 * bb + 0] = fmaf(sx, bf_lo(wx), acc[4 * bb + 0]); acc[4 * bb + 1] = fmaf(sx, bf_hi(wx), acc[4 * bb + 1]);
            acc[4 * bb + 2] = fmaf(sx, bf_lo(wy), acc[4 * bb + 2]); acc[4 * bb + 3] = fmaf(sx, bf_hi(wy), acc[4 * bb + 3]);
        }
    }
    sts128f(SM_ACT + warp * 1024 + lane * 16, make_float4(acc[0], acc[1], acc[2], acc[3]));
    sts128f(SM_ACT + warp * 1024 + 512 + lane * 16, make_float4(acc[4], acc[5], acc[6], acc[7]));
    __syncthreads();
    if (tid < 128) {
        float2 sum = make_float2(0.f, 0.f);
#pragma unroll
        for (int w = 0; w < 16; w++) { const float2 p = lds64f(SM_ACT + w * 1024 + tid * 8); sum.x += p.x; sum.y += p.y; }
        *reinterpret_cast<float2*>(&gs->emb[j * NB * C + tid * 2]) = sum;
        bar_sync(1, 128);
        if (tid < 2) asm volatile("red.release.gpu.global.add.u32 [%0], 1;" ::"l"(&gs->wcnt[(2 * NB + tid) * LS]) : "memory");
    }
}

__global__ void __cluster_dims__(2, 1, 1) __launch_bounds__(NTHREADS, 1)
resblock_kernel(const __nv_bfloat16* __restrict__ w1,
                const __nv_bfloat16* __restrict__ t_emb, const __nv_bfloat16* __restrict__ g1,
                const __nv_bfloat16* __restrict__ be1, const __nv_bfloat16* __restrict__ w_emb,
                const __nv_bfloat16* __restrict__ g2, const __nv_bfloat16* __restrict__ be2,
                const __nv_bfloat16* __restrict__ w2, __nv_bfloat16* __restrict__ out, Scratch* __restrict__ gs,
                const __grid_constant__ CUtensorMap xmap) {
    const unsigned clk0 = clock32();
    if (threadIdx.x == 480 && blockIdx.x >= NXTRA) TLG(1);
    const int tid = threadIdx.x, lane = tid & 31;
    const int cta = blockIdx.x - NXTRA, b = cta >> 6, r = cta & 63;
    uint4 v[5];
    if (tid < 32) weight_load(v, w1, cta & (NCTA - 1), lane);
    const int warp = __shfl_sync(0xffffffffu, tid >> 5, 0);
    if (cta < 0) { side_jobs(t_emb, w_emb, w2, gs, clk0); return; }

    const int seg = lane & 7;
    if (warp != 3) asm volatile("barrier.cluster.arrive.relaxed.aligned;" ::: "memory");
    const bool has_outer = (r != 0) && (r != HW - 1);
    if (warp == 1 || warp == 2 || warp == 4 || warp == 5) {
        const int g = warp < 3 ? warp - 1 : 7 - warp;
        if (elect_one()) {
            asm volatile("prefetch.tensormap [%0];" ::"l"(&xmap) : "memory");
            mbar_init(BAR(BAR_X) + 8 * g, 1);
            if (g == 3) mbar_init(BAR(BAR_X + 4), 1);
            mbar_expect(BAR(BAR_X) + 8 * g, 4096);
            fence_async_smem();
            while (clock32() - clk0 < XDELAY + (g >> 1) * XSTAG + (g & 1) * XSTAG2) {}
            tma_x(SM_XOWN + g * 4096, &xmap, r, b * C + g * 32, BAR(BAR_X) + 8 * g);
            if (g == 3 && has_outer) {
                mbar_expect(BAR(BAR_X + 4), 16384);
#pragma unroll
                for (int i = 0; i < 4; i++) tma_x(SM_XOUT + i * 4096, &xmap, r + ((r & 1) ? 1 : -1), b * C + i * 32, BAR(BAR_X + 4));
            }
        }
        __syncwarp();
        bar_arrive(4, 256 + 64 + 128);
        mbar_wait(BAR(BAR_X) + 8 * g, 0);
        if (lane == 0) TL(70 + g);
        float c[8][4];
#pragma unroll
        for (int k = 0; k < 8; k++) {
            const uint4 q = lds128(SM_XOWN + g * 4096 + k * 512 + lane * 16);
            c[k][0] = c[k][1] = c[k][2] = c[k][3] = 0.f;
            stat_mma(c[k], q.x, q.y); stat_mma(c[k], q.z, q.w);
        }
#pragma unroll
        for (int i = 0; i < 4; i++) c[0][i] = ((c[0][i] + c[1][i]) + (c[2][i] + c[3][i])) + ((c[4][i] + c[5][i]) + (c[6][i] + c[7][i]));
        if (lane == 0 && g == 0) { if (c[0][0] == 1.2345f) sts32f(SM_RED, 0.f); TL(92); }
        stat_store(c[0], SM_RED + g * 48, lane);
        __syncwarp();
        if (lane == 0) {
            const uint32_t a = SM_RED + g * 48;
            red_add4(&gs->acc1[b * 4 * LS + g * GS1], 1.f, sum4(lds128f(a + 32)), sum4(lds128f(a)) + sum4(lds128f(a + 16)), 1.f);
            TL(74 + g);
        }
    }
    if (warp == 3) {
            if (elect_one()) {
#pragma unroll
                for (int i = 0; i < NSTAGE; i++) mbar_init(BAR(BAR_FULL + i), (i >> 3) == 1 ? 1 : 5);
#pragma unroll
                for (int i = 0; i < NS + 2; i++) mbar_init(BAR(BAR_WEMPTY + i), 4);
#pragma unroll
                for (int i = BAR_STATS; i < BAR_X; i++) mbar_init(BAR(i), i == BAR_EMB ? 3 : 1);
                asm volatile("fence.mbarrier_init.release.cluster;" ::: "memory");
            }
            __syncwarp();
            fence_async_smem();
            bar_arrive(0, 96);
            bar_arrive(5, 96);
            bar_arrive(4, 256 + 64 + 128);
            const uint4 z = make_uint4(0, 0, 0, 0);
#pragma unroll
            for (int i = 0; i < 2; i++) sts128(SM_ACT + (i * 16 + (lane >> 1)) * CH_PITCH + (lane & 1) * 16, z);
            if (lane < 4) sts128(SM_ACT + (2 + (lane >> 1)) * ROW_BYTES + (lane & 1) * 16, z);
            if (lane < 16) sts128(SM_ONES + lane * 16, make_uint4(lane < 8 ? 0x3f803f80u : 0u, 0, 0, 0));
            fence_async_smem();
            asm volatile("barrier.cluster.arrive.relaxed.aligned;" ::: "memory");
            if (lane == 0) TL(5);
            while (clock32() - clk0 < W2DELAY) {}
            weight_load(v, w2, cta, lane);
        }
    if (warp == 0 || warp == 3) {
        const int k = warp & 1;
#pragma unroll
        for (int i = 0; i < 5; i++)
            if (i < 4 || lane < 16) sts128(SM_BNC + k * 2304 + (lane + 32 * i) * 16, v[i]);
        if (lane == 0) TL(k ? 14 : 81);
        __syncwarp();
        weight_block(SM_BNC + k * 2304, gs->wt + k * NSTAGE * STAGE_BYTES, cta, lane, true, gs);
        __syncwarp();
        if (lane == 0) TL(k ? 13 : 4);
        if (lane < 2) asm volatile("red.relaxed.gpu.global.add.u32 [%0], 1;" ::"l"(&gs->wcnt[(k * NB + lane) * LS + (k ? 0 : cta >> 4)]) : "memory");
    }

    if (warp >= 8) {
        const int nw = warp - 8;
        bar_sync(4, 256 + 64 + 128);
        const int par = nw >> 2, wq = nw & 3;
        const uint32_t act_off = SM_ACT + (par * 2 + (lane >> 4)) * CH_PITCH + (2 + wq * 16 + (lane & 15)) * 16;
        const uint32_t stg_off = (par * 16 + (lane >> 4) * 8 + (lane & 7)) * 128 + (((2 * wq + ((lane >> 3) & 1)) ^ (lane & 7)) << 4);
        const uint32_t cfa = SM_COEF + par * 128 + (lane & 3) * 16;
        const uint32_t fbar = BAR(BAR_FULL) + 8 * par;
        uint4* inbox = gs->box + cta * 1024 + nw * 32 + lane;
#pragma unroll 1
        for (int conv = 0; conv < 2; conv++) {
            uint32_t u[4][4], w[4][4];
            float4 cf[8];
            if (conv == 0) {
#pragma unroll
                for (int i = 0; i < 4; i++) { mbar_wait(BAR(BAR_X + i), 0); ldsm4t(u[i], SM_XOWN + stg_off + i * 4096); }
            } else {
                mbar_wait(BAR(BAR_HW), 0);
#pragma unroll
                for (int i = 0; i < 4; i++) ldsm4(u[i], act_off + i * 2 * KC_BYTES);
            }
#pragma unroll
            for (int i = 0; i < 8; i++) cf[i] = lds128f(cfa + conv * 1024 + (i >> 1) * 256 + (i & 1) * 64);
            const uint32_t gst = SM_GST + conv * 32;
            float gv[8];
            read_stats(gst, gv);
            group_coefs<0>(gst, gv, cf);
            if (tid == 256) TL(22 + conv * 4);
            if (par) { const unsigned c1 = clock32(); while (clock32() - c1 < PDELAY) {} }
            norm_block<0, 1>(u, cf, act_off, ~0u, fbar, lane);
            if (tid == 256) TL(8 + conv * 8);
            group_coefs<1>(gst, gv, cf);
            norm_unit(u[1], cf[2], cf[3]);
            stsm4(act_off + 2 * KC_BYTES, u[1][0], u[1][1], u[1][2], u[1][3]);
            next_unit<2>(u, cf, gst, gv, act_off, fbar, lane);
            next_unit<3>(u, cf, gst, gv, act_off, fbar, lane);
            publish(fbar + 48, lane);
            if (tid == 256) TL(84 + conv);
            if (has_outer) {
                mbar_wait(BAR(BAR_X + 4), conv);
                if (conv == 0) {
#pragma unroll
                    for (int i = 0; i < 4; i++) ldsm4t(w[i], SM_XOUT + stg_off + i * 4096);
                } else {
#pragma unroll
                    for (int i = 0; i < 4; i++) {
                        const uint4 q = lds128(SM_XOWN + (tid - 256) * 16 + i * 4096);
                        w[i][0] = q.x; w[i][1] = q.y; w[i][2] = q.z; w[i][3] = q.w;
                    }
                    unsigned it = 0;
                    while (true) {
                        bool ok = true;
#pragma unroll
                        for (int i = 0; i < 16; i++) ok = ok && w[i >> 2][i & 3] != 0;
                        if (__all_sync(0xffffffffu, ok) || ++it > SPIN_LIMIT) break;
#pragma unroll
                        for (int i = 0; i < 4; i++) ld_unit(w[i], inbox + i * 256);
                    }
#pragma unroll
                    for (int i = 0; i < 16; i++) w[i >> 2][i & 3] = ~w[i >> 2][i & 3];
                }
            }
            if (conv == 0) {
                bar_sync(3, 256);
                if (nw == 0) sts128(SM_ACT + 2 * ROW_BYTES + (lane >> 1) * CH_PITCH + (lane & 1) * 16, make_uint4(0, 0, 0, 0));
            }
            if (tid == 256) TL(24 + conv * 4);
            norm_block<0, 2>(w, cf, act_off + 2 * ROW_BYTES, has_outer ? ~0u : 0u, fbar + 128, lane);
            if (tid == 256) TL(88 + conv);
            norm_block<2, 2>(w, cf, act_off + 2 * ROW_BYTES, has_outer ? ~0u : 0u, fbar + 128, lane);
            if (tid == 256) TL(23 + conv * 4);
        }
        if (has_outer) {
            mbar_wait(BAR(BAR_FULL + NSTAGE - 1), 1);
#pragma unroll
            for (int i = 0; i < 4; i++) inbox[i * 256] = make_uint4(0, 0, 0, 0);
        }
    } else if (warp < 4) {
        const int wq = warp;
        bar_sync(2, 128);

        float d[64];
#pragma unroll
        for (int i = 0; i < 64; i++) d[i] = 0.f;
#pragma unroll 1
        for (int conv = 0; conv < 2; conv++) {
            fence_acc(d);
            mma_stages<0>(d, conv, tid, gs);
            if (conv == 0) {
                asm volatile("wgmma.fence.sync.aligned;" ::: "memory");
                wgmma128<(SM_ONES >> 4) | (8u << 16), (SM_EMB >> 4), 0, 8>(d);
                asm volatile("wgmma.commit_group.sync.aligned;" ::: "memory");
            }
            asm volatile("wgmma.wait_group.sync.aligned 0;" ::: "memory");
            fence_acc(d);
            if (tid == 0) TL(10 + conv * 8);
            if (conv == 1) break;

            uint32_t hp[32];
#pragma unroll
            for (int g = 0; g < 4; g++) {
                float c[4] = {0.f, 0.f, 0.f, 0.f};
#pragma unroll
                for (int i = 0; i < 8; i++) hp[8 * g + i] = pack_bf(d[16 * g + 2 * i], d[16 * g + 2 * i + 1]);
#pragma unroll
                for (int i = 0; i < 4; i++) stat_mma(c, hp[8 * g + 2 * i], hp[8 * g + 2 * i + 1]);
                stat_store(c, SM_RED + (g * 4 + wq) * 48, lane);
            }
            bar_sync(2, 128);
            if (wq == 0) stat_publish(SM_RED, &gs->acc2[b * LS], lane, true);
            if (tid == 0) TL(11);
            const uint32_t hbase = SM_ACT + (lane >> 4) * CH_PITCH + (2 + wq * 16 + (lane & 15)) * 16;
#pragma unroll
            for (int kc = 0; kc < 8; kc++) stsm4(hbase + kc * 2 * CH_PITCH, hp[4 * kc], hp[4 * kc + 1], hp[4 * kc + 2], hp[4 * kc + 3]);
            __syncwarp();
            if (lane == 0) mbar_arrive(BAR(BAR_HW));
            if (lane < LAG) mbar_arrive(BAR(BAR_WEMPTY + (NSTAGE - LAG) % NS) + 8 * lane);
            if (has_outer) {
                uint4* outbox = gs->box + (cta + ((r & 1) ? 1 : -1)) * 1024 + tid;
#pragma unroll
                for (int kc = 0; kc < 8; kc++) outbox[kc * 128] = make_uint4(~hp[4 * kc], ~hp[4 * kc + 1], ~hp[4 * kc + 2], ~hp[4 * kc + 3]);
            }
            if (tid == 0) TL(12);
            const uint32_t xbase = SM_XOWN + ((lane >> 4) * 8 + (lane & 7)) * 128 + (((2 * wq + ((lane >> 3) & 1)) ^ (lane & 7)) << 4);
#pragma unroll
            for (int kc = 0; kc < 8; kc++) {
                uint32_t p[4];
                ldsm4t(p, xbase + kc * 2048);
#pragma unroll
                for (int i = 0; i < 4; i++) { d[8 * kc + 2 * i] = bf_lo(p[i]); d[8 * kc + 2 * i + 1] = bf_hi(p[i]); }
            }
            fence_async_smem();
            __syncwarp();
            if (lane == 0) mbar_arrive(BAR(BAR_XFREE));
        }
        {
            const uint32_t obase = slot_addr(0) + ((lane >> 4) * 8 + (lane & 7)) * OUT_PITCH + (wq * 16 + ((lane >> 3) & 1) * 8) * 2;
#pragma unroll
            for (int kc = 0; kc < 8; kc++) {
                stsm4t(obase + kc * 16 * OUT_PITCH, pack_bf(d[8 * kc + 0], d[8 * kc + 1]), pack_bf(d[8 * kc + 2], d[8 * kc + 3]),
                       pack_bf(d[8 * kc + 4], d[8 * kc + 5]), pack_bf(d[8 * kc + 6], d[8 * kc + 7]));
            }
            bar_sync(2, 128);
            const int oc0 = tid >> 3;
            __nv_bfloat16* dst = out + ((size_t)(b * C + oc0) * HW + r) * HW + seg * 8;
#pragma unroll
            for (int i = 0; i < 8; i++)
                *reinterpret_cast<uint4*>(dst + (size_t)i * 16 * HW * HW) = lds128(slot_addr(0) + (oc0 + 16 * i) * OUT_PITCH + seg * 16);
            if (tid == 0) { TL(20); TLG(21); }
        }
    } else if (warp < 6) {
        bar_sync(5, 96);
        if (warp == 5) {
            asm volatile("barrier.cluster.wait.acquire.aligned;" ::: "memory");
            const uint32_t peer = (r & 1) ^ 1;
            const uint32_t self0 = mapa(0, r & 1), peer0 = mapa(0, peer);
#pragma unroll 1
            for (int conv = 0; conv < 2; conv++) {
#pragma unroll 1
                for (int kc = 0; kc < 8; kc++) {
                    mbar_wait(BAR(BAR_FULL) + 8 * kc, conv);
                    if (elect_one())
                        asm volatile("cp.async.bulk.shared::cluster.shared::cta.mbarrier::complete_tx::bytes [%0], [%1], %2, [%3];"
                                     ::"r"(peer0 + SM_ACT + ROW_BYTES + kc * KC_BYTES), "r"(self0 + SM_ACT + kc * KC_BYTES), "r"(KC_BYTES),
                                       "r"(peer0 + BAR(BAR_FULL + 8) + 8 * kc) : "memory");
                }
                if (lane == 0) TL(86 + conv);
#pragma unroll 1
                for (int kc = 0; kc < 8; kc++) mbar_wait(BAR(BAR_FULL + 8) + 8 * kc, conv);
                if (lane == 0)
                    asm volatile("mbarrier.arrive.release.cluster.shared::cluster.b64 _, [%0];" ::"r"(peer0 + (conv ? BAR(BAR_ACK) : BAR(BAR_EMB))) : "memory");
            }
            mbar_wait(BAR(BAR_ACK), 0);
        } else {
            mbar_wait(BAR(BAR_STATS), 0);
            unsigned it = 0;
            while (ld_relaxed(&gs->wcnt[(2 * NB + b) * LS]) < (unsigned)NXTRA && ++it < SPIN_LIMIT) __nanosleep(100);
            fence_acquire();
            float ev[4] = {0.f, 0.f, 0.f, 0.f};
#pragma unroll
            for (int j = 0; j < NXTRA; j++) {
                const uint4 ef = ld_relaxed_v4(&gs->emb[(j * NB + b) * C + lane * 4]);
                ev[0] += __uint_as_float(ef.x); ev[1] += __uint_as_float(ef.y); ev[2] += __uint_as_float(ef.z); ev[3] += __uint_as_float(ef.w);
            }
#pragma unroll
            for (int i = 0; i < 4; i++) {
                const float hi = bf_lo(pack_bf(ev[i], 0.f));
                sts128(SM_EMB + (lane * 4 + i) * 16, make_uint4(pack_bf(hi, ev[i] - hi), 0, 0, 0));
            }
            fence_async_smem();
            __syncwarp();
            if (lane == 0) { mbar_arrive(BAR(BAR_EMB)); TL(19); }
        }
    } else if (warp == 6) {
        bar_sync(0, 96);
        const uint32_t ebytes = STAGE_BYTES + ((lane >> 3) == 1 ? KC_BYTES : 0);
        if (lane < NSTAGE) mbar_expect(BAR(BAR_FULL) + 8 * lane, ebytes);
        const int swap = (r & 1) ? 0 : 8 * STAGE_BYTES;
        unsigned it = 0;
        {
            int g = 0;
#pragma unroll 1
            while (g < NS) {
                unsigned ready = __ballot_sync(0xffffffffu, ld_relaxed(&gs->wcnt[b * LS + (lane & 7)]) >= 16u) >> g;
                if (++it > SPIN_LIMIT) ready = ~0u;
                if (!(ready & 1)) continue;
                fence_acquire();
                fence_async_global();
                if (lane == 0) TL(g ? 3 : 6);
#pragma unroll 1
                for (; (ready & 1) && g < NS; g++, ready >>= 1)
                    if (elect_one())
                        bulk_g2s(S0 + SM_W + g * STAGE_BYTES, gs->wt + g * STAGE_BYTES + (g >= 8 ? swap : 0), STAGE_BYTES, S0 + BAR(BAR_FULL) + 8 * g);
            }
        }
#pragma unroll 1
        for (int q = 3; q < 12; q++) {
            const int conv = q >= 6, qs = conv ? q - 6 : q, sl = q % 3;
            const unsigned char* wsrc = gs->wt + q * 4 * STAGE_BYTES + (qs < 2 ? 0 : (qs < 4 ? swap : -swap));
            const uint32_t par = (q / 3 - 1) & 1;
            if (q == 6) {
                it = 0;
                while (ld_relaxed(&gs->wcnt[(NB + b) * LS]) < (unsigned)NCTA && ++it < SPIN_LIMIT) {}
                fence_acquire();
                fence_async_global();
                if (lane == 0) { mbar_arrive(BAR(BAR_EMB)); TL(2); }
            }
#pragma unroll
            for (int i = 0; i < 4; i++) {
                mbar_wait(BAR(BAR_WEMPTY + i) + 32 * sl, par);
                if (i == 0 && (q == 6 || q == 9)) {
                    if ((lane >= NS) == (q == 9) && lane < NSTAGE) mbar_expect(BAR(BAR_FULL) + 8 * lane, ebytes);
                    __syncwarp();
                }
                if (elect_one())
                    bulk_g2s(S0 + SM_W + (sl * 4 + i) * STAGE_BYTES, wsrc + i * STAGE_BYTES, STAGE_BYTES, S0 + BAR(BAR_FULL + i) + 32 * qs);
            }
        }
    } else {
        const uint2 ga1 = __ldg(reinterpret_cast<const uint2*>(g1) + lane), bt1 = __ldg(reinterpret_cast<const uint2*>(be1) + lane);
        const uint2 ga2 = __ldg(reinterpret_cast<const uint2*>(g2) + lane), bt2 = __ldg(reinterpret_cast<const uint2*>(be2) + lane);
        if (lane < 8) sts128(SM_GST + lane * 16, make_uint4(0, 0, 0, 0));
        sts128f(SM_COEF + lane * 32, make_float4(0.5f * bf_lo(ga1.x), 0.5f * bf_hi(ga1.x), 0.5f * bf_lo(bt1.x), 0.5f * bf_hi(bt1.x)));
        sts128f(SM_COEF + lane * 32 + 16, make_float4(0.5f * bf_lo(ga1.y), 0.5f * bf_hi(ga1.y), 0.5f * bf_lo(bt1.y), 0.5f * bf_hi(bt1.y)));
        sts128f(SM_COEF + 1024 + lane * 32, make_float4(0.5f * bf_lo(ga2.x), 0.5f * bf_hi(ga2.x), 0.5f * bf_lo(bt2.x), 0.5f * bf_hi(bt2.x)));
        sts128f(SM_COEF + 1024 + lane * 32 + 16, make_float4(0.5f * bf_lo(ga2.y), 0.5f * bf_hi(ga2.y), 0.5f * bf_lo(bt2.y), 0.5f * bf_hi(bt2.y)));
        bar_arrive(4, 256 + 64 + 128);
        bar_sync(0, 96);
#pragma unroll 1
        for (int conv = 0; conv < 2; conv++) {
            if (conv == 1) {
                mbar_wait(BAR(BAR_HW), 0);
                const unsigned c1 = clock32();
                while (clock32() - c1 < PD2) {}
            } else {
                while (clock32() - clk0 < PD) {}
            }
            const float* asrc = conv ? &gs->acc2[b * LS + (lane & 3) * 4] : &gs->acc1[b * 4 * LS + (lane & 3) * GS1];
            unsigned it = 0;
            uint4 fq[NPOLL];
#pragma unroll
            for (int i = 0; i < NPOLL; i++) {
                fq[i] = ld_relaxed_v4(asrc);
                if (i + 1 < NPOLL) { const unsigned c1 = clock32(); while (clock32() - c1 < 450 / NPOLL) {} }
            }
            bool all = false;
#pragma unroll 1
            while (!all) {
#pragma unroll
                for (int i = 0; i < NPOLL; i++) {
                    const uint4 f = fq[i];
                    const bool ok = ((f.x == 0x42800000u) & (f.w == 0x42800000u)) || it > SPIN_LIMIT;
                    if (ok && lane < 4) {
                        const float inv_n = 1.0f / (32.0f * HW * HW);
                        const float mean = __uint_as_float(f.y) * inv_n;
                        const float rs = rsqrtf(fmaxf(fmaf(-mean, mean, __uint_as_float(f.z) * inv_n), 0.f) + 1e-5f);
                        asm volatile("st.shared.v2.f32 [%0], {%1,%2};" ::"r"(S0 + SM_GST + conv * 32 + lane * 8), "f"(rs == 0.f ? 1e-38f : rs), "f"(mean * rs) : "memory");
                    }
                    if (__all_sync(0xffffffffu, ok)) { all = true; break; }
                    fq[i] = ld_relaxed_v4(asrc);
                }
                it++;
            }
            if (lane == 0) { mbar_arrive(BAR(BAR_STATS)); TL(7 + conv * 8); }
        }
        mbar_wait(BAR(BAR_XFREE), 0);
        if (has_outer && elect_one()) {
            mbar_expect(BAR(BAR_X + 4), 16384);
            bulk_g2s(S0 + SM_XOWN, gs->box + cta * 1024, 16384, S0 + BAR(BAR_X + 4));
        }
        if (r == 0) {
            if (lane < 16) gs->acc1[b * 4 * LS + (lane >> 2) * GS1 + (lane & 3)] = 0.f;
            if (lane < 24) gs->wcnt[((lane >> 3) * NB + b) * LS + (lane & 7)] = 0;
        }
    }
}

}

extern "C" void kernel_launch(void* const* d_in, const int* in_sizes, int n_in, void* d_out, int out_size) {
    (void)in_sizes; (void)n_in; (void)out_size;
    typedef CUresult (*EncodeFn)(CUtensorMap*, CUtensorMapDataType, cuuint32_t, void*, const cuuint64_t*, const cuuint64_t*,
                                 const cuuint32_t*, const cuuint32_t*, CUtensorMapInterleave, CUtensorMapSwizzle,
                                 CUtensorMapL2promotion, CUtensorMapFloatOOBfill);
    static Scratch* gs = nullptr;
    static EncodeFn encode = nullptr;
    if (!gs) {
        cudaFuncSetAttribute(resblock_kernel, cudaFuncAttributeMaxDynamicSharedMemorySize, SM_TOTAL);
        cudaGetSymbolAddress((void**)&gs, g_scratch);
        cudaDriverEntryPointQueryResult qr;
        cudaGetDriverEntryPoint("cuTensorMapEncodeTiled", (void**)&encode, cudaEnableDefault, &qr);
    }
    CUtensorMap xmap;
    const cuuint64_t dims[3] = {HW, HW, NB * C}, strides[2] = {HW * 2, HW * HW * 2};
    const cuuint32_t box[3] = {HW, 1, 32}, es[3] = {1, 1, 1};
    encode(&xmap, CU_TENSOR_MAP_DATA_TYPE_BFLOAT16, 3, d_in[0], dims, strides, box, es, CU_TENSOR_MAP_INTERLEAVE_NONE,
           CU_TENSOR_MAP_SWIZZLE_128B, CU_TENSOR_MAP_L2_PROMOTION_NONE, CU_TENSOR_MAP_FLOAT_OOB_FILL_NONE);
    resblock_kernel<<<NCTA + NXTRA, NTHREADS, SM_TOTAL>>>(
        (const __nv_bfloat16*)d_in[4], (const __nv_bfloat16*)d_in[1],
        (const __nv_bfloat16*)d_in[2], (const __nv_bfloat16*)d_in[3], (const __nv_bfloat16*)d_in[5],
        (const __nv_bfloat16*)d_in[6], (const __nv_bfloat16*)d_in[7], (const __nv_bfloat16*)d_in[8],
        (__nv_bfloat16*)d_out, gs, xmap);
}
```

```cpp
#include <cuda_runtime.h>
#include <cuda.h>
#include <cuda_bf16.h>
#include <stdint.h>

namespace {

constexpr int C = 128, HW = 64, NB = 2, E = 768;
constexpr int NCTA = NB * HW;
constexpr int NXTRA = 4;
constexpr int NTHREADS = 16 * 32;
constexpr int CH_PITCH = 66 * 16;
constexpr int ROW_BYTES = 16 * CH_PITCH;
constexpr int STEP_BYTES = 4096;
constexpr int STAGE_BYTES = 3 * STEP_BYTES;
constexpr int NSTAGE = 24;
constexpr int KC_BYTES = 2 * CH_PITCH;
constexpr int NS = 12;
constexpr int LAG = 1;
#define XDELAY 400
#define HDELAY 600
#define SEQ 0
#define MMA0_WAIT mbar_try
#define SPINPAUSE
#define NPOLL 1
#define PD2 0
#define PDELAY 60
#define RB 1
#define XSTAG2 400
#define XSTAG 800
#define HSEND 0
#define W2DELAY 1800

constexpr uint32_t SMEM_BASE = 0x400;
constexpr uint32_t SM_XOWN = SMEM_BASE;
constexpr uint32_t SM_ACT = SM_XOWN + 16384 + 512;
constexpr uint32_t SM_XOUT = SM_ACT + 2 * ROW_BYTES + 512;
static_assert(SM_XOUT % 1024 == 0, "swizzle atom alignment");
constexpr uint32_t SM_W = SM_ACT + 3 * ROW_BYTES + 128;
__host__ __device__ constexpr uint32_t slot_addr(int slot) { return SM_W + slot * STAGE_BYTES; }
constexpr uint32_t SM_COEF = SM_W + NS * STAGE_BYTES;
constexpr uint32_t SM_GST = SM_COEF + 2048;
constexpr uint32_t SM_EMB = SM_GST + 128;
constexpr uint32_t SM_ONES = SM_EMB + 2048;
constexpr uint32_t SM_RED = SM_ONES + 256;
constexpr uint32_t SM_BNC = SM_RED + 1280;
constexpr uint32_t SM_BAR = SM_BNC + 2 * 2304;
constexpr int BAR_FULL = 0, BAR_WEMPTY = NSTAGE, BAR_HW = BAR_WEMPTY + NS, BAR_XFREE = BAR_HW + 1, BAR_STATS = BAR_XFREE + 1,
              BAR_EMB = BAR_STATS + 1, BAR_ACK = BAR_EMB + 1, BAR_X = BAR_ACK + 1  , NBAR = BAR_X + 5;
constexpr int SM_TOTAL = SM_BAR + NBAR * 8 - SMEM_BASE;
static_assert(SM_TOTAL <= 232448, "smem");
static_assert(NBAR <= 96, "barrier init");
constexpr int OUT_PITCH = 144;
__host__ __device__ constexpr uint32_t BAR(int i) { return SM_BAR + 8 * i; }
__host__ __device__ constexpr int ky_of(int kyo) { return kyo == 0 ? 1 : (kyo == 1 ? 0 : 2); }

constexpr unsigned SPIN_LIMIT = 1u << 16;

#define LS 1056
#define GS1 4
#define PD 0
struct Scratch {
    float acc1[NB * 4 * LS];
    float acc2[NB * LS];
    unsigned wcnt[3 * NB * LS];
    float emb[NXTRA * NB * C];
    unsigned char wt[2 * NSTAGE * STAGE_BYTES];
    uint4 box[NCTA * 1024];
};
__device__ __align__(1024) Scratch g_scratch;
#define TL(i) do {} while (0)
#define TLG(i) do {} while (0)

__device__ __forceinline__ unsigned clock32() { unsigned c; asm volatile("mov.u32 %0, %%clock;" : "=r"(c)); return c; }
__device__ __forceinline__ uint32_t mapa(uint32_t a, uint32_t rank) {
    uint32_t d;
    asm("mapa.shared::cluster.u32 %0, %1, %2;" : "=r"(d) : "r"(a), "r"(rank));
    return d;
}
#define S0 mapa(0, blockIdx.x & 1)
__device__ __forceinline__ void mbar_init(uint32_t bar, int cnt) {
    asm volatile("mbarrier.init.shared::cta.b64 [%0], %1;" ::"r"(bar + S0), "r"(cnt) : "memory");
}
__device__ __forceinline__ void mbar_arrive(uint32_t bar) {
    asm volatile("mbarrier.arrive.shared::cta.b64 _, [%0];" ::"r"(bar + S0) : "memory");
}
__device__ __forceinline__ void mbar_expect(uint32_t bar, uint32_t bytes) {
    asm volatile("mbarrier.arrive.expect_tx.shared::cta.b64 _, [%0], %1;" ::"r"(bar + S0), "r"(bytes) : "memory");
}
__device__ __forceinline__ bool mbar_try(uint32_t bar, uint32_t par) {
    uint32_t ok;
    asm volatile("{\n.reg .pred p;\nmbarrier.try_wait.parity.shared::cta.b64 p, [%1], %2;\nselp.u32 %0, 1, 0, p;\n}"
                 : "=r"(ok) : "r"(bar + S0), "r"(par) : "memory");
    return ok;
}
__device__ __forceinline__ bool mbar_test(uint32_t bar, uint32_t par) {
    uint32_t ok;
    asm volatile("{\n.reg .pred p;\nmbarrier.test_wait.parity.shared::cta.b64 p, [%1], %2;\nselp.u32 %0, 1, 0, p;\n}"
                 : "=r"(ok) : "r"(bar + S0), "r"(par) : "memory");
    return ok;
}
__device__ __forceinline__ void mbar_wait(uint32_t bar, uint32_t par) {
    unsigned it = 0;
#pragma unroll 1
    while (!mbar_try(bar, par) && ++it < SPIN_LIMIT) {}
}
__device__ __forceinline__ bool elect_one() {
    uint32_t p;
    asm volatile("{\n.reg .pred p;\nelect.sync _|p, 0xffffffff;\nselp.u32 %0, 1, 0, p;\n}" : "=r"(p));
    return p;
}
__device__ __forceinline__ void fence_async_smem() { asm volatile("fence.proxy.async.shared::cta;" ::: "memory"); }
__device__ __forceinline__ void fence_async_global() { asm volatile("fence.proxy.async.global;" ::: "memory"); }
__device__ __forceinline__ void fence_acquire() { asm volatile("fence.acquire.gpu;" ::: "memory"); }
__device__ __forceinline__ void bar_sync(int id, int n) { asm volatile("bar.sync %0, %1;" ::"r"(id), "r"(n) : "memory"); }
__device__ __forceinline__ void bar_arrive(int id, int n) { asm volatile("bar.arrive %0, %1;" ::"r"(id), "r"(n) : "memory"); }
__device__ __forceinline__ void bulk_g2s(uint32_t dst, const void* src, uint32_t bytes, uint32_t bar) {
    asm volatile("cp.async.bulk.shared::cluster.global.mbarrier::complete_tx::bytes [%0], [%1], %2, [%3];"
                 ::"r"(dst), "l"(src), "r"(bytes), "r"(bar) : "memory");
}
__device__ __forceinline__ void tma_x(uint32_t dst, const CUtensorMap* tm, int row, int ch, uint32_t bar) {
    asm volatile("cp.async.bulk.tensor.3d.shared::cluster.global.mbarrier::complete_tx::bytes [%0], [%1, {%2, %3, %4}], [%5];"
                 ::"r"(dst + S0), "l"(tm), "r"(0), "r"(row), "r"(ch), "r"(bar + S0) : "memory");
}
__device__ __forceinline__ uint4 ld_relaxed_v4(const void* p) {
    uint4 v;
    asm volatile("ld.relaxed.gpu.global.v4.u32 {%0,%1,%2,%3}, [%4];" : "=r"(v.x), "=r"(v.y), "=r"(v.z), "=r"(v.w) : "l"(p) : "memory");
    return v;
}
__device__ __forceinline__ unsigned ld_relaxed(const void* p) {
    unsigned v;
    asm volatile("ld.relaxed.gpu.global.u32 %0, [%1];" : "=r"(v) : "l"(p) : "memory");
    return v;
}
__device__ __forceinline__ void red_add4(float* p, float a, float b, float c, float d) {
    asm volatile("red.relaxed.gpu.global.add.v4.f32 [%0], {%1,%2,%3,%4};" ::"l"(p), "f"(a), "f"(b), "f"(c), "f"(d) : "memory");
}
__device__ __forceinline__ void sts128(uint32_t a, uint4 v) {
    asm volatile("st.shared.v4.u32 [%0], {%1,%2,%3,%4};" ::"r"(a + S0), "r"(v.x), "r"(v.y), "r"(v.z), "r"(v.w) : "memory");
}
__device__ __forceinline__ void sts128f(uint32_t a, float4 v) {
    asm volatile("st.shared.v4.f32 [%0], {%1,%2,%3,%4};" ::"r"(a + S0), "f"(v.x), "f"(v.y), "f"(v.z), "f"(v.w) : "memory");
}
__device__ __forceinline__ void sts32f(uint32_t a, float v) { asm volatile("st.shared.f32 [%0], %1;" ::"r"(a + S0), "f"(v) : "memory"); }
__device__ __forceinline__ uint4 lds128(uint32_t a) {
    uint4 v;
    asm volatile("ld.shared.v4.u32 {%0,%1,%2,%3}, [%4];" : "=r"(v.x), "=r"(v.y), "=r"(v.z), "=r"(v.w) : "r"(a + S0) : "memory");
    return v;
}
__device__ __forceinline__ float4 lds128f(uint32_t a) {
    float4 v;
    asm volatile("ld.shared.v4.f32 {%0,%1,%2,%3}, [%4];" : "=f"(v.x), "=f"(v.y), "=f"(v.z), "=f"(v.w) : "r"(a + S0) : "memory");
    return v;
}
__device__ __forceinline__ float2 lds64f(uint32_t a) {
    float2 v;
    asm volatile("ld.shared.v2.f32 {%0,%1}, [%2];" : "=f"(v.x), "=f"(v.y) : "r"(a + S0) : "memory");
    return v;
}
__device__ __forceinline__ float bf_lo(uint32_t u) { return __uint_as_float(u << 16); }
__device__ __forceinline__ float bf_hi(uint32_t u) { return __uint_as_float(u & 0xffff0000u); }
__device__ __forceinline__ uint32_t pack_bf(float lo, float hi) {
    uint32_t r;
    asm("cvt.rn.bf16x2.f32 %0, %1, %2;" : "=r"(r) : "f"(hi), "f"(lo));
    return r;
}
__device__ __forceinline__ float tanh_fast(float x) {
    float r;
    asm("tanh.approx.f32 %0, %1;" : "=f"(r) : "f"(x));
    return r;
}
__device__ __forceinline__ float silu_half(float h) { return fmaf(h, tanh_fast(h), h); }
__device__ __forceinline__ void ldsm4(uint32_t (&u)[4], uint32_t a) {
    asm volatile("ldmatrix.sync.aligned.m8n8.x4.shared.b16 {%0,%1,%2,%3}, [%4];"
                 : "=r"(u[0]), "=r"(u[1]), "=r"(u[2]), "=r"(u[3]) : "r"(a + S0) : "memory");
}
__device__ __forceinline__ void ldsm4t(uint32_t (&u)[4], uint32_t a) {
    asm volatile("ldmatrix.sync.aligned.m8n8.x4.trans.shared.b16 {%0,%1,%2,%3}, [%4];"
                 : "=r"(u[0]), "=r"(u[1]), "=r"(u[2]), "=r"(u[3]) : "r"(a + S0) : "memory");
}
__device__ __forceinline__ void stsm4(uint32_t a, uint32_t p0, uint32_t p1, uint32_t p2, uint32_t p3) {
    asm volatile("stmatrix.sync.aligned.m8n8.x4.shared.b16 [%0], {%1,%2,%3,%4};" ::"r"(a + S0), "r"(p0), "r"(p1), "r"(p2), "r"(p3) : "memory");
}
__device__ __forceinline__ void stsm4t(uint32_t a, uint32_t p0, uint32_t p1, uint32_t p2, uint32_t p3) {
    asm volatile("stmatrix.sync.aligned.m8n8.x4.trans.shared.b16 [%0], {%1,%2,%3,%4};" ::"r"(a + S0), "r"(p0), "r"(p1), "r"(p2), "r"(p3) : "memory");
}

#define R8(o) "+f"(d[o]), "+f"(d[o + 1]), "+f"(d[o + 2]), "+f"(d[o + 3]), "+f"(d[o + 4]), "+f"(d[o + 5]), "+f"(d[o + 6]), "+f"(d[o + 7])
template <uint32_t ALO, uint32_t BLO, uint64_t AHI = 8, uint64_t BHI = 48>
__device__ __forceinline__ void wgmma128(float (&d)[64]) {
    asm volatile(
        "wgmma.mma_async.sync.aligned.m64n128k16.f32.bf16.bf16 "
        "{%0,%1,%2,%3,%4,%5,%6,%7,%8,%9,%10,%11,%12,%13,%14,%15,%16,%17,%18,%19,%20,%21,%22,%23,%24,%25,%26,%27,%28,%29,%30,%31,"
        "%32,%33,%34,%35,%36,%37,%38,%39,%40,%41,%42,%43,%44,%45,%46,%47,%48,%49,%50,%51,%52,%53,%54,%55,%56,%57,%58,%59,%60,%61,%62,%63},"
        " %64, %65, 1, 1, 1, 0, 0;"
        : R8(0), R8(8), R8(16), R8(24), R8(32), R8(40), R8(48), R8(56)
        : "l"((AHI << 32) | ALO), "l"((BHI << 32) | BLO));
}
template <int S>
__device__ __forceinline__ void mma_stages(float (&d)[64], int conv, int tid, Scratch* gs) {
    constexpr uint32_t A = ((SM_ACT + S * 2 * CH_PITCH + 16) >> 4) | ((CH_PITCH >> 4) << 16);
    constexpr uint32_t B = (slot_addr(S % NS) >> 4) | (8u << 16);
    if (S == 0) {
        unsigned it = 0;
#pragma unroll 1
        while (!MMA0_WAIT(BAR(BAR_FULL), conv) && ++it < SPIN_LIMIT) {}
    }
    bool next_ok = true;
    constexpr uint32_t NEXT = S + 1 < NSTAGE ? BAR(BAR_FULL + S + 1) : BAR(BAR_EMB);
    const int npar = S + 1 < NSTAGE ? conv : 0;
    next_ok = mbar_test(NEXT, npar);
    if (S == 0 && tid == 0) TL(32 + conv * 24);
    asm volatile("wgmma.fence.sync.aligned;" ::: "memory");
    wgmma128<A, B>(d);
    wgmma128<A + 1, B + 16>(d);
    wgmma128<A + 2, B + 32>(d);
    asm volatile("wgmma.commit_group.sync.aligned;" ::: "memory");
    if (S >= LAG) {
        asm volatile("wgmma.wait_group.sync.aligned %0;" ::"n"(LAG) : "memory");
        if ((tid & 31) == 0) mbar_arrive(BAR(BAR_WEMPTY + (S + NS - LAG) % NS));
    }
    if (!next_ok) mbar_wait(NEXT, npar);
    if constexpr (S + 1 < NSTAGE) mma_stages<S + 1>(d, conv, tid, gs);
}

__device__ __forceinline__ void weight_load(uint4 (&t)[5], const __nv_bfloat16* w, int cta, int lane) {
    const char* base = reinterpret_cast<const char*>(w) + ((cta & 15) * 8 * C + (cta >> 4) * 16) * 18;
#pragma unroll
    for (int k = 0; k < 5; k++) {
        const int i = lane + 32 * k, row = (i * 57) >> 10;
        if (k < 4 || lane < 16) t[k] = __ldg(reinterpret_cast<const uint4*>(base + row * (C * 18 - 288) + i * 16));
    }
}
__device__ __forceinline__ void weight_block(uint32_t bounce, unsigned char* wt, int cta, int lane, bool readback, Scratch* gs) {
    unsigned char* dst = wt + (cta >> 4) * STAGE_BYTES + (cta & 15) * 768;
    if (lane < 16) {
        uint32_t v[36];
#pragma unroll
        for (int i = 0; i < 9; i++) {
            const uint4 q = lds128(bounce + (lane & 7) * 288 + (lane >> 3) * 144 + i * 16);
            v[4 * i] = q.x; v[4 * i + 1] = q.y; v[4 * i + 2] = q.z; v[4 * i + 3] = q.w;
        }
#pragma unroll
        for (int kyo = 0; kyo < 3; kyo++) {
#pragma unroll
            for (int kx = 0; kx < 3; kx++) {
                const int tap = ky_of(kyo) * 3 + kx;
                uint32_t o[4];
#pragma unroll
                for (int m = 0; m < 4; m++) {
                    const int i0 = 18 * m + tap, i1 = i0 + 9;
                    const uint32_t sel = ((i0 & 1) ? 0x32u : 0x10u) | ((i1 & 1) ? 0x7600u : 0x5400u);
                    o[m] = __byte_perm(v[i0 >> 1], v[i1 >> 1], sel);
                }
                *reinterpret_cast<uint4*>(dst + kyo * 8 * STAGE_BYTES + kx * 256 + lane * 16) = make_uint4(o[0], o[1], o[2], o[3]);
            }
        }
    }
    if (readback) {
        __syncwarp();
        unsigned acc = 0;
        if (lane < 24) {
#pragma unroll
            for (int i = 0; i < 3; i++) acc |= ld_relaxed(dst + i * 8 * STAGE_BYTES + lane * 32);
        }
        asm volatile("{\n.reg .pred p;\nsetp.eq.u32 p, %0, 0x9e3779b9;\n@p st.shared.u32 [%1], %0;\n}" ::"r"(acc), "r"(bounce + S0) : "memory");
    }
}
__device__ __forceinline__ uint32_t act2(uint32_t u, const float4& cf) {
    return pack_bf(silu_half(fmaf(bf_lo(u), cf.x, cf.z)), silu_half(fmaf(bf_hi(u), cf.y, cf.w)));
}
__device__ __forceinline__ void norm_unit(uint32_t (&u)[4], const float4& ca, const float4& cb) {
    u[0] = act2(u[0], ca); u[1] = act2(u[1], ca); u[2] = act2(u[2], cb); u[3] = act2(u[3], cb);
}
__device__ __forceinline__ void read_stats(uint32_t gst, float (&g)[8]) {
    asm volatile("ld.volatile.shared.v4.f32 {%0,%1,%2,%3}, [%4];" : "=f"(g[0]), "=f"(g[1]), "=f"(g[2]), "=f"(g[3]) : "r"(gst + S0) : "memory");
    asm volatile("ld.volatile.shared.v4.f32 {%0,%1,%2,%3}, [%4];" : "=f"(g[4]), "=f"(g[5]), "=f"(g[6]), "=f"(g[7]) : "r"(gst + 16 + S0) : "memory");
}
template <int T>
__device__ __forceinline__ void group_coefs(uint32_t gst, float (&g)[8], float4 (&cf)[8]) {
    unsigned it = 0;
#pragma unroll 1
    while (!__all_sync(0xffffffffu, g[2 * T] != 0.f) && ++it < 8 * SPIN_LIMIT) { SPINPAUSE; read_stats(gst, g); }
    float4 &ca = cf[2 * T], &cb = cf[2 * T + 1];
    const float rs = g[2 * T], mr = g[2 * T + 1];
    ca.z = fmaf(-mr, ca.x, ca.z); ca.w = fmaf(-mr, ca.y, ca.w); ca.x *= rs; ca.y *= rs;
    cb.z = fmaf(-mr, cb.x, cb.z); cb.w = fmaf(-mr, cb.y, cb.w); cb.x *= rs; cb.y *= rs;
}
template <int FIRST, int N>
__device__ __forceinline__ void norm_block(uint32_t (&u)[4][4], float4 (&cf)[8], uint32_t act, uint32_t mask, uint32_t fbar, int lane) {
#pragma unroll
    for (int t = FIRST; t < FIRST + N; t++) {
        norm_unit(u[t], cf[2 * t], cf[2 * t + 1]);
        stsm4(act + t * 2 * KC_BYTES, u[t][0] & mask, u[t][1] & mask, u[t][2] & mask, u[t][3] & mask);
    }
    fence_async_smem();
    __syncwarp();
    if (lane < N) mbar_arrive(fbar + 16 * (FIRST + lane));
}
__device__ __forceinline__ void publish(uint32_t bar, int lane) {
    fence_async_smem();
    __syncwarp();
    if (lane == 0) mbar_arrive(bar);
}
template <int T>
__device__ __forceinline__ void next_unit(uint32_t (&u)[4][4], float4 (&cf)[8], uint32_t gst, float (&g)[8], uint32_t act, uint32_t fbar, int lane) {
    const bool have = __all_sync(0xffffffffu, g[2 * T] != 0.f);
    if (!have) publish(fbar + 16 * (T - 1), lane);
    group_coefs<T>(gst, g, cf);
    norm_unit(u[T], cf[2 * T], cf[2 * T + 1]);
    if (have) publish(fbar + 16 * (T - 1), lane);
    stsm4(act + T * 2 * KC_BYTES, u[T][0], u[T][1], u[T][2], u[T][3]);
}
__device__ __forceinline__ void stat_mma(float (&c)[4], uint32_t p, uint32_t q) {
    asm("mma.sync.aligned.m16n8k16.row.col.f32.bf16.bf16.f32 {%0,%1,%2,%3}, {%4,%5,%6,%5}, {%4,%6}, {%0,%1,%2,%3};"
        : "+f"(c[0]), "+f"(c[1]), "+f"(c[2]), "+f"(c[3]) : "r"(p), "r"(0x3f803f80u), "r"(q));
}
__device__ __forceinline__ void stat_store(const float (&c)[4], uint32_t dst, int lane) {
    const int g = lane >> 2, t = lane & 3;
    if (t == (g >> 1)) sts32f(dst + g * 4, (g & 1) ? c[1] : c[0]);
    if (g == 7) sts32f(dst + 32 + t * 4, c[2] + c[3]);
}
__device__ __forceinline__ float sum4(float4 v) { return (v.x + v.y) + (v.z + v.w); }
__device__ __forceinline__ void stat_publish(uint32_t src, float* acc, int lane, bool real) {
    const uint32_t a = src + (lane & 15) * 48;
    float q = sum4(lds128f(a)) + sum4(lds128f(a + 16)), sm = sum4(lds128f(a + 32));
    q += __shfl_xor_sync(0xffffffffu, q, 1); sm += __shfl_xor_sync(0xffffffffu, sm, 1);
    q += __shfl_xor_sync(0xffffffffu, q, 2); sm += __shfl_xor_sync(0xffffffffu, sm, 2);
    if (real && (lane & 19) == 0) red_add4(acc + lane, 1.f, sm, q, 1.f);
}
__device__ __forceinline__ void fence_acc(float (&d)[64]) {
#pragma unroll
    for (int i = 0; i < 64; i++) asm volatile("" : "+f"(d[i])::"memory");
}
__device__ __forceinline__ void ld_unit(uint32_t (&u)[4], const uint4* p) {
    asm volatile("ld.relaxed.gpu.global.v4.u32 {%0,%1,%2,%3}, [%4];" : "=r"(u[0]), "=r"(u[1]), "=r"(u[2]), "=r"(u[3]) : "l"(p) : "memory");
}

__device__ __noinline__ void side_jobs(const __nv_bfloat16* __restrict__ t_emb, const __nv_bfloat16* __restrict__ w_emb,
                                       const __nv_bfloat16* __restrict__ w2, Scratch* __restrict__ gs, unsigned clk0) {
    const int tid = threadIdx.x, warp = tid >> 5, lane = tid & 31, j = blockIdx.x;
    float tv = 0.f;
    if (lane < 24) tv = __bfloat162float(t_emb[(lane / 12) * E + j * 192 + warp * 12 + lane % 12]);
    if (tid == 0) {
        mbar_init(BAR(0), 1);
        mbar_expect(BAR(0), 192 * C * 2);
        fence_async_smem();
        while (clock32() - clk0 < W2DELAY) {}
#pragma unroll
        for (int i = 0; i < 4; i++) bulk_g2s(S0 + SM_W + i * 12288, w_emb + (j * 192 + i * 48) * C, 12288, S0 + BAR(0));
    }
    if (j == 0 && tid < 32) gs->acc2[(tid >> 4) * LS + (tid & 15)] = 0.f;
    const float sv = silu_half(0.5f * tv);
    __syncthreads();
    mbar_wait(BAR(0), 0);
    float acc[8] = {0.f, 0.f, 0.f, 0.f, 0.f, 0.f, 0.f, 0.f};
#pragma unroll
    for (int i = 0; i < 12; i++) {
        const float2 wq = lds64f(SM_W + (warp * 12 + i) * 256 + lane * 8);
        const uint32_t wx = __float_as_uint(wq.x), wy = __float_as_uint(wq.y);
#pragma unroll
        for (int bb = 0; bb < 2; bb++) {
            const float sx = __shfl_sync(0xffffffffu, sv, bb * 12 + i);
            acc[4 * bb + 0] = fmaf(sx, bf_lo(wx), acc[4 * bb + 0]); acc[4 * bb + 1] = fmaf(sx, bf_hi(wx), acc[4 * bb + 1]);
            acc[4 * bb + 2] = fmaf(sx, bf_lo(wy), acc[4 * bb + 2]); acc[4 * bb + 3] = fmaf(sx, bf_hi(wy), acc[4 * bb + 3]);
        }
    }
    sts128f(SM_ACT + warp * 1024 + lane * 16, make_float4(acc[0], acc[1], acc[2], acc[3]));
    sts128f(SM_ACT + warp * 1024 + 512 + lane * 16, make_float4(acc[4], acc[5], acc[6], acc[7]));
    __syncthreads();
    if (tid < 128) {
        float2 sum = make_float2(0.f, 0.f);
#pragma unroll
        for (int w = 0; w < 16; w++) { const float2 p = lds64f(SM_ACT + w * 1024 + tid * 8); sum.x += p.x; sum.y += p.y; }
        *reinterpret_cast<float2*>(&gs->emb[j * NB * C + tid * 2]) = sum;
        bar_sync(1, 128);
        if (tid < 2) asm volatile("red.release.gpu.global.add.u32 [%0], 1;" ::"l"(&gs->wcnt[(2 * NB + tid) * LS]) : "memory");
    }
}

__global__ void __cluster_dims__(2, 1, 1) __launch_bounds__(NTHREADS, 1)
resblock_kernel(const __nv_bfloat16* __restrict__ w1,
                const __nv_bfloat16* __restrict__ t_emb, const __nv_bfloat16* __restrict__ g1,
                const __nv_bfloat16* __restrict__ be1, const __nv_bfloat16* __restrict__ w_emb,
                const __nv_bfloat16* __restrict__ g2, const __nv_bfloat16* __restrict__ be2,
                const __nv_bfloat16* __restrict__ w2, Scratch* __restrict__ gs,
                const __grid_constant__ CUtensorMap xmap, const __grid_constant__ CUtensorMap omap) {
    const unsigned clk0 = clock32();
    if (threadIdx.x == 480 && blockIdx.x >= NXTRA) TLG(1);
    const int tid = threadIdx.x, lane = tid & 31;
    const int cta = blockIdx.x - NXTRA, b = cta >> 6, r = cta & 63;
    uint4 v[5];
    if (tid < 32) weight_load(v, w1, cta & (NCTA - 1), lane);
    const int warp = __shfl_sync(0xffffffffu, tid >> 5, 0);
    if (cta < 0) { side_jobs(t_emb, w_emb, w2, gs, clk0); return; }

    if (warp != 3) asm volatile("barrier.cluster.arrive.relaxed.aligned;" ::: "memory");
    const bool has_outer = (r != 0) && (r != HW - 1);
    if (warp == 1 || warp == 2 || warp == 4 || warp == 5) {
        const int g = warp < 3 ? warp - 1 : 7 - warp;
        if (elect_one()) {
            asm volatile("prefetch.tensormap [%0];" ::"l"(&xmap) : "memory");
            mbar_init(BAR(BAR_X) + 8 * g, 1);
            if (g == 3) mbar_init(BAR(BAR_X + 4), 1);
            mbar_expect(BAR(BAR_X) + 8 * g, 4096);
            fence_async_smem();
            while (clock32() - clk0 < XDELAY + (g >> 1) * XSTAG + (g & 1) * XSTAG2) {}
            tma_x(SM_XOWN + g * 4096, &xmap, r, b * C + g * 32, BAR(BAR_X) + 8 * g);
            if (g == 3 && has_outer) {
                mbar_expect(BAR(BAR_X + 4), 16384);
#pragma unroll
                for (int i = 0; i < 4; i++) tma_x(SM_XOUT + i * 4096, &xmap, r + ((r & 1) ? 1 : -1), b * C + i * 32, BAR(BAR_X + 4));
            }
        }
        __syncwarp();
        bar_arrive(4, 256 + 64 + 128);
        mbar_wait(BAR(BAR_X) + 8 * g, 0);
        if (lane == 0) TL(70 + g);
        float c[8][4];
#pragma unroll
        for (int k = 0; k < 8; k++) {
            const uint4 q = lds128(SM_XOWN + g * 4096 + k * 512 + lane * 16);
            c[k][0] = c[k][1] = c[k][2] = c[k][3] = 0.f;
            stat_mma(c[k], q.x, q.y); stat_mma(c[k], q.z, q.w);
        }
#pragma unroll
        for (int i = 0; i < 4; i++) c[0][i] = ((c[0][i] + c[1][i]) + (c[2][i] + c[3][i])) + ((c[4][i] + c[5][i]) + (c[6][i] + c[7][i]));
        if (lane == 0 && g == 0) { if (c[0][0] == 1.2345f) sts32f(SM_RED, 0.f); TL(92); }
        stat_store(c[0], SM_RED + g * 48, lane);
        __syncwarp();
        if (lane == 0) {
            const uint32_t a = SM_RED + g * 48;
            red_add4(&gs->acc1[b * 4 * LS + g * GS1], 1.f, sum4(lds128f(a + 32)), sum4(lds128f(a)) + sum4(lds128f(a + 16)), 1.f);
            TL(74 + g);
        }
    }
    if (warp == 3) {
            if (elect_one()) {
#pragma unroll
                for (int i = 0; i < NSTAGE; i++) mbar_init(BAR(BAR_FULL + i), (i >> 3) == 1 ? 1 : 5);
#pragma unroll
                for (int i = 0; i < NS + 2; i++) mbar_init(BAR(BAR_WEMPTY + i), 4);
#pragma unroll
                for (int i = BAR_STATS; i < BAR_X; i++) mbar_init(BAR(i), i == BAR_EMB ? 3 : 1);
                asm volatile("fence.mbarrier_init.release.cluster;" ::: "memory");
            }
            __syncwarp();
            fence_async_smem();
            bar_arrive(0, 96);
            bar_arrive(5, 96);
            bar_arrive(4, 256 + 64 + 128);
            const uint4 z = make_uint4(0, 0, 0, 0);
#pragma unroll
            for (int i = 0; i < 2; i++) sts128(SM_ACT + (i * 16 + (lane >> 1)) * CH_PITCH + (lane & 1) * 16, z);
            if (lane < 4) sts128(SM_ACT + (2 + (lane >> 1)) * ROW_BYTES + (lane & 1) * 16, z);
            if (lane < 16) sts128(SM_ONES + lane * 16, make_uint4(lane < 8 ? 0x3f803f80u : 0u, 0, 0, 0));
            fence_async_smem();
            asm volatile("barrier.cluster.arrive.relaxed.aligned;" ::: "memory");
            if (lane == 0) TL(5);
            while (clock32() - clk0 < W2DELAY) {}
            weight_load(v, w2, cta, lane);
        }
    if (warp == 0 || warp == 3) {
        const int k = warp & 1;
#pragma unroll
        for (int i = 0; i < 5; i++)
            if (i < 4 || lane < 16) sts128(SM_BNC + k * 2304 + (lane + 32 * i) * 16, v[i]);
        if (lane == 0) TL(k ? 14 : 81);
        __syncwarp();
        weight_block(SM_BNC + k * 2304, gs->wt + k * NSTAGE * STAGE_BYTES, cta, lane, true, gs);
        __syncwarp();
        if (lane == 0) TL(k ? 13 : 4);
        if (lane < 2) asm volatile("red.relaxed.gpu.global.add.u32 [%0], 1;" ::"l"(&gs->wcnt[(k * NB + lane) * LS + (k ? 0 : cta >> 4)]) : "memory");
    }

    if (warp >= 8) {
        const int nw = warp - 8;
        bar_sync(4, 256 + 64 + 128);
        const int par = nw >> 2, wq = nw & 3;
        const uint32_t act_off = SM_ACT + (par * 2 + (lane >> 4)) * CH_PITCH + (2 + wq * 16 + (lane & 15)) * 16;
        const uint32_t stg_off = (par * 16 + (lane >> 4) * 8 + (lane & 7)) * 128 + (((2 * wq + ((lane >> 3) & 1)) ^ (lane & 7)) << 4);
        const uint32_t cfa = SM_COEF + par * 128 + (lane & 3) * 16;
        const uint32_t fbar = BAR(BAR_FULL) + 8 * par;
        uint4* inbox = gs->box + cta * 1024 + nw * 32 + lane;
#pragma unroll 1
        for (int conv = 0; conv < 2; conv++) {
            uint32_t u[4][4], w[4][4];
            float4 cf[8];
            if (conv == 0) {
#pragma unroll
                for (int i = 0; i < 4; i++) { mbar_wait(BAR(BAR_X + i), 0); ldsm4t(u[i], SM_XOWN + stg_off + i * 4096); }
            } else {
                mbar_wait(BAR(BAR_HW), 0);
#pragma unroll
                for (int i = 0; i < 4; i++) ldsm4(u[i], act_off + i * 2 * KC_BYTES);
            }
#pragma unroll
            for (int i = 0; i < 8; i++) cf[i] = lds128f(cfa + conv * 1024 + (i >> 1) * 256 + (i & 1) * 64);
            const uint32_t gst = SM_GST + conv * 32;
            float gv[8];
            read_stats(gst, gv);
            group_coefs<0>(gst, gv, cf);
            if (tid == 256) TL(22 + conv * 4);
            if (par) { const unsigned c1 = clock32(); while (clock32() - c1 < PDELAY) {} }
            norm_block<0, 1>(u, cf, act_off, ~0u, fbar, lane);
            if (tid == 256) TL(8 + conv * 8);
            group_coefs<1>(gst, gv, cf);
            norm_unit(u[1], cf[2], cf[3]);
            stsm4(act_off + 2 * KC_BYTES, u[1][0], u[1][1], u[1][2], u[1][3]);
            next_unit<2>(u, cf, gst, gv, act_off, fbar, lane);
            next_unit<3>(u, cf, gst, gv, act_off, fbar, lane);
            publish(fbar + 48, lane);
            if (tid == 256) TL(84 + conv);
            if (has_outer) {
                mbar_wait(BAR(BAR_X + 4), conv);
                if (conv == 0) {
#pragma unroll
                    for (int i = 0; i < 4; i++) ldsm4t(w[i], SM_XOUT + stg_off + i * 4096);
                } else {
#pragma unroll
                    for (int i = 0; i < 4; i++) {
                        const uint4 q = lds128(SM_XOWN + (tid - 256) * 16 + i * 4096);
                        w[i][0] = q.x; w[i][1] = q.y; w[i][2] = q.z; w[i][3] = q.w;
                    }
                    unsigned it = 0;
                    while (true) {
                        bool ok = true;
#pragma unroll
                        for (int i = 0; i < 16; i++) ok = ok && w[i >> 2][i & 3] != 0;
                        if (__all_sync(0xffffffffu, ok) || ++it > SPIN_LIMIT) break;
#pragma unroll
                        for (int i = 0; i < 4; i++) ld_unit(w[i], inbox + i * 256);
                    }
#pragma unroll
                    for (int i = 0; i < 16; i++) w[i >> 2][i & 3] = ~w[i >> 2][i & 3];
                }
            }
            if (conv == 0) {
                bar_sync(3, 256);
                if (nw == 0) sts128(SM_ACT + 2 * ROW_BYTES + (lane >> 1) * CH_PITCH + (lane & 1) * 16, make_uint4(0, 0, 0, 0));
            }
            if (tid == 256) TL(24 + conv * 4);
            norm_block<0, 2>(w, cf, act_off + 2 * ROW_BYTES, has_outer ? ~0u : 0u, fbar + 128, lane);
            if (tid == 256) TL(88 + conv);
            norm_block<2, 2>(w, cf, act_off + 2 * ROW_BYTES, has_outer ? ~0u : 0u, fbar + 128, lane);
            if (tid == 256) TL(23 + conv * 4);
        }
        if (has_outer) {
            mbar_wait(BAR(BAR_FULL + NSTAGE - 1), 1);
#pragma unroll
            for (int i = 0; i < 4; i++) inbox[i * 256] = make_uint4(0, 0, 0, 0);
        }
    } else if (warp < 4) {
        const int wq = warp;
        bar_sync(2, 128);

        const uint32_t xbase = SM_XOWN + ((lane >> 4) * 8 + (lane & 7)) * 128 + (((2 * wq + ((lane >> 3) & 1)) ^ (lane & 7)) << 4);
        if (tid == 0) asm volatile("prefetch.tensormap [%0];" ::"l"(&omap) : "memory");
        float d[64];
#pragma unroll
        for (int i = 0; i < 64; i++) d[i] = 0.f;
#pragma unroll 1
        for (int conv = 0; conv < 2; conv++) {
            fence_acc(d);
            mma_stages<0>(d, conv, tid, gs);
            if (conv == 0) {
                asm volatile("wgmma.fence.sync.aligned;" ::: "memory");
                wgmma128<(SM_ONES >> 4) | (8u << 16), (SM_EMB >> 4), 0, 8>(d);
                asm volatile("wgmma.commit_group.sync.aligned;" ::: "memory");
            }
            asm volatile("wgmma.wait_group.sync.aligned 0;" ::: "memory");
            fence_acc(d);
            if (tid == 0) TL(10 + conv * 8);
            uint32_t hp[32];
#pragma unroll
            for (int i = 0; i < 32; i++) hp[i] = pack_bf(d[2 * i], d[2 * i + 1]);
            if (conv == 1) {
#pragma unroll
                for (int kc = 0; kc < 8; kc++) stsm4t(xbase + kc * 2048, hp[4 * kc], hp[4 * kc + 1], hp[4 * kc + 2], hp[4 * kc + 3]);
                fence_async_smem();
                bar_sync(2, 128);
                if (elect_one()) {
                    asm volatile("cp.async.bulk.tensor.3d.global.shared::cta.bulk_group [%0, {%1, %2, %3}], [%4];"
                                 ::"l"(&omap), "r"(0), "r"(r), "r"(b * C + wq * 32), "r"(S0 + SM_XOWN + wq * 4096) : "memory");
                    asm volatile("cp.async.bulk.commit_group;" ::: "memory");
                    asm volatile("cp.async.bulk.wait_group.read 0;" ::: "memory");
                }
                break;
            }
#pragma unroll
            for (int g = 0; g < 4; g++) {
                float c[4] = {0.f, 0.f, 0.f, 0.f};
#pragma unroll
                for (int i = 0; i < 4; i++) stat_mma(c, hp[8 * g + 2 * i], hp[8 * g + 2 * i + 1]);
                stat_store(c, SM_RED + (g * 4 + wq) * 48, lane);
            }
            bar_sync(2, 128);
            if (wq == 0) stat_publish(SM_RED, &gs->acc2[b * LS], lane, true);
            if (tid == 0) TL(11);
            const uint32_t hbase = SM_ACT + (lane >> 4) * CH_PITCH + (2 + wq * 16 + (lane & 15)) * 16;
#pragma unroll
            for (int kc = 0; kc < 8; kc++) stsm4(hbase + kc * 2 * CH_PITCH, hp[4 * kc], hp[4 * kc + 1], hp[4 * kc + 2], hp[4 * kc + 3]);
            __syncwarp();
            if (lane == 0) mbar_arrive(BAR(BAR_HW));
            if (lane < LAG) mbar_arrive(BAR(BAR_WEMPTY + (NSTAGE - LAG) % NS) + 8 * lane);
            if (has_outer) {
                uint4* outbox = gs->box + (cta + ((r & 1) ? 1 : -1)) * 1024 + tid;
#pragma unroll
                for (int kc = 0; kc < 8; kc++) outbox[kc * 128] = make_uint4(~hp[4 * kc], ~hp[4 * kc + 1], ~hp[4 * kc + 2], ~hp[4 * kc + 3]);
            }
            if (tid == 0) TL(12);
#pragma unroll
            for (int kc = 0; kc < 8; kc++) {
                uint32_t p[4];
                ldsm4t(p, xbase + kc * 2048);
#pragma unroll
                for (int i = 0; i < 4; i++) { d[8 * kc + 2 * i] = bf_lo(p[i]); d[8 * kc + 2 * i + 1] = bf_hi(p[i]); }
            }
            fence_async_smem();
            __syncwarp();
            if (lane == 0) mbar_arrive(BAR(BAR_XFREE));
        }
        {
            if (tid == 0) { TL(20); TLG(21); }
        }
    } else if (warp < 6) {
        bar_sync(5, 96);
        if (warp == 5) {
            asm volatile("barrier.cluster.wait.acquire.aligned;" ::: "memory");
            const uint32_t peer = (r & 1) ^ 1;
            const uint32_t self0 = mapa(0, r & 1), peer0 = mapa(0, peer);
#pragma unroll 1
            for (int conv = 0; conv < 2; conv++) {
#pragma unroll 1
                for (int kc = 0; kc < 8; kc++) {
                    mbar_wait(BAR(BAR_FULL) + 8 * kc, conv);
                    if (elect_one())
                        asm volatile("cp.async.bulk.shared::cluster.shared::cta.mbarrier::complete_tx::bytes [%0], [%1], %2, [%3];"
                                     ::"r"(peer0 + SM_ACT + ROW_BYTES + kc * KC_BYTES), "r"(self0 + SM_ACT + kc * KC_BYTES), "r"(KC_BYTES),
                                       "r"(peer0 + BAR(BAR_FULL + 8) + 8 * kc) : "memory");
                }
                if (lane == 0) TL(86 + conv);
#pragma unroll 1
                for (int kc = 0; kc < 8; kc++) mbar_wait(BAR(BAR_FULL + 8) + 8 * kc, conv);
                if (lane == 0)
                    asm volatile("mbarrier.arrive.release.cluster.shared::cluster.b64 _, [%0];" ::"r"(peer0 + (conv ? BAR(BAR_ACK) : BAR(BAR_EMB))) : "memory");
            }
            mbar_wait(BAR(BAR_ACK), 0);
        } else {
            mbar_wait(BAR(BAR_STATS), 0);
            unsigned it = 0;
            while (ld_relaxed(&gs->wcnt[(2 * NB + b) * LS]) < (unsigned)NXTRA && ++it < SPIN_LIMIT) __nanosleep(100);
            fence_acquire();
            float ev[4] = {0.f, 0.f, 0.f, 0.f};
#pragma unroll
            for (int j = 0; j < NXTRA; j++) {
                const uint4 ef = ld_relaxed_v4(&gs->emb[(j * NB + b) * C + lane * 4]);
                ev[0] += __uint_as_float(ef.x); ev[1] += __uint_as_float(ef.y); ev[2] += __uint_as_float(ef.z); ev[3] += __uint_as_float(ef.w);
            }
#pragma unroll
            for (int i = 0; i < 4; i++) {
                const float hi = bf_lo(pack_bf(ev[i], 0.f));
                sts128(SM_EMB + (lane * 4 + i) * 16, make_uint4(pack_bf(hi, ev[i] - hi), 0, 0, 0));
            }
            fence_async_smem();
            __syncwarp();
            if (lane == 0) { mbar_arrive(BAR(BAR_EMB)); TL(19); }
        }
    } else if (warp == 6) {
        bar_sync(0, 96);
        const uint32_t ebytes = STAGE_BYTES + ((lane >> 3) == 1 ? KC_BYTES : 0);
        if (lane < NSTAGE) mbar_expect(BAR(BAR_FULL) + 8 * lane, ebytes);
        const int swap = (r & 1) ? 0 : 8 * STAGE_BYTES;
        unsigned it = 0;
        {
            int g = 0;
#pragma unroll 1
            while (g < NS) {
                unsigned ready = __ballot_sync(0xffffffffu, ld_relaxed(&gs->wcnt[b * LS + (lane & 7)]) >= 16u) >> g;
                if (++it > SPIN_LIMIT) ready = ~0u;
                if (!(ready & 1)) continue;
                fence_acquire();
                fence_async_global();
                if (lane == 0) TL(g ? 3 : 6);
#pragma unroll 1
                for (; (ready & 1) && g < NS; g++, ready >>= 1)
                    if (elect_one())
                        bulk_g2s(S0 + SM_W + g * STAGE_BYTES, gs->wt + g * STAGE_BYTES + (g >= 8 ? swap : 0), STAGE_BYTES, S0 + BAR(BAR_FULL) + 8 * g);
            }
        }
#pragma unroll 1
        for (int q = 3; q < 12; q++) {
            const int conv = q >= 6, qs = conv ? q - 6 : q, sl = q % 3;
            const unsigned char* wsrc = gs->wt + q * 4 * STAGE_BYTES + (qs < 2 ? 0 : (qs < 4 ? swap : -swap));
            const uint32_t par = (q / 3 - 1) & 1;
            if (q == 6) {
                it = 0;
                while (ld_relaxed(&gs->wcnt[(NB + b) * LS]) < (unsigned)NCTA && ++it < SPIN_LIMIT) {}
                fence_acquire();
                fence_async_global();
                if (lane == 0) { mbar_arrive(BAR(BAR_EMB)); TL(2); }
            }
#pragma unroll
            for (int i = 0; i < 4; i++) {
                mbar_wait(BAR(BAR_WEMPTY + i) + 32 * sl, par);
                if (i == 0 && (q == 6 || q == 9)) {
                    if ((lane >= NS) == (q == 9) && lane < NSTAGE) mbar_expect(BAR(BAR_FULL) + 8 * lane, ebytes);
                    __syncwarp();
                }
                if (elect_one())
                    bulk_g2s(S0 + SM_W + (sl * 4 + i) * STAGE_BYTES, wsrc + i * STAGE_BYTES, STAGE_BYTES, S0 + BAR(BAR_FULL + i) + 32 * qs);
            }
        }
    } else {
        const uint2 ga1 = __ldg(reinterpret_cast<const uint2*>(g1) + lane), bt1 = __ldg(reinterpret_cast<const uint2*>(be1) + lane);
        const uint2 ga2 = __ldg(reinterpret_cast<const uint2*>(g2) + lane), bt2 = __ldg(reinterpret_cast<const uint2*>(be2) + lane);
        if (lane < 8) sts128(SM_GST + lane * 16, make_uint4(0, 0, 0, 0));
        sts128f(SM_COEF + lane * 32, make_float4(0.5f * bf_lo(ga1.x), 0.5f * bf_hi(ga1.x), 0.5f * bf_lo(bt1.x), 0.5f * bf_hi(bt1.x)));
        sts128f(SM_COEF + lane * 32 + 16, make_float4(0.5f * bf_lo(ga1.y), 0.5f * bf_hi(ga1.y), 0.5f * bf_lo(bt1.y), 0.5f * bf_hi(bt1.y)));
        sts128f(SM_COEF + 1024 + lane * 32, make_float4(0.5f * bf_lo(ga2.x), 0.5f * bf_hi(ga2.x), 0.5f * bf_lo(bt2.x), 0.5f * bf_hi(bt2.x)));
        sts128f(SM_COEF + 1024 + lane * 32 + 16, make_float4(0.5f * bf_lo(ga2.y), 0.5f * bf_hi(ga2.y), 0.5f * bf_lo(bt2.y), 0.5f * bf_hi(bt2.y)));
        bar_arrive(4, 256 + 64 + 128);
        bar_sync(0, 96);
#pragma unroll 1
        for (int conv = 0; conv < 2; conv++) {
            if (conv == 1) {
                mbar_wait(BAR(BAR_HW), 0);
                const unsigned c1 = clock32();
                while (clock32() - c1 < PD2) {}
            } else {
                while (clock32() - clk0 < PD) {}
            }
            const float* asrc = conv ? &gs->acc2[b * LS + (lane & 3) * 4] : &gs->acc1[b * 4 * LS + (lane & 3) * GS1];
            unsigned it = 0;
            uint4 fq[NPOLL];
#pragma unroll
            for (int i = 0; i < NPOLL; i++) {
                fq[i] = ld_relaxed_v4(asrc);
                if (i + 1 < NPOLL) { const unsigned c1 = clock32(); while (clock32() - c1 < 450 / NPOLL) {} }
            }
            bool all = false;
#pragma unroll 1
            while (!all) {
#pragma unroll
                for (int i = 0; i < NPOLL; i++) {
                    const uint4 f = fq[i];
                    const bool ok = ((f.x == 0x42800000u) & (f.w == 0x42800000u)) || it > SPIN_LIMIT;
                    if (ok && lane < 4) {
                        const float inv_n = 1.0f / (32.0f * HW * HW);
                        const float mean = __uint_as_float(f.y) * inv_n;
                        const float rs = rsqrtf(fmaxf(fmaf(-mean, mean, __uint_as_float(f.z) * inv_n), 0.f) + 1e-5f);
                        asm volatile("st.shared.v2.f32 [%0], {%1,%2};" ::"r"(S0 + SM_GST + conv * 32 + lane * 8), "f"(rs == 0.f ? 1e-38f : rs), "f"(mean * rs) : "memory");
                    }
                    if (__all_sync(0xffffffffu, ok)) { all = true; break; }
                    fq[i] = ld_relaxed_v4(asrc);
                }
                it++;
            }
            if (lane == 0) { mbar_arrive(BAR(BAR_STATS)); TL(7 + conv * 8); }
        }
        mbar_wait(BAR(BAR_XFREE), 0);
        if (has_outer && elect_one()) {
            mbar_expect(BAR(BAR_X + 4), 16384);
            bulk_g2s(S0 + SM_XOWN, gs->box + cta * 1024, 16384, S0 + BAR(BAR_X + 4));
        }
        if (r == 0) {
            if (lane < 16) gs->acc1[b * 4 * LS + (lane >> 2) * GS1 + (lane & 3)] = 0.f;
            if (lane < 24) gs->wcnt[((lane >> 3) * NB + b) * LS + (lane & 7)] = 0;
        }
    }
}

}

extern "C" void kernel_launch(void* const* d_in, const int* in_sizes, int n_in, void* d_out, int out_size) {
    (void)in_sizes; (void)n_in; (void)out_size;
    typedef CUresult (*EncodeFn)(CUtensorMap*, CUtensorMapDataType, cuuint32_t, void*, const cuuint64_t*, const cuuint64_t*,
                                 const cuuint32_t*, const cuuint32_t*, CUtensorMapInterleave, CUtensorMapSwizzle,
                                 CUtensorMapL2promotion, CUtensorMapFloatOOBfill);
    static Scratch* gs = nullptr;
    static EncodeFn encode = nullptr;
    if (!gs) {
        cudaFuncSetAttribute(resblock_kernel, cudaFuncAttributeMaxDynamicSharedMemorySize, SM_TOTAL);
        cudaGetSymbolAddress((void**)&gs, g_scratch);
        cudaDriverEntryPointQueryResult qr;
        cudaGetDriverEntryPoint("cuTensorMapEncodeTiled", (void**)&encode, cudaEnableDefault, &qr);
    }
    CUtensorMap xmap, omap;
    const cuuint64_t dims[3] = {HW, HW, NB * C}, strides[2] = {HW * 2, HW * HW * 2};
    const cuuint32_t box[3] = {HW, 1, 32}, es[3] = {1, 1, 1};
    encode(&xmap, CU_TENSOR_MAP_DATA_TYPE_BFLOAT16, 3, d_in[0], dims, strides, box, es, CU_TENSOR_MAP_INTERLEAVE_NONE,
           CU_TENSOR_MAP_SWIZZLE_128B, CU_TENSOR_MAP_L2_PROMOTION_NONE, CU_TENSOR_MAP_FLOAT_OOB_FILL_NONE);
    encode(&omap, CU_TENSOR_MAP_DATA_TYPE_BFLOAT16, 3, d_out, dims, strides, box, es, CU_TENSOR_MAP_INTERLEAVE_NONE,
           CU_TENSOR_MAP_SWIZZLE_128B, CU_TENSOR_MAP_L2_PROMOTION_NONE, CU_TENSOR_MAP_FLOAT_OOB_FILL_NONE);
    resblock_kernel<<<NCTA + NXTRA, NTHREADS, SM_TOTAL>>>(
        (const __nv_bfloat16*)d_in[4], (const __nv_bfloat16*)d_in[1],
        (const __nv_bfloat16*)d_in[2], (const __nv_bfloat16*)d_in[3], (const __nv_bfloat16*)d_in[5],
        (const __nv_bfloat16*)d_in[6], (const __nv_bfloat16*)d_in[7], (const __nv_bfloat16*)d_in[8],
        gs, xmap, omap);
}
```

```cpp
#include <cuda_runtime.h>
#include <cuda.h>
#include <cuda_bf16.h>
#include <stdint.h>

namespace {

constexpr int C = 128, HW = 64, NB = 2, E = 768;
constexpr int NCTA = NB * HW;
constexpr int NXTRA = 4;
constexpr int NTHREADS = 16 * 32;
constexpr int CH_PITCH = 66 * 16;
constexpr int ROW_BYTES = 16 * CH_PITCH;
constexpr int STEP_BYTES = 4096;
constexpr int STAGE_BYTES = 3 * STEP_BYTES;
constexpr int NSTAGE = 24;
constexpr int KC_BYTES = 2 * CH_PITCH;
constexpr int NS = 12;
constexpr int LAG = 1;
#define XDELAY 400
#define HDELAY 600
#define SEQ 0
#define MMA0_WAIT mbar_try
#define SPINPAUSE
#define NPOLL 1
#define PD2 0
#define PDELAY 60
#define RB 1
#define XSTAG2 400
#define XSTAG 800
#define HSEND 0
#define W2DELAY 1800

constexpr uint32_t SMEM_BASE = 0x400;
constexpr uint32_t SM_XOWN = SMEM_BASE;
constexpr uint32_t SM_ACT = SM_XOWN + 16384 + 512;
constexpr uint32_t SM_XOUT = SM_ACT + 2 * ROW_BYTES + 512;
static_assert(SM_XOUT % 1024 == 0, "swizzle atom alignment");
constexpr uint32_t SM_W = SM_ACT + 3 * ROW_BYTES + 128;
__host__ __device__ constexpr uint32_t slot_addr(int slot) { return SM_W + slot * STAGE_BYTES; }
constexpr uint32_t SM_COEF = SM_W + NS * STAGE_BYTES;
constexpr uint32_t SM_GST = SM_COEF + 2048;
constexpr uint32_t SM_EMB = SM_GST + 128;
constexpr uint32_t SM_ONES = SM_EMB + 2048;
constexpr uint32_t SM_RED = SM_ONES + 256;
constexpr uint32_t SM_BNC = SM_RED + 1280;
constexpr uint32_t SM_BAR = SM_BNC + 2 * 2304;
constexpr int BAR_FULL = 0, BAR_WEMPTY = NSTAGE, BAR_HW = BAR_WEMPTY + NS, BAR_XFREE = BAR_HW + 1, BAR_STATS = BAR_XFREE + 1,
              BAR_EMB = BAR_STATS + 1, BAR_ACK = BAR_EMB + 1, BAR_X = BAR_ACK + 1  , NBAR = BAR_X + 5;
constexpr int SM_TOTAL = SM_BAR + NBAR * 8 - SMEM_BASE;
static_assert(SM_TOTAL <= 232448, "smem");
static_assert(NBAR <= 96, "barrier init");
__host__ __device__ constexpr uint32_t BAR(int i) { return SM_BAR + 8 * i; }
__host__ __device__ constexpr int ky_of(int kyo) { return kyo == 0 ? 1 : (kyo == 1 ? 0 : 2); }

constexpr unsigned SPIN_LIMIT = 1u << 16;

#define LS 1056
#define GS1 4
#define PD 0
struct Scratch {
    float acc1[NB * 4 * LS];
    float acc2[NB * LS];
    unsigned wcnt[3 * NB * LS];
    float emb[NXTRA * NB * C];
    unsigned char wt[2 * NSTAGE * STAGE_BYTES];
    uint4 box[NCTA * 1024];
};
__device__ __align__(1024) Scratch g_scratch;
#define TL(i) do {} while (0)
#define TLG(i) do {} while (0)

__device__ __forceinline__ unsigned clock32() { unsigned c; asm volatile("mov.u32 %0, %%clock;" : "=r"(c)); return c; }
__device__ __forceinline__ uint32_t mapa(uint32_t a, uint32_t rank) {
    uint32_t d;
    asm("mapa.shared::cluster.u32 %0, %1, %2;" : "=r"(d) : "r"(a), "r"(rank));
    return d;
}
#define S0 mapa(0, blockIdx.x & 1)
__device__ __forceinline__ void mbar_init(uint32_t bar, int cnt) {
    asm volatile("mbarrier.init.shared::cta.b64 [%0], %1;" ::"r"(bar + S0), "r"(cnt) : "memory");
}
__device__ __forceinline__ void mbar_arrive(uint32_t bar) {
    asm volatile("mbarrier.arrive.shared::cta.b64 _, [%0];" ::"r"(bar + S0) : "memory");
}
__device__ __forceinline__ void mbar_expect(uint32_t bar, uint32_t bytes) {
    asm volatile("mbarrier.arrive.expect_tx.shared::cta.b64 _, [%0], %1;" ::"r"(bar + S0), "r"(bytes) : "memory");
}
__device__ __forceinline__ bool mbar_try(uint32_t bar, uint32_t par) {
    uint32_t ok;
    asm volatile("{\n.reg .pred p;\nmbarrier.try_wait.parity.shared::cta.b64 p, [%1], %2;\nselp.u32 %0, 1, 0, p;\n}"
                 : "=r"(ok) : "r"(bar + S0), "r"(par) : "memory");
    return ok;
}
__device__ __forceinline__ bool mbar_test(uint32_t bar, uint32_t par) {
    uint32_t ok;
    asm volatile("{\n.reg .pred p;\nmbarrier.test_wait.parity.shared::cta.b64 p, [%1], %2;\nselp.u32 %0, 1, 0, p;\n}"
                 : "=r"(ok) : "r"(bar + S0), "r"(par) : "memory");
    return ok;
}
__device__ __forceinline__ void mbar_wait(uint32_t bar, uint32_t par) {
    unsigned it = 0;
#pragma unroll 1
    while (!mbar_try(bar, par) && ++it < SPIN_LIMIT) {}
}
__device__ __forceinline__ bool elect_one() {
    uint32_t p;
    asm volatile("{\n.reg .pred p;\nelect.sync _|p, 0xffffffff;\nselp.u32 %0, 1, 0, p;\n}" : "=r"(p));
    return p;
}
__device__ __forceinline__ void fence_async_smem() { asm volatile("fence.proxy.async.shared::cta;" ::: "memory"); }
__device__ __forceinline__ void fence_async_global() { asm volatile("fence.proxy.async.global;" ::: "memory"); }
__device__ __forceinline__ void fence_acquire() { asm volatile("fence.acquire.gpu;" ::: "memory"); }
__device__ __forceinline__ void bar_sync(int id, int n) { asm volatile("bar.sync %0, %1;" ::"r"(id), "r"(n) : "memory"); }
__device__ __forceinline__ void bar_arrive(int id, int n) { asm volatile("bar.arrive %0, %1;" ::"r"(id), "r"(n) : "memory"); }
__device__ __forceinline__ void bulk_g2s(uint32_t dst, const void* src, uint32_t bytes, uint32_t bar) {
    asm volatile("cp.async.bulk.shared::cluster.global.mbarrier::complete_tx::bytes [%0], [%1], %2, [%3];"
                 ::"r"(dst), "l"(src), "r"(bytes), "r"(bar) : "memory");
}
__device__ __forceinline__ void tma_x(uint32_t dst, const CUtensorMap* tm, int row, int ch, uint32_t bar) {
    asm volatile("cp.async.bulk.tensor.3d.shared::cluster.global.mbarrier::complete_tx::bytes [%0], [%1, {%2, %3, %4}], [%5];"
                 ::"r"(dst + S0), "l"(tm), "r"(0), "r"(row), "r"(ch), "r"(bar + S0) : "memory");
}
__device__ __forceinline__ uint4 ld_relaxed_v4(const void* p) {
    uint4 v;
    asm volatile("ld.relaxed.gpu.global.v4.u32 {%0,%1,%2,%3}, [%4];" : "=r"(v.x), "=r"(v.y), "=r"(v.z), "=r"(v.w) : "l"(p) : "memory");
    return v;
}
__device__ __forceinline__ unsigned ld_relaxed(const void* p) {
    unsigned v;
    asm volatile("ld.relaxed.gpu.global.u32 %0, [%1];" : "=r"(v) : "l"(p) : "memory");
    return v;
}
__device__ __forceinline__ void red_add4(float* p, float a, float b, float c, float d) {
    asm volatile("red.relaxed.gpu.global.add.v4.f32 [%0], {%1,%2,%3,%4};" ::"l"(p), "f"(a), "f"(b), "f"(c), "f"(d) : "memory");
}
__device__ __forceinline__ void sts128(uint32_t a, uint4 v) {
    asm volatile("st.shared.v4.u32 [%0], {%1,%2,%3,%4};" ::"r"(a + S0), "r"(v.x), "r"(v.y), "r"(v.z), "r"(v.w) : "memory");
}
__device__ __forceinline__ void sts128f(uint32_t a, float4 v) {
    asm volatile("st.shared.v4.f32 [%0], {%1,%2,%3,%4};" ::"r"(a + S0), "f"(v.x), "f"(v.y), "f"(v.z), "f"(v.w) : "memory");
}
__device__ __forceinline__ void sts32f(uint32_t a, float v) { asm volatile("st.shared.f32 [%0], %1;" ::"r"(a + S0), "f"(v) : "memory"); }
__device__ __forceinline__ uint4 lds128(uint32_t a) {
    uint4 v;
    asm volatile("ld.shared.v4.u32 {%0,%1,%2,%3}, [%4];" : "=r"(v.x), "=r"(v.y), "=r"(v.z), "=r"(v.w) : "r"(a + S0) : "memory");
    return v;
}
__device__ __forceinline__ float4 lds128f(uint32_t a) {
    float4 v;
    asm volatile("ld.shared.v4.f32 {%0,%1,%2,%3}, [%4];" : "=f"(v.x), "=f"(v.y), "=f"(v.z), "=f"(v.w) : "r"(a + S0) : "memory");
    return v;
}
__device__ __forceinline__ float2 lds64f(uint32_t a) {
    float2 v;
    asm volatile("ld.shared.v2.f32 {%0,%1}, [%2];" : "=f"(v.x), "=f"(v.y) : "r"(a + S0) : "memory");
    return v;
}
__device__ __forceinline__ float bf_lo(uint32_t u) { return __uint_as_float(u << 16); }
__device__ __forceinline__ float bf_hi(uint32_t u) { return __uint_as_float(u & 0xffff0000u); }
__device__ __forceinline__ uint32_t pack_bf(float lo, float hi) {
    uint32_t r;
    asm("cvt.rn.bf16x2.f32 %0, %1, %2;" : "=r"(r) : "f"(hi), "f"(lo));
    return r;
}
__device__ __forceinline__ float tanh_fast(float x) {
    float r;
    asm("tanh.approx.f32 %0, %1;" : "=f"(r) : "f"(x));
    return r;
}
__device__ __forceinline__ float silu_half(float h) { return fmaf(h, tanh_fast(h), h); }
__device__ __forceinline__ void ldsm4(uint32_t (&u)[4], uint32_t a) {
    asm volatile("ldmatrix.sync.aligned.m8n8.x4.shared.b16 {%0,%1,%2,%3}, [%4];"
                 : "=r"(u[0]), "=r"(u[1]), "=r"(u[2]), "=r"(u[3]) : "r"(a + S0) : "memory");
}
__device__ __forceinline__ void ldsm4t(uint32_t (&u)[4], uint32_t a) {
    asm volatile("ldmatrix.sync.aligned.m8n8.x4.trans.shared.b16 {%0,%1,%2,%3}, [%4];"
                 : "=r"(u[0]), "=r"(u[1]), "=r"(u[2]), "=r"(u[3]) : "r"(a + S0) : "memory");
}
__device__ __forceinline__ void stsm4(uint32_t a, uint32_t p0, uint32_t p1, uint32_t p2, uint32_t p3) {
    asm volatile("stmatrix.sync.aligned.m8n8.x4.shared.b16 [%0], {%1,%2,%3,%4};" ::"r"(a + S0), "r"(p0), "r"(p1), "r"(p2), "r"(p3) : "memory");
}
__device__ __forceinline__ void stsm4t(uint32_t a, uint32_t p0, uint32_t p1, uint32_t p2, uint32_t p3) {
    asm volatile("stmatrix.sync.aligned.m8n8.x4.trans.shared.b16 [%0], {%1,%2,%3,%4};" ::"r"(a + S0), "r"(p0), "r"(p1), "r"(p2), "r"(p3) : "memory");
}

#define R8(o) "+f"(d[o]), "+f"(d[o + 1]), "+f"(d[o + 2]), "+f"(d[o + 3]), "+f"(d[o + 4]), "+f"(d[o + 5]), "+f"(d[o + 6]), "+f"(d[o + 7])
template <uint32_t ALO, uint32_t BLO, uint64_t AHI = 8, uint64_t BHI = 48>
__device__ __forceinline__ void wgmma128(float (&d)[64]) {
    asm volatile(
        "wgmma.mma_async.sync.aligned.m64n128k16.f32.bf16.bf16 "
        "{%0,%1,%2,%3,%4,%5,%6,%7,%8,%9,%10,%11,%12,%13,%14,%15,%16,%17,%18,%19,%20,%21,%22,%23,%24,%25,%26,%27,%28,%29,%30,%31,"
        "%32,%33,%34,%35,%36,%37,%38,%39,%40,%41,%42,%43,%44,%45,%46,%47,%48,%49,%50,%51,%52,%53,%54,%55,%56,%57,%58,%59,%60,%61,%62,%63},"
        " %64, %65, 1, 1, 1, 0, 0;"
        : R8(0), R8(8), R8(16), R8(24), R8(32), R8(40), R8(48), R8(56)
        : "l"((AHI << 32) | ALO), "l"((BHI << 32) | BLO));
}
template <int S>
__device__ __forceinline__ void mma_stages(float (&d)[64], int conv, int tid, Scratch* gs) {
    constexpr uint32_t A = ((SM_ACT + S * 2 * CH_PITCH + 16) >> 4) | ((CH_PITCH >> 4) << 16);
    constexpr uint32_t B = (slot_addr(S % NS) >> 4) | (8u << 16);
    if (S == 0) {
        unsigned it = 0;
#pragma unroll 1
        while (!MMA0_WAIT(BAR(BAR_FULL), conv) && ++it < SPIN_LIMIT) {}
    }
    bool next_ok = true;
    constexpr uint32_t NEXT = S + 1 < NSTAGE ? BAR(BAR_FULL + S + 1) : BAR(BAR_EMB);
    const int npar = S + 1 < NSTAGE ? conv : 0;
    next_ok = mbar_test(NEXT, npar);
    if (S == 0 && tid == 0) TL(32 + conv * 24);
    asm volatile("wgmma.fence.sync.aligned;" ::: "memory");
    wgmma128<A, B>(d);
    wgmma128<A + 1, B + 16>(d);
    wgmma128<A + 2, B + 32>(d);
    asm volatile("wgmma.commit_group.sync.aligned;" ::: "memory");
    if (S >= LAG) {
        asm volatile("wgmma.wait_group.sync.aligned %0;" ::"n"(LAG) : "memory");
        if ((tid & 31) == 0) mbar_arrive(BAR(BAR_WEMPTY + (S + NS - LAG) % NS));
    }
    if (!next_ok) mbar_wait(NEXT, npar);
    if constexpr (S + 1 < NSTAGE) mma_stages<S + 1>(d, conv, tid, gs);
}

__device__ __forceinline__ void weight_load(uint4 (&t)[5], const __nv_bfloat16* w, int cta, int lane) {
    const char* base = reinterpret_cast<const char*>(w) + ((cta & 15) * 8 * C + (cta >> 4) * 16) * 18;
#pragma unroll
    for (int k = 0; k < 5; k++) {
        const int i = lane + 32 * k, row = (i * 57) >> 10;
        if (k < 4 || lane < 16) t[k] = __ldg(reinterpret_cast<const uint4*>(base + row * (C * 18 - 288) + i * 16));
    }
}
__device__ __forceinline__ void weight_block(uint32_t bounce, unsigned char* wt, int cta, int lane, bool readback, Scratch* gs) {
    unsigned char* dst = wt + (cta >> 4) * STAGE_BYTES + (cta & 15) * 768;
    if (lane < 16) {
        uint32_t v[36];
#pragma unroll
        for (int i = 0; i < 9; i++) {
            const uint4 q = lds128(bounce + (lane & 7) * 288 + (lane >> 3) * 144 + i * 16);
            v[4 * i] = q.x; v[4 * i + 1] = q.y; v[4 * i + 2] = q.z; v[4 * i + 3] = q.w;
        }
#pragma unroll
        for (int kyo = 0; kyo < 3; kyo++) {
#pragma unroll
            for (int kx = 0; kx < 3; kx++) {
                const int tap = ky_of(kyo) * 3 + kx;
                uint32_t o[4];
#pragma unroll
                for (int m = 0; m < 4; m++) {
                    const int i0 = 18 * m + tap, i1 = i0 + 9;
                    const uint32_t sel = ((i0 & 1) ? 0x32u : 0x10u) | ((i1 & 1) ? 0x7600u : 0x5400u);
                    o[m] = __byte_perm(v[i0 >> 1], v[i1 >> 1], sel);
                }
                *reinterpret_cast<uint4*>(dst + kyo * 8 * STAGE_BYTES + kx * 256 + lane * 16) = make_uint4(o[0], o[1], o[2], o[3]);
            }
        }
    }
    if (readback) {
        __syncwarp();
        unsigned acc = 0;
        if (lane < 24) {
#pragma unroll
            for (int i = 0; i < 3; i++) acc |= ld_relaxed(dst + i * 8 * STAGE_BYTES + lane * 32);
        }
        asm volatile("{\n.reg .pred p;\nsetp.eq.u32 p, %0, 0x9e3779b9;\n@p st.shared.u32 [%1], %0;\n}" ::"r"(acc), "r"(bounce + S0) : "memory");
    }
}
__device__ __forceinline__ uint32_t act2(uint32_t u, const float4& cf) {
    return pack_bf(silu_half(fmaf(bf_lo(u), cf.x, cf.z)), silu_half(fmaf(bf_hi(u), cf.y, cf.w)));
}
__device__ __forceinline__ void norm_unit(uint32_t (&u)[4], const float4& ca, const float4& cb) {
    u[0] = act2(u[0], ca); u[1] = act2(u[1], ca); u[2] = act2(u[2], cb); u[3] = act2(u[3], cb);
}
__device__ __forceinline__ void read_stats(uint32_t gst, float (&g)[8]) {
    asm volatile("ld.volatile.shared.v4.f32 {%0,%1,%2,%3}, [%4];" : "=f"(g[0]), "=f"(g[1]), "=f"(g[2]), "=f"(g[3]) : "r"(gst + S0) : "memory");
    asm volatile("ld.volatile.shared.v4.f32 {%0,%1,%2,%3}, [%4];" : "=f"(g[4]), "=f"(g[5]), "=f"(g[6]), "=f"(g[7]) : "r"(gst + 16 + S0) : "memory");
}
template <int T>
__device__ __forceinline__ void group_coefs(uint32_t gst, float (&g)[8], float4 (&cf)[8]) {
    unsigned it = 0;
#pragma unroll 1
    while (!__all_sync(0xffffffffu, g[2 * T] != 0.f) && ++it < 8 * SPIN_LIMIT) { SPINPAUSE; read_stats(gst, g); }
    float4 &ca = cf[2 * T], &cb = cf[2 * T + 1];
    const float rs = g[2 * T], mr = g[2 * T + 1];
    ca.z = fmaf(-mr, ca.x, ca.z); ca.w = fmaf(-mr, ca.y, ca.w); ca.x *= rs; ca.y *= rs;
    cb.z = fmaf(-mr, cb.x, cb.z); cb.w = fmaf(-mr, cb.y, cb.w); cb.x *= rs; cb.y *= rs;
}
template <int FIRST, int N>
__device__ __forceinline__ void norm_block(uint32_t (&u)[4][4], float4 (&cf)[8], uint32_t act, uint32_t mask, uint32_t fbar, int lane) {
#pragma unroll
    for (int t = FIRST; t < FIRST + N; t++) {
        norm_unit(u[t], cf[2 * t], cf[2 * t + 1]);
        stsm4(act + t * 2 * KC_BYTES, u[t][0] & mask, u[t][1] & mask, u[t][2] & mask, u[t][3] & mask);
    }
    fence_async_smem();
    __syncwarp();
    if (lane < N) mbar_arrive(fbar + 16 * (FIRST + lane));
}
__device__ __forceinline__ void publish(uint32_t bar, int lane) {
    fence_async_smem();
    __syncwarp();
    if (lane == 0) mbar_arrive(bar);
}
template <int T>
__device__ __forceinline__ void next_unit(uint32_t (&u)[4][4], float4 (&cf)[8], uint32_t gst, float (&g)[8], uint32_t act, uint32_t fbar, int lane) {
    const bool have = __all_sync(0xffffffffu, g[2 * T] != 0.f);
    if (!have) publish(fbar + 16 * (T - 1), lane);
    group_coefs<T>(gst, g, cf);
    norm_unit(u[T], cf[2 * T], cf[2 * T + 1]);
    if (have) publish(fbar + 16 * (T - 1), lane);
    stsm4(act + T * 2 * KC_BYTES, u[T][0], u[T][1], u[T][2], u[T][3]);
}
__device__ __forceinline__ void stat_mma(float (&c)[4], uint32_t p, uint32_t q) {
    asm("mma.sync.aligned.m16n8k16.row.col.f32.bf16.bf16.f32 {%0,%1,%2,%3}, {%4,%5,%6,%5}, {%4,%6}, {%0,%1,%2,%3};"
        : "+f"(c[0]), "+f"(c[1]), "+f"(c[2]), "+f"(c[3]) : "r"(p), "r"(0x3f803f80u), "r"(q));
}
__device__ __forceinline__ void stat_store(const float (&c)[4], uint32_t dst, int lane) {
    const int g = lane >> 2, t = lane & 3;
    if (t == (g >> 1)) sts32f(dst + g * 4, (g & 1) ? c[1] : c[0]);
    if (g == 7) sts32f(dst + 32 + t * 4, c[2] + c[3]);
}
__device__ __forceinline__ float sum4(float4 v) { return (v.x + v.y) + (v.z + v.w); }
__device__ __forceinline__ void stat_publish(uint32_t src, float* acc, int lane, bool real) {
    const uint32_t a = src + (lane & 15) * 48;
    float q = sum4(lds128f(a)) + sum4(lds128f(a + 16)), sm = sum4(lds128f(a + 32));
    q += __shfl_xor_sync(0xffffffffu, q, 1); sm += __shfl_xor_sync(0xffffffffu, sm, 1);
    q += __shfl_xor_sync(0xffffffffu, q, 2); sm += __shfl_xor_sync(0xffffffffu, sm, 2);
    if (real && (lane & 19) == 0) red_add4(acc + lane, 1.f, sm, q, 1.f);
}
__device__ __forceinline__ void fence_acc(float (&d)[64]) {
#pragma unroll
    for (int i = 0; i < 64; i++) asm volatile("" : "+f"(d[i])::"memory");
}
__device__ __forceinline__ void ld_unit(uint32_t (&u)[4], const uint4* p) {
    asm volatile("ld.relaxed.gpu.global.v4.u32 {%0,%1,%2,%3}, [%4];" : "=r"(u[0]), "=r"(u[1]), "=r"(u[2]), "=r"(u[3]) : "l"(p) : "memory");
}

__device__ __noinline__ void side_jobs(const __nv_bfloat16* __restrict__ t_emb, const __nv_bfloat16* __restrict__ w_emb,
                                       const __nv_bfloat16* __restrict__ w2, Scratch* __restrict__ gs, unsigned clk0) {
    const int tid = threadIdx.x, warp = tid >> 5, lane = tid & 31, j = blockIdx.x;
    float tv = 0.f;
    if (lane < 24) tv = __bfloat162float(t_emb[(lane / 12) * E + j * 192 + warp * 12 + lane % 12]);
    if (tid == 0) {
        mbar_init(BAR(0), 1);
        mbar_expect(BAR(0), 192 * C * 2);
        fence_async_smem();
        while (clock32() - clk0 < W2DELAY) {}
#pragma unroll
        for (int i = 0; i < 4; i++) bulk_g2s(S0 + SM_W + i * 12288, w_emb + (j * 192 + i * 48) * C, 12288, S0 + BAR(0));
    }
    if (j == 0 && tid < 32) gs->acc2[(tid >> 4) * LS + (tid & 15)] = 0.f;
    const float sv = silu_half(0.5f * tv);
    __syncthreads();
    mbar_wait(BAR(0), 0);
    float acc[8] = {0.f, 0.f, 0.f, 0.f, 0.f, 0.f, 0.f, 0.f};
#pragma unroll
    for (int i = 0; i < 12; i++) {
        const float2 wq = lds64f(SM_W + (warp * 12 + i) * 256 + lane * 8);
        const uint32_t wx = __float_as_uint(wq.x), wy = __float_as_uint(wq.y);
#pragma unroll
        for (int bb = 0; bb < 2; bb++) {
            const float sx = __shfl_sync(0xffffffffu, sv, bb * 12 + i);
            acc[4 * bb + 0] = fmaf(sx, bf_lo(wx), acc[4 * bb + 0]); acc[4 * bb + 1] = fmaf(sx, bf_hi(wx), acc[4 * bb + 1]);
            acc[4 * bb + 2] = fmaf(sx, bf_lo(wy), acc[4 * bb + 2]); acc[4 * bb + 3] = fmaf(sx, bf_hi(wy), acc[4 * bb + 3]);
        }
    }
    sts128f(SM_ACT + warp * 1024 + lane * 16, make_float4(acc[0], acc[1], acc[2], acc[3]));
    sts128f(SM_ACT + warp * 1024 + 512 + lane * 16, make_float4(acc[4], acc[5], acc[6], acc[7]));
    __syncthreads();
    if (tid < 128) {
        float2 sum = make_float2(0.f, 0.f);
#pragma unroll
        for (int w = 0; w < 16; w++) { const float2 p = lds64f(SM_ACT + w * 1024 + tid * 8); sum.x += p.x; sum.y += p.y; }
        *reinterpret_cast<float2*>(&gs->emb[j * NB * C + tid * 2]) = sum;
        bar_sync(1, 128);
        if (tid < 2) asm volatile("red.release.gpu.global.add.u32 [%0], 1;" ::"l"(&gs->wcnt[(2 * NB + tid) * LS]) : "memory");
    }
}

__global__ void __cluster_dims__(2, 1, 1) __launch_bounds__(NTHREADS, 1)
resblock_kernel(const __nv_bfloat16* __restrict__ w1,
                const __nv_bfloat16* __restrict__ t_emb, const __nv_bfloat16* __restrict__ g1,
                const __nv_bfloat16* __restrict__ be1, const __nv_bfloat16* __restrict__ w_emb,
                const __nv_bfloat16* __restrict__ g2, const __nv_bfloat16* __restrict__ be2,
                const __nv_bfloat16* __restrict__ w2, __nv_bfloat16* __restrict__ out, Scratch* __restrict__ gs,
                const __grid_constant__ CUtensorMap xmap) {
    const unsigned clk0 = clock32();
    if (threadIdx.x == 480 && blockIdx.x >= NXTRA) TLG(1);
    const int tid = threadIdx.x, lane = tid & 31;
    const int cta = blockIdx.x - NXTRA, b = cta >> 6, r = cta & 63;
    uint4 v[5];
    if (tid < 32) weight_load(v, w1, cta & (NCTA - 1), lane);
    const int warp = __shfl_sync(0xffffffffu, tid >> 5, 0);
    if (cta < 0) { side_jobs(t_emb, w_emb, w2, gs, clk0); return; }

    if (warp != 3) asm volatile("barrier.cluster.arrive.relaxed.aligned;" ::: "memory");
    const bool has_outer = (r != 0) && (r != HW - 1);
    if (warp == 1 || warp == 2 || warp == 4 || warp == 5) {
        const int g = warp < 3 ? warp - 1 : 7 - warp;
        if (elect_one()) {
            asm volatile("prefetch.tensormap [%0];" ::"l"(&xmap) : "memory");
            mbar_init(BAR(BAR_X) + 8 * g, 1);
            if (g == 3) mbar_init(BAR(BAR_X + 4), 1);
            mbar_expect(BAR(BAR_X) + 8 * g, 4096);
            fence_async_smem();
            while (clock32() - clk0 < XDELAY + (g >> 1) * XSTAG + (g & 1) * XSTAG2) {}
            tma_x(SM_XOWN + g * 4096, &xmap, r, b * C + g * 32, BAR(BAR_X) + 8 * g);
            if (g == 3 && has_outer) {
                mbar_expect(BAR(BAR_X + 4), 16384);
#pragma unroll
                for (int i = 0; i < 4; i++) tma_x(SM_XOUT + i * 4096, &xmap, r + ((r & 1) ? 1 : -1), b * C + i * 32, BAR(BAR_X + 4));
            }
        }
        __syncwarp();
        bar_arrive(4, 256 + 64 + 128);
        mbar_wait(BAR(BAR_X) + 8 * g, 0);
        if (lane == 0) TL(70 + g);
        float c[8][4];
#pragma unroll
        for (int k = 0; k < 8; k++) {
            const uint4 q = lds128(SM_XOWN + g * 4096 + k * 512 + lane * 16);
            c[k][0] = c[k][1] = c[k][2] = c[k][3] = 0.f;
            stat_mma(c[k], q.x, q.y); stat_mma(c[k], q.z, q.w);
        }
#pragma unroll
        for (int i = 0; i < 4; i++) c[0][i] = ((c[0][i] + c[1][i]) + (c[2][i] + c[3][i])) + ((c[4][i] + c[5][i]) + (c[6][i] + c[7][i]));
        if (lane == 0 && g == 0) { if (c[0][0] == 1.2345f) sts32f(SM_RED, 0.f); TL(92); }
        stat_store(c[0], SM_RED + g * 48, lane);
        __syncwarp();
        if (lane == 0) {
            const uint32_t a = SM_RED + g * 48;
            red_add4(&gs->acc1[b * 4 * LS + g * GS1], 1.f, sum4(lds128f(a + 32)), sum4(lds128f(a)) + sum4(lds128f(a + 16)), 1.f);
            TL(74 + g);
        }
    }
    if (warp == 3) {
            if (elect_one()) {
#pragma unroll
                for (int i = 0; i < NSTAGE; i++) mbar_init(BAR(BAR_FULL + i), (i >> 3) == 1 ? 1 : 5);
#pragma unroll
                for (int i = 0; i < NS + 2; i++) mbar_init(BAR(BAR_WEMPTY + i), 4);
#pragma unroll
                for (int i = BAR_STATS; i < BAR_X; i++) mbar_init(BAR(i), i == BAR_EMB ? 3 : 1);
                asm volatile("fence.mbarrier_init.release.cluster;" ::: "memory");
            }
            __syncwarp();
            fence_async_smem();
            bar_arrive(0, 96);
            bar_arrive(5, 96);
            bar_arrive(4, 256 + 64 + 128);
            const uint4 z = make_uint4(0, 0, 0, 0);
#pragma unroll
            for (int i = 0; i < 2; i++) sts128(SM_ACT + (i * 16 + (lane >> 1)) * CH_PITCH + (lane & 1) * 16, z);
            if (lane < 4) sts128(SM_ACT + (2 + (lane >> 1)) * ROW_BYTES + (lane & 1) * 16, z);
            if (lane < 16) sts128(SM_ONES + lane * 16, make_uint4(lane < 8 ? 0x3f803f80u : 0u, 0, 0, 0));
            fence_async_smem();
            asm volatile("barrier.cluster.arrive.relaxed.aligned;" ::: "memory");
            if (lane == 0) TL(5);
            while (clock32() - clk0 < W2DELAY) {}
            weight_load(v, w2, cta, lane);
        }
    if (warp == 0 || warp == 3) {
        const int k = warp & 1;
#pragma unroll
        for (int i = 0; i < 5; i++)
            if (i < 4 || lane < 16) sts128(SM_BNC + k * 2304 + (lane + 32 * i) * 16, v[i]);
        if (lane == 0) TL(k ? 14 : 81);
        __syncwarp();
        weight_block(SM_BNC + k * 2304, gs->wt + k * NSTAGE * STAGE_BYTES, cta, lane, true, gs);
        __syncwarp();
        if (lane == 0) TL(k ? 13 : 4);
        if (lane < 2) asm volatile("red.relaxed.gpu.global.add.u32 [%0], 1;" ::"l"(&gs->wcnt[(k * NB + lane) * LS + (k ? 0 : cta >> 4)]) : "memory");
    }

    if (warp >= 8) {
        const int nw = warp - 8;
        bar_sync(4, 256 + 64 + 128);
        const int par = nw >> 2, wq = nw & 3;
        const uint32_t act_off = SM_ACT + (par * 2 + (lane >> 4)) * CH_PITCH + (2 + wq * 16 + (lane & 15)) * 16;
        const uint32_t stg_off = (par * 16 + (lane >> 4) * 8 + (lane & 7)) * 128 + (((2 * wq + ((lane >> 3) & 1)) ^ (lane & 7)) << 4);
        const uint32_t cfa = SM_COEF + par * 128 + (lane & 3) * 16;
        const uint32_t fbar = BAR(BAR_FULL) + 8 * par;
        uint4* inbox = gs->box + cta * 1024 + nw * 32 + lane;
#pragma unroll 1
        for (int conv = 0; conv < 2; conv++) {
            uint32_t u[4][4], w[4][4];
            float4 cf[8];
            if (conv == 0) {
#pragma unroll
                for (int i = 0; i < 4; i++) { mbar_wait(BAR(BAR_X + i), 0); ldsm4t(u[i], SM_XOWN + stg_off + i * 4096); }
            } else {
                mbar_wait(BAR(BAR_HW), 0);
#pragma unroll
                for (int i = 0; i < 4; i++) ldsm4(u[i], act_off + i * 2 * KC_BYTES);
            }
#pragma unroll
            for (int i = 0; i < 8; i++) cf[i] = lds128f(cfa + conv * 1024 + (i >> 1) * 256 + (i & 1) * 64);
            const uint32_t gst = SM_GST + conv * 32;
            float gv[8];
            read_stats(gst, gv);
            group_coefs<0>(gst, gv, cf);
            if (tid == 256) TL(22 + conv * 4);
            if (par) { const unsigned c1 = clock32(); while (clock32() - c1 < PDELAY) {} }
            norm_block<0, 1>(u, cf, act_off, ~0u, fbar, lane);
            if (tid == 256) TL(8 + conv * 8);
            group_coefs<1>(gst, gv, cf);
            norm_unit(u[1], cf[2], cf[3]);
            stsm4(act_off + 2 * KC_BYTES, u[1][0], u[1][1], u[1][2], u[1][3]);
            next_unit<2>(u, cf, gst, gv, act_off, fbar, lane);
            next_unit<3>(u, cf, gst, gv, act_off, fbar, lane);
            publish(fbar + 48, lane);
            if (tid == 256) TL(84 + conv);
            if (has_outer) {
                mbar_wait(BAR(BAR_X + 4), conv);
                if (conv == 0) {
#pragma unroll
                    for (int i = 0; i < 4; i++) ldsm4t(w[i], SM_XOUT + stg_off + i * 4096);
                } else {
#pragma unroll
                    for (int i = 0; i < 4; i++) {
                        const uint4 q = lds128(SM_XOWN + (tid - 256) * 16 + i * 4096);
                        w[i][0] = q.x; w[i][1] = q.y; w[i][2] = q.z; w[i][3] = q.w;
                    }
                    unsigned it = 0;
                    while (true) {
                        bool ok = true;
#pragma unroll
                        for (int i = 0; i < 16; i++) ok = ok && w[i >> 2][i & 3] != 0;
                        if (__all_sync(0xffffffffu, ok) || ++it > SPIN_LIMIT) break;
#pragma unroll
                        for (int i = 0; i < 4; i++) ld_unit(w[i], inbox + i * 256);
                    }
#pragma unroll
                    for (int i = 0; i < 16; i++) w[i >> 2][i & 3] = ~w[i >> 2][i & 3];
                }
            }
            if (conv == 0) {
                bar_sync(3, 256);
                if (nw == 0) sts128(SM_ACT + 2 * ROW_BYTES + (lane >> 1) * CH_PITCH + (lane & 1) * 16, make_uint4(0, 0, 0, 0));
            }
            if (tid == 256) TL(24 + conv * 4);
            norm_block<0, 2>(w, cf, act_off + 2 * ROW_BYTES, has_outer ? ~0u : 0u, fbar + 128, lane);
            if (tid == 256) TL(88 + conv);
            norm_block<2, 2>(w, cf, act_off + 2 * ROW_BYTES, has_outer ? ~0u : 0u, fbar + 128, lane);
            if (tid == 256) TL(23 + conv * 4);
        }
        if (has_outer) {
            mbar_wait(BAR(BAR_FULL + NSTAGE - 1), 1);
#pragma unroll
            for (int i = 0; i < 4; i++) inbox[i * 256] = make_uint4(0, 0, 0, 0);
        }
        {
            const int oc0 = (tid - 256) >> 3, seg = lane & 7;
            __nv_bfloat16* dst = out + ((size_t)(b * C + oc0) * HW + r) * HW + seg * 8;
            const uint32_t src = SM_XOWN + oc0 * 128 + ((seg ^ (oc0 & 7)) << 4);
            bar_sync(6, 128 + 256);
#pragma unroll
            for (int i = 0; i < 4; i++) *reinterpret_cast<uint4*>(dst + (size_t)i * 32 * HW * HW) = lds128(src + i * 4096);
            if (tid == 256) { TL(20); TLG(21); }
        }
    } else if (warp < 4) {
        const int wq = warp;
        bar_sync(2, 128);

        const uint32_t xbase = SM_XOWN + ((lane >> 4) * 8 + (lane & 7)) * 128 + (((2 * wq + ((lane >> 3) & 1)) ^ (lane & 7)) << 4);
        float d[64];
#pragma unroll
        for (int i = 0; i < 64; i++) d[i] = 0.f;
#pragma unroll 1
        for (int conv = 0; conv < 2; conv++) {
            fence_acc(d);
            mma_stages<0>(d, conv, tid, gs);
            if (conv == 0) {
                asm volatile("wgmma.fence.sync.aligned;" ::: "memory");
                wgmma128<(SM_ONES >> 4) | (8u << 16), (SM_EMB >> 4), 0, 8>(d);
                asm volatile("wgmma.commit_group.sync.aligned;" ::: "memory");
            }
            asm volatile("wgmma.wait_group.sync.aligned 0;" ::: "memory");
            fence_acc(d);
            if (tid == 0) TL(10 + conv * 8);
            uint32_t hp[32];
#pragma unroll
            for (int i = 0; i < 32; i++) hp[i] = pack_bf(d[2 * i], d[2 * i + 1]);
            if (conv == 1) {
#pragma unroll
                for (int kc = 0; kc < 8; kc++) stsm4t(xbase + kc * 2048, hp[4 * kc], hp[4 * kc + 1], hp[4 * kc + 2], hp[4 * kc + 3]);
                bar_arrive(6, 128 + 256);
                break;
            }
#pragma unroll
            for (int g = 0; g < 4; g++) {
                float c[4] = {0.f, 0.f, 0.f, 0.f};
#pragma unroll
                for (int i = 0; i < 4; i++) stat_mma(c, hp[8 * g + 2 * i], hp[8 * g + 2 * i + 1]);
                stat_store(c, SM_RED + (g * 4 + wq) * 48, lane);
            }
            bar_sync(2, 128);
            if (wq == 0) stat_publish(SM_RED, &gs->acc2[b * LS], lane, true);
            if (tid == 0) TL(11);
            const uint32_t hbase = SM_ACT + (lane >> 4) * CH_PITCH + (2 + wq * 16 + (lane & 15)) * 16;
#pragma unroll
            for (int kc = 0; kc < 8; kc++) stsm4(hbase + kc * 2 * CH_PITCH, hp[4 * kc], hp[4 * kc + 1], hp[4 * kc + 2], hp[4 * kc + 3]);
            __syncwarp();
            if (lane == 0) mbar_arrive(BAR(BAR_HW));
            if (lane < LAG) mbar_arrive(BAR(BAR_WEMPTY + (NSTAGE - LAG) % NS) + 8 * lane);
            if (has_outer) {
                uint4* outbox = gs->box + (cta + ((r & 1) ? 1 : -1)) * 1024 + tid;
#pragma unroll
                for (int kc = 0; kc < 8; kc++) outbox[kc * 128] = make_uint4(~hp[4 * kc], ~hp[4 * kc + 1], ~hp[4 * kc + 2], ~hp[4 * kc + 3]);
            }
            if (tid == 0) TL(12);
#pragma unroll
            for (int kc = 0; kc < 8; kc++) {
                uint32_t p[4];
                ldsm4t(p, xbase + kc * 2048);
#pragma unroll
                for (int i = 0; i < 4; i++) { d[8 * kc + 2 * i] = bf_lo(p[i]); d[8 * kc + 2 * i + 1] = bf_hi(p[i]); }
            }
            fence_async_smem();
            __syncwarp();
            if (lane == 0) mbar_arrive(BAR(BAR_XFREE));
        }
        {
        }
    } else if (warp < 6) {
        bar_sync(5, 96);
        if (warp == 5) {
            asm volatile("barrier.cluster.wait.acquire.aligned;" ::: "memory");
            const uint32_t peer = (r & 1) ^ 1;
            const uint32_t self0 = mapa(0, r & 1), peer0 = mapa(0, peer);
#pragma unroll 1
            for (int conv = 0; conv < 2; conv++) {
#pragma unroll 1
                for (int kc = 0; kc < 8; kc++) {
                    mbar_wait(BAR(BAR_FULL) + 8 * kc, conv);
                    if (elect_one())
                        asm volatile("cp.async.bulk.shared::cluster.shared::cta.mbarrier::complete_tx::bytes [%0], [%1], %2, [%3];"
                                     ::"r"(peer0 + SM_ACT + ROW_BYTES + kc * KC_BYTES), "r"(self0 + SM_ACT + kc * KC_BYTES), "r"(KC_BYTES),
                                       "r"(peer0 + BAR(BAR_FULL + 8) + 8 * kc) : "memory");
                }
                if (lane == 0) TL(86 + conv);
#pragma unroll 1
                for (int kc = 0; kc < 8; kc++) mbar_wait(BAR(BAR_FULL + 8) + 8 * kc, conv);
                if (lane == 0)
                    asm volatile("mbarrier.arrive.release.cluster.shared::cluster.b64 _, [%0];" ::"r"(peer0 + (conv ? BAR(BAR_ACK) : BAR(BAR_EMB))) : "memory");
            }
            mbar_wait(BAR(BAR_ACK), 0);
        } else {
            mbar_wait(BAR(BAR_STATS), 0);
            unsigned it = 0;
            while (ld_relaxed(&gs->wcnt[(2 * NB + b) * LS]) < (unsigned)NXTRA && ++it < SPIN_LIMIT) __nanosleep(100);
            fence_acquire();
            float ev[4] = {0.f, 0.f, 0.f, 0.f};
#pragma unroll
            for (int j = 0; j < NXTRA; j++) {
                const uint4 ef = ld_relaxed_v4(&gs->emb[(j * NB + b) * C + lane * 4]);
                ev[0] += __uint_as_float(ef.x); ev[1] += __uint_as_float(ef.y); ev[2] += __uint_as_float(ef.z); ev[3] += __uint_as_float(ef.w);
            }
#pragma unroll
            for (int i = 0; i < 4; i++) {
                const float hi = bf_lo(pack_bf(ev[i], 0.f));
                sts128(SM_EMB + (lane * 4 + i) * 16, make_uint4(pack_bf(hi, ev[i] - hi), 0, 0, 0));
            }
            fence_async_smem();
            __syncwarp();
            if (lane == 0) { mbar_arrive(BAR(BAR_EMB)); TL(19); }
        }
    } else if (warp == 6) {
        bar_sync(0, 96);
        const uint32_t ebytes = STAGE_BYTES + ((lane >> 3) == 1 ? KC_BYTES : 0);
        if (lane < NSTAGE) mbar_expect(BAR(BAR_FULL) + 8 * lane, ebytes);
        const int swap = (r & 1) ? 0 : 8 * STAGE_BYTES;
        unsigned it = 0;
        {
            int g = 0;
#pragma unroll 1
            while (g < NS) {
                unsigned ready = __ballot_sync(0xffffffffu, ld_relaxed(&gs->wcnt[b * LS + (lane & 7)]) >= 16u) >> g;
                if (++it > SPIN_LIMIT) ready = ~0u;
                if (!(ready & 1)) continue;
                fence_acquire();
                fence_async_global();
                if (lane == 0) TL(g ? 3 : 6);
#pragma unroll 1
                for (; (ready & 1) && g < NS; g++, ready >>= 1)
                    if (elect_one())
                        bulk_g2s(S0 + SM_W + g * STAGE_BYTES, gs->wt + g * STAGE_BYTES + (g >= 8 ? swap : 0), STAGE_BYTES, S0 + BAR(BAR_FULL) + 8 * g);
            }
        }
#pragma unroll 1
        for (int q = 3; q < 12; q++) {
            const int conv = q >= 6, qs = conv ? q - 6 : q, sl = q % 3;
            const unsigned char* wsrc = gs->wt + q * 4 * STAGE_BYTES + (qs < 2 ? 0 : (qs < 4 ? swap : -swap));
            const uint32_t par = (q / 3 - 1) & 1;
            if (q == 6) {
                it = 0;
                while (ld_relaxed(&gs->wcnt[(NB + b) * LS]) < (unsigned)NCTA && ++it < SPIN_LIMIT) {}
                fence_acquire();
                fence_async_global();
                if (lane == 0) { mbar_arrive(BAR(BAR_EMB)); TL(2); }
            }
#pragma unroll
            for (int i = 0; i < 4; i++) {
                mbar_wait(BAR(BAR_WEMPTY + i) + 32 * sl, par);
                if (i == 0 && (q == 6 || q == 9)) {
                    if ((lane >= NS) == (q == 9) && lane < NSTAGE) mbar_expect(BAR(BAR_FULL) + 8 * lane, ebytes);
                    __syncwarp();
                }
                if (elect_one())
                    bulk_g2s(S0 + SM_W + (sl * 4 + i) * STAGE_BYTES, wsrc + i * STAGE_BYTES, STAGE_BYTES, S0 + BAR(BAR_FULL + i) + 32 * qs);
            }
        }
    } else {
        const uint2 ga1 = __ldg(reinterpret_cast<const uint2*>(g1) + lane), bt1 = __ldg(reinterpret_cast<const uint2*>(be1) + lane);
        const uint2 ga2 = __ldg(reinterpret_cast<const uint2*>(g2) + lane), bt2 = __ldg(reinterpret_cast<const uint2*>(be2) + lane);
        if (lane < 8) sts128(SM_GST + lane * 16, make_uint4(0, 0, 0, 0));
        sts128f(SM_COEF + lane * 32, make_float4(0.5f * bf_lo(ga1.x), 0.5f * bf_hi(ga1.x), 0.5f * bf_lo(bt1.x), 0.5f * bf_hi(bt1.x)));
        sts128f(SM_COEF + lane * 32 + 16, make_float4(0.5f * bf_lo(ga1.y), 0.5f * bf_hi(ga1.y), 0.5f * bf_lo(bt1.y), 0.5f * bf_hi(bt1.y)));
        sts128f(SM_COEF + 1024 + lane * 32, make_float4(0.5f * bf_lo(ga2.x), 0.5f * bf_hi(ga2.x), 0.5f * bf_lo(bt2.x), 0.5f * bf_hi(bt2.x)));
        sts128f(SM_COEF + 1024 + lane * 32 + 16, make_float4(0.5f * bf_lo(ga2.y), 0.5f * bf_hi(ga2.y), 0.5f * bf_lo(bt2.y), 0.5f * bf_hi(bt2.y)));
        bar_arrive(4, 256 + 64 + 128);
        bar_sync(0, 96);
#pragma unroll 1
        for (int conv = 0; conv < 2; conv++) {
            if (conv == 1) {
                mbar_wait(BAR(BAR_HW), 0);
                const unsigned c1 = clock32();
                while (clock32() - c1 < PD2) {}
            } else {
                while (clock32() - clk0 < PD) {}
            }
            const float* asrc = conv ? &gs->acc2[b * LS + (lane & 3) * 4] : &gs->acc1[b * 4 * LS + (lane & 3) * GS1];
            unsigned it = 0;
            uint4 fq[NPOLL];
#pragma unroll
            for (int i = 0; i < NPOLL; i++) {
                fq[i] = ld_relaxed_v4(asrc);
                if (i + 1 < NPOLL) { const unsigned c1 = clock32(); while (clock32() - c1 < 450 / NPOLL) {} }
            }
            bool all = false;
#pragma unroll 1
            while (!all) {
#pragma unroll
                for (int i = 0; i < NPOLL; i++) {
                    const uint4 f = fq[i];
                    const bool ok = ((f.x == 0x42800000u) & (f.w == 0x42800000u)) || it > SPIN_LIMIT;
                    if (ok && lane < 4) {
                        const float inv_n = 1.0f / (32.0f * HW * HW);
                        const float mean = __uint_as_float(f.y) * inv_n;
                        const float rs = rsqrtf(fmaxf(fmaf(-mean, mean, __uint_as_float(f.z) * inv_n), 0.f) + 1e-5f);
                        asm volatile("st.shared.v2.f32 [%0], {%1,%2};" ::"r"(S0 + SM_GST + conv * 32 + lane * 8), "f"(rs == 0.f ? 1e-38f : rs), "f"(mean * rs) : "memory");
                    }
                    if (__all_sync(0xffffffffu, ok)) { all = true; break; }
                    fq[i] = ld_relaxed_v4(asrc);
                }
                it++;
            }
            if (lane == 0) { mbar_arrive(BAR(BAR_STATS)); TL(7 + conv * 8); }
        }
        mbar_wait(BAR(BAR_XFREE), 0);
        if (has_outer && elect_one()) {
            mbar_expect(BAR(BAR_X + 4), 16384);
            bulk_g2s(S0 + SM_XOWN, gs->box + cta * 1024, 16384, S0 + BAR(BAR_X + 4));
        }
        if (r == 0) {
            if (lane < 16) gs->acc1[b * 4 * LS + (lane >> 2) * GS1 + (lane & 3)] = 0.f;
            if (lane < 24) gs->wcnt[((lane >> 3) * NB + b) * LS + (lane & 7)] = 0;
        }
    }
}

}

extern "C" void kernel_launch(void* const* d_in, const int* in_sizes, int n_in, void* d_out, int out_size) {
    (void)in_sizes; (void)n_in; (void)out_size;
    typedef CUresult (*EncodeFn)(CUtensorMap*, CUtensorMapDataType, cuuint32_t, void*, const cuuint64_t*, const cuuint64_t*,
                                 const cuuint32_t*, const cuuint32_t*, CUtensorMapInterleave, CUtensorMapSwizzle,
                                 CUtensorMapL2promotion, CUtensorMapFloatOOBfill);
    static Scratch* gs = nullptr;
    static EncodeFn encode = nullptr;
    if (!gs) {
        cudaFuncSetAttribute(resblock_kernel, cudaFuncAttributeMaxDynamicSharedMemorySize, SM_TOTAL);
        cudaGetSymbolAddress((void**)&gs, g_scratch);
        cudaDriverEntryPointQueryResult qr;
        cudaGetDriverEntryPoint("cuTensorMapEncodeTiled", (void**)&encode, cudaEnableDefault, &qr);
    }
    CUtensorMap xmap;
    const cuuint64_t dims[3] = {HW, HW, NB * C}, strides[2] = {HW * 2, HW * HW * 2};
    const cuuint32_t box[3] = {HW, 1, 32}, es[3] = {1, 1, 1};
    encode(&xmap, CU_TENSOR_MAP_DATA_TYPE_BFLOAT16, 3, d_in[0], dims, strides, box, es, CU_TENSOR_MAP_INTERLEAVE_NONE,
           CU_TENSOR_MAP_SWIZZLE_128B, CU_TENSOR_MAP_L2_PROMOTION_NONE, CU_TENSOR_MAP_FLOAT_OOB_FILL_NONE);
    resblock_kernel<<<NCTA + NXTRA, NTHREADS, SM_TOTAL>>>(
        (const __nv_bfloat16*)d_in[4], (const __nv_bfloat16*)d_in[1],
        (const __nv_bfloat16*)d_in[2], (const __nv_bfloat16*)d_in[3], (const __nv_bfloat16*)d_in[5],
        (const __nv_bfloat16*)d_in[6], (const __nv_bfloat16*)d_in[7], (const __nv_bfloat16*)d_in[8],
        (__nv_bfloat16*)d_out, gs, xmap);
}
```

```cpp
#include <cuda_runtime.h>
#include <cuda.h>
#include <cuda_bf16.h>
#include <stdint.h>

namespace {

constexpr int C = 128, HW = 64, NB = 2, E = 768;
constexpr int NCTA = NB * HW;
constexpr int NXTRA = 4;
constexpr int NTHREADS = 16 * 32;
constexpr int CH_PITCH = 66 * 16;
constexpr int ROW_BYTES = 16 * CH_PITCH;
constexpr int STEP_BYTES = 4096;
constexpr int STAGE_BYTES = 3 * STEP_BYTES;
constexpr int NSTAGE = 24;
constexpr int KC_BYTES = 2 * CH_PITCH;
constexpr int NS = 12;
constexpr int LAG = 1;
#define XDELAY 400
#define HDELAY 600
#define SEQ 0
#define MMA0_WAIT mbar_try
#define SPINPAUSE
#define NPOLL 1
#define PD2 0
#define PDELAY 60
#define RB 1
#define XSTAG2 400
#define XSTAG 800
#define HSEND 0
#define W2DELAY 1800

constexpr uint32_t SMEM_BASE = 0x400;
constexpr uint32_t SM_XOWN = SMEM_BASE;
constexpr uint32_t SM_ACT = SM_XOWN + 16384 + 512;
constexpr uint32_t SM_XOUT = SM_ACT + 2 * ROW_BYTES + 512;
static_assert(SM_XOUT % 1024 == 0, "swizzle atom alignment");
constexpr uint32_t SM_W = SM_ACT + 3 * ROW_BYTES + 128;
__host__ __device__ constexpr uint32_t slot_addr(int slot) { return SM_W + slot * STAGE_BYTES; }
constexpr uint32_t SM_COEF = SM_W + NS * STAGE_BYTES;
constexpr uint32_t SM_GST = SM_COEF + 2048;
constexpr uint32_t SM_EMB = SM_GST + 128;
constexpr uint32_t SM_ONES = SM_EMB + 2048;
constexpr uint32_t SM_RED = SM_ONES + 256;
constexpr uint32_t SM_BNC = SM_RED + 1536;
constexpr uint32_t SM_BAR = SM_BNC + 2 * 2304;
constexpr int BAR_FULL = 0, BAR_WEMPTY = NSTAGE, BAR_HW = BAR_WEMPTY + NS, BAR_XFREE = BAR_HW + 1, BAR_STATS = BAR_XFREE + 1,
              BAR_EMB = BAR_STATS + 1, BAR_ACK = BAR_EMB + 1, BAR_X = BAR_ACK + 1  , BAR_P = BAR_X + 5  , NBAR = BAR_P + 4;
constexpr int SM_TOTAL = SM_BAR + NBAR * 8 - SMEM_BASE;
static_assert(SM_TOTAL <= 232448, "smem");
static_assert(NBAR <= 96, "barrier init");
__host__ __device__ constexpr uint32_t BAR(int i) { return SM_BAR + 8 * i; }
__host__ __device__ constexpr int ky_of(int kyo) { return kyo == 0 ? 1 : (kyo == 1 ? 0 : 2); }

constexpr unsigned SPIN_LIMIT = 1u << 16;

#define LS 1056
#define GS1 4
#define PD 0
struct Scratch {
    float acc1[NB * 4 * LS];
    float acc2[NB * LS];
    unsigned wcnt[3 * NB * LS];
    float emb[NXTRA * NB * C];
    unsigned char wt[2 * NSTAGE * STAGE_BYTES];
    uint4 box[NCTA * 1024];
};
__device__ __align__(1024) Scratch g_scratch;
#define TL(i) do {} while (0)
#define TLG(i) do {} while (0)

__device__ __forceinline__ unsigned clock32() { unsigned c; asm volatile("mov.u32 %0, %%clock;" : "=r"(c)); return c; }
__device__ __forceinline__ uint32_t mapa(uint32_t a, uint32_t rank) {
    uint32_t d;
    asm("mapa.shared::cluster.u32 %0, %1, %2;" : "=r"(d) : "r"(a), "r"(rank));
    return d;
}
#define S0 mapa(0, blockIdx.x & 1)
__device__ __forceinline__ void mbar_init(uint32_t bar, int cnt) {
    asm volatile("mbarrier.init.shared::cta.b64 [%0], %1;" ::"r"(bar + S0), "r"(cnt) : "memory");
}
__device__ __forceinline__ void mbar_arrive(uint32_t bar) {
    asm volatile("mbarrier.arrive.shared::cta.b64 _, [%0];" ::"r"(bar + S0) : "memory");
}
__device__ __forceinline__ void mbar_expect(uint32_t bar, uint32_t bytes) {
    asm volatile("mbarrier.arrive.expect_tx.shared::cta.b64 _, [%0], %1;" ::"r"(bar + S0), "r"(bytes) : "memory");
}
__device__ __forceinline__ bool mbar_try(uint32_t bar, uint32_t par) {
    uint32_t ok;
    asm volatile("{\n.reg .pred p;\nmbarrier.try_wait.parity.shared::cta.b64 p, [%1], %2;\nselp.u32 %0, 1, 0, p;\n}"
                 : "=r"(ok) : "r"(bar + S0), "r"(par) : "memory");
    return ok;
}
__device__ __forceinline__ bool mbar_test(uint32_t bar, uint32_t par) {
    uint32_t ok;
    asm volatile("{\n.reg .pred p;\nmbarrier.test_wait.parity.shared::cta.b64 p, [%1], %2;\nselp.u32 %0, 1, 0, p;\n}"
                 : "=r"(ok) : "r"(bar + S0), "r"(par) : "memory");
    return ok;
}
__device__ __forceinline__ void mbar_wait(uint32_t bar, uint32_t par) {
    unsigned it = 0;
#pragma unroll 1
    while (!mbar_try(bar, par) && ++it < SPIN_LIMIT) {}
}
__device__ __forceinline__ bool elect_one() {
    uint32_t p;
    asm volatile("{\n.reg .pred p;\nelect.sync _|p, 0xffffffff;\nselp.u32 %0, 1, 0, p;\n}" : "=r"(p));
    return p;
}
__device__ __forceinline__ void fence_async_smem() { asm volatile("fence.proxy.async.shared::cta;" ::: "memory"); }
__device__ __forceinline__ void fence_async_global() { asm volatile("fence.proxy.async.global;" ::: "memory"); }
__device__ __forceinline__ void fence_acquire() { asm volatile("fence.acquire.gpu;" ::: "memory"); }
__device__ __forceinline__ void bar_sync(int id, int n) { asm volatile("bar.sync %0, %1;" ::"r"(id), "r"(n) : "memory"); }
__device__ __forceinline__ void bar_arrive(int id, int n) { asm volatile("bar.arrive %0, %1;" ::"r"(id), "r"(n) : "memory"); }
__device__ __forceinline__ void bulk_g2s(uint32_t dst, const void* src, uint32_t bytes, uint32_t bar) {
    asm volatile("cp.async.bulk.shared::cluster.global.mbarrier::complete_tx::bytes [%0], [%1], %2, [%3];"
                 ::"r"(dst), "l"(src), "r"(bytes), "r"(bar) : "memory");
}
__device__ __forceinline__ void tma_x(uint32_t dst, const CUtensorMap* tm, int row, int ch, uint32_t bar) {
    asm volatile("cp.async.bulk.tensor.3d.shared::cluster.global.mbarrier::complete_tx::bytes [%0], [%1, {%2, %3, %4}], [%5];"
                 ::"r"(dst + S0), "l"(tm), "r"(0), "r"(row), "r"(ch), "r"(bar + S0) : "memory");
}
__device__ __forceinline__ uint4 ld_relaxed_v4(const void* p) {
    uint4 v;
    asm volatile("ld.relaxed.gpu.global.v4.u32 {%0,%1,%2,%3}, [%4];" : "=r"(v.x), "=r"(v.y), "=r"(v.z), "=r"(v.w) : "l"(p) : "memory");
    return v;
}
__device__ __forceinline__ unsigned ld_relaxed(const void* p) {
    unsigned v;
    asm volatile("ld.relaxed.gpu.global.u32 %0, [%1];" : "=r"(v) : "l"(p) : "memory");
    return v;
}
__device__ __forceinline__ void red_add4(float* p, float a, float b, float c, float d) {
    asm volatile("red.relaxed.gpu.global.add.v4.f32 [%0], {%1,%2,%3,%4};" ::"l"(p), "f"(a), "f"(b), "f"(c), "f"(d) : "memory");
}
__device__ __forceinline__ void sts128(uint32_t a, uint4 v) {
    asm volatile("st.shared.v4.u32 [%0], {%1,%2,%3,%4};" ::"r"(a + S0), "r"(v.x), "r"(v.y), "r"(v.z), "r"(v.w) : "memory");
}
__device__ __forceinline__ void sts128f(uint32_t a, float4 v) {
    asm volatile("st.shared.v4.f32 [%0], {%1,%2,%3,%4};" ::"r"(a + S0), "f"(v.x), "f"(v.y), "f"(v.z), "f"(v.w) : "memory");
}
__device__ __forceinline__ void sts32f(uint32_t a, float v) { asm volatile("st.shared.f32 [%0], %1;" ::"r"(a + S0), "f"(v) : "memory"); }
__device__ __forceinline__ uint4 lds128(uint32_t a) {
    uint4 v;
    asm volatile("ld.shared.v4.u32 {%0,%1,%2,%3}, [%4];" : "=r"(v.x), "=r"(v.y), "=r"(v.z), "=r"(v.w) : "r"(a + S0) : "memory");
    return v;
}
__device__ __forceinline__ float4 lds128f(uint32_t a) {
    float4 v;
    asm volatile("ld.shared.v4.f32 {%0,%1,%2,%3}, [%4];" : "=f"(v.x), "=f"(v.y), "=f"(v.z), "=f"(v.w) : "r"(a + S0) : "memory");
    return v;
}
__device__ __forceinline__ float2 lds64f(uint32_t a) {
    float2 v;
    asm volatile("ld.shared.v2.f32 {%0,%1}, [%2];" : "=f"(v.x), "=f"(v.y) : "r"(a + S0) : "memory");
    return v;
}
__device__ __forceinline__ float bf_lo(uint32_t u) { return __uint_as_float(u << 16); }
__device__ __forceinline__ float bf_hi(uint32_t u) { return __uint_as_float(u & 0xffff0000u); }
__device__ __forceinline__ uint32_t pack_bf(float lo, float hi) {
    uint32_t r;
    asm("cvt.rn.bf16x2.f32 %0, %1, %2;" : "=r"(r) : "f"(hi), "f"(lo));
    return r;
}
__device__ __forceinline__ float tanh_fast(float x) {
    float r;
    asm("tanh.approx.f32 %0, %1;" : "=f"(r) : "f"(x));
    return r;
}
__device__ __forceinline__ float silu_half(float h) { return fmaf(h, tanh_fast(h), h); }
__device__ __forceinline__ void ldsm4(uint32_t (&u)[4], uint32_t a) {
    asm volatile("ldmatrix.sync.aligned.m8n8.x4.shared.b16 {%0,%1,%2,%3}, [%4];"
                 : "=r"(u[0]), "=r"(u[1]), "=r"(u[2]), "=r"(u[3]) : "r"(a + S0) : "memory");
}
__device__ __forceinline__ void ldsm4t(uint32_t (&u)[4], uint32_t a) {
    asm volatile("ldmatrix.sync.aligned.m8n8.x4.trans.shared.b16 {%0,%1,%2,%3}, [%4];"
                 : "=r"(u[0]), "=r"(u[1]), "=r"(u[2]), "=r"(u[3]) : "r"(a + S0) : "memory");
}
__device__ __forceinline__ void stsm4(uint32_t a, uint32_t p0, uint32_t p1, uint32_t p2, uint32_t p3) {
    asm volatile("stmatrix.sync.aligned.m8n8.x4.shared.b16 [%0], {%1,%2,%3,%4};" ::"r"(a + S0), "r"(p0), "r"(p1), "r"(p2), "r"(p3) : "memory");
}
__device__ __forceinline__ void stsm4t(uint32_t a, uint32_t p0, uint32_t p1, uint32_t p2, uint32_t p3) {
    asm volatile("stmatrix.sync.aligned.m8n8.x4.trans.shared.b16 [%0], {%1,%2,%3,%4};" ::"r"(a + S0), "r"(p0), "r"(p1), "r"(p2), "r"(p3) : "memory");
}

#define R8(o) "+f"(d[o]), "+f"(d[o + 1]), "+f"(d[o + 2]), "+f"(d[o + 3]), "+f"(d[o + 4]), "+f"(d[o + 5]), "+f"(d[o + 6]), "+f"(d[o + 7])
template <uint32_t ALO, uint32_t BLO, uint64_t AHI = 8, uint64_t BHI = 48>
__device__ __forceinline__ void wgmma128(float (&d)[64]) {
    asm volatile(
        "wgmma.mma_async.sync.aligned.m64n128k16.f32.bf16.bf16 "
        "{%0,%1,%2,%3,%4,%5,%6,%7,%8,%9,%10,%11,%12,%13,%14,%15,%16,%17,%18,%19,%20,%21,%22,%23,%24,%25,%26,%27,%28,%29,%30,%31,"
        "%32,%33,%34,%35,%36,%37,%38,%39,%40,%41,%42,%43,%44,%45,%46,%47,%48,%49,%50,%51,%52,%53,%54,%55,%56,%57,%58,%59,%60,%61,%62,%63},"
        " %64, %65, 1, 1, 1, 0, 0;"
        : R8(0), R8(8), R8(16), R8(24), R8(32), R8(40), R8(48), R8(56)
        : "l"((AHI << 32) | ALO), "l"((BHI << 32) | BLO));
}
template <int S>
__device__ __forceinline__ void mma_stages(float (&d)[64], int conv, int tid, Scratch* gs) {
    constexpr uint32_t A = ((SM_ACT + S * 2 * CH_PITCH + 16) >> 4) | ((CH_PITCH >> 4) << 16);
    constexpr uint32_t B = (slot_addr(S % NS) >> 4) | (8u << 16);
    if (S == 0) {
        unsigned it = 0;
#pragma unroll 1
        while (!MMA0_WAIT(BAR(BAR_FULL), conv) && ++it < SPIN_LIMIT) {}
    }
    bool next_ok = true;
    constexpr uint32_t NEXT = S + 1 < NSTAGE ? BAR(BAR_FULL + S + 1) : BAR(BAR_EMB);
    const int npar = S + 1 < NSTAGE ? conv : 0;
    next_ok = mbar_test(NEXT, npar);
    if (S == 0 && tid == 0) TL(32 + conv * 24);
    asm volatile("wgmma.fence.sync.aligned;" ::: "memory");
    wgmma128<A, B>(d);
    wgmma128<A + 1, B + 16>(d);
    wgmma128<A + 2, B + 32>(d);
    asm volatile("wgmma.commit_group.sync.aligned;" ::: "memory");
    if (S >= LAG) {
        asm volatile("wgmma.wait_group.sync.aligned %0;" ::"n"(LAG) : "memory");
        if ((tid & 31) == 0) mbar_arrive(BAR(BAR_WEMPTY + (S + NS - LAG) % NS));
    }
    if (!next_ok) mbar_wait(NEXT, npar);
    if constexpr (S + 1 < NSTAGE) mma_stages<S + 1>(d, conv, tid, gs);
}

__device__ __forceinline__ void weight_load(uint4 (&t)[5], const __nv_bfloat16* w, int cta, int lane) {
    const char* base = reinterpret_cast<const char*>(w) + ((cta & 15) * 8 * C + (cta >> 4) * 16) * 18;
#pragma unroll
    for (int k = 0; k < 5; k++) {
        const int i = lane + 32 * k, row = (i * 57) >> 10;
        if (k < 4 || lane < 16) t[k] = __ldg(reinterpret_cast<const uint4*>(base + row * (C * 18 - 288) + i * 16));
    }
}
__device__ __forceinline__ void weight_block(uint32_t bounce, unsigned char* wt, int cta, int lane, bool readback, Scratch* gs) {
    unsigned char* dst = wt + (cta >> 4) * STAGE_BYTES + (cta & 15) * 768;
    if (lane < 16) {
        uint32_t v[36];
#pragma unroll
        for (int i = 0; i < 9; i++) {
            const uint4 q = lds128(bounce + (lane & 7) * 288 + (lane >> 3) * 144 + i * 16);
            v[4 * i] = q.x; v[4 * i + 1] = q.y; v[4 * i + 2] = q.z; v[4 * i + 3] = q.w;
        }
#pragma unroll
        for (int kyo = 0; kyo < 3; kyo++) {
#pragma unroll
            for (int kx = 0; kx < 3; kx++) {
                const int tap = ky_of(kyo) * 3 + kx;
                uint32_t o[4];
#pragma unroll
                for (int m = 0; m < 4; m++) {
                    const int i0 = 18 * m + tap, i1 = i0 + 9;
                    const uint32_t sel = ((i0 & 1) ? 0x32u : 0x10u) | ((i1 & 1) ? 0x7600u : 0x5400u);
                    o[m] = __byte_perm(v[i0 >> 1], v[i1 >> 1], sel);
                }
                *reinterpret_cast<uint4*>(dst + kyo * 8 * STAGE_BYTES + kx * 256 + lane * 16) = make_uint4(o[0], o[1], o[2], o[3]);
            }
        }
    }
    if (readback) {
        __syncwarp();
        unsigned acc = 0;
        if (lane < 24) {
#pragma unroll
            for (int i = 0; i < 3; i++) acc |= ld_relaxed(dst + i * 8 * STAGE_BYTES + lane * 32);
        }
        asm volatile("{\n.reg .pred p;\nsetp.eq.u32 p, %0, 0x9e3779b9;\n@p st.shared.u32 [%1], %0;\n}" ::"r"(acc), "r"(bounce + S0) : "memory");
    }
}
__device__ __forceinline__ uint32_t act2(uint32_t u, const float4& cf) {
    return pack_bf(silu_half(fmaf(bf_lo(u), cf.x, cf.z)), silu_half(fmaf(bf_hi(u), cf.y, cf.w)));
}
__device__ __forceinline__ void norm_unit(uint32_t (&u)[4], const float4& ca, const float4& cb) {
    u[0] = act2(u[0], ca); u[1] = act2(u[1], ca); u[2] = act2(u[2], cb); u[3] = act2(u[3], cb);
}
__device__ __forceinline__ void read_stats(uint32_t gst, float (&g)[8]) {
    asm volatile("ld.volatile.shared.v4.f32 {%0,%1,%2,%3}, [%4];" : "=f"(g[0]), "=f"(g[1]), "=f"(g[2]), "=f"(g[3]) : "r"(gst + S0) : "memory");
    asm volatile("ld.volatile.shared.v4.f32 {%0,%1,%2,%3}, [%4];" : "=f"(g[4]), "=f"(g[5]), "=f"(g[6]), "=f"(g[7]) : "r"(gst + 16 + S0) : "memory");
}
template <int T>
__device__ __forceinline__ void group_coefs(uint32_t gst, float (&g)[8], float4 (&cf)[8]) {
    unsigned it = 0;
    if (!__all_sync(0xffffffffu, g[2 * T] != 0.f)) {
        float rs0;
#pragma unroll 1
        do {
            SPINPAUSE;
            asm volatile("ld.volatile.shared.f32 %0, [%1];" : "=f"(rs0) : "r"(gst + 8 * T + S0) : "memory");
        } while (!__all_sync(0xffffffffu, rs0 != 0.f) && ++it < 8 * SPIN_LIMIT);
        read_stats(gst, g);
    }
    float4 &ca = cf[2 * T], &cb = cf[2 * T + 1];
    const float rs = g[2 * T], mr = g[2 * T + 1];
    ca.z = fmaf(-mr, ca.x, ca.z); ca.w = fmaf(-mr, ca.y, ca.w); ca.x *= rs; ca.y *= rs;
    cb.z = fmaf(-mr, cb.x, cb.z); cb.w = fmaf(-mr, cb.y, cb.w); cb.x *= rs; cb.y *= rs;
}
template <int FIRST, int N>
__device__ __forceinline__ void norm_block(uint32_t (&u)[4][4], float4 (&cf)[8], uint32_t act, uint32_t mask, uint32_t fbar, int lane) {
#pragma unroll
    for (int t = FIRST; t < FIRST + N; t++) {
        norm_unit(u[t], cf[2 * t], cf[2 * t + 1]);
        stsm4(act + t * 2 * KC_BYTES, u[t][0] & mask, u[t][1] & mask, u[t][2] & mask, u[t][3] & mask);
    }
    fence_async_smem();
    __syncwarp();
    if (lane < N) mbar_arrive(fbar + 16 * (FIRST + lane));
}
__device__ __forceinline__ void publish(uint32_t bar, int lane) {
    fence_async_smem();
    __syncwarp();
    if (lane == 0) mbar_arrive(bar);
}
template <int T>
__device__ __forceinline__ void next_unit(uint32_t (&u)[4][4], float4 (&cf)[8], uint32_t gst, float (&g)[8], uint32_t act, uint32_t fbar, int lane) {
    const bool have = __all_sync(0xffffffffu, g[2 * T] != 0.f);
    if (!have) publish(fbar + 16 * (T - 1), lane);
    group_coefs<T>(gst, g, cf);
    norm_unit(u[T], cf[2 * T], cf[2 * T + 1]);
    if (have) publish(fbar + 16 * (T - 1), lane);
    stsm4(act + T * 2 * KC_BYTES, u[T][0], u[T][1], u[T][2], u[T][3]);
}
__device__ __forceinline__ void stat_mma(float (&c)[4], uint32_t p, uint32_t q) {
    asm("mma.sync.aligned.m16n8k16.row.col.f32.bf16.bf16.f32 {%0,%1,%2,%3}, {%4,%5,%6,%5}, {%4,%6}, {%0,%1,%2,%3};"
        : "+f"(c[0]), "+f"(c[1]), "+f"(c[2]), "+f"(c[3]) : "r"(p), "r"(0x3f803f80u), "r"(q));
}
__device__ __forceinline__ void stat_store(const float (&c)[4], uint32_t dst, int lane) {
    const int g = lane >> 2, t = lane & 3;
    if (t == (g >> 1)) sts32f(dst + g * 4, (g & 1) ? c[1] : c[0]);
    if (g == 7) sts32f(dst + 32 + t * 4, c[2] + c[3]);
}
__device__ __forceinline__ float sum4(float4 v) { return (v.x + v.y) + (v.z + v.w); }
__device__ __forceinline__ void stat_publish(uint32_t src, float* acc, int lane, bool real) {
    const uint32_t a = src + (lane & 15) * 48;
    float q = sum4(lds128f(a)) + sum4(lds128f(a + 16)), sm = sum4(lds128f(a + 32));
    q += __shfl_xor_sync(0xffffffffu, q, 1); sm += __shfl_xor_sync(0xffffffffu, sm, 1);
    q += __shfl_xor_sync(0xffffffffu, q, 2); sm += __shfl_xor_sync(0xffffffffu, sm, 2);
    if (real && (lane & 19) == 0) red_add4(acc + lane, 1.f, sm, q, 1.f);
}
__device__ __forceinline__ void fence_acc(float (&d)[64]) {
#pragma unroll
    for (int i = 0; i < 64; i++) asm volatile("" : "+f"(d[i])::"memory");
}
__device__ __forceinline__ void ld_unit(uint32_t (&u)[4], const uint4* p) {
    asm volatile("ld.relaxed.gpu.global.v4.u32 {%0,%1,%2,%3}, [%4];" : "=r"(u[0]), "=r"(u[1]), "=r"(u[2]), "=r"(u[3]) : "l"(p) : "memory");
}

__device__ __noinline__ void side_jobs(const __nv_bfloat16* __restrict__ t_emb, const __nv_bfloat16* __restrict__ w_emb,
                                       const __nv_bfloat16* __restrict__ w2, Scratch* __restrict__ gs, unsigned clk0) {
    const int tid = threadIdx.x, warp = tid >> 5, lane = tid & 31, j = blockIdx.x;
    float tv = 0.f;
    if (lane < 24) tv = __bfloat162float(t_emb[(lane / 12) * E + j * 192 + warp * 12 + lane % 12]);
    if (tid == 0) {
        mbar_init(BAR(0), 1);
        mbar_expect(BAR(0), 192 * C * 2);
        fence_async_smem();
        while (clock32() - clk0 < W2DELAY) {}
#pragma unroll
        for (int i = 0; i < 4; i++) bulk_g2s(S0 + SM_W + i * 12288, w_emb + (j * 192 + i * 48) * C, 12288, S0 + BAR(0));
    }
    if (j == 0 && tid < 32) gs->acc2[(tid >> 4) * LS + (tid & 15)] = 0.f;
    const float sv = silu_half(0.5f * tv);
    __syncthreads();
    mbar_wait(BAR(0), 0);
    float acc[8] = {0.f, 0.f, 0.f, 0.f, 0.f, 0.f, 0.f, 0.f};
#pragma unroll
    for (int i = 0; i < 12; i++) {
        const float2 wq = lds64f(SM_W + (warp * 12 + i) * 256 + lane * 8);
        const uint32_t wx = __float_as_uint(wq.x), wy = __float_as_uint(wq.y);
#pragma unroll
        for (int bb = 0; bb < 2; bb++) {
            const float sx = __shfl_sync(0xffffffffu, sv, bb * 12 + i);
            acc[4 * bb + 0] = fmaf(sx, bf_lo(wx), acc[4 * bb + 0]); acc[4 * bb + 1] = fmaf(sx, bf_hi(wx), acc[4 * bb + 1]);
            acc[4 * bb + 2] = fmaf(sx, bf_lo(wy), acc[4 * bb + 2]); acc[4 * bb + 3] = fmaf(sx, bf_hi(wy), acc[4 * bb + 3]);
        }
    }
    sts128f(SM_ACT + warp * 1024 + lane * 16, make_float4(acc[0], acc[1], acc[2], acc[3]));
    sts128f(SM_ACT + warp * 1024 + 512 + lane * 16, make_float4(acc[4], acc[5], acc[6], acc[7]));
    __syncthreads();
    if (tid < 128) {
        float2 sum = make_float2(0.f, 0.f);
#pragma unroll
        for (int w = 0; w < 16; w++) { const float2 p = lds64f(SM_ACT + w * 1024 + tid * 8); sum.x += p.x; sum.y += p.y; }
        *reinterpret_cast<float2*>(&gs->emb[j * NB * C + tid * 2]) = sum;
        bar_sync(1, 128);
        if (tid < 2) asm volatile("red.release.gpu.global.add.u32 [%0], 1;" ::"l"(&gs->wcnt[(2 * NB + tid) * LS]) : "memory");
    }
}

__global__ void __cluster_dims__(2, 1, 1) __launch_bounds__(NTHREADS, 1)
resblock_kernel(const __nv_bfloat16* __restrict__ w1,
                const __nv_bfloat16* __restrict__ t_emb, const __nv_bfloat16* __restrict__ g1,
                const __nv_bfloat16* __restrict__ be1, const __nv_bfloat16* __restrict__ w_emb,
                const __nv_bfloat16* __restrict__ g2, const __nv_bfloat16* __restrict__ be2,
                const __nv_bfloat16* __restrict__ w2, __nv_bfloat16* __restrict__ out, Scratch* __restrict__ gs,
                const __grid_constant__ CUtensorMap xmap) {
    const unsigned clk0 = clock32();
    if (threadIdx.x == 480 && blockIdx.x >= NXTRA) TLG(1);
    const int tid = threadIdx.x, lane = tid & 31;
    const int cta = blockIdx.x - NXTRA, b = cta >> 6, r = cta & 63;
    uint4 v[5];
    if (tid < 32) weight_load(v, w1, cta & (NCTA - 1), lane);
    const int warp = __shfl_sync(0xffffffffu, tid >> 5, 0);
    if (cta < 0) { side_jobs(t_emb, w_emb, w2, gs, clk0); return; }

    if (warp != 3) asm volatile("barrier.cluster.arrive.relaxed.aligned;" ::: "memory");
    const bool has_outer = (r != 0) && (r != HW - 1);
    if (warp == 1 || warp == 2 || warp == 4 || warp == 5) {
        const int g = warp < 3 ? warp - 1 : 7 - warp;
        if (elect_one()) {
            asm volatile("prefetch.tensormap [%0];" ::"l"(&xmap) : "memory");
            mbar_init(BAR(BAR_X) + 8 * g, 1);
            mbar_init(BAR(BAR_P) + 8 * g, 8);
            if (g == 3) mbar_init(BAR(BAR_X + 4), 1);
            mbar_expect(BAR(BAR_X) + 8 * g, 4096);
            fence_async_smem();
            while (clock32() - clk0 < XDELAY + (g >> 1) * XSTAG + (g & 1) * XSTAG2) {}
            tma_x(SM_XOWN + g * 4096, &xmap, r, b * C + g * 32, BAR(BAR_X) + 8 * g);
            if (g == 3 && has_outer) {
                mbar_expect(BAR(BAR_X + 4), 16384);
#pragma unroll
                for (int i = 0; i < 4; i++) tma_x(SM_XOUT + i * 4096, &xmap, r + ((r & 1) ? 1 : -1), b * C + i * 32, BAR(BAR_X + 4));
            }
        }
        __syncwarp();
        bar_arrive(4, 256 + 64 + 128);
        mbar_wait(BAR(BAR_P) + 8 * g, 0);
        if (lane == 0) TL(70 + g);
        const uint32_t a = SM_RED + (g * 8 + (lane & 7)) * 48;
        float q = sum4(lds128f(a)) + sum4(lds128f(a + 16)), sm = sum4(lds128f(a + 32));
#pragma unroll
        for (int m = 1; m < 8; m <<= 1) { q += __shfl_xor_sync(0xffffffffu, q, m); sm += __shfl_xor_sync(0xffffffffu, sm, m); }
        if (lane == 0) { red_add4(&gs->acc1[b * 4 * LS + g * GS1], 1.f, sm, q, 1.f); TL(74 + g); }
    }
    if (warp == 3) {
            if (elect_one()) {
#pragma unroll
                for (int i = 0; i < NSTAGE; i++) mbar_init(BAR(BAR_FULL + i), (i >> 3) == 1 ? 1 : 5);
#pragma unroll
                for (int i = 0; i < NS + 2; i++) mbar_init(BAR(BAR_WEMPTY + i), 4);
#pragma unroll
                for (int i = BAR_STATS; i < BAR_X; i++) mbar_init(BAR(i), i == BAR_EMB ? 3 : 1);
                asm volatile("fence.mbarrier_init.release.cluster;" ::: "memory");
            }
            __syncwarp();
            fence_async_smem();
            bar_arrive(0, 96);
            bar_arrive(5, 96);
            bar_arrive(4, 256 + 64 + 128);
            const uint4 z = make_uint4(0, 0, 0, 0);
#pragma unroll
            for (int i = 0; i < 2; i++) sts128(SM_ACT + (i * 16 + (lane >> 1)) * CH_PITCH + (lane & 1) * 16, z);
            if (lane < 4) sts128(SM_ACT + (2 + (lane >> 1)) * ROW_BYTES + (lane & 1) * 16, z);
            if (lane < 16) sts128(SM_ONES + lane * 16, make_uint4(lane < 8 ? 0x3f803f80u : 0u, 0, 0, 0));
            fence_async_smem();
            asm volatile("barrier.cluster.arrive.relaxed.aligned;" ::: "memory");
            if (lane == 0) TL(5);
            while (clock32() - clk0 < W2DELAY) {}
            weight_load(v, w2, cta, lane);
        }
    if (warp == 0 || warp == 3) {
        const int k = warp & 1;
#pragma unroll
        for (int i = 0; i < 5; i++)
            if (i < 4 || lane < 16) sts128(SM_BNC + k * 2304 + (lane + 32 * i) * 16, v[i]);
        if (lane == 0) TL(k ? 14 : 81);
        __syncwarp();
        weight_block(SM_BNC + k * 2304, gs->wt + k * NSTAGE * STAGE_BYTES, cta, lane, true, gs);
        __syncwarp();
        if (lane == 0) TL(k ? 13 : 4);
        if (lane < 2) asm volatile("red.relaxed.gpu.global.add.u32 [%0], 1;" ::"l"(&gs->wcnt[(k * NB + lane) * LS + (k ? 0 : cta >> 4)]) : "memory");
    }

    if (warp >= 8) {
        const int nw = warp - 8;
        bar_sync(4, 256 + 64 + 128);
        const int par = nw >> 2, wq = nw & 3;
        const uint32_t act_off = SM_ACT + (par * 2 + (lane >> 4)) * CH_PITCH + (2 + wq * 16 + (lane & 15)) * 16;
        const uint32_t stg_off = (par * 16 + (lane >> 4) * 8 + (lane & 7)) * 128 + (((2 * wq + ((lane >> 3) & 1)) ^ (lane & 7)) << 4);
        const uint32_t cfa = SM_COEF + par * 128 + (lane & 3) * 16;
        const uint32_t fbar = BAR(BAR_FULL) + 8 * par;
        uint4* inbox = gs->box + cta * 1024 + nw * 32 + lane;
#pragma unroll 1
        for (int conv = 0; conv < 2; conv++) {
            uint32_t u[4][4], w[4][4];
            float4 cf[8];
            if (conv == 0) {
#pragma unroll
                for (int i = 0; i < 4; i++) {
                    mbar_wait(BAR(BAR_X + i), 0);
                    if (i == 0 && tid == 256) TL(92);
                    ldsm4t(u[i], SM_XOWN + stg_off + i * 4096);
                    float c[4] = {0.f, 0.f, 0.f, 0.f};
                    stat_mma(c, u[i][0], u[i][1]); stat_mma(c, u[i][2], u[i][3]);
                    stat_store(c, SM_RED + (i * 8 + nw) * 48, lane);
                    __syncwarp();
                    if (lane == 0) mbar_arrive(BAR(BAR_P + i));
                }
            } else {
                mbar_wait(BAR(BAR_HW), 0);
#pragma unroll
                for (int i = 0; i < 4; i++) ldsm4(u[i], act_off + i * 2 * KC_BYTES);
            }
#pragma unroll
            for (int i = 0; i < 8; i++) cf[i] = lds128f(cfa + conv * 1024 + (i >> 1) * 256 + (i & 1) * 64);
            const uint32_t gst = SM_GST + conv * 32;
            float gv[8];
            read_stats(gst, gv);
            group_coefs<0>(gst, gv, cf);
            if (tid == 256) TL(22 + conv * 4);
            if (par) { const unsigned c1 = clock32(); while (clock32() - c1 < PDELAY) {} }
            norm_block<0, 1>(u, cf, act_off, ~0u, fbar, lane);
            if (tid == 256) TL(8 + conv * 8);
            group_coefs<1>(gst, gv, cf);
            norm_unit(u[1], cf[2], cf[3]);
            stsm4(act_off + 2 * KC_BYTES, u[1][0], u[1][1], u[1][2], u[1][3]);
            next_unit<2>(u, cf, gst, gv, act_off, fbar, lane);
            next_unit<3>(u, cf, gst, gv, act_off, fbar, lane);
            publish(fbar + 48, lane);
            if (tid == 256) TL(84 + conv);
            if (has_outer) {
                mbar_wait(BAR(BAR_X + 4), conv);
                if (conv == 0) {
#pragma unroll
                    for (int i = 0; i < 4; i++) ldsm4t(w[i], SM_XOUT + stg_off + i * 4096);
                } else {
#pragma unroll
                    for (int i = 0; i < 4; i++) {
                        const uint4 q = lds128(SM_XOWN + (tid - 256) * 16 + i * 4096);
                        w[i][0] = q.x; w[i][1] = q.y; w[i][2] = q.z; w[i][3] = q.w;
                    }
                    unsigned it = 0;
                    while (true) {
                        bool ok = true;
#pragma unroll
                        for (int i = 0; i < 16; i++) ok = ok && w[i >> 2][i & 3] != 0;
                        if (__all_sync(0xffffffffu, ok) || ++it > SPIN_LIMIT) break;
#pragma unroll
                        for (int i = 0; i < 4; i++) ld_unit(w[i], inbox + i * 256);
                    }
#pragma unroll
                    for (int i = 0; i < 16; i++) w[i >> 2][i & 3] = ~w[i >> 2][i & 3];
                }
            }
            if (conv == 0) {
                bar_sync(3, 256);
                if (nw == 0) sts128(SM_ACT + 2 * ROW_BYTES + (lane >> 1) * CH_PITCH + (lane & 1) * 16, make_uint4(0, 0, 0, 0));
            }
            if (tid == 256) TL(24 + conv * 4);
            norm_block<0, 2>(w, cf, act_off + 2 * ROW_BYTES, has_outer ? ~0u : 0u, fbar + 128, lane);
            if (tid == 256) TL(88 + conv);
            norm_block<2, 2>(w, cf, act_off + 2 * ROW_BYTES, has_outer ? ~0u : 0u, fbar + 128, lane);
            if (tid == 256) TL(23 + conv * 4);
        }
        if (has_outer) {
            mbar_wait(BAR(BAR_FULL + NSTAGE - 1), 1);
#pragma unroll
            for (int i = 0; i < 4; i++) inbox[i * 256] = make_uint4(0, 0, 0, 0);
        }
        {
            const int oc0 = (tid - 256) >> 3, seg = lane & 7;
            __nv_bfloat16* dst = out + ((size_t)(b * C + oc0) * HW + r) * HW + seg * 8;
            const uint32_t src = SM_XOWN + oc0 * 128 + ((seg ^ (oc0 & 7)) << 4);
            bar_sync(6, 128 + 256);
#pragma unroll
            for (int i = 0; i < 4; i++) *reinterpret_cast<uint4*>(dst + (size_t)i * 32 * HW * HW) = lds128(src + i * 4096);
            if (tid == 256) { TL(20); TLG(21); }
        }
    } else if (warp < 4) {
        const int wq = warp;
        bar_sync(2, 128);

        const uint32_t xbase = SM_XOWN + ((lane >> 4) * 8 + (lane & 7)) * 128 + (((2 * wq + ((lane >> 3) & 1)) ^ (lane & 7)) << 4);
        float d[64];
#pragma unroll
        for (int i = 0; i < 64; i++) d[i] = 0.f;
#pragma unroll 1
        for (int conv = 0; conv < 2; conv++) {
            fence_acc(d);
            mma_stages<0>(d, conv, tid, gs);
            if (conv == 0) {
                asm volatile("wgmma.fence.sync.aligned;" ::: "memory");
                wgmma128<(SM_ONES >> 4) | (8u << 16), (SM_EMB >> 4), 0, 8>(d);
                asm volatile("wgmma.commit_group.sync.aligned;" ::: "memory");
            }
            asm volatile("wgmma.wait_group.sync.aligned 0;" ::: "memory");
            fence_acc(d);
            if (tid == 0) TL(10 + conv * 8);
            uint32_t hp[32];
#pragma unroll
            for (int i = 0; i < 32; i++) hp[i] = pack_bf(d[2 * i], d[2 * i + 1]);
            if (conv == 1) {
#pragma unroll
                for (int kc = 0; kc < 8; kc++) stsm4t(xbase + kc * 2048, hp[4 * kc], hp[4 * kc + 1], hp[4 * kc + 2], hp[4 * kc + 3]);
                bar_arrive(6, 128 + 256);
                break;
            }
#pragma unroll
            for (int g = 0; g < 4; g++) {
                float c[4] = {0.f, 0.f, 0.f, 0.f};
#pragma unroll
                for (int i = 0; i < 4; i++) stat_mma(c, hp[8 * g + 2 * i], hp[8 * g + 2 * i + 1]);
                stat_store(c, SM_RED + (g * 4 + wq) * 48, lane);
            }
            bar_sync(2, 128);
            if (wq == 0) stat_publish(SM_RED, &gs->acc2[b * LS], lane, true);
            if (tid == 0) TL(11);
            const uint32_t hbase = SM_ACT + (lane >> 4) * CH_PITCH + (2 + wq * 16 + (lane & 15)) * 16;
#pragma unroll
            for (int kc = 0; kc < 8; kc++) stsm4(hbase + kc * 2 * CH_PITCH, hp[4 * kc], hp[4 * kc + 1], hp[4 * kc + 2], hp[4 * kc + 3]);
            __syncwarp();
            if (lane == 0) mbar_arrive(BAR(BAR_HW));
            if (lane < LAG) mbar_arrive(BAR(BAR_WEMPTY + (NSTAGE - LAG) % NS) + 8 * lane);
            if (has_outer) {
                uint4* outbox = gs->box + (cta + ((r & 1) ? 1 : -1)) * 1024 + tid;
#pragma unroll
                for (int kc = 0; kc < 8; kc++) outbox[kc * 128] = make_uint4(~hp[4 * kc], ~hp[4 * kc + 1], ~hp[4 * kc + 2], ~hp[4 * kc + 3]);
            }
            if (tid == 0) TL(12);
#pragma unroll
            for (int kc = 0; kc < 8; kc++) {
                uint32_t p[4];
                ldsm4t(p, xbase + kc * 2048);
#pragma unroll
                for (int i = 0; i < 4; i++) { d[8 * kc + 2 * i] = bf_lo(p[i]); d[8 * kc + 2 * i + 1] = bf_hi(p[i]); }
            }
            fence_async_smem();
            __syncwarp();
            if (lane == 0) mbar_arrive(BAR(BAR_XFREE));
        }
        {
        }
    } else if (warp < 6) {
        bar_sync(5, 96);
        if (warp == 5) {
            asm volatile("barrier.cluster.wait.acquire.aligned;" ::: "memory");
            const uint32_t peer = (r & 1) ^ 1;
            const uint32_t self0 = mapa(0, r & 1), peer0 = mapa(0, peer);
#pragma unroll 1
            for (int conv = 0; conv < 2; conv++) {
#pragma unroll 1
                for (int kc = 0; kc < 8; kc++) {
                    mbar_wait(BAR(BAR_FULL) + 8 * kc, conv);
                    if (elect_one())
                        asm volatile("cp.async.bulk.shared::cluster.shared::cta.mbarrier::complete_tx::bytes [%0], [%1], %2, [%3];"
                                     ::"r"(peer0 + SM_ACT + ROW_BYTES + kc * KC_BYTES), "r"(self0 + SM_ACT + kc * KC_BYTES), "r"(KC_BYTES),
                                       "r"(peer0 + BAR(BAR_FULL + 8) + 8 * kc) : "memory");
                }
                if (lane == 0) TL(86 + conv);
#pragma unroll 1
                for (int kc = 0; kc < 8; kc++) mbar_wait(BAR(BAR_FULL + 8) + 8 * kc, conv);
                if (lane == 0)
                    asm volatile("mbarrier.arrive.release.cluster.shared::cluster.b64 _, [%0];" ::"r"(peer0 + (conv ? BAR(BAR_ACK) : BAR(BAR_EMB))) : "memory");
            }
            mbar_wait(BAR(BAR_ACK), 0);
        } else {
            mbar_wait(BAR(BAR_STATS), 0);
            unsigned it = 0;
            while (ld_relaxed(&gs->wcnt[(2 * NB + b) * LS]) < (unsigned)NXTRA && ++it < SPIN_LIMIT) __nanosleep(100);
            fence_acquire();
            float ev[4] = {0.f, 0.f, 0.f, 0.f};
#pragma unroll
            for (int j = 0; j < NXTRA; j++) {
                const uint4 ef = ld_relaxed_v4(&gs->emb[(j * NB + b) * C + lane * 4]);
                ev[0] += __uint_as_float(ef.x); ev[1] += __uint_as_float(ef.y); ev[2] += __uint_as_float(ef.z); ev[3] += __uint_as_float(ef.w);
            }
#pragma unroll
            for (int i = 0; i < 4; i++) {
                const float hi = bf_lo(pack_bf(ev[i], 0.f));
                sts128(SM_EMB + (lane * 4 + i) * 16, make_uint4(pack_bf(hi, ev[i] - hi), 0, 0, 0));
            }
            fence_async_smem();
            __syncwarp();
            if (lane == 0) { mbar_arrive(BAR(BAR_EMB)); TL(19); }
        }
    } else if (warp == 6) {
        bar_sync(0, 96);
        const uint32_t ebytes = STAGE_BYTES + ((lane >> 3) == 1 ? KC_BYTES : 0);
        if (lane < NSTAGE) mbar_expect(BAR(BAR_FULL) + 8 * lane, ebytes);
        const int swap = (r & 1) ? 0 : 8 * STAGE_BYTES;
        unsigned it = 0;
        {
            int g = 0;
#pragma unroll 1
            while (g < NS) {
                unsigned ready = __ballot_sync(0xffffffffu, ld_relaxed(&gs->wcnt[b * LS + (lane & 7)]) >= 16u) >> g;
                if (++it > SPIN_LIMIT) ready = ~0u;
                if (!(ready & 1)) continue;
                fence_acquire();
                fence_async_global();
                if (lane == 0) TL(g ? 3 : 6);
#pragma unroll 1
                for (; (ready & 1) && g < NS; g++, ready >>= 1)
                    if (elect_one())
                        bulk_g2s(S0 + SM_W + g * STAGE_BYTES, gs->wt + g * STAGE_BYTES + (g >= 8 ? swap : 0), STAGE_BYTES, S0 + BAR(BAR_FULL) + 8 * g);
            }
        }
#pragma unroll 1
        for (int q = 3; q < 12; q++) {
            const int conv = q >= 6, qs = conv ? q - 6 : q, sl = q % 3;
            const unsigned char* wsrc = gs->wt + q * 4 * STAGE_BYTES + (qs < 2 ? 0 : (qs < 4 ? swap : -swap));
            const uint32_t par = (q / 3 - 1) & 1;
            if (q == 6) {
                it = 0;
                while (ld_relaxed(&gs->wcnt[(NB + b) * LS]) < (unsigned)NCTA && ++it < SPIN_LIMIT) {}
                fence_acquire();
                fence_async_global();
                if (lane == 0) { mbar_arrive(BAR(BAR_EMB)); TL(2); }
            }
#pragma unroll
            for (int i = 0; i < 4; i++) {
                mbar_wait(BAR(BAR_WEMPTY + i) + 32 * sl, par);
                if (i == 0 && (q == 6 || q == 9)) {
                    if ((lane >= NS) == (q == 9) && lane < NSTAGE) mbar_expect(BAR(BAR_FULL) + 8 * lane, ebytes);
                    __syncwarp();
                }
                if (elect_one())
                    bulk_g2s(S0 + SM_W + (sl * 4 + i) * STAGE_BYTES, wsrc + i * STAGE_BYTES, STAGE_BYTES, S0 + BAR(BAR_FULL + i) + 32 * qs);
            }
        }
    } else {
        const uint2 ga1 = __ldg(reinterpret_cast<const uint2*>(g1) + lane), bt1 = __ldg(reinterpret_cast<const uint2*>(be1) + lane);
        const uint2 ga2 = __ldg(reinterpret_cast<const uint2*>(g2) + lane), bt2 = __ldg(reinterpret_cast<const uint2*>(be2) + lane);
        if (lane < 8) sts128(SM_GST + lane * 16, make_uint4(0, 0, 0, 0));
        sts128f(SM_COEF + lane * 32, make_float4(0.5f * bf_lo(ga1.x), 0.5f * bf_hi(ga1.x), 0.5f * bf_lo(bt1.x), 0.5f * bf_hi(bt1.x)));
        sts128f(SM_COEF + lane * 32 + 16, make_float4(0.5f * bf_lo(ga1.y), 0.5f * bf_hi(ga1.y), 0.5f * bf_lo(bt1.y), 0.5f * bf_hi(bt1.y)));
        sts128f(SM_COEF + 1024 + lane * 32, make_float4(0.5f * bf_lo(ga2.x), 0.5f * bf_hi(ga2.x), 0.5f * bf_lo(bt2.x), 0.5f * bf_hi(bt2.x)));
        sts128f(SM_COEF + 1024 + lane * 32 + 16, make_float4(0.5f * bf_lo(ga2.y), 0.5f * bf_hi(ga2.y), 0.5f * bf_lo(bt2.y), 0.5f * bf_hi(bt2.y)));
        bar_arrive(4, 256 + 64 + 128);
        bar_sync(0, 96);
#pragma unroll 1
        for (int conv = 0; conv < 2; conv++) {
            if (conv == 1) {
                mbar_wait(BAR(BAR_HW), 0);
                const unsigned c1 = clock32();
                while (clock32() - c1 < PD2) {}
            } else {
                while (clock32() - clk0 < PD) {}
            }
            const float* asrc = conv ? &gs->acc2[b * LS + (lane & 3) * 4] : &gs->acc1[b * 4 * LS + (lane & 3) * GS1];
            unsigned it = 0;
            uint4 fq[NPOLL];
#pragma unroll
            for (int i = 0; i < NPOLL; i++) {
                fq[i] = ld_relaxed_v4(asrc);
                if (i + 1 < NPOLL) { const unsigned c1 = clock32(); while (clock32() - c1 < 450 / NPOLL) {} }
            }
            bool all = false;
#pragma unroll 1
            while (!all) {
#pragma unroll
                for (int i = 0; i < NPOLL; i++) {
                    const uint4 f = fq[i];
                    const bool ok = ((f.x == 0x42800000u) & (f.w == 0x42800000u)) || it > SPIN_LIMIT;
                    if (ok && lane < 4) {
                        const float inv_n = 1.0f / (32.0f * HW * HW);
                        const float mean = __uint_as_float(f.y) * inv_n;
                        const float rs = rsqrtf(fmaxf(fmaf(-mean, mean, __uint_as_float(f.z) * inv_n), 0.f) + 1e-5f);
                        asm volatile("st.shared.v2.f32 [%0], {%1,%2};" ::"r"(S0 + SM_GST + conv * 32 + lane * 8), "f"(rs == 0.f ? 1e-38f : rs), "f"(mean * rs) : "memory");
                    }
                    if (__all_sync(0xffffffffu, ok)) { all = true; break; }
                    fq[i] = ld_relaxed_v4(asrc);
                }
                it++;
            }
            if (lane == 0) { mbar_arrive(BAR(BAR_STATS)); TL(7 + conv * 8); }
        }
        mbar_wait(BAR(BAR_XFREE), 0);
        if (has_outer && elect_one()) {
            mbar_expect(BAR(BAR_X + 4), 16384);
            bulk_g2s(S0 + SM_XOWN, gs->box + cta * 1024, 16384, S0 + BAR(BAR_X + 4));
        }
        if (r == 0) {
            if (lane < 16) gs->acc1[b * 4 * LS + (lane >> 2) * GS1 + (lane & 3)] = 0.f;
            if (lane < 24) gs->wcnt[((lane >> 3) * NB + b) * LS + (lane & 7)] = 0;
        }
    }
}

}

extern "C" void kernel_launch(void* const* d_in, const int* in_sizes, int n_in, void* d_out, int out_size) {
    (void)in_sizes; (void)n_in; (void)out_size;
    typedef CUresult (*EncodeFn)(CUtensorMap*, CUtensorMapDataType, cuuint32_t, void*, const cuuint64_t*, const cuuint64_t*,
                                 const cuuint32_t*, const cuuint32_t*, CUtensorMapInterleave, CUtensorMapSwizzle,
                                 CUtensorMapL2promotion, CUtensorMapFloatOOBfill);
    static Scratch* gs = nullptr;
    static EncodeFn encode = nullptr;
    if (!gs) {
        cudaFuncSetAttribute(resblock_kernel, cudaFuncAttributeMaxDynamicSharedMemorySize, SM_TOTAL);
        cudaGetSymbolAddress((void**)&gs, g_scratch);
        cudaDriverEntryPointQueryResult qr;
        cudaGetDriverEntryPoint("cuTensorMapEncodeTiled", (void**)&encode, cudaEnableDefault, &qr);
    }
    CUtensorMap xmap;
    const cuuint64_t dims[3] = {HW, HW, NB * C}, strides[2] = {HW * 2, HW * HW * 2};
    const cuuint32_t box[3] = {HW, 1, 32}, es[3] = {1, 1, 1};
    encode(&xmap, CU_TENSOR_MAP_DATA_TYPE_BFLOAT16, 3, d_in[0], dims, strides, box, es, CU_TENSOR_MAP_INTERLEAVE_NONE,
           CU_TENSOR_MAP_SWIZZLE_128B, CU_TENSOR_MAP_L2_PROMOTION_NONE, CU_TENSOR_MAP_FLOAT_OOB_FILL_NONE);
    resblock_kernel<<<NCTA + NXTRA, NTHREADS, SM_TOTAL>>>(
        (const __nv_bfloat16*)d_in[4], (const __nv_bfloat16*)d_in[1],
        (const __nv_bfloat16*)d_in[2], (const __nv_bfloat16*)d_in[3], (const __nv_bfloat16*)d_in[5],
        (const __nv_bfloat16*)d_in[6], (const __nv_bfloat16*)d_in[7], (const __nv_bfloat16*)d_in[8],
        (__nv_bfloat16*)d_out, gs, xmap);
}
```

```cpp
#include <cuda_runtime.h>
#include <cuda.h>
#include <cuda_bf16.h>
#include <stdint.h>

namespace {

constexpr int C = 128, HW = 64, NB = 2, E = 768;
constexpr int NCTA = NB * HW;
constexpr int NXTRA = 4;
constexpr int NTHREADS = 16 * 32;
constexpr int CH_PITCH = 66 * 16;
constexpr int ROW_BYTES = 16 * CH_PITCH;
constexpr int STEP_BYTES = 4096;
constexpr int STAGE_BYTES = 3 * STEP_BYTES;
constexpr int NSTAGE = 24;
constexpr int KC_BYTES = 2 * CH_PITCH;
constexpr int NS = 12;
constexpr int LAG = 1;
#define XDELAY 400
#define HDELAY 600
#define SEQ 0
#define MMA0_WAIT mbar_try
#define SPINPAUSE
#define NPOLL 1
#define PD2 0
#define PDELAY 60
#define RB 1
#define XSTAG2 400
#define XSTAG 800
#define HSEND 0
#define W2DELAY 1800

constexpr uint32_t SMEM_BASE = 0x400;
constexpr uint32_t SM_XOWN = SMEM_BASE;
constexpr uint32_t SM_ACT = SM_XOWN + 16384 + 512;
constexpr uint32_t SM_XOUT = SM_ACT + 2 * ROW_BYTES + 512;
static_assert(SM_XOUT % 1024 == 0, "swizzle atom alignment");
constexpr uint32_t SM_W = SM_ACT + 3 * ROW_BYTES + 128;
__host__ __device__ constexpr uint32_t slot_addr(int slot) { return SM_W + slot * STAGE_BYTES; }
constexpr uint32_t SM_COEF = SM_W + NS * STAGE_BYTES;
constexpr uint32_t SM_GST = SM_COEF + 2048;
constexpr uint32_t SM_EMB = SM_GST + 128;
constexpr uint32_t SM_ONES = SM_EMB + 2048;
constexpr uint32_t SM_RED = SM_ONES + 256;
constexpr uint32_t SM_BNC = SM_RED + 1536;
constexpr uint32_t SM_BAR = SM_BNC + 2 * 2304;
constexpr int BAR_FULL = 0, BAR_WEMPTY = NSTAGE, BAR_HW = BAR_WEMPTY + NS, BAR_XFREE = BAR_HW + 1, BAR_STATS = BAR_XFREE + 1,
              BAR_EMB = BAR_STATS + 1, BAR_ACK = BAR_EMB + 1, BAR_X = BAR_ACK + 1  , BAR_P = BAR_X + 5  , NBAR = BAR_P + 4;
constexpr int SM_TOTAL = SM_BAR + NBAR * 8 - SMEM_BASE;
static_assert(SM_TOTAL <= 232448, "smem");
static_assert(NBAR <= 96, "barrier init");
__host__ __device__ constexpr uint32_t BAR(int i) { return SM_BAR + 8 * i; }
__host__ __device__ constexpr int ky_of(int kyo) { return kyo == 0 ? 1 : (kyo == 1 ? 0 : 2); }

constexpr unsigned SPIN_LIMIT = 1u << 16;

#define LS 1056
#define GS1 4
#define PD 0
struct Scratch {
    float acc1[NB * 4 * LS];
    float acc2[NB * LS];
    unsigned wcnt[3 * NB * LS];
    float emb[NXTRA * NB * C];
    unsigned char wt[2 * NSTAGE * STAGE_BYTES];
    uint4 box[NCTA * 1024];
};
__device__ __align__(1024) Scratch g_scratch;
#define TL(i) do {} while (0)
#define TLG(i) do {} while (0)

__device__ __forceinline__ unsigned clock32() { unsigned c; asm volatile("mov.u32 %0, %%clock;" : "=r"(c)); return c; }
__device__ __forceinline__ uint32_t mapa(uint32_t a, uint32_t rank) {
    uint32_t d;
    asm("mapa.shared::cluster.u32 %0, %1, %2;" : "=r"(d) : "r"(a), "r"(rank));
    return d;
}
#define S0 mapa(0, blockIdx.x & 1)
__device__ __forceinline__ void mbar_init(uint32_t bar, int cnt) {
    asm volatile("mbarrier.init.shared::cta.b64 [%0], %1;" ::"r"(bar + S0), "r"(cnt) : "memory");
}
__device__ __forceinline__ void mbar_arrive(uint32_t bar) {
    asm volatile("mbarrier.arrive.shared::cta.b64 _, [%0];" ::"r"(bar + S0) : "memory");
}
__device__ __forceinline__ void mbar_expect(uint32_t bar, uint32_t bytes) {
    asm volatile("mbarrier.arrive.expect_tx.shared::cta.b64 _, [%0], %1;" ::"r"(bar + S0), "r"(bytes) : "memory");
}
__device__ __forceinline__ bool mbar_try(uint32_t bar, uint32_t par) {
    uint32_t ok;
    asm volatile("{\n.reg .pred p;\nmbarrier.try_wait.parity.shared::cta.b64 p, [%1], %2;\nselp.u32 %0, 1, 0, p;\n}"
                 : "=r"(ok) : "r"(bar + S0), "r"(par) : "memory");
    return ok;
}
__device__ __forceinline__ bool mbar_test(uint32_t bar, uint32_t par) {
    uint32_t ok;
    asm volatile("{\n.reg .pred p;\nmbarrier.test_wait.parity.shared::cta.b64 p, [%1], %2;\nselp.u32 %0, 1, 0, p;\n}"
                 : "=r"(ok) : "r"(bar + S0), "r"(par) : "memory");
    return ok;
}
__device__ __forceinline__ void mbar_wait(uint32_t bar, uint32_t par) {
    unsigned it = 0;
#pragma unroll 1
    while (!mbar_try(bar, par) && ++it < SPIN_LIMIT) {}
}
__device__ __forceinline__ bool elect_one() {
    uint32_t p;
    asm volatile("{\n.reg .pred p;\nelect.sync _|p, 0xffffffff;\nselp.u32 %0, 1, 0, p;\n}" : "=r"(p));
    return p;
}
__device__ __forceinline__ void fence_async_smem() { asm volatile("fence.proxy.async.shared::cta;" ::: "memory"); }
__device__ __forceinline__ void fence_async_global() { asm volatile("fence.proxy.async.global;" ::: "memory"); }
__device__ __forceinline__ void fence_acquire() { asm volatile("fence.acquire.gpu;" ::: "memory"); }
__device__ __forceinline__ void bar_sync(int id, int n) { asm volatile("bar.sync %0, %1;" ::"r"(id), "r"(n) : "memory"); }
__device__ __forceinline__ void bar_arrive(int id, int n) { asm volatile("bar.arrive %0, %1;" ::"r"(id), "r"(n) : "memory"); }
__device__ __forceinline__ void bulk_g2s(uint32_t dst, const void* src, uint32_t bytes, uint32_t bar) {
    asm volatile("cp.async.bulk.shared::cluster.global.mbarrier::complete_tx::bytes [%0], [%1], %2, [%3];"
                 ::"r"(dst), "l"(src), "r"(bytes), "r"(bar) : "memory");
}
__device__ __forceinline__ void tma_x(uint32_t dst, const CUtensorMap* tm, int row, int ch, uint32_t bar) {
    asm volatile("cp.async.bulk.tensor.3d.shared::cluster.global.mbarrier::complete_tx::bytes [%0], [%1, {%2, %3, %4}], [%5];"
                 ::"r"(dst + S0), "l"(tm), "r"(0), "r"(row), "r"(ch), "r"(bar + S0) : "memory");
}
__device__ __forceinline__ uint4 ld_relaxed_v4(const void* p) {
    uint4 v;
    asm volatile("ld.relaxed.gpu.global.v4.u32 {%0,%1,%2,%3}, [%4];" : "=r"(v.x), "=r"(v.y), "=r"(v.z), "=r"(v.w) : "l"(p) : "memory");
    return v;
}
__device__ __forceinline__ unsigned ld_relaxed(const void* p) {
    unsigned v;
    asm volatile("ld.relaxed.gpu.global.u32 %0, [%1];" : "=r"(v) : "l"(p) : "memory");
    return v;
}
__device__ __forceinline__ void red_add4(float* p, float a, float b, float c, float d) {
    asm volatile("red.relaxed.gpu.global.add.v4.f32 [%0], {%1,%2,%3,%4};" ::"l"(p), "f"(a), "f"(b), "f"(c), "f"(d) : "memory");
}
__device__ __forceinline__ void sts128(uint32_t a, uint4 v) {
    asm volatile("st.shared.v4.u32 [%0], {%1,%2,%3,%4};" ::"r"(a + S0), "r"(v.x), "r"(v.y), "r"(v.z), "r"(v.w) : "memory");
}
__device__ __forceinline__ void sts128f(uint32_t a, float4 v) {
    asm volatile("st.shared.v4.f32 [%0], {%1,%2,%3,%4};" ::"r"(a + S0), "f"(v.x), "f"(v.y), "f"(v.z), "f"(v.w) : "memory");
}
__device__ __forceinline__ void sts32f(uint32_t a, float v) { asm volatile("st.shared.f32 [%0], %1;" ::"r"(a + S0), "f"(v) : "memory"); }
__device__ __forceinline__ uint4 lds128(uint32_t a) {
    uint4 v;
    asm volatile("ld.shared.v4.u32 {%0,%1,%2,%3}, [%4];" : "=r"(v.x), "=r"(v.y), "=r"(v.z), "=r"(v.w) : "r"(a + S0) : "memory");
    return v;
}
__device__ __forceinline__ float4 lds128f(uint32_t a) {
    float4 v;
    asm volatile("ld.shared.v4.f32 {%0,%1,%2,%3}, [%4];" : "=f"(v.x), "=f"(v.y), "=f"(v.z), "=f"(v.w) : "r"(a + S0) : "memory");
    return v;
}
__device__ __forceinline__ float2 lds64f(uint32_t a) {
    float2 v;
    asm volatile("ld.shared.v2.f32 {%0,%1}, [%2];" : "=f"(v.x), "=f"(v.y) : "r"(a + S0) : "memory");
    return v;
}
__device__ __forceinline__ float bf_lo(uint32_t u) { return __uint_as_float(u << 16); }
__device__ __forceinline__ float bf_hi(uint32_t u) { return __uint_as_float(u & 0xffff0000u); }
__device__ __forceinline__ uint32_t pack_bf(float lo, float hi) {
    uint32_t r;
    asm("cvt.rn.bf16x2.f32 %0, %1, %2;" : "=r"(r) : "f"(hi), "f"(lo));
    return r;
}
__device__ __forceinline__ float tanh_fast(float x) {
    float r;
    asm("tanh.approx.f32 %0, %1;" : "=f"(r) : "f"(x));
    return r;
}
__device__ __forceinline__ float silu_half(float h) { return fmaf(h, tanh_fast(h), h); }
__device__ __forceinline__ void ldsm4(uint32_t (&u)[4], uint32_t a) {
    asm volatile("ldmatrix.sync.aligned.m8n8.x4.shared.b16 {%0,%1,%2,%3}, [%4];"
                 : "=r"(u[0]), "=r"(u[1]), "=r"(u[2]), "=r"(u[3]) : "r"(a + S0) : "memory");
}
__device__ __forceinline__ void ldsm4t(uint32_t (&u)[4], uint32_t a) {
    asm volatile("ldmatrix.sync.aligned.m8n8.x4.trans.shared.b16 {%0,%1,%2,%3}, [%4];"
                 : "=r"(u[0]), "=r"(u[1]), "=r"(u[2]), "=r"(u[3]) : "r"(a + S0) : "memory");
}
__device__ __forceinline__ void stsm4(uint32_t a, uint32_t p0, uint32_t p1, uint32_t p2, uint32_t p3) {
    asm volatile("stmatrix.sync.aligned.m8n8.x4.shared.b16 [%0], {%1,%2,%3,%4};" ::"r"(a + S0), "r"(p0), "r"(p1), "r"(p2), "r"(p3) : "memory");
}
__device__ __forceinline__ void stsm4t(uint32_t a, uint32_t p0, uint32_t p1, uint32_t p2, uint32_t p3) {
    asm volatile("stmatrix.sync.aligned.m8n8.x4.trans.shared.b16 [%0], {%1,%2,%3,%4};" ::"r"(a + S0), "r"(p0), "r"(p1), "r"(p2), "r"(p3) : "memory");
}

#define R8(o) "+f"(d[o]), "+f"(d[o + 1]), "+f"(d[o + 2]), "+f"(d[o + 3]), "+f"(d[o + 4]), "+f"(d[o + 5]), "+f"(d[o + 6]), "+f"(d[o + 7])
template <uint32_t ALO, uint32_t BLO, uint64_t AHI = 8, uint64_t BHI = 48>
__device__ __forceinline__ void wgmma128(float (&d)[64]) {
    asm volatile(
        "wgmma.mma_async.sync.aligned.m64n128k16.f32.bf16.bf16 "
        "{%0,%1,%2,%3,%4,%5,%6,%7,%8,%9,%10,%11,%12,%13,%14,%15,%16,%17,%18,%19,%20,%21,%22,%23,%24,%25,%26,%27,%28,%29,%30,%31,"
        "%32,%33,%34,%35,%36,%37,%38,%39,%40,%41,%42,%43,%44,%45,%46,%47,%48,%49,%50,%51,%52,%53,%54,%55,%56,%57,%58,%59,%60,%61,%62,%63},"
        " %64, %65, 1, 1, 1, 0, 0;"
        : R8(0), R8(8), R8(16), R8(24), R8(32), R8(40), R8(48), R8(56)
        : "l"((AHI << 32) | ALO), "l"((BHI << 32) | BLO));
}
template <int S>
__device__ __forceinline__ void mma_stages(float (&d)[64], int conv, int tid, Scratch* gs) {
    constexpr uint32_t A = ((SM_ACT + S * 2 * CH_PITCH + 16) >> 4) | ((CH_PITCH >> 4) << 16);
    constexpr uint32_t B = (slot_addr(S % NS) >> 4) | (8u << 16);
    if (S == 0) {
        unsigned it = 0;
#pragma unroll 1
        while (!MMA0_WAIT(BAR(BAR_FULL), conv) && ++it < SPIN_LIMIT) {}
    }
    bool next_ok = true;
    constexpr uint32_t NEXT = S + 1 < NSTAGE ? BAR(BAR_FULL + S + 1) : BAR(BAR_EMB);
    const int npar = S + 1 < NSTAGE ? conv : 0;
    next_ok = mbar_test(NEXT, npar);
    if (S == 0 && tid == 0) TL(32 + conv * 24);
    asm volatile("wgmma.fence.sync.aligned;" ::: "memory");
    wgmma128<A, B>(d);
    wgmma128<A + 1, B + 16>(d);
    wgmma128<A + 2, B + 32>(d);
    asm volatile("wgmma.commit_group.sync.aligned;" ::: "memory");
    if (S >= LAG) {
        asm volatile("wgmma.wait_group.sync.aligned %0;" ::"n"(LAG) : "memory");
        if ((tid & 31) == 0) mbar_arrive(BAR(BAR_WEMPTY + (S + NS - LAG) % NS));
    }
    if (!next_ok) mbar_wait(NEXT, npar);
    if constexpr (S + 1 < NSTAGE) mma_stages<S + 1>(d, conv, tid, gs);
}

__device__ __forceinline__ void weight_load(uint4 (&t)[5], const __nv_bfloat16* w, int cta, int lane) {
    const char* base = reinterpret_cast<const char*>(w) + ((cta & 15) * 8 * C + (cta >> 4) * 16) * 18;
#pragma unroll
    for (int k = 0; k < 5; k++) {
        const int i = lane + 32 * k, row = (i * 57) >> 10;
        if (k < 4 || lane < 16) t[k] = __ldg(reinterpret_cast<const uint4*>(base + row * (C * 18 - 288) + i * 16));
    }
}
__device__ __forceinline__ void weight_block(uint32_t bounce, unsigned char* wt, int cta, int lane, bool readback, Scratch* gs) {
    unsigned char* dst = wt + (cta >> 4) * STAGE_BYTES + (cta & 15) * 768;
    if (lane < 16) {
        uint32_t v[36];
#pragma unroll
        for (int i = 0; i < 9; i++) {
            const uint4 q = lds128(bounce + (lane & 7) * 288 + (lane >> 3) * 144 + i * 16);
            v[4 * i] = q.x; v[4 * i + 1] = q.y; v[4 * i + 2] = q.z; v[4 * i + 3] = q.w;
        }
#pragma unroll
        for (int kyo = 0; kyo < 3; kyo++) {
#pragma unroll
            for (int kx = 0; kx < 3; kx++) {
                const int tap = ky_of(kyo) * 3 + kx;
                uint32_t o[4];
#pragma unroll
                for (int m = 0; m < 4; m++) {
                    const int i0 = 18 * m + tap, i1 = i0 + 9;
                    const uint32_t sel = ((i0 & 1) ? 0x32u : 0x10u) | ((i1 & 1) ? 0x7600u : 0x5400u);
                    o[m] = __byte_perm(v[i0 >> 1], v[i1 >> 1], sel);
                }
                *reinterpret_cast<uint4*>(dst + kyo * 8 * STAGE_BYTES + kx * 256 + lane * 16) = make_uint4(o[0], o[1], o[2], o[3]);
            }
        }
    }
    if (readback) {
        __syncwarp();
        unsigned acc = 0;
        if (lane < 24) {
#pragma unroll
            for (int i = 0; i < 3; i++) acc |= ld_relaxed(dst + i * 8 * STAGE_BYTES + lane * 32);
        }
        asm volatile("{\n.reg .pred p;\nsetp.eq.u32 p, %0, 0x9e3779b9;\n@p st.shared.u32 [%1], %0;\n}" ::"r"(acc), "r"(bounce + S0) : "memory");
    }
}
__device__ __forceinline__ uint32_t act2(uint32_t u, const float4& cf) {
    return pack_bf(silu_half(fmaf(bf_lo(u), cf.x, cf.z)), silu_half(fmaf(bf_hi(u), cf.y, cf.w)));
}
__device__ __forceinline__ void norm_unit(uint32_t (&u)[4], const float4& ca, const float4& cb) {
    u[0] = act2(u[0], ca); u[1] = act2(u[1], ca); u[2] = act2(u[2], cb); u[3] = act2(u[3], cb);
}
__device__ __forceinline__ void read_stats(uint32_t gst, float (&g)[8]) {
    asm volatile("ld.volatile.shared.v4.f32 {%0,%1,%2,%3}, [%4];" : "=f"(g[0]), "=f"(g[1]), "=f"(g[2]), "=f"(g[3]) : "r"(gst + S0) : "memory");
    asm volatile("ld.volatile.shared.v4.f32 {%0,%1,%2,%3}, [%4];" : "=f"(g[4]), "=f"(g[5]), "=f"(g[6]), "=f"(g[7]) : "r"(gst + 16 + S0) : "memory");
}
template <int T>
__device__ __forceinline__ void group_coefs(uint32_t gst, float (&g)[8], float4 (&cf)[8]) {
    unsigned it = 0;
    if (!__all_sync(0xffffffffu, g[2 * T] != 0.f)) {
        float rs0;
#pragma unroll 1
        do {
            SPINPAUSE;
            asm volatile("ld.volatile.shared.f32 %0, [%1];" : "=f"(rs0) : "r"(gst + 8 * T + S0) : "memory");
        } while (!__all_sync(0xffffffffu, rs0 != 0.f) && ++it < 8 * SPIN_LIMIT);
        read_stats(gst, g);
    }
    float4 &ca = cf[2 * T], &cb = cf[2 * T + 1];
    const float rs = g[2 * T], mr = g[2 * T + 1];
    ca.z = fmaf(-mr, ca.x, ca.z); ca.w = fmaf(-mr, ca.y, ca.w); ca.x *= rs; ca.y *= rs;
    cb.z = fmaf(-mr, cb.x, cb.z); cb.w = fmaf(-mr, cb.y, cb.w); cb.x *= rs; cb.y *= rs;
}
template <int FIRST, int N>
__device__ __forceinline__ void norm_block(uint32_t (&u)[4][4], float4 (&cf)[8], uint32_t act, uint32_t mask, uint32_t fbar, int lane) {
#pragma unroll
    for (int t = FIRST; t < FIRST + N; t++) {
        norm_unit(u[t], cf[2 * t], cf[2 * t + 1]);
        stsm4(act + t * 2 * KC_BYTES, u[t][0] & mask, u[t][1] & mask, u[t][2] & mask, u[t][3] & mask);
    }
    fence_async_smem();
    __syncwarp();
    if (lane < N) mbar_arrive(fbar + 16 * (FIRST + lane));
}
__device__ __forceinline__ void publish(uint32_t bar, int lane) {
    fence_async_smem();
    __syncwarp();
    if (lane == 0) mbar_arrive(bar);
}
template <int T>
__device__ __forceinline__ void next_unit(uint32_t (&u)[4][4], float4 (&cf)[8], uint32_t gst, float (&g)[8], uint32_t act, uint32_t fbar, int lane) {
    const bool have = __all_sync(0xffffffffu, g[2 * T] != 0.f);
    if (!have) publish(fbar + 16 * (T - 1), lane);
    group_coefs<T>(gst, g, cf);
    norm_unit(u[T], cf[2 * T], cf[2 * T + 1]);
    if (have) publish(fbar + 16 * (T - 1), lane);
    stsm4(act + T * 2 * KC_BYTES, u[T][0], u[T][1], u[T][2], u[T][3]);
}
__device__ __forceinline__ void stat_mma(float (&c)[4], uint32_t p, uint32_t q) {
    asm("mma.sync.aligned.m16n8k16.row.col.f32.bf16.bf16.f32 {%0,%1,%2,%3}, {%4,%5,%6,%5}, {%4,%6}, {%0,%1,%2,%3};"
        : "+f"(c[0]), "+f"(c[1]), "+f"(c[2]), "+f"(c[3]) : "r"(p), "r"(0x3f803f80u), "r"(q));
}
__device__ __forceinline__ void stat_store(const float (&c)[4], uint32_t dst, int lane) {
    const int g = lane >> 2, t = lane & 3;
    if (t == (g >> 1)) sts32f(dst + g * 4, (g & 1) ? c[1] : c[0]);
    if (g == 7) sts32f(dst + 32 + t * 4, c[2] + c[3]);
}
__device__ __forceinline__ float sum4(float4 v) { return (v.x + v.y) + (v.z + v.w); }
__device__ __forceinline__ void stat_publish(uint32_t src, float* acc, int lane, bool real) {
    const uint32_t a = src + (lane & 15) * 48;
    float q = sum4(lds128f(a)) + sum4(lds128f(a + 16)), sm = sum4(lds128f(a + 32));
    q += __shfl_xor_sync(0xffffffffu, q, 1); sm += __shfl_xor_sync(0xffffffffu, sm, 1);
    q += __shfl_xor_sync(0xffffffffu, q, 2); sm += __shfl_xor_sync(0xffffffffu, sm, 2);
    if (real && (lane & 19) == 0) red_add4(acc + lane, 1.f, sm, q, 1.f);
}
__device__ __forceinline__ void fence_acc(float (&d)[64]) {
#pragma unroll
    for (int i = 0; i < 64; i++) asm volatile("" : "+f"(d[i])::"memory");
}
__device__ __forceinline__ void ld_unit(uint32_t (&u)[4], const uint4* p) {
    asm volatile("ld.relaxed.gpu.global.v4.u32 {%0,%1,%2,%3}, [%4];" : "=r"(u[0]), "=r"(u[1]), "=r"(u[2]), "=r"(u[3]) : "l"(p) : "memory");
}

__device__ __noinline__ void side_jobs(const __nv_bfloat16* __restrict__ t_emb, const __nv_bfloat16* __restrict__ w_emb,
                                       const __nv_bfloat16* __restrict__ w2, Scratch* __restrict__ gs, unsigned clk0) {
    const int tid = threadIdx.x, warp = tid >> 5, lane = tid & 31, j = blockIdx.x;
    float tv = 0.f;
    if (lane < 24) tv = __bfloat162float(t_emb[(lane / 12) * E + j * 192 + warp * 12 + lane % 12]);
    if (tid == 0) {
        mbar_init(BAR(0), 1);
        mbar_expect(BAR(0), 192 * C * 2);
        fence_async_smem();
        while (clock32() - clk0 < W2DELAY) {}
#pragma unroll
        for (int i = 0; i < 4; i++) bulk_g2s(S0 + SM_W + i * 12288, w_emb + (j * 192 + i * 48) * C, 12288, S0 + BAR(0));
    }
    if (j == 0 && tid < 32) gs->acc2[(tid >> 4) * LS + (tid & 15)] = 0.f;
    const float sv = silu_half(0.5f * tv);
    __syncthreads();
    mbar_wait(BAR(0), 0);
    float acc[8] = {0.f, 0.f, 0.f, 0.f, 0.f, 0.f, 0.f, 0.f};
#pragma unroll
    for (int i = 0; i < 12; i++) {
        const float2 wq = lds64f(SM_W + (warp * 12 + i) * 256 + lane * 8);
        const uint32_t wx = __float_as_uint(wq.x), wy = __float_as_uint(wq.y);
#pragma unroll
        for (int bb = 0; bb < 2; bb++) {
            const float sx = __shfl_sync(0xffffffffu, sv, bb * 12 + i);
            acc[4 * bb + 0] = fmaf(sx, bf_lo(wx), acc[4 * bb + 0]); acc[4 * bb + 1] = fmaf(sx, bf_hi(wx), acc[4 * bb + 1]);
            acc[4 * bb + 2] = fmaf(sx, bf_lo(wy), acc[4 * bb + 2]); acc[4 * bb + 3] = fmaf(sx, bf_hi(wy), acc[4 * bb + 3]);
        }
    }
    sts128f(SM_ACT + warp * 1024 + lane * 16, make_float4(acc[0], acc[1], acc[2], acc[3]));
    sts128f(SM_ACT + warp * 1024 + 512 + lane * 16, make_float4(acc[4], acc[5], acc[6], acc[7]));
    __syncthreads();
    if (tid < 128) {
        float2 sum = make_float2(0.f, 0.f);
#pragma unroll
        for (int w = 0; w < 16; w++) { const float2 p = lds64f(SM_ACT + w * 1024 + tid * 8); sum.x += p.x; sum.y += p.y; }
        *reinterpret_cast<float2*>(&gs->emb[j * NB * C + tid * 2]) = sum;
        bar_sync(1, 128);
        if (tid < 2) asm volatile("red.release.gpu.global.add.u32 [%0], 1;" ::"l"(&gs->wcnt[(2 * NB + tid) * LS]) : "memory");
    }
}

__global__ void __cluster_dims__(2, 1, 1) __launch_bounds__(NTHREADS, 1)
resblock_kernel(const __nv_bfloat16* __restrict__ w1,
                const __nv_bfloat16* __restrict__ t_emb, const __nv_bfloat16* __restrict__ g1,
                const __nv_bfloat16* __restrict__ be1, const __nv_bfloat16* __restrict__ w_emb,
                const __nv_bfloat16* __restrict__ g2, const __nv_bfloat16* __restrict__ be2,
                const __nv_bfloat16* __restrict__ w2, __nv_bfloat16* __restrict__ out, Scratch* __restrict__ gs,
                const __grid_constant__ CUtensorMap xmap) {
    const unsigned clk0 = clock32();
    if (threadIdx.x == 480 && blockIdx.x >= NXTRA) TLG(1);
    const int tid = threadIdx.x, lane = tid & 31;
    const int cta = blockIdx.x - NXTRA, b = cta >> 6, r = cta & 63;
    uint4 v[5];
    if (tid < 32) weight_load(v, w1, cta & (NCTA - 1), lane);
    const int warp = __shfl_sync(0xffffffffu, tid >> 5, 0);
    if (cta < 0) { side_jobs(t_emb, w_emb, w2, gs, clk0); return; }

    if (warp != 3) asm volatile("barrier.cluster.arrive.relaxed.aligned;" ::: "memory");
    const bool has_outer = (r != 0) && (r != HW - 1);
    if (warp == 1 || warp == 2 || warp == 4 || warp == 5) {
        const int g = warp < 3 ? warp - 1 : 7 - warp;
        if (elect_one()) {
            asm volatile("prefetch.tensormap [%0];" ::"l"(&xmap) : "memory");
            mbar_init(BAR(BAR_X) + 8 * g, 1);
            mbar_init(BAR(BAR_P) + 8 * g, 8);
            if (g == 3) mbar_init(BAR(BAR_X + 4), 1);
            mbar_expect(BAR(BAR_X) + 8 * g, 4096);
            fence_async_smem();
        }
        __syncwarp();
        bar_arrive(4, 256 + 64 + 128);
        if (elect_one()) {
            while (clock32() - clk0 < XDELAY + (g >> 1) * XSTAG + (g & 1) * XSTAG2) {}
            tma_x(SM_XOWN + g * 4096, &xmap, r, b * C + g * 32, BAR(BAR_X) + 8 * g);
            if (g == 3 && has_outer) {
                mbar_expect(BAR(BAR_X + 4), 16384);
#pragma unroll
                for (int i = 0; i < 4; i++) tma_x(SM_XOUT + i * 4096, &xmap, r + ((r & 1) ? 1 : -1), b * C + i * 32, BAR(BAR_X + 4));
            }
        }
        __syncwarp();
        mbar_wait(BAR(BAR_P) + 8 * g, 0);
        if (lane == 0) TL(70 + g);
        const uint32_t a = SM_RED + (g * 8 + (lane & 7)) * 48;
        float q = sum4(lds128f(a)) + sum4(lds128f(a + 16)), sm = sum4(lds128f(a + 32));
#pragma unroll
        for (int m = 1; m < 8; m <<= 1) { q += __shfl_xor_sync(0xffffffffu, q, m); sm += __shfl_xor_sync(0xffffffffu, sm, m); }
        if (lane == 0) { red_add4(&gs->acc1[b * 4 * LS + g * GS1], 1.f, sm, q, 1.f); TL(74 + g); }
    }
    if (warp == 3) {
            if (elect_one()) {
#pragma unroll
                for (int i = 0; i < NSTAGE; i++) mbar_init(BAR(BAR_FULL + i), (i >> 3) == 1 ? 1 : 5);
#pragma unroll
                for (int i = 0; i < NS + 2; i++) mbar_init(BAR(BAR_WEMPTY + i), 4);
#pragma unroll
                for (int i = BAR_STATS; i < BAR_X; i++) mbar_init(BAR(i), i == BAR_EMB ? 3 : 1);
                asm volatile("fence.mbarrier_init.release.cluster;" ::: "memory");
            }
            __syncwarp();
            fence_async_smem();
            bar_arrive(0, 96);
            bar_arrive(5, 96);
            bar_arrive(4, 256 + 64 + 128);
            const uint4 z = make_uint4(0, 0, 0, 0);
#pragma unroll
            for (int i = 0; i < 2; i++) sts128(SM_ACT + (i * 16 + (lane >> 1)) * CH_PITCH + (lane & 1) * 16, z);
            if (lane < 4) sts128(SM_ACT + (2 + (lane >> 1)) * ROW_BYTES + (lane & 1) * 16, z);
            if (lane < 16) sts128(SM_ONES + lane * 16, make_uint4(lane < 8 ? 0x3f803f80u : 0u, 0, 0, 0));
            fence_async_smem();
            asm volatile("barrier.cluster.arrive.relaxed.aligned;" ::: "memory");
            if (lane == 0) TL(5);
            while (clock32() - clk0 < W2DELAY) {}
            weight_load(v, w2, cta, lane);
        }
    if (warp == 0 || warp == 3) {
        const int k = warp & 1;
#pragma unroll
        for (int i = 0; i < 5; i++)
            if (i < 4 || lane < 16) sts128(SM_BNC + k * 2304 + (lane + 32 * i) * 16, v[i]);
        if (lane == 0) TL(k ? 14 : 81);
        __syncwarp();
        weight_block(SM_BNC + k * 2304, gs->wt + k * NSTAGE * STAGE_BYTES, cta, lane, true, gs);
        __syncwarp();
        if (lane == 0) TL(k ? 13 : 4);
        if (lane < 2) asm volatile("red.relaxed.gpu.global.add.u32 [%0], 1;" ::"l"(&gs->wcnt[(k * NB + lane) * LS + (k ? 0 : cta >> 4)]) : "memory");
    }

    if (warp >= 8) {
        const int nw = warp - 8;
        bar_sync(4, 256 + 64 + 128);
        const int par = nw >> 2, wq = nw & 3;
        const uint32_t act_off = SM_ACT + (par * 2 + (lane >> 4)) * CH_PITCH + (2 + wq * 16 + (lane & 15)) * 16;
        const uint32_t stg_off = (par * 16 + (lane >> 4) * 8 + (lane & 7)) * 128 + (((2 * wq + ((lane >> 3) & 1)) ^ (lane & 7)) << 4);
        const uint32_t cfa = SM_COEF + par * 128 + (lane & 3) * 16;
        const uint32_t fbar = BAR(BAR_FULL) + 8 * par;
        uint4* inbox = gs->box + cta * 1024 + nw * 32 + lane;
#pragma unroll 1
        for (int i = -1; i < 4; i++) {
            if (i >= 0) mbar_wait(BAR(BAR_X) + 8 * i, 0);
            if (i == 0 && tid == 256) TL(92);
            const uint4 q = lds128(SM_XOWN + (i & 3) * 4096 + (tid - 256) * 16);
            float c[4] = {0.f, 0.f, 0.f, 0.f};
            stat_mma(c, q.x, q.y); stat_mma(c, q.z, q.w);
            stat_store(c, SM_RED + ((i & 3) * 8 + nw) * 48, lane);
            __syncwarp();
            if (i >= 0 && lane == 0) mbar_arrive(BAR(BAR_P) + 8 * i);
        }
#pragma unroll 1
        for (int conv = 0; conv < 2; conv++) {
            uint32_t u[4][4], w[4][4];
            float4 cf[8];
            if (conv == 0) {
#pragma unroll
                for (int i = 0; i < 4; i++) ldsm4t(u[i], SM_XOWN + stg_off + i * 4096);
            } else {
                mbar_wait(BAR(BAR_HW), 0);
#pragma unroll
                for (int i = 0; i < 4; i++) ldsm4(u[i], act_off + i * 2 * KC_BYTES);
            }
#pragma unroll
            for (int i = 0; i < 8; i++) cf[i] = lds128f(cfa + conv * 1024 + (i >> 1) * 256 + (i & 1) * 64);
            const uint32_t gst = SM_GST + conv * 32;
            float gv[8];
            read_stats(gst, gv);
            group_coefs<0>(gst, gv, cf);
            if (tid == 256) TL(22 + conv * 4);
            if (par) { const unsigned c1 = clock32(); while (clock32() - c1 < PDELAY) {} }
            norm_block<0, 1>(u, cf, act_off, ~0u, fbar, lane);
            if (tid == 256) TL(8 + conv * 8);
            group_coefs<1>(gst, gv, cf);
            norm_unit(u[1], cf[2], cf[3]);
            stsm4(act_off + 2 * KC_BYTES, u[1][0], u[1][1], u[1][2], u[1][3]);
            next_unit<2>(u, cf, gst, gv, act_off, fbar, lane);
            next_unit<3>(u, cf, gst, gv, act_off, fbar, lane);
            publish(fbar + 48, lane);
            if (tid == 256) TL(84 + conv);
            if (has_outer) {
                mbar_wait(BAR(BAR_X + 4), conv);
                if (conv == 0) {
#pragma unroll
                    for (int i = 0; i < 4; i++) ldsm4t(w[i], SM_XOUT + stg_off + i * 4096);
                } else {
#pragma unroll
                    for (int i = 0; i < 4; i++) {
                        const uint4 q = lds128(SM_XOWN + (tid - 256) * 16 + i * 4096);
                        w[i][0] = q.x; w[i][1] = q.y; w[i][2] = q.z; w[i][3] = q.w;
                    }
                    unsigned it = 0;
                    while (true) {
                        bool ok = true;
#pragma unroll
                        for (int i = 0; i < 16; i++) ok = ok && w[i >> 2][i & 3] != 0;
                        if (__all_sync(0xffffffffu, ok) || ++it > SPIN_LIMIT) break;
#pragma unroll
                        for (int i = 0; i < 4; i++) ld_unit(w[i], inbox + i * 256);
                    }
#pragma unroll
                    for (int i = 0; i < 16; i++) w[i >> 2][i & 3] = ~w[i >> 2][i & 3];
                }
            }
            if (conv == 0) {
                bar_sync(3, 256);
                if (nw == 0) sts128(SM_ACT + 2 * ROW_BYTES + (lane >> 1) * CH_PITCH + (lane & 1) * 16, make_uint4(0, 0, 0, 0));
            }
            if (tid == 256) TL(24 + conv * 4);
            norm_block<0, 2>(w, cf, act_off + 2 * ROW_BYTES, has_outer ? ~0u : 0u, fbar + 128, lane);
            if (tid == 256) TL(88 + conv);
            norm_block<2, 2>(w, cf, act_off + 2 * ROW_BYTES, has_outer ? ~0u : 0u, fbar + 128, lane);
            if (tid == 256) TL(23 + conv * 4);
        }
        if (has_outer) {
            mbar_wait(BAR(BAR_FULL + NSTAGE - 1), 1);
#pragma unroll
            for (int i = 0; i < 4; i++) inbox[i * 256] = make_uint4(0, 0, 0, 0);
        }
        {
            const int oc0 = (tid - 256) >> 3, seg = lane & 7;
            __nv_bfloat16* dst = out + ((size_t)(b * C + oc0) * HW + r) * HW + seg * 8;
            const uint32_t src = SM_XOWN + oc0 * 128 + ((seg ^ (oc0 & 7)) << 4);
            bar_sync(6, 128 + 256);
#pragma unroll
            for (int i = 0; i < 4; i++) *reinterpret_cast<uint4*>(dst + (size_t)i * 32 * HW * HW) = lds128(src + i * 4096);
            if (tid == 256) { TL(20); TLG(21); }
        }
    } else if (warp < 4) {
        const int wq = warp;
        bar_sync(2, 128);

        const uint32_t xbase = SM_XOWN + ((lane >> 4) * 8 + (lane & 7)) * 128 + (((2 * wq + ((lane >> 3) & 1)) ^ (lane & 7)) << 4);
        float d[64];
#pragma unroll
        for (int i = 0; i < 64; i++) d[i] = 0.f;
#pragma unroll 1
        for (int conv = 0; conv < 2; conv++) {
            fence_acc(d);
            mma_stages<0>(d, conv, tid, gs);
            if (conv == 0) {
                asm volatile("wgmma.fence.sync.aligned;" ::: "memory");
                wgmma128<(SM_ONES >> 4) | (8u << 16), (SM_EMB >> 4), 0, 8>(d);
                asm volatile("wgmma.commit_group.sync.aligned;" ::: "memory");
            }
            asm volatile("wgmma.wait_group.sync.aligned 0;" ::: "memory");
            fence_acc(d);
            if (tid == 0) TL(10 + conv * 8);
            uint32_t hp[32];
#pragma unroll
            for (int i = 0; i < 32; i++) hp[i] = pack_bf(d[2 * i], d[2 * i + 1]);
            if (conv == 1) {
#pragma unroll
                for (int kc = 0; kc < 8; kc++) stsm4t(xbase + kc * 2048, hp[4 * kc], hp[4 * kc + 1], hp[4 * kc + 2], hp[4 * kc + 3]);
                bar_arrive(6, 128 + 256);
                break;
            }
#pragma unroll
            for (int g = 0; g < 4; g++) {
                float c[4] = {0.f, 0.f, 0.f, 0.f};
#pragma unroll
                for (int i = 0; i < 4; i++) stat_mma(c, hp[8 * g + 2 * i], hp[8 * g + 2 * i + 1]);
                stat_store(c, SM_RED + (g * 4 + wq) * 48, lane);
            }
            bar_sync(2, 128);
            if (wq == 0) stat_publish(SM_RED, &gs->acc2[b * LS], lane, true);
            if (tid == 0) TL(11);
            const uint32_t hbase = SM_ACT + (lane >> 4) * CH_PITCH + (2 + wq * 16 + (lane & 15)) * 16;
#pragma unroll
            for (int kc = 0; kc < 8; kc++) stsm4(hbase + kc * 2 * CH_PITCH, hp[4 * kc], hp[4 * kc + 1], hp[4 * kc + 2], hp[4 * kc + 3]);
            __syncwarp();
            if (lane == 0) mbar_arrive(BAR(BAR_HW));
            if (lane < LAG) mbar_arrive(BAR(BAR_WEMPTY + (NSTAGE - LAG) % NS) + 8 * lane);
            if (has_outer) {
                uint4* outbox = gs->box + (cta + ((r & 1) ? 1 : -1)) * 1024 + tid;
#pragma unroll
                for (int kc = 0; kc < 8; kc++) outbox[kc * 128] = make_uint4(~hp[4 * kc], ~hp[4 * kc + 1], ~hp[4 * kc + 2], ~hp[4 * kc + 3]);
            }
            if (tid == 0) TL(12);
#pragma unroll
            for (int kc = 0; kc < 8; kc++) {
                uint32_t p[4];
                ldsm4t(p, xbase + kc * 2048);
#pragma unroll
                for (int i = 0; i < 4; i++) { d[8 * kc + 2 * i] = bf_lo(p[i]); d[8 * kc + 2 * i + 1] = bf_hi(p[i]); }
            }
            fence_async_smem();
            __syncwarp();
            if (lane == 0) mbar_arrive(BAR(BAR_XFREE));
        }
        {
        }
    } else if (warp < 6) {
        bar_sync(5, 96);
        if (warp == 5) {
            asm volatile("barrier.cluster.wait.acquire.aligned;" ::: "memory");
            const uint32_t peer = (r & 1) ^ 1;
            const uint32_t self0 = mapa(0, r & 1), peer0 = mapa(0, peer);
#pragma unroll 1
            for (int conv = 0; conv < 2; conv++) {
#pragma unroll 1
                for (int kc = 0; kc < 8; kc++) {
                    mbar_wait(BAR(BAR_FULL) + 8 * kc, conv);
                    if (elect_one())
                        asm volatile("cp.async.bulk.shared::cluster.shared::cta.mbarrier::complete_tx::bytes [%0], [%1], %2, [%3];"
                                     ::"r"(peer0 + SM_ACT + ROW_BYTES + kc * KC_BYTES), "r"(self0 + SM_ACT + kc * KC_BYTES), "r"(KC_BYTES),
                                       "r"(peer0 + BAR(BAR_FULL + 8) + 8 * kc) : "memory");
                }
                if (lane == 0) TL(86 + conv);
#pragma unroll 1
                for (int kc = 0; kc < 8; kc++) mbar_wait(BAR(BAR_FULL + 8) + 8 * kc, conv);
                if (lane == 0)
                    asm volatile("mbarrier.arrive.release.cluster.shared::cluster.b64 _, [%0];" ::"r"(peer0 + (conv ? BAR(BAR_ACK) : BAR(BAR_EMB))) : "memory");
            }
            mbar_wait(BAR(BAR_ACK), 0);
        } else {
            mbar_wait(BAR(BAR_STATS), 0);
            unsigned it = 0;
            while (ld_relaxed(&gs->wcnt[(2 * NB + b) * LS]) < (unsigned)NXTRA && ++it < SPIN_LIMIT) __nanosleep(100);
            fence_acquire();
            float ev[4] = {0.f, 0.f, 0.f, 0.f};
#pragma unroll
            for (int j = 0; j < NXTRA; j++) {
                const uint4 ef = ld_relaxed_v4(&gs->emb[(j * NB + b) * C + lane * 4]);
                ev[0] += __uint_as_float(ef.x); ev[1] += __uint_as_float(ef.y); ev[2] += __uint_as_float(ef.z); ev[3] += __uint_as_float(ef.w);
            }
#pragma unroll
            for (int i = 0; i < 4; i++) {
                const float hi = bf_lo(pack_bf(ev[i], 0.f));
                sts128(SM_EMB + (lane * 4 + i) * 16, make_uint4(pack_bf(hi, ev[i] - hi), 0, 0, 0));
            }
            fence_async_smem();
            __syncwarp();
            if (lane == 0) { mbar_arrive(BAR(BAR_EMB)); TL(19); }
        }
    } else if (warp == 6) {
        bar_sync(0, 96);
        const uint32_t ebytes = STAGE_BYTES + ((lane >> 3) == 1 ? KC_BYTES : 0);
        if (lane < NSTAGE) mbar_expect(BAR(BAR_FULL) + 8 * lane, ebytes);
        const int swap = (r & 1) ? 0 : 8 * STAGE_BYTES;
        unsigned it = 0;
        {
            int g = 0;
#pragma unroll 1
            while (g < NS) {
                unsigned ready = __ballot_sync(0xffffffffu, ld_relaxed(&gs->wcnt[b * LS + (lane & 7)]) >= 16u) >> g;
                if (++it > SPIN_LIMIT) ready = ~0u;
                if (!(ready & 1)) continue;
                fence_acquire();
                fence_async_global();
                if (lane == 0) TL(g ? 3 : 6);
#pragma unroll 1
                for (; (ready & 1) && g < NS; g++, ready >>= 1)
                    if (elect_one())
                        bulk_g2s(S0 + SM_W + g * STAGE_BYTES, gs->wt + g * STAGE_BYTES + (g >= 8 ? swap : 0), STAGE_BYTES, S0 + BAR(BAR_FULL) + 8 * g);
            }
        }
#pragma unroll 1
        for (int q = 3; q < 12; q++) {
            const int conv = q >= 6, qs = conv ? q - 6 : q, sl = q % 3;
            const unsigned char* wsrc = gs->wt + q * 4 * STAGE_BYTES + (qs < 2 ? 0 : (qs < 4 ? swap : -swap));
            const uint32_t par = (q / 3 - 1) & 1;
            if (q == 6) {
                it = 0;
                while (ld_relaxed(&gs->wcnt[(NB + b) * LS]) < (unsigned)NCTA && ++it < SPIN_LIMIT) {}
                fence_acquire();
                fence_async_global();
                if (lane == 0) { mbar_arrive(BAR(BAR_EMB)); TL(2); }
            }
#pragma unroll
            for (int i = 0; i < 4; i++) {
                mbar_wait(BAR(BAR_WEMPTY + i) + 32 * sl, par);
                if (i == 0 && (q == 6 || q == 9)) {
                    if ((lane >= NS) == (q == 9) && lane < NSTAGE) mbar_expect(BAR(BAR_FULL) + 8 * lane, ebytes);
                    __syncwarp();
                }
                if (elect_one())
                    bulk_g2s(S0 + SM_W + (sl * 4 + i) * STAGE_BYTES, wsrc + i * STAGE_BYTES, STAGE_BYTES, S0 + BAR(BAR_FULL + i) + 32 * qs);
            }
        }
    } else {
        const uint2 ga1 = __ldg(reinterpret_cast<const uint2*>(g1) + lane), bt1 = __ldg(reinterpret_cast<const uint2*>(be1) + lane);
        const uint2 ga2 = __ldg(reinterpret_cast<const uint2*>(g2) + lane), bt2 = __ldg(reinterpret_cast<const uint2*>(be2) + lane);
        if (lane < 8) sts128(SM_GST + lane * 16, make_uint4(0, 0, 0, 0));
        sts128f(SM_COEF + lane * 32, make_float4(0.5f * bf_lo(ga1.x), 0.5f * bf_hi(ga1.x), 0.5f * bf_lo(bt1.x), 0.5f * bf_hi(bt1.x)));
        sts128f(SM_COEF + lane * 32 + 16, make_float4(0.5f * bf_lo(ga1.y), 0.5f * bf_hi(ga1.y), 0.5f * bf_lo(bt1.y), 0.5f * bf_hi(bt1.y)));
        sts128f(SM_COEF + 1024 + lane * 32, make_float4(0.5f * bf_lo(ga2.x), 0.5f * bf_hi(ga2.x), 0.5f * bf_lo(bt2.x), 0.5f * bf_hi(bt2.x)));
        sts128f(SM_COEF + 1024 + lane * 32 + 16, make_float4(0.5f * bf_lo(ga2.y), 0.5f * bf_hi(ga2.y), 0.5f * bf_lo(bt2.y), 0.5f * bf_hi(bt2.y)));
        bar_arrive(4, 256 + 64 + 128);
        bar_sync(0, 96);
#pragma unroll 1
        for (int conv = 0; conv < 2; conv++) {
            if (conv == 1) {
                mbar_wait(BAR(BAR_HW), 0);
                const unsigned c1 = clock32();
                while (clock32() - c1 < PD2) {}
            } else {
                while (clock32() - clk0 < PD) {}
            }
            const float* asrc = conv ? &gs->acc2[b * LS + (lane & 3) * 4] : &gs->acc1[b * 4 * LS + (lane & 3) * GS1];
            unsigned it = 0;
            uint4 fq[NPOLL];
#pragma unroll
            for (int i = 0; i < NPOLL; i++) {
                fq[i] = ld_relaxed_v4(asrc);
                if (i + 1 < NPOLL) { const unsigned c1 = clock32(); while (clock32() - c1 < 450 / NPOLL) {} }
            }
            bool all = false;
#pragma unroll 1
            while (!all) {
#pragma unroll
                for (int i = 0; i < NPOLL; i++) {
                    const uint4 f = fq[i];
                    const bool ok = ((f.x == 0x42800000u) & (f.w == 0x42800000u)) || it > SPIN_LIMIT;
                    if (ok && lane < 4) {
                        const float inv_n = 1.0f / (32.0f * HW * HW);
                        const float mean = __uint_as_float(f.y) * inv_n;
                        const float rs = rsqrtf(fmaxf(fmaf(-mean, mean, __uint_as_float(f.z) * inv_n), 0.f) + 1e-5f);
                        asm volatile("st.shared.v2.f32 [%0], {%1,%2};" ::"r"(S0 + SM_GST + conv * 32 + lane * 8), "f"(rs == 0.f ? 1e-38f : rs), "f"(mean * rs) : "memory");
                    }
                    if (__all_sync(0xffffffffu, ok)) { all = true; break; }
                    fq[i] = ld_relaxed_v4(asrc);
                }
                it++;
            }
            if (lane == 0) { mbar_arrive(BAR(BAR_STATS)); TL(7 + conv * 8); }
        }
        mbar_wait(BAR(BAR_XFREE), 0);
        if (has_outer && elect_one()) {
            mbar_expect(BAR(BAR_X + 4), 16384);
            bulk_g2s(S0 + SM_XOWN, gs->box + cta * 1024, 16384, S0 + BAR(BAR_X + 4));
        }
        if (r == 0) {
            if (lane < 16) gs->acc1[b * 4 * LS + (lane >> 2) * GS1 + (lane & 3)] = 0.f;
            if (lane < 24) gs->wcnt[((lane >> 3) * NB + b) * LS + (lane & 7)] = 0;
        }
    }
}

}

extern "C" void kernel_launch(void* const* d_in, const int* in_sizes, int n_in, void* d_out, int out_size) {
    (void)in_sizes; (void)n_in; (void)out_size;
    typedef CUresult (*EncodeFn)(CUtensorMap*, CUtensorMapDataType, cuuint32_t, void*, const cuuint64_t*, const cuuint64_t*,
                                 const cuuint32_t*, const cuuint32_t*, CUtensorMapInterleave, CUtensorMapSwizzle,
                                 CUtensorMapL2promotion, CUtensorMapFloatOOBfill);
    static Scratch* gs = nullptr;
    static EncodeFn encode = nullptr;
    if (!gs) {
        cudaFuncSetAttribute(resblock_kernel, cudaFuncAttributeMaxDynamicSharedMemorySize, SM_TOTAL);
        cudaGetSymbolAddress((void**)&gs, g_scratch);
        cudaDriverEntryPointQueryResult qr;
        cudaGetDriverEntryPoint("cuTensorMapEncodeTiled", (void**)&encode, cudaEnableDefault, &qr);
    }
    CUtensorMap xmap;
    const cuuint64_t dims[3] = {HW, HW, NB * C}, strides[2] = {HW * 2, HW * HW * 2};
    const cuuint32_t box[3] = {HW, 1, 32}, es[3] = {1, 1, 1};
    encode(&xmap, CU_TENSOR_MAP_DATA_TYPE_BFLOAT16, 3, d_in[0], dims, strides, box, es, CU_TENSOR_MAP_INTERLEAVE_NONE,
           CU_TENSOR_MAP_SWIZZLE_128B, CU_TENSOR_MAP_L2_PROMOTION_NONE, CU_TENSOR_MAP_FLOAT_OOB_FILL_NONE);
    resblock_kernel<<<NCTA + NXTRA, NTHREADS, SM_TOTAL>>>(
        (const __nv_bfloat16*)d_in[4], (const __nv_bfloat16*)d_in[1],
        (const __nv_bfloat16*)d_in[2], (const __nv_bfloat16*)d_in[3], (const __nv_bfloat16*)d_in[5],
        (const __nv_bfloat16*)d_in[6], (const __nv_bfloat16*)d_in[7], (const __nv_bfloat16*)d_in[8],
        (__nv_bfloat16*)d_out, gs, xmap);
}
```

```cpp
#include <cuda_runtime.h>
#include <cuda.h>
#include <cuda_bf16.h>
#include <stdint.h>

namespace {

constexpr int C = 128, HW = 64, NB = 2, E = 768;
constexpr int NCTA = NB * HW;
constexpr int NXTRA = 4;
constexpr int NTHREADS = 16 * 32;
constexpr int CH_PITCH = 66 * 16;
constexpr int ROW_BYTES = 16 * CH_PITCH;
constexpr int STEP_BYTES = 4096;
constexpr int STAGE_BYTES = 3 * STEP_BYTES;
constexpr int NSTAGE = 24;
constexpr int KC_BYTES = 2 * CH_PITCH;
constexpr int NS = 12;
constexpr int LAG = 1;
#define XDELAY 400
#define HDELAY 600
#define SEQ 0
#define MMA0_WAIT mbar_try
#define SPINPAUSE
#define NPOLL 1
#define PD2 0
#define ODELAY 100
#define PDELAY 60
#define RB 1
#define XSTAG2 400
#define XSTAG 800
#define HSEND 0
#define W2DELAY 1800

constexpr uint32_t SMEM_BASE = 0x400;
constexpr uint32_t SM_XOWN = SMEM_BASE;
constexpr uint32_t SM_ACT = SM_XOWN + 16384 + 512;
constexpr uint32_t SM_XOUT = SM_ACT + 2 * ROW_BYTES + 512;
static_assert(SM_XOUT % 1024 == 0, "swizzle atom alignment");
constexpr uint32_t SM_W = SM_ACT + 3 * ROW_BYTES + 128;
__host__ __device__ constexpr uint32_t slot_addr(int slot) { return SM_W + slot * STAGE_BYTES; }
constexpr uint32_t SM_COEF = SM_W + NS * STAGE_BYTES;
constexpr uint32_t SM_GST = SM_COEF + 2048;
constexpr uint32_t SM_EMB = SM_GST + 128;
constexpr uint32_t SM_ONES = SM_EMB + 2048;
constexpr uint32_t SM_RED = SM_ONES + 256;
constexpr uint32_t SM_BNC = SM_RED + 1536;
constexpr uint32_t SM_BAR = SM_BNC + 2 * 2304;
constexpr int BAR_FULL = 0, BAR_WEMPTY = NSTAGE, BAR_HW = BAR_WEMPTY + NS, BAR_XFREE = BAR_HW + 1, BAR_STATS = BAR_XFREE + 1,
              BAR_EMB = BAR_STATS + 1, BAR_ACK = BAR_EMB + 1, BAR_X = BAR_ACK + 1  , NBAR = BAR_X + 5;
constexpr int SM_TOTAL = SM_BAR + NBAR * 8 - SMEM_BASE;
static_assert(SM_TOTAL <= 232448, "smem");
static_assert(NBAR <= 96, "barrier init");
__host__ __device__ constexpr uint32_t BAR(int i) { return SM_BAR + 8 * i; }
__host__ __device__ constexpr int ky_of(int kyo) { return kyo == 0 ? 1 : (kyo == 1 ? 0 : 2); }

constexpr unsigned SPIN_LIMIT = 1u << 16;

#define LS 1056
#define GS1 4
#define PD 0
struct Scratch {
    float acc1[NB * 4 * LS];
    float acc2[NB * LS];
    unsigned wcnt[3 * NB * LS];
    float emb[NXTRA * NB * C];
    unsigned char wt[2 * NSTAGE * STAGE_BYTES];
    uint4 box[NCTA * 1024];
};
__device__ __align__(1024) Scratch g_scratch;
#define TL(i) do {} while (0)
#define TLG(i) do {} while (0)

__device__ __forceinline__ unsigned clock32() { unsigned c; asm volatile("mov.u32 %0, %%clock;" : "=r"(c)); return c; }
__device__ __forceinline__ uint32_t mapa(uint32_t a, uint32_t rank) {
    uint32_t d;
    asm("mapa.shared::cluster.u32 %0, %1, %2;" : "=r"(d) : "r"(a), "r"(rank));
    return d;
}
#define S0 mapa(0, blockIdx.x & 1)
__device__ __forceinline__ void mbar_init(uint32_t bar, int cnt) {
    asm volatile("mbarrier.init.shared::cta.b64 [%0], %1;" ::"r"(bar + S0), "r"(cnt) : "memory");
}
__device__ __forceinline__ void mbar_arrive(uint32_t bar) {
    asm volatile("mbarrier.arrive.shared::cta.b64 _, [%0];" ::"r"(bar + S0) : "memory");
}
__device__ __forceinline__ void mbar_expect(uint32_t bar, uint32_t bytes) {
    asm volatile("mbarrier.arrive.expect_tx.shared::cta.b64 _, [%0], %1;" ::"r"(bar + S0), "r"(bytes) : "memory");
}
__device__ __forceinline__ bool mbar_try(uint32_t bar, uint32_t par) {
    uint32_t ok;
    asm volatile("{\n.reg .pred p;\nmbarrier.try_wait.parity.shared::cta.b64 p, [%1], %2;\nselp.u32 %0, 1, 0, p;\n}"
                 : "=r"(ok) : "r"(bar + S0), "r"(par) : "memory");
    return ok;
}
__device__ __forceinline__ bool mbar_test(uint32_t bar, uint32_t par) {
    uint32_t ok;
    asm volatile("{\n.reg .pred p;\nmbarrier.test_wait.parity.shared::cta.b64 p, [%1], %2;\nselp.u32 %0, 1, 0, p;\n}"
                 : "=r"(ok) : "r"(bar + S0), "r"(par) : "memory");
    return ok;
}
__device__ __forceinline__ void mbar_wait(uint32_t bar, uint32_t par) {
    unsigned it = 0;
#pragma unroll 1
    while (!mbar_try(bar, par) && ++it < SPIN_LIMIT) {}
}
__device__ __forceinline__ bool elect_one() {
    uint32_t p;
    asm volatile("{\n.reg .pred p;\nelect.sync _|p, 0xffffffff;\nselp.u32 %0, 1, 0, p;\n}" : "=r"(p));
    return p;
}
__device__ __forceinline__ void fence_async_smem() { asm volatile("fence.proxy.async.shared::cta;" ::: "memory"); }
__device__ __forceinline__ void fence_async_global() { asm volatile("fence.proxy.async.global;" ::: "memory"); }
__device__ __forceinline__ void fence_acquire() { asm volatile("fence.acquire.gpu;" ::: "memory"); }
__device__ __forceinline__ void bar_sync(int id, int n) { asm volatile("bar.sync %0, %1;" ::"r"(id), "r"(n) : "memory"); }
__device__ __forceinline__ void bar_arrive(int id, int n) { asm volatile("bar.arrive %0, %1;" ::"r"(id), "r"(n) : "memory"); }
__device__ __forceinline__ void bulk_g2s(uint32_t dst, const void* src, uint32_t bytes, uint32_t bar) {
    asm volatile("cp.async.bulk.shared::cluster.global.mbarrier::complete_tx::bytes [%0], [%1], %2, [%3];"
                 ::"r"(dst), "l"(src), "r"(bytes), "r"(bar) : "memory");
}
__device__ __forceinline__ void tma_x(uint32_t dst, const CUtensorMap* tm, int row, int ch, uint32_t bar) {
    asm volatile("cp.async.bulk.tensor.3d.shared::cluster.global.mbarrier::complete_tx::bytes [%0], [%1, {%2, %3, %4}], [%5];"
                 ::"r"(dst + S0), "l"(tm), "r"(0), "r"(row), "r"(ch), "r"(bar + S0) : "memory");
}
__device__ __forceinline__ uint4 ld_relaxed_v4(const void* p) {
    uint4 v;
    asm volatile("ld.relaxed.gpu.global.v4.u32 {%0,%1,%2,%3}, [%4];" : "=r"(v.x), "=r"(v.y), "=r"(v.z), "=r"(v.w) : "l"(p) : "memory");
    return v;
}
__device__ __forceinline__ unsigned ld_relaxed(const void* p) {
    unsigned v;
    asm volatile("ld.relaxed.gpu.global.u32 %0, [%1];" : "=r"(v) : "l"(p) : "memory");
    return v;
}
__device__ __forceinline__ void red_add4(float* p, float a, float b, float c, float d) {
    asm volatile("red.relaxed.gpu.global.add.v4.f32 [%0], {%1,%2,%3,%4};" ::"l"(p), "f"(a), "f"(b), "f"(c), "f"(d) : "memory");
}
__device__ __forceinline__ void sts128(uint32_t a, uint4 v) {
    asm volatile("st.shared.v4.u32 [%0], {%1,%2,%3,%4};" ::"r"(a + S0), "r"(v.x), "r"(v.y), "r"(v.z), "r"(v.w) : "memory");
}
__device__ __forceinline__ void sts128f(uint32_t a, float4 v) {
    asm volatile("st.shared.v4.f32 [%0], {%1,%2,%3,%4};" ::"r"(a + S0), "f"(v.x), "f"(v.y), "f"(v.z), "f"(v.w) : "memory");
}
__device__ __forceinline__ void sts32f(uint32_t a, float v) { asm volatile("st.shared.f32 [%0], %1;" ::"r"(a + S0), "f"(v) : "memory"); }
__device__ __forceinline__ uint4 lds128(uint32_t a) {
    uint4 v;
    asm volatile("ld.shared.v4.u32 {%0,%1,%2,%3}, [%4];" : "=r"(v.x), "=r"(v.y), "=r"(v.z), "=r"(v.w) : "r"(a + S0) : "memory");
    return v;
}
__device__ __forceinline__ float4 lds128f(uint32_t a) {
    float4 v;
    asm volatile("ld.shared.v4.f32 {%0,%1,%2,%3}, [%4];" : "=f"(v.x), "=f"(v.y), "=f"(v.z), "=f"(v.w) : "r"(a + S0) : "memory");
    return v;
}
__device__ __forceinline__ float2 lds64f(uint32_t a) {
    float2 v;
    asm volatile("ld.shared.v2.f32 {%0,%1}, [%2];" : "=f"(v.x), "=f"(v.y) : "r"(a + S0) : "memory");
    return v;
}
__device__ __forceinline__ float bf_lo(uint32_t u) { return __uint_as_float(u << 16); }
__device__ __forceinline__ float bf_hi(uint32_t u) { return __uint_as_float(u & 0xffff0000u); }
__device__ __forceinline__ uint32_t pack_bf(float lo, float hi) {
    uint32_t r;
    asm("cvt.rn.bf16x2.f32 %0, %1, %2;" : "=r"(r) : "f"(hi), "f"(lo));
    return r;
}
__device__ __forceinline__ float tanh_fast(float x) {
    float r;
    asm("tanh.approx.f32 %0, %1;" : "=f"(r) : "f"(x));
    return r;
}
__device__ __forceinline__ float silu_half(float h) { return fmaf(h, tanh_fast(h), h); }
__device__ __forceinline__ void ldsm4(uint32_t (&u)[4], uint32_t a) {
    asm volatile("ldmatrix.sync.aligned.m8n8.x4.shared.b16 {%0,%1,%2,%3}, [%4];"
                 : "=r"(u[0]), "=r"(u[1]), "=r"(u[2]), "=r"(u[3]) : "r"(a + S0) : "memory");
}
__device__ __forceinline__ void ldsm4t(uint32_t (&u)[4], uint32_t a) {
    asm volatile("ldmatrix.sync.aligned.m8n8.x4.trans.shared.b16 {%0,%1,%2,%3}, [%4];"
                 : "=r"(u[0]), "=r"(u[1]), "=r"(u[2]), "=r"(u[3]) : "r"(a + S0) : "memory");
}
__device__ __forceinline__ void stsm4(uint32_t a, uint32_t p0, uint32_t p1, uint32_t p2, uint32_t p3) {
    asm volatile("stmatrix.sync.aligned.m8n8.x4.shared.b16 [%0], {%1,%2,%3,%4};" ::"r"(a + S0), "r"(p0), "r"(p1), "r"(p2), "r"(p3) : "memory");
}
__device__ __forceinline__ void stsm4t(uint32_t a, uint32_t p0, uint32_t p1, uint32_t p2, uint32_t p3) {
    asm volatile("stmatrix.sync.aligned.m8n8.x4.trans.shared.b16 [%0], {%1,%2,%3,%4};" ::"r"(a + S0), "r"(p0), "r"(p1), "r"(p2), "r"(p3) : "memory");
}

#define R8(o) "+f"(d[o]), "+f"(d[o + 1]), "+f"(d[o + 2]), "+f"(d[o + 3]), "+f"(d[o + 4]), "+f"(d[o + 5]), "+f"(d[o + 6]), "+f"(d[o + 7])
template <uint32_t ALO, uint32_t BLO, uint64_t AHI = 8, uint64_t BHI = 48>
__device__ __forceinline__ void wgmma128(float (&d)[64]) {
    asm volatile(
        "wgmma.mma_async.sync.aligned.m64n128k16.f32.bf16.bf16 "
        "{%0,%1,%2,%3,%4,%5,%6,%7,%8,%9,%10,%11,%12,%13,%14,%15,%16,%17,%18,%19,%20,%21,%22,%23,%24,%25,%26,%27,%28,%29,%30,%31,"
        "%32,%33,%34,%35,%36,%37,%38,%39,%40,%41,%42,%43,%44,%45,%46,%47,%48,%49,%50,%51,%52,%53,%54,%55,%56,%57,%58,%59,%60,%61,%62,%63},"
        " %64, %65, 1, 1, 1, 0, 0;"
        : R8(0), R8(8), R8(16), R8(24), R8(32), R8(40), R8(48), R8(56)
        : "l"((AHI << 32) | ALO), "l"((BHI << 32) | BLO));
}
template <int S>
__device__ __forceinline__ void mma_stages(float (&d)[64], int conv, int tid, Scratch* gs) {
    constexpr uint32_t A = ((SM_ACT + S * 2 * CH_PITCH + 16) >> 4) | ((CH_PITCH >> 4) << 16);
    constexpr uint32_t B = (slot_addr(S % NS) >> 4) | (8u << 16);
    if (S == 0) {
        unsigned it = 0;
#pragma unroll 1
        while (!MMA0_WAIT(BAR(BAR_FULL), conv) && ++it < SPIN_LIMIT) {}
    }
    bool next_ok = true;
    constexpr uint32_t NEXT = S + 1 < NSTAGE ? BAR(BAR_FULL + S + 1) : BAR(BAR_EMB);
    const int npar = S + 1 < NSTAGE ? conv : 0;
    next_ok = mbar_test(NEXT, npar);
    if (S == 0 && tid == 0) TL(32 + conv * 24);
    asm volatile("wgmma.fence.sync.aligned;" ::: "memory");
    wgmma128<A, B>(d);
    wgmma128<A + 1, B + 16>(d);
    wgmma128<A + 2, B + 32>(d);
    asm volatile("wgmma.commit_group.sync.aligned;" ::: "memory");
    if (S >= LAG) {
        asm volatile("wgmma.wait_group.sync.aligned %0;" ::"n"(LAG) : "memory");
        if ((tid & 31) == 0) mbar_arrive(BAR(BAR_WEMPTY + (S + NS - LAG) % NS));
    }
    if (!next_ok) mbar_wait(NEXT, npar);
    if constexpr (S + 1 < NSTAGE) mma_stages<S + 1>(d, conv, tid, gs);
}

__device__ __forceinline__ void weight_load(uint4 (&t)[5], const __nv_bfloat16* w, int cta, int lane) {
    const char* base = reinterpret_cast<const char*>(w) + ((cta & 15) * 8 * C + (cta >> 4) * 16) * 18;
#pragma unroll
    for (int k = 0; k < 5; k++) {
        const int i = lane + 32 * k, row = (i * 57) >> 10;
        if (k < 4 || lane < 16) t[k] = __ldg(reinterpret_cast<const uint4*>(base + row * (C * 18 - 288) + i * 16));
    }
}
__device__ __forceinline__ void weight_block(uint32_t bounce, unsigned char* wt, int cta, int lane, bool readback, Scratch* gs) {
    unsigned char* dst = wt + (cta >> 4) * STAGE_BYTES + (cta & 15) * 768;
    if (lane < 16) {
        uint32_t v[36];
#pragma unroll
        for (int i = 0; i < 9; i++) {
            const uint4 q = lds128(bounce + (lane & 7) * 288 + (lane >> 3) * 144 + i * 16);
            v[4 * i] = q.x; v[4 * i + 1] = q.y; v[4 * i + 2] = q.z; v[4 * i + 3] = q.w;
        }
#pragma unroll
        for (int kyo = 0; kyo < 3; kyo++) {
#pragma unroll
            for (int kx = 0; kx < 3; kx++) {
                const int tap = ky_of(kyo) * 3 + kx;
                uint32_t o[4];
#pragma unroll
                for (int m = 0; m < 4; m++) {
                    const int i0 = 18 * m + tap, i1 = i0 + 9;
                    const uint32_t sel = ((i0 & 1) ? 0x32u : 0x10u) | ((i1 & 1) ? 0x7600u : 0x5400u);
                    o[m] = __byte_perm(v[i0 >> 1], v[i1 >> 1], sel);
                }
                *reinterpret_cast<uint4*>(dst + kyo * 8 * STAGE_BYTES + kx * 256 + lane * 16) = make_uint4(o[0], o[1], o[2], o[3]);
            }
        }
    }
    if (readback) {
        __syncwarp();
        unsigned acc = 0;
        if (lane < 24) {
#pragma unroll
            for (int i = 0; i < 3; i++) acc |= ld_relaxed(dst + i * 8 * STAGE_BYTES + lane * 32);
        }
        asm volatile("{\n.reg .pred p;\nsetp.eq.u32 p, %0, 0x9e3779b9;\n@p st.shared.u32 [%1], %0;\n}" ::"r"(acc), "r"(bounce + S0) : "memory");
    }
}
__device__ __forceinline__ uint32_t act2(uint32_t u, const float4& cf) {
    return pack_bf(silu_half(fmaf(bf_lo(u), cf.x, cf.z)), silu_half(fmaf(bf_hi(u), cf.y, cf.w)));
}
__device__ __forceinline__ void norm_unit(uint32_t (&u)[4], const float4& ca, const float4& cb) {
    u[0] = act2(u[0], ca); u[1] = act2(u[1], ca); u[2] = act2(u[2], cb); u[3] = act2(u[3], cb);
}
__device__ __forceinline__ void read_stats(uint32_t gst, float (&g)[8]) {
    asm volatile("ld.volatile.shared.v4.f32 {%0,%1,%2,%3}, [%4];" : "=f"(g[0]), "=f"(g[1]), "=f"(g[2]), "=f"(g[3]) : "r"(gst + S0) : "memory");
    asm volatile("ld.volatile.shared.v4.f32 {%0,%1,%2,%3}, [%4];" : "=f"(g[4]), "=f"(g[5]), "=f"(g[6]), "=f"(g[7]) : "r"(gst + 16 + S0) : "memory");
}
template <int T>
__device__ __forceinline__ void group_coefs(uint32_t gst, float (&g)[8], float4 (&cf)[8]) {
    unsigned it = 0;
    if (!__all_sync(0xffffffffu, g[2 * T] != 0.f)) {
        float rs0;
#pragma unroll 1
        do {
            SPINPAUSE;
            asm volatile("ld.volatile.shared.f32 %0, [%1];" : "=f"(rs0) : "r"(gst + 8 * T + S0) : "memory");
        } while (!__all_sync(0xffffffffu, rs0 != 0.f) && ++it < 8 * SPIN_LIMIT);
        read_stats(gst, g);
    }
    float4 &ca = cf[2 * T], &cb = cf[2 * T + 1];
    const float rs = g[2 * T], mr = g[2 * T + 1];
    ca.z = fmaf(-mr, ca.x, ca.z); ca.w = fmaf(-mr, ca.y, ca.w); ca.x *= rs; ca.y *= rs;
    cb.z = fmaf(-mr, cb.x, cb.z); cb.w = fmaf(-mr, cb.y, cb.w); cb.x *= rs; cb.y *= rs;
}
template <int FIRST, int N>
__device__ __forceinline__ void norm_block(uint32_t (&u)[4][4], float4 (&cf)[8], uint32_t act, uint32_t mask, uint32_t fbar, int lane) {
#pragma unroll
    for (int t = FIRST; t < FIRST + N; t++) {
        norm_unit(u[t], cf[2 * t], cf[2 * t + 1]);
        stsm4(act + t * 2 * KC_BYTES, u[t][0] & mask, u[t][1] & mask, u[t][2] & mask, u[t][3] & mask);
    }
    fence_async_smem();
    __syncwarp();
    if (lane < N) mbar_arrive(fbar + 16 * (FIRST + lane));
}
__device__ __forceinline__ void publish(uint32_t bar, int lane) {
    fence_async_smem();
    __syncwarp();
    if (lane == 0) mbar_arrive(bar);
}
template <int T>
__device__ __forceinline__ void next_unit(uint32_t (&u)[4][4], float4 (&cf)[8], uint32_t gst, float (&g)[8], uint32_t act, uint32_t fbar, int lane) {
    const bool have = __all_sync(0xffffffffu, g[2 * T] != 0.f);
    if (!have) publish(fbar + 16 * (T - 1), lane);
    group_coefs<T>(gst, g, cf);
    norm_unit(u[T], cf[2 * T], cf[2 * T + 1]);
    if (have) publish(fbar + 16 * (T - 1), lane);
    stsm4(act + T * 2 * KC_BYTES, u[T][0], u[T][1], u[T][2], u[T][3]);
}
__device__ __forceinline__ void stat_mma(float (&c)[4], uint32_t p, uint32_t q) {
    asm("mma.sync.aligned.m16n8k16.row.col.f32.bf16.bf16.f32 {%0,%1,%2,%3}, {%4,%5,%6,%5}, {%4,%6}, {%0,%1,%2,%3};"
        : "+f"(c[0]), "+f"(c[1]), "+f"(c[2]), "+f"(c[3]) : "r"(p), "r"(0x3f803f80u), "r"(q));
}
__device__ __forceinline__ void stat_store(const float (&c)[4], uint32_t dst, int lane) {
    const int g = lane >> 2, t = lane & 3;
    if (t == (g >> 1)) sts32f(dst + g * 4, (g & 1) ? c[1] : c[0]);
    if (g == 7) sts32f(dst + 32 + t * 4, c[2] + c[3]);
}
__device__ __forceinline__ float sum4(float4 v) { return (v.x + v.y) + (v.z + v.w); }
__device__ __forceinline__ void stat_publish(uint32_t src, float* acc, int lane, bool real) {
    const uint32_t a = src + (lane & 15) * 48;
    float q = sum4(lds128f(a)) + sum4(lds128f(a + 16)), sm = sum4(lds128f(a + 32));
    q += __shfl_xor_sync(0xffffffffu, q, 1); sm += __shfl_xor_sync(0xffffffffu, sm, 1);
    q += __shfl_xor_sync(0xffffffffu, q, 2); sm += __shfl_xor_sync(0xffffffffu, sm, 2);
    if (real && (lane & 19) == 0) red_add4(acc + lane, 1.f, sm, q, 1.f);
}
__device__ __forceinline__ void fence_acc(float (&d)[64]) {
#pragma unroll
    for (int i = 0; i < 64; i++) asm volatile("" : "+f"(d[i])::"memory");
}
__device__ __forceinline__ void ld_unit(uint32_t (&u)[4], const uint4* p) {
    asm volatile("ld.relaxed.gpu.global.v4.u32 {%0,%1,%2,%3}, [%4];" : "=r"(u[0]), "=r"(u[1]), "=r"(u[2]), "=r"(u[3]) : "l"(p) : "memory");
}

__device__ __noinline__ void side_jobs(const __nv_bfloat16* __restrict__ t_emb, const __nv_bfloat16* __restrict__ w_emb,
                                       const __nv_bfloat16* __restrict__ w2, Scratch* __restrict__ gs, unsigned clk0) {
    const int tid = threadIdx.x, warp = tid >> 5, lane = tid & 31, j = blockIdx.x;
    float tv = 0.f;
    if (lane < 24) tv = __bfloat162float(t_emb[(lane / 12) * E + j * 192 + warp * 12 + lane % 12]);
    if (tid == 0) {
        mbar_init(BAR(0), 1);
        mbar_expect(BAR(0), 192 * C * 2);
        fence_async_smem();
        while (clock32() - clk0 < W2DELAY) {}
#pragma unroll
        for (int i = 0; i < 4; i++) bulk_g2s(S0 + SM_W + i * 12288, w_emb + (j * 192 + i * 48) * C, 12288, S0 + BAR(0));
    }
    if (j == 0 && tid < 32) gs->acc2[(tid >> 4) * LS + (tid & 15)] = 0.f;
    const float sv = silu_half(0.5f * tv);
    __syncthreads();
    mbar_wait(BAR(0), 0);
    float acc[8] = {0.f, 0.f, 0.f, 0.f, 0.f, 0.f, 0.f, 0.f};
#pragma unroll
    for (int i = 0; i < 12; i++) {
        const float2 wq = lds64f(SM_W + (warp * 12 + i) * 256 + lane * 8);
        const uint32_t wx = __float_as_uint(wq.x), wy = __float_as_uint(wq.y);
#pragma unroll
        for (int bb = 0; bb < 2; bb++) {
            const float sx = __shfl_sync(0xffffffffu, sv, bb * 12 + i);
            acc[4 * bb + 0] = fmaf(sx, bf_lo(wx), acc[4 * bb + 0]); acc[4 * bb + 1] = fmaf(sx, bf_hi(wx), acc[4 * bb + 1]);
            acc[4 * bb + 2] = fmaf(sx, bf_lo(wy), acc[4 * bb + 2]); acc[4 * bb + 3] = fmaf(sx, bf_hi(wy), acc[4 * bb + 3]);
        }
    }
    sts128f(SM_ACT + warp * 1024 + lane * 16, make_float4(acc[0], acc[1], acc[2], acc[3]));
    sts128f(SM_ACT + warp * 1024 + 512 + lane * 16, make_float4(acc[4], acc[5], acc[6], acc[7]));
    __syncthreads();
    if (tid < 128) {
        float2 sum = make_float2(0.f, 0.f);
#pragma unroll
        for (int w = 0; w < 16; w++) { const float2 p = lds64f(SM_ACT + w * 1024 + tid * 8); sum.x += p.x; sum.y += p.y; }
        *reinterpret_cast<float2*>(&gs->emb[j * NB * C + tid * 2]) = sum;
        bar_sync(1, 128);
        if (tid < 2) asm volatile("red.release.gpu.global.add.u32 [%0], 1;" ::"l"(&gs->wcnt[(2 * NB + tid) * LS]) : "memory");
    }
}

__global__ void __cluster_dims__(2, 1, 1) __launch_bounds__(NTHREADS, 1)
resblock_kernel(const __nv_bfloat16* __restrict__ w1,
                const __nv_bfloat16* __restrict__ t_emb, const __nv_bfloat16* __restrict__ g1,
                const __nv_bfloat16* __restrict__ be1, const __nv_bfloat16* __restrict__ w_emb,
                const __nv_bfloat16* __restrict__ g2, const __nv_bfloat16* __restrict__ be2,
                const __nv_bfloat16* __restrict__ w2, __nv_bfloat16* __restrict__ out, Scratch* __restrict__ gs,
                const __grid_constant__ CUtensorMap xmap) {
    const unsigned clk0 = clock32();
    if (threadIdx.x == 480 && blockIdx.x >= NXTRA) TLG(1);
    const int tid = threadIdx.x, lane = tid & 31;
    const int cta = blockIdx.x - NXTRA, b = cta >> 6, r = cta & 63;
    uint4 v[5];
    if (tid < 32) weight_load(v, w1, cta & (NCTA - 1), lane);
    const int warp = __shfl_sync(0xffffffffu, tid >> 5, 0);
    if (cta < 0) { side_jobs(t_emb, w_emb, w2, gs, clk0); return; }

    if (warp != 3) asm volatile("barrier.cluster.arrive.relaxed.aligned;" ::: "memory");
    const bool has_outer = (r != 0) && (r != HW - 1);
    if (warp >= 8) {
        const int g = (warp - 8) >> 1, hf = warp & 1;
        if (hf == 0 && elect_one()) {
            asm volatile("prefetch.tensormap [%0];" ::"l"(&xmap) : "memory");
            mbar_init(BAR(BAR_X) + 8 * g, 1);
            mbar_expect(BAR(BAR_X) + 8 * g, 4096);
            fence_async_smem();
            while (clock32() - clk0 < XDELAY + (g >> 1) * XSTAG + (g & 1) * XSTAG2) {}
            tma_x(SM_XOWN + g * 4096, &xmap, r, b * C + g * 32, BAR(BAR_X) + 8 * g);
        }
        bar_sync(8 + g, 64);
        mbar_wait(BAR(BAR_X) + 8 * g, 0);
        if (hf == 0 && lane == 0) TL(70 + g);
        float c[4][4];
#pragma unroll
        for (int k = 0; k < 4; k++) {
            const uint4 q = lds128(SM_XOWN + (warp - 8) * 2048 + k * 512 + lane * 16);
            c[k][0] = c[k][1] = c[k][2] = c[k][3] = 0.f;
            stat_mma(c[k], q.x, q.y); stat_mma(c[k], q.z, q.w);
        }
#pragma unroll
        for (int i = 0; i < 4; i++) c[0][i] = (c[0][i] + c[1][i]) + (c[2][i] + c[3][i]);
        stat_store(c[0], SM_RED + (warp - 8) * 48, lane);
        bar_sync(8 + g, 64);
        if (hf == 0 && lane == 0) {
            const uint32_t a = SM_RED + g * 96;
            red_add4(&gs->acc1[b * 4 * LS + g * GS1], 1.f, sum4(lds128f(a + 32)) + sum4(lds128f(a + 80)),
                     (sum4(lds128f(a)) + sum4(lds128f(a + 16))) + (sum4(lds128f(a + 48)) + sum4(lds128f(a + 64))), 1.f);
            TL(74 + g);
        }
    }
    if (warp == 3) {
            if (elect_one()) {
#pragma unroll
                for (int i = 0; i < NSTAGE; i++) mbar_init(BAR(BAR_FULL + i), (i >> 3) == 1 ? 1 : 5);
#pragma unroll
                for (int i = 0; i < NS + 2; i++) mbar_init(BAR(BAR_WEMPTY + i), 4);
#pragma unroll
                for (int i = BAR_STATS; i < BAR_X; i++) mbar_init(BAR(i), i == BAR_EMB ? 3 : 1);
                mbar_init(BAR(BAR_X + 4), 1);
                asm volatile("fence.mbarrier_init.release.cluster;" ::: "memory");
            }
            __syncwarp();
            fence_async_smem();
            bar_arrive(0, 96);
            bar_arrive(5, 96);
            bar_arrive(4, 256 + 64);
            const uint4 z = make_uint4(0, 0, 0, 0);
#pragma unroll
            for (int i = 0; i < 2; i++) sts128(SM_ACT + (i * 16 + (lane >> 1)) * CH_PITCH + (lane & 1) * 16, z);
            if (lane < 4) sts128(SM_ACT + (2 + (lane >> 1)) * ROW_BYTES + (lane & 1) * 16, z);
            if (lane < 16) sts128(SM_ONES + lane * 16, make_uint4(lane < 8 ? 0x3f803f80u : 0u, 0, 0, 0));
            fence_async_smem();
            asm volatile("barrier.cluster.arrive.relaxed.aligned;" ::: "memory");
            if (lane == 0) TL(5);
            while (clock32() - clk0 < W2DELAY) {}
            weight_load(v, w2, cta, lane);
        }
    if (warp == 0 || warp == 3) {
        const int k = warp & 1;
#pragma unroll
        for (int i = 0; i < 5; i++)
            if (i < 4 || lane < 16) sts128(SM_BNC + k * 2304 + (lane + 32 * i) * 16, v[i]);
        if (lane == 0) TL(k ? 14 : 81);
        __syncwarp();
        weight_block(SM_BNC + k * 2304, gs->wt + k * NSTAGE * STAGE_BYTES, cta, lane, true, gs);
        __syncwarp();
        if (lane == 0) TL(k ? 13 : 4);
        if (lane < 2) asm volatile("red.relaxed.gpu.global.add.u32 [%0], 1;" ::"l"(&gs->wcnt[(k * NB + lane) * LS + (k ? 0 : cta >> 4)]) : "memory");
    }

    if (warp >= 8) {
        const int nw = warp - 8;
        bar_sync(4, 256 + 64);
        const int par = nw >> 2, wq = nw & 3;
        const uint32_t act_off = SM_ACT + (par * 2 + (lane >> 4)) * CH_PITCH + (2 + wq * 16 + (lane & 15)) * 16;
        const uint32_t stg_off = (par * 16 + (lane >> 4) * 8 + (lane & 7)) * 128 + (((2 * wq + ((lane >> 3) & 1)) ^ (lane & 7)) << 4);
        const uint32_t cfa = SM_COEF + par * 128 + (lane & 3) * 16;
        const uint32_t fbar = BAR(BAR_FULL) + 8 * par;
        uint4* inbox = gs->box + cta * 1024 + nw * 32 + lane;
#pragma unroll 1
        for (int conv = 0; conv < 2; conv++) {
            uint32_t u[4][4], w[4][4];
            float4 cf[8];
            if (conv == 0) {
#pragma unroll
                for (int i = 0; i < 4; i++) ldsm4t(u[i], SM_XOWN + stg_off + i * 4096);
            } else {
                mbar_wait(BAR(BAR_HW), 0);
#pragma unroll
                for (int i = 0; i < 4; i++) ldsm4(u[i], act_off + i * 2 * KC_BYTES);
            }
#pragma unroll
            for (int i = 0; i < 8; i++) cf[i] = lds128f(cfa + conv * 1024 + (i >> 1) * 256 + (i & 1) * 64);
            const uint32_t gst = SM_GST + conv * 32;
            float gv[8];
            read_stats(gst, gv);
            group_coefs<0>(gst, gv, cf);
            if (tid == 256) TL(22 + conv * 4);
            if (par) { const unsigned c1 = clock32(); while (clock32() - c1 < PDELAY) {} }
            norm_block<0, 1>(u, cf, act_off, ~0u, fbar, lane);
            if (tid == 256) TL(8 + conv * 8);
            group_coefs<1>(gst, gv, cf);
            norm_unit(u[1], cf[2], cf[3]);
            stsm4(act_off + 2 * KC_BYTES, u[1][0], u[1][1], u[1][2], u[1][3]);
            next_unit<2>(u, cf, gst, gv, act_off, fbar, lane);
            next_unit<3>(u, cf, gst, gv, act_off, fbar, lane);
            publish(fbar + 48, lane);
            if (tid == 256) TL(84 + conv);
            if (has_outer) {
                mbar_wait(BAR(BAR_X + 4), conv);
                if (conv == 0) {
#pragma unroll
                    for (int i = 0; i < 4; i++) ldsm4t(w[i], SM_XOUT + stg_off + i * 4096);
                } else {
#pragma unroll
                    for (int i = 0; i < 4; i++) {
                        const uint4 q = lds128(SM_XOWN + (tid - 256) * 16 + i * 4096);
                        w[i][0] = q.x; w[i][1] = q.y; w[i][2] = q.z; w[i][3] = q.w;
                    }
                    unsigned it = 0;
                    while (true) {
                        bool ok = true;
#pragma unroll
                        for (int i = 0; i < 16; i++) ok = ok && w[i >> 2][i & 3] != 0;
                        if (__all_sync(0xffffffffu, ok) || ++it > SPIN_LIMIT) break;
#pragma unroll
                        for (int i = 0; i < 4; i++) ld_unit(w[i], inbox + i * 256);
                    }
#pragma unroll
                    for (int i = 0; i < 16; i++) w[i >> 2][i & 3] = ~w[i >> 2][i & 3];
                }
            }
            if (conv == 0) {
                bar_sync(3, 256);
                if (nw == 0) sts128(SM_ACT + 2 * ROW_BYTES + (lane >> 1) * CH_PITCH + (lane & 1) * 16, make_uint4(0, 0, 0, 0));
            }
            if (tid == 256) TL(24 + conv * 4);
            norm_block<0, 2>(w, cf, act_off + 2 * ROW_BYTES, has_outer ? ~0u : 0u, fbar + 128, lane);
            if (tid == 256) TL(88 + conv);
            norm_block<2, 2>(w, cf, act_off + 2 * ROW_BYTES, has_outer ? ~0u : 0u, fbar + 128, lane);
            if (tid == 256) TL(23 + conv * 4);
        }
        if (has_outer) {
            mbar_wait(BAR(BAR_FULL + NSTAGE - 1), 1);
#pragma unroll
            for (int i = 0; i < 4; i++) inbox[i * 256] = make_uint4(0, 0, 0, 0);
        }
        {
            const int oc0 = (tid - 256) >> 3, seg = lane & 7;
            __nv_bfloat16* dst = out + ((size_t)(b * C + oc0) * HW + r) * HW + seg * 8;
            const uint32_t src = SM_XOWN + oc0 * 128 + ((seg ^ (oc0 & 7)) << 4);
            bar_sync(6, 128 + 256);
#pragma unroll
            for (int i = 0; i < 4; i++) *reinterpret_cast<uint4*>(dst + (size_t)i * 32 * HW * HW) = lds128(src + i * 4096);
            if (tid == 256) { TL(20); TLG(21); }
        }
    } else if (warp < 4) {
        const int wq = warp;
        bar_sync(2, 128);

        const uint32_t xbase = SM_XOWN + ((lane >> 4) * 8 + (lane & 7)) * 128 + (((2 * wq + ((lane >> 3) & 1)) ^ (lane & 7)) << 4);
        float d[64];
#pragma unroll
        for (int i = 0; i < 64; i++) d[i] = 0.f;
#pragma unroll 1
        for (int conv = 0; conv < 2; conv++) {
            fence_acc(d);
            mma_stages<0>(d, conv, tid, gs);
            if (conv == 0) {
                asm volatile("wgmma.fence.sync.aligned;" ::: "memory");
                wgmma128<(SM_ONES >> 4) | (8u << 16), (SM_EMB >> 4), 0, 8>(d);
                asm volatile("wgmma.commit_group.sync.aligned;" ::: "memory");
            }
            asm volatile("wgmma.wait_group.sync.aligned 0;" ::: "memory");
            fence_acc(d);
            if (tid == 0) TL(10 + conv * 8);
            uint32_t hp[32];
#pragma unroll
            for (int i = 0; i < 32; i++) hp[i] = pack_bf(d[2 * i], d[2 * i + 1]);
            if (conv == 1) {
#pragma unroll
                for (int kc = 0; kc < 8; kc++) stsm4t(xbase + kc * 2048, hp[4 * kc], hp[4 * kc + 1], hp[4 * kc + 2], hp[4 * kc + 3]);
                bar_arrive(6, 128 + 256);
                break;
            }
#pragma unroll
            for (int g = 0; g < 4; g++) {
                float c[4] = {0.f, 0.f, 0.f, 0.f};
#pragma unroll
                for (int i = 0; i < 4; i++) stat_mma(c, hp[8 * g + 2 * i], hp[8 * g + 2 * i + 1]);
                stat_store(c, SM_RED + (g * 4 + wq) * 48, lane);
            }
            bar_sync(2, 128);
            if (wq == 0) stat_publish(SM_RED, &gs->acc2[b * LS], lane, true);
            if (tid == 0) TL(11);
            const uint32_t hbase = SM_ACT + (lane >> 4) * CH_PITCH + (2 + wq * 16 + (lane & 15)) * 16;
#pragma unroll
            for (int kc = 0; kc < 8; kc++) stsm4(hbase + kc * 2 * CH_PITCH, hp[4 * kc], hp[4 * kc + 1], hp[4 * kc + 2], hp[4 * kc + 3]);
            __syncwarp();
            if (lane == 0) mbar_arrive(BAR(BAR_HW));
            if (lane < LAG) mbar_arrive(BAR(BAR_WEMPTY + (NSTAGE - LAG) % NS) + 8 * lane);
            if (has_outer) {
                uint4* outbox = gs->box + (cta + ((r & 1) ? 1 : -1)) * 1024 + tid;
#pragma unroll
                for (int kc = 0; kc < 8; kc++) outbox[kc * 128] = make_uint4(~hp[4 * kc], ~hp[4 * kc + 1], ~hp[4 * kc + 2], ~hp[4 * kc + 3]);
            }
            if (tid == 0) TL(12);
#pragma unroll
            for (int kc = 0; kc < 8; kc++) {
                uint32_t p[4];
                ldsm4t(p, xbase + kc * 2048);
#pragma unroll
                for (int i = 0; i < 4; i++) { d[8 * kc + 2 * i] = bf_lo(p[i]); d[8 * kc + 2 * i + 1] = bf_hi(p[i]); }
            }
            fence_async_smem();
            __syncwarp();
            if (lane == 0) mbar_arrive(BAR(BAR_XFREE));
        }
        {
        }
    } else if (warp < 6) {
        bar_sync(5, 96);
        if (warp == 5) {
            asm volatile("barrier.cluster.wait.acquire.aligned;" ::: "memory");
            const uint32_t peer = (r & 1) ^ 1;
            const uint32_t self0 = mapa(0, r & 1), peer0 = mapa(0, peer);
#pragma unroll 1
            for (int conv = 0; conv < 2; conv++) {
#pragma unroll 1
                for (int kc = 0; kc < 8; kc++) {
                    mbar_wait(BAR(BAR_FULL) + 8 * kc, conv);
                    if (elect_one())
                        asm volatile("cp.async.bulk.shared::cluster.shared::cta.mbarrier::complete_tx::bytes [%0], [%1], %2, [%3];"
                                     ::"r"(peer0 + SM_ACT + ROW_BYTES + kc * KC_BYTES), "r"(self0 + SM_ACT + kc * KC_BYTES), "r"(KC_BYTES),
                                       "r"(peer0 + BAR(BAR_FULL + 8) + 8 * kc) : "memory");
                }
                if (lane == 0) TL(86 + conv);
#pragma unroll 1
                for (int kc = 0; kc < 8; kc++) mbar_wait(BAR(BAR_FULL + 8) + 8 * kc, conv);
                if (lane == 0)
                    asm volatile("mbarrier.arrive.release.cluster.shared::cluster.b64 _, [%0];" ::"r"(peer0 + (conv ? BAR(BAR_ACK) : BAR(BAR_EMB))) : "memory");
            }
            mbar_wait(BAR(BAR_ACK), 0);
        } else {
            if (has_outer && elect_one()) {
                mbar_expect(BAR(BAR_X + 4), 16384);
                while (clock32() - clk0 < XDELAY + XSTAG + XSTAG2 + ODELAY) {}
#pragma unroll
                for (int i = 0; i < 4; i++) tma_x(SM_XOUT + i * 4096, &xmap, r + ((r & 1) ? 1 : -1), b * C + i * 32, BAR(BAR_X + 4));
            }
            __syncwarp();
            mbar_wait(BAR(BAR_STATS), 0);
            unsigned it = 0;
            while (ld_relaxed(&gs->wcnt[(2 * NB + b) * LS]) < (unsigned)NXTRA && ++it < SPIN_LIMIT) __nanosleep(100);
            fence_acquire();
            float ev[4] = {0.f, 0.f, 0.f, 0.f};
#pragma unroll
            for (int j = 0; j < NXTRA; j++) {
                const uint4 ef = ld_relaxed_v4(&gs->emb[(j * NB + b) * C + lane * 4]);
                ev[0] += __uint_as_float(ef.x); ev[1] += __uint_as_float(ef.y); ev[2] += __uint_as_float(ef.z); ev[3] += __uint_as_float(ef.w);
            }
#pragma unroll
            for (int i = 0; i < 4; i++) {
                const float hi = bf_lo(pack_bf(ev[i], 0.f));
                sts128(SM_EMB + (lane * 4 + i) * 16, make_uint4(pack_bf(hi, ev[i] - hi), 0, 0, 0));
            }
            fence_async_smem();
            __syncwarp();
            if (lane == 0) { mbar_arrive(BAR(BAR_EMB)); TL(19); }
        }
    } else if (warp == 6) {
        bar_sync(0, 96);
        const uint32_t ebytes = STAGE_BYTES + ((lane >> 3) == 1 ? KC_BYTES : 0);
        if (lane < NSTAGE) mbar_expect(BAR(BAR_FULL) + 8 * lane, ebytes);
        const int swap = (r & 1) ? 0 : 8 * STAGE_BYTES;
        unsigned it = 0;
        {
            int g = 0;
#pragma unroll 1
            while (g < NS) {
                unsigned ready = __ballot_sync(0xffffffffu, ld_relaxed(&gs->wcnt[b * LS + (lane & 7)]) >= 16u) >> g;
                if (++it > SPIN_LIMIT) ready = ~0u;
                if (!(ready & 1)) continue;
                fence_acquire();
                fence_async_global();
                if (lane == 0) TL(g ? 3 : 6);
#pragma unroll 1
                for (; (ready & 1) && g < NS; g++, ready >>= 1)
                    if (elect_one())
                        bulk_g2s(S0 + SM_W + g * STAGE_BYTES, gs->wt + g * STAGE_BYTES + (g >= 8 ? swap : 0), STAGE_BYTES, S0 + BAR(BAR_FULL) + 8 * g);
            }
        }
#pragma unroll 1
        for (int q = 3; q < 12; q++) {
            const int conv = q >= 6, qs = conv ? q - 6 : q, sl = q % 3;
            const unsigned char* wsrc = gs->wt + q * 4 * STAGE_BYTES + (qs < 2 ? 0 : (qs < 4 ? swap : -swap));
            const uint32_t par = (q / 3 - 1) & 1;
            if (q == 6) {
                it = 0;
                while (ld_relaxed(&gs->wcnt[(NB + b) * LS]) < (unsigned)NCTA && ++it < SPIN_LIMIT) {}
                fence_acquire();
                fence_async_global();
                if (lane == 0) { mbar_arrive(BAR(BAR_EMB)); TL(2); }
            }
#pragma unroll
            for (int i = 0; i < 4; i++) {
                mbar_wait(BAR(BAR_WEMPTY + i) + 32 * sl, par);
                if (i == 0 && (q == 6 || q == 9)) {
                    if ((lane >= NS) == (q == 9) && lane < NSTAGE) mbar_expect(BAR(BAR_FULL) + 8 * lane, ebytes);
                    __syncwarp();
                }
                if (elect_one())
                    bulk_g2s(S0 + SM_W + (sl * 4 + i) * STAGE_BYTES, wsrc + i * STAGE_BYTES, STAGE_BYTES, S0 + BAR(BAR_FULL + i) + 32 * qs);
            }
        }
    } else {
        const uint2 ga1 = __ldg(reinterpret_cast<const uint2*>(g1) + lane), bt1 = __ldg(reinterpret_cast<const uint2*>(be1) + lane);
        const uint2 ga2 = __ldg(reinterpret_cast<const uint2*>(g2) + lane), bt2 = __ldg(reinterpret_cast<const uint2*>(be2) + lane);
        if (lane < 8) sts128(SM_GST + lane * 16, make_uint4(0, 0, 0, 0));
        sts128f(SM_COEF + lane * 32, make_float4(0.5f * bf_lo(ga1.x), 0.5f * bf_hi(ga1.x), 0.5f * bf_lo(bt1.x), 0.5f * bf_hi(bt1.x)));
        sts128f(SM_COEF + lane * 32 + 16, make_float4(0.5f * bf_lo(ga1.y), 0.5f * bf_hi(ga1.y), 0.5f * bf_lo(bt1.y), 0.5f * bf_hi(bt1.y)));
        sts128f(SM_COEF + 1024 + lane * 32, make_float4(0.5f * bf_lo(ga2.x), 0.5f * bf_hi(ga2.x), 0.5f * bf_lo(bt2.x), 0.5f * bf_hi(bt2.x)));
        sts128f(SM_COEF + 1024 + lane * 32 + 16, make_float4(0.5f * bf_lo(ga2.y), 0.5f * bf_hi(ga2.y), 0.5f * bf_lo(bt2.y), 0.5f * bf_hi(bt2.y)));
        bar_arrive(4, 256 + 64);
        bar_sync(0, 96);
#pragma unroll 1
        for (int conv = 0; conv < 2; conv++) {
            if (conv == 1) {
                mbar_wait(BAR(BAR_HW), 0);
                const unsigned c1 = clock32();
                while (clock32() - c1 < PD2) {}
            } else {
                while (clock32() - clk0 < PD) {}
            }
            const float* asrc = conv ? &gs->acc2[b * LS + (lane & 3) * 4] : &gs->acc1[b * 4 * LS + (lane & 3) * GS1];
            unsigned it = 0;
            uint4 fq[NPOLL];
#pragma unroll
            for (int i = 0; i < NPOLL; i++) {
                fq[i] = ld_relaxed_v4(asrc);
                if (i + 1 < NPOLL) { const unsigned c1 = clock32(); while (clock32() - c1 < 450 / NPOLL) {} }
            }
            bool all = false;
#pragma unroll 1
            while (!all) {
#pragma unroll
                for (int i = 0; i < NPOLL; i++) {
                    const uint4 f = fq[i];
                    const bool ok = ((f.x == 0x42800000u) & (f.w == 0x42800000u)) || it > SPIN_LIMIT;
                    if (ok && lane < 4) {
                        const float inv_n = 1.0f / (32.0f * HW * HW);
                        const float mean = __uint_as_float(f.y) * inv_n;
                        const float rs = rsqrtf(fmaxf(fmaf(-mean, mean, __uint_as_float(f.z) * inv_n), 0.f) + 1e-5f);
                        asm volatile("st.shared.v2.f32 [%0], {%1,%2};" ::"r"(S0 + SM_GST + conv * 32 + lane * 8), "f"(rs == 0.f ? 1e-38f : rs), "f"(mean * rs) : "memory");
                    }
                    if (__all_sync(0xffffffffu, ok)) { all = true; break; }
                    fq[i] = ld_relaxed_v4(asrc);
                }
                it++;
            }
            if (lane == 0) { mbar_arrive(BAR(BAR_STATS)); TL(7 + conv * 8); }
        }
        mbar_wait(BAR(BAR_XFREE), 0);
        if (has_outer && elect_one()) {
            mbar_expect(BAR(BAR_X + 4), 16384);
            bulk_g2s(S0 + SM_XOWN, gs->box + cta * 1024, 16384, S0 + BAR(BAR_X + 4));
        }
        if (r == 0) {
            if (lane < 16) gs->acc1[b * 4 * LS + (lane >> 2) * GS1 + (lane & 3)] = 0.f;
            if (lane < 24) gs->wcnt[((lane >> 3) * NB + b) * LS + (lane & 7)] = 0;
        }
    }
}

}

extern "C" void kernel_launch(void* const* d_in, const int* in_sizes, int n_in, void* d_out, int out_size) {
    (void)in_sizes; (void)n_in; (void)out_size;
    typedef CUresult (*EncodeFn)(CUtensorMap*, CUtensorMapDataType, cuuint32_t, void*, const cuuint64_t*, const cuuint64_t*,
                                 const cuuint32_t*, const cuuint32_t*, CUtensorMapInterleave, CUtensorMapSwizzle,
                                 CUtensorMapL2promotion, CUtensorMapFloatOOBfill);
    static Scratch* gs = nullptr;
    static EncodeFn encode = nullptr;
    if (!gs) {
        cudaFuncSetAttribute(resblock_kernel, cudaFuncAttributeMaxDynamicSharedMemorySize, SM_TOTAL);
        cudaGetSymbolAddress((void**)&gs, g_scratch);
        cudaDriverEntryPointQueryResult qr;
        cudaGetDriverEntryPoint("cuTensorMapEncodeTiled", (void**)&encode, cudaEnableDefault, &qr);
    }
    CUtensorMap xmap;
    const cuuint64_t dims[3] = {HW, HW, NB * C}, strides[2] = {HW * 2, HW * HW * 2};
    const cuuint32_t box[3] = {HW, 1, 32}, es[3] = {1, 1, 1};
    encode(&xmap, CU_TENSOR_MAP_DATA_TYPE_BFLOAT16, 3, d_in[0], dims, strides, box, es, CU_TENSOR_MAP_INTERLEAVE_NONE,
           CU_TENSOR_MAP_SWIZZLE_128B, CU_TENSOR_MAP_L2_PROMOTION_NONE, CU_TENSOR_MAP_FLOAT_OOB_FILL_NONE);
    resblock_kernel<<<NCTA + NXTRA, NTHREADS, SM_TOTAL>>>(
        (const __nv_bfloat16*)d_in[4], (const __nv_bfloat16*)d_in[1],
        (const __nv_bfloat16*)d_in[2], (const __nv_bfloat16*)d_in[3], (const __nv_bfloat16*)d_in[5],
        (const __nv_bfloat16*)d_in[6], (const __nv_bfloat16*)d_in[7], (const __nv_bfloat16*)d_in[8],
        (__nv_bfloat16*)d_out, gs, xmap);
}
```

```cpp
#include <cuda_runtime.h>
#include <cuda.h>
#include <cuda_bf16.h>
#include <stdint.h>

namespace {

constexpr int C = 128, HW = 64, NB = 2, E = 768;
constexpr int NCTA = NB * HW;
constexpr int NXTRA = 4;
constexpr int NTHREADS = 16 * 32;
constexpr int CH_PITCH = 66 * 16;
constexpr int ROW_BYTES = 16 * CH_PITCH;
constexpr int STEP_BYTES = 4096;
constexpr int STAGE_BYTES = 3 * STEP_BYTES;
constexpr int NSTAGE = 24;
constexpr int KC_BYTES = 2 * CH_PITCH;
constexpr int NS = 12;
constexpr int LAG = 1;
#define XDELAY 400
#define HDELAY 600
#define SEQ 0
#define MMA0_WAIT mbar_try
#define SPINPAUSE
#define NPOLL 1
#define PD2 0
#define ODELAY 100
#define PDELAY 60
#define RB 1
#define XSTAG2 400
#define XSTAG 800
#define HSEND 0
#define W2DELAY 1800

constexpr uint32_t SMEM_BASE = 0x400;
constexpr uint32_t SM_XOWN = SMEM_BASE;
constexpr uint32_t SM_ACT = SM_XOWN + 16384 + 512;
constexpr uint32_t SM_XOUT = SM_ACT + 2 * ROW_BYTES + 512;
static_assert(SM_XOUT % 1024 == 0, "swizzle atom alignment");
constexpr uint32_t SM_W = SM_ACT + 3 * ROW_BYTES + 128;
__host__ __device__ constexpr uint32_t slot_addr(int slot) { return SM_W + slot * STAGE_BYTES; }
constexpr uint32_t SM_COEF = SM_W + NS * STAGE_BYTES;
constexpr uint32_t SM_GST = SM_COEF + 2048;
constexpr uint32_t SM_EMB = SM_GST + 128;
constexpr uint32_t SM_ONES = SM_EMB + 2048;
constexpr uint32_t SM_RED = SM_ONES + 256;
constexpr uint32_t SM_BNC = SM_RED + 1536;
constexpr uint32_t SM_BAR = SM_BNC + 2 * 2304;
constexpr int BAR_FULL = 0, BAR_WEMPTY = NSTAGE, BAR_HW = BAR_WEMPTY + NS, BAR_XFREE = BAR_HW + 1, BAR_STATS = BAR_XFREE + 1,
              BAR_EMB = BAR_STATS + 1, BAR_ACK = BAR_EMB + 1, BAR_X = BAR_ACK + 1  , NBAR = BAR_X + 5;
constexpr int SM_TOTAL = SM_BAR + NBAR * 8 - SMEM_BASE;
static_assert(SM_TOTAL <= 232448, "smem");
static_assert(NBAR <= 96, "barrier init");
__host__ __device__ constexpr uint32_t BAR(int i) { return SM_BAR + 8 * i; }
__host__ __device__ constexpr int ky_of(int kyo) { return kyo == 0 ? 1 : (kyo == 1 ? 0 : 2); }

constexpr unsigned SPIN_LIMIT = 1u << 16;

#define LS 1056
#define GS1 4
#define PD 0
struct Scratch {
    float acc1[NB * 4 * LS];
    float acc2[NB * LS];
    unsigned wcnt[3 * NB * LS];
    float emb[NXTRA * NB * C];
    unsigned char wt[2 * NSTAGE * STAGE_BYTES];
    uint4 box[NCTA * 1024];
};
__device__ __align__(1024) Scratch g_scratch;
#define TL(i) do {} while (0)
#define TLG(i) do {} while (0)

__device__ __forceinline__ unsigned clock32() { unsigned c; asm volatile("mov.u32 %0, %%clock;" : "=r"(c)); return c; }
__device__ __forceinline__ uint32_t mapa(uint32_t a, uint32_t rank) {
    uint32_t d;
    asm("mapa.shared::cluster.u32 %0, %1, %2;" : "=r"(d) : "r"(a), "r"(rank));
    return d;
}
#define S0 mapa(0, blockIdx.x & 1)
__device__ __forceinline__ void mbar_init(uint32_t bar, int cnt) {
    asm volatile("mbarrier.init.shared::cta.b64 [%0], %1;" ::"r"(bar + S0), "r"(cnt) : "memory");
}
__device__ __forceinline__ void mbar_arrive(uint32_t bar) {
    asm volatile("mbarrier.arrive.shared::cta.b64 _, [%0];" ::"r"(bar + S0) : "memory");
}
__device__ __forceinline__ void mbar_expect(uint32_t bar, uint32_t bytes) {
    asm volatile("mbarrier.arrive.expect_tx.shared::cta.b64 _, [%0], %1;" ::"r"(bar + S0), "r"(bytes) : "memory");
}
__device__ __forceinline__ bool mbar_try(uint32_t bar, uint32_t par) {
    uint32_t ok;
    asm volatile("{\n.reg .pred p;\nmbarrier.try_wait.parity.shared::cta.b64 p, [%1], %2;\nselp.u32 %0, 1, 0, p;\n}"
                 : "=r"(ok) : "r"(bar + S0), "r"(par) : "memory");
    return ok;
}
__device__ __forceinline__ bool mbar_test(uint32_t bar, uint32_t par) {
    uint32_t ok;
    asm volatile("{\n.reg .pred p;\nmbarrier.test_wait.parity.shared::cta.b64 p, [%1], %2;\nselp.u32 %0, 1, 0, p;\n}"
                 : "=r"(ok) : "r"(bar + S0), "r"(par) : "memory");
    return ok;
}
__device__ __forceinline__ void mbar_wait(uint32_t bar, uint32_t par) {
    unsigned it = 0;
#pragma unroll 1
    while (!mbar_try(bar, par) && ++it < SPIN_LIMIT) {}
}
__device__ __forceinline__ bool elect_one() {
    uint32_t p;
    asm volatile("{\n.reg .pred p;\nelect.sync _|p, 0xffffffff;\nselp.u32 %0, 1, 0, p;\n}" : "=r"(p));
    return p;
}
__device__ __forceinline__ void fence_async_smem() { asm volatile("fence.proxy.async.shared::cta;" ::: "memory"); }
__device__ __forceinline__ void fence_async_global() { asm volatile("fence.proxy.async.global;" ::: "memory"); }
__device__ __forceinline__ void fence_acquire() { asm volatile("fence.acquire.gpu;" ::: "memory"); }
__device__ __forceinline__ void bar_sync(int id, int n) { asm volatile("bar.sync %0, %1;" ::"r"(id), "r"(n) : "memory"); }
__device__ __forceinline__ void bar_arrive(int id, int n) { asm volatile("bar.arrive %0, %1;" ::"r"(id), "r"(n) : "memory"); }
__device__ __forceinline__ void bulk_g2s(uint32_t dst, const void* src, uint32_t bytes, uint32_t bar) {
    asm volatile("cp.async.bulk.shared::cluster.global.mbarrier::complete_tx::bytes [%0], [%1], %2, [%3];"
                 ::"r"(dst), "l"(src), "r"(bytes), "r"(bar) : "memory");
}
__device__ __forceinline__ void tma_x(uint32_t dst, const CUtensorMap* tm, int row, int ch, uint32_t bar) {
    asm volatile("cp.async.bulk.tensor.3d.shared::cluster.global.mbarrier::complete_tx::bytes [%0], [%1, {%2, %3, %4}], [%5];"
                 ::"r"(dst + S0), "l"(tm), "r"(0), "r"(row), "r"(ch), "r"(bar + S0) : "memory");
}
__device__ __forceinline__ uint4 ld_relaxed_v4(const void* p) {
    uint4 v;
    asm volatile("ld.relaxed.gpu.global.v4.u32 {%0,%1,%2,%3}, [%4];" : "=r"(v.x), "=r"(v.y), "=r"(v.z), "=r"(v.w) : "l"(p) : "memory");
    return v;
}
__device__ __forceinline__ unsigned ld_relaxed(const void* p) {
    unsigned v;
    asm volatile("ld.relaxed.gpu.global.u32 %0, [%1];" : "=r"(v) : "l"(p) : "memory");
    return v;
}
__device__ __forceinline__ void red_add4(float* p, float a, float b, float c, float d) {
    asm volatile("red.relaxed.gpu.global.add.v4.f32 [%0], {%1,%2,%3,%4};" ::"l"(p), "f"(a), "f"(b), "f"(c), "f"(d) : "memory");
}
__device__ __forceinline__ void sts128(uint32_t a, uint4 v) {
    asm volatile("st.shared.v4.u32 [%0], {%1,%2,%3,%4};" ::"r"(a + S0), "r"(v.x), "r"(v.y), "r"(v.z), "r"(v.w) : "memory");
}
__device__ __forceinline__ void sts128f(uint32_t a, float4 v) {
    asm volatile("st.shared.v4.f32 [%0], {%1,%2,%3,%4};" ::"r"(a + S0), "f"(v.x), "f"(v.y), "f"(v.z), "f"(v.w) : "memory");
}
__device__ __forceinline__ void sts32f(uint32_t a, float v) { asm volatile("st.shared.f32 [%0], %1;" ::"r"(a + S0), "f"(v) : "memory"); }
__device__ __forceinline__ uint4 lds128(uint32_t a) {
    uint4 v;
    asm volatile("ld.shared.v4.u32 {%0,%1,%2,%3}, [%4];" : "=r"(v.x), "=r"(v.y), "=r"(v.z), "=r"(v.w) : "r"(a + S0) : "memory");
    return v;
}
__device__ __forceinline__ float4 lds128f(uint32_t a) {
    float4 v;
    asm volatile("ld.shared.v4.f32 {%0,%1,%2,%3}, [%4];" : "=f"(v.x), "=f"(v.y), "=f"(v.z), "=f"(v.w) : "r"(a + S0) : "memory");
    return v;
}
__device__ __forceinline__ float2 lds64f(uint32_t a) {
    float2 v;
    asm volatile("ld.shared.v2.f32 {%0,%1}, [%2];" : "=f"(v.x), "=f"(v.y) : "r"(a + S0) : "memory");
    return v;
}
__device__ __forceinline__ float bf_lo(uint32_t u) { return __uint_as_float(u << 16); }
__device__ __forceinline__ float bf_hi(uint32_t u) { return __uint_as_float(u & 0xffff0000u); }
__device__ __forceinline__ uint32_t pack_bf(float lo, float hi) {
    uint32_t r;
    asm("cvt.rn.bf16x2.f32 %0, %1, %2;" : "=r"(r) : "f"(hi), "f"(lo));
    return r;
}
__device__ __forceinline__ float tanh_fast(float x) {
    float r;
    asm("tanh.approx.f32 %0, %1;" : "=f"(r) : "f"(x));
    return r;
}
__device__ __forceinline__ float silu_half(float h) { return fmaf(h, tanh_fast(h), h); }
__device__ __forceinline__ void ldsm4(uint32_t (&u)[4], uint32_t a) {
    asm volatile("ldmatrix.sync.aligned.m8n8.x4.shared.b16 {%0,%1,%2,%3}, [%4];"
                 : "=r"(u[0]), "=r"(u[1]), "=r"(u[2]), "=r"(u[3]) : "r"(a + S0) : "memory");
}
__device__ __forceinline__ void ldsm4t(uint32_t (&u)[4], uint32_t a) {
    asm volatile("ldmatrix.sync.aligned.m8n8.x4.trans.shared.b16 {%0,%1,%2,%3}, [%4];"
                 : "=r"(u[0]), "=r"(u[1]), "=r"(u[2]), "=r"(u[3]) : "r"(a + S0) : "memory");
}
__device__ __forceinline__ void stsm4(uint32_t a, uint32_t p0, uint32_t p1, uint32_t p2, uint32_t p3) {
    asm volatile("stmatrix.sync.aligned.m8n8.x4.shared.b16 [%0], {%1,%2,%3,%4};" ::"r"(a + S0), "r"(p0), "r"(p1), "r"(p2), "r"(p3) : "memory");
}
__device__ __forceinline__ void stsm4t(uint32_t a, uint32_t p0, uint32_t p1, uint32_t p2, uint32_t p3) {
    asm volatile("stmatrix.sync.aligned.m8n8.x4.trans.shared.b16 [%0], {%1,%2,%3,%4};" ::"r"(a + S0), "r"(p0), "r"(p1), "r"(p2), "r"(p3) : "memory");
}

#define R8(o) "+f"(d[o]), "+f"(d[o + 1]), "+f"(d[o + 2]), "+f"(d[o + 3]), "+f"(d[o + 4]), "+f"(d[o + 5]), "+f"(d[o + 6]), "+f"(d[o + 7])
template <uint32_t ALO, uint32_t BLO, uint64_t AHI = 8, uint64_t BHI = 48>
__device__ __forceinline__ void wgmma128(float (&d)[64]) {
    asm volatile(
        "wgmma.mma_async.sync.aligned.m64n128k16.f32.bf16.bf16 "
        "{%0,%1,%2,%3,%4,%5,%6,%7,%8,%9,%10,%11,%12,%13,%14,%15,%16,%17,%18,%19,%20,%21,%22,%23,%24,%25,%26,%27,%28,%29,%30,%31,"
        "%32,%33,%34,%35,%36,%37,%38,%39,%40,%41,%42,%43,%44,%45,%46,%47,%48,%49,%50,%51,%52,%53,%54,%55,%56,%57,%58,%59,%60,%61,%62,%63},"
        " %64, %65, 1, 1, 1, 0, 0;"
        : R8(0), R8(8), R8(16), R8(24), R8(32), R8(40), R8(48), R8(56)
        : "l"((AHI << 32) | ALO), "l"((BHI << 32) | BLO));
}
template <int S>
__device__ __forceinline__ void mma_stages(float (&d)[64], int conv, int tid, Scratch* gs) {
    constexpr uint32_t A = ((SM_ACT + S * 2 * CH_PITCH + 16) >> 4) | ((CH_PITCH >> 4) << 16);
    constexpr uint32_t B = (slot_addr(S % NS) >> 4) | (8u << 16);
    if (S == 0) {
        unsigned it = 0;
#pragma unroll 1
        while (!MMA0_WAIT(BAR(BAR_FULL), conv) && ++it < SPIN_LIMIT) {}
    }
    bool next_ok = true;
    constexpr uint32_t NEXT = S + 1 < NSTAGE ? BAR(BAR_FULL + S + 1) : BAR(BAR_EMB);
    const int npar = S + 1 < NSTAGE ? conv : 0;
    next_ok = mbar_test(NEXT, npar);
    if (S == 0 && tid == 0) TL(32 + conv * 24);
    asm volatile("wgmma.fence.sync.aligned;" ::: "memory");
    wgmma128<A, B>(d);
    wgmma128<A + 1, B + 16>(d);
    wgmma128<A + 2, B + 32>(d);
    asm volatile("wgmma.commit_group.sync.aligned;" ::: "memory");
    if (S >= LAG) {
        asm volatile("wgmma.wait_group.sync.aligned %0;" ::"n"(LAG) : "memory");
        if ((tid & 31) == 0) mbar_arrive(BAR(BAR_WEMPTY + (S + NS - LAG) % NS));
    }
    if (!next_ok) mbar_wait(NEXT, npar);
    if constexpr (S + 1 < NSTAGE) mma_stages<S + 1>(d, conv, tid, gs);
}

__device__ __forceinline__ void weight_load(uint4 (&t)[5], const __nv_bfloat16* w, int cta, int lane) {
    const char* base = reinterpret_cast<const char*>(w) + ((cta & 15) * 8 * C + (cta >> 4) * 16) * 18;
#pragma unroll
    for (int k = 0; k < 5; k++) {
        const int i = lane + 32 * k, row = (i * 57) >> 10;
        if (k < 4 || lane < 16) t[k] = __ldg(reinterpret_cast<const uint4*>(base + row * (C * 18 - 288) + i * 16));
    }
}
__device__ __forceinline__ void weight_block(uint32_t bounce, unsigned char* wt, int cta, int lane, bool readback, Scratch* gs) {
    unsigned char* dst = wt + (cta >> 4) * STAGE_BYTES + (cta & 15) * 768;
    if (lane < 16) {
        uint32_t v[36];
#pragma unroll
        for (int i = 0; i < 9; i++) {
            const uint4 q = lds128(bounce + (lane & 7) * 288 + (lane >> 3) * 144 + i * 16);
            v[4 * i] = q.x; v[4 * i + 1] = q.y; v[4 * i + 2] = q.z; v[4 * i + 3] = q.w;
        }
#pragma unroll
        for (int kyo = 0; kyo < 3; kyo++) {
#pragma unroll
            for (int kx = 0; kx < 3; kx++) {
                const int tap = ky_of(kyo) * 3 + kx;
                uint32_t o[4];
#pragma unroll
                for (int m = 0; m < 4; m++) {
                    const int i0 = 18 * m + tap, i1 = i0 + 9;
                    const uint32_t sel = ((i0 & 1) ? 0x32u : 0x10u) | ((i1 & 1) ? 0x7600u : 0x5400u);
                    o[m] = __byte_perm(v[i0 >> 1], v[i1 >> 1], sel);
                }
                *reinterpret_cast<uint4*>(dst + kyo * 8 * STAGE_BYTES + kx * 256 + lane * 16) = make_uint4(o[0], o[1], o[2], o[3]);
            }
        }
    }
    if (readback) {
        __syncwarp();
        unsigned acc = 0;
        if (lane < 24) {
#pragma unroll
            for (int i = 0; i < 3; i++) acc |= ld_relaxed(dst + i * 8 * STAGE_BYTES + lane * 32);
        }
        asm volatile("{\n.reg .pred p;\nsetp.eq.u32 p, %0, 0x9e3779b9;\n@p st.shared.u32 [%1], %0;\n}" ::"r"(acc), "r"(bounce + S0) : "memory");
    }
}
__device__ __forceinline__ uint32_t act2(uint32_t u, const float4& cf) {
    return pack_bf(silu_half(fmaf(bf_lo(u), cf.x, cf.z)), silu_half(fmaf(bf_hi(u), cf.y, cf.w)));
}
__device__ __forceinline__ void norm_unit(uint32_t (&u)[4], const float4& ca, const float4& cb) {
    u[0] = act2(u[0], ca); u[1] = act2(u[1], ca); u[2] = act2(u[2], cb); u[3] = act2(u[3], cb);
}
__device__ __forceinline__ void read_stats(uint32_t gst, float (&g)[8]) {
    asm volatile("ld.volatile.shared.v4.f32 {%0,%1,%2,%3}, [%4];" : "=f"(g[0]), "=f"(g[1]), "=f"(g[2]), "=f"(g[3]) : "r"(gst + S0) : "memory");
    asm volatile("ld.volatile.shared.v4.f32 {%0,%1,%2,%3}, [%4];" : "=f"(g[4]), "=f"(g[5]), "=f"(g[6]), "=f"(g[7]) : "r"(gst + 16 + S0) : "memory");
}
template <int T>
__device__ __forceinline__ void group_coefs(uint32_t gst, float (&g)[8], float4 (&cf)[8]) {
    unsigned it = 0;
    if (!__all_sync(0xffffffffu, g[2 * T] != 0.f)) {
        float rs0;
#pragma unroll 1
        do {
            SPINPAUSE;
            asm volatile("ld.volatile.shared.f32 %0, [%1];" : "=f"(rs0) : "r"(gst + 8 * T + S0) : "memory");
        } while (!__all_sync(0xffffffffu, rs0 != 0.f) && ++it < 8 * SPIN_LIMIT);
        read_stats(gst, g);
    }
    float4 &ca = cf[2 * T], &cb = cf[2 * T + 1];
    const float rs = g[2 * T], mr = g[2 * T + 1];
    ca.z = fmaf(-mr, ca.x, ca.z); ca.w = fmaf(-mr, ca.y, ca.w); ca.x *= rs; ca.y *= rs;
    cb.z = fmaf(-mr, cb.x, cb.z); cb.w = fmaf(-mr, cb.y, cb.w); cb.x *= rs; cb.y *= rs;
}
template <int FIRST, int N>
__device__ __forceinline__ void norm_block(uint32_t (&u)[4][4], float4 (&cf)[8], uint32_t act, uint32_t mask, uint32_t fbar, int lane) {
#pragma unroll
    for (int t = FIRST; t < FIRST + N; t++) {
        norm_unit(u[t], cf[2 * t], cf[2 * t + 1]);
        stsm4(act + t * 2 * KC_BYTES, u[t][0] & mask, u[t][1] & mask, u[t][2] & mask, u[t][3] & mask);
    }
    fence_async_smem();
    __syncwarp();
    if (lane < N) mbar_arrive(fbar + 16 * (FIRST + lane));
}
__device__ __forceinline__ void publish(uint32_t bar, int lane) {
    fence_async_smem();
    __syncwarp();
    if (lane == 0) mbar_arrive(bar);
}
template <int T>
__device__ __forceinline__ void next_unit(uint32_t (&u)[4][4], float4 (&cf)[8], uint32_t gst, float (&g)[8], uint32_t act, uint32_t fbar, int lane) {
    const bool have = __all_sync(0xffffffffu, g[2 * T] != 0.f);
    if (!have) publish(fbar + 16 * (T - 1), lane);
    group_coefs<T>(gst, g, cf);
    norm_unit(u[T], cf[2 * T], cf[2 * T + 1]);
    if (have) publish(fbar + 16 * (T - 1), lane);
    stsm4(act + T * 2 * KC_BYTES, u[T][0], u[T][1], u[T][2], u[T][3]);
}
__device__ __forceinline__ void stat_mma(float (&c)[4], uint32_t p, uint32_t q) {
    asm("mma.sync.aligned.m16n8k16.row.col.f32.bf16.bf16.f32 {%0,%1,%2,%3}, {%4,%5,%6,%5}, {%4,%6}, {%0,%1,%2,%3};"
        : "+f"(c[0]), "+f"(c[1]), "+f"(c[2]), "+f"(c[3]) : "r"(p), "r"(0x3f803f80u), "r"(q));
}
__device__ __forceinline__ void stat_store(const float (&c)[4], uint32_t dst, int lane) {
    const int g = lane >> 2, t = lane & 3;
    if (t == (g >> 1)) sts32f(dst + g * 4, (g & 1) ? c[1] : c[0]);
    if (g == 7) sts32f(dst + 32 + t * 4, c[2] + c[3]);
}
__device__ __forceinline__ float sum4(float4 v) { return (v.x + v.y) + (v.z + v.w); }
__device__ __forceinline__ void stat_publish(uint32_t src, float* acc, int lane, bool real) {
    const uint32_t a = src + (lane & 15) * 48;
    float q = sum4(lds128f(a)) + sum4(lds128f(a + 16)), sm = sum4(lds128f(a + 32));
    q += __shfl_xor_sync(0xffffffffu, q, 1); sm += __shfl_xor_sync(0xffffffffu, sm, 1);
    q += __shfl_xor_sync(0xffffffffu, q, 2); sm += __shfl_xor_sync(0xffffffffu, sm, 2);
    if (real && (lane & 19) == 0) red_add4(acc + lane, 1.f, sm, q, 1.f);
}
__device__ __forceinline__ void fence_acc(float (&d)[64]) {
#pragma unroll
    for (int i = 0; i < 64; i++) asm volatile("" : "+f"(d[i])::"memory");
}
__device__ __forceinline__ void ld_unit(uint32_t (&u)[4], const uint4* p) {
    asm volatile("ld.relaxed.gpu.global.v4.u32 {%0,%1,%2,%3}, [%4];" : "=r"(u[0]), "=r"(u[1]), "=r"(u[2]), "=r"(u[3]) : "l"(p) : "memory");
}

__device__ __noinline__ void side_jobs(const __nv_bfloat16* __restrict__ t_emb, const __nv_bfloat16* __restrict__ w_emb,
                                       const __nv_bfloat16* __restrict__ w2, Scratch* __restrict__ gs, unsigned clk0) {
    const int tid = threadIdx.x, warp = tid >> 5, lane = tid & 31, j = blockIdx.x;
    float tv = 0.f;
    if (lane < 24) tv = __bfloat162float(t_emb[(lane / 12) * E + j * 192 + warp * 12 + lane % 12]);
    if (tid == 0) {
        mbar_init(BAR(0), 1);
        mbar_expect(BAR(0), 192 * C * 2);
        fence_async_smem();
        while (clock32() - clk0 < W2DELAY) {}
#pragma unroll
        for (int i = 0; i < 4; i++) bulk_g2s(S0 + SM_W + i * 12288, w_emb + (j * 192 + i * 48) * C, 12288, S0 + BAR(0));
    }
    if (j == 0 && tid < 32) gs->acc2[(tid >> 4) * LS + (tid & 15)] = 0.f;
    const float sv = silu_half(0.5f * tv);
    __syncthreads();
    mbar_wait(BAR(0), 0);
    float acc[8] = {0.f, 0.f, 0.f, 0.f, 0.f, 0.f, 0.f, 0.f};
#pragma unroll
    for (int i = 0; i < 12; i++) {
        const float2 wq = lds64f(SM_W + (warp * 12 + i) * 256 + lane * 8);
        const uint32_t wx = __float_as_uint(wq.x), wy = __float_as_uint(wq.y);
#pragma unroll
        for (int bb = 0; bb < 2; bb++) {
            const float sx = __shfl_sync(0xffffffffu, sv, bb * 12 + i);
            acc[4 * bb + 0] = fmaf(sx, bf_lo(wx), acc[4 * bb + 0]); acc[4 * bb + 1] = fmaf(sx, bf_hi(wx), acc[4 * bb + 1]);
            acc[4 * bb + 2] = fmaf(sx, bf_lo(wy), acc[4 * bb + 2]); acc[4 * bb + 3] = fmaf(sx, bf_hi(wy), acc[4 * bb + 3]);
        }
    }
    sts128f(SM_ACT + warp * 1024 + lane * 16, make_float4(acc[0], acc[1], acc[2], acc[3]));
    sts128f(SM_ACT + warp * 1024 + 512 + lane * 16, make_float4(acc[4], acc[5], acc[6], acc[7]));
    __syncthreads();
    if (tid < 128) {
        float2 sum = make_float2(0.f, 0.f);
#pragma unroll
        for (int w = 0; w < 16; w++) { const float2 p = lds64f(SM_ACT + w * 1024 + tid * 8); sum.x += p.x; sum.y += p.y; }
        *reinterpret_cast<float2*>(&gs->emb[j * NB * C + tid * 2]) = sum;
        bar_sync(1, 128);
        if (tid < 2) asm volatile("red.release.gpu.global.add.u32 [%0], 1;" ::"l"(&gs->wcnt[(2 * NB + tid) * LS]) : "memory");
    }
}

__global__ void __cluster_dims__(2, 1, 1) __launch_bounds__(NTHREADS, 1)
resblock_kernel(const __nv_bfloat16* __restrict__ w1,
                const __nv_bfloat16* __restrict__ t_emb, const __nv_bfloat16* __restrict__ g1,
                const __nv_bfloat16* __restrict__ be1, const __nv_bfloat16* __restrict__ w_emb,
                const __nv_bfloat16* __restrict__ g2, const __nv_bfloat16* __restrict__ be2,
                const __nv_bfloat16* __restrict__ w2, __nv_bfloat16* __restrict__ out, Scratch* __restrict__ gs,
                const __grid_constant__ CUtensorMap xmap) {
    const unsigned clk0 = clock32();
    if (threadIdx.x == 480 && blockIdx.x >= NXTRA) TLG(1);
    const int tid = threadIdx.x, lane = tid & 31;
    const int cta = blockIdx.x - NXTRA, b = cta >> 6, r = cta & 63;
    uint4 v[5];
    if (tid < 32) weight_load(v, w1, cta & (NCTA - 1), lane);
    const int warp = __shfl_sync(0xffffffffu, tid >> 5, 0);
    if (cta < 0) { side_jobs(t_emb, w_emb, w2, gs, clk0); return; }

    if (warp != 3) asm volatile("barrier.cluster.arrive.relaxed.aligned;" ::: "memory");
    const bool has_outer = (r != 0) && (r != HW - 1);
    if (warp == 1 || warp == 2 || warp == 4 || warp == 5) {
        const int g = warp < 3 ? warp - 1 : warp - 2;
        if (elect_one()) {
            asm volatile("prefetch.tensormap [%0];" ::"l"(&xmap) : "memory");
            mbar_init(BAR(BAR_X) + 8 * g, 1);
            mbar_expect(BAR(BAR_X) + 8 * g, 4096);
            fence_async_smem();
        }
        __syncwarp();
        bar_arrive(4, 256 + 64 + 128);
        if (elect_one()) {
            while (clock32() - clk0 < XDELAY + (g >> 1) * XSTAG + (g & 1) * XSTAG2) {}
            tma_x(SM_XOWN + g * 4096, &xmap, r, b * C + g * 32, BAR(BAR_X) + 8 * g);
        }
        __syncwarp();
        mbar_wait(BAR(BAR_X) + 8 * g, 0);
        if (lane == 0) TL(70 + g);
        float c[8][4];
#pragma unroll
        for (int k = 0; k < 8; k++) {
            const uint4 q = lds128(SM_XOWN + g * 4096 + k * 512 + lane * 16);
            c[k][0] = c[k][1] = c[k][2] = c[k][3] = 0.f;
            stat_mma(c[k], q.x, q.y); stat_mma(c[k], q.z, q.w);
        }
#pragma unroll
        for (int i = 0; i < 4; i++) c[0][i] = ((c[0][i] + c[1][i]) + (c[2][i] + c[3][i])) + ((c[4][i] + c[5][i]) + (c[6][i] + c[7][i]));
        stat_store(c[0], SM_RED + g * 48, lane);
        __syncwarp();
        if (lane == 0) {
            const uint32_t a = SM_RED + g * 48;
            red_add4(&gs->acc1[b * 4 * LS + g * GS1], 1.f, sum4(lds128f(a + 32)), sum4(lds128f(a)) + sum4(lds128f(a + 16)), 1.f);
            TL(74 + g);
        }
    }
    if (warp == 3) {
            if (elect_one()) {
#pragma unroll
                for (int i = 0; i < NSTAGE; i++) mbar_init(BAR(BAR_FULL + i), (i >> 3) == 1 ? 1 : 5);
#pragma unroll
                for (int i = 0; i < NS + 2; i++) mbar_init(BAR(BAR_WEMPTY + i), 4);
#pragma unroll
                for (int i = BAR_STATS; i < BAR_X; i++) mbar_init(BAR(i), i == BAR_EMB ? 3 : 1);
                mbar_init(BAR(BAR_X + 4), 1);
                asm volatile("fence.mbarrier_init.release.cluster;" ::: "memory");
            }
            __syncwarp();
            fence_async_smem();
            bar_arrive(0, 96);
            bar_arrive(5, 96);
            bar_arrive(4, 256 + 64 + 128);
            const uint4 z = make_uint4(0, 0, 0, 0);
#pragma unroll
            for (int i = 0; i < 2; i++) sts128(SM_ACT + (i * 16 + (lane >> 1)) * CH_PITCH + (lane & 1) * 16, z);
            if (lane < 4) sts128(SM_ACT + (2 + (lane >> 1)) * ROW_BYTES + (lane & 1) * 16, z);
            if (lane < 16) sts128(SM_ONES + lane * 16, make_uint4(lane < 8 ? 0x3f803f80u : 0u, 0, 0, 0));
            fence_async_smem();
            asm volatile("barrier.cluster.arrive.relaxed.aligned;" ::: "memory");
            if (lane == 0) TL(5);
            while (clock32() - clk0 < W2DELAY) {}
            weight_load(v, w2, cta, lane);
        }
    if (warp == 0 || warp == 3) {
        const int k = warp & 1;
#pragma unroll
        for (int i = 0; i < 5; i++)
            if (i < 4 || lane < 16) sts128(SM_BNC + k * 2304 + (lane + 32 * i) * 16, v[i]);
        if (lane == 0) TL(k ? 14 : 81);
        __syncwarp();
        weight_block(SM_BNC + k * 2304, gs->wt + k * NSTAGE * STAGE_BYTES, cta, lane, true, gs);
        __syncwarp();
        if (lane == 0) TL(k ? 13 : 4);
        if (lane < 2) asm volatile("red.relaxed.gpu.global.add.u32 [%0], 1;" ::"l"(&gs->wcnt[(k * NB + lane) * LS + (k ? 0 : cta >> 4)]) : "memory");
    }

    if (warp >= 8) {
        const int nw = warp - 8;
        bar_sync(4, 256 + 64 + 128);
        const int par = nw >> 2, wq = nw & 3;
        const uint32_t act_off = SM_ACT + (par * 2 + (lane >> 4)) * CH_PITCH + (2 + wq * 16 + (lane & 15)) * 16;
        const uint32_t stg_off = (par * 16 + (lane >> 4) * 8 + (lane & 7)) * 128 + (((2 * wq + ((lane >> 3) & 1)) ^ (lane & 7)) << 4);
        const uint32_t cfa = SM_COEF + par * 128 + (lane & 3) * 16;
        const uint32_t fbar = BAR(BAR_FULL) + 8 * par;
        uint4* inbox = gs->box + cta * 1024 + nw * 32 + lane;
#pragma unroll 1
        for (int conv = 0; conv < 2; conv++) {
            uint32_t u[4][4], w[4][4];
            float4 cf[8];
            if (conv == 0) {
#pragma unroll
                for (int i = 0; i < 4; i++) { mbar_wait(BAR(BAR_X + i), 0); ldsm4t(u[i], SM_XOWN + stg_off + i * 4096); }
            } else {
                mbar_wait(BAR(BAR_HW), 0);
#pragma unroll
                for (int i = 0; i < 4; i++) ldsm4(u[i], act_off + i * 2 * KC_BYTES);
            }
#pragma unroll
            for (int i = 0; i < 8; i++) cf[i] = lds128f(cfa + conv * 1024 + (i >> 1) * 256 + (i & 1) * 64);
            const uint32_t gst = SM_GST + conv * 32;
            float gv[8];
            read_stats(gst, gv);
            group_coefs<0>(gst, gv, cf);
            if (tid == 256) TL(22 + conv * 4);
            if (par) { const unsigned c1 = clock32(); while (clock32() - c1 < PDELAY) {} }
            norm_block<0, 1>(u, cf, act_off, ~0u, fbar, lane);
            if (tid == 256) TL(8 + conv * 8);
            group_coefs<1>(gst, gv, cf);
            norm_unit(u[1], cf[2], cf[3]);
            stsm4(act_off + 2 * KC_BYTES, u[1][0], u[1][1], u[1][2], u[1][3]);
            next_unit<2>(u, cf, gst, gv, act_off, fbar, lane);
            next_unit<3>(u, cf, gst, gv, act_off, fbar, lane);
            publish(fbar + 48, lane);
            if (tid == 256) TL(84 + conv);
            if (has_outer) {
                mbar_wait(BAR(BAR_X + 4), conv);
                if (conv == 0) {
#pragma unroll
                    for (int i = 0; i < 4; i++) ldsm4t(w[i], SM_XOUT + stg_off + i * 4096);
                } else {
#pragma unroll
                    for (int i = 0; i < 4; i++) {
                        const uint4 q = lds128(SM_XOWN + (tid - 256) * 16 + i * 4096);
                        w[i][0] = q.x; w[i][1] = q.y; w[i][2] = q.z; w[i][3] = q.w;
                    }
                    unsigned it = 0;
                    while (true) {
                        bool ok = true;
#pragma unroll
                        for (int i = 0; i < 16; i++) ok = ok && w[i >> 2][i & 3] != 0;
                        if (__all_sync(0xffffffffu, ok) || ++it > SPIN_LIMIT) break;
#pragma unroll
                        for (int i = 0; i < 4; i++) ld_unit(w[i], inbox + i * 256);
                    }
#pragma unroll
                    for (int i = 0; i < 16; i++) w[i >> 2][i & 3] = ~w[i >> 2][i & 3];
                }
            }
            if (conv == 0) {
                bar_sync(3, 256);
                if (nw == 0) sts128(SM_ACT + 2 * ROW_BYTES + (lane >> 1) * CH_PITCH + (lane & 1) * 16, make_uint4(0, 0, 0, 0));
            }
            if (tid == 256) TL(24 + conv * 4);
            norm_block<0, 2>(w, cf, act_off + 2 * ROW_BYTES, has_outer ? ~0u : 0u, fbar + 128, lane);
            if (tid == 256) TL(88 + conv);
            norm_block<2, 2>(w, cf, act_off + 2 * ROW_BYTES, has_outer ? ~0u : 0u, fbar + 128, lane);
            if (tid == 256) TL(23 + conv * 4);
        }
        if (has_outer) {
            mbar_wait(BAR(BAR_FULL + NSTAGE - 1), 1);
#pragma unroll
            for (int i = 0; i < 4; i++) inbox[i * 256] = make_uint4(0, 0, 0, 0);
        }
        {
            const int oc0 = (tid - 256) >> 3, seg = lane & 7;
            __nv_bfloat16* dst = out + ((size_t)(b * C + oc0) * HW + r) * HW + seg * 8;
            const uint32_t src = SM_XOWN + oc0 * 128 + ((seg ^ (oc0 & 7)) << 4);
            bar_sync(6, 128 + 256);
#pragma unroll
            for (int i = 0; i < 4; i++) *reinterpret_cast<uint4*>(dst + (size_t)i * 32 * HW * HW) = lds128(src + i * 4096);
            if (tid == 256) { TL(20); TLG(21); }
        }
    } else if (warp < 4) {
        const int wq = warp;
        bar_sync(2, 128);

        const uint32_t xbase = SM_XOWN + ((lane >> 4) * 8 + (lane & 7)) * 128 + (((2 * wq + ((lane >> 3) & 1)) ^ (lane & 7)) << 4);
        float d[64];
#pragma unroll
        for (int i = 0; i < 64; i++) d[i] = 0.f;
#pragma unroll 1
        for (int conv = 0; conv < 2; conv++) {
            fence_acc(d);
            mma_stages<0>(d, conv, tid, gs);
            if (conv == 0) {
                asm volatile("wgmma.fence.sync.aligned;" ::: "memory");
                wgmma128<(SM_ONES >> 4) | (8u << 16), (SM_EMB >> 4), 0, 8>(d);
                asm volatile("wgmma.commit_group.sync.aligned;" ::: "memory");
            }
            asm volatile("wgmma.wait_group.sync.aligned 0;" ::: "memory");
            fence_acc(d);
            if (tid == 0) TL(10 + conv * 8);
            uint32_t hp[32];
#pragma unroll
            for (int i = 0; i < 32; i++) hp[i] = pack_bf(d[2 * i], d[2 * i + 1]);
            if (conv == 1) {
#pragma unroll
                for (int kc = 0; kc < 8; kc++) stsm4t(xbase + kc * 2048, hp[4 * kc], hp[4 * kc + 1], hp[4 * kc + 2], hp[4 * kc + 3]);
                bar_arrive(6, 128 + 256);
                break;
            }
#pragma unroll
            for (int g = 0; g < 4; g++) {
                float c[4] = {0.f, 0.f, 0.f, 0.f};
#pragma unroll
                for (int i = 0; i < 4; i++) stat_mma(c, hp[8 * g + 2 * i], hp[8 * g + 2 * i + 1]);
                stat_store(c, SM_RED + (g * 4 + wq) * 48, lane);
            }
            bar_sync(2, 128);
            if (wq == 0) stat_publish(SM_RED, &gs->acc2[b * LS], lane, true);
            if (tid == 0) TL(11);
            const uint32_t hbase = SM_ACT + (lane >> 4) * CH_PITCH + (2 + wq * 16 + (lane & 15)) * 16;
#pragma unroll
            for (int kc = 0; kc < 8; kc++) stsm4(hbase + kc * 2 * CH_PITCH, hp[4 * kc], hp[4 * kc + 1], hp[4 * kc + 2], hp[4 * kc + 3]);
            __syncwarp();
            if (lane == 0) mbar_arrive(BAR(BAR_HW));
            if (lane < LAG) mbar_arrive(BAR(BAR_WEMPTY + (NSTAGE - LAG) % NS) + 8 * lane);
            if (has_outer) {
                uint4* outbox = gs->box + (cta + ((r & 1) ? 1 : -1)) * 1024 + tid;
#pragma unroll
                for (int kc = 0; kc < 8; kc++) outbox[kc * 128] = make_uint4(~hp[4 * kc], ~hp[4 * kc + 1], ~hp[4 * kc + 2], ~hp[4 * kc + 3]);
            }
            if (tid == 0) TL(12);
#pragma unroll
            for (int kc = 0; kc < 8; kc++) {
                uint32_t p[4];
                ldsm4t(p, xbase + kc * 2048);
#pragma unroll
                for (int i = 0; i < 4; i++) { d[8 * kc + 2 * i] = bf_lo(p[i]); d[8 * kc + 2 * i + 1] = bf_hi(p[i]); }
            }
            fence_async_smem();
            __syncwarp();
            if (lane == 0) mbar_arrive(BAR(BAR_XFREE));
        }
        {
        }
    } else if (warp < 6) {
        bar_sync(5, 96);
        if (warp == 5) {
            asm volatile("barrier.cluster.wait.acquire.aligned;" ::: "memory");
            const uint32_t peer = (r & 1) ^ 1;
            const uint32_t self0 = mapa(0, r & 1), peer0 = mapa(0, peer);
#pragma unroll 1
            for (int conv = 0; conv < 2; conv++) {
#pragma unroll 1
                for (int kc = 0; kc < 8; kc++) {
                    mbar_wait(BAR(BAR_FULL) + 8 * kc, conv);
                    if (elect_one())
                        asm volatile("cp.async.bulk.shared::cluster.shared::cta.mbarrier::complete_tx::bytes [%0], [%1], %2, [%3];"
                                     ::"r"(peer0 + SM_ACT + ROW_BYTES + kc * KC_BYTES), "r"(self0 + SM_ACT + kc * KC_BYTES), "r"(KC_BYTES),
                                       "r"(peer0 + BAR(BAR_FULL + 8) + 8 * kc) : "memory");
                }
                if (lane == 0) TL(86 + conv);
#pragma unroll 1
                for (int kc = 0; kc < 8; kc++) mbar_wait(BAR(BAR_FULL + 8) + 8 * kc, conv);
                if (lane == 0)
                    asm volatile("mbarrier.arrive.release.cluster.shared::cluster.b64 _, [%0];" ::"r"(peer0 + (conv ? BAR(BAR_ACK) : BAR(BAR_EMB))) : "memory");
            }
            mbar_wait(BAR(BAR_ACK), 0);
        } else {
            if (has_outer && elect_one()) {
                mbar_expect(BAR(BAR_X + 4), 16384);
#pragma unroll
                for (int i = 0; i < 4; i++) tma_x(SM_XOUT + i * 4096, &xmap, r + ((r & 1) ? 1 : -1), b * C + i * 32, BAR(BAR_X + 4));
            }
            __syncwarp();
            mbar_wait(BAR(BAR_STATS), 0);
            unsigned it = 0;
            while (ld_relaxed(&gs->wcnt[(2 * NB + b) * LS]) < (unsigned)NXTRA && ++it < SPIN_LIMIT) __nanosleep(100);
            fence_acquire();
            float ev[4] = {0.f, 0.f, 0.f, 0.f};
#pragma unroll
            for (int j = 0; j < NXTRA; j++) {
                const uint4 ef = ld_relaxed_v4(&gs->emb[(j * NB + b) * C + lane * 4]);
                ev[0] += __uint_as_float(ef.x); ev[1] += __uint_as_float(ef.y); ev[2] += __uint_as_float(ef.z); ev[3] += __uint_as_float(ef.w);
            }
#pragma unroll
            for (int i = 0; i < 4; i++) {
                const float hi = bf_lo(pack_bf(ev[i], 0.f));
                sts128(SM_EMB + (lane * 4 + i) * 16, make_uint4(pack_bf(hi, ev[i] - hi), 0, 0, 0));
            }
            fence_async_smem();
            __syncwarp();
            if (lane == 0) { mbar_arrive(BAR(BAR_EMB)); TL(19); }
        }
    } else if (warp == 6) {
        bar_sync(0, 96);
        const uint32_t ebytes = STAGE_BYTES + ((lane >> 3) == 1 ? KC_BYTES : 0);
        if (lane < NSTAGE) mbar_expect(BAR(BAR_FULL) + 8 * lane, ebytes);
        const int swap = (r & 1) ? 0 : 8 * STAGE_BYTES;
        unsigned it = 0;
        {
            int g = 0;
#pragma unroll 1
            while (g < NS) {
                unsigned ready = __ballot_sync(0xffffffffu, ld_relaxed(&gs->wcnt[b * LS + (lane & 7)]) >= 16u) >> g;
                if (++it > SPIN_LIMIT) ready = ~0u;
                if (!(ready & 1)) continue;
                fence_acquire();
                fence_async_global();
                if (lane == 0) TL(g ? 3 : 6);
#pragma unroll 1
                for (; (ready & 1) && g < NS; g++, ready >>= 1)
                    if (elect_one())
                        bulk_g2s(S0 + SM_W + g * STAGE_BYTES, gs->wt + g * STAGE_BYTES + (g >= 8 ? swap : 0), STAGE_BYTES, S0 + BAR(BAR_FULL) + 8 * g);
            }
        }
#pragma unroll 1
        for (int q = 3; q < 12; q++) {
            const int conv = q >= 6, qs = conv ? q - 6 : q, sl = q % 3;
            const unsigned char* wsrc = gs->wt + q * 4 * STAGE_BYTES + (qs < 2 ? 0 : (qs < 4 ? swap : -swap));
            const uint32_t par = (q / 3 - 1) & 1;
            if (q == 6) {
                it = 0;
                while (ld_relaxed(&gs->wcnt[(NB + b) * LS]) < (unsigned)NCTA && ++it < SPIN_LIMIT) {}
                fence_acquire();
                fence_async_global();
                if (lane == 0) { mbar_arrive(BAR(BAR_EMB)); TL(2); }
            }
#pragma unroll
            for (int i = 0; i < 4; i++) {
                mbar_wait(BAR(BAR_WEMPTY + i) + 32 * sl, par);
                if (i == 0 && (q == 6 || q == 9)) {
                    if ((lane >= NS) == (q == 9) && lane < NSTAGE) mbar_expect(BAR(BAR_FULL) + 8 * lane, ebytes);
                    __syncwarp();
                }
                if (elect_one())
                    bulk_g2s(S0 + SM_W + (sl * 4 + i) * STAGE_BYTES, wsrc + i * STAGE_BYTES, STAGE_BYTES, S0 + BAR(BAR_FULL + i) + 32 * qs);
            }
        }
    } else {
        const uint2 ga1 = __ldg(reinterpret_cast<const uint2*>(g1) + lane), bt1 = __ldg(reinterpret_cast<const uint2*>(be1) + lane);
        const uint2 ga2 = __ldg(reinterpret_cast<const uint2*>(g2) + lane), bt2 = __ldg(reinterpret_cast<const uint2*>(be2) + lane);
        if (lane < 8) sts128(SM_GST + lane * 16, make_uint4(0, 0, 0, 0));
        sts128f(SM_COEF + lane * 32, make_float4(0.5f * bf_lo(ga1.x), 0.5f * bf_hi(ga1.x), 0.5f * bf_lo(bt1.x), 0.5f * bf_hi(bt1.x)));
        sts128f(SM_COEF + lane * 32 + 16, make_float4(0.5f * bf_lo(ga1.y), 0.5f * bf_hi(ga1.y), 0.5f * bf_lo(bt1.y), 0.5f * bf_hi(bt1.y)));
        sts128f(SM_COEF + 1024 + lane * 32, make_float4(0.5f * bf_lo(ga2.x), 0.5f * bf_hi(ga2.x), 0.5f * bf_lo(bt2.x), 0.5f * bf_hi(bt2.x)));
        sts128f(SM_COEF + 1024 + lane * 32 + 16, make_float4(0.5f * bf_lo(ga2.y), 0.5f * bf_hi(ga2.y), 0.5f * bf_lo(bt2.y), 0.5f * bf_hi(bt2.y)));
        bar_arrive(4, 256 + 64 + 128);
        bar_sync(0, 96);
#pragma unroll 1
        for (int conv = 0; conv < 2; conv++) {
            if (conv == 1) {
                mbar_wait(BAR(BAR_HW), 0);
                const unsigned c1 = clock32();
                while (clock32() - c1 < PD2) {}
            } else {
                while (clock32() - clk0 < PD) {}
            }
            const float* asrc = conv ? &gs->acc2[b * LS + (lane & 3) * 4] : &gs->acc1[b * 4 * LS + (lane & 3) * GS1];
            unsigned it = 0;
            uint4 fq[NPOLL];
#pragma unroll
            for (int i = 0; i < NPOLL; i++) {
                fq[i] = ld_relaxed_v4(asrc);
                if (i + 1 < NPOLL) { const unsigned c1 = clock32(); while (clock32() - c1 < 450 / NPOLL) {} }
            }
            bool all = false;
#pragma unroll 1
            while (!all) {
#pragma unroll
                for (int i = 0; i < NPOLL; i++) {
                    const uint4 f = fq[i];
                    const bool ok = ((f.x == 0x42800000u) & (f.w == 0x42800000u)) || it > SPIN_LIMIT;
                    if (ok && lane < 4) {
                        const float inv_n = 1.0f / (32.0f * HW * HW);
                        const float mean = __uint_as_float(f.y) * inv_n;
                        const float rs = rsqrtf(fmaxf(fmaf(-mean, mean, __uint_as_float(f.z) * inv_n), 0.f) + 1e-5f);
                        asm volatile("st.shared.v2.f32 [%0], {%1,%2};" ::"r"(S0 + SM_GST + conv * 32 + lane * 8), "f"(rs == 0.f ? 1e-38f : rs), "f"(mean * rs) : "memory");
                    }
                    if (__all_sync(0xffffffffu, ok)) { all = true; break; }
                    fq[i] = ld_relaxed_v4(asrc);
                }
                it++;
            }
            if (lane == 0) { mbar_arrive(BAR(BAR_STATS)); TL(7 + conv * 8); }
        }
        mbar_wait(BAR(BAR_XFREE), 0);
        if (has_outer && elect_one()) {
            mbar_expect(BAR(BAR_X + 4), 16384);
            bulk_g2s(S0 + SM_XOWN, gs->box + cta * 1024, 16384, S0 + BAR(BAR_X + 4));
        }
        if (r == 0) {
            if (lane < 16) gs->acc1[b * 4 * LS + (lane >> 2) * GS1 + (lane & 3)] = 0.f;
            if (lane < 24) gs->wcnt[((lane >> 3) * NB + b) * LS + (lane & 7)] = 0;
        }
    }
}

}

extern "C" void kernel_launch(void* const* d_in, const int* in_sizes, int n_in, void* d_out, int out_size) {
    (void)in_sizes; (void)n_in; (void)out_size;
    typedef CUresult (*EncodeFn)(CUtensorMap*, CUtensorMapDataType, cuuint32_t, void*, const cuuint64_t*, const cuuint64_t*,
                                 const cuuint32_t*, const cuuint32_t*, CUtensorMapInterleave, CUtensorMapSwizzle,
                                 CUtensorMapL2promotion, CUtensorMapFloatOOBfill);
    static Scratch* gs = nullptr;
    static EncodeFn encode = nullptr;
    if (!gs) {
        cudaFuncSetAttribute(resblock_kernel, cudaFuncAttributeMaxDynamicSharedMemorySize, SM_TOTAL);
        cudaGetSymbolAddress((void**)&gs, g_scratch);
        cudaDriverEntryPointQueryResult qr;
        cudaGetDriverEntryPoint("cuTensorMapEncodeTiled", (void**)&encode, cudaEnableDefault, &qr);
    }
    CUtensorMap xmap;
    const cuuint64_t dims[3] = {HW, HW, NB * C}, strides[2] = {HW * 2, HW * HW * 2};
    const cuuint32_t box[3] = {HW, 1, 32}, es[3] = {1, 1, 1};
    encode(&xmap, CU_TENSOR_MAP_DATA_TYPE_BFLOAT16, 3, d_in[0], dims, strides, box, es, CU_TENSOR_MAP_INTERLEAVE_NONE,
           CU_TENSOR_MAP_SWIZZLE_128B, CU_TENSOR_MAP_L2_PROMOTION_NONE, CU_TENSOR_MAP_FLOAT_OOB_FILL_NONE);
    resblock_kernel<<<NCTA + NXTRA, NTHREADS, SM_TOTAL>>>(
        (const __nv_bfloat16*)d_in[4], (const __nv_bfloat16*)d_in[1],
        (const __nv_bfloat16*)d_in[2], (const __nv_bfloat16*)d_in[3], (const __nv_bfloat16*)d_in[5],
        (const __nv_bfloat16*)d_in[6], (const __nv_bfloat16*)d_in[7], (const __nv_bfloat16*)d_in[8],
        (__nv_bfloat16*)d_out, gs, xmap);
}
```

```cpp
#include <cuda_runtime.h>
#include <cuda.h>
#include <cuda_bf16.h>
#include <stdint.h>

namespace {

constexpr int C = 128, HW = 64, NB = 2, E = 768;
constexpr int NCTA = NB * HW;
constexpr int NXTRA = 4;
constexpr int NTHREADS = 16 * 32;
constexpr int CH_PITCH = 66 * 16;
constexpr int ROW_BYTES = 16 * CH_PITCH;
constexpr int STEP_BYTES = 4096;
constexpr int STAGE_BYTES = 3 * STEP_BYTES;
constexpr int NSTAGE = 24;
constexpr int KC_BYTES = 2 * CH_PITCH;
constexpr int NS = 12;
constexpr int LAG = 1;
#define XDELAY 400
#define HDELAY 600
#define SEQ 0
#define MMA0_WAIT mbar_try
#define SPINPAUSE
#define NPOLL 1
#define PD2 0
#define ODELAY 100
#define NCPA 2
#define PDELAY 60
#define RB 1
#define XSTAG2 400
#define XSTAG 800
#define HSEND 0
#define W2DELAY 1800

constexpr uint32_t SMEM_BASE = 0x400;
constexpr uint32_t SM_XOWN = SMEM_BASE;
constexpr uint32_t SM_ACT = SM_XOWN + 16384 + 512;
constexpr uint32_t SM_XOUT = SM_ACT + 2 * ROW_BYTES + 512;
static_assert(SM_XOUT % 1024 == 0, "swizzle atom alignment");
constexpr uint32_t SM_W = SM_ACT + 3 * ROW_BYTES + 128;
__host__ __device__ constexpr uint32_t slot_addr(int slot) { return SM_W + slot * STAGE_BYTES; }
constexpr uint32_t SM_COEF = SM_W + NS * STAGE_BYTES;
constexpr uint32_t SM_GST = SM_COEF + 2048;
constexpr uint32_t SM_EMB = SM_GST + 128;
constexpr uint32_t SM_ONES = SM_EMB + 2048;
constexpr uint32_t SM_RED = SM_ONES + 256;
constexpr uint32_t SM_BNC = SM_RED + 1536;
constexpr uint32_t SM_BAR = SM_BNC + 2 * 2304;
constexpr int BAR_FULL = 0, BAR_WEMPTY = NSTAGE, BAR_HW = BAR_WEMPTY + NS, BAR_XFREE = BAR_HW + 1, BAR_STATS = BAR_XFREE + 1,
              BAR_EMB = BAR_STATS + 1, BAR_ACK = BAR_EMB + 1, BAR_X = BAR_ACK + 1  , NBAR = BAR_X + 5;
constexpr int SM_TOTAL = SM_BAR + NBAR * 8 - SMEM_BASE;
static_assert(SM_TOTAL <= 232448, "smem");
static_assert(NBAR <= 96, "barrier init");
__host__ __device__ constexpr uint32_t BAR(int i) { return SM_BAR + 8 * i; }
__host__ __device__ constexpr int ky_of(int kyo) { return kyo == 0 ? 1 : (kyo == 1 ? 0 : 2); }

constexpr unsigned SPIN_LIMIT = 1u << 16;

#define LS 1056
#define GS1 4
#define PD 0
struct Scratch {
    float acc1[NB * 4 * LS];
    float acc2[NB * LS];
    unsigned wcnt[3 * NB * LS];
    float emb[NXTRA * NB * C];
    unsigned char wt[2 * NSTAGE * STAGE_BYTES];
    uint4 box[NCTA * 1024];
};
__device__ __align__(1024) Scratch g_scratch;
#define TL(i) do {} while (0)
#define TLG(i) do {} while (0)

__device__ __forceinline__ unsigned clock32() { unsigned c; asm volatile("mov.u32 %0, %%clock;" : "=r"(c)); return c; }
__device__ __forceinline__ uint32_t mapa(uint32_t a, uint32_t rank) {
    uint32_t d;
    asm("mapa.shared::cluster.u32 %0, %1, %2;" : "=r"(d) : "r"(a), "r"(rank));
    return d;
}
#define S0 mapa(0, blockIdx.x & 1)
__device__ __forceinline__ void mbar_init(uint32_t bar, int cnt) {
    asm volatile("mbarrier.init.shared::cta.b64 [%0], %1;" ::"r"(bar + S0), "r"(cnt) : "memory");
}
__device__ __forceinline__ void mbar_arrive(uint32_t bar) {
    asm volatile("mbarrier.arrive.shared::cta.b64 _, [%0];" ::"r"(bar + S0) : "memory");
}
__device__ __forceinline__ void mbar_expect(uint32_t bar, uint32_t bytes) {
    asm volatile("mbarrier.arrive.expect_tx.shared::cta.b64 _, [%0], %1;" ::"r"(bar + S0), "r"(bytes) : "memory");
}
__device__ __forceinline__ bool mbar_try(uint32_t bar, uint32_t par) {
    uint32_t ok;
    asm volatile("{\n.reg .pred p;\nmbarrier.try_wait.parity.shared::cta.b64 p, [%1], %2;\nselp.u32 %0, 1, 0, p;\n}"
                 : "=r"(ok) : "r"(bar + S0), "r"(par) : "memory");
    return ok;
}
__device__ __forceinline__ bool mbar_test(uint32_t bar, uint32_t par) {
    uint32_t ok;
    asm volatile("{\n.reg .pred p;\nmbarrier.test_wait.parity.shared::cta.b64 p, [%1], %2;\nselp.u32 %0, 1, 0, p;\n}"
                 : "=r"(ok) : "r"(bar + S0), "r"(par) : "memory");
    return ok;
}
__device__ __forceinline__ void mbar_wait(uint32_t bar, uint32_t par) {
    unsigned it = 0;
#pragma unroll 1
    while (!mbar_try(bar, par) && ++it < SPIN_LIMIT) {}
}
__device__ __forceinline__ bool elect_one() {
    uint32_t p;
    asm volatile("{\n.reg .pred p;\nelect.sync _|p, 0xffffffff;\nselp.u32 %0, 1, 0, p;\n}" : "=r"(p));
    return p;
}
__device__ __forceinline__ void fence_async_smem() { asm volatile("fence.proxy.async.shared::cta;" ::: "memory"); }
__device__ __forceinline__ void fence_async_global() { asm volatile("fence.proxy.async.global;" ::: "memory"); }
__device__ __forceinline__ void fence_acquire() { asm volatile("fence.acquire.gpu;" ::: "memory"); }
__device__ __forceinline__ void bar_sync(int id, int n) { asm volatile("bar.sync %0, %1;" ::"r"(id), "r"(n) : "memory"); }
__device__ __forceinline__ void bar_arrive(int id, int n) { asm volatile("bar.arrive %0, %1;" ::"r"(id), "r"(n) : "memory"); }
__device__ __forceinline__ void bulk_g2s(uint32_t dst, const void* src, uint32_t bytes, uint32_t bar) {
    asm volatile("cp.async.bulk.shared::cluster.global.mbarrier::complete_tx::bytes [%0], [%1], %2, [%3];"
                 ::"r"(dst), "l"(src), "r"(bytes), "r"(bar) : "memory");
}
__device__ __forceinline__ void tma_x(uint32_t dst, const CUtensorMap* tm, int row, int ch, uint32_t bar) {
    asm volatile("cp.async.bulk.tensor.3d.shared::cluster.global.mbarrier::complete_tx::bytes [%0], [%1, {%2, %3, %4}], [%5];"
                 ::"r"(dst + S0), "l"(tm), "r"(0), "r"(row), "r"(ch), "r"(bar + S0) : "memory");
}
__device__ __forceinline__ uint4 ld_relaxed_v4(const void* p) {
    uint4 v;
    asm volatile("ld.relaxed.gpu.global.v4.u32 {%0,%1,%2,%3}, [%4];" : "=r"(v.x), "=r"(v.y), "=r"(v.z), "=r"(v.w) : "l"(p) : "memory");
    return v;
}
__device__ __forceinline__ unsigned ld_relaxed(const void* p) {
    unsigned v;
    asm volatile("ld.relaxed.gpu.global.u32 %0, [%1];" : "=r"(v) : "l"(p) : "memory");
    return v;
}
__device__ __forceinline__ void red_add4(float* p, float a, float b, float c, float d) {
    asm volatile("red.relaxed.gpu.global.add.v4.f32 [%0], {%1,%2,%3,%4};" ::"l"(p), "f"(a), "f"(b), "f"(c), "f"(d) : "memory");
}
__device__ __forceinline__ void sts128(uint32_t a, uint4 v) {
    asm volatile("st.shared.v4.u32 [%0], {%1,%2,%3,%4};" ::"r"(a + S0), "r"(v.x), "r"(v.y), "r"(v.z), "r"(v.w) : "memory");
}
__device__ __forceinline__ void sts128f(uint32_t a, float4 v) {
    asm volatile("st.shared.v4.f32 [%0], {%1,%2,%3,%4};" ::"r"(a + S0), "f"(v.x), "f"(v.y), "f"(v.z), "f"(v.w) : "memory");
}
__device__ __forceinline__ void sts32f(uint32_t a, float v) { asm volatile("st.shared.f32 [%0], %1;" ::"r"(a + S0), "f"(v) : "memory"); }
__device__ __forceinline__ uint4 lds128(uint32_t a) {
    uint4 v;
    asm volatile("ld.shared.v4.u32 {%0,%1,%2,%3}, [%4];" : "=r"(v.x), "=r"(v.y), "=r"(v.z), "=r"(v.w) : "r"(a + S0) : "memory");
    return v;
}
__device__ __forceinline__ float4 lds128f(uint32_t a) {
    float4 v;
    asm volatile("ld.shared.v4.f32 {%0,%1,%2,%3}, [%4];" : "=f"(v.x), "=f"(v.y), "=f"(v.z), "=f"(v.w) : "r"(a + S0) : "memory");
    return v;
}
__device__ __forceinline__ float2 lds64f(uint32_t a) {
    float2 v;
    asm volatile("ld.shared.v2.f32 {%0,%1}, [%2];" : "=f"(v.x), "=f"(v.y) : "r"(a + S0) : "memory");
    return v;
}
__device__ __forceinline__ float bf_lo(uint32_t u) { return __uint_as_float(u << 16); }
__device__ __forceinline__ float bf_hi(uint32_t u) { return __uint_as_float(u & 0xffff0000u); }
__device__ __forceinline__ uint32_t pack_bf(float lo, float hi) {
    uint32_t r;
    asm("cvt.rn.bf16x2.f32 %0, %1, %2;" : "=r"(r) : "f"(hi), "f"(lo));
    return r;
}
__device__ __forceinline__ float tanh_fast(float x) {
    float r;
    asm("tanh.approx.f32 %0, %1;" : "=f"(r) : "f"(x));
    return r;
}
__device__ __forceinline__ float silu_half(float h) { return fmaf(h, tanh_fast(h), h); }
__device__ __forceinline__ void ldsm4(uint32_t (&u)[4], uint32_t a) {
    asm volatile("ldmatrix.sync.aligned.m8n8.x4.shared.b16 {%0,%1,%2,%3}, [%4];"
                 : "=r"(u[0]), "=r"(u[1]), "=r"(u[2]), "=r"(u[3]) : "r"(a + S0) : "memory");
}
__device__ __forceinline__ void ldsm4t(uint32_t (&u)[4], uint32_t a) {
    asm volatile("ldmatrix.sync.aligned.m8n8.x4.trans.shared.b16 {%0,%1,%2,%3}, [%4];"
                 : "=r"(u[0]), "=r"(u[1]), "=r"(u[2]), "=r"(u[3]) : "r"(a + S0) : "memory");
}
__device__ __forceinline__ void stsm4(uint32_t a, uint32_t p0, uint32_t p1, uint32_t p2, uint32_t p3) {
    asm volatile("stmatrix.sync.aligned.m8n8.x4.shared.b16 [%0], {%1,%2,%3,%4};" ::"r"(a + S0), "r"(p0), "r"(p1), "r"(p2), "r"(p3) : "memory");
}
__device__ __forceinline__ void stsm4t(uint32_t a, uint32_t p0, uint32_t p1, uint32_t p2, uint32_t p3) {
    asm volatile("stmatrix.sync.aligned.m8n8.x4.trans.shared.b16 [%0], {%1,%2,%3,%4};" ::"r"(a + S0), "r"(p0), "r"(p1), "r"(p2), "r"(p3) : "memory");
}

#define R8(o) "+f"(d[o]), "+f"(d[o + 1]), "+f"(d[o + 2]), "+f"(d[o + 3]), "+f"(d[o + 4]), "+f"(d[o + 5]), "+f"(d[o + 6]), "+f"(d[o + 7])
template <uint32_t ALO, uint32_t BLO, uint64_t AHI = 8, uint64_t BHI = 48>
__device__ __forceinline__ void wgmma128(float (&d)[64]) {
    asm volatile(
        "wgmma.mma_async.sync.aligned.m64n128k16.f32.bf16.bf16 "
        "{%0,%1,%2,%3,%4,%5,%6,%7,%8,%9,%10,%11,%12,%13,%14,%15,%16,%17,%18,%19,%20,%21,%22,%23,%24,%25,%26,%27,%28,%29,%30,%31,"
        "%32,%33,%34,%35,%36,%37,%38,%39,%40,%41,%42,%43,%44,%45,%46,%47,%48,%49,%50,%51,%52,%53,%54,%55,%56,%57,%58,%59,%60,%61,%62,%63},"
        " %64, %65, 1, 1, 1, 0, 0;"
        : R8(0), R8(8), R8(16), R8(24), R8(32), R8(40), R8(48), R8(56)
        : "l"((AHI << 32) | ALO), "l"((BHI << 32) | BLO));
}
template <int S>
__device__ __forceinline__ void mma_stages(float (&d)[64], int conv, int tid, Scratch* gs) {
    constexpr uint32_t A = ((SM_ACT + S * 2 * CH_PITCH + 16) >> 4) | ((CH_PITCH >> 4) << 16);
    constexpr uint32_t B = (slot_addr(S % NS) >> 4) | (8u << 16);
    if (S == 0) {
        unsigned it = 0;
#pragma unroll 1
        while (!MMA0_WAIT(BAR(BAR_FULL), conv) && ++it < SPIN_LIMIT) {}
    }
    bool next_ok = true;
    constexpr uint32_t NEXT = S + 1 < NSTAGE ? BAR(BAR_FULL + S + 1) : BAR(BAR_EMB);
    const int npar = S + 1 < NSTAGE ? conv : 0;
    next_ok = mbar_test(NEXT, npar);
    if (S == 0 && tid == 0) TL(32 + conv * 24);
    asm volatile("wgmma.fence.sync.aligned;" ::: "memory");
    wgmma128<A, B>(d);
    wgmma128<A + 1, B + 16>(d);
    wgmma128<A + 2, B + 32>(d);
    asm volatile("wgmma.commit_group.sync.aligned;" ::: "memory");
    if (S >= LAG) {
        asm volatile("wgmma.wait_group.sync.aligned %0;" ::"n"(LAG) : "memory");
        if ((tid & 31) == 0) mbar_arrive(BAR(BAR_WEMPTY + (S + NS - LAG) % NS));
    }
    if (!next_ok) mbar_wait(NEXT, npar);
    if constexpr (S + 1 < NSTAGE) mma_stages<S + 1>(d, conv, tid, gs);
}

__device__ __forceinline__ void weight_load(uint4 (&t)[5], const __nv_bfloat16* w, int cta, int lane) {
    const char* base = reinterpret_cast<const char*>(w) + ((cta & 15) * 8 * C + (cta >> 4) * 16) * 18;
#pragma unroll
    for (int k = 0; k < 5; k++) {
        const int i = lane + 32 * k, row = (i * 57) >> 10;
        if (k < 4 || lane < 16) t[k] = __ldg(reinterpret_cast<const uint4*>(base + row * (C * 18 - 288) + i * 16));
    }
}
__device__ __forceinline__ void weight_block(uint32_t bounce, unsigned char* wt, int cta, int lane, bool readback, Scratch* gs) {
    unsigned char* dst = wt + (cta >> 4) * STAGE_BYTES + (cta & 15) * 768;
    if (lane < 16) {
        uint32_t v[36];
#pragma unroll
        for (int i = 0; i < 9; i++) {
            const uint4 q = lds128(bounce + (lane & 7) * 288 + (lane >> 3) * 144 + i * 16);
            v[4 * i] = q.x; v[4 * i + 1] = q.y; v[4 * i + 2] = q.z; v[4 * i + 3] = q.w;
        }
#pragma unroll
        for (int kyo = 0; kyo < 3; kyo++) {
#pragma unroll
            for (int kx = 0; kx < 3; kx++) {
                const int tap = ky_of(kyo) * 3 + kx;
                uint32_t o[4];
#pragma unroll
                for (int m = 0; m < 4; m++) {
                    const int i0 = 18 * m + tap, i1 = i0 + 9;
                    const uint32_t sel = ((i0 & 1) ? 0x32u : 0x10u) | ((i1 & 1) ? 0x7600u : 0x5400u);
                    o[m] = __byte_perm(v[i0 >> 1], v[i1 >> 1], sel);
                }
                *reinterpret_cast<uint4*>(dst + kyo * 8 * STAGE_BYTES + kx * 256 + lane * 16) = make_uint4(o[0], o[1], o[2], o[3]);
            }
        }
    }
    if (readback) {
        __syncwarp();
        unsigned acc = 0;
        if (lane < 24) {
#pragma unroll
            for (int i = 0; i < 3; i++) acc |= ld_relaxed(dst + i * 8 * STAGE_BYTES + lane * 32);
        }
        asm volatile("{\n.reg .pred p;\nsetp.eq.u32 p, %0, 0x9e3779b9;\n@p st.shared.u32 [%1], %0;\n}" ::"r"(acc), "r"(bounce + S0) : "memory");
    }
}
__device__ __forceinline__ uint32_t act2(uint32_t u, const float4& cf) {
    return pack_bf(silu_half(fmaf(bf_lo(u), cf.x, cf.z)), silu_half(fmaf(bf_hi(u), cf.y, cf.w)));
}
__device__ __forceinline__ void norm_unit(uint32_t (&u)[4], const float4& ca, const float4& cb) {
    u[0] = act2(u[0], ca); u[1] = act2(u[1], ca); u[2] = act2(u[2], cb); u[3] = act2(u[3], cb);
}
__device__ __forceinline__ void read_stats(uint32_t gst, float (&g)[8]) {
    asm volatile("ld.volatile.shared.v4.f32 {%0,%1,%2,%3}, [%4];" : "=f"(g[0]), "=f"(g[1]), "=f"(g[2]), "=f"(g[3]) : "r"(gst + S0) : "memory");
    asm volatile("ld.volatile.shared.v4.f32 {%0,%1,%2,%3}, [%4];" : "=f"(g[4]), "=f"(g[5]), "=f"(g[6]), "=f"(g[7]) : "r"(gst + 16 + S0) : "memory");
}
template <int T>
__device__ __forceinline__ void group_coefs(uint32_t gst, float (&g)[8], float4 (&cf)[8]) {
    unsigned it = 0;
    if (!__all_sync(0xffffffffu, g[2 * T] != 0.f)) {
        float rs0;
#pragma unroll 1
        do {
            SPINPAUSE;
            asm volatile("ld.volatile.shared.f32 %0, [%1];" : "=f"(rs0) : "r"(gst + 8 * T + S0) : "memory");
        } while (!__all_sync(0xffffffffu, rs0 != 0.f) && ++it < 8 * SPIN_LIMIT);
        read_stats(gst, g);
    }
    float4 &ca = cf[2 * T], &cb = cf[2 * T + 1];
    const float rs = g[2 * T], mr = g[2 * T + 1];
    ca.z = fmaf(-mr, ca.x, ca.z); ca.w = fmaf(-mr, ca.y, ca.w); ca.x *= rs; ca.y *= rs;
    cb.z = fmaf(-mr, cb.x, cb.z); cb.w = fmaf(-mr, cb.y, cb.w); cb.x *= rs; cb.y *= rs;
}
template <int FIRST, int N>
__device__ __forceinline__ void norm_block(uint32_t (&u)[4][4], float4 (&cf)[8], uint32_t act, uint32_t mask, uint32_t fbar, int lane) {
#pragma unroll
    for (int t = FIRST; t < FIRST + N; t++) {
        norm_unit(u[t], cf[2 * t], cf[2 * t + 1]);
        stsm4(act + t * 2 * KC_BYTES, u[t][0] & mask, u[t][1] & mask, u[t][2] & mask, u[t][3] & mask);
    }
    fence_async_smem();
    __syncwarp();
    if (lane < N) mbar_arrive(fbar + 16 * (FIRST + lane));
}
__device__ __forceinline__ void publish(uint32_t bar, int lane) {
    fence_async_smem();
    __syncwarp();
    if (lane == 0) mbar_arrive(bar);
}
template <int T>
__device__ __forceinline__ void next_unit(uint32_t (&u)[4][4], float4 (&cf)[8], uint32_t gst, float (&g)[8], uint32_t act, uint32_t fbar, int lane) {
    const bool have = __all_sync(0xffffffffu, g[2 * T] != 0.f);
    if (!have) publish(fbar + 16 * (T - 1), lane);
    group_coefs<T>(gst, g, cf);
    norm_unit(u[T], cf[2 * T], cf[2 * T + 1]);
    if (have) publish(fbar + 16 * (T - 1), lane);
    stsm4(act + T * 2 * KC_BYTES, u[T][0], u[T][1], u[T][2], u[T][3]);
}
__device__ __forceinline__ void stat_mma(float (&c)[4], uint32_t p, uint32_t q) {
    asm("mma.sync.aligned.m16n8k16.row.col.f32.bf16.bf16.f32 {%0,%1,%2,%3}, {%4,%5,%6,%5}, {%4,%6}, {%0,%1,%2,%3};"
        : "+f"(c[0]), "+f"(c[1]), "+f"(c[2]), "+f"(c[3]) : "r"(p), "r"(0x3f803f80u), "r"(q));
}
__device__ __forceinline__ void stat_store(const float (&c)[4], uint32_t dst, int lane) {
    const int g = lane >> 2, t = lane & 3;
    if (t == (g >> 1)) sts32f(dst + g * 4, (g & 1) ? c[1] : c[0]);
    if (g == 7) sts32f(dst + 32 + t * 4, c[2] + c[3]);
}
__device__ __forceinline__ float sum4(float4 v) { return (v.x + v.y) + (v.z + v.w); }
__device__ __forceinline__ void stat_publish(uint32_t src, float* acc, int lane, bool real) {
    const uint32_t a = src + (lane & 15) * 48;
    float q = sum4(lds128f(a)) + sum4(lds128f(a + 16)), sm = sum4(lds128f(a + 32));
    q += __shfl_xor_sync(0xffffffffu, q, 1); sm += __shfl_xor_sync(0xffffffffu, sm, 1);
    q += __shfl_xor_sync(0xffffffffu, q, 2); sm += __shfl_xor_sync(0xffffffffu, sm, 2);
    if (real && (lane & 19) == 0) red_add4(acc + lane, 1.f, sm, q, 1.f);
}
__device__ __forceinline__ void fence_acc(float (&d)[64]) {
#pragma unroll
    for (int i = 0; i < 64; i++) asm volatile("" : "+f"(d[i])::"memory");
}
__device__ __forceinline__ void ld_unit(uint32_t (&u)[4], const uint4* p) {
    asm volatile("ld.relaxed.gpu.global.v4.u32 {%0,%1,%2,%3}, [%4];" : "=r"(u[0]), "=r"(u[1]), "=r"(u[2]), "=r"(u[3]) : "l"(p) : "memory");
}

__device__ __noinline__ void side_jobs(const __nv_bfloat16* __restrict__ t_emb, const __nv_bfloat16* __restrict__ w_emb,
                                       const __nv_bfloat16* __restrict__ w2, Scratch* __restrict__ gs, unsigned clk0) {
    const int tid = threadIdx.x, warp = tid >> 5, lane = tid & 31, j = blockIdx.x;
    float tv = 0.f;
    if (lane < 24) tv = __bfloat162float(t_emb[(lane / 12) * E + j * 192 + warp * 12 + lane % 12]);
    if (tid == 0) {
        mbar_init(BAR(0), 1);
        mbar_expect(BAR(0), 192 * C * 2);
        fence_async_smem();
        while (clock32() - clk0 < W2DELAY) {}
#pragma unroll
        for (int i = 0; i < 4; i++) bulk_g2s(S0 + SM_W + i * 12288, w_emb + (j * 192 + i * 48) * C, 12288, S0 + BAR(0));
    }
    if (j == 0 && tid < 32) gs->acc2[(tid >> 4) * LS + (tid & 15)] = 0.f;
    const float sv = silu_half(0.5f * tv);
    __syncthreads();
    mbar_wait(BAR(0), 0);
    float acc[8] = {0.f, 0.f, 0.f, 0.f, 0.f, 0.f, 0.f, 0.f};
#pragma unroll
    for (int i = 0; i < 12; i++) {
        const float2 wq = lds64f(SM_W + (warp * 12 + i) * 256 + lane * 8);
        const uint32_t wx = __float_as_uint(wq.x), wy = __float_as_uint(wq.y);
#pragma unroll
        for (int bb = 0; bb < 2; bb++) {
            const float sx = __shfl_sync(0xffffffffu, sv, bb * 12 + i);
            acc[4 * bb + 0] = fmaf(sx, bf_lo(wx), acc[4 * bb + 0]); acc[4 * bb + 1] = fmaf(sx, bf_hi(wx), acc[4 * bb + 1]);
            acc[4 * bb + 2] = fmaf(sx, bf_lo(wy), acc[4 * bb + 2]); acc[4 * bb + 3] = fmaf(sx, bf_hi(wy), acc[4 * bb + 3]);
        }
    }
    sts128f(SM_ACT + warp * 1024 + lane * 16, make_float4(acc[0], acc[1], acc[2], acc[3]));
    sts128f(SM_ACT + warp * 1024 + 512 + lane * 16, make_float4(acc[4], acc[5], acc[6], acc[7]));
    __syncthreads();
    if (tid < 128) {
        float2 sum = make_float2(0.f, 0.f);
#pragma unroll
        for (int w = 0; w < 16; w++) { const float2 p = lds64f(SM_ACT + w * 1024 + tid * 8); sum.x += p.x; sum.y += p.y; }
        *reinterpret_cast<float2*>(&gs->emb[j * NB * C + tid * 2]) = sum;
        bar_sync(1, 128);
        if (tid < 2) asm volatile("red.release.gpu.global.add.u32 [%0], 1;" ::"l"(&gs->wcnt[(2 * NB + tid) * LS]) : "memory");
    }
}

__global__ void __cluster_dims__(2, 1, 1) __launch_bounds__(NTHREADS, 1)
resblock_kernel(const __nv_bfloat16* __restrict__ w1, const __nv_bfloat16* __restrict__ x,
                const __nv_bfloat16* __restrict__ t_emb, const __nv_bfloat16* __restrict__ g1,
                const __nv_bfloat16* __restrict__ be1, const __nv_bfloat16* __restrict__ w_emb,
                const __nv_bfloat16* __restrict__ g2, const __nv_bfloat16* __restrict__ be2,
                const __nv_bfloat16* __restrict__ w2, __nv_bfloat16* __restrict__ out, Scratch* __restrict__ gs,
                const __grid_constant__ CUtensorMap xmap) {
    const unsigned clk0 = clock32();
    if (threadIdx.x == 480 && blockIdx.x >= NXTRA) TLG(1);
    const int tid = threadIdx.x, lane = tid & 31;
    const int cta = blockIdx.x - NXTRA, b = cta >> 6, r = cta & 63;
    uint4 v[5];
    if (tid < 32) weight_load(v, w1, cta & (NCTA - 1), lane);
    const int warp = __shfl_sync(0xffffffffu, tid >> 5, 0);
    if (cta < 0) { side_jobs(t_emb, w_emb, w2, gs, clk0); return; }

    if (warp != 3) asm volatile("barrier.cluster.arrive.relaxed.aligned;" ::: "memory");
    const bool has_outer = (r != 0) && (r != HW - 1);
    if (warp == 1 || warp == 2 || warp == 4 || warp == 5) {
        const int g = warp < 3 ? warp - 1 : warp - 2;
        if (elect_one()) {
            asm volatile("prefetch.tensormap [%0];" ::"l"(&xmap) : "memory");
            mbar_init(BAR(BAR_X) + 8 * g, g < NCPA ? 32 : 1);
            if (g >= NCPA) mbar_expect(BAR(BAR_X) + 8 * g, 4096);
            fence_async_smem();
        }
        __syncwarp();
        bar_arrive(4, 256 + 64 + 128);
        while (clock32() - clk0 < XDELAY + (g >> 1) * XSTAG + (g & 1) * XSTAG2) {}
        if (g < NCPA) {
            const char* src = reinterpret_cast<const char*>(x) + (uint32_t)(((b * C + g * 32 + (lane >> 3)) * HW + r) * HW * 2 + (lane & 7) * 16);
#pragma unroll
            for (int i = 0; i < 8; i++)
                asm volatile("cp.async.cg.shared.global [%0], [%1], 16;"
                             ::"r"(S0 + SM_XOWN + g * 4096 + i * 512 + (lane >> 3) * 128 + (((lane & 7) ^ ((lane >> 3) + 4 * (i & 1))) << 4)),
                               "l"(src + i * (4 * HW * HW * 2)) : "memory");
            asm volatile("cp.async.mbarrier.arrive.noinc.shared::cta.b64 [%0];" ::"r"(S0 + BAR(BAR_X) + 8 * g) : "memory");
        } else if (elect_one()) {
            tma_x(SM_XOWN + g * 4096, &xmap, r, b * C + g * 32, BAR(BAR_X) + 8 * g);
        }
        __syncwarp();
        mbar_wait(BAR(BAR_X) + 8 * g, 0);
        if (lane == 0) TL(70 + g);
        float c[8][4];
#pragma unroll
        for (int k = 0; k < 8; k++) {
            const uint4 q = lds128(SM_XOWN + g * 4096 + k * 512 + lane * 16);
            c[k][0] = c[k][1] = c[k][2] = c[k][3] = 0.f;
            stat_mma(c[k], q.x, q.y); stat_mma(c[k], q.z, q.w);
        }
#pragma unroll
        for (int i = 0; i < 4; i++) c[0][i] = ((c[0][i] + c[1][i]) + (c[2][i] + c[3][i])) + ((c[4][i] + c[5][i]) + (c[6][i] + c[7][i]));
        stat_store(c[0], SM_RED + g * 48, lane);
        __syncwarp();
        if (lane == 0) {
            const uint32_t a = SM_RED + g * 48;
            red_add4(&gs->acc1[b * 4 * LS + g * GS1], 1.f, sum4(lds128f(a + 32)), sum4(lds128f(a)) + sum4(lds128f(a + 16)), 1.f);
            TL(74 + g);
        }
    }
    if (warp == 3) {
            if (elect_one()) {
#pragma unroll
                for (int i = 0; i < NSTAGE; i++) mbar_init(BAR(BAR_FULL + i), (i >> 3) == 1 ? 1 : 5);
#pragma unroll
                for (int i = 0; i < NS + 2; i++) mbar_init(BAR(BAR_WEMPTY + i), 4);
#pragma unroll
                for (int i = BAR_STATS; i < BAR_X; i++) mbar_init(BAR(i), i == BAR_EMB ? 3 : 1);
                mbar_init(BAR(BAR_X + 4), 1);
                asm volatile("fence.mbarrier_init.release.cluster;" ::: "memory");
            }
            __syncwarp();
            fence_async_smem();
            bar_arrive(0, 96);
            bar_arrive(5, 96);
            bar_arrive(4, 256 + 64 + 128);
            const uint4 z = make_uint4(0, 0, 0, 0);
#pragma unroll
            for (int i = 0; i < 2; i++) sts128(SM_ACT + (i * 16 + (lane >> 1)) * CH_PITCH + (lane & 1) * 16, z);
            if (lane < 4) sts128(SM_ACT + (2 + (lane >> 1)) * ROW_BYTES + (lane & 1) * 16, z);
            if (lane < 16) sts128(SM_ONES + lane * 16, make_uint4(lane < 8 ? 0x3f803f80u : 0u, 0, 0, 0));
            fence_async_smem();
            asm volatile("barrier.cluster.arrive.relaxed.aligned;" ::: "memory");
            if (lane == 0) TL(5);
            while (clock32() - clk0 < W2DELAY) {}
            weight_load(v, w2, cta, lane);
        }
    if (warp == 0 || warp == 3) {
        const int k = warp & 1;
#pragma unroll
        for (int i = 0; i < 5; i++)
            if (i < 4 || lane < 16) sts128(SM_BNC + k * 2304 + (lane + 32 * i) * 16, v[i]);
        if (lane == 0) TL(k ? 14 : 81);
        __syncwarp();
        weight_block(SM_BNC + k * 2304, gs->wt + k * NSTAGE * STAGE_BYTES, cta, lane, true, gs);
        __syncwarp();
        if (lane == 0) TL(k ? 13 : 4);
        if (lane < 2) asm volatile("red.relaxed.gpu.global.add.u32 [%0], 1;" ::"l"(&gs->wcnt[(k * NB + lane) * LS + (k ? 0 : cta >> 4)]) : "memory");
    }

    if (warp >= 8) {
        const int nw = warp - 8;
        bar_sync(4, 256 + 64 + 128);
        const int par = nw >> 2, wq = nw & 3;
        const uint32_t act_off = SM_ACT + (par * 2 + (lane >> 4)) * CH_PITCH + (2 + wq * 16 + (lane & 15)) * 16;
        const uint32_t stg_off = (par * 16 + (lane >> 4) * 8 + (lane & 7)) * 128 + (((2 * wq + ((lane >> 3) & 1)) ^ (lane & 7)) << 4);
        const uint32_t cfa = SM_COEF + par * 128 + (lane & 3) * 16;
        const uint32_t fbar = BAR(BAR_FULL) + 8 * par;
        uint4* inbox = gs->box + cta * 1024 + nw * 32 + lane;
#pragma unroll 1
        for (int conv = 0; conv < 2; conv++) {
            uint32_t u[4][4], w[4][4];
            float4 cf[8];
            if (conv == 0) {
#pragma unroll
                for (int i = 0; i < 4; i++) { mbar_wait(BAR(BAR_X + i), 0); ldsm4t(u[i], SM_XOWN + stg_off + i * 4096); }
            } else {
                mbar_wait(BAR(BAR_HW), 0);
#pragma unroll
                for (int i = 0; i < 4; i++) ldsm4(u[i], act_off + i * 2 * KC_BYTES);
            }
#pragma unroll
            for (int i = 0; i < 8; i++) cf[i] = lds128f(cfa + conv * 1024 + (i >> 1) * 256 + (i & 1) * 64);
            const uint32_t gst = SM_GST + conv * 32;
            float gv[8];
            read_stats(gst, gv);
            group_coefs<0>(gst, gv, cf);
            if (tid == 256) TL(22 + conv * 4);
            if (par) { const unsigned c1 = clock32(); while (clock32() - c1 < PDELAY) {} }
            norm_block<0, 1>(u, cf, act_off, ~0u, fbar, lane);
            if (tid == 256) TL(8 + conv * 8);
            group_coefs<1>(gst, gv, cf);
            norm_unit(u[1], cf[2], cf[3]);
            stsm4(act_off + 2 * KC_BYTES, u[1][0], u[1][1], u[1][2], u[1][3]);
            next_unit<2>(u, cf, gst, gv, act_off, fbar, lane);
            next_unit<3>(u, cf, gst, gv, act_off, fbar, lane);
            publish(fbar + 48, lane);
            if (tid == 256) TL(84 + conv);
            if (has_outer) {
                mbar_wait(BAR(BAR_X + 4), conv);
                if (conv == 0) {
#pragma unroll
                    for (int i = 0; i < 4; i++) ldsm4t(w[i], SM_XOUT + stg_off + i * 4096);
                } else {
#pragma unroll
                    for (int i = 0; i < 4; i++) {
                        const uint4 q = lds128(SM_XOWN + (tid - 256) * 16 + i * 4096);
                        w[i][0] = q.x; w[i][1] = q.y; w[i][2] = q.z; w[i][3] = q.w;
                    }
                    unsigned it = 0;
                    while (true) {
                        bool ok = true;
#pragma unroll
                        for (int i = 0; i < 16; i++) ok = ok && w[i >> 2][i & 3] != 0;
                        if (__all_sync(0xffffffffu, ok) || ++it > SPIN_LIMIT) break;
#pragma unroll
                        for (int i = 0; i < 4; i++) ld_unit(w[i], inbox + i * 256);
                    }
#pragma unroll
                    for (int i = 0; i < 16; i++) w[i >> 2][i & 3] = ~w[i >> 2][i & 3];
                }
            }
            if (conv == 0) {
                bar_sync(3, 256);
                if (nw == 0) sts128(SM_ACT + 2 * ROW_BYTES + (lane >> 1) * CH_PITCH + (lane & 1) * 16, make_uint4(0, 0, 0, 0));
            }
            if (tid == 256) TL(24 + conv * 4);
            norm_block<0, 2>(w, cf, act_off + 2 * ROW_BYTES, has_outer ? ~0u : 0u, fbar + 128, lane);
            if (tid == 256) TL(88 + conv);
            norm_block<2, 2>(w, cf, act_off + 2 * ROW_BYTES, has_outer ? ~0u : 0u, fbar + 128, lane);
            if (tid == 256) TL(23 + conv * 4);
        }
        if (has_outer) {
            mbar_wait(BAR(BAR_FULL + NSTAGE - 1), 1);
#pragma unroll
            for (int i = 0; i < 4; i++) inbox[i * 256] = make_uint4(0, 0, 0, 0);
        }
        {
            const int oc0 = (tid - 256) >> 3, seg = lane & 7;
            __nv_bfloat16* dst = out + ((size_t)(b * C + oc0) * HW + r) * HW + seg * 8;
            const uint32_t src = SM_XOWN + oc0 * 128 + ((seg ^ (oc0 & 7)) << 4);
            bar_sync(6, 128 + 256);
#pragma unroll
            for (int i = 0; i < 4; i++) *reinterpret_cast<uint4*>(dst + (size_t)i * 32 * HW * HW) = lds128(src + i * 4096);
            if (tid == 256) { TL(20); TLG(21); }
        }
    } else if (warp < 4) {
        const int wq = warp;
        bar_sync(2, 128);

        const uint32_t xbase = SM_XOWN + ((lane >> 4) * 8 + (lane & 7)) * 128 + (((2 * wq + ((lane >> 3) & 1)) ^ (lane & 7)) << 4);
        float d[64];
#pragma unroll
        for (int i = 0; i < 64; i++) d[i] = 0.f;
#pragma unroll 1
        for (int conv = 0; conv < 2; conv++) {
            fence_acc(d);
            mma_stages<0>(d, conv, tid, gs);
            if (conv == 0) {
                asm volatile("wgmma.fence.sync.aligned;" ::: "memory");
                wgmma128<(SM_ONES >> 4) | (8u << 16), (SM_EMB >> 4), 0, 8>(d);
                asm volatile("wgmma.commit_group.sync.aligned;" ::: "memory");
            }
            asm volatile("wgmma.wait_group.sync.aligned 0;" ::: "memory");
            fence_acc(d);
            if (tid == 0) TL(10 + conv * 8);
            uint32_t hp[32];
#pragma unroll
            for (int i = 0; i < 32; i++) hp[i] = pack_bf(d[2 * i], d[2 * i + 1]);
            if (conv == 1) {
#pragma unroll
                for (int kc = 0; kc < 8; kc++) stsm4t(xbase + kc * 2048, hp[4 * kc], hp[4 * kc + 1], hp[4 * kc + 2], hp[4 * kc + 3]);
                bar_arrive(6, 128 + 256);
                break;
            }
#pragma unroll
            for (int g = 0; g < 4; g++) {
                float c[4] = {0.f, 0.f, 0.f, 0.f};
#pragma unroll
                for (int i = 0; i < 4; i++) stat_mma(c, hp[8 * g + 2 * i], hp[8 * g + 2 * i + 1]);
                stat_store(c, SM_RED + (g * 4 + wq) * 48, lane);
            }
            bar_sync(2, 128);
            if (wq == 0) stat_publish(SM_RED, &gs->acc2[b * LS], lane, true);
            if (tid == 0) TL(11);
            const uint32_t hbase = SM_ACT + (lane >> 4) * CH_PITCH + (2 + wq * 16 + (lane & 15)) * 16;
#pragma unroll
            for (int kc = 0; kc < 8; kc++) stsm4(hbase + kc * 2 * CH_PITCH, hp[4 * kc], hp[4 * kc + 1], hp[4 * kc + 2], hp[4 * kc + 3]);
            __syncwarp();
            if (lane == 0) mbar_arrive(BAR(BAR_HW));
            if (lane < LAG) mbar_arrive(BAR(BAR_WEMPTY + (NSTAGE - LAG) % NS) + 8 * lane);
            if (has_outer) {
                uint4* outbox = gs->box + (cta + ((r & 1) ? 1 : -1)) * 1024 + tid;
#pragma unroll
                for (int kc = 0; kc < 8; kc++) outbox[kc * 128] = make_uint4(~hp[4 * kc], ~hp[4 * kc + 1], ~hp[4 * kc + 2], ~hp[4 * kc + 3]);
            }
            if (tid == 0) TL(12);
#pragma unroll
            for (int kc = 0; kc < 8; kc++) {
                uint32_t p[4];
                ldsm4t(p, xbase + kc * 2048);
#pragma unroll
                for (int i = 0; i < 4; i++) { d[8 * kc + 2 * i] = bf_lo(p[i]); d[8 * kc + 2 * i + 1] = bf_hi(p[i]); }
            }
            fence_async_smem();
            __syncwarp();
            if (lane == 0) mbar_arrive(BAR(BAR_XFREE));
        }
        {
        }
    } else if (warp < 6) {
        bar_sync(5, 96);
        if (warp == 5) {
            asm volatile("barrier.cluster.wait.acquire.aligned;" ::: "memory");
            const uint32_t peer = (r & 1) ^ 1;
            const uint32_t self0 = mapa(0, r & 1), peer0 = mapa(0, peer);
#pragma unroll 1
            for (int conv = 0; conv < 2; conv++) {
#pragma unroll 1
                for (int kc = 0; kc < 8; kc++) {
                    mbar_wait(BAR(BAR_FULL) + 8 * kc, conv);
                    if (elect_one())
                        asm volatile("cp.async.bulk.shared::cluster.shared::cta.mbarrier::complete_tx::bytes [%0], [%1], %2, [%3];"
                                     ::"r"(peer0 + SM_ACT + ROW_BYTES + kc * KC_BYTES), "r"(self0 + SM_ACT + kc * KC_BYTES), "r"(KC_BYTES),
                                       "r"(peer0 + BAR(BAR_FULL + 8) + 8 * kc) : "memory");
                }
                if (lane == 0) TL(86 + conv);
#pragma unroll 1
                for (int kc = 0; kc < 8; kc++) mbar_wait(BAR(BAR_FULL + 8) + 8 * kc, conv);
                if (lane == 0)
                    asm volatile("mbarrier.arrive.release.cluster.shared::cluster.b64 _, [%0];" ::"r"(peer0 + (conv ? BAR(BAR_ACK) : BAR(BAR_EMB))) : "memory");
            }
            mbar_wait(BAR(BAR_ACK), 0);
        } else {
            if (has_outer && elect_one()) {
                mbar_expect(BAR(BAR_X + 4), 16384);
#pragma unroll
                for (int i = 0; i < 4; i++) tma_x(SM_XOUT + i * 4096, &xmap, r + ((r & 1) ? 1 : -1), b * C + i * 32, BAR(BAR_X + 4));
            }
            __syncwarp();
            mbar_wait(BAR(BAR_STATS), 0);
            unsigned it = 0;
            while (ld_relaxed(&gs->wcnt[(2 * NB + b) * LS]) < (unsigned)NXTRA && ++it < SPIN_LIMIT) __nanosleep(100);
            fence_acquire();
            float ev[4] = {0.f, 0.f, 0.f, 0.f};
#pragma unroll
            for (int j = 0; j < NXTRA; j++) {
                const uint4 ef = ld_relaxed_v4(&gs->emb[(j * NB + b) * C + lane * 4]);
                ev[0] += __uint_as_float(ef.x); ev[1] += __uint_as_float(ef.y); ev[2] += __uint_as_float(ef.z); ev[3] += __uint_as_float(ef.w);
            }
#pragma unroll
            for (int i = 0; i < 4; i++) {
                const float hi = bf_lo(pack_bf(ev[i], 0.f));
                sts128(SM_EMB + (lane * 4 + i) * 16, make_uint4(pack_bf(hi, ev[i] - hi), 0, 0, 0));
            }
            fence_async_smem();
            __syncwarp();
            if (lane == 0) { mbar_arrive(BAR(BAR_EMB)); TL(19); }
        }
    } else if (warp == 6) {
        bar_sync(0, 96);
        const uint32_t ebytes = STAGE_BYTES + ((lane >> 3) == 1 ? KC_BYTES : 0);
        if (lane < NSTAGE) mbar_expect(BAR(BAR_FULL) + 8 * lane, ebytes);
        const int swap = (r & 1) ? 0 : 8 * STAGE_BYTES;
        unsigned it = 0;
        {
            int g = 0;
#pragma unroll 1
            while (g < NS) {
                unsigned ready = __ballot_sync(0xffffffffu, ld_relaxed(&gs->wcnt[b * LS + (lane & 7)]) >= 16u) >> g;
                if (++it > SPIN_LIMIT) ready = ~0u;
                if (!(ready & 1)) continue;
                fence_acquire();
                fence_async_global();
                if (lane == 0) TL(g ? 3 : 6);
#pragma unroll 1
                for (; (ready & 1) && g < NS; g++, ready >>= 1)
                    if (elect_one())
                        bulk_g2s(S0 + SM_W + g * STAGE_BYTES, gs->wt + g * STAGE_BYTES + (g >= 8 ? swap : 0), STAGE_BYTES, S0 + BAR(BAR_FULL) + 8 * g);
            }
        }
#pragma unroll 1
        for (int q = 3; q < 12; q++) {
            const int conv = q >= 6, qs = conv ? q - 6 : q, sl = q % 3;
            const unsigned char* wsrc = gs->wt + q * 4 * STAGE_BYTES + (qs < 2 ? 0 : (qs < 4 ? swap : -swap));
            const uint32_t par = (q / 3 - 1) & 1;
            if (q == 6) {
                it = 0;
                while (ld_relaxed(&gs->wcnt[(NB + b) * LS]) < (unsigned)NCTA && ++it < SPIN_LIMIT) {}
                fence_acquire();
                fence_async_global();
                if (lane == 0) { mbar_arrive(BAR(BAR_EMB)); TL(2); }
            }
#pragma unroll
            for (int i = 0; i < 4; i++) {
                mbar_wait(BAR(BAR_WEMPTY + i) + 32 * sl, par);
                if (i == 0 && (q == 6 || q == 9)) {
                    if ((lane >= NS) == (q == 9) && lane < NSTAGE) mbar_expect(BAR(BAR_FULL) + 8 * lane, ebytes);
                    __syncwarp();
                }
                if (elect_one())
                    bulk_g2s(S0 + SM_W + (sl * 4 + i) * STAGE_BYTES, wsrc + i * STAGE_BYTES, STAGE_BYTES, S0 + BAR(BAR_FULL + i) + 32 * qs);
            }
        }
    } else {
        const uint2 ga1 = __ldg(reinterpret_cast<const uint2*>(g1) + lane), bt1 = __ldg(reinterpret_cast<const uint2*>(be1) + lane);
        const uint2 ga2 = __ldg(reinterpret_cast<const uint2*>(g2) + lane), bt2 = __ldg(reinterpret_cast<const uint2*>(be2) + lane);
        if (lane < 8) sts128(SM_GST + lane * 16, make_uint4(0, 0, 0, 0));
        sts128f(SM_COEF + lane * 32, make_float4(0.5f * bf_lo(ga1.x), 0.5f * bf_hi(ga1.x), 0.5f * bf_lo(bt1.x), 0.5f * bf_hi(bt1.x)));
        sts128f(SM_COEF + lane * 32 + 16, make_float4(0.5f * bf_lo(ga1.y), 0.5f * bf_hi(ga1.y), 0.5f * bf_lo(bt1.y), 0.5f * bf_hi(bt1.y)));
        sts128f(SM_COEF + 1024 + lane * 32, make_float4(0.5f * bf_lo(ga2.x), 0.5f * bf_hi(ga2.x), 0.5f * bf_lo(bt2.x), 0.5f * bf_hi(bt2.x)));
        sts128f(SM_COEF + 1024 + lane * 32 + 16, make_float4(0.5f * bf_lo(ga2.y), 0.5f * bf_hi(ga2.y), 0.5f * bf_lo(bt2.y), 0.5f * bf_hi(bt2.y)));
        bar_arrive(4, 256 + 64 + 128);
        bar_sync(0, 96);
#pragma unroll 1
        for (int conv = 0; conv < 2; conv++) {
            if (conv == 1) {
                mbar_wait(BAR(BAR_HW), 0);
                const unsigned c1 = clock32();
                while (clock32() - c1 < PD2) {}
            } else {
                while (clock32() - clk0 < PD) {}
            }
            const float* asrc = conv ? &gs->acc2[b * LS + (lane & 3) * 4] : &gs->acc1[b * 4 * LS + (lane & 3) * GS1];
            unsigned it = 0;
            uint4 fq[NPOLL];
#pragma unroll
            for (int i = 0; i < NPOLL; i++) {
                fq[i] = ld_relaxed_v4(asrc);
                if (i + 1 < NPOLL) { const unsigned c1 = clock32(); while (clock32() - c1 < 450 / NPOLL) {} }
            }
            bool all = false;
#pragma unroll 1
            while (!all) {
#pragma unroll
                for (int i = 0; i < NPOLL; i++) {
                    const uint4 f = fq[i];
                    const bool ok = ((f.x == 0x42800000u) & (f.w == 0x42800000u)) || it > SPIN_LIMIT;
                    if (ok && lane < 4) {
                        const float inv_n = 1.0f / (32.0f * HW * HW);
                        const float mean = __uint_as_float(f.y) * inv_n;
                        const float rs = rsqrtf(fmaxf(fmaf(-mean, mean, __uint_as_float(f.z) * inv_n), 0.f) + 1e-5f);
                        asm volatile("st.shared.v2.f32 [%0], {%1,%2};" ::"r"(S0 + SM_GST + conv * 32 + lane * 8), "f"(rs == 0.f ? 1e-38f : rs), "f"(mean * rs) : "memory");
                    }
                    if (__all_sync(0xffffffffu, ok)) { all = true; break; }
                    fq[i] = ld_relaxed_v4(asrc);
                }
                it++;
            }
            if (lane == 0) { mbar_arrive(BAR(BAR_STATS)); TL(7 + conv * 8); }
        }
        mbar_wait(BAR(BAR_XFREE), 0);
        if (has_outer && elect_one()) {
            mbar_expect(BAR(BAR_X + 4), 16384);
            bulk_g2s(S0 + SM_XOWN, gs->box + cta * 1024, 16384, S0 + BAR(BAR_X + 4));
        }
        if (r == 0) {
            if (lane < 16) gs->acc1[b * 4 * LS + (lane >> 2) * GS1 + (lane & 3)] = 0.f;
            if (lane < 24) gs->wcnt[((lane >> 3) * NB + b) * LS + (lane & 7)] = 0;
        }
    }
}

}

extern "C" void kernel_launch(void* const* d_in, const int* in_sizes, int n_in, void* d_out, int out_size) {
    (void)in_sizes; (void)n_in; (void)out_size;
    typedef CUresult (*EncodeFn)(CUtensorMap*, CUtensorMapDataType, cuuint32_t, void*, const cuuint64_t*, const cuuint64_t*,
                                 const cuuint32_t*, const cuuint32_t*, CUtensorMapInterleave, CUtensorMapSwizzle,
                                 CUtensorMapL2promotion, CUtensorMapFloatOOBfill);
    static Scratch* gs = nullptr;
    static EncodeFn encode = nullptr;
    if (!gs) {
        cudaFuncSetAttribute(resblock_kernel, cudaFuncAttributeMaxDynamicSharedMemorySize, SM_TOTAL);
        cudaGetSymbolAddress((void**)&gs, g_scratch);
        cudaDriverEntryPointQueryResult qr;
        cudaGetDriverEntryPoint("cuTensorMapEncodeTiled", (void**)&encode, cudaEnableDefault, &qr);
    }
    CUtensorMap xmap;
    const cuuint64_t dims[3] = {HW, HW, NB * C}, strides[2] = {HW * 2, HW * HW * 2};
    const cuuint32_t box[3] = {HW, 1, 32}, es[3] = {1, 1, 1};
    encode(&xmap, CU_TENSOR_MAP_DATA_TYPE_BFLOAT16, 3, d_in[0], dims, strides, box, es, CU_TENSOR_MAP_INTERLEAVE_NONE,
           CU_TENSOR_MAP_SWIZZLE_128B, CU_TENSOR_MAP_L2_PROMOTION_NONE, CU_TENSOR_MAP_FLOAT_OOB_FILL_NONE);
    resblock_kernel<<<NCTA + NXTRA, NTHREADS, SM_TOTAL>>>(
        (const __nv_bfloat16*)d_in[4], (const __nv_bfloat16*)d_in[0], (const __nv_bfloat16*)d_in[1],
        (const __nv_bfloat16*)d_in[2], (const __nv_bfloat16*)d_in[3], (const __nv_bfloat16*)d_in[5],
        (const __nv_bfloat16*)d_in[6], (const __nv_bfloat16*)d_in[7], (const __nv_bfloat16*)d_in[8],
        (__nv_bfloat16*)d_out, gs, xmap);
}
```

```cpp
#include <cuda_runtime.h>
#include <cuda.h>
#include <cuda_bf16.h>
#include <stdint.h>

namespace {

constexpr int C = 128, HW = 64, NB = 2, E = 768;
constexpr int NCTA = NB * HW;
constexpr int NXTRA = 4;
constexpr int NTHREADS = 16 * 32;
constexpr int CH_PITCH = 66 * 16;
constexpr int POS_BYTES = 2 * CH_PITCH;
constexpr int VST_BYTES = 2 * POS_BYTES;
constexpr int STAGE_BYTES = 12288;
constexpr int NSTAGE = 16;
constexpr int NS = 8;
#define XDELAY 400
#define XSTAG 800
#define W2DELAY 1800
#define PDELAY 100
#define PAUSE 1
constexpr int LS = 1056;

constexpr uint32_t SMEM_BASE = 0x400;
constexpr uint32_t SM_XOWN = SMEM_BASE;
constexpr uint32_t SM_XOUT = SM_XOWN + 16384;
constexpr uint32_t SM_V = SM_XOUT + 16384;
constexpr uint32_t SM_W = SM_V + NSTAGE * VST_BYTES + 128;
constexpr uint32_t SM_COEF = SM_W + NS * STAGE_BYTES;
constexpr uint32_t SM_GST = SM_COEF + 2048;
constexpr uint32_t SM_EMB = SM_GST + 128;
constexpr uint32_t SM_ONES = SM_EMB + 1024;
constexpr uint32_t SM_RED = SM_ONES + 256;
constexpr uint32_t SM_BNC = SM_RED + 512;
constexpr uint32_t SM_BAR = SM_BNC + 2 * 2304;
constexpr int BAR_FULL = 0, BAR_WEMPTY = NSTAGE, BAR_HW = BAR_WEMPTY + NS, BAR_STATS = BAR_HW + 1, BAR_EMB = BAR_STATS + 1,
              BAR_ACK = BAR_EMB + 1, BAR_XO = BAR_ACK + 1, BAR_X = BAR_XO + 1  , NBAR = BAR_X + 4;
constexpr int SM_TOTAL = SM_BAR + NBAR * 8 - SMEM_BASE;
static_assert(SM_TOTAL <= 232448, "smem");
__host__ __device__ constexpr uint32_t BAR(int i) { return SM_BAR + 8 * i; }

constexpr unsigned SPIN_LIMIT = 1u << 16;

struct Scratch {
    float acc1[NB * LS];
    float acc2[NB * LS];
    unsigned wcnt[3 * NB * LS];
    float emb[NXTRA * NB * C];
    unsigned char wt[2 * 2 * NSTAGE * STAGE_BYTES];
    uint4 box[NCTA * 1024];
};
__device__ __align__(1024) Scratch g_scratch;
#define TL(i) do {} while (0)
#define TLG(i) do {} while (0)

__device__ __forceinline__ unsigned clock32() { unsigned c; asm volatile("mov.u32 %0, %%clock;" : "=r"(c)); return c; }
__device__ __forceinline__ uint32_t mapa(uint32_t a, uint32_t rank) {
    uint32_t d;
    asm("mapa.shared::cluster.u32 %0, %1, %2;" : "=r"(d) : "r"(a), "r"(rank));
    return d;
}
#define S0 mapa(0, blockIdx.x & 1)
__device__ __forceinline__ void mbar_init(uint32_t bar, int cnt) {
    asm volatile("mbarrier.init.shared::cta.b64 [%0], %1;" ::"r"(bar + S0), "r"(cnt) : "memory");
}
__device__ __forceinline__ void mbar_arrive(uint32_t bar) {
    asm volatile("mbarrier.arrive.shared::cta.b64 _, [%0];" ::"r"(bar + S0) : "memory");
}
__device__ __forceinline__ void mbar_expect(uint32_t bar, uint32_t bytes) {
    asm volatile("mbarrier.arrive.expect_tx.shared::cta.b64 _, [%0], %1;" ::"r"(bar + S0), "r"(bytes) : "memory");
}
__device__ __forceinline__ bool mbar_try(uint32_t bar, uint32_t par) {
    uint32_t ok;
    asm volatile("{\n.reg .pred p;\nmbarrier.try_wait.parity.shared::cta.b64 p, [%1], %2;\nselp.u32 %0, 1, 0, p;\n}"
                 : "=r"(ok) : "r"(bar + S0), "r"(par) : "memory");
    return ok;
}
__device__ __forceinline__ bool mbar_test(uint32_t bar, uint32_t par) {
    uint32_t ok;
    asm volatile("{\n.reg .pred p;\nmbarrier.test_wait.parity.shared::cta.b64 p, [%1], %2;\nselp.u32 %0, 1, 0, p;\n}"
                 : "=r"(ok) : "r"(bar + S0), "r"(par) : "memory");
    return ok;
}
__device__ __forceinline__ void mbar_wait(uint32_t bar, uint32_t par) {
    unsigned it = 0;
#pragma unroll 1
    while (!mbar_try(bar, par) && ++it < SPIN_LIMIT) {}
}
__device__ __forceinline__ bool elect_one() {
    uint32_t p;
    asm volatile("{\n.reg .pred p;\nelect.sync _|p, 0xffffffff;\nselp.u32 %0, 1, 0, p;\n}" : "=r"(p));
    return p;
}
__device__ __forceinline__ void fence_async_smem() { asm volatile("fence.proxy.async.shared::cta;" ::: "memory"); }
__device__ __forceinline__ void fence_async_global() { asm volatile("fence.proxy.async.global;" ::: "memory"); }
__device__ __forceinline__ void fence_acquire() { asm volatile("fence.acquire.gpu;" ::: "memory"); }
__device__ __forceinline__ void bar_sync(int id, int n) { asm volatile("bar.sync %0, %1;" ::"r"(id), "r"(n) : "memory"); }
__device__ __forceinline__ void bar_arrive(int id, int n) { asm volatile("bar.arrive %0, %1;" ::"r"(id), "r"(n) : "memory"); }
__device__ __forceinline__ void bulk_g2s(uint32_t dst, const void* src, uint32_t bytes, uint32_t bar) {
    asm volatile("cp.async.bulk.shared::cluster.global.mbarrier::complete_tx::bytes [%0], [%1], %2, [%3];"
                 ::"r"(dst), "l"(src), "r"(bytes), "r"(bar) : "memory");
}
__device__ __forceinline__ void tma_x(uint32_t dst, const CUtensorMap* tm, int row, int ch, uint32_t bar) {
    asm volatile("cp.async.bulk.tensor.3d.shared::cluster.global.mbarrier::complete_tx::bytes [%0], [%1, {%2, %3, %4}], [%5];"
                 ::"r"(dst + S0), "l"(tm), "r"(0), "r"(row), "r"(ch), "r"(bar + S0) : "memory");
}
__device__ __forceinline__ uint4 ld_relaxed_v4(const void* p) {
    uint4 v;
    asm volatile("ld.relaxed.gpu.global.v4.u32 {%0,%1,%2,%3}, [%4];" : "=r"(v.x), "=r"(v.y), "=r"(v.z), "=r"(v.w) : "l"(p) : "memory");
    return v;
}
__device__ __forceinline__ unsigned ld_relaxed(const void* p) {
    unsigned v;
    asm volatile("ld.relaxed.gpu.global.u32 %0, [%1];" : "=r"(v) : "l"(p) : "memory");
    return v;
}
__device__ __forceinline__ void red_add4(float* p, float a, float b, float c, float d) {
    asm volatile("red.relaxed.gpu.global.add.v4.f32 [%0], {%1,%2,%3,%4};" ::"l"(p), "f"(a), "f"(b), "f"(c), "f"(d) : "memory");
}
__device__ __forceinline__ void sts128(uint32_t a, uint4 v) {
    asm volatile("st.shared.v4.u32 [%0], {%1,%2,%3,%4};" ::"r"(a + S0), "r"(v.x), "r"(v.y), "r"(v.z), "r"(v.w) : "memory");
}
__device__ __forceinline__ void sts128f(uint32_t a, float4 v) {
    asm volatile("st.shared.v4.f32 [%0], {%1,%2,%3,%4};" ::"r"(a + S0), "f"(v.x), "f"(v.y), "f"(v.z), "f"(v.w) : "memory");
}
__device__ __forceinline__ void sts32f(uint32_t a, float v) { asm volatile("st.shared.f32 [%0], %1;" ::"r"(a + S0), "f"(v) : "memory"); }
__device__ __forceinline__ uint4 lds128(uint32_t a) {
    uint4 v;
    asm volatile("ld.shared.v4.u32 {%0,%1,%2,%3}, [%4];" : "=r"(v.x), "=r"(v.y), "=r"(v.z), "=r"(v.w) : "r"(a + S0) : "memory");
    return v;
}
__device__ __forceinline__ float4 lds128f(uint32_t a) {
    float4 v;
    asm volatile("ld.shared.v4.f32 {%0,%1,%2,%3}, [%4];" : "=f"(v.x), "=f"(v.y), "=f"(v.z), "=f"(v.w) : "r"(a + S0) : "memory");
    return v;
}
__device__ __forceinline__ float2 lds64f(uint32_t a) {
    float2 v;
    asm volatile("ld.shared.v2.f32 {%0,%1}, [%2];" : "=f"(v.x), "=f"(v.y) : "r"(a + S0) : "memory");
    return v;
}
__device__ __forceinline__ float bf_lo(uint32_t u) { return __uint_as_float(u << 16); }
__device__ __forceinline__ float bf_hi(uint32_t u) { return __uint_as_float(u & 0xffff0000u); }
__device__ __forceinline__ uint32_t pack_bf(float lo, float hi) {
    uint32_t r;
    asm("cvt.rn.bf16x2.f32 %0, %1, %2;" : "=r"(r) : "f"(hi), "f"(lo));
    return r;
}
__device__ __forceinline__ float tanh_fast(float x) {
    float r;
    asm("tanh.approx.f32 %0, %1;" : "=f"(r) : "f"(x));
    return r;
}
__device__ __forceinline__ float silu_half(float h) { return fmaf(h, tanh_fast(h), h); }
__device__ __forceinline__ void ldsm4(uint32_t (&u)[4], uint32_t a) {
    asm volatile("ldmatrix.sync.aligned.m8n8.x4.shared.b16 {%0,%1,%2,%3}, [%4];"
                 : "=r"(u[0]), "=r"(u[1]), "=r"(u[2]), "=r"(u[3]) : "r"(a + S0) : "memory");
}
__device__ __forceinline__ void ldsm4t(uint32_t (&u)[4], uint32_t a) {
    asm volatile("ldmatrix.sync.aligned.m8n8.x4.trans.shared.b16 {%0,%1,%2,%3}, [%4];"
                 : "=r"(u[0]), "=r"(u[1]), "=r"(u[2]), "=r"(u[3]) : "r"(a + S0) : "memory");
}
__device__ __forceinline__ void stsm4(uint32_t a, uint32_t p0, uint32_t p1, uint32_t p2, uint32_t p3) {
    asm volatile("stmatrix.sync.aligned.m8n8.x4.shared.b16 [%0], {%1,%2,%3,%4};" ::"r"(a + S0), "r"(p0), "r"(p1), "r"(p2), "r"(p3) : "memory");
}
__device__ __forceinline__ void stsm4t(uint32_t a, uint32_t p0, uint32_t p1, uint32_t p2, uint32_t p3) {
    asm volatile("stmatrix.sync.aligned.m8n8.x4.trans.shared.b16 [%0], {%1,%2,%3,%4};" ::"r"(a + S0), "r"(p0), "r"(p1), "r"(p2), "r"(p3) : "memory");
}

#define R8(o) "+f"(d[o]), "+f"(d[o + 1]), "+f"(d[o + 2]), "+f"(d[o + 3]), "+f"(d[o + 4]), "+f"(d[o + 5]), "+f"(d[o + 6]), "+f"(d[o + 7])
template <uint32_t ALO, uint32_t BLO, uint64_t AHI = 8, uint64_t BHI = 96>
__device__ __forceinline__ void wgmma64(float (&d)[32]) {
    asm volatile(
        "wgmma.mma_async.sync.aligned.m64n64k16.f32.bf16.bf16 "
        "{%0,%1,%2,%3,%4,%5,%6,%7,%8,%9,%10,%11,%12,%13,%14,%15,%16,%17,%18,%19,%20,%21,%22,%23,%24,%25,%26,%27,%28,%29,%30,%31},"
        " %32, %33, 1, 1, 1, 0, 0;"
        : R8(0), R8(8), R8(16), R8(24)
        : "l"((AHI << 32) | ALO), "l"((BHI << 32) | BLO));
}
__device__ __forceinline__ void fence_acc(float (&d)[32]) {
#pragma unroll
    for (int i = 0; i < 32; i++) asm volatile("" : "+f"(d[i])::"memory");
}
template <int S>
__device__ __forceinline__ void mma_stages(float (&d0)[32], float (&d1)[32], int conv, int tid, Scratch* gs) {
    constexpr uint32_t A = ((SM_V + S * VST_BYTES + 16) >> 4) | ((CH_PITCH >> 4) << 16), A1 = A + (POS_BYTES >> 4);
    constexpr uint32_t B = ((SM_W + (S % NS) * STAGE_BYTES) >> 4) | (8u << 16);
    if (S == 0) mbar_wait(BAR(BAR_FULL), conv);
    constexpr uint32_t NEXT = S + 1 < NSTAGE ? BAR(BAR_FULL + S + 1) : BAR(BAR_EMB);
    const int npar = S + 1 < NSTAGE ? conv : 0;
    const bool next_ok = S != 7 && mbar_test(NEXT, npar);
    if ((S & 7) == 0 && tid == 0) TL(32 + conv * 16 + S);
    asm volatile("wgmma.fence.sync.aligned;" ::: "memory");
    wgmma64<A, B>(d0); wgmma64<A + 1, B + 16>(d0); wgmma64<A + 2, B + 32>(d0);
    wgmma64<A1, B + 48>(d1); wgmma64<A1 + 1, B + 64>(d1); wgmma64<A1 + 2, B + 80>(d1);
    asm volatile("wgmma.commit_group.sync.aligned;" ::: "memory");
    if ((S & 7) != 0) {
        asm volatile("wgmma.wait_group.sync.aligned 1;" ::: "memory");
        if ((tid & 31) == 0) mbar_arrive(BAR(BAR_WEMPTY + (S - 1) % NS));
    }
    if (S == 7) {
        asm volatile("wgmma.wait_group.sync.aligned 0;" ::: "memory");
        fence_acc(d0); fence_acc(d1);
        if ((tid & 31) == 0) mbar_arrive(BAR(BAR_WEMPTY + 7));
#pragma unroll
        for (int i = 0; i < 32; i++) { const float p = d0[i], q = d1[i]; d0[i] = p + q; d1[i] = p - q; }
        fence_acc(d0); fence_acc(d1);
    }
    if (!next_ok) mbar_wait(NEXT, npar);
    if constexpr (S + 1 < NSTAGE) mma_stages<S + 1>(d0, d1, conv, tid, gs);
}

__device__ __forceinline__ int wblk_kc(int cta) { return (((cta >> 3) & 1) * 4 + (cta >> 4)) & 7; }
__device__ __forceinline__ void weight_load(uint4 (&t)[5], const __nv_bfloat16* w, int cta, int lane) {
    const char* base = reinterpret_cast<const char*>(w) + ((cta & 15) * 8 * C + wblk_kc(cta) * 16) * 18;
#pragma unroll
    for (int k = 0; k < 5; k++) {
        const int i = lane + 32 * k, row = (i * 57) >> 10;
        if (k < 4 || lane < 16) t[k] = __ldg(reinterpret_cast<const uint4*>(base + row * (C * 18 - 288) + i * 16));
    }
}
__device__ __forceinline__ void weight_block(uint32_t bounce, unsigned char* wt, int cta, int lane) {
    unsigned char* piece = wt + (((cta >> 3) & 1) * NSTAGE + wblk_kc(cta)) * STAGE_BYTES + (cta & 7) * 1536;
    uint32_t v[18];
#pragma unroll
    for (int i = 0; i < 9; i++) {
        const float2 q = lds64f(bounce + (lane & 7) * 288 + (lane >> 3) * 72 + i * 8);
        v[2 * i] = __float_as_uint(q.x); v[2 * i + 1] = __float_as_uint(q.y);
    }
    unsigned char* dst = piece + (lane >> 4) * 128 + (lane & 7) * 16 + ((lane >> 3) & 1) * 8;
#pragma unroll
    for (int kx = 0; kx < 3; kx++) {
        float u1[4], u2[4];
#pragma unroll
        for (int c = 0; c < 4; c++) {
            const int i0 = 9 * c + kx, i1 = i0 + 3, i2 = i0 + 6;
            const float g0 = (i0 & 1) ? bf_hi(v[i0 >> 1]) : bf_lo(v[i0 >> 1]);
            const float g1 = (i1 & 1) ? bf_hi(v[i1 >> 1]) : bf_lo(v[i1 >> 1]);
            const float g2 = (i2 & 1) ? bf_hi(v[i2 >> 1]) : bf_lo(v[i2 >> 1]);
            const float t = 0.5f * (g0 + g2);
            u1[c] = fmaf(g1, 0.5f, t); u2[c] = fmaf(g1, -0.5f, t);
        }
        *reinterpret_cast<uint2*>(dst + kx * 256) = make_uint2(pack_bf(u1[0], u1[1]), pack_bf(u1[2], u1[3]));
        *reinterpret_cast<uint2*>(dst + 768 + kx * 256) = make_uint2(pack_bf(u2[0], u2[1]), pack_bf(u2[2], u2[3]));
    }
#pragma unroll
    for (int j = 0; j < 6; j++) {
        const int tap = (j / 3) * 6 + j % 3;
        uint32_t o[2];
#pragma unroll
        for (int m = 0; m < 2; m++) {
            const int i0 = 18 * m + tap, i1 = i0 + 9;
            o[m] = __byte_perm(v[i0 >> 1], v[i1 >> 1], ((i0 & 1) ? 0x32u : 0x10u) | ((i1 & 1) ? 0x7600u : 0x5400u));
        }
        *reinterpret_cast<uint2*>(dst + 8 * STAGE_BYTES + j * 256) = make_uint2(o[0], o[1]);
    }
    __syncwarp();
    unsigned acc = 0;
#pragma unroll
    for (int i = 0; i < 3; i++) {
        const int sct = lane + 32 * i;
        acc |= ld_relaxed(piece + (sct >= 48 ? 8 * STAGE_BYTES - 1536 : 0) + sct * 32);
    }
    asm volatile("{\n.reg .pred p;\nsetp.eq.u32 p, %0, 0x9e3779b9;\n@p st.shared.u32 [%1], %0;\n}" ::"r"(acc), "r"(bounce + S0) : "memory");
}

__device__ __forceinline__ void act8(float (&a)[8], const uint32_t (&u)[4], const float4& ca, const float4& cb) {
#pragma unroll
    for (int i = 0; i < 4; i++) {
        const float4& cf = i < 2 ? ca : cb;
        a[2 * i] = silu_half(fmaf(bf_lo(u[i]), cf.x, cf.z));
        a[2 * i + 1] = silu_half(fmaf(bf_hi(u[i]), cf.y, cf.w));
    }
}
template <int SGN>
__device__ __forceinline__ void stsm_comb(uint32_t dst, const float (&p)[8], const float (&q)[8]) {
    uint32_t o[4];
#pragma unroll
    for (int i = 0; i < 4; i++)
        o[i] = SGN > 0 ? pack_bf(p[2 * i] + q[2 * i], p[2 * i + 1] + q[2 * i + 1]) : pack_bf(p[2 * i] - q[2 * i], p[2 * i + 1] - q[2 * i + 1]);
    stsm4(dst, o[0], o[1], o[2], o[3]);
}
template <int T>
__device__ __forceinline__ void group_coefs(uint32_t gst, float4& g, float4 (&cf)[4]) {
    unsigned it = 0;
#pragma unroll 1
    while (!__all_sync(0xffffffffu, (T ? g.z : g.x) != 0.f) && ++it < 8 * SPIN_LIMIT)
        asm volatile("ld.volatile.shared.v4.f32 {%0,%1,%2,%3}, [%4];" : "=f"(g.x), "=f"(g.y), "=f"(g.z), "=f"(g.w) : "r"(gst + S0) : "memory");
    float4 &ca = cf[2 * T], &cb = cf[2 * T + 1];
    const float rs = T ? g.z : g.x, mr = T ? g.w : g.y;
    ca.z = fmaf(-mr, ca.x, ca.z); ca.w = fmaf(-mr, ca.y, ca.w); ca.x *= rs; ca.y *= rs;
    cb.z = fmaf(-mr, cb.x, cb.z); cb.w = fmaf(-mr, cb.y, cb.w); cb.x *= rs; cb.y *= rs;
}
__device__ __forceinline__ void publish(uint32_t bar, int lane) {
    fence_async_smem();
    __syncwarp();
    if (lane == 0) mbar_arrive(bar);
}
__device__ __forceinline__ void ld_unit(uint32_t (&u)[4], const uint4* p) {
    asm volatile("ld.relaxed.gpu.global.v4.u32 {%0,%1,%2,%3}, [%4];" : "=r"(u[0]), "=r"(u[1]), "=r"(u[2]), "=r"(u[3]) : "l"(p) : "memory");
}
__device__ __forceinline__ void stat_mma(float (&c)[4], uint32_t p, uint32_t q) {
    asm("mma.sync.aligned.m16n8k16.row.col.f32.bf16.bf16.f32 {%0,%1,%2,%3}, {%4,%5,%6,%5}, {%4,%6}, {%0,%1,%2,%3};"
        : "+f"(c[0]), "+f"(c[1]), "+f"(c[2]), "+f"(c[3]) : "r"(p), "r"(0x3f803f80u), "r"(q));
}
__device__ __forceinline__ void stat_store(const float (&c)[4], uint32_t dst, int lane) {
    const int g = lane >> 2, t = lane & 3;
    if (t == (g >> 1)) sts32f(dst + g * 4, (g & 1) ? c[1] : c[0]);
    if (g == 7) sts32f(dst + 32 + t * 4, c[2] + c[3]);
}
__device__ __forceinline__ float sum4(float4 v) { return (v.x + v.y) + (v.z + v.w); }
__device__ __noinline__ void side_jobs(const __nv_bfloat16* __restrict__ t_emb, const __nv_bfloat16* __restrict__ w_emb,
                                       const __nv_bfloat16* __restrict__ w2, Scratch* __restrict__ gs, unsigned clk0) {
    const int tid = threadIdx.x, warp = tid >> 5, lane = tid & 31, j = blockIdx.x;
    float tv = 0.f;
    if (lane < 24) tv = __bfloat162float(t_emb[(lane / 12) * E + j * 192 + warp * 12 + lane % 12]);
    if (tid == 0) {
        mbar_init(BAR(0), 1);
        mbar_expect(BAR(0), 192 * C * 2);
        fence_async_smem();
        while (clock32() - clk0 < W2DELAY) {}
#pragma unroll
        for (int i = 0; i < 4; i++) bulk_g2s(S0 + SM_W + i * 12288, w_emb + (j * 192 + i * 48) * C, 12288, S0 + BAR(0));
    }
    if (j == 0 && tid < 32) gs->acc2[(tid >> 4) * LS + (tid & 15)] = 0.f;
    const float sv = silu_half(0.5f * tv);
    __syncthreads();
    mbar_wait(BAR(0), 0);
    float acc[8] = {0.f, 0.f, 0.f, 0.f, 0.f, 0.f, 0.f, 0.f};
#pragma unroll
    for (int i = 0; i < 12; i++) {
        const float2 wq = lds64f(SM_W + (warp * 12 + i) * 256 + lane * 8);
        const uint32_t wx = __float_as_uint(wq.x), wy = __float_as_uint(wq.y);
#pragma unroll
        for (int bb = 0; bb < 2; bb++) {
            const float sx = __shfl_sync(0xffffffffu, sv, bb * 12 + i);
            acc[4 * bb + 0] = fmaf(sx, bf_lo(wx), acc[4 * bb + 0]); acc[4 * bb + 1] = fmaf(sx, bf_hi(wx), acc[4 * bb + 1]);
            acc[4 * bb + 2] = fmaf(sx, bf_lo(wy), acc[4 * bb + 2]); acc[4 * bb + 3] = fmaf(sx, bf_hi(wy), acc[4 * bb + 3]);
        }
    }
    sts128f(SM_V + warp * 1024 + lane * 16, make_float4(acc[0], acc[1], acc[2], acc[3]));
    sts128f(SM_V + warp * 1024 + 512 + lane * 16, make_float4(acc[4], acc[5], acc[6], acc[7]));
    __syncthreads();
    if (tid < 128) {
        float2 sum = make_float2(0.f, 0.f);
#pragma unroll
        for (int w = 0; w < 16; w++) { const float2 p = lds64f(SM_V + w * 1024 + tid * 8); sum.x += p.x; sum.y += p.y; }
        *reinterpret_cast<float2*>(&gs->emb[j * NB * C + tid * 2]) = sum;
        bar_sync(1, 128);
        if (tid < 2) asm volatile("red.release.gpu.global.add.u32 [%0], 1;" ::"l"(&gs->wcnt[(2 * NB + tid) * LS]) : "memory");
    }
}

__global__ void __cluster_dims__(2, 1, 1) __launch_bounds__(NTHREADS, 1)
resblock_kernel(const __nv_bfloat16* __restrict__ w1, const __nv_bfloat16* __restrict__ x,
                const __nv_bfloat16* __restrict__ t_emb, const __nv_bfloat16* __restrict__ g1,
                const __nv_bfloat16* __restrict__ be1, const __nv_bfloat16* __restrict__ w_emb,
                const __nv_bfloat16* __restrict__ g2, const __nv_bfloat16* __restrict__ be2,
                const __nv_bfloat16* __restrict__ w2, __nv_bfloat16* __restrict__ out, Scratch* __restrict__ gs,
                const __grid_constant__ CUtensorMap xmap) {
    const unsigned clk0 = clock32();
    if (threadIdx.x == 480 && blockIdx.x >= NXTRA) TLG(1);
    const int tid = threadIdx.x, lane = tid & 31;
    const int cta = blockIdx.x - NXTRA, b = cta >> 6, rk = cta & 1, r0 = cta & 62;
    uint4 v[5];
    if (tid < 32) weight_load(v, w1, cta & (NCTA - 1), lane);
    const int warp = __shfl_sync(0xffffffffu, tid >> 5, 0);
    if (cta < 0) { side_jobs(t_emb, w_emb, w2, gs, clk0); return; }

    if (warp != 3) asm volatile("barrier.cluster.arrive.relaxed.aligned;" ::: "memory");
    const bool has_up = r0 != 0, has_dn = r0 != HW - 2;
    const int ch0 = b * C + rk * 64;
    if (warp == 1 || warp == 2 || warp == 4 || warp == 5) {
        const int i = warp < 3 ? warp - 1 : warp - 2, gl = i >> 1, row = i & 1;
        const uint32_t tile = SM_XOWN + row * 8192 + gl * 4096;
        if (elect_one()) {
            asm volatile("prefetch.tensormap [%0];" ::"l"(&xmap) : "memory");
            mbar_init(BAR(BAR_X) + 8 * i, 1);
            mbar_expect(BAR(BAR_X) + 8 * i, 4096);
            fence_async_smem();
            while (clock32() - clk0 < XDELAY + gl * XSTAG) {}
            tma_x(tile, &xmap, r0 + row, ch0 + gl * 32, BAR(BAR_X) + 8 * i);
        }
        __syncwarp();
        bar_arrive(4, 256 + 64 + 128);
        mbar_wait(BAR(BAR_X) + 8 * i, 0);
        if (lane == 0) TL(70 + i);
        float c[8][4];
#pragma unroll
        for (int k = 0; k < 8; k++) {
            const uint4 q = lds128(tile + k * 512 + lane * 16);
            c[k][0] = c[k][1] = c[k][2] = c[k][3] = 0.f;
            stat_mma(c[k], q.x, q.y); stat_mma(c[k], q.z, q.w);
        }
#pragma unroll
        for (int k = 0; k < 4; k++) c[0][k] = ((c[0][k] + c[1][k]) + (c[2][k] + c[3][k])) + ((c[4][k] + c[5][k]) + (c[6][k] + c[7][k]));
        stat_store(c[0], SM_RED + i * 48, lane);
        __syncwarp();
        if (lane == 0) {
            const uint32_t a = SM_RED + i * 48;
            red_add4(&gs->acc1[b * LS + (rk * 2 + gl) * 4], 1.f, sum4(lds128f(a + 32)), sum4(lds128f(a)) + sum4(lds128f(a + 16)), 1.f);
            TL(74 + i);
        }
    }
    if (warp == 3) {
        if (elect_one()) {
#pragma unroll
            for (int i = 0; i < NSTAGE; i++) mbar_init(BAR(BAR_FULL + i), (i & 4) ? (PAUSE && i == 4 ? 9 : 1) : 5);
#pragma unroll
            for (int i = 0; i <= NS; i++) mbar_init(BAR(BAR_WEMPTY + i), 4);
#pragma unroll
            for (int i = BAR_STATS; i < BAR_X; i++) mbar_init(BAR(i), i == BAR_EMB ? 3 : 1);
            asm volatile("fence.mbarrier_init.release.cluster;" ::: "memory");
        }
        __syncwarp();
        fence_async_smem();
        bar_arrive(0, 96);
        bar_arrive(5, 96);
        bar_arrive(4, 256 + 64 + 128);
        const uint4 z = make_uint4(0, 0, 0, 0);
#pragma unroll
        for (int i = 0; i < 4; i++) sts128(SM_V + (i * 16 + (lane >> 1)) * CH_PITCH + (lane & 1) * 16, z);
        if (lane < 2) sts128(SM_V + NSTAGE * VST_BYTES + lane * 16, z);
        if (lane < 16) sts128(SM_ONES + lane * 16, make_uint4(lane < 8 ? 0x3f803f80u : 0u, 0, 0, 0));
        fence_async_smem();
        asm volatile("barrier.cluster.arrive.relaxed.aligned;" ::: "memory");
        while (clock32() - clk0 < W2DELAY) {}
        weight_load(v, w2, cta, lane);
    }
    if (warp == 0 || warp == 3) {
        const int k = warp & 1;
#pragma unroll
        for (int i = 0; i < 5; i++)
            if (i < 4 || lane < 16) sts128(SM_BNC + k * 2304 + (lane + 32 * i) * 16, v[i]);
        if (lane == 0) TL(k ? 14 : 81);
        __syncwarp();
        weight_block(SM_BNC + k * 2304, gs->wt + k * 2 * NSTAGE * STAGE_BYTES, cta, lane);
        __syncwarp();
        if (lane == 0) TL(k ? 13 : 4);
        if (lane < 2) asm volatile("red.relaxed.gpu.global.add.u32 [%0], 1;" ::"l"(&gs->wcnt[(k * NB + lane) * LS + (k ? 0 : (cta & 8) + (cta >> 4))]) : "memory");
    }

    if (warp >= 8) {
        const int nw = warp - 8;
        bar_sync(4, 256 + 64 + 128);
        const int par = nw >> 2, wq = nw & 3;
        const uint32_t v_off = SM_V + par * VST_BYTES + (lane >> 4) * CH_PITCH + (2 + wq * 16 + (lane & 15)) * 16;
        const uint32_t stg_off = (par * 16 + (lane >> 4) * 8 + (lane & 7)) * 128 + (((2 * wq + ((lane >> 3) & 1)) ^ (lane & 7)) << 4);
        const uint32_t cfa = SM_COEF + rk * 512 + par * 128 + (lane & 3) * 16;
        const uint32_t fbar = BAR(BAR_FULL) + 8 * par;
        uint4* inbox = gs->box + cta * 1024 + nw * 32 + lane;
#pragma unroll 1
        for (int conv = 0; conv < 2; conv++) {
            uint32_t u[4][4];
            float4 cf[4];
            if (conv == 0) {
#pragma unroll
                for (int i = 0; i < 4; i++) { mbar_wait(BAR(BAR_X + i), 0); ldsm4t(u[i], SM_XOWN + stg_off + (i & 1) * 8192 + (i >> 1) * 4096); }
            } else {
                mbar_wait(BAR(BAR_HW), 0);
#pragma unroll
                for (int i = 0; i < 4; i++) ldsm4(u[i], v_off + (i >> 1) * 2 * VST_BYTES + (i & 1) * POS_BYTES);
            }
#pragma unroll
            for (int i = 0; i < 4; i++) cf[i] = lds128f(cfa + conv * 1024 + (i >> 1) * 256 + (i & 1) * 64);
            const uint32_t gst = SM_GST + conv * 16;
            float4 gv = make_float4(0.f, 0.f, 0.f, 0.f);
            float a[4][8];
            group_coefs<0>(gst, gv, cf);
            if (tid == 256) TL(22 + conv * 4);
            if (par) { const unsigned c1 = clock32(); while (clock32() - c1 < PDELAY) {} }
            act8(a[0], u[0], cf[0], cf[1]); act8(a[1], u[1], cf[0], cf[1]);
            stsm_comb<1>(v_off, a[1], a[0]); stsm_comb<-1>(v_off + POS_BYTES, a[1], a[0]);
            publish(fbar, lane);
            if (tid == 256) TL(8 + conv * 8);
            group_coefs<1>(gst, gv, cf);
            act8(a[2], u[2], cf[2], cf[3]); act8(a[3], u[3], cf[2], cf[3]);
            stsm_comb<1>(v_off + 2 * VST_BYTES, a[3], a[2]); stsm_comb<-1>(v_off + 2 * VST_BYTES + POS_BYTES, a[3], a[2]);
            publish(fbar + 16, lane);
            if (tid == 256) TL(84 + conv);
            mbar_wait(BAR(BAR_XO), conv);
            if (conv == 0) {
#pragma unroll
                for (int i = 0; i < 4; i++) ldsm4t(u[i], SM_XOUT + stg_off + (i & 1) * 8192 + (i >> 1) * 4096);
            } else {
#pragma unroll
                for (int i = 0; i < 4; i++) {
                    const uint4 q = lds128(SM_XOUT + (tid - 256) * 16 + (i & 1) * 8192 + (i >> 1) * 4096);
                    u[i][0] = q.x; u[i][1] = q.y; u[i][2] = q.z; u[i][3] = q.w;
                }
                unsigned it = 0;
                while (true) {
                    bool oku = true, okd = true;
#pragma unroll
                    for (int i = 0; i < 8; i++) { oku = oku && u[(i >> 2) * 2][i & 3] != 0; okd = okd && u[(i >> 2) * 2 + 1][i & 3] != 0; }
                    if (__all_sync(0xffffffffu, (oku || !has_up) && (okd || !has_dn)) || ++it > SPIN_LIMIT) break;
#pragma unroll
                    for (int i = 0; i < 4; i++) ld_unit(u[i], inbox + (i & 1) * 512 + (i >> 1) * 256);
                }
#pragma unroll
                for (int i = 0; i < 16; i++) u[i >> 2][i & 3] = ~u[i >> 2][i & 3];
            }
            asm volatile("{\n.reg .pred p;\nsetp.eq.u32 p, %1, 0;\n@p mbarrier.arrive.shared::cta.b64 _, [%0];\n}"
                         ::"r"(S0 + BAR(BAR_FULL + 4)), "r"(lane | ((u[0][0] ^ u[1][0] ^ u[2][0] ^ u[3][0]) == 0x9e3779b9u ? 0 : 0) | (u[3][3] & 0)) : "memory");
            if (tid == 256) TL(24 + conv * 4);
#pragma unroll
            for (int t = 0; t < 2; t++) {
                float o0[8], o3[8];
                act8(o0, u[2 * t], cf[2 * t], cf[2 * t + 1]); act8(o3, u[2 * t + 1], cf[2 * t], cf[2 * t + 1]);
#pragma unroll
                for (int i = 0; i < 8; i++) { o0[i] = has_up ? o0[i] : 0.f; o3[i] = has_dn ? o3[i] : 0.f; }
                stsm_comb<-1>(v_off + (8 + 2 * t) * VST_BYTES, o0, a[2 * t + 1]);
                stsm_comb<-1>(v_off + (8 + 2 * t) * VST_BYTES + POS_BYTES, o3, a[2 * t]);
            }
            fence_async_smem();
            __syncwarp();
            if (lane < 2) mbar_arrive(fbar + 64 + 16 * lane);
            if (tid == 256) TL(23 + conv * 4);
        }
        mbar_wait(BAR(BAR_FULL + NSTAGE - 1), 1);
#pragma unroll
        for (int i = 0; i < 4; i++) inbox[i * 256] = make_uint4(0, 0, 0, 0);
        {
            const int oc0 = (tid - 256) >> 3, seg = lane & 7;
            __nv_bfloat16* dst = out + ((size_t)(ch0 + oc0) * HW + r0) * HW + seg * 8;
            const uint32_t src = SM_XOWN + oc0 * 128 + ((seg ^ (oc0 & 7)) << 4);
            bar_sync(6, 128 + 256);
#pragma unroll
            for (int i = 0; i < 4; i++) *reinterpret_cast<uint4*>(dst + (i & 1) * 32 * HW * HW + (i >> 1) * HW) = lds128(src + i * 4096);
            if (tid == 256) { TL(20); TLG(21); }
        }
    } else if (warp < 4) {
        const int wq = warp;
        bar_sync(2, 128);
        const uint32_t xbase = SM_XOWN + ((lane >> 4) * 8 + (lane & 7)) * 128 + (((2 * wq + ((lane >> 3) & 1)) ^ (lane & 7)) << 4);
        float d0[32], d1[32];
#pragma unroll
        for (int i = 0; i < 32; i++) { d0[i] = 0.f; d1[i] = 0.f; }
#pragma unroll 1
        for (int conv = 0; conv < 2; conv++) {
            fence_acc(d0); fence_acc(d1);
            mma_stages<0>(d0, d1, conv, tid, gs);
            if (conv == 0) {
                asm volatile("wgmma.fence.sync.aligned;" ::: "memory");
                wgmma64<(SM_ONES >> 4) | (8u << 16), (SM_EMB >> 4), 0, 8>(d0);
                wgmma64<(SM_ONES >> 4) | (8u << 16), (SM_EMB >> 4), 0, 8>(d1);
                asm volatile("wgmma.commit_group.sync.aligned;" ::: "memory");
            }
            asm volatile("wgmma.wait_group.sync.aligned 0;" ::: "memory");
            fence_acc(d0); fence_acc(d1);
            if (tid == 0) TL(10 + conv * 8);
            uint32_t hp[32];
#pragma unroll
            for (int i = 0; i < 16; i++) { hp[i] = pack_bf(d0[2 * i], d0[2 * i + 1]); hp[16 + i] = pack_bf(d1[2 * i], d1[2 * i + 1]); }
            if (conv == 1) {
#pragma unroll
                for (int j = 0; j < 8; j++) stsm4t(xbase + j * 2048, hp[4 * j], hp[4 * j + 1], hp[4 * j + 2], hp[4 * j + 3]);
                bar_arrive(6, 128 + 256);
                break;
            }
#pragma unroll
            for (int g = 0; g < 2; g++) {
                float c[2][4] = {{0.f, 0.f, 0.f, 0.f}, {0.f, 0.f, 0.f, 0.f}};
#pragma unroll
                for (int i = 0; i < 4; i++) {
                    stat_mma(c[0], hp[8 * g + 2 * i], hp[8 * g + 2 * i + 1]);
                    stat_mma(c[1], hp[16 + 8 * g + 2 * i], hp[16 + 8 * g + 2 * i + 1]);
                }
#pragma unroll
                for (int i = 0; i < 4; i++) c[0][i] += c[1][i];
                stat_store(c[0], SM_RED + (g * 4 + wq) * 48, lane);
            }
            bar_sync(2, 128);
            if (wq == 0) {
                const uint32_t a = SM_RED + (lane & 7) * 48;
                float q = sum4(lds128f(a)) + sum4(lds128f(a + 16)), sm = sum4(lds128f(a + 32));
                q += __shfl_xor_sync(0xffffffffu, q, 1); sm += __shfl_xor_sync(0xffffffffu, sm, 1);
                q += __shfl_xor_sync(0xffffffffu, q, 2); sm += __shfl_xor_sync(0xffffffffu, sm, 2);
                if ((lane & 27) == 0) red_add4(&gs->acc2[b * LS + rk * 8 + lane], 2.f, sm, q, 2.f);
            }
            if (tid == 0) TL(11);
            const uint32_t hbase = SM_V + (lane >> 4) * CH_PITCH + (2 + wq * 16 + (lane & 15)) * 16;
#pragma unroll
            for (int j = 0; j < 8; j++)
                stsm4(hbase + (j & 3) * VST_BYTES + (j >> 2) * POS_BYTES, hp[4 * j], hp[4 * j + 1], hp[4 * j + 2], hp[4 * j + 3]);
            __syncwarp();
            if (lane == 0) { mbar_arrive(BAR(BAR_HW)); mbar_arrive(BAR(BAR_WEMPTY + 7)); }
#pragma unroll
            for (int row = 0; row < 2; row++) {
                if (row ? has_dn : has_up) {
                    uint4* outbox = gs->box + (row ? (cta + 2) * 1024 : (cta - 2) * 1024 + 512) + tid;
#pragma unroll
                    for (int j = 0; j < 4; j++)
                        outbox[j * 128] = make_uint4(~hp[16 * row + 4 * j], ~hp[16 * row + 4 * j + 1], ~hp[16 * row + 4 * j + 2], ~hp[16 * row + 4 * j + 3]);
                }
            }
            if (tid == 0) TL(12);
#pragma unroll
            for (int j = 0; j < 4; j++) {
                uint32_t p[4], q[4];
                ldsm4t(p, xbase + j * 2048); ldsm4t(q, xbase + 8192 + j * 2048);
#pragma unroll
                for (int i = 0; i < 4; i++) {
                    const float pl = 0.5f * bf_lo(p[i]), ph = 0.5f * bf_hi(p[i]);
                    d0[8 * j + 2 * i] = fmaf(bf_lo(q[i]), 0.5f, pl); d0[8 * j + 2 * i + 1] = fmaf(bf_hi(q[i]), 0.5f, ph);
                    d1[8 * j + 2 * i] = fmaf(bf_lo(q[i]), -0.5f, pl); d1[8 * j + 2 * i + 1] = fmaf(bf_hi(q[i]), -0.5f, ph);
                }
            }
        }
    } else if (warp < 6) {
        bar_sync(5, 96);
        if (warp == 5) {
            asm volatile("barrier.cluster.wait.acquire.aligned;" ::: "memory");
            const uint32_t peer0 = mapa(0, rk ^ 1);
#pragma unroll 1
            for (int conv = 0; conv < 2; conv++) {
#pragma unroll 1
                for (int i = 0; i < 8; i++) {
                    const int st = i + (i & 4);
                    mbar_wait(BAR(BAR_FULL) + 8 * st, conv);
                    if (elect_one())
                        asm volatile("cp.async.bulk.shared::cluster.shared::cta.mbarrier::complete_tx::bytes [%0], [%1], %2, [%3];"
                                     ::"r"(peer0 + SM_V + (st + 4) * VST_BYTES), "r"(S0 + SM_V + st * VST_BYTES), "r"(VST_BYTES),
                                       "r"(peer0 + BAR(BAR_FULL + 4) + 8 * st) : "memory");
                }
                if (lane == 0) TL(86 + conv);
#pragma unroll 1
                for (int i = 0; i < 8; i++) mbar_wait(BAR(BAR_FULL + 4) + 8 * (i + (i & 4)), conv);
                if (lane == 0)
                    asm volatile("mbarrier.arrive.release.cluster.shared::cluster.b64 _, [%0];" ::"r"(peer0 + (conv ? BAR(BAR_ACK) : BAR(BAR_EMB))) : "memory");
            }
            mbar_wait(BAR(BAR_ACK), 0);
        } else {
            if (elect_one()) {
                mbar_expect(BAR(BAR_XO), 16384);
#pragma unroll
                for (int i = 0; i < 4; i++) tma_x(SM_XOUT + i * 4096, &xmap, (i >> 1) ? r0 + 2 : r0 - 1, ch0 + (i & 1) * 32, BAR(BAR_XO));
            }
            __syncwarp();
            mbar_wait(BAR(BAR_STATS), 0);
            unsigned it = 0;
            while (ld_relaxed(&gs->wcnt[(2 * NB + b) * LS]) < (unsigned)NXTRA && ++it < SPIN_LIMIT) __nanosleep(100);
            fence_acquire();
            float ev[2] = {0.f, 0.f};
#pragma unroll
            for (int j = 0; j < NXTRA; j++) {
                ev[0] += __uint_as_float(ld_relaxed(&gs->emb[(j * NB + b) * C + rk * 64 + lane]));
                ev[1] += __uint_as_float(ld_relaxed(&gs->emb[(j * NB + b) * C + rk * 64 + 32 + lane]));
            }
#pragma unroll
            for (int i = 0; i < 2; i++) {
                const float hi = bf_lo(pack_bf(ev[i], 0.f));
                sts128(SM_EMB + (i * 32 + lane) * 16, make_uint4(pack_bf(hi, ev[i] - hi), 0, 0, 0));
            }
            fence_async_smem();
            __syncwarp();
            if (lane == 0) { mbar_arrive(BAR(BAR_EMB)); TL(19); }
        }
    } else if (warp == 6) {
        bar_sync(0, 96);
        const uint32_t ebytes = STAGE_BYTES + ((lane & 4) ? VST_BYTES : 0);
        if (lane < NSTAGE) mbar_expect(BAR(BAR_FULL) + 8 * lane, ebytes);
        const unsigned char* wbase = gs->wt + rk * NSTAGE * STAGE_BYTES;
        unsigned it = 0;
        {
            int g = 0;
#pragma unroll 1
            while (g < NS) {
                unsigned ready = __ballot_sync(0xffffffffu, ld_relaxed(&gs->wcnt[b * LS + rk * 8 + (lane & 7)]) >= 8u) >> g;
                if (++it > SPIN_LIMIT) ready = ~0u;
                if (!(ready & 1)) continue;
                fence_acquire();
                fence_async_global();
                if (lane == 0) TL(g ? 3 : 6);
#pragma unroll 1
                for (; (ready & 1) && g < NS; g++, ready >>= 1)
                    if (elect_one())
                        bulk_g2s(S0 + SM_W + g * STAGE_BYTES, wbase + ((rk * 4 + g) & 7) * STAGE_BYTES, STAGE_BYTES, S0 + BAR(BAR_FULL) + 8 * g);
            }
        }
#pragma unroll 1
        for (int q = 2; q < 8; q++) {
            const unsigned char* wsrc = wbase + ((q >> 2) * 2 * NSTAGE + (q & 2) * 4 + ((q ^ rk) & 1) * 4) * STAGE_BYTES;
            const uint32_t par = ((q >> 1) - 1) & 1;
            if (q == 4) {
                it = 0;
                while (ld_relaxed(&gs->wcnt[(NB + b) * LS]) < (unsigned)NCTA && ++it < SPIN_LIMIT) {}
                fence_acquire();
                fence_async_global();
                if (lane == 0) { mbar_arrive(BAR(BAR_EMB)); TL(2); }
            }
#pragma unroll
            for (int i = 0; i < 4; i++) {
                mbar_wait(BAR(BAR_WEMPTY + i) + 32 * (q & 1), par);
                if (i == 0 && (q == 4 || q == 6)) {
                    if ((lane >> 3) == (q - 4) / 2) mbar_expect(BAR(BAR_FULL) + 8 * lane, ebytes);
                    __syncwarp();
                }
                if (elect_one())
                    bulk_g2s(S0 + SM_W + ((q & 1) * 4 + i) * STAGE_BYTES, wsrc + i * STAGE_BYTES, STAGE_BYTES, S0 + BAR(BAR_FULL + i) + 32 * (q & 3));
            }
        }
    } else {
        const uint2 ga1 = __ldg(reinterpret_cast<const uint2*>(g1) + lane), bt1 = __ldg(reinterpret_cast<const uint2*>(be1) + lane);
        const uint2 ga2 = __ldg(reinterpret_cast<const uint2*>(g2) + lane), bt2 = __ldg(reinterpret_cast<const uint2*>(be2) + lane);
        if (lane < 2) sts128(SM_GST + lane * 16, make_uint4(0, 0, 0, 0));
        sts128f(SM_COEF + lane * 32, make_float4(0.5f * bf_lo(ga1.x), 0.5f * bf_hi(ga1.x), 0.5f * bf_lo(bt1.x), 0.5f * bf_hi(bt1.x)));
        sts128f(SM_COEF + lane * 32 + 16, make_float4(0.5f * bf_lo(ga1.y), 0.5f * bf_hi(ga1.y), 0.5f * bf_lo(bt1.y), 0.5f * bf_hi(bt1.y)));
        sts128f(SM_COEF + 1024 + lane * 32, make_float4(0.5f * bf_lo(ga2.x), 0.5f * bf_hi(ga2.x), 0.5f * bf_lo(bt2.x), 0.5f * bf_hi(bt2.x)));
        sts128f(SM_COEF + 1024 + lane * 32 + 16, make_float4(0.5f * bf_lo(ga2.y), 0.5f * bf_hi(ga2.y), 0.5f * bf_lo(bt2.y), 0.5f * bf_hi(bt2.y)));
        bar_arrive(4, 256 + 64 + 128);
        bar_sync(0, 96);
#pragma unroll 1
        for (int conv = 0; conv < 2; conv++) {
            if (conv == 1) mbar_wait(BAR(BAR_HW), 0);
            const bool wide = conv == 1 && (cta & 63) == 0;
            const float* asrc = (conv ? gs->acc2 : gs->acc1) + b * LS + (wide ? lane & 3 : rk * 2 + (lane & 1)) * 4;
            unsigned it = 0;
#pragma unroll 1
            while (true) {
                const uint4 f = ld_relaxed_v4(asrc);
                const bool ok = ((f.x == 0x42800000u) & (f.w == 0x42800000u)) || ++it > SPIN_LIMIT;
                if (ok && lane < 2) {
                    const float inv_n = 1.0f / (32.0f * HW * HW);
                    const float mean = __uint_as_float(f.y) * inv_n;
                    const float rs = rsqrtf(fmaxf(fmaf(-mean, mean, __uint_as_float(f.z) * inv_n), 0.f) + 1e-5f);
                    asm volatile("st.shared.v2.f32 [%0], {%1,%2};" ::"r"(S0 + SM_GST + conv * 16 + lane * 8), "f"(rs == 0.f ? 1e-38f : rs), "f"(mean * rs) : "memory");
                }
                if (__all_sync(0xffffffffu, ok)) break;
            }
            if (lane == 0) { if (conv == 0) mbar_arrive(BAR(BAR_STATS)); TL(7 + conv * 8); }
        }
        if (elect_one()) {
            mbar_expect(BAR(BAR_XO), 16384);
            bulk_g2s(S0 + SM_XOUT, gs->box + cta * 1024, 16384, S0 + BAR(BAR_XO));
        }
        if ((cta & 63) == 0) {
            if (lane < 16) { gs->acc1[b * LS + lane] = 0.f; gs->wcnt[b * LS + lane] = 0; }
            if (lane < 2) gs->wcnt[((1 + lane) * NB + b) * LS] = 0;
        }
    }
}

}

extern "C" void kernel_launch(void* const* d_in, const int* in_sizes, int n_in, void* d_out, int out_size) {
    (void)in_sizes; (void)n_in; (void)out_size;
    typedef CUresult (*EncodeFn)(CUtensorMap*, CUtensorMapDataType, cuuint32_t, void*, const cuuint64_t*, const cuuint64_t*,
                                 const cuuint32_t*, const cuuint32_t*, CUtensorMapInterleave, CUtensorMapSwizzle,
                                 CUtensorMapL2promotion, CUtensorMapFloatOOBfill);
    static Scratch* gs = nullptr;
    static EncodeFn encode = nullptr;
    if (!gs) {
        cudaFuncSetAttribute(resblock_kernel, cudaFuncAttributeMaxDynamicSharedMemorySize, SM_TOTAL);
        cudaGetSymbolAddress((void**)&gs, g_scratch);
        cudaDriverEntryPointQueryResult qr;
        cudaGetDriverEntryPoint("cuTensorMapEncodeTiled", (void**)&encode, cudaEnableDefault, &qr);
    }
    CUtensorMap xmap;
    const cuuint64_t dims[3] = {HW, HW, NB * C}, strides[2] = {HW * 2, HW * HW * 2};
    const cuuint32_t box[3] = {HW, 1, 32}, es[3] = {1, 1, 1};
    encode(&xmap, CU_TENSOR_MAP_DATA_TYPE_BFLOAT16, 3, d_in[0], dims, strides, box, es, CU_TENSOR_MAP_INTERLEAVE_NONE,
           CU_TENSOR_MAP_SWIZZLE_128B, CU_TENSOR_MAP_L2_PROMOTION_NONE, CU_TENSOR_MAP_FLOAT_OOB_FILL_NONE);
    resblock_kernel<<<NCTA + NXTRA, NTHREADS, SM_TOTAL>>>(
        (const __nv_bfloat16*)d_in[4], (const __nv_bfloat16*)d_in[0], (const __nv_bfloat16*)d_in[1],
        (const __nv_bfloat16*)d_in[2], (const __nv_bfloat16*)d_in[3], (const __nv_bfloat16*)d_in[5],
        (const __nv_bfloat16*)d_in[6], (const __nv_bfloat16*)d_in[7], (const __nv_bfloat16*)d_in[8],
        (__nv_bfloat16*)d_out, gs, xmap);
}
```

```cpp
#include <cuda_runtime.h>
#include <cuda.h>
#include <cuda_bf16.h>
#include <stdint.h>

namespace {

constexpr int C = 128, HW = 64, NB = 2, E = 768;
constexpr int NCTA = NB * HW;
constexpr int NXTRA = 4;
constexpr int NTHREADS = 16 * 32;
constexpr int CH_PITCH = 66 * 16;
constexpr int POS_BYTES = 2 * CH_PITCH;
constexpr int VST_BYTES = 2 * POS_BYTES;
constexpr int STAGE_BYTES = 12288;
constexpr int NSTAGE = 16;
constexpr int NS = 8;
#define XDELAY 400
#define XSTAG 800
#define W2DELAY 1800
#define PDELAY 0
#define PAUSE 0
constexpr int LS = 1056;

constexpr uint32_t SMEM_BASE = 0x400;
constexpr uint32_t SM_XOWN = SMEM_BASE;
constexpr uint32_t SM_XOUT = SM_XOWN + 16384;
constexpr uint32_t SM_V = SM_XOUT + 16384;
constexpr uint32_t SM_W = SM_V + NSTAGE * VST_BYTES + 128;
constexpr uint32_t SM_COEF = SM_W + NS * STAGE_BYTES;
constexpr uint32_t SM_GST = SM_COEF + 2048;
constexpr uint32_t SM_EMB = SM_GST + 128;
constexpr uint32_t SM_ONES = SM_EMB + 1024;
constexpr uint32_t SM_RED = SM_ONES + 256;
constexpr uint32_t SM_BNC = SM_RED + 512;
constexpr uint32_t SM_BAR = SM_BNC + 2 * 2304;
constexpr int BAR_FULL = 0, BAR_WEMPTY = NSTAGE, BAR_HW = BAR_WEMPTY + NS, BAR_STATS = BAR_HW + 1, BAR_EMB = BAR_STATS + 1,
              BAR_ACK = BAR_EMB + 1, BAR_PD = BAR_ACK + 1, BAR_XO = BAR_PD + 1, BAR_X = BAR_XO + 1  , NBAR = BAR_X + 4;
constexpr int SM_TOTAL = SM_BAR + NBAR * 8 - SMEM_BASE;
static_assert(SM_TOTAL <= 232448, "smem");
__host__ __device__ constexpr uint32_t BAR(int i) { return SM_BAR + 8 * i; }

constexpr unsigned SPIN_LIMIT = 1u << 16;

struct Scratch {
    float acc1[NB * LS];
    float acc2[NB * LS];
    unsigned wcnt[3 * NB * LS];
    float emb[NXTRA * NB * C];
    unsigned char wt[2 * 2 * NSTAGE * STAGE_BYTES];
    uint4 box[NCTA * 1024];
};
__device__ __align__(1024) Scratch g_scratch;
#define TL(i) do {} while (0)
#define TLG(i) do {} while (0)

__device__ __forceinline__ unsigned clock32() { unsigned c; asm volatile("mov.u32 %0, %%clock;" : "=r"(c)); return c; }
__device__ __forceinline__ uint32_t mapa(uint32_t a, uint32_t rank) {
    uint32_t d;
    asm("mapa.shared::cluster.u32 %0, %1, %2;" : "=r"(d) : "r"(a), "r"(rank));
    return d;
}
#define S0 mapa(0, blockIdx.x & 1)
__device__ __forceinline__ void mbar_init(uint32_t bar, int cnt) {
    asm volatile("mbarrier.init.shared::cta.b64 [%0], %1;" ::"r"(bar + S0), "r"(cnt) : "memory");
}
__device__ __forceinline__ void mbar_arrive(uint32_t bar) {
    asm volatile("mbarrier.arrive.shared::cta.b64 _, [%0];" ::"r"(bar + S0) : "memory");
}
__device__ __forceinline__ void mbar_expect(uint32_t bar, uint32_t bytes) {
    asm volatile("mbarrier.arrive.expect_tx.shared::cta.b64 _, [%0], %1;" ::"r"(bar + S0), "r"(bytes) : "memory");
}
__device__ __forceinline__ bool mbar_try(uint32_t bar, uint32_t par) {
    uint32_t ok;
    asm volatile("{\n.reg .pred p;\nmbarrier.try_wait.parity.shared::cta.b64 p, [%1], %2;\nselp.u32 %0, 1, 0, p;\n}"
                 : "=r"(ok) : "r"(bar + S0), "r"(par) : "memory");
    return ok;
}
__device__ __forceinline__ bool mbar_test(uint32_t bar, uint32_t par) {
    uint32_t ok;
    asm volatile("{\n.reg .pred p;\nmbarrier.test_wait.parity.shared::cta.b64 p, [%1], %2;\nselp.u32 %0, 1, 0, p;\n}"
                 : "=r"(ok) : "r"(bar + S0), "r"(par) : "memory");
    return ok;
}
__device__ __forceinline__ void mbar_wait(uint32_t bar, uint32_t par) {
    unsigned it = 0;
#pragma unroll 1
    while (!mbar_try(bar, par) && ++it < SPIN_LIMIT) {}
}
__device__ __forceinline__ bool elect_one() {
    uint32_t p;
    asm volatile("{\n.reg .pred p;\nelect.sync _|p, 0xffffffff;\nselp.u32 %0, 1, 0, p;\n}" : "=r"(p));
    return p;
}
__device__ __forceinline__ void fence_async_smem() { asm volatile("fence.proxy.async.shared::cta;" ::: "memory"); }
__device__ __forceinline__ void fence_async_global() { asm volatile("fence.proxy.async.global;" ::: "memory"); }
__device__ __forceinline__ void fence_acquire() { asm volatile("fence.acquire.gpu;" ::: "memory"); }
__device__ __forceinline__ void bar_sync(int id, int n) { asm volatile("bar.sync %0, %1;" ::"r"(id), "r"(n) : "memory"); }
__device__ __forceinline__ void bar_arrive(int id, int n) { asm volatile("bar.arrive %0, %1;" ::"r"(id), "r"(n) : "memory"); }
__device__ __forceinline__ void bulk_g2s(uint32_t dst, const void* src, uint32_t bytes, uint32_t bar) {
    asm volatile("cp.async.bulk.shared::cluster.global.mbarrier::complete_tx::bytes [%0], [%1], %2, [%3];"
                 ::"r"(dst), "l"(src), "r"(bytes), "r"(bar) : "memory");
}
__device__ __forceinline__ void tma_x(uint32_t dst, const CUtensorMap* tm, int row, int ch, uint32_t bar) {
    asm volatile("cp.async.bulk.tensor.3d.shared::cluster.global.mbarrier::complete_tx::bytes [%0], [%1, {%2, %3, %4}], [%5];"
                 ::"r"(dst + S0), "l"(tm), "r"(0), "r"(row), "r"(ch), "r"(bar + S0) : "memory");
}
__device__ __forceinline__ uint4 ld_relaxed_v4(const void* p) {
    uint4 v;
    asm volatile("ld.relaxed.gpu.global.v4.u32 {%0,%1,%2,%3}, [%4];" : "=r"(v.x), "=r"(v.y), "=r"(v.z), "=r"(v.w) : "l"(p) : "memory");
    return v;
}
__device__ __forceinline__ unsigned ld_relaxed(const void* p) {
    unsigned v;
    asm volatile("ld.relaxed.gpu.global.u32 %0, [%1];" : "=r"(v) : "l"(p) : "memory");
    return v;
}
__device__ __forceinline__ void red_add4(float* p, float a, float b, float c, float d) {
    asm volatile("red.relaxed.gpu.global.add.v4.f32 [%0], {%1,%2,%3,%4};" ::"l"(p), "f"(a), "f"(b), "f"(c), "f"(d) : "memory");
}
__device__ __forceinline__ void sts128(uint32_t a, uint4 v) {
    asm volatile("st.shared.v4.u32 [%0], {%1,%2,%3,%4};" ::"r"(a + S0), "r"(v.x), "r"(v.y), "r"(v.z), "r"(v.w) : "memory");
}
__device__ __forceinline__ void sts128f(uint32_t a, float4 v) {
    asm volatile("st.shared.v4.f32 [%0], {%1,%2,%3,%4};" ::"r"(a + S0), "f"(v.x), "f"(v.y), "f"(v.z), "f"(v.w) : "memory");
}
__device__ __forceinline__ void sts32f(uint32_t a, float v) { asm volatile("st.shared.f32 [%0], %1;" ::"r"(a + S0), "f"(v) : "memory"); }
__device__ __forceinline__ uint4 lds128(uint32_t a) {
    uint4 v;
    asm volatile("ld.shared.v4.u32 {%0,%1,%2,%3}, [%4];" : "=r"(v.x), "=r"(v.y), "=r"(v.z), "=r"(v.w) : "r"(a + S0) : "memory");
    return v;
}
__device__ __forceinline__ float4 lds128f(uint32_t a) {
    float4 v;
    asm volatile("ld.shared.v4.f32 {%0,%1,%2,%3}, [%4];" : "=f"(v.x), "=f"(v.y), "=f"(v.z), "=f"(v.w) : "r"(a + S0) : "memory");
    return v;
}
__device__ __forceinline__ float2 lds64f(uint32_t a) {
    float2 v;
    asm volatile("ld.shared.v2.f32 {%0,%1}, [%2];" : "=f"(v.x), "=f"(v.y) : "r"(a + S0) : "memory");
    return v;
}
__device__ __forceinline__ float bf_lo(uint32_t u) { return __uint_as_float(u << 16); }
__device__ __forceinline__ float bf_hi(uint32_t u) { return __uint_as_float(u & 0xffff0000u); }
__device__ __forceinline__ uint32_t pack_bf(float lo, float hi) {
    uint32_t r;
    asm("cvt.rn.bf16x2.f32 %0, %1, %2;" : "=r"(r) : "f"(hi), "f"(lo));
    return r;
}
__device__ __forceinline__ float tanh_fast(float x) {
    float r;
    asm("tanh.approx.f32 %0, %1;" : "=f"(r) : "f"(x));
    return r;
}
__device__ __forceinline__ float silu_half(float h) { return fmaf(h, tanh_fast(h), h); }
__device__ __forceinline__ void ldsm4(uint32_t (&u)[4], uint32_t a) {
    asm volatile("ldmatrix.sync.aligned.m8n8.x4.shared.b16 {%0,%1,%2,%3}, [%4];"
                 : "=r"(u[0]), "=r"(u[1]), "=r"(u[2]), "=r"(u[3]) : "r"(a + S0) : "memory");
}
__device__ __forceinline__ void ldsm4t(uint32_t (&u)[4], uint32_t a) {
    asm volatile("ldmatrix.sync.aligned.m8n8.x4.trans.shared.b16 {%0,%1,%2,%3}, [%4];"
                 : "=r"(u[0]), "=r"(u[1]), "=r"(u[2]), "=r"(u[3]) : "r"(a + S0) : "memory");
}
__device__ __forceinline__ void stsm4(uint32_t a, uint32_t p0, uint32_t p1, uint32_t p2, uint32_t p3) {
    asm volatile("stmatrix.sync.aligned.m8n8.x4.shared.b16 [%0], {%1,%2,%3,%4};" ::"r"(a + S0), "r"(p0), "r"(p1), "r"(p2), "r"(p3) : "memory");
}
__device__ __forceinline__ void stsm4t(uint32_t a, uint32_t p0, uint32_t p1, uint32_t p2, uint32_t p3) {
    asm volatile("stmatrix.sync.aligned.m8n8.x4.trans.shared.b16 [%0], {%1,%2,%3,%4};" ::"r"(a + S0), "r"(p0), "r"(p1), "r"(p2), "r"(p3) : "memory");
}

#define R8(o) "+f"(d[o]), "+f"(d[o + 1]), "+f"(d[o + 2]), "+f"(d[o + 3]), "+f"(d[o + 4]), "+f"(d[o + 5]), "+f"(d[o + 6]), "+f"(d[o + 7])
template <uint32_t ALO, uint32_t BLO, uint64_t AHI = 8, uint64_t BHI = 96>
__device__ __forceinline__ void wgmma64(float (&d)[32]) {
    asm volatile(
        "wgmma.mma_async.sync.aligned.m64n64k16.f32.bf16.bf16 "
        "{%0,%1,%2,%3,%4,%5,%6,%7,%8,%9,%10,%11,%12,%13,%14,%15,%16,%17,%18,%19,%20,%21,%22,%23,%24,%25,%26,%27,%28,%29,%30,%31},"
        " %32, %33, 1, 1, 1, 0, 0;"
        : R8(0), R8(8), R8(16), R8(24)
        : "l"((AHI << 32) | ALO), "l"((BHI << 32) | BLO));
}
__device__ __forceinline__ void fence_acc(float (&d)[32]) {
#pragma unroll
    for (int i = 0; i < 32; i++) asm volatile("" : "+f"(d[i])::"memory");
}
template <int S>
__device__ __forceinline__ void mma_stages(float (&d0)[32], float (&d1)[32], int conv, int tid, Scratch* gs) {
    constexpr uint32_t A = ((SM_V + S * VST_BYTES + 16) >> 4) | ((CH_PITCH >> 4) << 16), A1 = A + (POS_BYTES >> 4);
    constexpr uint32_t B = ((SM_W + (S % NS) * STAGE_BYTES) >> 4) | (8u << 16);
    if (S == 0) mbar_wait(BAR(BAR_FULL), conv);
    constexpr uint32_t NEXT = S + 1 < NSTAGE ? BAR(BAR_FULL + S + 1) : BAR(BAR_EMB);
    const int npar = S + 1 < NSTAGE ? conv : 0;
    const bool next_ok = S != 7 && mbar_test(NEXT, npar);
    if ((S & 7) == 0 && tid == 0) TL(32 + conv * 16 + S);
    asm volatile("wgmma.fence.sync.aligned;" ::: "memory");
    wgmma64<A, B>(d0); wgmma64<A + 1, B + 16>(d0); wgmma64<A + 2, B + 32>(d0);
    wgmma64<A1, B + 48>(d1); wgmma64<A1 + 1, B + 64>(d1); wgmma64<A1 + 2, B + 80>(d1);
    asm volatile("wgmma.commit_group.sync.aligned;" ::: "memory");
    if ((S & 7) != 0) {
        asm volatile("wgmma.wait_group.sync.aligned 1;" ::: "memory");
        if ((tid & 31) == 0) mbar_arrive(BAR(BAR_WEMPTY + (S - 1) % NS));
    }
    if (S == 7) {
        asm volatile("wgmma.wait_group.sync.aligned 0;" ::: "memory");
        fence_acc(d0); fence_acc(d1);
        if ((tid & 31) == 0) mbar_arrive(BAR(BAR_WEMPTY + 7));
#pragma unroll
        for (int i = 0; i < 32; i++) { const float p = d0[i], q = d1[i]; d0[i] = p + q; d1[i] = p - q; }
        fence_acc(d0); fence_acc(d1);
    }
    if (!next_ok) mbar_wait(NEXT, npar);
    if constexpr (S + 1 < NSTAGE) mma_stages<S + 1>(d0, d1, conv, tid, gs);
}

__device__ __forceinline__ int wblk_kc(int cta) { return (((cta >> 3) & 1) * 4 + (cta >> 4)) & 7; }
__device__ __forceinline__ void weight_load(uint4 (&t)[5], const __nv_bfloat16* w, int cta, int lane) {
    const char* base = reinterpret_cast<const char*>(w) + ((cta & 15) * 8 * C + wblk_kc(cta) * 16) * 18;
#pragma unroll
    for (int k = 0; k < 5; k++) {
        const int i = lane + 32 * k, row = (i * 57) >> 10;
        if (k < 4 || lane < 16) t[k] = __ldg(reinterpret_cast<const uint4*>(base + row * (C * 18 - 288) + i * 16));
    }
}
__device__ __forceinline__ void weight_block(uint32_t bounce, unsigned char* wt, int cta, int lane) {
    unsigned char* piece = wt + (((cta >> 3) & 1) * NSTAGE + wblk_kc(cta)) * STAGE_BYTES + (cta & 7) * 1536;
    uint32_t v[18];
#pragma unroll
    for (int i = 0; i < 9; i++) {
        const float2 q = lds64f(bounce + (lane & 7) * 288 + (lane >> 3) * 72 + i * 8);
        v[2 * i] = __float_as_uint(q.x); v[2 * i + 1] = __float_as_uint(q.y);
    }
    unsigned char* dst = piece + (lane >> 4) * 128 + (lane & 7) * 16 + ((lane >> 3) & 1) * 8;
#pragma unroll
    for (int kx = 0; kx < 3; kx++) {
        float u1[4], u2[4];
#pragma unroll
        for (int c = 0; c < 4; c++) {
            const int i0 = 9 * c + kx, i1 = i0 + 3, i2 = i0 + 6;
            const float g0 = (i0 & 1) ? bf_hi(v[i0 >> 1]) : bf_lo(v[i0 >> 1]);
            const float g1 = (i1 & 1) ? bf_hi(v[i1 >> 1]) : bf_lo(v[i1 >> 1]);
            const float g2 = (i2 & 1) ? bf_hi(v[i2 >> 1]) : bf_lo(v[i2 >> 1]);
            const float t = 0.5f * (g0 + g2);
            u1[c] = fmaf(g1, 0.5f, t); u2[c] = fmaf(g1, -0.5f, t);
        }
        *reinterpret_cast<uint2*>(dst + kx * 256) = make_uint2(pack_bf(u1[0], u1[1]), pack_bf(u1[2], u1[3]));
        *reinterpret_cast<uint2*>(dst + 768 + kx * 256) = make_uint2(pack_bf(u2[0], u2[1]), pack_bf(u2[2], u2[3]));
    }
#pragma unroll
    for (int j = 0; j < 6; j++) {
        const int tap = (j / 3) * 6 + j % 3;
        uint32_t o[2];
#pragma unroll
        for (int m = 0; m < 2; m++) {
            const int i0 = 18 * m + tap, i1 = i0 + 9;
            o[m] = __byte_perm(v[i0 >> 1], v[i1 >> 1], ((i0 & 1) ? 0x32u : 0x10u) | ((i1 & 1) ? 0x7600u : 0x5400u));
        }
        *reinterpret_cast<uint2*>(dst + 8 * STAGE_BYTES + j * 256) = make_uint2(o[0], o[1]);
    }
    __syncwarp();
    unsigned acc = 0;
#pragma unroll
    for (int i = 0; i < 3; i++) {
        const int sct = lane + 32 * i;
        acc |= ld_relaxed(piece + (sct >= 48 ? 8 * STAGE_BYTES - 1536 : 0) + sct * 32);
    }
    asm volatile("{\n.reg .pred p;\nsetp.eq.u32 p, %0, 0x9e3779b9;\n@p st.shared.u32 [%1], %0;\n}" ::"r"(acc), "r"(bounce + S0) : "memory");
}

__device__ __forceinline__ void act8(float (&a)[8], const uint32_t (&u)[4], const float4& ca, const float4& cb) {
#pragma unroll
    for (int i = 0; i < 4; i++) {
        const float4& cf = i < 2 ? ca : cb;
        a[2 * i] = silu_half(fmaf(bf_lo(u[i]), cf.x, cf.z));
        a[2 * i + 1] = silu_half(fmaf(bf_hi(u[i]), cf.y, cf.w));
    }
}
template <int SGN>
__device__ __forceinline__ void stsm_comb(uint32_t dst, const float (&p)[8], const float (&q)[8]) {
    uint32_t o[4];
#pragma unroll
    for (int i = 0; i < 4; i++)
        o[i] = SGN > 0 ? pack_bf(p[2 * i] + q[2 * i], p[2 * i + 1] + q[2 * i + 1]) : pack_bf(p[2 * i] - q[2 * i], p[2 * i + 1] - q[2 * i + 1]);
    stsm4(dst, o[0], o[1], o[2], o[3]);
}
template <int T>
__device__ __forceinline__ void group_coefs(uint32_t gst, float4& g, float4 (&cf)[4]) {
    unsigned it = 0;
#pragma unroll 1
    while (!__all_sync(0xffffffffu, (T ? g.z : g.x) != 0.f) && ++it < 8 * SPIN_LIMIT)
        asm volatile("ld.volatile.shared.v4.f32 {%0,%1,%2,%3}, [%4];" : "=f"(g.x), "=f"(g.y), "=f"(g.z), "=f"(g.w) : "r"(gst + S0) : "memory");
    float4 &ca = cf[2 * T], &cb = cf[2 * T + 1];
    const float rs = T ? g.z : g.x, mr = T ? g.w : g.y;
    ca.z = fmaf(-mr, ca.x, ca.z); ca.w = fmaf(-mr, ca.y, ca.w); ca.x *= rs; ca.y *= rs;
    cb.z = fmaf(-mr, cb.x, cb.z); cb.w = fmaf(-mr, cb.y, cb.w); cb.x *= rs; cb.y *= rs;
}
__device__ __forceinline__ void publish(uint32_t bar, int lane) {
    fence_async_smem();
    __syncwarp();
    if (lane == 0) mbar_arrive(bar);
}
__device__ __forceinline__ void load_outer(uint32_t (&w)[4][4], int conv, uint32_t stg_off, int tid) {
#pragma unroll
    for (int i = 0; i < 4; i++) {
        if (conv == 0) {
            ldsm4t(w[i], SM_XOUT + stg_off + (i & 1) * 8192 + (i >> 1) * 4096);
        } else {
            const uint4 q = lds128(SM_XOUT + (tid - 256) * 16 + (i & 1) * 8192 + (i >> 1) * 4096);
            w[i][0] = q.x; w[i][1] = q.y; w[i][2] = q.z; w[i][3] = q.w;
        }
    }
}
__device__ __forceinline__ void ld_unit(uint32_t (&u)[4], const uint4* p) {
    asm volatile("ld.relaxed.gpu.global.v4.u32 {%0,%1,%2,%3}, [%4];" : "=r"(u[0]), "=r"(u[1]), "=r"(u[2]), "=r"(u[3]) : "l"(p) : "memory");
}
__device__ __forceinline__ void stat_mma(float (&c)[4], uint32_t p, uint32_t q) {
    asm("mma.sync.aligned.m16n8k16.row.col.f32.bf16.bf16.f32 {%0,%1,%2,%3}, {%4,%5,%6,%5}, {%4,%6}, {%0,%1,%2,%3};"
        : "+f"(c[0]), "+f"(c[1]), "+f"(c[2]), "+f"(c[3]) : "r"(p), "r"(0x3f803f80u), "r"(q));
}
__device__ __forceinline__ void stat_store(const float (&c)[4], uint32_t dst, int lane) {
    const int g = lane >> 2, t = lane & 3;
    if (t == (g >> 1)) sts32f(dst + g * 4, (g & 1) ? c[1] : c[0]);
    if (g == 7) sts32f(dst + 32 + t * 4, c[2] + c[3]);
}
__device__ __forceinline__ float sum4(float4 v) { return (v.x + v.y) + (v.z + v.w); }
__device__ __noinline__ void side_jobs(const __nv_bfloat16* __restrict__ t_emb, const __nv_bfloat16* __restrict__ w_emb,
                                       const __nv_bfloat16* __restrict__ w2, Scratch* __restrict__ gs, unsigned clk0) {
    const int tid = threadIdx.x, warp = tid >> 5, lane = tid & 31, j = blockIdx.x;
    float tv = 0.f;
    if (lane < 24) tv = __bfloat162float(t_emb[(lane / 12) * E + j * 192 + warp * 12 + lane % 12]);
    if (tid == 0) {
        mbar_init(BAR(0), 1);
        mbar_expect(BAR(0), 192 * C * 2);
        fence_async_smem();
        while (clock32() - clk0 < W2DELAY) {}
#pragma unroll
        for (int i = 0; i < 4; i++) bulk_g2s(S0 + SM_W + i * 12288, w_emb + (j * 192 + i * 48) * C, 12288, S0 + BAR(0));
    }
    if (j == 0 && tid < 32) gs->acc2[(tid >> 4) * LS + (tid & 15)] = 0.f;
    const float sv = silu_half(0.5f * tv);
    __syncthreads();
    mbar_wait(BAR(0), 0);
    float acc[8] = {0.f, 0.f, 0.f, 0.f, 0.f, 0.f, 0.f, 0.f};
#pragma unroll
    for (int i = 0; i < 12; i++) {
        const float2 wq = lds64f(SM_W + (warp * 12 + i) * 256 + lane * 8);
        const uint32_t wx = __float_as_uint(wq.x), wy = __float_as_uint(wq.y);
#pragma unroll
        for (int bb = 0; bb < 2; bb++) {
            const float sx = __shfl_sync(0xffffffffu, sv, bb * 12 + i);
            acc[4 * bb + 0] = fmaf(sx, bf_lo(wx), acc[4 * bb + 0]); acc[4 * bb + 1] = fmaf(sx, bf_hi(wx), acc[4 * bb + 1]);
            acc[4 * bb + 2] = fmaf(sx, bf_lo(wy), acc[4 * bb + 2]); acc[4 * bb + 3] = fmaf(sx, bf_hi(wy), acc[4 * bb + 3]);
        }
    }
    sts128f(SM_V + warp * 1024 + lane * 16, make_float4(acc[0], acc[1], acc[2], acc[3]));
    sts128f(SM_V + warp * 1024 + 512 + lane * 16, make_float4(acc[4], acc[5], acc[6], acc[7]));
    __syncthreads();
    if (tid < 128) {
        float2 sum = make_float2(0.f, 0.f);
#pragma unroll
        for (int w = 0; w < 16; w++) { const float2 p = lds64f(SM_V + w * 1024 + tid * 8); sum.x += p.x; sum.y += p.y; }
        *reinterpret_cast<float2*>(&gs->emb[j * NB * C + tid * 2]) = sum;
        bar_sync(1, 128);
        if (tid < 2) asm volatile("red.release.gpu.global.add.u32 [%0], 1;" ::"l"(&gs->wcnt[(2 * NB + tid) * LS]) : "memory");
    }
}

__global__ void __cluster_dims__(2, 1, 1) __launch_bounds__(NTHREADS, 1)
resblock_kernel(const __nv_bfloat16* __restrict__ w1, const __nv_bfloat16* __restrict__ x,
                const __nv_bfloat16* __restrict__ t_emb, const __nv_bfloat16* __restrict__ g1,
                const __nv_bfloat16* __restrict__ be1, const __nv_bfloat16* __restrict__ w_emb,
                const __nv_bfloat16* __restrict__ g2, const __nv_bfloat16* __restrict__ be2,
                const __nv_bfloat16* __restrict__ w2, __nv_bfloat16* __restrict__ out, Scratch* __restrict__ gs,
                const __grid_constant__ CUtensorMap xmap) {
    const unsigned clk0 = clock32();
    if (threadIdx.x == 480 && blockIdx.x >= NXTRA) TLG(1);
    const int tid = threadIdx.x, lane = tid & 31;
    const int cta = blockIdx.x - NXTRA, b = cta >> 6, rk = cta & 1, r0 = cta & 62;
    uint4 v[5];
    if (tid < 32) weight_load(v, w1, cta & (NCTA - 1), lane);
    const int warp = __shfl_sync(0xffffffffu, tid >> 5, 0);
    if (cta < 0) { side_jobs(t_emb, w_emb, w2, gs, clk0); return; }

    if (warp != 3) asm volatile("barrier.cluster.arrive.relaxed.aligned;" ::: "memory");
    const bool has_up = r0 != 0, has_dn = r0 != HW - 2;
    const int ch0 = b * C + rk * 64;
    if (warp == 1 || warp == 2 || warp == 4 || warp == 5) {
        const int i = warp < 3 ? warp - 1 : warp - 2, gl = i >> 1, row = i & 1;
        const uint32_t tile = SM_XOWN + row * 8192 + gl * 4096;
        if (elect_one()) {
            asm volatile("prefetch.tensormap [%0];" ::"l"(&xmap) : "memory");
            mbar_init(BAR(BAR_X) + 8 * i, 1);
            mbar_expect(BAR(BAR_X) + 8 * i, 4096);
            fence_async_smem();
            while (clock32() - clk0 < XDELAY + gl * XSTAG) {}
            tma_x(tile, &xmap, r0 + row, ch0 + gl * 32, BAR(BAR_X) + 8 * i);
        }
        __syncwarp();
        bar_arrive(4, 256 + 64 + 128);
        mbar_wait(BAR(BAR_X) + 8 * i, 0);
        if (lane == 0) TL(70 + i);
        float c[8][4];
#pragma unroll
        for (int k = 0; k < 8; k++) {
            const uint4 q = lds128(tile + k * 512 + lane * 16);
            c[k][0] = c[k][1] = c[k][2] = c[k][3] = 0.f;
            stat_mma(c[k], q.x, q.y); stat_mma(c[k], q.z, q.w);
        }
#pragma unroll
        for (int k = 0; k < 4; k++) c[0][k] = ((c[0][k] + c[1][k]) + (c[2][k] + c[3][k])) + ((c[4][k] + c[5][k]) + (c[6][k] + c[7][k]));
        stat_store(c[0], SM_RED + i * 48, lane);
        __syncwarp();
        if (lane == 0) {
            const uint32_t a = SM_RED + i * 48;
            red_add4(&gs->acc1[b * LS + (rk * 2 + gl) * 4], 1.f, sum4(lds128f(a + 32)), sum4(lds128f(a)) + sum4(lds128f(a + 16)), 1.f);
            TL(74 + i);
        }
    }
    if (warp == 3) {
        if (elect_one()) {
#pragma unroll
            for (int i = 0; i < NSTAGE; i++) mbar_init(BAR(BAR_FULL + i), (i & 4) ? (PAUSE && i == PAUSE ? 9 : 1) : 5);
#pragma unroll
            for (int i = 0; i <= NS; i++) mbar_init(BAR(BAR_WEMPTY + i), 4);
#pragma unroll
            for (int i = BAR_STATS; i < BAR_X; i++) mbar_init(BAR(i), i == BAR_EMB ? 3 : 1);
            asm volatile("fence.mbarrier_init.release.cluster;" ::: "memory");
        }
        __syncwarp();
        fence_async_smem();
        bar_arrive(0, 96);
        bar_arrive(5, 96);
        bar_arrive(4, 256 + 64 + 128);
        const uint4 z = make_uint4(0, 0, 0, 0);
#pragma unroll
        for (int i = 0; i < 4; i++) sts128(SM_V + (i * 16 + (lane >> 1)) * CH_PITCH + (lane & 1) * 16, z);
        if (lane < 2) sts128(SM_V + NSTAGE * VST_BYTES + lane * 16, z);
        if (lane < 16) sts128(SM_ONES + lane * 16, make_uint4(lane < 8 ? 0x3f803f80u : 0u, 0, 0, 0));
        fence_async_smem();
        asm volatile("barrier.cluster.arrive.relaxed.aligned;" ::: "memory");
        while (clock32() - clk0 < W2DELAY) {}
        weight_load(v, w2, cta, lane);
    }
    if (warp == 0 || warp == 3) {
        const int k = warp & 1;
#pragma unroll
        for (int i = 0; i < 5; i++)
            if (i < 4 || lane < 16) sts128(SM_BNC + k * 2304 + (lane + 32 * i) * 16, v[i]);
        if (lane == 0) TL(k ? 14 : 81);
        __syncwarp();
        weight_block(SM_BNC + k * 2304, gs->wt + k * 2 * NSTAGE * STAGE_BYTES, cta, lane);
        __syncwarp();
        if (lane == 0) TL(k ? 13 : 4);
        if (lane < 2) asm volatile("red.relaxed.gpu.global.add.u32 [%0], 1;" ::"l"(&gs->wcnt[(k * NB + lane) * LS + (k ? 0 : (cta & 8) + (cta >> 4))]) : "memory");
    }

    if (warp >= 8) {
        const int nw = warp - 8;
        bar_sync(4, 256 + 64 + 128);
        const int par = nw >> 2, wq = nw & 3;
        const uint32_t v_off = SM_V + par * VST_BYTES + (lane >> 4) * CH_PITCH + (2 + wq * 16 + (lane & 15)) * 16;
        const uint32_t stg_off = (par * 16 + (lane >> 4) * 8 + (lane & 7)) * 128 + (((2 * wq + ((lane >> 3) & 1)) ^ (lane & 7)) << 4);
        const uint32_t cfa = SM_COEF + rk * 512 + par * 128 + (lane & 3) * 16;
        const uint32_t fbar = BAR(BAR_FULL) + 8 * par;
        uint4* inbox = gs->box + cta * 1024 + nw * 32 + lane;
#pragma unroll 1
        for (int conv = 0; conv < 2; conv++) {
            uint32_t u[4][4], w[4][4];
            float4 cf[4];
            if (conv == 0) {
#pragma unroll
                for (int i = 0; i < 4; i++) { mbar_wait(BAR(BAR_X + i), 0); ldsm4t(u[i], SM_XOWN + stg_off + (i & 1) * 8192 + (i >> 1) * 4096); }
            } else {
                mbar_wait(BAR(BAR_HW), 0);
#pragma unroll
                for (int i = 0; i < 4; i++) ldsm4(u[i], v_off + (i >> 1) * 2 * VST_BYTES + (i & 1) * POS_BYTES);
            }
#pragma unroll
            for (int i = 0; i < 4; i++) cf[i] = lds128f(cfa + conv * 1024 + (i >> 1) * 256 + (i & 1) * 64);
            const uint32_t gst = SM_GST + conv * 16;
            float4 gv;
            float a[4][8];
            bool have = false;
            {
                unsigned it = 0;
#pragma unroll 1
                while (true) {
                    asm volatile("ld.volatile.shared.v4.f32 {%0,%1,%2,%3}, [%4];" : "=f"(gv.x), "=f"(gv.y), "=f"(gv.z), "=f"(gv.w) : "r"(gst + S0) : "memory");
                    const bool xo = !have && mbar_test(BAR(BAR_XO), conv);
                    if (__all_sync(0xffffffffu, gv.x != 0.f) || ++it > 8 * SPIN_LIMIT) break;
                    if (xo) { load_outer(w, conv, stg_off, tid); have = true; }
                }
            }
            group_coefs<0>(gst, gv, cf);
            if (tid == 256) TL(22 + conv * 4);
            if (PDELAY && par) { const unsigned c1 = clock32(); while (clock32() - c1 < PDELAY) {} }
            act8(a[0], u[0], cf[0], cf[1]); act8(a[1], u[1], cf[0], cf[1]);
            stsm_comb<1>(v_off, a[1], a[0]); stsm_comb<-1>(v_off + POS_BYTES, a[1], a[0]);
            publish(fbar, lane);
            if (tid == 256) TL(8 + conv * 8);
            group_coefs<1>(gst, gv, cf);
            act8(a[2], u[2], cf[2], cf[3]); act8(a[3], u[3], cf[2], cf[3]);
            stsm_comb<1>(v_off + 2 * VST_BYTES, a[3], a[2]); stsm_comb<-1>(v_off + 2 * VST_BYTES + POS_BYTES, a[3], a[2]);
            publish(fbar + 16, lane);
            if (tid == 256) TL(84 + conv);
            if (!have) { mbar_wait(BAR(BAR_XO), conv); load_outer(w, conv, stg_off, tid); }
            if (conv == 1) {
                unsigned it = 0;
                while (true) {
                    bool oku = true, okd = true;
#pragma unroll
                    for (int i = 0; i < 8; i++) { oku = oku && w[(i >> 2) * 2][i & 3] != 0; okd = okd && w[(i >> 2) * 2 + 1][i & 3] != 0; }
                    if (__all_sync(0xffffffffu, (oku || !has_up) && (okd || !has_dn)) || ++it > SPIN_LIMIT) break;
#pragma unroll
                    for (int i = 0; i < 4; i++) ld_unit(w[i], inbox + (i & 1) * 512 + (i >> 1) * 256);
                }
#pragma unroll
                for (int i = 0; i < 16; i++) w[i >> 2][i & 3] = ~w[i >> 2][i & 3];
            }
            if (tid == 256) TL(24 + conv * 4);
#pragma unroll
            for (int t = 0; t < 2; t++) {
                float o0[8], o3[8];
                act8(o0, w[2 * t], cf[2 * t], cf[2 * t + 1]); act8(o3, w[2 * t + 1], cf[2 * t], cf[2 * t + 1]);
#pragma unroll
                for (int i = 0; i < 8; i++) { o0[i] = has_up ? o0[i] : 0.f; o3[i] = has_dn ? o3[i] : 0.f; }
                stsm_comb<-1>(v_off + (8 + 2 * t) * VST_BYTES, o0, a[2 * t + 1]);
                stsm_comb<-1>(v_off + (8 + 2 * t) * VST_BYTES + POS_BYTES, o3, a[2 * t]);
            }
            fence_async_smem();
            __syncwarp();
            if (lane < 2) mbar_arrive(fbar + 64 + 16 * lane);
            if (PAUSE && lane == 2) mbar_arrive(BAR(BAR_FULL + PAUSE));
            if (tid == 256) TL(23 + conv * 4);
        }
        mbar_wait(BAR(BAR_FULL + NSTAGE - 1), 1);
#pragma unroll
        for (int i = 0; i < 4; i++) inbox[i * 256] = make_uint4(0, 0, 0, 0);
        {
            const int oc0 = (tid - 256) >> 3, seg = lane & 7;
            __nv_bfloat16* dst = out + ((size_t)(ch0 + oc0) * HW + r0) * HW + seg * 8;
            const uint32_t src = SM_XOWN + oc0 * 128 + ((seg ^ (oc0 & 7)) << 4);
            bar_sync(6, 128 + 256);
#pragma unroll
            for (int i = 0; i < 4; i++) *reinterpret_cast<uint4*>(dst + (i & 1) * 32 * HW * HW + (i >> 1) * HW) = lds128(src + i * 4096);
            if (tid == 256) { TL(20); TLG(21); }
        }
    } else if (warp < 4) {
        const int wq = warp;
        bar_sync(2, 128);
        const uint32_t xbase = SM_XOWN + ((lane >> 4) * 8 + (lane & 7)) * 128 + (((2 * wq + ((lane >> 3) & 1)) ^ (lane & 7)) << 4);
        float d0[32], d1[32];
#pragma unroll
        for (int i = 0; i < 32; i++) { d0[i] = 0.f; d1[i] = 0.f; }
#pragma unroll 1
        for (int conv = 0; conv < 2; conv++) {
            fence_acc(d0); fence_acc(d1);
            mma_stages<0>(d0, d1, conv, tid, gs);
            if (conv == 0) {
                asm volatile("wgmma.fence.sync.aligned;" ::: "memory");
                wgmma64<(SM_ONES >> 4) | (8u << 16), (SM_EMB >> 4), 0, 8>(d0);
                wgmma64<(SM_ONES >> 4) | (8u << 16), (SM_EMB >> 4), 0, 8>(d1);
                asm volatile("wgmma.commit_group.sync.aligned;" ::: "memory");
            }
            asm volatile("wgmma.wait_group.sync.aligned 0;" ::: "memory");
            fence_acc(d0); fence_acc(d1);
            if (tid == 0) TL(10 + conv * 8);
            uint32_t hp[32];
#pragma unroll
            for (int i = 0; i < 16; i++) { hp[i] = pack_bf(d0[2 * i], d0[2 * i + 1]); hp[16 + i] = pack_bf(d1[2 * i], d1[2 * i + 1]); }
            if (conv == 1) {
#pragma unroll
                for (int j = 0; j < 8; j++) stsm4t(xbase + j * 2048, hp[4 * j], hp[4 * j + 1], hp[4 * j + 2], hp[4 * j + 3]);
                bar_arrive(6, 128 + 256);
                break;
            }
#pragma unroll
            for (int g = 0; g < 2; g++) {
                float c[2][4] = {{0.f, 0.f, 0.f, 0.f}, {0.f, 0.f, 0.f, 0.f}};
#pragma unroll
                for (int i = 0; i < 4; i++) {
                    stat_mma(c[0], hp[8 * g + 2 * i], hp[8 * g + 2 * i + 1]);
                    stat_mma(c[1], hp[16 + 8 * g + 2 * i], hp[16 + 8 * g + 2 * i + 1]);
                }
#pragma unroll
                for (int i = 0; i < 4; i++) c[0][i] += c[1][i];
                stat_store(c[0], SM_RED + (g * 4 + wq) * 48, lane);
            }
            bar_sync(2, 128);
            if (wq == 0) {
                const uint32_t a = SM_RED + (lane & 7) * 48;
                float q = sum4(lds128f(a)) + sum4(lds128f(a + 16)), sm = sum4(lds128f(a + 32));
                q += __shfl_xor_sync(0xffffffffu, q, 1); sm += __shfl_xor_sync(0xffffffffu, sm, 1);
                q += __shfl_xor_sync(0xffffffffu, q, 2); sm += __shfl_xor_sync(0xffffffffu, sm, 2);
                if ((lane & 27) == 0) red_add4(&gs->acc2[b * LS + rk * 8 + lane], 2.f, sm, q, 2.f);
            }
            if (tid == 32) asm volatile("mbarrier.arrive.relaxed.cluster.shared::cluster.b64 _, [%0];" ::"r"(mapa(BAR(BAR_PD), rk ^ 1)) : "memory");
            if (tid == 0) TL(11);
            const uint32_t hbase = SM_V + (lane >> 4) * CH_PITCH + (2 + wq * 16 + (lane & 15)) * 16;
#pragma unroll
            for (int j = 0; j < 8; j++)
                stsm4(hbase + (j & 3) * VST_BYTES + (j >> 2) * POS_BYTES, hp[4 * j], hp[4 * j + 1], hp[4 * j + 2], hp[4 * j + 3]);
            __syncwarp();
            if (lane == 0) { mbar_arrive(BAR(BAR_HW)); mbar_arrive(BAR(BAR_WEMPTY + 7)); }
#pragma unroll
            for (int row = 0; row < 2; row++) {
                if (row ? has_dn : has_up) {
                    uint4* outbox = gs->box + (row ? (cta + 2) * 1024 : (cta - 2) * 1024 + 512) + tid;
#pragma unroll
                    for (int j = 0; j < 4; j++)
                        outbox[j * 128] = make_uint4(~hp[16 * row + 4 * j], ~hp[16 * row + 4 * j + 1], ~hp[16 * row + 4 * j + 2], ~hp[16 * row + 4 * j + 3]);
                }
            }
            if (tid == 0) TL(12);
#pragma unroll
            for (int j = 0; j < 4; j++) {
                uint32_t p[4], q[4];
                ldsm4t(p, xbase + j * 2048); ldsm4t(q, xbase + 8192 + j * 2048);
#pragma unroll
                for (int i = 0; i < 4; i++) {
                    const float pl = 0.5f * bf_lo(p[i]), ph = 0.5f * bf_hi(p[i]);
                    d0[8 * j + 2 * i] = fmaf(bf_lo(q[i]), 0.5f, pl); d0[8 * j + 2 * i + 1] = fmaf(bf_hi(q[i]), 0.5f, ph);
                    d1[8 * j + 2 * i] = fmaf(bf_lo(q[i]), -0.5f, pl); d1[8 * j + 2 * i + 1] = fmaf(bf_hi(q[i]), -0.5f, ph);
                }
            }
        }
    } else if (warp < 6) {
        bar_sync(5, 96);
        if (warp == 5) {
            asm volatile("barrier.cluster.wait.acquire.aligned;" ::: "memory");
            const uint32_t peer0 = mapa(0, rk ^ 1);
#pragma unroll 1
            for (int ph = 0; ph < 4; ph++) {
                const int conv = ph >> 1, s0 = (ph & 1) * 8;
                if (ph == 2) mbar_wait(BAR(BAR_PD), 0);
#pragma unroll 1
                for (int st = s0; st < s0 + 4; st++) {
                    mbar_wait(BAR(BAR_FULL) + 8 * st, conv);
                    if (elect_one())
                        asm volatile("cp.async.bulk.shared::cluster.shared::cta.mbarrier::complete_tx::bytes [%0], [%1], %2, [%3];"
                                     ::"r"(peer0 + SM_V + (st + 4) * VST_BYTES), "r"(S0 + SM_V + st * VST_BYTES), "r"(VST_BYTES),
                                       "r"(peer0 + BAR(BAR_FULL + 4) + 8 * st) : "memory");
                }
                if (lane == 0) TL(86 + ph);
                if (ph == 1 || ph == 3) {
#pragma unroll 1
                    for (int i = 0; i < 4; i++) mbar_wait(BAR(BAR_FULL + 4) + 8 * (i + (ph & 2) * 4), conv);
                    if (lane == 0)
                        asm volatile("mbarrier.arrive.relaxed.cluster.shared::cluster.b64 _, [%0];" ::"r"(peer0 + (conv ? BAR(BAR_ACK) : BAR(BAR_EMB))) : "memory");
                }
            }
            mbar_wait(BAR(BAR_ACK), 0);
        } else {
            if (elect_one()) {
                mbar_expect(BAR(BAR_XO), 16384);
#pragma unroll
                for (int i = 0; i < 4; i++) tma_x(SM_XOUT + i * 4096, &xmap, (i >> 1) ? r0 + 2 : r0 - 1, ch0 + (i & 1) * 32, BAR(BAR_XO));
            }
            __syncwarp();
            mbar_wait(BAR(BAR_STATS), 0);
            unsigned it = 0;
            while (ld_relaxed(&gs->wcnt[(2 * NB + b) * LS]) < (unsigned)NXTRA && ++it < SPIN_LIMIT) __nanosleep(100);
            fence_acquire();
            float ev[2] = {0.f, 0.f};
#pragma unroll
            for (int j = 0; j < NXTRA; j++) {
                ev[0] += __uint_as_float(ld_relaxed(&gs->emb[(j * NB + b) * C + rk * 64 + lane]));
                ev[1] += __uint_as_float(ld_relaxed(&gs->emb[(j * NB + b) * C + rk * 64 + 32 + lane]));
            }
#pragma unroll
            for (int i = 0; i < 2; i++) {
                const float hi = bf_lo(pack_bf(ev[i], 0.f));
                sts128(SM_EMB + (i * 32 + lane) * 16, make_uint4(pack_bf(hi, ev[i] - hi), 0, 0, 0));
            }
            fence_async_smem();
            __syncwarp();
            if (lane == 0) { mbar_arrive(BAR(BAR_EMB)); TL(19); }
            mbar_wait(BAR(BAR_HW), 0);
            mbar_wait(BAR(BAR_PD), 0);
            const uint4* probe = gs->box + cta * 1024 + (lane >> 2 & 1) * 512 + 384 + (lane & 3) * 32 + 31;
            const bool need = (lane & 4) ? has_dn : has_up;
            it = 0;
            while (!__all_sync(0xffffffffu, !need || ld_relaxed(probe) != 0) && ++it < SPIN_LIMIT) {}
            if (elect_one()) {
                mbar_expect(BAR(BAR_XO), 16384);
                bulk_g2s(S0 + SM_XOUT, gs->box + cta * 1024, 16384, S0 + BAR(BAR_XO));
            }
            if (lane == 0) TL(5);
        }
    } else if (warp == 6) {
        bar_sync(0, 96);
        const uint32_t ebytes = STAGE_BYTES + ((lane & 4) ? VST_BYTES : 0);
        if (lane < NSTAGE) mbar_expect(BAR(BAR_FULL) + 8 * lane, ebytes);
        const unsigned char* wbase = gs->wt + rk * NSTAGE * STAGE_BYTES;
        unsigned it = 0;
        {
            int g = 0;
#pragma unroll 1
            while (g < NS) {
                unsigned ready = __ballot_sync(0xffffffffu, ld_relaxed(&gs->wcnt[b * LS + rk * 8 + (lane & 7)]) >= 8u) >> g;
                if (++it > SPIN_LIMIT) ready = ~0u;
                if (!(ready & 1)) continue;
                fence_acquire();
                fence_async_global();
                if (lane == 0) TL(g ? 3 : 6);
#pragma unroll 1
                for (; (ready & 1) && g < NS; g++, ready >>= 1)
                    if (elect_one())
                        bulk_g2s(S0 + SM_W + g * STAGE_BYTES, wbase + ((rk * 4 + g) & 7) * STAGE_BYTES, STAGE_BYTES, S0 + BAR(BAR_FULL) + 8 * g);
            }
        }
#pragma unroll 1
        for (int q = 2; q < 8; q++) {
            const unsigned char* wsrc = wbase + ((q >> 2) * 2 * NSTAGE + (q & 2) * 4 + ((q ^ rk) & 1) * 4) * STAGE_BYTES;
            const uint32_t par = ((q >> 1) - 1) & 1;
            if (q == 4) {
                it = 0;
                while (ld_relaxed(&gs->wcnt[(NB + b) * LS]) < (unsigned)NCTA && ++it < SPIN_LIMIT) {}
                fence_acquire();
                fence_async_global();
                if (lane == 0) { mbar_arrive(BAR(BAR_EMB)); TL(2); }
            }
#pragma unroll
            for (int i = 0; i < 4; i++) {
                mbar_wait(BAR(BAR_WEMPTY + i) + 32 * (q & 1), par);
                if (i == 0 && (q == 4 || q == 6)) {
                    if ((lane >> 3) == (q - 4) / 2) mbar_expect(BAR(BAR_FULL) + 8 * lane, ebytes);
                    __syncwarp();
                }
                if (elect_one())
                    bulk_g2s(S0 + SM_W + ((q & 1) * 4 + i) * STAGE_BYTES, wsrc + i * STAGE_BYTES, STAGE_BYTES, S0 + BAR(BAR_FULL + i) + 32 * (q & 3));
            }
        }
    } else {
        const uint2 ga1 = __ldg(reinterpret_cast<const uint2*>(g1) + lane), bt1 = __ldg(reinterpret_cast<const uint2*>(be1) + lane);
        const uint2 ga2 = __ldg(reinterpret_cast<const uint2*>(g2) + lane), bt2 = __ldg(reinterpret_cast<const uint2*>(be2) + lane);
        if (lane < 2) sts128(SM_GST + lane * 16, make_uint4(0, 0, 0, 0));
        sts128f(SM_COEF + lane * 32, make_float4(0.5f * bf_lo(ga1.x), 0.5f * bf_hi(ga1.x), 0.5f * bf_lo(bt1.x), 0.5f * bf_hi(bt1.x)));
        sts128f(SM_COEF + lane * 32 + 16, make_float4(0.5f * bf_lo(ga1.y), 0.5f * bf_hi(ga1.y), 0.5f * bf_lo(bt1.y), 0.5f * bf_hi(bt1.y)));
        sts128f(SM_COEF + 1024 + lane * 32, make_float4(0.5f * bf_lo(ga2.x), 0.5f * bf_hi(ga2.x), 0.5f * bf_lo(bt2.x), 0.5f * bf_hi(bt2.x)));
        sts128f(SM_COEF + 1024 + lane * 32 + 16, make_float4(0.5f * bf_lo(ga2.y), 0.5f * bf_hi(ga2.y), 0.5f * bf_lo(bt2.y), 0.5f * bf_hi(bt2.y)));
        bar_arrive(4, 256 + 64 + 128);
        bar_sync(0, 96);
#pragma unroll 1
        for (int conv = 0; conv < 2; conv++) {
            if (conv == 1) mbar_wait(BAR(BAR_HW), 0);
            const bool wide = conv == 1 && (cta & 63) == 0;
            const float* asrc = (conv ? gs->acc2 : gs->acc1) + b * LS + (wide ? lane & 3 : rk * 2 + (lane & 1)) * 4;
            unsigned it = 0;
#pragma unroll 1
            while (true) {
                const uint4 f = ld_relaxed_v4(asrc);
                const bool ok = ((f.x == 0x42800000u) & (f.w == 0x42800000u)) || ++it > SPIN_LIMIT;
                if (ok && lane < 2) {
                    const float inv_n = 1.0f / (32.0f * HW * HW);
                    const float mean = __uint_as_float(f.y) * inv_n;
                    const float rs = rsqrtf(fmaxf(fmaf(-mean, mean, __uint_as_float(f.z) * inv_n), 0.f) + 1e-5f);
                    asm volatile("st.shared.v2.f32 [%0], {%1,%2};" ::"r"(S0 + SM_GST + conv * 16 + lane * 8), "f"(rs == 0.f ? 1e-38f : rs), "f"(mean * rs) : "memory");
                }
                if (__all_sync(0xffffffffu, ok)) break;
            }
            if (lane == 0) { if (conv == 0) mbar_arrive(BAR(BAR_STATS)); TL(7 + conv * 8); }
        }
        if ((cta & 63) == 0) {
            if (lane < 16) { gs->acc1[b * LS + lane] = 0.f; gs->wcnt[b * LS + lane] = 0; }
            if (lane < 2) gs->wcnt[((1 + lane) * NB + b) * LS] = 0;
        }
    }
}

}

extern "C" void kernel_launch(void* const* d_in, const int* in_sizes, int n_in, void* d_out, int out_size) {
    (void)in_sizes; (void)n_in; (void)out_size;
    typedef CUresult (*EncodeFn)(CUtensorMap*, CUtensorMapDataType, cuuint32_t, void*, const cuuint64_t*, const cuuint64_t*,
                                 const cuuint32_t*, const cuuint32_t*, CUtensorMapInterleave, CUtensorMapSwizzle,
                                 CUtensorMapL2promotion, CUtensorMapFloatOOBfill);
    static Scratch* gs = nullptr;
    static EncodeFn encode = nullptr;
    if (!gs) {
        cudaFuncSetAttribute(resblock_kernel, cudaFuncAttributeMaxDynamicSharedMemorySize, SM_TOTAL);
        cudaGetSymbolAddress((void**)&gs, g_scratch);
        cudaDriverEntryPointQueryResult qr;
        cudaGetDriverEntryPoint("cuTensorMapEncodeTiled", (void**)&encode, cudaEnableDefault, &qr);
    }
    CUtensorMap xmap;
    const cuuint64_t dims[3] = {HW, HW, NB * C}, strides[2] = {HW * 2, HW * HW * 2};
    const cuuint32_t box[3] = {HW, 1, 32}, es[3] = {1, 1, 1};
    encode(&xmap, CU_TENSOR_MAP_DATA_TYPE_BFLOAT16, 3, d_in[0], dims, strides, box, es, CU_TENSOR_MAP_INTERLEAVE_NONE,
           CU_TENSOR_MAP_SWIZZLE_128B, CU_TENSOR_MAP_L2_PROMOTION_NONE, CU_TENSOR_MAP_FLOAT_OOB_FILL_NONE);
    resblock_kernel<<<NCTA + NXTRA, NTHREADS, SM_TOTAL>>>(
        (const __nv_bfloat16*)d_in[4], (const __nv_bfloat16*)d_in[0], (const __nv_bfloat16*)d_in[1],
        (const __nv_bfloat16*)d_in[2], (const __nv_bfloat16*)d_in[3], (const __nv_bfloat16*)d_in[5],
        (const __nv_bfloat16*)d_in[6], (const __nv_bfloat16*)d_in[7], (const __nv_bfloat16*)d_in[8],
        (__nv_bfloat16*)d_out, gs, xmap);
}
```

```cpp
#include <cuda_runtime.h>
#include <cuda.h>
#include <cuda_bf16.h>
#include <stdint.h>

namespace {

constexpr int C = 128, HW = 64, NB = 2, E = 768;
constexpr int NCTA = NB * HW;
constexpr int NXTRA = 4;
constexpr int NTHREADS = 16 * 32;
constexpr int CH_PITCH = 66 * 16;
constexpr int POS_BYTES = 2 * CH_PITCH;
constexpr int VST_BYTES = 2 * POS_BYTES;
constexpr int STAGE_BYTES = 12288;
constexpr int NSTAGE = 16;
constexpr int NS = 8;
#define XDELAY 400
#define XSTAG 800
#define W2DELAY 1800
#define SPLIT 0
#define FDELAY 1000
#define PAUSE 0
constexpr int LS = 1056;

constexpr uint32_t SMEM_BASE = 0x400;
constexpr uint32_t SM_XOWN = SMEM_BASE;
constexpr uint32_t SM_XOUT = SM_XOWN + 16384;
constexpr uint32_t SM_V = SM_XOUT + 16384;
constexpr uint32_t SM_W = SM_V + NSTAGE * VST_BYTES + 128;
constexpr uint32_t SM_COEF = SM_W + NS * STAGE_BYTES;
constexpr uint32_t SM_GST = SM_COEF + 2048;
constexpr uint32_t SM_EMB = SM_GST + 128;
constexpr uint32_t SM_ONES = SM_EMB + 1024;
constexpr uint32_t SM_RED = SM_ONES + 256;
constexpr uint32_t SM_BNC = SM_RED + 512;
constexpr uint32_t SM_BAR = SM_BNC + 2 * 2304;
constexpr int BAR_FULL = 0, BAR_WEMPTY = NSTAGE, BAR_HW = BAR_WEMPTY + NS, BAR_STATS = BAR_HW + 1, BAR_EMB = BAR_STATS + 1,
              BAR_ACK = BAR_EMB + 1, BAR_PD = BAR_ACK + 1, BAR_VD = BAR_PD + 1, BAR_XO = BAR_VD + 1, BAR_X = BAR_XO + 1  , NBAR = BAR_X + 4;
constexpr int SM_TOTAL = SM_BAR + NBAR * 8 - SMEM_BASE;
static_assert(SM_TOTAL <= 232448, "smem");
__host__ __device__ constexpr uint32_t BAR(int i) { return SM_BAR + 8 * i; }

constexpr unsigned SPIN_LIMIT = 1u << 16;

struct Scratch {
    float acc1[NB * LS];
    float acc2[NB * LS];
    unsigned wcnt[3 * NB * LS];
    float emb[NXTRA * NB * C];
    unsigned char wt[2 * 2 * NSTAGE * STAGE_BYTES];
    uint4 box[NCTA * 1024];
};
__device__ __align__(1024) Scratch g_scratch;
#define TL(i) do {} while (0)
#define TLG(i) do {} while (0)

__device__ __forceinline__ unsigned clock32() { unsigned c; asm volatile("mov.u32 %0, %%clock;" : "=r"(c)); return c; }
__device__ __forceinline__ uint32_t mapa(uint32_t a, uint32_t rank) {
    uint32_t d;
    asm("mapa.shared::cluster.u32 %0, %1, %2;" : "=r"(d) : "r"(a), "r"(rank));
    return d;
}
#define S0 mapa(0, blockIdx.x & 1)
__device__ __forceinline__ void mbar_init(uint32_t bar, int cnt) {
    asm volatile("mbarrier.init.shared::cta.b64 [%0], %1;" ::"r"(bar + S0), "r"(cnt) : "memory");
}
__device__ __forceinline__ void mbar_arrive(uint32_t bar) {
    asm volatile("mbarrier.arrive.shared::cta.b64 _, [%0];" ::"r"(bar + S0) : "memory");
}
__device__ __forceinline__ void mbar_expect(uint32_t bar, uint32_t bytes) {
    asm volatile("mbarrier.arrive.expect_tx.shared::cta.b64 _, [%0], %1;" ::"r"(bar + S0), "r"(bytes) : "memory");
}
__device__ __forceinline__ bool mbar_try(uint32_t bar, uint32_t par) {
    uint32_t ok;
    asm volatile("{\n.reg .pred p;\nmbarrier.try_wait.parity.shared::cta.b64 p, [%1], %2;\nselp.u32 %0, 1, 0, p;\n}"
                 : "=r"(ok) : "r"(bar + S0), "r"(par) : "memory");
    return ok;
}
__device__ __forceinline__ bool mbar_test(uint32_t bar, uint32_t par) {
    uint32_t ok;
    asm volatile("{\n.reg .pred p;\nmbarrier.test_wait.parity.shared::cta.b64 p, [%1], %2;\nselp.u32 %0, 1, 0, p;\n}"
                 : "=r"(ok) : "r"(bar + S0), "r"(par) : "memory");
    return ok;
}
__device__ __forceinline__ void mbar_wait(uint32_t bar, uint32_t par) {
    unsigned it = 0;
#pragma unroll 1
    while (!mbar_try(bar, par) && ++it < SPIN_LIMIT) {}
}
__device__ __forceinline__ bool elect_one() {
    uint32_t p;
    asm volatile("{\n.reg .pred p;\nelect.sync _|p, 0xffffffff;\nselp.u32 %0, 1, 0, p;\n}" : "=r"(p));
    return p;
}
__device__ __forceinline__ void fence_async_smem() { asm volatile("fence.proxy.async.shared::cta;" ::: "memory"); }
__device__ __forceinline__ void fence_async_global() { asm volatile("fence.proxy.async.global;" ::: "memory"); }
__device__ __forceinline__ void fence_acquire() { asm volatile("fence.acquire.gpu;" ::: "memory"); }
__device__ __forceinline__ void bar_sync(int id, int n) { asm volatile("bar.sync %0, %1;" ::"r"(id), "r"(n) : "memory"); }
__device__ __forceinline__ void bar_arrive(int id, int n) { asm volatile("bar.arrive %0, %1;" ::"r"(id), "r"(n) : "memory"); }
__device__ __forceinline__ void bulk_g2s(uint32_t dst, const void* src, uint32_t bytes, uint32_t bar) {
    asm volatile("cp.async.bulk.shared::cluster.global.mbarrier::complete_tx::bytes [%0], [%1], %2, [%3];"
                 ::"r"(dst), "l"(src), "r"(bytes), "r"(bar) : "memory");
}
__device__ __forceinline__ void tma_x(uint32_t dst, const CUtensorMap* tm, int row, int ch, uint32_t bar) {
    asm volatile("cp.async.bulk.tensor.3d.shared::cluster.global.mbarrier::complete_tx::bytes [%0], [%1, {%2, %3, %4}], [%5];"
                 ::"r"(dst + S0), "l"(tm), "r"(0), "r"(row), "r"(ch), "r"(bar + S0) : "memory");
}
__device__ __forceinline__ uint4 ld_relaxed_v4(const void* p) {
    uint4 v;
    asm volatile("ld.relaxed.gpu.global.v4.u32 {%0,%1,%2,%3}, [%4];" : "=r"(v.x), "=r"(v.y), "=r"(v.z), "=r"(v.w) : "l"(p) : "memory");
    return v;
}
__device__ __forceinline__ unsigned ld_relaxed(const void* p) {
    unsigned v;
    asm volatile("ld.relaxed.gpu.global.u32 %0, [%1];" : "=r"(v) : "l"(p) : "memory");
    return v;
}
__device__ __forceinline__ void red_add4(float* p, float a, float b, float c, float d) {
    asm volatile("red.relaxed.gpu.global.add.v4.f32 [%0], {%1,%2,%3,%4};" ::"l"(p), "f"(a), "f"(b), "f"(c), "f"(d) : "memory");
}
__device__ __forceinline__ void sts128(uint32_t a, uint4 v) {
    asm volatile("st.shared.v4.u32 [%0], {%1,%2,%3,%4};" ::"r"(a + S0), "r"(v.x), "r"(v.y), "r"(v.z), "r"(v.w) : "memory");
}
__device__ __forceinline__ void sts128f(uint32_t a, float4 v) {
    asm volatile("st.shared.v4.f32 [%0], {%1,%2,%3,%4};" ::"r"(a + S0), "f"(v.x), "f"(v.y), "f"(v.z), "f"(v.w) : "memory");
}
__device__ __forceinline__ void sts32f(uint32_t a, float v) { asm volatile("st.shared.f32 [%0], %1;" ::"r"(a + S0), "f"(v) : "memory"); }
__device__ __forceinline__ uint4 lds128(uint32_t a) {
    uint4 v;
    asm volatile("ld.shared.v4.u32 {%0,%1,%2,%3}, [%4];" : "=r"(v.x), "=r"(v.y), "=r"(v.z), "=r"(v.w) : "r"(a + S0) : "memory");
    return v;
}
__device__ __forceinline__ float4 lds128f(uint32_t a) {
    float4 v;
    asm volatile("ld.shared.v4.f32 {%0,%1,%2,%3}, [%4];" : "=f"(v.x), "=f"(v.y), "=f"(v.z), "=f"(v.w) : "r"(a + S0) : "memory");
    return v;
}
__device__ __forceinline__ float2 lds64f(uint32_t a) {
    float2 v;
    asm volatile("ld.shared.v2.f32 {%0,%1}, [%2];" : "=f"(v.x), "=f"(v.y) : "r"(a + S0) : "memory");
    return v;
}
__device__ __forceinline__ float bf_lo(uint32_t u) { return __uint_as_float(u << 16); }
__device__ __forceinline__ float bf_hi(uint32_t u) { return __uint_as_float(u & 0xffff0000u); }
__device__ __forceinline__ uint32_t pack_bf(float lo, float hi) {
    uint32_t r;
    asm("cvt.rn.bf16x2.f32 %0, %1, %2;" : "=r"(r) : "f"(hi), "f"(lo));
    return r;
}
__device__ __forceinline__ float tanh_fast(float x) {
    float r;
    asm("tanh.approx.f32 %0, %1;" : "=f"(r) : "f"(x));
    return r;
}
__device__ __forceinline__ float silu_half(float h) { return fmaf(h, tanh_fast(h), h); }
__device__ __forceinline__ void ldsm4(uint32_t (&u)[4], uint32_t a) {
    asm volatile("ldmatrix.sync.aligned.m8n8.x4.shared.b16 {%0,%1,%2,%3}, [%4];"
                 : "=r"(u[0]), "=r"(u[1]), "=r"(u[2]), "=r"(u[3]) : "r"(a + S0) : "memory");
}
__device__ __forceinline__ void ldsm4t(uint32_t (&u)[4], uint32_t a) {
    asm volatile("ldmatrix.sync.aligned.m8n8.x4.trans.shared.b16 {%0,%1,%2,%3}, [%4];"
                 : "=r"(u[0]), "=r"(u[1]), "=r"(u[2]), "=r"(u[3]) : "r"(a + S0) : "memory");
}
__device__ __forceinline__ void stsm4(uint32_t a, uint32_t p0, uint32_t p1, uint32_t p2, uint32_t p3) {
    asm volatile("stmatrix.sync.aligned.m8n8.x4.shared.b16 [%0], {%1,%2,%3,%4};" ::"r"(a + S0), "r"(p0), "r"(p1), "r"(p2), "r"(p3) : "memory");
}
__device__ __forceinline__ void stsm4t(uint32_t a, uint32_t p0, uint32_t p1, uint32_t p2, uint32_t p3) {
    asm volatile("stmatrix.sync.aligned.m8n8.x4.trans.shared.b16 [%0], {%1,%2,%3,%4};" ::"r"(a + S0), "r"(p0), "r"(p1), "r"(p2), "r"(p3) : "memory");
}

#define R8(o) "+f"(d[o]), "+f"(d[o + 1]), "+f"(d[o + 2]), "+f"(d[o + 3]), "+f"(d[o + 4]), "+f"(d[o + 5]), "+f"(d[o + 6]), "+f"(d[o + 7])
template <uint32_t ALO, uint32_t BLO, uint64_t AHI = 8, uint64_t BHI = 96>
__device__ __forceinline__ void wgmma64(float (&d)[32]) {
    asm volatile(
        "wgmma.mma_async.sync.aligned.m64n64k16.f32.bf16.bf16 "
        "{%0,%1,%2,%3,%4,%5,%6,%7,%8,%9,%10,%11,%12,%13,%14,%15,%16,%17,%18,%19,%20,%21,%22,%23,%24,%25,%26,%27,%28,%29,%30,%31},"
        " %32, %33, 1, 1, 1, 0, 0;"
        : R8(0), R8(8), R8(16), R8(24)
        : "l"((AHI << 32) | ALO), "l"((BHI << 32) | BLO));
}
__device__ __forceinline__ void fence_acc(float (&d)[32]) {
#pragma unroll
    for (int i = 0; i < 32; i++) asm volatile("" : "+f"(d[i])::"memory");
}
template <int S>
__device__ __forceinline__ void mma_stages(float (&d0)[32], float (&d1)[32], int conv, int tid, Scratch* gs) {
    constexpr uint32_t A = ((SM_V + S * VST_BYTES + 16) >> 4) | ((CH_PITCH >> 4) << 16), A1 = A + (POS_BYTES >> 4);
    constexpr uint32_t B = ((SM_W + (S % NS) * STAGE_BYTES) >> 4) | (8u << 16);
    if (S == 0) mbar_wait(BAR(BAR_FULL), conv);
    constexpr uint32_t NEXT = S + 1 < NSTAGE ? BAR(BAR_FULL + S + 1) : BAR(BAR_EMB);
    const int npar = S + 1 < NSTAGE ? conv : 0;
    const bool next_ok = S != 7 && mbar_test(NEXT, npar);
    if ((S & 7) == 0 && tid == 0) TL(32 + conv * 16 + S);
    asm volatile("wgmma.fence.sync.aligned;" ::: "memory");
    wgmma64<A, B>(d0); wgmma64<A + 1, B + 16>(d0); wgmma64<A + 2, B + 32>(d0);
    wgmma64<A1, B + 48>(d1); wgmma64<A1 + 1, B + 64>(d1); wgmma64<A1 + 2, B + 80>(d1);
    asm volatile("wgmma.commit_group.sync.aligned;" ::: "memory");
    if ((S & 7) != 0) {
        asm volatile("wgmma.wait_group.sync.aligned 1;" ::: "memory");
        if ((tid & 31) == 0) mbar_arrive(BAR(BAR_WEMPTY + (S - 1) % NS));
    }
    if (S == 7) {
        asm volatile("wgmma.wait_group.sync.aligned 0;" ::: "memory");
        fence_acc(d0); fence_acc(d1);
        if ((tid & 31) == 0) mbar_arrive(BAR(BAR_WEMPTY + 7));
#pragma unroll
        for (int i = 0; i < 32; i++) { const float p = d0[i], q = d1[i]; d0[i] = p + q; d1[i] = p - q; }
        fence_acc(d0); fence_acc(d1);
    }
    if (!next_ok) mbar_wait(NEXT, npar);
    if constexpr (S + 1 < NSTAGE) mma_stages<S + 1>(d0, d1, conv, tid, gs);
}

__device__ __forceinline__ int wblk_kc(int cta) { return (((cta >> 3) & 1) * 4 + (cta >> 4)) & 7; }
__device__ __forceinline__ void weight_load(uint4 (&t)[5], const __nv_bfloat16* w, int cta, int lane) {
    const char* base = reinterpret_cast<const char*>(w) + ((cta & 15) * 8 * C + wblk_kc(cta) * 16) * 18;
#pragma unroll
    for (int k = 0; k < 5; k++) {
        const int i = lane + 32 * k, row = (i * 57) >> 10;
        if (k < 4 || lane < 16) t[k] = __ldg(reinterpret_cast<const uint4*>(base + row * (C * 18 - 288) + i * 16));
    }
}
__device__ __forceinline__ void weight_block(uint32_t bounce, unsigned char* wt, int cta, int lane) {
    unsigned char* piece = wt + (((cta >> 3) & 1) * NSTAGE + wblk_kc(cta)) * STAGE_BYTES + (cta & 7) * 1536;
    uint32_t v[18];
#pragma unroll
    for (int i = 0; i < 9; i++) {
        const float2 q = lds64f(bounce + (lane & 7) * 288 + (lane >> 3) * 72 + i * 8);
        v[2 * i] = __float_as_uint(q.x); v[2 * i + 1] = __float_as_uint(q.y);
    }
    unsigned char* dst = piece + (lane >> 4) * 128 + (lane & 7) * 16 + ((lane >> 3) & 1) * 8;
#pragma unroll
    for (int kx = 0; kx < 3; kx++) {
        float u1[4], u2[4];
#pragma unroll
        for (int c = 0; c < 4; c++) {
            const int i0 = 9 * c + kx, i1 = i0 + 3, i2 = i0 + 6;
            const float g0 = (i0 & 1) ? bf_hi(v[i0 >> 1]) : bf_lo(v[i0 >> 1]);
            const float g1 = (i1 & 1) ? bf_hi(v[i1 >> 1]) : bf_lo(v[i1 >> 1]);
            const float g2 = (i2 & 1) ? bf_hi(v[i2 >> 1]) : bf_lo(v[i2 >> 1]);
            const float t = 0.5f * (g0 + g2);
            u1[c] = fmaf(g1, 0.5f, t); u2[c] = fmaf(g1, -0.5f, t);
        }
        *reinterpret_cast<uint2*>(dst + kx * 256) = make_uint2(pack_bf(u1[0], u1[1]), pack_bf(u1[2], u1[3]));
        *reinterpret_cast<uint2*>(dst + 768 + kx * 256) = make_uint2(pack_bf(u2[0], u2[1]), pack_bf(u2[2], u2[3]));
    }
#pragma unroll
    for (int j = 0; j < 6; j++) {
        const int tap = (j / 3) * 6 + j % 3;
        uint32_t o[2];
#pragma unroll
        for (int m = 0; m < 2; m++) {
            const int i0 = 18 * m + tap, i1 = i0 + 9;
            o[m] = __byte_perm(v[i0 >> 1], v[i1 >> 1], ((i0 & 1) ? 0x32u : 0x10u) | ((i1 & 1) ? 0x7600u : 0x5400u));
        }
        *reinterpret_cast<uint2*>(dst + 8 * STAGE_BYTES + j * 256) = make_uint2(o[0], o[1]);
    }
    __syncwarp();
    unsigned acc = 0;
#pragma unroll
    for (int i = 0; i < 3; i++) {
        const int sct = lane + 32 * i;
        acc |= ld_relaxed(piece + (sct >= 48 ? 8 * STAGE_BYTES - 1536 : 0) + sct * 32);
    }
    asm volatile("{\n.reg .pred p;\nsetp.eq.u32 p, %0, 0x9e3779b9;\n@p st.shared.u32 [%1], %0;\n}" ::"r"(acc), "r"(bounce + S0) : "memory");
}

__device__ __forceinline__ void act8(float (&a)[8], const uint32_t (&u)[4], const float4& ca, const float4& cb) {
#pragma unroll
    for (int i = 0; i < 4; i++) {
        const float4& cf = i < 2 ? ca : cb;
        a[2 * i] = silu_half(fmaf(bf_lo(u[i]), cf.x, cf.z));
        a[2 * i + 1] = silu_half(fmaf(bf_hi(u[i]), cf.y, cf.w));
    }
}
template <int SGN>
__device__ __forceinline__ void stsm_comb(uint32_t dst, const float (&p)[8], const float (&q)[8]) {
    uint32_t o[4];
#pragma unroll
    for (int i = 0; i < 4; i++)
        o[i] = SGN > 0 ? pack_bf(p[2 * i] + q[2 * i], p[2 * i + 1] + q[2 * i + 1]) : pack_bf(p[2 * i] - q[2 * i], p[2 * i + 1] - q[2 * i + 1]);
    stsm4(dst, o[0], o[1], o[2], o[3]);
}
template <int T>
__device__ __forceinline__ void group_coefs(uint32_t gst, float4& g, float4 (&cf)[4]) {
    unsigned it = 0;
#pragma unroll 1
    while (!__all_sync(0xffffffffu, (T ? g.z : g.x) != 0.f) && ++it < 8 * SPIN_LIMIT)
        asm volatile("ld.volatile.shared.v4.f32 {%0,%1,%2,%3}, [%4];" : "=f"(g.x), "=f"(g.y), "=f"(g.z), "=f"(g.w) : "r"(gst + S0) : "memory");
    float4 &ca = cf[2 * T], &cb = cf[2 * T + 1];
    const float rs = T ? g.z : g.x, mr = T ? g.w : g.y;
    ca.z = fmaf(-mr, ca.x, ca.z); ca.w = fmaf(-mr, ca.y, ca.w); ca.x *= rs; ca.y *= rs;
    cb.z = fmaf(-mr, cb.x, cb.z); cb.w = fmaf(-mr, cb.y, cb.w); cb.x *= rs; cb.y *= rs;
}
__device__ __forceinline__ void publish(uint32_t bar, int lane) {
    fence_async_smem();
    __syncwarp();
    if (lane == 0) mbar_arrive(bar);
}
__device__ __forceinline__ void load_outer(uint32_t (&w)[4][4], int conv, uint32_t stg_off, int tid) {
#pragma unroll
    for (int i = 0; i < 4; i++) {
        if (conv == 0) {
            ldsm4t(w[i], SM_XOUT + stg_off + (i & 1) * 8192 + (i >> 1) * 4096);
        } else {
            const uint4 q = lds128(SM_XOUT + (tid - 256) * 16 + (i & 1) * 8192 + (i >> 1) * 4096);
            w[i][0] = q.x; w[i][1] = q.y; w[i][2] = q.z; w[i][3] = q.w;
        }
    }
}
__device__ __forceinline__ void ld_unit(uint32_t (&u)[4], const uint4* p) {
    asm volatile("ld.relaxed.gpu.global.v4.u32 {%0,%1,%2,%3}, [%4];" : "=r"(u[0]), "=r"(u[1]), "=r"(u[2]), "=r"(u[3]) : "l"(p) : "memory");
}
__device__ __forceinline__ void stat_mma(float (&c)[4], uint32_t p, uint32_t q) {
    asm("mma.sync.aligned.m16n8k16.row.col.f32.bf16.bf16.f32 {%0,%1,%2,%3}, {%4,%5,%6,%5}, {%4,%6}, {%0,%1,%2,%3};"
        : "+f"(c[0]), "+f"(c[1]), "+f"(c[2]), "+f"(c[3]) : "r"(p), "r"(0x3f803f80u), "r"(q));
}
__device__ __forceinline__ void stat_store(const float (&c)[4], uint32_t dst, int lane) {
    const int g = lane >> 2, t = lane & 3;
    if (t == (g >> 1)) sts32f(dst + g * 4, (g & 1) ? c[1] : c[0]);
    if (g == 7) sts32f(dst + 32 + t * 4, c[2] + c[3]);
}
__device__ __forceinline__ float sum4(float4 v) { return (v.x + v.y) + (v.z + v.w); }
__device__ __noinline__ void side_jobs(const __nv_bfloat16* __restrict__ t_emb, const __nv_bfloat16* __restrict__ w_emb,
                                       const __nv_bfloat16* __restrict__ w2, Scratch* __restrict__ gs, unsigned clk0) {
    const int tid = threadIdx.x, warp = tid >> 5, lane = tid & 31, j = blockIdx.x;
    float tv = 0.f;
    if (lane < 24) tv = __bfloat162float(t_emb[(lane / 12) * E + j * 192 + warp * 12 + lane % 12]);
    if (tid == 0) {
        mbar_init(BAR(0), 1);
        mbar_expect(BAR(0), 192 * C * 2);
        fence_async_smem();
        while (clock32() - clk0 < W2DELAY) {}
#pragma unroll
        for (int i = 0; i < 4; i++) bulk_g2s(S0 + SM_W + i * 12288, w_emb + (j * 192 + i * 48) * C, 12288, S0 + BAR(0));
    }
    if (j == 0 && tid < 32) gs->acc2[(tid >> 4) * LS + (tid & 15)] = 0.f;
    const float sv = silu_half(0.5f * tv);
    __syncthreads();
    mbar_wait(BAR(0), 0);
    float acc[8] = {0.f, 0.f, 0.f, 0.f, 0.f, 0.f, 0.f, 0.f};
#pragma unroll
    for (int i = 0; i < 12; i++) {
        const float2 wq = lds64f(SM_W + (warp * 12 + i) * 256 + lane * 8);
        const uint32_t wx = __float_as_uint(wq.x), wy = __float_as_uint(wq.y);
#pragma unroll
        for (int bb = 0; bb < 2; bb++) {
            const float sx = __shfl_sync(0xffffffffu, sv, bb * 12 + i);
            acc[4 * bb + 0] = fmaf(sx, bf_lo(wx), acc[4 * bb + 0]); acc[4 * bb + 1] = fmaf(sx, bf_hi(wx), acc[4 * bb + 1]);
            acc[4 * bb + 2] = fmaf(sx, bf_lo(wy), acc[4 * bb + 2]); acc[4 * bb + 3] = fmaf(sx, bf_hi(wy), acc[4 * bb + 3]);
        }
    }
    sts128f(SM_V + warp * 1024 + lane * 16, make_float4(acc[0], acc[1], acc[2], acc[3]));
    sts128f(SM_V + warp * 1024 + 512 + lane * 16, make_float4(acc[4], acc[5], acc[6], acc[7]));
    __syncthreads();
    if (tid < 128) {
        float2 sum = make_float2(0.f, 0.f);
#pragma unroll
        for (int w = 0; w < 16; w++) { const float2 p = lds64f(SM_V + w * 1024 + tid * 8); sum.x += p.x; sum.y += p.y; }
        *reinterpret_cast<float2*>(&gs->emb[j * NB * C + tid * 2]) = sum;
        bar_sync(1, 128);
        if (tid < 2) asm volatile("red.release.gpu.global.add.u32 [%0], 1;" ::"l"(&gs->wcnt[(2 * NB + tid) * LS]) : "memory");
    }
}

__global__ void __cluster_dims__(2, 1, 1) __launch_bounds__(NTHREADS, 1)
resblock_kernel(const __nv_bfloat16* __restrict__ w1, const __nv_bfloat16* __restrict__ x,
                const __nv_bfloat16* __restrict__ t_emb, const __nv_bfloat16* __restrict__ g1,
                const __nv_bfloat16* __restrict__ be1, const __nv_bfloat16* __restrict__ w_emb,
                const __nv_bfloat16* __restrict__ g2, const __nv_bfloat16* __restrict__ be2,
                const __nv_bfloat16* __restrict__ w2, __nv_bfloat16* __restrict__ out, Scratch* __restrict__ gs,
                const __grid_constant__ CUtensorMap xmap) {
    const unsigned clk0 = clock32();
    if (threadIdx.x == 480 && blockIdx.x >= NXTRA) TLG(1);
    const int tid = threadIdx.x, lane = tid & 31;
    const int cta = blockIdx.x - NXTRA, b = cta >> 6, rk = cta & 1, r0 = cta & 62;
    uint4 v[5];
    if (tid < 32) weight_load(v, w1, cta & (NCTA - 1), lane);
    const int warp = __shfl_sync(0xffffffffu, tid >> 5, 0);
    if (cta < 0) { side_jobs(t_emb, w_emb, w2, gs, clk0); return; }

    if (warp != 3) asm volatile("barrier.cluster.arrive.relaxed.aligned;" ::: "memory");
    const bool has_up = r0 != 0, has_dn = r0 != HW - 2;
    const int ch0 = b * C + rk * 64;
    if (warp == 1 || warp == 2 || warp == 4 || warp == 5) {
        const int i = warp < 3 ? warp - 1 : warp - 2, gl = i >> 1, row = i & 1;
        const uint32_t tile = SM_XOWN + row * 8192 + gl * 4096;
        if (elect_one()) {
            asm volatile("prefetch.tensormap [%0];" ::"l"(&xmap) : "memory");
            mbar_init(BAR(BAR_X) + 8 * i, 1);
            mbar_expect(BAR(BAR_X) + 8 * i, 4096);
            fence_async_smem();
            while (clock32() - clk0 < XDELAY + gl * XSTAG) {}
            tma_x(tile, &xmap, r0 + row, ch0 + gl * 32, BAR(BAR_X) + 8 * i);
        }
        __syncwarp();
        bar_arrive(4, 256 + 64 + 128);
        mbar_wait(BAR(BAR_X) + 8 * i, 0);
        if (lane == 0) TL(70 + i);
        float c[8][4];
#pragma unroll
        for (int k = 0; k < 8; k++) {
            const uint4 q = lds128(tile + k * 512 + lane * 16);
            c[k][0] = c[k][1] = c[k][2] = c[k][3] = 0.f;
            stat_mma(c[k], q.x, q.y); stat_mma(c[k], q.z, q.w);
        }
#pragma unroll
        for (int k = 0; k < 4; k++) c[0][k] = ((c[0][k] + c[1][k]) + (c[2][k] + c[3][k])) + ((c[4][k] + c[5][k]) + (c[6][k] + c[7][k]));
        stat_store(c[0], SM_RED + i * 48, lane);
        __syncwarp();
        if (lane == 0) {
            const uint32_t a = SM_RED + i * 48;
            red_add4(&gs->acc1[b * LS + (rk * 2 + gl) * 4], 1.f, sum4(lds128f(a + 32)), sum4(lds128f(a)) + sum4(lds128f(a + 16)), 1.f);
            TL(74 + i);
        }
    }
    if (warp == 3) {
        if (elect_one()) {
#pragma unroll
            for (int i = 0; i < NSTAGE; i++) mbar_init(BAR(BAR_FULL + i), (i & 7) == 0 || (PAUSE && i == PAUSE) || (SPLIT && i == 2) ? 9 : 1);
#pragma unroll
            for (int i = 0; i <= NS; i++) mbar_init(BAR(BAR_WEMPTY + i), 4);
#pragma unroll
            for (int i = BAR_STATS; i < BAR_X; i++) mbar_init(BAR(i), i == BAR_EMB ? 3 : (i == BAR_VD ? 8 : 1));
            asm volatile("fence.mbarrier_init.release.cluster;" ::: "memory");
        }
        __syncwarp();
        fence_async_smem();
        bar_arrive(0, 96);
        bar_arrive(5, 96);
        bar_arrive(4, 256 + 64 + 128);
        const uint4 z = make_uint4(0, 0, 0, 0);
#pragma unroll
        for (int i = 0; i < 4; i++) sts128(SM_V + (i * 16 + (lane >> 1)) * CH_PITCH + (lane & 1) * 16, z);
        if (lane < 2) sts128(SM_V + NSTAGE * VST_BYTES + lane * 16, z);
        if (lane < 16) sts128(SM_ONES + lane * 16, make_uint4(lane < 8 ? 0x3f803f80u : 0u, 0, 0, 0));
        fence_async_smem();
        asm volatile("barrier.cluster.arrive.relaxed.aligned;" ::: "memory");
        while (clock32() - clk0 < W2DELAY) {}
        weight_load(v, w2, cta, lane);
    }
    if (warp == 0 || warp == 3) {
        const int k = warp & 1;
#pragma unroll
        for (int i = 0; i < 5; i++)
            if (i < 4 || lane < 16) sts128(SM_BNC + k * 2304 + (lane + 32 * i) * 16, v[i]);
        if (lane == 0) TL(k ? 14 : 81);
        __syncwarp();
        weight_block(SM_BNC + k * 2304, gs->wt + k * 2 * NSTAGE * STAGE_BYTES, cta, lane);
        __syncwarp();
        if (lane == 0) TL(k ? 13 : 4);
        if (lane < 2) asm volatile("red.relaxed.gpu.global.add.u32 [%0], 1;" ::"l"(&gs->wcnt[(k * NB + lane) * LS + (k ? 0 : (cta & 8) + (cta >> 4))]) : "memory");
    }

    if (warp >= 8) {
        const int nw = warp - 8;
        bar_sync(4, 256 + 64 + 128);
        const int par = nw >> 2, wq = nw & 3;
        const uint32_t v_off = SM_V + par * VST_BYTES + (lane >> 4) * CH_PITCH + (2 + wq * 16 + (lane & 15)) * 16;
        const uint32_t stg_off = (par * 16 + (lane >> 4) * 8 + (lane & 7)) * 128 + (((2 * wq + ((lane >> 3) & 1)) ^ (lane & 7)) << 4);
        const uint32_t cfa = SM_COEF + rk * 512 + par * 128 + (lane & 3) * 16;
        uint4* inbox = gs->box + cta * 1024 + nw * 32 + lane;
#pragma unroll 1
        for (int conv = 0; conv < 2; conv++) {
            uint32_t u[4][4], w[4][4];
            float4 cf[4];
            if (conv == 0) {
#pragma unroll
                for (int i = 0; i < 4; i++) { mbar_wait(BAR(BAR_X + i), 0); ldsm4t(u[i], SM_XOWN + stg_off + (i & 1) * 8192 + (i >> 1) * 4096); }
            } else {
                mbar_wait(BAR(BAR_HW), 0);
#pragma unroll
                for (int i = 0; i < 4; i++) ldsm4(u[i], v_off + (i >> 1) * 2 * VST_BYTES + (i & 1) * POS_BYTES);
            }
#pragma unroll
            for (int i = 0; i < 4; i++) cf[i] = lds128f(cfa + conv * 1024 + (i >> 1) * 256 + (i & 1) * 64);
            const uint32_t gst = SM_GST + conv * 16;
            float4 gv;
            float a[4][8];
            bool have = false;
            {
                unsigned it = 0;
#pragma unroll 1
                while (true) {
                    asm volatile("ld.volatile.shared.v4.f32 {%0,%1,%2,%3}, [%4];" : "=f"(gv.x), "=f"(gv.y), "=f"(gv.z), "=f"(gv.w) : "r"(gst + S0) : "memory");
                    const bool xo = !have && mbar_test(BAR(BAR_XO), conv);
                    if (__all_sync(0xffffffffu, gv.x != 0.f) || ++it > 8 * SPIN_LIMIT) break;
                    if (xo) { load_outer(w, conv, stg_off, tid); have = true; }
                }
            }
            group_coefs<0>(gst, gv, cf);
            if (tid == 256) TL(22 + conv * 4);
            group_coefs<1>(gst, gv, cf);
            act8(a[0], u[0], cf[0], cf[1]); act8(a[1], u[1], cf[0], cf[1]);
            stsm_comb<1>(v_off, a[1], a[0]); stsm_comb<-1>(v_off + POS_BYTES, a[1], a[0]);
            act8(a[2], u[2], cf[2], cf[3]); act8(a[3], u[3], cf[2], cf[3]);
            stsm_comb<1>(v_off + 2 * VST_BYTES, a[3], a[2]); stsm_comb<-1>(v_off + 2 * VST_BYTES + POS_BYTES, a[3], a[2]);
            fence_async_smem();
            __syncwarp();
            if (lane < 2) mbar_arrive(lane ? BAR(BAR_VD) : BAR(BAR_FULL + (SPLIT ? 2 : 0)));
            if (tid == 256) TL(84 + conv);
            if (!have) { mbar_wait(BAR(BAR_XO), conv); load_outer(w, conv, stg_off, tid); }
            if (conv == 1) {
                unsigned it = 0;
                while (true) {
                    bool oku = true, okd = true;
#pragma unroll
                    for (int i = 0; i < 8; i++) { oku = oku && w[(i >> 2) * 2][i & 3] != 0; okd = okd && w[(i >> 2) * 2 + 1][i & 3] != 0; }
                    if (__all_sync(0xffffffffu, (oku || !has_up) && (okd || !has_dn)) || ++it > SPIN_LIMIT) break;
#pragma unroll
                    for (int i = 0; i < 4; i++) ld_unit(w[i], inbox + (i & 1) * 512 + (i >> 1) * 256);
                }
#pragma unroll
                for (int i = 0; i < 16; i++) w[i >> 2][i & 3] = ~w[i >> 2][i & 3];
            }
            if (tid == 256) TL(24 + conv * 4);
#pragma unroll
            for (int i = 0; i < 4; i++) {
                float o[8];
                act8(o, w[i], cf[i & 2], cf[(i & 2) + 1]);
                const bool ok = (i & 1) ? has_dn : has_up;
#pragma unroll
                for (int j = 0; j < 4; j++) w[i][j] = pack_bf((ok ? o[2 * j] : 0.f) - a[i ^ 1][2 * j], (ok ? o[2 * j + 1] : 0.f) - a[i ^ 1][2 * j + 1]);
            }
            if (tid == 256) TL(90 + conv);
            __syncwarp();
#pragma unroll
            for (int i = 0; i < 4; i++) stsm4(v_off + (8 + (i & 2)) * VST_BYTES + (i & 1) * POS_BYTES, w[i][0], w[i][1], w[i][2], w[i][3]);
            fence_async_smem();
            __syncwarp();
            if (lane < (PAUSE ? 3 : 2)) mbar_arrive(lane == 0 ? BAR(BAR_VD) : (lane == 1 ? BAR(BAR_FULL + 8) : BAR(BAR_FULL + PAUSE)));
            if (tid == 256) TL(23 + conv * 4);
        }
        mbar_wait(BAR(BAR_FULL + NSTAGE - 1), 1);
#pragma unroll
        for (int i = 0; i < 4; i++) inbox[i * 256] = make_uint4(0, 0, 0, 0);
        {
            const int oc0 = (tid - 256) >> 3, seg = lane & 7;
            __nv_bfloat16* dst = out + ((size_t)(ch0 + oc0) * HW + r0) * HW + seg * 8;
            const uint32_t src = SM_XOWN + oc0 * 128 + ((seg ^ (oc0 & 7)) << 4);
            bar_sync(6, 128 + 256);
#pragma unroll
            for (int i = 0; i < 4; i++) *reinterpret_cast<uint4*>(dst + (i & 1) * 32 * HW * HW + (i >> 1) * HW) = lds128(src + i * 4096);
            if (tid == 256) { TL(20); TLG(21); }
        }
    } else if (warp < 4) {
        const int wq = warp;
        bar_sync(2, 128);
        const uint32_t xbase = SM_XOWN + ((lane >> 4) * 8 + (lane & 7)) * 128 + (((2 * wq + ((lane >> 3) & 1)) ^ (lane & 7)) << 4);
        float d0[32], d1[32];
#pragma unroll
        for (int i = 0; i < 32; i++) { d0[i] = 0.f; d1[i] = 0.f; }
#pragma unroll 1
        for (int conv = 0; conv < 2; conv++) {
            fence_acc(d0); fence_acc(d1);
            mma_stages<0>(d0, d1, conv, tid, gs);
            if (conv == 0) {
                asm volatile("wgmma.fence.sync.aligned;" ::: "memory");
                wgmma64<(SM_ONES >> 4) | (8u << 16), (SM_EMB >> 4), 0, 8>(d0);
                wgmma64<(SM_ONES >> 4) | (8u << 16), (SM_EMB >> 4), 0, 8>(d1);
                asm volatile("wgmma.commit_group.sync.aligned;" ::: "memory");
            }
            asm volatile("wgmma.wait_group.sync.aligned 0;" ::: "memory");
            fence_acc(d0); fence_acc(d1);
            if (tid == 0) TL(10 + conv * 8);
            uint32_t hp[32];
#pragma unroll
            for (int i = 0; i < 16; i++) { hp[i] = pack_bf(d0[2 * i], d0[2 * i + 1]); hp[16 + i] = pack_bf(d1[2 * i], d1[2 * i + 1]); }
            if (conv == 1) {
#pragma unroll
                for (int j = 0; j < 8; j++) stsm4t(xbase + j * 2048, hp[4 * j], hp[4 * j + 1], hp[4 * j + 2], hp[4 * j + 3]);
                bar_arrive(6, 128 + 256);
                break;
            }
#pragma unroll
            for (int g = 0; g < 2; g++) {
                float c[2][4] = {{0.f, 0.f, 0.f, 0.f}, {0.f, 0.f, 0.f, 0.f}};
#pragma unroll
                for (int i = 0; i < 4; i++) {
                    stat_mma(c[0], hp[8 * g + 2 * i], hp[8 * g + 2 * i + 1]);
                    stat_mma(c[1], hp[16 + 8 * g + 2 * i], hp[16 + 8 * g + 2 * i + 1]);
                }
#pragma unroll
                for (int i = 0; i < 4; i++) c[0][i] += c[1][i];
                stat_store(c[0], SM_RED + (g * 4 + wq) * 48, lane);
            }
            bar_sync(2, 128);
            if (wq == 0) {
                const uint32_t a = SM_RED + (lane & 7) * 48;
                float q = sum4(lds128f(a)) + sum4(lds128f(a + 16)), sm = sum4(lds128f(a + 32));
                q += __shfl_xor_sync(0xffffffffu, q, 1); sm += __shfl_xor_sync(0xffffffffu, sm, 1);
                q += __shfl_xor_sync(0xffffffffu, q, 2); sm += __shfl_xor_sync(0xffffffffu, sm, 2);
                if ((lane & 27) == 0) red_add4(&gs->acc2[b * LS + rk * 8 + lane], 2.f, sm, q, 2.f);
            }
            if (tid == 32) asm volatile("mbarrier.arrive.relaxed.cluster.shared::cluster.b64 _, [%0];" ::"r"(mapa(BAR(BAR_PD), rk ^ 1)) : "memory");
            if (tid == 0) TL(11);
            const uint32_t hbase = SM_V + (lane >> 4) * CH_PITCH + (2 + wq * 16 + (lane & 15)) * 16;
#pragma unroll
            for (int j = 0; j < 8; j++)
                stsm4(hbase + (j & 3) * VST_BYTES + (j >> 2) * POS_BYTES, hp[4 * j], hp[4 * j + 1], hp[4 * j + 2], hp[4 * j + 3]);
            __syncwarp();
            if (lane == 0) { mbar_arrive(BAR(BAR_HW)); mbar_arrive(BAR(BAR_WEMPTY + 7)); }
#pragma unroll
            for (int row = 0; row < 2; row++) {
                if (row ? has_dn : has_up) {
                    uint4* outbox = gs->box + (row ? (cta + 2) * 1024 : (cta - 2) * 1024 + 512) + tid;
#pragma unroll
                    for (int j = 0; j < 4; j++)
                        outbox[j * 128] = make_uint4(~hp[16 * row + 4 * j], ~hp[16 * row + 4 * j + 1], ~hp[16 * row + 4 * j + 2], ~hp[16 * row + 4 * j + 3]);
                }
            }
            if (tid == 0) TL(12);
#pragma unroll
            for (int j = 0; j < 4; j++) {
                uint32_t p[4], q[4];
                ldsm4t(p, xbase + j * 2048); ldsm4t(q, xbase + 8192 + j * 2048);
#pragma unroll
                for (int i = 0; i < 4; i++) {
                    const float pl = 0.5f * bf_lo(p[i]), ph = 0.5f * bf_hi(p[i]);
                    d0[8 * j + 2 * i] = fmaf(bf_lo(q[i]), 0.5f, pl); d0[8 * j + 2 * i + 1] = fmaf(bf_hi(q[i]), 0.5f, ph);
                    d1[8 * j + 2 * i] = fmaf(bf_lo(q[i]), -0.5f, pl); d1[8 * j + 2 * i + 1] = fmaf(bf_hi(q[i]), -0.5f, ph);
                }
            }
        }
    } else if (warp < 6) {
        bar_sync(5, 96);
        if (warp == 5) {
            asm volatile("barrier.cluster.wait.acquire.aligned;" ::: "memory");
            const uint32_t peer0 = mapa(0, rk ^ 1);
#pragma unroll 1
            for (int ph = 0; ph < 4; ph++) {
                const int conv = ph >> 1, s0 = (ph & 1) * 8;
                if (ph == 2) mbar_wait(BAR(BAR_PD), 0);
                mbar_wait(BAR(BAR_VD), ph & 1);
                if (elect_one())
                    asm volatile("cp.async.bulk.shared::cluster.shared::cta.mbarrier::complete_tx::bytes [%0], [%1], %2, [%3];"
                                 ::"r"(peer0 + SM_V + (s0 + 4) * VST_BYTES), "r"(S0 + SM_V + s0 * VST_BYTES), "r"(4 * VST_BYTES),
                                   "r"(peer0 + BAR(BAR_FULL + 4) + 8 * s0) : "memory");
                if (lane == 0) TL(86 + ph);
                if (ph == 1 || ph == 3) {
                    mbar_wait(BAR(BAR_FULL + 4) + (ph & 2) * 32, conv);
                    if (lane == 0)
                        asm volatile("mbarrier.arrive.relaxed.cluster.shared::cluster.b64 _, [%0];" ::"r"(peer0 + (conv ? BAR(BAR_ACK) : BAR(BAR_EMB))) : "memory");
                }
            }
            mbar_wait(BAR(BAR_ACK), 0);
        } else {
            if (elect_one()) {
                mbar_expect(BAR(BAR_XO), 16384);
#pragma unroll
                for (int i = 0; i < 4; i++) tma_x(SM_XOUT + i * 4096, &xmap, (i >> 1) ? r0 + 2 : r0 - 1, ch0 + (i & 1) * 32, BAR(BAR_XO));
            }
            __syncwarp();
            mbar_wait(BAR(BAR_STATS), 0);
            unsigned it = 0;
            while (ld_relaxed(&gs->wcnt[(2 * NB + b) * LS]) < (unsigned)NXTRA && ++it < SPIN_LIMIT) __nanosleep(100);
            fence_acquire();
            float ev[2] = {0.f, 0.f};
#pragma unroll
            for (int j = 0; j < NXTRA; j++) {
                ev[0] += __uint_as_float(ld_relaxed(&gs->emb[(j * NB + b) * C + rk * 64 + lane]));
                ev[1] += __uint_as_float(ld_relaxed(&gs->emb[(j * NB + b) * C + rk * 64 + 32 + lane]));
            }
#pragma unroll
            for (int i = 0; i < 2; i++) {
                const float hi = bf_lo(pack_bf(ev[i], 0.f));
                sts128(SM_EMB + (i * 32 + lane) * 16, make_uint4(pack_bf(hi, ev[i] - hi), 0, 0, 0));
            }
            fence_async_smem();
            __syncwarp();
            if (lane == 0) { mbar_arrive(BAR(BAR_EMB)); TL(19); }
            mbar_wait(BAR(BAR_HW), 0);
            mbar_wait(BAR(BAR_PD), 0);
            { const unsigned c1 = clock32(); while (clock32() - c1 < FDELAY) {} }
            if (elect_one()) {
                mbar_expect(BAR(BAR_XO), 16384);
                bulk_g2s(S0 + SM_XOUT, gs->box + cta * 1024, 16384, S0 + BAR(BAR_XO));
            }
            if (lane == 0) TL(5);
        }
    } else if (warp == 6) {
        bar_sync(0, 96);
        const uint32_t ebytes = STAGE_BYTES + ((lane & 7) == 4 ? 4 * VST_BYTES : 0);
        if (lane < NSTAGE) mbar_expect(BAR(BAR_FULL) + 8 * lane, ebytes);
        const unsigned char* wbase = gs->wt + rk * NSTAGE * STAGE_BYTES;
        unsigned it = 0;
        {
            int g = 0;
#pragma unroll 1
            while (g < NS) {
                unsigned ready = __ballot_sync(0xffffffffu, ld_relaxed(&gs->wcnt[b * LS + rk * 8 + (lane & 7)]) >= 8u) >> g;
                if (++it > SPIN_LIMIT) ready = ~0u;
                if (!(ready & 1)) continue;
                fence_acquire();
                fence_async_global();
                if (lane == 0) TL(g ? 3 : 6);
#pragma unroll 1
                for (; (ready & 1) && g < NS; g++, ready >>= 1)
                    if (elect_one())
                        bulk_g2s(S0 + SM_W + g * STAGE_BYTES, wbase + ((rk * 4 + g) & 7) * STAGE_BYTES, STAGE_BYTES, S0 + BAR(BAR_FULL) + 8 * g);
            }
        }
#pragma unroll 1
        for (int q = 2; q < 8; q++) {
            const unsigned char* wsrc = wbase + ((q >> 2) * 2 * NSTAGE + (q & 2) * 4 + ((q ^ rk) & 1) * 4) * STAGE_BYTES;
            const uint32_t par = ((q >> 1) - 1) & 1;
            if (q == 4) {
                it = 0;
                while (ld_relaxed(&gs->wcnt[(NB + b) * LS]) < (unsigned)NCTA && ++it < SPIN_LIMIT) {}
                fence_acquire();
                fence_async_global();
                if (lane == 0) { mbar_arrive(BAR(BAR_EMB)); TL(2); }
            }
#pragma unroll
            for (int i = 0; i < 4; i++) {
                mbar_wait(BAR(BAR_WEMPTY + i) + 32 * (q & 1), par);
                if (i == 0 && (q == 4 || q == 6)) {
                    if ((lane >> 3) == (q - 4) / 2) mbar_expect(BAR(BAR_FULL) + 8 * lane, ebytes);
                    __syncwarp();
                }
                if (elect_one())
                    bulk_g2s(S0 + SM_W + ((q & 1) * 4 + i) * STAGE_BYTES, wsrc + i * STAGE_BYTES, STAGE_BYTES, S0 + BAR(BAR_FULL + i) + 32 * (q & 3));
            }
        }
    } else {
        const uint2 ga1 = __ldg(reinterpret_cast<const uint2*>(g1) + lane), bt1 = __ldg(reinterpret_cast<const uint2*>(be1) + lane);
        const uint2 ga2 = __ldg(reinterpret_cast<const uint2*>(g2) + lane), bt2 = __ldg(reinterpret_cast<const uint2*>(be2) + lane);
        if (lane < 2) sts128(SM_GST + lane * 16, make_uint4(0, 0, 0, 0));
        sts128f(SM_COEF + lane * 32, make_float4(0.5f * bf_lo(ga1.x), 0.5f * bf_hi(ga1.x), 0.5f * bf_lo(bt1.x), 0.5f * bf_hi(bt1.x)));
        sts128f(SM_COEF + lane * 32 + 16, make_float4(0.5f * bf_lo(ga1.y), 0.5f * bf_hi(ga1.y), 0.5f * bf_lo(bt1.y), 0.5f * bf_hi(bt1.y)));
        sts128f(SM_COEF + 1024 + lane * 32, make_float4(0.5f * bf_lo(ga2.x), 0.5f * bf_hi(ga2.x), 0.5f * bf_lo(bt2.x), 0.5f * bf_hi(bt2.x)));
        sts128f(SM_COEF + 1024 + lane * 32 + 16, make_float4(0.5f * bf_lo(ga2.y), 0.5f * bf_hi(ga2.y), 0.5f * bf_lo(bt2.y), 0.5f * bf_hi(bt2.y)));
        bar_arrive(4, 256 + 64 + 128);
        bar_sync(0, 96);
#pragma unroll 1
        for (int conv = 0; conv < 2; conv++) {
            if (conv == 1) mbar_wait(BAR(BAR_HW), 0);
            const bool wide = conv == 1 && (cta & 63) == 0;
            const float* asrc = (conv ? gs->acc2 : gs->acc1) + b * LS + (wide ? lane & 3 : rk * 2 + (lane & 1)) * 4;
            unsigned it = 0;
#pragma unroll 1
            while (true) {
                const uint4 f = ld_relaxed_v4(asrc);
                const bool ok = ((f.x == 0x42800000u) & (f.w == 0x42800000u)) || ++it > SPIN_LIMIT;
                if (ok && lane < 2) {
                    const float inv_n = 1.0f / (32.0f * HW * HW);
                    const float mean = __uint_as_float(f.y) * inv_n;
                    const float rs = rsqrtf(fmaxf(fmaf(-mean, mean, __uint_as_float(f.z) * inv_n), 0.f) + 1e-5f);
                    asm volatile("st.shared.v2.f32 [%0], {%1,%2};" ::"r"(S0 + SM_GST + conv * 16 + lane * 8), "f"(rs == 0.f ? 1e-38f : rs), "f"(mean * rs) : "memory");
                }
                if (__all_sync(0xffffffffu, ok)) break;
            }
            if (lane == 0) { if (conv == 0) mbar_arrive(BAR(BAR_STATS)); TL(7 + conv * 8); }
        }
        if ((cta & 63) == 0) {
            if (lane < 16) { gs->acc1[b * LS + lane] = 0.f; gs->wcnt[b * LS + lane] = 0; }
            if (lane < 2) gs->wcnt[((1 + lane) * NB + b) * LS] = 0;
        }
    }
}

}

extern "C" void kernel_launch(void* const* d_in, const int* in_sizes, int n_in, void* d_out, int out_size) {
    (void)in_sizes; (void)n_in; (void)out_size;
    typedef CUresult (*EncodeFn)(CUtensorMap*, CUtensorMapDataType, cuuint32_t, void*, const cuuint64_t*, const cuuint64_t*,
                                 const cuuint32_t*, const cuuint32_t*, CUtensorMapInterleave, CUtensorMapSwizzle,
                                 CUtensorMapL2promotion, CUtensorMapFloatOOBfill);
    static Scratch* gs = nullptr;
    static EncodeFn encode = nullptr;
    if (!gs) {
        cudaFuncSetAttribute(resblock_kernel, cudaFuncAttributeMaxDynamicSharedMemorySize, SM_TOTAL);
        cudaGetSymbolAddress((void**)&gs, g_scratch);
        cudaDriverEntryPointQueryResult qr;
        cudaGetDriverEntryPoint("cuTensorMapEncodeTiled", (void**)&encode, cudaEnableDefault, &qr);
    }
    CUtensorMap xmap;
    const cuuint64_t dims[3] = {HW, HW, NB * C}, strides[2] = {HW * 2, HW * HW * 2};
    const cuuint32_t box[3] = {HW, 1, 32}, es[3] = {1, 1, 1};
    encode(&xmap, CU_TENSOR_MAP_DATA_TYPE_BFLOAT16, 3, d_in[0], dims, strides, box, es, CU_TENSOR_MAP_INTERLEAVE_NONE,
           CU_TENSOR_MAP_SWIZZLE_128B, CU_TENSOR_MAP_L2_PROMOTION_NONE, CU_TENSOR_MAP_FLOAT_OOB_FILL_NONE);
    resblock_kernel<<<NCTA + NXTRA, NTHREADS, SM_TOTAL>>>(
        (const __nv_bfloat16*)d_in[4], (const __nv_bfloat16*)d_in[0], (const __nv_bfloat16*)d_in[1],
        (const __nv_bfloat16*)d_in[2], (const __nv_bfloat16*)d_in[3], (const __nv_bfloat16*)d_in[5],
        (const __nv_bfloat16*)d_in[6], (const __nv_bfloat16*)d_in[7], (const __nv_bfloat16*)d_in[8],
        (__nv_bfloat16*)d_out, gs, xmap);
}
```

```cpp
#include <cuda_runtime.h>
#include <cuda.h>
#include <cuda_bf16.h>
#include <stdint.h>

namespace {

constexpr int C = 128, HW = 64, NB = 2, E = 768;
constexpr int NCTA = NB * HW;
constexpr int NXTRA = 4;
constexpr int NTHREADS = 16 * 32;
constexpr int CH_PITCH = 66 * 16;
constexpr int ROW_BYTES = 16 * CH_PITCH;
constexpr int STEP_BYTES = 4096;
constexpr int STAGE_BYTES = 3 * STEP_BYTES;
constexpr int NSTAGE = 24;
constexpr int KC_BYTES = 2 * CH_PITCH;
constexpr int NS = 12;
constexpr int LAG = 1;
#define XDELAY 400
#define HDELAY 600
#define SEQ 0
#define MMA0_WAIT mbar_try
#define SPINPAUSE
#define NPOLL 1
#define PD2 0
#define ODELAY 100
#define NLDG 2
#define PSTAG -1
#define PDELAY0 400
#define PDELAY 60
#define RB 1
#define XSTAG2 400
#define XSTAG 800
#define HSEND 0
#define W2DELAY 1800

constexpr uint32_t SMEM_BASE = 0x400;
constexpr uint32_t SM_XOWN = SMEM_BASE;
constexpr uint32_t SM_ACT = SM_XOWN + 16384 + 512;
constexpr uint32_t SM_XOUT = SM_ACT + 2 * ROW_BYTES + 512;
static_assert(SM_XOUT % 1024 == 0, "swizzle atom alignment");
constexpr uint32_t SM_W = SM_ACT + 3 * ROW_BYTES + 128;
__host__ __device__ constexpr uint32_t slot_addr(int slot) { return SM_W + slot * STAGE_BYTES; }
constexpr uint32_t SM_COEF = SM_W + NS * STAGE_BYTES;
constexpr uint32_t SM_GST = SM_COEF + 2048;
constexpr uint32_t SM_EMB = SM_GST + 128;
constexpr uint32_t SM_ONES = SM_EMB + 2048;
constexpr uint32_t SM_RED = SM_ONES + 256;
constexpr uint32_t SM_BNC = SM_RED + 1536;
constexpr uint32_t SM_BAR = SM_BNC + 2 * 2304;
constexpr int BAR_FULL = 0, BAR_WEMPTY = NSTAGE, BAR_HW = BAR_WEMPTY + NS, BAR_XFREE = BAR_HW + 1, BAR_STATS = BAR_XFREE + 1,
              BAR_EMB = BAR_STATS + 1, BAR_ACK = BAR_EMB + 1, BAR_X = BAR_ACK + 1  , NBAR = BAR_X + 5;
constexpr int SM_TOTAL = SM_BAR + NBAR * 8 - SMEM_BASE;
static_assert(SM_TOTAL <= 232448, "smem");
static_assert(NBAR <= 96, "barrier init");
__host__ __device__ constexpr uint32_t BAR(int i) { return SM_BAR + 8 * i; }
__host__ __device__ constexpr int ky_of(int kyo) { return kyo == 0 ? 1 : (kyo == 1 ? 0 : 2); }

constexpr unsigned SPIN_LIMIT = 1u << 16;

#define LS 1056
#define GS1 4
#define PD 0
struct Scratch {
    float acc1[NB * 4 * LS];
    float acc2[NB * LS];
    unsigned wcnt[3 * NB * LS];
    float emb[NXTRA * NB * C];
    unsigned char wt[2 * NSTAGE * STAGE_BYTES];
    uint4 box[NCTA * 1024];
};
__device__ __align__(1024) Scratch g_scratch;
#define TL(i) do {} while (0)
#define TLG(i) do {} while (0)

__device__ __forceinline__ unsigned clock32() { unsigned c; asm volatile("mov.u32 %0, %%clock;" : "=r"(c)); return c; }
__device__ __forceinline__ uint32_t mapa(uint32_t a, uint32_t rank) {
    uint32_t d;
    asm("mapa.shared::cluster.u32 %0, %1, %2;" : "=r"(d) : "r"(a), "r"(rank));
    return d;
}
#define S0 mapa(0, blockIdx.x & 1)
__device__ __forceinline__ void mbar_init(uint32_t bar, int cnt) {
    asm volatile("mbarrier.init.shared::cta.b64 [%0], %1;" ::"r"(bar + S0), "r"(cnt) : "memory");
}
__device__ __forceinline__ void mbar_arrive(uint32_t bar) {
    asm volatile("mbarrier.arrive.shared::cta.b64 _, [%0];" ::"r"(bar + S0) : "memory");
}
__device__ __forceinline__ void mbar_expect(uint32_t bar, uint32_t bytes) {
    asm volatile("mbarrier.arrive.expect_tx.shared::cta.b64 _, [%0], %1;" ::"r"(bar + S0), "r"(bytes) : "memory");
}
__device__ __forceinline__ bool mbar_try(uint32_t bar, uint32_t par) {
    uint32_t ok;
    asm volatile("{\n.reg .pred p;\nmbarrier.try_wait.parity.shared::cta.b64 p, [%1], %2;\nselp.u32 %0, 1, 0, p;\n}"
                 : "=r"(ok) : "r"(bar + S0), "r"(par) : "memory");
    return ok;
}
__device__ __forceinline__ bool mbar_test(uint32_t bar, uint32_t par) {
    uint32_t ok;
    asm volatile("{\n.reg .pred p;\nmbarrier.test_wait.parity.shared::cta.b64 p, [%1], %2;\nselp.u32 %0, 1, 0, p;\n}"
                 : "=r"(ok) : "r"(bar + S0), "r"(par) : "memory");
    return ok;
}
__device__ __forceinline__ void mbar_wait(uint32_t bar, uint32_t par) {
    unsigned it = 0;
#pragma unroll 1
    while (!mbar_try(bar, par) && ++it < SPIN_LIMIT) {}
}
__device__ __forceinline__ bool elect_one() {
    uint32_t p;
    asm volatile("{\n.reg .pred p;\nelect.sync _|p, 0xffffffff;\nselp.u32 %0, 1, 0, p;\n}" : "=r"(p));
    return p;
}
__device__ __forceinline__ void fence_async_smem() { asm volatile("fence.proxy.async.shared::cta;" ::: "memory"); }
__device__ __forceinline__ void fence_async_global() { asm volatile("fence.proxy.async.global;" ::: "memory"); }
__device__ __forceinline__ void fence_acquire() { asm volatile("fence.acquire.gpu;" ::: "memory"); }
__device__ __forceinline__ void bar_sync(int id, int n) { asm volatile("bar.sync %0, %1;" ::"r"(id), "r"(n) : "memory"); }
__device__ __forceinline__ void bar_arrive(int id, int n) { asm volatile("bar.arrive %0, %1;" ::"r"(id), "r"(n) : "memory"); }
__device__ __forceinline__ void bulk_g2s(uint32_t dst, const void* src, uint32_t bytes, uint32_t bar) {
    asm volatile("cp.async.bulk.shared::cluster.global.mbarrier::complete_tx::bytes [%0], [%1], %2, [%3];"
                 ::"r"(dst), "l"(src), "r"(bytes), "r"(bar) : "memory");
}
__device__ __forceinline__ void tma_x(uint32_t dst, const CUtensorMap* tm, int row, int ch, uint32_t bar) {
    asm volatile("cp.async.bulk.tensor.3d.shared::cluster.global.mbarrier::complete_tx::bytes [%0], [%1, {%2, %3, %4}], [%5];"
                 ::"r"(dst + S0), "l"(tm), "r"(0), "r"(row), "r"(ch), "r"(bar + S0) : "memory");
}
__device__ __forceinline__ uint4 ld_relaxed_v4(const void* p) {
    uint4 v;
    asm volatile("ld.relaxed.gpu.global.v4.u32 {%0,%1,%2,%3}, [%4];" : "=r"(v.x), "=r"(v.y), "=r"(v.z), "=r"(v.w) : "l"(p) : "memory");
    return v;
}
__device__ __forceinline__ unsigned ld_relaxed(const void* p) {
    unsigned v;
    asm volatile("ld.relaxed.gpu.global.u32 %0, [%1];" : "=r"(v) : "l"(p) : "memory");
    return v;
}
__device__ __forceinline__ void red_add4(float* p, float a, float b, float c, float d) {
    asm volatile("red.relaxed.gpu.global.add.v4.f32 [%0], {%1,%2,%3,%4};" ::"l"(p), "f"(a), "f"(b), "f"(c), "f"(d) : "memory");
}
__device__ __forceinline__ void sts128(uint32_t a, uint4 v) {
    asm volatile("st.shared.v4.u32 [%0], {%1,%2,%3,%4};" ::"r"(a + S0), "r"(v.x), "r"(v.y), "r"(v.z), "r"(v.w) : "memory");
}
__device__ __forceinline__ void sts128f(uint32_t a, float4 v) {
    asm volatile("st.shared.v4.f32 [%0], {%1,%2,%3,%4};" ::"r"(a + S0), "f"(v.x), "f"(v.y), "f"(v.z), "f"(v.w) : "memory");
}
__device__ __forceinline__ void sts32f(uint32_t a, float v) { asm volatile("st.shared.f32 [%0], %1;" ::"r"(a + S0), "f"(v) : "memory"); }
__device__ __forceinline__ uint4 lds128(uint32_t a) {
    uint4 v;
    asm volatile("ld.shared.v4.u32 {%0,%1,%2,%3}, [%4];" : "=r"(v.x), "=r"(v.y), "=r"(v.z), "=r"(v.w) : "r"(a + S0) : "memory");
    return v;
}
__device__ __forceinline__ float4 lds128f(uint32_t a) {
    float4 v;
    asm volatile("ld.shared.v4.f32 {%0,%1,%2,%3}, [%4];" : "=f"(v.x), "=f"(v.y), "=f"(v.z), "=f"(v.w) : "r"(a + S0) : "memory");
    return v;
}
__device__ __forceinline__ float2 lds64f(uint32_t a) {
    float2 v;
    asm volatile("ld.shared.v2.f32 {%0,%1}, [%2];" : "=f"(v.x), "=f"(v.y) : "r"(a + S0) : "memory");
    return v;
}
__device__ __forceinline__ float bf_lo(uint32_t u) { return __uint_as_float(u << 16); }
__device__ __forceinline__ float bf_hi(uint32_t u) { return __uint_as_float(u & 0xffff0000u); }
__device__ __forceinline__ uint32_t pack_bf(float lo, float hi) {
    uint32_t r;
    asm("cvt.rn.bf16x2.f32 %0, %1, %2;" : "=r"(r) : "f"(hi), "f"(lo));
    return r;
}
__device__ __forceinline__ float tanh_fast(float x) {
    float r;
    asm("tanh.approx.f32 %0, %1;" : "=f"(r) : "f"(x));
    return r;
}
__device__ __forceinline__ float silu_half(float h) { return fmaf(h, tanh_fast(h), h); }
__device__ __forceinline__ void ldsm4(uint32_t (&u)[4], uint32_t a) {
    asm volatile("ldmatrix.sync.aligned.m8n8.x4.shared.b16 {%0,%1,%2,%3}, [%4];"
                 : "=r"(u[0]), "=r"(u[1]), "=r"(u[2]), "=r"(u[3]) : "r"(a + S0) : "memory");
}
__device__ __forceinline__ void ldsm4t(uint32_t (&u)[4], uint32_t a) {
    asm volatile("ldmatrix.sync.aligned.m8n8.x4.trans.shared.b16 {%0,%1,%2,%3}, [%4];"
                 : "=r"(u[0]), "=r"(u[1]), "=r"(u[2]), "=r"(u[3]) : "r"(a + S0) : "memory");
}
__device__ __forceinline__ void stsm4(uint32_t a, uint32_t p0, uint32_t p1, uint32_t p2, uint32_t p3) {
    asm volatile("stmatrix.sync.aligned.m8n8.x4.shared.b16 [%0], {%1,%2,%3,%4};" ::"r"(a + S0), "r"(p0), "r"(p1), "r"(p2), "r"(p3) : "memory");
}
__device__ __forceinline__ void stsm4t(uint32_t a, uint32_t p0, uint32_t p1, uint32_t p2, uint32_t p3) {
    asm volatile("stmatrix.sync.aligned.m8n8.x4.trans.shared.b16 [%0], {%1,%2,%3,%4};" ::"r"(a + S0), "r"(p0), "r"(p1), "r"(p2), "r"(p3) : "memory");
}

#define R8(o) "+f"(d[o]), "+f"(d[o + 1]), "+f"(d[o + 2]), "+f"(d[o + 3]), "+f"(d[o + 4]), "+f"(d[o + 5]), "+f"(d[o + 6]), "+f"(d[o + 7])
template <uint32_t ALO, uint32_t BLO, uint64_t AHI = 8, uint64_t BHI = 48>
__device__ __forceinline__ void wgmma128(float (&d)[64]) {
    asm volatile(
        "wgmma.mma_async.sync.aligned.m64n128k16.f32.bf16.bf16 "
        "{%0,%1,%2,%3,%4,%5,%6,%7,%8,%9,%10,%11,%12,%13,%14,%15,%16,%17,%18,%19,%20,%21,%22,%23,%24,%25,%26,%27,%28,%29,%30,%31,"
        "%32,%33,%34,%35,%36,%37,%38,%39,%40,%41,%42,%43,%44,%45,%46,%47,%48,%49,%50,%51,%52,%53,%54,%55,%56,%57,%58,%59,%60,%61,%62,%63},"
        " %64, %65, 1, 1, 1, 0, 0;"
        : R8(0), R8(8), R8(16), R8(24), R8(32), R8(40), R8(48), R8(56)
        : "l"((AHI << 32) | ALO), "l"((BHI << 32) | BLO));
}
template <int S>
__device__ __forceinline__ void mma_stages(float (&d)[64], int conv, int tid, Scratch* gs) {
    constexpr uint32_t A = ((SM_ACT + S * 2 * CH_PITCH + 16) >> 4) | ((CH_PITCH >> 4) << 16);
    constexpr uint32_t B = (slot_addr(S % NS) >> 4) | (8u << 16);
    if (S == 0) {
        unsigned it = 0;
#pragma unroll 1
        while (!MMA0_WAIT(BAR(BAR_FULL), conv) && ++it < SPIN_LIMIT) {}
    }
    bool next_ok = true;
    constexpr uint32_t NEXT = S + 1 < NSTAGE ? BAR(BAR_FULL + S + 1) : BAR(BAR_EMB);
    const int npar = S + 1 < NSTAGE ? conv : 0;
    next_ok = mbar_test(NEXT, npar);
    if (S == 0 && tid == 0) TL(32 + conv * 24);
    asm volatile("wgmma.fence.sync.aligned;" ::: "memory");
    wgmma128<A, B>(d);
    wgmma128<A + 1, B + 16>(d);
    wgmma128<A + 2, B + 32>(d);
    asm volatile("wgmma.commit_group.sync.aligned;" ::: "memory");
    if (S >= LAG) {
        asm volatile("wgmma.wait_group.sync.aligned %0;" ::"n"(LAG) : "memory");
        if ((tid & 31) == 0) mbar_arrive(BAR(BAR_WEMPTY + (S + NS - LAG) % NS));
    }
    if (!next_ok) mbar_wait(NEXT, npar);
    if constexpr (S + 1 < NSTAGE) mma_stages<S + 1>(d, conv, tid, gs);
}

__device__ __forceinline__ void weight_load(uint4 (&t)[5], const __nv_bfloat16* w, int cta, int lane) {
    const char* base = reinterpret_cast<const char*>(w) + ((cta & 15) * 8 * C + (cta >> 4) * 16) * 18;
#pragma unroll
    for (int k = 0; k < 5; k++) {
        const int i = lane + 32 * k, row = (i * 57) >> 10;
        if (k < 4 || lane < 16) t[k] = __ldg(reinterpret_cast<const uint4*>(base + row * (C * 18 - 288) + i * 16));
    }
}
__device__ __forceinline__ void weight_block(uint32_t bounce, unsigned char* wt, int cta, int lane, bool readback, Scratch* gs) {
    unsigned char* dst = wt + (cta >> 4) * STAGE_BYTES + (cta & 15) * 768;
    if (lane < 16) {
        uint32_t v[36];
#pragma unroll
        for (int i = 0; i < 9; i++) {
            const uint4 q = lds128(bounce + (lane & 7) * 288 + (lane >> 3) * 144 + i * 16);
            v[4 * i] = q.x; v[4 * i + 1] = q.y; v[4 * i + 2] = q.z; v[4 * i + 3] = q.w;
        }
#pragma unroll
        for (int kyo = 0; kyo < 3; kyo++) {
#pragma unroll
            for (int kx = 0; kx < 3; kx++) {
                const int tap = ky_of(kyo) * 3 + kx;
                uint32_t o[4];
#pragma unroll
                for (int m = 0; m < 4; m++) {
                    const int i0 = 18 * m + tap, i1 = i0 + 9;
                    const uint32_t sel = ((i0 & 1) ? 0x32u : 0x10u) | ((i1 & 1) ? 0x7600u : 0x5400u);
                    o[m] = __byte_perm(v[i0 >> 1], v[i1 >> 1], sel);
                }
                *reinterpret_cast<uint4*>(dst + kyo * 8 * STAGE_BYTES + kx * 256 + lane * 16) = make_uint4(o[0], o[1], o[2], o[3]);
            }
        }
    }
    if (readback) {
        __syncwarp();
        unsigned acc = 0;
        if (lane < 24) {
#pragma unroll
            for (int i = 0; i < 3; i++) acc |= ld_relaxed(dst + i * 8 * STAGE_BYTES + lane * 32);
        }
        asm volatile("{\n.reg .pred p;\nsetp.eq.u32 p, %0, 0x9e3779b9;\n@p st.shared.u32 [%1], %0;\n}" ::"r"(acc), "r"(bounce + S0) : "memory");
    }
}
__device__ __forceinline__ uint32_t act2(uint32_t u, const float4& cf) {
    return pack_bf(silu_half(fmaf(bf_lo(u), cf.x, cf.z)), silu_half(fmaf(bf_hi(u), cf.y, cf.w)));
}
__device__ __forceinline__ void norm_unit(uint32_t (&u)[4], const float4& ca, const float4& cb) {
    u[0] = act2(u[0], ca); u[1] = act2(u[1], ca); u[2] = act2(u[2], cb); u[3] = act2(u[3], cb);
}
__device__ __forceinline__ void read_stats(uint32_t gst, float (&g)[8]) {
    asm volatile("ld.volatile.shared.v4.f32 {%0,%1,%2,%3}, [%4];" : "=f"(g[0]), "=f"(g[1]), "=f"(g[2]), "=f"(g[3]) : "r"(gst + S0) : "memory");
    asm volatile("ld.volatile.shared.v4.f32 {%0,%1,%2,%3}, [%4];" : "=f"(g[4]), "=f"(g[5]), "=f"(g[6]), "=f"(g[7]) : "r"(gst + 16 + S0) : "memory");
}
template <int T>
__device__ __forceinline__ void group_coefs(uint32_t gst, float (&g)[8], float4 (&cf)[8]) {
    unsigned it = 0;
    if (!__all_sync(0xffffffffu, g[2 * T] != 0.f)) {
        float rs0;
#pragma unroll 1
        do {
            SPINPAUSE;
            asm volatile("ld.volatile.shared.f32 %0, [%1];" : "=f"(rs0) : "r"(gst + 8 * T + S0) : "memory");
        } while (!__all_sync(0xffffffffu, rs0 != 0.f) && ++it < 8 * SPIN_LIMIT);
        read_stats(gst, g);
    }
    float4 &ca = cf[2 * T], &cb = cf[2 * T + 1];
    const float rs = g[2 * T], mr = g[2 * T + 1];
    ca.z = fmaf(-mr, ca.x, ca.z); ca.w = fmaf(-mr, ca.y, ca.w); ca.x *= rs; ca.y *= rs;
    cb.z = fmaf(-mr, cb.x, cb.z); cb.w = fmaf(-mr, cb.y, cb.w); cb.x *= rs; cb.y *= rs;
}
template <int FIRST, int N>
__device__ __forceinline__ void norm_block(uint32_t (&u)[4][4], float4 (&cf)[8], uint32_t act, uint32_t mask, uint32_t fbar, int lane) {
#pragma unroll
    for (int t = FIRST; t < FIRST + N; t++) {
        norm_unit(u[t], cf[2 * t], cf[2 * t + 1]);
        stsm4(act + t * 2 * KC_BYTES, u[t][0] & mask, u[t][1] & mask, u[t][2] & mask, u[t][3] & mask);
    }
    fence_async_smem();
    __syncwarp();
    if (lane < N) mbar_arrive(fbar + 16 * (FIRST + lane));
}
__device__ __forceinline__ void publish(uint32_t bar, int lane) {
    fence_async_smem();
    __syncwarp();
    if (lane == 0) mbar_arrive(bar);
}
template <int T>
__device__ __forceinline__ void next_unit(uint32_t (&u)[4][4], float4 (&cf)[8], uint32_t gst, float (&g)[8], uint32_t act, uint32_t fbar, int lane) {
    const bool have = __all_sync(0xffffffffu, g[2 * T] != 0.f);
    if (!have) publish(fbar + 16 * (T - 1), lane);
    group_coefs<T>(gst, g, cf);
    norm_unit(u[T], cf[2 * T], cf[2 * T + 1]);
    if (have) publish(fbar + 16 * (T - 1), lane);
    stsm4(act + T * 2 * KC_BYTES, u[T][0], u[T][1], u[T][2], u[T][3]);
}
__device__ __forceinline__ void stat_mma(float (&c)[4], uint32_t p, uint32_t q) {
    asm("mma.sync.aligned.m16n8k16.row.col.f32.bf16.bf16.f32 {%0,%1,%2,%3}, {%4,%5,%6,%5}, {%4,%6}, {%0,%1,%2,%3};"
        : "+f"(c[0]), "+f"(c[1]), "+f"(c[2]), "+f"(c[3]) : "r"(p), "r"(0x3f803f80u), "r"(q));
}
__device__ __forceinline__ void stat_store(const float (&c)[4], uint32_t dst, int lane) {
    const int g = lane >> 2, t = lane & 3;
    if (t == (g >> 1)) sts32f(dst + g * 4, (g & 1) ? c[1] : c[0]);
    if (g == 7) sts32f(dst + 32 + t * 4, c[2] + c[3]);
}
__device__ __forceinline__ float sum4(float4 v) { return (v.x + v.y) + (v.z + v.w); }
__device__ __forceinline__ void stat_publish(uint32_t src, float* acc, int lane, bool real) {
    const uint32_t a = src + (lane & 15) * 48;
    float q = sum4(lds128f(a)) + sum4(lds128f(a + 16)), sm = sum4(lds128f(a + 32));
    q += __shfl_xor_sync(0xffffffffu, q, 1); sm += __shfl_xor_sync(0xffffffffu, sm, 1);
    q += __shfl_xor_sync(0xffffffffu, q, 2); sm += __shfl_xor_sync(0xffffffffu, sm, 2);
    if (real && (lane & 19) == 0) red_add4(acc + lane, 1.f, sm, q, 1.f);
}
__device__ __forceinline__ void fence_acc(float (&d)[64]) {
#pragma unroll
    for (int i = 0; i < 64; i++) asm volatile("" : "+f"(d[i])::"memory");
}
__device__ __forceinline__ void ld_unit(uint32_t (&u)[4], const uint4* p) {
    asm volatile("ld.relaxed.gpu.global.v4.u32 {%0,%1,%2,%3}, [%4];" : "=r"(u[0]), "=r"(u[1]), "=r"(u[2]), "=r"(u[3]) : "l"(p) : "memory");
}

__device__ __noinline__ void side_jobs(const __nv_bfloat16* __restrict__ t_emb, const __nv_bfloat16* __restrict__ w_emb,
                                       const __nv_bfloat16* __restrict__ w2, Scratch* __restrict__ gs, unsigned clk0) {
    const int tid = threadIdx.x, warp = tid >> 5, lane = tid & 31, j = blockIdx.x;
    float tv = 0.f;
    if (lane < 24) tv = __bfloat162float(t_emb[(lane / 12) * E + j * 192 + warp * 12 + lane % 12]);
    if (tid == 0) {
        mbar_init(BAR(0), 1);
        mbar_expect(BAR(0), 192 * C * 2);
        fence_async_smem();
        while (clock32() - clk0 < W2DELAY) {}
#pragma unroll
        for (int i = 0; i < 4; i++) bulk_g2s(S0 + SM_W + i * 12288, w_emb + (j * 192 + i * 48) * C, 12288, S0 + BAR(0));
    }
    if (j == 0 && tid < 32) gs->acc2[(tid >> 4) * LS + (tid & 15)] = 0.f;
    const float sv = silu_half(0.5f * tv);
    __syncthreads();
    mbar_wait(BAR(0), 0);
    float acc[8] = {0.f, 0.f, 0.f, 0.f, 0.f, 0.f, 0.f, 0.f};
#pragma unroll
    for (int i = 0; i < 12; i++) {
        const float2 wq = lds64f(SM_W + (warp * 12 + i) * 256 + lane * 8);
        const uint32_t wx = __float_as_uint(wq.x), wy = __float_as_uint(wq.y);
#pragma unroll
        for (int bb = 0; bb < 2; bb++) {
            const float sx = __shfl_sync(0xffffffffu, sv, bb * 12 + i);
            acc[4 * bb + 0] = fmaf(sx, bf_lo(wx), acc[4 * bb + 0]); acc[4 * bb + 1] = fmaf(sx, bf_hi(wx), acc[4 * bb + 1]);
            acc[4 * bb + 2] = fmaf(sx, bf_lo(wy), acc[4 * bb + 2]); acc[4 * bb + 3] = fmaf(sx, bf_hi(wy), acc[4 * bb + 3]);
        }
    }
    sts128f(SM_ACT + warp * 1024 + lane * 16, make_float4(acc[0], acc[1], acc[2], acc[3]));
    sts128f(SM_ACT + warp * 1024 + 512 + lane * 16, make_float4(acc[4], acc[5], acc[6], acc[7]));
    __syncthreads();
    if (tid < 128) {
        float2 sum = make_float2(0.f, 0.f);
#pragma unroll
        for (int w = 0; w < 16; w++) { const float2 p = lds64f(SM_ACT + w * 1024 + tid * 8); sum.x += p.x; sum.y += p.y; }
        *reinterpret_cast<float2*>(&gs->emb[j * NB * C + tid * 2]) = sum;
        bar_sync(1, 128);
        if (tid < 2) asm volatile("red.release.gpu.global.add.u32 [%0], 1;" ::"l"(&gs->wcnt[(2 * NB + tid) * LS]) : "memory");
    }
}

__global__ void __cluster_dims__(2, 1, 1) __launch_bounds__(NTHREADS, 1)
resblock_kernel(const __nv_bfloat16* __restrict__ w1, const __nv_bfloat16* __restrict__ x,
                const __nv_bfloat16* __restrict__ t_emb, const __nv_bfloat16* __restrict__ g1,
                const __nv_bfloat16* __restrict__ be1, const __nv_bfloat16* __restrict__ w_emb,
                const __nv_bfloat16* __restrict__ g2, const __nv_bfloat16* __restrict__ be2,
                const __nv_bfloat16* __restrict__ w2, __nv_bfloat16* __restrict__ out, Scratch* __restrict__ gs,
                const __grid_constant__ CUtensorMap xmap) {
    const unsigned clk0 = clock32();
    if (threadIdx.x == 480 && blockIdx.x >= NXTRA) TLG(1);
    const int tid = threadIdx.x, lane = tid & 31;
    const int cta = blockIdx.x - NXTRA, b = cta >> 6, r = cta & 63;
    uint4 v[5];
    if (tid < 32) weight_load(v, w1, cta & (NCTA - 1), lane);
    uint4 xv[8];
    const int wg4 = (tid >> 5) - 1 - (tid >= 128);
    const bool early = tid >= 32 && wg4 < NLDG && (tid >> 5) != 3;
    if (early) {
        const char* src = reinterpret_cast<const char*>(x) + (uint32_t)((((b & 1) * C + wg4 * 32 + (lane >> 3)) * HW + r) * HW * 2 + (lane & 7) * 16);
        while (clock32() - clk0 < XDELAY + (wg4 >> 1) * XSTAG + (wg4 & 1) * XSTAG2) {}
#pragma unroll
        for (int i = 0; i < 8; i++) xv[i] = __ldg(reinterpret_cast<const uint4*>(src + i * (4 * HW * HW * 2)));
    }
    const int warp = __shfl_sync(0xffffffffu, tid >> 5, 0);
    if (cta < 0) { side_jobs(t_emb, w_emb, w2, gs, clk0); return; }

    if (warp != 3) asm volatile("barrier.cluster.arrive.relaxed.aligned;" ::: "memory");
    const bool has_outer = (r != 0) && (r != HW - 1);
    if (warp == 1 || warp == 2 || warp == 4 || warp == 5) {
        const int g = warp < 3 ? warp - 1 : warp - 2;
        if (elect_one()) {
            if (g >= NLDG) asm volatile("prefetch.tensormap [%0];" ::"l"(&xmap) : "memory");
            mbar_init(BAR(BAR_X) + 8 * g, 1);
            if (g >= NLDG) mbar_expect(BAR(BAR_X) + 8 * g, 4096);
            fence_async_smem();
        }
        __syncwarp();
        bar_arrive(4, 256 + 64 + 128);
        if (g >= NLDG) {
            while (clock32() - clk0 < XDELAY + (g >> 1) * XSTAG + (g & 1) * XSTAG2) {}
            if (elect_one()) tma_x(SM_XOWN + g * 4096, &xmap, r, b * C + g * 32, BAR(BAR_X) + 8 * g);
            __syncwarp();
            mbar_wait(BAR(BAR_X) + 8 * g, 0);
#pragma unroll
            for (int k = 0; k < 8; k++) xv[k] = lds128(SM_XOWN + g * 4096 + k * 512 + lane * 16);
        }
        float c[8][4];
#pragma unroll
        for (int k = 0; k < 8; k++) {
            c[k][0] = c[k][1] = c[k][2] = c[k][3] = 0.f;
            stat_mma(c[k], xv[k].x, xv[k].y); stat_mma(c[k], xv[k].z, xv[k].w);
        }
#pragma unroll
        for (int i = 0; i < 4; i++) c[0][i] = ((c[0][i] + c[1][i]) + (c[2][i] + c[3][i])) + ((c[4][i] + c[5][i]) + (c[6][i] + c[7][i]));
        stat_store(c[0], SM_RED + g * 48, lane);
        __syncwarp();
        if (lane == 0) {
            const uint32_t a = SM_RED + g * 48;
            red_add4(&gs->acc1[b * 4 * LS + g * GS1], 1.f, sum4(lds128f(a + 32)), sum4(lds128f(a)) + sum4(lds128f(a + 16)), 1.f);
            TL(74 + g);
        }
        if (g < NLDG) {
#pragma unroll
            for (int i = 0; i < 8; i++)
                sts128(SM_XOWN + g * 4096 + i * 512 + (lane >> 3) * 128 + (((lane & 7) ^ ((lane >> 3) + 4 * (i & 1))) << 4), xv[i]);
            __syncwarp();
            if (lane == 0) mbar_arrive(BAR(BAR_X) + 8 * g);
        }
    }
    if (warp == 3) {
            if (elect_one()) {
#pragma unroll
                for (int i = 0; i < NSTAGE; i++) mbar_init(BAR(BAR_FULL + i), (i >> 3) == 1 ? 1 : 5);
#pragma unroll
                for (int i = 0; i < NS + 2; i++) mbar_init(BAR(BAR_WEMPTY + i), 4);
#pragma unroll
                for (int i = BAR_STATS; i < BAR_X; i++) mbar_init(BAR(i), i == BAR_EMB ? 3 : 1);
                mbar_init(BAR(BAR_X + 4), 1);
                asm volatile("fence.mbarrier_init.release.cluster;" ::: "memory");
            }
            __syncwarp();
            fence_async_smem();
            bar_arrive(0, 96);
            bar_arrive(5, 96);
            bar_arrive(4, 256 + 64 + 128);
            const uint4 z = make_uint4(0, 0, 0, 0);
#pragma unroll
            for (int i = 0; i < 2; i++) sts128(SM_ACT + (i * 16 + (lane >> 1)) * CH_PITCH + (lane & 1) * 16, z);
            if (lane < 4) sts128(SM_ACT + (2 + (lane >> 1)) * ROW_BYTES + (lane & 1) * 16, z);
            if (lane < 16) sts128(SM_ONES + lane * 16, make_uint4(lane < 8 ? 0x3f803f80u : 0u, 0, 0, 0));
            fence_async_smem();
            asm volatile("barrier.cluster.arrive.relaxed.aligned;" ::: "memory");
            if (lane == 0) TL(5);
            while (clock32() - clk0 < W2DELAY) {}
            weight_load(v, w2, cta, lane);
        }
    if (warp == 0 || warp == 3) {
        const int k = warp & 1;
#pragma unroll
        for (int i = 0; i < 5; i++)
            if (i < 4 || lane < 16) sts128(SM_BNC + k * 2304 + (lane + 32 * i) * 16, v[i]);
        if (lane == 0) TL(k ? 14 : 81);
        __syncwarp();
        weight_block(SM_BNC + k * 2304, gs->wt + k * NSTAGE * STAGE_BYTES, cta, lane, true, gs);
        __syncwarp();
        if (lane == 0) TL(k ? 13 : 4);
        if (lane < 2) asm volatile("red.relaxed.gpu.global.add.u32 [%0], 1;" ::"l"(&gs->wcnt[(k * NB + lane) * LS + (k ? 0 : cta >> 4)]) : "memory");
    }

    if (warp >= 8) {
        const int nw = warp - 8;
        bar_sync(4, 256 + 64 + 128);
        const int par = nw >> 2, wq = nw & 3;
        const uint32_t act_off = SM_ACT + (par * 2 + (lane >> 4)) * CH_PITCH + (2 + wq * 16 + (lane & 15)) * 16;
        const uint32_t stg_off = (par * 16 + (lane >> 4) * 8 + (lane & 7)) * 128 + (((2 * wq + ((lane >> 3) & 1)) ^ (lane & 7)) << 4);
        const uint32_t cfa = SM_COEF + par * 128 + (lane & 3) * 16;
        const uint32_t fbar = BAR(BAR_FULL) + 8 * par;
        uint4* inbox = gs->box + cta * 1024 + nw * 32 + lane;
#pragma unroll 1
        for (int conv = 0; conv < 2; conv++) {
            uint32_t u[4][4], w[4][4];
            float4 cf[8];
            if (conv == 0) {
#pragma unroll
                for (int i = 0; i < 4; i++) { mbar_wait(BAR(BAR_X + i), 0); ldsm4t(u[i], SM_XOWN + stg_off + i * 4096); }
            } else {
                mbar_wait(BAR(BAR_HW), 0);
#pragma unroll
                for (int i = 0; i < 4; i++) ldsm4(u[i], act_off + i * 2 * KC_BYTES);
            }
#pragma unroll
            for (int i = 0; i < 8; i++) cf[i] = lds128f(cfa + conv * 1024 + (i >> 1) * 256 + (i & 1) * 64);
            const uint32_t gst = SM_GST + conv * 32;
            float gv[8];
            read_stats(gst, gv);
            group_coefs<0>(gst, gv, cf);
            if (tid == 256) TL(22 + conv * 4);
            if (par) { const unsigned c1 = clock32(); while (clock32() - c1 < PDELAY) {} }
            norm_block<0, 1>(u, cf, act_off, ~0u, fbar, lane);
            if (tid == 256) TL(8 + conv * 8);
            group_coefs<1>(gst, gv, cf);
            norm_unit(u[1], cf[2], cf[3]);
            stsm4(act_off + 2 * KC_BYTES, u[1][0], u[1][1], u[1][2], u[1][3]);
            next_unit<2>(u, cf, gst, gv, act_off, fbar, lane);
            next_unit<3>(u, cf, gst, gv, act_off, fbar, lane);
            publish(fbar + 48, lane);
            if (tid == 256) TL(84 + conv);
            if (has_outer) {
                mbar_wait(BAR(BAR_X + 4), conv);
                if (conv == 0) {
#pragma unroll
                    for (int i = 0; i < 4; i++) ldsm4t(w[i], SM_XOUT + stg_off + i * 4096);
                } else {
#pragma unroll
                    for (int i = 0; i < 4; i++) {
                        const uint4 q = lds128(SM_XOWN + (tid - 256) * 16 + i * 4096);
                        w[i][0] = q.x; w[i][1] = q.y; w[i][2] = q.z; w[i][3] = q.w;
                    }
                    unsigned it = 0;
                    while (true) {
                        bool ok = true;
#pragma unroll
                        for (int i = 0; i < 16; i++) ok = ok && w[i >> 2][i & 3] != 0;
                        if (__all_sync(0xffffffffu, ok) || ++it > SPIN_LIMIT) break;
#pragma unroll
                        for (int i = 0; i < 4; i++) ld_unit(w[i], inbox + i * 256);
                    }
#pragma unroll
                    for (int i = 0; i < 16; i++) w[i >> 2][i & 3] = ~w[i >> 2][i & 3];
                }
            }
            if (conv == 0) {
                bar_sync(3, 256);
                if (nw == 0) sts128(SM_ACT + 2 * ROW_BYTES + (lane >> 1) * CH_PITCH + (lane & 1) * 16, make_uint4(0, 0, 0, 0));
            }
            if (tid == 256) TL(24 + conv * 4);
            norm_block<0, 2>(w, cf, act_off + 2 * ROW_BYTES, has_outer ? ~0u : 0u, fbar + 128, lane);
            if (tid == 256) TL(88 + conv);
            norm_block<2, 2>(w, cf, act_off + 2 * ROW_BYTES, has_outer ? ~0u : 0u, fbar + 128, lane);
            if (tid == 256) TL(23 + conv * 4);
        }
        if (has_outer) {
            mbar_wait(BAR(BAR_FULL + NSTAGE - 1), 1);
#pragma unroll
            for (int i = 0; i < 4; i++) inbox[i * 256] = make_uint4(0, 0, 0, 0);
        }
        {
            const int oc0 = (tid - 256) >> 3, seg = lane & 7;
            __nv_bfloat16* dst = out + ((size_t)(b * C + oc0) * HW + r) * HW + seg * 8;
            const uint32_t src = SM_XOWN + oc0 * 128 + ((seg ^ (oc0 & 7)) << 4);
            bar_sync(6, 128 + 256);
#pragma unroll
            for (int i = 0; i < 4; i++) *reinterpret_cast<uint4*>(dst + (size_t)i * 32 * HW * HW) = lds128(src + i * 4096);
            if (tid == 256) { TL(20); TLG(21); }
        }
    } else if (warp < 4) {
        const int wq = warp;
        bar_sync(2, 128);

        const uint32_t xbase = SM_XOWN + ((lane >> 4) * 8 + (lane & 7)) * 128 + (((2 * wq + ((lane >> 3) & 1)) ^ (lane & 7)) << 4);
        float d[64];
#pragma unroll
        for (int i = 0; i < 64; i++) d[i] = 0.f;
#pragma unroll 1
        for (int conv = 0; conv < 2; conv++) {
            fence_acc(d);
            mma_stages<0>(d, conv, tid, gs);
            if (conv == 0) {
                asm volatile("wgmma.fence.sync.aligned;" ::: "memory");
                wgmma128<(SM_ONES >> 4) | (8u << 16), (SM_EMB >> 4), 0, 8>(d);
                asm volatile("wgmma.commit_group.sync.aligned;" ::: "memory");
            }
            asm volatile("wgmma.wait_group.sync.aligned 0;" ::: "memory");
            fence_acc(d);
            if (tid == 0) TL(10 + conv * 8);
            uint32_t hp[32];
#pragma unroll
            for (int i = 0; i < 32; i++) hp[i] = pack_bf(d[2 * i], d[2 * i + 1]);
            if (conv == 1) {
#pragma unroll
                for (int kc = 0; kc < 8; kc++) stsm4t(xbase + kc * 2048, hp[4 * kc], hp[4 * kc + 1], hp[4 * kc + 2], hp[4 * kc + 3]);
                bar_arrive(6, 128 + 256);
                break;
            }
#pragma unroll
            for (int g = 0; g < 4; g++) {
                float c[4] = {0.f, 0.f, 0.f, 0.f};
#pragma unroll
                for (int i = 0; i < 4; i++) stat_mma(c, hp[8 * g + 2 * i], hp[8 * g + 2 * i + 1]);
                stat_store(c, SM_RED + (g * 4 + wq) * 48, lane);
            }
            bar_sync(2, 128);
            if (wq == 0) stat_publish(SM_RED, &gs->acc2[b * LS], lane, true);
            if (tid == 0) TL(11);
            const uint32_t hbase = SM_ACT + (lane >> 4) * CH_PITCH + (2 + wq * 16 + (lane & 15)) * 16;
#pragma unroll
            for (int kc = 0; kc < 8; kc++) stsm4(hbase + kc * 2 * CH_PITCH, hp[4 * kc], hp[4 * kc + 1], hp[4 * kc + 2], hp[4 * kc + 3]);
            __syncwarp();
            if (lane == 0) mbar_arrive(BAR(BAR_HW));
            if (lane < LAG) mbar_arrive(BAR(BAR_WEMPTY + (NSTAGE - LAG) % NS) + 8 * lane);
            if (has_outer) {
                uint4* outbox = gs->box + (cta + ((r & 1) ? 1 : -1)) * 1024 + tid;
#pragma unroll
                for (int kc = 0; kc < 8; kc++) outbox[kc * 128] = make_uint4(~hp[4 * kc], ~hp[4 * kc + 1], ~hp[4 * kc + 2], ~hp[4 * kc + 3]);
            }
            if (tid == 0) TL(12);
#pragma unroll
            for (int kc = 0; kc < 8; kc++) {
                uint32_t p[4];
                ldsm4t(p, xbase + kc * 2048);
#pragma unroll
                for (int i = 0; i < 4; i++) { d[8 * kc + 2 * i] = bf_lo(p[i]); d[8 * kc + 2 * i + 1] = bf_hi(p[i]); }
            }
            fence_async_smem();
            __syncwarp();
            if (lane == 0) mbar_arrive(BAR(BAR_XFREE));
        }
        {
        }
    } else if (warp < 6) {
        bar_sync(5, 96);
        if (warp == 5) {
            asm volatile("barrier.cluster.wait.acquire.aligned;" ::: "memory");
            const uint32_t peer = (r & 1) ^ 1;
            const uint32_t self0 = mapa(0, r & 1), peer0 = mapa(0, peer);
#pragma unroll 1
            for (int conv = 0; conv < 2; conv++) {
#pragma unroll 1
                for (int kc = 0; kc < 8; kc++) {
                    mbar_wait(BAR(BAR_FULL) + 8 * kc, conv);
                    if (elect_one())
                        asm volatile("cp.async.bulk.shared::cluster.shared::cta.mbarrier::complete_tx::bytes [%0], [%1], %2, [%3];"
                                     ::"r"(peer0 + SM_ACT + ROW_BYTES + kc * KC_BYTES), "r"(self0 + SM_ACT + kc * KC_BYTES), "r"(KC_BYTES),
                                       "r"(peer0 + BAR(BAR_FULL + 8) + 8 * kc) : "memory");
                }
                if (lane == 0) TL(86 + conv);
#pragma unroll 1
                for (int kc = 0; kc < 8; kc++) mbar_wait(BAR(BAR_FULL + 8) + 8 * kc, conv);
                if (lane == 0)
                    asm volatile("mbarrier.arrive.release.cluster.shared::cluster.b64 _, [%0];" ::"r"(peer0 + (conv ? BAR(BAR_ACK) : BAR(BAR_EMB))) : "memory");
            }
            mbar_wait(BAR(BAR_ACK), 0);
        } else {
            if (has_outer && elect_one()) {
                mbar_expect(BAR(BAR_X + 4), 16384);
#pragma unroll
                for (int i = 0; i < 4; i++) tma_x(SM_XOUT + i * 4096, &xmap, r + ((r & 1) ? 1 : -1), b * C + i * 32, BAR(BAR_X + 4));
            }
            __syncwarp();
            mbar_wait(BAR(BAR_STATS), 0);
            unsigned it = 0;
            while (ld_relaxed(&gs->wcnt[(2 * NB + b) * LS]) < (unsigned)NXTRA && ++it < SPIN_LIMIT) __nanosleep(100);
            fence_acquire();
            float ev[4] = {0.f, 0.f, 0.f, 0.f};
#pragma unroll
            for (int j = 0; j < NXTRA; j++) {
                const uint4 ef = ld_relaxed_v4(&gs->emb[(j * NB + b) * C + lane * 4]);
                ev[0] += __uint_as_float(ef.x); ev[1] += __uint_as_float(ef.y); ev[2] += __uint_as_float(ef.z); ev[3] += __uint_as_float(ef.w);
            }
#pragma unroll
            for (int i = 0; i < 4; i++) {
                const float hi = bf_lo(pack_bf(ev[i], 0.f));
                sts128(SM_EMB + (lane * 4 + i) * 16, make_uint4(pack_bf(hi, ev[i] - hi), 0, 0, 0));
            }
            fence_async_smem();
            __syncwarp();
            if (lane == 0) { mbar_arrive(BAR(BAR_EMB)); TL(19); }
        }
    } else if (warp == 6) {
        bar_sync(0, 96);
        const uint32_t ebytes = STAGE_BYTES + ((lane >> 3) == 1 ? KC_BYTES : 0);
        if (lane < NSTAGE) mbar_expect(BAR(BAR_FULL) + 8 * lane, ebytes);
        const int swap = (r & 1) ? 0 : 8 * STAGE_BYTES;
        unsigned it = 0;
        {
            int g = 0;
#pragma unroll 1
            while (g < NS) {
                unsigned ready = __ballot_sync(0xffffffffu, ld_relaxed(&gs->wcnt[b * LS + (lane & 7)]) >= 16u) >> g;
                if (++it > SPIN_LIMIT) ready = ~0u;
                if (!(ready & 1)) continue;
                fence_acquire();
                fence_async_global();
                if (lane == 0) TL(g ? 3 : 6);
#pragma unroll 1
                for (; (ready & 1) && g < NS; g++, ready >>= 1)
                    if (elect_one())
                        bulk_g2s(S0 + SM_W + g * STAGE_BYTES, gs->wt + g * STAGE_BYTES + (g >= 8 ? swap : 0), STAGE_BYTES, S0 + BAR(BAR_FULL) + 8 * g);
            }
        }
#pragma unroll 1
        for (int q = 3; q < 12; q++) {
            const int conv = q >= 6, qs = conv ? q - 6 : q, sl = q % 3;
            const unsigned char* wsrc = gs->wt + q * 4 * STAGE_BYTES + (qs < 2 ? 0 : (qs < 4 ? swap : -swap));
            const uint32_t par = (q / 3 - 1) & 1;
            if (q == 6) {
                it = 0;
                while (ld_relaxed(&gs->wcnt[(NB + b) * LS]) < (unsigned)NCTA && ++it < SPIN_LIMIT) {}
                fence_acquire();
                fence_async_global();
                if (lane == 0) { mbar_arrive(BAR(BAR_EMB)); TL(2); }
            }
#pragma unroll
            for (int i = 0; i < 4; i++) {
                mbar_wait(BAR(BAR_WEMPTY + i) + 32 * sl, par);
                if (i == 0 && (q == 6 || q == 9)) {
                    if ((lane >= NS) == (q == 9) && lane < NSTAGE) mbar_expect(BAR(BAR_FULL) + 8 * lane, ebytes);
                    __syncwarp();
                }
                if (elect_one())
                    bulk_g2s(S0 + SM_W + (sl * 4 + i) * STAGE_BYTES, wsrc + i * STAGE_BYTES, STAGE_BYTES, S0 + BAR(BAR_FULL + i) + 32 * qs);
            }
        }
    } else {
        const uint2 ga1 = __ldg(reinterpret_cast<const uint2*>(g1) + lane), bt1 = __ldg(reinterpret_cast<const uint2*>(be1) + lane);
        const uint2 ga2 = __ldg(reinterpret_cast<const uint2*>(g2) + lane), bt2 = __ldg(reinterpret_cast<const uint2*>(be2) + lane);
        if (lane < 8) sts128(SM_GST + lane * 16, make_uint4(0, 0, 0, 0));
        sts128f(SM_COEF + lane * 32, make_float4(0.5f * bf_lo(ga1.x), 0.5f * bf_hi(ga1.x), 0.5f * bf_lo(bt1.x), 0.5f * bf_hi(bt1.x)));
        sts128f(SM_COEF + lane * 32 + 16, make_float4(0.5f * bf_lo(ga1.y), 0.5f * bf_hi(ga1.y), 0.5f * bf_lo(bt1.y), 0.5f * bf_hi(bt1.y)));
        sts128f(SM_COEF + 1024 + lane * 32, make_float4(0.5f * bf_lo(ga2.x), 0.5f * bf_hi(ga2.x), 0.5f * bf_lo(bt2.x), 0.5f * bf_hi(bt2.x)));
        sts128f(SM_COEF + 1024 + lane * 32 + 16, make_float4(0.5f * bf_lo(ga2.y), 0.5f * bf_hi(ga2.y), 0.5f * bf_lo(bt2.y), 0.5f * bf_hi(bt2.y)));
        bar_arrive(4, 256 + 64 + 128);
        bar_sync(0, 96);
#pragma unroll 1
        for (int conv = 0; conv < 2; conv++) {
            if (conv == 1) {
                mbar_wait(BAR(BAR_HW), 0);
                const unsigned c1 = clock32();
                while (clock32() - c1 < PD2) {}
            } else {
                while (clock32() - clk0 < PD) {}
            }
            const float* asrc = conv ? &gs->acc2[b * LS + (lane & 3) * 4] : &gs->acc1[b * 4 * LS + (lane & 3) * GS1];
            unsigned it = 0;
            uint4 fq[NPOLL];
#pragma unroll
            for (int i = 0; i < NPOLL; i++) {
                fq[i] = ld_relaxed_v4(asrc);
                if (i + 1 < NPOLL) { const unsigned c1 = clock32(); while (clock32() - c1 < 450 / NPOLL) {} }
            }
            bool all = false;
#pragma unroll 1
            while (!all) {
#pragma unroll
                for (int i = 0; i < NPOLL; i++) {
                    const uint4 f = fq[i];
                    const bool ok = ((f.x == 0x42800000u) & (f.w == 0x42800000u)) || it > SPIN_LIMIT;
                    if (ok && lane < 4) {
                        const float inv_n = 1.0f / (32.0f * HW * HW);
                        const float mean = __uint_as_float(f.y) * inv_n;
                        const float rs = rsqrtf(fmaxf(fmaf(-mean, mean, __uint_as_float(f.z) * inv_n), 0.f) + 1e-5f);
                        asm volatile("st.shared.v2.f32 [%0], {%1,%2};" ::"r"(S0 + SM_GST + conv * 32 + lane * 8), "f"(rs == 0.f ? 1e-38f : rs), "f"(mean * rs) : "memory");
                    }
                    if (__all_sync(0xffffffffu, ok)) { all = true; break; }
                    fq[i] = ld_relaxed_v4(asrc);
                }
                it++;
            }
            if (lane == 0) { mbar_arrive(BAR(BAR_STATS)); TL(7 + conv * 8); }
        }
        mbar_wait(BAR(BAR_XFREE), 0);
        if (has_outer && elect_one()) {
            mbar_expect(BAR(BAR_X + 4), 16384);
            bulk_g2s(S0 + SM_XOWN, gs->box + cta * 1024, 16384, S0 + BAR(BAR_X + 4));
        }
        if (r == 0) {
            if (lane < 16) gs->acc1[b * 4 * LS + (lane >> 2) * GS1 + (lane & 3)] = 0.f;
            if (lane < 24) gs->wcnt[((lane >> 3) * NB + b) * LS + (lane & 7)] = 0;
        }
    }
}

}

extern "C" void kernel_launch(void* const* d_in, const int* in_sizes, int n_in, void* d_out, int out_size) {
    (void)in_sizes; (void)n_in; (void)out_size;
    typedef CUresult (*EncodeFn)(CUtensorMap*, CUtensorMapDataType, cuuint32_t, void*, const cuuint64_t*, const cuuint64_t*,
                                 const cuuint32_t*, const cuuint32_t*, CUtensorMapInterleave, CUtensorMapSwizzle,
                                 CUtensorMapL2promotion, CUtensorMapFloatOOBfill);
    static Scratch* gs = nullptr;
    static EncodeFn encode = nullptr;
    if (!gs) {
        cudaFuncSetAttribute(resblock_kernel, cudaFuncAttributeMaxDynamicSharedMemorySize, SM_TOTAL);
        cudaGetSymbolAddress((void**)&gs, g_scratch);
        cudaDriverEntryPointQueryResult qr;
        cudaGetDriverEntryPoint("cuTensorMapEncodeTiled", (void**)&encode, cudaEnableDefault, &qr);
    }
    CUtensorMap xmap;
    const cuuint64_t dims[3] = {HW, HW, NB * C}, strides[2] = {HW * 2, HW * HW * 2};
    const cuuint32_t box[3] = {HW, 1, 32}, es[3] = {1, 1, 1};
    encode(&xmap, CU_TENSOR_MAP_DATA_TYPE_BFLOAT16, 3, d_in[0], dims, strides, box, es, CU_TENSOR_MAP_INTERLEAVE_NONE,
           CU_TENSOR_MAP_SWIZZLE_128B, CU_TENSOR_MAP_L2_PROMOTION_NONE, CU_TENSOR_MAP_FLOAT_OOB_FILL_NONE);
    resblock_kernel<<<NCTA + NXTRA, NTHREADS, SM_TOTAL>>>(
        (const __nv_bfloat16*)d_in[4], (const __nv_bfloat16*)d_in[0], (const __nv_bfloat16*)d_in[1],
        (const __nv_bfloat16*)d_in[2], (const __nv_bfloat16*)d_in[3], (const __nv_bfloat16*)d_in[5],
        (const __nv_bfloat16*)d_in[6], (const __nv_bfloat16*)d_in[7], (const __nv_bfloat16*)d_in[8],
        (__nv_bfloat16*)d_out, gs, xmap);
}
```

```cpp
#include <cuda_runtime.h>
#include <cuda.h>
#include <cuda_bf16.h>
#include <stdint.h>

namespace {

constexpr int C = 128, HW = 64, NB = 2, E = 768;
constexpr int NCTA = NB * HW;
constexpr int NXTRA = 4;
constexpr int NTHREADS = 16 * 32;
constexpr int CH_PITCH = 66 * 16;
constexpr int ROW_BYTES = 16 * CH_PITCH;
constexpr int STEP_BYTES = 4096;
constexpr int STAGE_BYTES = 3 * STEP_BYTES;
constexpr int NSTAGE = 24;
constexpr int KC_BYTES = 2 * CH_PITCH;
constexpr int NS = 12;
constexpr int LAG = 1;
#define XDELAY 400
#define HDELAY 600
#define SEQ 0
#define MMA0_WAIT mbar_try
#define SPINPAUSE
#define NPOLL 1
#define PD2 0
#define ODELAY 100
#define NLDG 2
#define PSTAG -1
#define PDELAY0 400
#define PDELAY 60
#define RB 1
#define XSTAG2 400
#define XSTAG 800
#define HSEND 0
#define W2DELAY 1800

constexpr uint32_t SMEM_BASE = 0x400;
constexpr uint32_t SM_XOWN = SMEM_BASE;
constexpr uint32_t SM_ACT = SM_XOWN + 16384 + 512;
constexpr uint32_t SM_XOUT = SM_ACT + 2 * ROW_BYTES + 512;
static_assert(SM_XOUT % 1024 == 0, "swizzle atom alignment");
constexpr uint32_t SM_W = SM_ACT + 3 * ROW_BYTES + 128;
__host__ __device__ constexpr uint32_t slot_addr(int slot) { return SM_W + slot * STAGE_BYTES; }
constexpr uint32_t SM_COEF = SM_W + NS * STAGE_BYTES;
constexpr uint32_t SM_GST = SM_COEF + 2048;
constexpr uint32_t SM_EMB = SM_GST + 128;
constexpr uint32_t SM_ONES = SM_EMB + 2048;
constexpr uint32_t SM_RED = SM_ONES + 256;
constexpr uint32_t SM_BNC = SM_RED + 1536;
constexpr uint32_t SM_BAR = SM_BNC + 2 * 2304;
constexpr int BAR_FULL = 0, BAR_WEMPTY = NSTAGE, BAR_HW = BAR_WEMPTY + NS, BAR_XFREE = BAR_HW + 1, BAR_STATS = BAR_XFREE + 1,
              BAR_EMB = BAR_STATS + 1, BAR_ACK = BAR_EMB + 1, BAR_X = BAR_ACK + 1  , NBAR = BAR_X + 5;
constexpr int SM_TOTAL = SM_BAR + NBAR * 8 - SMEM_BASE;
static_assert(SM_TOTAL <= 232448, "smem");
static_assert(NBAR <= 96, "barrier init");
__host__ __device__ constexpr uint32_t BAR(int i) { return SM_BAR + 8 * i; }
__host__ __device__ constexpr int ky_of(int kyo) { return kyo == 0 ? 1 : (kyo == 1 ? 0 : 2); }

constexpr unsigned SPIN_LIMIT = 1u << 16;

#define LS 1056
#define GS1 4
#define PD 0
struct Scratch {
    float acc1[NB * 4 * LS];
    float acc2[NB * LS];
    unsigned wcnt[3 * NB * LS];
    float emb[NXTRA * NB * C];
    unsigned char wt[2 * NSTAGE * STAGE_BYTES];
    uint4 box[NCTA * 1024];
};
__device__ __align__(1024) Scratch g_scratch;
#define TL(i) do {} while (0)
#define TLG(i) do {} while (0)

__device__ __forceinline__ unsigned clock32() { unsigned c; asm volatile("mov.u32 %0, %%clock;" : "=r"(c)); return c; }
__device__ __forceinline__ uint32_t mapa(uint32_t a, uint32_t rank) {
    uint32_t d;
    asm("mapa.shared::cluster.u32 %0, %1, %2;" : "=r"(d) : "r"(a), "r"(rank));
    return d;
}
#define S0 mapa(0, blockIdx.x & 1)
__device__ __forceinline__ void mbar_init(uint32_t bar, int cnt) {
    asm volatile("mbarrier.init.shared::cta.b64 [%0], %1;" ::"r"(bar + S0), "r"(cnt) : "memory");
}
__device__ __forceinline__ void mbar_arrive(uint32_t bar) {
    asm volatile("mbarrier.arrive.shared::cta.b64 _, [%0];" ::"r"(bar + S0) : "memory");
}
__device__ __forceinline__ void mbar_expect(uint32_t bar, uint32_t bytes) {
    asm volatile("mbarrier.arrive.expect_tx.shared::cta.b64 _, [%0], %1;" ::"r"(bar + S0), "r"(bytes) : "memory");
}
__device__ __forceinline__ bool mbar_try(uint32_t bar, uint32_t par) {
    uint32_t ok;
    asm volatile("{\n.reg .pred p;\nmbarrier.try_wait.parity.shared::cta.b64 p, [%1], %2;\nselp.u32 %0, 1, 0, p;\n}"
                 : "=r"(ok) : "r"(bar + S0), "r"(par) : "memory");
    return ok;
}
__device__ __forceinline__ bool mbar_test(uint32_t bar, uint32_t par) {
    uint32_t ok;
    asm volatile("{\n.reg .pred p;\nmbarrier.test_wait.parity.shared::cta.b64 p, [%1], %2;\nselp.u32 %0, 1, 0, p;\n}"
                 : "=r"(ok) : "r"(bar + S0), "r"(par) : "memory");
    return ok;
}
__device__ __forceinline__ void mbar_wait(uint32_t bar, uint32_t par) {
    unsigned it = 0;
#pragma unroll 1
    while (!mbar_try(bar, par) && ++it < SPIN_LIMIT) {}
}
__device__ __forceinline__ bool elect_one() {
    uint32_t p;
    asm volatile("{\n.reg .pred p;\nelect.sync _|p, 0xffffffff;\nselp.u32 %0, 1, 0, p;\n}" : "=r"(p));
    return p;
}
__device__ __forceinline__ void fence_async_smem() { asm volatile("fence.proxy.async.shared::cta;" ::: "memory"); }
__device__ __forceinline__ void fence_async_global() { asm volatile("fence.proxy.async.global;" ::: "memory"); }
__device__ __forceinline__ void fence_acquire() { asm volatile("fence.acquire.gpu;" ::: "memory"); }
__device__ __forceinline__ void bar_sync(int id, int n) { asm volatile("bar.sync %0, %1;" ::"r"(id), "r"(n) : "memory"); }
__device__ __forceinline__ void bar_arrive(int id, int n) { asm volatile("bar.arrive %0, %1;" ::"r"(id), "r"(n) : "memory"); }
__device__ __forceinline__ void bulk_g2s(uint32_t dst, const void* src, uint32_t bytes, uint32_t bar) {
    asm volatile("cp.async.bulk.shared::cluster.global.mbarrier::complete_tx::bytes [%0], [%1], %2, [%3];"
                 ::"r"(dst), "l"(src), "r"(bytes), "r"(bar) : "memory");
}
__device__ __forceinline__ void tma_x(uint32_t dst, const CUtensorMap* tm, int row, int ch, uint32_t bar) {
    asm volatile("cp.async.bulk.tensor.3d.shared::cluster.global.mbarrier::complete_tx::bytes [%0], [%1, {%2, %3, %4}], [%5];"
                 ::"r"(dst + S0), "l"(tm), "r"(0), "r"(row), "r"(ch), "r"(bar + S0) : "memory");
}
__device__ __forceinline__ uint4 ld_relaxed_v4(const void* p) {
    uint4 v;
    asm volatile("ld.relaxed.gpu.global.v4.u32 {%0,%1,%2,%3}, [%4];" : "=r"(v.x), "=r"(v.y), "=r"(v.z), "=r"(v.w) : "l"(p) : "memory");
    return v;
}
__device__ __forceinline__ unsigned ld_relaxed(const void* p) {
    unsigned v;
    asm volatile("ld.relaxed.gpu.global.u32 %0, [%1];" : "=r"(v) : "l"(p) : "memory");
    return v;
}
__device__ __forceinline__ void red_add4(float* p, float a, float b, float c, float d) {
    asm volatile("red.relaxed.gpu.global.add.v4.f32 [%0], {%1,%2,%3,%4};" ::"l"(p), "f"(a), "f"(b), "f"(c), "f"(d) : "memory");
}
__device__ __forceinline__ void sts128(uint32_t a, uint4 v) {
    asm volatile("st.shared.v4.u32 [%0], {%1,%2,%3,%4};" ::"r"(a + S0), "r"(v.x), "r"(v.y), "r"(v.z), "r"(v.w) : "memory");
}
__device__ __forceinline__ void sts128f(uint32_t a, float4 v) {
    asm volatile("st.shared.v4.f32 [%0], {%1,%2,%3,%4};" ::"r"(a + S0), "f"(v.x), "f"(v.y), "f"(v.z), "f"(v.w) : "memory");
}
__device__ __forceinline__ void sts32f(uint32_t a, float v) { asm volatile("st.shared.f32 [%0], %1;" ::"r"(a + S0), "f"(v) : "memory"); }
__device__ __forceinline__ uint4 lds128(uint32_t a) {
    uint4 v;
    asm volatile("ld.shared.v4.u32 {%0,%1,%2,%3}, [%4];" : "=r"(v.x), "=r"(v.y), "=r"(v.z), "=r"(v.w) : "r"(a + S0) : "memory");
    return v;
}
__device__ __forceinline__ float4 lds128f(uint32_t a) {
    float4 v;
    asm volatile("ld.shared.v4.f32 {%0,%1,%2,%3}, [%4];" : "=f"(v.x), "=f"(v.y), "=f"(v.z), "=f"(v.w) : "r"(a + S0) : "memory");
    return v;
}
__device__ __forceinline__ float2 lds64f(uint32_t a) {
    float2 v;
    asm volatile("ld.shared.v2.f32 {%0,%1}, [%2];" : "=f"(v.x), "=f"(v.y) : "r"(a + S0) : "memory");
    return v;
}
__device__ __forceinline__ float bf_lo(uint32_t u) { return __uint_as_float(u << 16); }
__device__ __forceinline__ float bf_hi(uint32_t u) { return __uint_as_float(u & 0xffff0000u); }
__device__ __forceinline__ uint32_t pack_bf(float lo, float hi) {
    uint32_t r;
    asm("cvt.rn.bf16x2.f32 %0, %1, %2;" : "=r"(r) : "f"(hi), "f"(lo));
    return r;
}
__device__ __forceinline__ float tanh_fast(float x) {
    float r;
    asm("tanh.approx.f32 %0, %1;" : "=f"(r) : "f"(x));
    return r;
}
__device__ __forceinline__ float silu_half(float h) { return fmaf(h, tanh_fast(h), h); }
__device__ __forceinline__ void ldsm4(uint32_t (&u)[4], uint32_t a) {
    asm volatile("ldmatrix.sync.aligned.m8n8.x4.shared.b16 {%0,%1,%2,%3}, [%4];"
                 : "=r"(u[0]), "=r"(u[1]), "=r"(u[2]), "=r"(u[3]) : "r"(a + S0) : "memory");
}
__device__ __forceinline__ void ldsm4t(uint32_t (&u)[4], uint32_t a) {
    asm volatile("ldmatrix.sync.aligned.m8n8.x4.trans.shared.b16 {%0,%1,%2,%3}, [%4];"
                 : "=r"(u[0]), "=r"(u[1]), "=r"(u[2]), "=r"(u[3]) : "r"(a + S0) : "memory");
}
__device__ __forceinline__ void stsm4(uint32_t a, uint32_t p0, uint32_t p1, uint32_t p2, uint32_t p3) {
    asm volatile("stmatrix.sync.aligned.m8n8.x4.shared.b16 [%0], {%1,%2,%3,%4};" ::"r"(a + S0), "r"(p0), "r"(p1), "r"(p2), "r"(p3) : "memory");
}
__device__ __forceinline__ void stsm4t(uint32_t a, uint32_t p0, uint32_t p1, uint32_t p2, uint32_t p3) {
    asm volatile("stmatrix.sync.aligned.m8n8.x4.trans.shared.b16 [%0], {%1,%2,%3,%4};" ::"r"(a + S0), "r"(p0), "r"(p1), "r"(p2), "r"(p3) : "memory");
}

#define R8(o) "+f"(d[o]), "+f"(d[o + 1]), "+f"(d[o + 2]), "+f"(d[o + 3]), "+f"(d[o + 4]), "+f"(d[o + 5]), "+f"(d[o + 6]), "+f"(d[o + 7])
template <uint32_t ALO, uint32_t BLO, uint64_t AHI = 8, uint64_t BHI = 48>
__device__ __forceinline__ void wgmma128(float (&d)[64]) {
    asm volatile(
        "wgmma.mma_async.sync.aligned.m64n128k16.f32.bf16.bf16 "
        "{%0,%1,%2,%3,%4,%5,%6,%7,%8,%9,%10,%11,%12,%13,%14,%15,%16,%17,%18,%19,%20,%21,%22,%23,%24,%25,%26,%27,%28,%29,%30,%31,"
        "%32,%33,%34,%35,%36,%37,%38,%39,%40,%41,%42,%43,%44,%45,%46,%47,%48,%49,%50,%51,%52,%53,%54,%55,%56,%57,%58,%59,%60,%61,%62,%63},"
        " %64, %65, 1, 1, 1, 0, 0;"
        : R8(0), R8(8), R8(16), R8(24), R8(32), R8(40), R8(48), R8(56)
        : "l"((AHI << 32) | ALO), "l"((BHI << 32) | BLO));
}
template <int S>
__device__ __forceinline__ void mma_stages(float (&d)[64], int conv, int tid, Scratch* gs) {
    constexpr uint32_t A = ((SM_ACT + S * 2 * CH_PITCH + 16) >> 4) | ((CH_PITCH >> 4) << 16);
    constexpr uint32_t B = (slot_addr(S % NS) >> 4) | (8u << 16);
    if (S == 0) {
        unsigned it = 0;
#pragma unroll 1
        while (!MMA0_WAIT(BAR(BAR_FULL), conv) && ++it < SPIN_LIMIT) {}
    }
    bool next_ok = true;
    constexpr uint32_t NEXT = S + 1 < NSTAGE ? BAR(BAR_FULL + S + 1) : BAR(BAR_EMB);
    const int npar = S + 1 < NSTAGE ? conv : 0;
    next_ok = mbar_test(NEXT, npar);
    if (S == 0 && tid == 0) TL(32 + conv * 24);
    asm volatile("wgmma.fence.sync.aligned;" ::: "memory");
    wgmma128<A, B>(d);
    wgmma128<A + 1, B + 16>(d);
    wgmma128<A + 2, B + 32>(d);
    asm volatile("wgmma.commit_group.sync.aligned;" ::: "memory");
    if (S >= LAG) {
        asm volatile("wgmma.wait_group.sync.aligned %0;" ::"n"(LAG) : "memory");
        if ((tid & 31) == 0) mbar_arrive(BAR(BAR_WEMPTY + (S + NS - LAG) % NS));
    }
    if (!next_ok) mbar_wait(NEXT, npar);
    if constexpr (S + 1 < NSTAGE) mma_stages<S + 1>(d, conv, tid, gs);
}

__device__ __forceinline__ void weight_load(uint4 (&t)[5], const __nv_bfloat16* w, int cta, int lane) {
    const char* base = reinterpret_cast<const char*>(w) + ((cta & 15) * 8 * C + (cta >> 4) * 16) * 18;
#pragma unroll
    for (int k = 0; k < 5; k++) {
        const int i = lane + 32 * k, row = (i * 57) >> 10;
        if (k < 4 || lane < 16) t[k] = __ldg(reinterpret_cast<const uint4*>(base + row * (C * 18 - 288) + i * 16));
    }
}
__device__ __forceinline__ void weight_block(uint32_t bounce, unsigned char* wt, int cta, int lane, bool readback, Scratch* gs) {
    unsigned char* dst = wt + (cta >> 4) * STAGE_BYTES + (cta & 15) * 768;
    if (lane < 16) {
        uint32_t v[36];
#pragma unroll
        for (int i = 0; i < 9; i++) {
            const uint4 q = lds128(bounce + (lane & 7) * 288 + (lane >> 3) * 144 + i * 16);
            v[4 * i] = q.x; v[4 * i + 1] = q.y; v[4 * i + 2] = q.z; v[4 * i + 3] = q.w;
        }
#pragma unroll
        for (int kyo = 0; kyo < 3; kyo++) {
#pragma unroll
            for (int kx = 0; kx < 3; kx++) {
                const int tap = ky_of(kyo) * 3 + kx;
                uint32_t o[4];
#pragma unroll
                for (int m = 0; m < 4; m++) {
                    const int i0 = 18 * m + tap, i1 = i0 + 9;
                    const uint32_t sel = ((i0 & 1) ? 0x32u : 0x10u) | ((i1 & 1) ? 0x7600u : 0x5400u);
                    o[m] = __byte_perm(v[i0 >> 1], v[i1 >> 1], sel);
                }
                *reinterpret_cast<uint4*>(dst + kyo * 8 * STAGE_BYTES + kx * 256 + lane * 16) = make_uint4(o[0], o[1], o[2], o[3]);
            }
        }
    }
    if (readback) {
        __syncwarp();
        unsigned acc = 0;
        if (lane < 24) {
#pragma unroll
            for (int i = 0; i < 3; i++) acc |= ld_relaxed(dst + i * 8 * STAGE_BYTES + lane * 32);
        }
        asm volatile("{\n.reg .pred p;\nsetp.eq.u32 p, %0, 0x9e3779b9;\n@p st.shared.u32 [%1], %0;\n}" ::"r"(acc), "r"(bounce + S0) : "memory");
    }
}
__device__ __forceinline__ uint32_t act2(uint32_t u, const float4& cf) {
    return pack_bf(silu_half(fmaf(bf_lo(u), cf.x, cf.z)), silu_half(fmaf(bf_hi(u), cf.y, cf.w)));
}
__device__ __forceinline__ void norm_unit(uint32_t (&u)[4], const float4& ca, const float4& cb) {
    u[0] = act2(u[0], ca); u[1] = act2(u[1], ca); u[2] = act2(u[2], cb); u[3] = act2(u[3], cb);
}
__device__ __forceinline__ void read_stats(uint32_t gst, float (&g)[8]) {
    asm volatile("ld.volatile.shared.v4.f32 {%0,%1,%2,%3}, [%4];" : "=f"(g[0]), "=f"(g[1]), "=f"(g[2]), "=f"(g[3]) : "r"(gst + S0) : "memory");
    asm volatile("ld.volatile.shared.v4.f32 {%0,%1,%2,%3}, [%4];" : "=f"(g[4]), "=f"(g[5]), "=f"(g[6]), "=f"(g[7]) : "r"(gst + 16 + S0) : "memory");
}
template <int T>
__device__ __forceinline__ void group_coefs(uint32_t gst, float (&g)[8], float4 (&cf)[8]) {
    unsigned it = 0;
    if (!__all_sync(0xffffffffu, g[2 * T] != 0.f)) {
        float rs0;
#pragma unroll 1
        do {
            SPINPAUSE;
            asm volatile("ld.volatile.shared.f32 %0, [%1];" : "=f"(rs0) : "r"(gst + 8 * T + S0) : "memory");
        } while (!__all_sync(0xffffffffu, rs0 != 0.f) && ++it < 8 * SPIN_LIMIT);
        read_stats(gst, g);
    }
    float4 &ca = cf[2 * T], &cb = cf[2 * T + 1];
    const float rs = g[2 * T], mr = g[2 * T + 1];
    ca.z = fmaf(-mr, ca.x, ca.z); ca.w = fmaf(-mr, ca.y, ca.w); ca.x *= rs; ca.y *= rs;
    cb.z = fmaf(-mr, cb.x, cb.z); cb.w = fmaf(-mr, cb.y, cb.w); cb.x *= rs; cb.y *= rs;
}
template <int FIRST, int N>
__device__ __forceinline__ void norm_block(uint32_t (&u)[4][4], float4 (&cf)[8], uint32_t act, uint32_t mask, uint32_t fbar, int lane) {
#pragma unroll
    for (int t = FIRST; t < FIRST + N; t++) {
        norm_unit(u[t], cf[2 * t], cf[2 * t + 1]);
        stsm4(act + t * 2 * KC_BYTES, u[t][0] & mask, u[t][1] & mask, u[t][2] & mask, u[t][3] & mask);
    }
    fence_async_smem();
    __syncwarp();
    if (lane < N) mbar_arrive(fbar + 16 * (FIRST + lane));
}
__device__ __forceinline__ void publish(uint32_t bar, int lane) {
    fence_async_smem();
    __syncwarp();
    if (lane == 0) mbar_arrive(bar);
}
template <int T>
__device__ __forceinline__ void next_unit(uint32_t (&u)[4][4], float4 (&cf)[8], uint32_t gst, float (&g)[8], uint32_t act, uint32_t fbar, int lane) {
    const bool have = __all_sync(0xffffffffu, g[2 * T] != 0.f);
    if (!have) publish(fbar + 16 * (T - 1), lane);
    group_coefs<T>(gst, g, cf);
    norm_unit(u[T], cf[2 * T], cf[2 * T + 1]);
    if (have) publish(fbar + 16 * (T - 1), lane);
    stsm4(act + T * 2 * KC_BYTES, u[T][0], u[T][1], u[T][2], u[T][3]);
}
__device__ __forceinline__ void stat_mma(float (&c)[4], uint32_t p, uint32_t q) {
    asm("mma.sync.aligned.m16n8k16.row.col.f32.bf16.bf16.f32 {%0,%1,%2,%3}, {%4,%5,%6,%5}, {%4,%6}, {%0,%1,%2,%3};"
        : "+f"(c[0]), "+f"(c[1]), "+f"(c[2]), "+f"(c[3]) : "r"(p), "r"(0x3f803f80u), "r"(q));
}
__device__ __forceinline__ void stat_store(const float (&c)[4], uint32_t dst, int lane) {
    const int g = lane >> 2, t = lane & 3;
    if (t == (g >> 1)) sts32f(dst + g * 4, (g & 1) ? c[1] : c[0]);
    if (g == 7) sts32f(dst + 32 + t * 4, c[2] + c[3]);
}
__device__ __forceinline__ float sum4(float4 v) { return (v.x + v.y) + (v.z + v.w); }
__device__ __forceinline__ void stat_publish(uint32_t src, float* acc, int lane, bool real) {
    const uint32_t a = src + (lane & 15) * 48;
    float q = sum4(lds128f(a)) + sum4(lds128f(a + 16)), sm = sum4(lds128f(a + 32));
    q += __shfl_xor_sync(0xffffffffu, q, 1); sm += __shfl_xor_sync(0xffffffffu, sm, 1);
    q += __shfl_xor_sync(0xffffffffu, q, 2); sm += __shfl_xor_sync(0xffffffffu, sm, 2);
    if (real && (lane & 19) == 0) red_add4(acc + lane, 1.f, sm, q, 1.f);
}
__device__ __forceinline__ void fence_acc(float (&d)[64]) {
#pragma unroll
    for (int i = 0; i < 64; i++) asm volatile("" : "+f"(d[i])::"memory");
}
__device__ __forceinline__ void ld_unit(uint32_t (&u)[4], const uint4* p) {
    asm volatile("ld.relaxed.gpu.global.v4.u32 {%0,%1,%2,%3}, [%4];" : "=r"(u[0]), "=r"(u[1]), "=r"(u[2]), "=r"(u[3]) : "l"(p) : "memory");
}

__device__ __noinline__ void side_jobs(const __nv_bfloat16* __restrict__ t_emb, const __nv_bfloat16* __restrict__ w_emb,
                                       const __nv_bfloat16* __restrict__ w2, Scratch* __restrict__ gs, unsigned clk0) {
    const int tid = threadIdx.x, warp = tid >> 5, lane = tid & 31, j = blockIdx.x;
    float tv = 0.f;
    if (lane < 24) tv = __bfloat162float(t_emb[(lane / 12) * E + j * 192 + warp * 12 + lane % 12]);
    if (tid == 0) {
        mbar_init(BAR(0), 1);
        mbar_expect(BAR(0), 192 * C * 2);
        fence_async_smem();
        while (clock32() - clk0 < W2DELAY) {}
#pragma unroll
        for (int i = 0; i < 4; i++) bulk_g2s(S0 + SM_W + i * 12288, w_emb + (j * 192 + i * 48) * C, 12288, S0 + BAR(0));
    }
    if (j == 0 && tid < 32) gs->acc2[(tid >> 4) * LS + (tid & 15)] = 0.f;
    const float sv = silu_half(0.5f * tv);
    __syncthreads();
    mbar_wait(BAR(0), 0);
    float acc[8] = {0.f, 0.f, 0.f, 0.f, 0.f, 0.f, 0.f, 0.f};
#pragma unroll
    for (int i = 0; i < 12; i++) {
        const float2 wq = lds64f(SM_W + (warp * 12 + i) * 256 + lane * 8);
        const uint32_t wx = __float_as_uint(wq.x), wy = __float_as_uint(wq.y);
#pragma unroll
        for (int bb = 0; bb < 2; bb++) {
            const float sx = __shfl_sync(0xffffffffu, sv, bb * 12 + i);
            acc[4 * bb + 0] = fmaf(sx, bf_lo(wx), acc[4 * bb + 0]); acc[4 * bb + 1] = fmaf(sx, bf_hi(wx), acc[4 * bb + 1]);
            acc[4 * bb + 2] = fmaf(sx, bf_lo(wy), acc[4 * bb + 2]); acc[4 * bb + 3] = fmaf(sx, bf_hi(wy), acc[4 * bb + 3]);
        }
    }
    sts128f(SM_ACT + warp * 1024 + lane * 16, make_float4(acc[0], acc[1], acc[2], acc[3]));
    sts128f(SM_ACT + warp * 1024 + 512 + lane * 16, make_float4(acc[4], acc[5], acc[6], acc[7]));
    __syncthreads();
    if (tid < 128) {
        float2 sum = make_float2(0.f, 0.f);
#pragma unroll
        for (int w = 0; w < 16; w++) { const float2 p = lds64f(SM_ACT + w * 1024 + tid * 8); sum.x += p.x; sum.y += p.y; }
        *reinterpret_cast<float2*>(&gs->emb[j * NB * C + tid * 2]) = sum;
        bar_sync(1, 128);
        if (tid < 2) asm volatile("red.release.gpu.global.add.u32 [%0], 1;" ::"l"(&gs->wcnt[(2 * NB + tid) * LS]) : "memory");
    }
}

__global__ void __cluster_dims__(2, 1, 1) __launch_bounds__(NTHREADS, 1)
resblock_kernel(const __nv_bfloat16* __restrict__ w1, const __nv_bfloat16* __restrict__ x,
                const __nv_bfloat16* __restrict__ t_emb, const __nv_bfloat16* __restrict__ g1,
                const __nv_bfloat16* __restrict__ be1, const __nv_bfloat16* __restrict__ w_emb,
                const __nv_bfloat16* __restrict__ g2, const __nv_bfloat16* __restrict__ be2,
                const __nv_bfloat16* __restrict__ w2, __nv_bfloat16* __restrict__ out, Scratch* __restrict__ gs,
                const __grid_constant__ CUtensorMap xmap) {
    const unsigned clk0 = clock32();
    if (threadIdx.x == 480 && blockIdx.x >= NXTRA) TLG(1);
    const int tid = threadIdx.x, lane = tid & 31;
    const int cta = blockIdx.x - NXTRA, b = cta >> 6, r = cta & 63;
    uint4 v[5];
    if (tid < 32) weight_load(v, w1, cta & (NCTA - 1), lane);
    uint4 xv[8];
    const int wg4 = (tid >> 5) - 1;
    const bool early = tid >= 32 && wg4 < NLDG;
    if (early) {
        const char* src = reinterpret_cast<const char*>(x) + (uint32_t)((((b & 1) * C + wg4 * 32 + (lane >> 3)) * HW + r) * HW * 2 + (lane & 7) * 16);
        while (clock32() - clk0 < XDELAY + (wg4 >> 1) * XSTAG + (wg4 & 1) * XSTAG2) {}
#pragma unroll
        for (int i = 0; i < 8; i++) xv[i] = __ldg(reinterpret_cast<const uint4*>(src + i * (4 * HW * HW * 2)));
    }
    const int warp = __shfl_sync(0xffffffffu, tid >> 5, 0);
    if (cta < 0) { side_jobs(t_emb, w_emb, w2, gs, clk0); return; }

    if (warp != 4) asm volatile("barrier.cluster.arrive.relaxed.aligned;" ::: "memory");
    const bool has_outer = (r != 0) && (r != HW - 1);
    if (warp == 1 || warp == 2 || warp == 3 || warp == 5) {
        const int g = warp < 4 ? warp - 1 : 3;
        if (elect_one()) {
            if (g >= NLDG) asm volatile("prefetch.tensormap [%0];" ::"l"(&xmap) : "memory");
            mbar_init(BAR(BAR_X) + 8 * g, 1);
            if (g >= NLDG) mbar_expect(BAR(BAR_X) + 8 * g, 4096);
            fence_async_smem();
        }
        __syncwarp();
        bar_arrive(4, 256 + 64 + 128);
        if (g >= NLDG) {
            while (clock32() - clk0 < XDELAY + (g >> 1) * XSTAG + (g & 1) * XSTAG2) {}
            if (elect_one()) tma_x(SM_XOWN + g * 4096, &xmap, r, b * C + g * 32, BAR(BAR_X) + 8 * g);
            __syncwarp();
            mbar_wait(BAR(BAR_X) + 8 * g, 0);
#pragma unroll
            for (int k = 0; k < 8; k++) xv[k] = lds128(SM_XOWN + g * 4096 + k * 512 + lane * 16);
        }
        float c[8][4];
#pragma unroll
        for (int k = 0; k < 8; k++) {
            c[k][0] = c[k][1] = c[k][2] = c[k][3] = 0.f;
            stat_mma(c[k], xv[k].x, xv[k].y); stat_mma(c[k], xv[k].z, xv[k].w);
        }
#pragma unroll
        for (int i = 0; i < 4; i++) c[0][i] = ((c[0][i] + c[1][i]) + (c[2][i] + c[3][i])) + ((c[4][i] + c[5][i]) + (c[6][i] + c[7][i]));
        stat_store(c[0], SM_RED + g * 48, lane);
        __syncwarp();
        if (lane == 0) {
            const uint32_t a = SM_RED + g * 48;
            red_add4(&gs->acc1[b * 4 * LS + g * GS1], 1.f, sum4(lds128f(a + 32)), sum4(lds128f(a)) + sum4(lds128f(a + 16)), 1.f);
            TL(74 + g);
        }
        if (g < NLDG) {
#pragma unroll
            for (int i = 0; i < 8; i++)
                sts128(SM_XOWN + g * 4096 + i * 512 + (lane >> 3) * 128 + (((lane & 7) ^ ((lane >> 3) + 4 * (i & 1))) << 4), xv[i]);
            __syncwarp();
            if (lane == 0) mbar_arrive(BAR(BAR_X) + 8 * g);
        }
    }
    if (warp == 4) {
            if (elect_one()) {
#pragma unroll
                for (int i = 0; i < NSTAGE; i++) mbar_init(BAR(BAR_FULL + i), (i >> 3) == 1 ? 1 : 5);
#pragma unroll
                for (int i = 0; i < NS + 2; i++) mbar_init(BAR(BAR_WEMPTY + i), 4);
#pragma unroll
                for (int i = BAR_STATS; i < BAR_X; i++) mbar_init(BAR(i), i == BAR_EMB ? 3 : 1);
                mbar_init(BAR(BAR_X + 4), 1);
                asm volatile("fence.mbarrier_init.release.cluster;" ::: "memory");
            }
            __syncwarp();
            fence_async_smem();
            bar_arrive(0, 96);
            bar_arrive(5, 64);
            bar_arrive(4, 256 + 64 + 128);
            const uint4 z = make_uint4(0, 0, 0, 0);
#pragma unroll
            for (int i = 0; i < 2; i++) sts128(SM_ACT + (i * 16 + (lane >> 1)) * CH_PITCH + (lane & 1) * 16, z);
            if (lane < 4) sts128(SM_ACT + (2 + (lane >> 1)) * ROW_BYTES + (lane & 1) * 16, z);
            if (lane < 16) sts128(SM_ONES + lane * 16, make_uint4(lane < 8 ? 0x3f803f80u : 0u, 0, 0, 0));
            fence_async_smem();
            bar_arrive(7, 160);
            asm volatile("barrier.cluster.arrive.relaxed.aligned;" ::: "memory");
            if (lane == 0) TL(5);
            while (clock32() - clk0 < W2DELAY) {}
            weight_load(v, w2, cta, lane);
        }
    if (warp == 0 || warp == 4) {
        const int k = warp >> 2;
#pragma unroll
        for (int i = 0; i < 5; i++)
            if (i < 4 || lane < 16) sts128(SM_BNC + k * 2304 + (lane + 32 * i) * 16, v[i]);
        if (lane == 0) TL(k ? 14 : 81);
        __syncwarp();
        weight_block(SM_BNC + k * 2304, gs->wt + k * NSTAGE * STAGE_BYTES, cta, lane, true, gs);
        __syncwarp();
        if (lane == 0) TL(k ? 13 : 4);
        if (lane < 2) asm volatile("red.relaxed.gpu.global.add.u32 [%0], 1;" ::"l"(&gs->wcnt[(k * NB + lane) * LS + (k ? 0 : cta >> 4)]) : "memory");
    }

    if (warp >= 8) {
        const int nw = warp - 8;
        bar_sync(4, 256 + 64 + 128);
        const int par = nw >> 2, wq = nw & 3;
        const uint32_t act_off = SM_ACT + (par * 2 + (lane >> 4)) * CH_PITCH + (2 + wq * 16 + (lane & 15)) * 16;
        const uint32_t stg_off = (par * 16 + (lane >> 4) * 8 + (lane & 7)) * 128 + (((2 * wq + ((lane >> 3) & 1)) ^ (lane & 7)) << 4);
        const uint32_t cfa = SM_COEF + par * 128 + (lane & 3) * 16;
        const uint32_t fbar = BAR(BAR_FULL) + 8 * par;
        uint4* inbox = gs->box + cta * 1024 + nw * 32 + lane;
#pragma unroll 1
        for (int conv = 0; conv < 2; conv++) {
            uint32_t u[4][4], w[4][4];
            float4 cf[8];
            if (conv == 0) {
#pragma unroll
                for (int i = 0; i < 4; i++) { mbar_wait(BAR(BAR_X + i), 0); ldsm4t(u[i], SM_XOWN + stg_off + i * 4096); }
            } else {
                mbar_wait(BAR(BAR_HW), 0);
#pragma unroll
                for (int i = 0; i < 4; i++) ldsm4(u[i], act_off + i * 2 * KC_BYTES);
            }
#pragma unroll
            for (int i = 0; i < 8; i++) cf[i] = lds128f(cfa + conv * 1024 + (i >> 1) * 256 + (i & 1) * 64);
            const uint32_t gst = SM_GST + conv * 32;
            float gv[8];
            read_stats(gst, gv);
            group_coefs<0>(gst, gv, cf);
            if (tid == 256) TL(22 + conv * 4);
            if (par) { const unsigned c1 = clock32(); while (clock32() - c1 < PDELAY) {} }
            norm_block<0, 1>(u, cf, act_off, ~0u, fbar, lane);
            if (tid == 256) TL(8 + conv * 8);
            group_coefs<1>(gst, gv, cf);
            norm_unit(u[1], cf[2], cf[3]);
            stsm4(act_off + 2 * KC_BYTES, u[1][0], u[1][1], u[1][2], u[1][3]);
            next_unit<2>(u, cf, gst, gv, act_off, fbar, lane);
            next_unit<3>(u, cf, gst, gv, act_off, fbar, lane);
            publish(fbar + 48, lane);
            if (tid == 256) TL(84 + conv);
            if (has_outer) {
                mbar_wait(BAR(BAR_X + 4), conv);
                if (conv == 0) {
#pragma unroll
                    for (int i = 0; i < 4; i++) ldsm4t(w[i], SM_XOUT + stg_off + i * 4096);
                } else {
#pragma unroll
                    for (int i = 0; i < 4; i++) {
                        const uint4 q = lds128(SM_XOWN + (tid - 256) * 16 + i * 4096);
                        w[i][0] = q.x; w[i][1] = q.y; w[i][2] = q.z; w[i][3] = q.w;
                    }
                    unsigned it = 0;
                    while (true) {
                        bool ok = true;
#pragma unroll
                        for (int i = 0; i < 16; i++) ok = ok && w[i >> 2][i & 3] != 0;
                        if (__all_sync(0xffffffffu, ok) || ++it > SPIN_LIMIT) break;
#pragma unroll
                        for (int i = 0; i < 4; i++) ld_unit(w[i], inbox + i * 256);
                    }
#pragma unroll
                    for (int i = 0; i < 16; i++) w[i >> 2][i & 3] = ~w[i >> 2][i & 3];
                }
            }
            if (conv == 0) {
                bar_sync(3, 256);
                if (nw == 0) sts128(SM_ACT + 2 * ROW_BYTES + (lane >> 1) * CH_PITCH + (lane & 1) * 16, make_uint4(0, 0, 0, 0));
            }
            if (tid == 256) TL(24 + conv * 4);
            norm_block<0, 2>(w, cf, act_off + 2 * ROW_BYTES, has_outer ? ~0u : 0u, fbar + 128, lane);
            if (tid == 256) TL(88 + conv);
            norm_block<2, 2>(w, cf, act_off + 2 * ROW_BYTES, has_outer ? ~0u : 0u, fbar + 128, lane);
            if (tid == 256) TL(23 + conv * 4);
        }
        if (has_outer) {
            mbar_wait(BAR(BAR_FULL + NSTAGE - 1), 1);
#pragma unroll
            for (int i = 0; i < 4; i++) inbox[i * 256] = make_uint4(0, 0, 0, 0);
        }
        {
            const int oc0 = (tid - 256) >> 3, seg = lane & 7;
            __nv_bfloat16* dst = out + ((size_t)(b * C + oc0) * HW + r) * HW + seg * 8;
            const uint32_t src = SM_XOWN + oc0 * 128 + ((seg ^ (oc0 & 7)) << 4);
            bar_sync(6, 128 + 256);
#pragma unroll
            for (int i = 0; i < 4; i++) *reinterpret_cast<uint4*>(dst + (size_t)i * 32 * HW * HW) = lds128(src + i * 4096);
            if (tid == 256) { TL(20); TLG(21); }
        }
    } else if (warp < 4) {
        const int wq = warp;
        bar_sync(7, 160);

        const uint32_t xbase = SM_XOWN + ((lane >> 4) * 8 + (lane & 7)) * 128 + (((2 * wq + ((lane >> 3) & 1)) ^ (lane & 7)) << 4);
        float d[64];
#pragma unroll
        for (int i = 0; i < 64; i++) d[i] = 0.f;
#pragma unroll 1
        for (int conv = 0; conv < 2; conv++) {
            fence_acc(d);
            mma_stages<0>(d, conv, tid, gs);
            if (conv == 0) {
                asm volatile("wgmma.fence.sync.aligned;" ::: "memory");
                wgmma128<(SM_ONES >> 4) | (8u << 16), (SM_EMB >> 4), 0, 8>(d);
                asm volatile("wgmma.commit_group.sync.aligned;" ::: "memory");
            }
            asm volatile("wgmma.wait_group.sync.aligned 0;" ::: "memory");
            fence_acc(d);
            if (tid == 0) TL(10 + conv * 8);
            uint32_t hp[32];
#pragma unroll
            for (int i = 0; i < 32; i++) hp[i] = pack_bf(d[2 * i], d[2 * i + 1]);
            if (conv == 1) {
#pragma unroll
                for (int kc = 0; kc < 8; kc++) stsm4t(xbase + kc * 2048, hp[4 * kc], hp[4 * kc + 1], hp[4 * kc + 2], hp[4 * kc + 3]);
                bar_arrive(6, 128 + 256);
                break;
            }
#pragma unroll
            for (int g = 0; g < 4; g++) {
                float c[4] = {0.f, 0.f, 0.f, 0.f};
#pragma unroll
                for (int i = 0; i < 4; i++) stat_mma(c, hp[8 * g + 2 * i], hp[8 * g + 2 * i + 1]);
                stat_store(c, SM_RED + (g * 4 + wq) * 48, lane);
            }
            bar_sync(2, 128);
            if (wq == 0) stat_publish(SM_RED, &gs->acc2[b * LS], lane, true);
            if (tid == 0) TL(11);
            const uint32_t hbase = SM_ACT + (lane >> 4) * CH_PITCH + (2 + wq * 16 + (lane & 15)) * 16;
#pragma unroll
            for (int kc = 0; kc < 8; kc++) stsm4(hbase + kc * 2 * CH_PITCH, hp[4 * kc], hp[4 * kc + 1], hp[4 * kc + 2], hp[4 * kc + 3]);
            __syncwarp();
            if (lane == 0) mbar_arrive(BAR(BAR_HW));
            if (lane < LAG) mbar_arrive(BAR(BAR_WEMPTY + (NSTAGE - LAG) % NS) + 8 * lane);
            if (has_outer) {
                uint4* outbox = gs->box + (cta + ((r & 1) ? 1 : -1)) * 1024 + tid;
#pragma unroll
                for (int kc = 0; kc < 8; kc++) outbox[kc * 128] = make_uint4(~hp[4 * kc], ~hp[4 * kc + 1], ~hp[4 * kc + 2], ~hp[4 * kc + 3]);
            }
            if (tid == 0) TL(12);
#pragma unroll
            for (int kc = 0; kc < 8; kc++) {
                uint32_t p[4];
                ldsm4t(p, xbase + kc * 2048);
#pragma unroll
                for (int i = 0; i < 4; i++) { d[8 * kc + 2 * i] = bf_lo(p[i]); d[8 * kc + 2 * i + 1] = bf_hi(p[i]); }
            }
            fence_async_smem();
            __syncwarp();
            if (lane == 0) mbar_arrive(BAR(BAR_XFREE));
        }
        {
        }
    } else if (warp < 6) {
        if (warp == 5) {
            bar_sync(5, 64);
            if (has_outer && elect_one()) {
                mbar_expect(BAR(BAR_X + 4), 16384);
#pragma unroll
                for (int i = 0; i < 4; i++) tma_x(SM_XOUT + i * 4096, &xmap, r + ((r & 1) ? 1 : -1), b * C + i * 32, BAR(BAR_X + 4));
            }
            __syncwarp();
            asm volatile("barrier.cluster.wait.acquire.aligned;" ::: "memory");
            const uint32_t peer = (r & 1) ^ 1;
            const uint32_t self0 = mapa(0, r & 1), peer0 = mapa(0, peer);
#pragma unroll 1
            for (int conv = 0; conv < 2; conv++) {
#pragma unroll 1
                for (int kc = 0; kc < 8; kc++) {
                    mbar_wait(BAR(BAR_FULL) + 8 * kc, conv);
                    if (elect_one())
                        asm volatile("cp.async.bulk.shared::cluster.shared::cta.mbarrier::complete_tx::bytes [%0], [%1], %2, [%3];"
                                     ::"r"(peer0 + SM_ACT + ROW_BYTES + kc * KC_BYTES), "r"(self0 + SM_ACT + kc * KC_BYTES), "r"(KC_BYTES),
                                       "r"(peer0 + BAR(BAR_FULL + 8) + 8 * kc) : "memory");
                }
                if (lane == 0) TL(86 + conv);
#pragma unroll 1
                for (int kc = 0; kc < 8; kc++) mbar_wait(BAR(BAR_FULL + 8) + 8 * kc, conv);
                if (lane == 0)
                    asm volatile("mbarrier.arrive.release.cluster.shared::cluster.b64 _, [%0];" ::"r"(peer0 + (conv ? BAR(BAR_ACK) : BAR(BAR_EMB))) : "memory");
            }
            mbar_wait(BAR(BAR_ACK), 0);
        } else {
            mbar_wait(BAR(BAR_STATS), 0);
            unsigned it = 0;
            while (ld_relaxed(&gs->wcnt[(2 * NB + b) * LS]) < (unsigned)NXTRA && ++it < SPIN_LIMIT) __nanosleep(100);
            fence_acquire();
            float ev[4] = {0.f, 0.f, 0.f, 0.f};
#pragma unroll
            for (int j = 0; j < NXTRA; j++) {
                const uint4 ef = ld_relaxed_v4(&gs->emb[(j * NB + b) * C + lane * 4]);
                ev[0] += __uint_as_float(ef.x); ev[1] += __uint_as_float(ef.y); ev[2] += __uint_as_float(ef.z); ev[3] += __uint_as_float(ef.w);
            }
#pragma unroll
            for (int i = 0; i < 4; i++) {
                const float hi = bf_lo(pack_bf(ev[i], 0.f));
                sts128(SM_EMB + (lane * 4 + i) * 16, make_uint4(pack_bf(hi, ev[i] - hi), 0, 0, 0));
            }
            fence_async_smem();
            __syncwarp();
            if (lane == 0) { mbar_arrive(BAR(BAR_EMB)); TL(19); }
        }
    } else if (warp == 6) {
        bar_sync(0, 96);
        const uint32_t ebytes = STAGE_BYTES + ((lane >> 3) == 1 ? KC_BYTES : 0);
        if (lane < NSTAGE) mbar_expect(BAR(BAR_FULL) + 8 * lane, ebytes);
        const int swap = (r & 1) ? 0 : 8 * STAGE_BYTES;
        unsigned it = 0;
        {
            int g = 0;
#pragma unroll 1
            while (g < NS) {
                unsigned ready = __ballot_sync(0xffffffffu, ld_relaxed(&gs->wcnt[b * LS + (lane & 7)]) >= 16u) >> g;
                if (++it > SPIN_LIMIT) ready = ~0u;
                if (!(ready & 1)) continue;
                fence_acquire();
                fence_async_global();
                if (lane == 0) TL(g ? 3 : 6);
#pragma unroll 1
                for (; (ready & 1) && g < NS; g++, ready >>= 1)
                    if (elect_one())
                        bulk_g2s(S0 + SM_W + g * STAGE_BYTES, gs->wt + g * STAGE_BYTES + (g >= 8 ? swap : 0), STAGE_BYTES, S0 + BAR(BAR_FULL) + 8 * g);
            }
        }
#pragma unroll 1
        for (int q = 3; q < 12; q++) {
            const int conv = q >= 6, qs = conv ? q - 6 : q, sl = q % 3;
            const unsigned char* wsrc = gs->wt + q * 4 * STAGE_BYTES + (qs < 2 ? 0 : (qs < 4 ? swap : -swap));
            const uint32_t par = (q / 3 - 1) & 1;
            if (q == 6) {
                it = 0;
                while (ld_relaxed(&gs->wcnt[(NB + b) * LS]) < (unsigned)NCTA && ++it < SPIN_LIMIT) {}
                fence_acquire();
                fence_async_global();
                if (lane == 0) { mbar_arrive(BAR(BAR_EMB)); TL(2); }
            }
#pragma unroll
            for (int i = 0; i < 4; i++) {
                mbar_wait(BAR(BAR_WEMPTY + i) + 32 * sl, par);
                if (i == 0 && (q == 6 || q == 9)) {
                    if ((lane >= NS) == (q == 9) && lane < NSTAGE) mbar_expect(BAR(BAR_FULL) + 8 * lane, ebytes);
                    __syncwarp();
                }
                if (elect_one())
                    bulk_g2s(S0 + SM_W + (sl * 4 + i) * STAGE_BYTES, wsrc + i * STAGE_BYTES, STAGE_BYTES, S0 + BAR(BAR_FULL + i) + 32 * qs);
            }
        }
    } else {
        const uint2 ga1 = __ldg(reinterpret_cast<const uint2*>(g1) + lane), bt1 = __ldg(reinterpret_cast<const uint2*>(be1) + lane);
        const uint2 ga2 = __ldg(reinterpret_cast<const uint2*>(g2) + lane), bt2 = __ldg(reinterpret_cast<const uint2*>(be2) + lane);
        if (lane < 8) sts128(SM_GST + lane * 16, make_uint4(0, 0, 0, 0));
        sts128f(SM_COEF + lane * 32, make_float4(0.5f * bf_lo(ga1.x), 0.5f * bf_hi(ga1.x), 0.5f * bf_lo(bt1.x), 0.5f * bf_hi(bt1.x)));
        sts128f(SM_COEF + lane * 32 + 16, make_float4(0.5f * bf_lo(ga1.y), 0.5f * bf_hi(ga1.y), 0.5f * bf_lo(bt1.y), 0.5f * bf_hi(bt1.y)));
        sts128f(SM_COEF + 1024 + lane * 32, make_float4(0.5f * bf_lo(ga2.x), 0.5f * bf_hi(ga2.x), 0.5f * bf_lo(bt2.x), 0.5f * bf_hi(bt2.x)));
        sts128f(SM_COEF + 1024 + lane * 32 + 16, make_float4(0.5f * bf_lo(ga2.y), 0.5f * bf_hi(ga2.y), 0.5f * bf_lo(bt2.y), 0.5f * bf_hi(bt2.y)));
        bar_arrive(4, 256 + 64 + 128);
        bar_sync(0, 96);
#pragma unroll 1
        for (int conv = 0; conv < 2; conv++) {
            if (conv == 1) {
                mbar_wait(BAR(BAR_HW), 0);
                const unsigned c1 = clock32();
                while (clock32() - c1 < PD2) {}
            } else {
                while (clock32() - clk0 < PD) {}
            }
            const float* asrc = conv ? &gs->acc2[b * LS + (lane & 3) * 4] : &gs->acc1[b * 4 * LS + (lane & 3) * GS1];
            unsigned it = 0;
            uint4 fq[NPOLL];
#pragma unroll
            for (int i = 0; i < NPOLL; i++) {
                fq[i] = ld_relaxed_v4(asrc);
                if (i + 1 < NPOLL) { const unsigned c1 = clock32(); while (clock32() - c1 < 450 / NPOLL) {} }
            }
            bool all = false;
#pragma unroll 1
            while (!all) {
#pragma unroll
                for (int i = 0; i < NPOLL; i++) {
                    const uint4 f = fq[i];
                    const bool ok = ((f.x == 0x42800000u) & (f.w == 0x42800000u)) || it > SPIN_LIMIT;
                    if (ok && lane < 4) {
                        const float inv_n = 1.0f / (32.0f * HW * HW);
                        const float mean = __uint_as_float(f.y) * inv_n;
                        const float rs = rsqrtf(fmaxf(fmaf(-mean, mean, __uint_as_float(f.z) * inv_n), 0.f) + 1e-5f);
                        asm volatile("st.shared.v2.f32 [%0], {%1,%2};" ::"r"(S0 + SM_GST + conv * 32 + lane * 8), "f"(rs == 0.f ? 1e-38f : rs), "f"(mean * rs) : "memory");
                    }
                    if (__all_sync(0xffffffffu, ok)) { all = true; break; }
                    fq[i] = ld_relaxed_v4(asrc);
                }
                it++;
            }
            if (lane == 0) { mbar_arrive(BAR(BAR_STATS)); TL(7 + conv * 8); }
        }
        mbar_wait(BAR(BAR_XFREE), 0);
        if (has_outer && elect_one()) {
            mbar_expect(BAR(BAR_X + 4), 16384);
            bulk_g2s(S0 + SM_XOWN, gs->box + cta * 1024, 16384, S0 + BAR(BAR_X + 4));
        }
        if (r == 0) {
            if (lane < 16) gs->acc1[b * 4 * LS + (lane >> 2) * GS1 + (lane & 3)] = 0.f;
            if (lane < 24) gs->wcnt[((lane >> 3) * NB + b) * LS + (lane & 7)] = 0;
        }
    }
}

}

extern "C" void kernel_launch(void* const* d_in, const int* in_sizes, int n_in, void* d_out, int out_size) {
    (void)in_sizes; (void)n_in; (void)out_size;
    typedef CUresult (*EncodeFn)(CUtensorMap*, CUtensorMapDataType, cuuint32_t, void*, const cuuint64_t*, const cuuint64_t*,
                                 const cuuint32_t*, const cuuint32_t*, CUtensorMapInterleave, CUtensorMapSwizzle,
                                 CUtensorMapL2promotion, CUtensorMapFloatOOBfill);
    static Scratch* gs = nullptr;
    static EncodeFn encode = nullptr;
    if (!gs) {
        cudaFuncSetAttribute(resblock_kernel, cudaFuncAttributeMaxDynamicSharedMemorySize, SM_TOTAL);
        cudaGetSymbolAddress((void**)&gs, g_scratch);
        cudaDriverEntryPointQueryResult qr;
        cudaGetDriverEntryPoint("cuTensorMapEncodeTiled", (void**)&encode, cudaEnableDefault, &qr);
    }
    CUtensorMap xmap;
    const cuuint64_t dims[3] = {HW, HW, NB * C}, strides[2] = {HW * 2, HW * HW * 2};
    const cuuint32_t box[3] = {HW, 1, 32}, es[3] = {1, 1, 1};
    encode(&xmap, CU_TENSOR_MAP_DATA_TYPE_BFLOAT16, 3, d_in[0], dims, strides, box, es, CU_TENSOR_MAP_INTERLEAVE_NONE,
           CU_TENSOR_MAP_SWIZZLE_128B, CU_TENSOR_MAP_L2_PROMOTION_NONE, CU_TENSOR_MAP_FLOAT_OOB_FILL_NONE);
    resblock_kernel<<<NCTA + NXTRA, NTHREADS, SM_TOTAL>>>(
        (const __nv_bfloat16*)d_in[4], (const __nv_bfloat16*)d_in[0], (const __nv_bfloat16*)d_in[1],
        (const __nv_bfloat16*)d_in[2], (const __nv_bfloat16*)d_in[3], (const __nv_bfloat16*)d_in[5],
        (const __nv_bfloat16*)d_in[6], (const __nv_bfloat16*)d_in[7], (const __nv_bfloat16*)d_in[8],
        (__nv_bfloat16*)d_out, gs, xmap);
}
```

```cpp
#include <cuda_runtime.h>
#include <cuda.h>
#include <cuda_bf16.h>
#include <stdint.h>

namespace {

constexpr int C = 128, HW = 64, NB = 2, E = 768;
constexpr int NCTA = NB * HW;
constexpr int NXTRA = 4;
constexpr int NTHREADS = 16 * 32;
constexpr int CH_PITCH = 66 * 16;
constexpr int ROW_BYTES = 16 * CH_PITCH;
constexpr int STEP_BYTES = 4096;
constexpr int STAGE_BYTES = 3 * STEP_BYTES;
constexpr int NSTAGE = 24;
constexpr int KC_BYTES = 2 * CH_PITCH;
constexpr int NS = 12;
constexpr int LAG = 1;
#define XDELAY 400
#define HDELAY 600
#define SEQ 0
#define MMA0_WAIT mbar_try
#define SPINPAUSE
#define NPOLL 1
#define PD2 0
#define ODELAY 100
#define NLDG 2
#define PSTAG -1
#define PDELAY0 400
#define PDELAY 60
#define RB 1
#define XSTAG2 400
#define XSTAG 800
#define HSEND 0
#define SDELAY 1200
#define OAFTER 0
#define W2DELAY 3000

constexpr uint32_t SMEM_BASE = 0x400;
constexpr uint32_t SM_XOWN = SMEM_BASE;
constexpr uint32_t SM_ACT = SM_XOWN + 16384 + 512;
constexpr uint32_t SM_XOUT = SM_ACT + 2 * ROW_BYTES + 512;
static_assert(SM_XOUT % 1024 == 0, "swizzle atom alignment");
constexpr uint32_t SM_W = SM_ACT + 3 * ROW_BYTES + 128;
__host__ __device__ constexpr uint32_t slot_addr(int slot) { return SM_W + slot * STAGE_BYTES; }
constexpr uint32_t SM_COEF = SM_W + NS * STAGE_BYTES;
constexpr uint32_t SM_GST = SM_COEF + 2048;
constexpr uint32_t SM_EMB = SM_GST + 128;
constexpr uint32_t SM_ONES = SM_EMB + 2048;
constexpr uint32_t SM_RED = SM_ONES + 256;
constexpr uint32_t SM_BNC = SM_RED + 1536;
constexpr uint32_t SM_BAR = SM_BNC + 2 * 2304;
constexpr int BAR_FULL = 0, BAR_WEMPTY = NSTAGE, BAR_HW = BAR_WEMPTY + NS, BAR_XFREE = BAR_HW + 1, BAR_STATS = BAR_XFREE + 1,
              BAR_EMB = BAR_STATS + 1, BAR_ACK = BAR_EMB + 1, BAR_X = BAR_ACK + 1  , NBAR = BAR_X + 5;
constexpr int SM_TOTAL = SM_BAR + NBAR * 8 - SMEM_BASE;
static_assert(SM_TOTAL <= 232448, "smem");
static_assert(NBAR <= 96, "barrier init");
__host__ __device__ constexpr uint32_t BAR(int i) { return SM_BAR + 8 * i; }
__host__ __device__ constexpr int ky_of(int kyo) { return kyo == 0 ? 1 : (kyo == 1 ? 0 : 2); }

constexpr unsigned SPIN_LIMIT = 1u << 16;

#define LS 1056
#define GS1 4
#define PD 0
struct Scratch {
    float acc1[NB * 4 * LS];
    float acc2[NB * LS];
    unsigned wcnt[3 * NB * LS];
    float emb[NXTRA * NB * C];
    unsigned char wt[2 * NSTAGE * STAGE_BYTES];
    uint4 box[NCTA * 1024];
};
__device__ __align__(1024) Scratch g_scratch;
#define TL(i) do {} while (0)
#define TLG(i) do {} while (0)

__device__ __forceinline__ unsigned clock32() { unsigned c; asm volatile("mov.u32 %0, %%clock;" : "=r"(c)); return c; }
__device__ __forceinline__ uint32_t mapa(uint32_t a, uint32_t rank) {
    uint32_t d;
    asm("mapa.shared::cluster.u32 %0, %1, %2;" : "=r"(d) : "r"(a), "r"(rank));
    return d;
}
#define S0 mapa(0, blockIdx.x & 1)
__device__ __forceinline__ void mbar_init(uint32_t bar, int cnt) {
    asm volatile("mbarrier.init.shared::cta.b64 [%0], %1;" ::"r"(bar + S0), "r"(cnt) : "memory");
}
__device__ __forceinline__ void mbar_arrive(uint32_t bar) {
    asm volatile("mbarrier.arrive.shared::cta.b64 _, [%0];" ::"r"(bar + S0) : "memory");
}
__device__ __forceinline__ void mbar_expect(uint32_t bar, uint32_t bytes) {
    asm volatile("mbarrier.arrive.expect_tx.shared::cta.b64 _, [%0], %1;" ::"r"(bar + S0), "r"(bytes) : "memory");
}
__device__ __forceinline__ bool mbar_try(uint32_t bar, uint32_t par) {
    uint32_t ok;
    asm volatile("{\n.reg .pred p;\nmbarrier.try_wait.parity.shared::cta.b64 p, [%1], %2;\nselp.u32 %0, 1, 0, p;\n}"
                 : "=r"(ok) : "r"(bar + S0), "r"(par) : "memory");
    return ok;
}
__device__ __forceinline__ bool mbar_test(uint32_t bar, uint32_t par) {
    uint32_t ok;
    asm volatile("{\n.reg .pred p;\nmbarrier.test_wait.parity.shared::cta.b64 p, [%1], %2;\nselp.u32 %0, 1, 0, p;\n}"
                 : "=r"(ok) : "r"(bar + S0), "r"(par) : "memory");
    return ok;
}
__device__ __forceinline__ void mbar_wait(uint32_t bar, uint32_t par) {
    unsigned it = 0;
#pragma unroll 1
    while (!mbar_try(bar, par) && ++it < SPIN_LIMIT) {}
}
__device__ __forceinline__ bool elect_one() {
    uint32_t p;
    asm volatile("{\n.reg .pred p;\nelect.sync _|p, 0xffffffff;\nselp.u32 %0, 1, 0, p;\n}" : "=r"(p));
    return p;
}
__device__ __forceinline__ void fence_async_smem() { asm volatile("fence.proxy.async.shared::cta;" ::: "memory"); }
__device__ __forceinline__ void fence_async_global() { asm volatile("fence.proxy.async.global;" ::: "memory"); }
__device__ __forceinline__ void fence_acquire() { asm volatile("fence.acquire.gpu;" ::: "memory"); }
__device__ __forceinline__ void bar_sync(int id, int n) { asm volatile("bar.sync %0, %1;" ::"r"(id), "r"(n) : "memory"); }
__device__ __forceinline__ void bar_arrive(int id, int n) { asm volatile("bar.arrive %0, %1;" ::"r"(id), "r"(n) : "memory"); }
__device__ __forceinline__ void bulk_g2s(uint32_t dst, const void* src, uint32_t bytes, uint32_t bar) {
    asm volatile("cp.async.bulk.shared::cluster.global.mbarrier::complete_tx::bytes [%0], [%1], %2, [%3];"
                 ::"r"(dst), "l"(src), "r"(bytes), "r"(bar) : "memory");
}
__device__ __forceinline__ void tma_x(uint32_t dst, const CUtensorMap* tm, int row, int ch, uint32_t bar) {
    asm volatile("cp.async.bulk.tensor.3d.shared::cluster.global.mbarrier::complete_tx::bytes [%0], [%1, {%2, %3, %4}], [%5];"
                 ::"r"(dst + S0), "l"(tm), "r"(0), "r"(row), "r"(ch), "r"(bar + S0) : "memory");
}
__device__ __forceinline__ uint4 ld_relaxed_v4(const void* p) {
    uint4 v;
    asm volatile("ld.relaxed.gpu.global.v4.u32 {%0,%1,%2,%3}, [%4];" : "=r"(v.x), "=r"(v.y), "=r"(v.z), "=r"(v.w) : "l"(p) : "memory");
    return v;
}
__device__ __forceinline__ unsigned ld_relaxed(const void* p) {
    unsigned v;
    asm volatile("ld.relaxed.gpu.global.u32 %0, [%1];" : "=r"(v) : "l"(p) : "memory");
    return v;
}
__device__ __forceinline__ void red_add4(float* p, float a, float b, float c, float d) {
    asm volatile("red.relaxed.gpu.global.add.v4.f32 [%0], {%1,%2,%3,%4};" ::"l"(p), "f"(a), "f"(b), "f"(c), "f"(d) : "memory");
}
__device__ __forceinline__ void sts128(uint32_t a, uint4 v) {
    asm volatile("st.shared.v4.u32 [%0], {%1,%2,%3,%4};" ::"r"(a + S0), "r"(v.x), "r"(v.y), "r"(v.z), "r"(v.w) : "memory");
}
__device__ __forceinline__ void sts128f(uint32_t a, float4 v) {
    asm volatile("st.shared.v4.f32 [%0], {%1,%2,%3,%4};" ::"r"(a + S0), "f"(v.x), "f"(v.y), "f"(v.z), "f"(v.w) : "memory");
}
__device__ __forceinline__ void sts32f(uint32_t a, float v) { asm volatile("st.shared.f32 [%0], %1;" ::"r"(a + S0), "f"(v) : "memory"); }
__device__ __forceinline__ uint4 lds128(uint32_t a) {
    uint4 v;
    asm volatile("ld.shared.v4.u32 {%0,%1,%2,%3}, [%4];" : "=r"(v.x), "=r"(v.y), "=r"(v.z), "=r"(v.w) : "r"(a + S0) : "memory");
    return v;
}
__device__ __forceinline__ float4 lds128f(uint32_t a) {
    float4 v;
    asm volatile("ld.shared.v4.f32 {%0,%1,%2,%3}, [%4];" : "=f"(v.x), "=f"(v.y), "=f"(v.z), "=f"(v.w) : "r"(a + S0) : "memory");
    return v;
}
__device__ __forceinline__ float2 lds64f(uint32_t a) {
    float2 v;
    asm volatile("ld.shared.v2.f32 {%0,%1}, [%2];" : "=f"(v.x), "=f"(v.y) : "r"(a + S0) : "memory");
    return v;
}
__device__ __forceinline__ float bf_lo(uint32_t u) { return __uint_as_float(u << 16); }
__device__ __forceinline__ float bf_hi(uint32_t u) { return __uint_as_float(u & 0xffff0000u); }
__device__ __forceinline__ uint32_t pack_bf(float lo, float hi) {
    uint32_t r;
    asm("cvt.rn.bf16x2.f32 %0, %1, %2;" : "=r"(r) : "f"(hi), "f"(lo));
    return r;
}
__device__ __forceinline__ float tanh_fast(float x) {
    float r;
    asm("tanh.approx.f32 %0, %1;" : "=f"(r) : "f"(x));
    return r;
}
__device__ __forceinline__ float silu_half(float h) { return fmaf(h, tanh_fast(h), h); }
__device__ __forceinline__ void ldsm4(uint32_t (&u)[4], uint32_t a) {
    asm volatile("ldmatrix.sync.aligned.m8n8.x4.shared.b16 {%0,%1,%2,%3}, [%4];"
                 : "=r"(u[0]), "=r"(u[1]), "=r"(u[2]), "=r"(u[3]) : "r"(a + S0) : "memory");
}
__device__ __forceinline__ void ldsm4t(uint32_t (&u)[4], uint32_t a) {
    asm volatile("ldmatrix.sync.aligned.m8n8.x4.trans.shared.b16 {%0,%1,%2,%3}, [%4];"
                 : "=r"(u[0]), "=r"(u[1]), "=r"(u[2]), "=r"(u[3]) : "r"(a + S0) : "memory");
}
__device__ __forceinline__ void stsm4(uint32_t a, uint32_t p0, uint32_t p1, uint32_t p2, uint32_t p3) {
    asm volatile("stmatrix.sync.aligned.m8n8.x4.shared.b16 [%0], {%1,%2,%3,%4};" ::"r"(a + S0), "r"(p0), "r"(p1), "r"(p2), "r"(p3) : "memory");
}
__device__ __forceinline__ void stsm4t(uint32_t a, uint32_t p0, uint32_t p1, uint32_t p2, uint32_t p3) {
    asm volatile("stmatrix.sync.aligned.m8n8.x4.trans.shared.b16 [%0], {%1,%2,%3,%4};" ::"r"(a + S0), "r"(p0), "r"(p1), "r"(p2), "r"(p3) : "memory");
}

#define R8(o) "+f"(d[o]), "+f"(d[o + 1]), "+f"(d[o + 2]), "+f"(d[o + 3]), "+f"(d[o + 4]), "+f"(d[o + 5]), "+f"(d[o + 6]), "+f"(d[o + 7])
template <uint32_t ALO, uint32_t BLO, uint64_t AHI = 8, uint64_t BHI = 48>
__device__ __forceinline__ void wgmma128(float (&d)[64]) {
    asm volatile(
        "wgmma.mma_async.sync.aligned.m64n128k16.f32.bf16.bf16 "
        "{%0,%1,%2,%3,%4,%5,%6,%7,%8,%9,%10,%11,%12,%13,%14,%15,%16,%17,%18,%19,%20,%21,%22,%23,%24,%25,%26,%27,%28,%29,%30,%31,"
        "%32,%33,%34,%35,%36,%37,%38,%39,%40,%41,%42,%43,%44,%45,%46,%47,%48,%49,%50,%51,%52,%53,%54,%55,%56,%57,%58,%59,%60,%61,%62,%63},"
        " %64, %65, 1, 1, 1, 0, 0;"
        : R8(0), R8(8), R8(16), R8(24), R8(32), R8(40), R8(48), R8(56)
        : "l"((AHI << 32) | ALO), "l"((BHI << 32) | BLO));
}
template <int S>
__device__ __forceinline__ void mma_stages(float (&d)[64], int conv, int tid, Scratch* gs) {
    constexpr uint32_t A = ((SM_ACT + S * 2 * CH_PITCH + 16) >> 4) | ((CH_PITCH >> 4) << 16);
    constexpr uint32_t B = (slot_addr(S % NS) >> 4) | (8u << 16);
    if (S == 0) {
        unsigned it = 0;
#pragma unroll 1
        while (!MMA0_WAIT(BAR(BAR_FULL), conv) && ++it < SPIN_LIMIT) {}
    }
    bool next_ok = true;
    constexpr uint32_t NEXT = S + 1 < NSTAGE ? BAR(BAR_FULL + S + 1) : BAR(BAR_EMB);
    const int npar = S + 1 < NSTAGE ? conv : 0;
    next_ok = mbar_test(NEXT, npar);
    if (S == 0 && tid == 0) TL(32 + conv * 24);
    asm volatile("wgmma.fence.sync.aligned;" ::: "memory");
    wgmma128<A, B>(d);
    wgmma128<A + 1, B + 16>(d);
    wgmma128<A + 2, B + 32>(d);
    asm volatile("wgmma.commit_group.sync.aligned;" ::: "memory");
    if (S >= LAG) {
        asm volatile("wgmma.wait_group.sync.aligned %0;" ::"n"(LAG) : "memory");
        if ((tid & 31) == 0) mbar_arrive(BAR(BAR_WEMPTY + (S + NS - LAG) % NS));
    }
    if (!next_ok) mbar_wait(NEXT, npar);
    if constexpr (S + 1 < NSTAGE) mma_stages<S + 1>(d, conv, tid, gs);
}

__device__ __forceinline__ void weight_load(uint4 (&t)[5], const __nv_bfloat16* w, int cta, int lane) {
    const char* base = reinterpret_cast<const char*>(w) + ((cta & 15) * 8 * C + (cta >> 4) * 16) * 18;
#pragma unroll
    for (int k = 0; k < 5; k++) {
        const int i = lane + 32 * k, row = (i * 57) >> 10;
        if (k < 4 || lane < 16) t[k] = __ldg(reinterpret_cast<const uint4*>(base + row * (C * 18 - 288) + i * 16));
    }
}
__device__ __forceinline__ void weight_block(uint32_t bounce, unsigned char* wt, int cta, int lane, bool readback, Scratch* gs) {
    unsigned char* dst = wt + (cta >> 4) * STAGE_BYTES + (cta & 15) * 768;
    if (lane < 16) {
        uint32_t v[36];
#pragma unroll
        for (int i = 0; i < 9; i++) {
            const uint4 q = lds128(bounce + (lane & 7) * 288 + (lane >> 3) * 144 + i * 16);
            v[4 * i] = q.x; v[4 * i + 1] = q.y; v[4 * i + 2] = q.z; v[4 * i + 3] = q.w;
        }
#pragma unroll
        for (int kyo = 0; kyo < 3; kyo++) {
#pragma unroll
            for (int kx = 0; kx < 3; kx++) {
                const int tap = ky_of(kyo) * 3 + kx;
                uint32_t o[4];
#pragma unroll
                for (int m = 0; m < 4; m++) {
                    const int i0 = 18 * m + tap, i1 = i0 + 9;
                    const uint32_t sel = ((i0 & 1) ? 0x32u : 0x10u) | ((i1 & 1) ? 0x7600u : 0x5400u);
                    o[m] = __byte_perm(v[i0 >> 1], v[i1 >> 1], sel);
                }
                *reinterpret_cast<uint4*>(dst + kyo * 8 * STAGE_BYTES + kx * 256 + lane * 16) = make_uint4(o[0], o[1], o[2], o[3]);
            }
        }
    }
    if (readback) {
        __syncwarp();
        unsigned acc = 0;
        if (lane < 24) {
#pragma unroll
            for (int i = 0; i < 3; i++) acc |= ld_relaxed(dst + i * 8 * STAGE_BYTES + lane * 32);
        }
        asm volatile("{\n.reg .pred p;\nsetp.eq.u32 p, %0, 0x9e3779b9;\n@p st.shared.u32 [%1], %0;\n}" ::"r"(acc), "r"(bounce + S0) : "memory");
    }
}
__device__ __forceinline__ uint32_t act2(uint32_t u, const float4& cf) {
    return pack_bf(silu_half(fmaf(bf_lo(u), cf.x, cf.z)), silu_half(fmaf(bf_hi(u), cf.y, cf.w)));
}
__device__ __forceinline__ void norm_unit(uint32_t (&u)[4], const float4& ca, const float4& cb) {
    u[0] = act2(u[0], ca); u[1] = act2(u[1], ca); u[2] = act2(u[2], cb); u[3] = act2(u[3], cb);
}
__device__ __forceinline__ void read_stats(uint32_t gst, float (&g)[8]) {
    asm volatile("ld.volatile.shared.v4.f32 {%0,%1,%2,%3}, [%4];" : "=f"(g[0]), "=f"(g[1]), "=f"(g[2]), "=f"(g[3]) : "r"(gst + S0) : "memory");
    asm volatile("ld.volatile.shared.v4.f32 {%0,%1,%2,%3}, [%4];" : "=f"(g[4]), "=f"(g[5]), "=f"(g[6]), "=f"(g[7]) : "r"(gst + 16 + S0) : "memory");
}
template <int T>
__device__ __forceinline__ void group_coefs(uint32_t gst, float (&g)[8], float4 (&cf)[8]) {
    unsigned it = 0;
    if (!__all_sync(0xffffffffu, g[2 * T] != 0.f)) {
        float rs0;
#pragma unroll 1
        do {
            SPINPAUSE;
            asm volatile("ld.volatile.shared.f32 %0, [%1];" : "=f"(rs0) : "r"(gst + 8 * T + S0) : "memory");
        } while (!__all_sync(0xffffffffu, rs0 != 0.f) && ++it < 8 * SPIN_LIMIT);
        read_stats(gst, g);
    }
    float4 &ca = cf[2 * T], &cb = cf[2 * T + 1];
    const float rs = g[2 * T], mr = g[2 * T + 1];
    ca.z = fmaf(-mr, ca.x, ca.z); ca.w = fmaf(-mr, ca.y, ca.w); ca.x *= rs; ca.y *= rs;
    cb.z = fmaf(-mr, cb.x, cb.z); cb.w = fmaf(-mr, cb.y, cb.w); cb.x *= rs; cb.y *= rs;
}
template <int FIRST, int N>
__device__ __forceinline__ void norm_block(uint32_t (&u)[4][4], float4 (&cf)[8], uint32_t act, uint32_t mask, uint32_t fbar, int lane) {
#pragma unroll
    for (int t = FIRST; t < FIRST + N; t++) {
        norm_unit(u[t], cf[2 * t], cf[2 * t + 1]);
        stsm4(act + t * 2 * KC_BYTES, u[t][0] & mask, u[t][1] & mask, u[t][2] & mask, u[t][3] & mask);
    }
    fence_async_smem();
    __syncwarp();
    if (lane < N) mbar_arrive(fbar + 16 * (FIRST + lane));
}
__device__ __forceinline__ void publish(uint32_t bar, int lane) {
    fence_async_smem();
    __syncwarp();
    if (lane == 0) mbar_arrive(bar);
}
template <int T>
__device__ __forceinline__ void next_unit(uint32_t (&u)[4][4], float4 (&cf)[8], uint32_t gst, float (&g)[8], uint32_t act, uint32_t fbar, int lane) {
    const bool have = __all_sync(0xffffffffu, g[2 * T] != 0.f);
    if (!have) publish(fbar + 16 * (T - 1), lane);
    group_coefs<T>(gst, g, cf);
    norm_unit(u[T], cf[2 * T], cf[2 * T + 1]);
    if (have) publish(fbar + 16 * (T - 1), lane);
    stsm4(act + T * 2 * KC_BYTES, u[T][0], u[T][1], u[T][2], u[T][3]);
}
__device__ __forceinline__ void stat_mma(float (&c)[4], uint32_t p, uint32_t q) {
    asm("mma.sync.aligned.m16n8k16.row.col.f32.bf16.bf16.f32 {%0,%1,%2,%3}, {%4,%5,%6,%5}, {%4,%6}, {%0,%1,%2,%3};"
        : "+f"(c[0]), "+f"(c[1]), "+f"(c[2]), "+f"(c[3]) : "r"(p), "r"(0x3f803f80u), "r"(q));
}
__device__ __forceinline__ void stat_store(const float (&c)[4], uint32_t dst, int lane) {
    const int g = lane >> 2, t = lane & 3;
    if (t == (g >> 1)) sts32f(dst + g * 4, (g & 1) ? c[1] : c[0]);
    if (g == 7) sts32f(dst + 32 + t * 4, c[2] + c[3]);
}
__device__ __forceinline__ float sum4(float4 v) { return (v.x + v.y) + (v.z + v.w); }
__device__ __forceinline__ void stat_publish(uint32_t src, float* acc, int lane, bool real) {
    const uint32_t a = src + (lane & 15) * 48;
    float q = sum4(lds128f(a)) + sum4(lds128f(a + 16)), sm = sum4(lds128f(a + 32));
    q += __shfl_xor_sync(0xffffffffu, q, 1); sm += __shfl_xor_sync(0xffffffffu, sm, 1);
    q += __shfl_xor_sync(0xffffffffu, q, 2); sm += __shfl_xor_sync(0xffffffffu, sm, 2);
    if (real && (lane & 19) == 0) red_add4(acc + lane, 1.f, sm, q, 1.f);
}
__device__ __forceinline__ void fence_acc(float (&d)[64]) {
#pragma unroll
    for (int i = 0; i < 64; i++) asm volatile("" : "+f"(d[i])::"memory");
}
__device__ __forceinline__ void ld_unit(uint32_t (&u)[4], const uint4* p) {
    asm volatile("ld.relaxed.gpu.global.v4.u32 {%0,%1,%2,%3}, [%4];" : "=r"(u[0]), "=r"(u[1]), "=r"(u[2]), "=r"(u[3]) : "l"(p) : "memory");
}

__device__ __noinline__ void side_jobs(const __nv_bfloat16* __restrict__ t_emb, const __nv_bfloat16* __restrict__ w_emb,
                                       const __nv_bfloat16* __restrict__ w2, Scratch* __restrict__ gs, unsigned clk0) {
    const int tid = threadIdx.x, warp = tid >> 5, lane = tid & 31, j = blockIdx.x;
    float tv = 0.f;
    if (lane < 24) tv = __bfloat162float(t_emb[(lane / 12) * E + j * 192 + warp * 12 + lane % 12]);
    if (tid == 0) {
        mbar_init(BAR(0), 1);
        mbar_expect(BAR(0), 192 * C * 2);
        fence_async_smem();
        while (clock32() - clk0 < SDELAY) {}
#pragma unroll
        for (int i = 0; i < 4; i++)
            asm volatile("cp.async.bulk.prefetch.L2.global [%0], 18432;" ::"l"(reinterpret_cast<const char*>(w2) + (j * 4 + i) * 18432) : "memory");
#pragma unroll
        for (int i = 0; i < 4; i++) bulk_g2s(S0 + SM_W + i * 12288, w_emb + (j * 192 + i * 48) * C, 12288, S0 + BAR(0));
    }
    if (j == 0 && tid < 32) gs->acc2[(tid >> 4) * LS + (tid & 15)] = 0.f;
    const float sv = silu_half(0.5f * tv);
    __syncthreads();
    mbar_wait(BAR(0), 0);
    float acc[8] = {0.f, 0.f, 0.f, 0.f, 0.f, 0.f, 0.f, 0.f};
#pragma unroll
    for (int i = 0; i < 12; i++) {
        const float2 wq = lds64f(SM_W + (warp * 12 + i) * 256 + lane * 8);
        const uint32_t wx = __float_as_uint(wq.x), wy = __float_as_uint(wq.y);
#pragma unroll
        for (int bb = 0; bb < 2; bb++) {
            const float sx = __shfl_sync(0xffffffffu, sv, bb * 12 + i);
            acc[4 * bb + 0] = fmaf(sx, bf_lo(wx), acc[4 * bb + 0]); acc[4 * bb + 1] = fmaf(sx, bf_hi(wx), acc[4 * bb + 1]);
            acc[4 * bb + 2] = fmaf(sx, bf_lo(wy), acc[4 * bb + 2]); acc[4 * bb + 3] = fmaf(sx, bf_hi(wy), acc[4 * bb + 3]);
        }
    }
    sts128f(SM_ACT + warp * 1024 + lane * 16, make_float4(acc[0], acc[1], acc[2], acc[3]));
    sts128f(SM_ACT + warp * 1024 + 512 + lane * 16, make_float4(acc[4], acc[5], acc[6], acc[7]));
    __syncthreads();
    if (tid < 128) {
        float2 sum = make_float2(0.f, 0.f);
#pragma unroll
        for (int w = 0; w < 16; w++) { const float2 p = lds64f(SM_ACT + w * 1024 + tid * 8); sum.x += p.x; sum.y += p.y; }
        *reinterpret_cast<float2*>(&gs->emb[j * NB * C + tid * 2]) = sum;
        bar_sync(1, 128);
        if (tid < 2) asm volatile("red.release.gpu.global.add.u32 [%0], 1;" ::"l"(&gs->wcnt[(2 * NB + tid) * LS]) : "memory");
    }
}

__global__ void __cluster_dims__(2, 1, 1) __launch_bounds__(NTHREADS, 1)
resblock_kernel(const __nv_bfloat16* __restrict__ w1, const __nv_bfloat16* __restrict__ x,
                const __nv_bfloat16* __restrict__ t_emb, const __nv_bfloat16* __restrict__ g1,
                const __nv_bfloat16* __restrict__ be1, const __nv_bfloat16* __restrict__ w_emb,
                const __nv_bfloat16* __restrict__ g2, const __nv_bfloat16* __restrict__ be2,
                const __nv_bfloat16* __restrict__ w2, __nv_bfloat16* __restrict__ out, Scratch* __restrict__ gs,
                const __grid_constant__ CUtensorMap xmap) {
    const unsigned clk0 = clock32();
    if (threadIdx.x == 480 && blockIdx.x >= NXTRA) TLG(1);
    const int tid = threadIdx.x, lane = tid & 31;
    const int cta = blockIdx.x - NXTRA, b = cta >> 6, r = cta & 63;
    uint4 v[5];
    if (tid < 32) weight_load(v, w1, cta & (NCTA - 1), lane);
    uint4 xv[8];
    const int wg4 = (tid >> 5) - 1;
    const bool early = tid >= 32 && wg4 < NLDG;
    if (early) {
        const char* src = reinterpret_cast<const char*>(x) + (uint32_t)((((b & 1) * C + wg4 * 32 + (lane >> 3)) * HW + r) * HW * 2 + (lane & 7) * 16);
        while (clock32() - clk0 < XDELAY + (wg4 >> 1) * XSTAG + (wg4 & 1) * XSTAG2) {}
#pragma unroll
        for (int i = 0; i < 8; i++) xv[i] = __ldg(reinterpret_cast<const uint4*>(src + i * (4 * HW * HW * 2)));
    }
    const int warp = __shfl_sync(0xffffffffu, tid >> 5, 0);
    if (cta < 0) { side_jobs(t_emb, w_emb, w2, gs, clk0); return; }

    if (warp != 4) asm volatile("barrier.cluster.arrive.relaxed.aligned;" ::: "memory");
    const bool has_outer = (r != 0) && (r != HW - 1);
    if (warp == 1 || warp == 2 || warp == 3 || warp == 5) {
        const int g = warp < 4 ? warp - 1 : 3;
        if (elect_one()) {
            if (g >= NLDG) asm volatile("prefetch.tensormap [%0];" ::"l"(&xmap) : "memory");
            mbar_init(BAR(BAR_X) + 8 * g, 1);
            if (g >= NLDG) mbar_expect(BAR(BAR_X) + 8 * g, 4096);
            fence_async_smem();
        }
        __syncwarp();
        bar_arrive(4, 256 + 64 + 128);
        if (g >= NLDG) {
            while (clock32() - clk0 < XDELAY + (g >> 1) * XSTAG + (g & 1) * XSTAG2) {}
            if (elect_one()) tma_x(SM_XOWN + g * 4096, &xmap, r, b * C + g * 32, BAR(BAR_X) + 8 * g);
            __syncwarp();
            mbar_wait(BAR(BAR_X) + 8 * g, 0);
#pragma unroll
            for (int k = 0; k < 8; k++) xv[k] = lds128(SM_XOWN + g * 4096 + k * 512 + lane * 16);
        }
        float c[8][4];
#pragma unroll
        for (int k = 0; k < 8; k++) {
            c[k][0] = c[k][1] = c[k][2] = c[k][3] = 0.f;
            stat_mma(c[k], xv[k].x, xv[k].y); stat_mma(c[k], xv[k].z, xv[k].w);
        }
#pragma unroll
        for (int i = 0; i < 4; i++) c[0][i] = ((c[0][i] + c[1][i]) + (c[2][i] + c[3][i])) + ((c[4][i] + c[5][i]) + (c[6][i] + c[7][i]));
        stat_store(c[0], SM_RED + g * 48, lane);
        __syncwarp();
        if (lane == 0) {
            const uint32_t a = SM_RED + g * 48;
            red_add4(&gs->acc1[b * 4 * LS + g * GS1], 1.f, sum4(lds128f(a + 32)), sum4(lds128f(a)) + sum4(lds128f(a + 16)), 1.f);
            TL(74 + g);
        }
        if (g < NLDG) {
#pragma unroll
            for (int i = 0; i < 8; i++)
                sts128(SM_XOWN + g * 4096 + i * 512 + (lane >> 3) * 128 + (((lane & 7) ^ ((lane >> 3) + 4 * (i & 1))) << 4), xv[i]);
            __syncwarp();
            if (lane == 0) mbar_arrive(BAR(BAR_X) + 8 * g);
        }
    }
    if (warp == 4) {
            if (elect_one()) {
#pragma unroll
                for (int i = 0; i < NSTAGE; i++) mbar_init(BAR(BAR_FULL + i), (i >> 3) == 1 ? 1 : 5);
#pragma unroll
                for (int i = 0; i < NS + 2; i++) mbar_init(BAR(BAR_WEMPTY + i), 4);
#pragma unroll
                for (int i = BAR_STATS; i < BAR_X; i++) mbar_init(BAR(i), i == BAR_EMB ? 3 : 1);
                mbar_init(BAR(BAR_X + 4), 1);
                asm volatile("fence.mbarrier_init.release.cluster;" ::: "memory");
            }
            __syncwarp();
            fence_async_smem();
            bar_arrive(0, 96);
            bar_arrive(5, 64);
            bar_arrive(4, 256 + 64 + 128);
            const uint4 z = make_uint4(0, 0, 0, 0);
#pragma unroll
            for (int i = 0; i < 2; i++) sts128(SM_ACT + (i * 16 + (lane >> 1)) * CH_PITCH + (lane & 1) * 16, z);
            if (lane < 4) sts128(SM_ACT + (2 + (lane >> 1)) * ROW_BYTES + (lane & 1) * 16, z);
            if (lane < 16) sts128(SM_ONES + lane * 16, make_uint4(lane < 8 ? 0x3f803f80u : 0u, 0, 0, 0));
            fence_async_smem();
            bar_arrive(7, 160);
            asm volatile("barrier.cluster.arrive.relaxed.aligned;" ::: "memory");
            if (lane == 0) TL(5);
            while (clock32() - clk0 < W2DELAY) {}
            weight_load(v, w2, cta, lane);
        }
    if (warp == 0 || warp == 4) {
        const int k = warp >> 2;
#pragma unroll
        for (int i = 0; i < 5; i++)
            if (i < 4 || lane < 16) sts128(SM_BNC + k * 2304 + (lane + 32 * i) * 16, v[i]);
        if (lane == 0) TL(k ? 14 : 81);
        __syncwarp();
        weight_block(SM_BNC + k * 2304, gs->wt + k * NSTAGE * STAGE_BYTES, cta, lane, true, gs);
        __syncwarp();
        if (lane == 0) TL(k ? 13 : 4);
        if (lane < 2) asm volatile("red.relaxed.gpu.global.add.u32 [%0], 1;" ::"l"(&gs->wcnt[(k * NB + lane) * LS + (k ? 0 : cta >> 4)]) : "memory");
    }

    if (warp >= 8) {
        const int nw = warp - 8;
        bar_sync(4, 256 + 64 + 128);
        const int par = nw >> 2, wq = nw & 3;
        const uint32_t act_off = SM_ACT + (par * 2 + (lane >> 4)) * CH_PITCH + (2 + wq * 16 + (lane & 15)) * 16;
        const uint32_t stg_off = (par * 16 + (lane >> 4) * 8 + (lane & 7)) * 128 + (((2 * wq + ((lane >> 3) & 1)) ^ (lane & 7)) << 4);
        const uint32_t cfa = SM_COEF + par * 128 + (lane & 3) * 16;
        const uint32_t fbar = BAR(BAR_FULL) + 8 * par;
        uint4* inbox = gs->box + cta * 1024 + nw * 32 + lane;
#pragma unroll 1
        for (int conv = 0; conv < 2; conv++) {
            uint32_t u[4][4], w[4][4];
            float4 cf[8];
            if (conv == 0) {
#pragma unroll
                for (int i = 0; i < 4; i++) { mbar_wait(BAR(BAR_X + i), 0); ldsm4t(u[i], SM_XOWN + stg_off + i * 4096); }
            } else {
                mbar_wait(BAR(BAR_HW), 0);
#pragma unroll
                for (int i = 0; i < 4; i++) ldsm4(u[i], act_off + i * 2 * KC_BYTES);
            }
#pragma unroll
            for (int i = 0; i < 8; i++) cf[i] = lds128f(cfa + conv * 1024 + (i >> 1) * 256 + (i & 1) * 64);
            const uint32_t gst = SM_GST + conv * 32;
            float gv[8];
            read_stats(gst, gv);
            group_coefs<0>(gst, gv, cf);
            if (tid == 256) TL(22 + conv * 4);
            if (par) { const unsigned c1 = clock32(); while (clock32() - c1 < PDELAY) {} }
            norm_block<0, 1>(u, cf, act_off, ~0u, fbar, lane);
            if (tid == 256) TL(8 + conv * 8);
            group_coefs<1>(gst, gv, cf);
            norm_unit(u[1], cf[2], cf[3]);
            stsm4(act_off + 2 * KC_BYTES, u[1][0], u[1][1], u[1][2], u[1][3]);
            next_unit<2>(u, cf, gst, gv, act_off, fbar, lane);
            next_unit<3>(u, cf, gst, gv, act_off, fbar, lane);
            publish(fbar + 48, lane);
            if (tid == 256) TL(84 + conv);
            if (has_outer) {
                mbar_wait(BAR(BAR_X + 4), conv);
                if (conv == 0) {
#pragma unroll
                    for (int i = 0; i < 4; i++) ldsm4t(w[i], SM_XOUT + stg_off + i * 4096);
                } else {
#pragma unroll
                    for (int i = 0; i < 4; i++) {
                        const uint4 q = lds128(SM_XOWN + (tid - 256) * 16 + i * 4096);
                        w[i][0] = q.x; w[i][1] = q.y; w[i][2] = q.z; w[i][3] = q.w;
                    }
                    unsigned it = 0;
                    while (true) {
                        bool ok = true;
#pragma unroll
                        for (int i = 0; i < 16; i++) ok = ok && w[i >> 2][i & 3] != 0;
                        if (__all_sync(0xffffffffu, ok) || ++it > SPIN_LIMIT) break;
#pragma unroll
                        for (int i = 0; i < 4; i++) ld_unit(w[i], inbox + i * 256);
                    }
#pragma unroll
                    for (int i = 0; i < 16; i++) w[i >> 2][i & 3] = ~w[i >> 2][i & 3];
                }
            }
            if (conv == 0) {
                bar_sync(3, 256);
                if (nw == 0) sts128(SM_ACT + 2 * ROW_BYTES + (lane >> 1) * CH_PITCH + (lane & 1) * 16, make_uint4(0, 0, 0, 0));
            }
            if (tid == 256) TL(24 + conv * 4);
            norm_block<0, 2>(w, cf, act_off + 2 * ROW_BYTES, has_outer ? ~0u : 0u, fbar + 128, lane);
            if (tid == 256) TL(88 + conv);
            norm_block<2, 2>(w, cf, act_off + 2 * ROW_BYTES, has_outer ? ~0u : 0u, fbar + 128, lane);
            if (tid == 256) TL(23 + conv * 4);
        }
        if (has_outer) {
            mbar_wait(BAR(BAR_FULL + NSTAGE - 1), 1);
#pragma unroll
            for (int i = 0; i < 4; i++) inbox[i * 256] = make_uint4(0, 0, 0, 0);
        }
        {
            const int oc0 = (tid - 256) >> 3, seg = lane & 7;
            __nv_bfloat16* dst = out + ((size_t)(b * C + oc0) * HW + r) * HW + seg * 8;
            const uint32_t src = SM_XOWN + oc0 * 128 + ((seg ^ (oc0 & 7)) << 4);
            bar_sync(6, 128 + 256);
#pragma unroll
            for (int i = 0; i < 4; i++) *reinterpret_cast<uint4*>(dst + (size_t)i * 32 * HW * HW) = lds128(src + i * 4096);
            if (tid == 256) { TL(20); TLG(21); }
        }
    } else if (warp < 4) {
        const int wq = warp;
        bar_sync(7, 160);

        const uint32_t xbase = SM_XOWN + ((lane >> 4) * 8 + (lane & 7)) * 128 + (((2 * wq + ((lane >> 3) & 1)) ^ (lane & 7)) << 4);
        float d[64];
#pragma unroll
        for (int i = 0; i < 64; i++) d[i] = 0.f;
#pragma unroll 1
        for (int conv = 0; conv < 2; conv++) {
            fence_acc(d);
            mma_stages<0>(d, conv, tid, gs);
            if (conv == 0) {
                asm volatile("wgmma.fence.sync.aligned;" ::: "memory");
                wgmma128<(SM_ONES >> 4) | (8u << 16), (SM_EMB >> 4), 0, 8>(d);
                asm volatile("wgmma.commit_group.sync.aligned;" ::: "memory");
            }
            asm volatile("wgmma.wait_group.sync.aligned 0;" ::: "memory");
            fence_acc(d);
            if (tid == 0) TL(10 + conv * 8);
            uint32_t hp[32];
#pragma unroll
            for (int i = 0; i < 32; i++) hp[i] = pack_bf(d[2 * i], d[2 * i + 1]);
            if (conv == 1) {
#pragma unroll
                for (int kc = 0; kc < 8; kc++) stsm4t(xbase + kc * 2048, hp[4 * kc], hp[4 * kc + 1], hp[4 * kc + 2], hp[4 * kc + 3]);
                bar_arrive(6, 128 + 256);
                break;
            }
#pragma unroll
            for (int g = 0; g < 4; g++) {
                float c[4] = {0.f, 0.f, 0.f, 0.f};
#pragma unroll
                for (int i = 0; i < 4; i++) stat_mma(c, hp[8 * g + 2 * i], hp[8 * g + 2 * i + 1]);
                stat_store(c, SM_RED + (g * 4 + wq) * 48, lane);
            }
            bar_sync(2, 128);
            if (wq == 0) stat_publish(SM_RED, &gs->acc2[b * LS], lane, true);
            if (tid == 0) TL(11);
            const uint32_t hbase = SM_ACT + (lane >> 4) * CH_PITCH + (2 + wq * 16 + (lane & 15)) * 16;
#pragma unroll
            for (int kc = 0; kc < 8; kc++) stsm4(hbase + kc * 2 * CH_PITCH, hp[4 * kc], hp[4 * kc + 1], hp[4 * kc + 2], hp[4 * kc + 3]);
            __syncwarp();
            if (lane == 0) mbar_arrive(BAR(BAR_HW));
            if (lane < LAG) mbar_arrive(BAR(BAR_WEMPTY + (NSTAGE - LAG) % NS) + 8 * lane);
            if (has_outer) {
                uint4* outbox = gs->box + (cta + ((r & 1) ? 1 : -1)) * 1024 + tid;
#pragma unroll
                for (int kc = 0; kc < 8; kc++) outbox[kc * 128] = make_uint4(~hp[4 * kc], ~hp[4 * kc + 1], ~hp[4 * kc + 2], ~hp[4 * kc + 3]);
            }
            if (tid == 0) TL(12);
#pragma unroll
            for (int kc = 0; kc < 8; kc++) {
                uint32_t p[4];
                ldsm4t(p, xbase + kc * 2048);
#pragma unroll
                for (int i = 0; i < 4; i++) { d[8 * kc + 2 * i] = bf_lo(p[i]); d[8 * kc + 2 * i + 1] = bf_hi(p[i]); }
            }
            fence_async_smem();
            __syncwarp();
            if (lane == 0) mbar_arrive(BAR(BAR_XFREE));
        }
        {
        }
    } else if (warp < 6) {
        if (warp == 5) {
            bar_sync(5, 64);
            mbar_wait(BAR(BAR_FULL + OAFTER), 0);
            if (has_outer && elect_one()) {
                mbar_expect(BAR(BAR_X + 4), 16384);
#pragma unroll
                for (int i = 0; i < 4; i++) tma_x(SM_XOUT + i * 4096, &xmap, r + ((r & 1) ? 1 : -1), b * C + i * 32, BAR(BAR_X + 4));
            }
            __syncwarp();
            asm volatile("barrier.cluster.wait.acquire.aligned;" ::: "memory");
            const uint32_t peer = (r & 1) ^ 1;
            const uint32_t self0 = mapa(0, r & 1), peer0 = mapa(0, peer);
#pragma unroll 1
            for (int conv = 0; conv < 2; conv++) {
#pragma unroll 1
                for (int kc = 0; kc < 8; kc++) {
                    mbar_wait(BAR(BAR_FULL) + 8 * kc, conv);
                    if (elect_one())
                        asm volatile("cp.async.bulk.shared::cluster.shared::cta.mbarrier::complete_tx::bytes [%0], [%1], %2, [%3];"
                                     ::"r"(peer0 + SM_ACT + ROW_BYTES + kc * KC_BYTES), "r"(self0 + SM_ACT + kc * KC_BYTES), "r"(KC_BYTES),
                                       "r"(peer0 + BAR(BAR_FULL + 8) + 8 * kc) : "memory");
                }
                if (lane == 0) TL(86 + conv);
#pragma unroll 1
                for (int kc = 0; kc < 8; kc++) mbar_wait(BAR(BAR_FULL + 8) + 8 * kc, conv);
                if (lane == 0)
                    asm volatile("mbarrier.arrive.release.cluster.shared::cluster.b64 _, [%0];" ::"r"(peer0 + (conv ? BAR(BAR_ACK) : BAR(BAR_EMB))) : "memory");
            }
            mbar_wait(BAR(BAR_ACK), 0);
        } else {
            mbar_wait(BAR(BAR_STATS), 0);
            unsigned it = 0;
            while (ld_relaxed(&gs->wcnt[(2 * NB + b) * LS]) < (unsigned)NXTRA && ++it < SPIN_LIMIT) __nanosleep(100);
            fence_acquire();
            float ev[4] = {0.f, 0.f, 0.f, 0.f};
#pragma unroll
            for (int j = 0; j < NXTRA; j++) {
                const uint4 ef = ld_relaxed_v4(&gs->emb[(j * NB + b) * C + lane * 4]);
                ev[0] += __uint_as_float(ef.x); ev[1] += __uint_as_float(ef.y); ev[2] += __uint_as_float(ef.z); ev[3] += __uint_as_float(ef.w);
            }
#pragma unroll
            for (int i = 0; i < 4; i++) {
                const float hi = bf_lo(pack_bf(ev[i], 0.f));
                sts128(SM_EMB + (lane * 4 + i) * 16, make_uint4(pack_bf(hi, ev[i] - hi), 0, 0, 0));
            }
            fence_async_smem();
            __syncwarp();
            if (lane == 0) { mbar_arrive(BAR(BAR_EMB)); TL(19); }
        }
    } else if (warp == 6) {
        bar_sync(0, 96);
        const uint32_t ebytes = STAGE_BYTES + ((lane >> 3) == 1 ? KC_BYTES : 0);
        if (lane < NSTAGE) mbar_expect(BAR(BAR_FULL) + 8 * lane, ebytes);
        const int swap = (r & 1) ? 0 : 8 * STAGE_BYTES;
        unsigned it = 0;
        {
            int g = 0;
#pragma unroll 1
            while (g < NS) {
                unsigned ready = __ballot_sync(0xffffffffu, ld_relaxed(&gs->wcnt[b * LS + (lane & 7)]) >= 16u) >> g;
                if (++it > SPIN_LIMIT) ready = ~0u;
                if (!(ready & 1)) continue;
                fence_acquire();
                fence_async_global();
                if (lane == 0) TL(g ? 3 : 6);
#pragma unroll 1
                for (; (ready & 1) && g < NS; g++, ready >>= 1)
                    if (elect_one())
                        bulk_g2s(S0 + SM_W + g * STAGE_BYTES, gs->wt + g * STAGE_BYTES + (g >= 8 ? swap : 0), STAGE_BYTES, S0 + BAR(BAR_FULL) + 8 * g);
            }
        }
#pragma unroll 1
        for (int q = 3; q < 12; q++) {
            const int conv = q >= 6, qs = conv ? q - 6 : q, sl = q % 3;
            const unsigned char* wsrc = gs->wt + q * 4 * STAGE_BYTES + (qs < 2 ? 0 : (qs < 4 ? swap : -swap));
            const uint32_t par = (q / 3 - 1) & 1;
            if (q == 6) {
                it = 0;
                while (ld_relaxed(&gs->wcnt[(NB + b) * LS]) < (unsigned)NCTA && ++it < SPIN_LIMIT) {}
                fence_acquire();
                fence_async_global();
                if (lane == 0) { mbar_arrive(BAR(BAR_EMB)); TL(2); }
            }
#pragma unroll
            for (int i = 0; i < 4; i++) {
                mbar_wait(BAR(BAR_WEMPTY + i) + 32 * sl, par);
                if (i == 0 && (q == 6 || q == 9)) {
                    if ((lane >= NS) == (q == 9) && lane < NSTAGE) mbar_expect(BAR(BAR_FULL) + 8 * lane, ebytes);
                    __syncwarp();
                }
                if (elect_one())
                    bulk_g2s(S0 + SM_W + (sl * 4 + i) * STAGE_BYTES, wsrc + i * STAGE_BYTES, STAGE_BYTES, S0 + BAR(BAR_FULL + i) + 32 * qs);
            }
        }
    } else {
        const uint2 ga1 = __ldg(reinterpret_cast<const uint2*>(g1) + lane), bt1 = __ldg(reinterpret_cast<const uint2*>(be1) + lane);
        const uint2 ga2 = __ldg(reinterpret_cast<const uint2*>(g2) + lane), bt2 = __ldg(reinterpret_cast<const uint2*>(be2) + lane);
        if (lane < 8) sts128(SM_GST + lane * 16, make_uint4(0, 0, 0, 0));
        sts128f(SM_COEF + lane * 32, make_float4(0.5f * bf_lo(ga1.x), 0.5f * bf_hi(ga1.x), 0.5f * bf_lo(bt1.x), 0.5f * bf_hi(bt1.x)));
        sts128f(SM_COEF + lane * 32 + 16, make_float4(0.5f * bf_lo(ga1.y), 0.5f * bf_hi(ga1.y), 0.5f * bf_lo(bt1.y), 0.5f * bf_hi(bt1.y)));
        sts128f(SM_COEF + 1024 + lane * 32, make_float4(0.5f * bf_lo(ga2.x), 0.5f * bf_hi(ga2.x), 0.5f * bf_lo(bt2.x), 0.5f * bf_hi(bt2.x)));
        sts128f(SM_COEF + 1024 + lane * 32 + 16, make_float4(0.5f * bf_lo(ga2.y), 0.5f * bf_hi(ga2.y), 0.5f * bf_lo(bt2.y), 0.5f * bf_hi(bt2.y)));
        bar_arrive(4, 256 + 64 + 128);
        bar_sync(0, 96);
#pragma unroll 1
        for (int conv = 0; conv < 2; conv++) {
            if (conv == 1) {
                mbar_wait(BAR(BAR_HW), 0);
                const unsigned c1 = clock32();
                while (clock32() - c1 < PD2) {}
            } else {
                while (clock32() - clk0 < PD) {}
            }
            const float* asrc = conv ? &gs->acc2[b * LS + (lane & 3) * 4] : &gs->acc1[b * 4 * LS + (lane & 3) * GS1];
            unsigned it = 0;
            uint4 fq[NPOLL];
#pragma unroll
            for (int i = 0; i < NPOLL; i++) {
                fq[i] = ld_relaxed_v4(asrc);
                if (i + 1 < NPOLL) { const unsigned c1 = clock32(); while (clock32() - c1 < 450 / NPOLL) {} }
            }
            bool all = false;
#pragma unroll 1
            while (!all) {
#pragma unroll
                for (int i = 0; i < NPOLL; i++) {
                    const uint4 f = fq[i];
                    const bool ok = ((f.x == 0x42800000u) & (f.w == 0x42800000u)) || it > SPIN_LIMIT;
                    if (ok && lane < 4) {
                        const float inv_n = 1.0f / (32.0f * HW * HW);
                        const float mean = __uint_as_float(f.y) * inv_n;
                        const float rs = rsqrtf(fmaxf(fmaf(-mean, mean, __uint_as_float(f.z) * inv_n), 0.f) + 1e-5f);
                        asm volatile("st.shared.v2.f32 [%0], {%1,%2};" ::"r"(S0 + SM_GST + conv * 32 + lane * 8), "f"(rs == 0.f ? 1e-38f : rs), "f"(mean * rs) : "memory");
                    }
                    if (__all_sync(0xffffffffu, ok)) { all = true; break; }
                    fq[i] = ld_relaxed_v4(asrc);
                }
                it++;
            }
            if (lane == 0) { mbar_arrive(BAR(BAR_STATS)); TL(7 + conv * 8); }
        }
        mbar_wait(BAR(BAR_XFREE), 0);
        if (has_outer && elect_one()) {
            mbar_expect(BAR(BAR_X + 4), 16384);
            bulk_g2s(S0 + SM_XOWN, gs->box + cta * 1024, 16384, S0 + BAR(BAR_X + 4));
        }
        if (r == 0) {
            if (lane < 16) gs->acc1[b * 4 * LS + (lane >> 2) * GS1 + (lane & 3)] = 0.f;
            if (lane < 24) gs->wcnt[((lane >> 3) * NB + b) * LS + (lane & 7)] = 0;
        }
    }
}

}

extern "C" void kernel_launch(void* const* d_in, const int* in_sizes, int n_in, void* d_out, int out_size) {
    (void)in_sizes; (void)n_in; (void)out_size;
    typedef CUresult (*EncodeFn)(CUtensorMap*, CUtensorMapDataType, cuuint32_t, void*, const cuuint64_t*, const cuuint64_t*,
                                 const cuuint32_t*, const cuuint32_t*, CUtensorMapInterleave, CUtensorMapSwizzle,
                                 CUtensorMapL2promotion, CUtensorMapFloatOOBfill);
    static Scratch* gs = nullptr;
    static EncodeFn encode = nullptr;
    if (!gs) {
        cudaFuncSetAttribute(resblock_kernel, cudaFuncAttributeMaxDynamicSharedMemorySize, SM_TOTAL);
        cudaGetSymbolAddress((void**)&gs, g_scratch);
        cudaDriverEntryPointQueryResult qr;
        cudaGetDriverEntryPoint("cuTensorMapEncodeTiled", (void**)&encode, cudaEnableDefault, &qr);
    }
    CUtensorMap xmap;
    const cuuint64_t dims[3] = {HW, HW, NB * C}, strides[2] = {HW * 2, HW * HW * 2};
    const cuuint32_t box[3] = {HW, 1, 32}, es[3] = {1, 1, 1};
    encode(&xmap, CU_TENSOR_MAP_DATA_TYPE_BFLOAT16, 3, d_in[0], dims, strides, box, es, CU_TENSOR_MAP_INTERLEAVE_NONE,
           CU_TENSOR_MAP_SWIZZLE_128B, CU_TENSOR_MAP_L2_PROMOTION_NONE, CU_TENSOR_MAP_FLOAT_OOB_FILL_NONE);
    resblock_kernel<<<NCTA + NXTRA, NTHREADS, SM_TOTAL>>>(
        (const __nv_bfloat16*)d_in[4], (const __nv_bfloat16*)d_in[0], (const __nv_bfloat16*)d_in[1],
        (const __nv_bfloat16*)d_in[2], (const __nv_bfloat16*)d_in[3], (const __nv_bfloat16*)d_in[5],
        (const __nv_bfloat16*)d_in[6], (const __nv_bfloat16*)d_in[7], (const __nv_bfloat16*)d_in[8],
        (__nv_bfloat16*)d_out, gs, xmap);
}
```

```cpp
#include <cuda_runtime.h>
#include <cuda.h>
#include <cuda_bf16.h>
#include <stdint.h>

namespace {

constexpr int C = 128, HW = 64, NB = 2, E = 768;
constexpr int NCTA = NB * HW;
constexpr int NXTRA = 4;
constexpr int NTHREADS = 16 * 32;
constexpr int CH_PITCH = 66 * 16;
constexpr int ROW_BYTES = 16 * CH_PITCH;
constexpr int STEP_BYTES = 4096;
constexpr int STAGE_BYTES = 3 * STEP_BYTES;
constexpr int NSTAGE = 24;
constexpr int KC_BYTES = 2 * CH_PITCH;
constexpr int NS = 12;
constexpr int LAG = 1;
#define XDELAY 400
#define HDELAY 600
#define SEQ 0
#define MMA0_WAIT mbar_try
#define SPINPAUSE
#define NPOLL 1
#define PD2 0
#define ODELAY 100
#define NLDG 2
#define PSTAG -1
#define PDELAY0 400
#define PDELAY 60
#define RB 1
#define XSTAG2 400
#define XSTAG 800
#define HSEND 0
#define SDELAY 600
#define OAFTER 0
#define W2DELAY 2400

constexpr uint32_t SMEM_BASE = 0x400;
constexpr uint32_t SM_XOWN = SMEM_BASE;
constexpr uint32_t SM_ACT = SM_XOWN + 16384 + 512;
constexpr uint32_t SM_XOUT = SM_ACT + 2 * ROW_BYTES + 512;
static_assert(SM_XOUT % 1024 == 0, "swizzle atom alignment");
constexpr uint32_t SM_W = SM_ACT + 3 * ROW_BYTES + 128;
__host__ __device__ constexpr uint32_t slot_addr(int slot) { return SM_W + slot * STAGE_BYTES; }
constexpr uint32_t SM_COEF = SM_W + NS * STAGE_BYTES;
constexpr uint32_t SM_GST = SM_COEF + 2048;
constexpr uint32_t SM_EMB = SM_GST + 128;
constexpr uint32_t SM_ONES = SM_EMB + 2048;
constexpr uint32_t SM_RED = SM_ONES + 256;
constexpr uint32_t SM_BNC = SM_RED + 1536;
constexpr uint32_t SM_BAR = SM_BNC + 2 * 2304;
constexpr int BAR_FULL = 0, BAR_WEMPTY = NSTAGE, BAR_HW = BAR_WEMPTY + NS, BAR_XFREE = BAR_HW + 1, BAR_STATS = BAR_XFREE + 1,
              BAR_EMB = BAR_STATS + 1, BAR_ACK = BAR_EMB + 1, BAR_X = BAR_ACK + 1  , NBAR = BAR_X + 5;
constexpr int SM_TOTAL = SM_BAR + NBAR * 8 - SMEM_BASE;
static_assert(SM_TOTAL <= 232448, "smem");
static_assert(NBAR <= 96, "barrier init");
__host__ __device__ constexpr uint32_t BAR(int i) { return SM_BAR + 8 * i; }
__host__ __device__ constexpr int ky_of(int kyo) { return kyo == 0 ? 1 : (kyo == 1 ? 0 : 2); }

constexpr unsigned SPIN_LIMIT = 1u << 16;

#define LS 1056
#define GS1 4
#define PD 0
#define KS 1056
#define PW 8
struct Scratch {
    float acc1[NB * 4 * LS];
    float acc2[NB * LS];
    unsigned wcnt[3 * NB * LS];
    unsigned w1cnt[NB * 8 * KS];
    float emb[NXTRA * NB * C];
    unsigned char wt[2 * NSTAGE * STAGE_BYTES];
    uint4 box[NCTA * 1024];
};
__device__ __align__(1024) Scratch g_scratch;
#define TL(i) do {} while (0)
#define TLG(i) do {} while (0)

__device__ __forceinline__ unsigned clock32() { unsigned c; asm volatile("mov.u32 %0, %%clock;" : "=r"(c)); return c; }
__device__ __forceinline__ uint32_t mapa(uint32_t a, uint32_t rank) {
    uint32_t d;
    asm("mapa.shared::cluster.u32 %0, %1, %2;" : "=r"(d) : "r"(a), "r"(rank));
    return d;
}
#define S0 mapa(0, blockIdx.x & 1)
__device__ __forceinline__ void mbar_init(uint32_t bar, int cnt) {
    asm volatile("mbarrier.init.shared::cta.b64 [%0], %1;" ::"r"(bar + S0), "r"(cnt) : "memory");
}
__device__ __forceinline__ void mbar_arrive(uint32_t bar) {
    asm volatile("mbarrier.arrive.shared::cta.b64 _, [%0];" ::"r"(bar + S0) : "memory");
}
__device__ __forceinline__ void mbar_expect(uint32_t bar, uint32_t bytes) {
    asm volatile("mbarrier.arrive.expect_tx.shared::cta.b64 _, [%0], %1;" ::"r"(bar + S0), "r"(bytes) : "memory");
}
__device__ __forceinline__ bool mbar_try(uint32_t bar, uint32_t par) {
    uint32_t ok;
    asm volatile("{\n.reg .pred p;\nmbarrier.try_wait.parity.shared::cta.b64 p, [%1], %2;\nselp.u32 %0, 1, 0, p;\n}"
                 : "=r"(ok) : "r"(bar + S0), "r"(par) : "memory");
    return ok;
}
__device__ __forceinline__ bool mbar_test(uint32_t bar, uint32_t par) {
    uint32_t ok;
    asm volatile("{\n.reg .pred p;\nmbarrier.test_wait.parity.shared::cta.b64 p, [%1], %2;\nselp.u32 %0, 1, 0, p;\n}"
                 : "=r"(ok) : "r"(bar + S0), "r"(par) : "memory");
    return ok;
}
__device__ __forceinline__ void mbar_wait(uint32_t bar, uint32_t par) {
    unsigned it = 0;
#pragma unroll 1
    while (!mbar_try(bar, par) && ++it < SPIN_LIMIT) {}
}
__device__ __forceinline__ bool elect_one() {
    uint32_t p;
    asm volatile("{\n.reg .pred p;\nelect.sync _|p, 0xffffffff;\nselp.u32 %0, 1, 0, p;\n}" : "=r"(p));
    return p;
}
__device__ __forceinline__ void fence_async_smem() { asm volatile("fence.proxy.async.shared::cta;" ::: "memory"); }
__device__ __forceinline__ void fence_async_global() { asm volatile("fence.proxy.async.global;" ::: "memory"); }
__device__ __forceinline__ void fence_acquire() { asm volatile("fence.acquire.gpu;" ::: "memory"); }
__device__ __forceinline__ void bar_sync(int id, int n) { asm volatile("bar.sync %0, %1;" ::"r"(id), "r"(n) : "memory"); }
__device__ __forceinline__ void bar_arrive(int id, int n) { asm volatile("bar.arrive %0, %1;" ::"r"(id), "r"(n) : "memory"); }
__device__ __forceinline__ void bulk_g2s(uint32_t dst, const void* src, uint32_t bytes, uint32_t bar) {
    asm volatile("cp.async.bulk.shared::cluster.global.mbarrier::complete_tx::bytes [%0], [%1], %2, [%3];"
                 ::"r"(dst), "l"(src), "r"(bytes), "r"(bar) : "memory");
}
__device__ __forceinline__ void tma_x(uint32_t dst, const CUtensorMap* tm, int row, int ch, uint32_t bar) {
    asm volatile("cp.async.bulk.tensor.3d.shared::cluster.global.mbarrier::complete_tx::bytes [%0], [%1, {%2, %3, %4}], [%5];"
                 ::"r"(dst + S0), "l"(tm), "r"(0), "r"(row), "r"(ch), "r"(bar + S0) : "memory");
}
__device__ __forceinline__ uint4 ld_relaxed_v4(const void* p) {
    uint4 v;
    asm volatile("ld.relaxed.gpu.global.v4.u32 {%0,%1,%2,%3}, [%4];" : "=r"(v.x), "=r"(v.y), "=r"(v.z), "=r"(v.w) : "l"(p) : "memory");
    return v;
}
__device__ __forceinline__ unsigned ld_relaxed(const void* p) {
    unsigned v;
    asm volatile("ld.relaxed.gpu.global.u32 %0, [%1];" : "=r"(v) : "l"(p) : "memory");
    return v;
}
__device__ __forceinline__ void red_add4(float* p, float a, float b, float c, float d) {
    asm volatile("red.relaxed.gpu.global.add.v4.f32 [%0], {%1,%2,%3,%4};" ::"l"(p), "f"(a), "f"(b), "f"(c), "f"(d) : "memory");
}
__device__ __forceinline__ void sts128(uint32_t a, uint4 v) {
    asm volatile("st.shared.v4.u32 [%0], {%1,%2,%3,%4};" ::"r"(a + S0), "r"(v.x), "r"(v.y), "r"(v.z), "r"(v.w) : "memory");
}
__device__ __forceinline__ void sts128f(uint32_t a, float4 v) {
    asm volatile("st.shared.v4.f32 [%0], {%1,%2,%3,%4};" ::"r"(a + S0), "f"(v.x), "f"(v.y), "f"(v.z), "f"(v.w) : "memory");
}
__device__ __forceinline__ void sts32f(uint32_t a, float v) { asm volatile("st.shared.f32 [%0], %1;" ::"r"(a + S0), "f"(v) : "memory"); }
__device__ __forceinline__ uint4 lds128(uint32_t a) {
    uint4 v;
    asm volatile("ld.shared.v4.u32 {%0,%1,%2,%3}, [%4];" : "=r"(v.x), "=r"(v.y), "=r"(v.z), "=r"(v.w) : "r"(a + S0) : "memory");
    return v;
}
__device__ __forceinline__ float4 lds128f(uint32_t a) {
    float4 v;
    asm volatile("ld.shared.v4.f32 {%0,%1,%2,%3}, [%4];" : "=f"(v.x), "=f"(v.y), "=f"(v.z), "=f"(v.w) : "r"(a + S0) : "memory");
    return v;
}
__device__ __forceinline__ float2 lds64f(uint32_t a) {
    float2 v;
    asm volatile("ld.shared.v2.f32 {%0,%1}, [%2];" : "=f"(v.x), "=f"(v.y) : "r"(a + S0) : "memory");
    return v;
}
__device__ __forceinline__ float bf_lo(uint32_t u) { return __uint_as_float(u << 16); }
__device__ __forceinline__ float bf_hi(uint32_t u) { return __uint_as_float(u & 0xffff0000u); }
__device__ __forceinline__ uint32_t pack_bf(float lo, float hi) {
    uint32_t r;
    asm("cvt.rn.bf16x2.f32 %0, %1, %2;" : "=r"(r) : "f"(hi), "f"(lo));
    return r;
}
__device__ __forceinline__ float tanh_fast(float x) {
    float r;
    asm("tanh.approx.f32 %0, %1;" : "=f"(r) : "f"(x));
    return r;
}
__device__ __forceinline__ float silu_half(float h) { return fmaf(h, tanh_fast(h), h); }
__device__ __forceinline__ void ldsm4(uint32_t (&u)[4], uint32_t a) {
    asm volatile("ldmatrix.sync.aligned.m8n8.x4.shared.b16 {%0,%1,%2,%3}, [%4];"
                 : "=r"(u[0]), "=r"(u[1]), "=r"(u[2]), "=r"(u[3]) : "r"(a + S0) : "memory");
}
__device__ __forceinline__ void ldsm4t(uint32_t (&u)[4], uint32_t a) {
    asm volatile("ldmatrix.sync.aligned.m8n8.x4.trans.shared.b16 {%0,%1,%2,%3}, [%4];"
                 : "=r"(u[0]), "=r"(u[1]), "=r"(u[2]), "=r"(u[3]) : "r"(a + S0) : "memory");
}
__device__ __forceinline__ void stsm4(uint32_t a, uint32_t p0, uint32_t p1, uint32_t p2, uint32_t p3) {
    asm volatile("stmatrix.sync.aligned.m8n8.x4.shared.b16 [%0], {%1,%2,%3,%4};" ::"r"(a + S0), "r"(p0), "r"(p1), "r"(p2), "r"(p3) : "memory");
}
__device__ __forceinline__ void stsm4t(uint32_t a, uint32_t p0, uint32_t p1, uint32_t p2, uint32_t p3) {
    asm volatile("stmatrix.sync.aligned.m8n8.x4.trans.shared.b16 [%0], {%1,%2,%3,%4};" ::"r"(a + S0), "r"(p0), "r"(p1), "r"(p2), "r"(p3) : "memory");
}

#define R8(o) "+f"(d[o]), "+f"(d[o + 1]), "+f"(d[o + 2]), "+f"(d[o + 3]), "+f"(d[o + 4]), "+f"(d[o + 5]), "+f"(d[o + 6]), "+f"(d[o + 7])
template <uint32_t ALO, uint32_t BLO, uint64_t AHI = 8, uint64_t BHI = 48>
__device__ __forceinline__ void wgmma128(float (&d)[64]) {
    asm volatile(
        "wgmma.mma_async.sync.aligned.m64n128k16.f32.bf16.bf16 "
        "{%0,%1,%2,%3,%4,%5,%6,%7,%8,%9,%10,%11,%12,%13,%14,%15,%16,%17,%18,%19,%20,%21,%22,%23,%24,%25,%26,%27,%28,%29,%30,%31,"
        "%32,%33,%34,%35,%36,%37,%38,%39,%40,%41,%42,%43,%44,%45,%46,%47,%48,%49,%50,%51,%52,%53,%54,%55,%56,%57,%58,%59,%60,%61,%62,%63},"
        " %64, %65, 1, 1, 1, 0, 0;"
        : R8(0), R8(8), R8(16), R8(24), R8(32), R8(40), R8(48), R8(56)
        : "l"((AHI << 32) | ALO), "l"((BHI << 32) | BLO));
}
template <int S>
__device__ __forceinline__ void mma_stages(float (&d)[64], int conv, int tid, Scratch* gs) {
    constexpr uint32_t A = ((SM_ACT + S * 2 * CH_PITCH + 16) >> 4) | ((CH_PITCH >> 4) << 16);
    constexpr uint32_t B = (slot_addr(S % NS) >> 4) | (8u << 16);
    if (S == 0) {
        unsigned it = 0;
#pragma unroll 1
        while (!MMA0_WAIT(BAR(BAR_FULL), conv) && ++it < SPIN_LIMIT) {}
    }
    bool next_ok = true;
    constexpr uint32_t NEXT = S + 1 < NSTAGE ? BAR(BAR_FULL + S + 1) : BAR(BAR_EMB);
    const int npar = S + 1 < NSTAGE ? conv : 0;
    next_ok = mbar_test(NEXT, npar);
    if (S == 0 && tid == 0) TL(32 + conv * 24);
    asm volatile("wgmma.fence.sync.aligned;" ::: "memory");
    wgmma128<A, B>(d);
    wgmma128<A + 1, B + 16>(d);
    wgmma128<A + 2, B + 32>(d);
    asm volatile("wgmma.commit_group.sync.aligned;" ::: "memory");
    if (S >= LAG) {
        asm volatile("wgmma.wait_group.sync.aligned %0;" ::"n"(LAG) : "memory");
        if ((tid & 31) == 0) mbar_arrive(BAR(BAR_WEMPTY + (S + NS - LAG) % NS));
    }
    if (!next_ok) mbar_wait(NEXT, npar);
    if constexpr (S + 1 < NSTAGE) mma_stages<S + 1>(d, conv, tid, gs);
}

__device__ __forceinline__ void weight_load(uint4 (&t)[5], const __nv_bfloat16* w, int cta, int lane) {
    const char* base = reinterpret_cast<const char*>(w) + ((cta & 15) * 8 * C + (cta >> 4) * 16) * 18;
#pragma unroll
    for (int k = 0; k < 5; k++) {
        const int i = lane + 32 * k, row = (i * 57) >> 10;
        if (k < 4 || lane < 16) t[k] = __ldg(reinterpret_cast<const uint4*>(base + row * (C * 18 - 288) + i * 16));
    }
}
__device__ __forceinline__ void weight_block(uint32_t bounce, unsigned char* wt, int cta, int lane, bool readback, Scratch* gs) {
    unsigned char* dst = wt + (cta >> 4) * STAGE_BYTES + (cta & 15) * 768;
    if (lane < 16) {
        uint32_t v[36];
#pragma unroll
        for (int i = 0; i < 9; i++) {
            const uint4 q = lds128(bounce + (lane & 7) * 288 + (lane >> 3) * 144 + i * 16);
            v[4 * i] = q.x; v[4 * i + 1] = q.y; v[4 * i + 2] = q.z; v[4 * i + 3] = q.w;
        }
#pragma unroll
        for (int kyo = 0; kyo < 3; kyo++) {
#pragma unroll
            for (int kx = 0; kx < 3; kx++) {
                const int tap = ky_of(kyo) * 3 + kx;
                uint32_t o[4];
#pragma unroll
                for (int m = 0; m < 4; m++) {
                    const int i0 = 18 * m + tap, i1 = i0 + 9;
                    const uint32_t sel = ((i0 & 1) ? 0x32u : 0x10u) | ((i1 & 1) ? 0x7600u : 0x5400u);
                    o[m] = __byte_perm(v[i0 >> 1], v[i1 >> 1], sel);
                }
                *reinterpret_cast<uint4*>(dst + kyo * 8 * STAGE_BYTES + kx * 256 + lane * 16) = make_uint4(o[0], o[1], o[2], o[3]);
            }
        }
    }
    if (readback) {
        __syncwarp();
        unsigned acc = 0;
        if (lane < 24) {
#pragma unroll
            for (int i = 0; i < 3; i++) acc |= ld_relaxed(dst + i * 8 * STAGE_BYTES + lane * 32);
        }
        asm volatile("{\n.reg .pred p;\nsetp.eq.u32 p, %0, 0x9e3779b9;\n@p st.shared.u32 [%1], %0;\n}" ::"r"(acc), "r"(bounce + S0) : "memory");
    }
}
__device__ __forceinline__ uint32_t act2(uint32_t u, const float4& cf) {
    return pack_bf(silu_half(fmaf(bf_lo(u), cf.x, cf.z)), silu_half(fmaf(bf_hi(u), cf.y, cf.w)));
}
__device__ __forceinline__ void norm_unit(uint32_t (&u)[4], const float4& ca, const float4& cb) {
    u[0] = act2(u[0], ca); u[1] = act2(u[1], ca); u[2] = act2(u[2], cb); u[3] = act2(u[3], cb);
}
__device__ __forceinline__ void read_stats(uint32_t gst, float (&g)[8]) {
    asm volatile("ld.volatile.shared.v4.f32 {%0,%1,%2,%3}, [%4];" : "=f"(g[0]), "=f"(g[1]), "=f"(g[2]), "=f"(g[3]) : "r"(gst + S0) : "memory");
    asm volatile("ld.volatile.shared.v4.f32 {%0,%1,%2,%3}, [%4];" : "=f"(g[4]), "=f"(g[5]), "=f"(g[6]), "=f"(g[7]) : "r"(gst + 16 + S0) : "memory");
}
template <int T>
__device__ __forceinline__ void group_coefs(uint32_t gst, float (&g)[8], float4 (&cf)[8]) {
    unsigned it = 0;
    if (!__all_sync(0xffffffffu, g[2 * T] != 0.f)) {
        float rs0;
#pragma unroll 1
        do {
            SPINPAUSE;
            asm volatile("ld.volatile.shared.f32 %0, [%1];" : "=f"(rs0) : "r"(gst + 8 * T + S0) : "memory");
        } while (!__all_sync(0xffffffffu, rs0 != 0.f) && ++it < 8 * SPIN_LIMIT);
        read_stats(gst, g);
    }
    float4 &ca = cf[2 * T], &cb = cf[2 * T + 1];
    const float rs = g[2 * T], mr = g[2 * T + 1];
    ca.z = fmaf(-mr, ca.x, ca.z); ca.w = fmaf(-mr, ca.y, ca.w); ca.x *= rs; ca.y *= rs;
    cb.z = fmaf(-mr, cb.x, cb.z); cb.w = fmaf(-mr, cb.y, cb.w); cb.x *= rs; cb.y *= rs;
}
template <int FIRST, int N>
__device__ __forceinline__ void norm_block(uint32_t (&u)[4][4], float4 (&cf)[8], uint32_t act, uint32_t mask, uint32_t fbar, int lane) {
#pragma unroll
    for (int t = FIRST; t < FIRST + N; t++) {
        norm_unit(u[t], cf[2 * t], cf[2 * t + 1]);
        stsm4(act + t * 2 * KC_BYTES, u[t][0] & mask, u[t][1] & mask, u[t][2] & mask, u[t][3] & mask);
    }
    fence_async_smem();
    __syncwarp();
    if (lane < N) mbar_arrive(fbar + 16 * (FIRST + lane));
}
__device__ __forceinline__ void publish(uint32_t bar, int lane) {
    fence_async_smem();
    __syncwarp();
    if (lane == 0) mbar_arrive(bar);
}
template <int T>
__device__ __forceinline__ void next_unit(uint32_t (&u)[4][4], float4 (&cf)[8], uint32_t gst, float (&g)[8], uint32_t act, uint32_t fbar, int lane) {
    const bool have = __all_sync(0xffffffffu, g[2 * T] != 0.f);
    if (!have) publish(fbar + 16 * (T - 1), lane);
    group_coefs<T>(gst, g, cf);
    norm_unit(u[T], cf[2 * T], cf[2 * T + 1]);
    if (have) publish(fbar + 16 * (T - 1), lane);
    stsm4(act + T * 2 * KC_BYTES, u[T][0], u[T][1], u[T][2], u[T][3]);
}
__device__ __forceinline__ void stat_mma(float (&c)[4], uint32_t p, uint32_t q) {
    asm("mma.sync.aligned.m16n8k16.row.col.f32.bf16.bf16.f32 {%0,%1,%2,%3}, {%4,%5,%6,%5}, {%4,%6}, {%0,%1,%2,%3};"
        : "+f"(c[0]), "+f"(c[1]), "+f"(c[2]), "+f"(c[3]) : "r"(p), "r"(0x3f803f80u), "r"(q));
}
__device__ __forceinline__ void stat_store(const float (&c)[4], uint32_t dst, int lane) {
    const int g = lane >> 2, t = lane & 3;
    if (t == (g >> 1)) sts32f(dst + g * 4, (g & 1) ? c[1] : c[0]);
    if (g == 7) sts32f(dst + 32 + t * 4, c[2] + c[3]);
}
__device__ __forceinline__ float sum4(float4 v) { return (v.x + v.y) + (v.z + v.w); }
__device__ __forceinline__ void stat_publish(uint32_t src, float* acc, int lane, bool real) {
    const uint32_t a = src + (lane & 15) * 48;
    float q = sum4(lds128f(a)) + sum4(lds128f(a + 16)), sm = sum4(lds128f(a + 32));
    q += __shfl_xor_sync(0xffffffffu, q, 1); sm += __shfl_xor_sync(0xffffffffu, sm, 1);
    q += __shfl_xor_sync(0xffffffffu, q, 2); sm += __shfl_xor_sync(0xffffffffu, sm, 2);
    if (real && (lane & 19) == 0) red_add4(acc + lane, 1.f, sm, q, 1.f);
}
__device__ __forceinline__ void fence_acc(float (&d)[64]) {
#pragma unroll
    for (int i = 0; i < 64; i++) asm volatile("" : "+f"(d[i])::"memory");
}
__device__ __forceinline__ void ld_unit(uint32_t (&u)[4], const uint4* p) {
    asm volatile("ld.relaxed.gpu.global.v4.u32 {%0,%1,%2,%3}, [%4];" : "=r"(u[0]), "=r"(u[1]), "=r"(u[2]), "=r"(u[3]) : "l"(p) : "memory");
}

__device__ __noinline__ void side_jobs(const __nv_bfloat16* __restrict__ t_emb, const __nv_bfloat16* __restrict__ w_emb,
                                       const __nv_bfloat16* __restrict__ w2, Scratch* __restrict__ gs, unsigned clk0) {
    const int tid = threadIdx.x, warp = tid >> 5, lane = tid & 31, j = blockIdx.x;
    float tv = 0.f;
    if (lane < 24) tv = __bfloat162float(t_emb[(lane / 12) * E + j * 192 + warp * 12 + lane % 12]);
    if (tid == 0) {
        mbar_init(BAR(0), 1);
        mbar_expect(BAR(0), 192 * C * 2);
        fence_async_smem();
        while (clock32() - clk0 < SDELAY) {}
#pragma unroll
        for (int i = 0; i < 4; i++)
            asm volatile("cp.async.bulk.prefetch.L2.global [%0], 18432;" ::"l"(reinterpret_cast<const char*>(w2) + (j * 4 + i) * 18432) : "memory");
#pragma unroll
        for (int i = 0; i < 4; i++) bulk_g2s(S0 + SM_W + i * 12288, w_emb + (j * 192 + i * 48) * C, 12288, S0 + BAR(0));
    }
    if (j == 0 && tid < 32) gs->acc2[(tid >> 4) * LS + (tid & 15)] = 0.f;
    const float sv = silu_half(0.5f * tv);
    __syncthreads();
    mbar_wait(BAR(0), 0);
    float acc[8] = {0.f, 0.f, 0.f, 0.f, 0.f, 0.f, 0.f, 0.f};
#pragma unroll
    for (int i = 0; i < 12; i++) {
        const float2 wq = lds64f(SM_W + (warp * 12 + i) * 256 + lane * 8);
        const uint32_t wx = __float_as_uint(wq.x), wy = __float_as_uint(wq.y);
#pragma unroll
        for (int bb = 0; bb < 2; bb++) {
            const float sx = __shfl_sync(0xffffffffu, sv, bb * 12 + i);
            acc[4 * bb + 0] = fmaf(sx, bf_lo(wx), acc[4 * bb + 0]); acc[4 * bb + 1] = fmaf(sx, bf_hi(wx), acc[4 * bb + 1]);
            acc[4 * bb + 2] = fmaf(sx, bf_lo(wy), acc[4 * bb + 2]); acc[4 * bb + 3] = fmaf(sx, bf_hi(wy), acc[4 * bb + 3]);
        }
    }
    sts128f(SM_ACT + warp * 1024 + lane * 16, make_float4(acc[0], acc[1], acc[2], acc[3]));
    sts128f(SM_ACT + warp * 1024 + 512 + lane * 16, make_float4(acc[4], acc[5], acc[6], acc[7]));
    __syncthreads();
    if (tid < 128) {
        float2 sum = make_float2(0.f, 0.f);
#pragma unroll
        for (int w = 0; w < 16; w++) { const float2 p = lds64f(SM_ACT + w * 1024 + tid * 8); sum.x += p.x; sum.y += p.y; }
        *reinterpret_cast<float2*>(&gs->emb[j * NB * C + tid * 2]) = sum;
        bar_sync(1, 128);
        if (tid < 2) asm volatile("red.release.gpu.global.add.u32 [%0], 1;" ::"l"(&gs->wcnt[(2 * NB + tid) * LS]) : "memory");
    }
}

__global__ void __cluster_dims__(2, 1, 1) __launch_bounds__(NTHREADS, 1)
resblock_kernel(const __nv_bfloat16* __restrict__ w1, const __nv_bfloat16* __restrict__ x,
                const __nv_bfloat16* __restrict__ t_emb, const __nv_bfloat16* __restrict__ g1,
                const __nv_bfloat16* __restrict__ be1, const __nv_bfloat16* __restrict__ w_emb,
                const __nv_bfloat16* __restrict__ g2, const __nv_bfloat16* __restrict__ be2,
                const __nv_bfloat16* __restrict__ w2, __nv_bfloat16* __restrict__ out, Scratch* __restrict__ gs,
                const __grid_constant__ CUtensorMap xmap) {
    const unsigned clk0 = clock32();
    if (threadIdx.x == 480 && blockIdx.x >= NXTRA) TLG(1);
    const int tid = threadIdx.x, lane = tid & 31;
    const int cta = blockIdx.x - NXTRA, b = cta >> 6, r = cta & 63;
    uint4 v[5];
    if (tid < 32) weight_load(v, w1, cta & (NCTA - 1), lane);
    uint4 xv[8];
    const int wg4 = (tid >> 5) - 1;
    const bool early = tid >= 32 && wg4 < NLDG;
    if (early) {
        const char* src = reinterpret_cast<const char*>(x) + (uint32_t)((((b & 1) * C + wg4 * 32 + (lane >> 3)) * HW + r) * HW * 2 + (lane & 7) * 16);
        while (clock32() - clk0 < XDELAY + (wg4 >> 1) * XSTAG + (wg4 & 1) * XSTAG2) {}
#pragma unroll
        for (int i = 0; i < 8; i++) xv[i] = __ldg(reinterpret_cast<const uint4*>(src + i * (4 * HW * HW * 2)));
    }
    const int warp = __shfl_sync(0xffffffffu, tid >> 5, 0);
    if (cta < 0) { side_jobs(t_emb, w_emb, w2, gs, clk0); return; }

    if (warp != 4) asm volatile("barrier.cluster.arrive.relaxed.aligned;" ::: "memory");
    const bool has_outer = (r != 0) && (r != HW - 1);
    if (warp == 1 || warp == 2 || warp == 3 || warp == 5) {
        const int g = warp < 4 ? warp - 1 : 3;
        if (elect_one()) {
            if (g >= NLDG) asm volatile("prefetch.tensormap [%0];" ::"l"(&xmap) : "memory");
            mbar_init(BAR(BAR_X) + 8 * g, 1);
            if (g >= NLDG) mbar_expect(BAR(BAR_X) + 8 * g, 4096);
            fence_async_smem();
        }
        __syncwarp();
        bar_arrive(4, 256 + 64 + 128);
        if (g >= NLDG) {
            while (clock32() - clk0 < XDELAY + (g >> 1) * XSTAG + (g & 1) * XSTAG2) {}
            if (elect_one()) tma_x(SM_XOWN + g * 4096, &xmap, r, b * C + g * 32, BAR(BAR_X) + 8 * g);
            __syncwarp();
            mbar_wait(BAR(BAR_X) + 8 * g, 0);
#pragma unroll
            for (int k = 0; k < 8; k++) xv[k] = lds128(SM_XOWN + g * 4096 + k * 512 + lane * 16);
        }
        float c[8][4];
#pragma unroll
        for (int k = 0; k < 8; k++) {
            c[k][0] = c[k][1] = c[k][2] = c[k][3] = 0.f;
            stat_mma(c[k], xv[k].x, xv[k].y); stat_mma(c[k], xv[k].z, xv[k].w);
        }
#pragma unroll
        for (int i = 0; i < 4; i++) c[0][i] = ((c[0][i] + c[1][i]) + (c[2][i] + c[3][i])) + ((c[4][i] + c[5][i]) + (c[6][i] + c[7][i]));
        stat_store(c[0], SM_RED + g * 48, lane);
        __syncwarp();
        if (lane == 0) {
            const uint32_t a = SM_RED + g * 48;
            red_add4(&gs->acc1[b * 4 * LS + g * GS1], 1.f, sum4(lds128f(a + 32)), sum4(lds128f(a)) + sum4(lds128f(a + 16)), 1.f);
            TL(74 + g);
        }
        if (g < NLDG) {
#pragma unroll
            for (int i = 0; i < 8; i++)
                sts128(SM_XOWN + g * 4096 + i * 512 + (lane >> 3) * 128 + (((lane & 7) ^ ((lane >> 3) + 4 * (i & 1))) << 4), xv[i]);
            __syncwarp();
            if (lane == 0) mbar_arrive(BAR(BAR_X) + 8 * g);
        }
    }
    if (warp == 4) {
            if (elect_one()) {
#pragma unroll
                for (int i = 0; i < NSTAGE; i++) mbar_init(BAR(BAR_FULL + i), (i >> 3) == 1 ? 1 : 5);
#pragma unroll
                for (int i = 0; i < NS + 2; i++) mbar_init(BAR(BAR_WEMPTY + i), 4);
#pragma unroll
                for (int i = BAR_STATS; i < BAR_X; i++) mbar_init(BAR(i), i == BAR_EMB ? 3 : 1);
                mbar_init(BAR(BAR_X + 4), 1);
                asm volatile("fence.mbarrier_init.release.cluster;" ::: "memory");
            }
            __syncwarp();
            fence_async_smem();
            bar_arrive(0, 96);
            bar_arrive(5, 64);
            bar_arrive(4, 256 + 64 + 128);
            const uint4 z = make_uint4(0, 0, 0, 0);
#pragma unroll
            for (int i = 0; i < 2; i++) sts128(SM_ACT + (i * 16 + (lane >> 1)) * CH_PITCH + (lane & 1) * 16, z);
            if (lane < 4) sts128(SM_ACT + (2 + (lane >> 1)) * ROW_BYTES + (lane & 1) * 16, z);
            if (lane < 16) sts128(SM_ONES + lane * 16, make_uint4(lane < 8 ? 0x3f803f80u : 0u, 0, 0, 0));
            fence_async_smem();
            bar_arrive(7, 160);
            asm volatile("barrier.cluster.arrive.relaxed.aligned;" ::: "memory");
            if (lane == 0) TL(5);
            while (clock32() - clk0 < W2DELAY) {}
            weight_load(v, w2, cta, lane);
        }
    if (warp == 0 || warp == 4) {
        const int k = warp >> 2;
#pragma unroll
        for (int i = 0; i < 5; i++)
            if (i < 4 || lane < 16) sts128(SM_BNC + k * 2304 + (lane + 32 * i) * 16, v[i]);
        if (lane == 0) TL(k ? 14 : 81);
        __syncwarp();
        weight_block(SM_BNC + k * 2304, gs->wt + k * NSTAGE * STAGE_BYTES, cta, lane, true, gs);
        __syncwarp();
        if (lane == 0) TL(k ? 13 : 4);
        if (lane < 2) asm volatile("red.relaxed.gpu.global.add.u32 [%0], 1;" ::"l"(k ? &gs->wcnt[(NB + lane) * LS] : &gs->w1cnt[(lane * 8 + (cta >> 4)) * KS]) : "memory");
    }

    if (warp >= 8) {
        const int nw = warp - 8;
        bar_sync(4, 256 + 64 + 128);
        const int par = nw >> 2, wq = nw & 3;
        const uint32_t act_off = SM_ACT + (par * 2 + (lane >> 4)) * CH_PITCH + (2 + wq * 16 + (lane & 15)) * 16;
        const uint32_t stg_off = (par * 16 + (lane >> 4) * 8 + (lane & 7)) * 128 + (((2 * wq + ((lane >> 3) & 1)) ^ (lane & 7)) << 4);
        const uint32_t cfa = SM_COEF + par * 128 + (lane & 3) * 16;
        const uint32_t fbar = BAR(BAR_FULL) + 8 * par;
        uint4* inbox = gs->box + cta * 1024 + nw * 32 + lane;
#pragma unroll 1
        for (int conv = 0; conv < 2; conv++) {
            uint32_t u[4][4], w[4][4];
            float4 cf[8];
            if (conv == 0) {
#pragma unroll
                for (int i = 0; i < 4; i++) { mbar_wait(BAR(BAR_X + i), 0); ldsm4t(u[i], SM_XOWN + stg_off + i * 4096); }
            } else {
                mbar_wait(BAR(BAR_HW), 0);
#pragma unroll
                for (int i = 0; i < 4; i++) ldsm4(u[i], act_off + i * 2 * KC_BYTES);
            }
#pragma unroll
            for (int i = 0; i < 8; i++) cf[i] = lds128f(cfa + conv * 1024 + (i >> 1) * 256 + (i & 1) * 64);
            const uint32_t gst = SM_GST + conv * 32;
            float gv[8];
            read_stats(gst, gv);
            group_coefs<0>(gst, gv, cf);
            if (tid == 256) TL(22 + conv * 4);
            if (par) { const unsigned c1 = clock32(); while (clock32() - c1 < PDELAY) {} }
            norm_block<0, 1>(u, cf, act_off, ~0u, fbar, lane);
            if (tid == 256) TL(8 + conv * 8);
            group_coefs<1>(gst, gv, cf);
            norm_unit(u[1], cf[2], cf[3]);
            stsm4(act_off + 2 * KC_BYTES, u[1][0], u[1][1], u[1][2], u[1][3]);
            next_unit<2>(u, cf, gst, gv, act_off, fbar, lane);
            next_unit<3>(u, cf, gst, gv, act_off, fbar, lane);
            publish(fbar + 48, lane);
            if (tid == 256) TL(84 + conv);
            if (has_outer) {
                mbar_wait(BAR(BAR_X + 4), conv);
                if (conv == 0) {
#pragma unroll
                    for (int i = 0; i < 4; i++) ldsm4t(w[i], SM_XOUT + stg_off + i * 4096);
                } else {
#pragma unroll
                    for (int i = 0; i < 4; i++) {
                        const uint4 q = lds128(SM_XOWN + (tid - 256) * 16 + i * 4096);
                        w[i][0] = q.x; w[i][1] = q.y; w[i][2] = q.z; w[i][3] = q.w;
                    }
                    unsigned it = 0;
                    while (true) {
                        bool ok = true;
#pragma unroll
                        for (int i = 0; i < 16; i++) ok = ok && w[i >> 2][i & 3] != 0;
                        if (__all_sync(0xffffffffu, ok) || ++it > SPIN_LIMIT) break;
#pragma unroll
                        for (int i = 0; i < 4; i++) ld_unit(w[i], inbox + i * 256);
                    }
#pragma unroll
                    for (int i = 0; i < 16; i++) w[i >> 2][i & 3] = ~w[i >> 2][i & 3];
                }
            }
            if (conv == 0) {
                bar_sync(3, 256);
                if (nw == 0) sts128(SM_ACT + 2 * ROW_BYTES + (lane >> 1) * CH_PITCH + (lane & 1) * 16, make_uint4(0, 0, 0, 0));
            }
            if (tid == 256) TL(24 + conv * 4);
            norm_block<0, 2>(w, cf, act_off + 2 * ROW_BYTES, has_outer ? ~0u : 0u, fbar + 128, lane);
            if (tid == 256) TL(88 + conv);
            norm_block<2, 2>(w, cf, act_off + 2 * ROW_BYTES, has_outer ? ~0u : 0u, fbar + 128, lane);
            if (tid == 256) TL(23 + conv * 4);
        }
        if (has_outer) {
            mbar_wait(BAR(BAR_FULL + NSTAGE - 1), 1);
#pragma unroll
            for (int i = 0; i < 4; i++) inbox[i * 256] = make_uint4(0, 0, 0, 0);
        }
        {
            const int oc0 = (tid - 256) >> 3, seg = lane & 7;
            __nv_bfloat16* dst = out + ((size_t)(b * C + oc0) * HW + r) * HW + seg * 8;
            const uint32_t src = SM_XOWN + oc0 * 128 + ((seg ^ (oc0 & 7)) << 4);
            bar_sync(6, 128 + 256);
#pragma unroll
            for (int i = 0; i < 4; i++) *reinterpret_cast<uint4*>(dst + (size_t)i * 32 * HW * HW) = lds128(src + i * 4096);
            if (tid == 256) { TL(20); TLG(21); }
        }
    } else if (warp < 4) {
        const int wq = warp;
        bar_sync(7, 160);

        const uint32_t xbase = SM_XOWN + ((lane >> 4) * 8 + (lane & 7)) * 128 + (((2 * wq + ((lane >> 3) & 1)) ^ (lane & 7)) << 4);
        float d[64];
#pragma unroll
        for (int i = 0; i < 64; i++) d[i] = 0.f;
#pragma unroll 1
        for (int conv = 0; conv < 2; conv++) {
            fence_acc(d);
            mma_stages<0>(d, conv, tid, gs);
            if (conv == 0) {
                asm volatile("wgmma.fence.sync.aligned;" ::: "memory");
                wgmma128<(SM_ONES >> 4) | (8u << 16), (SM_EMB >> 4), 0, 8>(d);
                asm volatile("wgmma.commit_group.sync.aligned;" ::: "memory");
            }
            asm volatile("wgmma.wait_group.sync.aligned 0;" ::: "memory");
            fence_acc(d);
            if (tid == 0) TL(10 + conv * 8);
            uint32_t hp[32];
#pragma unroll
            for (int i = 0; i < 32; i++) hp[i] = pack_bf(d[2 * i], d[2 * i + 1]);
            if (conv == 1) {
#pragma unroll
                for (int kc = 0; kc < 8; kc++) stsm4t(xbase + kc * 2048, hp[4 * kc], hp[4 * kc + 1], hp[4 * kc + 2], hp[4 * kc + 3]);
                bar_arrive(6, 128 + 256);
                break;
            }
#pragma unroll
            for (int g = 0; g < 4; g++) {
                float c[4] = {0.f, 0.f, 0.f, 0.f};
#pragma unroll
                for (int i = 0; i < 4; i++) stat_mma(c, hp[8 * g + 2 * i], hp[8 * g + 2 * i + 1]);
                stat_store(c, SM_RED + (g * 4 + wq) * 48, lane);
            }
            bar_sync(2, 128);
            if (wq == 0) stat_publish(SM_RED, &gs->acc2[b * LS], lane, true);
            if (tid == 0) TL(11);
            const uint32_t hbase = SM_ACT + (lane >> 4) * CH_PITCH + (2 + wq * 16 + (lane & 15)) * 16;
#pragma unroll
            for (int kc = 0; kc < 8; kc++) stsm4(hbase + kc * 2 * CH_PITCH, hp[4 * kc], hp[4 * kc + 1], hp[4 * kc + 2], hp[4 * kc + 3]);
            __syncwarp();
            if (lane == 0) mbar_arrive(BAR(BAR_HW));
            if (lane < LAG) mbar_arrive(BAR(BAR_WEMPTY + (NSTAGE - LAG) % NS) + 8 * lane);
            if (has_outer) {
                uint4* outbox = gs->box + (cta + ((r & 1) ? 1 : -1)) * 1024 + tid;
#pragma unroll
                for (int kc = 0; kc < 8; kc++) outbox[kc * 128] = make_uint4(~hp[4 * kc], ~hp[4 * kc + 1], ~hp[4 * kc + 2], ~hp[4 * kc + 3]);
            }
            if (tid == 0) TL(12);
#pragma unroll
            for (int kc = 0; kc < 8; kc++) {
                uint32_t p[4];
                ldsm4t(p, xbase + kc * 2048);
#pragma unroll
                for (int i = 0; i < 4; i++) { d[8 * kc + 2 * i] = bf_lo(p[i]); d[8 * kc + 2 * i + 1] = bf_hi(p[i]); }
            }
            fence_async_smem();
            __syncwarp();
            if (lane == 0) mbar_arrive(BAR(BAR_XFREE));
        }
        {
        }
    } else if (warp < 6) {
        if (warp == 5) {
            bar_sync(5, 64);
            mbar_wait(BAR(BAR_FULL + OAFTER), 0);
            if (has_outer && elect_one()) {
                mbar_expect(BAR(BAR_X + 4), 16384);
#pragma unroll
                for (int i = 0; i < 4; i++) tma_x(SM_XOUT + i * 4096, &xmap, r + ((r & 1) ? 1 : -1), b * C + i * 32, BAR(BAR_X + 4));
            }
            __syncwarp();
            asm volatile("barrier.cluster.wait.acquire.aligned;" ::: "memory");
            const uint32_t peer = (r & 1) ^ 1;
            const uint32_t self0 = mapa(0, r & 1), peer0 = mapa(0, peer);
#pragma unroll 1
            for (int conv = 0; conv < 2; conv++) {
#pragma unroll 1
                for (int kc = 0; kc < 8; kc++) {
                    mbar_wait(BAR(BAR_FULL) + 8 * kc, conv);
                    if (elect_one())
                        asm volatile("cp.async.bulk.shared::cluster.shared::cta.mbarrier::complete_tx::bytes [%0], [%1], %2, [%3];"
                                     ::"r"(peer0 + SM_ACT + ROW_BYTES + kc * KC_BYTES), "r"(self0 + SM_ACT + kc * KC_BYTES), "r"(KC_BYTES),
                                       "r"(peer0 + BAR(BAR_FULL + 8) + 8 * kc) : "memory");
                }
                if (lane == 0) TL(86 + conv);
#pragma unroll 1
                for (int kc = 0; kc < 8; kc++) mbar_wait(BAR(BAR_FULL + 8) + 8 * kc, conv);
                if (lane == 0)
                    asm volatile("mbarrier.arrive.release.cluster.shared::cluster.b64 _, [%0];" ::"r"(peer0 + (conv ? BAR(BAR_ACK) : BAR(BAR_EMB))) : "memory");
            }
            mbar_wait(BAR(BAR_ACK), 0);
        } else {
            mbar_wait(BAR(BAR_STATS), 0);
            unsigned it = 0;
            while (ld_relaxed(&gs->wcnt[(2 * NB + b) * LS]) < (unsigned)NXTRA && ++it < SPIN_LIMIT) __nanosleep(100);
            fence_acquire();
            float ev[4] = {0.f, 0.f, 0.f, 0.f};
#pragma unroll
            for (int j = 0; j < NXTRA; j++) {
                const uint4 ef = ld_relaxed_v4(&gs->emb[(j * NB + b) * C + lane * 4]);
                ev[0] += __uint_as_float(ef.x); ev[1] += __uint_as_float(ef.y); ev[2] += __uint_as_float(ef.z); ev[3] += __uint_as_float(ef.w);
            }
#pragma unroll
            for (int i = 0; i < 4; i++) {
                const float hi = bf_lo(pack_bf(ev[i], 0.f));
                sts128(SM_EMB + (lane * 4 + i) * 16, make_uint4(pack_bf(hi, ev[i] - hi), 0, 0, 0));
            }
            fence_async_smem();
            __syncwarp();
            if (lane == 0) { mbar_arrive(BAR(BAR_EMB)); TL(19); }
        }
    } else if (warp == 6) {
        bar_sync(0, 96);
        const uint32_t ebytes = STAGE_BYTES + ((lane >> 3) == 1 ? KC_BYTES : 0);
        if (lane < NSTAGE) mbar_expect(BAR(BAR_FULL) + 8 * lane, ebytes);
        const int swap = (r & 1) ? 0 : 8 * STAGE_BYTES;
        unsigned it = 0;
        {
            int g = 0;
#pragma unroll 1
            while (g < NS) {
                const int pk = min(g + (lane & (PW - 1)), 7);
                unsigned ready = g >= 8 ? ~0u : __ballot_sync(0xffffffffu, ld_relaxed(&gs->w1cnt[(b * 8 + pk) * KS]) >= 16u) & ((1u << PW) - 1);
                if (++it > SPIN_LIMIT) ready = ~0u;
                if (!(ready & 1)) continue;
                fence_acquire();
                fence_async_global();
                if (lane == 0) TL(g ? 3 : 6);
#pragma unroll 1
                for (; (ready & 1) && g < NS; g++, ready >>= 1)
                    if (elect_one())
                        bulk_g2s(S0 + SM_W + g * STAGE_BYTES, gs->wt + g * STAGE_BYTES + (g >= 8 ? swap : 0), STAGE_BYTES, S0 + BAR(BAR_FULL) + 8 * g);
            }
        }
#pragma unroll 1
        for (int q = 3; q < 12; q++) {
            const int conv = q >= 6, qs = conv ? q - 6 : q, sl = q % 3;
            const unsigned char* wsrc = gs->wt + q * 4 * STAGE_BYTES + (qs < 2 ? 0 : (qs < 4 ? swap : -swap));
            const uint32_t par = (q / 3 - 1) & 1;
            if (q == 6) {
                it = 0;
                while (ld_relaxed(&gs->wcnt[(NB + b) * LS]) < (unsigned)NCTA && ++it < SPIN_LIMIT) {}
                fence_acquire();
                fence_async_global();
                if (lane == 0) { mbar_arrive(BAR(BAR_EMB)); TL(2); }
            }
#pragma unroll
            for (int i = 0; i < 4; i++) {
                mbar_wait(BAR(BAR_WEMPTY + i) + 32 * sl, par);
                if (i == 0 && (q == 6 || q == 9)) {
                    if ((lane >= NS) == (q == 9) && lane < NSTAGE) mbar_expect(BAR(BAR_FULL) + 8 * lane, ebytes);
                    __syncwarp();
                }
                if (elect_one())
                    bulk_g2s(S0 + SM_W + (sl * 4 + i) * STAGE_BYTES, wsrc + i * STAGE_BYTES, STAGE_BYTES, S0 + BAR(BAR_FULL + i) + 32 * qs);
            }
        }
    } else {
        const uint2 ga1 = __ldg(reinterpret_cast<const uint2*>(g1) + lane), bt1 = __ldg(reinterpret_cast<const uint2*>(be1) + lane);
        const uint2 ga2 = __ldg(reinterpret_cast<const uint2*>(g2) + lane), bt2 = __ldg(reinterpret_cast<const uint2*>(be2) + lane);
        if (lane < 8) sts128(SM_GST + lane * 16, make_uint4(0, 0, 0, 0));
        sts128f(SM_COEF + lane * 32, make_float4(0.5f * bf_lo(ga1.x), 0.5f * bf_hi(ga1.x), 0.5f * bf_lo(bt1.x), 0.5f * bf_hi(bt1.x)));
        sts128f(SM_COEF + lane * 32 + 16, make_float4(0.5f * bf_lo(ga1.y), 0.5f * bf_hi(ga1.y), 0.5f * bf_lo(bt1.y), 0.5f * bf_hi(bt1.y)));
        sts128f(SM_COEF + 1024 + lane * 32, make_float4(0.5f * bf_lo(ga2.x), 0.5f * bf_hi(ga2.x), 0.5f * bf_lo(bt2.x), 0.5f * bf_hi(bt2.x)));
        sts128f(SM_COEF + 1024 + lane * 32 + 16, make_float4(0.5f * bf_lo(ga2.y), 0.5f * bf_hi(ga2.y), 0.5f * bf_lo(bt2.y), 0.5f * bf_hi(bt2.y)));
        bar_arrive(4, 256 + 64 + 128);
        bar_sync(0, 96);
#pragma unroll 1
        for (int conv = 0; conv < 2; conv++) {
            if (conv == 1) {
                mbar_wait(BAR(BAR_HW), 0);
                const unsigned c1 = clock32();
                while (clock32() - c1 < PD2) {}
            } else {
                while (clock32() - clk0 < PD) {}
            }
            const float* asrc = conv ? &gs->acc2[b * LS + (lane & 3) * 4] : &gs->acc1[b * 4 * LS + (lane & 3) * GS1];
            unsigned it = 0;
            uint4 fq[NPOLL];
#pragma unroll
            for (int i = 0; i < NPOLL; i++) {
                fq[i] = ld_relaxed_v4(asrc);
                if (i + 1 < NPOLL) { const unsigned c1 = clock32(); while (clock32() - c1 < 450 / NPOLL) {} }
            }
            bool all = false;
#pragma unroll 1
            while (!all) {
#pragma unroll
                for (int i = 0; i < NPOLL; i++) {
                    const uint4 f = fq[i];
                    const bool ok = ((f.x == 0x42800000u) & (f.w == 0x42800000u)) || it > SPIN_LIMIT;
                    if (ok && lane < 4) {
                        const float inv_n = 1.0f / (32.0f * HW * HW);
                        const float mean = __uint_as_float(f.y) * inv_n;
                        const float rs = rsqrtf(fmaxf(fmaf(-mean, mean, __uint_as_float(f.z) * inv_n), 0.f) + 1e-5f);
                        asm volatile("st.shared.v2.f32 [%0], {%1,%2};" ::"r"(S0 + SM_GST + conv * 32 + lane * 8), "f"(rs == 0.f ? 1e-38f : rs), "f"(mean * rs) : "memory");
                    }
                    if (__all_sync(0xffffffffu, ok)) { all = true; break; }
                    fq[i] = ld_relaxed_v4(asrc);
                }
                it++;
            }
            if (lane == 0) { mbar_arrive(BAR(BAR_STATS)); TL(7 + conv * 8); }
        }
        mbar_wait(BAR(BAR_XFREE), 0);
        if (has_outer && elect_one()) {
            mbar_expect(BAR(BAR_X + 4), 16384);
            bulk_g2s(S0 + SM_XOWN, gs->box + cta * 1024, 16384, S0 + BAR(BAR_X + 4));
        }
        if (r == 0) {
            if (lane < 16) gs->acc1[b * 4 * LS + (lane >> 2) * GS1 + (lane & 3)] = 0.f;
            if (lane < 3) gs->wcnt[(lane * NB + b) * LS] = 0;
            if (lane < 8) gs->w1cnt[(b * 8 + lane) * KS] = 0;
        }
    }
}

}

extern "C" void kernel_launch(void* const* d_in, const int* in_sizes, int n_in, void* d_out, int out_size) {
    (void)in_sizes; (void)n_in; (void)out_size;
    typedef CUresult (*EncodeFn)(CUtensorMap*, CUtensorMapDataType, cuuint32_t, void*, const cuuint64_t*, const cuuint64_t*,
                                 const cuuint32_t*, const cuuint32_t*, CUtensorMapInterleave, CUtensorMapSwizzle,
                                 CUtensorMapL2promotion, CUtensorMapFloatOOBfill);
    static Scratch* gs = nullptr;
    static EncodeFn encode = nullptr;
    if (!gs) {
        cudaFuncSetAttribute(resblock_kernel, cudaFuncAttributeMaxDynamicSharedMemorySize, SM_TOTAL);
        cudaGetSymbolAddress((void**)&gs, g_scratch);
        cudaDriverEntryPointQueryResult qr;
        cudaGetDriverEntryPoint("cuTensorMapEncodeTiled", (void**)&encode, cudaEnableDefault, &qr);
    }
    CUtensorMap xmap;
    const cuuint64_t dims[3] = {HW, HW, NB * C}, strides[2] = {HW * 2, HW * HW * 2};
    const cuuint32_t box[3] = {HW, 1, 32}, es[3] = {1, 1, 1};
    encode(&xmap, CU_TENSOR_MAP_DATA_TYPE_BFLOAT16, 3, d_in[0], dims, strides, box, es, CU_TENSOR_MAP_INTERLEAVE_NONE,
           CU_TENSOR_MAP_SWIZZLE_128B, CU_TENSOR_MAP_L2_PROMOTION_NONE, CU_TENSOR_MAP_FLOAT_OOB_FILL_NONE);
    resblock_kernel<<<NCTA + NXTRA, NTHREADS, SM_TOTAL>>>(
        (const __nv_bfloat16*)d_in[4], (const __nv_bfloat16*)d_in[0], (const __nv_bfloat16*)d_in[1],
        (const __nv_bfloat16*)d_in[2], (const __nv_bfloat16*)d_in[3], (const __nv_bfloat16*)d_in[5],
        (const __nv_bfloat16*)d_in[6], (const __nv_bfloat16*)d_in[7], (const __nv_bfloat16*)d_in[8],
        (__nv_bfloat16*)d_out, gs, xmap);
}
```

```cpp
#include <cuda_runtime.h>
#include <cuda.h>
#include <cuda_bf16.h>
#include <stdint.h>

namespace {

constexpr int C = 128, HW = 64, NB = 2, E = 768;
constexpr int NCTA = NB * HW;
constexpr int NXTRA = 4;
constexpr int NTHREADS = 16 * 32;
constexpr int CH_PITCH = 66 * 16;
constexpr int ROW_BYTES = 16 * CH_PITCH;
constexpr int STEP_BYTES = 4096;
constexpr int STAGE_BYTES = 3 * STEP_BYTES;
constexpr int NSTAGE = 24;
constexpr int KC_BYTES = 2 * CH_PITCH;
constexpr int NS = 12;
constexpr int LAG = 1;
#define XDELAY 400
#define HDELAY 600
#define SEQ 0
#define MMA0_WAIT mbar_try
#define SPINPAUSE
#define NPOLL 1
#define PD2 0
#define ODELAY 100
#define NLDG 2
#define PSTAG -1
#define PDELAY0 400
#define PDELAY 60
#define RB 1
#define XSTAG2 400
#define XSTAG 800
#define HSEND 0
#define SDELAY 600
#define OAFTER 0
#define W2DELAY 2400

constexpr uint32_t SMEM_BASE = 0x400;
constexpr uint32_t SM_XOWN = SMEM_BASE;
constexpr uint32_t SM_ACT = SM_XOWN + 16384 + 512;
constexpr uint32_t SM_XOUT = SM_ACT + 2 * ROW_BYTES + 512;
static_assert(SM_XOUT % 1024 == 0, "swizzle atom alignment");
constexpr uint32_t SM_W = SM_ACT + 3 * ROW_BYTES + 128;
__host__ __device__ constexpr uint32_t slot_addr(int slot) { return SM_W + slot * STAGE_BYTES; }
constexpr uint32_t SM_COEF = SM_W + NS * STAGE_BYTES;
constexpr uint32_t SM_GST = SM_COEF + 2048;
constexpr uint32_t SM_EMB = SM_GST + 128;
constexpr uint32_t SM_ONES = SM_EMB + 2048;
constexpr uint32_t SM_RED = SM_ONES + 256;
constexpr uint32_t SM_BNC = SM_RED + 1536;
constexpr uint32_t SM_BAR = SM_BNC + 2 * 2304;
constexpr int BAR_FULL = 0, BAR_WEMPTY = NSTAGE, BAR_HW = BAR_WEMPTY + NS, BAR_XFREE = BAR_HW + 1, BAR_STATS = BAR_XFREE + 1,
              BAR_EMB = BAR_STATS + 1, BAR_ACK = BAR_EMB + 1, BAR_X = BAR_ACK + 1  , NBAR = BAR_X + 5;
constexpr int SM_TOTAL = SM_BAR + NBAR * 8 - SMEM_BASE;
static_assert(SM_TOTAL <= 232448, "smem");
static_assert(NBAR <= 96, "barrier init");
__host__ __device__ constexpr uint32_t BAR(int i) { return SM_BAR + 8 * i; }
__host__ __device__ constexpr int ky_of(int kyo) { return kyo == 0 ? 1 : (kyo == 1 ? 0 : 2); }

constexpr unsigned SPIN_LIMIT = 1u << 16;

#define LS 1056
#define GS1 4
#define PD 0
#define KS 1056
#define PW 8
struct Scratch {
    float acc1[NB * 4 * LS];
    float acc2[NB * LS];
    unsigned wcnt[3 * NB * LS];
    unsigned w1cnt[NB * 8 * KS];
    float emb[NXTRA * NB * C];
    unsigned char wt[2 * NSTAGE * STAGE_BYTES];
    uint4 box[NCTA * 1024];
};
__device__ __align__(1024) Scratch g_scratch;
#define TL(i) do {} while (0)
#define TLG(i) do {} while (0)

__device__ __forceinline__ unsigned clock32() { unsigned c; asm volatile("mov.u32 %0, %%clock;" : "=r"(c)); return c; }
__device__ __forceinline__ uint32_t mapa(uint32_t a, uint32_t rank) {
    uint32_t d;
    asm("mapa.shared::cluster.u32 %0, %1, %2;" : "=r"(d) : "r"(a), "r"(rank));
    return d;
}
#define S0 mapa(0, blockIdx.x & 1)
__device__ __forceinline__ void mbar_init(uint32_t bar, int cnt) {
    asm volatile("mbarrier.init.shared::cta.b64 [%0], %1;" ::"r"(bar + S0), "r"(cnt) : "memory");
}
__device__ __forceinline__ void mbar_arrive(uint32_t bar) {
    asm volatile("mbarrier.arrive.shared::cta.b64 _, [%0];" ::"r"(bar + S0) : "memory");
}
__device__ __forceinline__ void mbar_expect(uint32_t bar, uint32_t bytes) {
    asm volatile("mbarrier.arrive.expect_tx.shared::cta.b64 _, [%0], %1;" ::"r"(bar + S0), "r"(bytes) : "memory");
}
__device__ __forceinline__ bool mbar_try(uint32_t bar, uint32_t par) {
    uint32_t ok;
    asm volatile("{\n.reg .pred p;\nmbarrier.try_wait.parity.shared::cta.b64 p, [%1], %2;\nselp.u32 %0, 1, 0, p;\n}"
                 : "=r"(ok) : "r"(bar + S0), "r"(par) : "memory");
    return ok;
}
__device__ __forceinline__ bool mbar_test(uint32_t bar, uint32_t par) {
    uint32_t ok;
    asm volatile("{\n.reg .pred p;\nmbarrier.test_wait.parity.shared::cta.b64 p, [%1], %2;\nselp.u32 %0, 1, 0, p;\n}"
                 : "=r"(ok) : "r"(bar + S0), "r"(par) : "memory");
    return ok;
}
__device__ __forceinline__ void mbar_wait(uint32_t bar, uint32_t par) {
    unsigned it = 0;
#pragma unroll 1
    while (!mbar_try(bar, par) && ++it < SPIN_LIMIT) {}
}
__device__ __forceinline__ bool elect_one() {
    uint32_t p;
    asm volatile("{\n.reg .pred p;\nelect.sync _|p, 0xffffffff;\nselp.u32 %0, 1, 0, p;\n}" : "=r"(p));
    return p;
}
__device__ __forceinline__ void fence_async_smem() { asm volatile("fence.proxy.async.shared::cta;" ::: "memory"); }
__device__ __forceinline__ void fence_async_global() { asm volatile("fence.proxy.async.global;" ::: "memory"); }
__device__ __forceinline__ void fence_acquire() { asm volatile("fence.acquire.gpu;" ::: "memory"); }
__device__ __forceinline__ void bar_sync(int id, int n) { asm volatile("bar.sync %0, %1;" ::"r"(id), "r"(n) : "memory"); }
__device__ __forceinline__ void bar_arrive(int id, int n) { asm volatile("bar.arrive %0, %1;" ::"r"(id), "r"(n) : "memory"); }
__device__ __forceinline__ void bulk_g2s(uint32_t dst, const void* src, uint32_t bytes, uint32_t bar) {
    asm volatile("cp.async.bulk.shared::cluster.global.mbarrier::complete_tx::bytes [%0], [%1], %2, [%3];"
                 ::"r"(dst), "l"(src), "r"(bytes), "r"(bar) : "memory");
}
__device__ __forceinline__ void tma_x(uint32_t dst, const CUtensorMap* tm, int row, int ch, uint32_t bar) {
    asm volatile("cp.async.bulk.tensor.3d.shared::cluster.global.mbarrier::complete_tx::bytes [%0], [%1, {%2, %3, %4}], [%5];"
                 ::"r"(dst + S0), "l"(tm), "r"(0), "r"(row), "r"(ch), "r"(bar + S0) : "memory");
}
__device__ __forceinline__ uint4 ld_relaxed_v4(const void* p) {
    uint4 v;
    asm volatile("ld.relaxed.gpu.global.v4.u32 {%0,%1,%2,%3}, [%4];" : "=r"(v.x), "=r"(v.y), "=r"(v.z), "=r"(v.w) : "l"(p) : "memory");
    return v;
}
__device__ __forceinline__ unsigned ld_relaxed(const void* p) {
    unsigned v;
    asm volatile("ld.relaxed.gpu.global.u32 %0, [%1];" : "=r"(v) : "l"(p) : "memory");
    return v;
}
__device__ __forceinline__ void red_add4(float* p, float a, float b, float c, float d) {
    asm volatile("red.relaxed.gpu.global.add.v4.f32 [%0], {%1,%2,%3,%4};" ::"l"(p), "f"(a), "f"(b), "f"(c), "f"(d) : "memory");
}
__device__ __forceinline__ void sts128(uint32_t a, uint4 v) {
    asm volatile("st.shared.v4.u32 [%0], {%1,%2,%3,%4};" ::"r"(a + S0), "r"(v.x), "r"(v.y), "r"(v.z), "r"(v.w) : "memory");
}
__device__ __forceinline__ void sts128f(uint32_t a, float4 v) {
    asm volatile("st.shared.v4.f32 [%0], {%1,%2,%3,%4};" ::"r"(a + S0), "f"(v.x), "f"(v.y), "f"(v.z), "f"(v.w) : "memory");
}
__device__ __forceinline__ void sts32f(uint32_t a, float v) { asm volatile("st.shared.f32 [%0], %1;" ::"r"(a + S0), "f"(v) : "memory"); }
__device__ __forceinline__ uint4 lds128(uint32_t a) {
    uint4 v;
    asm volatile("ld.shared.v4.u32 {%0,%1,%2,%3}, [%4];" : "=r"(v.x), "=r"(v.y), "=r"(v.z), "=r"(v.w) : "r"(a + S0) : "memory");
    return v;
}
__device__ __forceinline__ float4 lds128f(uint32_t a) {
    float4 v;
    asm volatile("ld.shared.v4.f32 {%0,%1,%2,%3}, [%4];" : "=f"(v.x), "=f"(v.y), "=f"(v.z), "=f"(v.w) : "r"(a + S0) : "memory");
    return v;
}
__device__ __forceinline__ float2 lds64f(uint32_t a) {
    float2 v;
    asm volatile("ld.shared.v2.f32 {%0,%1}, [%2];" : "=f"(v.x), "=f"(v.y) : "r"(a + S0) : "memory");
    return v;
}
__device__ __forceinline__ float bf_lo(uint32_t u) { return __uint_as_float(u << 16); }
__device__ __forceinline__ float bf_hi(uint32_t u) { return __uint_as_float(u & 0xffff0000u); }
__device__ __forceinline__ uint32_t pack_bf(float lo, float hi) {
    uint32_t r;
    asm("cvt.rn.bf16x2.f32 %0, %1, %2;" : "=r"(r) : "f"(hi), "f"(lo));
    return r;
}
__device__ __forceinline__ float tanh_fast(float x) {
    float r;
    asm("tanh.approx.f32 %0, %1;" : "=f"(r) : "f"(x));
    return r;
}
__device__ __forceinline__ float silu_half(float h) { return fmaf(h, tanh_fast(h), h); }
__device__ __forceinline__ void ldsm4(uint32_t (&u)[4], uint32_t a) {
    asm volatile("ldmatrix.sync.aligned.m8n8.x4.shared.b16 {%0,%1,%2,%3}, [%4];"
                 : "=r"(u[0]), "=r"(u[1]), "=r"(u[2]), "=r"(u[3]) : "r"(a + S0) : "memory");
}
__device__ __forceinline__ void ldsm4t(uint32_t (&u)[4], uint32_t a) {
    asm volatile("ldmatrix.sync.aligned.m8n8.x4.trans.shared.b16 {%0,%1,%2,%3}, [%4];"
                 : "=r"(u[0]), "=r"(u[1]), "=r"(u[2]), "=r"(u[3]) : "r"(a + S0) : "memory");
}
__device__ __forceinline__ void stsm4(uint32_t a, uint32_t p0, uint32_t p1, uint32_t p2, uint32_t p3) {
    asm volatile("stmatrix.sync.aligned.m8n8.x4.shared.b16 [%0], {%1,%2,%3,%4};" ::"r"(a + S0), "r"(p0), "r"(p1), "r"(p2), "r"(p3) : "memory");
}
__device__ __forceinline__ void stsm4t(uint32_t a, uint32_t p0, uint32_t p1, uint32_t p2, uint32_t p3) {
    asm volatile("stmatrix.sync.aligned.m8n8.x4.trans.shared.b16 [%0], {%1,%2,%3,%4};" ::"r"(a + S0), "r"(p0), "r"(p1), "r"(p2), "r"(p3) : "memory");
}

#define R8(o) "+f"(d[o]), "+f"(d[o + 1]), "+f"(d[o + 2]), "+f"(d[o + 3]), "+f"(d[o + 4]), "+f"(d[o + 5]), "+f"(d[o + 6]), "+f"(d[o + 7])
template <uint32_t ALO, uint32_t BLO, uint64_t AHI = 8, uint64_t BHI = 48>
__device__ __forceinline__ void wgmma128(float (&d)[64]) {
    asm volatile(
        "wgmma.mma_async.sync.aligned.m64n128k16.f32.bf16.bf16 "
        "{%0,%1,%2,%3,%4,%5,%6,%7,%8,%9,%10,%11,%12,%13,%14,%15,%16,%17,%18,%19,%20,%21,%22,%23,%24,%25,%26,%27,%28,%29,%30,%31,"
        "%32,%33,%34,%35,%36,%37,%38,%39,%40,%41,%42,%43,%44,%45,%46,%47,%48,%49,%50,%51,%52,%53,%54,%55,%56,%57,%58,%59,%60,%61,%62,%63},"
        " %64, %65, 1, 1, 1, 0, 0;"
        : R8(0), R8(8), R8(16), R8(24), R8(32), R8(40), R8(48), R8(56)
        : "l"((AHI << 32) | ALO), "l"((BHI << 32) | BLO));
}
template <int S>
__device__ __forceinline__ void mma_stages(float (&d)[64], int conv, int tid, Scratch* gs) {
    constexpr uint32_t A = ((SM_ACT + S * 2 * CH_PITCH + 16) >> 4) | ((CH_PITCH >> 4) << 16);
    constexpr uint32_t B = (slot_addr(S % NS) >> 4) | (8u << 16);
    if (S == 0) {
        unsigned it = 0;
#pragma unroll 1
        while (!MMA0_WAIT(BAR(BAR_FULL), conv) && ++it < SPIN_LIMIT) {}
    }
    bool next_ok = true;
    constexpr uint32_t NEXT = S + 1 < NSTAGE ? BAR(BAR_FULL + S + 1) : BAR(BAR_EMB);
    const int npar = S + 1 < NSTAGE ? conv : 0;
    next_ok = mbar_test(NEXT, npar);
    if (S == 0 && tid == 0) TL(32 + conv * 24);
    asm volatile("wgmma.fence.sync.aligned;" ::: "memory");
    wgmma128<A, B>(d);
    wgmma128<A + 1, B + 16>(d);
    wgmma128<A + 2, B + 32>(d);
    asm volatile("wgmma.commit_group.sync.aligned;" ::: "memory");
    if (S >= LAG) {
        asm volatile("wgmma.wait_group.sync.aligned %0;" ::"n"(LAG) : "memory");
        if ((tid & 31) == 0) mbar_arrive(BAR(BAR_WEMPTY + (S + NS - LAG) % NS));
    }
    if (!next_ok) mbar_wait(NEXT, npar);
    if constexpr (S + 1 < NSTAGE) mma_stages<S + 1>(d, conv, tid, gs);
}

__device__ __forceinline__ void weight_load(uint4 (&t)[5], const __nv_bfloat16* w, int cta, int lane) {
    const char* base = reinterpret_cast<const char*>(w) + ((cta & 15) * 8 * C + (cta >> 4) * 16) * 18;
#pragma unroll
    for (int k = 0; k < 5; k++) {
        const int i = lane + 32 * k, row = (i * 57) >> 10;
        if (k < 4 || lane < 16) t[k] = __ldg(reinterpret_cast<const uint4*>(base + row * (C * 18 - 288) + i * 16));
    }
}
__device__ __forceinline__ void weight_block(uint32_t bounce, unsigned char* wt, int cta, int lane, bool readback, Scratch* gs) {
    unsigned char* dst = wt + (cta >> 4) * STAGE_BYTES + (cta & 15) * 768;
    if (lane < 16) {
        uint32_t v[36];
#pragma unroll
        for (int i = 0; i < 9; i++) {
            const uint4 q = lds128(bounce + (lane & 7) * 288 + (lane >> 3) * 144 + i * 16);
            v[4 * i] = q.x; v[4 * i + 1] = q.y; v[4 * i + 2] = q.z; v[4 * i + 3] = q.w;
        }
#pragma unroll
        for (int kyo = 0; kyo < 3; kyo++) {
#pragma unroll
            for (int kx = 0; kx < 3; kx++) {
                const int tap = ky_of(kyo) * 3 + kx;
                uint32_t o[4];
#pragma unroll
                for (int m = 0; m < 4; m++) {
                    const int i0 = 18 * m + tap, i1 = i0 + 9;
                    const uint32_t sel = ((i0 & 1) ? 0x32u : 0x10u) | ((i1 & 1) ? 0x7600u : 0x5400u);
                    o[m] = __byte_perm(v[i0 >> 1], v[i1 >> 1], sel);
                }
                *reinterpret_cast<uint4*>(dst + kyo * 8 * STAGE_BYTES + kx * 256 + lane * 16) = make_uint4(o[0], o[1], o[2], o[3]);
            }
        }
    }
    if (readback) {
        __syncwarp();
        unsigned acc = 0;
        if (lane < 24) {
#pragma unroll
            for (int i = 0; i < 3; i++) acc |= ld_relaxed(dst + i * 8 * STAGE_BYTES + lane * 32);
        }
        asm volatile("{\n.reg .pred p;\nsetp.eq.u32 p, %0, 0x9e3779b9;\n@p st.shared.u32 [%1], %0;\n}" ::"r"(acc), "r"(bounce + S0) : "memory");
    }
}
__device__ __forceinline__ uint32_t act2(uint32_t u, const float4& cf) {
    return pack_bf(silu_half(fmaf(bf_lo(u), cf.x, cf.z)), silu_half(fmaf(bf_hi(u), cf.y, cf.w)));
}
__device__ __forceinline__ void norm_unit(uint32_t (&u)[4], const float4& ca, const float4& cb) {
    u[0] = act2(u[0], ca); u[1] = act2(u[1], ca); u[2] = act2(u[2], cb); u[3] = act2(u[3], cb);
}
__device__ __forceinline__ void read_stats(uint32_t gst, float (&g)[8]) {
    asm volatile("ld.volatile.shared.v4.f32 {%0,%1,%2,%3}, [%4];" : "=f"(g[0]), "=f"(g[1]), "=f"(g[2]), "=f"(g[3]) : "r"(gst + S0) : "memory");
    asm volatile("ld.volatile.shared.v4.f32 {%0,%1,%2,%3}, [%4];" : "=f"(g[4]), "=f"(g[5]), "=f"(g[6]), "=f"(g[7]) : "r"(gst + 16 + S0) : "memory");
}
template <int T>
__device__ __forceinline__ void group_coefs(uint32_t gst, float (&g)[8], float4 (&cf)[8]) {
    unsigned it = 0;
    if (!__all_sync(0xffffffffu, g[2 * T] != 0.f)) {
        float rs0;
#pragma unroll 1
        do {
            SPINPAUSE;
            asm volatile("ld.volatile.shared.f32 %0, [%1];" : "=f"(rs0) : "r"(gst + 8 * T + S0) : "memory");
        } while (!__all_sync(0xffffffffu, rs0 != 0.f) && ++it < 8 * SPIN_LIMIT);
        read_stats(gst, g);
    }
    float4 &ca = cf[2 * T], &cb = cf[2 * T + 1];
    const float rs = g[2 * T], mr = g[2 * T + 1];
    ca.z = fmaf(-mr, ca.x, ca.z); ca.w = fmaf(-mr, ca.y, ca.w); ca.x *= rs; ca.y *= rs;
    cb.z = fmaf(-mr, cb.x, cb.z); cb.w = fmaf(-mr, cb.y, cb.w); cb.x *= rs; cb.y *= rs;
}
template <int FIRST, int N>
__device__ __forceinline__ void norm_block(uint32_t (&u)[4][4], float4 (&cf)[8], uint32_t act, uint32_t mask, uint32_t fbar, int lane) {
#pragma unroll
    for (int t = FIRST; t < FIRST + N; t++) {
        norm_unit(u[t], cf[2 * t], cf[2 * t + 1]);
        stsm4(act + t * 2 * KC_BYTES, u[t][0] & mask, u[t][1] & mask, u[t][2] & mask, u[t][3] & mask);
    }
    fence_async_smem();
    __syncwarp();
    if (lane < N) mbar_arrive(fbar + 16 * (FIRST + lane));
}
__device__ __forceinline__ void publish(uint32_t bar, int lane) {
    fence_async_smem();
    __syncwarp();
    if (lane == 0) mbar_arrive(bar);
}
template <int T>
__device__ __forceinline__ void next_unit(uint32_t (&u)[4][4], float4 (&cf)[8], uint32_t gst, float (&g)[8], uint32_t act, uint32_t fbar, int lane) {
    const bool have = __all_sync(0xffffffffu, g[2 * T] != 0.f);
    if (!have) publish(fbar + 16 * (T - 1), lane);
    group_coefs<T>(gst, g, cf);
    norm_unit(u[T], cf[2 * T], cf[2 * T + 1]);
    if (have) publish(fbar + 16 * (T - 1), lane);
    stsm4(act + T * 2 * KC_BYTES, u[T][0], u[T][1], u[T][2], u[T][3]);
}
__device__ __forceinline__ void stat_mma(float (&c)[4], uint32_t p, uint32_t q) {
    asm("mma.sync.aligned.m16n8k16.row.col.f32.bf16.bf16.f32 {%0,%1,%2,%3}, {%4,%5,%6,%5}, {%4,%6}, {%0,%1,%2,%3};"
        : "+f"(c[0]), "+f"(c[1]), "+f"(c[2]), "+f"(c[3]) : "r"(p), "r"(0x3f803f80u), "r"(q));
}
__device__ __forceinline__ void stat_store(const float (&c)[4], uint32_t dst, int lane) {
    const int g = lane >> 2, t = lane & 3;
    if (t == (g >> 1)) sts32f(dst + g * 4, (g & 1) ? c[1] : c[0]);
    if (g == 7) sts32f(dst + 32 + t * 4, c[2] + c[3]);
}
__device__ __forceinline__ float sum4(float4 v) { return (v.x + v.y) + (v.z + v.w); }
__device__ __forceinline__ void stat_publish(uint32_t src, float* acc, int lane, bool real) {
    const uint32_t a = src + (lane & 15) * 48;
    float q = sum4(lds128f(a)) + sum4(lds128f(a + 16)), sm = sum4(lds128f(a + 32));
    q += __shfl_xor_sync(0xffffffffu, q, 1); sm += __shfl_xor_sync(0xffffffffu, sm, 1);
    q += __shfl_xor_sync(0xffffffffu, q, 2); sm += __shfl_xor_sync(0xffffffffu, sm, 2);
    if (real && (lane & 19) == 0) red_add4(acc + lane, 1.f, sm, q, 1.f);
}
__device__ __forceinline__ void fence_acc(float (&d)[64]) {
#pragma unroll
    for (int i = 0; i < 64; i++) asm volatile("" : "+f"(d[i])::"memory");
}
__device__ __forceinline__ void ld_unit(uint32_t (&u)[4], const uint4* p) {
    asm volatile("ld.relaxed.gpu.global.v4.u32 {%0,%1,%2,%3}, [%4];" : "=r"(u[0]), "=r"(u[1]), "=r"(u[2]), "=r"(u[3]) : "l"(p) : "memory");
}

__device__ __noinline__ void side_jobs(const __nv_bfloat16* __restrict__ t_emb, const __nv_bfloat16* __restrict__ w_emb,
                                       const __nv_bfloat16* __restrict__ w2, Scratch* __restrict__ gs, unsigned clk0) {
    const int tid = threadIdx.x, warp = tid >> 5, lane = tid & 31, j = blockIdx.x;
    float tv = 0.f;
    if (lane < 24) tv = __bfloat162float(t_emb[(lane / 12) * E + j * 192 + warp * 12 + lane % 12]);
    if (tid == 0) {
        mbar_init(BAR(0), 1);
        mbar_expect(BAR(0), 192 * C * 2);
        fence_async_smem();
        while (clock32() - clk0 < SDELAY) {}
#pragma unroll
        for (int i = 0; i < 4; i++)
            asm volatile("cp.async.bulk.prefetch.L2.global [%0], 18432;" ::"l"(reinterpret_cast<const char*>(w2) + (j * 4 + i) * 18432) : "memory");
#pragma unroll
        for (int i = 0; i < 4; i++) bulk_g2s(S0 + SM_W + i * 12288, w_emb + (j * 192 + i * 48) * C, 12288, S0 + BAR(0));
    }
    if (j == 0 && tid < 32) gs->acc2[(tid >> 4) * LS + (tid & 15)] = 0.f;
    const float sv = silu_half(0.5f * tv);
    __syncthreads();
    mbar_wait(BAR(0), 0);
    float acc[8] = {0.f, 0.f, 0.f, 0.f, 0.f, 0.f, 0.f, 0.f};
#pragma unroll
    for (int i = 0; i < 12; i++) {
        const float2 wq = lds64f(SM_W + (warp * 12 + i) * 256 + lane * 8);
        const uint32_t wx = __float_as_uint(wq.x), wy = __float_as_uint(wq.y);
#pragma unroll
        for (int bb = 0; bb < 2; bb++) {
            const float sx = __shfl_sync(0xffffffffu, sv, bb * 12 + i);
            acc[4 * bb + 0] = fmaf(sx, bf_lo(wx), acc[4 * bb + 0]); acc[4 * bb + 1] = fmaf(sx, bf_hi(wx), acc[4 * bb + 1]);
            acc[4 * bb + 2] = fmaf(sx, bf_lo(wy), acc[4 * bb + 2]); acc[4 * bb + 3] = fmaf(sx, bf_hi(wy), acc[4 * bb + 3]);
        }
    }
    sts128f(SM_ACT + warp * 1024 + lane * 16, make_float4(acc[0], acc[1], acc[2], acc[3]));
    sts128f(SM_ACT + warp * 1024 + 512 + lane * 16, make_float4(acc[4], acc[5], acc[6], acc[7]));
    __syncthreads();
    if (tid < 128) {
        float2 sum = make_float2(0.f, 0.f);
#pragma unroll
        for (int w = 0; w < 16; w++) { const float2 p = lds64f(SM_ACT + w * 1024 + tid * 8); sum.x += p.x; sum.y += p.y; }
        *reinterpret_cast<float2*>(&gs->emb[j * NB * C + tid * 2]) = sum;
        bar_sync(1, 128);
        if (tid < 2) asm volatile("red.release.gpu.global.add.u32 [%0], 1;" ::"l"(&gs->wcnt[(2 * NB + tid) * LS]) : "memory");
    }
}

__global__ void __cluster_dims__(2, 1, 1) __launch_bounds__(NTHREADS, 1)
resblock_kernel(const __nv_bfloat16* __restrict__ w1, const __nv_bfloat16* __restrict__ x,
                const __nv_bfloat16* __restrict__ t_emb, const __nv_bfloat16* __restrict__ g1,
                const __nv_bfloat16* __restrict__ be1, const __nv_bfloat16* __restrict__ w_emb,
                const __nv_bfloat16* __restrict__ g2, const __nv_bfloat16* __restrict__ be2,
                const __nv_bfloat16* __restrict__ w2, __nv_bfloat16* __restrict__ out, Scratch* __restrict__ gs,
                const __grid_constant__ CUtensorMap xmap) {
    const unsigned clk0 = clock32();
    if (threadIdx.x == 480 && blockIdx.x >= NXTRA) TLG(1);
    const int tid = threadIdx.x, lane = tid & 31;
    const int cta = blockIdx.x - NXTRA, b = cta >> 6, r = cta & 63;
    uint4 v[5];
    if (tid < 32) weight_load(v, w1, cta & (NCTA - 1), lane);
    uint4 xv[8];
    const int wg4 = (tid >> 5) - 1;
    const bool early = tid >= 32 && wg4 < NLDG;
    if (early) {
        const char* src = reinterpret_cast<const char*>(x) + (uint32_t)((((b & 1) * C + wg4 * 32 + (lane >> 3)) * HW + r) * HW * 2 + (lane & 7) * 16);
        while (clock32() - clk0 < XDELAY + (wg4 >> 1) * XSTAG + (wg4 & 1) * XSTAG2) {}
#pragma unroll
        for (int i = 0; i < 8; i++) xv[i] = __ldg(reinterpret_cast<const uint4*>(src + i * (4 * HW * HW * 2)));
    }
    const int warp = __shfl_sync(0xffffffffu, tid >> 5, 0);
    if (cta < 0) { side_jobs(t_emb, w_emb, w2, gs, clk0); return; }

    if (warp != 4) asm volatile("barrier.cluster.arrive.relaxed.aligned;" ::: "memory");
    const bool has_outer = (r != 0) && (r != HW - 1);
    if (warp == 1 || warp == 2 || warp == 3 || warp == 5) {
        const int g = warp < 4 ? warp - 1 : 3;
        if (elect_one()) {
            if (g >= NLDG) asm volatile("prefetch.tensormap [%0];" ::"l"(&xmap) : "memory");
            mbar_init(BAR(BAR_X) + 8 * g, 1);
            if (g >= NLDG) mbar_expect(BAR(BAR_X) + 8 * g, 4096);
            fence_async_smem();
        }
        __syncwarp();
        bar_arrive(4, 256 + 32 + 128);
        if (g >= NLDG) {
            while (clock32() - clk0 < XDELAY + (g >> 1) * XSTAG + (g & 1) * XSTAG2) {}
            if (elect_one()) tma_x(SM_XOWN + g * 4096, &xmap, r, b * C + g * 32, BAR(BAR_X) + 8 * g);
            __syncwarp();
            mbar_wait(BAR(BAR_X) + 8 * g, 0);
#pragma unroll
            for (int k = 0; k < 8; k++) xv[k] = lds128(SM_XOWN + g * 4096 + k * 512 + lane * 16);
        }
        float c[8][4];
#pragma unroll
        for (int k = 0; k < 8; k++) {
            c[k][0] = c[k][1] = c[k][2] = c[k][3] = 0.f;
            stat_mma(c[k], xv[k].x, xv[k].y); stat_mma(c[k], xv[k].z, xv[k].w);
        }
#pragma unroll
        for (int i = 0; i < 4; i++) c[0][i] = ((c[0][i] + c[1][i]) + (c[2][i] + c[3][i])) + ((c[4][i] + c[5][i]) + (c[6][i] + c[7][i]));
        stat_store(c[0], SM_RED + g * 48, lane);
        __syncwarp();
        if (lane == 0) {
            const uint32_t a = SM_RED + g * 48;
            red_add4(&gs->acc1[b * 4 * LS + g * GS1], 1.f, sum4(lds128f(a + 32)), sum4(lds128f(a)) + sum4(lds128f(a + 16)), 1.f);
            TL(74 + g);
        }
        if (g < NLDG) {
#pragma unroll
            for (int i = 0; i < 8; i++)
                sts128(SM_XOWN + g * 4096 + i * 512 + (lane >> 3) * 128 + (((lane & 7) ^ ((lane >> 3) + 4 * (i & 1))) << 4), xv[i]);
            __syncwarp();
            if (lane == 0) mbar_arrive(BAR(BAR_X) + 8 * g);
        }
    }
    if (warp == 4) {
            if (elect_one()) {
#pragma unroll
                for (int i = 0; i < NSTAGE; i++) mbar_init(BAR(BAR_FULL + i), (i >> 3) == 1 ? 1 : 5);
#pragma unroll
                for (int i = 0; i < NS + 2; i++) mbar_init(BAR(BAR_WEMPTY + i), 4);
#pragma unroll
                for (int i = BAR_STATS; i < BAR_X; i++) mbar_init(BAR(i), i == BAR_EMB ? 3 : 1);
                mbar_init(BAR(BAR_X + 4), 1);
                asm volatile("fence.mbarrier_init.release.cluster;" ::: "memory");
            }
            if (lane < 4) sts128(SM_GST + lane * 16, make_uint4(0, 0, 0, 0));
            __syncwarp();
            fence_async_smem();
            bar_arrive(0, 96);
            bar_arrive(5, 64);
            bar_arrive(4, 256 + 32 + 128);
            const uint4 z = make_uint4(0, 0, 0, 0);
#pragma unroll
            for (int i = 0; i < 2; i++) sts128(SM_ACT + (i * 16 + (lane >> 1)) * CH_PITCH + (lane & 1) * 16, z);
            if (lane < 4) sts128(SM_ACT + (2 + (lane >> 1)) * ROW_BYTES + (lane & 1) * 16, z);
            if (lane < 16) sts128(SM_ONES + lane * 16, make_uint4(lane < 8 ? 0x3f803f80u : 0u, 0, 0, 0));
            fence_async_smem();
            bar_arrive(7, 160);
            asm volatile("barrier.cluster.arrive.relaxed.aligned;" ::: "memory");
            if (lane == 0) TL(5);
            while (clock32() - clk0 < W2DELAY) {}
            weight_load(v, w2, cta, lane);
        }
    if (warp == 0 || warp == 4) {
        const int k = warp >> 2;
#pragma unroll
        for (int i = 0; i < 5; i++)
            if (i < 4 || lane < 16) sts128(SM_BNC + k * 2304 + (lane + 32 * i) * 16, v[i]);
        if (lane == 0) TL(k ? 14 : 81);
        __syncwarp();
        weight_block(SM_BNC + k * 2304, gs->wt + k * NSTAGE * STAGE_BYTES, cta, lane, true, gs);
        __syncwarp();
        if (lane == 0) TL(k ? 13 : 4);
        if (lane < 2) asm volatile("red.relaxed.gpu.global.add.u32 [%0], 1;" ::"l"(k ? &gs->wcnt[(NB + lane) * LS] : &gs->w1cnt[(lane * 8 + (cta >> 4)) * KS]) : "memory");
    }

    if (warp >= 8) {
        const int nw = warp - 8;
        if (nw < 2) {
            const uint2 ga = __ldg(reinterpret_cast<const uint2*>(nw ? g2 : g1) + lane), bt = __ldg(reinterpret_cast<const uint2*>(nw ? be2 : be1) + lane);
            sts128f(SM_COEF + nw * 1024 + lane * 32, make_float4(0.5f * bf_lo(ga.x), 0.5f * bf_hi(ga.x), 0.5f * bf_lo(bt.x), 0.5f * bf_hi(bt.x)));
            sts128f(SM_COEF + nw * 1024 + lane * 32 + 16, make_float4(0.5f * bf_lo(ga.y), 0.5f * bf_hi(ga.y), 0.5f * bf_lo(bt.y), 0.5f * bf_hi(bt.y)));
        }
        bar_sync(4, 256 + 32 + 128);
        const int par = nw >> 2, wq = nw & 3;
        const uint32_t act_off = SM_ACT + (par * 2 + (lane >> 4)) * CH_PITCH + (2 + wq * 16 + (lane & 15)) * 16;
        const uint32_t stg_off = (par * 16 + (lane >> 4) * 8 + (lane & 7)) * 128 + (((2 * wq + ((lane >> 3) & 1)) ^ (lane & 7)) << 4);
        const uint32_t cfa = SM_COEF + par * 128 + (lane & 3) * 16;
        const uint32_t fbar = BAR(BAR_FULL) + 8 * par;
        uint4* inbox = gs->box + cta * 1024 + nw * 32 + lane;
#pragma unroll 1
        for (int conv = 0; conv < 2; conv++) {
            uint32_t u[4][4], w[4][4];
            float4 cf[8];
            if (conv == 0) {
#pragma unroll
                for (int i = 0; i < 4; i++) { mbar_wait(BAR(BAR_X + i), 0); ldsm4t(u[i], SM_XOWN + stg_off + i * 4096); }
            } else {
                mbar_wait(BAR(BAR_HW), 0);
#pragma unroll
                for (int i = 0; i < 4; i++) ldsm4(u[i], act_off + i * 2 * KC_BYTES);
            }
#pragma unroll
            for (int i = 0; i < 8; i++) cf[i] = lds128f(cfa + conv * 1024 + (i >> 1) * 256 + (i & 1) * 64);
            const uint32_t gst = SM_GST + conv * 32;
            float gv[8];
            read_stats(gst, gv);
            group_coefs<0>(gst, gv, cf);
            if (tid == 256) TL(22 + conv * 4);
            if (par) { const unsigned c1 = clock32(); while (clock32() - c1 < PDELAY) {} }
            norm_block<0, 1>(u, cf, act_off, ~0u, fbar, lane);
            if (tid == 256) TL(8 + conv * 8);
            group_coefs<1>(gst, gv, cf);
            norm_unit(u[1], cf[2], cf[3]);
            stsm4(act_off + 2 * KC_BYTES, u[1][0], u[1][1], u[1][2], u[1][3]);
            next_unit<2>(u, cf, gst, gv, act_off, fbar, lane);
            next_unit<3>(u, cf, gst, gv, act_off, fbar, lane);
            publish(fbar + 48, lane);
            if (tid == 256) TL(84 + conv);
            if (has_outer) {
                mbar_wait(BAR(BAR_X + 4), conv);
                if (conv == 0) {
#pragma unroll
                    for (int i = 0; i < 4; i++) ldsm4t(w[i], SM_XOUT + stg_off + i * 4096);
                } else {
#pragma unroll
                    for (int i = 0; i < 4; i++) {
                        const uint4 q = lds128(SM_XOWN + (tid - 256) * 16 + i * 4096);
                        w[i][0] = q.x; w[i][1] = q.y; w[i][2] = q.z; w[i][3] = q.w;
                    }
                    unsigned it = 0;
                    while (true) {
                        bool ok = true;
#pragma unroll
                        for (int i = 0; i < 16; i++) ok = ok && w[i >> 2][i & 3] != 0;
                        if (__all_sync(0xffffffffu, ok) || ++it > SPIN_LIMIT) break;
#pragma unroll
                        for (int i = 0; i < 4; i++) ld_unit(w[i], inbox + i * 256);
                    }
#pragma unroll
                    for (int i = 0; i < 16; i++) w[i >> 2][i & 3] = ~w[i >> 2][i & 3];
                }
            }
            if (conv == 0) {
                bar_sync(3, 256);
                if (nw == 0) sts128(SM_ACT + 2 * ROW_BYTES + (lane >> 1) * CH_PITCH + (lane & 1) * 16, make_uint4(0, 0, 0, 0));
            }
            if (tid == 256) TL(24 + conv * 4);
            norm_block<0, 2>(w, cf, act_off + 2 * ROW_BYTES, has_outer ? ~0u : 0u, fbar + 128, lane);
            if (tid == 256) TL(88 + conv);
            norm_block<2, 2>(w, cf, act_off + 2 * ROW_BYTES, has_outer ? ~0u : 0u, fbar + 128, lane);
            if (tid == 256) TL(23 + conv * 4);
        }
        if (has_outer) {
            mbar_wait(BAR(BAR_FULL + NSTAGE - 1), 1);
#pragma unroll
            for (int i = 0; i < 4; i++) inbox[i * 256] = make_uint4(0, 0, 0, 0);
        }
        {
            const int oc0 = (tid - 256) >> 3, seg = lane & 7;
            __nv_bfloat16* dst = out + ((size_t)(b * C + oc0) * HW + r) * HW + seg * 8;
            const uint32_t src = SM_XOWN + oc0 * 128 + ((seg ^ (oc0 & 7)) << 4);
            bar_sync(6, 128 + 256);
#pragma unroll
            for (int i = 0; i < 4; i++) *reinterpret_cast<uint4*>(dst + (size_t)i * 32 * HW * HW) = lds128(src + i * 4096);
            if (tid == 256) { TL(20); TLG(21); }
        }
    } else if (warp < 4) {
        const int wq = warp;
        bar_sync(7, 160);

        const uint32_t xbase = SM_XOWN + ((lane >> 4) * 8 + (lane & 7)) * 128 + (((2 * wq + ((lane >> 3) & 1)) ^ (lane & 7)) << 4);
        float d[64];
#pragma unroll
        for (int i = 0; i < 64; i++) d[i] = 0.f;
#pragma unroll 1
        for (int conv = 0; conv < 2; conv++) {
            fence_acc(d);
            mma_stages<0>(d, conv, tid, gs);
            if (conv == 0) {
                asm volatile("wgmma.fence.sync.aligned;" ::: "memory");
                wgmma128<(SM_ONES >> 4) | (8u << 16), (SM_EMB >> 4), 0, 8>(d);
                asm volatile("wgmma.commit_group.sync.aligned;" ::: "memory");
            }
            asm volatile("wgmma.wait_group.sync.aligned 0;" ::: "memory");
            fence_acc(d);
            if (tid == 0) TL(10 + conv * 8);
            uint32_t hp[32];
#pragma unroll
            for (int i = 0; i < 32; i++) hp[i] = pack_bf(d[2 * i], d[2 * i + 1]);
            if (conv == 1) {
#pragma unroll
                for (int kc = 0; kc < 8; kc++) stsm4t(xbase + kc * 2048, hp[4 * kc], hp[4 * kc + 1], hp[4 * kc + 2], hp[4 * kc + 3]);
                bar_arrive(6, 128 + 256);
                break;
            }
#pragma unroll
            for (int g = 0; g < 4; g++) {
                float c[4] = {0.f, 0.f, 0.f, 0.f};
#pragma unroll
                for (int i = 0; i < 4; i++) stat_mma(c, hp[8 * g + 2 * i], hp[8 * g + 2 * i + 1]);
                stat_store(c, SM_RED + (g * 4 + wq) * 48, lane);
            }
            bar_sync(2, 128);
            if (wq == 0) stat_publish(SM_RED, &gs->acc2[b * LS], lane, true);
            if (tid == 0) TL(11);
            const uint32_t hbase = SM_ACT + (lane >> 4) * CH_PITCH + (2 + wq * 16 + (lane & 15)) * 16;
#pragma unroll
            for (int kc = 0; kc < 8; kc++) stsm4(hbase + kc * 2 * CH_PITCH, hp[4 * kc], hp[4 * kc + 1], hp[4 * kc + 2], hp[4 * kc + 3]);
            __syncwarp();
            if (lane == 0) mbar_arrive(BAR(BAR_HW));
            if (lane < LAG) mbar_arrive(BAR(BAR_WEMPTY + (NSTAGE - LAG) % NS) + 8 * lane);
            if (has_outer) {
                uint4* outbox = gs->box + (cta + ((r & 1) ? 1 : -1)) * 1024 + tid;
#pragma unroll
                for (int kc = 0; kc < 8; kc++) outbox[kc * 128] = make_uint4(~hp[4 * kc], ~hp[4 * kc + 1], ~hp[4 * kc + 2], ~hp[4 * kc + 3]);
            }
            if (tid == 0) TL(12);
#pragma unroll
            for (int kc = 0; kc < 8; kc++) {
                uint32_t p[4];
                ldsm4t(p, xbase + kc * 2048);
#pragma unroll
                for (int i = 0; i < 4; i++) { d[8 * kc + 2 * i] = bf_lo(p[i]); d[8 * kc + 2 * i + 1] = bf_hi(p[i]); }
            }
            fence_async_smem();
            __syncwarp();
            if (lane == 0) mbar_arrive(BAR(BAR_XFREE));
        }
        {
        }
    } else if (warp < 6) {
        if (warp == 5) {
            bar_sync(5, 64);
            mbar_wait(BAR(BAR_FULL + OAFTER), 0);
            if (has_outer && elect_one()) {
                mbar_expect(BAR(BAR_X + 4), 16384);
#pragma unroll
                for (int i = 0; i < 4; i++) tma_x(SM_XOUT + i * 4096, &xmap, r + ((r & 1) ? 1 : -1), b * C + i * 32, BAR(BAR_X + 4));
            }
            __syncwarp();
            asm volatile("barrier.cluster.wait.acquire.aligned;" ::: "memory");
            const uint32_t peer = (r & 1) ^ 1;
            const uint32_t self0 = mapa(0, r & 1), peer0 = mapa(0, peer);
#pragma unroll 1
            for (int conv = 0; conv < 2; conv++) {
#pragma unroll 1
                for (int kc = 0; kc < 8; kc++) {
                    mbar_wait(BAR(BAR_FULL) + 8 * kc, conv);
                    if (elect_one())
                        asm volatile("cp.async.bulk.shared::cluster.shared::cta.mbarrier::complete_tx::bytes [%0], [%1], %2, [%3];"
                                     ::"r"(peer0 + SM_ACT + ROW_BYTES + kc * KC_BYTES), "r"(self0 + SM_ACT + kc * KC_BYTES), "r"(KC_BYTES),
                                       "r"(peer0 + BAR(BAR_FULL + 8) + 8 * kc) : "memory");
                }
                if (lane == 0) TL(86 + conv);
#pragma unroll 1
                for (int kc = 0; kc < 8; kc++) mbar_wait(BAR(BAR_FULL + 8) + 8 * kc, conv);
                if (lane == 0)
                    asm volatile("mbarrier.arrive.release.cluster.shared::cluster.b64 _, [%0];" ::"r"(peer0 + (conv ? BAR(BAR_ACK) : BAR(BAR_EMB))) : "memory");
            }
            mbar_wait(BAR(BAR_ACK), 0);
        } else {
            mbar_wait(BAR(BAR_STATS), 0);
            unsigned it = 0;
            while (ld_relaxed(&gs->wcnt[(2 * NB + b) * LS]) < (unsigned)NXTRA && ++it < SPIN_LIMIT) __nanosleep(100);
            fence_acquire();
            float ev[4] = {0.f, 0.f, 0.f, 0.f};
#pragma unroll
            for (int j = 0; j < NXTRA; j++) {
                const uint4 ef = ld_relaxed_v4(&gs->emb[(j * NB + b) * C + lane * 4]);
                ev[0] += __uint_as_float(ef.x); ev[1] += __uint_as_float(ef.y); ev[2] += __uint_as_float(ef.z); ev[3] += __uint_as_float(ef.w);
            }
#pragma unroll
            for (int i = 0; i < 4; i++) {
                const float hi = bf_lo(pack_bf(ev[i], 0.f));
                sts128(SM_EMB + (lane * 4 + i) * 16, make_uint4(pack_bf(hi, ev[i] - hi), 0, 0, 0));
            }
            fence_async_smem();
            __syncwarp();
            if (lane == 0) { mbar_arrive(BAR(BAR_EMB)); TL(19); }
        }
    } else if (warp == 6) {
        bar_sync(0, 96);
        const uint32_t ebytes = STAGE_BYTES + ((lane >> 3) == 1 ? KC_BYTES : 0);
        if (lane < NSTAGE) mbar_expect(BAR(BAR_FULL) + 8 * lane, ebytes);
        const int swap = (r & 1) ? 0 : 8 * STAGE_BYTES;
        unsigned it = 0;
        {
            int g = 0;
#pragma unroll 1
            while (g < NS) {
                const int pk = min(g + (lane & (PW - 1)), 7);
                unsigned ready = g >= 8 ? ~0u : __ballot_sync(0xffffffffu, ld_relaxed(&gs->w1cnt[(b * 8 + pk) * KS]) >= 16u) & ((1u << PW) - 1);
                if (++it > SPIN_LIMIT) ready = ~0u;
                if (!(ready & 1)) continue;
                fence_acquire();
                fence_async_global();
                if (lane == 0) TL(g ? 3 : 6);
#pragma unroll 1
                for (; (ready & 1) && g < NS; g++, ready >>= 1)
                    if (elect_one())
                        bulk_g2s(S0 + SM_W + g * STAGE_BYTES, gs->wt + g * STAGE_BYTES + (g >= 8 ? swap : 0), STAGE_BYTES, S0 + BAR(BAR_FULL) + 8 * g);
            }
        }
#pragma unroll 1
        for (int q = 3; q < 12; q++) {
            const int conv = q >= 6, qs = conv ? q - 6 : q, sl = q % 3;
            const unsigned char* wsrc = gs->wt + q * 4 * STAGE_BYTES + (qs < 2 ? 0 : (qs < 4 ? swap : -swap));
            const uint32_t par = (q / 3 - 1) & 1;
            if (q == 6) {
                it = 0;
                while (ld_relaxed(&gs->wcnt[(NB + b) * LS]) < (unsigned)NCTA && ++it < SPIN_LIMIT) {}
                fence_acquire();
                fence_async_global();
                if (lane == 0) { mbar_arrive(BAR(BAR_EMB)); TL(2); }
            }
#pragma unroll
            for (int i = 0; i < 4; i++) {
                mbar_wait(BAR(BAR_WEMPTY + i) + 32 * sl, par);
                if (i == 0 && (q == 6 || q == 9)) {
                    if ((lane >= NS) == (q == 9) && lane < NSTAGE) mbar_expect(BAR(BAR_FULL) + 8 * lane, ebytes);
                    __syncwarp();
                }
                if (elect_one())
                    bulk_g2s(S0 + SM_W + (sl * 4 + i) * STAGE_BYTES, wsrc + i * STAGE_BYTES, STAGE_BYTES, S0 + BAR(BAR_FULL + i) + 32 * qs);
            }
        }
    } else {
        bar_sync(0, 96);
#pragma unroll 1
        for (int conv = 0; conv < 2; conv++) {
            if (conv == 1) {
                mbar_wait(BAR(BAR_HW), 0);
                const unsigned c1 = clock32();
                while (clock32() - c1 < PD2) {}
            } else {
                while (clock32() - clk0 < PD) {}
            }
            const float* asrc = conv ? &gs->acc2[b * LS + (lane & 3) * 4] : &gs->acc1[b * 4 * LS + (lane & 3) * GS1];
            unsigned it = 0;
            uint4 fq[NPOLL];
#pragma unroll
            for (int i = 0; i < NPOLL; i++) {
                fq[i] = ld_relaxed_v4(asrc);
                if (i + 1 < NPOLL) { const unsigned c1 = clock32(); while (clock32() - c1 < 450 / NPOLL) {} }
            }
            bool all = false;
#pragma unroll 1
            while (!all) {
#pragma unroll
                for (int i = 0; i < NPOLL; i++) {
                    const uint4 f = fq[i];
                    const bool ok = ((f.x == 0x42800000u) & (f.w == 0x42800000u)) || it > SPIN_LIMIT;
                    if (ok && lane < 4) {
                        const float inv_n = 1.0f / (32.0f * HW * HW);
                        const float mean = __uint_as_float(f.y) * inv_n;
                        const float rs = rsqrtf(fmaxf(fmaf(-mean, mean, __uint_as_float(f.z) * inv_n), 0.f) + 1e-5f);
                        asm volatile("st.shared.v2.f32 [%0], {%1,%2};" ::"r"(S0 + SM_GST + conv * 32 + lane * 8), "f"(rs == 0.f ? 1e-38f : rs), "f"(mean * rs) : "memory");
                    }
                    if (__all_sync(0xffffffffu, ok)) { all = true; break; }
                    fq[i] = ld_relaxed_v4(asrc);
                }
                it++;
            }
            if (lane == 0) { mbar_arrive(BAR(BAR_STATS)); TL(7 + conv * 8); }
        }
        mbar_wait(BAR(BAR_XFREE), 0);
        if (has_outer && elect_one()) {
            mbar_expect(BAR(BAR_X + 4), 16384);
            bulk_g2s(S0 + SM_XOWN, gs->box + cta * 1024, 16384, S0 + BAR(BAR_X + 4));
        }
        if (r == 0) {
            if (lane < 16) gs->acc1[b * 4 * LS + (lane >> 2) * GS1 + (lane & 3)] = 0.f;
            if (lane < 3) gs->wcnt[(lane * NB + b) * LS] = 0;
            if (lane < 8) gs->w1cnt[(b * 8 + lane) * KS] = 0;
        }
    }
}

}

extern "C" void kernel_launch(void* const* d_in, const int* in_sizes, int n_in, void* d_out, int out_size) {
    (void)in_sizes; (void)n_in; (void)out_size;
    typedef CUresult (*EncodeFn)(CUtensorMap*, CUtensorMapDataType, cuuint32_t, void*, const cuuint64_t*, const cuuint64_t*,
                                 const cuuint32_t*, const cuuint32_t*, CUtensorMapInterleave, CUtensorMapSwizzle,
                                 CUtensorMapL2promotion, CUtensorMapFloatOOBfill);
    static Scratch* gs = nullptr;
    static EncodeFn encode = nullptr;
    if (!gs) {
        cudaFuncSetAttribute(resblock_kernel, cudaFuncAttributeMaxDynamicSharedMemorySize, SM_TOTAL);
        cudaGetSymbolAddress((void**)&gs, g_scratch);
        cudaDriverEntryPointQueryResult qr;
        cudaGetDriverEntryPoint("cuTensorMapEncodeTiled", (void**)&encode, cudaEnableDefault, &qr);
    }
    CUtensorMap xmap;
    const cuuint64_t dims[3] = {HW, HW, NB * C}, strides[2] = {HW * 2, HW * HW * 2};
    const cuuint32_t box[3] = {HW, 1, 32}, es[3] = {1, 1, 1};
    encode(&xmap, CU_TENSOR_MAP_DATA_TYPE_BFLOAT16, 3, d_in[0], dims, strides, box, es, CU_TENSOR_MAP_INTERLEAVE_NONE,
           CU_TENSOR_MAP_SWIZZLE_128B, CU_TENSOR_MAP_L2_PROMOTION_NONE, CU_TENSOR_MAP_FLOAT_OOB_FILL_NONE);
    resblock_kernel<<<NCTA + NXTRA, NTHREADS, SM_TOTAL>>>(
        (const __nv_bfloat16*)d_in[4], (const __nv_bfloat16*)d_in[0], (const __nv_bfloat16*)d_in[1],
        (const __nv_bfloat16*)d_in[2], (const __nv_bfloat16*)d_in[3], (const __nv_bfloat16*)d_in[5],
        (const __nv_bfloat16*)d_in[6], (const __nv_bfloat16*)d_in[7], (const __nv_bfloat16*)d_in[8],
        (__nv_bfloat16*)d_out, gs, xmap);
}
```

```cpp
#include <cuda_runtime.h>
#include <cuda.h>
#include <cuda_bf16.h>
#include <stdint.h>

namespace {

constexpr int C = 128, HW = 64, NB = 2, E = 768;
constexpr int NCTA = NB * HW;
constexpr int NXTRA = 4;
constexpr int NTHREADS = 16 * 32;
constexpr int CH_PITCH = 66 * 16;
constexpr int ROW_BYTES = 16 * CH_PITCH;
constexpr int STEP_BYTES = 4096;
constexpr int STAGE_BYTES = 3 * STEP_BYTES;
constexpr int NSTAGE = 24;
constexpr int KC_BYTES = 2 * CH_PITCH;
constexpr int NS = 12;
constexpr int LAG = 1;
#define XDELAY 400
#define HDELAY 600
#define SEQ 0
#define MMA0_WAIT mbar_try
#define SPINPAUSE
#define NPOLL 1
#define PD2 0
#define ODELAY 100
#define NLDG 2
#define PSTAG -1
#define PDELAY0 400
#define PDELAY 60
#define RB 1
#define XSTAG2 400
#define XSTAG 800
#define HSEND 0
#define SDELAY 600
#define OAFTER 0
#define W2DELAY 2400

constexpr uint32_t SMEM_BASE = 0x400;
constexpr uint32_t SM_XOWN = SMEM_BASE;
constexpr uint32_t SM_ACT = SM_XOWN + 16384 + 512;
constexpr uint32_t SM_XOUT = SM_ACT + 2 * ROW_BYTES + 512;
static_assert(SM_XOUT % 1024 == 0, "swizzle atom alignment");
constexpr uint32_t SM_W = SM_ACT + 3 * ROW_BYTES + 128;
__host__ __device__ constexpr uint32_t slot_addr(int slot) { return SM_W + slot * STAGE_BYTES; }
constexpr uint32_t SM_COEF = SM_W + NS * STAGE_BYTES;
constexpr uint32_t SM_GST = SM_COEF + 2048;
constexpr uint32_t SM_EMB = SM_GST + 128;
constexpr uint32_t SM_ONES = SM_EMB + 2048;
constexpr uint32_t SM_RED = SM_ONES + 256;
constexpr uint32_t SM_BNC = SM_RED + 1536;
constexpr uint32_t SM_BAR = SM_BNC + 2 * 2304;
constexpr int BAR_FULL = 0, BAR_WEMPTY = NSTAGE, BAR_HW = BAR_WEMPTY + NS, BAR_XFREE = BAR_HW + 1, BAR_STATS = BAR_XFREE + 1,
              BAR_EMB = BAR_STATS + 1, BAR_ACK = BAR_EMB + 1, BAR_X = BAR_ACK + 1  , NBAR = BAR_X + 5;
constexpr int SM_TOTAL = SM_BAR + NBAR * 8 - SMEM_BASE;
static_assert(SM_TOTAL <= 232448, "smem");
static_assert(NBAR <= 96, "barrier init");
__host__ __device__ constexpr uint32_t BAR(int i) { return SM_BAR + 8 * i; }
__host__ __device__ constexpr int ky_of(int kyo) { return kyo == 0 ? 1 : (kyo == 1 ? 0 : 2); }

constexpr unsigned SPIN_LIMIT = 1u << 16;

#define LS 1056
#define GS1 4
#define PD 0
#define PDW 0
#define SHARE 8
#define KS 32
#define PW 8
struct Scratch {
    float acc1[NB * LS];
    float acc2[NB * LS];
    unsigned wcnt[3 * NB * LS];
    unsigned w1cnt[NB * 8 * KS];
    float emb[NXTRA * NB * C];
    alignas(1024) unsigned char wt[2 * NSTAGE * STAGE_BYTES];
    uint4 box[NCTA * 1024];
};
__device__ __align__(1024) Scratch g_scratch;
#define TL(i) do {} while (0)
#define TLG(i) do {} while (0)

__device__ __forceinline__ unsigned clock32() { unsigned c; asm volatile("mov.u32 %0, %%clock;" : "=r"(c)); return c; }
__device__ __forceinline__ uint32_t mapa(uint32_t a, uint32_t rank) {
    uint32_t d;
    asm("mapa.shared::cluster.u32 %0, %1, %2;" : "=r"(d) : "r"(a), "r"(rank));
    return d;
}
#define S0 mapa(0, blockIdx.x & 1)
__device__ __forceinline__ void mbar_init(uint32_t bar, int cnt) {
    asm volatile("mbarrier.init.shared::cta.b64 [%0], %1;" ::"r"(bar + S0), "r"(cnt) : "memory");
}
__device__ __forceinline__ void mbar_arrive(uint32_t bar) {
    asm volatile("mbarrier.arrive.shared::cta.b64 _, [%0];" ::"r"(bar + S0) : "memory");
}
__device__ __forceinline__ void mbar_expect(uint32_t bar, uint32_t bytes) {
    asm volatile("mbarrier.arrive.expect_tx.shared::cta.b64 _, [%0], %1;" ::"r"(bar + S0), "r"(bytes) : "memory");
}
__device__ __forceinline__ bool mbar_try(uint32_t bar, uint32_t par) {
    uint32_t ok;
    asm volatile("{\n.reg .pred p;\nmbarrier.try_wait.parity.shared::cta.b64 p, [%1], %2;\nselp.u32 %0, 1, 0, p;\n}"
                 : "=r"(ok) : "r"(bar + S0), "r"(par) : "memory");
    return ok;
}
__device__ __forceinline__ bool mbar_test(uint32_t bar, uint32_t par) {
    uint32_t ok;
    asm volatile("{\n.reg .pred p;\nmbarrier.test_wait.parity.shared::cta.b64 p, [%1], %2;\nselp.u32 %0, 1, 0, p;\n}"
                 : "=r"(ok) : "r"(bar + S0), "r"(par) : "memory");
    return ok;
}
__device__ __forceinline__ void mbar_wait(uint32_t bar, uint32_t par) {
    unsigned it = 0;
#pragma unroll 1
    while (!mbar_try(bar, par) && ++it < SPIN_LIMIT) {}
}
__device__ __forceinline__ bool elect_one() {
    uint32_t p;
    asm volatile("{\n.reg .pred p;\nelect.sync _|p, 0xffffffff;\nselp.u32 %0, 1, 0, p;\n}" : "=r"(p));
    return p;
}
__device__ __forceinline__ void fence_async_smem() { asm volatile("fence.proxy.async.shared::cta;" ::: "memory"); }
__device__ __forceinline__ void fence_async_global() { asm volatile("fence.proxy.async.global;" ::: "memory"); }
__device__ __forceinline__ void fence_acquire() { asm volatile("fence.acquire.gpu;" ::: "memory"); }
__device__ __forceinline__ void bar_sync(int id, int n) { asm volatile("bar.sync %0, %1;" ::"r"(id), "r"(n) : "memory"); }
__device__ __forceinline__ void bar_arrive(int id, int n) { asm volatile("bar.arrive %0, %1;" ::"r"(id), "r"(n) : "memory"); }
__device__ __forceinline__ void bulk_g2s(uint32_t dst, const void* src, uint32_t bytes, uint32_t bar) {
    asm volatile("cp.async.bulk.shared::cluster.global.mbarrier::complete_tx::bytes [%0], [%1], %2, [%3];"
                 ::"r"(dst), "l"(src), "r"(bytes), "r"(bar) : "memory");
}
__device__ __forceinline__ void tma_x(uint32_t dst, const CUtensorMap* tm, int row, int ch, uint32_t bar) {
    asm volatile("cp.async.bulk.tensor.3d.shared::cluster.global.mbarrier::complete_tx::bytes [%0], [%1, {%2, %3, %4}], [%5];"
                 ::"r"(dst + S0), "l"(tm), "r"(0), "r"(row), "r"(ch), "r"(bar + S0) : "memory");
}
__device__ __forceinline__ uint4 ld_relaxed_v4(const void* p) {
    uint4 v;
    asm volatile("ld.relaxed.gpu.global.v4.u32 {%0,%1,%2,%3}, [%4];" : "=r"(v.x), "=r"(v.y), "=r"(v.z), "=r"(v.w) : "l"(p) : "memory");
    return v;
}
__device__ __forceinline__ unsigned ld_relaxed(const void* p) {
    unsigned v;
    asm volatile("ld.relaxed.gpu.global.u32 %0, [%1];" : "=r"(v) : "l"(p) : "memory");
    return v;
}
__device__ __forceinline__ void red_add4(float* p, float a, float b, float c, float d) {
    asm volatile("red.relaxed.gpu.global.add.v4.f32 [%0], {%1,%2,%3,%4};" ::"l"(p), "f"(a), "f"(b), "f"(c), "f"(d) : "memory");
}
__device__ __forceinline__ void sts128(uint32_t a, uint4 v) {
    asm volatile("st.shared.v4.u32 [%0], {%1,%2,%3,%4};" ::"r"(a + S0), "r"(v.x), "r"(v.y), "r"(v.z), "r"(v.w) : "memory");
}
__device__ __forceinline__ void sts128f(uint32_t a, float4 v) {
    asm volatile("st.shared.v4.f32 [%0], {%1,%2,%3,%4};" ::"r"(a + S0), "f"(v.x), "f"(v.y), "f"(v.z), "f"(v.w) : "memory");
}
__device__ __forceinline__ void sts32f(uint32_t a, float v) { asm volatile("st.shared.f32 [%0], %1;" ::"r"(a + S0), "f"(v) : "memory"); }
__device__ __forceinline__ uint4 lds128(uint32_t a) {
    uint4 v;
    asm volatile("ld.shared.v4.u32 {%0,%1,%2,%3}, [%4];" : "=r"(v.x), "=r"(v.y), "=r"(v.z), "=r"(v.w) : "r"(a + S0) : "memory");
    return v;
}
__device__ __forceinline__ float4 lds128f(uint32_t a) {
    float4 v;
    asm volatile("ld.shared.v4.f32 {%0,%1,%2,%3}, [%4];" : "=f"(v.x), "=f"(v.y), "=f"(v.z), "=f"(v.w) : "r"(a + S0) : "memory");
    return v;
}
__device__ __forceinline__ float2 lds64f(uint32_t a) {
    float2 v;
    asm volatile("ld.shared.v2.f32 {%0,%1}, [%2];" : "=f"(v.x), "=f"(v.y) : "r"(a + S0) : "memory");
    return v;
}
__device__ __forceinline__ float bf_lo(uint32_t u) { return __uint_as_float(u << 16); }
__device__ __forceinline__ float bf_hi(uint32_t u) { return __uint_as_float(u & 0xffff0000u); }
__device__ __forceinline__ uint32_t pack_bf(float lo, float hi) {
    uint32_t r;
    asm("cvt.rn.bf16x2.f32 %0, %1, %2;" : "=r"(r) : "f"(hi), "f"(lo));
    return r;
}
__device__ __forceinline__ float tanh_fast(float x) {
    float r;
    asm("tanh.approx.f32 %0, %1;" : "=f"(r) : "f"(x));
    return r;
}
__device__ __forceinline__ float silu_half(float h) { return fmaf(h, tanh_fast(h), h); }
__device__ __forceinline__ void ldsm4(uint32_t (&u)[4], uint32_t a) {
    asm volatile("ldmatrix.sync.aligned.m8n8.x4.shared.b16 {%0,%1,%2,%3}, [%4];"
                 : "=r"(u[0]), "=r"(u[1]), "=r"(u[2]), "=r"(u[3]) : "r"(a + S0) : "memory");
}
__device__ __forceinline__ void ldsm4t(uint32_t (&u)[4], uint32_t a) {
    asm volatile("ldmatrix.sync.aligned.m8n8.x4.trans.shared.b16 {%0,%1,%2,%3}, [%4];"
                 : "=r"(u[0]), "=r"(u[1]), "=r"(u[2]), "=r"(u[3]) : "r"(a + S0) : "memory");
}
__device__ __forceinline__ void stsm4(uint32_t a, uint32_t p0, uint32_t p1, uint32_t p2, uint32_t p3) {
    asm volatile("stmatrix.sync.aligned.m8n8.x4.shared.b16 [%0], {%1,%2,%3,%4};" ::"r"(a + S0), "r"(p0), "r"(p1), "r"(p2), "r"(p3) : "memory");
}
__device__ __forceinline__ void stsm4t(uint32_t a, uint32_t p0, uint32_t p1, uint32_t p2, uint32_t p3) {
    asm volatile("stmatrix.sync.aligned.m8n8.x4.trans.shared.b16 [%0], {%1,%2,%3,%4};" ::"r"(a + S0), "r"(p0), "r"(p1), "r"(p2), "r"(p3) : "memory");
}

#define R8(o) "+f"(d[o]), "+f"(d[o + 1]), "+f"(d[o + 2]), "+f"(d[o + 3]), "+f"(d[o + 4]), "+f"(d[o + 5]), "+f"(d[o + 6]), "+f"(d[o + 7])
template <uint32_t ALO, uint32_t BLO, uint64_t AHI = 8, uint64_t BHI = 48>
__device__ __forceinline__ void wgmma128(float (&d)[64]) {
    asm volatile(
        "wgmma.mma_async.sync.aligned.m64n128k16.f32.bf16.bf16 "
        "{%0,%1,%2,%3,%4,%5,%6,%7,%8,%9,%10,%11,%12,%13,%14,%15,%16,%17,%18,%19,%20,%21,%22,%23,%24,%25,%26,%27,%28,%29,%30,%31,"
        "%32,%33,%34,%35,%36,%37,%38,%39,%40,%41,%42,%43,%44,%45,%46,%47,%48,%49,%50,%51,%52,%53,%54,%55,%56,%57,%58,%59,%60,%61,%62,%63},"
        " %64, %65, 1, 1, 1, 0, 0;"
        : R8(0), R8(8), R8(16), R8(24), R8(32), R8(40), R8(48), R8(56)
        : "l"((AHI << 32) | ALO), "l"((BHI << 32) | BLO));
}
template <int S>
__device__ __forceinline__ void mma_stages(float (&d)[64], int conv, int tid, Scratch* gs) {
    constexpr uint32_t A = ((SM_ACT + S * 2 * CH_PITCH + 16) >> 4) | ((CH_PITCH >> 4) << 16);
    constexpr uint32_t B = (slot_addr(S % NS) >> 4) | (8u << 16);
    if (S == 0) {
        unsigned it = 0;
#pragma unroll 1
        while (!MMA0_WAIT(BAR(BAR_FULL), conv) && ++it < SPIN_LIMIT) {}
    }
    bool next_ok = true;
    constexpr uint32_t NEXT = S + 1 < NSTAGE ? BAR(BAR_FULL + S + 1) : BAR(BAR_EMB);
    const int npar = S + 1 < NSTAGE ? conv : 0;
    next_ok = mbar_test(NEXT, npar);
    if (S == 0 && tid == 0) TL(32 + conv * 24);
    asm volatile("wgmma.fence.sync.aligned;" ::: "memory");
    wgmma128<A, B>(d);
    wgmma128<A + 1, B + 16>(d);
    wgmma128<A + 2, B + 32>(d);
    asm volatile("wgmma.commit_group.sync.aligned;" ::: "memory");
    if (S >= LAG) {
        asm volatile("wgmma.wait_group.sync.aligned %0;" ::"n"(LAG) : "memory");
        if ((tid & 31) == 0) mbar_arrive(BAR(BAR_WEMPTY + (S + NS - LAG) % NS));
    }
    if (!next_ok) mbar_wait(NEXT, npar);
    if constexpr (S + 1 < NSTAGE) mma_stages<S + 1>(d, conv, tid, gs);
}

__device__ __forceinline__ void weight_load(uint4 (&t)[5], const __nv_bfloat16* w, int cta, int lane) {
    const char* base = reinterpret_cast<const char*>(w) + ((cta & 15) * 8 * C + (cta >> 4) * 16) * 18;
#pragma unroll
    for (int k = 0; k < 5; k++) {
        const int i = lane + 32 * k, row = (i * 57) >> 10;
        if (k < 4 || lane < 16) t[k] = __ldg(reinterpret_cast<const uint4*>(base + row * (C * 18 - 288) + i * 16));
    }
}
__device__ __forceinline__ void weight_block(uint32_t bounce, unsigned char* wt, int cta, int lane, bool readback, Scratch* gs) {
    unsigned char* dst = wt + (cta >> 4) * STAGE_BYTES + (cta & 15) * 768;
    if (lane < 16) {
        uint32_t v[36];
#pragma unroll
        for (int i = 0; i < 9; i++) {
            const uint4 q = lds128(bounce + (lane & 7) * 288 + (lane >> 3) * 144 + i * 16);
            v[4 * i] = q.x; v[4 * i + 1] = q.y; v[4 * i + 2] = q.z; v[4 * i + 3] = q.w;
        }
#pragma unroll
        for (int kyo = 0; kyo < 3; kyo++) {
#pragma unroll
            for (int kx = 0; kx < 3; kx++) {
                const int tap = ky_of(kyo) * 3 + kx;
                uint32_t o[4];
#pragma unroll
                for (int m = 0; m < 4; m++) {
                    const int i0 = 18 * m + tap, i1 = i0 + 9;
                    const uint32_t sel = ((i0 & 1) ? 0x32u : 0x10u) | ((i1 & 1) ? 0x7600u : 0x5400u);
                    o[m] = __byte_perm(v[i0 >> 1], v[i1 >> 1], sel);
                }
                *reinterpret_cast<uint4*>(dst + kyo * 8 * STAGE_BYTES + kx * 256 + lane * 16) = make_uint4(o[0], o[1], o[2], o[3]);
            }
        }
    }
    if (readback) {
        __syncwarp();
        unsigned acc = 0;
        if (lane < 24) {
#pragma unroll
            for (int i = 0; i < 3; i++) acc |= ld_relaxed(dst + i * 8 * STAGE_BYTES + lane * 32);
        }
        asm volatile("{\n.reg .pred p;\nsetp.eq.u32 p, %0, 0x9e3779b9;\n@p st.shared.u32 [%1], %0;\n}" ::"r"(acc), "r"(bounce + S0) : "memory");
    }
}
__device__ __forceinline__ uint32_t act2(uint32_t u, const float4& cf) {
    return pack_bf(silu_half(fmaf(bf_lo(u), cf.x, cf.z)), silu_half(fmaf(bf_hi(u), cf.y, cf.w)));
}
__device__ __forceinline__ void norm_unit(uint32_t (&u)[4], const float4& ca, const float4& cb) {
    u[0] = act2(u[0], ca); u[1] = act2(u[1], ca); u[2] = act2(u[2], cb); u[3] = act2(u[3], cb);
}
__device__ __forceinline__ void read_stats(uint32_t gst, float (&g)[8]) {
    asm volatile("ld.volatile.shared.v4.f32 {%0,%1,%2,%3}, [%4];" : "=f"(g[0]), "=f"(g[1]), "=f"(g[2]), "=f"(g[3]) : "r"(gst + S0) : "memory");
    asm volatile("ld.volatile.shared.v4.f32 {%0,%1,%2,%3}, [%4];" : "=f"(g[4]), "=f"(g[5]), "=f"(g[6]), "=f"(g[7]) : "r"(gst + 16 + S0) : "memory");
}
template <int T>
__device__ __forceinline__ void group_coefs(uint32_t gst, float (&g)[8], float4 (&cf)[8]) {
    unsigned it = 0;
    if (!__all_sync(0xffffffffu, g[2 * T] != 0.f)) {
        float rs0;
#pragma unroll 1
        do {
            SPINPAUSE;
            asm volatile("ld.volatile.shared.f32 %0, [%1];" : "=f"(rs0) : "r"(gst + 8 * T + S0) : "memory");
        } while (!__all_sync(0xffffffffu, rs0 != 0.f) && ++it < 8 * SPIN_LIMIT);
        read_stats(gst, g);
    }
    float4 &ca = cf[2 * T], &cb = cf[2 * T + 1];
    const float rs = g[2 * T], mr = g[2 * T + 1];
    ca.z = fmaf(-mr, ca.x, ca.z); ca.w = fmaf(-mr, ca.y, ca.w); ca.x *= rs; ca.y *= rs;
    cb.z = fmaf(-mr, cb.x, cb.z); cb.w = fmaf(-mr, cb.y, cb.w); cb.x *= rs; cb.y *= rs;
}
template <int FIRST, int N>
__device__ __forceinline__ void norm_block(uint32_t (&u)[4][4], float4 (&cf)[8], uint32_t act, uint32_t mask, uint32_t fbar, int lane) {
#pragma unroll
    for (int t = FIRST; t < FIRST + N; t++) {
        norm_unit(u[t], cf[2 * t], cf[2 * t + 1]);
        stsm4(act + t * 2 * KC_BYTES, u[t][0] & mask, u[t][1] & mask, u[t][2] & mask, u[t][3] & mask);
    }
    fence_async_smem();
    __syncwarp();
    if (lane < N) mbar_arrive(fbar + 16 * (FIRST + lane));
}
__device__ __forceinline__ void publish(uint32_t bar, int lane) {
    fence_async_smem();
    __syncwarp();
    if (lane == 0) mbar_arrive(bar);
}
template <int T>
__device__ __forceinline__ void next_unit(uint32_t (&u)[4][4], float4 (&cf)[8], uint32_t gst, float (&g)[8], uint32_t act, uint32_t fbar, int lane) {
    const bool have = __all_sync(0xffffffffu, g[2 * T] != 0.f);
    if (!have) publish(fbar + 16 * (T - 1), lane);
    group_coefs<T>(gst, g, cf);
    norm_unit(u[T], cf[2 * T], cf[2 * T + 1]);
    if (have) publish(fbar + 16 * (T - 1), lane);
    stsm4(act + T * 2 * KC_BYTES, u[T][0], u[T][1], u[T][2], u[T][3]);
}
__device__ __forceinline__ void stat_mma(float (&c)[4], uint32_t p, uint32_t q) {
    asm("mma.sync.aligned.m16n8k16.row.col.f32.bf16.bf16.f32 {%0,%1,%2,%3}, {%4,%5,%6,%5}, {%4,%6}, {%0,%1,%2,%3};"
        : "+f"(c[0]), "+f"(c[1]), "+f"(c[2]), "+f"(c[3]) : "r"(p), "r"(0x3f803f80u), "r"(q));
}
__device__ __forceinline__ void stat_store(const float (&c)[4], uint32_t dst, int lane) {
    const int g = lane >> 2, t = lane & 3;
    if (t == (g >> 1)) sts32f(dst + g * 4, (g & 1) ? c[1] : c[0]);
    if (g == 7) sts32f(dst + 32 + t * 4, c[2] + c[3]);
}
__device__ __forceinline__ float sum4(float4 v) { return (v.x + v.y) + (v.z + v.w); }
__device__ __forceinline__ void stat_publish(uint32_t src, float* acc, int lane, bool real) {
    const uint32_t a = src + (lane & 15) * 48;
    float q = sum4(lds128f(a)) + sum4(lds128f(a + 16)), sm = sum4(lds128f(a + 32));
    q += __shfl_xor_sync(0xffffffffu, q, 1); sm += __shfl_xor_sync(0xffffffffu, sm, 1);
    q += __shfl_xor_sync(0xffffffffu, q, 2); sm += __shfl_xor_sync(0xffffffffu, sm, 2);
    if (real && (lane & 19) == 0) red_add4(acc + lane, 1.f, sm, q, 1.f);
}
__device__ __forceinline__ void fence_acc(float (&d)[64]) {
#pragma unroll
    for (int i = 0; i < 64; i++) asm volatile("" : "+f"(d[i])::"memory");
}
__device__ __forceinline__ void ld_unit(uint32_t (&u)[4], const uint4* p) {
    asm volatile("ld.relaxed.gpu.global.v4.u32 {%0,%1,%2,%3}, [%4];" : "=r"(u[0]), "=r"(u[1]), "=r"(u[2]), "=r"(u[3]) : "l"(p) : "memory");
}

__device__ __noinline__ void side_jobs(const __nv_bfloat16* __restrict__ t_emb, const __nv_bfloat16* __restrict__ w_emb,
                                       const __nv_bfloat16* __restrict__ w2, Scratch* __restrict__ gs, unsigned clk0) {
    const int tid = threadIdx.x, warp = tid >> 5, lane = tid & 31, j = blockIdx.x;
    float tv = 0.f;
    if (lane < 24) tv = __bfloat162float(t_emb[(lane / 12) * E + j * 192 + warp * 12 + lane % 12]);
    if (tid == 0) {
        mbar_init(BAR(0), 1);
        mbar_expect(BAR(0), 192 * C * 2);
        fence_async_smem();
        while (clock32() - clk0 < SDELAY) {}
#pragma unroll
        for (int i = 0; i < 4; i++)
            asm volatile("cp.async.bulk.prefetch.L2.global [%0], 18432;" ::"l"(reinterpret_cast<const char*>(w2) + (j * 4 + i) * 18432) : "memory");
#pragma unroll
        for (int i = 0; i < 4; i++) bulk_g2s(S0 + SM_W + i * 12288, w_emb + (j * 192 + i * 48) * C, 12288, S0 + BAR(0));
    }
    if (j == 0 && tid < 32) gs->acc2[(tid >> 4) * LS + (tid & 15)] = 0.f;
    const float sv = silu_half(0.5f * tv);
    __syncthreads();
    mbar_wait(BAR(0), 0);
    float acc[8] = {0.f, 0.f, 0.f, 0.f, 0.f, 0.f, 0.f, 0.f};
#pragma unroll
    for (int i = 0; i < 12; i++) {
        const float2 wq = lds64f(SM_W + (warp * 12 + i) * 256 + lane * 8);
        const uint32_t wx = __float_as_uint(wq.x), wy = __float_as_uint(wq.y);
#pragma unroll
        for (int bb = 0; bb < 2; bb++) {
            const float sx = __shfl_sync(0xffffffffu, sv, bb * 12 + i);
            acc[4 * bb + 0] = fmaf(sx, bf_lo(wx), acc[4 * bb + 0]); acc[4 * bb + 1] = fmaf(sx, bf_hi(wx), acc[4 * bb + 1]);
            acc[4 * bb + 2] = fmaf(sx, bf_lo(wy), acc[4 * bb + 2]); acc[4 * bb + 3] = fmaf(sx, bf_hi(wy), acc[4 * bb + 3]);
        }
    }
    sts128f(SM_ACT + warp * 1024 + lane * 16, make_float4(acc[0], acc[1], acc[2], acc[3]));
    sts128f(SM_ACT + warp * 1024 + 512 + lane * 16, make_float4(acc[4], acc[5], acc[6], acc[7]));
    __syncthreads();
    if (tid < 128) {
        float2 sum = make_float2(0.f, 0.f);
#pragma unroll
        for (int w = 0; w < 16; w++) { const float2 p = lds64f(SM_ACT + w * 1024 + tid * 8); sum.x += p.x; sum.y += p.y; }
        *reinterpret_cast<float2*>(&gs->emb[j * NB * C + tid * 2]) = sum;
        bar_sync(1, 128);
        if (tid < 2) asm volatile("red.release.gpu.global.add.u32 [%0], 1;" ::"l"(&gs->wcnt[(2 * NB + tid) * LS]) : "memory");
    }
}

__global__ void __cluster_dims__(2, 1, 1) __launch_bounds__(NTHREADS, 1)
resblock_kernel(const __nv_bfloat16* __restrict__ w1, const __nv_bfloat16* __restrict__ x,
                const __nv_bfloat16* __restrict__ t_emb, const __nv_bfloat16* __restrict__ g1,
                const __nv_bfloat16* __restrict__ be1, const __nv_bfloat16* __restrict__ w_emb,
                const __nv_bfloat16* __restrict__ g2, const __nv_bfloat16* __restrict__ be2,
                const __nv_bfloat16* __restrict__ w2, __nv_bfloat16* __restrict__ out, Scratch* __restrict__ gs,
                const __grid_constant__ CUtensorMap xmap) {
    const unsigned clk0 = clock32();
    if (threadIdx.x == 480 && blockIdx.x >= NXTRA) TLG(1);
    const int tid = threadIdx.x, lane = tid & 31;
    const int cta = blockIdx.x - NXTRA, b = cta >> 6, r = cta & 63;
    uint4 v[5];
    if (tid < 32) weight_load(v, w1, cta & (NCTA - 1), lane);
    uint4 xv[8];
    const int wg4 = (tid >> 5) - 1;
    const bool early = tid >= 32 && wg4 < NLDG;
    if (early) {
        const char* src = reinterpret_cast<const char*>(x) + (uint32_t)((((b & 1) * C + wg4 * 32 + (lane >> 3)) * HW + r) * HW * 2 + (lane & 7) * 16);
        while (clock32() - clk0 < XDELAY + (wg4 >> 1) * XSTAG + (wg4 & 1) * XSTAG2) {}
#pragma unroll
        for (int i = 0; i < 8; i++) xv[i] = __ldg(reinterpret_cast<const uint4*>(src + i * (4 * HW * HW * 2)));
    }
    const int warp = __shfl_sync(0xffffffffu, tid >> 5, 0);
    if (cta < 0) { side_jobs(t_emb, w_emb, w2, gs, clk0); return; }

    if (warp != 4) asm volatile("barrier.cluster.arrive.relaxed.aligned;" ::: "memory");
    const bool has_outer = (r != 0) && (r != HW - 1);
    if (warp == 1 || warp == 2 || warp == 3 || warp == 5) {
        const int g = warp < 4 ? warp - 1 : 3;
        if (elect_one()) {
            if (g >= NLDG) asm volatile("prefetch.tensormap [%0];" ::"l"(&xmap) : "memory");
            mbar_init(BAR(BAR_X) + 8 * g, 1);
            if (g >= NLDG) mbar_expect(BAR(BAR_X) + 8 * g, 4096);
            fence_async_smem();
        }
        __syncwarp();
        bar_arrive(4, 256 + 32 + 128);
        if (g >= NLDG) {
            while (clock32() - clk0 < XDELAY + (g >> 1) * XSTAG + (g & 1) * XSTAG2) {}
            if (elect_one()) tma_x(SM_XOWN + g * 4096, &xmap, r, b * C + g * 32, BAR(BAR_X) + 8 * g);
            __syncwarp();
            mbar_wait(BAR(BAR_X) + 8 * g, 0);
#pragma unroll
            for (int k = 0; k < 8; k++) xv[k] = lds128(SM_XOWN + g * 4096 + k * 512 + lane * 16);
        }
        float c[8][4];
#pragma unroll
        for (int k = 0; k < 8; k++) {
            c[k][0] = c[k][1] = c[k][2] = c[k][3] = 0.f;
            stat_mma(c[k], xv[k].x, xv[k].y); stat_mma(c[k], xv[k].z, xv[k].w);
        }
#pragma unroll
        for (int i = 0; i < 4; i++) c[0][i] = ((c[0][i] + c[1][i]) + (c[2][i] + c[3][i])) + ((c[4][i] + c[5][i]) + (c[6][i] + c[7][i]));
        stat_store(c[0], SM_RED + g * 48, lane);
        __syncwarp();
        if (lane == 0) {
            const uint32_t a = SM_RED + g * 48;
            red_add4(&gs->acc1[b * LS + g * 4], 1.f, sum4(lds128f(a + 32)), sum4(lds128f(a)) + sum4(lds128f(a + 16)), 1.f);
            TL(74 + g);
        }
        if (g < NLDG) {
#pragma unroll
            for (int i = 0; i < 8; i++)
                sts128(SM_XOWN + g * 4096 + i * 512 + (lane >> 3) * 128 + (((lane & 7) ^ ((lane >> 3) + 4 * (i & 1))) << 4), xv[i]);
            __syncwarp();
            if (lane == 0) mbar_arrive(BAR(BAR_X) + 8 * g);
        }
    }
    if (warp == 4) {
            if (elect_one()) {
#pragma unroll
                for (int i = 0; i < NSTAGE; i++) mbar_init(BAR(BAR_FULL + i), (i >> 3) == 1 ? 1 : 5);
#pragma unroll
                for (int i = 0; i < NS + 2; i++) mbar_init(BAR(BAR_WEMPTY + i), 4);
#pragma unroll
                for (int i = BAR_STATS; i < BAR_X; i++) mbar_init(BAR(i), i == BAR_EMB ? 3 : 1);
                mbar_init(BAR(BAR_X + 4), 1);
                asm volatile("fence.mbarrier_init.release.cluster;" ::: "memory");
            }
            if (lane < 4) sts128(SM_GST + lane * 16, make_uint4(0, 0, 0, 0));
            __syncwarp();
            fence_async_smem();
            bar_arrive(0, 96);
            bar_arrive(5, 64);
            bar_arrive(4, 256 + 32 + 128);
            const uint4 z = make_uint4(0, 0, 0, 0);
#pragma unroll
            for (int i = 0; i < 2; i++) sts128(SM_ACT + (i * 16 + (lane >> 1)) * CH_PITCH + (lane & 1) * 16, z);
            if (lane < 4) sts128(SM_ACT + (2 + (lane >> 1)) * ROW_BYTES + (lane & 1) * 16, z);
            if (lane < 16) sts128(SM_ONES + lane * 16, make_uint4(lane < 8 ? 0x3f803f80u : 0u, 0, 0, 0));
            fence_async_smem();
            bar_arrive(7, 160);
            asm volatile("barrier.cluster.arrive.relaxed.aligned;" ::: "memory");
            if (lane == 0) TL(5);
            while (clock32() - clk0 < W2DELAY) {}
            weight_load(v, w2, cta, lane);
        }
    if (warp == 0 || warp == 4) {
        const int k = warp >> 2;
#pragma unroll
        for (int i = 0; i < 5; i++)
            if (i < 4 || lane < 16) sts128(SM_BNC + k * 2304 + (lane + 32 * i) * 16, v[i]);
        if (lane == 0) TL(k ? 14 : 81);
        __syncwarp();
        weight_block(SM_BNC + k * 2304, gs->wt + k * NSTAGE * STAGE_BYTES, cta, lane, true, gs);
        __syncwarp();
        if (lane == 0) TL(k ? 13 : 4);
        if (lane < 2) asm volatile("red.relaxed.gpu.global.add.u32 [%0], 1;" ::"l"(k ? &gs->wcnt[(NB + lane) * LS] : &gs->w1cnt[(lane * 8 + (cta >> 4)) * KS]) : "memory");
    }

    if (warp >= 8) {
        const int nw = warp - 8;
        if (nw < 2) {
            const uint2 ga = __ldg(reinterpret_cast<const uint2*>(nw ? g2 : g1) + lane), bt = __ldg(reinterpret_cast<const uint2*>(nw ? be2 : be1) + lane);
            sts128f(SM_COEF + nw * 1024 + lane * 32, make_float4(0.5f * bf_lo(ga.x), 0.5f * bf_hi(ga.x), 0.5f * bf_lo(bt.x), 0.5f * bf_hi(bt.x)));
            sts128f(SM_COEF + nw * 1024 + lane * 32 + 16, make_float4(0.5f * bf_lo(ga.y), 0.5f * bf_hi(ga.y), 0.5f * bf_lo(bt.y), 0.5f * bf_hi(bt.y)));
        }
        bar_sync(4, 256 + 32 + 128);
        const int par = nw >> 2, wq = nw & 3;
        const uint32_t act_off = SM_ACT + (par * 2 + (lane >> 4)) * CH_PITCH + (2 + wq * 16 + (lane & 15)) * 16;
        const uint32_t stg_off = (par * 16 + (lane >> 4) * 8 + (lane & 7)) * 128 + (((2 * wq + ((lane >> 3) & 1)) ^ (lane & 7)) << 4);
        const uint32_t cfa = SM_COEF + par * 128 + (lane & 3) * 16;
        const uint32_t fbar = BAR(BAR_FULL) + 8 * par;
        uint4* inbox = gs->box + cta * 1024 + nw * 32 + lane;
#pragma unroll 1
        for (int conv = 0; conv < 2; conv++) {
            uint32_t u[4][4], w[4][4];
            float4 cf[8];
            if (conv == 0) {
#pragma unroll
                for (int i = 0; i < 4; i++) { mbar_wait(BAR(BAR_X + i), 0); ldsm4t(u[i], SM_XOWN + stg_off + i * 4096); }
            } else {
                mbar_wait(BAR(BAR_HW), 0);
#pragma unroll
                for (int i = 0; i < 4; i++) ldsm4(u[i], act_off + i * 2 * KC_BYTES);
            }
#pragma unroll
            for (int i = 0; i < 8; i++) cf[i] = lds128f(cfa + conv * 1024 + (i >> 1) * 256 + (i & 1) * 64);
            const uint32_t gst = SM_GST + conv * 32;
            float gv[8];
            read_stats(gst, gv);
            group_coefs<0>(gst, gv, cf);
            if (tid == 256) TL(22 + conv * 4);
            if (par) { const unsigned c1 = clock32(); while (clock32() - c1 < PDELAY) {} }
            norm_block<0, 1>(u, cf, act_off, ~0u, fbar, lane);
            if (tid == 256) TL(8 + conv * 8);
            group_coefs<1>(gst, gv, cf);
            norm_unit(u[1], cf[2], cf[3]);
            stsm4(act_off + 2 * KC_BYTES, u[1][0], u[1][1], u[1][2], u[1][3]);
            next_unit<2>(u, cf, gst, gv, act_off, fbar, lane);
            next_unit<3>(u, cf, gst, gv, act_off, fbar, lane);
            publish(fbar + 48, lane);
            if (tid == 256) TL(84 + conv);
            if (has_outer) {
                mbar_wait(BAR(BAR_X + 4), conv);
                if (conv == 0) {
#pragma unroll
                    for (int i = 0; i < 4; i++) ldsm4t(w[i], SM_XOUT + stg_off + i * 4096);
                } else {
#pragma unroll
                    for (int i = 0; i < 4; i++) {
                        const uint4 q = lds128(SM_XOWN + (tid - 256) * 16 + i * 4096);
                        w[i][0] = q.x; w[i][1] = q.y; w[i][2] = q.z; w[i][3] = q.w;
                    }
                    unsigned it = 0;
                    while (true) {
                        bool ok = true;
#pragma unroll
                        for (int i = 0; i < 16; i++) ok = ok && w[i >> 2][i & 3] != 0;
                        if (__all_sync(0xffffffffu, ok) || ++it > SPIN_LIMIT) break;
#pragma unroll
                        for (int i = 0; i < 4; i++) ld_unit(w[i], inbox + i * 256);
                    }
#pragma unroll
                    for (int i = 0; i < 16; i++) w[i >> 2][i & 3] = ~w[i >> 2][i & 3];
                }
            }
            if (conv == 0) {
                bar_sync(3, 256);
                if (nw == 0) sts128(SM_ACT + 2 * ROW_BYTES + (lane >> 1) * CH_PITCH + (lane & 1) * 16, make_uint4(0, 0, 0, 0));
            }
            if (tid == 256) TL(24 + conv * 4);
            norm_block<0, 2>(w, cf, act_off + 2 * ROW_BYTES, has_outer ? ~0u : 0u, fbar + 128, lane);
            if (tid == 256) TL(88 + conv);
            norm_block<2, 2>(w, cf, act_off + 2 * ROW_BYTES, has_outer ? ~0u : 0u, fbar + 128, lane);
            if (tid == 256) TL(23 + conv * 4);
        }
        if (has_outer) {
            mbar_wait(BAR(BAR_FULL + NSTAGE - 1), 1);
#pragma unroll
            for (int i = 0; i < 4; i++) inbox[i * 256] = make_uint4(0, 0, 0, 0);
        }
        {
            const int oc0 = (tid - 256) >> 3, seg = lane & 7;
            __nv_bfloat16* dst = out + ((size_t)(b * C + oc0) * HW + r) * HW + seg * 8;
            const uint32_t src = SM_XOWN + oc0 * 128 + ((seg ^ (oc0 & 7)) << 4);
            bar_sync(6, 128 + 256);
#pragma unroll
            for (int i = 0; i < 4; i++) *reinterpret_cast<uint4*>(dst + (size_t)i * 32 * HW * HW) = lds128(src + i * 4096);
            if (tid == 256) { TL(20); TLG(21); }
        }
    } else if (warp < 4) {
        const int wq = warp;
        bar_sync(7, 160);

        const uint32_t xbase = SM_XOWN + ((lane >> 4) * 8 + (lane & 7)) * 128 + (((2 * wq + ((lane >> 3) & 1)) ^ (lane & 7)) << 4);
        float d[64];
#pragma unroll
        for (int i = 0; i < 64; i++) d[i] = 0.f;
#pragma unroll 1
        for (int conv = 0; conv < 2; conv++) {
            fence_acc(d);
            mma_stages<0>(d, conv, tid, gs);
            if (conv == 0) {
                asm volatile("wgmma.fence.sync.aligned;" ::: "memory");
                wgmma128<(SM_ONES >> 4) | (8u << 16), (SM_EMB >> 4), 0, 8>(d);
                asm volatile("wgmma.commit_group.sync.aligned;" ::: "memory");
            }
            asm volatile("wgmma.wait_group.sync.aligned 0;" ::: "memory");
            fence_acc(d);
            if (tid == 0) TL(10 + conv * 8);
            uint32_t hp[32];
#pragma unroll
            for (int i = 0; i < 32; i++) hp[i] = pack_bf(d[2 * i], d[2 * i + 1]);
            if (conv == 1) {
#pragma unroll
                for (int kc = 0; kc < 8; kc++) stsm4t(xbase + kc * 2048, hp[4 * kc], hp[4 * kc + 1], hp[4 * kc + 2], hp[4 * kc + 3]);
                bar_arrive(6, 128 + 256);
                break;
            }
#pragma unroll
            for (int g = 0; g < 4; g++) {
                float c[4] = {0.f, 0.f, 0.f, 0.f};
#pragma unroll
                for (int i = 0; i < 4; i++) stat_mma(c, hp[8 * g + 2 * i], hp[8 * g + 2 * i + 1]);
                stat_store(c, SM_RED + (g * 4 + wq) * 48, lane);
            }
            bar_sync(2, 128);
            if (wq == 0) stat_publish(SM_RED, &gs->acc2[b * LS], lane, true);
            if (tid == 0) TL(11);
            const uint32_t hbase = SM_ACT + (lane >> 4) * CH_PITCH + (2 + wq * 16 + (lane & 15)) * 16;
#pragma unroll
            for (int kc = 0; kc < 8; kc++) stsm4(hbase + kc * 2 * CH_PITCH, hp[4 * kc], hp[4 * kc + 1], hp[4 * kc + 2], hp[4 * kc + 3]);
            __syncwarp();
            if (lane == 0) mbar_arrive(BAR(BAR_HW));
            if (lane < LAG) mbar_arrive(BAR(BAR_WEMPTY + (NSTAGE - LAG) % NS) + 8 * lane);
            if (has_outer) {
                uint4* outbox = gs->box + (cta + ((r & 1) ? 1 : -1)) * 1024 + tid;
#pragma unroll
                for (int kc = 0; kc < 8; kc++) outbox[kc * 128] = make_uint4(~hp[4 * kc], ~hp[4 * kc + 1], ~hp[4 * kc + 2], ~hp[4 * kc + 3]);
            }
            if (tid == 0) TL(12);
#pragma unroll
            for (int kc = 0; kc < 8; kc++) {
                uint32_t p[4];
                ldsm4t(p, xbase + kc * 2048);
#pragma unroll
                for (int i = 0; i < 4; i++) { d[8 * kc + 2 * i] = bf_lo(p[i]); d[8 * kc + 2 * i + 1] = bf_hi(p[i]); }
            }
            fence_async_smem();
            __syncwarp();
            if (lane == 0) mbar_arrive(BAR(BAR_XFREE));
        }
        {
        }
    } else if (warp < 6) {
        if (warp == 5) {
            bar_sync(5, 64);
            mbar_wait(BAR(BAR_FULL + OAFTER), 0);
            if (has_outer && elect_one()) {
                mbar_expect(BAR(BAR_X + 4), 16384);
#pragma unroll
                for (int i = 0; i < 4; i++) tma_x(SM_XOUT + i * 4096, &xmap, r + ((r & 1) ? 1 : -1), b * C + i * 32, BAR(BAR_X + 4));
            }
            __syncwarp();
            asm volatile("barrier.cluster.wait.acquire.aligned;" ::: "memory");
            const uint32_t peer = (r & 1) ^ 1;
            const uint32_t self0 = mapa(0, r & 1), peer0 = mapa(0, peer);
#pragma unroll 1
            for (int conv = 0; conv < 2; conv++) {
#pragma unroll 1
                for (int kc = 0; kc < 8; kc++) {
                    mbar_wait(BAR(BAR_FULL) + 8 * kc, conv);
                    if (elect_one())
                        asm volatile("cp.async.bulk.shared::cluster.shared::cta.mbarrier::complete_tx::bytes [%0], [%1], %2, [%3];"
                                     ::"r"(peer0 + SM_ACT + ROW_BYTES + kc * KC_BYTES), "r"(self0 + SM_ACT + kc * KC_BYTES), "r"(KC_BYTES),
                                       "r"(peer0 + BAR(BAR_FULL + 8) + 8 * kc) : "memory");
                }
                if (lane == 0) TL(86 + conv);
#pragma unroll 1
                for (int kc = 0; kc < 8; kc++) mbar_wait(BAR(BAR_FULL + 8) + 8 * kc, conv);
                if (conv) mbar_wait(BAR(BAR_STATS), 1);
                if (lane == 0)
                    asm volatile("mbarrier.arrive.relaxed.cluster.shared::cluster.b64 _, [%0];" ::"r"(peer0 + (conv ? BAR(BAR_ACK) : BAR(BAR_EMB))) : "memory");
            }
            mbar_wait(BAR(BAR_ACK), 0);
        } else {
            mbar_wait(BAR(BAR_STATS), 0);
            unsigned it = 0;
            while (ld_relaxed(&gs->wcnt[(2 * NB + b) * LS]) < (unsigned)NXTRA && ++it < SPIN_LIMIT) __nanosleep(100);
            fence_acquire();
            float ev[4] = {0.f, 0.f, 0.f, 0.f};
#pragma unroll
            for (int j = 0; j < NXTRA; j++) {
                const uint4 ef = ld_relaxed_v4(&gs->emb[(j * NB + b) * C + lane * 4]);
                ev[0] += __uint_as_float(ef.x); ev[1] += __uint_as_float(ef.y); ev[2] += __uint_as_float(ef.z); ev[3] += __uint_as_float(ef.w);
            }
#pragma unroll
            for (int i = 0; i < 4; i++) {
                const float hi = bf_lo(pack_bf(ev[i], 0.f));
                sts128(SM_EMB + (lane * 4 + i) * 16, make_uint4(pack_bf(hi, ev[i] - hi), 0, 0, 0));
            }
            fence_async_smem();
            __syncwarp();
            if (lane == 0) { mbar_arrive(BAR(BAR_EMB)); TL(19); }
        }
    } else if (warp == 6) {
        bar_sync(0, 96);
        const uint32_t ebytes = STAGE_BYTES + ((lane >> 3) == 1 ? KC_BYTES : 0);
        if (lane < NSTAGE) mbar_expect(BAR(BAR_FULL) + 8 * lane, ebytes);
        const int swap = (r & 1) ? 0 : 8 * STAGE_BYTES;
        unsigned it = 0;
        {
            int g = 0;
            while (clock32() - clk0 < PDW) {}
#pragma unroll 1
            while (g < NS) {
                const int pk = min(g + (lane & (PW - 1)), 7);
                unsigned ready = g >= 8 ? ~0u : __ballot_sync(0xffffffffu, ld_relaxed(&gs->w1cnt[(b * 8 + pk) * KS]) >= 16u) & ((1u << PW) - 1);
                if (++it > SPIN_LIMIT) ready = ~0u;
                if (!(ready & 1)) continue;
                fence_acquire();
                fence_async_global();
                if (lane == 0) TL(g ? 3 : 6);
#pragma unroll 1
                for (; (ready & 1) && g < NS; g++, ready >>= 1)
                    if (elect_one())
                        bulk_g2s(S0 + SM_W + g * STAGE_BYTES, gs->wt + g * STAGE_BYTES + (g >= 8 ? swap : 0), STAGE_BYTES, S0 + BAR(BAR_FULL) + 8 * g);
            }
        }
#pragma unroll 1
        for (int q = 3; q < 12; q++) {
            const int conv = q >= 6, qs = conv ? q - 6 : q, sl = q % 3;
            const unsigned char* wsrc = gs->wt + q * 4 * STAGE_BYTES + (qs < 2 ? 0 : (qs < 4 ? swap : -swap));
            const uint32_t par = (q / 3 - 1) & 1;
            if (q == 6) {
                it = 0;
                while (ld_relaxed(&gs->wcnt[(NB + b) * LS]) < (unsigned)NCTA && ++it < SPIN_LIMIT) {}
                fence_acquire();
                fence_async_global();
                if (lane == 0) { mbar_arrive(BAR(BAR_EMB)); TL(2); }
            }
#pragma unroll
            for (int i = 0; i < 4; i++) {
                mbar_wait(BAR(BAR_WEMPTY + i) + 32 * sl, par);
                if (i == 0 && (q == 6 || q == 9)) {
                    if ((lane >= NS) == (q == 9) && lane < NSTAGE) mbar_expect(BAR(BAR_FULL) + 8 * lane, ebytes);
                    __syncwarp();
                }
                if (elect_one())
                    bulk_g2s(S0 + SM_W + (sl * 4 + i) * STAGE_BYTES, wsrc + i * STAGE_BYTES, STAGE_BYTES, S0 + BAR(BAR_FULL + i) + 32 * qs);
            }
        }
    } else {
        bar_sync(0, 96);
        asm volatile("barrier.cluster.wait.acquire.aligned;" ::: "memory");
        const uint32_t gdst = mapa(SM_GST + (lane & 3) * 8, (r & 1) ^ ((lane >> 2) & 1));
#pragma unroll 1
        for (int conv = 0; conv < 2; conv++) {
            if (conv == 1) mbar_wait(BAR(BAR_HW), 0);
            const float* asrc = (conv ? gs->acc2 : gs->acc1) + b * LS + (lane & 3) * 4;
            unsigned it = 0;
            bool done = false;
#pragma unroll 1
            while (true) {
                const uint4 f = ld_relaxed_v4(asrc);
                const bool ok = ((f.x == 0x42800000u) & (f.w == 0x42800000u)) || ++it > SPIN_LIMIT;
                if (ok && !done && lane < SHARE) {
                    const float inv_n = 1.0f / (32.0f * HW * HW);
                    const float mean = __uint_as_float(f.y) * inv_n;
                    const float rs = rsqrtf(fmaxf(fmaf(-mean, mean, __uint_as_float(f.z) * inv_n), 0.f) + 1e-5f);
                    if (lane < 4) asm volatile("st.shared.v2.f32 [%0], {%1,%2};" ::"r"(gdst + conv * 32), "f"(rs == 0.f ? 1e-38f : rs), "f"(mean * rs) : "memory");
                    else asm volatile("st.shared::cluster.v2.f32 [%0], {%1,%2};" ::"r"(gdst + conv * 32), "f"(rs == 0.f ? 1e-38f : rs), "f"(mean * rs) : "memory");
                }
                done = ok;
                if (__all_sync(0xffffffffu, ok)) break;
            }
            if (lane == 0) { mbar_arrive(BAR(BAR_STATS)); TL(7 + conv * 8); }
        }
        mbar_wait(BAR(BAR_XFREE), 0);
        if (has_outer && elect_one()) {
            mbar_expect(BAR(BAR_X + 4), 16384);
            bulk_g2s(S0 + SM_XOWN, gs->box + cta * 1024, 16384, S0 + BAR(BAR_X + 4));
        }
        if (r == 0) {
            if (lane < 16) gs->acc1[b * LS + lane] = 0.f;
            if (lane < 3) gs->wcnt[(lane * NB + b) * LS] = 0;
            if (lane < 8) gs->w1cnt[(b * 8 + lane) * KS] = 0;
        }
    }
}

}

extern "C" void kernel_launch(void* const* d_in, const int* in_sizes, int n_in, void* d_out, int out_size) {
    (void)in_sizes; (void)n_in; (void)out_size;
    typedef CUresult (*EncodeFn)(CUtensorMap*, CUtensorMapDataType, cuuint32_t, void*, const cuuint64_t*, const cuuint64_t*,
                                 const cuuint32_t*, const cuuint32_t*, CUtensorMapInterleave, CUtensorMapSwizzle,
                                 CUtensorMapL2promotion, CUtensorMapFloatOOBfill);
    static Scratch* gs = nullptr;
    static EncodeFn encode = nullptr;
    if (!gs) {
        cudaFuncSetAttribute(resblock_kernel, cudaFuncAttributeMaxDynamicSharedMemorySize, SM_TOTAL);
        cudaGetSymbolAddress((void**)&gs, g_scratch);
        cudaDriverEntryPointQueryResult qr;
        cudaGetDriverEntryPoint("cuTensorMapEncodeTiled", (void**)&encode, cudaEnableDefault, &qr);
    }
    CUtensorMap xmap;
    const cuuint64_t dims[3] = {HW, HW, NB * C}, strides[2] = {HW * 2, HW * HW * 2};
    const cuuint32_t box[3] = {HW, 1, 32}, es[3] = {1, 1, 1};
    encode(&xmap, CU_TENSOR_MAP_DATA_TYPE_BFLOAT16, 3, d_in[0], dims, strides, box, es, CU_TENSOR_MAP_INTERLEAVE_NONE,
           CU_TENSOR_MAP_SWIZZLE_128B, CU_TENSOR_MAP_L2_PROMOTION_NONE, CU_TENSOR_MAP_FLOAT_OOB_FILL_NONE);
    resblock_kernel<<<NCTA + NXTRA, NTHREADS, SM_TOTAL>>>(
        (const __nv_bfloat16*)d_in[4], (const __nv_bfloat16*)d_in[0], (const __nv_bfloat16*)d_in[1],
        (const __nv_bfloat16*)d_in[2], (const __nv_bfloat16*)d_in[3], (const __nv_bfloat16*)d_in[5],
        (const __nv_bfloat16*)d_in[6], (const __nv_bfloat16*)d_in[7], (const __nv_bfloat16*)d_in[8],
        (__nv_bfloat16*)d_out, gs, xmap);
}
```

```cpp
#include <cuda_runtime.h>
#include <cuda.h>
#include <cuda_bf16.h>
#include <stdint.h>

namespace {

constexpr int C = 128, HW = 64, NB = 2, E = 768;
constexpr int NCTA = NB * HW;
constexpr int NXTRA = 4;
constexpr int NTHREADS = 16 * 32;
constexpr int CH_PITCH = 66 * 16;
constexpr int ROW_BYTES = 16 * CH_PITCH;
constexpr int STEP_BYTES = 4096;
constexpr int STAGE_BYTES = 3 * STEP_BYTES;
constexpr int NSTAGE = 24;
constexpr int KC_BYTES = 2 * CH_PITCH;
constexpr int NS = 12;
constexpr int LAG = 1;
#define XDELAY 400
#define HDELAY 600
#define SEQ 0
#define MMA0_WAIT mbar_try
#define SPINPAUSE
#define NPOLL 1
#define PD2 0
#define ODELAY 100
#define NLDG 2
#define PSTAG -1
#define PDELAY0 400
#define PDELAY 60
#define RB 1
#define XSTAG2 400
#define XSTAG 800
#define HSEND 0
#define SDELAY 600
#define OAFTER 0
#define W2DELAY 2400

constexpr uint32_t SMEM_BASE = 0x400;
constexpr uint32_t SM_XOWN = SMEM_BASE;
constexpr uint32_t SM_ACT = SM_XOWN + 16384 + 512;
constexpr uint32_t SM_XOUT = SM_ACT + 2 * ROW_BYTES + 512;
static_assert(SM_XOUT % 1024 == 0, "swizzle atom alignment");
constexpr uint32_t SM_W = SM_ACT + 3 * ROW_BYTES + 128;
__host__ __device__ constexpr uint32_t slot_addr(int slot) { return SM_W + slot * STAGE_BYTES; }
constexpr uint32_t SM_COEF = SM_W + NS * STAGE_BYTES;
constexpr uint32_t SM_GST = SM_COEF + 2048;
constexpr uint32_t SM_EMB = SM_GST + 128;
constexpr uint32_t SM_ONES = SM_EMB + 2048;
constexpr uint32_t SM_RED = SM_ONES + 256;
constexpr uint32_t SM_BNC = SM_RED + 1536;
constexpr uint32_t SM_BAR = SM_BNC + 2 * 2304;
constexpr int BAR_FULL = 0, BAR_WEMPTY = NSTAGE, BAR_HW = BAR_WEMPTY + NS, BAR_XFREE = BAR_HW + 1, BAR_STATS = BAR_XFREE + 1,
              BAR_EMB = BAR_STATS + 1, BAR_ACK = BAR_EMB + 1, BAR_WR = BAR_ACK + 1  , BAR_WRF = BAR_WR + 2, BAR_X = BAR_WRF + 1  , NBAR = BAR_X + 5;
constexpr int SM_TOTAL = SM_BAR + NBAR * 8 - SMEM_BASE;
static_assert(SM_TOTAL <= 232448, "smem");
static_assert(NBAR <= 96, "barrier init");
__host__ __device__ constexpr uint32_t BAR(int i) { return SM_BAR + 8 * i; }
__host__ __device__ constexpr int ky_of(int kyo) { return kyo == 0 ? 1 : (kyo == 1 ? 0 : 2); }

constexpr unsigned SPIN_LIMIT = 1u << 16;

#define LS 1056
#define GS1 4
#define PD 0
#define WRDELAY 1700
#define KS 32
struct Scratch {
    float acc1[NB * LS];
    float acc2[NB * LS];
    unsigned wcnt[3 * NB * LS];
    unsigned w1cnt[NB * 8 * KS];
    float emb[NXTRA * NB * C];
    alignas(1024) unsigned char wt[2 * NSTAGE * STAGE_BYTES];
    uint4 box[NCTA * 1024];
};
__device__ __align__(1024) Scratch g_scratch;
#define TL(i) do {} while (0)
#define TLG(i) do {} while (0)

__device__ __forceinline__ unsigned clock32() { unsigned c; asm volatile("mov.u32 %0, %%clock;" : "=r"(c)); return c; }
__device__ __forceinline__ uint32_t mapa(uint32_t a, uint32_t rank) {
    uint32_t d;
    asm("mapa.shared::cluster.u32 %0, %1, %2;" : "=r"(d) : "r"(a), "r"(rank));
    return d;
}
#define S0 mapa(0, blockIdx.x & 1)
__device__ __forceinline__ void mbar_init(uint32_t bar, int cnt) {
    asm volatile("mbarrier.init.shared::cta.b64 [%0], %1;" ::"r"(bar + S0), "r"(cnt) : "memory");
}
__device__ __forceinline__ void mbar_arrive(uint32_t bar) {
    asm volatile("mbarrier.arrive.shared::cta.b64 _, [%0];" ::"r"(bar + S0) : "memory");
}
__device__ __forceinline__ void mbar_expect(uint32_t bar, uint32_t bytes) {
    asm volatile("mbarrier.arrive.expect_tx.shared::cta.b64 _, [%0], %1;" ::"r"(bar + S0), "r"(bytes) : "memory");
}
__device__ __forceinline__ bool mbar_try(uint32_t bar, uint32_t par) {
    uint32_t ok;
    asm volatile("{\n.reg .pred p;\nmbarrier.try_wait.parity.shared::cta.b64 p, [%1], %2;\nselp.u32 %0, 1, 0, p;\n}"
                 : "=r"(ok) : "r"(bar + S0), "r"(par) : "memory");
    return ok;
}
__device__ __forceinline__ bool mbar_test(uint32_t bar, uint32_t par) {
    uint32_t ok;
    asm volatile("{\n.reg .pred p;\nmbarrier.test_wait.parity.shared::cta.b64 p, [%1], %2;\nselp.u32 %0, 1, 0, p;\n}"
                 : "=r"(ok) : "r"(bar + S0), "r"(par) : "memory");
    return ok;
}
__device__ __forceinline__ void mbar_wait(uint32_t bar, uint32_t par) {
    unsigned it = 0;
#pragma unroll 1
    while (!mbar_try(bar, par) && ++it < SPIN_LIMIT) {}
}
__device__ __forceinline__ bool elect_one() {
    uint32_t p;
    asm volatile("{\n.reg .pred p;\nelect.sync _|p, 0xffffffff;\nselp.u32 %0, 1, 0, p;\n}" : "=r"(p));
    return p;
}
__device__ __forceinline__ void fence_async_smem() { asm volatile("fence.proxy.async.shared::cta;" ::: "memory"); }
__device__ __forceinline__ void fence_async_global() { asm volatile("fence.proxy.async.global;" ::: "memory"); }
__device__ __forceinline__ void fence_acquire() { asm volatile("fence.acquire.gpu;" ::: "memory"); }
__device__ __forceinline__ void bar_sync(int id, int n) { asm volatile("bar.sync %0, %1;" ::"r"(id), "r"(n) : "memory"); }
__device__ __forceinline__ void bar_arrive(int id, int n) { asm volatile("bar.arrive %0, %1;" ::"r"(id), "r"(n) : "memory"); }
__device__ __forceinline__ void bulk_g2s(uint32_t dst, const void* src, uint32_t bytes, uint32_t bar) {
    asm volatile("cp.async.bulk.shared::cluster.global.mbarrier::complete_tx::bytes [%0], [%1], %2, [%3];"
                 ::"r"(dst), "l"(src), "r"(bytes), "r"(bar) : "memory");
}
__device__ __forceinline__ void tma_x(uint32_t dst, const CUtensorMap* tm, int row, int ch, uint32_t bar) {
    asm volatile("cp.async.bulk.tensor.3d.shared::cluster.global.mbarrier::complete_tx::bytes [%0], [%1, {%2, %3, %4}], [%5];"
                 ::"r"(dst + S0), "l"(tm), "r"(0), "r"(row), "r"(ch), "r"(bar + S0) : "memory");
}
__device__ __forceinline__ uint4 ld_relaxed_v4(const void* p) {
    uint4 v;
    asm volatile("ld.relaxed.gpu.global.v4.u32 {%0,%1,%2,%3}, [%4];" : "=r"(v.x), "=r"(v.y), "=r"(v.z), "=r"(v.w) : "l"(p) : "memory");
    return v;
}
__device__ __forceinline__ unsigned ld_relaxed(const void* p) {
    unsigned v;
    asm volatile("ld.relaxed.gpu.global.u32 %0, [%1];" : "=r"(v) : "l"(p) : "memory");
    return v;
}
__device__ __forceinline__ void red_add4(float* p, float a, float b, float c, float d) {
    asm volatile("red.relaxed.gpu.global.add.v4.f32 [%0], {%1,%2,%3,%4};" ::"l"(p), "f"(a), "f"(b), "f"(c), "f"(d) : "memory");
}
__device__ __forceinline__ void sts128(uint32_t a, uint4 v) {
    asm volatile("st.shared.v4.u32 [%0], {%1,%2,%3,%4};" ::"r"(a + S0), "r"(v.x), "r"(v.y), "r"(v.z), "r"(v.w) : "memory");
}
__device__ __forceinline__ void sts128f(uint32_t a, float4 v) {
    asm volatile("st.shared.v4.f32 [%0], {%1,%2,%3,%4};" ::"r"(a + S0), "f"(v.x), "f"(v.y), "f"(v.z), "f"(v.w) : "memory");
}
__device__ __forceinline__ void sts32f(uint32_t a, float v) { asm volatile("st.shared.f32 [%0], %1;" ::"r"(a + S0), "f"(v) : "memory"); }
__device__ __forceinline__ uint4 lds128(uint32_t a) {
    uint4 v;
    asm volatile("ld.shared.v4.u32 {%0,%1,%2,%3}, [%4];" : "=r"(v.x), "=r"(v.y), "=r"(v.z), "=r"(v.w) : "r"(a + S0) : "memory");
    return v;
}
__device__ __forceinline__ float4 lds128f(uint32_t a) {
    float4 v;
    asm volatile("ld.shared.v4.f32 {%0,%1,%2,%3}, [%4];" : "=f"(v.x), "=f"(v.y), "=f"(v.z), "=f"(v.w) : "r"(a + S0) : "memory");
    return v;
}
__device__ __forceinline__ float2 lds64f(uint32_t a) {
    float2 v;
    asm volatile("ld.shared.v2.f32 {%0,%1}, [%2];" : "=f"(v.x), "=f"(v.y) : "r"(a + S0) : "memory");
    return v;
}
__device__ __forceinline__ float bf_lo(uint32_t u) { return __uint_as_float(u << 16); }
__device__ __forceinline__ float bf_hi(uint32_t u) { return __uint_as_float(u & 0xffff0000u); }
__device__ __forceinline__ uint32_t pack_bf(float lo, float hi) {
    uint32_t r;
    asm("cvt.rn.bf16x2.f32 %0, %1, %2;" : "=r"(r) : "f"(hi), "f"(lo));
    return r;
}
__device__ __forceinline__ float tanh_fast(float x) {
    float r;
    asm("tanh.approx.f32 %0, %1;" : "=f"(r) : "f"(x));
    return r;
}
__device__ __forceinline__ float silu_half(float h) { return fmaf(h, tanh_fast(h), h); }
__device__ __forceinline__ void ldsm4(uint32_t (&u)[4], uint32_t a) {
    asm volatile("ldmatrix.sync.aligned.m8n8.x4.shared.b16 {%0,%1,%2,%3}, [%4];"
                 : "=r"(u[0]), "=r"(u[1]), "=r"(u[2]), "=r"(u[3]) : "r"(a + S0) : "memory");
}
__device__ __forceinline__ void ldsm4t(uint32_t (&u)[4], uint32_t a) {
    asm volatile("ldmatrix.sync.aligned.m8n8.x4.trans.shared.b16 {%0,%1,%2,%3}, [%4];"
                 : "=r"(u[0]), "=r"(u[1]), "=r"(u[2]), "=r"(u[3]) : "r"(a + S0) : "memory");
}
__device__ __forceinline__ void stsm4(uint32_t a, uint32_t p0, uint32_t p1, uint32_t p2, uint32_t p3) {
    asm volatile("stmatrix.sync.aligned.m8n8.x4.shared.b16 [%0], {%1,%2,%3,%4};" ::"r"(a + S0), "r"(p0), "r"(p1), "r"(p2), "r"(p3) : "memory");
}
__device__ __forceinline__ void stsm4t(uint32_t a, uint32_t p0, uint32_t p1, uint32_t p2, uint32_t p3) {
    asm volatile("stmatrix.sync.aligned.m8n8.x4.trans.shared.b16 [%0], {%1,%2,%3,%4};" ::"r"(a + S0), "r"(p0), "r"(p1), "r"(p2), "r"(p3) : "memory");
}

#define R8(o) "+f"(d[o]), "+f"(d[o + 1]), "+f"(d[o + 2]), "+f"(d[o + 3]), "+f"(d[o + 4]), "+f"(d[o + 5]), "+f"(d[o + 6]), "+f"(d[o + 7])
template <uint32_t ALO, uint32_t BLO, uint64_t AHI = 8, uint64_t BHI = 48>
__device__ __forceinline__ void wgmma128(float (&d)[64]) {
    asm volatile(
        "wgmma.mma_async.sync.aligned.m64n128k16.f32.bf16.bf16 "
        "{%0,%1,%2,%3,%4,%5,%6,%7,%8,%9,%10,%11,%12,%13,%14,%15,%16,%17,%18,%19,%20,%21,%22,%23,%24,%25,%26,%27,%28,%29,%30,%31,"
        "%32,%33,%34,%35,%36,%37,%38,%39,%40,%41,%42,%43,%44,%45,%46,%47,%48,%49,%50,%51,%52,%53,%54,%55,%56,%57,%58,%59,%60,%61,%62,%63},"
        " %64, %65, 1, 1, 1, 0, 0;"
        : R8(0), R8(8), R8(16), R8(24), R8(32), R8(40), R8(48), R8(56)
        : "l"((AHI << 32) | ALO), "l"((BHI << 32) | BLO));
}
template <int S>
__device__ __forceinline__ void mma_stages(float (&d)[64], int conv, int tid, Scratch* gs) {
    constexpr uint32_t A = ((SM_ACT + S * 2 * CH_PITCH + 16) >> 4) | ((CH_PITCH >> 4) << 16);
    constexpr uint32_t B = (slot_addr(S % NS) >> 4) | (8u << 16);
    if (S == 0) {
        unsigned it = 0;
#pragma unroll 1
        while (!MMA0_WAIT(BAR(BAR_FULL), conv) && ++it < SPIN_LIMIT) {}
    }
    bool next_ok = true;
    constexpr uint32_t NEXT = S + 1 < NSTAGE ? BAR(BAR_FULL + S + 1) : BAR(BAR_EMB);
    const int npar = S + 1 < NSTAGE ? conv : 0;
    next_ok = mbar_test(NEXT, npar);
    if (S == 0 && tid == 0) TL(32 + conv * 24);
    asm volatile("wgmma.fence.sync.aligned;" ::: "memory");
    wgmma128<A, B>(d);
    wgmma128<A + 1, B + 16>(d);
    wgmma128<A + 2, B + 32>(d);
    asm volatile("wgmma.commit_group.sync.aligned;" ::: "memory");
    if (S >= LAG) {
        asm volatile("wgmma.wait_group.sync.aligned %0;" ::"n"(LAG) : "memory");
        if ((tid & 31) == 0) mbar_arrive(BAR(BAR_WEMPTY + (S + NS - LAG) % NS));
    }
    if (!next_ok) mbar_wait(NEXT, npar);
    if constexpr (S + 1 < NSTAGE) mma_stages<S + 1>(d, conv, tid, gs);
}

__device__ __forceinline__ int wblk_kc(int cta) { return ((cta >> 4) + 2) & 7; }
__device__ __forceinline__ void weight_load(uint4 (&t)[5], const __nv_bfloat16* w, int cta, int lane) {
    const char* base = reinterpret_cast<const char*>(w) + ((cta & 15) * 8 * C + wblk_kc(cta) * 16) * 18;
#pragma unroll
    for (int k = 0; k < 5; k++) {
        const int i = lane + 32 * k, row = (i * 57) >> 10;
        if (k < 4 || lane < 16) t[k] = __ldg(reinterpret_cast<const uint4*>(base + row * (C * 18 - 288) + i * 16));
    }
}
__device__ __forceinline__ void weight_block(uint32_t bounce, unsigned char* wt, int cta, int lane, bool readback, Scratch* gs) {
    unsigned char* dst = wt + wblk_kc(cta) * STAGE_BYTES + (cta & 15) * 768;
    if (lane < 16) {
        uint32_t v[36];
#pragma unroll
        for (int i = 0; i < 9; i++) {
            const uint4 q = lds128(bounce + (lane & 7) * 288 + (lane >> 3) * 144 + i * 16);
            v[4 * i] = q.x; v[4 * i + 1] = q.y; v[4 * i + 2] = q.z; v[4 * i + 3] = q.w;
        }
#pragma unroll
        for (int kyo = 0; kyo < 3; kyo++) {
#pragma unroll
            for (int kx = 0; kx < 3; kx++) {
                const int tap = ky_of(kyo) * 3 + kx;
                uint32_t o[4];
#pragma unroll
                for (int m = 0; m < 4; m++) {
                    const int i0 = 18 * m + tap, i1 = i0 + 9;
                    const uint32_t sel = ((i0 & 1) ? 0x32u : 0x10u) | ((i1 & 1) ? 0x7600u : 0x5400u);
                    o[m] = __byte_perm(v[i0 >> 1], v[i1 >> 1], sel);
                }
                *reinterpret_cast<uint4*>(dst + kyo * 8 * STAGE_BYTES + kx * 256 + lane * 16) = make_uint4(o[0], o[1], o[2], o[3]);
            }
        }
    }
    if (readback) {
        __syncwarp();
        unsigned acc = 0;
        if (lane < 24) {
#pragma unroll
            for (int i = 0; i < 3; i++) acc |= ld_relaxed(dst + i * 8 * STAGE_BYTES + lane * 32);
        }
        asm volatile("{\n.reg .pred p;\nsetp.eq.u32 p, %0, 0x9e3779b9;\n@p st.shared.u32 [%1], %0;\n}" ::"r"(acc), "r"(bounce + S0) : "memory");
    }
}
__device__ __forceinline__ uint32_t act2(uint32_t u, const float4& cf) {
    return pack_bf(silu_half(fmaf(bf_lo(u), cf.x, cf.z)), silu_half(fmaf(bf_hi(u), cf.y, cf.w)));
}
__device__ __forceinline__ void norm_unit(uint32_t (&u)[4], const float4& ca, const float4& cb) {
    u[0] = act2(u[0], ca); u[1] = act2(u[1], ca); u[2] = act2(u[2], cb); u[3] = act2(u[3], cb);
}
__device__ __forceinline__ void read_stats(uint32_t gst, float (&g)[8]) {
    asm volatile("ld.volatile.shared.v4.f32 {%0,%1,%2,%3}, [%4];" : "=f"(g[0]), "=f"(g[1]), "=f"(g[2]), "=f"(g[3]) : "r"(gst + S0) : "memory");
    asm volatile("ld.volatile.shared.v4.f32 {%0,%1,%2,%3}, [%4];" : "=f"(g[4]), "=f"(g[5]), "=f"(g[6]), "=f"(g[7]) : "r"(gst + 16 + S0) : "memory");
}
template <int T>
__device__ __forceinline__ void group_coefs(uint32_t gst, float (&g)[8], float4 (&cf)[8]) {
    unsigned it = 0;
    if (!__all_sync(0xffffffffu, g[2 * T] != 0.f)) {
        float rs0;
#pragma unroll 1
        do {
            SPINPAUSE;
            asm volatile("ld.volatile.shared.f32 %0, [%1];" : "=f"(rs0) : "r"(gst + 8 * T + S0) : "memory");
        } while (!__all_sync(0xffffffffu, rs0 != 0.f) && ++it < 8 * SPIN_LIMIT);
        read_stats(gst, g);
    }
    float4 &ca = cf[2 * T], &cb = cf[2 * T + 1];
    const float rs = g[2 * T], mr = g[2 * T + 1];
    ca.z = fmaf(-mr, ca.x, ca.z); ca.w = fmaf(-mr, ca.y, ca.w); ca.x *= rs; ca.y *= rs;
    cb.z = fmaf(-mr, cb.x, cb.z); cb.w = fmaf(-mr, cb.y, cb.w); cb.x *= rs; cb.y *= rs;
}
template <int FIRST, int N>
__device__ __forceinline__ void norm_block(uint32_t (&u)[4][4], float4 (&cf)[8], uint32_t act, uint32_t mask, uint32_t fbar, int lane) {
#pragma unroll
    for (int t = FIRST; t < FIRST + N; t++) {
        norm_unit(u[t], cf[2 * t], cf[2 * t + 1]);
        stsm4(act + t * 2 * KC_BYTES, u[t][0] & mask, u[t][1] & mask, u[t][2] & mask, u[t][3] & mask);
    }
    fence_async_smem();
    __syncwarp();
    if (lane < N) mbar_arrive(fbar + 16 * (FIRST + lane));
}
__device__ __forceinline__ void publish(uint32_t bar, int lane) {
    fence_async_smem();
    __syncwarp();
    if (lane == 0) mbar_arrive(bar);
}
template <int T>
__device__ __forceinline__ void next_unit(uint32_t (&u)[4][4], float4 (&cf)[8], uint32_t gst, float (&g)[8], uint32_t act, uint32_t fbar, int lane) {
    const bool have = __all_sync(0xffffffffu, g[2 * T] != 0.f);
    if (!have) publish(fbar + 16 * (T - 1), lane);
    group_coefs<T>(gst, g, cf);
    norm_unit(u[T], cf[2 * T], cf[2 * T + 1]);
    if (have) publish(fbar + 16 * (T - 1), lane);
    stsm4(act + T * 2 * KC_BYTES, u[T][0], u[T][1], u[T][2], u[T][3]);
}
__device__ __forceinline__ void stat_mma(float (&c)[4], uint32_t p, uint32_t q) {
    asm("mma.sync.aligned.m16n8k16.row.col.f32.bf16.bf16.f32 {%0,%1,%2,%3}, {%4,%5,%6,%5}, {%4,%6}, {%0,%1,%2,%3};"
        : "+f"(c[0]), "+f"(c[1]), "+f"(c[2]), "+f"(c[3]) : "r"(p), "r"(0x3f803f80u), "r"(q));
}
__device__ __forceinline__ void stat_store(const float (&c)[4], uint32_t dst, int lane) {
    const int g = lane >> 2, t = lane & 3;
    if (t == (g >> 1)) sts32f(dst + g * 4, (g & 1) ? c[1] : c[0]);
    if (g == 7) sts32f(dst + 32 + t * 4, c[2] + c[3]);
}
__device__ __forceinline__ float sum4(float4 v) { return (v.x + v.y) + (v.z + v.w); }
__device__ __forceinline__ void stat_publish(uint32_t src, float* acc, int lane, bool real) {
    const uint32_t a = src + (lane & 15) * 48;
    float q = sum4(lds128f(a)) + sum4(lds128f(a + 16)), sm = sum4(lds128f(a + 32));
    q += __shfl_xor_sync(0xffffffffu, q, 1); sm += __shfl_xor_sync(0xffffffffu, sm, 1);
    q += __shfl_xor_sync(0xffffffffu, q, 2); sm += __shfl_xor_sync(0xffffffffu, sm, 2);
    if (real && (lane & 19) == 0) red_add4(acc + lane, 1.f, sm, q, 1.f);
}
__device__ __forceinline__ void fence_acc(float (&d)[64]) {
#pragma unroll
    for (int i = 0; i < 64; i++) asm volatile("" : "+f"(d[i])::"memory");
}
__device__ __forceinline__ void ld_unit(uint32_t (&u)[4], const uint4* p) {
    asm volatile("ld.relaxed.gpu.global.v4.u32 {%0,%1,%2,%3}, [%4];" : "=r"(u[0]), "=r"(u[1]), "=r"(u[2]), "=r"(u[3]) : "l"(p) : "memory");
}

__device__ __noinline__ void side_jobs(const __nv_bfloat16* __restrict__ t_emb, const __nv_bfloat16* __restrict__ w_emb,
                                       const __nv_bfloat16* __restrict__ w2, Scratch* __restrict__ gs, unsigned clk0) {
    const int tid = threadIdx.x, warp = tid >> 5, lane = tid & 31, j = blockIdx.x;
    float tv = 0.f;
    if (lane < 24) tv = __bfloat162float(t_emb[(lane / 12) * E + j * 192 + warp * 12 + lane % 12]);
    if (tid == 0) {
        mbar_init(BAR(0), 1);
        mbar_expect(BAR(0), 192 * C * 2);
        fence_async_smem();
        while (clock32() - clk0 < SDELAY) {}
#pragma unroll
        for (int i = 0; i < 4; i++)
            asm volatile("cp.async.bulk.prefetch.L2.global [%0], 18432;" ::"l"(reinterpret_cast<const char*>(w2) + (j * 4 + i) * 18432) : "memory");
#pragma unroll
        for (int i = 0; i < 4; i++) bulk_g2s(S0 + SM_W + i * 12288, w_emb + (j * 192 + i * 48) * C, 12288, S0 + BAR(0));
    }
    if (j == 0 && tid < 32) gs->acc2[(tid >> 4) * LS + (tid & 15)] = 0.f;
    const float sv = silu_half(0.5f * tv);
    __syncthreads();
    mbar_wait(BAR(0), 0);
    float acc[8] = {0.f, 0.f, 0.f, 0.f, 0.f, 0.f, 0.f, 0.f};
#pragma unroll
    for (int i = 0; i < 12; i++) {
        const float2 wq = lds64f(SM_W + (warp * 12 + i) * 256 + lane * 8);
        const uint32_t wx = __float_as_uint(wq.x), wy = __float_as_uint(wq.y);
#pragma unroll
        for (int bb = 0; bb < 2; bb++) {
            const float sx = __shfl_sync(0xffffffffu, sv, bb * 12 + i);
            acc[4 * bb + 0] = fmaf(sx, bf_lo(wx), acc[4 * bb + 0]); acc[4 * bb + 1] = fmaf(sx, bf_hi(wx), acc[4 * bb + 1]);
            acc[4 * bb + 2] = fmaf(sx, bf_lo(wy), acc[4 * bb + 2]); acc[4 * bb + 3] = fmaf(sx, bf_hi(wy), acc[4 * bb + 3]);
        }
    }
    sts128f(SM_ACT + warp * 1024 + lane * 16, make_float4(acc[0], acc[1], acc[2], acc[3]));
    sts128f(SM_ACT + warp * 1024 + 512 + lane * 16, make_float4(acc[4], acc[5], acc[6], acc[7]));
    __syncthreads();
    if (tid < 128) {
        float2 sum = make_float2(0.f, 0.f);
#pragma unroll
        for (int w = 0; w < 16; w++) { const float2 p = lds64f(SM_ACT + w * 1024 + tid * 8); sum.x += p.x; sum.y += p.y; }
        *reinterpret_cast<float2*>(&gs->emb[j * NB * C + tid * 2]) = sum;
        bar_sync(1, 128);
        if (tid < 2) asm volatile("red.release.gpu.global.add.u32 [%0], 1;" ::"l"(&gs->wcnt[(2 * NB + tid) * LS]) : "memory");
    }
}

__global__ void __cluster_dims__(2, 1, 1) __launch_bounds__(NTHREADS, 1)
resblock_kernel(const __nv_bfloat16* __restrict__ w1, const __nv_bfloat16* __restrict__ x,
                const __nv_bfloat16* __restrict__ t_emb, const __nv_bfloat16* __restrict__ g1,
                const __nv_bfloat16* __restrict__ be1, const __nv_bfloat16* __restrict__ w_emb,
                const __nv_bfloat16* __restrict__ g2, const __nv_bfloat16* __restrict__ be2,
                const __nv_bfloat16* __restrict__ w2, __nv_bfloat16* __restrict__ out, Scratch* __restrict__ gs,
                const __grid_constant__ CUtensorMap xmap, const __grid_constant__ CUtensorMap wmap) {
    const unsigned clk0 = clock32();
    if (threadIdx.x == 480 && blockIdx.x >= NXTRA) TLG(1);
    const int tid = threadIdx.x, lane = tid & 31;
    const int cta = blockIdx.x - NXTRA, b = cta >> 6, r = cta & 63;
    uint4 v[5];
    if (tid < 32) weight_load(v, w1, cta & (NCTA - 1), lane);
    uint4 xv[8];
    const int wg4 = (tid >> 5) - 1;
    const bool early = tid >= 32 && wg4 < NLDG;
    if (early) {
        const char* src = reinterpret_cast<const char*>(x) + (uint32_t)((((b & 1) * C + wg4 * 32 + (lane >> 3)) * HW + r) * HW * 2 + (lane & 7) * 16);
        while (clock32() - clk0 < XDELAY + (wg4 >> 1) * XSTAG + (wg4 & 1) * XSTAG2) {}
#pragma unroll
        for (int i = 0; i < 8; i++) xv[i] = __ldg(reinterpret_cast<const uint4*>(src + i * (4 * HW * HW * 2)));
    }
    const int warp = __shfl_sync(0xffffffffu, tid >> 5, 0);
    if (cta < 0) { side_jobs(t_emb, w_emb, w2, gs, clk0); return; }

    if (warp != 4 && warp != 8) asm volatile("barrier.cluster.arrive.relaxed.aligned;" ::: "memory");
    const bool has_outer = (r != 0) && (r != HW - 1);
    if (warp == 1 || warp == 2 || warp == 3 || warp == 5) {
        const int g = warp < 4 ? warp - 1 : 3;
        if (elect_one()) {
            if (g >= NLDG) asm volatile("prefetch.tensormap [%0];" ::"l"(&xmap) : "memory");
            mbar_init(BAR(BAR_X) + 8 * g, 1);
            if (g >= NLDG) mbar_expect(BAR(BAR_X) + 8 * g, 4096);
            fence_async_smem();
        }
        __syncwarp();
        bar_arrive(4, 256 + 32 + 128);
        if (g >= NLDG) {
            while (clock32() - clk0 < XDELAY + (g >> 1) * XSTAG + (g & 1) * XSTAG2) {}
            if (elect_one()) tma_x(SM_XOWN + g * 4096, &xmap, r, b * C + g * 32, BAR(BAR_X) + 8 * g);
            __syncwarp();
            mbar_wait(BAR(BAR_X) + 8 * g, 0);
#pragma unroll
            for (int k = 0; k < 8; k++) xv[k] = lds128(SM_XOWN + g * 4096 + k * 512 + lane * 16);
        }
        float c[8][4];
#pragma unroll
        for (int k = 0; k < 8; k++) {
            c[k][0] = c[k][1] = c[k][2] = c[k][3] = 0.f;
            stat_mma(c[k], xv[k].x, xv[k].y); stat_mma(c[k], xv[k].z, xv[k].w);
        }
#pragma unroll
        for (int i = 0; i < 4; i++) c[0][i] = ((c[0][i] + c[1][i]) + (c[2][i] + c[3][i])) + ((c[4][i] + c[5][i]) + (c[6][i] + c[7][i]));
        stat_store(c[0], SM_RED + g * 48, lane);
        __syncwarp();
        if (lane == 0) {
            const uint32_t a = SM_RED + g * 48;
            red_add4(&gs->acc1[b * LS + g * 4], 1.f, sum4(lds128f(a + 32)), sum4(lds128f(a)) + sum4(lds128f(a + 16)), 1.f);
            TL(74 + g);
        }
        if (g < NLDG) {
#pragma unroll
            for (int i = 0; i < 8; i++)
                sts128(SM_XOWN + g * 4096 + i * 512 + (lane >> 3) * 128 + (((lane & 7) ^ ((lane >> 3) + 4 * (i & 1))) << 4), xv[i]);
            __syncwarp();
            if (lane == 0) mbar_arrive(BAR(BAR_X) + 8 * g);
        }
    }
    if (warp == 4) {
            if (elect_one()) {
#pragma unroll
                for (int i = 0; i < NSTAGE; i++) mbar_init(BAR(BAR_FULL + i), (i >> 3) == 1 ? 1 : 5);
#pragma unroll
                for (int i = 0; i < NS + 2; i++) mbar_init(BAR(BAR_WEMPTY + i), 4);
#pragma unroll
                for (int i = BAR_STATS; i < BAR_X; i++) mbar_init(BAR(i), i == BAR_EMB ? 3 : 1);
                mbar_init(BAR(BAR_X + 4), 1);
                asm volatile("fence.mbarrier_init.release.cluster;" ::: "memory");
            }
            if (lane < 4) sts128(SM_GST + lane * 16, make_uint4(0, 0, 0, 0));
            __syncwarp();
            fence_async_smem();
            bar_arrive(0, 96);
            bar_arrive(5, 64);
            bar_arrive(4, 256 + 32 + 128);
            if (elect_one()) {
                asm volatile("prefetch.tensormap [%0];" ::"l"(&wmap) : "memory");
                mbar_expect(BAR(BAR_WR), 36864);
                mbar_expect(BAR(BAR_WR + 1), 36864);
                while (clock32() - clk0 < WRDELAY) {}
#pragma unroll
                for (int i = 0; i < 2; i++)
                    asm volatile("cp.async.bulk.tensor.2d.shared::cluster.global.mbarrier::complete_tx::bytes [%0], [%1, {%2, %3}], [%4];"
                                 ::"r"(S0 + (i ? slot_addr(2) : SM_ACT)), "l"(&wmap), "r"(i * 144), "r"(0), "r"(S0 + BAR(BAR_WR + i)) : "memory");
            }
            __syncwarp();
            if (lane < 16) sts128(SM_ONES + lane * 16, make_uint4(lane < 8 ? 0x3f803f80u : 0u, 0, 0, 0));
            fence_async_smem();
            bar_arrive(7, 160);
            asm volatile("barrier.cluster.arrive.relaxed.aligned;" ::: "memory");
            if (lane == 0) TL(5);
            while (clock32() - clk0 < W2DELAY) {}
            weight_load(v, w2, cta, lane);
        }
    if (warp == 0 || warp == 4) {
        const int k = warp >> 2;
#pragma unroll
        for (int i = 0; i < 5; i++)
            if (i < 4 || lane < 16) sts128(SM_BNC + k * 2304 + (lane + 32 * i) * 16, v[i]);
        if (lane == 0) TL(k ? 14 : 81);
        __syncwarp();
        weight_block(SM_BNC + k * 2304, gs->wt + k * NSTAGE * STAGE_BYTES, cta, lane, true, gs);
        __syncwarp();
        if (lane == 0) TL(k ? 13 : 4);
        if (lane < 2) asm volatile("red.relaxed.gpu.global.add.u32 [%0], 1;" ::"l"(k ? &gs->wcnt[(NB + lane) * LS] : &gs->w1cnt[(lane * 8 + wblk_kc(cta)) * KS]) : "memory");
    }

    if (warp >= 8) {
        const int nw = warp - 8;
        if (nw < 2) {
            const uint2 ga = __ldg(reinterpret_cast<const uint2*>(nw ? g2 : g1) + lane), bt = __ldg(reinterpret_cast<const uint2*>(nw ? be2 : be1) + lane);
            sts128f(SM_COEF + nw * 1024 + lane * 32, make_float4(0.5f * bf_lo(ga.x), 0.5f * bf_hi(ga.x), 0.5f * bf_lo(bt.x), 0.5f * bf_hi(bt.x)));
            sts128f(SM_COEF + nw * 1024 + lane * 32 + 16, make_float4(0.5f * bf_lo(ga.y), 0.5f * bf_hi(ga.y), 0.5f * bf_lo(bt.y), 0.5f * bf_hi(bt.y)));
        }
        bar_sync(4, 256 + 32 + 128);
#pragma unroll 1
        for (int kc = -1; kc < 2; kc++) {
            if (kc >= 0) mbar_wait(BAR(BAR_WR) + 8 * kc, 0);
            const uint32_t src = (kc > 0 ? slot_addr(2) : SM_ACT) + (nw * 16 + (lane >> 4) * 8 + (lane & 7)) * 288 + ((lane >> 3) & 1) * 144;
            uint32_t wv[36];
#pragma unroll
            for (int i = 0; i < 9; i++) {
                const uint4 q = lds128(src + i * 16);
                wv[4 * i] = q.x; wv[4 * i + 1] = q.y; wv[4 * i + 2] = q.z; wv[4 * i + 3] = q.w;
            }
            const uint32_t dst = slot_addr(0) + (kc & 1) * STAGE_BYTES + (nw * 2 + (lane >> 4)) * 768 + (lane & 15) * 16;
#pragma unroll
            for (int tap = 0; tap < 9; tap++) {
                uint32_t o[4];
#pragma unroll
                for (int m = 0; m < 4; m++) {
                    const int i0 = 18 * m + tap, i1 = i0 + 9;
                    o[m] = __byte_perm(wv[i0 >> 1], wv[i1 >> 1], ((i0 & 1) ? 0x32u : 0x10u) | ((i1 & 1) ? 0x7600u : 0x5400u));
                }
                if (tap / 3 == 1 || (tap / 3 == 0) == (r & 1))
                    sts128(dst + (tap / 3 == 1 ? 0 : 8 * STAGE_BYTES) + (tap % 3) * 256, make_uint4(o[0], o[1], o[2], o[3]));
            }
        }
        fence_async_smem();
        bar_sync(3, 256);
        if (tid == 256) { mbar_arrive(BAR(BAR_WRF)); TL(92); }
        if (nw == 0) asm volatile("barrier.cluster.arrive.relaxed.aligned;" ::: "memory");
        if (tid < 256 + 68) {
            const int t = tid - 256;
            sts128(SM_ACT + (t < 66 ? (t >> 1) * CH_PITCH : 3 * ROW_BYTES) + (t & 1) * 16, make_uint4(0, 0, 0, 0));
        }
        const int par = nw >> 2, wq = nw & 3;
        const uint32_t act_off = SM_ACT + (par * 2 + (lane >> 4)) * CH_PITCH + (2 + wq * 16 + (lane & 15)) * 16;
        const uint32_t stg_off = (par * 16 + (lane >> 4) * 8 + (lane & 7)) * 128 + (((2 * wq + ((lane >> 3) & 1)) ^ (lane & 7)) << 4);
        const uint32_t cfa = SM_COEF + par * 128 + (lane & 3) * 16;
        const uint32_t fbar = BAR(BAR_FULL) + 8 * par;
        uint4* inbox = gs->box + cta * 1024 + nw * 32 + lane;
#pragma unroll 1
        for (int conv = 0; conv < 2; conv++) {
            uint32_t u[4][4], w[4][4];
            float4 cf[8];
            if (conv == 0) {
#pragma unroll
                for (int i = 0; i < 4; i++) { mbar_wait(BAR(BAR_X + i), 0); ldsm4t(u[i], SM_XOWN + stg_off + i * 4096); }
            } else {
                mbar_wait(BAR(BAR_HW), 0);
#pragma unroll
                for (int i = 0; i < 4; i++) ldsm4(u[i], act_off + i * 2 * KC_BYTES);
            }
#pragma unroll
            for (int i = 0; i < 8; i++) cf[i] = lds128f(cfa + conv * 1024 + (i >> 1) * 256 + (i & 1) * 64);
            const uint32_t gst = SM_GST + conv * 32;
            float gv[8];
            read_stats(gst, gv);
            group_coefs<0>(gst, gv, cf);
            if (tid == 256) TL(22 + conv * 4);
            if (par) { const unsigned c1 = clock32(); while (clock32() - c1 < PDELAY) {} }
            norm_block<0, 1>(u, cf, act_off, ~0u, fbar, lane);
            if (tid == 256) TL(8 + conv * 8);
            group_coefs<1>(gst, gv, cf);
            norm_unit(u[1], cf[2], cf[3]);
            stsm4(act_off + 2 * KC_BYTES, u[1][0], u[1][1], u[1][2], u[1][3]);
            next_unit<2>(u, cf, gst, gv, act_off, fbar, lane);
            next_unit<3>(u, cf, gst, gv, act_off, fbar, lane);
            publish(fbar + 48, lane);
            if (tid == 256) TL(84 + conv);
            if (has_outer) {
                mbar_wait(BAR(BAR_X + 4), conv);
                if (conv == 0) {
#pragma unroll
                    for (int i = 0; i < 4; i++) ldsm4t(w[i], SM_XOUT + stg_off + i * 4096);
                } else {
#pragma unroll
                    for (int i = 0; i < 4; i++) {
                        const uint4 q = lds128(SM_XOWN + (tid - 256) * 16 + i * 4096);
                        w[i][0] = q.x; w[i][1] = q.y; w[i][2] = q.z; w[i][3] = q.w;
                    }
                    unsigned it = 0;
                    while (true) {
                        bool ok = true;
#pragma unroll
                        for (int i = 0; i < 16; i++) ok = ok && w[i >> 2][i & 3] != 0;
                        if (__all_sync(0xffffffffu, ok) || ++it > SPIN_LIMIT) break;
#pragma unroll
                        for (int i = 0; i < 4; i++) ld_unit(w[i], inbox + i * 256);
                    }
#pragma unroll
                    for (int i = 0; i < 16; i++) w[i >> 2][i & 3] = ~w[i >> 2][i & 3];
                }
            }
            if (conv == 0) {
                bar_sync(3, 256);
                if (nw == 0) sts128(SM_ACT + 2 * ROW_BYTES + (lane >> 1) * CH_PITCH + (lane & 1) * 16, make_uint4(0, 0, 0, 0));
            }
            if (tid == 256) TL(24 + conv * 4);
            norm_block<0, 2>(w, cf, act_off + 2 * ROW_BYTES, has_outer ? ~0u : 0u, fbar + 128, lane);
            if (tid == 256) TL(88 + conv);
            norm_block<2, 2>(w, cf, act_off + 2 * ROW_BYTES, has_outer ? ~0u : 0u, fbar + 128, lane);
            if (tid == 256) TL(23 + conv * 4);
        }
        if (has_outer) {
            mbar_wait(BAR(BAR_FULL + NSTAGE - 1), 1);
#pragma unroll
            for (int i = 0; i < 4; i++) inbox[i * 256] = make_uint4(0, 0, 0, 0);
        }
        {
            const int oc0 = (tid - 256) >> 3, seg = lane & 7;
            __nv_bfloat16* dst = out + ((size_t)(b * C + oc0) * HW + r) * HW + seg * 8;
            const uint32_t src = SM_XOWN + oc0 * 128 + ((seg ^ (oc0 & 7)) << 4);
            bar_sync(6, 128 + 256);
#pragma unroll
            for (int i = 0; i < 4; i++) *reinterpret_cast<uint4*>(dst + (size_t)i * 32 * HW * HW) = lds128(src + i * 4096);
            if (tid == 256) { TL(20); TLG(21); }
        }
    } else if (warp < 4) {
        const int wq = warp;
        bar_sync(7, 160);

        const uint32_t xbase = SM_XOWN + ((lane >> 4) * 8 + (lane & 7)) * 128 + (((2 * wq + ((lane >> 3) & 1)) ^ (lane & 7)) << 4);
        float d[64];
#pragma unroll
        for (int i = 0; i < 64; i++) d[i] = 0.f;
#pragma unroll 1
        for (int conv = 0; conv < 2; conv++) {
            fence_acc(d);
            mma_stages<0>(d, conv, tid, gs);
            if (conv == 0) {
                asm volatile("wgmma.fence.sync.aligned;" ::: "memory");
                wgmma128<(SM_ONES >> 4) | (8u << 16), (SM_EMB >> 4), 0, 8>(d);
                asm volatile("wgmma.commit_group.sync.aligned;" ::: "memory");
            }
            asm volatile("wgmma.wait_group.sync.aligned 0;" ::: "memory");
            fence_acc(d);
            if (tid == 0) TL(10 + conv * 8);
            uint32_t hp[32];
#pragma unroll
            for (int i = 0; i < 32; i++) hp[i] = pack_bf(d[2 * i], d[2 * i + 1]);
            if (conv == 1) {
#pragma unroll
                for (int kc = 0; kc < 8; kc++) stsm4t(xbase + kc * 2048, hp[4 * kc], hp[4 * kc + 1], hp[4 * kc + 2], hp[4 * kc + 3]);
                bar_arrive(6, 128 + 256);
                break;
            }
#pragma unroll
            for (int g = 0; g < 4; g++) {
                float c[4] = {0.f, 0.f, 0.f, 0.f};
#pragma unroll
                for (int i = 0; i < 4; i++) stat_mma(c, hp[8 * g + 2 * i], hp[8 * g + 2 * i + 1]);
                stat_store(c, SM_RED + (g * 4 + wq) * 48, lane);
            }
            bar_sync(2, 128);
            if (wq == 0) stat_publish(SM_RED, &gs->acc2[b * LS], lane, true);
            if (tid == 0) TL(11);
            const uint32_t hbase = SM_ACT + (lane >> 4) * CH_PITCH + (2 + wq * 16 + (lane & 15)) * 16;
#pragma unroll
            for (int kc = 0; kc < 8; kc++) stsm4(hbase + kc * 2 * CH_PITCH, hp[4 * kc], hp[4 * kc + 1], hp[4 * kc + 2], hp[4 * kc + 3]);
            __syncwarp();
            if (lane == 0) mbar_arrive(BAR(BAR_HW));
            if (lane < LAG) mbar_arrive(BAR(BAR_WEMPTY + (NSTAGE - LAG) % NS) + 8 * lane);
            if (has_outer) {
                uint4* outbox = gs->box + (cta + ((r & 1) ? 1 : -1)) * 1024 + tid;
#pragma unroll
                for (int kc = 0; kc < 8; kc++) outbox[kc * 128] = make_uint4(~hp[4 * kc], ~hp[4 * kc + 1], ~hp[4 * kc + 2], ~hp[4 * kc + 3]);
            }
            if (tid == 0) TL(12);
#pragma unroll
            for (int kc = 0; kc < 8; kc++) {
                uint32_t p[4];
                ldsm4t(p, xbase + kc * 2048);
#pragma unroll
                for (int i = 0; i < 4; i++) { d[8 * kc + 2 * i] = bf_lo(p[i]); d[8 * kc + 2 * i + 1] = bf_hi(p[i]); }
            }
            fence_async_smem();
            __syncwarp();
            if (lane == 0) mbar_arrive(BAR(BAR_XFREE));
        }
        {
        }
    } else if (warp < 6) {
        if (warp == 5) {
            bar_sync(5, 64);
            mbar_wait(BAR(BAR_FULL + OAFTER), 0);
            if (has_outer && elect_one()) {
                mbar_expect(BAR(BAR_X + 4), 16384);
#pragma unroll
                for (int i = 0; i < 4; i++) tma_x(SM_XOUT + i * 4096, &xmap, r + ((r & 1) ? 1 : -1), b * C + i * 32, BAR(BAR_X + 4));
            }
            __syncwarp();
            asm volatile("barrier.cluster.wait.acquire.aligned;" ::: "memory");
            const uint32_t peer = (r & 1) ^ 1;
            const uint32_t self0 = mapa(0, r & 1), peer0 = mapa(0, peer);
#pragma unroll 1
            for (int conv = 0; conv < 2; conv++) {
#pragma unroll 1
                for (int kc = 0; kc < 8; kc++) {
                    mbar_wait(BAR(BAR_FULL) + 8 * kc, conv);
                    if (elect_one())
                        asm volatile("cp.async.bulk.shared::cluster.shared::cta.mbarrier::complete_tx::bytes [%0], [%1], %2, [%3];"
                                     ::"r"(peer0 + SM_ACT + ROW_BYTES + kc * KC_BYTES), "r"(self0 + SM_ACT + kc * KC_BYTES), "r"(KC_BYTES),
                                       "r"(peer0 + BAR(BAR_FULL + 8) + 8 * kc) : "memory");
                }
                if (lane == 0) TL(86 + conv);
#pragma unroll 1
                for (int kc = 0; kc < 8; kc++) mbar_wait(BAR(BAR_FULL + 8) + 8 * kc, conv);
                if (lane == 0)
                    asm volatile("mbarrier.arrive.relaxed.cluster.shared::cluster.b64 _, [%0];" ::"r"(peer0 + (conv ? BAR(BAR_ACK) : BAR(BAR_EMB))) : "memory");
            }
            mbar_wait(BAR(BAR_ACK), 0);
        } else {
            mbar_wait(BAR(BAR_STATS), 0);
            unsigned it = 0;
            while (ld_relaxed(&gs->wcnt[(2 * NB + b) * LS]) < (unsigned)NXTRA && ++it < SPIN_LIMIT) __nanosleep(100);
            fence_acquire();
            float ev[4] = {0.f, 0.f, 0.f, 0.f};
#pragma unroll
            for (int j = 0; j < NXTRA; j++) {
                const uint4 ef = ld_relaxed_v4(&gs->emb[(j * NB + b) * C + lane * 4]);
                ev[0] += __uint_as_float(ef.x); ev[1] += __uint_as_float(ef.y); ev[2] += __uint_as_float(ef.z); ev[3] += __uint_as_float(ef.w);
            }
#pragma unroll
            for (int i = 0; i < 4; i++) {
                const float hi = bf_lo(pack_bf(ev[i], 0.f));
                sts128(SM_EMB + (lane * 4 + i) * 16, make_uint4(pack_bf(hi, ev[i] - hi), 0, 0, 0));
            }
            fence_async_smem();
            __syncwarp();
            if (lane == 0) { mbar_arrive(BAR(BAR_EMB)); TL(19); }
        }
    } else if (warp == 6) {
        bar_sync(0, 96);
        const uint32_t ebytes = STAGE_BYTES + ((lane >> 3) == 1 ? KC_BYTES : 0);
        if (lane < NSTAGE) mbar_expect(BAR(BAR_FULL) + 8 * lane, ebytes - ((lane & 22) == 0 ? STAGE_BYTES : 0));
        const int swap = (r & 1) ? 0 : 8 * STAGE_BYTES;
        unsigned it = 0;
        {
            int g = 2;
#pragma unroll 1
            while (g < NS) {
                unsigned ready = __ballot_sync(0xffffffffu, ld_relaxed(&gs->w1cnt[(b * 8 + (lane & 7)) * KS]) >= 16u) >> g;
                if (++it > SPIN_LIMIT) ready = ~0u;
                if (!(ready & 1)) continue;
                fence_acquire();
                fence_async_global();
                if (g == 2) mbar_wait(BAR(BAR_WRF), 0);
                if (lane == 0) TL(g > 2 ? 3 : 6);
#pragma unroll 1
                for (; (ready & 1) && g < NS; g++, ready >>= 1)
                    if ((g & 6) != 0 && elect_one())
                        bulk_g2s(S0 + SM_W + g * STAGE_BYTES, gs->wt + g * STAGE_BYTES + (g >= 8 ? swap : 0), STAGE_BYTES, S0 + BAR(BAR_FULL) + 8 * g);
            }
        }
#pragma unroll 1
        for (int q = 3; q < 12; q++) {
            const int conv = q >= 6, qs = conv ? q - 6 : q, sl = q % 3;
            const unsigned char* wsrc = gs->wt + q * 4 * STAGE_BYTES + (qs < 2 ? 0 : (qs < 4 ? swap : -swap));
            const uint32_t par = (q / 3 - 1) & 1;
            if (q == 6) {
                it = 0;
                while (ld_relaxed(&gs->wcnt[(NB + b) * LS]) < (unsigned)NCTA && ++it < SPIN_LIMIT) {}
                fence_acquire();
                fence_async_global();
                if (lane == 0) { mbar_arrive(BAR(BAR_EMB)); TL(2); }
            }
#pragma unroll
            for (int i = 0; i < 4; i++) {
                mbar_wait(BAR(BAR_WEMPTY + i) + 32 * sl, par);
                if (i == 0 && (q == 6 || q == 9)) {
                    if ((lane >= NS) == (q == 9) && lane < NSTAGE) mbar_expect(BAR(BAR_FULL) + 8 * lane, ebytes);
                    __syncwarp();
                }
                if (elect_one())
                    bulk_g2s(S0 + SM_W + (sl * 4 + i) * STAGE_BYTES, wsrc + i * STAGE_BYTES, STAGE_BYTES, S0 + BAR(BAR_FULL + i) + 32 * qs);
            }
        }
    } else {
        bar_sync(0, 96);
#pragma unroll 1
        for (int conv = 0; conv < 2; conv++) {
            if (conv == 1) mbar_wait(BAR(BAR_HW), 0);
            const float* asrc = (conv ? gs->acc2 : gs->acc1) + b * LS + (lane & 3) * 4;
            unsigned it = 0;
#pragma unroll 1
            while (true) {
                const uint4 f = ld_relaxed_v4(asrc);
                const bool ok = ((f.x == 0x42800000u) & (f.w == 0x42800000u)) || ++it > SPIN_LIMIT;
                if (ok && lane < 4) {
                    const float inv_n = 1.0f / (32.0f * HW * HW);
                    const float mean = __uint_as_float(f.y) * inv_n;
                    const float rs = rsqrtf(fmaxf(fmaf(-mean, mean, __uint_as_float(f.z) * inv_n), 0.f) + 1e-5f);
                    asm volatile("st.shared.v2.f32 [%0], {%1,%2};" ::"r"(S0 + SM_GST + conv * 32 + lane * 8), "f"(rs == 0.f ? 1e-38f : rs), "f"(mean * rs) : "memory");
                }
                if (__all_sync(0xffffffffu, ok)) break;
            }
            if (lane == 0) { mbar_arrive(BAR(BAR_STATS)); TL(7 + conv * 8); }
        }
        mbar_wait(BAR(BAR_XFREE), 0);
        if (has_outer && elect_one()) {
            mbar_expect(BAR(BAR_X + 4), 16384);
            bulk_g2s(S0 + SM_XOWN, gs->box + cta * 1024, 16384, S0 + BAR(BAR_X + 4));
        }
        if (r == 0) {
            if (lane < 16) gs->acc1[b * LS + lane] = 0.f;
            if (lane < 3) gs->wcnt[(lane * NB + b) * LS] = 0;
            if (lane < 8) gs->w1cnt[(b * 8 + lane) * KS] = 0;
        }
    }
}

}

extern "C" void kernel_launch(void* const* d_in, const int* in_sizes, int n_in, void* d_out, int out_size) {
    (void)in_sizes; (void)n_in; (void)out_size;
    typedef CUresult (*EncodeFn)(CUtensorMap*, CUtensorMapDataType, cuuint32_t, void*, const cuuint64_t*, const cuuint64_t*,
                                 const cuuint32_t*, const cuuint32_t*, CUtensorMapInterleave, CUtensorMapSwizzle,
                                 CUtensorMapL2promotion, CUtensorMapFloatOOBfill);
    static Scratch* gs = nullptr;
    static EncodeFn encode = nullptr;
    if (!gs) {
        cudaFuncSetAttribute(resblock_kernel, cudaFuncAttributeMaxDynamicSharedMemorySize, SM_TOTAL);
        cudaGetSymbolAddress((void**)&gs, g_scratch);
        cudaDriverEntryPointQueryResult qr;
        cudaGetDriverEntryPoint("cuTensorMapEncodeTiled", (void**)&encode, cudaEnableDefault, &qr);
    }
    CUtensorMap xmap, wmap;
    const cuuint64_t dims[3] = {HW, HW, NB * C}, strides[2] = {HW * 2, HW * HW * 2};
    const cuuint32_t box[3] = {HW, 1, 32}, es[3] = {1, 1, 1};
    encode(&xmap, CU_TENSOR_MAP_DATA_TYPE_BFLOAT16, 3, d_in[0], dims, strides, box, es, CU_TENSOR_MAP_INTERLEAVE_NONE,
           CU_TENSOR_MAP_SWIZZLE_128B, CU_TENSOR_MAP_L2_PROMOTION_NONE, CU_TENSOR_MAP_FLOAT_OOB_FILL_NONE);
    const cuuint64_t wdims[2] = {C * 9, C}, wstr[1] = {C * 18};
    const cuuint32_t wbox[2] = {144, C};
    encode(&wmap, CU_TENSOR_MAP_DATA_TYPE_BFLOAT16, 2, d_in[4], wdims, wstr, wbox, es, CU_TENSOR_MAP_INTERLEAVE_NONE,
           CU_TENSOR_MAP_SWIZZLE_NONE, CU_TENSOR_MAP_L2_PROMOTION_NONE, CU_TENSOR_MAP_FLOAT_OOB_FILL_NONE);
    resblock_kernel<<<NCTA + NXTRA, NTHREADS, SM_TOTAL>>>(
        (const __nv_bfloat16*)d_in[4], (const __nv_bfloat16*)d_in[0], (const __nv_bfloat16*)d_in[1],
        (const __nv_bfloat16*)d_in[2], (const __nv_bfloat16*)d_in[3], (const __nv_bfloat16*)d_in[5],
        (const __nv_bfloat16*)d_in[6], (const __nv_bfloat16*)d_in[7], (const __nv_bfloat16*)d_in[8],
        (__nv_bfloat16*)d_out, gs, xmap, wmap);
}
```

```cpp
#include <cuda_runtime.h>
#include <cuda.h>
#include <cuda_bf16.h>
#include <stdint.h>

namespace {

constexpr int C = 128, HW = 64, NB = 2, E = 768;
constexpr int NCTA = NB * HW;
constexpr int NXTRA = 4;
constexpr int NTHREADS = 16 * 32;
constexpr int CH_PITCH = 66 * 16;
constexpr int ROW_BYTES = 16 * CH_PITCH;
constexpr int STEP_BYTES = 4096;
constexpr int STAGE_BYTES = 3 * STEP_BYTES;
constexpr int NSTAGE = 24;
constexpr int KC_BYTES = 2 * CH_PITCH;
constexpr int NS = 12;
constexpr int LAG = 1;
#define XDELAY 400
#define HDELAY 600
#define SEQ 0
#define MMA0_WAIT mbar_try
#define SPINPAUSE
#define NPOLL 1
#define PD2 0
#define ODELAY 100
#define NLDG 2
#define PSTAG -1
#define PDELAY0 400
#define PDELAY 60
#define RB 1
#define XSTAG2 400
#define XSTAG 800
#define HSEND 0
#define SDELAY 600
#define OAFTER 0
#define W2DELAY 2400

constexpr uint32_t SMEM_BASE = 0x400;
constexpr uint32_t SM_XOWN = SMEM_BASE;
constexpr uint32_t SM_ACT = SM_XOWN + 16384 + 512;
constexpr uint32_t SM_XOUT = SM_ACT + 2 * ROW_BYTES + 512;
static_assert(SM_XOUT % 1024 == 0, "swizzle atom alignment");
constexpr uint32_t SM_W = SM_ACT + 3 * ROW_BYTES + 128;
__host__ __device__ constexpr uint32_t slot_addr(int slot) { return SM_W + slot * STAGE_BYTES; }
constexpr uint32_t SM_COEF = SM_W + NS * STAGE_BYTES;
constexpr uint32_t SM_GST = SM_COEF + 2048;
constexpr uint32_t SM_EMB = SM_GST + 128;
constexpr uint32_t SM_ONES = SM_EMB + 2048;
constexpr uint32_t SM_RED = SM_ONES + 256;
constexpr uint32_t SM_BNC = SM_RED + 1536;
constexpr uint32_t SM_BAR = SM_BNC + 2 * 2304;
constexpr int BAR_FULL = 0, BAR_WEMPTY = NSTAGE, BAR_HW = BAR_WEMPTY + NS, BAR_XFREE = BAR_HW + 1, BAR_STATS = BAR_XFREE + 1,
              BAR_EMB = BAR_STATS + 1, BAR_ACK = BAR_EMB + 1, BAR_X = BAR_ACK + 1  , NBAR = BAR_X + 5;
constexpr int SM_TOTAL = SM_BAR + NBAR * 8 - SMEM_BASE;
static_assert(SM_TOTAL <= 232448, "smem");
static_assert(NBAR <= 96, "barrier init");
__host__ __device__ constexpr uint32_t BAR(int i) { return SM_BAR + 8 * i; }
__host__ __device__ constexpr int ky_of(int kyo) { return kyo == 0 ? 1 : (kyo == 1 ? 0 : 2); }

constexpr unsigned SPIN_LIMIT = 1u << 16;

#define LS 1056
#define GS1 4
#define PD 0
#define DEFER 0
#define KS 32
struct Scratch {
    float acc1[NB * LS];
    float acc2[NB * LS];
    unsigned wcnt[3 * NB * LS];
    unsigned w1cnt[NB * 8 * KS];
    float emb[NXTRA * NB * C];
    alignas(1024) unsigned char wt[2 * NSTAGE * STAGE_BYTES];
    uint4 box[NCTA * 1024];
};
__device__ __align__(1024) Scratch g_scratch;
#define TL(i) do {} while (0)
#define TLG(i) do {} while (0)

__device__ __forceinline__ unsigned clock32() { unsigned c; asm volatile("mov.u32 %0, %%clock;" : "=r"(c)); return c; }
__device__ __forceinline__ uint32_t mapa(uint32_t a, uint32_t rank) {
    uint32_t d;
    asm("mapa.shared::cluster.u32 %0, %1, %2;" : "=r"(d) : "r"(a), "r"(rank));
    return d;
}
#define S0 mapa(0, blockIdx.x & 1)
__device__ __forceinline__ void mbar_init(uint32_t bar, int cnt) {
    asm volatile("mbarrier.init.shared::cta.b64 [%0], %1;" ::"r"(bar + S0), "r"(cnt) : "memory");
}
__device__ __forceinline__ void mbar_arrive(uint32_t bar) {
    asm volatile("mbarrier.arrive.shared::cta.b64 _, [%0];" ::"r"(bar + S0) : "memory");
}
__device__ __forceinline__ void mbar_expect(uint32_t bar, uint32_t bytes) {
    asm volatile("mbarrier.arrive.expect_tx.shared::cta.b64 _, [%0], %1;" ::"r"(bar + S0), "r"(bytes) : "memory");
}
__device__ __forceinline__ bool mbar_try(uint32_t bar, uint32_t par) {
    uint32_t ok;
    asm volatile("{\n.reg .pred p;\nmbarrier.try_wait.parity.shared::cta.b64 p, [%1], %2;\nselp.u32 %0, 1, 0, p;\n}"
                 : "=r"(ok) : "r"(bar + S0), "r"(par) : "memory");
    return ok;
}
__device__ __forceinline__ bool mbar_test(uint32_t bar, uint32_t par) {
    uint32_t ok;
    asm volatile("{\n.reg .pred p;\nmbarrier.test_wait.parity.shared::cta.b64 p, [%1], %2;\nselp.u32 %0, 1, 0, p;\n}"
                 : "=r"(ok) : "r"(bar + S0), "r"(par) : "memory");
    return ok;
}
__device__ __forceinline__ void mbar_wait(uint32_t bar, uint32_t par) {
    unsigned it = 0;
#pragma unroll 1
    while (!mbar_try(bar, par) && ++it < SPIN_LIMIT) {}
}
__device__ __forceinline__ bool elect_one() {
    uint32_t p;
    asm volatile("{\n.reg .pred p;\nelect.sync _|p, 0xffffffff;\nselp.u32 %0, 1, 0, p;\n}" : "=r"(p));
    return p;
}
__device__ __forceinline__ void fence_async_smem() { asm volatile("fence.proxy.async.shared::cta;" ::: "memory"); }
__device__ __forceinline__ void fence_async_global() { asm volatile("fence.proxy.async.global;" ::: "memory"); }
__device__ __forceinline__ void fence_acquire() { asm volatile("fence.acquire.gpu;" ::: "memory"); }
__device__ __forceinline__ void bar_sync(int id, int n) { asm volatile("bar.sync %0, %1;" ::"r"(id), "r"(n) : "memory"); }
__device__ __forceinline__ void bar_arrive(int id, int n) { asm volatile("bar.arrive %0, %1;" ::"r"(id), "r"(n) : "memory"); }
__device__ __forceinline__ void bulk_g2s(uint32_t dst, const void* src, uint32_t bytes, uint32_t bar) {
    asm volatile("cp.async.bulk.shared::cluster.global.mbarrier::complete_tx::bytes [%0], [%1], %2, [%3];"
                 ::"r"(dst), "l"(src), "r"(bytes), "r"(bar) : "memory");
}
__device__ __forceinline__ void tma_x(uint32_t dst, const CUtensorMap* tm, int row, int ch, uint32_t bar) {
    asm volatile("cp.async.bulk.tensor.3d.shared::cluster.global.mbarrier::complete_tx::bytes [%0], [%1, {%2, %3, %4}], [%5];"
                 ::"r"(dst + S0), "l"(tm), "r"(0), "r"(row), "r"(ch), "r"(bar + S0) : "memory");
}
__device__ __forceinline__ uint4 ld_relaxed_v4(const void* p) {
    uint4 v;
    asm volatile("ld.relaxed.gpu.global.v4.u32 {%0,%1,%2,%3}, [%4];" : "=r"(v.x), "=r"(v.y), "=r"(v.z), "=r"(v.w) : "l"(p) : "memory");
    return v;
}
__device__ __forceinline__ unsigned ld_relaxed(const void* p) {
    unsigned v;
    asm volatile("ld.relaxed.gpu.global.u32 %0, [%1];" : "=r"(v) : "l"(p) : "memory");
    return v;
}
__device__ __forceinline__ void red_add4(float* p, float a, float b, float c, float d) {
    asm volatile("red.relaxed.gpu.global.add.v4.f32 [%0], {%1,%2,%3,%4};" ::"l"(p), "f"(a), "f"(b), "f"(c), "f"(d) : "memory");
}
__device__ __forceinline__ void sts128(uint32_t a, uint4 v) {
    asm volatile("st.shared.v4.u32 [%0], {%1,%2,%3,%4};" ::"r"(a + S0), "r"(v.x), "r"(v.y), "r"(v.z), "r"(v.w) : "memory");
}
__device__ __forceinline__ void sts128f(uint32_t a, float4 v) {
    asm volatile("st.shared.v4.f32 [%0], {%1,%2,%3,%4};" ::"r"(a + S0), "f"(v.x), "f"(v.y), "f"(v.z), "f"(v.w) : "memory");
}
__device__ __forceinline__ void sts32f(uint32_t a, float v) { asm volatile("st.shared.f32 [%0], %1;" ::"r"(a + S0), "f"(v) : "memory"); }
__device__ __forceinline__ uint4 lds128(uint32_t a) {
    uint4 v;
    asm volatile("ld.shared.v4.u32 {%0,%1,%2,%3}, [%4];" : "=r"(v.x), "=r"(v.y), "=r"(v.z), "=r"(v.w) : "r"(a + S0) : "memory");
    return v;
}
__device__ __forceinline__ float4 lds128f(uint32_t a) {
    float4 v;
    asm volatile("ld.shared.v4.f32 {%0,%1,%2,%3}, [%4];" : "=f"(v.x), "=f"(v.y), "=f"(v.z), "=f"(v.w) : "r"(a + S0) : "memory");
    return v;
}
__device__ __forceinline__ float2 lds64f(uint32_t a) {
    float2 v;
    asm volatile("ld.shared.v2.f32 {%0,%1}, [%2];" : "=f"(v.x), "=f"(v.y) : "r"(a + S0) : "memory");
    return v;
}
__device__ __forceinline__ float bf_lo(uint32_t u) { return __uint_as_float(u << 16); }
__device__ __forceinline__ float bf_hi(uint32_t u) { return __uint_as_float(u & 0xffff0000u); }
__device__ __forceinline__ uint32_t pack_bf(float lo, float hi) {
    uint32_t r;
    asm("cvt.rn.bf16x2.f32 %0, %1, %2;" : "=r"(r) : "f"(hi), "f"(lo));
    return r;
}
__device__ __forceinline__ float tanh_fast(float x) {
    float r;
    asm("tanh.approx.f32 %0, %1;" : "=f"(r) : "f"(x));
    return r;
}
__device__ __forceinline__ float silu_half(float h) { return fmaf(h, tanh_fast(h), h); }
__device__ __forceinline__ void ldsm4(uint32_t (&u)[4], uint32_t a) {
    asm volatile("ldmatrix.sync.aligned.m8n8.x4.shared.b16 {%0,%1,%2,%3}, [%4];"
                 : "=r"(u[0]), "=r"(u[1]), "=r"(u[2]), "=r"(u[3]) : "r"(a + S0) : "memory");
}
__device__ __forceinline__ void ldsm4t(uint32_t (&u)[4], uint32_t a) {
    asm volatile("ldmatrix.sync.aligned.m8n8.x4.trans.shared.b16 {%0,%1,%2,%3}, [%4];"
                 : "=r"(u[0]), "=r"(u[1]), "=r"(u[2]), "=r"(u[3]) : "r"(a + S0) : "memory");
}
__device__ __forceinline__ void stsm4(uint32_t a, uint32_t p0, uint32_t p1, uint32_t p2, uint32_t p3) {
    asm volatile("stmatrix.sync.aligned.m8n8.x4.shared.b16 [%0], {%1,%2,%3,%4};" ::"r"(a + S0), "r"(p0), "r"(p1), "r"(p2), "r"(p3) : "memory");
}
__device__ __forceinline__ void stsm4t(uint32_t a, uint32_t p0, uint32_t p1, uint32_t p2, uint32_t p3) {
    asm volatile("stmatrix.sync.aligned.m8n8.x4.trans.shared.b16 [%0], {%1,%2,%3,%4};" ::"r"(a + S0), "r"(p0), "r"(p1), "r"(p2), "r"(p3) : "memory");
}

#define R8(o) "+f"(d[o]), "+f"(d[o + 1]), "+f"(d[o + 2]), "+f"(d[o + 3]), "+f"(d[o + 4]), "+f"(d[o + 5]), "+f"(d[o + 6]), "+f"(d[o + 7])
template <uint32_t ALO, uint32_t BLO, uint64_t AHI = 8, uint64_t BHI = 48>
__device__ __forceinline__ void wgmma128(float (&d)[64]) {
    asm volatile(
        "wgmma.mma_async.sync.aligned.m64n128k16.f32.bf16.bf16 "
        "{%0,%1,%2,%3,%4,%5,%6,%7,%8,%9,%10,%11,%12,%13,%14,%15,%16,%17,%18,%19,%20,%21,%22,%23,%24,%25,%26,%27,%28,%29,%30,%31,"
        "%32,%33,%34,%35,%36,%37,%38,%39,%40,%41,%42,%43,%44,%45,%46,%47,%48,%49,%50,%51,%52,%53,%54,%55,%56,%57,%58,%59,%60,%61,%62,%63},"
        " %64, %65, 1, 1, 1, 0, 0;"
        : R8(0), R8(8), R8(16), R8(24), R8(32), R8(40), R8(48), R8(56)
        : "l"((AHI << 32) | ALO), "l"((BHI << 32) | BLO));
}
template <int S>
__device__ __forceinline__ void mma_stages(float (&d)[64], int conv, int tid, Scratch* gs) {
    constexpr uint32_t A = ((SM_ACT + S * 2 * CH_PITCH + 16) >> 4) | ((CH_PITCH >> 4) << 16);
    constexpr uint32_t B = (slot_addr(S % NS) >> 4) | (8u << 16);
    if (S == 0) {
        unsigned it = 0;
#pragma unroll 1
        while (!MMA0_WAIT(BAR(BAR_FULL), conv) && ++it < SPIN_LIMIT) {}
    }
    bool next_ok = true;
    constexpr uint32_t NEXT = S + 1 < NSTAGE ? BAR(BAR_FULL + S + 1) : BAR(BAR_EMB);
    const int npar = S + 1 < NSTAGE ? conv : 0;
    next_ok = mbar_test(NEXT, npar);
    if (S == 0 && tid == 0) TL(32 + conv * 24);
    asm volatile("wgmma.fence.sync.aligned;" ::: "memory");
    wgmma128<A, B>(d);
    wgmma128<A + 1, B + 16>(d);
    wgmma128<A + 2, B + 32>(d);
    asm volatile("wgmma.commit_group.sync.aligned;" ::: "memory");
    if (S >= LAG) {
        asm volatile("wgmma.wait_group.sync.aligned %0;" ::"n"(LAG) : "memory");
        if ((tid & 31) == 0) mbar_arrive(BAR(BAR_WEMPTY + (S + NS - LAG) % NS));
    }
    if (!next_ok) mbar_wait(NEXT, npar);
    if constexpr (S + 1 < NSTAGE) mma_stages<S + 1>(d, conv, tid, gs);
}

__device__ __forceinline__ void weight_load(uint4 (&t)[5], const __nv_bfloat16* w, int cta, int lane) {
    const char* base = reinterpret_cast<const char*>(w) + ((cta & 15) * 8 * C + (cta >> 4) * 16) * 18;
#pragma unroll
    for (int k = 0; k < 5; k++) {
        const int i = lane + 32 * k, row = (i * 57) >> 10;
        if (k < 4 || lane < 16) t[k] = __ldg(reinterpret_cast<const uint4*>(base + row * (C * 18 - 288) + i * 16));
    }
}
__device__ __forceinline__ void weight_block(uint32_t bounce, unsigned char* wt, int cta, int lane, bool readback, Scratch* gs) {
    unsigned char* dst = wt + (cta >> 4) * STAGE_BYTES + (cta & 15) * 768;
    if (lane < 16) {
        uint32_t v[36];
#pragma unroll
        for (int i = 0; i < 9; i++) {
            const uint4 q = lds128(bounce + (lane & 7) * 288 + (lane >> 3) * 144 + i * 16);
            v[4 * i] = q.x; v[4 * i + 1] = q.y; v[4 * i + 2] = q.z; v[4 * i + 3] = q.w;
        }
#pragma unroll
        for (int kyo = 0; kyo < 3; kyo++) {
#pragma unroll
            for (int kx = 0; kx < 3; kx++) {
                const int tap = ky_of(kyo) * 3 + kx;
                uint32_t o[4];
#pragma unroll
                for (int m = 0; m < 4; m++) {
                    const int i0 = 18 * m + tap, i1 = i0 + 9;
                    const uint32_t sel = ((i0 & 1) ? 0x32u : 0x10u) | ((i1 & 1) ? 0x7600u : 0x5400u);
                    o[m] = __byte_perm(v[i0 >> 1], v[i1 >> 1], sel);
                }
                *reinterpret_cast<uint4*>(dst + kyo * 8 * STAGE_BYTES + kx * 256 + lane * 16) = make_uint4(o[0], o[1], o[2], o[3]);
            }
        }
    }
    if (readback) {
        __syncwarp();
        unsigned acc = 0;
        if (lane < 24) {
#pragma unroll
            for (int i = 0; i < 3; i++) acc |= ld_relaxed(dst + i * 8 * STAGE_BYTES + lane * 32);
        }
        asm volatile("{\n.reg .pred p;\nsetp.eq.u32 p, %0, 0x9e3779b9;\n@p st.shared.u32 [%1], %0;\n}" ::"r"(acc), "r"(bounce + S0) : "memory");
    }
}
__device__ __forceinline__ uint32_t act2(uint32_t u, const float4& cf) {
    return pack_bf(silu_half(fmaf(bf_lo(u), cf.x, cf.z)), silu_half(fmaf(bf_hi(u), cf.y, cf.w)));
}
__device__ __forceinline__ void norm_unit(uint32_t (&u)[4], const float4& ca, const float4& cb) {
    u[0] = act2(u[0], ca); u[1] = act2(u[1], ca); u[2] = act2(u[2], cb); u[3] = act2(u[3], cb);
}
__device__ __forceinline__ void read_stats(uint32_t gst, float (&g)[8]) {
    asm volatile("ld.volatile.shared.v4.f32 {%0,%1,%2,%3}, [%4];" : "=f"(g[0]), "=f"(g[1]), "=f"(g[2]), "=f"(g[3]) : "r"(gst + S0) : "memory");
    asm volatile("ld.volatile.shared.v4.f32 {%0,%1,%2,%3}, [%4];" : "=f"(g[4]), "=f"(g[5]), "=f"(g[6]), "=f"(g[7]) : "r"(gst + 16 + S0) : "memory");
}
template <int T>
__device__ __forceinline__ void group_coefs(uint32_t gst, float (&g)[8], float4 (&cf)[8]) {
    unsigned it = 0;
    if (!__all_sync(0xffffffffu, g[2 * T] != 0.f)) {
        float rs0;
#pragma unroll 1
        do {
            SPINPAUSE;
            asm volatile("ld.volatile.shared.f32 %0, [%1];" : "=f"(rs0) : "r"(gst + 8 * T + S0) : "memory");
        } while (!__all_sync(0xffffffffu, rs0 != 0.f) && ++it < 8 * SPIN_LIMIT);
        read_stats(gst, g);
    }
    float4 &ca = cf[2 * T], &cb = cf[2 * T + 1];
    const float rs = g[2 * T], mr = g[2 * T + 1];
    ca.z = fmaf(-mr, ca.x, ca.z); ca.w = fmaf(-mr, ca.y, ca.w); ca.x *= rs; ca.y *= rs;
    cb.z = fmaf(-mr, cb.x, cb.z); cb.w = fmaf(-mr, cb.y, cb.w); cb.x *= rs; cb.y *= rs;
}
template <int FIRST, int N>
__device__ __forceinline__ void norm_block(uint32_t (&u)[4][4], float4 (&cf)[8], uint32_t act, uint32_t mask, uint32_t fbar, int lane) {
#pragma unroll
    for (int t = FIRST; t < FIRST + N; t++) {
        norm_unit(u[t], cf[2 * t], cf[2 * t + 1]);
        stsm4(act + t * 2 * KC_BYTES, u[t][0] & mask, u[t][1] & mask, u[t][2] & mask, u[t][3] & mask);
    }
    fence_async_smem();
    __syncwarp();
    if (lane < N) mbar_arrive(fbar + 16 * (FIRST + lane));
}
__device__ __forceinline__ void publish(uint32_t bar, int lane) {
    fence_async_smem();
    __syncwarp();
    if (lane == 0) mbar_arrive(bar);
}
template <int T>
__device__ __forceinline__ void next_unit(uint32_t (&u)[4][4], float4 (&cf)[8], uint32_t gst, float (&g)[8], uint32_t act, uint32_t fbar, int lane) {
    const bool have = __all_sync(0xffffffffu, g[2 * T] != 0.f);
    if (!have) publish(fbar + 16 * (T - 1), lane);
    group_coefs<T>(gst, g, cf);
    norm_unit(u[T], cf[2 * T], cf[2 * T + 1]);
    if (have) publish(fbar + 16 * (T - 1), lane);
    stsm4(act + T * 2 * KC_BYTES, u[T][0], u[T][1], u[T][2], u[T][3]);
}
__device__ __forceinline__ void stat_mma(float (&c)[4], uint32_t p, uint32_t q) {
    asm("mma.sync.aligned.m16n8k16.row.col.f32.bf16.bf16.f32 {%0,%1,%2,%3}, {%4,%5,%6,%5}, {%4,%6}, {%0,%1,%2,%3};"
        : "+f"(c[0]), "+f"(c[1]), "+f"(c[2]), "+f"(c[3]) : "r"(p), "r"(0x3f803f80u), "r"(q));
}
__device__ __forceinline__ void stat_store(const float (&c)[4], uint32_t dst, int lane) {
    const int g = lane >> 2, t = lane & 3;
    if (t == (g >> 1)) sts32f(dst + g * 4, (g & 1) ? c[1] : c[0]);
    if (g == 7) sts32f(dst + 32 + t * 4, c[2] + c[3]);
}
__device__ __forceinline__ float sum4(float4 v) { return (v.x + v.y) + (v.z + v.w); }
__device__ __forceinline__ void stat_publish(uint32_t src, float* acc, int lane, bool real) {
    const uint32_t a = src + (lane & 15) * 48;
    float q = sum4(lds128f(a)) + sum4(lds128f(a + 16)), sm = sum4(lds128f(a + 32));
    q += __shfl_xor_sync(0xffffffffu, q, 1); sm += __shfl_xor_sync(0xffffffffu, sm, 1);
    q += __shfl_xor_sync(0xffffffffu, q, 2); sm += __shfl_xor_sync(0xffffffffu, sm, 2);
    if (real && (lane & 19) == 0) red_add4(acc + lane, 1.f, sm, q, 1.f);
}
__device__ __forceinline__ void fence_acc(float (&d)[64]) {
#pragma unroll
    for (int i = 0; i < 64; i++) asm volatile("" : "+f"(d[i])::"memory");
}
__device__ __forceinline__ void ld_unit(uint32_t (&u)[4], const uint4* p) {
    asm volatile("ld.relaxed.gpu.global.v4.u32 {%0,%1,%2,%3}, [%4];" : "=r"(u[0]), "=r"(u[1]), "=r"(u[2]), "=r"(u[3]) : "l"(p) : "memory");
}

__device__ __noinline__ void side_jobs(const __nv_bfloat16* __restrict__ t_emb, const __nv_bfloat16* __restrict__ w_emb,
                                       const __nv_bfloat16* __restrict__ w2, Scratch* __restrict__ gs, unsigned clk0) {
    const int tid = threadIdx.x, warp = tid >> 5, lane = tid & 31, j = blockIdx.x;
    float tv = 0.f;
    if (lane < 24) tv = __bfloat162float(t_emb[(lane / 12) * E + j * 192 + warp * 12 + lane % 12]);
    if (tid == 0) {
        mbar_init(BAR(0), 1);
        mbar_expect(BAR(0), 192 * C * 2);
        fence_async_smem();
        while (clock32() - clk0 < SDELAY) {}
#pragma unroll
        for (int i = 0; i < 4; i++)
            asm volatile("cp.async.bulk.prefetch.L2.global [%0], 18432;" ::"l"(reinterpret_cast<const char*>(w2) + (j * 4 + i) * 18432) : "memory");
#pragma unroll
        for (int i = 0; i < 4; i++) bulk_g2s(S0 + SM_W + i * 12288, w_emb + (j * 192 + i * 48) * C, 12288, S0 + BAR(0));
    }
    if (j == 0 && tid < 32) gs->acc2[(tid >> 4) * LS + (tid & 15)] = 0.f;
    const float sv = silu_half(0.5f * tv);
    __syncthreads();
    mbar_wait(BAR(0), 0);
    float acc[8] = {0.f, 0.f, 0.f, 0.f, 0.f, 0.f, 0.f, 0.f};
#pragma unroll
    for (int i = 0; i < 12; i++) {
        const float2 wq = lds64f(SM_W + (warp * 12 + i) * 256 + lane * 8);
        const uint32_t wx = __float_as_uint(wq.x), wy = __float_as_uint(wq.y);
#pragma unroll
        for (int bb = 0; bb < 2; bb++) {
            const float sx = __shfl_sync(0xffffffffu, sv, bb * 12 + i);
            acc[4 * bb + 0] = fmaf(sx, bf_lo(wx), acc[4 * bb + 0]); acc[4 * bb + 1] = fmaf(sx, bf_hi(wx), acc[4 * bb + 1]);
            acc[4 * bb + 2] = fmaf(sx, bf_lo(wy), acc[4 * bb + 2]); acc[4 * bb + 3] = fmaf(sx, bf_hi(wy), acc[4 * bb + 3]);
        }
    }
    sts128f(SM_ACT + warp * 1024 + lane * 16, make_float4(acc[0], acc[1], acc[2], acc[3]));
    sts128f(SM_ACT + warp * 1024 + 512 + lane * 16, make_float4(acc[4], acc[5], acc[6], acc[7]));
    __syncthreads();
    if (tid < 128) {
        float2 sum = make_float2(0.f, 0.f);
#pragma unroll
        for (int w = 0; w < 16; w++) { const float2 p = lds64f(SM_ACT + w * 1024 + tid * 8); sum.x += p.x; sum.y += p.y; }
        *reinterpret_cast<float2*>(&gs->emb[j * NB * C + tid * 2]) = sum;
        bar_sync(1, 128);
        if (tid < 2) asm volatile("red.release.gpu.global.add.u32 [%0], 1;" ::"l"(&gs->wcnt[(2 * NB + tid) * LS]) : "memory");
    }
}

__global__ void __cluster_dims__(2, 1, 1) __launch_bounds__(NTHREADS, 1)
resblock_kernel(const __nv_bfloat16* __restrict__ w1, const __nv_bfloat16* __restrict__ x,
                const __nv_bfloat16* __restrict__ t_emb, const __nv_bfloat16* __restrict__ g1,
                const __nv_bfloat16* __restrict__ be1, const __nv_bfloat16* __restrict__ w_emb,
                const __nv_bfloat16* __restrict__ g2, const __nv_bfloat16* __restrict__ be2,
                const __nv_bfloat16* __restrict__ w2, __nv_bfloat16* __restrict__ out, Scratch* __restrict__ gs,
                const __grid_constant__ CUtensorMap xmap) {
    const unsigned clk0 = clock32();
    if (threadIdx.x == 480 && blockIdx.x >= NXTRA) TLG(1);
    const int tid = threadIdx.x, lane = tid & 31;
    const int cta = blockIdx.x - NXTRA, b = cta >> 6, r = cta & 63;
    uint4 v[5];
    if (tid < 32) weight_load(v, w1, cta & (NCTA - 1), lane);
    uint4 xv[8];
    const int wg4 = (tid >> 5) - 1;
    const bool early = tid >= 32 && wg4 < NLDG;
    if (early) {
        const char* src = reinterpret_cast<const char*>(x) + (uint32_t)((((b & 1) * C + wg4 * 32 + (lane >> 3)) * HW + r) * HW * 2 + (lane & 7) * 16);
        while (clock32() - clk0 < XDELAY + (wg4 >> 1) * XSTAG + (wg4 & 1) * XSTAG2) {}
#pragma unroll
        for (int i = 0; i < 8; i++) xv[i] = __ldg(reinterpret_cast<const uint4*>(src + i * (4 * HW * HW * 2)));
    }
    const int warp = __shfl_sync(0xffffffffu, tid >> 5, 0);
    if (cta < 0) { side_jobs(t_emb, w_emb, w2, gs, clk0); return; }

    if (warp != 4) asm volatile("barrier.cluster.arrive.relaxed.aligned;" ::: "memory");
    const bool has_outer = (r != 0) && (r != HW - 1);
    if (warp == 1 || warp == 2 || warp == 3 || warp == 5) {
        const int g = warp < 4 ? warp - 1 : 3;
        if (elect_one()) {
            if (g >= NLDG) asm volatile("prefetch.tensormap [%0];" ::"l"(&xmap) : "memory");
            mbar_init(BAR(BAR_X) + 8 * g, 1);
            if (g >= NLDG) mbar_expect(BAR(BAR_X) + 8 * g, 4096);
            fence_async_smem();
        }
        __syncwarp();
        bar_arrive(4, 256 + 32 + 128);
        if (g >= NLDG) {
            while (clock32() - clk0 < XDELAY + (g >> 1) * XSTAG + (g & 1) * XSTAG2) {}
            if (elect_one()) tma_x(SM_XOWN + g * 4096, &xmap, r, b * C + g * 32, BAR(BAR_X) + 8 * g);
            __syncwarp();
            mbar_wait(BAR(BAR_X) + 8 * g, 0);
#pragma unroll
            for (int k = 0; k < 8; k++) xv[k] = lds128(SM_XOWN + g * 4096 + k * 512 + lane * 16);
        }
        float c[8][4];
#pragma unroll
        for (int k = 0; k < 8; k++) {
            c[k][0] = c[k][1] = c[k][2] = c[k][3] = 0.f;
            stat_mma(c[k], xv[k].x, xv[k].y); stat_mma(c[k], xv[k].z, xv[k].w);
        }
#pragma unroll
        for (int i = 0; i < 4; i++) c[0][i] = ((c[0][i] + c[1][i]) + (c[2][i] + c[3][i])) + ((c[4][i] + c[5][i]) + (c[6][i] + c[7][i]));
        stat_store(c[0], SM_RED + g * 48, lane);
        __syncwarp();
        if (lane == 0) {
            const uint32_t a = SM_RED + g * 48;
            red_add4(&gs->acc1[b * LS + g * 4], 1.f, sum4(lds128f(a + 32)), sum4(lds128f(a)) + sum4(lds128f(a + 16)), 1.f);
            TL(74 + g);
        }
        if (g < NLDG) {
#pragma unroll
            for (int i = 0; i < 8; i++)
                sts128(SM_XOWN + g * 4096 + i * 512 + (lane >> 3) * 128 + (((lane & 7) ^ ((lane >> 3) + 4 * (i & 1))) << 4), xv[i]);
            __syncwarp();
            if (lane == 0) mbar_arrive(BAR(BAR_X) + 8 * g);
        }
    }
    if (warp == 4) {
            if (elect_one()) {
#pragma unroll
                for (int i = 0; i < NSTAGE; i++) mbar_init(BAR(BAR_FULL + i), (i >> 3) == 1 ? 1 : 5);
#pragma unroll
                for (int i = 0; i < NS + 2; i++) mbar_init(BAR(BAR_WEMPTY + i), 4);
#pragma unroll
                for (int i = BAR_STATS; i < BAR_X; i++) mbar_init(BAR(i), i == BAR_EMB ? 3 : 1);
                mbar_init(BAR(BAR_X + 4), 1);
                asm volatile("fence.mbarrier_init.release.cluster;" ::: "memory");
            }
            if (lane < 4) sts128(SM_GST + lane * 16, make_uint4(0, 0, 0, 0));
            __syncwarp();
            fence_async_smem();
            bar_arrive(0, 96);
            bar_arrive(5, 64);
            bar_arrive(4, 256 + 32 + 128);
            const uint4 z = make_uint4(0, 0, 0, 0);
#pragma unroll
            for (int i = 0; i < 2; i++) sts128(SM_ACT + (i * 16 + (lane >> 1)) * CH_PITCH + (lane & 1) * 16, z);
            if (lane < 4) sts128(SM_ACT + (2 + (lane >> 1)) * ROW_BYTES + (lane & 1) * 16, z);
            if (lane < 16) sts128(SM_ONES + lane * 16, make_uint4(lane < 8 ? 0x3f803f80u : 0u, 0, 0, 0));
            fence_async_smem();
            bar_arrive(7, 160 + 64);
            asm volatile("barrier.cluster.arrive.relaxed.aligned;" ::: "memory");
            if (lane == 0) TL(5);
            while (clock32() - clk0 < W2DELAY) {}
            weight_load(v, w2, cta, lane);
        }
    if (warp == 0 || warp == 4) {
        const int k = warp >> 2;
#pragma unroll
        for (int i = 0; i < 5; i++)
            if (i < 4 || lane < 16) sts128(SM_BNC + k * 2304 + (lane + 32 * i) * 16, v[i]);
        if (lane == 0) TL(k ? 14 : 81);
        __syncwarp();
        weight_block(SM_BNC + k * 2304, gs->wt + k * NSTAGE * STAGE_BYTES, cta, lane, true, gs);
        __syncwarp();
        if (lane == 0) TL(k ? 13 : 4);
        if (lane < 2) asm volatile("red.relaxed.gpu.global.add.u32 [%0], 1;" ::"l"(k ? &gs->wcnt[(NB + lane) * LS] : &gs->w1cnt[(lane * 8 + (cta >> 4)) * KS]) : "memory");
    }

    if (warp >= 8) {
        const int nw = warp - 8;
        if (nw < 2) {
            const uint2 ga = __ldg(reinterpret_cast<const uint2*>(nw ? g2 : g1) + lane), bt = __ldg(reinterpret_cast<const uint2*>(nw ? be2 : be1) + lane);
            sts128f(SM_COEF + nw * 1024 + lane * 32, make_float4(0.5f * bf_lo(ga.x), 0.5f * bf_hi(ga.x), 0.5f * bf_lo(bt.x), 0.5f * bf_hi(bt.x)));
            sts128f(SM_COEF + nw * 1024 + lane * 32 + 16, make_float4(0.5f * bf_lo(ga.y), 0.5f * bf_hi(ga.y), 0.5f * bf_lo(bt.y), 0.5f * bf_hi(bt.y)));
        }
        if (nw < 2) bar_arrive(7, 160 + 64);
        bar_sync(4, 256 + 32 + 128);
        const int par = nw >> 2, wq = nw & 3;
        const uint32_t act_off = SM_ACT + (par * 2 + (lane >> 4)) * CH_PITCH + (2 + wq * 16 + (lane & 15)) * 16;
        const uint32_t stg_off = (par * 16 + (lane >> 4) * 8 + (lane & 7)) * 128 + (((2 * wq + ((lane >> 3) & 1)) ^ (lane & 7)) << 4);
        const uint32_t cfa = SM_COEF + par * 128 + (lane & 3) * 16;
        const uint32_t fbar = BAR(BAR_FULL) + 8 * par;
        uint4* inbox = gs->box + cta * 1024 + nw * 32 + lane;
#pragma unroll 1
        for (int conv = 0; conv < 2; conv++) {
            uint32_t u[4][4], w[4][4];
            float4 cf[8];
            if (conv == 0) {
#pragma unroll
                for (int i = 0; i < 4; i++) if (i != 1) { mbar_wait(BAR(BAR_X + i), 0); ldsm4t(u[i], SM_XOWN + stg_off + i * 4096); }
            } else {
                mbar_wait(BAR(BAR_HW), 0);
#pragma unroll
                for (int i = 0; i < 4; i++) if (i != 1) ldsm4(u[i], act_off + i * 2 * KC_BYTES);
            }
#pragma unroll
            for (int i = 0; i < 8; i++) cf[i] = lds128f(cfa + conv * 1024 + (i >> 1) * 256 + (i & 1) * 64);
            const uint32_t gst = SM_GST + conv * 32;
            float gv[8];
            read_stats(gst, gv);
            group_coefs<0>(gst, gv, cf);
            if (tid == 256) TL(22 + conv * 4);
            if (par) { const unsigned c1 = clock32(); while (clock32() - c1 < PDELAY) {} }
            norm_block<0, 1>(u, cf, act_off, ~0u, fbar, lane);
            if (tid == 256) TL(8 + conv * 8);
            group_coefs<2>(gst, gv, cf);
            norm_unit(u[2], cf[4], cf[5]);
            stsm4(act_off + 4 * KC_BYTES, u[2][0], u[2][1], u[2][2], u[2][3]);
            publish(fbar + 32, lane);
            group_coefs<3>(gst, gv, cf);
            norm_block<3, 1>(u, cf, act_off, ~0u, fbar, lane);
            group_coefs<1>(gst, gv, cf);
            if (tid == 256) TL(84 + conv);
            if (has_outer) {
                mbar_wait(BAR(BAR_X + 4), conv);
                if (conv == 0) {
#pragma unroll
                    for (int i = 0; i < 4; i++) ldsm4t(w[i], SM_XOUT + stg_off + i * 4096);
                } else {
#pragma unroll
                    for (int i = 0; i < 4; i++) {
                        const uint4 q = lds128(SM_XOWN + (tid - 256) * 16 + i * 4096);
                        w[i][0] = q.x; w[i][1] = q.y; w[i][2] = q.z; w[i][3] = q.w;
                    }
                    unsigned it = 0;
                    while (true) {
                        bool ok = true;
#pragma unroll
                        for (int i = 0; i < 16; i++) ok = ok && w[i >> 2][i & 3] != 0;
                        if (__all_sync(0xffffffffu, ok) || ++it > SPIN_LIMIT) break;
#pragma unroll
                        for (int i = 0; i < 4; i++) ld_unit(w[i], inbox + i * 256);
                    }
#pragma unroll
                    for (int i = 0; i < 16; i++) w[i >> 2][i & 3] = ~w[i >> 2][i & 3];
                }
            }
            if (conv == 0) {
                bar_sync(3, 256);
                if (nw == 0) sts128(SM_ACT + 2 * ROW_BYTES + (lane >> 1) * CH_PITCH + (lane & 1) * 16, make_uint4(0, 0, 0, 0));
            }
            if (tid == 256) TL(24 + conv * 4);
            norm_block<0, 2>(w, cf, act_off + 2 * ROW_BYTES, has_outer ? ~0u : 0u, fbar + 128, lane);
            if (tid == 256) TL(88 + conv);
            norm_block<2, 2>(w, cf, act_off + 2 * ROW_BYTES, has_outer ? ~0u : 0u, fbar + 128, lane);
            if (tid == 256) TL(23 + conv * 4);
        }
        if (has_outer) {
            mbar_wait(BAR(BAR_FULL + NSTAGE - 1), 1);
#pragma unroll
            for (int i = 0; i < 4; i++) inbox[i * 256] = make_uint4(0, 0, 0, 0);
        }
        {
            const int oc0 = (tid - 256) >> 3, seg = lane & 7;
            __nv_bfloat16* dst = out + ((size_t)(b * C + oc0) * HW + r) * HW + seg * 8;
            const uint32_t src = SM_XOWN + oc0 * 128 + ((seg ^ (oc0 & 7)) << 4);
            bar_sync(6, 128 + 256);
#pragma unroll
            for (int i = 0; i < 4; i++) *reinterpret_cast<uint4*>(dst + (size_t)i * 32 * HW * HW) = lds128(src + i * 4096);
            if (tid == 256) { TL(20); TLG(21); }
        }
    } else if (warp < 4) {
        const int wq = warp;
        bar_sync(7, 160 + 64);

        const uint32_t xbase = SM_XOWN + ((lane >> 4) * 8 + (lane & 7)) * 128 + (((2 * wq + ((lane >> 3) & 1)) ^ (lane & 7)) << 4);
        const uint32_t hbase = SM_ACT + (lane >> 4) * CH_PITCH + (2 + wq * 16 + (lane & 15)) * 16;
        uint32_t m[2][4];
        ldsm4t(m[0], xbase + 2 * 2048); ldsm4t(m[1], xbase + 3 * 2048);
        float d[64];
#pragma unroll
        for (int i = 0; i < 64; i++) d[i] = 0.f;
#pragma unroll 1
        for (int conv = 0; conv < 2; conv++) {
            {
                float4 cf[4];
#pragma unroll
                for (int i = 0; i < 4; i++) cf[i] = lds128f(SM_COEF + conv * 1024 + (4 + i) * 64 + (lane & 3) * 16);
                float2 g;
                unsigned it = 0;
#pragma unroll 1
                do {
                    asm volatile("ld.volatile.shared.v2.f32 {%0,%1}, [%2];" : "=f"(g.x), "=f"(g.y) : "r"(S0 + SM_GST + conv * 32 + 8) : "memory");
                } while (!__all_sync(0xffffffffu, g.x != 0.f) && ++it < 8 * SPIN_LIMIT);
#pragma unroll
                for (int i = 0; i < 4; i++) {
                    cf[i].z = fmaf(-g.y, cf[i].x, cf[i].z); cf[i].w = fmaf(-g.y, cf[i].y, cf[i].w); cf[i].x *= g.x; cf[i].y *= g.x;
                }
                norm_unit(m[0], cf[0], cf[1]); norm_unit(m[1], cf[2], cf[3]);
                stsm4(hbase + 2 * KC_BYTES, m[0][0], m[0][1], m[0][2], m[0][3]);
                stsm4(hbase + 3 * KC_BYTES, m[1][0], m[1][1], m[1][2], m[1][3]);
                fence_async_smem();
                __syncwarp();
                if (lane < 2) mbar_arrive(BAR(BAR_FULL + 2) + 8 * lane);
            }
            fence_acc(d);
            mma_stages<0>(d, conv, tid, gs);
            if (conv == 0) {
                asm volatile("wgmma.fence.sync.aligned;" ::: "memory");
                wgmma128<(SM_ONES >> 4) | (8u << 16), (SM_EMB >> 4), 0, 8>(d);
                asm volatile("wgmma.commit_group.sync.aligned;" ::: "memory");
            }
            asm volatile("wgmma.wait_group.sync.aligned 0;" ::: "memory");
            fence_acc(d);
            if (tid == 0) TL(10 + conv * 8);
            uint32_t hp[32];
#pragma unroll
            for (int i = 0; i < 32; i++) hp[i] = pack_bf(d[2 * i], d[2 * i + 1]);
            if (conv == 1) {
#pragma unroll
                for (int kc = 0; kc < 8; kc++) stsm4t(xbase + kc * 2048, hp[4 * kc], hp[4 * kc + 1], hp[4 * kc + 2], hp[4 * kc + 3]);
                bar_arrive(6, 128 + 256);
                break;
            }
#pragma unroll
            for (int g = 0; g < 4; g++) {
                float c[4] = {0.f, 0.f, 0.f, 0.f};
#pragma unroll
                for (int i = 0; i < 4; i++) stat_mma(c, hp[8 * g + 2 * i], hp[8 * g + 2 * i + 1]);
                stat_store(c, SM_RED + (g * 4 + wq) * 48, lane);
            }
            bar_sync(2, 128);
            if (wq == 0) stat_publish(SM_RED, &gs->acc2[b * LS], lane, true);
            if (tid == 0) TL(11);
#pragma unroll
            for (int kc = 0; kc < 8; kc++)
                if (kc >> 1 != 1) stsm4(hbase + kc * 2 * CH_PITCH, hp[4 * kc], hp[4 * kc + 1], hp[4 * kc + 2], hp[4 * kc + 3]);
#pragma unroll
            for (int i = 0; i < 8; i++) m[i >> 2][i & 3] = hp[8 + i];
            __syncwarp();
            if (lane == 0) mbar_arrive(BAR(BAR_HW));
            if (lane < LAG) mbar_arrive(BAR(BAR_WEMPTY + (NSTAGE - LAG) % NS) + 8 * lane);
            if (has_outer) {
                uint4* outbox = gs->box + (cta + ((r & 1) ? 1 : -1)) * 1024 + tid;
#pragma unroll
                for (int kc = 0; kc < 8; kc++) outbox[kc * 128] = make_uint4(~hp[4 * kc], ~hp[4 * kc + 1], ~hp[4 * kc + 2], ~hp[4 * kc + 3]);
            }
            if (tid == 0) TL(12);
#pragma unroll
            for (int kc = 0; kc < 8; kc++) {
                uint32_t p[4];
                ldsm4t(p, xbase + kc * 2048);
#pragma unroll
                for (int i = 0; i < 4; i++) { d[8 * kc + 2 * i] = bf_lo(p[i]); d[8 * kc + 2 * i + 1] = bf_hi(p[i]); }
            }
            fence_async_smem();
            __syncwarp();
            if (lane == 0) mbar_arrive(BAR(BAR_XFREE));
        }
        {
        }
    } else if (warp < 6) {
        if (warp == 5) {
            bar_sync(5, 64);
            mbar_wait(BAR(BAR_FULL + OAFTER), 0);
            if (has_outer && elect_one()) {
                mbar_expect(BAR(BAR_X + 4), 16384);
#pragma unroll
                for (int i = 0; i < 4; i++) tma_x(SM_XOUT + i * 4096, &xmap, r + ((r & 1) ? 1 : -1), b * C + i * 32, BAR(BAR_X + 4));
            }
            __syncwarp();
            asm volatile("barrier.cluster.wait.acquire.aligned;" ::: "memory");
            const uint32_t peer = (r & 1) ^ 1;
            const uint32_t self0 = mapa(0, r & 1), peer0 = mapa(0, peer);
#pragma unroll 1
            for (int conv = 0; conv < 2; conv++) {
#pragma unroll 1
                for (int kc = 0; kc < 8; kc++) {
                    mbar_wait(BAR(BAR_FULL) + 8 * kc, conv);
                    if (elect_one())
                        asm volatile("cp.async.bulk.shared::cluster.shared::cta.mbarrier::complete_tx::bytes [%0], [%1], %2, [%3];"
                                     ::"r"(peer0 + SM_ACT + ROW_BYTES + kc * KC_BYTES), "r"(self0 + SM_ACT + kc * KC_BYTES), "r"(KC_BYTES),
                                       "r"(peer0 + BAR(BAR_FULL + 8) + 8 * kc) : "memory");
                }
                if (lane == 0) TL(86 + conv);
#pragma unroll 1
                for (int kc = 0; kc < 8; kc++) mbar_wait(BAR(BAR_FULL + 8) + 8 * kc, conv);
                if (lane == 0)
                    asm volatile("mbarrier.arrive.relaxed.cluster.shared::cluster.b64 _, [%0];" ::"r"(peer0 + (conv ? BAR(BAR_ACK) : BAR(BAR_EMB))) : "memory");
            }
            mbar_wait(BAR(BAR_ACK), 0);
        } else {
            mbar_wait(BAR(BAR_STATS), 0);
            unsigned it = 0;
            while (ld_relaxed(&gs->wcnt[(2 * NB + b) * LS]) < (unsigned)NXTRA && ++it < SPIN_LIMIT) __nanosleep(100);
            fence_acquire();
            float ev[4] = {0.f, 0.f, 0.f, 0.f};
#pragma unroll
            for (int j = 0; j < NXTRA; j++) {
                const uint4 ef = ld_relaxed_v4(&gs->emb[(j * NB + b) * C + lane * 4]);
                ev[0] += __uint_as_float(ef.x); ev[1] += __uint_as_float(ef.y); ev[2] += __uint_as_float(ef.z); ev[3] += __uint_as_float(ef.w);
            }
#pragma unroll
            for (int i = 0; i < 4; i++) {
                const float hi = bf_lo(pack_bf(ev[i], 0.f));
                sts128(SM_EMB + (lane * 4 + i) * 16, make_uint4(pack_bf(hi, ev[i] - hi), 0, 0, 0));
            }
            fence_async_smem();
            __syncwarp();
            if (lane == 0) { mbar_arrive(BAR(BAR_EMB)); TL(19); }
        }
    } else if (warp == 6) {
        bar_sync(0, 96);
        const uint32_t ebytes = STAGE_BYTES + ((lane >> 3) == 1 ? KC_BYTES : 0);
        if (lane < NSTAGE) mbar_expect(BAR(BAR_FULL) + 8 * lane, ebytes);
        const int swap = (r & 1) ? 0 : 8 * STAGE_BYTES;
        unsigned it = 0;
        {
            int g = 0;
            const unsigned* cnt = &gs->w1cnt[(b * 8 + (lane & 7)) * KS];
            unsigned cv = ld_relaxed(cnt);
#pragma unroll 1
            while (g < NS) {
                unsigned ready = __ballot_sync(0xffffffffu, cv >= 16u);
                if (ready != ~0u) cv = ld_relaxed(cnt);
                ready >>= g;
                if (++it > SPIN_LIMIT) ready = ~0u;
                if (!(ready & 1)) continue;
                fence_async_global();
                if (lane == 0) TL(g ? 3 : 6);
#pragma unroll 1
                for (; (ready & 1) && g < NS; g++, ready >>= 1)
                    if (elect_one())
                        bulk_g2s(S0 + SM_W + g * STAGE_BYTES, gs->wt + g * STAGE_BYTES + (g >= 8 ? swap : 0), STAGE_BYTES, S0 + BAR(BAR_FULL) + 8 * g);
            }
        }
#pragma unroll 1
        for (int q = 3; q < 12; q++) {
            const int conv = q >= 6, qs = conv ? q - 6 : q, sl = q % 3;
            const unsigned char* wsrc = gs->wt + q * 4 * STAGE_BYTES + (qs < 2 ? 0 : (qs < 4 ? swap : -swap));
            const uint32_t par = (q / 3 - 1) & 1;
            if (q == 6) {
                it = 0;
                while (ld_relaxed(&gs->wcnt[(NB + b) * LS]) < (unsigned)NCTA && ++it < SPIN_LIMIT) {}
                fence_acquire();
                fence_async_global();
                if (lane == 0) { mbar_arrive(BAR(BAR_EMB)); TL(2); }
            }
#pragma unroll
            for (int i = 0; i < 4; i++) {
                mbar_wait(BAR(BAR_WEMPTY + i) + 32 * sl, par);
                if (i == 0 && (q == 6 || q == 9)) {
                    if ((lane >= NS) == (q == 9) && lane < NSTAGE) mbar_expect(BAR(BAR_FULL) + 8 * lane, ebytes);
                    __syncwarp();
                }
                if (elect_one())
                    bulk_g2s(S0 + SM_W + (sl * 4 + i) * STAGE_BYTES, wsrc + i * STAGE_BYTES, STAGE_BYTES, S0 + BAR(BAR_FULL + i) + 32 * qs);
            }
        }
    } else {
        bar_sync(0, 96);
#pragma unroll 1
        for (int conv = 0; conv < 2; conv++) {
            if (conv == 1) mbar_wait(BAR(BAR_HW), 0);
            const float* asrc = (conv ? gs->acc2 : gs->acc1) + b * LS + (lane & 3) * 4;
            unsigned it = 0;
#pragma unroll 1
            while (true) {
                const uint4 f = ld_relaxed_v4(asrc);
                const bool ok = ((f.x == 0x42800000u) & (f.w == 0x42800000u)) || ++it > SPIN_LIMIT;
                if (ok && lane < 4) {
                    const float inv_n = 1.0f / (32.0f * HW * HW);
                    const float mean = __uint_as_float(f.y) * inv_n;
                    const float rs = rsqrtf(fmaxf(fmaf(-mean, mean, __uint_as_float(f.z) * inv_n), 0.f) + 1e-5f);
                    asm volatile("st.shared.v2.f32 [%0], {%1,%2};" ::"r"(S0 + SM_GST + conv * 32 + lane * 8), "f"(rs == 0.f ? 1e-38f : rs), "f"(mean * rs) : "memory");
                }
                if (__all_sync(0xffffffffu, ok)) break;
            }
            if (lane == 0) { mbar_arrive(BAR(BAR_STATS)); TL(7 + conv * 8); }
        }
        mbar_wait(BAR(BAR_XFREE), 0);
        if (has_outer && elect_one()) {
            mbar_expect(BAR(BAR_X + 4), 16384);
            bulk_g2s(S0 + SM_XOWN, gs->box + cta * 1024, 16384, S0 + BAR(BAR_X + 4));
        }
        if (r == 0) {
            if (lane < 16) gs->acc1[b * LS + lane] = 0.f;
            if (lane < 3) gs->wcnt[(lane * NB + b) * LS] = 0;
            if (lane < 8) gs->w1cnt[(b * 8 + lane) * KS] = 0;
        }
    }
}

}

extern "C" void kernel_launch(void* const* d_in, const int* in_sizes, int n_in, void* d_out, int out_size) {
    (void)in_sizes; (void)n_in; (void)out_size;
    typedef CUresult (*EncodeFn)(CUtensorMap*, CUtensorMapDataType, cuuint32_t, void*, const cuuint64_t*, const cuuint64_t*,
                                 const cuuint32_t*, const cuuint32_t*, CUtensorMapInterleave, CUtensorMapSwizzle,
                                 CUtensorMapL2promotion, CUtensorMapFloatOOBfill);
    static Scratch* gs = nullptr;
    static EncodeFn encode = nullptr;
    if (!gs) {
        cudaFuncSetAttribute(resblock_kernel, cudaFuncAttributeMaxDynamicSharedMemorySize, SM_TOTAL);
        cudaGetSymbolAddress((void**)&gs, g_scratch);
        cudaDriverEntryPointQueryResult qr;
        cudaGetDriverEntryPoint("cuTensorMapEncodeTiled", (void**)&encode, cudaEnableDefault, &qr);
    }
    CUtensorMap xmap;
    const cuuint64_t dims[3] = {HW, HW, NB * C}, strides[2] = {HW * 2, HW * HW * 2};
    const cuuint32_t box[3] = {HW, 1, 32}, es[3] = {1, 1, 1};
    encode(&xmap, CU_TENSOR_MAP_DATA_TYPE_BFLOAT16, 3, d_in[0], dims, strides, box, es, CU_TENSOR_MAP_INTERLEAVE_NONE,
           CU_TENSOR_MAP_SWIZZLE_128B, CU_TENSOR_MAP_L2_PROMOTION_NONE, CU_TENSOR_MAP_FLOAT_OOB_FILL_NONE);
    resblock_kernel<<<NCTA + NXTRA, NTHREADS, SM_TOTAL>>>(
        (const __nv_bfloat16*)d_in[4], (const __nv_bfloat16*)d_in[0], (const __nv_bfloat16*)d_in[1],
        (const __nv_bfloat16*)d_in[2], (const __nv_bfloat16*)d_in[3], (const __nv_bfloat16*)d_in[5],
        (const __nv_bfloat16*)d_in[6], (const __nv_bfloat16*)d_in[7], (const __nv_bfloat16*)d_in[8],
        (__nv_bfloat16*)d_out, gs, xmap);
}
```

```cpp
#include <cuda_runtime.h>
#include <cuda.h>
#include <cuda_bf16.h>
#include <stdint.h>

namespace {

constexpr int C = 128, HW = 64, NB = 2, E = 768;
constexpr int NCTA = NB * HW;
constexpr int NXTRA = 4;
constexpr int NTHREADS = 16 * 32;
constexpr int CH_PITCH = 66 * 16;
constexpr int ROW_BYTES = 16 * CH_PITCH;
constexpr int STEP_BYTES = 4096;
constexpr int STAGE_BYTES = 3 * STEP_BYTES;
constexpr int NSTAGE = 24;
constexpr int KC_BYTES = 2 * CH_PITCH;
constexpr int NS = 12;
constexpr int LAG = 1;
#define XDELAY 400
#define HDELAY 600
#define SEQ 0
#define MMA0_WAIT mbar_try
#define SPINPAUSE
#define NPOLL 1
#define PD2 0
#define ODELAY 100
#define NLDG 2
#define PSTAG -1
#define PDELAY0 400
#define PDELAY 60
#define RB 1
#define XSTAG2 400
#define XSTAG 800
#define HSEND 0
#define SDELAY 600
#define OAFTER 0
#define W2DELAY 2400

constexpr uint32_t SMEM_BASE = 0x400;
constexpr uint32_t SM_XOWN = SMEM_BASE;
constexpr uint32_t SM_ACT = SM_XOWN + 16384 + 512;
constexpr uint32_t SM_XOUT = SM_ACT + 2 * ROW_BYTES + 512;
static_assert(SM_XOUT % 1024 == 0, "swizzle atom alignment");
constexpr uint32_t SM_W = SM_ACT + 3 * ROW_BYTES + 128;
__host__ __device__ constexpr uint32_t slot_addr(int slot) { return SM_W + slot * STAGE_BYTES; }
constexpr uint32_t SM_COEF = SM_W + NS * STAGE_BYTES;
constexpr uint32_t SM_GST = SM_COEF + 2048;
constexpr uint32_t SM_EMB = SM_GST + 128;
constexpr uint32_t SM_ONES = SM_EMB + 2048;
constexpr uint32_t SM_RED = SM_ONES + 256;
constexpr uint32_t SM_BNC = SM_RED + 1536;
constexpr uint32_t SM_BAR = SM_BNC + 2 * 2304;
constexpr int BAR_FULL = 0, BAR_WEMPTY = NSTAGE, BAR_HW = BAR_WEMPTY + NS, BAR_XFREE = BAR_HW + 1, BAR_STATS = BAR_XFREE + 1,
              BAR_EMB = BAR_STATS + 1, BAR_ACK = BAR_EMB + 1, BAR_SP = BAR_ACK + 1  , BAR_X = BAR_SP + 8  , NBAR = BAR_X + 5;
constexpr int SM_TOTAL = SM_BAR + NBAR * 8 - SMEM_BASE;
static_assert(SM_TOTAL <= 232448, "smem");
static_assert(NBAR <= 96, "barrier init");
__host__ __device__ constexpr uint32_t BAR(int i) { return SM_BAR + 8 * i; }
__host__ __device__ constexpr int ky_of(int kyo) { return kyo == 0 ? 1 : (kyo == 1 ? 0 : 2); }

constexpr unsigned SPIN_LIMIT = 1u << 16;

#define LS 1056
#define GS1 4
#define PD 0
#define NSPEC 4
#define KS 32
struct Scratch {
    float acc1[NB * LS];
    float acc2[NB * LS];
    unsigned wcnt[3 * NB * LS];
    unsigned w1cnt[NB * 8 * KS];
    float emb[NXTRA * NB * C];
    alignas(1024) unsigned char wt[2 * NSTAGE * STAGE_BYTES];
    uint4 box[NCTA * 1024];
};
__device__ __align__(1024) Scratch g_scratch;
#define TL(i) do {} while (0)
#define TLG(i) do {} while (0)

__device__ __forceinline__ unsigned clock32() { unsigned c; asm volatile("mov.u32 %0, %%clock;" : "=r"(c)); return c; }
__device__ __forceinline__ uint32_t mapa(uint32_t a, uint32_t rank) {
    uint32_t d;
    asm("mapa.shared::cluster.u32 %0, %1, %2;" : "=r"(d) : "r"(a), "r"(rank));
    return d;
}
#define S0 mapa(0, blockIdx.x & 1)
__device__ __forceinline__ void mbar_init(uint32_t bar, int cnt) {
    asm volatile("mbarrier.init.shared::cta.b64 [%0], %1;" ::"r"(bar + S0), "r"(cnt) : "memory");
}
__device__ __forceinline__ void mbar_arrive(uint32_t bar) {
    asm volatile("mbarrier.arrive.shared::cta.b64 _, [%0];" ::"r"(bar + S0) : "memory");
}
__device__ __forceinline__ void mbar_expect(uint32_t bar, uint32_t bytes) {
    asm volatile("mbarrier.arrive.expect_tx.shared::cta.b64 _, [%0], %1;" ::"r"(bar + S0), "r"(bytes) : "memory");
}
__device__ __forceinline__ bool mbar_try(uint32_t bar, uint32_t par) {
    uint32_t ok;
    asm volatile("{\n.reg .pred p;\nmbarrier.try_wait.parity.shared::cta.b64 p, [%1], %2;\nselp.u32 %0, 1, 0, p;\n}"
                 : "=r"(ok) : "r"(bar + S0), "r"(par) : "memory");
    return ok;
}
__device__ __forceinline__ bool mbar_test(uint32_t bar, uint32_t par) {
    uint32_t ok;
    asm volatile("{\n.reg .pred p;\nmbarrier.test_wait.parity.shared::cta.b64 p, [%1], %2;\nselp.u32 %0, 1, 0, p;\n}"
                 : "=r"(ok) : "r"(bar + S0), "r"(par) : "memory");
    return ok;
}
__device__ __forceinline__ void mbar_wait(uint32_t bar, uint32_t par) {
    unsigned it = 0;
#pragma unroll 1
    while (!mbar_try(bar, par) && ++it < SPIN_LIMIT) {}
}
__device__ __forceinline__ bool elect_one() {
    uint32_t p;
    asm volatile("{\n.reg .pred p;\nelect.sync _|p, 0xffffffff;\nselp.u32 %0, 1, 0, p;\n}" : "=r"(p));
    return p;
}
__device__ __forceinline__ void fence_async_smem() { asm volatile("fence.proxy.async.shared::cta;" ::: "memory"); }
__device__ __forceinline__ void fence_async_global() { asm volatile("fence.proxy.async.global;" ::: "memory"); }
__device__ __forceinline__ void fence_acquire() { asm volatile("fence.acquire.gpu;" ::: "memory"); }
__device__ __forceinline__ void bar_sync(int id, int n) { asm volatile("bar.sync %0, %1;" ::"r"(id), "r"(n) : "memory"); }
__device__ __forceinline__ void bar_arrive(int id, int n) { asm volatile("bar.arrive %0, %1;" ::"r"(id), "r"(n) : "memory"); }
__device__ __forceinline__ void bulk_g2s(uint32_t dst, const void* src, uint32_t bytes, uint32_t bar) {
    asm volatile("cp.async.bulk.shared::cluster.global.mbarrier::complete_tx::bytes [%0], [%1], %2, [%3];"
                 ::"r"(dst), "l"(src), "r"(bytes), "r"(bar) : "memory");
}
__device__ __forceinline__ void tma_x(uint32_t dst, const CUtensorMap* tm, int row, int ch, uint32_t bar) {
    asm volatile("cp.async.bulk.tensor.3d.shared::cluster.global.mbarrier::complete_tx::bytes [%0], [%1, {%2, %3, %4}], [%5];"
                 ::"r"(dst + S0), "l"(tm), "r"(0), "r"(row), "r"(ch), "r"(bar + S0) : "memory");
}
__device__ __forceinline__ uint4 ld_relaxed_v4(const void* p) {
    uint4 v;
    asm volatile("ld.relaxed.gpu.global.v4.u32 {%0,%1,%2,%3}, [%4];" : "=r"(v.x), "=r"(v.y), "=r"(v.z), "=r"(v.w) : "l"(p) : "memory");
    return v;
}
__device__ __forceinline__ unsigned ld_relaxed(const void* p) {
    unsigned v;
    asm volatile("ld.relaxed.gpu.global.u32 %0, [%1];" : "=r"(v) : "l"(p) : "memory");
    return v;
}
__device__ __forceinline__ void red_add4(float* p, float a, float b, float c, float d) {
    asm volatile("red.relaxed.gpu.global.add.v4.f32 [%0], {%1,%2,%3,%4};" ::"l"(p), "f"(a), "f"(b), "f"(c), "f"(d) : "memory");
}
__device__ __forceinline__ void sts128(uint32_t a, uint4 v) {
    asm volatile("st.shared.v4.u32 [%0], {%1,%2,%3,%4};" ::"r"(a + S0), "r"(v.x), "r"(v.y), "r"(v.z), "r"(v.w) : "memory");
}
__device__ __forceinline__ void sts128f(uint32_t a, float4 v) {
    asm volatile("st.shared.v4.f32 [%0], {%1,%2,%3,%4};" ::"r"(a + S0), "f"(v.x), "f"(v.y), "f"(v.z), "f"(v.w) : "memory");
}
__device__ __forceinline__ void sts32f(uint32_t a, float v) { asm volatile("st.shared.f32 [%0], %1;" ::"r"(a + S0), "f"(v) : "memory"); }
__device__ __forceinline__ uint4 lds128(uint32_t a) {
    uint4 v;
    asm volatile("ld.shared.v4.u32 {%0,%1,%2,%3}, [%4];" : "=r"(v.x), "=r"(v.y), "=r"(v.z), "=r"(v.w) : "r"(a + S0) : "memory");
    return v;
}
__device__ __forceinline__ float4 lds128f(uint32_t a) {
    float4 v;
    asm volatile("ld.shared.v4.f32 {%0,%1,%2,%3}, [%4];" : "=f"(v.x), "=f"(v.y), "=f"(v.z), "=f"(v.w) : "r"(a + S0) : "memory");
    return v;
}
__device__ __forceinline__ float2 lds64f(uint32_t a) {
    float2 v;
    asm volatile("ld.shared.v2.f32 {%0,%1}, [%2];" : "=f"(v.x), "=f"(v.y) : "r"(a + S0) : "memory");
    return v;
}
__device__ __forceinline__ float bf_lo(uint32_t u) { return __uint_as_float(u << 16); }
__device__ __forceinline__ float bf_hi(uint32_t u) { return __uint_as_float(u & 0xffff0000u); }
__device__ __forceinline__ uint32_t pack_bf(float lo, float hi) {
    uint32_t r;
    asm("cvt.rn.bf16x2.f32 %0, %1, %2;" : "=r"(r) : "f"(hi), "f"(lo));
    return r;
}
__device__ __forceinline__ float tanh_fast(float x) {
    float r;
    asm("tanh.approx.f32 %0, %1;" : "=f"(r) : "f"(x));
    return r;
}
__device__ __forceinline__ float silu_half(float h) { return fmaf(h, tanh_fast(h), h); }
__device__ __forceinline__ void ldsm4(uint32_t (&u)[4], uint32_t a) {
    asm volatile("ldmatrix.sync.aligned.m8n8.x4.shared.b16 {%0,%1,%2,%3}, [%4];"
                 : "=r"(u[0]), "=r"(u[1]), "=r"(u[2]), "=r"(u[3]) : "r"(a + S0) : "memory");
}
__device__ __forceinline__ void ldsm4t(uint32_t (&u)[4], uint32_t a) {
    asm volatile("ldmatrix.sync.aligned.m8n8.x4.trans.shared.b16 {%0,%1,%2,%3}, [%4];"
                 : "=r"(u[0]), "=r"(u[1]), "=r"(u[2]), "=r"(u[3]) : "r"(a + S0) : "memory");
}
__device__ __forceinline__ void stsm4(uint32_t a, uint32_t p0, uint32_t p1, uint32_t p2, uint32_t p3) {
    asm volatile("stmatrix.sync.aligned.m8n8.x4.shared.b16 [%0], {%1,%2,%3,%4};" ::"r"(a + S0), "r"(p0), "r"(p1), "r"(p2), "r"(p3) : "memory");
}
__device__ __forceinline__ void stsm4t(uint32_t a, uint32_t p0, uint32_t p1, uint32_t p2, uint32_t p3) {
    asm volatile("stmatrix.sync.aligned.m8n8.x4.trans.shared.b16 [%0], {%1,%2,%3,%4};" ::"r"(a + S0), "r"(p0), "r"(p1), "r"(p2), "r"(p3) : "memory");
}

#define R8(o) "+f"(d[o]), "+f"(d[o + 1]), "+f"(d[o + 2]), "+f"(d[o + 3]), "+f"(d[o + 4]), "+f"(d[o + 5]), "+f"(d[o + 6]), "+f"(d[o + 7])
template <uint32_t ALO, uint32_t BLO, uint64_t AHI = 8, uint64_t BHI = 48>
__device__ __forceinline__ void wgmma128(float (&d)[64]) {
    asm volatile(
        "wgmma.mma_async.sync.aligned.m64n128k16.f32.bf16.bf16 "
        "{%0,%1,%2,%3,%4,%5,%6,%7,%8,%9,%10,%11,%12,%13,%14,%15,%16,%17,%18,%19,%20,%21,%22,%23,%24,%25,%26,%27,%28,%29,%30,%31,"
        "%32,%33,%34,%35,%36,%37,%38,%39,%40,%41,%42,%43,%44,%45,%46,%47,%48,%49,%50,%51,%52,%53,%54,%55,%56,%57,%58,%59,%60,%61,%62,%63},"
        " %64, %65, 1, 1, 1, 0, 0;"
        : R8(0), R8(8), R8(16), R8(24), R8(32), R8(40), R8(48), R8(56)
        : "l"((AHI << 32) | ALO), "l"((BHI << 32) | BLO));
}
template <int S>
__device__ __forceinline__ void mma_stages(float (&d)[64], int conv, int tid, Scratch* gs) {
    constexpr uint32_t A = ((SM_ACT + S * 2 * CH_PITCH + 16) >> 4) | ((CH_PITCH >> 4) << 16);
    constexpr uint32_t B = (slot_addr(S % NS) >> 4) | (8u << 16);
    if (S == 0) {
        unsigned it = 0;
#pragma unroll 1
        while (!MMA0_WAIT(BAR(BAR_FULL), conv) && ++it < SPIN_LIMIT) {}
    }
    bool next_ok = true;
    constexpr uint32_t NEXT = S + 1 < NSTAGE ? BAR(BAR_FULL + S + 1) : BAR(BAR_EMB);
    const int npar = S + 1 < NSTAGE ? conv : 0;
    next_ok = mbar_test(NEXT, npar);
    if (S == 0 && tid == 0) TL(32 + conv * 24);
    asm volatile("wgmma.fence.sync.aligned;" ::: "memory");
    wgmma128<A, B>(d);
    wgmma128<A + 1, B + 16>(d);
    wgmma128<A + 2, B + 32>(d);
    asm volatile("wgmma.commit_group.sync.aligned;" ::: "memory");
    if (S >= LAG) {
        asm volatile("wgmma.wait_group.sync.aligned %0;" ::"n"(LAG) : "memory");
        if ((tid & 31) == 0) mbar_arrive(BAR(BAR_WEMPTY + (S + NS - LAG) % NS));
    }
    if (!next_ok) mbar_wait(NEXT, npar);
    if constexpr (S + 1 < NSTAGE) mma_stages<S + 1>(d, conv, tid, gs);
}

__device__ __forceinline__ void weight_load(uint4 (&t)[5], const __nv_bfloat16* w, int cta, int lane) {
    const char* base = reinterpret_cast<const char*>(w) + ((cta & 15) * 8 * C + (cta >> 4) * 16) * 18;
#pragma unroll
    for (int k = 0; k < 5; k++) {
        const int i = lane + 32 * k, row = (i * 57) >> 10;
        if (k < 4 || lane < 16) t[k] = __ldg(reinterpret_cast<const uint4*>(base + row * (C * 18 - 288) + i * 16));
    }
}
__device__ __forceinline__ void weight_block(uint32_t bounce, unsigned char* wt, int cta, int lane, unsigned* hint) {
    unsigned char* dst = wt + (cta >> 4) * STAGE_BYTES + (cta & 15) * 768;
    if (lane < 16) {
        uint32_t v[36];
#pragma unroll
        for (int i = 0; i < 9; i++) {
            const uint4 q = lds128(bounce + (lane & 7) * 288 + (lane >> 3) * 144 + i * 16);
            v[4 * i] = q.x; v[4 * i + 1] = q.y; v[4 * i + 2] = q.z; v[4 * i + 3] = q.w;
        }
#pragma unroll
        for (int kyo = 0; kyo < 3; kyo++) {
#pragma unroll
            for (int kx = 0; kx < 3; kx++) {
                const int tap = ky_of(kyo) * 3 + kx;
                uint32_t o[4];
#pragma unroll
                for (int m = 0; m < 4; m++) {
                    const int i0 = 18 * m + tap, i1 = i0 + 9;
                    const uint32_t sel = ((i0 & 1) ? 0x32u : 0x10u) | ((i1 & 1) ? 0x7600u : 0x5400u);
                    o[m] = __byte_perm(v[i0 >> 1], v[i1 >> 1], sel);
                }
                if (kyo == 0) o[0] = max(o[0], 1u);
                *reinterpret_cast<uint4*>(dst + kyo * 8 * STAGE_BYTES + kx * 256 + lane * 16) = make_uint4(o[0], o[1], o[2], o[3]);
            }
        }
    }
    {
        __syncwarp();
        if (hint && lane < 2) asm volatile("red.relaxed.gpu.global.add.u32 [%0], 0x10000;" ::"l"(hint) : "memory");
        unsigned acc = 0;
        if (lane < 24) {
#pragma unroll
            for (int i = 0; i < 3; i++) acc |= ld_relaxed(dst + i * 8 * STAGE_BYTES + lane * 32);
        }
        asm volatile("{\n.reg .pred p;\nsetp.eq.u32 p, %0, 0x9e3779b9;\n@p st.shared.u32 [%1], %0;\n}" ::"r"(acc), "r"(bounce + S0) : "memory");
    }
}
__device__ __forceinline__ uint32_t act2(uint32_t u, const float4& cf) {
    return pack_bf(silu_half(fmaf(bf_lo(u), cf.x, cf.z)), silu_half(fmaf(bf_hi(u), cf.y, cf.w)));
}
__device__ __forceinline__ void norm_unit(uint32_t (&u)[4], const float4& ca, const float4& cb) {
    u[0] = act2(u[0], ca); u[1] = act2(u[1], ca); u[2] = act2(u[2], cb); u[3] = act2(u[3], cb);
}
__device__ __forceinline__ void read_stats(uint32_t gst, float (&g)[8]) {
    asm volatile("ld.volatile.shared.v4.f32 {%0,%1,%2,%3}, [%4];" : "=f"(g[0]), "=f"(g[1]), "=f"(g[2]), "=f"(g[3]) : "r"(gst + S0) : "memory");
    asm volatile("ld.volatile.shared.v4.f32 {%0,%1,%2,%3}, [%4];" : "=f"(g[4]), "=f"(g[5]), "=f"(g[6]), "=f"(g[7]) : "r"(gst + 16 + S0) : "memory");
}
template <int T>
__device__ __forceinline__ void group_coefs(uint32_t gst, float (&g)[8], float4 (&cf)[8]) {
    unsigned it = 0;
    if (!__all_sync(0xffffffffu, g[2 * T] != 0.f)) {
        float rs0;
#pragma unroll 1
        do {
            SPINPAUSE;
            asm volatile("ld.volatile.shared.f32 %0, [%1];" : "=f"(rs0) : "r"(gst + 8 * T + S0) : "memory");
        } while (!__all_sync(0xffffffffu, rs0 != 0.f) && ++it < 8 * SPIN_LIMIT);
        read_stats(gst, g);
    }
    float4 &ca = cf[2 * T], &cb = cf[2 * T + 1];
    const float rs = g[2 * T], mr = g[2 * T + 1];
    ca.z = fmaf(-mr, ca.x, ca.z); ca.w = fmaf(-mr, ca.y, ca.w); ca.x *= rs; ca.y *= rs;
    cb.z = fmaf(-mr, cb.x, cb.z); cb.w = fmaf(-mr, cb.y, cb.w); cb.x *= rs; cb.y *= rs;
}
template <int FIRST, int N>
__device__ __forceinline__ void norm_block(uint32_t (&u)[4][4], float4 (&cf)[8], uint32_t act, uint32_t mask, uint32_t fbar, int lane) {
#pragma unroll
    for (int t = FIRST; t < FIRST + N; t++) {
        norm_unit(u[t], cf[2 * t], cf[2 * t + 1]);
        stsm4(act + t * 2 * KC_BYTES, u[t][0] & mask, u[t][1] & mask, u[t][2] & mask, u[t][3] & mask);
    }
    fence_async_smem();
    __syncwarp();
    if (lane < N) mbar_arrive(fbar + 16 * (FIRST + lane));
}
__device__ __forceinline__ void publish(uint32_t bar, int lane) {
    fence_async_smem();
    __syncwarp();
    if (lane == 0) mbar_arrive(bar);
}
template <int T>
__device__ __forceinline__ void next_unit(uint32_t (&u)[4][4], float4 (&cf)[8], uint32_t gst, float (&g)[8], uint32_t act, uint32_t fbar, int lane) {
    const bool have = __all_sync(0xffffffffu, g[2 * T] != 0.f);
    if (!have) publish(fbar + 16 * (T - 1), lane);
    group_coefs<T>(gst, g, cf);
    norm_unit(u[T], cf[2 * T], cf[2 * T + 1]);
    if (have) publish(fbar + 16 * (T - 1), lane);
    stsm4(act + T * 2 * KC_BYTES, u[T][0], u[T][1], u[T][2], u[T][3]);
}
__device__ __forceinline__ void stat_mma(float (&c)[4], uint32_t p, uint32_t q) {
    asm("mma.sync.aligned.m16n8k16.row.col.f32.bf16.bf16.f32 {%0,%1,%2,%3}, {%4,%5,%6,%5}, {%4,%6}, {%0,%1,%2,%3};"
        : "+f"(c[0]), "+f"(c[1]), "+f"(c[2]), "+f"(c[3]) : "r"(p), "r"(0x3f803f80u), "r"(q));
}
__device__ __forceinline__ void stat_store(const float (&c)[4], uint32_t dst, int lane) {
    const int g = lane >> 2, t = lane & 3;
    if (t == (g >> 1)) sts32f(dst + g * 4, (g & 1) ? c[1] : c[0]);
    if (g == 7) sts32f(dst + 32 + t * 4, c[2] + c[3]);
}
__device__ __forceinline__ float sum4(float4 v) { return (v.x + v.y) + (v.z + v.w); }
__device__ __forceinline__ void stat_publish(uint32_t src, float* acc, int lane, bool real) {
    const uint32_t a = src + (lane & 15) * 48;
    float q = sum4(lds128f(a)) + sum4(lds128f(a + 16)), sm = sum4(lds128f(a + 32));
    q += __shfl_xor_sync(0xffffffffu, q, 1); sm += __shfl_xor_sync(0xffffffffu, sm, 1);
    q += __shfl_xor_sync(0xffffffffu, q, 2); sm += __shfl_xor_sync(0xffffffffu, sm, 2);
    if (real && (lane & 19) == 0) red_add4(acc + lane, 1.f, sm, q, 1.f);
}
__device__ __forceinline__ void fence_acc(float (&d)[64]) {
#pragma unroll
    for (int i = 0; i < 64; i++) asm volatile("" : "+f"(d[i])::"memory");
}
__device__ __forceinline__ void ld_unit(uint32_t (&u)[4], const uint4* p) {
    asm volatile("ld.relaxed.gpu.global.v4.u32 {%0,%1,%2,%3}, [%4];" : "=r"(u[0]), "=r"(u[1]), "=r"(u[2]), "=r"(u[3]) : "l"(p) : "memory");
}

__device__ __noinline__ void side_jobs(const __nv_bfloat16* __restrict__ t_emb, const __nv_bfloat16* __restrict__ w_emb,
                                       const __nv_bfloat16* __restrict__ w2, Scratch* __restrict__ gs, unsigned clk0) {
    const int tid = threadIdx.x, warp = tid >> 5, lane = tid & 31, j = blockIdx.x;
    float tv = 0.f;
    if (lane < 24) tv = __bfloat162float(t_emb[(lane / 12) * E + j * 192 + warp * 12 + lane % 12]);
    if (tid == 0) {
        mbar_init(BAR(0), 1);
        mbar_expect(BAR(0), 192 * C * 2);
        fence_async_smem();
        while (clock32() - clk0 < SDELAY) {}
#pragma unroll
        for (int i = 0; i < 4; i++)
            asm volatile("cp.async.bulk.prefetch.L2.global [%0], 18432;" ::"l"(reinterpret_cast<const char*>(w2) + (j * 4 + i) * 18432) : "memory");
#pragma unroll
        for (int i = 0; i < 4; i++) bulk_g2s(S0 + SM_W + i * 12288, w_emb + (j * 192 + i * 48) * C, 12288, S0 + BAR(0));
    }
    if (j == 0 && tid < 32) gs->acc2[(tid >> 4) * LS + (tid & 15)] = 0.f;
    const float sv = silu_half(0.5f * tv);
    __syncthreads();
    mbar_wait(BAR(0), 0);
    float acc[8] = {0.f, 0.f, 0.f, 0.f, 0.f, 0.f, 0.f, 0.f};
#pragma unroll
    for (int i = 0; i < 12; i++) {
        const float2 wq = lds64f(SM_W + (warp * 12 + i) * 256 + lane * 8);
        const uint32_t wx = __float_as_uint(wq.x), wy = __float_as_uint(wq.y);
#pragma unroll
        for (int bb = 0; bb < 2; bb++) {
            const float sx = __shfl_sync(0xffffffffu, sv, bb * 12 + i);
            acc[4 * bb + 0] = fmaf(sx, bf_lo(wx), acc[4 * bb + 0]); acc[4 * bb + 1] = fmaf(sx, bf_hi(wx), acc[4 * bb + 1]);
            acc[4 * bb + 2] = fmaf(sx, bf_lo(wy), acc[4 * bb + 2]); acc[4 * bb + 3] = fmaf(sx, bf_hi(wy), acc[4 * bb + 3]);
        }
    }
    sts128f(SM_ACT + warp * 1024 + lane * 16, make_float4(acc[0], acc[1], acc[2], acc[3]));
    sts128f(SM_ACT + warp * 1024 + 512 + lane * 16, make_float4(acc[4], acc[5], acc[6], acc[7]));
    __syncthreads();
    if (tid < 128) {
        float2 sum = make_float2(0.f, 0.f);
#pragma unroll
        for (int w = 0; w < 16; w++) { const float2 p = lds64f(SM_ACT + w * 1024 + tid * 8); sum.x += p.x; sum.y += p.y; }
        *reinterpret_cast<float2*>(&gs->emb[j * NB * C + tid * 2]) = sum;
        bar_sync(1, 128);
        if (tid < 2) asm volatile("red.release.gpu.global.add.u32 [%0], 1;" ::"l"(&gs->wcnt[(2 * NB + tid) * LS]) : "memory");
    }
}

__global__ void __cluster_dims__(2, 1, 1) __launch_bounds__(NTHREADS, 1)
resblock_kernel(const __nv_bfloat16* __restrict__ w1, const __nv_bfloat16* __restrict__ x,
                const __nv_bfloat16* __restrict__ t_emb, const __nv_bfloat16* __restrict__ g1,
                const __nv_bfloat16* __restrict__ be1, const __nv_bfloat16* __restrict__ w_emb,
                const __nv_bfloat16* __restrict__ g2, const __nv_bfloat16* __restrict__ be2,
                const __nv_bfloat16* __restrict__ w2, __nv_bfloat16* __restrict__ out, Scratch* __restrict__ gs,
                const __grid_constant__ CUtensorMap xmap) {
    const unsigned clk0 = clock32();
    if (threadIdx.x == 480 && blockIdx.x >= NXTRA) TLG(1);
    const int tid = threadIdx.x, lane = tid & 31;
    const int cta = blockIdx.x - NXTRA, b = cta >> 6, r = cta & 63;
    uint4 v[5];
    if (tid < 32) weight_load(v, w1, cta & (NCTA - 1), lane);
    uint4 xv[8];
    const int wg4 = (tid >> 5) - 1;
    const bool early = tid >= 32 && wg4 < NLDG;
    if (early) {
        const char* src = reinterpret_cast<const char*>(x) + (uint32_t)((((b & 1) * C + wg4 * 32 + (lane >> 3)) * HW + r) * HW * 2 + (lane & 7) * 16);
        while (clock32() - clk0 < XDELAY + (wg4 >> 1) * XSTAG + (wg4 & 1) * XSTAG2) {}
#pragma unroll
        for (int i = 0; i < 8; i++) xv[i] = __ldg(reinterpret_cast<const uint4*>(src + i * (4 * HW * HW * 2)));
    }
    const int warp = __shfl_sync(0xffffffffu, tid >> 5, 0);
    if (cta < 0) { side_jobs(t_emb, w_emb, w2, gs, clk0); return; }

    if (warp != 4) asm volatile("barrier.cluster.arrive.relaxed.aligned;" ::: "memory");
    const bool has_outer = (r != 0) && (r != HW - 1);
    if (warp == 1 || warp == 2 || warp == 3 || warp == 5) {
        const int g = warp < 4 ? warp - 1 : 3;
        if (elect_one()) {
            if (g >= NLDG) asm volatile("prefetch.tensormap [%0];" ::"l"(&xmap) : "memory");
            mbar_init(BAR(BAR_X) + 8 * g, 1);
            if (g >= NLDG) mbar_expect(BAR(BAR_X) + 8 * g, 4096);
            fence_async_smem();
        }
        __syncwarp();
        bar_arrive(4, 256 + 32 + 128);
        if (g >= NLDG) {
            while (clock32() - clk0 < XDELAY + (g >> 1) * XSTAG + (g & 1) * XSTAG2) {}
            if (elect_one()) tma_x(SM_XOWN + g * 4096, &xmap, r, b * C + g * 32, BAR(BAR_X) + 8 * g);
            __syncwarp();
            mbar_wait(BAR(BAR_X) + 8 * g, 0);
#pragma unroll
            for (int k = 0; k < 8; k++) xv[k] = lds128(SM_XOWN + g * 4096 + k * 512 + lane * 16);
        }
        float c[8][4];
#pragma unroll
        for (int k = 0; k < 8; k++) {
            c[k][0] = c[k][1] = c[k][2] = c[k][3] = 0.f;
            stat_mma(c[k], xv[k].x, xv[k].y); stat_mma(c[k], xv[k].z, xv[k].w);
        }
#pragma unroll
        for (int i = 0; i < 4; i++) c[0][i] = ((c[0][i] + c[1][i]) + (c[2][i] + c[3][i])) + ((c[4][i] + c[5][i]) + (c[6][i] + c[7][i]));
        stat_store(c[0], SM_RED + g * 48, lane);
        __syncwarp();
        if (lane == 0) {
            const uint32_t a = SM_RED + g * 48;
            red_add4(&gs->acc1[b * LS + g * 4], 1.f, sum4(lds128f(a + 32)), sum4(lds128f(a)) + sum4(lds128f(a + 16)), 1.f);
            TL(74 + g);
        }
        if (g < NLDG) {
#pragma unroll
            for (int i = 0; i < 8; i++)
                sts128(SM_XOWN + g * 4096 + i * 512 + (lane >> 3) * 128 + (((lane & 7) ^ ((lane >> 3) + 4 * (i & 1))) << 4), xv[i]);
            __syncwarp();
            if (lane == 0) mbar_arrive(BAR(BAR_X) + 8 * g);
        }
    }
    if (warp == 4) {
            if (elect_one()) {
#pragma unroll
                for (int i = 0; i < NSTAGE; i++) mbar_init(BAR(BAR_FULL + i), (i >> 3) == 1 ? 1 : 5);
#pragma unroll
                for (int i = 0; i < NS + 2; i++) mbar_init(BAR(BAR_WEMPTY + i), 4);
#pragma unroll
                for (int i = BAR_STATS; i < BAR_X; i++) mbar_init(BAR(i), i == BAR_EMB ? 3 : 1);
                mbar_init(BAR(BAR_X + 4), 1);
                asm volatile("fence.mbarrier_init.release.cluster;" ::: "memory");
            }
            if (lane < 4) sts128(SM_GST + lane * 16, make_uint4(0, 0, 0, 0));
            __syncwarp();
            fence_async_smem();
            bar_arrive(0, 96);
            bar_arrive(5, 64);
            bar_arrive(4, 256 + 32 + 128);
            const uint4 z = make_uint4(0, 0, 0, 0);
#pragma unroll
            for (int i = 0; i < 2; i++) sts128(SM_ACT + (i * 16 + (lane >> 1)) * CH_PITCH + (lane & 1) * 16, z);
            if (lane < 4) sts128(SM_ACT + (2 + (lane >> 1)) * ROW_BYTES + (lane & 1) * 16, z);
            if (lane < 16) sts128(SM_ONES + lane * 16, make_uint4(lane < 8 ? 0x3f803f80u : 0u, 0, 0, 0));
            fence_async_smem();
            bar_arrive(7, 160);
            asm volatile("barrier.cluster.arrive.relaxed.aligned;" ::: "memory");
            if (lane == 0) TL(5);
            while (clock32() - clk0 < W2DELAY) {}
            weight_load(v, w2, cta, lane);
        }
    if (warp == 0 || warp == 4) {
        const int k = warp >> 2;
#pragma unroll
        for (int i = 0; i < 5; i++)
            if (i < 4 || lane < 16) sts128(SM_BNC + k * 2304 + (lane + 32 * i) * 16, v[i]);
        if (lane == 0) TL(k ? 14 : 81);
        __syncwarp();
        unsigned* cnt = k ? &gs->wcnt[(NB + (lane & 1)) * LS] : &gs->w1cnt[((lane & 1) * 8 + (cta >> 4)) * KS];
        weight_block(SM_BNC + k * 2304, gs->wt + k * NSTAGE * STAGE_BYTES, cta, lane, (k == 0 && (cta >> 4) < NSPEC) ? cnt : nullptr);
        __syncwarp();
        if (lane == 0) TL(k ? 13 : 4);
        if (lane < 2) asm volatile("red.relaxed.gpu.global.add.u32 [%0], 1;" ::"l"(cnt) : "memory");
    }

    if (warp >= 8) {
        const int nw = warp - 8;
        if (nw < 2) {
            const uint2 ga = __ldg(reinterpret_cast<const uint2*>(nw ? g2 : g1) + lane), bt = __ldg(reinterpret_cast<const uint2*>(nw ? be2 : be1) + lane);
            sts128f(SM_COEF + nw * 1024 + lane * 32, make_float4(0.5f * bf_lo(ga.x), 0.5f * bf_hi(ga.x), 0.5f * bf_lo(bt.x), 0.5f * bf_hi(bt.x)));
            sts128f(SM_COEF + nw * 1024 + lane * 32 + 16, make_float4(0.5f * bf_lo(ga.y), 0.5f * bf_hi(ga.y), 0.5f * bf_lo(bt.y), 0.5f * bf_hi(bt.y)));
        }
        bar_sync(4, 256 + 32 + 128);
        const int par = nw >> 2, wq = nw & 3;
        const uint32_t act_off = SM_ACT + (par * 2 + (lane >> 4)) * CH_PITCH + (2 + wq * 16 + (lane & 15)) * 16;
        const uint32_t stg_off = (par * 16 + (lane >> 4) * 8 + (lane & 7)) * 128 + (((2 * wq + ((lane >> 3) & 1)) ^ (lane & 7)) << 4);
        const uint32_t cfa = SM_COEF + par * 128 + (lane & 3) * 16;
        const uint32_t fbar = BAR(BAR_FULL) + 8 * par;
        uint4* inbox = gs->box + cta * 1024 + nw * 32 + lane;
#pragma unroll 1
        for (int conv = 0; conv < 2; conv++) {
            uint32_t u[4][4], w[4][4];
            float4 cf[8];
            if (conv == 0) {
#pragma unroll
                for (int i = 0; i < 4; i++) { mbar_wait(BAR(BAR_X + i), 0); ldsm4t(u[i], SM_XOWN + stg_off + i * 4096); }
            } else {
                mbar_wait(BAR(BAR_HW), 0);
#pragma unroll
                for (int i = 0; i < 4; i++) ldsm4(u[i], act_off + i * 2 * KC_BYTES);
            }
#pragma unroll
            for (int i = 0; i < 8; i++) cf[i] = lds128f(cfa + conv * 1024 + (i >> 1) * 256 + (i & 1) * 64);
            const uint32_t gst = SM_GST + conv * 32;
            float gv[8];
            read_stats(gst, gv);
            group_coefs<0>(gst, gv, cf);
            if (tid == 256) TL(22 + conv * 4);
            if (par) { const unsigned c1 = clock32(); while (clock32() - c1 < PDELAY) {} }
            norm_block<0, 1>(u, cf, act_off, ~0u, fbar, lane);
            if (tid == 256) TL(8 + conv * 8);
            group_coefs<1>(gst, gv, cf);
            norm_unit(u[1], cf[2], cf[3]);
            stsm4(act_off + 2 * KC_BYTES, u[1][0], u[1][1], u[1][2], u[1][3]);
            next_unit<2>(u, cf, gst, gv, act_off, fbar, lane);
            next_unit<3>(u, cf, gst, gv, act_off, fbar, lane);
            publish(fbar + 48, lane);
            if (tid == 256) TL(84 + conv);
            if (has_outer) {
                mbar_wait(BAR(BAR_X + 4), conv);
                if (conv == 0) {
#pragma unroll
                    for (int i = 0; i < 4; i++) ldsm4t(w[i], SM_XOUT + stg_off + i * 4096);
                } else {
#pragma unroll
                    for (int i = 0; i < 4; i++) {
                        const uint4 q = lds128(SM_XOWN + (tid - 256) * 16 + i * 4096);
                        w[i][0] = q.x; w[i][1] = q.y; w[i][2] = q.z; w[i][3] = q.w;
                    }
                    unsigned it = 0;
                    while (true) {
                        bool ok = true;
#pragma unroll
                        for (int i = 0; i < 16; i++) ok = ok && w[i >> 2][i & 3] != 0;
                        if (__all_sync(0xffffffffu, ok) || ++it > SPIN_LIMIT) break;
#pragma unroll
                        for (int i = 0; i < 4; i++) ld_unit(w[i], inbox + i * 256);
                    }
#pragma unroll
                    for (int i = 0; i < 16; i++) w[i >> 2][i & 3] = ~w[i >> 2][i & 3];
                }
            }
            if (conv == 0) {
                bar_sync(3, 256);
                if (nw == 0) sts128(SM_ACT + 2 * ROW_BYTES + (lane >> 1) * CH_PITCH + (lane & 1) * 16, make_uint4(0, 0, 0, 0));
            }
            if (tid == 256) TL(24 + conv * 4);
            norm_block<0, 2>(w, cf, act_off + 2 * ROW_BYTES, has_outer ? ~0u : 0u, fbar + 128, lane);
            if (tid == 256) TL(88 + conv);
            norm_block<2, 2>(w, cf, act_off + 2 * ROW_BYTES, has_outer ? ~0u : 0u, fbar + 128, lane);
            if (tid == 256) TL(23 + conv * 4);
        }
        if (has_outer) {
            mbar_wait(BAR(BAR_FULL + NSTAGE - 1), 1);
#pragma unroll
            for (int i = 0; i < 4; i++) inbox[i * 256] = make_uint4(0, 0, 0, 0);
        }
        {
            const int oc0 = (tid - 256) >> 3, seg = lane & 7;
            __nv_bfloat16* dst = out + ((size_t)(b * C + oc0) * HW + r) * HW + seg * 8;
            const uint32_t src = SM_XOWN + oc0 * 128 + ((seg ^ (oc0 & 7)) << 4);
            bar_sync(6, 128 + 256);
#pragma unroll
            for (int i = 0; i < 4; i++) *reinterpret_cast<uint4*>(dst + (size_t)i * 32 * HW * HW) = lds128(src + i * 4096);
            if (tid == 256) { TL(20); TLG(21); }
        }
    } else if (warp < 4) {
        const int wq = warp;
        bar_sync(7, 160);

        const uint32_t xbase = SM_XOWN + ((lane >> 4) * 8 + (lane & 7)) * 128 + (((2 * wq + ((lane >> 3) & 1)) ^ (lane & 7)) << 4);
        float d[64];
#pragma unroll
        for (int i = 0; i < 64; i++) d[i] = 0.f;
#pragma unroll 1
        for (int conv = 0; conv < 2; conv++) {
            fence_acc(d);
            mma_stages<0>(d, conv, tid, gs);
            if (conv == 0) {
                asm volatile("wgmma.fence.sync.aligned;" ::: "memory");
                wgmma128<(SM_ONES >> 4) | (8u << 16), (SM_EMB >> 4), 0, 8>(d);
                asm volatile("wgmma.commit_group.sync.aligned;" ::: "memory");
            }
            asm volatile("wgmma.wait_group.sync.aligned 0;" ::: "memory");
            fence_acc(d);
            if (tid == 0) TL(10 + conv * 8);
            uint32_t hp[32];
#pragma unroll
            for (int i = 0; i < 32; i++) hp[i] = pack_bf(d[2 * i], d[2 * i + 1]);
            if (conv == 1) {
#pragma unroll
                for (int kc = 0; kc < 8; kc++) stsm4t(xbase + kc * 2048, hp[4 * kc], hp[4 * kc + 1], hp[4 * kc + 2], hp[4 * kc + 3]);
                bar_arrive(6, 128 + 256);
                break;
            }
#pragma unroll
            for (int g = 0; g < 4; g++) {
                float c[4] = {0.f, 0.f, 0.f, 0.f};
#pragma unroll
                for (int i = 0; i < 4; i++) stat_mma(c, hp[8 * g + 2 * i], hp[8 * g + 2 * i + 1]);
                stat_store(c, SM_RED + (g * 4 + wq) * 48, lane);
            }
            bar_sync(2, 128);
            if (wq == 0) stat_publish(SM_RED, &gs->acc2[b * LS], lane, true);
            if (tid == 0) TL(11);
            const uint32_t hbase = SM_ACT + (lane >> 4) * CH_PITCH + (2 + wq * 16 + (lane & 15)) * 16;
#pragma unroll
            for (int kc = 0; kc < 8; kc++) stsm4(hbase + kc * 2 * CH_PITCH, hp[4 * kc], hp[4 * kc + 1], hp[4 * kc + 2], hp[4 * kc + 3]);
            __syncwarp();
            if (lane == 0) mbar_arrive(BAR(BAR_HW));
            if (lane < LAG) mbar_arrive(BAR(BAR_WEMPTY + (NSTAGE - LAG) % NS) + 8 * lane);
            if (has_outer) {
                uint4* outbox = gs->box + (cta + ((r & 1) ? 1 : -1)) * 1024 + tid;
#pragma unroll
                for (int kc = 0; kc < 8; kc++) outbox[kc * 128] = make_uint4(~hp[4 * kc], ~hp[4 * kc + 1], ~hp[4 * kc + 2], ~hp[4 * kc + 3]);
            }
            if (tid == 0) TL(12);
#pragma unroll
            for (int kc = 0; kc < 8; kc++) {
                uint32_t p[4];
                ldsm4t(p, xbase + kc * 2048);
#pragma unroll
                for (int i = 0; i < 4; i++) { d[8 * kc + 2 * i] = bf_lo(p[i]); d[8 * kc + 2 * i + 1] = bf_hi(p[i]); }
            }
            fence_async_smem();
            __syncwarp();
            if (lane == 0) mbar_arrive(BAR(BAR_XFREE));
        }
        {
        }
    } else if (warp < 6) {
        if (warp == 5) {
            bar_sync(5, 64);
#pragma unroll 1
            for (int st = 0; st < NSPEC; st++) {
#pragma unroll 1
                for (unsigned tr = 0; tr < SPIN_LIMIT; tr++) {
                    mbar_wait(BAR(BAR_SP) + 8 * st, tr & 1);
                    bool ok = true;
#pragma unroll
                    for (int i = 0; i < 12; i++) {
                        uint32_t wd;
                        asm volatile("ld.shared.u32 %0, [%1];" : "=r"(wd) : "r"(S0 + SM_W + st * STAGE_BYTES + i * 1024 + lane * 32 + ((lane >> 2) & 1) * 16) : "memory");
                        ok = ok && wd != 0;
                    }
                    if (__all_sync(0xffffffffu, ok)) break;
                    fence_async_smem();
                    __syncwarp();
                    if (elect_one()) {
                        mbar_expect(BAR(BAR_SP) + 8 * st, STAGE_BYTES);
                        bulk_g2s(S0 + SM_W + st * STAGE_BYTES, gs->wt + st * STAGE_BYTES, STAGE_BYTES, S0 + BAR(BAR_SP) + 8 * st);
                    }
                    if (lane == 0) TL(93);
                }
                if (lane == 0) { mbar_arrive(BAR(BAR_FULL) + 8 * st); if (st == 0) TL(92); }
            }
            mbar_wait(BAR(BAR_FULL + OAFTER), 0);
            if (has_outer && elect_one()) {
                mbar_expect(BAR(BAR_X + 4), 16384);
#pragma unroll
                for (int i = 0; i < 4; i++) tma_x(SM_XOUT + i * 4096, &xmap, r + ((r & 1) ? 1 : -1), b * C + i * 32, BAR(BAR_X + 4));
            }
            __syncwarp();
            asm volatile("barrier.cluster.wait.acquire.aligned;" ::: "memory");
            const uint32_t peer = (r & 1) ^ 1;
            const uint32_t self0 = mapa(0, r & 1), peer0 = mapa(0, peer);
#pragma unroll 1
            for (int conv = 0; conv < 2; conv++) {
#pragma unroll 1
                for (int kc = 0; kc < 8; kc++) {
                    mbar_wait(BAR(BAR_FULL) + 8 * kc, conv);
                    if (elect_one())
                        asm volatile("cp.async.bulk.shared::cluster.shared::cta.mbarrier::complete_tx::bytes [%0], [%1], %2, [%3];"
                                     ::"r"(peer0 + SM_ACT + ROW_BYTES + kc * KC_BYTES), "r"(self0 + SM_ACT + kc * KC_BYTES), "r"(KC_BYTES),
                                       "r"(peer0 + BAR(BAR_FULL + 8) + 8 * kc) : "memory");
                }
                if (lane == 0) TL(86 + conv);
#pragma unroll 1
                for (int kc = 0; kc < 8; kc++) mbar_wait(BAR(BAR_FULL + 8) + 8 * kc, conv);
                if (lane == 0)
                    asm volatile("mbarrier.arrive.relaxed.cluster.shared::cluster.b64 _, [%0];" ::"r"(peer0 + (conv ? BAR(BAR_ACK) : BAR(BAR_EMB))) : "memory");
            }
            mbar_wait(BAR(BAR_ACK), 0);
        } else {
            mbar_wait(BAR(BAR_STATS), 0);
            unsigned it = 0;
            while (ld_relaxed(&gs->wcnt[(2 * NB + b) * LS]) < (unsigned)NXTRA && ++it < SPIN_LIMIT) __nanosleep(100);
            fence_acquire();
            float ev[4] = {0.f, 0.f, 0.f, 0.f};
#pragma unroll
            for (int j = 0; j < NXTRA; j++) {
                const uint4 ef = ld_relaxed_v4(&gs->emb[(j * NB + b) * C + lane * 4]);
                ev[0] += __uint_as_float(ef.x); ev[1] += __uint_as_float(ef.y); ev[2] += __uint_as_float(ef.z); ev[3] += __uint_as_float(ef.w);
            }
#pragma unroll
            for (int i = 0; i < 4; i++) {
                const float hi = bf_lo(pack_bf(ev[i], 0.f));
                sts128(SM_EMB + (lane * 4 + i) * 16, make_uint4(pack_bf(hi, ev[i] - hi), 0, 0, 0));
            }
            fence_async_smem();
            __syncwarp();
            if (lane == 0) { mbar_arrive(BAR(BAR_EMB)); TL(19); }
        }
    } else if (warp == 6) {
        bar_sync(0, 96);
        const uint32_t ebytes = STAGE_BYTES + ((lane >> 3) == 1 ? KC_BYTES : 0);
        if (lane < NSTAGE) mbar_expect(lane < NSPEC ? BAR(BAR_SP) + 8 * lane : BAR(BAR_FULL) + 8 * lane, ebytes);
        const int swap = (r & 1) ? 0 : 8 * STAGE_BYTES;
        unsigned it = 0;
        {
            int g = 0;
            const unsigned* cnt = &gs->w1cnt[(b * 8 + (lane & 7)) * KS];
            unsigned cv = ld_relaxed(cnt);
#pragma unroll 1
            while (g < NS) {
                unsigned ready = __ballot_sync(0xffffffffu, (lane < NSPEC ? cv >> 16 : cv & 0xffffu) >= 16u);
                if (ready != ~0u) cv = ld_relaxed(cnt);
                ready >>= g;
                if (++it > SPIN_LIMIT) ready = ~0u;
                if (!(ready & 1)) continue;
                fence_async_global();
                if (lane == 0) TL(g ? 3 : 6);
#pragma unroll 1
                for (; (ready & 1) && g < NS; g++, ready >>= 1)
                    if (elect_one())
                        bulk_g2s(S0 + SM_W + g * STAGE_BYTES, gs->wt + g * STAGE_BYTES + (g >= 8 ? swap : 0), STAGE_BYTES,
                                 S0 + (g < NSPEC ? BAR(BAR_SP) : BAR(BAR_FULL)) + 8 * g);
            }
            static_assert(NSPEC <= 4, "stages 8..11 check the confirmed counts of the hinted chunks");
        }
#pragma unroll 1
        for (int q = 3; q < 12; q++) {
            const int conv = q >= 6, qs = conv ? q - 6 : q, sl = q % 3;
            const unsigned char* wsrc = gs->wt + q * 4 * STAGE_BYTES + (qs < 2 ? 0 : (qs < 4 ? swap : -swap));
            const uint32_t par = (q / 3 - 1) & 1;
            if (q == 6) {
                it = 0;
                while (ld_relaxed(&gs->wcnt[(NB + b) * LS]) < (unsigned)NCTA && ++it < SPIN_LIMIT) {}
                fence_acquire();
                fence_async_global();
                if (lane == 0) { mbar_arrive(BAR(BAR_EMB)); TL(2); }
            }
#pragma unroll
            for (int i = 0; i < 4; i++) {
                mbar_wait(BAR(BAR_WEMPTY + i) + 32 * sl, par);
                if (i == 0 && (q == 6 || q == 9)) {
                    if ((lane >= NS) == (q == 9) && lane < NSTAGE) mbar_expect(BAR(BAR_FULL) + 8 * lane, ebytes);
                    __syncwarp();
                }
                if (elect_one())
                    bulk_g2s(S0 + SM_W + (sl * 4 + i) * STAGE_BYTES, wsrc + i * STAGE_BYTES, STAGE_BYTES, S0 + BAR(BAR_FULL + i) + 32 * qs);
            }
        }
    } else {
        bar_sync(0, 96);
#pragma unroll 1
        for (int conv = 0; conv < 2; conv++) {
            if (conv == 1) mbar_wait(BAR(BAR_HW), 0);
            const float* asrc = (conv ? gs->acc2 : gs->acc1) + b * LS + (lane & 3) * 4;
            unsigned it = 0;
#pragma unroll 1
            while (true) {
                const uint4 f = ld_relaxed_v4(asrc);
                const bool ok = ((f.x == 0x42800000u) & (f.w == 0x42800000u)) || ++it > SPIN_LIMIT;
                if (ok && lane < 4) {
                    const float inv_n = 1.0f / (32.0f * HW * HW);
                    const float mean = __uint_as_float(f.y) * inv_n;
                    const float rs = rsqrtf(fmaxf(fmaf(-mean, mean, __uint_as_float(f.z) * inv_n), 0.f) + 1e-5f);
                    asm volatile("st.shared.v2.f32 [%0], {%1,%2};" ::"r"(S0 + SM_GST + conv * 32 + lane * 8), "f"(rs == 0.f ? 1e-38f : rs), "f"(mean * rs) : "memory");
                }
                if (__all_sync(0xffffffffu, ok)) break;
            }
            if (lane == 0) { mbar_arrive(BAR(BAR_STATS)); TL(7 + conv * 8); }
        }
        mbar_wait(BAR(BAR_XFREE), 0);
        if (has_outer && elect_one()) {
            mbar_expect(BAR(BAR_X + 4), 16384);
            bulk_g2s(S0 + SM_XOWN, gs->box + cta * 1024, 16384, S0 + BAR(BAR_X + 4));
        }
        if ((cta >> 4) < NSPEC) {
            unsigned it = 0;
            while (!__all_sync(0xffffffffu, ld_relaxed(&gs->acc2[(b ^ 1) * LS]) == 0x42800000u) && ++it < SPIN_LIMIT) __nanosleep(200);
            if (lane < 24) {
                uint4* z = reinterpret_cast<uint4*>(gs->wt + (cta >> 4) * STAGE_BYTES + (cta & 15) * 768) + lane * 2;
                z[0] = make_uint4(0, 0, 0, 0); z[1] = make_uint4(0, 0, 0, 0);
            }
        }
        if (r == 0) {
            if (lane < 16) gs->acc1[b * LS + lane] = 0.f;
            if (lane < 3) gs->wcnt[(lane * NB + b) * LS] = 0;
            if (lane < 8) gs->w1cnt[(b * 8 + lane) * KS] = 0;
        }
    }
}

}

extern "C" void kernel_launch(void* const* d_in, const int* in_sizes, int n_in, void* d_out, int out_size) {
    (void)in_sizes; (void)n_in; (void)out_size;
    typedef CUresult (*EncodeFn)(CUtensorMap*, CUtensorMapDataType, cuuint32_t, void*, const cuuint64_t*, const cuuint64_t*,
                                 const cuuint32_t*, const cuuint32_t*, CUtensorMapInterleave, CUtensorMapSwizzle,
                                 CUtensorMapL2promotion, CUtensorMapFloatOOBfill);
    static Scratch* gs = nullptr;
    static EncodeFn encode = nullptr;
    if (!gs) {
        cudaFuncSetAttribute(resblock_kernel, cudaFuncAttributeMaxDynamicSharedMemorySize, SM_TOTAL);
        cudaGetSymbolAddress((void**)&gs, g_scratch);
        cudaDriverEntryPointQueryResult qr;
        cudaGetDriverEntryPoint("cuTensorMapEncodeTiled", (void**)&encode, cudaEnableDefault, &qr);
    }
    CUtensorMap xmap;
    const cuuint64_t dims[3] = {HW, HW, NB * C}, strides[2] = {HW * 2, HW * HW * 2};
    const cuuint32_t box[3] = {HW, 1, 32}, es[3] = {1, 1, 1};
    encode(&xmap, CU_TENSOR_MAP_DATA_TYPE_BFLOAT16, 3, d_in[0], dims, strides, box, es, CU_TENSOR_MAP_INTERLEAVE_NONE,
           CU_TENSOR_MAP_SWIZZLE_128B, CU_TENSOR_MAP_L2_PROMOTION_NONE, CU_TENSOR_MAP_FLOAT_OOB_FILL_NONE);
    resblock_kernel<<<NCTA + NXTRA, NTHREADS, SM_TOTAL>>>(
        (const __nv_bfloat16*)d_in[4], (const __nv_bfloat16*)d_in[0], (const __nv_bfloat16*)d_in[1],
        (const __nv_bfloat16*)d_in[2], (const __nv_bfloat16*)d_in[3], (const __nv_bfloat16*)d_in[5],
        (const __nv_bfloat16*)d_in[6], (const __nv_bfloat16*)d_in[7], (const __nv_bfloat16*)d_in[8],
        (__nv_bfloat16*)d_out, gs, xmap);
}
```

```cpp
#include <cuda_runtime.h>
#include <cuda.h>
#include <cuda_bf16.h>
#include <stdint.h>

namespace {

constexpr int C = 128, HW = 64, NB = 2, E = 768;
constexpr int NCTA = NB * HW;
constexpr int NXTRA = 4;
constexpr int NTHREADS = 16 * 32;
constexpr int CH_PITCH = 66 * 16;
constexpr int ROW_BYTES = 16 * CH_PITCH;
constexpr int STEP_BYTES = 4096;
constexpr int STAGE_BYTES = 3 * STEP_BYTES;
constexpr int NSTAGE = 24;
constexpr int KC_BYTES = 2 * CH_PITCH;
constexpr int NS = 12;
constexpr int LAG = 1;
#define XDELAY 400
#define HDELAY 600
#define SEQ 1
#define MMA0_WAIT mbar_try
#define NPOLL 1
#define PD2 0
#define ODELAY 100
#define NLDG 2
#define PSTAG -1
#define PDELAY0 400
#define PDELAY 60
#define RB 1
#define XSTAG2 400
#define XSTAG 800
#define HSEND 0
#define SDELAY 600
#define OAFTER 0
#define W2DELAY 2400

constexpr uint32_t SMEM_BASE = 0x400;
constexpr uint32_t SM_XOWN = SMEM_BASE;
constexpr uint32_t SM_ACT = SM_XOWN + 16384 + 512;
constexpr uint32_t SM_XOUT = SM_ACT + 2 * ROW_BYTES + 512;
static_assert(SM_XOUT % 1024 == 0, "swizzle atom alignment");
constexpr uint32_t SM_W = SM_ACT + 3 * ROW_BYTES + 128;
__host__ __device__ constexpr uint32_t slot_addr(int slot) { return SM_W + slot * STAGE_BYTES; }
constexpr uint32_t SM_COEF = SM_W + NS * STAGE_BYTES;
constexpr uint32_t SM_GST = SM_COEF + 2048;
constexpr uint32_t SM_EMB = SM_GST + 128;
constexpr uint32_t SM_ONES = SM_EMB + 2048;
constexpr uint32_t SM_RED = SM_ONES + 256;
constexpr uint32_t SM_BNC = SM_RED + 1536;
constexpr uint32_t SM_BAR = SM_BNC + 2 * 2304;
constexpr int BAR_FULL = 0, BAR_WEMPTY = NSTAGE, BAR_HW = BAR_WEMPTY + NS, BAR_XFREE = BAR_HW + 1, BAR_STATS = BAR_XFREE + 1,
              BAR_EMB = BAR_STATS + 1, BAR_ACK = BAR_EMB + 1, BAR_X = BAR_ACK + 1  , NBAR = BAR_X + 5;
constexpr int SM_TOTAL = SM_BAR + NBAR * 8 - SMEM_BASE;
static_assert(SM_TOTAL <= 232448, "smem");
static_assert(NBAR <= 96, "barrier init");
__host__ __device__ constexpr uint32_t BAR(int i) { return SM_BAR + 8 * i; }
__host__ __device__ constexpr int ky_of(int kyo) { return kyo == 0 ? 1 : (kyo == 1 ? 0 : 2); }

constexpr unsigned SPIN_LIMIT = 1u << 16;

#define LS 1056
#define GS1 4
#define PD 0
#define EPI 0
#define KS 32
struct Scratch {
    float acc1[NB * LS];
    float acc2[NB * LS];
    unsigned wcnt[3 * NB * LS];
    unsigned w1cnt[NB * 8 * KS];
    float emb[NXTRA * NB * C];
    alignas(1024) unsigned char wt[2 * NSTAGE * STAGE_BYTES];
    uint4 box[NCTA * 1024];
};
__device__ __align__(1024) Scratch g_scratch;
#define TL(i) do {} while (0)
#define TLG(i) do {} while (0)

__device__ __forceinline__ unsigned clock32() { unsigned c; asm volatile("mov.u32 %0, %%clock;" : "=r"(c)); return c; }
__device__ __forceinline__ uint32_t mapa(uint32_t a, uint32_t rank) {
    uint32_t d;
    asm("mapa.shared::cluster.u32 %0, %1, %2;" : "=r"(d) : "r"(a), "r"(rank));
    return d;
}
#define S0 mapa(0, blockIdx.x & 1)
__device__ __forceinline__ void mbar_init(uint32_t bar, int cnt) {
    asm volatile("mbarrier.init.shared::cta.b64 [%0], %1;" ::"r"(bar + S0), "r"(cnt) : "memory");
}
__device__ __forceinline__ void mbar_arrive(uint32_t bar) {
    asm volatile("mbarrier.arrive.shared::cta.b64 _, [%0];" ::"r"(bar + S0) : "memory");
}
__device__ __forceinline__ void mbar_expect(uint32_t bar, uint32_t bytes) {
    asm volatile("mbarrier.arrive.expect_tx.shared::cta.b64 _, [%0], %1;" ::"r"(bar + S0), "r"(bytes) : "memory");
}
__device__ __forceinline__ bool mbar_try(uint32_t bar, uint32_t par) {
    uint32_t ok;
    asm volatile("{\n.reg .pred p;\nmbarrier.try_wait.parity.shared::cta.b64 p, [%1], %2;\nselp.u32 %0, 1, 0, p;\n}"
                 : "=r"(ok) : "r"(bar + S0), "r"(par) : "memory");
    return ok;
}
__device__ __forceinline__ bool mbar_test(uint32_t bar, uint32_t par) {
    uint32_t ok;
    asm volatile("{\n.reg .pred p;\nmbarrier.test_wait.parity.shared::cta.b64 p, [%1], %2;\nselp.u32 %0, 1, 0, p;\n}"
                 : "=r"(ok) : "r"(bar + S0), "r"(par) : "memory");
    return ok;
}
__device__ __forceinline__ void mbar_wait(uint32_t bar, uint32_t par) {
    unsigned it = 0;
#pragma unroll 1
    while (!mbar_try(bar, par) && ++it < SPIN_LIMIT) {}
}
__device__ __forceinline__ bool elect_one() {
    uint32_t p;
    asm volatile("{\n.reg .pred p;\nelect.sync _|p, 0xffffffff;\nselp.u32 %0, 1, 0, p;\n}" : "=r"(p));
    return p;
}
__device__ __forceinline__ void fence_async_smem() { asm volatile("fence.proxy.async.shared::cta;" ::: "memory"); }
__device__ __forceinline__ void fence_async_global() { asm volatile("fence.proxy.async.global;" ::: "memory"); }
__device__ __forceinline__ void fence_acquire() { asm volatile("fence.acquire.gpu;" ::: "memory"); }
__device__ __forceinline__ void bar_sync(int id, int n) { asm volatile("bar.sync %0, %1;" ::"r"(id), "r"(n) : "memory"); }
__device__ __forceinline__ void bar_arrive(int id, int n) { asm volatile("bar.arrive %0, %1;" ::"r"(id), "r"(n) : "memory"); }
__device__ __forceinline__ void bulk_g2s(uint32_t dst, const void* src, uint32_t bytes, uint32_t bar) {
    asm volatile("cp.async.bulk.shared::cluster.global.mbarrier::complete_tx::bytes [%0], [%1], %2, [%3];"
                 ::"r"(dst), "l"(src), "r"(bytes), "r"(bar) : "memory");
}
__device__ __forceinline__ void tma_x(uint32_t dst, const CUtensorMap* tm, int row, int ch, uint32_t bar) {
    asm volatile("cp.async.bulk.tensor.3d.shared::cluster.global.mbarrier::complete_tx::bytes [%0], [%1, {%2, %3, %4}], [%5];"
                 ::"r"(dst + S0), "l"(tm), "r"(0), "r"(row), "r"(ch), "r"(bar + S0) : "memory");
}
__device__ __forceinline__ uint4 ld_relaxed_v4(const void* p) {
    uint4 v;
    asm volatile("ld.relaxed.gpu.global.v4.u32 {%0,%1,%2,%3}, [%4];" : "=r"(v.x), "=r"(v.y), "=r"(v.z), "=r"(v.w) : "l"(p) : "memory");
    return v;
}
__device__ __forceinline__ unsigned ld_relaxed(const void* p) {
    unsigned v;
    asm volatile("ld.relaxed.gpu.global.u32 %0, [%1];" : "=r"(v) : "l"(p) : "memory");
    return v;
}
__device__ __forceinline__ void red_add4(float* p, float a, float b, float c, float d) {
    asm volatile("red.relaxed.gpu.global.add.v4.f32 [%0], {%1,%2,%3,%4};" ::"l"(p), "f"(a), "f"(b), "f"(c), "f"(d) : "memory");
}
__device__ __forceinline__ void sts128(uint32_t a, uint4 v) {
    asm volatile("st.shared.v4.u32 [%0], {%1,%2,%3,%4};" ::"r"(a + S0), "r"(v.x), "r"(v.y), "r"(v.z), "r"(v.w) : "memory");
}
__device__ __forceinline__ void sts128f(uint32_t a, float4 v) {
    asm volatile("st.shared.v4.f32 [%0], {%1,%2,%3,%4};" ::"r"(a + S0), "f"(v.x), "f"(v.y), "f"(v.z), "f"(v.w) : "memory");
}
__device__ __forceinline__ void sts32f(uint32_t a, float v) { asm volatile("st.shared.f32 [%0], %1;" ::"r"(a + S0), "f"(v) : "memory"); }
__device__ __forceinline__ uint4 lds128(uint32_t a) {
    uint4 v;
    asm volatile("ld.shared.v4.u32 {%0,%1,%2,%3}, [%4];" : "=r"(v.x), "=r"(v.y), "=r"(v.z), "=r"(v.w) : "r"(a + S0) : "memory");
    return v;
}
__device__ __forceinline__ float4 lds128f(uint32_t a) {
    float4 v;
    asm volatile("ld.shared.v4.f32 {%0,%1,%2,%3}, [%4];" : "=f"(v.x), "=f"(v.y), "=f"(v.z), "=f"(v.w) : "r"(a + S0) : "memory");
    return v;
}
__device__ __forceinline__ float2 lds64f(uint32_t a) {
    float2 v;
    asm volatile("ld.shared.v2.f32 {%0,%1}, [%2];" : "=f"(v.x), "=f"(v.y) : "r"(a + S0) : "memory");
    return v;
}
__device__ __forceinline__ float bf_lo(uint32_t u) { return __uint_as_float(u << 16); }
__device__ __forceinline__ float bf_hi(uint32_t u) { return __uint_as_float(u & 0xffff0000u); }
__device__ __forceinline__ uint32_t pack_bf(float lo, float hi) {
    uint32_t r;
    asm("cvt.rn.bf16x2.f32 %0, %1, %2;" : "=r"(r) : "f"(hi), "f"(lo));
    return r;
}
__device__ __forceinline__ float tanh_fast(float x) {
    float r;
    asm("tanh.approx.f32 %0, %1;" : "=f"(r) : "f"(x));
    return r;
}
__device__ __forceinline__ float silu_half(float h) { return fmaf(h, tanh_fast(h), h); }
__device__ __forceinline__ void ldsm4(uint32_t (&u)[4], uint32_t a) {
    asm volatile("ldmatrix.sync.aligned.m8n8.x4.shared.b16 {%0,%1,%2,%3}, [%4];"
                 : "=r"(u[0]), "=r"(u[1]), "=r"(u[2]), "=r"(u[3]) : "r"(a + S0) : "memory");
}
__device__ __forceinline__ void ldsm4t(uint32_t (&u)[4], uint32_t a) {
    asm volatile("ldmatrix.sync.aligned.m8n8.x4.trans.shared.b16 {%0,%1,%2,%3}, [%4];"
                 : "=r"(u[0]), "=r"(u[1]), "=r"(u[2]), "=r"(u[3]) : "r"(a + S0) : "memory");
}
__device__ __forceinline__ void stsm4(uint32_t a, uint32_t p0, uint32_t p1, uint32_t p2, uint32_t p3) {
    asm volatile("stmatrix.sync.aligned.m8n8.x4.shared.b16 [%0], {%1,%2,%3,%4};" ::"r"(a + S0), "r"(p0), "r"(p1), "r"(p2), "r"(p3) : "memory");
}
__device__ __forceinline__ void stsm4t(uint32_t a, uint32_t p0, uint32_t p1, uint32_t p2, uint32_t p3) {
    asm volatile("stmatrix.sync.aligned.m8n8.x4.trans.shared.b16 [%0], {%1,%2,%3,%4};" ::"r"(a + S0), "r"(p0), "r"(p1), "r"(p2), "r"(p3) : "memory");
}

#define R8(o) "+f"(d[o]), "+f"(d[o + 1]), "+f"(d[o + 2]), "+f"(d[o + 3]), "+f"(d[o + 4]), "+f"(d[o + 5]), "+f"(d[o + 6]), "+f"(d[o + 7])
template <uint32_t ALO, uint32_t BLO, uint64_t AHI = 8, uint64_t BHI = 48>
__device__ __forceinline__ void wgmma128(float (&d)[64]) {
    asm volatile(
        "wgmma.mma_async.sync.aligned.m64n128k16.f32.bf16.bf16 "
        "{%0,%1,%2,%3,%4,%5,%6,%7,%8,%9,%10,%11,%12,%13,%14,%15,%16,%17,%18,%19,%20,%21,%22,%23,%24,%25,%26,%27,%28,%29,%30,%31,"
        "%32,%33,%34,%35,%36,%37,%38,%39,%40,%41,%42,%43,%44,%45,%46,%47,%48,%49,%50,%51,%52,%53,%54,%55,%56,%57,%58,%59,%60,%61,%62,%63},"
        " %64, %65, 1, 1, 1, 0, 0;"
        : R8(0), R8(8), R8(16), R8(24), R8(32), R8(40), R8(48), R8(56)
        : "l"((AHI << 32) | ALO), "l"((BHI << 32) | BLO));
}
template <int S>
__device__ __forceinline__ void mma_stages(float (&d)[64], int conv, int tid, Scratch* gs) {
    constexpr uint32_t A = ((SM_ACT + S * 2 * CH_PITCH + 16) >> 4) | ((CH_PITCH >> 4) << 16);
    constexpr uint32_t B = (slot_addr(S % NS) >> 4) | (8u << 16);
    if (S == 0) {
        unsigned it = 0;
#pragma unroll 1
        while (!MMA0_WAIT(BAR(BAR_FULL), conv) && ++it < SPIN_LIMIT) {}
    }
    bool next_ok = true;
    constexpr uint32_t NEXT = S + 1 < NSTAGE ? BAR(BAR_FULL + S + 1) : BAR(BAR_EMB);
    const int npar = S + 1 < NSTAGE ? conv : 0;
    next_ok = mbar_test(NEXT, npar);
    if (S == 0 && tid == 0) TL(32 + conv * 24);
    asm volatile("wgmma.fence.sync.aligned;" ::: "memory");
    wgmma128<A, B>(d);
    wgmma128<A + 1, B + 16>(d);
    wgmma128<A + 2, B + 32>(d);
    asm volatile("wgmma.commit_group.sync.aligned;" ::: "memory");
    if (S >= LAG) {
        asm volatile("wgmma.wait_group.sync.aligned %0;" ::"n"(LAG) : "memory");
        if ((tid & 31) == 0) mbar_arrive(BAR(BAR_WEMPTY + (S + NS - LAG) % NS));
    }
    if (!next_ok) mbar_wait(NEXT, npar);
    if constexpr (S + 1 < NSTAGE) mma_stages<S + 1>(d, conv, tid, gs);
}

__device__ __forceinline__ void weight_load(uint4 (&t)[5], const __nv_bfloat16* w, int cta, int lane) {
    const char* base = reinterpret_cast<const char*>(w) + ((cta & 15) * 8 * C + (cta >> 4) * 16) * 18;
#pragma unroll
    for (int k = 0; k < 5; k++) {
        const int i = lane + 32 * k, row = (i * 57) >> 10;
        if (k < 4 || lane < 16) t[k] = __ldg(reinterpret_cast<const uint4*>(base + row * (C * 18 - 288) + i * 16));
    }
}
__device__ __forceinline__ void weight_block(uint32_t bounce, unsigned char* wt, int cta, int lane, bool readback, Scratch* gs) {
    unsigned char* dst = wt + (cta >> 4) * STAGE_BYTES + (cta & 15) * 768;
    if (lane < 16) {
        uint32_t v[36];
#pragma unroll
        for (int i = 0; i < 9; i++) {
            const uint4 q = lds128(bounce + (lane & 7) * 288 + (lane >> 3) * 144 + i * 16);
            v[4 * i] = q.x; v[4 * i + 1] = q.y; v[4 * i + 2] = q.z; v[4 * i + 3] = q.w;
        }
#pragma unroll
        for (int kyo = 0; kyo < 3; kyo++) {
#pragma unroll
            for (int kx = 0; kx < 3; kx++) {
                const int tap = ky_of(kyo) * 3 + kx;
                uint32_t o[4];
#pragma unroll
                for (int m = 0; m < 4; m++) {
                    const int i0 = 18 * m + tap, i1 = i0 + 9;
                    const uint32_t sel = ((i0 & 1) ? 0x32u : 0x10u) | ((i1 & 1) ? 0x7600u : 0x5400u);
                    o[m] = __byte_perm(v[i0 >> 1], v[i1 >> 1], sel);
                }
                *reinterpret_cast<uint4*>(dst + kyo * 8 * STAGE_BYTES + kx * 256 + lane * 16) = make_uint4(o[0], o[1], o[2], o[3]);
            }
        }
    }
    if (readback) {
        __syncwarp();
        unsigned acc = 0;
        if (lane < 24) {
#pragma unroll
            for (int i = 0; i < 3; i++) acc |= ld_relaxed(dst + i * 8 * STAGE_BYTES + lane * 32);
        }
        asm volatile("{\n.reg .pred p;\nsetp.eq.u32 p, %0, 0x9e3779b9;\n@p st.shared.u32 [%1], %0;\n}" ::"r"(acc), "r"(bounce + S0) : "memory");
    }
}
__device__ __forceinline__ uint32_t act2(uint32_t u, const float4& cf) {
    return pack_bf(silu_half(fmaf(bf_lo(u), cf.x, cf.z)), silu_half(fmaf(bf_hi(u), cf.y, cf.w)));
}
__device__ __forceinline__ void norm_unit(uint32_t (&u)[4], const float4& ca, const float4& cb) {
    u[0] = act2(u[0], ca); u[1] = act2(u[1], ca); u[2] = act2(u[2], cb); u[3] = act2(u[3], cb);
}
__device__ __forceinline__ void read_stats(uint32_t gst, float (&g)[8]) {
    asm volatile("ld.volatile.shared.v4.f32 {%0,%1,%2,%3}, [%4];" : "=f"(g[0]), "=f"(g[1]), "=f"(g[2]), "=f"(g[3]) : "r"(gst + S0) : "memory");
    asm volatile("ld.volatile.shared.v4.f32 {%0,%1,%2,%3}, [%4];" : "=f"(g[4]), "=f"(g[5]), "=f"(g[6]), "=f"(g[7]) : "r"(gst + 16 + S0) : "memory");
}
template <int T>
__device__ __forceinline__ void group_coefs(uint32_t gst, float (&g)[8], float4 (&cf)[8]) {
    float rs = g[2 * T], mr = g[2 * T + 1];
    if (!__all_sync(0xffffffffu, rs != 0.f)) {
        unsigned it = 0;
#pragma unroll 1
        do {
            asm volatile("ld.volatile.shared.v2.f32 {%0,%1}, [%2];" : "=f"(rs), "=f"(mr) : "r"(gst + 8 * T + S0) : "memory");
        } while (!__all_sync(0xffffffffu, rs != 0.f) && ++it < 8 * SPIN_LIMIT);
        if (T < 3) read_stats(gst, g);
    }
    float4 &ca = cf[2 * T], &cb = cf[2 * T + 1];
    ca.z = fmaf(-mr, ca.x, ca.z); ca.w = fmaf(-mr, ca.y, ca.w); ca.x *= rs; ca.y *= rs;
    cb.z = fmaf(-mr, cb.x, cb.z); cb.w = fmaf(-mr, cb.y, cb.w); cb.x *= rs; cb.y *= rs;
}
template <int FIRST, int N>
__device__ __forceinline__ void norm_block(uint32_t (&u)[4][4], float4 (&cf)[8], uint32_t act, uint32_t mask, uint32_t fbar, int lane) {
#pragma unroll
    for (int t = FIRST; t < FIRST + N; t++) {
        norm_unit(u[t], cf[2 * t], cf[2 * t + 1]);
        stsm4(act + t * 2 * KC_BYTES, u[t][0] & mask, u[t][1] & mask, u[t][2] & mask, u[t][3] & mask);
    }
    fence_async_smem();
    __syncwarp();
    if (lane < N) mbar_arrive(fbar + 16 * (FIRST + lane));
}
__device__ __forceinline__ void publish(uint32_t bar, int lane) {
    fence_async_smem();
    __syncwarp();
    if (lane == 0) mbar_arrive(bar);
}
template <int T>
__device__ __forceinline__ void next_unit(uint32_t (&u)[4][4], float4 (&cf)[8], uint32_t gst, float (&g)[8], uint32_t act, uint32_t fbar, int lane) {
    const bool have = __all_sync(0xffffffffu, g[2 * T] != 0.f);
    if (!have) publish(fbar + 16 * (T - 1), lane);
    group_coefs<T>(gst, g, cf);
    norm_unit(u[T], cf[2 * T], cf[2 * T + 1]);
    if (have) publish(fbar + 16 * (T - 1), lane);
    stsm4(act + T * 2 * KC_BYTES, u[T][0], u[T][1], u[T][2], u[T][3]);
}
__device__ __forceinline__ void stat_mma(float (&c)[4], uint32_t p, uint32_t q) {
    asm("mma.sync.aligned.m16n8k16.row.col.f32.bf16.bf16.f32 {%0,%1,%2,%3}, {%4,%5,%6,%5}, {%4,%6}, {%0,%1,%2,%3};"
        : "+f"(c[0]), "+f"(c[1]), "+f"(c[2]), "+f"(c[3]) : "r"(p), "r"(0x3f803f80u), "r"(q));
}
__device__ __forceinline__ void stat_store(const float (&c)[4], uint32_t dst, int lane) {
    const int g = lane >> 2, t = lane & 3;
    if (t == (g >> 1)) sts32f(dst + g * 4, (g & 1) ? c[1] : c[0]);
    if (g == 7) sts32f(dst + 32 + t * 4, c[2] + c[3]);
}
__device__ __forceinline__ float sum4(float4 v) { return (v.x + v.y) + (v.z + v.w); }
__device__ __forceinline__ void stat_publish(uint32_t src, float* acc, int lane, bool real) {
    const uint32_t a = src + (lane & 15) * 48;
    float q = sum4(lds128f(a)) + sum4(lds128f(a + 16)), sm = sum4(lds128f(a + 32));
    q += __shfl_xor_sync(0xffffffffu, q, 1); sm += __shfl_xor_sync(0xffffffffu, sm, 1);
    q += __shfl_xor_sync(0xffffffffu, q, 2); sm += __shfl_xor_sync(0xffffffffu, sm, 2);
    if (real && (lane & 19) == 0) red_add4(acc + lane, 1.f, sm, q, 1.f);
}
__device__ __forceinline__ void fence_acc(float (&d)[64]) {
#pragma unroll
    for (int i = 0; i < 64; i++) asm volatile("" : "+f"(d[i])::"memory");
}
__device__ __forceinline__ void ld_unit(uint32_t (&u)[4], const uint4* p) {
    asm volatile("ld.relaxed.gpu.global.v4.u32 {%0,%1,%2,%3}, [%4];" : "=r"(u[0]), "=r"(u[1]), "=r"(u[2]), "=r"(u[3]) : "l"(p) : "memory");
}

__device__ __noinline__ void side_jobs(const __nv_bfloat16* __restrict__ t_emb, const __nv_bfloat16* __restrict__ w_emb,
                                       const __nv_bfloat16* __restrict__ w2, Scratch* __restrict__ gs, unsigned clk0) {
    const int tid = threadIdx.x, warp = tid >> 5, lane = tid & 31, j = blockIdx.x;
    float tv = 0.f;
    if (lane < 24) tv = __bfloat162float(t_emb[(lane / 12) * E + j * 192 + warp * 12 + lane % 12]);
    if (tid == 0) {
        mbar_init(BAR(0), 1);
        mbar_expect(BAR(0), 192 * C * 2);
        fence_async_smem();
        while (clock32() - clk0 < SDELAY) {}
#pragma unroll
        for (int i = 0; i < 4; i++)
            asm volatile("cp.async.bulk.prefetch.L2.global [%0], 18432;" ::"l"(reinterpret_cast<const char*>(w2) + (j * 4 + i) * 18432) : "memory");
#pragma unroll
        for (int i = 0; i < 4; i++) bulk_g2s(S0 + SM_W + i * 12288, w_emb + (j * 192 + i * 48) * C, 12288, S0 + BAR(0));
    }
    if (j == 0 && tid < 32) gs->acc2[(tid >> 4) * LS + (tid & 15)] = 0.f;
    const float sv = silu_half(0.5f * tv);
    __syncthreads();
    mbar_wait(BAR(0), 0);
    float acc[8] = {0.f, 0.f, 0.f, 0.f, 0.f, 0.f, 0.f, 0.f};
#pragma unroll
    for (int i = 0; i < 12; i++) {
        const float2 wq = lds64f(SM_W + (warp * 12 + i) * 256 + lane * 8);
        const uint32_t wx = __float_as_uint(wq.x), wy = __float_as_uint(wq.y);
#pragma unroll
        for (int bb = 0; bb < 2; bb++) {
            const float sx = __shfl_sync(0xffffffffu, sv, bb * 12 + i);
            acc[4 * bb + 0] = fmaf(sx, bf_lo(wx), acc[4 * bb + 0]); acc[4 * bb + 1] = fmaf(sx, bf_hi(wx), acc[4 * bb + 1]);
            acc[4 * bb + 2] = fmaf(sx, bf_lo(wy), acc[4 * bb + 2]); acc[4 * bb + 3] = fmaf(sx, bf_hi(wy), acc[4 * bb + 3]);
        }
    }
    sts128f(SM_ACT + warp * 1024 + lane * 16, make_float4(acc[0], acc[1], acc[2], acc[3]));
    sts128f(SM_ACT + warp * 1024 + 512 + lane * 16, make_float4(acc[4], acc[5], acc[6], acc[7]));
    __syncthreads();
    if (tid < 128) {
        float2 sum = make_float2(0.f, 0.f);
#pragma unroll
        for (int w = 0; w < 16; w++) { const float2 p = lds64f(SM_ACT + w * 1024 + tid * 8); sum.x += p.x; sum.y += p.y; }
        *reinterpret_cast<float2*>(&gs->emb[j * NB * C + tid * 2]) = sum;
        bar_sync(1, 128);
        if (tid < 2) asm volatile("red.release.gpu.global.add.u32 [%0], 1;" ::"l"(&gs->wcnt[(2 * NB + tid) * LS]) : "memory");
    }
}

__global__ void __cluster_dims__(2, 1, 1) __launch_bounds__(NTHREADS, 1)
resblock_kernel(const __nv_bfloat16* __restrict__ w1, const __nv_bfloat16* __restrict__ x,
                const __nv_bfloat16* __restrict__ t_emb, const __nv_bfloat16* __restrict__ g1,
                const __nv_bfloat16* __restrict__ be1, const __nv_bfloat16* __restrict__ w_emb,
                const __nv_bfloat16* __restrict__ g2, const __nv_bfloat16* __restrict__ be2,
                const __nv_bfloat16* __restrict__ w2, __nv_bfloat16* __restrict__ out, Scratch* __restrict__ gs,
                const __grid_constant__ CUtensorMap xmap) {
    const unsigned clk0 = clock32();
    if (threadIdx.x == 480 && blockIdx.x >= NXTRA) TLG(1);
    const int tid = threadIdx.x, lane = tid & 31;
    const int cta = blockIdx.x - NXTRA, b = cta >> 6, r = cta & 63;
    uint4 v[5];
    if (tid < 32) weight_load(v, w1, cta & (NCTA - 1), lane);
    uint4 xv[8];
    const int wg4 = (tid >> 5) - 1;
    const bool early = tid >= 32 && wg4 < NLDG;
    if (early) {
        const char* src = reinterpret_cast<const char*>(x) + (uint32_t)((((b & 1) * C + wg4 * 32 + (lane >> 3)) * HW + r) * HW * 2 + (lane & 7) * 16);
        while (clock32() - clk0 < XDELAY + (wg4 >> 1) * XSTAG + (wg4 & 1) * XSTAG2) {}
#pragma unroll
        for (int i = 0; i < 8; i++) xv[i] = __ldg(reinterpret_cast<const uint4*>(src + i * (4 * HW * HW * 2)));
    }
    const int warp = __shfl_sync(0xffffffffu, tid >> 5, 0);
    if (cta < 0) { side_jobs(t_emb, w_emb, w2, gs, clk0); return; }

    if (warp != 4) asm volatile("barrier.cluster.arrive.relaxed.aligned;" ::: "memory");
    const bool has_outer = (r != 0) && (r != HW - 1);
    if (warp == 1 || warp == 2 || warp == 3 || warp == 5) {
        const int g = warp < 4 ? warp - 1 : 3;
        if (elect_one()) {
            if (g >= NLDG) asm volatile("prefetch.tensormap [%0];" ::"l"(&xmap) : "memory");
            mbar_init(BAR(BAR_X) + 8 * g, 1);
            if (g >= NLDG) mbar_expect(BAR(BAR_X) + 8 * g, 4096);
            fence_async_smem();
        }
        __syncwarp();
        bar_arrive(4, 256 + 32 + 128);
        if (g >= NLDG) {
            while (clock32() - clk0 < XDELAY + (g >> 1) * XSTAG + (g & 1) * XSTAG2) {}
            if (elect_one()) tma_x(SM_XOWN + g * 4096, &xmap, r, b * C + g * 32, BAR(BAR_X) + 8 * g);
            __syncwarp();
            mbar_wait(BAR(BAR_X) + 8 * g, 0);
#pragma unroll
            for (int k = 0; k < 8; k++) xv[k] = lds128(SM_XOWN + g * 4096 + k * 512 + lane * 16);
        }
        float c[8][4];
#pragma unroll
        for (int k = 0; k < 8; k++) {
            c[k][0] = c[k][1] = c[k][2] = c[k][3] = 0.f;
            stat_mma(c[k], xv[k].x, xv[k].y); stat_mma(c[k], xv[k].z, xv[k].w);
        }
#pragma unroll
        for (int i = 0; i < 4; i++) c[0][i] = ((c[0][i] + c[1][i]) + (c[2][i] + c[3][i])) + ((c[4][i] + c[5][i]) + (c[6][i] + c[7][i]));
        stat_store(c[0], SM_RED + g * 48, lane);
        __syncwarp();
        if (lane == 0) {
            const uint32_t a = SM_RED + g * 48;
            red_add4(&gs->acc1[b * LS + g * 4], 1.f, sum4(lds128f(a + 32)), sum4(lds128f(a)) + sum4(lds128f(a + 16)), 1.f);
            TL(74 + g);
        }
        if (g < NLDG) {
#pragma unroll
            for (int i = 0; i < 8; i++)
                sts128(SM_XOWN + g * 4096 + i * 512 + (lane >> 3) * 128 + (((lane & 7) ^ ((lane >> 3) + 4 * (i & 1))) << 4), xv[i]);
            __syncwarp();
            if (lane == 0) mbar_arrive(BAR(BAR_X) + 8 * g);
        }
    }
    if (warp == 4) {
            if (elect_one()) {
#pragma unroll
                for (int i = 0; i < NSTAGE; i++) mbar_init(BAR(BAR_FULL + i), (i >> 3) == 1 ? 1 : 5);
#pragma unroll
                for (int i = 0; i < NS + 2; i++) mbar_init(BAR(BAR_WEMPTY + i), 4);
#pragma unroll
                for (int i = BAR_STATS; i < BAR_X; i++) mbar_init(BAR(i), i == BAR_EMB ? 3 : 1);
                mbar_init(BAR(BAR_X + 4), 1);
                asm volatile("fence.mbarrier_init.release.cluster;" ::: "memory");
            }
            if (lane < 4) sts128(SM_GST + lane * 16, make_uint4(0, 0, 0, 0));
            __syncwarp();
            fence_async_smem();
            bar_arrive(0, 96);
            bar_arrive(5, 64);
            bar_arrive(4, 256 + 32 + 128);
            const uint4 z = make_uint4(0, 0, 0, 0);
#pragma unroll
            for (int i = 0; i < 2; i++) sts128(SM_ACT + (i * 16 + (lane >> 1)) * CH_PITCH + (lane & 1) * 16, z);
            if (lane < 4) sts128(SM_ACT + (2 + (lane >> 1)) * ROW_BYTES + (lane & 1) * 16, z);
            if (lane < 16) sts128(SM_ONES + lane * 16, make_uint4(lane < 8 ? 0x3f803f80u : 0u, 0, 0, 0));
            fence_async_smem();
            bar_arrive(7, 160);
            asm volatile("barrier.cluster.arrive.relaxed.aligned;" ::: "memory");
            if (lane == 0) TL(5);
            while (clock32() - clk0 < W2DELAY) {}
            weight_load(v, w2, cta, lane);
        }
    if (warp == 0 || warp == 4) {
        const int k = warp >> 2;
#pragma unroll
        for (int i = 0; i < 5; i++)
            if (i < 4 || lane < 16) sts128(SM_BNC + k * 2304 + (lane + 32 * i) * 16, v[i]);
        if (lane == 0) TL(k ? 14 : 81);
        __syncwarp();
        weight_block(SM_BNC + k * 2304, gs->wt + k * NSTAGE * STAGE_BYTES, cta, lane, true, gs);
        __syncwarp();
        if (lane == 0) TL(k ? 13 : 4);
        if (lane < 2) asm volatile("red.relaxed.gpu.global.add.u32 [%0], 1;" ::"l"(k ? &gs->wcnt[(NB + lane) * LS] : &gs->w1cnt[(lane * 8 + (cta >> 4)) * KS]) : "memory");
    }

    if (warp >= 8) {
        const int nw = warp - 8;
        if (nw < 2) {
            const uint2 ga = __ldg(reinterpret_cast<const uint2*>(nw ? g2 : g1) + lane), bt = __ldg(reinterpret_cast<const uint2*>(nw ? be2 : be1) + lane);
            sts128f(SM_COEF + nw * 1024 + lane * 32, make_float4(0.5f * bf_lo(ga.x), 0.5f * bf_hi(ga.x), 0.5f * bf_lo(bt.x), 0.5f * bf_hi(bt.x)));
            sts128f(SM_COEF + nw * 1024 + lane * 32 + 16, make_float4(0.5f * bf_lo(ga.y), 0.5f * bf_hi(ga.y), 0.5f * bf_lo(bt.y), 0.5f * bf_hi(bt.y)));
        }
        bar_sync(4, 256 + 32 + 128);
        const int par = nw >> 2, wq = nw & 3;
        const uint32_t act_off = SM_ACT + (par * 2 + (lane >> 4)) * CH_PITCH + (2 + wq * 16 + (lane & 15)) * 16;
        const uint32_t stg_off = (par * 16 + (lane >> 4) * 8 + (lane & 7)) * 128 + (((2 * wq + ((lane >> 3) & 1)) ^ (lane & 7)) << 4);
        const uint32_t cfa = SM_COEF + par * 128 + (lane & 3) * 16;
        const uint32_t fbar = BAR(BAR_FULL) + 8 * par;
        uint4* inbox = gs->box + cta * 1024 + nw * 32 + lane;
#pragma unroll 1
        for (int conv = 0; conv < 2; conv++) {
            uint32_t u[4][4], w[4][4];
            float4 cf[8];
            if (conv == 0) {
#pragma unroll
                for (int i = 0; i < 4; i++) { mbar_wait(BAR(BAR_X + i), 0); ldsm4t(u[i], SM_XOWN + stg_off + i * 4096); }
            } else {
                mbar_wait(BAR(BAR_HW), 0);
#pragma unroll
                for (int i = 0; i < 4; i++) ldsm4(u[i], act_off + i * 2 * KC_BYTES);
            }
#pragma unroll
            for (int i = 0; i < 8; i++) cf[i] = lds128f(cfa + conv * 1024 + (i >> 1) * 256 + (i & 1) * 64);
            const uint32_t gst = SM_GST + conv * 32;
            float gv[8] = {0.f, 0.f, 0.f, 0.f, 0.f, 0.f, 0.f, 0.f};
            group_coefs<0>(gst, gv, cf);
            if (tid == 256) TL(22 + conv * 4);
            if (par) { const unsigned c1 = clock32(); while (clock32() - c1 < PDELAY) {} }
            norm_block<0, 1>(u, cf, act_off, ~0u, fbar, lane);
            if (tid == 256) TL(8 + conv * 8);
            group_coefs<1>(gst, gv, cf);
            norm_block<1, 1>(u, cf, act_off, ~0u, fbar, lane);
            group_coefs<2>(gst, gv, cf);
            norm_unit(u[2], cf[4], cf[5]);
            stsm4(act_off + 4 * KC_BYTES, u[2][0], u[2][1], u[2][2], u[2][3]);
            next_unit<3>(u, cf, gst, gv, act_off, fbar, lane);
            publish(fbar + 48, lane);
            if (tid == 256) TL(84 + conv);
            if (has_outer) {
                mbar_wait(BAR(BAR_X + 4), conv);
                if (conv == 0) {
#pragma unroll
                    for (int i = 0; i < 4; i++) ldsm4t(w[i], SM_XOUT + stg_off + i * 4096);
                } else {
#pragma unroll
                    for (int i = 0; i < 4; i++) {
                        const uint4 q = lds128(SM_XOWN + (tid - 256) * 16 + i * 4096);
                        w[i][0] = q.x; w[i][1] = q.y; w[i][2] = q.z; w[i][3] = q.w;
                    }
                    unsigned it = 0;
                    while (true) {
                        bool ok = true;
#pragma unroll
                        for (int i = 0; i < 16; i++) ok = ok && w[i >> 2][i & 3] != 0;
                        if (__all_sync(0xffffffffu, ok) || ++it > SPIN_LIMIT) break;
#pragma unroll
                        for (int i = 0; i < 4; i++) ld_unit(w[i], inbox + i * 256);
                    }
#pragma unroll
                    for (int i = 0; i < 16; i++) w[i >> 2][i & 3] = ~w[i >> 2][i & 3];
                }
            }
            if (conv == 0) {
                bar_sync(3, 256);
                if (nw == 0) sts128(SM_ACT + 2 * ROW_BYTES + (lane >> 1) * CH_PITCH + (lane & 1) * 16, make_uint4(0, 0, 0, 0));
            }
            if (tid == 256) TL(24 + conv * 4);
            norm_block<0, 2>(w, cf, act_off + 2 * ROW_BYTES, has_outer ? ~0u : 0u, fbar + 128, lane);
            if (tid == 256) TL(88 + conv);
            norm_block<2, 2>(w, cf, act_off + 2 * ROW_BYTES, has_outer ? ~0u : 0u, fbar + 128, lane);
            if (tid == 256) TL(23 + conv * 4);
        }
        if (has_outer) {
            mbar_wait(BAR(BAR_FULL + NSTAGE - 1), 1);
#pragma unroll
            for (int i = 0; i < 4; i++) inbox[i * 256] = make_uint4(0, 0, 0, 0);
        }
        {
            const int oc0 = par * 64 + ((tid & 127) >> 3), seg = lane & 7;
            __nv_bfloat16* dst = out + ((size_t)(b * C + oc0) * HW + r) * HW + seg * 8;
            const uint32_t src = SM_XOWN + oc0 * 128 + ((seg ^ (oc0 & 7)) << 4);
            bar_sync(par ? 1 : 6, 128 + 128);
#pragma unroll
            for (int i = 0; i < 4; i++) *reinterpret_cast<uint4*>(dst + (size_t)i * 16 * HW * HW) = lds128(src + i * 2048);
            if (tid == 384) { TL(20); TLG(21); }
        }
    } else if (warp < 4) {
        const int wq = warp;
        bar_sync(7, 160);

        const uint32_t xbase = SM_XOWN + ((lane >> 4) * 8 + (lane & 7)) * 128 + (((2 * wq + ((lane >> 3) & 1)) ^ (lane & 7)) << 4);
        float d[64];
#pragma unroll
        for (int i = 0; i < 64; i++) d[i] = 0.f;
#pragma unroll 1
        for (int conv = 0; conv < 2; conv++) {
            fence_acc(d);
            mma_stages<0>(d, conv, tid, gs);
            if (conv == 0) {
                asm volatile("wgmma.fence.sync.aligned;" ::: "memory");
                wgmma128<(SM_ONES >> 4) | (8u << 16), (SM_EMB >> 4), 0, 8>(d);
                asm volatile("wgmma.commit_group.sync.aligned;" ::: "memory");
            }
            asm volatile("wgmma.wait_group.sync.aligned 0;" ::: "memory");
            fence_acc(d);
            if (tid == 0) TL(10 + conv * 8);
            if (conv == 1) {
                fence_acc(d);
#pragma unroll
                for (int kc = 0; kc < 8; kc++) {
                    stsm4t(xbase + kc * 2048, pack_bf(d[8 * kc], d[8 * kc + 1]), pack_bf(d[8 * kc + 2], d[8 * kc + 3]),
                           pack_bf(d[8 * kc + 4], d[8 * kc + 5]), pack_bf(d[8 * kc + 6], d[8 * kc + 7]));
                    if (kc == 3) bar_arrive(6, 128 + 128);
                }
                bar_arrive(1, 128 + 128);
                break;
            }
            uint32_t hp[32];
#pragma unroll
            for (int i = 0; i < 32; i++) hp[i] = pack_bf(d[2 * i], d[2 * i + 1]);
#pragma unroll
            for (int g = 0; g < 4; g++) {
                float c[4] = {0.f, 0.f, 0.f, 0.f};
#pragma unroll
                for (int i = 0; i < 4; i++) stat_mma(c, hp[8 * g + 2 * i], hp[8 * g + 2 * i + 1]);
                stat_store(c, SM_RED + (g * 4 + wq) * 48, lane);
            }
            bar_sync(2, 128);
            if (wq == 0) stat_publish(SM_RED, &gs->acc2[b * LS], lane, true);
            if (tid == 0) TL(11);
            const uint32_t hbase = SM_ACT + (lane >> 4) * CH_PITCH + (2 + wq * 16 + (lane & 15)) * 16;
#pragma unroll
            for (int kc = 0; kc < 8; kc++) stsm4(hbase + kc * 2 * CH_PITCH, hp[4 * kc], hp[4 * kc + 1], hp[4 * kc + 2], hp[4 * kc + 3]);
            __syncwarp();
            if (lane == 0) mbar_arrive(BAR(BAR_HW));
            if (lane < LAG) mbar_arrive(BAR(BAR_WEMPTY + (NSTAGE - LAG) % NS) + 8 * lane);
            if (has_outer) {
                uint4* outbox = gs->box + (cta + ((r & 1) ? 1 : -1)) * 1024 + tid;
#pragma unroll
                for (int kc = 0; kc < 8; kc++) outbox[kc * 128] = make_uint4(~hp[4 * kc], ~hp[4 * kc + 1], ~hp[4 * kc + 2], ~hp[4 * kc + 3]);
            }
            if (tid == 0) TL(12);
#pragma unroll
            for (int kc = 0; kc < 8; kc++) {
                uint32_t p[4];
                ldsm4t(p, xbase + kc * 2048);
#pragma unroll
                for (int i = 0; i < 4; i++) { d[8 * kc + 2 * i] = bf_lo(p[i]); d[8 * kc + 2 * i + 1] = bf_hi(p[i]); }
            }
            fence_async_smem();
            __syncwarp();
            if (lane == 0) mbar_arrive(BAR(BAR_XFREE));
        }
        {
        }
    } else if (warp < 6) {
        if (warp == 5) {
            bar_sync(5, 64);
            mbar_wait(BAR(BAR_FULL + OAFTER), 0);
            if (has_outer && elect_one()) {
                mbar_expect(BAR(BAR_X + 4), 16384);
#pragma unroll
                for (int i = 0; i < 4; i++) tma_x(SM_XOUT + i * 4096, &xmap, r + ((r & 1) ? 1 : -1), b * C + i * 32, BAR(BAR_X + 4));
            }
            __syncwarp();
            asm volatile("barrier.cluster.wait.acquire.aligned;" ::: "memory");
            const uint32_t peer = (r & 1) ^ 1;
            const uint32_t self0 = mapa(0, r & 1), peer0 = mapa(0, peer);
#pragma unroll 1
            for (int conv = 0; conv < 2; conv++) {
#pragma unroll 1
                for (int kc = 0; kc < 8; kc++) {
                    mbar_wait(BAR(BAR_FULL) + 8 * kc, conv);
                    if (elect_one())
                        asm volatile("cp.async.bulk.shared::cluster.shared::cta.mbarrier::complete_tx::bytes [%0], [%1], %2, [%3];"
                                     ::"r"(peer0 + SM_ACT + ROW_BYTES + kc * KC_BYTES), "r"(self0 + SM_ACT + kc * KC_BYTES), "r"(KC_BYTES),
                                       "r"(peer0 + BAR(BAR_FULL + 8) + 8 * kc) : "memory");
                }
                if (lane == 0) TL(86 + conv);
#pragma unroll 1
                for (int kc = 0; kc < 8; kc++) mbar_wait(BAR(BAR_FULL + 8) + 8 * kc, conv);
                if (lane == 0)
                    asm volatile("mbarrier.arrive.relaxed.cluster.shared::cluster.b64 _, [%0];" ::"r"(peer0 + (conv ? BAR(BAR_ACK) : BAR(BAR_EMB))) : "memory");
            }
            mbar_wait(BAR(BAR_ACK), 0);
        } else {
            mbar_wait(BAR(BAR_STATS), 0);
            unsigned it = 0;
            while (ld_relaxed(&gs->wcnt[(2 * NB + b) * LS]) < (unsigned)NXTRA && ++it < SPIN_LIMIT) __nanosleep(100);
            fence_acquire();
            float ev[4] = {0.f, 0.f, 0.f, 0.f};
#pragma unroll
            for (int j = 0; j < NXTRA; j++) {
                const uint4 ef = ld_relaxed_v4(&gs->emb[(j * NB + b) * C + lane * 4]);
                ev[0] += __uint_as_float(ef.x); ev[1] += __uint_as_float(ef.y); ev[2] += __uint_as_float(ef.z); ev[3] += __uint_as_float(ef.w);
            }
#pragma unroll
            for (int i = 0; i < 4; i++) {
                const float hi = bf_lo(pack_bf(ev[i], 0.f));
                sts128(SM_EMB + (lane * 4 + i) * 16, make_uint4(pack_bf(hi, ev[i] - hi), 0, 0, 0));
            }
            fence_async_smem();
            __syncwarp();
            if (lane == 0) { mbar_arrive(BAR(BAR_EMB)); TL(19); }
        }
    } else if (warp == 6) {
        bar_sync(0, 96);
        const uint32_t ebytes = STAGE_BYTES + ((lane >> 3) == 1 ? KC_BYTES : 0);
        if (lane < NSTAGE) mbar_expect(BAR(BAR_FULL) + 8 * lane, ebytes);
        const int swap = (r & 1) ? 0 : 8 * STAGE_BYTES;
        unsigned it = 0;
        {
            int g = 0;
            const unsigned* cnt = &gs->w1cnt[(b * 8 + (lane & 7)) * KS];
            unsigned cv = ld_relaxed(cnt);
#pragma unroll 1
            while (g < NS) {
                unsigned ready = __ballot_sync(0xffffffffu, cv >= 16u);
                if (ready != ~0u) cv = ld_relaxed(cnt);
                ready >>= g;
                if (++it > SPIN_LIMIT) ready = ~0u;
                if (!(ready & 1)) continue;
                fence_async_global();
                if (lane == 0) TL(g ? 3 : 6);
#pragma unroll 1
                for (; (ready & 1) && g < NS; g++, ready >>= 1)
                    if (elect_one())
                        bulk_g2s(S0 + SM_W + g * STAGE_BYTES, gs->wt + g * STAGE_BYTES + (g >= 8 ? swap : 0), STAGE_BYTES, S0 + BAR(BAR_FULL) + 8 * g);
            }
        }
#pragma unroll 1
        for (int q = 3; q < 12; q++) {
            const int conv = q >= 6, qs = conv ? q - 6 : q, sl = q % 3;
            const unsigned char* wsrc = gs->wt + q * 4 * STAGE_BYTES + (qs < 2 ? 0 : (qs < 4 ? swap : -swap));
            const uint32_t par = (q / 3 - 1) & 1;
            if (q == 6) {
                it = 0;
                while (ld_relaxed(&gs->wcnt[(NB + b) * LS]) < (unsigned)NCTA && ++it < SPIN_LIMIT) {}
                fence_acquire();
                fence_async_global();
                if (lane == 0) { mbar_arrive(BAR(BAR_EMB)); TL(2); }
            }
#pragma unroll
            for (int i = 0; i < 4; i++) {
                mbar_wait(BAR(BAR_WEMPTY + i) + 32 * sl, par);
                if (i == 0 && (q == 6 || q == 9)) {
                    if ((lane >= NS) == (q == 9) && lane < NSTAGE) mbar_expect(BAR(BAR_FULL) + 8 * lane, ebytes);
                    __syncwarp();
                }
                if (elect_one())
                    bulk_g2s(S0 + SM_W + (sl * 4 + i) * STAGE_BYTES, wsrc + i * STAGE_BYTES, STAGE_BYTES, S0 + BAR(BAR_FULL + i) + 32 * qs);
            }
        }
    } else {
        bar_sync(0, 96);
#pragma unroll 1
        for (int conv = 0; conv < 2; conv++) {
            if (conv == 1) mbar_wait(BAR(BAR_HW), 0);
            const float* asrc = (conv ? gs->acc2 : gs->acc1) + b * LS + (lane & 3) * 4;
            unsigned it = 0;
#pragma unroll 1
            while (true) {
                const uint4 f = ld_relaxed_v4(asrc);
                const bool ok = ((f.x == 0x42800000u) & (f.w == 0x42800000u)) || ++it > SPIN_LIMIT;
                if (ok && lane < 4) {
                    const float inv_n = 1.0f / (32.0f * HW * HW);
                    const float mean = __uint_as_float(f.y) * inv_n;
                    float rs;
                    asm("rsqrt.approx.ftz.f32 %0, %1;" : "=f"(rs) : "f"(fmaxf(fmaf(-mean, mean, __uint_as_float(f.z) * inv_n), 0.f) + 1e-5f));
                    asm volatile("st.shared.v2.f32 [%0], {%1,%2};" ::"r"(S0 + SM_GST + conv * 32 + lane * 8), "f"(rs == 0.f ? 1e-38f : rs), "f"(mean * rs) : "memory");
                }
                if (__all_sync(0xffffffffu, ok)) break;
            }
            if (lane == 0) { mbar_arrive(BAR(BAR_STATS)); TL(7 + conv * 8); }
        }
        mbar_wait(BAR(BAR_XFREE), 0);
        if (has_outer && elect_one()) {
            mbar_expect(BAR(BAR_X + 4), 16384);
            bulk_g2s(S0 + SM_XOWN, gs->box + cta * 1024, 16384, S0 + BAR(BAR_X + 4));
        }
        if (r == 0) {
            if (lane < 16) gs->acc1[b * LS + lane] = 0.f;
            if (lane < 3) gs->wcnt[(lane * NB + b) * LS] = 0;
            if (lane < 8) gs->w1cnt[(b * 8 + lane) * KS] = 0;
        }
    }
}

}

extern "C" void kernel_launch(void* const* d_in, const int* in_sizes, int n_in, void* d_out, int out_size) {
    (void)in_sizes; (void)n_in; (void)out_size;
    typedef CUresult (*EncodeFn)(CUtensorMap*, CUtensorMapDataType, cuuint32_t, void*, const cuuint64_t*, const cuuint64_t*,
                                 const cuuint32_t*, const cuuint32_t*, CUtensorMapInterleave, CUtensorMapSwizzle,
                                 CUtensorMapL2promotion, CUtensorMapFloatOOBfill);
    static Scratch* gs = nullptr;
    static EncodeFn encode = nullptr;
    if (!gs) {
        cudaFuncSetAttribute(resblock_kernel, cudaFuncAttributeMaxDynamicSharedMemorySize, SM_TOTAL);
        cudaGetSymbolAddress((void**)&gs, g_scratch);
        cudaDriverEntryPointQueryResult qr;
        cudaGetDriverEntryPoint("cuTensorMapEncodeTiled", (void**)&encode, cudaEnableDefault, &qr);
    }
    CUtensorMap xmap;
    const cuuint64_t dims[3] = {HW, HW, NB * C}, strides[2] = {HW * 2, HW * HW * 2};
    const cuuint32_t box[3] = {HW, 1, 32}, es[3] = {1, 1, 1};
    encode(&xmap, CU_TENSOR_MAP_DATA_TYPE_BFLOAT16, 3, d_in[0], dims, strides, box, es, CU_TENSOR_MAP_INTERLEAVE_NONE,
           CU_TENSOR_MAP_SWIZZLE_128B, CU_TENSOR_MAP_L2_PROMOTION_NONE, CU_TENSOR_MAP_FLOAT_OOB_FILL_NONE);
    resblock_kernel<<<NCTA + NXTRA, NTHREADS, SM_TOTAL>>>(
        (const __nv_bfloat16*)d_in[4], (const __nv_bfloat16*)d_in[0], (const __nv_bfloat16*)d_in[1],
        (const __nv_bfloat16*)d_in[2], (const __nv_bfloat16*)d_in[3], (const __nv_bfloat16*)d_in[5],
        (const __nv_bfloat16*)d_in[6], (const __nv_bfloat16*)d_in[7], (const __nv_bfloat16*)d_in[8],
        (__nv_bfloat16*)d_out, gs, xmap);
}
```

```cpp
#include <cuda_runtime.h>
#include <cuda.h>
#include <cuda_bf16.h>
#include <stdint.h>

namespace {

constexpr int C = 128, HW = 64, NB = 2, E = 768;
constexpr int NCTA = NB * HW;
constexpr int NXTRA = 4;
constexpr int NTHREADS = 16 * 32;
constexpr int CH_PITCH = 66 * 16;
constexpr int ROW_BYTES = 16 * CH_PITCH;
constexpr int STEP_BYTES = 4096;
constexpr int STAGE_BYTES = 3 * STEP_BYTES;
constexpr int NSTAGE = 24;
constexpr int KC_BYTES = 2 * CH_PITCH;
constexpr int NS = 12;
constexpr int LAG = 1;
#define XDELAY 400
#define HDELAY 600
#define SEQ 1
#define MMA0_WAIT mbar_try
#define NPOLL 1
#define PD2 0
#define ODELAY 100
#define NLDG 2
#define PSTAG -1
#define PDELAY0 400
#define PDELAY 60
#define RB 1
#define XSTAG2 400
#define XSTAG 800
#define HSEND 0
#define SDELAY 600
#define OAFTER 0
#define W2DELAY 2400

constexpr uint32_t SMEM_BASE = 0x400;
constexpr uint32_t SM_XOWN = SMEM_BASE;
constexpr uint32_t SM_ACT = SM_XOWN + 16384 + 512;
constexpr uint32_t SM_XOUT = SM_ACT + 2 * ROW_BYTES + 512;
static_assert(SM_XOUT % 1024 == 0, "swizzle atom alignment");
constexpr uint32_t SM_W = SM_ACT + 3 * ROW_BYTES + 128;
__host__ __device__ constexpr uint32_t slot_addr(int slot) { return SM_W + slot * STAGE_BYTES; }
constexpr uint32_t SM_COEF = SM_W + NS * STAGE_BYTES;
constexpr uint32_t SM_GST = SM_COEF + 2048;
constexpr uint32_t SM_EMB = SM_GST + 128;
constexpr uint32_t SM_ONES = SM_EMB + 2048;
constexpr uint32_t SM_RED = SM_ONES + 256;
constexpr uint32_t SM_BNC = SM_RED + 1536;
constexpr uint32_t SM_BAR = SM_BNC + 2 * 2304;
constexpr int BAR_FULL = 0, BAR_WEMPTY = NSTAGE, BAR_HW = BAR_WEMPTY + NS, BAR_XFREE = BAR_HW + 1, BAR_STATS = BAR_XFREE + 1,
              BAR_EMB = BAR_STATS + 1, BAR_ACK = BAR_EMB + 1, BAR_X = BAR_ACK + 1  , NBAR = BAR_X + 5;
constexpr int SM_TOTAL = SM_BAR + NBAR * 8 - SMEM_BASE;
static_assert(SM_TOTAL <= 232448, "smem");
static_assert(NBAR <= 96, "barrier init");
__host__ __device__ constexpr uint32_t BAR(int i) { return SM_BAR + 8 * i; }
__host__ __device__ constexpr int ky_of(int kyo) { return kyo == 0 ? 1 : (kyo == 1 ? 0 : 2); }

constexpr unsigned SPIN_LIMIT = 1u << 16;

#define LS 1056
#define GS1 4
#define PD 0
#define DRY 1
#define KS 32
struct Scratch {
    float acc1[NB * LS];
    float acc2[NB * LS];
    unsigned wcnt[3 * NB * LS];
    unsigned w1cnt[NB * 8 * KS];
    float emb[NXTRA * NB * C];
    alignas(1024) unsigned char wt[2 * NSTAGE * STAGE_BYTES];
    uint4 box[NCTA * 1024];
};
__device__ __align__(1024) Scratch g_scratch;
#define TL(i) do {} while (0)
#define TLG(i) do {} while (0)

__device__ __forceinline__ unsigned clock32() { unsigned c; asm volatile("mov.u32 %0, %%clock;" : "=r"(c)); return c; }
__device__ __forceinline__ uint32_t mapa(uint32_t a, uint32_t rank) {
    uint32_t d;
    asm("mapa.shared::cluster.u32 %0, %1, %2;" : "=r"(d) : "r"(a), "r"(rank));
    return d;
}
#define S0 mapa(0, blockIdx.x & 1)
__device__ __forceinline__ void mbar_init(uint32_t bar, int cnt) {
    asm volatile("mbarrier.init.shared::cta.b64 [%0], %1;" ::"r"(bar + S0), "r"(cnt) : "memory");
}
__device__ __forceinline__ void mbar_arrive(uint32_t bar) {
    asm volatile("mbarrier.arrive.shared::cta.b64 _, [%0];" ::"r"(bar + S0) : "memory");
}
__device__ __forceinline__ void mbar_expect(uint32_t bar, uint32_t bytes) {
    asm volatile("mbarrier.arrive.expect_tx.shared::cta.b64 _, [%0], %1;" ::"r"(bar + S0), "r"(bytes) : "memory");
}
__device__ __forceinline__ bool mbar_try(uint32_t bar, uint32_t par) {
    uint32_t ok;
    asm volatile("{\n.reg .pred p;\nmbarrier.try_wait.parity.shared::cta.b64 p, [%1], %2;\nselp.u32 %0, 1, 0, p;\n}"
                 : "=r"(ok) : "r"(bar + S0), "r"(par) : "memory");
    return ok;
}
__device__ __forceinline__ bool mbar_test(uint32_t bar, uint32_t par) {
    uint32_t ok;
    asm volatile("{\n.reg .pred p;\nmbarrier.test_wait.parity.shared::cta.b64 p, [%1], %2;\nselp.u32 %0, 1, 0, p;\n}"
                 : "=r"(ok) : "r"(bar + S0), "r"(par) : "memory");
    return ok;
}
__device__ __forceinline__ void mbar_wait(uint32_t bar, uint32_t par) {
    unsigned it = 0;
#pragma unroll 1
    while (!mbar_try(bar, par) && ++it < SPIN_LIMIT) {}
}
__device__ __forceinline__ bool elect_one() {
    uint32_t p;
    asm volatile("{\n.reg .pred p;\nelect.sync _|p, 0xffffffff;\nselp.u32 %0, 1, 0, p;\n}" : "=r"(p));
    return p;
}
__device__ __forceinline__ void fence_async_smem() { asm volatile("fence.proxy.async.shared::cta;" ::: "memory"); }
__device__ __forceinline__ void fence_async_global() { asm volatile("fence.proxy.async.global;" ::: "memory"); }
__device__ __forceinline__ void fence_acquire() { asm volatile("fence.acquire.gpu;" ::: "memory"); }
__device__ __forceinline__ void bar_sync(int id, int n) { asm volatile("bar.sync %0, %1;" ::"r"(id), "r"(n) : "memory"); }
__device__ __forceinline__ void bar_arrive(int id, int n) { asm volatile("bar.arrive %0, %1;" ::"r"(id), "r"(n) : "memory"); }
__device__ __forceinline__ void bulk_g2s(uint32_t dst, const void* src, uint32_t bytes, uint32_t bar) {
    asm volatile("cp.async.bulk.shared::cluster.global.mbarrier::complete_tx::bytes [%0], [%1], %2, [%3];"
                 ::"r"(dst), "l"(src), "r"(bytes), "r"(bar) : "memory");
}
__device__ __forceinline__ void tma_x(uint32_t dst, const CUtensorMap* tm, int row, int ch, uint32_t bar) {
    asm volatile("cp.async.bulk.tensor.3d.shared::cluster.global.mbarrier::complete_tx::bytes [%0], [%1, {%2, %3, %4}], [%5];"
                 ::"r"(dst + S0), "l"(tm), "r"(0), "r"(row), "r"(ch), "r"(bar + S0) : "memory");
}
__device__ __forceinline__ uint4 ld_relaxed_v4(const void* p) {
    uint4 v;
    asm volatile("ld.relaxed.gpu.global.v4.u32 {%0,%1,%2,%3}, [%4];" : "=r"(v.x), "=r"(v.y), "=r"(v.z), "=r"(v.w) : "l"(p) : "memory");
    return v;
}
__device__ __forceinline__ unsigned ld_relaxed(const void* p) {
    unsigned v;
    asm volatile("ld.relaxed.gpu.global.u32 %0, [%1];" : "=r"(v) : "l"(p) : "memory");
    return v;
}
__device__ __forceinline__ void red_add4(float* p, float a, float b, float c, float d) {
    asm volatile("red.relaxed.gpu.global.add.v4.f32 [%0], {%1,%2,%3,%4};" ::"l"(p), "f"(a), "f"(b), "f"(c), "f"(d) : "memory");
}
__device__ __forceinline__ void sts128(uint32_t a, uint4 v) {
    asm volatile("st.shared.v4.u32 [%0], {%1,%2,%3,%4};" ::"r"(a + S0), "r"(v.x), "r"(v.y), "r"(v.z), "r"(v.w) : "memory");
}
__device__ __forceinline__ void sts128f(uint32_t a, float4 v) {
    asm volatile("st.shared.v4.f32 [%0], {%1,%2,%3,%4};" ::"r"(a + S0), "f"(v.x), "f"(v.y), "f"(v.z), "f"(v.w) : "memory");
}
__device__ __forceinline__ void sts32f(uint32_t a, float v) { asm volatile("st.shared.f32 [%0], %1;" ::"r"(a + S0), "f"(v) : "memory"); }
__device__ __forceinline__ uint4 lds128(uint32_t a) {
    uint4 v;
    asm volatile("ld.shared.v4.u32 {%0,%1,%2,%3}, [%4];" : "=r"(v.x), "=r"(v.y), "=r"(v.z), "=r"(v.w) : "r"(a + S0) : "memory");
    return v;
}
__device__ __forceinline__ float4 lds128f(uint32_t a) {
    float4 v;
    asm volatile("ld.shared.v4.f32 {%0,%1,%2,%3}, [%4];" : "=f"(v.x), "=f"(v.y), "=f"(v.z), "=f"(v.w) : "r"(a + S0) : "memory");
    return v;
}
__device__ __forceinline__ float2 lds64f(uint32_t a) {
    float2 v;
    asm volatile("ld.shared.v2.f32 {%0,%1}, [%2];" : "=f"(v.x), "=f"(v.y) : "r"(a + S0) : "memory");
    return v;
}
__device__ __forceinline__ float bf_lo(uint32_t u) { return __uint_as_float(u << 16); }
__device__ __forceinline__ float bf_hi(uint32_t u) { return __uint_as_float(u & 0xffff0000u); }
__device__ __forceinline__ uint32_t pack_bf(float lo, float hi) {
    uint32_t r;
    asm("cvt.rn.bf16x2.f32 %0, %1, %2;" : "=r"(r) : "f"(hi), "f"(lo));
    return r;
}
__device__ __forceinline__ float tanh_fast(float x) {
    float r;
    asm("tanh.approx.f32 %0, %1;" : "=f"(r) : "f"(x));
    return r;
}
__device__ __forceinline__ float silu_half(float h) { return fmaf(h, tanh_fast(h), h); }
__device__ __forceinline__ void ldsm4(uint32_t (&u)[4], uint32_t a) {
    asm volatile("ldmatrix.sync.aligned.m8n8.x4.shared.b16 {%0,%1,%2,%3}, [%4];"
                 : "=r"(u[0]), "=r"(u[1]), "=r"(u[2]), "=r"(u[3]) : "r"(a + S0) : "memory");
}
__device__ __forceinline__ void ldsm4t(uint32_t (&u)[4], uint32_t a) {
    asm volatile("ldmatrix.sync.aligned.m8n8.x4.trans.shared.b16 {%0,%1,%2,%3}, [%4];"
                 : "=r"(u[0]), "=r"(u[1]), "=r"(u[2]), "=r"(u[3]) : "r"(a + S0) : "memory");
}
__device__ __forceinline__ void stsm4(uint32_t a, uint32_t p0, uint32_t p1, uint32_t p2, uint32_t p3) {
    asm volatile("stmatrix.sync.aligned.m8n8.x4.shared.b16 [%0], {%1,%2,%3,%4};" ::"r"(a + S0), "r"(p0), "r"(p1), "r"(p2), "r"(p3) : "memory");
}
__device__ __forceinline__ void stsm4t(uint32_t a, uint32_t p0, uint32_t p1, uint32_t p2, uint32_t p3) {
    asm volatile("stmatrix.sync.aligned.m8n8.x4.trans.shared.b16 [%0], {%1,%2,%3,%4};" ::"r"(a + S0), "r"(p0), "r"(p1), "r"(p2), "r"(p3) : "memory");
}

#define R8(o) "+f"(d[o]), "+f"(d[o + 1]), "+f"(d[o + 2]), "+f"(d[o + 3]), "+f"(d[o + 4]), "+f"(d[o + 5]), "+f"(d[o + 6]), "+f"(d[o + 7])
template <uint32_t ALO, uint32_t BLO, uint64_t AHI = 8, uint64_t BHI = 48>
__device__ __forceinline__ void wgmma128(float (&d)[64]) {
    asm volatile(
        "wgmma.mma_async.sync.aligned.m64n128k16.f32.bf16.bf16 "
        "{%0,%1,%2,%3,%4,%5,%6,%7,%8,%9,%10,%11,%12,%13,%14,%15,%16,%17,%18,%19,%20,%21,%22,%23,%24,%25,%26,%27,%28,%29,%30,%31,"
        "%32,%33,%34,%35,%36,%37,%38,%39,%40,%41,%42,%43,%44,%45,%46,%47,%48,%49,%50,%51,%52,%53,%54,%55,%56,%57,%58,%59,%60,%61,%62,%63},"
        " %64, %65, 1, 1, 1, 0, 0;"
        : R8(0), R8(8), R8(16), R8(24), R8(32), R8(40), R8(48), R8(56)
        : "l"((AHI << 32) | ALO), "l"((BHI << 32) | BLO));
}
template <int S>
__device__ __forceinline__ void mma_stages(float (&d)[64], int conv, int tid, Scratch* gs) {
    constexpr uint32_t A = ((SM_ACT + S * 2 * CH_PITCH + 16) >> 4) | ((CH_PITCH >> 4) << 16);
    constexpr uint32_t B = (slot_addr(S % NS) >> 4) | (8u << 16);
    if (S == 0) {
        unsigned it = 0;
#pragma unroll 1
        while (!MMA0_WAIT(BAR(BAR_FULL), conv) && ++it < SPIN_LIMIT) {}
    }
    bool next_ok = true;
    constexpr uint32_t NEXT = S + 1 < NSTAGE ? BAR(BAR_FULL + S + 1) : BAR(BAR_EMB);
    const int npar = S + 1 < NSTAGE ? conv : 0;
    next_ok = mbar_test(NEXT, npar);
    if (S == 0 && tid == 0) TL(32 + conv * 24);
    asm volatile("wgmma.fence.sync.aligned;" ::: "memory");
    wgmma128<A, B>(d);
    wgmma128<A + 1, B + 16>(d);
    wgmma128<A + 2, B + 32>(d);
    asm volatile("wgmma.commit_group.sync.aligned;" ::: "memory");
    if (S >= LAG) {
        asm volatile("wgmma.wait_group.sync.aligned %0;" ::"n"(LAG) : "memory");
        if ((tid & 31) == 0) mbar_arrive(BAR(BAR_WEMPTY + (S + NS - LAG) % NS));
    }
    if (!next_ok) mbar_wait(NEXT, npar);
    if constexpr (S + 1 < NSTAGE) mma_stages<S + 1>(d, conv, tid, gs);
}

__device__ __forceinline__ void weight_load(uint4 (&t)[5], const __nv_bfloat16* w, int cta, int lane) {
    const char* base = reinterpret_cast<const char*>(w) + ((cta & 15) * 8 * C + (cta >> 4) * 16) * 18;
#pragma unroll
    for (int k = 0; k < 5; k++) {
        const int i = lane + 32 * k, row = (i * 57) >> 10;
        if (k < 4 || lane < 16) t[k] = __ldg(reinterpret_cast<const uint4*>(base + row * (C * 18 - 288) + i * 16));
    }
}
__device__ __forceinline__ void weight_block(uint32_t bounce, unsigned char* wt, int cta, int lane, bool readback, Scratch* gs) {
    unsigned char* dst = wt + (cta >> 4) * STAGE_BYTES + (cta & 15) * 768;
    if (lane < 16) {
        uint32_t v[36];
#pragma unroll
        for (int i = 0; i < 9; i++) {
            const uint4 q = lds128(bounce + (lane & 7) * 288 + (lane >> 3) * 144 + i * 16);
            v[4 * i] = q.x; v[4 * i + 1] = q.y; v[4 * i + 2] = q.z; v[4 * i + 3] = q.w;
        }
#pragma unroll
        for (int kyo = 0; kyo < 3; kyo++) {
#pragma unroll
            for (int kx = 0; kx < 3; kx++) {
                const int tap = ky_of(kyo) * 3 + kx;
                uint32_t o[4];
#pragma unroll
                for (int m = 0; m < 4; m++) {
                    const int i0 = 18 * m + tap, i1 = i0 + 9;
                    const uint32_t sel = ((i0 & 1) ? 0x32u : 0x10u) | ((i1 & 1) ? 0x7600u : 0x5400u);
                    o[m] = __byte_perm(v[i0 >> 1], v[i1 >> 1], sel);
                }
                *reinterpret_cast<uint4*>(dst + kyo * 8 * STAGE_BYTES + kx * 256 + lane * 16) = make_uint4(o[0], o[1], o[2], o[3]);
            }
        }
    }
    if (readback) {
        __syncwarp();
        unsigned acc = 0;
        if (lane < 24) {
#pragma unroll
            for (int i = 0; i < 3; i++) acc |= ld_relaxed(dst + i * 8 * STAGE_BYTES + lane * 32);
        }
        asm volatile("{\n.reg .pred p;\nsetp.eq.u32 p, %0, 0x9e3779b9;\n@p st.shared.u32 [%1], %0;\n}" ::"r"(acc), "r"(bounce + S0) : "memory");
    }
}
__device__ __forceinline__ uint32_t act2(uint32_t u, const float4& cf) {
    return pack_bf(silu_half(fmaf(bf_lo(u), cf.x, cf.z)), silu_half(fmaf(bf_hi(u), cf.y, cf.w)));
}
__device__ __forceinline__ void norm_unit(uint32_t (&u)[4], const float4& ca, const float4& cb) {
    u[0] = act2(u[0], ca); u[1] = act2(u[1], ca); u[2] = act2(u[2], cb); u[3] = act2(u[3], cb);
}
__device__ __forceinline__ void read_stats(uint32_t gst, float (&g)[8]) {
    asm volatile("ld.volatile.shared.v4.f32 {%0,%1,%2,%3}, [%4];" : "=f"(g[0]), "=f"(g[1]), "=f"(g[2]), "=f"(g[3]) : "r"(gst + S0) : "memory");
    asm volatile("ld.volatile.shared.v4.f32 {%0,%1,%2,%3}, [%4];" : "=f"(g[4]), "=f"(g[5]), "=f"(g[6]), "=f"(g[7]) : "r"(gst + 16 + S0) : "memory");
}
template <int T>
__device__ __forceinline__ void group_coefs(uint32_t gst, float (&g)[8], float4 (&cf)[8]) {
    float rs = g[2 * T], mr = g[2 * T + 1];
    if (!__all_sync(0xffffffffu, rs != 0.f)) {
        unsigned it = 0;
#pragma unroll 1
        do {
            asm volatile("ld.volatile.shared.v2.f32 {%0,%1}, [%2];" : "=f"(rs), "=f"(mr) : "r"(gst + 8 * T + S0) : "memory");
        } while (!__all_sync(0xffffffffu, rs != 0.f) && ++it < 8 * SPIN_LIMIT);
        if (T < 3) read_stats(gst, g);
    }
    float4 &ca = cf[2 * T], &cb = cf[2 * T + 1];
    ca.z = fmaf(-mr, ca.x, ca.z); ca.w = fmaf(-mr, ca.y, ca.w); ca.x *= rs; ca.y *= rs;
    cb.z = fmaf(-mr, cb.x, cb.z); cb.w = fmaf(-mr, cb.y, cb.w); cb.x *= rs; cb.y *= rs;
}
template <int FIRST, int N>
__device__ __forceinline__ void norm_block(uint32_t (&u)[4][4], float4 (&cf)[8], uint32_t act, uint32_t mask, uint32_t fbar, int lane) {
#pragma unroll
    for (int t = FIRST; t < FIRST + N; t++) {
        norm_unit(u[t], cf[2 * t], cf[2 * t + 1]);
        stsm4(act + t * 2 * KC_BYTES, u[t][0] & mask, u[t][1] & mask, u[t][2] & mask, u[t][3] & mask);
    }
    fence_async_smem();
    __syncwarp();
    if (lane < N) mbar_arrive(fbar + 16 * (FIRST + lane));
}
__device__ __forceinline__ void publish(uint32_t bar, int lane) {
    fence_async_smem();
    __syncwarp();
    if (lane == 0) mbar_arrive(bar);
}
template <int T>
__device__ __forceinline__ void next_unit(uint32_t (&u)[4][4], float4 (&cf)[8], uint32_t gst, float (&g)[8], uint32_t act, uint32_t fbar, int lane) {
    const bool have = __all_sync(0xffffffffu, g[2 * T] != 0.f);
    if (!have) publish(fbar + 16 * (T - 1), lane);
    group_coefs<T>(gst, g, cf);
    norm_unit(u[T], cf[2 * T], cf[2 * T + 1]);
    if (have) publish(fbar + 16 * (T - 1), lane);
    stsm4(act + T * 2 * KC_BYTES, u[T][0], u[T][1], u[T][2], u[T][3]);
}
__device__ __forceinline__ void stat_mma(float (&c)[4], uint32_t p, uint32_t q) {
    asm("mma.sync.aligned.m16n8k16.row.col.f32.bf16.bf16.f32 {%0,%1,%2,%3}, {%4,%5,%6,%5}, {%4,%6}, {%0,%1,%2,%3};"
        : "+f"(c[0]), "+f"(c[1]), "+f"(c[2]), "+f"(c[3]) : "r"(p), "r"(0x3f803f80u), "r"(q));
}
__device__ __forceinline__ void stat_store(const float (&c)[4], uint32_t dst, int lane) {
    const int g = lane >> 2, t = lane & 3;
    if (t == (g >> 1)) sts32f(dst + g * 4, (g & 1) ? c[1] : c[0]);
    if (g == 7) sts32f(dst + 32 + t * 4, c[2] + c[3]);
}
__device__ __forceinline__ float sum4(float4 v) { return (v.x + v.y) + (v.z + v.w); }
__device__ __forceinline__ void stat_publish(uint32_t src, float* acc, int lane, bool real) {
    const uint32_t a = src + (lane & 15) * 48;
    float q = sum4(lds128f(a)) + sum4(lds128f(a + 16)), sm = sum4(lds128f(a + 32));
    q += __shfl_xor_sync(0xffffffffu, q, 1); sm += __shfl_xor_sync(0xffffffffu, sm, 1);
    q += __shfl_xor_sync(0xffffffffu, q, 2); sm += __shfl_xor_sync(0xffffffffu, sm, 2);
    if (real && (lane & 19) == 0) red_add4(acc + lane, 1.f, sm, q, 1.f);
}
__device__ __forceinline__ void fence_acc(float (&d)[64]) {
#pragma unroll
    for (int i = 0; i < 64; i++) asm volatile("" : "+f"(d[i])::"memory");
}
__device__ __forceinline__ void ld_unit(uint32_t (&u)[4], const uint4* p) {
    asm volatile("ld.relaxed.gpu.global.v4.u32 {%0,%1,%2,%3}, [%4];" : "=r"(u[0]), "=r"(u[1]), "=r"(u[2]), "=r"(u[3]) : "l"(p) : "memory");
}

__device__ __noinline__ void side_jobs(const __nv_bfloat16* __restrict__ t_emb, const __nv_bfloat16* __restrict__ w_emb,
                                       const __nv_bfloat16* __restrict__ w2, Scratch* __restrict__ gs, unsigned clk0) {
    const int tid = threadIdx.x, warp = tid >> 5, lane = tid & 31, j = blockIdx.x;
    float tv = 0.f;
    if (lane < 24) tv = __bfloat162float(t_emb[(lane / 12) * E + j * 192 + warp * 12 + lane % 12]);
    if (tid == 0) {
        mbar_init(BAR(0), 1);
        mbar_expect(BAR(0), 192 * C * 2);
        fence_async_smem();
        while (clock32() - clk0 < SDELAY) {}
#pragma unroll
        for (int i = 0; i < 4; i++)
            asm volatile("cp.async.bulk.prefetch.L2.global [%0], 18432;" ::"l"(reinterpret_cast<const char*>(w2) + (j * 4 + i) * 18432) : "memory");
#pragma unroll
        for (int i = 0; i < 4; i++) bulk_g2s(S0 + SM_W + i * 12288, w_emb + (j * 192 + i * 48) * C, 12288, S0 + BAR(0));
    }
    if (j == 0 && tid < 32) gs->acc2[(tid >> 4) * LS + (tid & 15)] = 0.f;
    const float sv = silu_half(0.5f * tv);
    __syncthreads();
    mbar_wait(BAR(0), 0);
    float acc[8] = {0.f, 0.f, 0.f, 0.f, 0.f, 0.f, 0.f, 0.f};
#pragma unroll
    for (int i = 0; i < 12; i++) {
        const float2 wq = lds64f(SM_W + (warp * 12 + i) * 256 + lane * 8);
        const uint32_t wx = __float_as_uint(wq.x), wy = __float_as_uint(wq.y);
#pragma unroll
        for (int bb = 0; bb < 2; bb++) {
            const float sx = __shfl_sync(0xffffffffu, sv, bb * 12 + i);
            acc[4 * bb + 0] = fmaf(sx, bf_lo(wx), acc[4 * bb + 0]); acc[4 * bb + 1] = fmaf(sx, bf_hi(wx), acc[4 * bb + 1]);
            acc[4 * bb + 2] = fmaf(sx, bf_lo(wy), acc[4 * bb + 2]); acc[4 * bb + 3] = fmaf(sx, bf_hi(wy), acc[4 * bb + 3]);
        }
    }
    sts128f(SM_ACT + warp * 1024 + lane * 16, make_float4(acc[0], acc[1], acc[2], acc[3]));
    sts128f(SM_ACT + warp * 1024 + 512 + lane * 16, make_float4(acc[4], acc[5], acc[6], acc[7]));
    __syncthreads();
    if (tid < 128) {
        float2 sum = make_float2(0.f, 0.f);
#pragma unroll
        for (int w = 0; w < 16; w++) { const float2 p = lds64f(SM_ACT + w * 1024 + tid * 8); sum.x += p.x; sum.y += p.y; }
        *reinterpret_cast<float2*>(&gs->emb[j * NB * C + tid * 2]) = sum;
        bar_sync(1, 128);
        if (tid < 2) asm volatile("red.release.gpu.global.add.u32 [%0], 1;" ::"l"(&gs->wcnt[(2 * NB + tid) * LS]) : "memory");
    }
}

__global__ void __cluster_dims__(2, 1, 1) __launch_bounds__(NTHREADS, 1)
resblock_kernel(const __nv_bfloat16* __restrict__ w1, const __nv_bfloat16* __restrict__ x,
                const __nv_bfloat16* __restrict__ t_emb, const __nv_bfloat16* __restrict__ g1,
                const __nv_bfloat16* __restrict__ be1, const __nv_bfloat16* __restrict__ w_emb,
                const __nv_bfloat16* __restrict__ g2, const __nv_bfloat16* __restrict__ be2,
                const __nv_bfloat16* __restrict__ w2, __nv_bfloat16* __restrict__ out, Scratch* __restrict__ gs,
                const __grid_constant__ CUtensorMap xmap) {
    const unsigned clk0 = clock32();
    if (threadIdx.x == 480 && blockIdx.x >= NXTRA) TLG(1);
    const int tid = threadIdx.x, lane = tid & 31;
    const int cta = blockIdx.x - NXTRA, b = cta >> 6, r = cta & 63;
    uint4 v[5];
    if (tid < 32) weight_load(v, w1, cta & (NCTA - 1), lane);
    uint4 xv[8];
    const int wg4 = (tid >> 5) - 1;
    const bool early = tid >= 32 && wg4 < NLDG;
    if (early) {
        const char* src = reinterpret_cast<const char*>(x) + (uint32_t)((((b & 1) * C + wg4 * 32 + (lane >> 3)) * HW + r) * HW * 2 + (lane & 7) * 16);
        while (clock32() - clk0 < XDELAY + (wg4 >> 1) * XSTAG + (wg4 & 1) * XSTAG2) {}
#pragma unroll
        for (int i = 0; i < 8; i++) xv[i] = __ldg(reinterpret_cast<const uint4*>(src + i * (4 * HW * HW * 2)));
    }
    const int warp = __shfl_sync(0xffffffffu, tid >> 5, 0);
    if (cta < 0) { side_jobs(t_emb, w_emb, w2, gs, clk0); return; }

    if (warp != 4) asm volatile("barrier.cluster.arrive.relaxed.aligned;" ::: "memory");
    const bool has_outer = (r != 0) && (r != HW - 1);
    if (warp == 1 || warp == 2 || warp == 3 || warp == 5) {
        const int g = warp < 4 ? warp - 1 : 3;
        if (elect_one()) {
            if (g >= NLDG) asm volatile("prefetch.tensormap [%0];" ::"l"(&xmap) : "memory");
            mbar_init(BAR(BAR_X) + 8 * g, 1);
            if (g >= NLDG) mbar_expect(BAR(BAR_X) + 8 * g, 4096);
            fence_async_smem();
        }
        __syncwarp();
        bar_arrive(4, 256 + 32 + 128);
        if (g >= NLDG) {
            while (clock32() - clk0 < XDELAY + (g >> 1) * XSTAG + (g & 1) * XSTAG2) {}
            if (elect_one()) tma_x(SM_XOWN + g * 4096, &xmap, r, b * C + g * 32, BAR(BAR_X) + 8 * g);
            __syncwarp();
            mbar_wait(BAR(BAR_X) + 8 * g, 0);
#pragma unroll
            for (int k = 0; k < 8; k++) xv[k] = lds128(SM_XOWN + g * 4096 + k * 512 + lane * 16);
        }
        float c[8][4];
#pragma unroll
        for (int k = 0; k < 8; k++) {
            c[k][0] = c[k][1] = c[k][2] = c[k][3] = 0.f;
            stat_mma(c[k], xv[k].x, xv[k].y); stat_mma(c[k], xv[k].z, xv[k].w);
        }
#pragma unroll
        for (int i = 0; i < 4; i++) c[0][i] = ((c[0][i] + c[1][i]) + (c[2][i] + c[3][i])) + ((c[4][i] + c[5][i]) + (c[6][i] + c[7][i]));
        stat_store(c[0], SM_RED + g * 48, lane);
        __syncwarp();
        if (lane == 0) {
            const uint32_t a = SM_RED + g * 48;
            red_add4(&gs->acc1[b * LS + g * 4], 1.f, sum4(lds128f(a + 32)), sum4(lds128f(a)) + sum4(lds128f(a + 16)), 1.f);
            TL(74 + g);
        }
        if (g < NLDG) {
#pragma unroll
            for (int i = 0; i < 8; i++)
                sts128(SM_XOWN + g * 4096 + i * 512 + (lane >> 3) * 128 + (((lane & 7) ^ ((lane >> 3) + 4 * (i & 1))) << 4), xv[i]);
            __syncwarp();
            if (lane == 0) mbar_arrive(BAR(BAR_X) + 8 * g);
        }
    }
    if (warp == 4) {
            if (elect_one()) {
#pragma unroll
                for (int i = 0; i < NSTAGE; i++) mbar_init(BAR(BAR_FULL + i), (i >> 3) == 1 ? 1 : 5);
#pragma unroll
                for (int i = 0; i < NS + 2; i++) mbar_init(BAR(BAR_WEMPTY + i), 4);
#pragma unroll
                for (int i = BAR_STATS; i < BAR_X; i++) mbar_init(BAR(i), i == BAR_EMB ? 3 : 1);
                mbar_init(BAR(BAR_X + 4), 1);
                asm volatile("fence.mbarrier_init.release.cluster;" ::: "memory");
            }
            if (lane < 4) sts128(SM_GST + lane * 16, make_uint4(0, 0, 0, 0));
            __syncwarp();
            fence_async_smem();
            bar_arrive(0, 96);
            bar_arrive(5, 64);
            bar_arrive(4, 256 + 32 + 128);
            const uint4 z = make_uint4(0, 0, 0, 0);
#pragma unroll
            for (int i = 0; i < 2; i++) sts128(SM_ACT + (i * 16 + (lane >> 1)) * CH_PITCH + (lane & 1) * 16, z);
            if (lane < 4) sts128(SM_ACT + (2 + (lane >> 1)) * ROW_BYTES + (lane & 1) * 16, z);
            if (lane < 16) sts128(SM_ONES + lane * 16, make_uint4(lane < 8 ? 0x3f803f80u : 0u, 0, 0, 0));
            fence_async_smem();
            bar_arrive(7, 160);
            asm volatile("barrier.cluster.arrive.relaxed.aligned;" ::: "memory");
            if (lane == 0) TL(5);
            while (clock32() - clk0 < W2DELAY) {}
            weight_load(v, w2, cta, lane);
        }
    if (warp == 0 || warp == 4) {
        const int k = warp >> 2;
#pragma unroll
        for (int i = 0; i < 5; i++)
            if (i < 4 || lane < 16) sts128(SM_BNC + k * 2304 + (lane + 32 * i) * 16, v[i]);
        if (lane == 0) TL(k ? 14 : 81);
        __syncwarp();
        weight_block(SM_BNC + k * 2304, gs->wt + k * NSTAGE * STAGE_BYTES, cta, lane, true, gs);
        __syncwarp();
        if (lane == 0) TL(k ? 13 : 4);
        if (lane < 2) asm volatile("red.relaxed.gpu.global.add.u32 [%0], 1;" ::"l"(k ? &gs->wcnt[(NB + lane) * LS] : &gs->w1cnt[(lane * 8 + (cta >> 4)) * KS]) : "memory");
    }

    if (warp >= 8) {
        const int nw = warp - 8;
        if (nw < 2) {
            const uint2 ga = __ldg(reinterpret_cast<const uint2*>(nw ? g2 : g1) + lane), bt = __ldg(reinterpret_cast<const uint2*>(nw ? be2 : be1) + lane);
            sts128f(SM_COEF + nw * 1024 + lane * 32, make_float4(0.5f * bf_lo(ga.x), 0.5f * bf_hi(ga.x), 0.5f * bf_lo(bt.x), 0.5f * bf_hi(bt.x)));
            sts128f(SM_COEF + nw * 1024 + lane * 32 + 16, make_float4(0.5f * bf_lo(ga.y), 0.5f * bf_hi(ga.y), 0.5f * bf_lo(bt.y), 0.5f * bf_hi(bt.y)));
        }
        bar_sync(4, 256 + 32 + 128);
        const int par = nw >> 2, wq = nw & 3;
        const uint32_t act_off = SM_ACT + (par * 2 + (lane >> 4)) * CH_PITCH + (2 + wq * 16 + (lane & 15)) * 16;
        const uint32_t stg_off = (par * 16 + (lane >> 4) * 8 + (lane & 7)) * 128 + (((2 * wq + ((lane >> 3) & 1)) ^ (lane & 7)) << 4);
        const uint32_t cfa = SM_COEF + par * 128 + (lane & 3) * 16;
        const uint32_t fbar = BAR(BAR_FULL) + 8 * par;
        uint4* inbox = gs->box + cta * 1024 + nw * 32 + lane;
#pragma unroll 1
        for (int conv = 0; conv < 2; conv++) {
            uint32_t u[4][4], w[4][4];
            float4 cf[8];
            if (conv == 0) {
#pragma unroll
                for (int i = 0; i < 4; i++) { mbar_wait(BAR(BAR_X + i), 0); ldsm4t(u[i], SM_XOWN + stg_off + i * 4096); }
            } else {
                mbar_wait(BAR(BAR_HW), 0);
#pragma unroll
                for (int i = 0; i < 4; i++) ldsm4(u[i], act_off + i * 2 * KC_BYTES);
            }
#pragma unroll
            for (int i = 0; i < 8; i++) cf[i] = lds128f(cfa + conv * 1024 + (i >> 1) * 256 + (i & 1) * 64);
            const uint32_t gst = SM_GST + conv * 32;
            float gv[8] = {0.f, 0.f, 0.f, 0.f, 0.f, 0.f, 0.f, 0.f};
            group_coefs<0>(gst, gv, cf);
            if (tid == 256) TL(22 + conv * 4);
            if (par) { const unsigned c1 = clock32(); while (clock32() - c1 < PDELAY) {} }
            norm_block<0, 1>(u, cf, act_off, ~0u, fbar, lane);
            if (tid == 256) TL(8 + conv * 8);
            group_coefs<1>(gst, gv, cf);
            norm_block<1, 1>(u, cf, act_off, ~0u, fbar, lane);
            group_coefs<2>(gst, gv, cf);
            norm_unit(u[2], cf[4], cf[5]);
            stsm4(act_off + 4 * KC_BYTES, u[2][0], u[2][1], u[2][2], u[2][3]);
            next_unit<3>(u, cf, gst, gv, act_off, fbar, lane);
            publish(fbar + 48, lane);
            if (tid == 256) TL(84 + conv);
            if (has_outer) {
                mbar_wait(BAR(BAR_X + 4), conv);
                if (conv == 0) {
#pragma unroll
                    for (int i = 0; i < 4; i++) ldsm4t(w[i], SM_XOUT + stg_off + i * 4096);
                } else {
#pragma unroll
                    for (int i = 0; i < 4; i++) {
                        const uint4 q = lds128(SM_XOWN + (tid - 256) * 16 + i * 4096);
                        w[i][0] = q.x; w[i][1] = q.y; w[i][2] = q.z; w[i][3] = q.w;
                    }
                    unsigned it = 0;
                    while (true) {
                        bool ok = true;
#pragma unroll
                        for (int i = 0; i < 16; i++) ok = ok && w[i >> 2][i & 3] != 0;
                        if (__all_sync(0xffffffffu, ok) || ++it > SPIN_LIMIT) break;
#pragma unroll
                        for (int i = 0; i < 4; i++) ld_unit(w[i], inbox + i * 256);
                    }
#pragma unroll
                    for (int i = 0; i < 16; i++) w[i >> 2][i & 3] = ~w[i >> 2][i & 3];
                }
            }
            if (conv == 0) {
                bar_sync(3, 256);
                if (nw == 0) sts128(SM_ACT + 2 * ROW_BYTES + (lane >> 1) * CH_PITCH + (lane & 1) * 16, make_uint4(0, 0, 0, 0));
            }
            if (tid == 256) TL(24 + conv * 4);
            norm_block<0, 2>(w, cf, act_off + 2 * ROW_BYTES, has_outer ? ~0u : 0u, fbar + 128, lane);
            if (tid == 256) TL(88 + conv);
            norm_block<2, 2>(w, cf, act_off + 2 * ROW_BYTES, has_outer ? ~0u : 0u, fbar + 128, lane);
            if (tid == 256) TL(23 + conv * 4);
        }
        if (has_outer) {
            mbar_wait(BAR(BAR_FULL + NSTAGE - 1), 1);
#pragma unroll
            for (int i = 0; i < 4; i++) inbox[i * 256] = make_uint4(0, 0, 0, 0);
        }
        {
            const int oc0 = par * 64 + ((tid & 127) >> 3), seg = lane & 7;
            __nv_bfloat16* dst = out + ((size_t)(b * C + oc0) * HW + r) * HW + seg * 8;
            const uint32_t src = SM_XOWN + oc0 * 128 + ((seg ^ (oc0 & 7)) << 4);
            bar_sync(par ? 1 : 6, 128 + 128);
#pragma unroll
            for (int i = 0; i < 4; i++) *reinterpret_cast<uint4*>(dst + (size_t)i * 16 * HW * HW) = lds128(src + i * 2048);
            if (tid == 384) { TL(20); TLG(21); }
        }
    } else if (warp < 4) {
        const int wq = warp;
        bar_sync(7, 160);

        const uint32_t xbase = SM_XOWN + ((lane >> 4) * 8 + (lane & 7)) * 128 + (((2 * wq + ((lane >> 3) & 1)) ^ (lane & 7)) << 4);
        float d[64];
#pragma unroll
        for (int i = 0; i < 64; i++) d[i] = 0.f;
#pragma unroll 1
        for (int conv = -DRY; conv < 2; conv++) {
            if (conv >= 0) {
                fence_acc(d);
                mma_stages<0>(d, conv, tid, gs);
                if (conv == 0) {
                    asm volatile("wgmma.fence.sync.aligned;" ::: "memory");
                    wgmma128<(SM_ONES >> 4) | (8u << 16), (SM_EMB >> 4), 0, 8>(d);
                    asm volatile("wgmma.commit_group.sync.aligned;" ::: "memory");
                }
                asm volatile("wgmma.wait_group.sync.aligned 0;" ::: "memory");
                fence_acc(d);
                if (tid == 0) TL(10 + conv * 8);
            }
            if (conv == 1) {
                fence_acc(d);
#pragma unroll
                for (int kc = 0; kc < 8; kc++) {
                    stsm4t(xbase + kc * 2048, pack_bf(d[8 * kc], d[8 * kc + 1]), pack_bf(d[8 * kc + 2], d[8 * kc + 3]),
                           pack_bf(d[8 * kc + 4], d[8 * kc + 5]), pack_bf(d[8 * kc + 6], d[8 * kc + 7]));
                    if (kc == 3) bar_arrive(6, 128 + 128);
                }
                bar_arrive(1, 128 + 128);
                break;
            }
            uint32_t hp[32];
#pragma unroll
            for (int i = 0; i < 32; i++) hp[i] = pack_bf(d[2 * i], d[2 * i + 1]);
#pragma unroll
            for (int g = 0; g < 4; g++) {
                float c[4] = {0.f, 0.f, 0.f, 0.f};
#pragma unroll
                for (int i = 0; i < 4; i++) stat_mma(c, hp[8 * g + 2 * i], hp[8 * g + 2 * i + 1]);
                stat_store(c, SM_RED + 256 + (g * 4 + wq) * 48, lane);
            }
            bar_sync(2, 128);
            if (wq == 0) stat_publish(SM_RED + 256, &gs->acc2[b * LS], lane, conv == 0);
            if (conv < 0) {
#pragma unroll
                for (int i = 0; i < 64; i++) d[i] = 0.f;
                continue;
            }
            if (tid == 0) TL(11);
            const uint32_t hbase = SM_ACT + (lane >> 4) * CH_PITCH + (2 + wq * 16 + (lane & 15)) * 16;
#pragma unroll
            for (int kc = 0; kc < 8; kc++) stsm4(hbase + kc * 2 * CH_PITCH, hp[4 * kc], hp[4 * kc + 1], hp[4 * kc + 2], hp[4 * kc + 3]);
            __syncwarp();
            if (lane == 0) mbar_arrive(BAR(BAR_HW));
            if (lane < LAG) mbar_arrive(BAR(BAR_WEMPTY + (NSTAGE - LAG) % NS) + 8 * lane);
            if (has_outer) {
                uint4* outbox = gs->box + (cta + ((r & 1) ? 1 : -1)) * 1024 + tid;
#pragma unroll
                for (int kc = 0; kc < 8; kc++) outbox[kc * 128] = make_uint4(~hp[4 * kc], ~hp[4 * kc + 1], ~hp[4 * kc + 2], ~hp[4 * kc + 3]);
            }
            if (tid == 0) TL(12);
#pragma unroll
            for (int kc = 0; kc < 8; kc++) {
                uint32_t p[4];
                ldsm4t(p, xbase + kc * 2048);
#pragma unroll
                for (int i = 0; i < 4; i++) { d[8 * kc + 2 * i] = bf_lo(p[i]); d[8 * kc + 2 * i + 1] = bf_hi(p[i]); }
            }
            fence_async_smem();
            __syncwarp();
            if (lane == 0) mbar_arrive(BAR(BAR_XFREE));
        }
        {
        }
    } else if (warp < 6) {
        if (warp == 5) {
            bar_sync(5, 64);
            mbar_wait(BAR(BAR_FULL + OAFTER), 0);
            if (has_outer && elect_one()) {
                mbar_expect(BAR(BAR_X + 4), 16384);
#pragma unroll
                for (int i = 0; i < 4; i++) tma_x(SM_XOUT + i * 4096, &xmap, r + ((r & 1) ? 1 : -1), b * C + i * 32, BAR(BAR_X + 4));
            }
            __syncwarp();
            asm volatile("barrier.cluster.wait.acquire.aligned;" ::: "memory");
            const uint32_t peer = (r & 1) ^ 1;
            const uint32_t self0 = mapa(0, r & 1), peer0 = mapa(0, peer);
#pragma unroll 1
            for (int conv = 0; conv < 2; conv++) {
#pragma unroll 1
                for (int kc = 0; kc < 8; kc++) {
                    mbar_wait(BAR(BAR_FULL) + 8 * kc, conv);
                    if (elect_one())
                        asm volatile("cp.async.bulk.shared::cluster.shared::cta.mbarrier::complete_tx::bytes [%0], [%1], %2, [%3];"
                                     ::"r"(peer0 + SM_ACT + ROW_BYTES + kc * KC_BYTES), "r"(self0 + SM_ACT + kc * KC_BYTES), "r"(KC_BYTES),
                                       "r"(peer0 + BAR(BAR_FULL + 8) + 8 * kc) : "memory");
                }
                if (lane == 0) TL(86 + conv);
#pragma unroll 1
                for (int kc = 0; kc < 8; kc++) mbar_wait(BAR(BAR_FULL + 8) + 8 * kc, conv);
                if (lane == 0)
                    asm volatile("mbarrier.arrive.relaxed.cluster.shared::cluster.b64 _, [%0];" ::"r"(peer0 + (conv ? BAR(BAR_ACK) : BAR(BAR_EMB))) : "memory");
            }
            mbar_wait(BAR(BAR_ACK), 0);
        } else {
            mbar_wait(BAR(BAR_STATS), 0);
            unsigned it = 0;
            while (ld_relaxed(&gs->wcnt[(2 * NB + b) * LS]) < (unsigned)NXTRA && ++it < SPIN_LIMIT) __nanosleep(100);
            fence_acquire();
            float ev[4] = {0.f, 0.f, 0.f, 0.f};
#pragma unroll
            for (int j = 0; j < NXTRA; j++) {
                const uint4 ef = ld_relaxed_v4(&gs->emb[(j * NB + b) * C + lane * 4]);
                ev[0] += __uint_as_float(ef.x); ev[1] += __uint_as_float(ef.y); ev[2] += __uint_as_float(ef.z); ev[3] += __uint_as_float(ef.w);
            }
#pragma unroll
            for (int i = 0; i < 4; i++) {
                const float hi = bf_lo(pack_bf(ev[i], 0.f));
                sts128(SM_EMB + (lane * 4 + i) * 16, make_uint4(pack_bf(hi, ev[i] - hi), 0, 0, 0));
            }
            fence_async_smem();
            __syncwarp();
            if (lane == 0) { mbar_arrive(BAR(BAR_EMB)); TL(19); }
        }
    } else if (warp == 6) {
        bar_sync(0, 96);
        const uint32_t ebytes = STAGE_BYTES + ((lane >> 3) == 1 ? KC_BYTES : 0);
        if (lane < NSTAGE) mbar_expect(BAR(BAR_FULL) + 8 * lane, ebytes);
        const int swap = (r & 1) ? 0 : 8 * STAGE_BYTES;
        unsigned it = 0;
        {
            int g = 0;
            const unsigned* cnt = &gs->w1cnt[(b * 8 + (lane & 7)) * KS];
            unsigned cv = ld_relaxed(cnt);
#pragma unroll 1
            while (g < NS) {
                unsigned ready = __ballot_sync(0xffffffffu, cv >= 16u);
                if (ready != ~0u) cv = ld_relaxed(cnt);
                ready >>= g;
                if (++it > SPIN_LIMIT) ready = ~0u;
                if (!(ready & 1)) continue;
                fence_async_global();
                if (lane == 0) TL(g ? 3 : 6);
#pragma unroll 1
                for (; (ready & 1) && g < NS; g++, ready >>= 1)
                    if (elect_one())
                        bulk_g2s(S0 + SM_W + g * STAGE_BYTES, gs->wt + g * STAGE_BYTES + (g >= 8 ? swap : 0), STAGE_BYTES, S0 + BAR(BAR_FULL) + 8 * g);
            }
        }
#pragma unroll 1
        for (int q = 3; q < 12; q++) {
            const int conv = q >= 6, qs = conv ? q - 6 : q, sl = q % 3;
            const unsigned char* wsrc = gs->wt + q * 4 * STAGE_BYTES + (qs < 2 ? 0 : (qs < 4 ? swap : -swap));
            const uint32_t par = (q / 3 - 1) & 1;
            if (q == 6) {
                it = 0;
                while (ld_relaxed(&gs->wcnt[(NB + b) * LS]) < (unsigned)NCTA && ++it < SPIN_LIMIT) {}
                fence_acquire();
                fence_async_global();
                if (lane == 0) { mbar_arrive(BAR(BAR_EMB)); TL(2); }
            }
#pragma unroll
            for (int i = 0; i < 4; i++) {
                mbar_wait(BAR(BAR_WEMPTY + i) + 32 * sl, par);
                if (i == 0 && (q == 6 || q == 9)) {
                    if ((lane >= NS) == (q == 9) && lane < NSTAGE) mbar_expect(BAR(BAR_FULL) + 8 * lane, ebytes);
                    __syncwarp();
                }
                if (elect_one())
                    bulk_g2s(S0 + SM_W + (sl * 4 + i) * STAGE_BYTES, wsrc + i * STAGE_BYTES, STAGE_BYTES, S0 + BAR(BAR_FULL + i) + 32 * qs);
            }
        }
    } else {
        bar_sync(0, 96);
#pragma unroll 1
        for (int conv = 0; conv < 2; conv++) {
            if (conv == 1) mbar_wait(BAR(BAR_HW), 0);
            const float* asrc = (conv ? gs->acc2 : gs->acc1) + b * LS + (lane & 3) * 4;
            unsigned it = 0;
#pragma unroll 1
            while (true) {
                const uint4 f = ld_relaxed_v4(asrc);
                const bool ok = ((f.x == 0x42800000u) & (f.w == 0x42800000u)) || ++it > SPIN_LIMIT;
                if (ok && lane < 4) {
                    const float inv_n = 1.0f / (32.0f * HW * HW);
                    const float mean = __uint_as_float(f.y) * inv_n;
                    float rs;
                    asm("rsqrt.approx.ftz.f32 %0, %1;" : "=f"(rs) : "f"(fmaxf(fmaf(-mean, mean, __uint_as_float(f.z) * inv_n), 0.f) + 1e-5f));
                    asm volatile("st.shared.v2.f32 [%0], {%1,%2};" ::"r"(S0 + SM_GST + conv * 32 + lane * 8), "f"(rs == 0.f ? 1e-38f : rs), "f"(mean * rs) : "memory");
                }
                if (__all_sync(0xffffffffu, ok)) break;
            }
            if (lane == 0) { mbar_arrive(BAR(BAR_STATS)); TL(7 + conv * 8); }
        }
        mbar_wait(BAR(BAR_XFREE), 0);
        if (has_outer && elect_one()) {
            mbar_expect(BAR(BAR_X + 4), 16384);
            bulk_g2s(S0 + SM_XOWN, gs->box + cta * 1024, 16384, S0 + BAR(BAR_X + 4));
        }
        if (r == 0) {
            if (lane < 16) gs->acc1[b * LS + lane] = 0.f;
            if (lane < 3) gs->wcnt[(lane * NB + b) * LS] = 0;
            if (lane < 8) gs->w1cnt[(b * 8 + lane) * KS] = 0;
        }
    }
}

}

extern "C" void kernel_launch(void* const* d_in, const int* in_sizes, int n_in, void* d_out, int out_size) {
    (void)in_sizes; (void)n_in; (void)out_size;
    typedef CUresult (*EncodeFn)(CUtensorMap*, CUtensorMapDataType, cuuint32_t, void*, const cuuint64_t*, const cuuint64_t*,
                                 const cuuint32_t*, const cuuint32_t*, CUtensorMapInterleave, CUtensorMapSwizzle,
                                 CUtensorMapL2promotion, CUtensorMapFloatOOBfill);
    static Scratch* gs = nullptr;
    static EncodeFn encode = nullptr;
    if (!gs) {
        cudaFuncSetAttribute(resblock_kernel, cudaFuncAttributeMaxDynamicSharedMemorySize, SM_TOTAL);
        cudaGetSymbolAddress((void**)&gs, g_scratch);
        cudaDriverEntryPointQueryResult qr;
        cudaGetDriverEntryPoint("cuTensorMapEncodeTiled", (void**)&encode, cudaEnableDefault, &qr);
    }
    CUtensorMap xmap;
    const cuuint64_t dims[3] = {HW, HW, NB * C}, strides[2] = {HW * 2, HW * HW * 2};
    const cuuint32_t box[3] = {HW, 1, 32}, es[3] = {1, 1, 1};
    encode(&xmap, CU_TENSOR_MAP_DATA_TYPE_BFLOAT16, 3, d_in[0], dims, strides, box, es, CU_TENSOR_MAP_INTERLEAVE_NONE,
           CU_TENSOR_MAP_SWIZZLE_128B, CU_TENSOR_MAP_L2_PROMOTION_NONE, CU_TENSOR_MAP_FLOAT_OOB_FILL_NONE);
    resblock_kernel<<<NCTA + NXTRA, NTHREADS, SM_TOTAL>>>(
        (const __nv_bfloat16*)d_in[4], (const __nv_bfloat16*)d_in[0], (const __nv_bfloat16*)d_in[1],
        (const __nv_bfloat16*)d_in[2], (const __nv_bfloat16*)d_in[3], (const __nv_bfloat16*)d_in[5],
        (const __nv_bfloat16*)d_in[6], (const __nv_bfloat16*)d_in[7], (const __nv_bfloat16*)d_in[8],
        (__nv_bfloat16*)d_out, gs, xmap);
}
```

```cpp
#include <cuda_runtime.h>
#include <cuda.h>
#include <cuda_bf16.h>
#include <stdint.h>

namespace {

constexpr int C = 128, HW = 64, NB = 2, E = 768;
constexpr int NCTA = NB * HW;
constexpr int NXTRA = 4;
constexpr int NTHREADS = 16 * 32;
constexpr int CH_PITCH = 66 * 16;
constexpr int ROW_BYTES = 16 * CH_PITCH;
constexpr int STEP_BYTES = 4096;
constexpr int STAGE_BYTES = 3 * STEP_BYTES;
constexpr int NSTAGE = 24;
constexpr int KC_BYTES = 2 * CH_PITCH;
constexpr int NS = 12;
constexpr int LAG = 1;
#define XDELAY 400
#define HDELAY 600
#define SEQ 1
#define MMA0_WAIT mbar_try
#define NPOLL 1
#define PD2 0
#define ODELAY 100
#define NLDG 2
#define PSTAG -1
#define PDELAY0 400
#define PDELAY 60
#define RB 1
#define XSTAG2 400
#define XSTAG 800
#define HSEND 0
#define SDELAY 600
#define OAFTER 0
#define W2DELAY 2400

constexpr uint32_t SMEM_BASE = 0x400;
constexpr uint32_t SM_XOWN = SMEM_BASE;
constexpr uint32_t SM_ACT = SM_XOWN + 16384 + 512;
constexpr uint32_t SM_XOUT = SM_ACT + 2 * ROW_BYTES + 512;
static_assert(SM_XOUT % 1024 == 0, "swizzle atom alignment");
constexpr uint32_t SM_W = SM_ACT + 3 * ROW_BYTES + 128;
__host__ __device__ constexpr uint32_t slot_addr(int slot) { return SM_W + slot * STAGE_BYTES; }
constexpr uint32_t SM_COEF = SM_W + NS * STAGE_BYTES;
constexpr uint32_t SM_GST = SM_COEF + 2048;
constexpr uint32_t SM_EMB = SM_GST + 128;
constexpr uint32_t SM_ONES = SM_EMB + 2048;
constexpr uint32_t SM_RED = SM_ONES + 256;
constexpr uint32_t SM_BNC = SM_RED + 1536;
constexpr uint32_t SM_BAR = SM_BNC + 2 * 2304;
constexpr int BAR_FULL = 0, BAR_WEMPTY = NSTAGE, BAR_HW = BAR_WEMPTY + NS, BAR_XFREE = BAR_HW + 1, BAR_STATS = BAR_XFREE + 1,
              BAR_EMB = BAR_STATS + 1, BAR_ACK = BAR_EMB + 1, BAR_X = BAR_ACK + 1  , NBAR = BAR_X + 5;
constexpr int SM_TOTAL = SM_BAR + NBAR * 8 - SMEM_BASE;
static_assert(SM_TOTAL <= 232448, "smem");
static_assert(NBAR <= 96, "barrier init");
__host__ __device__ constexpr uint32_t BAR(int i) { return SM_BAR + 8 * i; }
__host__ __device__ constexpr int ky_of(int kyo) { return kyo == 0 ? 1 : (kyo == 1 ? 0 : 2); }

constexpr unsigned SPIN_LIMIT = 1u << 16;

#define LS 1056
#define GS1 4
#define PD 0
#define KS 32
struct Scratch {
    float acc1[NB * LS];
    float acc2[NB * LS];
    unsigned wcnt[3 * NB * LS];
    unsigned w1cnt[NB * 8 * KS];
    float emb[NXTRA * NB * C];
    alignas(1024) unsigned char wt[2 * NSTAGE * STAGE_BYTES];
    uint4 box[NCTA * 1024];
};
__device__ __align__(1024) Scratch g_scratch;
#define TL(i) do {} while (0)
#define TLG(i) do {} while (0)

__device__ __forceinline__ unsigned clock32() { unsigned c; asm volatile("mov.u32 %0, %%clock;" : "=r"(c)); return c; }
__device__ __forceinline__ uint32_t mapa(uint32_t a, uint32_t rank) {
    uint32_t d;
    asm("mapa.shared::cluster.u32 %0, %1, %2;" : "=r"(d) : "r"(a), "r"(rank));
    return d;
}
#define S0 mapa(0, blockIdx.x & 1)
__device__ __forceinline__ void mbar_init(uint32_t bar, int cnt) {
    asm volatile("mbarrier.init.shared::cta.b64 [%0], %1;" ::"r"(bar + S0), "r"(cnt) : "memory");
}
__device__ __forceinline__ void mbar_arrive(uint32_t bar) {
    asm volatile("mbarrier.arrive.shared::cta.b64 _, [%0];" ::"r"(bar + S0) : "memory");
}
__device__ __forceinline__ void mbar_expect(uint32_t bar, uint32_t bytes) {
    asm volatile("mbarrier.arrive.expect_tx.shared::cta.b64 _, [%0], %1;" ::"r"(bar + S0), "r"(bytes) : "memory");
}
__device__ __forceinline__ bool mbar_try(uint32_t bar, uint32_t par) {
    uint32_t ok;
    asm volatile("{\n.reg .pred p;\nmbarrier.try_wait.parity.shared::cta.b64 p, [%1], %2;\nselp.u32 %0, 1, 0, p;\n}"
                 : "=r"(ok) : "r"(bar + S0), "r"(par) : "memory");
    return ok;
}
__device__ __forceinline__ bool mbar_test(uint32_t bar, uint32_t par) {
    uint32_t ok;
    asm volatile("{\n.reg .pred p;\nmbarrier.test_wait.parity.shared::cta.b64 p, [%1], %2;\nselp.u32 %0, 1, 0, p;\n}"
                 : "=r"(ok) : "r"(bar + S0), "r"(par) : "memory");
    return ok;
}
__device__ __forceinline__ void mbar_wait(uint32_t bar, uint32_t par) {
    unsigned it = 0;
#pragma unroll 1
    while (!mbar_try(bar, par) && ++it < SPIN_LIMIT) {}
}
__device__ __forceinline__ bool elect_one() {
    uint32_t p;
    asm volatile("{\n.reg .pred p;\nelect.sync _|p, 0xffffffff;\nselp.u32 %0, 1, 0, p;\n}" : "=r"(p));
    return p;
}
__device__ __forceinline__ void fence_async_smem() { asm volatile("fence.proxy.async.shared::cta;" ::: "memory"); }
__device__ __forceinline__ void fence_async_global() { asm volatile("fence.proxy.async.global;" ::: "memory"); }
__device__ __forceinline__ void fence_acquire() { asm volatile("fence.acquire.gpu;" ::: "memory"); }
__device__ __forceinline__ void bar_sync(int id, int n) { asm volatile("bar.sync %0, %1;" ::"r"(id), "r"(n) : "memory"); }
__device__ __forceinline__ void bar_arrive(int id, int n) { asm volatile("bar.arrive %0, %1;" ::"r"(id), "r"(n) : "memory"); }
__device__ __forceinline__ void bulk_g2s(uint32_t dst, const void* src, uint32_t bytes, uint32_t bar) {
    asm volatile("cp.async.bulk.shared::cluster.global.mbarrier::complete_tx::bytes [%0], [%1], %2, [%3];"
                 ::"r"(dst), "l"(src), "r"(bytes), "r"(bar) : "memory");
}
__device__ __forceinline__ void tma_x(uint32_t dst, const CUtensorMap* tm, int row, int ch, uint32_t bar) {
    asm volatile("cp.async.bulk.tensor.3d.shared::cluster.global.mbarrier::complete_tx::bytes [%0], [%1, {%2, %3, %4}], [%5];"
                 ::"r"(dst + S0), "l"(tm), "r"(0), "r"(row), "r"(ch), "r"(bar + S0) : "memory");
}
__device__ __forceinline__ uint4 ld_relaxed_v4(const void* p) {
    uint4 v;
    asm volatile("ld.relaxed.gpu.global.v4.u32 {%0,%1,%2,%3}, [%4];" : "=r"(v.x), "=r"(v.y), "=r"(v.z), "=r"(v.w) : "l"(p) : "memory");
    return v;
}
__device__ __forceinline__ unsigned ld_relaxed(const void* p) {
    unsigned v;
    asm volatile("ld.relaxed.gpu.global.u32 %0, [%1];" : "=r"(v) : "l"(p) : "memory");
    return v;
}
__device__ __forceinline__ void red_add4(float* p, float a, float b, float c, float d) {
    asm volatile("red.relaxed.gpu.global.add.v4.f32 [%0], {%1,%2,%3,%4};" ::"l"(p), "f"(a), "f"(b), "f"(c), "f"(d) : "memory");
}
__device__ __forceinline__ void sts128(uint32_t a, uint4 v) {
    asm volatile("st.shared.v4.u32 [%0], {%1,%2,%3,%4};" ::"r"(a + S0), "r"(v.x), "r"(v.y), "r"(v.z), "r"(v.w) : "memory");
}
__device__ __forceinline__ void sts128f(uint32_t a, float4 v) {
    asm volatile("st.shared.v4.f32 [%0], {%1,%2,%3,%4};" ::"r"(a + S0), "f"(v.x), "f"(v.y), "f"(v.z), "f"(v.w) : "memory");
}
__device__ __forceinline__ void sts32f(uint32_t a, float v) { asm volatile("st.shared.f32 [%0], %1;" ::"r"(a + S0), "f"(v) : "memory"); }
__device__ __forceinline__ uint4 lds128(uint32_t a) {
    uint4 v;
    asm volatile("ld.shared.v4.u32 {%0,%1,%2,%3}, [%4];" : "=r"(v.x), "=r"(v.y), "=r"(v.z), "=r"(v.w) : "r"(a + S0) : "memory");
    return v;
}
__device__ __forceinline__ float4 lds128f(uint32_t a) {
    float4 v;
    asm volatile("ld.shared.v4.f32 {%0,%1,%2,%3}, [%4];" : "=f"(v.x), "=f"(v.y), "=f"(v.z), "=f"(v.w) : "r"(a + S0) : "memory");
    return v;
}
__device__ __forceinline__ float2 lds64f(uint32_t a) {
    float2 v;
    asm volatile("ld.shared.v2.f32 {%0,%1}, [%2];" : "=f"(v.x), "=f"(v.y) : "r"(a + S0) : "memory");
    return v;
}
__device__ __forceinline__ float bf_lo(uint32_t u) { return __uint_as_float(u << 16); }
__device__ __forceinline__ float bf_hi(uint32_t u) { return __uint_as_float(u & 0xffff0000u); }
__device__ __forceinline__ uint32_t pack_bf(float lo, float hi) {
    uint32_t r;
    asm("cvt.rn.bf16x2.f32 %0, %1, %2;" : "=r"(r) : "f"(hi), "f"(lo));
    return r;
}
__device__ __forceinline__ float tanh_fast(float x) {
    float r;
    asm("tanh.approx.f32 %0, %1;" : "=f"(r) : "f"(x));
    return r;
}
__device__ __forceinline__ float silu_half(float h) { return fmaf(h, tanh_fast(h), h); }
__device__ __forceinline__ void ldsm4(uint32_t (&u)[4], uint32_t a) {
    asm volatile("ldmatrix.sync.aligned.m8n8.x4.shared.b16 {%0,%1,%2,%3}, [%4];"
                 : "=r"(u[0]), "=r"(u[1]), "=r"(u[2]), "=r"(u[3]) : "r"(a + S0) : "memory");
}
__device__ __forceinline__ void ldsm4t(uint32_t (&u)[4], uint32_t a) {
    asm volatile("ldmatrix.sync.aligned.m8n8.x4.trans.shared.b16 {%0,%1,%2,%3}, [%4];"
                 : "=r"(u[0]), "=r"(u[1]), "=r"(u[2]), "=r"(u[3]) : "r"(a + S0) : "memory");
}
__device__ __forceinline__ void stsm4(uint32_t a, uint32_t p0, uint32_t p1, uint32_t p2, uint32_t p3) {
    asm volatile("stmatrix.sync.aligned.m8n8.x4.shared.b16 [%0], {%1,%2,%3,%4};" ::"r"(a + S0), "r"(p0), "r"(p1), "r"(p2), "r"(p3) : "memory");
}
__device__ __forceinline__ void stsm4t(uint32_t a, uint32_t p0, uint32_t p1, uint32_t p2, uint32_t p3) {
    asm volatile("stmatrix.sync.aligned.m8n8.x4.trans.shared.b16 [%0], {%1,%2,%3,%4};" ::"r"(a + S0), "r"(p0), "r"(p1), "r"(p2), "r"(p3) : "memory");
}

#define R8(o) "+f"(d[o]), "+f"(d[o + 1]), "+f"(d[o + 2]), "+f"(d[o + 3]), "+f"(d[o + 4]), "+f"(d[o + 5]), "+f"(d[o + 6]), "+f"(d[o + 7])
template <uint32_t ALO, uint32_t BLO, uint64_t AHI = 8, uint64_t BHI = 48>
__device__ __forceinline__ void wgmma128(float (&d)[64]) {
    asm volatile(
        "wgmma.mma_async.sync.aligned.m64n128k16.f32.bf16.bf16 "
        "{%0,%1,%2,%3,%4,%5,%6,%7,%8,%9,%10,%11,%12,%13,%14,%15,%16,%17,%18,%19,%20,%21,%22,%23,%24,%25,%26,%27,%28,%29,%30,%31,"
        "%32,%33,%34,%35,%36,%37,%38,%39,%40,%41,%42,%43,%44,%45,%46,%47,%48,%49,%50,%51,%52,%53,%54,%55,%56,%57,%58,%59,%60,%61,%62,%63},"
        " %64, %65, 1, 1, 1, 0, 0;"
        : R8(0), R8(8), R8(16), R8(24), R8(32), R8(40), R8(48), R8(56)
        : "l"((AHI << 32) | ALO), "l"((BHI << 32) | BLO));
}
template <int S>
__device__ __forceinline__ void mma_stages(float (&d)[64], int conv, int tid, Scratch* gs) {
    constexpr uint32_t A = ((SM_ACT + S * 2 * CH_PITCH + 16) >> 4) | ((CH_PITCH >> 4) << 16);
    constexpr uint32_t B = (slot_addr(S % NS) >> 4) | (8u << 16);
    if (S == 0) {
        unsigned it = 0;
#pragma unroll 1
        while (!MMA0_WAIT(BAR(BAR_FULL), conv) && ++it < SPIN_LIMIT) {}
    }
    bool next_ok = true;
    constexpr uint32_t NEXT = S + 1 < NSTAGE ? BAR(BAR_FULL + S + 1) : BAR(BAR_EMB);
    const int npar = S + 1 < NSTAGE ? conv : 0;
    next_ok = mbar_test(NEXT, npar);
    if (S == 0 && tid == 0) TL(32 + conv * 24);
    asm volatile("wgmma.fence.sync.aligned;" ::: "memory");
    wgmma128<A, B>(d);
    wgmma128<A + 1, B + 16>(d);
    wgmma128<A + 2, B + 32>(d);
    asm volatile("wgmma.commit_group.sync.aligned;" ::: "memory");
    if (S >= LAG) {
        asm volatile("wgmma.wait_group.sync.aligned %0;" ::"n"(LAG) : "memory");
        if ((tid & 31) == 0) mbar_arrive(BAR(BAR_WEMPTY + (S + NS - LAG) % NS));
    }
    if (!next_ok) mbar_wait(NEXT, npar);
    if constexpr (S + 1 < NSTAGE) mma_stages<S + 1>(d, conv, tid, gs);
}

__device__ __forceinline__ void weight_load(uint4 (&t)[5], const __nv_bfloat16* w, int cta, int lane) {
    const char* base = reinterpret_cast<const char*>(w) + ((cta & 15) * 8 * C + (cta >> 4) * 16) * 18;
#pragma unroll
    for (int k = 0; k < 5; k++) {
        const int i = lane + 32 * k, row = (i * 57) >> 10;
        if (k < 4 || lane < 16) t[k] = __ldg(reinterpret_cast<const uint4*>(base + row * (C * 18 - 288) + i * 16));
    }
}
__device__ __forceinline__ void weight_block(uint32_t bounce, unsigned char* wt, int cta, int lane, bool readback, Scratch* gs) {
    unsigned char* dst = wt + (cta >> 4) * STAGE_BYTES + (cta & 15) * 768;
    if (lane < 16) {
        uint32_t v[36];
#pragma unroll
        for (int i = 0; i < 9; i++) {
            const uint4 q = lds128(bounce + (lane & 7) * 288 + (lane >> 3) * 144 + i * 16);
            v[4 * i] = q.x; v[4 * i + 1] = q.y; v[4 * i + 2] = q.z; v[4 * i + 3] = q.w;
        }
#pragma unroll
        for (int kyo = 0; kyo < 3; kyo++) {
#pragma unroll
            for (int kx = 0; kx < 3; kx++) {
                const int tap = ky_of(kyo) * 3 + kx;
                uint32_t o[4];
#pragma unroll
                for (int m = 0; m < 4; m++) {
                    const int i0 = 18 * m + tap, i1 = i0 + 9;
                    const uint32_t sel = ((i0 & 1) ? 0x32u : 0x10u) | ((i1 & 1) ? 0x7600u : 0x5400u);
                    o[m] = __byte_perm(v[i0 >> 1], v[i1 >> 1], sel);
                }
                *reinterpret_cast<uint4*>(dst + kyo * 8 * STAGE_BYTES + kx * 256 + lane * 16) = make_uint4(o[0], o[1], o[2], o[3]);
            }
        }
    }
    if (readback) {
        __syncwarp();
        unsigned acc = 0;
        if (lane < 24) {
#pragma unroll
            for (int i = 0; i < 3; i++) acc |= ld_relaxed(dst + i * 8 * STAGE_BYTES + lane * 32);
        }
        asm volatile("{\n.reg .pred p;\nsetp.eq.u32 p, %0, 0x9e3779b9;\n@p st.shared.u32 [%1], %0;\n}" ::"r"(acc), "r"(bounce + S0) : "memory");
    }
}
__device__ __forceinline__ uint32_t act2(uint32_t u, const float4& cf) {
    return pack_bf(silu_half(fmaf(bf_lo(u), cf.x, cf.z)), silu_half(fmaf(bf_hi(u), cf.y, cf.w)));
}
__device__ __forceinline__ void norm_unit(uint32_t (&u)[4], const float4& ca, const float4& cb) {
    u[0] = act2(u[0], ca); u[1] = act2(u[1], ca); u[2] = act2(u[2], cb); u[3] = act2(u[3], cb);
}
__device__ __forceinline__ void read_stats(uint32_t gst, float (&g)[8]) {
    asm volatile("ld.volatile.shared.v4.f32 {%0,%1,%2,%3}, [%4];" : "=f"(g[0]), "=f"(g[1]), "=f"(g[2]), "=f"(g[3]) : "r"(gst + S0) : "memory");
    asm volatile("ld.volatile.shared.v4.f32 {%0,%1,%2,%3}, [%4];" : "=f"(g[4]), "=f"(g[5]), "=f"(g[6]), "=f"(g[7]) : "r"(gst + 16 + S0) : "memory");
}
template <int T>
__device__ __forceinline__ void group_coefs(uint32_t gst, float (&g)[8], float4 (&cf)[8]) {
    float rs = g[2 * T], mr = g[2 * T + 1];
    if (!__all_sync(0xffffffffu, rs != 0.f)) {
        unsigned it = 0;
#pragma unroll 1
        do {
            asm volatile("ld.volatile.shared.v2.f32 {%0,%1}, [%2];" : "=f"(rs), "=f"(mr) : "r"(gst + 8 * T + S0) : "memory");
        } while (!__all_sync(0xffffffffu, rs != 0.f) && ++it < 8 * SPIN_LIMIT);
        if (T < 3) read_stats(gst, g);
    }
    float4 &ca = cf[2 * T], &cb = cf[2 * T + 1];
    ca.z = fmaf(-mr, ca.x, ca.z); ca.w = fmaf(-mr, ca.y, ca.w); ca.x *= rs; ca.y *= rs;
    cb.z = fmaf(-mr, cb.x, cb.z); cb.w = fmaf(-mr, cb.y, cb.w); cb.x *= rs; cb.y *= rs;
}
template <int FIRST, int N>
__device__ __forceinline__ void norm_block(uint32_t (&u)[4][4], float4 (&cf)[8], uint32_t act, uint32_t mask, uint32_t fbar, int lane) {
#pragma unroll
    for (int t = FIRST; t < FIRST + N; t++) {
        norm_unit(u[t], cf[2 * t], cf[2 * t + 1]);
        stsm4(act + t * 2 * KC_BYTES, u[t][0] & mask, u[t][1] & mask, u[t][2] & mask, u[t][3] & mask);
    }
    fence_async_smem();
    __syncwarp();
    if (lane < N) mbar_arrive(fbar + 16 * (FIRST + lane));
}
__device__ __forceinline__ void publish(uint32_t bar, int lane) {
    fence_async_smem();
    __syncwarp();
    if (lane == 0) mbar_arrive(bar);
}
template <int T>
__device__ __forceinline__ void next_unit(uint32_t (&u)[4][4], float4 (&cf)[8], uint32_t gst, float (&g)[8], uint32_t act, uint32_t fbar, int lane) {
    const bool have = __all_sync(0xffffffffu, g[2 * T] != 0.f);
    if (!have) publish(fbar + 16 * (T - 1), lane);
    group_coefs<T>(gst, g, cf);
    norm_unit(u[T], cf[2 * T], cf[2 * T + 1]);
    if (have) publish(fbar + 16 * (T - 1), lane);
    stsm4(act + T * 2 * KC_BYTES, u[T][0], u[T][1], u[T][2], u[T][3]);
}
__device__ __forceinline__ void stat_mma(float (&c)[4], uint32_t p, uint32_t q) {
    asm("mma.sync.aligned.m16n8k16.row.col.f32.bf16.bf16.f32 {%0,%1,%2,%3}, {%4,%5,%6,%5}, {%4,%6}, {%0,%1,%2,%3};"
        : "+f"(c[0]), "+f"(c[1]), "+f"(c[2]), "+f"(c[3]) : "r"(p), "r"(0x3f803f80u), "r"(q));
}
__device__ __forceinline__ void stat_store(const float (&c)[4], uint32_t dst, int lane) {
    const int g = lane >> 2, t = lane & 3;
    if (t == (g >> 1)) sts32f(dst + g * 4, (g & 1) ? c[1] : c[0]);
    if (g == 7) sts32f(dst + 32 + t * 4, c[2] + c[3]);
}
__device__ __forceinline__ float sum4(float4 v) { return (v.x + v.y) + (v.z + v.w); }
__device__ __forceinline__ void stat_publish(uint32_t src, float* acc, int lane, bool real) {
    const uint32_t a = src + (lane & 15) * 48;
    float q = sum4(lds128f(a)) + sum4(lds128f(a + 16)), sm = sum4(lds128f(a + 32));
    q += __shfl_xor_sync(0xffffffffu, q, 1); sm += __shfl_xor_sync(0xffffffffu, sm, 1);
    q += __shfl_xor_sync(0xffffffffu, q, 2); sm += __shfl_xor_sync(0xffffffffu, sm, 2);
    if (real && (lane & 19) == 0) red_add4(acc + lane, 1.f, sm, q, 1.f);
}
__device__ __forceinline__ void fence_acc(float (&d)[64]) {
#pragma unroll
    for (int i = 0; i < 64; i++) asm volatile("" : "+f"(d[i])::"memory");
}
__device__ __forceinline__ void ld_unit(uint32_t (&u)[4], const uint4* p) {
    asm volatile("ld.relaxed.gpu.global.v4.u32 {%0,%1,%2,%3}, [%4];" : "=r"(u[0]), "=r"(u[1]), "=r"(u[2]), "=r"(u[3]) : "l"(p) : "memory");
}

__device__ __noinline__ void side_jobs(const __nv_bfloat16* __restrict__ t_emb, const __nv_bfloat16* __restrict__ w_emb,
                                       const __nv_bfloat16* __restrict__ w2, Scratch* __restrict__ gs, unsigned clk0) {
    const int tid = threadIdx.x, warp = tid >> 5, lane = tid & 31, j = blockIdx.x;
    float tv = 0.f;
    if (lane < 24) tv = __bfloat162float(t_emb[(lane / 12) * E + j * 192 + warp * 12 + lane % 12]);
    if (tid == 0) {
        mbar_init(BAR(0), 1);
        mbar_expect(BAR(0), 192 * C * 2);
        fence_async_smem();
        while (clock32() - clk0 < SDELAY) {}
#pragma unroll
        for (int i = 0; i < 4; i++)
            asm volatile("cp.async.bulk.prefetch.L2.global [%0], 18432;" ::"l"(reinterpret_cast<const char*>(w2) + (j * 4 + i) * 18432) : "memory");
#pragma unroll
        for (int i = 0; i < 4; i++) bulk_g2s(S0 + SM_W + i * 12288, w_emb + (j * 192 + i * 48) * C, 12288, S0 + BAR(0));
    }
    if (j == 0 && tid < 32) gs->acc2[(tid >> 4) * LS + (tid & 15)] = 0.f;
    const float sv = silu_half(0.5f * tv);
    __syncthreads();
    mbar_wait(BAR(0), 0);
    float acc[8] = {0.f, 0.f, 0.f, 0.f, 0.f, 0.f, 0.f, 0.f};
#pragma unroll
    for (int i = 0; i < 12; i++) {
        const float2 wq = lds64f(SM_W + (warp * 12 + i) * 256 + lane * 8);
        const uint32_t wx = __float_as_uint(wq.x), wy = __float_as_uint(wq.y);
#pragma unroll
        for (int bb = 0; bb < 2; bb++) {
            const float sx = __shfl_sync(0xffffffffu, sv, bb * 12 + i);
            acc[4 * bb + 0] = fmaf(sx, bf_lo(wx), acc[4 * bb + 0]); acc[4 * bb + 1] = fmaf(sx, bf_hi(wx), acc[4 * bb + 1]);
            acc[4 * bb + 2] = fmaf(sx, bf_lo(wy), acc[4 * bb + 2]); acc[4 * bb + 3] = fmaf(sx, bf_hi(wy), acc[4 * bb + 3]);
        }
    }
    sts128f(SM_ACT + warp * 1024 + lane * 16, make_float4(acc[0], acc[1], acc[2], acc[3]));
    sts128f(SM_ACT + warp * 1024 + 512 + lane * 16, make_float4(acc[4], acc[5], acc[6], acc[7]));
    __syncthreads();
    if (tid < 128) {
        float2 sum = make_float2(0.f, 0.f);
#pragma unroll
        for (int w = 0; w < 16; w++) { const float2 p = lds64f(SM_ACT + w * 1024 + tid * 8); sum.x += p.x; sum.y += p.y; }
        *reinterpret_cast<float2*>(&gs->emb[j * NB * C + tid * 2]) = sum;
        bar_sync(1, 128);
        if (tid < 2) asm volatile("red.release.gpu.global.add.u32 [%0], 1;" ::"l"(&gs->wcnt[(2 * NB + tid) * LS]) : "memory");
    }
}

__global__ void __cluster_dims__(2, 1, 1) __launch_bounds__(NTHREADS, 1)
resblock_kernel(const __nv_bfloat16* __restrict__ w1, const __nv_bfloat16* __restrict__ x,
                const __nv_bfloat16* __restrict__ t_emb, const __nv_bfloat16* __restrict__ g1,
                const __nv_bfloat16* __restrict__ be1, const __nv_bfloat16* __restrict__ w_emb,
                const __nv_bfloat16* __restrict__ g2, const __nv_bfloat16* __restrict__ be2,
                const __nv_bfloat16* __restrict__ w2, __nv_bfloat16* __restrict__ out, Scratch* __restrict__ gs,
                const __grid_constant__ CUtensorMap xmap) {
    const unsigned clk0 = clock32();
    if (threadIdx.x == 480 && blockIdx.x >= NXTRA) TLG(1);
    const int tid = threadIdx.x, lane = tid & 31;
    const int cta = blockIdx.x - NXTRA, b = cta >> 6, r = cta & 63;
    uint4 v[5];
    if (tid < 32) weight_load(v, w1, cta & (NCTA - 1), lane);
    uint4 xv[8];
    const int wg4 = (tid >> 5) - 1;
    const bool early = tid >= 32 && wg4 < NLDG;
    if (early) {
        const char* src = reinterpret_cast<const char*>(x) + (uint32_t)((((b & 1) * C + wg4 * 32 + (lane >> 3)) * HW + r) * HW * 2 + (lane & 7) * 16);
        while (clock32() - clk0 < XDELAY + (wg4 >> 1) * XSTAG + (wg4 & 1) * XSTAG2) {}
#pragma unroll
        for (int i = 0; i < 8; i++) xv[i] = __ldg(reinterpret_cast<const uint4*>(src + i * (4 * HW * HW * 2)));
    }
    const int warp = __shfl_sync(0xffffffffu, tid >> 5, 0);
    if (cta < 0) { side_jobs(t_emb, w_emb, w2, gs, clk0); return; }

    if (warp != 4) asm volatile("barrier.cluster.arrive.relaxed.aligned;" ::: "memory");
    const bool has_outer = (r != 0) && (r != HW - 1);
    if (warp == 1 || warp == 2 || warp == 3 || warp == 5) {
        const int g = warp < 4 ? warp - 1 : 3;
        if (elect_one()) {
            if (g >= NLDG) asm volatile("prefetch.tensormap [%0];" ::"l"(&xmap) : "memory");
            mbar_init(BAR(BAR_X) + 8 * g, 1);
            if (g >= NLDG) mbar_expect(BAR(BAR_X) + 8 * g, 4096);
            fence_async_smem();
        }
        __syncwarp();
        bar_arrive(4, 256 + 32 + 128);
        if (g >= NLDG) {
            while (clock32() - clk0 < XDELAY + (g >> 1) * XSTAG + (g & 1) * XSTAG2) {}
            if (elect_one()) tma_x(SM_XOWN + g * 4096, &xmap, r, b * C + g * 32, BAR(BAR_X) + 8 * g);
            __syncwarp();
            mbar_wait(BAR(BAR_X) + 8 * g, 0);
#pragma unroll
            for (int k = 0; k < 8; k++) xv[k] = lds128(SM_XOWN + g * 4096 + k * 512 + lane * 16);
        }
        float c[8][4];
#pragma unroll
        for (int k = 0; k < 8; k++) {
            c[k][0] = c[k][1] = c[k][2] = c[k][3] = 0.f;
            stat_mma(c[k], xv[k].x, xv[k].y); stat_mma(c[k], xv[k].z, xv[k].w);
        }
#pragma unroll
        for (int i = 0; i < 4; i++) c[0][i] = ((c[0][i] + c[1][i]) + (c[2][i] + c[3][i])) + ((c[4][i] + c[5][i]) + (c[6][i] + c[7][i]));
        stat_store(c[0], SM_RED + g * 48, lane);
        __syncwarp();
        if (lane == 0) {
            const uint32_t a = SM_RED + g * 48;
            red_add4(&gs->acc1[b * LS + g * 4], 1.f, sum4(lds128f(a + 32)), sum4(lds128f(a)) + sum4(lds128f(a + 16)), 1.f);
            TL(74 + g);
        }
        if (g < NLDG) {
#pragma unroll
            for (int i = 0; i < 8; i++)
                sts128(SM_XOWN + g * 4096 + i * 512 + (lane >> 3) * 128 + (((lane & 7) ^ ((lane >> 3) + 4 * (i & 1))) << 4), xv[i]);
            __syncwarp();
            if (lane == 0) mbar_arrive(BAR(BAR_X) + 8 * g);
        }
    }
    if (warp == 4) {
            if (elect_one()) {
#pragma unroll
                for (int i = 0; i < NSTAGE; i++) mbar_init(BAR(BAR_FULL + i), (i >> 3) == 1 ? 1 : 5);
#pragma unroll
                for (int i = 0; i < NS + 2; i++) mbar_init(BAR(BAR_WEMPTY + i), 4);
#pragma unroll
                for (int i = BAR_STATS; i < BAR_X; i++) mbar_init(BAR(i), i == BAR_EMB ? 3 : 1);
                mbar_init(BAR(BAR_X + 4), 1);
                asm volatile("fence.mbarrier_init.release.cluster;" ::: "memory");
            }
            if (lane < 4) sts128(SM_GST + lane * 16, make_uint4(0, 0, 0, 0));
            __syncwarp();
            fence_async_smem();
            bar_arrive(0, 96);
            bar_arrive(5, 64);
            bar_arrive(4, 256 + 32 + 128);
            const uint4 z = make_uint4(0, 0, 0, 0);
#pragma unroll
            for (int i = 0; i < 2; i++) sts128(SM_ACT + (i * 16 + (lane >> 1)) * CH_PITCH + (lane & 1) * 16, z);
            if (lane < 4) sts128(SM_ACT + (2 + (lane >> 1)) * ROW_BYTES + (lane & 1) * 16, z);
            if (lane < 16) sts128(SM_ONES + lane * 16, make_uint4(lane < 8 ? 0x3f803f80u : 0u, 0, 0, 0));
            fence_async_smem();
            bar_arrive(7, 160);
            asm volatile("barrier.cluster.arrive.relaxed.aligned;" ::: "memory");
            if (lane == 0) TL(5);
            while (clock32() - clk0 < W2DELAY) {}
            weight_load(v, w2, cta, lane);
        }
    if (warp == 0 || warp == 4) {
        const int k = warp >> 2;
#pragma unroll
        for (int i = 0; i < 5; i++)
            if (i < 4 || lane < 16) sts128(SM_BNC + k * 2304 + (lane + 32 * i) * 16, v[i]);
        if (lane == 0) TL(k ? 14 : 81);
        __syncwarp();
        weight_block(SM_BNC + k * 2304, gs->wt + k * NSTAGE * STAGE_BYTES, cta, lane, true, gs);
        __syncwarp();
        if (lane == 0) TL(k ? 13 : 4);
        if (lane < 2) asm volatile("red.relaxed.gpu.global.add.u32 [%0], 1;" ::"l"(k ? &gs->wcnt[(NB + lane) * LS] : &gs->w1cnt[(lane * 8 + (cta >> 4)) * KS]) : "memory");
    }

    if (warp >= 8) {
        const int nw = warp - 8;
        if (nw < 2) {
            const uint2 ga = __ldg(reinterpret_cast<const uint2*>(nw ? g2 : g1) + lane), bt = __ldg(reinterpret_cast<const uint2*>(nw ? be2 : be1) + lane);
            sts128f(SM_COEF + nw * 1024 + lane * 32, make_float4(0.5f * bf_lo(ga.x), 0.5f * bf_hi(ga.x), 0.5f * bf_lo(bt.x), 0.5f * bf_hi(bt.x)));
            sts128f(SM_COEF + nw * 1024 + lane * 32 + 16, make_float4(0.5f * bf_lo(ga.y), 0.5f * bf_hi(ga.y), 0.5f * bf_lo(bt.y), 0.5f * bf_hi(bt.y)));
        }
        bar_sync(4, 256 + 32 + 128);
        const int par = nw >> 2, wq = nw & 3;
        const uint32_t act_off = SM_ACT + (par * 2 + (lane >> 4)) * CH_PITCH + (2 + wq * 16 + (lane & 15)) * 16;
        const uint32_t stg_off = (par * 16 + (lane >> 4) * 8 + (lane & 7)) * 128 + (((2 * wq + ((lane >> 3) & 1)) ^ (lane & 7)) << 4);
        const uint32_t cfa = SM_COEF + par * 128 + (lane & 3) * 16;
        const uint32_t fbar = BAR(BAR_FULL) + 8 * par;
        uint4* inbox = gs->box + cta * 1024 + nw * 32 + lane;
#pragma unroll 1
        for (int conv = 0; conv < 2; conv++) {
            uint32_t u[4][4], w[4][4];
            float4 cf[8];
            if (conv == 0) {
#pragma unroll
                for (int i = 0; i < 4; i++) { mbar_wait(BAR(BAR_X + i), 0); ldsm4t(u[i], SM_XOWN + stg_off + i * 4096); }
            } else {
                mbar_wait(BAR(BAR_HW), 0);
#pragma unroll
                for (int i = 0; i < 4; i++) ldsm4(u[i], act_off + i * 2 * KC_BYTES);
            }
#pragma unroll
            for (int i = 0; i < 8; i++) cf[i] = lds128f(cfa + conv * 1024 + (i >> 1) * 256 + (i & 1) * 64);
            const uint32_t gst = SM_GST + conv * 32;
            float gv[8] = {0.f, 0.f, 0.f, 0.f, 0.f, 0.f, 0.f, 0.f};
            group_coefs<0>(gst, gv, cf);
            if (tid == 256) TL(22 + conv * 4);
            if (par) { const unsigned c1 = clock32(); while (clock32() - c1 < PDELAY) {} }
            norm_block<0, 1>(u, cf, act_off, ~0u, fbar, lane);
            if (tid == 256) TL(8 + conv * 8);
            group_coefs<1>(gst, gv, cf);
            norm_block<1, 1>(u, cf, act_off, ~0u, fbar, lane);
            group_coefs<2>(gst, gv, cf);
            norm_unit(u[2], cf[4], cf[5]);
            stsm4(act_off + 4 * KC_BYTES, u[2][0], u[2][1], u[2][2], u[2][3]);
            next_unit<3>(u, cf, gst, gv, act_off, fbar, lane);
            publish(fbar + 48, lane);
            if (tid == 256) TL(84 + conv);
            if (has_outer) {
                mbar_wait(BAR(BAR_X + 4), conv);
                if (conv == 0) {
#pragma unroll
                    for (int i = 0; i < 4; i++) ldsm4t(w[i], SM_XOUT + stg_off + i * 4096);
                } else {
#pragma unroll
                    for (int i = 0; i < 4; i++) {
                        const uint4 q = lds128(SM_XOWN + (tid - 256) * 16 + i * 4096);
                        w[i][0] = q.x; w[i][1] = q.y; w[i][2] = q.z; w[i][3] = q.w;
                    }
                    unsigned it = 0;
                    while (true) {
                        bool ok = true;
#pragma unroll
                        for (int i = 0; i < 16; i++) ok = ok && w[i >> 2][i & 3] != 0;
                        if (__all_sync(0xffffffffu, ok) || ++it > SPIN_LIMIT) break;
#pragma unroll
                        for (int i = 0; i < 4; i++) ld_unit(w[i], inbox + i * 256);
                    }
#pragma unroll
                    for (int i = 0; i < 16; i++) w[i >> 2][i & 3] = ~w[i >> 2][i & 3];
                }
            }
            if (conv == 0) {
                bar_sync(3, 256);
                if (nw == 0) sts128(SM_ACT + 2 * ROW_BYTES + (lane >> 1) * CH_PITCH + (lane & 1) * 16, make_uint4(0, 0, 0, 0));
            }
            if (tid == 256) TL(24 + conv * 4);
            norm_block<0, 2>(w, cf, act_off + 2 * ROW_BYTES, has_outer ? ~0u : 0u, fbar + 128, lane);
            if (tid == 256) TL(88 + conv);
            norm_block<2, 2>(w, cf, act_off + 2 * ROW_BYTES, has_outer ? ~0u : 0u, fbar + 128, lane);
            if (tid == 256) TL(23 + conv * 4);
        }
        if (has_outer) {
            mbar_wait(BAR(BAR_FULL + NSTAGE - 1), 1);
#pragma unroll
            for (int i = 0; i < 4; i++) inbox[i * 256] = make_uint4(0, 0, 0, 0);
        }
        {
            const int oc0 = par * 64 + ((tid & 127) >> 3), seg = lane & 7;
            __nv_bfloat16* dst = out + ((size_t)(b * C + oc0) * HW + r) * HW + seg * 8;
            const uint32_t src = SM_XOWN + oc0 * 128 + ((seg ^ (oc0 & 7)) << 4);
            bar_sync(par ? 1 : 6, 128 + 128);
#pragma unroll
            for (int i = 0; i < 4; i++) *reinterpret_cast<uint4*>(dst + (size_t)i * 16 * HW * HW) = lds128(src + i * 2048);
            if (tid == 384) { TL(20); TLG(21); }
        }
    } else if (warp < 4) {
        const int wq = warp;
        bar_sync(7, 160);

        const uint32_t xbase = SM_XOWN + ((lane >> 4) * 8 + (lane & 7)) * 128 + (((2 * wq + ((lane >> 3) & 1)) ^ (lane & 7)) << 4);
        float d[64];
#pragma unroll
        for (int i = 0; i < 64; i++) d[i] = 0.f;
#pragma unroll 1
        for (int conv = 0; conv < 2; conv++) {
            fence_acc(d);
            mma_stages<0>(d, conv, tid, gs);
            if (conv == 0) {
                asm volatile("wgmma.fence.sync.aligned;" ::: "memory");
                wgmma128<(SM_ONES >> 4) | (8u << 16), (SM_EMB >> 4), 0, 8>(d);
                asm volatile("wgmma.commit_group.sync.aligned;" ::: "memory");
            }
            asm volatile("wgmma.wait_group.sync.aligned 0;" ::: "memory");
            fence_acc(d);
            if (tid == 0) TL(10 + conv * 8);
            if (conv == 0) {
            uint32_t hp[32];
#pragma unroll
            for (int i = 0; i < 32; i++) hp[i] = pack_bf(d[2 * i], d[2 * i + 1]);
#pragma unroll
            for (int g = 0; g < 4; g++) {
                float c[4] = {0.f, 0.f, 0.f, 0.f};
#pragma unroll
                for (int i = 0; i < 4; i++) stat_mma(c, hp[8 * g + 2 * i], hp[8 * g + 2 * i + 1]);
                stat_store(c, SM_RED + (g * 4 + wq) * 48, lane);
            }
            bar_sync(2, 128);
            if (wq == 0) stat_publish(SM_RED, &gs->acc2[b * LS], lane, true);
            if (tid == 0) TL(11);
            const uint32_t hbase = SM_ACT + (lane >> 4) * CH_PITCH + (2 + wq * 16 + (lane & 15)) * 16;
#pragma unroll
            for (int kc = 0; kc < 8; kc++) stsm4(hbase + kc * 2 * CH_PITCH, hp[4 * kc], hp[4 * kc + 1], hp[4 * kc + 2], hp[4 * kc + 3]);
            __syncwarp();
            if (lane == 0) mbar_arrive(BAR(BAR_HW));
            if (lane < LAG) mbar_arrive(BAR(BAR_WEMPTY + (NSTAGE - LAG) % NS) + 8 * lane);
            if (has_outer) {
                uint4* outbox = gs->box + (cta + ((r & 1) ? 1 : -1)) * 1024 + tid;
#pragma unroll
                for (int kc = 0; kc < 8; kc++) outbox[kc * 128] = make_uint4(~hp[4 * kc], ~hp[4 * kc + 1], ~hp[4 * kc + 2], ~hp[4 * kc + 3]);
            }
            if (tid == 0) TL(12);
#pragma unroll
            for (int kc = 0; kc < 8; kc++) {
                uint32_t p[4];
                ldsm4t(p, xbase + kc * 2048);
#pragma unroll
                for (int i = 0; i < 4; i++) { d[8 * kc + 2 * i] = bf_lo(p[i]); d[8 * kc + 2 * i + 1] = bf_hi(p[i]); }
            }
            }
            fence_acc(d);
#pragma unroll
            for (int kc = 0; kc < 8; kc++) {
                stsm4t(xbase + kc * 2048, pack_bf(d[8 * kc], d[8 * kc + 1]), pack_bf(d[8 * kc + 2], d[8 * kc + 3]),
                       pack_bf(d[8 * kc + 4], d[8 * kc + 5]), pack_bf(d[8 * kc + 6], d[8 * kc + 7]));
                if ((kc & 3) == 3)
                    asm volatile("{\n.reg .pred p;\nsetp.ne.s32 p, %1, 0;\n@p bar.arrive %0, 256;\n}" ::"r"(kc == 3 ? 6 : 1), "r"(conv) : "memory");
            }
            fence_async_smem();
            __syncwarp();
            if (lane == 0) mbar_arrive(BAR(BAR_XFREE));
        }
        {
        }
    } else if (warp < 6) {
        if (warp == 5) {
            bar_sync(5, 64);
            mbar_wait(BAR(BAR_FULL + OAFTER), 0);
            if (has_outer && elect_one()) {
                mbar_expect(BAR(BAR_X + 4), 16384);
#pragma unroll
                for (int i = 0; i < 4; i++) tma_x(SM_XOUT + i * 4096, &xmap, r + ((r & 1) ? 1 : -1), b * C + i * 32, BAR(BAR_X + 4));
            }
            __syncwarp();
            asm volatile("barrier.cluster.wait.acquire.aligned;" ::: "memory");
            const uint32_t peer = (r & 1) ^ 1;
            const uint32_t self0 = mapa(0, r & 1), peer0 = mapa(0, peer);
#pragma unroll 1
            for (int conv = 0; conv < 2; conv++) {
#pragma unroll 1
                for (int kc = 0; kc < 8; kc++) {
                    mbar_wait(BAR(BAR_FULL) + 8 * kc, conv);
                    if (elect_one())
                        asm volatile("cp.async.bulk.shared::cluster.shared::cta.mbarrier::complete_tx::bytes [%0], [%1], %2, [%3];"
                                     ::"r"(peer0 + SM_ACT + ROW_BYTES + kc * KC_BYTES), "r"(self0 + SM_ACT + kc * KC_BYTES), "r"(KC_BYTES),
                                       "r"(peer0 + BAR(BAR_FULL + 8) + 8 * kc) : "memory");
                }
                if (lane == 0) TL(86 + conv);
#pragma unroll 1
                for (int kc = 0; kc < 8; kc++) mbar_wait(BAR(BAR_FULL + 8) + 8 * kc, conv);
                if (lane == 0)
                    asm volatile("mbarrier.arrive.relaxed.cluster.shared::cluster.b64 _, [%0];" ::"r"(peer0 + (conv ? BAR(BAR_ACK) : BAR(BAR_EMB))) : "memory");
            }
            mbar_wait(BAR(BAR_ACK), 0);
        } else {
            mbar_wait(BAR(BAR_STATS), 0);
            unsigned it = 0;
            while (ld_relaxed(&gs->wcnt[(2 * NB + b) * LS]) < (unsigned)NXTRA && ++it < SPIN_LIMIT) __nanosleep(100);
            fence_acquire();
            float ev[4] = {0.f, 0.f, 0.f, 0.f};
#pragma unroll
            for (int j = 0; j < NXTRA; j++) {
                const uint4 ef = ld_relaxed_v4(&gs->emb[(j * NB + b) * C + lane * 4]);
                ev[0] += __uint_as_float(ef.x); ev[1] += __uint_as_float(ef.y); ev[2] += __uint_as_float(ef.z); ev[3] += __uint_as_float(ef.w);
            }
#pragma unroll
            for (int i = 0; i < 4; i++) {
                const float hi = bf_lo(pack_bf(ev[i], 0.f));
                sts128(SM_EMB + (lane * 4 + i) * 16, make_uint4(pack_bf(hi, ev[i] - hi), 0, 0, 0));
            }
            fence_async_smem();
            __syncwarp();
            if (lane == 0) { mbar_arrive(BAR(BAR_EMB)); TL(19); }
        }
    } else if (warp == 6) {
        bar_sync(0, 96);
        const uint32_t ebytes = STAGE_BYTES + ((lane >> 3) == 1 ? KC_BYTES : 0);
        if (lane < NSTAGE) mbar_expect(BAR(BAR_FULL) + 8 * lane, ebytes);
        const int swap = (r & 1) ? 0 : 8 * STAGE_BYTES;
        unsigned it = 0;
        {
            int g = 0;
            const unsigned* cnt = &gs->w1cnt[(b * 8 + (lane & 7)) * KS];
            unsigned cv = ld_relaxed(cnt);
#pragma unroll 1
            while (g < NS) {
                unsigned ready = __ballot_sync(0xffffffffu, cv >= 16u);
                if (ready != ~0u) cv = ld_relaxed(cnt);
                ready >>= g;
                if (++it > SPIN_LIMIT) ready = ~0u;
                if (!(ready & 1)) continue;
                fence_async_global();
                if (lane == 0) TL(g ? 3 : 6);
#pragma unroll 1
                for (; (ready & 1) && g < NS; g++, ready >>= 1)
                    if (elect_one())
                        bulk_g2s(S0 + SM_W + g * STAGE_BYTES, gs->wt + g * STAGE_BYTES + (g >= 8 ? swap : 0), STAGE_BYTES, S0 + BAR(BAR_FULL) + 8 * g);
            }
        }
#pragma unroll 1
        for (int q = 3; q < 12; q++) {
            const int conv = q >= 6, qs = conv ? q - 6 : q, sl = q % 3;
            const unsigned char* wsrc = gs->wt + q * 4 * STAGE_BYTES + (qs < 2 ? 0 : (qs < 4 ? swap : -swap));
            const uint32_t par = (q / 3 - 1) & 1;
            if (q == 6) {
                it = 0;
                while (ld_relaxed(&gs->wcnt[(NB + b) * LS]) < (unsigned)NCTA && ++it < SPIN_LIMIT) {}
                fence_acquire();
                fence_async_global();
                if (lane == 0) { mbar_arrive(BAR(BAR_EMB)); TL(2); }
            }
#pragma unroll
            for (int i = 0; i < 4; i++) {
                mbar_wait(BAR(BAR_WEMPTY + i) + 32 * sl, par);
                if (i == 0 && (q == 6 || q == 9)) {
                    if ((lane >= NS) == (q == 9) && lane < NSTAGE) mbar_expect(BAR(BAR_FULL) + 8 * lane, ebytes);
                    __syncwarp();
                }
                if (elect_one())
                    bulk_g2s(S0 + SM_W + (sl * 4 + i) * STAGE_BYTES, wsrc + i * STAGE_BYTES, STAGE_BYTES, S0 + BAR(BAR_FULL + i) + 32 * qs);
            }
        }
    } else {
        bar_sync(0, 96);
#pragma unroll 1
        for (int conv = 0; conv < 2; conv++) {
            if (conv == 1) mbar_wait(BAR(BAR_HW), 0);
            const float* asrc = (conv ? gs->acc2 : gs->acc1) + b * LS + (lane & 3) * 4;
            unsigned it = 0;
#pragma unroll 1
            while (true) {
                const uint4 f = ld_relaxed_v4(asrc);
                const bool ok = ((f.x == 0x42800000u) & (f.w == 0x42800000u)) || ++it > SPIN_LIMIT;
                if (ok && lane < 4) {
                    const float inv_n = 1.0f / (32.0f * HW * HW);
                    const float mean = __uint_as_float(f.y) * inv_n;
                    float rs;
                    asm("rsqrt.approx.ftz.f32 %0, %1;" : "=f"(rs) : "f"(fmaxf(fmaf(-mean, mean, __uint_as_float(f.z) * inv_n), 0.f) + 1e-5f));
                    asm volatile("st.shared.v2.f32 [%0], {%1,%2};" ::"r"(S0 + SM_GST + conv * 32 + lane * 8), "f"(rs == 0.f ? 1e-38f : rs), "f"(mean * rs) : "memory");
                }
                if (__all_sync(0xffffffffu, ok)) break;
            }
            if (lane == 0) { mbar_arrive(BAR(BAR_STATS)); TL(7 + conv * 8); }
        }
        mbar_wait(BAR(BAR_XFREE), 0);
        if (has_outer && elect_one()) {
            mbar_expect(BAR(BAR_X + 4), 16384);
            bulk_g2s(S0 + SM_XOWN, gs->box + cta * 1024, 16384, S0 + BAR(BAR_X + 4));
        }
        if (r == 0) {
            if (lane < 16) gs->acc1[b * LS + lane] = 0.f;
            if (lane < 3) gs->wcnt[(lane * NB + b) * LS] = 0;
            if (lane < 8) gs->w1cnt[(b * 8 + lane) * KS] = 0;
        }
    }
}

}

extern "C" void kernel_launch(void* const* d_in, const int* in_sizes, int n_in, void* d_out, int out_size) {
    (void)in_sizes; (void)n_in; (void)out_size;
    typedef CUresult (*EncodeFn)(CUtensorMap*, CUtensorMapDataType, cuuint32_t, void*, const cuuint64_t*, const cuuint64_t*,
                                 const cuuint32_t*, const cuuint32_t*, CUtensorMapInterleave, CUtensorMapSwizzle,
                                 CUtensorMapL2promotion, CUtensorMapFloatOOBfill);
    static Scratch* gs = nullptr;
    static EncodeFn encode = nullptr;
    if (!gs) {
        cudaFuncSetAttribute(resblock_kernel, cudaFuncAttributeMaxDynamicSharedMemorySize, SM_TOTAL);
        cudaGetSymbolAddress((void**)&gs, g_scratch);
        cudaDriverEntryPointQueryResult qr;
        cudaGetDriverEntryPoint("cuTensorMapEncodeTiled", (void**)&encode, cudaEnableDefault, &qr);
    }
    CUtensorMap xmap;
    const cuuint64_t dims[3] = {HW, HW, NB * C}, strides[2] = {HW * 2, HW * HW * 2};
    const cuuint32_t box[3] = {HW, 1, 32}, es[3] = {1, 1, 1};
    encode(&xmap, CU_TENSOR_MAP_DATA_TYPE_BFLOAT16, 3, d_in[0], dims, strides, box, es, CU_TENSOR_MAP_INTERLEAVE_NONE,
           CU_TENSOR_MAP_SWIZZLE_128B, CU_TENSOR_MAP_L2_PROMOTION_NONE, CU_TENSOR_MAP_FLOAT_OOB_FILL_NONE);
    resblock_kernel<<<NCTA + NXTRA, NTHREADS, SM_TOTAL>>>(
        (const __nv_bfloat16*)d_in[4], (const __nv_bfloat16*)d_in[0], (const __nv_bfloat16*)d_in[1],
        (const __nv_bfloat16*)d_in[2], (const __nv_bfloat16*)d_in[3], (const __nv_bfloat16*)d_in[5],
        (const __nv_bfloat16*)d_in[6], (const __nv_bfloat16*)d_in[7], (const __nv_bfloat16*)d_in[8],
        (__nv_bfloat16*)d_out, gs, xmap);
}
```

```cpp
#include <cuda_runtime.h>
#include <cuda.h>
#include <cuda_bf16.h>
#include <stdint.h>

namespace {

constexpr int C = 128, HW = 64, NB = 2, E = 768;
constexpr int NCTA = NB * HW;
constexpr int NXTRA = 4;
constexpr int NTHREADS = 16 * 32;
constexpr int CH_PITCH = 66 * 16;
constexpr int ROW_BYTES = 16 * CH_PITCH;
constexpr int STEP_BYTES = 4096;
constexpr int STAGE_BYTES = 3 * STEP_BYTES;
constexpr int NSTAGE = 24;
constexpr int KC_BYTES = 2 * CH_PITCH;
constexpr int NS = 12;
constexpr int LAG = 1;
#define XDELAY 400
#define HDELAY 600
#define SEQ 0
#define MMA0_WAIT mbar_try
#define NPOLL 1
#define PD2 0
#define ODELAY 100
#define NLDG 2
#define PSTAG -1
#define PDELAY0 400
#define PDELAY 60
#define RB 1
#define XSTAG2 400
#define XSTAG 800
#define HSEND 0
#define SDELAY 600
#define OAFTER 0
#define W2DELAY 2400

constexpr uint32_t SMEM_BASE = 0x400;
constexpr uint32_t SM_XOWN = SMEM_BASE;
constexpr uint32_t SM_ACT = SM_XOWN + 16384 + 512;
constexpr uint32_t SM_XOUT = SM_ACT + 2 * ROW_BYTES + 512;
static_assert(SM_XOUT % 1024 == 0, "swizzle atom alignment");
constexpr uint32_t SM_W = SM_ACT + 3 * ROW_BYTES + 128;
__host__ __device__ constexpr uint32_t slot_addr(int slot) { return SM_W + slot * STAGE_BYTES; }
constexpr uint32_t SM_COEF = SM_W + NS * STAGE_BYTES;
constexpr uint32_t SM_GST = SM_COEF + 2048;
constexpr uint32_t SM_EMB = SM_GST + 128;
constexpr uint32_t SM_ONES = SM_EMB + 2048;
constexpr uint32_t SM_RED = SM_ONES + 256;
constexpr uint32_t SM_BNC = SM_RED + 1536;
constexpr uint32_t SM_BAR = SM_BNC + 2 * 2304;
constexpr int BAR_FULL = 0, BAR_WEMPTY = NSTAGE, BAR_HW = BAR_WEMPTY + NS, BAR_XFREE = BAR_HW + 1, BAR_STATS = BAR_XFREE + 1,
              BAR_EMB = BAR_STATS + 1, BAR_ACK = BAR_EMB + 1, BAR_X = BAR_ACK + 1  , NBAR = BAR_X + 5;
constexpr int SM_TOTAL = SM_BAR + NBAR * 8 - SMEM_BASE;
static_assert(SM_TOTAL <= 232448, "smem");
static_assert(NBAR <= 96, "barrier init");
__host__ __device__ constexpr uint32_t BAR(int i) { return SM_BAR + 8 * i; }
__host__ __device__ constexpr int ky_of(int kyo) { return kyo == 0 ? 1 : (kyo == 1 ? 0 : 2); }

constexpr unsigned SPIN_LIMIT = 1u << 16;

#define LS 1056
#define GS1 4
#define PD 0
#define FWD0 0
#define KS 32
struct Scratch {
    float acc1[NB * LS];
    float acc2[NB * LS];
    unsigned wcnt[3 * NB * LS];
    unsigned w1cnt[NB * 8 * KS];
    float emb[NXTRA * NB * C];
    alignas(1024) unsigned char wt[2 * NSTAGE * STAGE_BYTES];
    uint4 box[NCTA * 1024];
};
__device__ __align__(1024) Scratch g_scratch;
#define TL(i) do {} while (0)
#define TLG(i) do {} while (0)

__device__ __forceinline__ unsigned clock32() { unsigned c; asm volatile("mov.u32 %0, %%clock;" : "=r"(c)); return c; }
__device__ __forceinline__ uint32_t mapa(uint32_t a, uint32_t rank) {
    uint32_t d;
    asm("mapa.shared::cluster.u32 %0, %1, %2;" : "=r"(d) : "r"(a), "r"(rank));
    return d;
}
#define S0 mapa(0, blockIdx.x & 1)
__device__ __forceinline__ void mbar_init(uint32_t bar, int cnt) {
    asm volatile("mbarrier.init.shared::cta.b64 [%0], %1;" ::"r"(bar + S0), "r"(cnt) : "memory");
}
__device__ __forceinline__ void mbar_arrive(uint32_t bar) {
    asm volatile("mbarrier.arrive.shared::cta.b64 _, [%0];" ::"r"(bar + S0) : "memory");
}
__device__ __forceinline__ void mbar_expect(uint32_t bar, uint32_t bytes) {
    asm volatile("mbarrier.arrive.expect_tx.shared::cta.b64 _, [%0], %1;" ::"r"(bar + S0), "r"(bytes) : "memory");
}
__device__ __forceinline__ bool mbar_try(uint32_t bar, uint32_t par) {
    uint32_t ok;
    asm volatile("{\n.reg .pred p;\nmbarrier.try_wait.parity.shared::cta.b64 p, [%1], %2;\nselp.u32 %0, 1, 0, p;\n}"
                 : "=r"(ok) : "r"(bar + S0), "r"(par) : "memory");
    return ok;
}
__device__ __forceinline__ bool mbar_test(uint32_t bar, uint32_t par) {
    uint32_t ok;
    asm volatile("{\n.reg .pred p;\nmbarrier.test_wait.parity.shared::cta.b64 p, [%1], %2;\nselp.u32 %0, 1, 0, p;\n}"
                 : "=r"(ok) : "r"(bar + S0), "r"(par) : "memory");
    return ok;
}
__device__ __forceinline__ void mbar_wait(uint32_t bar, uint32_t par) {
    unsigned it = 0;
#pragma unroll 1
    while (!mbar_try(bar, par) && ++it < SPIN_LIMIT) {}
}
__device__ __forceinline__ bool elect_one() {
    uint32_t p;
    asm volatile("{\n.reg .pred p;\nelect.sync _|p, 0xffffffff;\nselp.u32 %0, 1, 0, p;\n}" : "=r"(p));
    return p;
}
__device__ __forceinline__ void fence_async_smem() { asm volatile("fence.proxy.async.shared::cta;" ::: "memory"); }
__device__ __forceinline__ void fence_async_global() { asm volatile("fence.proxy.async.global;" ::: "memory"); }
__device__ __forceinline__ void fence_acquire() { asm volatile("fence.acquire.gpu;" ::: "memory"); }
__device__ __forceinline__ void bar_sync(int id, int n) { asm volatile("bar.sync %0, %1;" ::"r"(id), "r"(n) : "memory"); }
__device__ __forceinline__ void bar_arrive(int id, int n) { asm volatile("bar.arrive %0, %1;" ::"r"(id), "r"(n) : "memory"); }
__device__ __forceinline__ void bulk_g2s(uint32_t dst, const void* src, uint32_t bytes, uint32_t bar) {
    asm volatile("cp.async.bulk.shared::cluster.global.mbarrier::complete_tx::bytes [%0], [%1], %2, [%3];"
                 ::"r"(dst), "l"(src), "r"(bytes), "r"(bar) : "memory");
}
__device__ __forceinline__ void tma_x(uint32_t dst, const CUtensorMap* tm, int row, int ch, uint32_t bar) {
    asm volatile("cp.async.bulk.tensor.3d.shared::cluster.global.mbarrier::complete_tx::bytes [%0], [%1, {%2, %3, %4}], [%5];"
                 ::"r"(dst + S0), "l"(tm), "r"(0), "r"(row), "r"(ch), "r"(bar + S0) : "memory");
}
__device__ __forceinline__ uint4 ld_relaxed_v4(const void* p) {
    uint4 v;
    asm volatile("ld.relaxed.gpu.global.v4.u32 {%0,%1,%2,%3}, [%4];" : "=r"(v.x), "=r"(v.y), "=r"(v.z), "=r"(v.w) : "l"(p) : "memory");
    return v;
}
__device__ __forceinline__ unsigned ld_relaxed(const void* p) {
    unsigned v;
    asm volatile("ld.relaxed.gpu.global.u32 %0, [%1];" : "=r"(v) : "l"(p) : "memory");
    return v;
}
__device__ __forceinline__ void red_add4(float* p, float a, float b, float c, float d) {
    asm volatile("red.relaxed.gpu.global.add.v4.f32 [%0], {%1,%2,%3,%4};" ::"l"(p), "f"(a), "f"(b), "f"(c), "f"(d) : "memory");
}
__device__ __forceinline__ void sts128(uint32_t a, uint4 v) {
    asm volatile("st.shared.v4.u32 [%0], {%1,%2,%3,%4};" ::"r"(a + S0), "r"(v.x), "r"(v.y), "r"(v.z), "r"(v.w) : "memory");
}
__device__ __forceinline__ void sts128f(uint32_t a, float4 v) {
    asm volatile("st.shared.v4.f32 [%0], {%1,%2,%3,%4};" ::"r"(a + S0), "f"(v.x), "f"(v.y), "f"(v.z), "f"(v.w) : "memory");
}
__device__ __forceinline__ void sts32f(uint32_t a, float v) { asm volatile("st.shared.f32 [%0], %1;" ::"r"(a + S0), "f"(v) : "memory"); }
__device__ __forceinline__ uint4 lds128(uint32_t a) {
    uint4 v;
    asm volatile("ld.shared.v4.u32 {%0,%1,%2,%3}, [%4];" : "=r"(v.x), "=r"(v.y), "=r"(v.z), "=r"(v.w) : "r"(a + S0) : "memory");
    return v;
}
__device__ __forceinline__ float4 lds128f(uint32_t a) {
    float4 v;
    asm volatile("ld.shared.v4.f32 {%0,%1,%2,%3}, [%4];" : "=f"(v.x), "=f"(v.y), "=f"(v.z), "=f"(v.w) : "r"(a + S0) : "memory");
    return v;
}
__device__ __forceinline__ float2 lds64f(uint32_t a) {
    float2 v;
    asm volatile("ld.shared.v2.f32 {%0,%1}, [%2];" : "=f"(v.x), "=f"(v.y) : "r"(a + S0) : "memory");
    return v;
}
__device__ __forceinline__ float bf_lo(uint32_t u) { return __uint_as_float(u << 16); }
__device__ __forceinline__ float bf_hi(uint32_t u) { return __uint_as_float(u & 0xffff0000u); }
__device__ __forceinline__ uint32_t pack_bf(float lo, float hi) {
    uint32_t r;
    asm("cvt.rn.bf16x2.f32 %0, %1, %2;" : "=r"(r) : "f"(hi), "f"(lo));
    return r;
}
__device__ __forceinline__ float tanh_fast(float x) {
    float r;
    asm("tanh.approx.f32 %0, %1;" : "=f"(r) : "f"(x));
    return r;
}
__device__ __forceinline__ float silu_half(float h) { return fmaf(h, tanh_fast(h), h); }
__device__ __forceinline__ void ldsm4(uint32_t (&u)[4], uint32_t a) {
    asm volatile("ldmatrix.sync.aligned.m8n8.x4.shared.b16 {%0,%1,%2,%3}, [%4];"
                 : "=r"(u[0]), "=r"(u[1]), "=r"(u[2]), "=r"(u[3]) : "r"(a + S0) : "memory");
}
__device__ __forceinline__ void ldsm4t(uint32_t (&u)[4], uint32_t a) {
    asm volatile("ldmatrix.sync.aligned.m8n8.x4.trans.shared.b16 {%0,%1,%2,%3}, [%4];"
                 : "=r"(u[0]), "=r"(u[1]), "=r"(u[2]), "=r"(u[3]) : "r"(a + S0) : "memory");
}
__device__ __forceinline__ void stsm4(uint32_t a, uint32_t p0, uint32_t p1, uint32_t p2, uint32_t p3) {
    asm volatile("stmatrix.sync.aligned.m8n8.x4.shared.b16 [%0], {%1,%2,%3,%4};" ::"r"(a + S0), "r"(p0), "r"(p1), "r"(p2), "r"(p3) : "memory");
}
__device__ __forceinline__ void stsm4t(uint32_t a, uint32_t p0, uint32_t p1, uint32_t p2, uint32_t p3) {
    asm volatile("stmatrix.sync.aligned.m8n8.x4.trans.shared.b16 [%0], {%1,%2,%3,%4};" ::"r"(a + S0), "r"(p0), "r"(p1), "r"(p2), "r"(p3) : "memory");
}

#define R8(o) "+f"(d[o]), "+f"(d[o + 1]), "+f"(d[o + 2]), "+f"(d[o + 3]), "+f"(d[o + 4]), "+f"(d[o + 5]), "+f"(d[o + 6]), "+f"(d[o + 7])
template <uint32_t ALO, uint32_t BLO, uint64_t AHI = 8, uint64_t BHI = 48>
__device__ __forceinline__ void wgmma128(float (&d)[64]) {
    asm volatile(
        "wgmma.mma_async.sync.aligned.m64n128k16.f32.bf16.bf16 "
        "{%0,%1,%2,%3,%4,%5,%6,%7,%8,%9,%10,%11,%12,%13,%14,%15,%16,%17,%18,%19,%20,%21,%22,%23,%24,%25,%26,%27,%28,%29,%30,%31,"
        "%32,%33,%34,%35,%36,%37,%38,%39,%40,%41,%42,%43,%44,%45,%46,%47,%48,%49,%50,%51,%52,%53,%54,%55,%56,%57,%58,%59,%60,%61,%62,%63},"
        " %64, %65, 1, 1, 1, 0, 0;"
        : R8(0), R8(8), R8(16), R8(24), R8(32), R8(40), R8(48), R8(56)
        : "l"((AHI << 32) | ALO), "l"((BHI << 32) | BLO));
}
template <int S>
__device__ __forceinline__ void mma_stages(float (&d)[64], int conv, int tid, Scratch* gs) {
    constexpr uint32_t A = ((SM_ACT + S * 2 * CH_PITCH + 16) >> 4) | ((CH_PITCH >> 4) << 16);
    constexpr uint32_t B = (slot_addr(S % NS) >> 4) | (8u << 16);
    if (S == 0) {
        unsigned it = 0;
#pragma unroll 1
        while (!MMA0_WAIT(BAR(BAR_FULL), conv) && ++it < SPIN_LIMIT) {}
    }
    bool next_ok = true;
    constexpr uint32_t NEXT = S + 1 < NSTAGE ? BAR(BAR_FULL + S + 1) : BAR(BAR_EMB);
    const int npar = S + 1 < NSTAGE ? conv : 0;
    next_ok = mbar_test(NEXT, npar);
    if (S == 0 && tid == 0) TL(32 + conv * 24);
    asm volatile("wgmma.fence.sync.aligned;" ::: "memory");
    wgmma128<A, B>(d);
    wgmma128<A + 1, B + 16>(d);
    wgmma128<A + 2, B + 32>(d);
    asm volatile("wgmma.commit_group.sync.aligned;" ::: "memory");
    if (S >= LAG) {
        asm volatile("wgmma.wait_group.sync.aligned %0;" ::"n"(LAG) : "memory");
        if ((tid & 31) == 0) mbar_arrive(BAR(BAR_WEMPTY + (S + NS - LAG) % NS));
    }
    if (!next_ok) mbar_wait(NEXT, npar);
    if constexpr (S + 1 < NSTAGE) mma_stages<S + 1>(d, conv, tid, gs);
}

__device__ __forceinline__ void weight_load(uint4 (&t)[5], const __nv_bfloat16* w, int cta, int lane) {
    const char* base = reinterpret_cast<const char*>(w) + ((cta & 15) * 8 * C + (cta >> 4) * 16) * 18;
#pragma unroll
    for (int k = 0; k < 5; k++) {
        const int i = lane + 32 * k, row = (i * 57) >> 10;
        if (k < 4 || lane < 16) t[k] = __ldg(reinterpret_cast<const uint4*>(base + row * (C * 18 - 288) + i * 16));
    }
}
__device__ __forceinline__ void weight_block(uint32_t bounce, unsigned char* wt, int cta, int lane, bool readback, Scratch* gs) {
    unsigned char* dst = wt + (cta >> 4) * STAGE_BYTES + (cta & 15) * 768;
    if (lane < 16) {
        uint32_t v[36];
#pragma unroll
        for (int i = 0; i < 9; i++) {
            const uint4 q = lds128(bounce + (lane & 7) * 288 + (lane >> 3) * 144 + i * 16);
            v[4 * i] = q.x; v[4 * i + 1] = q.y; v[4 * i + 2] = q.z; v[4 * i + 3] = q.w;
        }
#pragma unroll
        for (int kyo = 0; kyo < 3; kyo++) {
#pragma unroll
            for (int kx = 0; kx < 3; kx++) {
                const int tap = ky_of(kyo) * 3 + kx;
                uint32_t o[4];
#pragma unroll
                for (int m = 0; m < 4; m++) {
                    const int i0 = 18 * m + tap, i1 = i0 + 9;
                    const uint32_t sel = ((i0 & 1) ? 0x32u : 0x10u) | ((i1 & 1) ? 0x7600u : 0x5400u);
                    o[m] = __byte_perm(v[i0 >> 1], v[i1 >> 1], sel);
                }
                *reinterpret_cast<uint4*>(dst + kyo * 8 * STAGE_BYTES + kx * 256 + lane * 16) = make_uint4(o[0], o[1], o[2], o[3]);
            }
        }
    }
    if (readback) {
        __syncwarp();
        unsigned acc = 0;
        if (lane < 24) {
#pragma unroll
            for (int i = 0; i < 3; i++) acc |= ld_relaxed(dst + i * 8 * STAGE_BYTES + lane * 32);
        }
        asm volatile("{\n.reg .pred p;\nsetp.eq.u32 p, %0, 0x9e3779b9;\n@p st.shared.u32 [%1], %0;\n}" ::"r"(acc), "r"(bounce + S0) : "memory");
    }
}
__device__ __forceinline__ uint32_t act2(uint32_t u, const float4& cf) {
    return pack_bf(silu_half(fmaf(bf_lo(u), cf.x, cf.z)), silu_half(fmaf(bf_hi(u), cf.y, cf.w)));
}
__device__ __forceinline__ void norm_unit(uint32_t (&u)[4], const float4& ca, const float4& cb) {
    u[0] = act2(u[0], ca); u[1] = act2(u[1], ca); u[2] = act2(u[2], cb); u[3] = act2(u[3], cb);
}
__device__ __forceinline__ void read_stats(uint32_t gst, float (&g)[8]) {
    asm volatile("ld.volatile.shared.v4.f32 {%0,%1,%2,%3}, [%4];" : "=f"(g[0]), "=f"(g[1]), "=f"(g[2]), "=f"(g[3]) : "r"(gst + S0) : "memory");
    asm volatile("ld.volatile.shared.v4.f32 {%0,%1,%2,%3}, [%4];" : "=f"(g[4]), "=f"(g[5]), "=f"(g[6]), "=f"(g[7]) : "r"(gst + 16 + S0) : "memory");
}
template <int T>
__device__ __forceinline__ void wait_stats(uint32_t gst, float (&g)[8]) {
    float rs, mr;
    unsigned it = 0;
#pragma unroll 1
    do {
        asm volatile("ld.volatile.shared.v2.f32 {%0,%1}, [%2];" : "=f"(rs), "=f"(mr) : "r"(gst + 8 * T + S0) : "memory");
    } while (!__all_sync(0xffffffffu, rs != 0.f) && ++it < 8 * SPIN_LIMIT);
    if (T < 3) read_stats(gst, g);
    g[2 * T] = rs; g[2 * T + 1] = mr;
}
template <int T>
__device__ __forceinline__ void own_unit(uint32_t (&o)[4], const float (&z)[8], float4 (&cf)[8], const float (&g)[8]) {
    float4 &ca = cf[2 * T], &cb = cf[2 * T + 1];
    const float rs = g[2 * T], mr = g[2 * T + 1];
    ca.z = fmaf(-mr, ca.x, ca.z); ca.w = fmaf(-mr, ca.y, ca.w);
    cb.z = fmaf(-mr, cb.x, cb.z); cb.w = fmaf(-mr, cb.y, cb.w);
#pragma unroll
    for (int i = 0; i < 4; i++)
        o[i] = pack_bf(silu_half(fmaf(z[2 * i], rs, i < 2 ? ca.z : cb.z)), silu_half(fmaf(z[2 * i + 1], rs, i < 2 ? ca.w : cb.w)));
}
template <int FIRST, int N>
__device__ __forceinline__ void norm_block(uint32_t (&u)[4][4], float4 (&cf)[8], uint32_t act, uint32_t mask, uint32_t fbar, int lane) {
#pragma unroll
    for (int t = FIRST; t < FIRST + N; t++) {
        norm_unit(u[t], cf[2 * t], cf[2 * t + 1]);
        stsm4(act + t * 2 * KC_BYTES, u[t][0] & mask, u[t][1] & mask, u[t][2] & mask, u[t][3] & mask);
    }
    fence_async_smem();
    __syncwarp();
    if (lane < N) mbar_arrive(fbar + 16 * (FIRST + lane));
}
__device__ __forceinline__ void publish(uint32_t bar, int lane) {
    fence_async_smem();
    __syncwarp();
    if (lane == 0) mbar_arrive(bar);
}
template <int T>
__device__ __forceinline__ void next_unit(const float (&z)[8], float4 (&cf)[8], uint32_t gst, float (&g)[8], uint32_t act, uint32_t fbar, int lane) {
    const bool have = __all_sync(0xffffffffu, g[2 * T] != 0.f);
    if (!have) { publish(fbar + 16 * (T - 1), lane); wait_stats<T>(gst, g); }
    uint32_t o[4];
    own_unit<T>(o, z, cf, g);
    if (have) publish(fbar + 16 * (T - 1), lane);
    stsm4(act + T * 2 * KC_BYTES, o[0], o[1], o[2], o[3]);
}
__device__ __forceinline__ void stat_mma(float (&c)[4], uint32_t p, uint32_t q) {
    asm("mma.sync.aligned.m16n8k16.row.col.f32.bf16.bf16.f32 {%0,%1,%2,%3}, {%4,%5,%6,%5}, {%4,%6}, {%0,%1,%2,%3};"
        : "+f"(c[0]), "+f"(c[1]), "+f"(c[2]), "+f"(c[3]) : "r"(p), "r"(0x3f803f80u), "r"(q));
}
__device__ __forceinline__ void stat_store(const float (&c)[4], uint32_t dst, int lane) {
    const int g = lane >> 2, t = lane & 3;
    if (t == (g >> 1)) sts32f(dst + g * 4, (g & 1) ? c[1] : c[0]);
    if (g == 7) sts32f(dst + 32 + t * 4, c[2] + c[3]);
}
__device__ __forceinline__ float sum4(float4 v) { return (v.x + v.y) + (v.z + v.w); }
__device__ __forceinline__ void stat_publish(uint32_t src, float* acc, int lane, bool real) {
    const uint32_t a = src + (lane & 15) * 48;
    float q = sum4(lds128f(a)) + sum4(lds128f(a + 16)), sm = sum4(lds128f(a + 32));
    q += __shfl_xor_sync(0xffffffffu, q, 1); sm += __shfl_xor_sync(0xffffffffu, sm, 1);
    q += __shfl_xor_sync(0xffffffffu, q, 2); sm += __shfl_xor_sync(0xffffffffu, sm, 2);
    if (real && (lane & 19) == 0) red_add4(acc + lane, 1.f, sm, q, 1.f);
}
__device__ __forceinline__ void fence_acc(float (&d)[64]) {
#pragma unroll
    for (int i = 0; i < 64; i++) asm volatile("" : "+f"(d[i])::"memory");
}
__device__ __forceinline__ void ld_unit(uint32_t (&u)[4], const uint4* p) {
    asm volatile("ld.relaxed.gpu.global.v4.u32 {%0,%1,%2,%3}, [%4];" : "=r"(u[0]), "=r"(u[1]), "=r"(u[2]), "=r"(u[3]) : "l"(p) : "memory");
}

__device__ __noinline__ void side_jobs(const __nv_bfloat16* __restrict__ t_emb, const __nv_bfloat16* __restrict__ w_emb,
                                       const __nv_bfloat16* __restrict__ w2, Scratch* __restrict__ gs, unsigned clk0) {
    const int tid = threadIdx.x, warp = tid >> 5, lane = tid & 31, j = blockIdx.x;
    float tv = 0.f;
    if (lane < 24) tv = __bfloat162float(t_emb[(lane / 12) * E + j * 192 + warp * 12 + lane % 12]);
    if (tid == 0) {
        mbar_init(BAR(0), 1);
        mbar_expect(BAR(0), 192 * C * 2);
        fence_async_smem();
        while (clock32() - clk0 < SDELAY) {}
#pragma unroll
        for (int i = 0; i < 4; i++)
            asm volatile("cp.async.bulk.prefetch.L2.global [%0], 18432;" ::"l"(reinterpret_cast<const char*>(w2) + (j * 4 + i) * 18432) : "memory");
#pragma unroll
        for (int i = 0; i < 4; i++) bulk_g2s(S0 + SM_W + i * 12288, w_emb + (j * 192 + i * 48) * C, 12288, S0 + BAR(0));
    }
    if (j == 0 && tid < 32) gs->acc2[(tid >> 4) * LS + (tid & 15)] = 0.f;
    const float sv = silu_half(0.5f * tv);
    __syncthreads();
    mbar_wait(BAR(0), 0);
    float acc[8] = {0.f, 0.f, 0.f, 0.f, 0.f, 0.f, 0.f, 0.f};
#pragma unroll
    for (int i = 0; i < 12; i++) {
        const float2 wq = lds64f(SM_W + (warp * 12 + i) * 256 + lane * 8);
        const uint32_t wx = __float_as_uint(wq.x), wy = __float_as_uint(wq.y);
#pragma unroll
        for (int bb = 0; bb < 2; bb++) {
            const float sx = __shfl_sync(0xffffffffu, sv, bb * 12 + i);
            acc[4 * bb + 0] = fmaf(sx, bf_lo(wx), acc[4 * bb + 0]); acc[4 * bb + 1] = fmaf(sx, bf_hi(wx), acc[4 * bb + 1]);
            acc[4 * bb + 2] = fmaf(sx, bf_lo(wy), acc[4 * bb + 2]); acc[4 * bb + 3] = fmaf(sx, bf_hi(wy), acc[4 * bb + 3]);
        }
    }
    sts128f(SM_ACT + warp * 1024 + lane * 16, make_float4(acc[0], acc[1], acc[2], acc[3]));
    sts128f(SM_ACT + warp * 1024 + 512 + lane * 16, make_float4(acc[4], acc[5], acc[6], acc[7]));
    __syncthreads();
    if (tid < 128) {
        float2 sum = make_float2(0.f, 0.f);
#pragma unroll
        for (int w = 0; w < 16; w++) { const float2 p = lds64f(SM_ACT + w * 1024 + tid * 8); sum.x += p.x; sum.y += p.y; }
        *reinterpret_cast<float2*>(&gs->emb[j * NB * C + tid * 2]) = sum;
        bar_sync(1, 128);
        if (tid < 2) asm volatile("red.release.gpu.global.add.u32 [%0], 1;" ::"l"(&gs->wcnt[(2 * NB + tid) * LS]) : "memory");
    }
}

__global__ void __cluster_dims__(2, 1, 1) __launch_bounds__(NTHREADS, 1)
resblock_kernel(const __nv_bfloat16* __restrict__ w1, const __nv_bfloat16* __restrict__ x,
                const __nv_bfloat16* __restrict__ t_emb, const __nv_bfloat16* __restrict__ g1,
                const __nv_bfloat16* __restrict__ be1, const __nv_bfloat16* __restrict__ w_emb,
                const __nv_bfloat16* __restrict__ g2, const __nv_bfloat16* __restrict__ be2,
                const __nv_bfloat16* __restrict__ w2, __nv_bfloat16* __restrict__ out, Scratch* __restrict__ gs,
                const __grid_constant__ CUtensorMap xmap) {
    const unsigned clk0 = clock32();
    if (threadIdx.x == 480 && blockIdx.x >= NXTRA) TLG(1);
    const int tid = threadIdx.x, lane = tid & 31;
    const int cta = blockIdx.x - NXTRA, b = cta >> 6, r = cta & 63;
    uint4 v[5];
    if (tid < 32) weight_load(v, w1, cta & (NCTA - 1), lane);
    uint4 xv[8];
    const int wg4 = (tid >> 5) - 1;
    const bool early = tid >= 32 && wg4 < NLDG;
    if (early) {
        const char* src = reinterpret_cast<const char*>(x) + (uint32_t)((((b & 1) * C + wg4 * 32 + (lane >> 3)) * HW + r) * HW * 2 + (lane & 7) * 16);
        while (clock32() - clk0 < XDELAY + (wg4 >> 1) * XSTAG + (wg4 & 1) * XSTAG2) {}
#pragma unroll
        for (int i = 0; i < 8; i++) xv[i] = __ldg(reinterpret_cast<const uint4*>(src + i * (4 * HW * HW * 2)));
    }
    const int warp = __shfl_sync(0xffffffffu, tid >> 5, 0);
    if (cta < 0) { side_jobs(t_emb, w_emb, w2, gs, clk0); return; }

    if (warp != 4) asm volatile("barrier.cluster.arrive.relaxed.aligned;" ::: "memory");
    const bool has_outer = (r != 0) && (r != HW - 1);
    if (warp == 1 || warp == 2 || warp == 3 || warp == 5) {
        const int g = warp < 4 ? warp - 1 : 3;
        if (elect_one()) {
            if (g >= NLDG) asm volatile("prefetch.tensormap [%0];" ::"l"(&xmap) : "memory");
            mbar_init(BAR(BAR_X) + 8 * g, 1);
            if (g >= NLDG) mbar_expect(BAR(BAR_X) + 8 * g, 4096);
            fence_async_smem();
        }
        __syncwarp();
        bar_arrive(4, 256 + 32 + 128);
        if (g >= NLDG) {
            while (clock32() - clk0 < XDELAY + (g >> 1) * XSTAG + (g & 1) * XSTAG2) {}
            if (elect_one()) tma_x(SM_XOWN + g * 4096, &xmap, r, b * C + g * 32, BAR(BAR_X) + 8 * g);
            __syncwarp();
            mbar_wait(BAR(BAR_X) + 8 * g, 0);
#pragma unroll
            for (int k = 0; k < 8; k++) xv[k] = lds128(SM_XOWN + g * 4096 + k * 512 + lane * 16);
        }
        float c[8][4];
#pragma unroll
        for (int k = 0; k < 8; k++) {
            c[k][0] = c[k][1] = c[k][2] = c[k][3] = 0.f;
            stat_mma(c[k], xv[k].x, xv[k].y); stat_mma(c[k], xv[k].z, xv[k].w);
        }
#pragma unroll
        for (int i = 0; i < 4; i++) c[0][i] = ((c[0][i] + c[1][i]) + (c[2][i] + c[3][i])) + ((c[4][i] + c[5][i]) + (c[6][i] + c[7][i]));
        stat_store(c[0], SM_RED + g * 48, lane);
        __syncwarp();
        if (lane == 0) {
            const uint32_t a = SM_RED + g * 48;
            red_add4(&gs->acc1[b * LS + g * 4], 1.f, sum4(lds128f(a + 32)), sum4(lds128f(a)) + sum4(lds128f(a + 16)), 1.f);
            TL(74 + g);
        }
        if (g < NLDG) {
#pragma unroll
            for (int i = 0; i < 8; i++)
                sts128(SM_XOWN + g * 4096 + i * 512 + (lane >> 3) * 128 + (((lane & 7) ^ ((lane >> 3) + 4 * (i & 1))) << 4), xv[i]);
            __syncwarp();
            if (lane == 0) mbar_arrive(BAR(BAR_X) + 8 * g);
        }
    }
    if (warp == 4) {
            if (elect_one()) {
#pragma unroll
                for (int i = 0; i < NSTAGE; i++) mbar_init(BAR(BAR_FULL + i), (i >> 3) == 1 ? 1 : 5);
#pragma unroll
                for (int i = 0; i < NS + 2; i++) mbar_init(BAR(BAR_WEMPTY + i), 4);
#pragma unroll
                for (int i = BAR_STATS; i < BAR_X; i++) mbar_init(BAR(i), i == BAR_EMB ? 3 : 1);
                mbar_init(BAR(BAR_X + 4), 1);
                asm volatile("fence.mbarrier_init.release.cluster;" ::: "memory");
            }
            if (lane < 4) sts128(SM_GST + lane * 16, make_uint4(0, 0, 0, 0));
            __syncwarp();
            fence_async_smem();
            bar_arrive(0, 96);
            bar_arrive(5, 64);
            bar_arrive(4, 256 + 32 + 128);
            const uint4 z = make_uint4(0, 0, 0, 0);
#pragma unroll
            for (int i = 0; i < 2; i++) sts128(SM_ACT + (i * 16 + (lane >> 1)) * CH_PITCH + (lane & 1) * 16, z);
            if (lane < 4) sts128(SM_ACT + (2 + (lane >> 1)) * ROW_BYTES + (lane & 1) * 16, z);
            if (lane < 16) sts128(SM_ONES + lane * 16, make_uint4(lane < 8 ? 0x3f803f80u : 0u, 0, 0, 0));
            fence_async_smem();
            bar_arrive(7, 160);
            asm volatile("barrier.cluster.arrive.relaxed.aligned;" ::: "memory");
            if (lane == 0) TL(5);
            while (clock32() - clk0 < W2DELAY) {}
            weight_load(v, w2, cta, lane);
        }
    if (warp == 0 || warp == 4) {
        const int k = warp >> 2;
#pragma unroll
        for (int i = 0; i < 5; i++)
            if (i < 4 || lane < 16) sts128(SM_BNC + k * 2304 + (lane + 32 * i) * 16, v[i]);
        if (lane == 0) TL(k ? 14 : 81);
        __syncwarp();
        weight_block(SM_BNC + k * 2304, gs->wt + k * NSTAGE * STAGE_BYTES, cta, lane, true, gs);
        __syncwarp();
        if (lane == 0) TL(k ? 13 : 4);
        if (lane < 2) asm volatile("red.relaxed.gpu.global.add.u32 [%0], 1;" ::"l"(k ? &gs->wcnt[(NB + lane) * LS] : &gs->w1cnt[(lane * 8 + (cta >> 4)) * KS]) : "memory");
    }

    if (warp >= 8) {
        const int nw = warp - 8;
        if (nw < 2) {
            const uint2 ga = __ldg(reinterpret_cast<const uint2*>(nw ? g2 : g1) + lane), bt = __ldg(reinterpret_cast<const uint2*>(nw ? be2 : be1) + lane);
            sts128f(SM_COEF + nw * 1024 + lane * 32, make_float4(0.5f * bf_lo(ga.x), 0.5f * bf_hi(ga.x), 0.5f * bf_lo(bt.x), 0.5f * bf_hi(bt.x)));
            sts128f(SM_COEF + nw * 1024 + lane * 32 + 16, make_float4(0.5f * bf_lo(ga.y), 0.5f * bf_hi(ga.y), 0.5f * bf_lo(bt.y), 0.5f * bf_hi(bt.y)));
        }
        bar_sync(4, 256 + 32 + 128);
        const int par = nw >> 2, wq = nw & 3;
        const uint32_t act_off = SM_ACT + (par * 2 + (lane >> 4)) * CH_PITCH + (2 + wq * 16 + (lane & 15)) * 16;
        const uint32_t stg_off = (par * 16 + (lane >> 4) * 8 + (lane & 7)) * 128 + (((2 * wq + ((lane >> 3) & 1)) ^ (lane & 7)) << 4);
        const uint32_t cfa = SM_COEF + par * 128 + (lane & 3) * 16;
        const uint32_t fbar = BAR(BAR_FULL) + 8 * par;
        uint4* inbox = gs->box + cta * 1024 + nw * 32 + lane;
#pragma unroll 1
        for (int conv = 0; conv < 2; conv++) {
            uint32_t u[4][4], w[4][4];
            float4 cf[8];
            if (conv == 0) {
#pragma unroll
                for (int i = 0; i < 4; i++) { mbar_wait(BAR(BAR_X + i), 0); ldsm4t(u[i], SM_XOWN + stg_off + i * 4096); }
            } else {
                mbar_wait(BAR(BAR_HW), 0);
#pragma unroll
                for (int i = 0; i < 4; i++) ldsm4(u[i], act_off + i * 2 * KC_BYTES);
            }
#pragma unroll
            for (int i = 0; i < 8; i++) cf[i] = lds128f(cfa + conv * 1024 + (i >> 1) * 256 + (i & 1) * 64);
            const uint32_t gst = SM_GST + conv * 32;
            float gv[8], z[4][8];
#pragma unroll
            for (int i = 0; i < 16; i++) {
                const float4& c = cf[i >> 1];
                z[i >> 2][2 * (i & 3)] = bf_lo(u[i >> 2][i & 3]) * c.x; z[i >> 2][2 * (i & 3) + 1] = bf_hi(u[i >> 2][i & 3]) * c.y;
                asm volatile("" : "+f"(z[i >> 2][2 * (i & 3)]), "+f"(z[i >> 2][2 * (i & 3) + 1]));
            }
            wait_stats<0>(gst, gv);
            if (tid == 256) TL(22 + conv * 4);
            if (par) { const unsigned c1 = clock32(); while (clock32() - c1 < PDELAY) {} }
            uint32_t o[4];
            own_unit<0>(o, z[0], cf, gv);
            stsm4(act_off, o[0], o[1], o[2], o[3]);
            publish(fbar, lane);
            if (tid == 256) TL(8 + conv * 8);
            if (!__all_sync(0xffffffffu, gv[2] != 0.f)) wait_stats<1>(gst, gv);
            own_unit<1>(o, z[1], cf, gv);
            stsm4(act_off + 2 * KC_BYTES, o[0], o[1], o[2], o[3]);
            next_unit<2>(z[2], cf, gst, gv, act_off, fbar, lane);
            next_unit<3>(z[3], cf, gst, gv, act_off, fbar, lane);
            publish(fbar + 48, lane);
#pragma unroll
            for (int i = 0; i < 8; i++) { cf[i].x *= gv[i & ~1]; cf[i].y *= gv[i & ~1]; }
            if (tid == 256) TL(84 + conv);
            if (has_outer) {
                mbar_wait(BAR(BAR_X + 4), conv);
                if (conv == 0) {
#pragma unroll
                    for (int i = 0; i < 4; i++) ldsm4t(w[i], SM_XOUT + stg_off + i * 4096);
                } else {
#pragma unroll
                    for (int i = 0; i < 4; i++) {
                        const uint4 q = lds128(SM_XOWN + (tid - 256) * 16 + i * 4096);
                        w[i][0] = q.x; w[i][1] = q.y; w[i][2] = q.z; w[i][3] = q.w;
                    }
                    unsigned it = 0;
                    while (true) {
                        bool ok = true;
#pragma unroll
                        for (int i = 0; i < 16; i++) ok = ok && w[i >> 2][i & 3] != 0;
                        if (__all_sync(0xffffffffu, ok) || ++it > SPIN_LIMIT) break;
#pragma unroll
                        for (int i = 0; i < 4; i++) ld_unit(w[i], inbox + i * 256);
                    }
#pragma unroll
                    for (int i = 0; i < 16; i++) w[i >> 2][i & 3] = ~w[i >> 2][i & 3];
                }
            }
            if (conv == 0) {
                bar_sync(3, 256);
                if (nw == 0) sts128(SM_ACT + 2 * ROW_BYTES + (lane >> 1) * CH_PITCH + (lane & 1) * 16, make_uint4(0, 0, 0, 0));
            }
            if (tid == 256) TL(24 + conv * 4);
            norm_block<0, 2>(w, cf, act_off + 2 * ROW_BYTES, has_outer ? ~0u : 0u, fbar + 128, lane);
            if (tid == 256) TL(88 + conv);
            norm_block<2, 2>(w, cf, act_off + 2 * ROW_BYTES, has_outer ? ~0u : 0u, fbar + 128, lane);
            if (tid == 256) TL(23 + conv * 4);
        }
        if (has_outer) {
            mbar_wait(BAR(BAR_FULL + NSTAGE - 1), 1);
#pragma unroll
            for (int i = 0; i < 4; i++) inbox[i * 256] = make_uint4(0, 0, 0, 0);
        }
        {
            const int oc0 = par * 64 + ((tid & 127) >> 3), seg = lane & 7;
            __nv_bfloat16* dst = out + ((size_t)(b * C + oc0) * HW + r) * HW + seg * 8;
            const uint32_t src = SM_XOWN + oc0 * 128 + ((seg ^ (oc0 & 7)) << 4);
            bar_sync(par ? 1 : 6, 128 + 128);
#pragma unroll
            for (int i = 0; i < 4; i++) *reinterpret_cast<uint4*>(dst + (size_t)i * 16 * HW * HW) = lds128(src + i * 2048);
            if (tid == 384) { TL(20); TLG(21); }
        }
    } else if (warp < 4) {
        const int wq = warp;
        bar_sync(7, 160);

        const uint32_t xbase = SM_XOWN + ((lane >> 4) * 8 + (lane & 7)) * 128 + (((2 * wq + ((lane >> 3) & 1)) ^ (lane & 7)) << 4);
        float d[64];
#pragma unroll
        for (int i = 0; i < 64; i++) d[i] = 0.f;
#pragma unroll 1
        for (int conv = 0; conv < 2; conv++) {
            fence_acc(d);
            mma_stages<0>(d, conv, tid, gs);
            if (conv == 0) {
                asm volatile("wgmma.fence.sync.aligned;" ::: "memory");
                wgmma128<(SM_ONES >> 4) | (8u << 16), (SM_EMB >> 4), 0, 8>(d);
                asm volatile("wgmma.commit_group.sync.aligned;" ::: "memory");
            }
            asm volatile("wgmma.wait_group.sync.aligned 0;" ::: "memory");
            fence_acc(d);
            if (tid == 0) TL(10 + conv * 8);
            if (conv == 1) {
                fence_acc(d);
#pragma unroll
                for (int kc = 0; kc < 8; kc++) {
                    stsm4t(xbase + kc * 2048, pack_bf(d[8 * kc], d[8 * kc + 1]), pack_bf(d[8 * kc + 2], d[8 * kc + 3]),
                           pack_bf(d[8 * kc + 4], d[8 * kc + 5]), pack_bf(d[8 * kc + 6], d[8 * kc + 7]));
                    if (kc == 3) bar_arrive(6, 128 + 128);
                }
                bar_arrive(1, 128 + 128);
                break;
            }
            uint32_t hp[32];
#pragma unroll
            for (int i = 0; i < 32; i++) hp[i] = pack_bf(d[2 * i], d[2 * i + 1]);
#pragma unroll
            for (int g = 0; g < 4; g++) {
                float c[4] = {0.f, 0.f, 0.f, 0.f};
#pragma unroll
                for (int i = 0; i < 4; i++) stat_mma(c, hp[8 * g + 2 * i], hp[8 * g + 2 * i + 1]);
                stat_store(c, SM_RED + (g * 4 + wq) * 48, lane);
            }
            bar_sync(2, 128);
            if (wq == 0) stat_publish(SM_RED, &gs->acc2[b * LS], lane, true);
            if (tid == 0) TL(11);
            const uint32_t hbase = SM_ACT + (lane >> 4) * CH_PITCH + (2 + wq * 16 + (lane & 15)) * 16;
#pragma unroll
            for (int kc = 0; kc < 8; kc++) stsm4(hbase + kc * 2 * CH_PITCH, hp[4 * kc], hp[4 * kc + 1], hp[4 * kc + 2], hp[4 * kc + 3]);
            __syncwarp();
            if (lane == 0) mbar_arrive(BAR(BAR_HW));
            if (lane < LAG) mbar_arrive(BAR(BAR_WEMPTY + (NSTAGE - LAG) % NS) + 8 * lane);
            if (has_outer) {
                uint4* outbox = gs->box + (cta + ((r & 1) ? 1 : -1)) * 1024 + tid;
#pragma unroll
                for (int kc = 0; kc < 8; kc++) outbox[kc * 128] = make_uint4(~hp[4 * kc], ~hp[4 * kc + 1], ~hp[4 * kc + 2], ~hp[4 * kc + 3]);
            }
            if (tid == 0) TL(12);
#pragma unroll
            for (int kc = 0; kc < 8; kc++) {
                uint32_t p[4];
                ldsm4t(p, xbase + kc * 2048);
#pragma unroll
                for (int i = 0; i < 4; i++) { d[8 * kc + 2 * i] = bf_lo(p[i]); d[8 * kc + 2 * i + 1] = bf_hi(p[i]); }
            }
            fence_async_smem();
            __syncwarp();
            if (lane == 0) mbar_arrive(BAR(BAR_XFREE));
        }
        {
        }
    } else if (warp < 6) {
        if (warp == 5) {
            bar_sync(5, 64);
            mbar_wait(BAR(BAR_FULL + OAFTER), 0);
            if (has_outer && elect_one()) {
                mbar_expect(BAR(BAR_X + 4), 16384);
#pragma unroll
                for (int i = 0; i < 4; i++) tma_x(SM_XOUT + i * 4096, &xmap, r + ((r & 1) ? 1 : -1), b * C + i * 32, BAR(BAR_X + 4));
            }
            __syncwarp();
            asm volatile("barrier.cluster.wait.acquire.aligned;" ::: "memory");
            const uint32_t peer = (r & 1) ^ 1;
            const uint32_t self0 = mapa(0, r & 1), peer0 = mapa(0, peer);
#pragma unroll 1
            for (int conv = 0; conv < 2; conv++) {
                if (FWD0) mbar_wait(BAR(BAR_FULL + FWD0), conv);
#pragma unroll 1
                for (int kc = 0; kc < 8; kc++) {
                    mbar_wait(BAR(BAR_FULL) + 8 * kc, conv);
                    if (elect_one())
                        asm volatile("cp.async.bulk.shared::cluster.shared::cta.mbarrier::complete_tx::bytes [%0], [%1], %2, [%3];"
                                     ::"r"(peer0 + SM_ACT + ROW_BYTES + kc * KC_BYTES), "r"(self0 + SM_ACT + kc * KC_BYTES), "r"(KC_BYTES),
                                       "r"(peer0 + BAR(BAR_FULL + 8) + 8 * kc) : "memory");
                }
                if (lane == 0) TL(86 + conv);
#pragma unroll 1
                for (int kc = 0; kc < 8; kc++) mbar_wait(BAR(BAR_FULL + 8) + 8 * kc, conv);
                if (lane == 0)
                    asm volatile("mbarrier.arrive.relaxed.cluster.shared::cluster.b64 _, [%0];" ::"r"(peer0 + (conv ? BAR(BAR_ACK) : BAR(BAR_EMB))) : "memory");
            }
            mbar_wait(BAR(BAR_ACK), 0);
        } else {
            mbar_wait(BAR(BAR_STATS), 0);
            unsigned it = 0;
            while (ld_relaxed(&gs->wcnt[(2 * NB + b) * LS]) < (unsigned)NXTRA && ++it < SPIN_LIMIT) __nanosleep(100);
            fence_acquire();
            float ev[4] = {0.f, 0.f, 0.f, 0.f};
#pragma unroll
            for (int j = 0; j < NXTRA; j++) {
                const uint4 ef = ld_relaxed_v4(&gs->emb[(j * NB + b) * C + lane * 4]);
                ev[0] += __uint_as_float(ef.x); ev[1] += __uint_as_float(ef.y); ev[2] += __uint_as_float(ef.z); ev[3] += __uint_as_float(ef.w);
            }
#pragma unroll
            for (int i = 0; i < 4; i++) {
                const float hi = bf_lo(pack_bf(ev[i], 0.f));
                sts128(SM_EMB + (lane * 4 + i) * 16, make_uint4(pack_bf(hi, ev[i] - hi), 0, 0, 0));
            }
            fence_async_smem();
            __syncwarp();
            if (lane == 0) { mbar_arrive(BAR(BAR_EMB)); TL(19); }
        }
    } else if (warp == 6) {
        bar_sync(0, 96);
        const uint32_t ebytes = STAGE_BYTES + ((lane >> 3) == 1 ? KC_BYTES : 0);
        if (lane < NSTAGE) mbar_expect(BAR(BAR_FULL) + 8 * lane, ebytes);
        const int swap = (r & 1) ? 0 : 8 * STAGE_BYTES;
        unsigned it = 0;
        {
            int g = 0;
            const unsigned* cnt = &gs->w1cnt[(b * 8 + (lane & 7)) * KS];
            unsigned cv = ld_relaxed(cnt);
#pragma unroll 1
            while (g < NS) {
                unsigned ready = __ballot_sync(0xffffffffu, cv >= 16u);
                if (ready != ~0u) cv = ld_relaxed(cnt);
                ready >>= g;
                if (++it > SPIN_LIMIT) ready = ~0u;
                if (!(ready & 1)) continue;
                fence_async_global();
                if (lane == 0) TL(g ? 3 : 6);
#pragma unroll 1
                for (; (ready & 1) && g < NS; g++, ready >>= 1)
                    if (elect_one())
                        bulk_g2s(S0 + SM_W + g * STAGE_BYTES, gs->wt + g * STAGE_BYTES + (g >= 8 ? swap : 0), STAGE_BYTES, S0 + BAR(BAR_FULL) + 8 * g);
            }
        }
#pragma unroll 1
        for (int q = 3; q < 12; q++) {
            const int conv = q >= 6, qs = conv ? q - 6 : q, sl = q % 3;
            const unsigned char* wsrc = gs->wt + q * 4 * STAGE_BYTES + (qs < 2 ? 0 : (qs < 4 ? swap : -swap));
            const uint32_t par = (q / 3 - 1) & 1;
            if (q == 6) {
                it = 0;
                while (ld_relaxed(&gs->wcnt[(NB + b) * LS]) < (unsigned)NCTA && ++it < SPIN_LIMIT) {}
                fence_acquire();
                fence_async_global();
                if (lane == 0) { mbar_arrive(BAR(BAR_EMB)); TL(2); }
            }
#pragma unroll
            for (int i = 0; i < 4; i++) {
                mbar_wait(BAR(BAR_WEMPTY + i) + 32 * sl, par);
                if (i == 0 && (q == 6 || q == 9)) {
                    if ((lane >= NS) == (q == 9) && lane < NSTAGE) mbar_expect(BAR(BAR_FULL) + 8 * lane, ebytes);
                    __syncwarp();
                }
                if (elect_one())
                    bulk_g2s(S0 + SM_W + (sl * 4 + i) * STAGE_BYTES, wsrc + i * STAGE_BYTES, STAGE_BYTES, S0 + BAR(BAR_FULL + i) + 32 * qs);
            }
        }
    } else {
        bar_sync(0, 96);
#pragma unroll 1
        for (int conv = 0; conv < 2; conv++) {
            if (conv == 1) mbar_wait(BAR(BAR_HW), 0);
            const float* asrc = (conv ? gs->acc2 : gs->acc1) + b * LS + (lane & 3) * 4;
            unsigned it = 0;
#pragma unroll 1
            while (true) {
                const uint4 f = ld_relaxed_v4(asrc);
                const bool ok = ((f.x == 0x42800000u) & (f.w == 0x42800000u)) || ++it > SPIN_LIMIT;
                if (ok && lane < 4) {
                    const float inv_n = 1.0f / (32.0f * HW * HW);
                    const float mean = __uint_as_float(f.y) * inv_n;
                    float rs;
                    asm("rsqrt.approx.ftz.f32 %0, %1;" : "=f"(rs) : "f"(fmaxf(fmaf(-mean, mean, __uint_as_float(f.z) * inv_n), 0.f) + 1e-5f));
                    asm volatile("st.shared.v2.f32 [%0], {%1,%2};" ::"r"(S0 + SM_GST + conv * 32 + lane * 8), "f"(rs == 0.f ? 1e-38f : rs), "f"(mean * rs) : "memory");
                }
                if (__all_sync(0xffffffffu, ok)) break;
            }
            if (lane == 0) { mbar_arrive(BAR(BAR_STATS)); TL(7 + conv * 8); }
        }
        mbar_wait(BAR(BAR_XFREE), 0);
        if (has_outer && elect_one()) {
            mbar_expect(BAR(BAR_X + 4), 16384);
            bulk_g2s(S0 + SM_XOWN, gs->box + cta * 1024, 16384, S0 + BAR(BAR_X + 4));
        }
        if (r == 0) {
            if (lane < 16) gs->acc1[b * LS + lane] = 0.f;
            if (lane < 3) gs->wcnt[(lane * NB + b) * LS] = 0;
            if (lane < 8) gs->w1cnt[(b * 8 + lane) * KS] = 0;
        }
    }
}

}

extern "C" void kernel_launch(void* const* d_in, const int* in_sizes, int n_in, void* d_out, int out_size) {
    (void)in_sizes; (void)n_in; (void)out_size;
    typedef CUresult (*EncodeFn)(CUtensorMap*, CUtensorMapDataType, cuuint32_t, void*, const cuuint64_t*, const cuuint64_t*,
                                 const cuuint32_t*, const cuuint32_t*, CUtensorMapInterleave, CUtensorMapSwizzle,
                                 CUtensorMapL2promotion, CUtensorMapFloatOOBfill);
    static Scratch* gs = nullptr;
    static EncodeFn encode = nullptr;
    if (!gs) {
        cudaFuncSetAttribute(resblock_kernel, cudaFuncAttributeMaxDynamicSharedMemorySize, SM_TOTAL);
        cudaGetSymbolAddress((void**)&gs, g_scratch);
        cudaDriverEntryPointQueryResult qr;
        cudaGetDriverEntryPoint("cuTensorMapEncodeTiled", (void**)&encode, cudaEnableDefault, &qr);
    }
    CUtensorMap xmap;
    const cuuint64_t dims[3] = {HW, HW, NB * C}, strides[2] = {HW * 2, HW * HW * 2};
    const cuuint32_t box[3] = {HW, 1, 32}, es[3] = {1, 1, 1};
    encode(&xmap, CU_TENSOR_MAP_DATA_TYPE_BFLOAT16, 3, d_in[0], dims, strides, box, es, CU_TENSOR_MAP_INTERLEAVE_NONE,
           CU_TENSOR_MAP_SWIZZLE_128B, CU_TENSOR_MAP_L2_PROMOTION_NONE, CU_TENSOR_MAP_FLOAT_OOB_FILL_NONE);
    resblock_kernel<<<NCTA + NXTRA, NTHREADS, SM_TOTAL>>>(
        (const __nv_bfloat16*)d_in[4], (const __nv_bfloat16*)d_in[0], (const __nv_bfloat16*)d_in[1],
        (const __nv_bfloat16*)d_in[2], (const __nv_bfloat16*)d_in[3], (const __nv_bfloat16*)d_in[5],
        (const __nv_bfloat16*)d_in[6], (const __nv_bfloat16*)d_in[7], (const __nv_bfloat16*)d_in[8],
        (__nv_bfloat16*)d_out, gs, xmap);
}
```

```cpp
#include <cuda_runtime.h>
#include <cuda.h>
#include <cuda_bf16.h>
#include <stdint.h>

namespace {

constexpr int C = 128, HW = 64, NB = 2, E = 768;
constexpr int NCTA = NB * HW;
constexpr int NXTRA = 4;
constexpr int NTHREADS = 16 * 32;
constexpr int CH_PITCH = 66 * 16;
constexpr int ROW_BYTES = 16 * CH_PITCH;
constexpr int STEP_BYTES = 4096;
constexpr int STAGE_BYTES = 3 * STEP_BYTES;
constexpr int NSTAGE = 24;
constexpr int KC_BYTES = 2 * CH_PITCH;
constexpr int NS = 12;
constexpr int LAG = 1;
#define XDELAY 400
#define HDELAY 600
#define SEQ 0
#define MMA0_WAIT mbar_try
#define NPOLL 1
#define PD2 0
#define ODELAY 100
#define NLDG 2
#define PSTAG -1
#define PDELAY0 400
#define PDELAY 60
#define RB 1
#define XSTAG2 400
#define XSTAG 800
#define HSEND 0
#define SDELAY 600
#define OAFTER 0
#define W2DELAY 2400

constexpr uint32_t SMEM_BASE = 0x400;
constexpr uint32_t SM_XOWN = SMEM_BASE;
constexpr uint32_t SM_ACT = SM_XOWN + 16384 + 512;
constexpr uint32_t SM_XOUT = SM_ACT + 2 * ROW_BYTES + 512;
static_assert(SM_XOUT % 1024 == 0, "swizzle atom alignment");
constexpr uint32_t SM_W = SM_ACT + 3 * ROW_BYTES + 128;
__host__ __device__ constexpr uint32_t slot_addr(int slot) { return SM_W + slot * STAGE_BYTES; }
constexpr uint32_t SM_COEF = SM_W + NS * STAGE_BYTES;
constexpr uint32_t SM_GST = SM_COEF + 2048;
constexpr uint32_t SM_EMB = SM_GST + 128;
constexpr uint32_t SM_ONES = SM_EMB + 2048;
constexpr uint32_t SM_RED = SM_ONES + 256;
constexpr uint32_t SM_BNC = SM_RED + 1536;
constexpr uint32_t SM_BAR = SM_BNC + 2 * 2304;
constexpr int BAR_FULL = 0, BAR_WEMPTY = NSTAGE, BAR_HW = BAR_WEMPTY + NS, BAR_XFREE = BAR_HW + 1, BAR_STATS = BAR_XFREE + 1,
              BAR_EMB = BAR_STATS + 1, BAR_ACK = BAR_EMB + 1, BAR_X = BAR_ACK + 1  , NBAR = BAR_X + 5;
constexpr int SM_TOTAL = SM_BAR + NBAR * 8 - SMEM_BASE;
static_assert(SM_TOTAL <= 232448, "smem");
static_assert(NBAR <= 96, "barrier init");
__host__ __device__ constexpr uint32_t BAR(int i) { return SM_BAR + 8 * i; }
__host__ __device__ constexpr int ky_of(int kyo) { return kyo == 0 ? 1 : (kyo == 1 ? 0 : 2); }

constexpr unsigned SPIN_LIMIT = 1u << 16;

#define LS 1056
#define GS1 4
#define PD 0
#define FWD0 0
#define HPACE 26
#define FDELAY 1600
#define WPAUSE 3
#define KS 32
struct Scratch {
    float acc1[NB * LS];
    float acc2[NB * LS];
    unsigned wcnt[3 * NB * LS];
    unsigned w1cnt[NB * 8 * KS];
    float emb[NXTRA * NB * C];
    alignas(1024) unsigned char wt[2 * NSTAGE * STAGE_BYTES];
    uint4 box[NCTA * 1024];
};
__device__ __align__(1024) Scratch g_scratch;
#define TL(i) do {} while (0)
#define TLG(i) do {} while (0)

__device__ __forceinline__ unsigned clock32() { unsigned c; asm volatile("mov.u32 %0, %%clock;" : "=r"(c)); return c; }
__device__ __forceinline__ uint32_t mapa(uint32_t a, uint32_t rank) {
    uint32_t d;
    asm("mapa.shared::cluster.u32 %0, %1, %2;" : "=r"(d) : "r"(a), "r"(rank));
    return d;
}
#define S0 mapa(0, blockIdx.x & 1)
__device__ __forceinline__ void mbar_init(uint32_t bar, int cnt) {
    asm volatile("mbarrier.init.shared::cta.b64 [%0], %1;" ::"r"(bar + S0), "r"(cnt) : "memory");
}
__device__ __forceinline__ void mbar_arrive(uint32_t bar) {
    asm volatile("mbarrier.arrive.shared::cta.b64 _, [%0];" ::"r"(bar + S0) : "memory");
}
__device__ __forceinline__ void mbar_expect(uint32_t bar, uint32_t bytes) {
    asm volatile("mbarrier.arrive.expect_tx.shared::cta.b64 _, [%0], %1;" ::"r"(bar + S0), "r"(bytes) : "memory");
}
__device__ __forceinline__ bool mbar_try(uint32_t bar, uint32_t par) {
    uint32_t ok;
    asm volatile("{\n.reg .pred p;\nmbarrier.try_wait.parity.shared::cta.b64 p, [%1], %2;\nselp.u32 %0, 1, 0, p;\n}"
                 : "=r"(ok) : "r"(bar + S0), "r"(par) : "memory");
    return ok;
}
__device__ __forceinline__ bool mbar_test(uint32_t bar, uint32_t par) {
    uint32_t ok;
    asm volatile("{\n.reg .pred p;\nmbarrier.test_wait.parity.shared::cta.b64 p, [%1], %2;\nselp.u32 %0, 1, 0, p;\n}"
                 : "=r"(ok) : "r"(bar + S0), "r"(par) : "memory");
    return ok;
}
__device__ __forceinline__ void mbar_wait(uint32_t bar, uint32_t par) {
    unsigned it = 0;
#pragma unroll 1
    while (!mbar_try(bar, par) && ++it < SPIN_LIMIT) {}
}
__device__ __forceinline__ bool elect_one() {
    uint32_t p;
    asm volatile("{\n.reg .pred p;\nelect.sync _|p, 0xffffffff;\nselp.u32 %0, 1, 0, p;\n}" : "=r"(p));
    return p;
}
__device__ __forceinline__ void fence_async_smem() { asm volatile("fence.proxy.async.shared::cta;" ::: "memory"); }
__device__ __forceinline__ void fence_async_global() { asm volatile("fence.proxy.async.global;" ::: "memory"); }
__device__ __forceinline__ void fence_acquire() { asm volatile("fence.acquire.gpu;" ::: "memory"); }
__device__ __forceinline__ void bar_sync(int id, int n) { asm volatile("bar.sync %0, %1;" ::"r"(id), "r"(n) : "memory"); }
__device__ __forceinline__ void bar_arrive(int id, int n) { asm volatile("bar.arrive %0, %1;" ::"r"(id), "r"(n) : "memory"); }
__device__ __forceinline__ void bulk_g2s(uint32_t dst, const void* src, uint32_t bytes, uint32_t bar) {
    asm volatile("cp.async.bulk.shared::cluster.global.mbarrier::complete_tx::bytes [%0], [%1], %2, [%3];"
                 ::"r"(dst), "l"(src), "r"(bytes), "r"(bar) : "memory");
}
__device__ __forceinline__ void tma_x(uint32_t dst, const CUtensorMap* tm, int row, int ch, uint32_t bar) {
    asm volatile("cp.async.bulk.tensor.3d.shared::cluster.global.mbarrier::complete_tx::bytes [%0], [%1, {%2, %3, %4}], [%5];"
                 ::"r"(dst + S0), "l"(tm), "r"(0), "r"(row), "r"(ch), "r"(bar + S0) : "memory");
}
__device__ __forceinline__ uint4 ld_relaxed_v4(const void* p) {
    uint4 v;
    asm volatile("ld.relaxed.gpu.global.v4.u32 {%0,%1,%2,%3}, [%4];" : "=r"(v.x), "=r"(v.y), "=r"(v.z), "=r"(v.w) : "l"(p) : "memory");
    return v;
}
__device__ __forceinline__ unsigned ld_relaxed(const void* p) {
    unsigned v;
    asm volatile("ld.relaxed.gpu.global.u32 %0, [%1];" : "=r"(v) : "l"(p) : "memory");
    return v;
}
__device__ __forceinline__ void red_add4(float* p, float a, float b, float c, float d) {
    asm volatile("red.relaxed.gpu.global.add.v4.f32 [%0], {%1,%2,%3,%4};" ::"l"(p), "f"(a), "f"(b), "f"(c), "f"(d) : "memory");
}
__device__ __forceinline__ void sts128(uint32_t a, uint4 v) {
    asm volatile("st.shared.v4.u32 [%0], {%1,%2,%3,%4};" ::"r"(a + S0), "r"(v.x), "r"(v.y), "r"(v.z), "r"(v.w) : "memory");
}
__device__ __forceinline__ void sts128f(uint32_t a, float4 v) {
    asm volatile("st.shared.v4.f32 [%0], {%1,%2,%3,%4};" ::"r"(a + S0), "f"(v.x), "f"(v.y), "f"(v.z), "f"(v.w) : "memory");
}
__device__ __forceinline__ void sts32f(uint32_t a, float v) { asm volatile("st.shared.f32 [%0], %1;" ::"r"(a + S0), "f"(v) : "memory"); }
__device__ __forceinline__ uint4 lds128(uint32_t a) {
    uint4 v;
    asm volatile("ld.shared.v4.u32 {%0,%1,%2,%3}, [%4];" : "=r"(v.x), "=r"(v.y), "=r"(v.z), "=r"(v.w) : "r"(a + S0) : "memory");
    return v;
}
__device__ __forceinline__ float4 lds128f(uint32_t a) {
    float4 v;
    asm volatile("ld.shared.v4.f32 {%0,%1,%2,%3}, [%4];" : "=f"(v.x), "=f"(v.y), "=f"(v.z), "=f"(v.w) : "r"(a + S0) : "memory");
    return v;
}
__device__ __forceinline__ float2 lds64f(uint32_t a) {
    float2 v;
    asm volatile("ld.shared.v2.f32 {%0,%1}, [%2];" : "=f"(v.x), "=f"(v.y) : "r"(a + S0) : "memory");
    return v;
}
__device__ __forceinline__ float bf_lo(uint32_t u) { return __uint_as_float(u << 16); }
__device__ __forceinline__ float bf_hi(uint32_t u) { return __uint_as_float(u & 0xffff0000u); }
__device__ __forceinline__ uint32_t pack_bf(float lo, float hi) {
    uint32_t r;
    asm("cvt.rn.bf16x2.f32 %0, %1, %2;" : "=r"(r) : "f"(hi), "f"(lo));
    return r;
}
__device__ __forceinline__ float tanh_fast(float x) {
    float r;
    asm("tanh.approx.f32 %0, %1;" : "=f"(r) : "f"(x));
    return r;
}
__device__ __forceinline__ float silu_half(float h) { return fmaf(h, tanh_fast(h), h); }
__device__ __forceinline__ void ldsm4(uint32_t (&u)[4], uint32_t a) {
    asm volatile("ldmatrix.sync.aligned.m8n8.x4.shared.b16 {%0,%1,%2,%3}, [%4];"
                 : "=r"(u[0]), "=r"(u[1]), "=r"(u[2]), "=r"(u[3]) : "r"(a + S0) : "memory");
}
__device__ __forceinline__ void ldsm4t(uint32_t (&u)[4], uint32_t a) {
    asm volatile("ldmatrix.sync.aligned.m8n8.x4.trans.shared.b16 {%0,%1,%2,%3}, [%4];"
                 : "=r"(u[0]), "=r"(u[1]), "=r"(u[2]), "=r"(u[3]) : "r"(a + S0) : "memory");
}
__device__ __forceinline__ void stsm4(uint32_t a, uint32_t p0, uint32_t p1, uint32_t p2, uint32_t p3) {
    asm volatile("stmatrix.sync.aligned.m8n8.x4.shared.b16 [%0], {%1,%2,%3,%4};" ::"r"(a + S0), "r"(p0), "r"(p1), "r"(p2), "r"(p3) : "memory");
}
__device__ __forceinline__ void stsm4t(uint32_t a, uint32_t p0, uint32_t p1, uint32_t p2, uint32_t p3) {
    asm volatile("stmatrix.sync.aligned.m8n8.x4.trans.shared.b16 [%0], {%1,%2,%3,%4};" ::"r"(a + S0), "r"(p0), "r"(p1), "r"(p2), "r"(p3) : "memory");
}

#define R8(o) "+f"(d[o]), "+f"(d[o + 1]), "+f"(d[o + 2]), "+f"(d[o + 3]), "+f"(d[o + 4]), "+f"(d[o + 5]), "+f"(d[o + 6]), "+f"(d[o + 7])
template <uint32_t ALO, uint32_t BLO, uint64_t AHI = 8, uint64_t BHI = 48>
__device__ __forceinline__ void wgmma128(float (&d)[64]) {
    asm volatile(
        "wgmma.mma_async.sync.aligned.m64n128k16.f32.bf16.bf16 "
        "{%0,%1,%2,%3,%4,%5,%6,%7,%8,%9,%10,%11,%12,%13,%14,%15,%16,%17,%18,%19,%20,%21,%22,%23,%24,%25,%26,%27,%28,%29,%30,%31,"
        "%32,%33,%34,%35,%36,%37,%38,%39,%40,%41,%42,%43,%44,%45,%46,%47,%48,%49,%50,%51,%52,%53,%54,%55,%56,%57,%58,%59,%60,%61,%62,%63},"
        " %64, %65, 1, 1, 1, 0, 0;"
        : R8(0), R8(8), R8(16), R8(24), R8(32), R8(40), R8(48), R8(56)
        : "l"((AHI << 32) | ALO), "l"((BHI << 32) | BLO));
}
template <int S>
__device__ __forceinline__ void mma_stages(float (&d)[64], int conv, int tid, Scratch* gs) {
    constexpr uint32_t A = ((SM_ACT + S * 2 * CH_PITCH + 16) >> 4) | ((CH_PITCH >> 4) << 16);
    constexpr uint32_t B = (slot_addr(S % NS) >> 4) | (8u << 16);
    if (S == 0) {
        unsigned it = 0;
#pragma unroll 1
        while (!MMA0_WAIT(BAR(BAR_FULL), conv) && ++it < SPIN_LIMIT) {}
    }
    bool next_ok = true;
    constexpr uint32_t NEXT = S + 1 < NSTAGE ? BAR(BAR_FULL + S + 1) : BAR(BAR_EMB);
    const int npar = S + 1 < NSTAGE ? conv : 0;
    next_ok = mbar_test(NEXT, npar);
    if (S == 0 && tid == 0) TL(32 + conv * 24);
    asm volatile("wgmma.fence.sync.aligned;" ::: "memory");
    wgmma128<A, B>(d);
    wgmma128<A + 1, B + 16>(d);
    wgmma128<A + 2, B + 32>(d);
    asm volatile("wgmma.commit_group.sync.aligned;" ::: "memory");
    if (S >= LAG) {
        asm volatile("wgmma.wait_group.sync.aligned %0;" ::"n"(LAG) : "memory");
        if ((tid & 31) == 0) mbar_arrive(BAR(BAR_WEMPTY + (S + NS - LAG) % NS));
    }
    if (!next_ok) mbar_wait(NEXT, npar);
    if constexpr (S + 1 < NSTAGE) mma_stages<S + 1>(d, conv, tid, gs);
}

__device__ __forceinline__ void weight_load(uint4 (&t)[5], const __nv_bfloat16* w, int cta, int lane) {
    const char* base = reinterpret_cast<const char*>(w) + ((cta & 15) * 8 * C + (cta >> 4) * 16) * 18;
#pragma unroll
    for (int k = 0; k < 5; k++) {
        const int i = lane + 32 * k, row = (i * 57) >> 10;
        if (k < 4 || lane < 16) t[k] = __ldg(reinterpret_cast<const uint4*>(base + row * (C * 18 - 288) + i * 16));
    }
}
__device__ __forceinline__ void weight_block(uint32_t bounce, unsigned char* wt, int cta, int lane, bool readback, Scratch* gs) {
    unsigned char* dst = wt + (cta >> 4) * STAGE_BYTES + (cta & 15) * 768;
    if (lane < 16) {
        uint32_t v[36];
#pragma unroll
        for (int i = 0; i < 9; i++) {
            const uint4 q = lds128(bounce + (lane & 7) * 288 + (lane >> 3) * 144 + i * 16);
            v[4 * i] = q.x; v[4 * i + 1] = q.y; v[4 * i + 2] = q.z; v[4 * i + 3] = q.w;
        }
#pragma unroll
        for (int kyo = 0; kyo < 3; kyo++) {
#pragma unroll
            for (int kx = 0; kx < 3; kx++) {
                const int tap = ky_of(kyo) * 3 + kx;
                uint32_t o[4];
#pragma unroll
                for (int m = 0; m < 4; m++) {
                    const int i0 = 18 * m + tap, i1 = i0 + 9;
                    const uint32_t sel = ((i0 & 1) ? 0x32u : 0x10u) | ((i1 & 1) ? 0x7600u : 0x5400u);
                    o[m] = __byte_perm(v[i0 >> 1], v[i1 >> 1], sel);
                }
                *reinterpret_cast<uint4*>(dst + kyo * 8 * STAGE_BYTES + kx * 256 + lane * 16) = make_uint4(o[0], o[1], o[2], o[3]);
            }
        }
    }
    if (readback) {
        __syncwarp();
        unsigned acc = 0;
        if (lane < 24) {
#pragma unroll
            for (int i = 0; i < 3; i++) acc |= ld_relaxed(dst + i * 8 * STAGE_BYTES + lane * 32);
        }
        asm volatile("{\n.reg .pred p;\nsetp.eq.u32 p, %0, 0x9e3779b9;\n@p st.shared.u32 [%1], %0;\n}" ::"r"(acc), "r"(bounce + S0) : "memory");
    }
}
__device__ __forceinline__ uint32_t act2(uint32_t u, const float4& cf) {
    return pack_bf(silu_half(fmaf(bf_lo(u), cf.x, cf.z)), silu_half(fmaf(bf_hi(u), cf.y, cf.w)));
}
__device__ __forceinline__ void norm_unit(uint32_t (&u)[4], const float4& ca, const float4& cb) {
    u[0] = act2(u[0], ca); u[1] = act2(u[1], ca); u[2] = act2(u[2], cb); u[3] = act2(u[3], cb);
}
__device__ __forceinline__ void read_stats(uint32_t gst, float (&g)[8]) {
    asm volatile("ld.volatile.shared.v4.f32 {%0,%1,%2,%3}, [%4];" : "=f"(g[0]), "=f"(g[1]), "=f"(g[2]), "=f"(g[3]) : "r"(gst + S0) : "memory");
    asm volatile("ld.volatile.shared.v4.f32 {%0,%1,%2,%3}, [%4];" : "=f"(g[4]), "=f"(g[5]), "=f"(g[6]), "=f"(g[7]) : "r"(gst + 16 + S0) : "memory");
}
template <int T>
__device__ __forceinline__ void wait_stats(uint32_t gst, float (&g)[8]) {
    float rs, mr;
    unsigned it = 0;
#pragma unroll 1
    do {
        asm volatile("ld.volatile.shared.v2.f32 {%0,%1}, [%2];" : "=f"(rs), "=f"(mr) : "r"(gst + 8 * T + S0) : "memory");
    } while (!__all_sync(0xffffffffu, rs != 0.f) && ++it < 8 * SPIN_LIMIT);
    if (T < 3) read_stats(gst, g);
    g[2 * T] = rs; g[2 * T + 1] = mr;
}
template <int T>
__device__ __forceinline__ void own_unit(uint32_t (&o)[4], const float (&z)[8], float4 (&cf)[8], const float (&g)[8]) {
    float4 &ca = cf[2 * T], &cb = cf[2 * T + 1];
    const float rs = g[2 * T], mr = g[2 * T + 1];
    ca.z = fmaf(-mr, ca.x, ca.z); ca.w = fmaf(-mr, ca.y, ca.w);
    cb.z = fmaf(-mr, cb.x, cb.z); cb.w = fmaf(-mr, cb.y, cb.w);
#pragma unroll
    for (int i = 0; i < 4; i++)
        o[i] = pack_bf(silu_half(fmaf(z[2 * i], rs, i < 2 ? ca.z : cb.z)), silu_half(fmaf(z[2 * i + 1], rs, i < 2 ? ca.w : cb.w)));
}
template <int FIRST, int N>
__device__ __forceinline__ void norm_block(uint32_t (&u)[4][4], float4 (&cf)[8], uint32_t act, uint32_t mask, uint32_t fbar, int lane) {
#pragma unroll
    for (int t = FIRST; t < FIRST + N; t++) {
        norm_unit(u[t], cf[2 * t], cf[2 * t + 1]);
        stsm4(act + t * 2 * KC_BYTES, u[t][0] & mask, u[t][1] & mask, u[t][2] & mask, u[t][3] & mask);
    }
    fence_async_smem();
    __syncwarp();
    if (lane < N) mbar_arrive(fbar + 16 * (FIRST + lane));
}
__device__ __forceinline__ void publish(uint32_t bar, int lane) {
    fence_async_smem();
    __syncwarp();
    if (lane == 0) mbar_arrive(bar);
}
template <int T>
__device__ __forceinline__ void next_unit(const float (&z)[8], float4 (&cf)[8], uint32_t gst, float (&g)[8], uint32_t act, uint32_t fbar, int lane) {
    const bool have = __all_sync(0xffffffffu, g[2 * T] != 0.f);
    if (!have) { publish(fbar + 16 * (T - 1), lane); wait_stats<T>(gst, g); }
    uint32_t o[4];
    own_unit<T>(o, z, cf, g);
    if (have) publish(fbar + 16 * (T - 1), lane);
    stsm4(act + T * 2 * KC_BYTES, o[0], o[1], o[2], o[3]);
}
__device__ __forceinline__ void stat_mma(float (&c)[4], uint32_t p, uint32_t q) {
    asm("mma.sync.aligned.m16n8k16.row.col.f32.bf16.bf16.f32 {%0,%1,%2,%3}, {%4,%5,%6,%5}, {%4,%6}, {%0,%1,%2,%3};"
        : "+f"(c[0]), "+f"(c[1]), "+f"(c[2]), "+f"(c[3]) : "r"(p), "r"(0x3f803f80u), "r"(q));
}
__device__ __forceinline__ void stat_store(const float (&c)[4], uint32_t dst, int lane) {
    const int g = lane >> 2, t = lane & 3;
    if (t == (g >> 1)) sts32f(dst + g * 4, (g & 1) ? c[1] : c[0]);
    if (g == 7) sts32f(dst + 32 + t * 4, c[2] + c[3]);
}
__device__ __forceinline__ float sum4(float4 v) { return (v.x + v.y) + (v.z + v.w); }
__device__ __forceinline__ void stat_publish(uint32_t src, float* acc, int lane, bool real) {
    const uint32_t a = src + (lane & 15) * 48;
    float q = sum4(lds128f(a)) + sum4(lds128f(a + 16)), sm = sum4(lds128f(a + 32));
    q += __shfl_xor_sync(0xffffffffu, q, 1); sm += __shfl_xor_sync(0xffffffffu, sm, 1);
    q += __shfl_xor_sync(0xffffffffu, q, 2); sm += __shfl_xor_sync(0xffffffffu, sm, 2);
    if (real && (lane & 19) == 0) red_add4(acc + lane, 1.f, sm, q, 1.f);
}
__device__ __forceinline__ void fence_acc(float (&d)[64]) {
#pragma unroll
    for (int i = 0; i < 64; i++) asm volatile("" : "+f"(d[i])::"memory");
}
__device__ __forceinline__ void ld_unit(uint32_t (&u)[4], const uint4* p) {
    asm volatile("ld.relaxed.gpu.global.v4.u32 {%0,%1,%2,%3}, [%4];" : "=r"(u[0]), "=r"(u[1]), "=r"(u[2]), "=r"(u[3]) : "l"(p) : "memory");
}

__device__ __noinline__ void side_jobs(const __nv_bfloat16* __restrict__ t_emb, const __nv_bfloat16* __restrict__ w_emb,
                                       const __nv_bfloat16* __restrict__ w2, Scratch* __restrict__ gs, unsigned clk0) {
    const int tid = threadIdx.x, warp = tid >> 5, lane = tid & 31, j = blockIdx.x;
    float tv = 0.f;
    if (lane < 24) tv = __bfloat162float(t_emb[(lane / 12) * E + j * 192 + warp * 12 + lane % 12]);
    if (tid == 0) {
        mbar_init(BAR(0), 1);
        mbar_expect(BAR(0), 192 * C * 2);
        fence_async_smem();
        while (clock32() - clk0 < SDELAY) {}
#pragma unroll
        for (int i = 0; i < 4; i++)
            asm volatile("cp.async.bulk.prefetch.L2.global [%0], 18432;" ::"l"(reinterpret_cast<const char*>(w2) + (j * 4 + i) * 18432) : "memory");
#pragma unroll
        for (int i = 0; i < 4; i++) bulk_g2s(S0 + SM_W + i * 12288, w_emb + (j * 192 + i * 48) * C, 12288, S0 + BAR(0));
    }
    if (j == 0 && tid < 32) gs->acc2[(tid >> 4) * LS + (tid & 15)] = 0.f;
    const float sv = silu_half(0.5f * tv);
    __syncthreads();
    mbar_wait(BAR(0), 0);
    float acc[8] = {0.f, 0.f, 0.f, 0.f, 0.f, 0.f, 0.f, 0.f};
#pragma unroll
    for (int i = 0; i < 12; i++) {
        const float2 wq = lds64f(SM_W + (warp * 12 + i) * 256 + lane * 8);
        const uint32_t wx = __float_as_uint(wq.x), wy = __float_as_uint(wq.y);
#pragma unroll
        for (int bb = 0; bb < 2; bb++) {
            const float sx = __shfl_sync(0xffffffffu, sv, bb * 12 + i);
            acc[4 * bb + 0] = fmaf(sx, bf_lo(wx), acc[4 * bb + 0]); acc[4 * bb + 1] = fmaf(sx, bf_hi(wx), acc[4 * bb + 1]);
            acc[4 * bb + 2] = fmaf(sx, bf_lo(wy), acc[4 * bb + 2]); acc[4 * bb + 3] = fmaf(sx, bf_hi(wy), acc[4 * bb + 3]);
        }
    }
    sts128f(SM_ACT + warp * 1024 + lane * 16, make_float4(acc[0], acc[1], acc[2], acc[3]));
    sts128f(SM_ACT + warp * 1024 + 512 + lane * 16, make_float4(acc[4], acc[5], acc[6], acc[7]));
    __syncthreads();
    if (tid < 128) {
        float2 sum = make_float2(0.f, 0.f);
#pragma unroll
        for (int w = 0; w < 16; w++) { const float2 p = lds64f(SM_ACT + w * 1024 + tid * 8); sum.x += p.x; sum.y += p.y; }
        *reinterpret_cast<float2*>(&gs->emb[j * NB * C + tid * 2]) = sum;
        bar_sync(1, 128);
        if (tid < 2) asm volatile("red.release.gpu.global.add.u32 [%0], 1;" ::"l"(&gs->wcnt[(2 * NB + tid) * LS]) : "memory");
    }
}

__global__ void __cluster_dims__(2, 1, 1) __launch_bounds__(NTHREADS, 1)
resblock_kernel(const __nv_bfloat16* __restrict__ w1, const __nv_bfloat16* __restrict__ x,
                const __nv_bfloat16* __restrict__ t_emb, const __nv_bfloat16* __restrict__ g1,
                const __nv_bfloat16* __restrict__ be1, const __nv_bfloat16* __restrict__ w_emb,
                const __nv_bfloat16* __restrict__ g2, const __nv_bfloat16* __restrict__ be2,
                const __nv_bfloat16* __restrict__ w2, __nv_bfloat16* __restrict__ out, Scratch* __restrict__ gs,
                const __grid_constant__ CUtensorMap xmap) {
    const unsigned clk0 = clock32();
    if (threadIdx.x == 480 && blockIdx.x >= NXTRA) TLG(1);
    const int tid = threadIdx.x, lane = tid & 31;
    const int cta = blockIdx.x - NXTRA, b = cta >> 6, r = cta & 63;
    uint4 v[5];
    if (tid < 32) weight_load(v, w1, cta & (NCTA - 1), lane);
    uint4 xv[8];
    const int wg4 = (tid >> 5) - 1;
    const bool early = tid >= 32 && wg4 < NLDG;
    if (early) {
        const char* src = reinterpret_cast<const char*>(x) + (uint32_t)((((b & 1) * C + wg4 * 32 + (lane >> 3)) * HW + r) * HW * 2 + (lane & 7) * 16);
        while (clock32() - clk0 < XDELAY + (wg4 >> 1) * XSTAG + (wg4 & 1) * XSTAG2) {}
#pragma unroll
        for (int i = 0; i < 8; i++) xv[i] = __ldg(reinterpret_cast<const uint4*>(src + i * (4 * HW * HW * 2)));
    }
    const int warp = __shfl_sync(0xffffffffu, tid >> 5, 0);
    if (cta < 0) { side_jobs(t_emb, w_emb, w2, gs, clk0); return; }

    if (warp != 4) asm volatile("barrier.cluster.arrive.relaxed.aligned;" ::: "memory");
    const bool has_outer = (r != 0) && (r != HW - 1);
    if (warp == 1 || warp == 2 || warp == 3 || warp == 5) {
        const int g = warp < 4 ? warp - 1 : 3;
        if (elect_one()) {
            if (g >= NLDG) asm volatile("prefetch.tensormap [%0];" ::"l"(&xmap) : "memory");
            mbar_init(BAR(BAR_X) + 8 * g, 1);
            if (g >= NLDG) mbar_expect(BAR(BAR_X) + 8 * g, 4096);
            fence_async_smem();
        }
        __syncwarp();
        bar_arrive(4, 256 + 32 + 128);
        if (g >= NLDG) {
            while (clock32() - clk0 < XDELAY + (g >> 1) * XSTAG + (g & 1) * XSTAG2) {}
            if (elect_one()) tma_x(SM_XOWN + g * 4096, &xmap, r, b * C + g * 32, BAR(BAR_X) + 8 * g);
            __syncwarp();
            mbar_wait(BAR(BAR_X) + 8 * g, 0);
#pragma unroll
            for (int k = 0; k < 8; k++) xv[k] = lds128(SM_XOWN + g * 4096 + k * 512 + lane * 16);
        }
        float c[8][4];
#pragma unroll
        for (int k = 0; k < 8; k++) {
            c[k][0] = c[k][1] = c[k][2] = c[k][3] = 0.f;
            stat_mma(c[k], xv[k].x, xv[k].y); stat_mma(c[k], xv[k].z, xv[k].w);
        }
#pragma unroll
        for (int i = 0; i < 4; i++) c[0][i] = ((c[0][i] + c[1][i]) + (c[2][i] + c[3][i])) + ((c[4][i] + c[5][i]) + (c[6][i] + c[7][i]));
        stat_store(c[0], SM_RED + g * 48, lane);
        __syncwarp();
        if (lane == 0) {
            const uint32_t a = SM_RED + g * 48;
            red_add4(&gs->acc1[b * LS + g * 4], 1.f, sum4(lds128f(a + 32)), sum4(lds128f(a)) + sum4(lds128f(a + 16)), 1.f);
            TL(74 + g);
        }
        if (g < NLDG) {
#pragma unroll
            for (int i = 0; i < 8; i++)
                sts128(SM_XOWN + g * 4096 + i * 512 + (lane >> 3) * 128 + (((lane & 7) ^ ((lane >> 3) + 4 * (i & 1))) << 4), xv[i]);
            __syncwarp();
            if (lane == 0) mbar_arrive(BAR(BAR_X) + 8 * g);
        }
    }
    if (warp == 4) {
            if (elect_one()) {
#pragma unroll
                for (int i = 0; i < NSTAGE; i++) mbar_init(BAR(BAR_FULL + i), (i >> 3) == 1 ? 1 : 5);
#pragma unroll
                for (int i = 0; i < NS + 2; i++) mbar_init(BAR(BAR_WEMPTY + i), 4);
#pragma unroll
                for (int i = BAR_STATS; i < BAR_X; i++) mbar_init(BAR(i), i == BAR_EMB ? 3 : 1);
                mbar_init(BAR(BAR_X + 4), 1);
                asm volatile("fence.mbarrier_init.release.cluster;" ::: "memory");
            }
            if (lane < 4) sts128(SM_GST + lane * 16, make_uint4(0, 0, 0, 0));
            __syncwarp();
            fence_async_smem();
            bar_arrive(0, 96);
            bar_arrive(5, 64);
            bar_arrive(4, 256 + 32 + 128);
            const uint4 z = make_uint4(0, 0, 0, 0);
#pragma unroll
            for (int i = 0; i < 2; i++) sts128(SM_ACT + (i * 16 + (lane >> 1)) * CH_PITCH + (lane & 1) * 16, z);
            if (lane < 4) sts128(SM_ACT + (2 + (lane >> 1)) * ROW_BYTES + (lane & 1) * 16, z);
            if (lane < 16) sts128(SM_ONES + lane * 16, make_uint4(lane < 8 ? 0x3f803f80u : 0u, 0, 0, 0));
            fence_async_smem();
            bar_arrive(7, 160);
            asm volatile("barrier.cluster.arrive.relaxed.aligned;" ::: "memory");
            while (clock32() - clk0 < W2DELAY) {}
            weight_load(v, w2, cta, lane);
        }
    if (warp == 0 || warp == 4) {
        const int k = warp >> 2;
#pragma unroll
        for (int i = 0; i < 5; i++)
            if (i < 4 || lane < 16) sts128(SM_BNC + k * 2304 + (lane + 32 * i) * 16, v[i]);
        if (lane == 0) TL(k ? 14 : 81);
        __syncwarp();
        weight_block(SM_BNC + k * 2304, gs->wt + k * NSTAGE * STAGE_BYTES, cta, lane, true, gs);
        __syncwarp();
        if (lane == 0) TL(k ? 13 : 4);
        if (lane < 2) asm volatile("red.relaxed.gpu.global.add.u32 [%0], 1;" ::"l"(k ? &gs->wcnt[(NB + lane) * LS] : &gs->w1cnt[(lane * 8 + (cta >> 4)) * KS]) : "memory");
    }

    if (warp >= 8) {
        const int nw = warp - 8;
        if (nw < 2) {
            const uint2 ga = __ldg(reinterpret_cast<const uint2*>(nw ? g2 : g1) + lane), bt = __ldg(reinterpret_cast<const uint2*>(nw ? be2 : be1) + lane);
            sts128f(SM_COEF + nw * 1024 + lane * 32, make_float4(0.5f * bf_lo(ga.x), 0.5f * bf_hi(ga.x), 0.5f * bf_lo(bt.x), 0.5f * bf_hi(bt.x)));
            sts128f(SM_COEF + nw * 1024 + lane * 32 + 16, make_float4(0.5f * bf_lo(ga.y), 0.5f * bf_hi(ga.y), 0.5f * bf_lo(bt.y), 0.5f * bf_hi(bt.y)));
        }
        bar_sync(4, 256 + 32 + 128);
        const int par = nw >> 2, wq = nw & 3;
        const uint32_t act_off = SM_ACT + (par * 2 + (lane >> 4)) * CH_PITCH + (2 + wq * 16 + (lane & 15)) * 16;
        const uint32_t stg_off = (par * 16 + (lane >> 4) * 8 + (lane & 7)) * 128 + (((2 * wq + ((lane >> 3) & 1)) ^ (lane & 7)) << 4);
        const uint32_t cfa = SM_COEF + par * 128 + (lane & 3) * 16;
        const uint32_t fbar = BAR(BAR_FULL) + 8 * par;
        uint4* inbox = gs->box + cta * 1024 + nw * 32 + lane;
#pragma unroll 1
        for (int conv = 0; conv < 2; conv++) {
            uint32_t u[4][4], w[4][4];
            float4 cf[8];
            if (conv == 0) {
#pragma unroll
                for (int i = 0; i < 4; i++) { mbar_wait(BAR(BAR_X + i), 0); ldsm4t(u[i], SM_XOWN + stg_off + i * 4096); }
            } else {
                mbar_wait(BAR(BAR_HW), 0);
#pragma unroll
                for (int i = 0; i < 4; i++) ldsm4(u[i], act_off + i * 2 * KC_BYTES);
            }
#pragma unroll
            for (int i = 0; i < 8; i++) cf[i] = lds128f(cfa + conv * 1024 + (i >> 1) * 256 + (i & 1) * 64);
            const uint32_t gst = SM_GST + conv * 32;
            float gv[8], z[4][8];
#pragma unroll
            for (int i = 0; i < 16; i++) {
                const float4& c = cf[i >> 1];
                z[i >> 2][2 * (i & 3)] = bf_lo(u[i >> 2][i & 3]) * c.x; z[i >> 2][2 * (i & 3) + 1] = bf_hi(u[i >> 2][i & 3]) * c.y;
                asm volatile("" : "+f"(z[i >> 2][2 * (i & 3)]), "+f"(z[i >> 2][2 * (i & 3) + 1]));
            }
            wait_stats<0>(gst, gv);
            if (tid == 256) TL(22 + conv * 4);
            if (par) { const unsigned c1 = clock32(); while (clock32() - c1 < PDELAY) {} }
            uint32_t o[4];
            own_unit<0>(o, z[0], cf, gv);
            stsm4(act_off, o[0], o[1], o[2], o[3]);
            publish(fbar, lane);
            if (tid == 256) TL(8 + conv * 8);
            if (!__all_sync(0xffffffffu, gv[2] != 0.f)) wait_stats<1>(gst, gv);
            own_unit<1>(o, z[1], cf, gv);
            stsm4(act_off + 2 * KC_BYTES, o[0], o[1], o[2], o[3]);
            next_unit<2>(z[2], cf, gst, gv, act_off, fbar, lane);
            next_unit<3>(z[3], cf, gst, gv, act_off, fbar, lane);
            publish(fbar + 48, lane);
#pragma unroll
            for (int i = 0; i < 8; i++) { cf[i].x *= gv[i & ~1]; cf[i].y *= gv[i & ~1]; }
            if (tid == 256) TL(84 + conv);
            if (has_outer) {
                mbar_wait(BAR(BAR_X + 4), conv);
                if (conv == 0) {
#pragma unroll
                    for (int i = 0; i < 4; i++) ldsm4t(w[i], SM_XOUT + stg_off + i * 4096);
                } else {
#pragma unroll
                    for (int i = 0; i < 4; i++) {
                        const uint4 q = lds128(SM_XOWN + (tid - 256) * 16 + i * 4096);
                        w[i][0] = q.x; w[i][1] = q.y; w[i][2] = q.z; w[i][3] = q.w;
                    }
                    unsigned it = 0;
                    while (true) {
                        bool ok = true;
#pragma unroll
                        for (int i = 0; i < 16; i++) ok = ok && w[i >> 2][i & 3] != 0;
                        if (__all_sync(0xffffffffu, ok) || ++it > SPIN_LIMIT) break;
#pragma unroll
                        for (int i = 0; i < 4; i++) ld_unit(w[i], inbox + i * 256);
                        if (tid == 256) TL(93);
                    }
#pragma unroll
                    for (int i = 0; i < 16; i++) w[i >> 2][i & 3] = ~w[i >> 2][i & 3];
                }
            }
            if (conv == 0) {
                bar_sync(3, 256);
                if (nw == 0) sts128(SM_ACT + 2 * ROW_BYTES + (lane >> 1) * CH_PITCH + (lane & 1) * 16, make_uint4(0, 0, 0, 0));
            }
            if (tid == 256) TL(24 + conv * 4);
            norm_block<0, 2>(w, cf, act_off + 2 * ROW_BYTES, has_outer ? ~0u : 0u, fbar + 128, lane);
            if (tid == 256) TL(88 + conv);
            norm_block<2, 2>(w, cf, act_off + 2 * ROW_BYTES, has_outer ? ~0u : 0u, fbar + 128, lane);
            if (tid == 256) TL(23 + conv * 4);
        }
        if (has_outer) {
            mbar_wait(BAR(BAR_FULL + NSTAGE - 1), 1);
#pragma unroll
            for (int i = 0; i < 4; i++) inbox[i * 256] = make_uint4(0, 0, 0, 0);
        }
        {
            const int oc0 = par * 64 + ((tid & 127) >> 3), seg = lane & 7;
            __nv_bfloat16* dst = out + ((size_t)(b * C + oc0) * HW + r) * HW + seg * 8;
            const uint32_t src = SM_XOWN + oc0 * 128 + ((seg ^ (oc0 & 7)) << 4);
            bar_sync(par ? 1 : 6, 128 + 128);
#pragma unroll
            for (int i = 0; i < 4; i++) *reinterpret_cast<uint4*>(dst + (size_t)i * 16 * HW * HW) = lds128(src + i * 2048);
            if (tid == 384) { TL(20); TLG(21); }
        }
    } else if (warp < 4) {
        const int wq = warp;
        bar_sync(7, 160);

        const uint32_t xbase = SM_XOWN + ((lane >> 4) * 8 + (lane & 7)) * 128 + (((2 * wq + ((lane >> 3) & 1)) ^ (lane & 7)) << 4);
        float d[64];
#pragma unroll
        for (int i = 0; i < 64; i++) d[i] = 0.f;
#pragma unroll 1
        for (int conv = 0; conv < 2; conv++) {
            fence_acc(d);
            mma_stages<0>(d, conv, tid, gs);
            if (conv == 0) {
                asm volatile("wgmma.fence.sync.aligned;" ::: "memory");
                wgmma128<(SM_ONES >> 4) | (8u << 16), (SM_EMB >> 4), 0, 8>(d);
                asm volatile("wgmma.commit_group.sync.aligned;" ::: "memory");
            }
            asm volatile("wgmma.wait_group.sync.aligned 0;" ::: "memory");
            fence_acc(d);
            if (tid == 0) TL(10 + conv * 8);
            if (conv == 1) {
                fence_acc(d);
#pragma unroll
                for (int kc = 0; kc < 8; kc++) {
                    stsm4t(xbase + kc * 2048, pack_bf(d[8 * kc], d[8 * kc + 1]), pack_bf(d[8 * kc + 2], d[8 * kc + 3]),
                           pack_bf(d[8 * kc + 4], d[8 * kc + 5]), pack_bf(d[8 * kc + 6], d[8 * kc + 7]));
                    if (kc == 3) bar_arrive(6, 128 + 128);
                }
                bar_arrive(1, 128 + 128);
                break;
            }
            uint32_t hp[32];
#pragma unroll
            for (int i = 0; i < 32; i++) hp[i] = pack_bf(d[2 * i], d[2 * i + 1]);
#pragma unroll
            for (int g = 0; g < 4; g++) {
                float c[4] = {0.f, 0.f, 0.f, 0.f};
#pragma unroll
                for (int i = 0; i < 4; i++) stat_mma(c, hp[8 * g + 2 * i], hp[8 * g + 2 * i + 1]);
                stat_store(c, SM_RED + (g * 4 + wq) * 48, lane);
            }
            bar_sync(2, 128);
            if (wq == 0) stat_publish(SM_RED, &gs->acc2[b * LS], lane, true);
            if (tid == 0) TL(11);
            const uint32_t hbase = SM_ACT + (lane >> 4) * CH_PITCH + (2 + wq * 16 + (lane & 15)) * 16;
#pragma unroll
            for (int kc = 0; kc < 8; kc++) stsm4(hbase + kc * 2 * CH_PITCH, hp[4 * kc], hp[4 * kc + 1], hp[4 * kc + 2], hp[4 * kc + 3]);
            __syncwarp();
            if (lane == 0) mbar_arrive(BAR(BAR_HW));
            if (lane < LAG) mbar_arrive(BAR(BAR_WEMPTY + (NSTAGE - LAG) % NS) + 8 * lane);
            if (tid == 0) TL(12);
#pragma unroll
            for (int kc = 0; kc < 8; kc++) {
                uint32_t p[4];
                ldsm4t(p, xbase + kc * 2048);
#pragma unroll
                for (int i = 0; i < 4; i++) { d[8 * kc + 2 * i] = bf_lo(p[i]); d[8 * kc + 2 * i + 1] = bf_hi(p[i]); }
            }
            fence_acc(d);
            bar_sync(2, 128);
#pragma unroll
            for (int kc = 0; kc < 8; kc++) sts128(SM_XOWN + kc * 2048 + tid * 16, make_uint4(~hp[4 * kc], ~hp[4 * kc + 1], ~hp[4 * kc + 2], ~hp[4 * kc + 3]));
            __syncwarp();
            if (lane == 0) mbar_arrive(BAR(BAR_XFREE));
        }
        {
        }
    } else if (warp < 6) {
        if (warp == 5) {
            bar_sync(5, 64);
            mbar_wait(BAR(BAR_FULL + OAFTER), 0);
            if (has_outer && elect_one()) {
                mbar_expect(BAR(BAR_X + 4), 16384);
#pragma unroll
                for (int i = 0; i < 4; i++) tma_x(SM_XOUT + i * 4096, &xmap, r + ((r & 1) ? 1 : -1), b * C + i * 32, BAR(BAR_X + 4));
            }
            __syncwarp();
            asm volatile("barrier.cluster.wait.acquire.aligned;" ::: "memory");
            const uint32_t peer = (r & 1) ^ 1;
            const uint32_t self0 = mapa(0, r & 1), peer0 = mapa(0, peer);
#pragma unroll 1
            for (int conv = 0; conv < 2; conv++) {
                if (FWD0) mbar_wait(BAR(BAR_FULL + FWD0), conv);
#pragma unroll 1
                for (int kc = 0; kc < 8; kc++) {
                    mbar_wait(BAR(BAR_FULL) + 8 * kc, conv);
                    if (elect_one())
                        asm volatile("cp.async.bulk.shared::cluster.shared::cta.mbarrier::complete_tx::bytes [%0], [%1], %2, [%3];"
                                     ::"r"(peer0 + SM_ACT + ROW_BYTES + kc * KC_BYTES), "r"(self0 + SM_ACT + kc * KC_BYTES), "r"(KC_BYTES),
                                       "r"(peer0 + BAR(BAR_FULL + 8) + 8 * kc) : "memory");
                }
                if (lane == 0) TL(86 + conv);
#pragma unroll 1
                for (int kc = 0; kc < 8; kc++) mbar_wait(BAR(BAR_FULL + 8) + 8 * kc, conv);
                if (lane == 0)
                    asm volatile("mbarrier.arrive.relaxed.cluster.shared::cluster.b64 _, [%0];" ::"r"(peer0 + (conv ? BAR(BAR_ACK) : BAR(BAR_EMB))) : "memory");
            }
            mbar_wait(BAR(BAR_ACK), 0);
        } else {
            mbar_wait(BAR(BAR_STATS), 0);
            unsigned it = 0;
            while (ld_relaxed(&gs->wcnt[(2 * NB + b) * LS]) < (unsigned)NXTRA && ++it < SPIN_LIMIT) __nanosleep(100);
            fence_acquire();
            float ev[4] = {0.f, 0.f, 0.f, 0.f};
#pragma unroll
            for (int j = 0; j < NXTRA; j++) {
                const uint4 ef = ld_relaxed_v4(&gs->emb[(j * NB + b) * C + lane * 4]);
                ev[0] += __uint_as_float(ef.x); ev[1] += __uint_as_float(ef.y); ev[2] += __uint_as_float(ef.z); ev[3] += __uint_as_float(ef.w);
            }
#pragma unroll
            for (int i = 0; i < 4; i++) {
                const float hi = bf_lo(pack_bf(ev[i], 0.f));
                sts128(SM_EMB + (lane * 4 + i) * 16, make_uint4(pack_bf(hi, ev[i] - hi), 0, 0, 0));
            }
            fence_async_smem();
            __syncwarp();
            if (lane == 0) { mbar_arrive(BAR(BAR_EMB)); TL(19); }
            if (has_outer) {
                uint4* outbox = gs->box + (cta + ((r & 1) ? 1 : -1)) * 1024 + lane;
                mbar_wait(BAR(BAR_XFREE), 0);
                uint4 q[8];
#pragma unroll
                for (int i = 0; i < 8; i++) q[i] = lds128(SM_XOWN + i * 512 + lane * 16);
                mbar_wait(BAR(BAR_STATS), 1);
                const unsigned c1 = clock32();
#pragma unroll 1
                for (int j = 0; j < 4; j++) {
#pragma unroll
                    for (int i = 0; i < 8; i++) {
                        while (clock32() - c1 < (j * 8 + i) * HPACE) {}
                        outbox[(j * 8 + i) * 32] = q[i];
                        if (j < 3) q[i] = lds128(SM_XOWN + (j * 8 + 8 + i) * 512 + lane * 16);
                    }
                }
                if (lane == 0) TL(5);
                fence_async_smem();
                __syncwarp();
                while (clock32() - c1 < FDELAY) {}
                if (elect_one()) {
                    mbar_expect(BAR(BAR_X + 4), 16384);
                    bulk_g2s(S0 + SM_XOWN, gs->box + cta * 1024, 16384, S0 + BAR(BAR_X + 4));
                }
            }
        }
    } else if (warp == 6) {
        bar_sync(0, 96);
        const uint32_t ebytes = STAGE_BYTES + ((lane >> 3) == 1 ? KC_BYTES : 0);
        if (lane < NSTAGE) mbar_expect(BAR(BAR_FULL) + 8 * lane, ebytes);
        const int swap = (r & 1) ? 0 : 8 * STAGE_BYTES;
        unsigned it = 0;
        {
            int g = 0;
            const unsigned* cnt = &gs->w1cnt[(b * 8 + (lane & 7)) * KS];
            unsigned cv = ld_relaxed(cnt);
#pragma unroll 1
            while (g < NS) {
                unsigned ready = __ballot_sync(0xffffffffu, cv >= 16u);
                if (ready != ~0u) cv = ld_relaxed(cnt);
                ready >>= g;
                if (++it > SPIN_LIMIT) ready = ~0u;
                if (!(ready & 1)) continue;
                fence_async_global();
                if (lane == 0) TL(g ? 3 : 6);
#pragma unroll 1
                for (; (ready & 1) && g < NS; g++, ready >>= 1)
                    if (elect_one())
                        bulk_g2s(S0 + SM_W + g * STAGE_BYTES, gs->wt + g * STAGE_BYTES + (g >= 8 ? swap : 0), STAGE_BYTES, S0 + BAR(BAR_FULL) + 8 * g);
            }
        }
#pragma unroll 1
        for (int q = 3; q < 12; q++) {
            const int conv = q >= 6, qs = conv ? q - 6 : q, sl = q % 3;
            const unsigned char* wsrc = gs->wt + q * 4 * STAGE_BYTES + (qs < 2 ? 0 : (qs < 4 ? swap : -swap));
            const uint32_t par = (q / 3 - 1) & 1;
            if (q == 6) {
                it = 0;
                while (ld_relaxed(&gs->wcnt[(NB + b) * LS]) < (unsigned)NCTA && ++it < SPIN_LIMIT) {}
                fence_acquire();
                fence_async_global();
                if (lane == 0) { mbar_arrive(BAR(BAR_EMB)); TL(2); }
            }
            if (WPAUSE && q == 9) mbar_wait(BAR(BAR_WEMPTY + WPAUSE), par);
#pragma unroll
            for (int i = 0; i < 4; i++) {
                mbar_wait(BAR(BAR_WEMPTY + i) + 32 * sl, par);
                if (i == 0 && (q == 6 || q == 9)) {
                    if ((lane >= NS) == (q == 9) && lane < NSTAGE) mbar_expect(BAR(BAR_FULL) + 8 * lane, ebytes);
                    __syncwarp();
                }
                if (elect_one())
                    bulk_g2s(S0 + SM_W + (sl * 4 + i) * STAGE_BYTES, wsrc + i * STAGE_BYTES, STAGE_BYTES, S0 + BAR(BAR_FULL + i) + 32 * qs);
            }
        }
    } else {
        bar_sync(0, 96);
#pragma unroll 1
        for (int conv = 0; conv < 2; conv++) {
            if (conv == 1) mbar_wait(BAR(BAR_HW), 0);
            const float* asrc = (conv ? gs->acc2 : gs->acc1) + b * LS + (lane & 3) * 4;
            unsigned it = 0;
#pragma unroll 1
            while (true) {
                const uint4 f = ld_relaxed_v4(asrc);
                const bool ok = ((f.x == 0x42800000u) & (f.w == 0x42800000u)) || ++it > SPIN_LIMIT;
                if (ok && lane < 4) {
                    const float inv_n = 1.0f / (32.0f * HW * HW);
                    const float mean = __uint_as_float(f.y) * inv_n;
                    float rs;
                    asm("rsqrt.approx.ftz.f32 %0, %1;" : "=f"(rs) : "f"(fmaxf(fmaf(-mean, mean, __uint_as_float(f.z) * inv_n), 0.f) + 1e-5f));
                    asm volatile("st.shared.v2.f32 [%0], {%1,%2};" ::"r"(S0 + SM_GST + conv * 32 + lane * 8), "f"(rs == 0.f ? 1e-38f : rs), "f"(mean * rs) : "memory");
                }
                if (__all_sync(0xffffffffu, ok)) break;
            }
            if (lane == 0) { mbar_arrive(BAR(BAR_STATS)); TL(7 + conv * 8); }
        }
        if (r == 0) {
            if (lane < 16) gs->acc1[b * LS + lane] = 0.f;
            if (lane < 3) gs->wcnt[(lane * NB + b) * LS] = 0;
            if (lane < 8) gs->w1cnt[(b * 8 + lane) * KS] = 0;
        }
    }
}

}

extern "C" void kernel_launch(void* const* d_in, const int* in_sizes, int n_in, void* d_out, int out_size) {
    (void)in_sizes; (void)n_in; (void)out_size;
    typedef CUresult (*EncodeFn)(CUtensorMap*, CUtensorMapDataType, cuuint32_t, void*, const cuuint64_t*, const cuuint64_t*,
                                 const cuuint32_t*, const cuuint32_t*, CUtensorMapInterleave, CUtensorMapSwizzle,
                                 CUtensorMapL2promotion, CUtensorMapFloatOOBfill);
    static Scratch* gs = nullptr;
    static EncodeFn encode = nullptr;
    if (!gs) {
        cudaFuncSetAttribute(resblock_kernel, cudaFuncAttributeMaxDynamicSharedMemorySize, SM_TOTAL);
        cudaGetSymbolAddress((void**)&gs, g_scratch);
        cudaDriverEntryPointQueryResult qr;
        cudaGetDriverEntryPoint("cuTensorMapEncodeTiled", (void**)&encode, cudaEnableDefault, &qr);
    }
    CUtensorMap xmap;
    const cuuint64_t dims[3] = {HW, HW, NB * C}, strides[2] = {HW * 2, HW * HW * 2};
    const cuuint32_t box[3] = {HW, 1, 32}, es[3] = {1, 1, 1};
    encode(&xmap, CU_TENSOR_MAP_DATA_TYPE_BFLOAT16, 3, d_in[0], dims, strides, box, es, CU_TENSOR_MAP_INTERLEAVE_NONE,
           CU_TENSOR_MAP_SWIZZLE_128B, CU_TENSOR_MAP_L2_PROMOTION_NONE, CU_TENSOR_MAP_FLOAT_OOB_FILL_NONE);
    resblock_kernel<<<NCTA + NXTRA, NTHREADS, SM_TOTAL>>>(
        (const __nv_bfloat16*)d_in[4], (const __nv_bfloat16*)d_in[0], (const __nv_bfloat16*)d_in[1],
        (const __nv_bfloat16*)d_in[2], (const __nv_bfloat16*)d_in[3], (const __nv_bfloat16*)d_in[5],
        (const __nv_bfloat16*)d_in[6], (const __nv_bfloat16*)d_in[7], (const __nv_bfloat16*)d_in[8],
        (__nv_bfloat16*)d_out, gs, xmap);
}
```

```cpp
#include <cuda_runtime.h>
#include <cuda.h>
#include <cuda_bf16.h>
#include <stdint.h>

namespace {

constexpr int C = 128, HW = 64, NB = 2, E = 768;
constexpr int NCTA = NB * HW;
constexpr int NXTRA = 4;
constexpr int NTHREADS = 16 * 32;
constexpr int CH_PITCH = 66 * 16;
constexpr int ROW_BYTES = 16 * CH_PITCH;
constexpr int STEP_BYTES = 4096;
constexpr int STAGE_BYTES = 3 * STEP_BYTES;
constexpr int NSTAGE = 24;
constexpr int KC_BYTES = 2 * CH_PITCH;
constexpr int NS = 12;
constexpr int LAG = 1;
#define XDELAY 400
#define HDELAY 600
#define SEQ 0
#define MMA0_WAIT mbar_try
#define NPOLL 1
#define PD2 0
#define ODELAY 100
#define NLDG 2
#define PSTAG -1
#define PDELAY0 400
#define PDELAY 60
#define RB 1
#define XSTAG2 400
#define XSTAG 800
#define HSEND 0
#define SDELAY 600
#define OAFTER 0
#define W2DELAY 2400

constexpr uint32_t SMEM_BASE = 0x400;
constexpr uint32_t SM_XOWN = SMEM_BASE;
constexpr uint32_t SM_ACT = SM_XOWN + 16384 + 512;
constexpr uint32_t SM_XOUT = SM_ACT + 2 * ROW_BYTES + 512;
static_assert(SM_XOUT % 1024 == 0, "swizzle atom alignment");
constexpr uint32_t SM_W = SM_ACT + 3 * ROW_BYTES + 128;
__host__ __device__ constexpr uint32_t slot_addr(int slot) { return SM_W + slot * STAGE_BYTES; }
constexpr uint32_t SM_COEF = SM_W + NS * STAGE_BYTES;
constexpr uint32_t SM_GST = SM_COEF + 2048;
constexpr uint32_t SM_EMB = SM_GST + 128;
constexpr uint32_t SM_ONES = SM_EMB + 2048;
constexpr uint32_t SM_RED = SM_ONES + 256;
constexpr uint32_t SM_BNC = SM_RED + 1536;
constexpr uint32_t SM_BAR = SM_BNC + 2 * 2304;
constexpr int BAR_FULL = 0, BAR_WEMPTY = NSTAGE, BAR_HW = BAR_WEMPTY + NS, BAR_XFREE = BAR_HW + 1, BAR_STATS = BAR_XFREE + 1,
              BAR_EMB = BAR_STATS + 1, BAR_ACK = BAR_EMB + 1, BAR_X = BAR_ACK + 1  , NBAR = BAR_X + 5;
constexpr int SM_TOTAL = SM_BAR + NBAR * 8 - SMEM_BASE;
static_assert(SM_TOTAL <= 232448, "smem");
static_assert(NBAR <= 96, "barrier init");
__host__ __device__ constexpr uint32_t BAR(int i) { return SM_BAR + 8 * i; }
__host__ __device__ constexpr int ky_of(int kyo) { return kyo == 0 ? 1 : (kyo == 1 ? 0 : 2); }

constexpr unsigned SPIN_LIMIT = 1u << 16;

#define LS 1056
#define GS1 4
#define PD 0
#define FWD0 0
#define KS 32
struct Scratch {
    float acc1[NB * LS];
    float acc2[NB * LS];
    unsigned wcnt[3 * NB * LS];
    unsigned w1cnt[NB * 8 * KS];
    float emb[NXTRA * NB * C];
    alignas(1024) unsigned char wt[2 * NSTAGE * STAGE_BYTES];
    uint4 box[NCTA * 1024];
};
__device__ __align__(1024) Scratch g_scratch;
#define TL(i) do {} while (0)
#define TLG(i) do {} while (0)

__device__ __forceinline__ unsigned clock32() { unsigned c; asm volatile("mov.u32 %0, %%clock;" : "=r"(c)); return c; }
__device__ __forceinline__ uint32_t mapa(uint32_t a, uint32_t rank) {
    uint32_t d;
    asm("mapa.shared::cluster.u32 %0, %1, %2;" : "=r"(d) : "r"(a), "r"(rank));
    return d;
}
#define S0 mapa(0, blockIdx.x & 1)
__device__ __forceinline__ void mbar_init(uint32_t bar, int cnt) {
    asm volatile("mbarrier.init.shared::cta.b64 [%0], %1;" ::"r"(bar + S0), "r"(cnt) : "memory");
}
__device__ __forceinline__ void mbar_arrive(uint32_t bar) {
    asm volatile("mbarrier.arrive.shared::cta.b64 _, [%0];" ::"r"(bar + S0) : "memory");
}
__device__ __forceinline__ void mbar_expect(uint32_t bar, uint32_t bytes) {
    asm volatile("mbarrier.arrive.expect_tx.shared::cta.b64 _, [%0], %1;" ::"r"(bar + S0), "r"(bytes) : "memory");
}
__device__ __forceinline__ bool mbar_try(uint32_t bar, uint32_t par) {
    uint32_t ok;
    asm volatile("{\n.reg .pred p;\nmbarrier.try_wait.parity.shared::cta.b64 p, [%1], %2;\nselp.u32 %0, 1, 0, p;\n}"
                 : "=r"(ok) : "r"(bar + S0), "r"(par) : "memory");
    return ok;
}
__device__ __forceinline__ bool mbar_test(uint32_t bar, uint32_t par) {
    uint32_t ok;
    asm volatile("{\n.reg .pred p;\nmbarrier.test_wait.parity.shared::cta.b64 p, [%1], %2;\nselp.u32 %0, 1, 0, p;\n}"
                 : "=r"(ok) : "r"(bar + S0), "r"(par) : "memory");
    return ok;
}
__device__ __forceinline__ void mbar_wait(uint32_t bar, uint32_t par) {
    unsigned it = 0;
#pragma unroll 1
    while (!mbar_try(bar, par) && ++it < SPIN_LIMIT) {}
}
__device__ __forceinline__ bool elect_one() {
    uint32_t p;
    asm volatile("{\n.reg .pred p;\nelect.sync _|p, 0xffffffff;\nselp.u32 %0, 1, 0, p;\n}" : "=r"(p));
    return p;
}
__device__ __forceinline__ void fence_async_smem() { asm volatile("fence.proxy.async.shared::cta;" ::: "memory"); }
__device__ __forceinline__ void fence_async_global() { asm volatile("fence.proxy.async.global;" ::: "memory"); }
__device__ __forceinline__ void fence_acquire() { asm volatile("fence.acquire.gpu;" ::: "memory"); }
__device__ __forceinline__ void bar_sync(int id, int n) { asm volatile("bar.sync %0, %1;" ::"r"(id), "r"(n) : "memory"); }
__device__ __forceinline__ void bar_arrive(int id, int n) { asm volatile("bar.arrive %0, %1;" ::"r"(id), "r"(n) : "memory"); }
__device__ __forceinline__ void bulk_g2s(uint32_t dst, const void* src, uint32_t bytes, uint32_t bar) {
    asm volatile("cp.async.bulk.shared::cluster.global.mbarrier::complete_tx::bytes [%0], [%1], %2, [%3];"
                 ::"r"(dst), "l"(src), "r"(bytes), "r"(bar) : "memory");
}
__device__ __forceinline__ void tma_x(uint32_t dst, const CUtensorMap* tm, int row, int ch, uint32_t bar) {
    asm volatile("cp.async.bulk.tensor.3d.shared::cluster.global.mbarrier::complete_tx::bytes [%0], [%1, {%2, %3, %4}], [%5];"
                 ::"r"(dst + S0), "l"(tm), "r"(0), "r"(row), "r"(ch), "r"(bar + S0) : "memory");
}
__device__ __forceinline__ uint4 ld_relaxed_v4(const void* p) {
    uint4 v;
    asm volatile("ld.relaxed.gpu.global.v4.u32 {%0,%1,%2,%3}, [%4];" : "=r"(v.x), "=r"(v.y), "=r"(v.z), "=r"(v.w) : "l"(p) : "memory");
    return v;
}
__device__ __forceinline__ unsigned ld_relaxed(const void* p) {
    unsigned v;
    asm volatile("ld.relaxed.gpu.global.u32 %0, [%1];" : "=r"(v) : "l"(p) : "memory");
    return v;
}
__device__ __forceinline__ void red_add4(float* p, float a, float b, float c, float d) {
    asm volatile("red.relaxed.gpu.global.add.v4.f32 [%0], {%1,%2,%3,%4};" ::"l"(p), "f"(a), "f"(b), "f"(c), "f"(d) : "memory");
}
__device__ __forceinline__ void sts128(uint32_t a, uint4 v) {
    asm volatile("st.shared.v4.u32 [%0], {%1,%2,%3,%4};" ::"r"(a + S0), "r"(v.x), "r"(v.y), "r"(v.z), "r"(v.w) : "memory");
}
__device__ __forceinline__ void sts128f(uint32_t a, float4 v) {
    asm volatile("st.shared.v4.f32 [%0], {%1,%2,%3,%4};" ::"r"(a + S0), "f"(v.x), "f"(v.y), "f"(v.z), "f"(v.w) : "memory");
}
__device__ __forceinline__ void sts32f(uint32_t a, float v) { asm volatile("st.shared.f32 [%0], %1;" ::"r"(a + S0), "f"(v) : "memory"); }
__device__ __forceinline__ uint4 lds128(uint32_t a) {
    uint4 v;
    asm volatile("ld.shared.v4.u32 {%0,%1,%2,%3}, [%4];" : "=r"(v.x), "=r"(v.y), "=r"(v.z), "=r"(v.w) : "r"(a + S0) : "memory");
    return v;
}
__device__ __forceinline__ float4 lds128f(uint32_t a) {
    float4 v;
    asm volatile("ld.shared.v4.f32 {%0,%1,%2,%3}, [%4];" : "=f"(v.x), "=f"(v.y), "=f"(v.z), "=f"(v.w) : "r"(a + S0) : "memory");
    return v;
}
__device__ __forceinline__ float2 lds64f(uint32_t a) {
    float2 v;
    asm volatile("ld.shared.v2.f32 {%0,%1}, [%2];" : "=f"(v.x), "=f"(v.y) : "r"(a + S0) : "memory");
    return v;
}
__device__ __forceinline__ float bf_lo(uint32_t u) { return __uint_as_float(u << 16); }
__device__ __forceinline__ float bf_hi(uint32_t u) { return __uint_as_float(u & 0xffff0000u); }
__device__ __forceinline__ uint32_t pack_bf(float lo, float hi) {
    uint32_t r;
    asm("cvt.rn.bf16x2.f32 %0, %1, %2;" : "=r"(r) : "f"(hi), "f"(lo));
    return r;
}
__device__ __forceinline__ float tanh_fast(float x) {
    float r;
    asm("tanh.approx.f32 %0, %1;" : "=f"(r) : "f"(x));
    return r;
}
__device__ __forceinline__ float silu_half(float h) { return fmaf(h, tanh_fast(h), h); }
__device__ __forceinline__ void ldsm4(uint32_t (&u)[4], uint32_t a) {
    asm volatile("ldmatrix.sync.aligned.m8n8.x4.shared.b16 {%0,%1,%2,%3}, [%4];"
                 : "=r"(u[0]), "=r"(u[1]), "=r"(u[2]), "=r"(u[3]) : "r"(a + S0) : "memory");
}
__device__ __forceinline__ void ldsm4t(uint32_t (&u)[4], uint32_t a) {
    asm volatile("ldmatrix.sync.aligned.m8n8.x4.trans.shared.b16 {%0,%1,%2,%3}, [%4];"
                 : "=r"(u[0]), "=r"(u[1]), "=r"(u[2]), "=r"(u[3]) : "r"(a + S0) : "memory");
}
__device__ __forceinline__ void stsm4(uint32_t a, uint32_t p0, uint32_t p1, uint32_t p2, uint32_t p3) {
    asm volatile("stmatrix.sync.aligned.m8n8.x4.shared.b16 [%0], {%1,%2,%3,%4};" ::"r"(a + S0), "r"(p0), "r"(p1), "r"(p2), "r"(p3) : "memory");
}
__device__ __forceinline__ void stsm4t(uint32_t a, uint32_t p0, uint32_t p1, uint32_t p2, uint32_t p3) {
    asm volatile("stmatrix.sync.aligned.m8n8.x4.trans.shared.b16 [%0], {%1,%2,%3,%4};" ::"r"(a + S0), "r"(p0), "r"(p1), "r"(p2), "r"(p3) : "memory");
}

#define R8(o) "+f"(d[o]), "+f"(d[o + 1]), "+f"(d[o + 2]), "+f"(d[o + 3]), "+f"(d[o + 4]), "+f"(d[o + 5]), "+f"(d[o + 6]), "+f"(d[o + 7])
template <uint32_t ALO, uint32_t BLO, uint64_t AHI = 8, uint64_t BHI = 48>
__device__ __forceinline__ void wgmma128(float (&d)[64]) {
    asm volatile(
        "wgmma.mma_async.sync.aligned.m64n128k16.f32.bf16.bf16 "
        "{%0,%1,%2,%3,%4,%5,%6,%7,%8,%9,%10,%11,%12,%13,%14,%15,%16,%17,%18,%19,%20,%21,%22,%23,%24,%25,%26,%27,%28,%29,%30,%31,"
        "%32,%33,%34,%35,%36,%37,%38,%39,%40,%41,%42,%43,%44,%45,%46,%47,%48,%49,%50,%51,%52,%53,%54,%55,%56,%57,%58,%59,%60,%61,%62,%63},"
        " %64, %65, 1, 1, 1, 0, 0;"
        : R8(0), R8(8), R8(16), R8(24), R8(32), R8(40), R8(48), R8(56)
        : "l"((AHI << 32) | ALO), "l"((BHI << 32) | BLO));
}
template <int S>
__device__ __forceinline__ void mma_stages(float (&d)[64], int conv, int tid, Scratch* gs) {
    constexpr uint32_t A = ((SM_ACT + S * 2 * CH_PITCH + 16) >> 4) | ((CH_PITCH >> 4) << 16);
    constexpr uint32_t B = (slot_addr(S % NS) >> 4) | (8u << 16);
    if (S == 0) {
        unsigned it = 0;
#pragma unroll 1
        while (!MMA0_WAIT(BAR(BAR_FULL), conv) && ++it < SPIN_LIMIT) {}
    }
    bool next_ok = true;
    constexpr uint32_t NEXT = S + 1 < NSTAGE ? BAR(BAR_FULL + S + 1) : BAR(BAR_EMB);
    const int npar = S + 1 < NSTAGE ? conv : 0;
    next_ok = mbar_test(NEXT, npar);
    if (S == 0 && tid == 0) TL(32 + conv * 24);
    asm volatile("wgmma.fence.sync.aligned;" ::: "memory");
    wgmma128<A, B>(d);
    wgmma128<A + 1, B + 16>(d);
    wgmma128<A + 2, B + 32>(d);
    asm volatile("wgmma.commit_group.sync.aligned;" ::: "memory");
    if (S >= LAG) {
        asm volatile("wgmma.wait_group.sync.aligned %0;" ::"n"(LAG) : "memory");
        if ((tid & 31) == 0) mbar_arrive(BAR(BAR_WEMPTY + (S + NS - LAG) % NS));
    }
    if (!next_ok) mbar_wait(NEXT, npar);
    if constexpr (S + 1 < NSTAGE) mma_stages<S + 1>(d, conv, tid, gs);
}

__device__ __forceinline__ void weight_load(uint4 (&t)[5], const __nv_bfloat16* w, int cta, int lane) {
    const char* base = reinterpret_cast<const char*>(w) + (uint32_t)((((cta & 15) * 8 + (lane >> 2)) * 8 + (cta >> 4)) * 288 + (lane & 3) * 16);
#pragma unroll
    for (int k = 0; k < 5; k++)
        if (k < 4 || !(lane & 2)) t[k] = __ldg(reinterpret_cast<const uint4*>(base + k * 64));
}
__device__ __forceinline__ void weight_block(uint32_t bounce, unsigned char* wt, int cta, int lane, unsigned* cnt) {
    const unsigned opaque_one = gridDim.y;
    unsigned char* piece = wt + (cta >> 4) * STAGE_BYTES + (cta & 15) * 768;
    uint32_t v[18];
#pragma unroll
    for (int i = 0; i < 9; i++) {
        const float2 q = lds64f(bounce + (lane & 7) * 288 + (lane >> 3) * 72 + i * 8);
        v[2 * i] = __float_as_uint(q.x); v[2 * i + 1] = __float_as_uint(q.y);
    }
    unsigned char* dst = piece + (lane >> 4) * 128 + (lane & 7) * 16 + ((lane >> 3) & 1) * 8;
    unsigned rb[3];
#pragma unroll
    for (int kyo = 0; kyo < 3; kyo++) {
#pragma unroll
        for (int kx = 0; kx < 3; kx++) {
            const int tap = ky_of(kyo) * 3 + kx;
            uint32_t o[2];
#pragma unroll
            for (int m = 0; m < 2; m++) {
                const int i0 = 18 * m + tap, i1 = i0 + 9;
                o[m] = __byte_perm(v[i0 >> 1], v[i1 >> 1], ((i0 & 1) ? 0x32u : 0x10u) | ((i1 & 1) ? 0x7600u : 0x5400u));
            }
            asm volatile("st.global.v2.u32 [%0], {%1,%2};" ::"l"(dst + kyo * 8 * STAGE_BYTES + kx * 256), "r"(o[0]), "r"(o[1]) : "memory");
        }
        rb[kyo] = ld_relaxed(piece + kyo * 8 * STAGE_BYTES + (lane < 24 ? lane : 0) * 32);
    }
    const unsigned i0 = __any_sync(0xffffffffu, rb[0] == 0x9e3779b9u) ? opaque_one : 1u;
    if (lane < 2) asm volatile("red.relaxed.gpu.global.add.u32 [%0], %1;" ::"l"(cnt), "r"(i0) : "memory");
    const unsigned i1 = __any_sync(0xffffffffu, (rb[1] ^ rb[2]) == 0x9e3779b9u) ? opaque_one : 1u;
    if (lane < 2) asm volatile("red.relaxed.gpu.global.add.u32 [%0], %1;" ::"l"(cnt), "r"(i1 << 16) : "memory");
}
__device__ __forceinline__ uint32_t act2(uint32_t u, const float4& cf) {
    return pack_bf(silu_half(fmaf(bf_lo(u), cf.x, cf.z)), silu_half(fmaf(bf_hi(u), cf.y, cf.w)));
}
__device__ __forceinline__ void norm_unit(uint32_t (&u)[4], const float4& ca, const float4& cb) {
    u[0] = act2(u[0], ca); u[1] = act2(u[1], ca); u[2] = act2(u[2], cb); u[3] = act2(u[3], cb);
}
__device__ __forceinline__ void read_stats(uint32_t gst, float (&g)[8]) {
    asm volatile("ld.volatile.shared.v4.f32 {%0,%1,%2,%3}, [%4];" : "=f"(g[0]), "=f"(g[1]), "=f"(g[2]), "=f"(g[3]) : "r"(gst + S0) : "memory");
    asm volatile("ld.volatile.shared.v4.f32 {%0,%1,%2,%3}, [%4];" : "=f"(g[4]), "=f"(g[5]), "=f"(g[6]), "=f"(g[7]) : "r"(gst + 16 + S0) : "memory");
}
template <int T>
__device__ __forceinline__ void wait_stats(uint32_t gst, float (&g)[8]) {
    float rs, mr;
    unsigned it = 0;
#pragma unroll 1
    do {
        asm volatile("ld.volatile.shared.v2.f32 {%0,%1}, [%2];" : "=f"(rs), "=f"(mr) : "r"(gst + 8 * T + S0) : "memory");
    } while (!__all_sync(0xffffffffu, rs != 0.f) && ++it < 8 * SPIN_LIMIT);
    if (T < 3) read_stats(gst, g);
    g[2 * T] = rs; g[2 * T + 1] = mr;
}
template <int T>
__device__ __forceinline__ void own_unit(uint32_t (&o)[4], const float (&z)[8], float4 (&cf)[8], const float (&g)[8]) {
    float4 &ca = cf[2 * T], &cb = cf[2 * T + 1];
    const float rs = g[2 * T], mr = g[2 * T + 1];
    ca.z = fmaf(-mr, ca.x, ca.z); ca.w = fmaf(-mr, ca.y, ca.w);
    cb.z = fmaf(-mr, cb.x, cb.z); cb.w = fmaf(-mr, cb.y, cb.w);
#pragma unroll
    for (int i = 0; i < 4; i++)
        o[i] = pack_bf(silu_half(fmaf(z[2 * i], rs, i < 2 ? ca.z : cb.z)), silu_half(fmaf(z[2 * i + 1], rs, i < 2 ? ca.w : cb.w)));
}
template <int FIRST, int N>
__device__ __forceinline__ void norm_block(uint32_t (&u)[4][4], float4 (&cf)[8], uint32_t act, uint32_t mask, uint32_t fbar, int lane) {
#pragma unroll
    for (int t = FIRST; t < FIRST + N; t++) {
        norm_unit(u[t], cf[2 * t], cf[2 * t + 1]);
        stsm4(act + t * 2 * KC_BYTES, u[t][0] & mask, u[t][1] & mask, u[t][2] & mask, u[t][3] & mask);
    }
    fence_async_smem();
    __syncwarp();
    if (lane < N) mbar_arrive(fbar + 16 * (FIRST + lane));
}
__device__ __forceinline__ void publish(uint32_t bar, int lane) {
    fence_async_smem();
    __syncwarp();
    if (lane == 0) mbar_arrive(bar);
}
template <int T>
__device__ __forceinline__ void next_unit(const float (&z)[8], float4 (&cf)[8], uint32_t gst, float (&g)[8], uint32_t act, uint32_t fbar, int lane) {
    const bool have = __all_sync(0xffffffffu, g[2 * T] != 0.f);
    if (!have) { publish(fbar + 16 * (T - 1), lane); wait_stats<T>(gst, g); }
    uint32_t o[4];
    own_unit<T>(o, z, cf, g);
    if (have) publish(fbar + 16 * (T - 1), lane);
    stsm4(act + T * 2 * KC_BYTES, o[0], o[1], o[2], o[3]);
}
__device__ __forceinline__ void stat_mma(float (&c)[4], uint32_t p, uint32_t q) {
    asm("mma.sync.aligned.m16n8k16.row.col.f32.bf16.bf16.f32 {%0,%1,%2,%3}, {%4,%5,%6,%5}, {%4,%6}, {%0,%1,%2,%3};"
        : "+f"(c[0]), "+f"(c[1]), "+f"(c[2]), "+f"(c[3]) : "r"(p), "r"(0x3f803f80u), "r"(q));
}
__device__ __forceinline__ void stat_store(const float (&c)[4], uint32_t dst, int lane) {
    const int g = lane >> 2, t = lane & 3;
    if (t == (g >> 1)) sts32f(dst + g * 4, (g & 1) ? c[1] : c[0]);
    if (g == 7) sts32f(dst + 32 + t * 4, c[2] + c[3]);
}
__device__ __forceinline__ float sum4(float4 v) { return (v.x + v.y) + (v.z + v.w); }
__device__ __forceinline__ void stat_publish(uint32_t src, float* acc, int lane, bool real) {
    const uint32_t a = src + (lane & 15) * 48;
    float q = sum4(lds128f(a)) + sum4(lds128f(a + 16)), sm = sum4(lds128f(a + 32));
    q += __shfl_xor_sync(0xffffffffu, q, 1); sm += __shfl_xor_sync(0xffffffffu, sm, 1);
    q += __shfl_xor_sync(0xffffffffu, q, 2); sm += __shfl_xor_sync(0xffffffffu, sm, 2);
    if (real && (lane & 19) == 0) red_add4(acc + lane, 1.f, sm, q, 1.f);
}
__device__ __forceinline__ void fence_acc(float (&d)[64]) {
#pragma unroll
    for (int i = 0; i < 64; i++) asm volatile("" : "+f"(d[i])::"memory");
}
__device__ __forceinline__ void ld_unit(uint32_t (&u)[4], const uint4* p) {
    asm volatile("ld.relaxed.gpu.global.v4.u32 {%0,%1,%2,%3}, [%4];" : "=r"(u[0]), "=r"(u[1]), "=r"(u[2]), "=r"(u[3]) : "l"(p) : "memory");
}

__device__ __noinline__ void side_jobs(const __nv_bfloat16* __restrict__ t_emb, const __nv_bfloat16* __restrict__ w_emb,
                                       const __nv_bfloat16* __restrict__ w2, Scratch* __restrict__ gs, unsigned clk0) {
    const int tid = threadIdx.x, warp = tid >> 5, lane = tid & 31, j = blockIdx.x;
    float tv = 0.f;
    if (lane < 24) tv = __bfloat162float(t_emb[(lane / 12) * E + j * 192 + warp * 12 + lane % 12]);
    if (tid == 0) {
        mbar_init(BAR(0), 1);
        mbar_expect(BAR(0), 192 * C * 2);
        fence_async_smem();
        while (clock32() - clk0 < SDELAY) {}
#pragma unroll
        for (int i = 0; i < 4; i++)
            asm volatile("cp.async.bulk.prefetch.L2.global [%0], 18432;" ::"l"(reinterpret_cast<const char*>(w2) + (j * 4 + i) * 18432) : "memory");
#pragma unroll
        for (int i = 0; i < 4; i++) bulk_g2s(S0 + SM_W + i * 12288, w_emb + (j * 192 + i * 48) * C, 12288, S0 + BAR(0));
    }
    if (j == 0 && tid < 32) gs->acc2[(tid >> 4) * LS + (tid & 15)] = 0.f;
    const float sv = silu_half(0.5f * tv);
    __syncthreads();
    mbar_wait(BAR(0), 0);
    float acc[8] = {0.f, 0.f, 0.f, 0.f, 0.f, 0.f, 0.f, 0.f};
#pragma unroll
    for (int i = 0; i < 12; i++) {
        const float2 wq = lds64f(SM_W + (warp * 12 + i) * 256 + lane * 8);
        const uint32_t wx = __float_as_uint(wq.x), wy = __float_as_uint(wq.y);
#pragma unroll
        for (int bb = 0; bb < 2; bb++) {
            const float sx = __shfl_sync(0xffffffffu, sv, bb * 12 + i);
            acc[4 * bb + 0] = fmaf(sx, bf_lo(wx), acc[4 * bb + 0]); acc[4 * bb + 1] = fmaf(sx, bf_hi(wx), acc[4 * bb + 1]);
            acc[4 * bb + 2] = fmaf(sx, bf_lo(wy), acc[4 * bb + 2]); acc[4 * bb + 3] = fmaf(sx, bf_hi(wy), acc[4 * bb + 3]);
        }
    }
    sts128f(SM_ACT + warp * 1024 + lane * 16, make_float4(acc[0], acc[1], acc[2], acc[3]));
    sts128f(SM_ACT + warp * 1024 + 512 + lane * 16, make_float4(acc[4], acc[5], acc[6], acc[7]));
    __syncthreads();
    if (tid < 128) {
        float2 sum = make_float2(0.f, 0.f);
#pragma unroll
        for (int w = 0; w < 16; w++) { const float2 p = lds64f(SM_ACT + w * 1024 + tid * 8); sum.x += p.x; sum.y += p.y; }
        *reinterpret_cast<float2*>(&gs->emb[j * NB * C + tid * 2]) = sum;
        bar_sync(1, 128);
        if (tid < 2) asm volatile("red.release.gpu.global.add.u32 [%0], 1;" ::"l"(&gs->wcnt[(2 * NB + tid) * LS]) : "memory");
    }
}

__global__ void __cluster_dims__(2, 1, 1) __launch_bounds__(NTHREADS, 1)
resblock_kernel(const __nv_bfloat16* __restrict__ w1, const __nv_bfloat16* __restrict__ x,
                const __nv_bfloat16* __restrict__ t_emb, const __nv_bfloat16* __restrict__ g1,
                const __nv_bfloat16* __restrict__ be1, const __nv_bfloat16* __restrict__ w_emb,
                const __nv_bfloat16* __restrict__ g2, const __nv_bfloat16* __restrict__ be2,
                const __nv_bfloat16* __restrict__ w2, __nv_bfloat16* __restrict__ out, Scratch* __restrict__ gs,
                const __grid_constant__ CUtensorMap xmap) {
    const unsigned clk0 = clock32();
    if (threadIdx.x == 480 && blockIdx.x >= NXTRA) TLG(1);
    const int tid = threadIdx.x, lane = tid & 31;
    const int cta = blockIdx.x - NXTRA, b = cta >> 6, r = cta & 63;
    uint4 v[5];
    if (tid < 32) weight_load(v, w1, cta & (NCTA - 1), lane);
    uint4 xv[8];
    const int wg4 = (tid >> 5) - 1;
    const bool early = tid >= 32 && wg4 < NLDG;
    if (early) {
        const char* src = reinterpret_cast<const char*>(x) + (uint32_t)((((b & 1) * C + wg4 * 32 + (lane >> 3)) * HW + r) * HW * 2 + (lane & 7) * 16);
        while (clock32() - clk0 < XDELAY + (wg4 >> 1) * XSTAG + (wg4 & 1) * XSTAG2) {}
#pragma unroll
        for (int i = 0; i < 8; i++) xv[i] = __ldg(reinterpret_cast<const uint4*>(src + i * (4 * HW * HW * 2)));
    }
    const int warp = __shfl_sync(0xffffffffu, tid >> 5, 0);
    if (cta < 0) { side_jobs(t_emb, w_emb, w2, gs, clk0); return; }

    if (warp != 4) asm volatile("barrier.cluster.arrive.relaxed.aligned;" ::: "memory");
    const bool has_outer = (r != 0) && (r != HW - 1);
    if (warp == 1 || warp == 2 || warp == 3 || warp == 5) {
        const int g = warp < 4 ? warp - 1 : 3;
        if (elect_one()) {
            if (g >= NLDG) asm volatile("prefetch.tensormap [%0];" ::"l"(&xmap) : "memory");
            mbar_init(BAR(BAR_X) + 8 * g, 1);
            if (g >= NLDG) mbar_expect(BAR(BAR_X) + 8 * g, 4096);
            fence_async_smem();
        }
        __syncwarp();
        bar_arrive(4, 256 + 32 + 128);
        if (g >= NLDG) {
            while (clock32() - clk0 < XDELAY + (g >> 1) * XSTAG + (g & 1) * XSTAG2) {}
            if (elect_one()) tma_x(SM_XOWN + g * 4096, &xmap, r, b * C + g * 32, BAR(BAR_X) + 8 * g);
            __syncwarp();
            mbar_wait(BAR(BAR_X) + 8 * g, 0);
#pragma unroll
            for (int k = 0; k < 8; k++) xv[k] = lds128(SM_XOWN + g * 4096 + k * 512 + lane * 16);
        }
        float c[8][4];
#pragma unroll
        for (int k = 0; k < 8; k++) {
            c[k][0] = c[k][1] = c[k][2] = c[k][3] = 0.f;
            stat_mma(c[k], xv[k].x, xv[k].y); stat_mma(c[k], xv[k].z, xv[k].w);
        }
#pragma unroll
        for (int i = 0; i < 4; i++) c[0][i] = ((c[0][i] + c[1][i]) + (c[2][i] + c[3][i])) + ((c[4][i] + c[5][i]) + (c[6][i] + c[7][i]));
        stat_store(c[0], SM_RED + g * 48, lane);
        __syncwarp();
        if (lane == 0) {
            const uint32_t a = SM_RED + g * 48;
            red_add4(&gs->acc1[b * LS + g * 4], 1.f, sum4(lds128f(a + 32)), sum4(lds128f(a)) + sum4(lds128f(a + 16)), 1.f);
            TL(74 + g);
        }
        if (g < NLDG) {
#pragma unroll
            for (int i = 0; i < 8; i++)
                sts128(SM_XOWN + g * 4096 + i * 512 + (lane >> 3) * 128 + (((lane & 7) ^ ((lane >> 3) + 4 * (i & 1))) << 4), xv[i]);
            __syncwarp();
            if (lane == 0) mbar_arrive(BAR(BAR_X) + 8 * g);
        }
    }
    if (warp == 4) {
            if (elect_one()) {
#pragma unroll
                for (int i = 0; i < NSTAGE; i++) mbar_init(BAR(BAR_FULL + i), (i >> 3) == 1 ? 1 : 5);
#pragma unroll
                for (int i = 0; i < NS + 2; i++) mbar_init(BAR(BAR_WEMPTY + i), 4);
#pragma unroll
                for (int i = BAR_STATS; i < BAR_X; i++) mbar_init(BAR(i), i == BAR_EMB ? 3 : 1);
                mbar_init(BAR(BAR_X + 4), 1);
                asm volatile("fence.mbarrier_init.release.cluster;" ::: "memory");
            }
            if (lane < 4) sts128(SM_GST + lane * 16, make_uint4(0, 0, 0, 0));
            __syncwarp();
            fence_async_smem();
            bar_arrive(0, 96);
            bar_arrive(5, 64);
            bar_arrive(4, 256 + 32 + 128);
            const uint4 z = make_uint4(0, 0, 0, 0);
#pragma unroll
            for (int i = 0; i < 2; i++) sts128(SM_ACT + (i * 16 + (lane >> 1)) * CH_PITCH + (lane & 1) * 16, z);
            if (lane < 4) sts128(SM_ACT + (2 + (lane >> 1)) * ROW_BYTES + (lane & 1) * 16, z);
            if (lane < 16) sts128(SM_ONES + lane * 16, make_uint4(lane < 8 ? 0x3f803f80u : 0u, 0, 0, 0));
            fence_async_smem();
            bar_arrive(7, 160);
            asm volatile("barrier.cluster.arrive.relaxed.aligned;" ::: "memory");
            while (clock32() - clk0 < W2DELAY) {}
            weight_load(v, w2, cta, lane);
        }
    if (warp == 0 || warp == 4) {
        const int k = warp >> 2;
#pragma unroll
        for (int i = 0; i < 5; i++)
            if (i < 4 || !(lane & 2)) sts128(SM_BNC + k * 2304 + (lane >> 2) * 288 + (lane & 3) * 16 + i * 64, v[i]);
        if (lane == 0) TL(k ? 14 : 81);
        __syncwarp();
        weight_block(SM_BNC + k * 2304, gs->wt + k * NSTAGE * STAGE_BYTES, cta, lane,
                     k ? &gs->wcnt[(NB + (lane & 1)) * LS] : &gs->w1cnt[((lane & 1) * 8 + (cta >> 4)) * KS]);
        if (lane == 0) TL(k ? 13 : 4);
    }

    if (warp >= 8) {
        const int nw = warp - 8;
        if (nw < 2) {
            const uint2 ga = __ldg(reinterpret_cast<const uint2*>(nw ? g2 : g1) + lane), bt = __ldg(reinterpret_cast<const uint2*>(nw ? be2 : be1) + lane);
            sts128f(SM_COEF + nw * 1024 + lane * 32, make_float4(0.5f * bf_lo(ga.x), 0.5f * bf_hi(ga.x), 0.5f * bf_lo(bt.x), 0.5f * bf_hi(bt.x)));
            sts128f(SM_COEF + nw * 1024 + lane * 32 + 16, make_float4(0.5f * bf_lo(ga.y), 0.5f * bf_hi(ga.y), 0.5f * bf_lo(bt.y), 0.5f * bf_hi(bt.y)));
        }
        bar_sync(4, 256 + 32 + 128);
        const int par = nw >> 2, wq = nw & 3;
        const uint32_t act_off = SM_ACT + (par * 2 + (lane >> 4)) * CH_PITCH + (2 + wq * 16 + (lane & 15)) * 16;
        const uint32_t stg_off = (par * 16 + (lane >> 4) * 8 + (lane & 7)) * 128 + (((2 * wq + ((lane >> 3) & 1)) ^ (lane & 7)) << 4);
        const uint32_t cfa = SM_COEF + par * 128 + (lane & 3) * 16;
        const uint32_t fbar = BAR(BAR_FULL) + 8 * par;
        uint4* inbox = gs->box + cta * 1024 + nw * 32 + lane;
#pragma unroll 1
        for (int conv = 0; conv < 2; conv++) {
            uint32_t u[4][4], w[4][4];
            float4 cf[8];
            if (conv == 0) {
#pragma unroll
                for (int i = 0; i < 4; i++) { mbar_wait(BAR(BAR_X + i), 0); ldsm4t(u[i], SM_XOWN + stg_off + i * 4096); }
            } else {
                mbar_wait(BAR(BAR_HW), 0);
#pragma unroll
                for (int i = 0; i < 4; i++) ldsm4(u[i], act_off + i * 2 * KC_BYTES);
            }
#pragma unroll
            for (int i = 0; i < 8; i++) cf[i] = lds128f(cfa + conv * 1024 + (i >> 1) * 256 + (i & 1) * 64);
            const uint32_t gst = SM_GST + conv * 32;
            float gv[8], z[4][8];
#pragma unroll
            for (int i = 0; i < 16; i++) {
                const float4& c = cf[i >> 1];
                z[i >> 2][2 * (i & 3)] = bf_lo(u[i >> 2][i & 3]) * c.x; z[i >> 2][2 * (i & 3) + 1] = bf_hi(u[i >> 2][i & 3]) * c.y;
                asm volatile("" : "+f"(z[i >> 2][2 * (i & 3)]), "+f"(z[i >> 2][2 * (i & 3) + 1]));
            }
            wait_stats<0>(gst, gv);
            if (tid == 256) TL(22 + conv * 4);
            if (par) { const unsigned c1 = clock32(); while (clock32() - c1 < PDELAY) {} }
            uint32_t o[4];
            own_unit<0>(o, z[0], cf, gv);
            stsm4(act_off, o[0], o[1], o[2], o[3]);
            publish(fbar, lane);
            if (tid == 256) TL(8 + conv * 8);
            if (!__all_sync(0xffffffffu, gv[2] != 0.f)) wait_stats<1>(gst, gv);
            own_unit<1>(o, z[1], cf, gv);
            stsm4(act_off + 2 * KC_BYTES, o[0], o[1], o[2], o[3]);
            next_unit<2>(z[2], cf, gst, gv, act_off, fbar, lane);
            next_unit<3>(z[3], cf, gst, gv, act_off, fbar, lane);
            publish(fbar + 48, lane);
#pragma unroll
            for (int i = 0; i < 8; i++) { cf[i].x *= gv[i & ~1]; cf[i].y *= gv[i & ~1]; }
            if (tid == 256) TL(84 + conv);
            if (has_outer) {
                mbar_wait(BAR(BAR_X + 4), conv);
                if (conv == 0) {
#pragma unroll
                    for (int i = 0; i < 4; i++) ldsm4t(w[i], SM_XOUT + stg_off + i * 4096);
                } else {
#pragma unroll
                    for (int i = 0; i < 4; i++) {
                        const uint4 q = lds128(SM_XOWN + (tid - 256) * 16 + i * 4096);
                        w[i][0] = q.x; w[i][1] = q.y; w[i][2] = q.z; w[i][3] = q.w;
                    }
                    unsigned it = 0;
                    while (true) {
                        bool ok = true;
#pragma unroll
                        for (int i = 0; i < 16; i++) ok = ok && w[i >> 2][i & 3] != 0;
                        if (__all_sync(0xffffffffu, ok) || ++it > SPIN_LIMIT) break;
#pragma unroll
                        for (int i = 0; i < 4; i++) ld_unit(w[i], inbox + i * 256);
                    }
#pragma unroll
                    for (int i = 0; i < 16; i++) w[i >> 2][i & 3] = ~w[i >> 2][i & 3];
                }
            }
            if (conv == 0) {
                bar_sync(3, 256);
                if (nw == 0) sts128(SM_ACT + 2 * ROW_BYTES + (lane >> 1) * CH_PITCH + (lane & 1) * 16, make_uint4(0, 0, 0, 0));
            }
            if (tid == 256) TL(24 + conv * 4);
            norm_block<0, 2>(w, cf, act_off + 2 * ROW_BYTES, has_outer ? ~0u : 0u, fbar + 128, lane);
            if (tid == 256) TL(88 + conv);
            norm_block<2, 2>(w, cf, act_off + 2 * ROW_BYTES, has_outer ? ~0u : 0u, fbar + 128, lane);
            if (tid == 256) TL(23 + conv * 4);
        }
        if (has_outer) {
            mbar_wait(BAR(BAR_FULL + NSTAGE - 1), 1);
#pragma unroll
            for (int i = 0; i < 4; i++) inbox[i * 256] = make_uint4(0, 0, 0, 0);
        }
        {
            const int oc0 = par * 64 + ((tid & 127) >> 3), seg = lane & 7;
            __nv_bfloat16* dst = out + ((size_t)(b * C + oc0) * HW + r) * HW + seg * 8;
            const uint32_t src = SM_XOWN + oc0 * 128 + ((seg ^ (oc0 & 7)) << 4);
            asm volatile("{\n.reg .pred p;\nsetp.eq.u64 p, %0, 0;\n@p st.shared.u32 [%1], 0;\n}" ::"l"(dst), "r"(src + S0) : "memory");
            bar_sync(par ? 1 : 6, 128 + 128);
#pragma unroll
            for (int i = 0; i < 4; i++) *reinterpret_cast<uint4*>(dst + (size_t)i * 16 * HW * HW) = lds128(src + i * 2048);
            if (tid == 384) { TL(20); TLG(21); }
        }
    } else if (warp < 4) {
        const int wq = warp;
        bar_sync(7, 160);

        const uint32_t xbase = SM_XOWN + ((lane >> 4) * 8 + (lane & 7)) * 128 + (((2 * wq + ((lane >> 3) & 1)) ^ (lane & 7)) << 4);
        float d[64];
#pragma unroll
        for (int i = 0; i < 64; i++) d[i] = 0.f;
#pragma unroll 1
        for (int conv = 0; conv < 2; conv++) {
            fence_acc(d);
            mma_stages<0>(d, conv, tid, gs);
            if (conv == 0) {
                asm volatile("wgmma.fence.sync.aligned;" ::: "memory");
                wgmma128<(SM_ONES >> 4) | (8u << 16), (SM_EMB >> 4), 0, 8>(d);
                asm volatile("wgmma.commit_group.sync.aligned;" ::: "memory");
            }
            asm volatile("wgmma.wait_group.sync.aligned 0;" ::: "memory");
            fence_acc(d);
            if (tid == 0) TL(10 + conv * 8);
            if (conv == 1) {
                fence_acc(d);
#pragma unroll
                for (int kc = 0; kc < 8; kc++) {
                    stsm4t(xbase + kc * 2048, pack_bf(d[8 * kc], d[8 * kc + 1]), pack_bf(d[8 * kc + 2], d[8 * kc + 3]),
                           pack_bf(d[8 * kc + 4], d[8 * kc + 5]), pack_bf(d[8 * kc + 6], d[8 * kc + 7]));
                    if (kc == 3) bar_arrive(6, 128 + 128);
                }
                bar_arrive(1, 128 + 128);
                if (tid == 0) TL(5);
                break;
            }
            uint32_t hp[32];
#pragma unroll
            for (int i = 0; i < 32; i++) hp[i] = pack_bf(d[2 * i], d[2 * i + 1]);
#pragma unroll
            for (int g = 0; g < 4; g++) {
                float c[4] = {0.f, 0.f, 0.f, 0.f};
#pragma unroll
                for (int i = 0; i < 4; i++) stat_mma(c, hp[8 * g + 2 * i], hp[8 * g + 2 * i + 1]);
                stat_store(c, SM_RED + (g * 4 + wq) * 48, lane);
            }
            bar_sync(2, 128);
            if (wq == 0) stat_publish(SM_RED, &gs->acc2[b * LS], lane, true);
            if (tid == 0) TL(11);
            const uint32_t hbase = SM_ACT + (lane >> 4) * CH_PITCH + (2 + wq * 16 + (lane & 15)) * 16;
#pragma unroll
            for (int kc = 0; kc < 8; kc++) stsm4(hbase + kc * 2 * CH_PITCH, hp[4 * kc], hp[4 * kc + 1], hp[4 * kc + 2], hp[4 * kc + 3]);
            __syncwarp();
            if (lane == 0) mbar_arrive(BAR(BAR_HW));
            if (lane < LAG) mbar_arrive(BAR(BAR_WEMPTY + (NSTAGE - LAG) % NS) + 8 * lane);
            if (has_outer) {
                uint4* outbox = gs->box + (cta + ((r & 1) ? 1 : -1)) * 1024 + tid;
#pragma unroll
                for (int kc = 0; kc < 8; kc++) outbox[kc * 128] = make_uint4(~hp[4 * kc], ~hp[4 * kc + 1], ~hp[4 * kc + 2], ~hp[4 * kc + 3]);
            }
            if (tid == 0) TL(12);
#pragma unroll
            for (int kc = 0; kc < 8; kc++) {
                uint32_t p[4];
                ldsm4t(p, xbase + kc * 2048);
#pragma unroll
                for (int i = 0; i < 4; i++) { d[8 * kc + 2 * i] = bf_lo(p[i]); d[8 * kc + 2 * i + 1] = bf_hi(p[i]); }
            }
            fence_async_smem();
            __syncwarp();
            if (lane == 0) mbar_arrive(BAR(BAR_XFREE));
        }
        {
        }
    } else if (warp < 6) {
        if (warp == 5) {
            bar_sync(5, 64);
            mbar_wait(BAR(BAR_FULL + OAFTER), 0);
            if (has_outer && elect_one()) {
                mbar_expect(BAR(BAR_X + 4), 16384);
#pragma unroll
                for (int i = 0; i < 4; i++) tma_x(SM_XOUT + i * 4096, &xmap, r + ((r & 1) ? 1 : -1), b * C + i * 32, BAR(BAR_X + 4));
            }
            __syncwarp();
            asm volatile("barrier.cluster.wait.acquire.aligned;" ::: "memory");
            const uint32_t peer = (r & 1) ^ 1;
            const uint32_t self0 = mapa(0, r & 1), peer0 = mapa(0, peer);
#pragma unroll 1
            for (int conv = 0; conv < 2; conv++) {
                if (FWD0) mbar_wait(BAR(BAR_FULL + FWD0), conv);
#pragma unroll 1
                for (int kc = 0; kc < 8; kc++) {
                    mbar_wait(BAR(BAR_FULL) + 8 * kc, conv);
                    if (elect_one())
                        asm volatile("cp.async.bulk.shared::cluster.shared::cta.mbarrier::complete_tx::bytes [%0], [%1], %2, [%3];"
                                     ::"r"(peer0 + SM_ACT + ROW_BYTES + kc * KC_BYTES), "r"(self0 + SM_ACT + kc * KC_BYTES), "r"(KC_BYTES),
                                       "r"(peer0 + BAR(BAR_FULL + 8) + 8 * kc) : "memory");
                }
                if (lane == 0) TL(86 + conv);
#pragma unroll 1
                for (int kc = 0; kc < 8; kc++) mbar_wait(BAR(BAR_FULL + 8) + 8 * kc, conv);
                if (lane == 0)
                    asm volatile("mbarrier.arrive.relaxed.cluster.shared::cluster.b64 _, [%0];" ::"r"(peer0 + (conv ? BAR(BAR_ACK) : BAR(BAR_EMB))) : "memory");
            }
            mbar_wait(BAR(BAR_ACK), 0);
        } else {
            mbar_wait(BAR(BAR_STATS), 0);
            unsigned it = 0;
            while (!__all_sync(0xffffffffu, ld_relaxed(&gs->wcnt[(2 * NB + b) * LS]) >= (unsigned)NXTRA) && ++it < SPIN_LIMIT) __nanosleep(100);
            fence_acquire();
            float ev[4] = {0.f, 0.f, 0.f, 0.f};
#pragma unroll
            for (int j = 0; j < NXTRA; j++) {
                const uint4 ef = ld_relaxed_v4(&gs->emb[(j * NB + b) * C + lane * 4]);
                ev[0] += __uint_as_float(ef.x); ev[1] += __uint_as_float(ef.y); ev[2] += __uint_as_float(ef.z); ev[3] += __uint_as_float(ef.w);
            }
#pragma unroll
            for (int i = 0; i < 4; i++) {
                const float hi = bf_lo(pack_bf(ev[i], 0.f));
                sts128(SM_EMB + (lane * 4 + i) * 16, make_uint4(pack_bf(hi, ev[i] - hi), 0, 0, 0));
            }
            fence_async_smem();
            __syncwarp();
            if (lane == 0) { mbar_arrive(BAR(BAR_EMB)); TL(19); }
        }
    } else if (warp == 6) {
        bar_sync(0, 96);
        const uint32_t ebytes = STAGE_BYTES + ((lane >> 3) == 1 ? KC_BYTES : 0);
        if (lane < NSTAGE) mbar_expect(BAR(BAR_FULL) + 8 * lane, ebytes);
        const int swap = (r & 1) ? 0 : 8 * STAGE_BYTES;
        unsigned it = 0;
        {
            int g = 0;
            const unsigned* cnt = &gs->w1cnt[(b * 8 + (lane & 7)) * KS];
            unsigned cv = ld_relaxed(cnt);
#pragma unroll 1
            while (g < NS) {
                unsigned ready = __ballot_sync(0xffffffffu, (lane < 8 ? cv & 0xffffu : cv >> 16) >= 16u);
                if ((ready >> 8 & 0xff) != 0xff) ready &= 0xff;
                if (ready != ~0u) cv = ld_relaxed(cnt);
                ready >>= g;
                if (++it > SPIN_LIMIT) ready = ~0u;
                if (!(ready & 1)) continue;
                fence_async_global();
                if (lane == 0) TL(g ? 3 : 6);
#pragma unroll 1
                for (; (ready & 1) && g < NS; g++, ready >>= 1)
                    if (elect_one())
                        bulk_g2s(S0 + SM_W + g * STAGE_BYTES, gs->wt + g * STAGE_BYTES + (g >= 8 ? swap : 0), STAGE_BYTES, S0 + BAR(BAR_FULL) + 8 * g);
            }
        }
#pragma unroll 1
        for (int q = 3; q < 12; q++) {
            const int conv = q >= 6, qs = conv ? q - 6 : q, sl = q % 3;
            const unsigned char* wsrc = gs->wt + q * 4 * STAGE_BYTES + (qs < 2 ? 0 : (qs < 4 ? swap : -swap));
            const uint32_t par = (q / 3 - 1) & 1;
            if (q == 6) {
                it = 0;
                while (!__all_sync(0xffffffffu, ld_relaxed(&gs->wcnt[(NB + b) * LS]) == NCTA * 0x10001u) && ++it < SPIN_LIMIT) {}
                fence_acquire();
                fence_async_global();
                if (lane == 0) { mbar_arrive(BAR(BAR_EMB)); TL(2); }
            }
#pragma unroll
            for (int i = 0; i < 4; i++) {
                mbar_wait(BAR(BAR_WEMPTY + i) + 32 * sl, par);
                if (i == 0 && (q == 6 || q == 9)) {
                    if ((lane >= NS) == (q == 9) && lane < NSTAGE) mbar_expect(BAR(BAR_FULL) + 8 * lane, ebytes);
                    __syncwarp();
                }
                if (elect_one())
                    bulk_g2s(S0 + SM_W + (sl * 4 + i) * STAGE_BYTES, wsrc + i * STAGE_BYTES, STAGE_BYTES, S0 + BAR(BAR_FULL + i) + 32 * qs);
            }
        }
    } else {
        bar_sync(0, 96);
#pragma unroll 1
        for (int conv = 0; conv < 2; conv++) {
            if (conv == 1) mbar_wait(BAR(BAR_HW), 0);
            const float* asrc = (conv ? gs->acc2 : gs->acc1) + b * LS + (lane & 3) * 4;
            unsigned it = 0;
#pragma unroll 1
            while (true) {
                const uint4 f = ld_relaxed_v4(asrc);
                const bool ok = ((f.x == 0x42800000u) & (f.w == 0x42800000u)) || ++it > SPIN_LIMIT;
                if (ok && lane < 4) {
                    const float inv_n = 1.0f / (32.0f * HW * HW);
                    const float mean = __uint_as_float(f.y) * inv_n;
                    float rs;
                    asm("rsqrt.approx.ftz.f32 %0, %1;" : "=f"(rs) : "f"(fmaxf(fmaf(-mean, mean, __uint_as_float(f.z) * inv_n), 0.f) + 1e-5f));
                    asm volatile("st.shared.v2.f32 [%0], {%1,%2};" ::"r"(S0 + SM_GST + conv * 32 + lane * 8), "f"(rs == 0.f ? 1e-38f : rs), "f"(mean * rs) : "memory");
                }
                if (__all_sync(0xffffffffu, ok)) break;
            }
            if (lane == 0) { mbar_arrive(BAR(BAR_STATS)); TL(7 + conv * 8); }
        }
        mbar_wait(BAR(BAR_XFREE), 0);
        if (has_outer && elect_one()) {
            mbar_expect(BAR(BAR_X + 4), 16384);
            bulk_g2s(S0 + SM_XOWN, gs->box + cta * 1024, 16384, S0 + BAR(BAR_X + 4));
        }
        if (r == 0) {
            if (lane < 16) gs->acc1[b * LS + lane] = 0.f;
            if (lane < 3) gs->wcnt[(lane * NB + b) * LS] = 0;
            if (lane < 8) gs->w1cnt[(b * 8 + lane) * KS] = 0;
        }
    }
}

}

extern "C" void kernel_launch(void* const* d_in, const int* in_sizes, int n_in, void* d_out, int out_size) {
    (void)in_sizes; (void)n_in; (void)out_size;
    typedef CUresult (*EncodeFn)(CUtensorMap*, CUtensorMapDataType, cuuint32_t, void*, const cuuint64_t*, const cuuint64_t*,
                                 const cuuint32_t*, const cuuint32_t*, CUtensorMapInterleave, CUtensorMapSwizzle,
                                 CUtensorMapL2promotion, CUtensorMapFloatOOBfill);
    static Scratch* gs = nullptr;
    static EncodeFn encode = nullptr;
    if (!gs) {
        cudaFuncSetAttribute(resblock_kernel, cudaFuncAttributeMaxDynamicSharedMemorySize, SM_TOTAL);
        cudaGetSymbolAddress((void**)&gs, g_scratch);
        cudaDriverEntryPointQueryResult qr;
        cudaGetDriverEntryPoint("cuTensorMapEncodeTiled", (void**)&encode, cudaEnableDefault, &qr);
    }
    CUtensorMap xmap;
    const cuuint64_t dims[3] = {HW, HW, NB * C}, strides[2] = {HW * 2, HW * HW * 2};
    const cuuint32_t box[3] = {HW, 1, 32}, es[3] = {1, 1, 1};
    encode(&xmap, CU_TENSOR_MAP_DATA_TYPE_BFLOAT16, 3, d_in[0], dims, strides, box, es, CU_TENSOR_MAP_INTERLEAVE_NONE,
           CU_TENSOR_MAP_SWIZZLE_128B, CU_TENSOR_MAP_L2_PROMOTION_NONE, CU_TENSOR_MAP_FLOAT_OOB_FILL_NONE);
    resblock_kernel<<<NCTA + NXTRA, NTHREADS, SM_TOTAL>>>(
        (const __nv_bfloat16*)d_in[4], (const __nv_bfloat16*)d_in[0], (const __nv_bfloat16*)d_in[1],
        (const __nv_bfloat16*)d_in[2], (const __nv_bfloat16*)d_in[3], (const __nv_bfloat16*)d_in[5],
        (const __nv_bfloat16*)d_in[6], (const __nv_bfloat16*)d_in[7], (const __nv_bfloat16*)d_in[8],
        (__nv_bfloat16*)d_out, gs, xmap);
}
```

```cpp
#include <cuda_runtime.h>
#include <cuda.h>
#include <cuda_bf16.h>
#include <stdint.h>

namespace {

constexpr int C = 128, HW = 64, NB = 2, E = 768;
constexpr int NCTA = NB * HW;
constexpr int NXTRA = 4;
constexpr int NTHREADS = 16 * 32;
constexpr int CH_PITCH = 66 * 16;
constexpr int ROW_BYTES = 16 * CH_PITCH;
constexpr int STEP_BYTES = 4096;
constexpr int STAGE_BYTES = 3 * STEP_BYTES;
constexpr int NSTAGE = 24;
constexpr int KC_BYTES = 2 * CH_PITCH;
constexpr int NS = 12;
constexpr int LAG = 1;
#define XDELAY 300
#define HDELAY 600
#define SEQ 0
#define MMA0_WAIT mbar_try
#define NPOLL 1
#define PD2 0
#define ODELAY 100
#define NLDG 2
#define PSTAG -1
#define PDELAY0 400
#define PDELAY 60
#define RB 1
#define XSTAG2 300
#define XSTAG 800
#define HSEND 0
#define SDELAY 600
#define OAFTER 0
#define W2DELAY 2400

constexpr uint32_t SMEM_BASE = 0x400;
constexpr uint32_t SM_XOWN = SMEM_BASE;
constexpr uint32_t SM_ACT = SM_XOWN + 16384 + 512;
constexpr uint32_t SM_XOUT = SM_ACT + 2 * ROW_BYTES + 512;
static_assert(SM_XOUT % 1024 == 0, "swizzle atom alignment");
constexpr uint32_t SM_W = SM_ACT + 3 * ROW_BYTES + 128;
__host__ __device__ constexpr uint32_t slot_addr(int slot) { return SM_W + slot * STAGE_BYTES; }
constexpr uint32_t SM_COEF = SM_W + NS * STAGE_BYTES;
constexpr uint32_t SM_GST = SM_COEF + 2048;
constexpr uint32_t SM_EMB = SM_GST + 128;
constexpr uint32_t SM_ONES = SM_EMB + 2048;
constexpr uint32_t SM_RED = SM_ONES + 256;
constexpr uint32_t SM_BNC = SM_RED + 1536;
constexpr uint32_t SM_BAR = SM_BNC + 2 * 2304;
constexpr int BAR_FULL = 0, BAR_WEMPTY = NSTAGE, BAR_HW = BAR_WEMPTY + NS, BAR_XFREE = BAR_HW + 1, BAR_STATS = BAR_XFREE + 1,
              BAR_EMB = BAR_STATS + 1, BAR_ACK = BAR_EMB + 1, BAR_SP = BAR_ACK + 1  , BAR_X = BAR_SP + 8  , NBAR = BAR_X + 5;
constexpr int SM_TOTAL = SM_BAR + NBAR * 8 - SMEM_BASE;
static_assert(SM_TOTAL <= 232448, "smem");
static_assert(NBAR <= 96, "barrier init");
__host__ __device__ constexpr uint32_t BAR(int i) { return SM_BAR + 8 * i; }
__host__ __device__ constexpr int ky_of(int kyo) { return kyo == 0 ? 1 : (kyo == 1 ? 0 : 2); }

constexpr unsigned SPIN_LIMIT = 1u << 16;

#define LS 1056
#define GS1 4
#define PD 0
#define FWD0 0
#define WPF 64
#define NSPEC 4
#define KS 32
struct Scratch {
    float acc1[NB * LS];
    float acc2[NB * LS];
    unsigned wcnt[3 * NB * LS];
    unsigned w1cnt[NB * 8 * KS];
    float emb[NXTRA * NB * C];
    alignas(1024) unsigned char wt[2 * NSTAGE * STAGE_BYTES];
    uint4 box[NCTA * 1024];
};
__device__ __align__(1024) Scratch g_scratch;
#define TL(i) do {} while (0)
#define TLG(i) do {} while (0)

__device__ __forceinline__ unsigned clock32() { unsigned c; asm volatile("mov.u32 %0, %%clock;" : "=r"(c)); return c; }
__device__ __forceinline__ uint32_t mapa(uint32_t a, uint32_t rank) {
    uint32_t d;
    asm("mapa.shared::cluster.u32 %0, %1, %2;" : "=r"(d) : "r"(a), "r"(rank));
    return d;
}
#define S0 mapa(0, blockIdx.x & 1)
__device__ __forceinline__ void mbar_init(uint32_t bar, int cnt) {
    asm volatile("mbarrier.init.shared::cta.b64 [%0], %1;" ::"r"(bar + S0), "r"(cnt) : "memory");
}
__device__ __forceinline__ void mbar_arrive(uint32_t bar) {
    asm volatile("mbarrier.arrive.shared::cta.b64 _, [%0];" ::"r"(bar + S0) : "memory");
}
__device__ __forceinline__ void mbar_expect(uint32_t bar, uint32_t bytes) {
    asm volatile("mbarrier.arrive.expect_tx.shared::cta.b64 _, [%0], %1;" ::"r"(bar + S0), "r"(bytes) : "memory");
}
__device__ __forceinline__ bool mbar_try(uint32_t bar, uint32_t par) {
    uint32_t ok;
    asm volatile("{\n.reg .pred p;\nmbarrier.try_wait.parity.shared::cta.b64 p, [%1], %2;\nselp.u32 %0, 1, 0, p;\n}"
                 : "=r"(ok) : "r"(bar + S0), "r"(par) : "memory");
    return ok;
}
__device__ __forceinline__ bool mbar_test(uint32_t bar, uint32_t par) {
    uint32_t ok;
    asm volatile("{\n.reg .pred p;\nmbarrier.test_wait.parity.shared::cta.b64 p, [%1], %2;\nselp.u32 %0, 1, 0, p;\n}"
                 : "=r"(ok) : "r"(bar + S0), "r"(par) : "memory");
    return ok;
}
__device__ __forceinline__ void mbar_wait(uint32_t bar, uint32_t par) {
    unsigned it = 0;
#pragma unroll 1
    while (!mbar_try(bar, par) && ++it < SPIN_LIMIT) {}
}
__device__ __forceinline__ bool elect_one() {
    uint32_t p;
    asm volatile("{\n.reg .pred p;\nelect.sync _|p, 0xffffffff;\nselp.u32 %0, 1, 0, p;\n}" : "=r"(p));
    return p;
}
__device__ __forceinline__ void fence_async_smem() { asm volatile("fence.proxy.async.shared::cta;" ::: "memory"); }
__device__ __forceinline__ void fence_async_global() { asm volatile("fence.proxy.async.global;" ::: "memory"); }
__device__ __forceinline__ void fence_acquire() { asm volatile("fence.acquire.gpu;" ::: "memory"); }
__device__ __forceinline__ void bar_sync(int id, int n) { asm volatile("bar.sync %0, %1;" ::"r"(id), "r"(n) : "memory"); }
__device__ __forceinline__ void bar_arrive(int id, int n) { asm volatile("bar.arrive %0, %1;" ::"r"(id), "r"(n) : "memory"); }
__device__ __forceinline__ void bulk_g2s(uint32_t dst, const void* src, uint32_t bytes, uint32_t bar) {
    asm volatile("cp.async.bulk.shared::cluster.global.mbarrier::complete_tx::bytes [%0], [%1], %2, [%3];"
                 ::"r"(dst), "l"(src), "r"(bytes), "r"(bar) : "memory");
}
__device__ __forceinline__ void tma_x(uint32_t dst, const CUtensorMap* tm, int row, int ch, uint32_t bar) {
    asm volatile("cp.async.bulk.tensor.3d.shared::cluster.global.mbarrier::complete_tx::bytes [%0], [%1, {%2, %3, %4}], [%5];"
                 ::"r"(dst + S0), "l"(tm), "r"(0), "r"(row), "r"(ch), "r"(bar + S0) : "memory");
}
__device__ __forceinline__ uint4 ld_relaxed_v4(const void* p) {
    uint4 v;
    asm volatile("ld.relaxed.gpu.global.v4.u32 {%0,%1,%2,%3}, [%4];" : "=r"(v.x), "=r"(v.y), "=r"(v.z), "=r"(v.w) : "l"(p) : "memory");
    return v;
}
__device__ __forceinline__ unsigned ld_relaxed(const void* p) {
    unsigned v;
    asm volatile("ld.relaxed.gpu.global.u32 %0, [%1];" : "=r"(v) : "l"(p) : "memory");
    return v;
}
__device__ __forceinline__ void red_add4(float* p, float a, float b, float c, float d) {
    asm volatile("red.relaxed.gpu.global.add.v4.f32 [%0], {%1,%2,%3,%4};" ::"l"(p), "f"(a), "f"(b), "f"(c), "f"(d) : "memory");
}
__device__ __forceinline__ void sts128(uint32_t a, uint4 v) {
    asm volatile("st.shared.v4.u32 [%0], {%1,%2,%3,%4};" ::"r"(a + S0), "r"(v.x), "r"(v.y), "r"(v.z), "r"(v.w) : "memory");
}
__device__ __forceinline__ void sts128f(uint32_t a, float4 v) {
    asm volatile("st.shared.v4.f32 [%0], {%1,%2,%3,%4};" ::"r"(a + S0), "f"(v.x), "f"(v.y), "f"(v.z), "f"(v.w) : "memory");
}
__device__ __forceinline__ void sts32f(uint32_t a, float v) { asm volatile("st.shared.f32 [%0], %1;" ::"r"(a + S0), "f"(v) : "memory"); }
__device__ __forceinline__ uint4 lds128(uint32_t a) {
    uint4 v;
    asm volatile("ld.shared.v4.u32 {%0,%1,%2,%3}, [%4];" : "=r"(v.x), "=r"(v.y), "=r"(v.z), "=r"(v.w) : "r"(a + S0) : "memory");
    return v;
}
__device__ __forceinline__ float4 lds128f(uint32_t a) {
    float4 v;
    asm volatile("ld.shared.v4.f32 {%0,%1,%2,%3}, [%4];" : "=f"(v.x), "=f"(v.y), "=f"(v.z), "=f"(v.w) : "r"(a + S0) : "memory");
    return v;
}
__device__ __forceinline__ float2 lds64f(uint32_t a) {
    float2 v;
    asm volatile("ld.shared.v2.f32 {%0,%1}, [%2];" : "=f"(v.x), "=f"(v.y) : "r"(a + S0) : "memory");
    return v;
}
__device__ __forceinline__ float bf_lo(uint32_t u) { return __uint_as_float(u << 16); }
__device__ __forceinline__ float bf_hi(uint32_t u) { return __uint_as_float(u & 0xffff0000u); }
__device__ __forceinline__ uint32_t pack_bf(float lo, float hi) {
    uint32_t r;
    asm("cvt.rn.bf16x2.f32 %0, %1, %2;" : "=r"(r) : "f"(hi), "f"(lo));
    return r;
}
__device__ __forceinline__ float tanh_fast(float x) {
    float r;
    asm("tanh.approx.f32 %0, %1;" : "=f"(r) : "f"(x));
    return r;
}
__device__ __forceinline__ float silu_half(float h) { return fmaf(h, tanh_fast(h), h); }
__device__ __forceinline__ void ldsm4(uint32_t (&u)[4], uint32_t a) {
    asm volatile("ldmatrix.sync.aligned.m8n8.x4.shared.b16 {%0,%1,%2,%3}, [%4];"
                 : "=r"(u[0]), "=r"(u[1]), "=r"(u[2]), "=r"(u[3]) : "r"(a + S0) : "memory");
}
__device__ __forceinline__ void ldsm4t(uint32_t (&u)[4], uint32_t a) {
    asm volatile("ldmatrix.sync.aligned.m8n8.x4.trans.shared.b16 {%0,%1,%2,%3}, [%4];"
                 : "=r"(u[0]), "=r"(u[1]), "=r"(u[2]), "=r"(u[3]) : "r"(a + S0) : "memory");
}
__device__ __forceinline__ void stsm4(uint32_t a, uint32_t p0, uint32_t p1, uint32_t p2, uint32_t p3) {
    asm volatile("stmatrix.sync.aligned.m8n8.x4.shared.b16 [%0], {%1,%2,%3,%4};" ::"r"(a + S0), "r"(p0), "r"(p1), "r"(p2), "r"(p3) : "memory");
}
__device__ __forceinline__ void stsm4t(uint32_t a, uint32_t p0, uint32_t p1, uint32_t p2, uint32_t p3) {
    asm volatile("stmatrix.sync.aligned.m8n8.x4.trans.shared.b16 [%0], {%1,%2,%3,%4};" ::"r"(a + S0), "r"(p0), "r"(p1), "r"(p2), "r"(p3) : "memory");
}

#define R8(o) "+f"(d[o]), "+f"(d[o + 1]), "+f"(d[o + 2]), "+f"(d[o + 3]), "+f"(d[o + 4]), "+f"(d[o + 5]), "+f"(d[o + 6]), "+f"(d[o + 7])
template <uint32_t ALO, uint32_t BLO, uint64_t AHI = 8, uint64_t BHI = 48>
__device__ __forceinline__ void wgmma128(float (&d)[64]) {
    asm volatile(
        "wgmma.mma_async.sync.aligned.m64n128k16.f32.bf16.bf16 "
        "{%0,%1,%2,%3,%4,%5,%6,%7,%8,%9,%10,%11,%12,%13,%14,%15,%16,%17,%18,%19,%20,%21,%22,%23,%24,%25,%26,%27,%28,%29,%30,%31,"
        "%32,%33,%34,%35,%36,%37,%38,%39,%40,%41,%42,%43,%44,%45,%46,%47,%48,%49,%50,%51,%52,%53,%54,%55,%56,%57,%58,%59,%60,%61,%62,%63},"
        " %64, %65, 1, 1, 1, 0, 0;"
        : R8(0), R8(8), R8(16), R8(24), R8(32), R8(40), R8(48), R8(56)
        : "l"((AHI << 32) | ALO), "l"((BHI << 32) | BLO));
}
template <int S>
__device__ __forceinline__ void mma_stages(float (&d)[64], int conv, int tid, Scratch* gs) {
    constexpr uint32_t A = ((SM_ACT + S * 2 * CH_PITCH + 16) >> 4) | ((CH_PITCH >> 4) << 16);
    constexpr uint32_t B = (slot_addr(S % NS) >> 4) | (8u << 16);
    if (S == 0) {
        unsigned it = 0;
#pragma unroll 1
        while (!MMA0_WAIT(BAR(BAR_FULL), conv) && ++it < SPIN_LIMIT) {}
    }
    bool next_ok = true;
    constexpr uint32_t NEXT = S + 1 < NSTAGE ? BAR(BAR_FULL + S + 1) : BAR(BAR_EMB);
    const int npar = S + 1 < NSTAGE ? conv : 0;
    next_ok = mbar_test(NEXT, npar);
    if (S == 0 && tid == 0) TL(32 + conv * 24);
    asm volatile("wgmma.fence.sync.aligned;" ::: "memory");
    wgmma128<A, B>(d);
    wgmma128<A + 1, B + 16>(d);
    wgmma128<A + 2, B + 32>(d);
    asm volatile("wgmma.commit_group.sync.aligned;" ::: "memory");
    if (S >= LAG) {
        asm volatile("wgmma.wait_group.sync.aligned %0;" ::"n"(LAG) : "memory");
        if ((tid & 31) == 0) mbar_arrive(BAR(BAR_WEMPTY + (S + NS - LAG) % NS));
    }
    if (!next_ok) mbar_wait(NEXT, npar);
    if constexpr (S + 1 < NSTAGE) mma_stages<S + 1>(d, conv, tid, gs);
}

__device__ __forceinline__ void weight_load(uint4 (&t)[5], const __nv_bfloat16* w, int cta, int lane) {
    const char* base = reinterpret_cast<const char*>(w) + (uint32_t)((((cta & 15) * 8 + (lane >> 2)) * 8 + (cta >> 4)) * 288 + (lane & 3) * 16);
#pragma unroll
    for (int k = 0; k < 5; k++)
        if (k < 4 || !(lane & 2)) t[k] = __ldg(reinterpret_cast<const uint4*>(base + k * 64));
}
__device__ __forceinline__ void weight_block(uint32_t bounce, unsigned char* wt, int cta, int lane, unsigned* cnt, bool hint) {
    const unsigned opaque_one = gridDim.y;
    unsigned char* piece = wt + (cta >> 4) * STAGE_BYTES + (cta & 15) * 768;
    uint32_t v[18];
#pragma unroll
    for (int i = 0; i < 9; i++) {
        const float2 q = lds64f(bounce + (lane & 7) * 288 + (lane >> 3) * 72 + i * 8);
        v[2 * i] = __float_as_uint(q.x); v[2 * i + 1] = __float_as_uint(q.y);
    }
    unsigned char* dst = piece + (lane >> 4) * 128 + (lane & 7) * 16 + ((lane >> 3) & 1) * 8;
    unsigned rb[3];
#pragma unroll
    for (int kyo = 0; kyo < 3; kyo++) {
#pragma unroll
        for (int kx = 0; kx < 3; kx++) {
            const int tap = ky_of(kyo) * 3 + kx;
            uint32_t o[2];
#pragma unroll
            for (int m = 0; m < 2; m++) {
                const int i0 = 18 * m + tap, i1 = i0 + 9;
                o[m] = __byte_perm(v[i0 >> 1], v[i1 >> 1], ((i0 & 1) ? 0x32u : 0x10u) | ((i1 & 1) ? 0x7600u : 0x5400u));
            }
            if (kyo == 0) { o[0] = max(o[0], 1u); o[1] = max(o[1], 1u); }
            asm volatile("st.global.v2.u32 [%0], {%1,%2};" ::"l"(dst + kyo * 8 * STAGE_BYTES + kx * 256), "r"(o[0]), "r"(o[1]) : "memory");
        }
        if (kyo == 0 && hint && lane < 2) asm volatile("red.relaxed.gpu.global.add.u32 [%0], 0x1000000;" ::"l"(cnt) : "memory");
        rb[kyo] = ld_relaxed(piece + kyo * 8 * STAGE_BYTES + (lane < 24 ? lane : 0) * 32);
    }
    const unsigned i0 = __any_sync(0xffffffffu, rb[0] == 0x9e3779b9u) ? opaque_one : 1u;
    if (lane < 2) asm volatile("red.relaxed.gpu.global.add.u32 [%0], %1;" ::"l"(cnt), "r"(i0) : "memory");
    const unsigned i1 = __any_sync(0xffffffffu, (rb[1] ^ rb[2]) == 0x9e3779b9u) ? opaque_one : 1u;
    if (lane < 2) asm volatile("red.relaxed.gpu.global.add.u32 [%0], %1;" ::"l"(cnt), "r"(i1 << 16) : "memory");
}
__device__ __forceinline__ uint32_t act2(uint32_t u, const float4& cf) {
    return pack_bf(silu_half(fmaf(bf_lo(u), cf.x, cf.z)), silu_half(fmaf(bf_hi(u), cf.y, cf.w)));
}
__device__ __forceinline__ void norm_unit(uint32_t (&u)[4], const float4& ca, const float4& cb) {
    u[0] = act2(u[0], ca); u[1] = act2(u[1], ca); u[2] = act2(u[2], cb); u[3] = act2(u[3], cb);
}
__device__ __forceinline__ void read_stats(uint32_t gst, float (&g)[8]) {
    asm volatile("ld.volatile.shared.v4.f32 {%0,%1,%2,%3}, [%4];" : "=f"(g[0]), "=f"(g[1]), "=f"(g[2]), "=f"(g[3]) : "r"(gst + S0) : "memory");
    asm volatile("ld.volatile.shared.v4.f32 {%0,%1,%2,%3}, [%4];" : "=f"(g[4]), "=f"(g[5]), "=f"(g[6]), "=f"(g[7]) : "r"(gst + 16 + S0) : "memory");
}
template <int T>
__device__ __forceinline__ void wait_stats(uint32_t gst, float (&g)[8]) {
    float rs, mr;
    unsigned it = 0;
#pragma unroll 1
    do {
        asm volatile("ld.volatile.shared.v2.f32 {%0,%1}, [%2];" : "=f"(rs), "=f"(mr) : "r"(gst + 8 * T + S0) : "memory");
    } while (!__all_sync(0xffffffffu, rs != 0.f) && ++it < 8 * SPIN_LIMIT);
    if (T < 3) read_stats(gst, g);
    g[2 * T] = rs; g[2 * T + 1] = mr;
}
template <int T>
__device__ __forceinline__ void own_unit(uint32_t (&o)[4], const float (&z)[8], float4 (&cf)[8], const float (&g)[8]) {
    float4 &ca = cf[2 * T], &cb = cf[2 * T + 1];
    const float rs = g[2 * T], mr = g[2 * T + 1];
    ca.z = fmaf(-mr, ca.x, ca.z); ca.w = fmaf(-mr, ca.y, ca.w);
    cb.z = fmaf(-mr, cb.x, cb.z); cb.w = fmaf(-mr, cb.y, cb.w);
#pragma unroll
    for (int i = 0; i < 4; i++)
        o[i] = pack_bf(silu_half(fmaf(z[2 * i], rs, i < 2 ? ca.z : cb.z)), silu_half(fmaf(z[2 * i + 1], rs, i < 2 ? ca.w : cb.w)));
}
template <int FIRST, int N>
__device__ __forceinline__ void norm_block(uint32_t (&u)[4][4], float4 (&cf)[8], uint32_t act, uint32_t mask, uint32_t fbar, int lane) {
#pragma unroll
    for (int t = FIRST; t < FIRST + N; t++) {
        norm_unit(u[t], cf[2 * t], cf[2 * t + 1]);
        stsm4(act + t * 2 * KC_BYTES, u[t][0] & mask, u[t][1] & mask, u[t][2] & mask, u[t][3] & mask);
    }
    fence_async_smem();
    __syncwarp();
    if (lane < N) mbar_arrive(fbar + 16 * (FIRST + lane));
}
__device__ __forceinline__ void publish(uint32_t bar, int lane) {
    fence_async_smem();
    __syncwarp();
    if (lane == 0) mbar_arrive(bar);
}
template <int T>
__device__ __forceinline__ void next_unit(const float (&z)[8], float4 (&cf)[8], uint32_t gst, float (&g)[8], uint32_t act, uint32_t fbar, int lane) {
    const bool have = __all_sync(0xffffffffu, g[2 * T] != 0.f);
    if (!have) { publish(fbar + 16 * (T - 1), lane); wait_stats<T>(gst, g); }
    uint32_t o[4];
    own_unit<T>(o, z, cf, g);
    if (have) publish(fbar + 16 * (T - 1), lane);
    stsm4(act + T * 2 * KC_BYTES, o[0], o[1], o[2], o[3]);
}
__device__ __forceinline__ void stat_mma(float (&c)[4], uint32_t p, uint32_t q) {
    asm("mma.sync.aligned.m16n8k16.row.col.f32.bf16.bf16.f32 {%0,%1,%2,%3}, {%4,%5,%6,%5}, {%4,%6}, {%0,%1,%2,%3};"
        : "+f"(c[0]), "+f"(c[1]), "+f"(c[2]), "+f"(c[3]) : "r"(p), "r"(0x3f803f80u), "r"(q));
}
__device__ __forceinline__ void stat_store(const float (&c)[4], uint32_t dst, int lane) {
    const int g = lane >> 2, t = lane & 3;
    if (t == (g >> 1)) sts32f(dst + g * 4, (g & 1) ? c[1] : c[0]);
    if (g == 7) sts32f(dst + 32 + t * 4, c[2] + c[3]);
}
__device__ __forceinline__ float sum4(float4 v) { return (v.x + v.y) + (v.z + v.w); }
__device__ __forceinline__ void stat_publish(uint32_t src, float* acc, int lane, bool real) {
    const uint32_t a = src + (lane & 15) * 48;
    float q = sum4(lds128f(a)) + sum4(lds128f(a + 16)), sm = sum4(lds128f(a + 32));
    q += __shfl_xor_sync(0xffffffffu, q, 1); sm += __shfl_xor_sync(0xffffffffu, sm, 1);
    q += __shfl_xor_sync(0xffffffffu, q, 2); sm += __shfl_xor_sync(0xffffffffu, sm, 2);
    if (real && (lane & 19) == 0) red_add4(acc + lane, 1.f, sm, q, 1.f);
}
__device__ __forceinline__ void fence_acc(float (&d)[64]) {
#pragma unroll
    for (int i = 0; i < 64; i++) asm volatile("" : "+f"(d[i])::"memory");
}
__device__ __forceinline__ void ld_unit(uint32_t (&u)[4], const uint4* p) {
    asm volatile("ld.relaxed.gpu.global.v4.u32 {%0,%1,%2,%3}, [%4];" : "=r"(u[0]), "=r"(u[1]), "=r"(u[2]), "=r"(u[3]) : "l"(p) : "memory");
}

__device__ __noinline__ void side_jobs(const __nv_bfloat16* __restrict__ t_emb, const __nv_bfloat16* __restrict__ w_emb,
                                       const __nv_bfloat16* __restrict__ w2, Scratch* __restrict__ gs, unsigned clk0) {
    const int tid = threadIdx.x, warp = tid >> 5, lane = tid & 31, j = blockIdx.x;
    float tv = 0.f;
    if (lane < 24) tv = __bfloat162float(t_emb[(lane / 12) * E + j * 192 + warp * 12 + lane % 12]);
    if (tid == 0) {
        mbar_init(BAR(0), 1);
        mbar_expect(BAR(0), 192 * C * 2);
        fence_async_smem();
        while (clock32() - clk0 < SDELAY) {}
#pragma unroll
        for (int i = 0; i < 4; i++)
            asm volatile("cp.async.bulk.prefetch.L2.global [%0], 18432;" ::"l"(reinterpret_cast<const char*>(w2) + (j * 4 + i) * 18432) : "memory");
#pragma unroll
        for (int i = 0; i < 4; i++) bulk_g2s(S0 + SM_W + i * 12288, w_emb + (j * 192 + i * 48) * C, 12288, S0 + BAR(0));
    }
    if (j == 0 && tid < 32) gs->acc2[(tid >> 4) * LS + (tid & 15)] = 0.f;
    const float sv = silu_half(0.5f * tv);
    __syncthreads();
    mbar_wait(BAR(0), 0);
    float acc[8] = {0.f, 0.f, 0.f, 0.f, 0.f, 0.f, 0.f, 0.f};
#pragma unroll
    for (int i = 0; i < 12; i++) {
        const float2 wq = lds64f(SM_W + (warp * 12 + i) * 256 + lane * 8);
        const uint32_t wx = __float_as_uint(wq.x), wy = __float_as_uint(wq.y);
#pragma unroll
        for (int bb = 0; bb < 2; bb++) {
            const float sx = __shfl_sync(0xffffffffu, sv, bb * 12 + i);
            acc[4 * bb + 0] = fmaf(sx, bf_lo(wx), acc[4 * bb + 0]); acc[4 * bb + 1] = fmaf(sx, bf_hi(wx), acc[4 * bb + 1]);
            acc[4 * bb + 2] = fmaf(sx, bf_lo(wy), acc[4 * bb + 2]); acc[4 * bb + 3] = fmaf(sx, bf_hi(wy), acc[4 * bb + 3]);
        }
    }
    sts128f(SM_ACT + warp * 1024 + lane * 16, make_float4(acc[0], acc[1], acc[2], acc[3]));
    sts128f(SM_ACT + warp * 1024 + 512 + lane * 16, make_float4(acc[4], acc[5], acc[6], acc[7]));
    __syncthreads();
    if (tid < 128) {
        float2 sum = make_float2(0.f, 0.f);
#pragma unroll
        for (int w = 0; w < 16; w++) { const float2 p = lds64f(SM_ACT + w * 1024 + tid * 8); sum.x += p.x; sum.y += p.y; }
        *reinterpret_cast<float2*>(&gs->emb[j * NB * C + tid * 2]) = sum;
        bar_sync(1, 128);
        if (tid < 2) asm volatile("red.release.gpu.global.add.u32 [%0], 1;" ::"l"(&gs->wcnt[(2 * NB + tid) * LS]) : "memory");
    }
}

__global__ void __cluster_dims__(2, 1, 1) __launch_bounds__(NTHREADS, 1)
resblock_kernel(const __nv_bfloat16* __restrict__ w1, const __nv_bfloat16* __restrict__ x,
                const __nv_bfloat16* __restrict__ t_emb, const __nv_bfloat16* __restrict__ g1,
                const __nv_bfloat16* __restrict__ be1, const __nv_bfloat16* __restrict__ w_emb,
                const __nv_bfloat16* __restrict__ g2, const __nv_bfloat16* __restrict__ be2,
                const __nv_bfloat16* __restrict__ w2, __nv_bfloat16* __restrict__ out, Scratch* __restrict__ gs,
                const __grid_constant__ CUtensorMap xmap) {
    const unsigned clk0 = clock32();
    if (threadIdx.x == 480 && blockIdx.x >= NXTRA) TLG(1);
    const int tid = threadIdx.x, lane = tid & 31;
    const int cta = blockIdx.x - NXTRA, b = cta >> 6, r = cta & 63;
    uint4 v[5];
    if (tid < 32) weight_load(v, w1, cta & (NCTA - 1), lane);
    if (tid >= 192 && tid < 192 + 72) {
        const int c2 = (cta + WPF) & (NCTA - 1), t = tid - 192;
        asm volatile("prefetch.global.L2 [%0];" ::"l"(reinterpret_cast<const char*>(w1) + (uint32_t)((((c2 & 15) * 8 + (t & 7)) * 8 + (c2 >> 4)) * 288 + (t >> 3) * 32)));
    }
    uint4 xv[8];
    const int wg4 = (tid >> 5) - 1;
    const bool early = tid >= 32 && wg4 < NLDG;
    if (early) {
        const char* src = reinterpret_cast<const char*>(x) + (uint32_t)((((b & 1) * C + wg4 * 32 + (lane >> 3)) * HW + r) * HW * 2 + (lane & 7) * 16);
        while (clock32() - clk0 < XDELAY + (wg4 >> 1) * XSTAG + (wg4 & 1) * XSTAG2) {}
#pragma unroll
        for (int i = 0; i < 8; i++) xv[i] = __ldg(reinterpret_cast<const uint4*>(src + i * (4 * HW * HW * 2)));
    }
    const int warp = __shfl_sync(0xffffffffu, tid >> 5, 0);
    if (cta < 0) { side_jobs(t_emb, w_emb, w2, gs, clk0); return; }

    if (warp != 4) asm volatile("barrier.cluster.arrive.relaxed.aligned;" ::: "memory");
    const bool has_outer = (r != 0) && (r != HW - 1);
    if (warp == 1 || warp == 2 || warp == 3 || warp == 5) {
        const int g = warp < 4 ? warp - 1 : 3;
        if (elect_one()) {
            if (g >= NLDG) asm volatile("prefetch.tensormap [%0];" ::"l"(&xmap) : "memory");
            mbar_init(BAR(BAR_X) + 8 * g, 1);
            if (g >= NLDG) mbar_expect(BAR(BAR_X) + 8 * g, 4096);
            fence_async_smem();
        }
        __syncwarp();
        bar_arrive(4, 256 + 32 + 128);
        if (g >= NLDG) {
            while (clock32() - clk0 < XDELAY + (g >> 1) * XSTAG + (g & 1) * XSTAG2) {}
            if (elect_one()) tma_x(SM_XOWN + g * 4096, &xmap, r, b * C + g * 32, BAR(BAR_X) + 8 * g);
            __syncwarp();
            mbar_wait(BAR(BAR_X) + 8 * g, 0);
#pragma unroll
            for (int k = 0; k < 8; k++) xv[k] = lds128(SM_XOWN + g * 4096 + k * 512 + lane * 16);
        }
        float c[8][4];
#pragma unroll
        for (int k = 0; k < 8; k++) {
            c[k][0] = c[k][1] = c[k][2] = c[k][3] = 0.f;
            stat_mma(c[k], xv[k].x, xv[k].y); stat_mma(c[k], xv[k].z, xv[k].w);
        }
#pragma unroll
        for (int i = 0; i < 4; i++) c[0][i] = ((c[0][i] + c[1][i]) + (c[2][i] + c[3][i])) + ((c[4][i] + c[5][i]) + (c[6][i] + c[7][i]));
        stat_store(c[0], SM_RED + g * 48, lane);
        __syncwarp();
        if (lane == 0) {
            const uint32_t a = SM_RED + g * 48;
            red_add4(&gs->acc1[b * LS + g * 4], 1.f, sum4(lds128f(a + 32)), sum4(lds128f(a)) + sum4(lds128f(a + 16)), 1.f);
            TL(74 + g);
        }
        if (g < NLDG) {
#pragma unroll
            for (int i = 0; i < 8; i++)
                sts128(SM_XOWN + g * 4096 + i * 512 + (lane >> 3) * 128 + (((lane & 7) ^ ((lane >> 3) + 4 * (i & 1))) << 4), xv[i]);
            __syncwarp();
            if (lane == 0) mbar_arrive(BAR(BAR_X) + 8 * g);
        }
    }
    if (warp == 4) {
            if (elect_one()) {
#pragma unroll
                for (int i = 0; i < NSTAGE; i++) mbar_init(BAR(BAR_FULL + i), (i >> 3) == 1 ? 1 : 5);
#pragma unroll
                for (int i = 0; i < NS + 2; i++) mbar_init(BAR(BAR_WEMPTY + i), 4);
#pragma unroll
                for (int i = BAR_STATS; i < BAR_X; i++) mbar_init(BAR(i), i == BAR_EMB ? 3 : 1);
                mbar_init(BAR(BAR_X + 4), 1);
                asm volatile("fence.mbarrier_init.release.cluster;" ::: "memory");
            }
            if (lane < 4) sts128(SM_GST + lane * 16, make_uint4(0, 0, 0, 0));
            __syncwarp();
            fence_async_smem();
            bar_arrive(0, 96);
            bar_arrive(5, 64);
            bar_arrive(4, 256 + 32 + 128);
            const uint4 z = make_uint4(0, 0, 0, 0);
#pragma unroll
            for (int i = 0; i < 2; i++) sts128(SM_ACT + (i * 16 + (lane >> 1)) * CH_PITCH + (lane & 1) * 16, z);
            if (lane < 4) sts128(SM_ACT + (2 + (lane >> 1)) * ROW_BYTES + (lane & 1) * 16, z);
            if (lane < 16) sts128(SM_ONES + lane * 16, make_uint4(lane < 8 ? 0x3f803f80u : 0u, 0, 0, 0));
            fence_async_smem();
            bar_arrive(7, 160);
            asm volatile("barrier.cluster.arrive.relaxed.aligned;" ::: "memory");
            while (clock32() - clk0 < W2DELAY) {}
            weight_load(v, w2, cta, lane);
        }
    if (warp == 0 || warp == 4) {
        const int k = warp >> 2;
#pragma unroll
        for (int i = 0; i < 5; i++)
            if (i < 4 || !(lane & 2)) sts128(SM_BNC + k * 2304 + (lane >> 2) * 288 + (lane & 3) * 16 + i * 64, v[i]);
        if (lane == 0) TL(k ? 14 : 81);
        __syncwarp();
        weight_block(SM_BNC + k * 2304, gs->wt + k * NSTAGE * STAGE_BYTES, cta, lane,
                     k ? &gs->wcnt[(NB + (lane & 1)) * LS] : &gs->w1cnt[((lane & 1) * 8 + (cta >> 4)) * KS], k == 0 && (cta >> 4) < NSPEC);
        if (lane == 0) TL(k ? 13 : 4);
    }

    if (warp >= 8) {
        const int nw = warp - 8;
        if (nw < 2) {
            const uint2 ga = __ldg(reinterpret_cast<const uint2*>(nw ? g2 : g1) + lane), bt = __ldg(reinterpret_cast<const uint2*>(nw ? be2 : be1) + lane);
            sts128f(SM_COEF + nw * 1024 + lane * 32, make_float4(0.5f * bf_lo(ga.x), 0.5f * bf_hi(ga.x), 0.5f * bf_lo(bt.x), 0.5f * bf_hi(bt.x)));
            sts128f(SM_COEF + nw * 1024 + lane * 32 + 16, make_float4(0.5f * bf_lo(ga.y), 0.5f * bf_hi(ga.y), 0.5f * bf_lo(bt.y), 0.5f * bf_hi(bt.y)));
        }
        bar_sync(4, 256 + 32 + 128);
        const int par = nw >> 2, wq = nw & 3;
        const uint32_t act_off = SM_ACT + (par * 2 + (lane >> 4)) * CH_PITCH + (2 + wq * 16 + (lane & 15)) * 16;
        const uint32_t stg_off = (par * 16 + (lane >> 4) * 8 + (lane & 7)) * 128 + (((2 * wq + ((lane >> 3) & 1)) ^ (lane & 7)) << 4);
        const uint32_t cfa = SM_COEF + par * 128 + (lane & 3) * 16;
        const uint32_t fbar = BAR(BAR_FULL) + 8 * par;
        uint4* inbox = gs->box + cta * 1024 + nw * 32 + lane;
#pragma unroll 1
        for (int conv = 0; conv < 2; conv++) {
            uint32_t u[4][4], w[4][4];
            float4 cf[8];
            if (conv == 0) {
#pragma unroll
                for (int i = 0; i < 4; i++) { mbar_wait(BAR(BAR_X + i), 0); ldsm4t(u[i], SM_XOWN + stg_off + i * 4096); }
            } else {
                mbar_wait(BAR(BAR_HW), 0);
#pragma unroll
                for (int i = 0; i < 4; i++) ldsm4(u[i], act_off + i * 2 * KC_BYTES);
            }
#pragma unroll
            for (int i = 0; i < 8; i++) cf[i] = lds128f(cfa + conv * 1024 + (i >> 1) * 256 + (i & 1) * 64);
            const uint32_t gst = SM_GST + conv * 32;
            float gv[8], z[4][8];
#pragma unroll
            for (int i = 0; i < 16; i++) {
                const float4& c = cf[i >> 1];
                z[i >> 2][2 * (i & 3)] = bf_lo(u[i >> 2][i & 3]) * c.x; z[i >> 2][2 * (i & 3) + 1] = bf_hi(u[i >> 2][i & 3]) * c.y;
                asm volatile("" : "+f"(z[i >> 2][2 * (i & 3)]), "+f"(z[i >> 2][2 * (i & 3) + 1]));
            }
            wait_stats<0>(gst, gv);
            if (tid == 256) TL(22 + conv * 4);
            if (par) { const unsigned c1 = clock32(); while (clock32() - c1 < PDELAY) {} }
            uint32_t o[4];
            own_unit<0>(o, z[0], cf, gv);
            stsm4(act_off, o[0], o[1], o[2], o[3]);
            publish(fbar, lane);
            if (tid == 256) TL(8 + conv * 8);
            if (!__all_sync(0xffffffffu, gv[2] != 0.f)) wait_stats<1>(gst, gv);
            own_unit<1>(o, z[1], cf, gv);
            stsm4(act_off + 2 * KC_BYTES, o[0], o[1], o[2], o[3]);
            next_unit<2>(z[2], cf, gst, gv, act_off, fbar, lane);
            next_unit<3>(z[3], cf, gst, gv, act_off, fbar, lane);
            publish(fbar + 48, lane);
#pragma unroll
            for (int i = 0; i < 8; i++) { cf[i].x *= gv[i & ~1]; cf[i].y *= gv[i & ~1]; }
            if (tid == 256) TL(84 + conv);
            if (has_outer) {
                mbar_wait(BAR(BAR_X + 4), conv);
                if (conv == 0) {
#pragma unroll
                    for (int i = 0; i < 4; i++) ldsm4t(w[i], SM_XOUT + stg_off + i * 4096);
                } else {
#pragma unroll
                    for (int i = 0; i < 4; i++) {
                        const uint4 q = lds128(SM_XOWN + (tid - 256) * 16 + i * 4096);
                        w[i][0] = q.x; w[i][1] = q.y; w[i][2] = q.z; w[i][3] = q.w;
                    }
                    unsigned it = 0;
                    while (true) {
                        bool ok = true;
#pragma unroll
                        for (int i = 0; i < 16; i++) ok = ok && w[i >> 2][i & 3] != 0;
                        if (__all_sync(0xffffffffu, ok) || ++it > SPIN_LIMIT) break;
#pragma unroll
                        for (int i = 0; i < 4; i++) ld_unit(w[i], inbox + i * 256);
                    }
#pragma unroll
                    for (int i = 0; i < 16; i++) w[i >> 2][i & 3] = ~w[i >> 2][i & 3];
                }
            }
            if (conv == 0) {
                bar_sync(3, 256);
                if (nw == 0) sts128(SM_ACT + 2 * ROW_BYTES + (lane >> 1) * CH_PITCH + (lane & 1) * 16, make_uint4(0, 0, 0, 0));
            }
            if (tid == 256) TL(24 + conv * 4);
            norm_block<0, 2>(w, cf, act_off + 2 * ROW_BYTES, has_outer ? ~0u : 0u, fbar + 128, lane);
            if (tid == 256) TL(88 + conv);
            norm_block<2, 2>(w, cf, act_off + 2 * ROW_BYTES, has_outer ? ~0u : 0u, fbar + 128, lane);
            if (tid == 256) TL(23 + conv * 4);
        }
        if (has_outer) {
            mbar_wait(BAR(BAR_FULL + NSTAGE - 1), 1);
#pragma unroll
            for (int i = 0; i < 4; i++) inbox[i * 256] = make_uint4(0, 0, 0, 0);
        }
        {
            const int oc0 = par * 64 + ((tid & 127) >> 3), seg = lane & 7;
            __nv_bfloat16* dst = out + ((size_t)(b * C + oc0) * HW + r) * HW + seg * 8;
            const uint32_t src = SM_XOWN + oc0 * 128 + ((seg ^ (oc0 & 7)) << 4);
            asm volatile("{\n.reg .pred p;\nsetp.eq.u64 p, %0, 0;\n@p st.shared.u32 [%1], 0;\n}" ::"l"(dst), "r"(src + S0) : "memory");
            bar_sync(par ? 1 : 6, 128 + 128);
#pragma unroll
            for (int i = 0; i < 4; i++) *reinterpret_cast<uint4*>(dst + (size_t)i * 16 * HW * HW) = lds128(src + i * 2048);
            if (tid == 384) { TL(20); TLG(21); }
        }
    } else if (warp < 4) {
        const int wq = warp;
        bar_sync(7, 160);

        const uint32_t xbase = SM_XOWN + ((lane >> 4) * 8 + (lane & 7)) * 128 + (((2 * wq + ((lane >> 3) & 1)) ^ (lane & 7)) << 4);
        float d[64];
#pragma unroll
        for (int i = 0; i < 64; i++) d[i] = 0.f;
#pragma unroll 1
        for (int conv = 0; conv < 2; conv++) {
            fence_acc(d);
            mma_stages<0>(d, conv, tid, gs);
            if (conv == 0) {
                asm volatile("wgmma.fence.sync.aligned;" ::: "memory");
                wgmma128<(SM_ONES >> 4) | (8u << 16), (SM_EMB >> 4), 0, 8>(d);
                asm volatile("wgmma.commit_group.sync.aligned;" ::: "memory");
            }
            asm volatile("wgmma.wait_group.sync.aligned 0;" ::: "memory");
            fence_acc(d);
            if (tid == 0) TL(10 + conv * 8);
            if (conv == 1) {
                fence_acc(d);
#pragma unroll
                for (int kc = 0; kc < 8; kc++) {
                    stsm4t(xbase + kc * 2048, pack_bf(d[8 * kc], d[8 * kc + 1]), pack_bf(d[8 * kc + 2], d[8 * kc + 3]),
                           pack_bf(d[8 * kc + 4], d[8 * kc + 5]), pack_bf(d[8 * kc + 6], d[8 * kc + 7]));
                    if (kc == 3) bar_arrive(6, 128 + 128);
                }
                bar_arrive(1, 128 + 128);
                if (tid == 0) TL(5);
                break;
            }
            uint32_t hp[32];
#pragma unroll
            for (int i = 0; i < 32; i++) hp[i] = pack_bf(d[2 * i], d[2 * i + 1]);
#pragma unroll
            for (int g = 0; g < 4; g++) {
                float c[4] = {0.f, 0.f, 0.f, 0.f};
#pragma unroll
                for (int i = 0; i < 4; i++) stat_mma(c, hp[8 * g + 2 * i], hp[8 * g + 2 * i + 1]);
                stat_store(c, SM_RED + (g * 4 + wq) * 48, lane);
            }
            bar_sync(2, 128);
            if (wq == 0) stat_publish(SM_RED, &gs->acc2[b * LS], lane, true);
            if (tid == 0) TL(11);
            const uint32_t hbase = SM_ACT + (lane >> 4) * CH_PITCH + (2 + wq * 16 + (lane & 15)) * 16;
#pragma unroll
            for (int kc = 0; kc < 8; kc++) stsm4(hbase + kc * 2 * CH_PITCH, hp[4 * kc], hp[4 * kc + 1], hp[4 * kc + 2], hp[4 * kc + 3]);
            __syncwarp();
            if (lane == 0) mbar_arrive(BAR(BAR_HW));
            if (lane < LAG) mbar_arrive(BAR(BAR_WEMPTY + (NSTAGE - LAG) % NS) + 8 * lane);
            if (has_outer) {
                uint4* outbox = gs->box + (cta + ((r & 1) ? 1 : -1)) * 1024 + tid;
#pragma unroll
                for (int kc = 0; kc < 8; kc++) outbox[kc * 128] = make_uint4(~hp[4 * kc], ~hp[4 * kc + 1], ~hp[4 * kc + 2], ~hp[4 * kc + 3]);
            }
            if (tid == 0) TL(12);
#pragma unroll
            for (int kc = 0; kc < 8; kc++) {
                uint32_t p[4];
                ldsm4t(p, xbase + kc * 2048);
#pragma unroll
                for (int i = 0; i < 4; i++) { d[8 * kc + 2 * i] = bf_lo(p[i]); d[8 * kc + 2 * i + 1] = bf_hi(p[i]); }
            }
            fence_async_smem();
            __syncwarp();
            if (lane == 0) mbar_arrive(BAR(BAR_XFREE));
        }
        {
        }
    } else if (warp < 6) {
        if (warp == 5) {
            bar_sync(5, 64);
#pragma unroll 1
            for (int st = 0; st < NSPEC; st++) {
#pragma unroll 1
                for (unsigned tr = 0; tr < SPIN_LIMIT; tr++) {
                    mbar_wait(BAR(BAR_SP) + 8 * st, tr & 1);
                    bool ok = true;
#pragma unroll
                    for (int i = 0; i < 12; i++) {
                        uint32_t wd;
                        asm volatile("ld.shared.u32 %0, [%1];" : "=r"(wd) : "r"(S0 + SM_W + st * STAGE_BYTES + i * 1024 + lane * 32 + (lane >> 2) * 4) : "memory");
                        ok = ok && wd != 0;
                    }
                    if (__all_sync(0xffffffffu, ok)) break;
                    fence_async_smem();
                    __syncwarp();
                    if (elect_one()) {
                        mbar_expect(BAR(BAR_SP) + 8 * st, STAGE_BYTES);
                        bulk_g2s(S0 + SM_W + st * STAGE_BYTES, gs->wt + st * STAGE_BYTES, STAGE_BYTES, S0 + BAR(BAR_SP) + 8 * st);
                    }
                    if (lane == 0) TL(93);
                }
                if (lane == 0) { mbar_arrive(BAR(BAR_FULL) + 8 * st); if (st == 0) TL(92); }
            }
            mbar_wait(BAR(BAR_FULL + OAFTER), 0);
            if (has_outer && elect_one()) {
                mbar_expect(BAR(BAR_X + 4), 16384);
#pragma unroll
                for (int i = 0; i < 4; i++) tma_x(SM_XOUT + i * 4096, &xmap, r + ((r & 1) ? 1 : -1), b * C + i * 32, BAR(BAR_X + 4));
            }
            __syncwarp();
            asm volatile("barrier.cluster.wait.acquire.aligned;" ::: "memory");
            const uint32_t peer = (r & 1) ^ 1;
            const uint32_t self0 = mapa(0, r & 1), peer0 = mapa(0, peer);
#pragma unroll 1
            for (int conv = 0; conv < 2; conv++) {
                if (FWD0) mbar_wait(BAR(BAR_FULL + FWD0), conv);
#pragma unroll 1
                for (int kc = 0; kc < 8; kc++) {
                    mbar_wait(BAR(BAR_FULL) + 8 * kc, conv);
                    if (elect_one())
                        asm volatile("cp.async.bulk.shared::cluster.shared::cta.mbarrier::complete_tx::bytes [%0], [%1], %2, [%3];"
                                     ::"r"(peer0 + SM_ACT + ROW_BYTES + kc * KC_BYTES), "r"(self0 + SM_ACT + kc * KC_BYTES), "r"(KC_BYTES),
                                       "r"(peer0 + BAR(BAR_FULL + 8) + 8 * kc) : "memory");
                }
                if (lane == 0) TL(86 + conv);
#pragma unroll 1
                for (int kc = 0; kc < 8; kc++) mbar_wait(BAR(BAR_FULL + 8) + 8 * kc, conv);
                if (lane == 0)
                    asm volatile("mbarrier.arrive.relaxed.cluster.shared::cluster.b64 _, [%0];" ::"r"(peer0 + (conv ? BAR(BAR_ACK) : BAR(BAR_EMB))) : "memory");
            }
            mbar_wait(BAR(BAR_ACK), 0);
        } else {
            mbar_wait(BAR(BAR_STATS), 0);
            unsigned it = 0;
            while (!__all_sync(0xffffffffu, ld_relaxed(&gs->wcnt[(2 * NB + b) * LS]) >= (unsigned)NXTRA) && ++it < SPIN_LIMIT) __nanosleep(100);
            fence_acquire();
            float ev[4] = {0.f, 0.f, 0.f, 0.f};
#pragma unroll
            for (int j = 0; j < NXTRA; j++) {
                const uint4 ef = ld_relaxed_v4(&gs->emb[(j * NB + b) * C + lane * 4]);
                ev[0] += __uint_as_float(ef.x); ev[1] += __uint_as_float(ef.y); ev[2] += __uint_as_float(ef.z); ev[3] += __uint_as_float(ef.w);
            }
#pragma unroll
            for (int i = 0; i < 4; i++) {
                const float hi = bf_lo(pack_bf(ev[i], 0.f));
                sts128(SM_EMB + (lane * 4 + i) * 16, make_uint4(pack_bf(hi, ev[i] - hi), 0, 0, 0));
            }
            fence_async_smem();
            __syncwarp();
            if (lane == 0) { mbar_arrive(BAR(BAR_EMB)); TL(19); }
        }
    } else if (warp == 6) {
        bar_sync(0, 96);
        const uint32_t ebytes = STAGE_BYTES + ((lane >> 3) == 1 ? KC_BYTES : 0);
        if (lane < NSTAGE) mbar_expect(lane < NSPEC ? BAR(BAR_SP) + 8 * lane : BAR(BAR_FULL) + 8 * lane, ebytes);
        const int swap = (r & 1) ? 0 : 8 * STAGE_BYTES;
        unsigned it = 0;
        {
            int g = 0;
            const unsigned* cnt = &gs->w1cnt[(b * 8 + (lane & 7)) * KS];
            unsigned cv = ld_relaxed(cnt);
#pragma unroll 1
            while (g < NS) {
                unsigned ready = __ballot_sync(0xffffffffu, ((cv >> (lane < NSPEC ? 24 : (lane < 8 ? 0 : 16))) & 0xffu) >= 16u);
                if ((ready >> 8 & 0xff) != 0xff) ready &= 0xff;
                if (ready != ~0u) cv = ld_relaxed(cnt);
                ready >>= g;
                if (++it > SPIN_LIMIT) ready = ~0u;
                if (!(ready & 1)) continue;
                fence_async_global();
                if (lane == 0) TL(g ? 3 : 6);
#pragma unroll 1
                for (; (ready & 1) && g < NS; g++, ready >>= 1)
                    if (elect_one())
                        bulk_g2s(S0 + SM_W + g * STAGE_BYTES, gs->wt + g * STAGE_BYTES + (g >= 8 ? swap : 0), STAGE_BYTES,
                                 S0 + (g < NSPEC ? BAR(BAR_SP) : BAR(BAR_FULL)) + 8 * g);
            }
        }
#pragma unroll 1
        for (int q = 3; q < 12; q++) {
            const int conv = q >= 6, qs = conv ? q - 6 : q, sl = q % 3;
            const unsigned char* wsrc = gs->wt + q * 4 * STAGE_BYTES + (qs < 2 ? 0 : (qs < 4 ? swap : -swap));
            const uint32_t par = (q / 3 - 1) & 1;
            if (q == 6) {
                it = 0;
                while (!__all_sync(0xffffffffu, ld_relaxed(&gs->wcnt[(NB + b) * LS]) == NCTA * 0x10001u) && ++it < SPIN_LIMIT) {}
                fence_acquire();
                fence_async_global();
                if (lane == 0) { mbar_arrive(BAR(BAR_EMB)); TL(2); }
            }
#pragma unroll
            for (int i = 0; i < 4; i++) {
                mbar_wait(BAR(BAR_WEMPTY + i) + 32 * sl, par);
                if (i == 0 && (q == 6 || q == 9)) {
                    if ((lane >= NS) == (q == 9) && lane < NSTAGE) mbar_expect(BAR(BAR_FULL) + 8 * lane, ebytes);
                    __syncwarp();
                }
                if (elect_one())
                    bulk_g2s(S0 + SM_W + (sl * 4 + i) * STAGE_BYTES, wsrc + i * STAGE_BYTES, STAGE_BYTES, S0 + BAR(BAR_FULL + i) + 32 * qs);
            }
        }
    } else {
        bar_sync(0, 96);
#pragma unroll 1
        for (int conv = 0; conv < 2; conv++) {
            if (conv == 1) mbar_wait(BAR(BAR_HW), 0);
            const float* asrc = (conv ? gs->acc2 : gs->acc1) + b * LS + (lane & 3) * 4;
            unsigned it = 0;
#pragma unroll 1
            while (true) {
                const uint4 f = ld_relaxed_v4(asrc);
                const bool ok = ((f.x == 0x42800000u) & (f.w == 0x42800000u)) || ++it > SPIN_LIMIT;
                if (ok && lane < 4) {
                    const float inv_n = 1.0f / (32.0f * HW * HW);
                    const float mean = __uint_as_float(f.y) * inv_n;
                    float rs;
                    asm("rsqrt.approx.ftz.f32 %0, %1;" : "=f"(rs) : "f"(fmaxf(fmaf(-mean, mean, __uint_as_float(f.z) * inv_n), 0.f) + 1e-5f));
                    asm volatile("st.shared.v2.f32 [%0], {%1,%2};" ::"r"(S0 + SM_GST + conv * 32 + lane * 8), "f"(rs == 0.f ? 1e-38f : rs), "f"(mean * rs) : "memory");
                }
                if (__all_sync(0xffffffffu, ok)) break;
            }
            if (lane == 0) { mbar_arrive(BAR(BAR_STATS)); TL(7 + conv * 8); }
        }
        mbar_wait(BAR(BAR_XFREE), 0);
        if (has_outer && elect_one()) {
            mbar_expect(BAR(BAR_X + 4), 16384);
            bulk_g2s(S0 + SM_XOWN, gs->box + cta * 1024, 16384, S0 + BAR(BAR_X + 4));
        }
        if ((cta >> 4) < NSPEC) {
            unsigned it = 0;
            while (!__all_sync(0xffffffffu, ld_relaxed(&gs->acc2[(b ^ 1) * LS]) == 0x42800000u) && ++it < SPIN_LIMIT) __nanosleep(200);
            if (lane < 24) {
                uint4* z = reinterpret_cast<uint4*>(gs->wt + (cta >> 4) * STAGE_BYTES + (cta & 15) * 768) + lane * 2;
                z[0] = make_uint4(0, 0, 0, 0); z[1] = make_uint4(0, 0, 0, 0);
            }
        }
        if (r == 0) {
            if (lane < 16) gs->acc1[b * LS + lane] = 0.f;
            if (lane < 3) gs->wcnt[(lane * NB + b) * LS] = 0;
            if (lane < 8) gs->w1cnt[(b * 8 + lane) * KS] = 0;
        }
    }
}

}

extern "C" void kernel_launch(void* const* d_in, const int* in_sizes, int n_in, void* d_out, int out_size) {
    (void)in_sizes; (void)n_in; (void)out_size;
    typedef CUresult (*EncodeFn)(CUtensorMap*, CUtensorMapDataType, cuuint32_t, void*, const cuuint64_t*, const cuuint64_t*,
                                 const cuuint32_t*, const cuuint32_t*, CUtensorMapInterleave, CUtensorMapSwizzle,
                                 CUtensorMapL2promotion, CUtensorMapFloatOOBfill);
    static Scratch* gs = nullptr;
    static EncodeFn encode = nullptr;
    if (!gs) {
        cudaFuncSetAttribute(resblock_kernel, cudaFuncAttributeMaxDynamicSharedMemorySize, SM_TOTAL);
        cudaGetSymbolAddress((void**)&gs, g_scratch);
        cudaDriverEntryPointQueryResult qr;
        cudaGetDriverEntryPoint("cuTensorMapEncodeTiled", (void**)&encode, cudaEnableDefault, &qr);
    }
    CUtensorMap xmap;
    const cuuint64_t dims[3] = {HW, HW, NB * C}, strides[2] = {HW * 2, HW * HW * 2};
    const cuuint32_t box[3] = {HW, 1, 32}, es[3] = {1, 1, 1};
    encode(&xmap, CU_TENSOR_MAP_DATA_TYPE_BFLOAT16, 3, d_in[0], dims, strides, box, es, CU_TENSOR_MAP_INTERLEAVE_NONE,
           CU_TENSOR_MAP_SWIZZLE_128B, CU_TENSOR_MAP_L2_PROMOTION_NONE, CU_TENSOR_MAP_FLOAT_OOB_FILL_NONE);
    resblock_kernel<<<NCTA + NXTRA, NTHREADS, SM_TOTAL>>>(
        (const __nv_bfloat16*)d_in[4], (const __nv_bfloat16*)d_in[0], (const __nv_bfloat16*)d_in[1],
        (const __nv_bfloat16*)d_in[2], (const __nv_bfloat16*)d_in[3], (const __nv_bfloat16*)d_in[5],
        (const __nv_bfloat16*)d_in[6], (const __nv_bfloat16*)d_in[7], (const __nv_bfloat16*)d_in[8],
        (__nv_bfloat16*)d_out, gs, xmap);
}
```

```cpp
#include <cuda_runtime.h>
#include <cuda.h>
#include <cuda_bf16.h>
#include <stdint.h>

namespace {

constexpr int C = 128, HW = 64, NB = 2, E = 768;
constexpr int NCTA = NB * HW;
constexpr int NXTRA = 4;
constexpr int NTHREADS = 16 * 32;
constexpr int CH_PITCH = 66 * 16;
constexpr int ROW_BYTES = 16 * CH_PITCH;
constexpr int STAGE_BYTES = 12288;
constexpr int NSTAGE = 24;
constexpr int KC_BYTES = 2 * CH_PITCH;
constexpr int NS = 12;
constexpr int LAG = 1;
#define XDELAY 300
#define XSTAG 800
#define XSTAG2 300
#define SDELAY 600
#define W2DELAY 2400
#define PDELAY 60
constexpr int NLDG = 2;

constexpr uint32_t SMEM_BASE = 0x400;
constexpr uint32_t SM_XOWN = SMEM_BASE;
constexpr uint32_t SM_ACT = SM_XOWN + 16384 + 512;
constexpr uint32_t SM_XOUT = SM_ACT + 2 * ROW_BYTES + 512;
static_assert(SM_XOUT % 1024 == 0, "swizzle atom alignment");
constexpr uint32_t SM_W = SM_ACT + 3 * ROW_BYTES + 128;
__host__ __device__ constexpr uint32_t slot_addr(int slot) { return SM_W + slot * STAGE_BYTES; }
constexpr uint32_t SM_COEF = SM_W + NS * STAGE_BYTES;
constexpr uint32_t SM_GST = SM_COEF + 2048;
constexpr uint32_t SM_EMB = SM_GST + 128;
constexpr uint32_t SM_ONES = SM_EMB + 2048;
constexpr uint32_t SM_RED = SM_ONES + 256;
constexpr uint32_t SM_BNC = SM_RED + 1536;
constexpr uint32_t SM_BAR = SM_BNC + 2 * 2304;
constexpr int BAR_FULL = 0, BAR_WEMPTY = NSTAGE, BAR_HW = BAR_WEMPTY + NS, BAR_XFREE = BAR_HW + 1, BAR_STATS = BAR_XFREE + 1,
              BAR_EMB = BAR_STATS + 1, BAR_ACK = BAR_EMB + 1, BAR_X = BAR_ACK + 1  , NBAR = BAR_X + 5;
constexpr int SM_TOTAL = SM_BAR + NBAR * 8 - SMEM_BASE;
static_assert(SM_TOTAL <= 232448, "smem");
__host__ __device__ constexpr uint32_t BAR(int i) { return SM_BAR + 8 * i; }
__host__ __device__ constexpr int ky_of(int kyo) { return kyo == 0 ? 1 : (kyo == 1 ? 0 : 2); }

constexpr unsigned SPIN_LIMIT = 1u << 16;

constexpr int LS = 1056, KS = 32;
struct Scratch {
    float acc1[NB * LS];
    float acc2[NB * LS];
    unsigned wcnt[3 * NB * LS];
    unsigned w1cnt[NB * 8 * KS];
    float emb[NXTRA * NB * C];
    alignas(1024) unsigned char wt[2 * NSTAGE * STAGE_BYTES];
    uint4 box[NCTA * 1024];
};
__device__ __align__(1024) Scratch g_scratch;
#define TL(i) do {} while (0)
#define TLG(i) do {} while (0)

__device__ __forceinline__ unsigned clock32() { unsigned c; asm volatile("mov.u32 %0, %%clock;" : "=r"(c)); return c; }
__device__ __forceinline__ uint32_t mapa(uint32_t a, uint32_t rank) {
    uint32_t d;
    asm("mapa.shared::cluster.u32 %0, %1, %2;" : "=r"(d) : "r"(a), "r"(rank));
    return d;
}
#define S0 mapa(0, blockIdx.x & 1)
__device__ __forceinline__ void mbar_init(uint32_t bar, int cnt) {
    asm volatile("mbarrier.init.shared::cta.b64 [%0], %1;" ::"r"(bar + S0), "r"(cnt) : "memory");
}
__device__ __forceinline__ void mbar_arrive(uint32_t bar) {
    asm volatile("mbarrier.arrive.shared::cta.b64 _, [%0];" ::"r"(bar + S0) : "memory");
}
__device__ __forceinline__ void mbar_expect(uint32_t bar, uint32_t bytes) {
    asm volatile("mbarrier.arrive.expect_tx.shared::cta.b64 _, [%0], %1;" ::"r"(bar + S0), "r"(bytes) : "memory");
}
__device__ __forceinline__ bool mbar_try(uint32_t bar, uint32_t par) {
    uint32_t ok;
    asm volatile("{\n.reg .pred p;\nmbarrier.try_wait.parity.shared::cta.b64 p, [%1], %2;\nselp.u32 %0, 1, 0, p;\n}"
                 : "=r"(ok) : "r"(bar + S0), "r"(par) : "memory");
    return ok;
}
__device__ __forceinline__ bool mbar_test(uint32_t bar, uint32_t par) {
    uint32_t ok;
    asm volatile("{\n.reg .pred p;\nmbarrier.test_wait.parity.shared::cta.b64 p, [%1], %2;\nselp.u32 %0, 1, 0, p;\n}"
                 : "=r"(ok) : "r"(bar + S0), "r"(par) : "memory");
    return ok;
}
__device__ __forceinline__ void mbar_wait(uint32_t bar, uint32_t par) {
    unsigned it = 0;
#pragma unroll 1
    while (!mbar_try(bar, par) && ++it < SPIN_LIMIT) {}
}
__device__ __forceinline__ bool elect_one() {
    uint32_t p;
    asm volatile("{\n.reg .pred p;\nelect.sync _|p, 0xffffffff;\nselp.u32 %0, 1, 0, p;\n}" : "=r"(p));
    return p;
}
__device__ __forceinline__ void fence_async_smem() { asm volatile("fence.proxy.async.shared::cta;" ::: "memory"); }
__device__ __forceinline__ void fence_async_global() { asm volatile("fence.proxy.async.global;" ::: "memory"); }
__device__ __forceinline__ void fence_acquire() { asm volatile("fence.acquire.gpu;" ::: "memory"); }
__device__ __forceinline__ void bar_sync(int id, int n) { asm volatile("bar.sync %0, %1;" ::"r"(id), "r"(n) : "memory"); }
__device__ __forceinline__ void bar_arrive(int id, int n) { asm volatile("bar.arrive %0, %1;" ::"r"(id), "r"(n) : "memory"); }
__device__ __forceinline__ void bulk_g2s(uint32_t dst, const void* src, uint32_t bytes, uint32_t bar) {
    asm volatile("cp.async.bulk.shared::cluster.global.mbarrier::complete_tx::bytes [%0], [%1], %2, [%3];"
                 ::"r"(dst), "l"(src), "r"(bytes), "r"(bar) : "memory");
}
__device__ __forceinline__ void tma_x(uint32_t dst, const CUtensorMap* tm, int row, int ch, uint32_t bar) {
    asm volatile("cp.async.bulk.tensor.3d.shared::cluster.global.mbarrier::complete_tx::bytes [%0], [%1, {%2, %3, %4}], [%5];"
                 ::"r"(dst + S0), "l"(tm), "r"(0), "r"(row), "r"(ch), "r"(bar + S0) : "memory");
}
__device__ __forceinline__ uint4 ld_relaxed_v4(const void* p) {
    uint4 v;
    asm volatile("ld.relaxed.gpu.global.v4.u32 {%0,%1,%2,%3}, [%4];" : "=r"(v.x), "=r"(v.y), "=r"(v.z), "=r"(v.w) : "l"(p) : "memory");
    return v;
}
__device__ __forceinline__ unsigned ld_relaxed(const void* p) {
    unsigned v;
    asm volatile("ld.relaxed.gpu.global.u32 %0, [%1];" : "=r"(v) : "l"(p) : "memory");
    return v;
}
__device__ __forceinline__ void red_add4(float* p, float a, float b, float c, float d) {
    asm volatile("red.relaxed.gpu.global.add.v4.f32 [%0], {%1,%2,%3,%4};" ::"l"(p), "f"(a), "f"(b), "f"(c), "f"(d) : "memory");
}
__device__ __forceinline__ void sts128(uint32_t a, uint4 v) {
    asm volatile("st.shared.v4.u32 [%0], {%1,%2,%3,%4};" ::"r"(a + S0), "r"(v.x), "r"(v.y), "r"(v.z), "r"(v.w) : "memory");
}
__device__ __forceinline__ void sts128f(uint32_t a, float4 v) {
    asm volatile("st.shared.v4.f32 [%0], {%1,%2,%3,%4};" ::"r"(a + S0), "f"(v.x), "f"(v.y), "f"(v.z), "f"(v.w) : "memory");
}
__device__ __forceinline__ void sts32f(uint32_t a, float v) { asm volatile("st.shared.f32 [%0], %1;" ::"r"(a + S0), "f"(v) : "memory"); }
__device__ __forceinline__ uint4 lds128(uint32_t a) {
    uint4 v;
    asm volatile("ld.shared.v4.u32 {%0,%1,%2,%3}, [%4];" : "=r"(v.x), "=r"(v.y), "=r"(v.z), "=r"(v.w) : "r"(a + S0) : "memory");
    return v;
}
__device__ __forceinline__ float4 lds128f(uint32_t a) {
    float4 v;
    asm volatile("ld.shared.v4.f32 {%0,%1,%2,%3}, [%4];" : "=f"(v.x), "=f"(v.y), "=f"(v.z), "=f"(v.w) : "r"(a + S0) : "memory");
    return v;
}
__device__ __forceinline__ float2 lds64f(uint32_t a) {
    float2 v;
    asm volatile("ld.shared.v2.f32 {%0,%1}, [%2];" : "=f"(v.x), "=f"(v.y) : "r"(a + S0) : "memory");
    return v;
}
__device__ __forceinline__ float bf_lo(uint32_t u) { return __uint_as_float(u << 16); }
__device__ __forceinline__ float bf_hi(uint32_t u) { return __uint_as_float(u & 0xffff0000u); }
__device__ __forceinline__ uint32_t pack_bf(float lo, float hi) {
    uint32_t r;
    asm("cvt.rn.bf16x2.f32 %0, %1, %2;" : "=r"(r) : "f"(hi), "f"(lo));
    return r;
}
__device__ __forceinline__ float tanh_fast(float x) {
    float r;
    asm("tanh.approx.f32 %0, %1;" : "=f"(r) : "f"(x));
    return r;
}
__device__ __forceinline__ float silu_half(float h) { return fmaf(h, tanh_fast(h), h); }
__device__ __forceinline__ void ldsm4(uint32_t (&u)[4], uint32_t a) {
    asm volatile("ldmatrix.sync.aligned.m8n8.x4.shared.b16 {%0,%1,%2,%3}, [%4];"
                 : "=r"(u[0]), "=r"(u[1]), "=r"(u[2]), "=r"(u[3]) : "r"(a + S0) : "memory");
}
__device__ __forceinline__ void ldsm4t(uint32_t (&u)[4], uint32_t a) {
    asm volatile("ldmatrix.sync.aligned.m8n8.x4.trans.shared.b16 {%0,%1,%2,%3}, [%4];"
                 : "=r"(u[0]), "=r"(u[1]), "=r"(u[2]), "=r"(u[3]) : "r"(a + S0) : "memory");
}
__device__ __forceinline__ void stsm4(uint32_t a, uint32_t p0, uint32_t p1, uint32_t p2, uint32_t p3) {
    asm volatile("stmatrix.sync.aligned.m8n8.x4.shared.b16 [%0], {%1,%2,%3,%4};" ::"r"(a + S0), "r"(p0), "r"(p1), "r"(p2), "r"(p3) : "memory");
}
__device__ __forceinline__ void stsm4t(uint32_t a, uint32_t p0, uint32_t p1, uint32_t p2, uint32_t p3) {
    asm volatile("stmatrix.sync.aligned.m8n8.x4.trans.shared.b16 [%0], {%1,%2,%3,%4};" ::"r"(a + S0), "r"(p0), "r"(p1), "r"(p2), "r"(p3) : "memory");
}

#define R8(o) "+f"(d[o]), "+f"(d[o + 1]), "+f"(d[o + 2]), "+f"(d[o + 3]), "+f"(d[o + 4]), "+f"(d[o + 5]), "+f"(d[o + 6]), "+f"(d[o + 7])
template <uint32_t ALO, uint32_t BLO, uint64_t AHI = 8, uint64_t BHI = 48>
__device__ __forceinline__ void wgmma128(float (&d)[64]) {
    asm volatile(
        "wgmma.mma_async.sync.aligned.m64n128k16.f32.bf16.bf16 "
        "{%0,%1,%2,%3,%4,%5,%6,%7,%8,%9,%10,%11,%12,%13,%14,%15,%16,%17,%18,%19,%20,%21,%22,%23,%24,%25,%26,%27,%28,%29,%30,%31,"
        "%32,%33,%34,%35,%36,%37,%38,%39,%40,%41,%42,%43,%44,%45,%46,%47,%48,%49,%50,%51,%52,%53,%54,%55,%56,%57,%58,%59,%60,%61,%62,%63},"
        " %64, %65, 1, 1, 1, 0, 0;"
        : R8(0), R8(8), R8(16), R8(24), R8(32), R8(40), R8(48), R8(56)
        : "l"((AHI << 32) | ALO), "l"((BHI << 32) | BLO));
}
template <int S>
__device__ __forceinline__ void mma_stages(float (&d)[64], int conv, int tid, Scratch* gs) {
    constexpr uint32_t A = ((SM_ACT + S * 2 * CH_PITCH + 16) >> 4) | ((CH_PITCH >> 4) << 16);
    constexpr uint32_t B = (slot_addr(S % NS) >> 4) | (8u << 16);
    if (S == 0) mbar_wait(BAR(BAR_FULL), conv);
    bool next_ok = true;
    constexpr uint32_t NEXT = S + 1 < NSTAGE ? BAR(BAR_FULL + S + 1) : BAR(BAR_EMB);
    const int npar = S + 1 < NSTAGE ? conv : 0;
    next_ok = mbar_test(NEXT, npar);
    if (S == 0 && tid == 0) TL(32 + conv * 24);
    asm volatile("wgmma.fence.sync.aligned;" ::: "memory");
    wgmma128<A, B>(d);
    wgmma128<A + 1, B + 16>(d);
    wgmma128<A + 2, B + 32>(d);
    asm volatile("wgmma.commit_group.sync.aligned;" ::: "memory");
    if (S >= LAG) {
        asm volatile("wgmma.wait_group.sync.aligned %0;" ::"n"(LAG) : "memory");
        if ((tid & 31) == 0) mbar_arrive(BAR(BAR_WEMPTY + (S + NS - LAG) % NS));
    }
    if (!next_ok) mbar_wait(NEXT, npar);
    if constexpr (S + 1 < NSTAGE) mma_stages<S + 1>(d, conv, tid, gs);
}

__device__ __forceinline__ void weight_load(uint4 (&t)[5], const __nv_bfloat16* w, int cta, int lane) {
    const char* base = reinterpret_cast<const char*>(w) + (uint32_t)((((cta & 15) * 8 + (lane >> 2)) * 8 + (cta >> 4)) * 288 + (lane & 3) * 16);
#pragma unroll
    for (int k = 0; k < 5; k++)
        if (k < 4 || !(lane & 2)) t[k] = __ldg(reinterpret_cast<const uint4*>(base + k * 64));
}
__device__ __forceinline__ void weight_block(uint32_t bounce, unsigned char* wt, int cta, int lane, unsigned* cnt) {
    const unsigned opaque_one = gridDim.y;
    unsigned char* piece = wt + (cta >> 4) * STAGE_BYTES + (cta & 15) * 768;
    uint32_t v[18];
#pragma unroll
    for (int i = 0; i < 9; i++) {
        const float2 q = lds64f(bounce + (lane & 7) * 288 + (lane >> 3) * 72 + i * 8);
        v[2 * i] = __float_as_uint(q.x); v[2 * i + 1] = __float_as_uint(q.y);
    }
    unsigned char* dst = piece + (lane >> 4) * 128 + (lane & 7) * 16 + ((lane >> 3) & 1) * 8;
    unsigned rb[3];
#pragma unroll
    for (int kyo = 0; kyo < 3; kyo++) {
#pragma unroll
        for (int kx = 0; kx < 3; kx++) {
            const int tap = ky_of(kyo) * 3 + kx;
            uint32_t o[2];
#pragma unroll
            for (int m = 0; m < 2; m++) {
                const int i0 = 18 * m + tap, i1 = i0 + 9;
                o[m] = __byte_perm(v[i0 >> 1], v[i1 >> 1], ((i0 & 1) ? 0x32u : 0x10u) | ((i1 & 1) ? 0x7600u : 0x5400u));
            }
            asm volatile("st.global.v2.u32 [%0], {%1,%2};" ::"l"(dst + kyo * 8 * STAGE_BYTES + kx * 256), "r"(o[0]), "r"(o[1]) : "memory");
        }
        rb[kyo] = ld_relaxed(piece + kyo * 8 * STAGE_BYTES + (lane < 24 ? lane : 0) * 32);
    }
    const unsigned i0 = __any_sync(0xffffffffu, rb[0] == 0x9e3779b9u) ? opaque_one : 1u;
    if (lane < 2) asm volatile("red.relaxed.gpu.global.add.u32 [%0], %1;" ::"l"(cnt), "r"(i0) : "memory");
    const unsigned i1 = __any_sync(0xffffffffu, (rb[1] ^ rb[2]) == 0x9e3779b9u) ? opaque_one : 1u;
    if (lane < 2) asm volatile("red.relaxed.gpu.global.add.u32 [%0], %1;" ::"l"(cnt), "r"(i1 << 16) : "memory");
}
__device__ __forceinline__ uint32_t act2(uint32_t u, const float4& cf) {
    return pack_bf(silu_half(fmaf(bf_lo(u), cf.x, cf.z)), silu_half(fmaf(bf_hi(u), cf.y, cf.w)));
}
__device__ __forceinline__ void norm_unit(uint32_t (&u)[4], const float4& ca, const float4& cb) {
    u[0] = act2(u[0], ca); u[1] = act2(u[1], ca); u[2] = act2(u[2], cb); u[3] = act2(u[3], cb);
}
__device__ __forceinline__ void read_stats(uint32_t gst, float (&g)[8]) {
    asm volatile("ld.volatile.shared.v4.f32 {%0,%1,%2,%3}, [%4];" : "=f"(g[0]), "=f"(g[1]), "=f"(g[2]), "=f"(g[3]) : "r"(gst + S0) : "memory");
    asm volatile("ld.volatile.shared.v4.f32 {%0,%1,%2,%3}, [%4];" : "=f"(g[4]), "=f"(g[5]), "=f"(g[6]), "=f"(g[7]) : "r"(gst + 16 + S0) : "memory");
}
template <int T>
__device__ __forceinline__ void wait_stats(uint32_t gst, float (&g)[8]) {
    float rs, mr;
    unsigned it = 0;
#pragma unroll 1
    do {
        asm volatile("ld.volatile.shared.v2.f32 {%0,%1}, [%2];" : "=f"(rs), "=f"(mr) : "r"(gst + 8 * T + S0) : "memory");
    } while (!__all_sync(0xffffffffu, rs != 0.f) && ++it < 8 * SPIN_LIMIT);
    if (T < 3) read_stats(gst, g);
    g[2 * T] = rs; g[2 * T + 1] = mr;
}
template <int T>
__device__ __forceinline__ void own_unit(uint32_t (&o)[4], const float (&z)[8], float4 (&cf)[8], const float (&g)[8]) {
    float4 &ca = cf[2 * T], &cb = cf[2 * T + 1];
    const float rs = g[2 * T], mr = g[2 * T + 1];
    ca.z = fmaf(-mr, ca.x, ca.z); ca.w = fmaf(-mr, ca.y, ca.w);
    cb.z = fmaf(-mr, cb.x, cb.z); cb.w = fmaf(-mr, cb.y, cb.w);
#pragma unroll
    for (int i = 0; i < 4; i++)
        o[i] = pack_bf(silu_half(fmaf(z[2 * i], rs, i < 2 ? ca.z : cb.z)), silu_half(fmaf(z[2 * i + 1], rs, i < 2 ? ca.w : cb.w)));
}
template <int FIRST, int N>
__device__ __forceinline__ void norm_block(uint32_t (&u)[4][4], float4 (&cf)[8], uint32_t act, uint32_t mask, uint32_t fbar, int lane) {
#pragma unroll
    for (int t = FIRST; t < FIRST + N; t++) {
        norm_unit(u[t], cf[2 * t], cf[2 * t + 1]);
        stsm4(act + t * 2 * KC_BYTES, u[t][0] & mask, u[t][1] & mask, u[t][2] & mask, u[t][3] & mask);
    }
    fence_async_smem();
    __syncwarp();
    if (lane < N) mbar_arrive(fbar + 16 * (FIRST + lane));
}
__device__ __forceinline__ void publish(uint32_t bar, int lane) {
    fence_async_smem();
    __syncwarp();
    if (lane == 0) mbar_arrive(bar);
}
template <int T>
__device__ __forceinline__ void next_unit(const float (&z)[8], float4 (&cf)[8], uint32_t gst, float (&g)[8], uint32_t act, uint32_t fbar, int lane) {
    const bool have = __all_sync(0xffffffffu, g[2 * T] != 0.f);
    if (!have) { publish(fbar + 16 * (T - 1), lane); wait_stats<T>(gst, g); }
    uint32_t o[4];
    own_unit<T>(o, z, cf, g);
    if (have) publish(fbar + 16 * (T - 1), lane);
    stsm4(act + T * 2 * KC_BYTES, o[0], o[1], o[2], o[3]);
}
__device__ __forceinline__ void stat_mma(float (&c)[4], uint32_t p, uint32_t q) {
    asm("mma.sync.aligned.m16n8k16.row.col.f32.bf16.bf16.f32 {%0,%1,%2,%3}, {%4,%5,%6,%5}, {%4,%6}, {%0,%1,%2,%3};"
        : "+f"(c[0]), "+f"(c[1]), "+f"(c[2]), "+f"(c[3]) : "r"(p), "r"(0x3f803f80u), "r"(q));
}
__device__ __forceinline__ void stat_store(const float (&c)[4], uint32_t dst, int lane) {
    const int g = lane >> 2, t = lane & 3;
    if (t == (g >> 1)) sts32f(dst + g * 4, (g & 1) ? c[1] : c[0]);
    if (g == 7) sts32f(dst + 32 + t * 4, c[2] + c[3]);
}
__device__ __forceinline__ float sum4(float4 v) { return (v.x + v.y) + (v.z + v.w); }
__device__ __forceinline__ void stat_publish(uint32_t src, float* acc, int lane, bool real) {
    const uint32_t a = src + (lane & 15) * 48;
    float q = sum4(lds128f(a)) + sum4(lds128f(a + 16)), sm = sum4(lds128f(a + 32));
    q += __shfl_xor_sync(0xffffffffu, q, 1); sm += __shfl_xor_sync(0xffffffffu, sm, 1);
    q += __shfl_xor_sync(0xffffffffu, q, 2); sm += __shfl_xor_sync(0xffffffffu, sm, 2);
    if (real && (lane & 19) == 0) red_add4(acc + lane, 1.f, sm, q, 1.f);
}
__device__ __forceinline__ void fence_acc(float (&d)[64]) {
#pragma unroll
    for (int i = 0; i < 64; i++) asm volatile("" : "+f"(d[i])::"memory");
}
__device__ __forceinline__ void ld_unit(uint32_t (&u)[4], const uint4* p) {
    asm volatile("ld.relaxed.gpu.global.v4.u32 {%0,%1,%2,%3}, [%4];" : "=r"(u[0]), "=r"(u[1]), "=r"(u[2]), "=r"(u[3]) : "l"(p) : "memory");
}

__device__ __noinline__ void side_jobs(const __nv_bfloat16* __restrict__ t_emb, const __nv_bfloat16* __restrict__ w_emb,
                                       const __nv_bfloat16* __restrict__ w2, Scratch* __restrict__ gs, unsigned clk0) {
    const int tid = threadIdx.x, warp = tid >> 5, lane = tid & 31, j = blockIdx.x;
    float tv = 0.f;
    if (lane < 24) tv = __bfloat162float(t_emb[(lane / 12) * E + j * 192 + warp * 12 + lane % 12]);
    if (tid == 0) {
        mbar_init(BAR(0), 1);
        mbar_expect(BAR(0), 192 * C * 2);
        fence_async_smem();
        while (clock32() - clk0 < SDELAY) {}
#pragma unroll
        for (int i = 0; i < 4; i++)
            asm volatile("cp.async.bulk.prefetch.L2.global [%0], 18432;" ::"l"(reinterpret_cast<const char*>(w2) + (j * 4 + i) * 18432) : "memory");
#pragma unroll
        for (int i = 0; i < 4; i++) bulk_g2s(S0 + SM_W + i * 12288, w_emb + (j * 192 + i * 48) * C, 12288, S0 + BAR(0));
    }
    if (j == 0 && tid < 32) gs->acc2[(tid >> 4) * LS + (tid & 15)] = 0.f;
    const float sv = silu_half(0.5f * tv);
    __syncthreads();
    mbar_wait(BAR(0), 0);
    float acc[8] = {0.f, 0.f, 0.f, 0.f, 0.f, 0.f, 0.f, 0.f};
#pragma unroll
    for (int i = 0; i < 12; i++) {
        const float2 wq = lds64f(SM_W + (warp * 12 + i) * 256 + lane * 8);
        const uint32_t wx = __float_as_uint(wq.x), wy = __float_as_uint(wq.y);
#pragma unroll
        for (int bb = 0; bb < 2; bb++) {
            const float sx = __shfl_sync(0xffffffffu, sv, bb * 12 + i);
            acc[4 * bb + 0] = fmaf(sx, bf_lo(wx), acc[4 * bb + 0]); acc[4 * bb + 1] = fmaf(sx, bf_hi(wx), acc[4 * bb + 1]);
            acc[4 * bb + 2] = fmaf(sx, bf_lo(wy), acc[4 * bb + 2]); acc[4 * bb + 3] = fmaf(sx, bf_hi(wy), acc[4 * bb + 3]);
        }
    }
    sts128f(SM_ACT + warp * 1024 + lane * 16, make_float4(acc[0], acc[1], acc[2], acc[3]));
    sts128f(SM_ACT + warp * 1024 + 512 + lane * 16, make_float4(acc[4], acc[5], acc[6], acc[7]));
    __syncthreads();
    if (tid < 128) {
        float2 sum = make_float2(0.f, 0.f);
#pragma unroll
        for (int w = 0; w < 16; w++) { const float2 p = lds64f(SM_ACT + w * 1024 + tid * 8); sum.x += p.x; sum.y += p.y; }
        *reinterpret_cast<float2*>(&gs->emb[j * NB * C + tid * 2]) = sum;
        bar_sync(1, 128);
        if (tid < 2) asm volatile("red.release.gpu.global.add.u32 [%0], 1;" ::"l"(&gs->wcnt[(2 * NB + tid) * LS]) : "memory");
    }
}

__global__ void __cluster_dims__(2, 1, 1) __launch_bounds__(NTHREADS, 1)
resblock_kernel(const __nv_bfloat16* __restrict__ w1, const __nv_bfloat16* __restrict__ x,
                const __nv_bfloat16* __restrict__ t_emb, const __nv_bfloat16* __restrict__ g1,
                const __nv_bfloat16* __restrict__ be1, const __nv_bfloat16* __restrict__ w_emb,
                const __nv_bfloat16* __restrict__ g2, const __nv_bfloat16* __restrict__ be2,
                const __nv_bfloat16* __restrict__ w2, __nv_bfloat16* __restrict__ out, Scratch* __restrict__ gs,
                const __grid_constant__ CUtensorMap xmap) {
    const unsigned clk0 = clock32();
    if (threadIdx.x == 480 && blockIdx.x >= NXTRA) TLG(1);
    const int tid = threadIdx.x, lane = tid & 31;
    const int cta = blockIdx.x - NXTRA, b = cta >> 6, r = cta & 63;
    uint4 v[5];
    if (tid < 32) weight_load(v, w1, cta & (NCTA - 1), lane);
    if (tid >= 192 && tid < 192 + 72) {
        const int c2 = (cta + 64) & (NCTA - 1), t = tid - 192;
        asm volatile("prefetch.global.L2 [%0];" ::"l"(reinterpret_cast<const char*>(w1) + (uint32_t)((((c2 & 15) * 8 + (t & 7)) * 8 + (c2 >> 4)) * 288 + (t >> 3) * 32)));
    }
    uint4 xv[8];
    const int wg4 = (tid >> 5) - 1;
    const bool early = tid >= 32 && wg4 < NLDG;
    if (early) {
        const char* src = reinterpret_cast<const char*>(x) + (uint32_t)((((b & 1) * C + wg4 * 32 + (lane >> 3)) * HW + r) * HW * 2 + (lane & 7) * 16);
        while (clock32() - clk0 < XDELAY + (wg4 >> 1) * XSTAG + (wg4 & 1) * XSTAG2) {}
#pragma unroll
        for (int i = 0; i < 8; i++) xv[i] = __ldg(reinterpret_cast<const uint4*>(src + i * (4 * HW * HW * 2)));
    }
    const int warp = __shfl_sync(0xffffffffu, tid >> 5, 0);
    if (cta < 0) { side_jobs(t_emb, w_emb, w2, gs, clk0); return; }

    if (warp != 4) asm volatile("barrier.cluster.arrive.relaxed.aligned;" ::: "memory");
    const bool has_outer = (r != 0) && (r != HW - 1);
    if (warp == 1 || warp == 2 || warp == 3 || warp == 5) {
        const int g = warp < 4 ? warp - 1 : 3;
        if (elect_one()) {
            if (g >= NLDG) asm volatile("prefetch.tensormap [%0];" ::"l"(&xmap) : "memory");
            mbar_init(BAR(BAR_X) + 8 * g, 1);
            if (g >= NLDG) { mbar_expect(BAR(BAR_X) + 8 * g, 4096); fence_async_smem(); }
        }
        __syncwarp();
        bar_arrive(4, 256 + 32 + 128);
        if (g >= NLDG) {
            while (clock32() - clk0 < XDELAY + (g >> 1) * XSTAG + (g & 1) * XSTAG2) {}
            if (elect_one()) tma_x(SM_XOWN + g * 4096, &xmap, r, b * C + g * 32, BAR(BAR_X) + 8 * g);
            __syncwarp();
            mbar_wait(BAR(BAR_X) + 8 * g, 0);
#pragma unroll
            for (int k = 0; k < 8; k++) xv[k] = lds128(SM_XOWN + g * 4096 + k * 512 + lane * 16);
        }
        float c[8][4];
#pragma unroll
        for (int k = 0; k < 8; k++) {
            c[k][0] = c[k][1] = c[k][2] = c[k][3] = 0.f;
            stat_mma(c[k], xv[k].x, xv[k].y); stat_mma(c[k], xv[k].z, xv[k].w);
        }
#pragma unroll
        for (int i = 0; i < 4; i++) c[0][i] = ((c[0][i] + c[1][i]) + (c[2][i] + c[3][i])) + ((c[4][i] + c[5][i]) + (c[6][i] + c[7][i]));
        stat_store(c[0], SM_RED + g * 48, lane);
        __syncwarp();
        if (lane == 0) {
            const uint32_t a = SM_RED + g * 48;
            red_add4(&gs->acc1[b * LS + g * 4], 1.f, sum4(lds128f(a + 32)), sum4(lds128f(a)) + sum4(lds128f(a + 16)), 1.f);
            TL(74 + g);
        }
        if (g < NLDG) {
#pragma unroll
            for (int i = 0; i < 8; i++)
                sts128(SM_XOWN + g * 4096 + i * 512 + (lane >> 3) * 128 + (((lane & 7) ^ ((lane >> 3) + 4 * (i & 1))) << 4), xv[i]);
            __syncwarp();
            if (lane == 0) mbar_arrive(BAR(BAR_X) + 8 * g);
        }
    }
    if (warp == 4) {
            if (elect_one()) {
#pragma unroll
                for (int i = 0; i < NSTAGE; i++) mbar_init(BAR(BAR_FULL + i), (i >> 3) == 1 ? 1 : 5);
#pragma unroll
                for (int i = 0; i < NS + 2; i++) mbar_init(BAR(BAR_WEMPTY + i), 4);
#pragma unroll
                for (int i = BAR_STATS; i < BAR_X; i++) mbar_init(BAR(i), i == BAR_EMB ? 3 : 1);
                mbar_init(BAR(BAR_X + 4), 1);
                asm volatile("fence.mbarrier_init.release.cluster;" ::: "memory");
            }
            if (lane < 4) sts128(SM_GST + lane * 16, make_uint4(0, 0, 0, 0));
            __syncwarp();
            fence_async_smem();
            bar_arrive(0, 96);
            bar_arrive(5, 64);
            bar_arrive(4, 256 + 32 + 128);
            const uint4 z = make_uint4(0, 0, 0, 0);
#pragma unroll
            for (int i = 0; i < 2; i++) sts128(SM_ACT + (i * 16 + (lane >> 1)) * CH_PITCH + (lane & 1) * 16, z);
            if (lane < 4) sts128(SM_ACT + (2 + (lane >> 1)) * ROW_BYTES + (lane & 1) * 16, z);
            if (lane < 16) sts128(SM_ONES + lane * 16, make_uint4(lane < 8 ? 0x3f803f80u : 0u, 0, 0, 0));
            fence_async_smem();
            bar_arrive(7, 160);
            asm volatile("barrier.cluster.arrive.relaxed.aligned;" ::: "memory");
            while (clock32() - clk0 < W2DELAY) {}
            weight_load(v, w2, cta, lane);
        }
    if (warp == 0 || warp == 4) {
        const int k = warp >> 2;
#pragma unroll
        for (int i = 0; i < 5; i++)
            if (i < 4 || !(lane & 2)) sts128(SM_BNC + k * 2304 + (lane >> 2) * 288 + (lane & 3) * 16 + i * 64, v[i]);
        if (lane == 0) TL(k ? 14 : 81);
        __syncwarp();
        weight_block(SM_BNC + k * 2304, gs->wt + k * NSTAGE * STAGE_BYTES, cta, lane,
                     k ? &gs->wcnt[(NB + (lane & 1)) * LS] : &gs->w1cnt[((lane & 1) * 8 + (cta >> 4)) * KS]);
        if (lane == 0) TL(k ? 13 : 4);
    }

    if (warp >= 8) {
        const int nw = warp - 8;
        if (nw < 2) {
            const uint2 ga = __ldg(reinterpret_cast<const uint2*>(nw ? g2 : g1) + lane), bt = __ldg(reinterpret_cast<const uint2*>(nw ? be2 : be1) + lane);
            sts128f(SM_COEF + nw * 1024 + lane * 32, make_float4(0.5f * bf_lo(ga.x), 0.5f * bf_hi(ga.x), 0.5f * bf_lo(bt.x), 0.5f * bf_hi(bt.x)));
            sts128f(SM_COEF + nw * 1024 + lane * 32 + 16, make_float4(0.5f * bf_lo(ga.y), 0.5f * bf_hi(ga.y), 0.5f * bf_lo(bt.y), 0.5f * bf_hi(bt.y)));
        }
        bar_sync(4, 256 + 32 + 128);
        const int par = nw >> 2, wq = nw & 3;
        const uint32_t act_off = SM_ACT + (par * 2 + (lane >> 4)) * CH_PITCH + (2 + wq * 16 + (lane & 15)) * 16;
        const uint32_t stg_off = (par * 16 + (lane >> 4) * 8 + (lane & 7)) * 128 + (((2 * wq + ((lane >> 3) & 1)) ^ (lane & 7)) << 4);
        const uint32_t cfa = SM_COEF + par * 128 + (lane & 3) * 16;
        const uint32_t fbar = BAR(BAR_FULL) + 8 * par;
        uint4* inbox = gs->box + cta * 1024 + nw * 32 + lane;
#pragma unroll 1
        for (int conv = 0; conv < 2; conv++) {
            uint32_t u[4][4], w[4][4];
            float4 cf[8];
            if (conv == 0) {
#pragma unroll
                for (int i = 0; i < 4; i++) { mbar_wait(BAR(BAR_X + i), 0); ldsm4t(u[i], SM_XOWN + stg_off + i * 4096); }
            } else {
                mbar_wait(BAR(BAR_HW), 0);
#pragma unroll
                for (int i = 0; i < 4; i++) ldsm4(u[i], act_off + i * 2 * KC_BYTES);
            }
#pragma unroll
            for (int i = 0; i < 8; i++) cf[i] = lds128f(cfa + conv * 1024 + (i >> 1) * 256 + (i & 1) * 64);
            const uint32_t gst = SM_GST + conv * 32;
            float gv[8], z[4][8];
#pragma unroll
            for (int i = 0; i < 16; i++) {
                const float4& c = cf[i >> 1];
                z[i >> 2][2 * (i & 3)] = bf_lo(u[i >> 2][i & 3]) * c.x; z[i >> 2][2 * (i & 3) + 1] = bf_hi(u[i >> 2][i & 3]) * c.y;
                asm volatile("" : "+f"(z[i >> 2][2 * (i & 3)]), "+f"(z[i >> 2][2 * (i & 3) + 1]));
            }
            wait_stats<0>(gst, gv);
            if (tid == 256) TL(22 + conv * 4);
            if (par) { const unsigned c1 = clock32(); while (clock32() - c1 < PDELAY) {} }
            uint32_t o[4];
            own_unit<0>(o, z[0], cf, gv);
            stsm4(act_off, o[0], o[1], o[2], o[3]);
            publish(fbar, lane);
            if (tid == 256) TL(8 + conv * 8);
            if (!__all_sync(0xffffffffu, gv[2] != 0.f)) wait_stats<1>(gst, gv);
            own_unit<1>(o, z[1], cf, gv);
            stsm4(act_off + 2 * KC_BYTES, o[0], o[1], o[2], o[3]);
            next_unit<2>(z[2], cf, gst, gv, act_off, fbar, lane);
            next_unit<3>(z[3], cf, gst, gv, act_off, fbar, lane);
            publish(fbar + 48, lane);
#pragma unroll
            for (int i = 0; i < 8; i++) { cf[i].x *= gv[i & ~1]; cf[i].y *= gv[i & ~1]; }
            if (tid == 256) TL(84 + conv);
            if (has_outer) {
                mbar_wait(BAR(BAR_X + 4), conv);
                if (conv == 0) {
#pragma unroll
                    for (int i = 0; i < 4; i++) ldsm4t(w[i], SM_XOUT + stg_off + i * 4096);
                } else {
#pragma unroll
                    for (int i = 0; i < 4; i++) {
                        const uint4 q = lds128(SM_XOWN + (tid - 256) * 16 + i * 4096);
                        w[i][0] = q.x; w[i][1] = q.y; w[i][2] = q.z; w[i][3] = q.w;
                    }
                    unsigned it = 0;
                    while (true) {
                        bool ok = true;
#pragma unroll
                        for (int i = 0; i < 16; i++) ok = ok && w[i >> 2][i & 3] != 0;
                        if (__all_sync(0xffffffffu, ok) || ++it > SPIN_LIMIT) break;
#pragma unroll
                        for (int i = 0; i < 4; i++) ld_unit(w[i], inbox + i * 256);
                    }
#pragma unroll
                    for (int i = 0; i < 16; i++) w[i >> 2][i & 3] = ~w[i >> 2][i & 3];
                }
            }
            if (conv == 0) {
                bar_sync(3, 256);
                if (nw == 0) sts128(SM_ACT + 2 * ROW_BYTES + (lane >> 1) * CH_PITCH + (lane & 1) * 16, make_uint4(0, 0, 0, 0));
            }
            if (tid == 256) TL(24 + conv * 4);
            norm_block<0, 2>(w, cf, act_off + 2 * ROW_BYTES, has_outer ? ~0u : 0u, fbar + 128, lane);
            if (tid == 256) TL(88 + conv);
            norm_block<2, 2>(w, cf, act_off + 2 * ROW_BYTES, has_outer ? ~0u : 0u, fbar + 128, lane);
            if (tid == 256) TL(23 + conv * 4);
        }
        if (has_outer) {
            mbar_wait(BAR(BAR_FULL + NSTAGE - 1), 1);
#pragma unroll
            for (int i = 0; i < 4; i++) inbox[i * 256] = make_uint4(0, 0, 0, 0);
        }
        {
            const int oc0 = par * 64 + ((tid & 127) >> 3), seg = lane & 7;
            __nv_bfloat16* dst = out + ((size_t)(b * C + oc0) * HW + r) * HW + seg * 8;
            const uint32_t src = SM_XOWN + oc0 * 128 + ((seg ^ (oc0 & 7)) << 4);
            asm volatile("{\n.reg .pred p;\nsetp.eq.u64 p, %0, 0;\n@p st.shared.u32 [%1], 0;\n}" ::"l"(dst), "r"(src + S0) : "memory");
            bar_sync(par ? 1 : 6, 128 + 128);
#pragma unroll
            for (int i = 0; i < 4; i++) *reinterpret_cast<uint4*>(dst + (size_t)i * 16 * HW * HW) = lds128(src + i * 2048);
            if (tid == 384) { TL(20); TLG(21); }
        }
    } else if (warp < 4) {
        const int wq = warp;
        bar_sync(7, 160);

        const uint32_t xbase = SM_XOWN + ((lane >> 4) * 8 + (lane & 7)) * 128 + (((2 * wq + ((lane >> 3) & 1)) ^ (lane & 7)) << 4);
        float d[64];
#pragma unroll
        for (int i = 0; i < 64; i++) d[i] = 0.f;
#pragma unroll 1
        for (int conv = 0; conv < 2; conv++) {
            fence_acc(d);
            mma_stages<0>(d, conv, tid, gs);
            if (conv == 0) {
                asm volatile("wgmma.fence.sync.aligned;" ::: "memory");
                wgmma128<(SM_ONES >> 4) | (8u << 16), (SM_EMB >> 4), 0, 8>(d);
                asm volatile("wgmma.commit_group.sync.aligned;" ::: "memory");
            }
            asm volatile("wgmma.wait_group.sync.aligned 0;" ::: "memory");
            fence_acc(d);
            if (tid == 0) TL(10 + conv * 8);
            if (conv == 1) {
                fence_acc(d);
#pragma unroll
                for (int kc = 0; kc < 8; kc++) {
                    stsm4t(xbase + kc * 2048, pack_bf(d[8 * kc], d[8 * kc + 1]), pack_bf(d[8 * kc + 2], d[8 * kc + 3]),
                           pack_bf(d[8 * kc + 4], d[8 * kc + 5]), pack_bf(d[8 * kc + 6], d[8 * kc + 7]));
                    if (kc == 3) bar_arrive(6, 128 + 128);
                }
                bar_arrive(1, 128 + 128);
                if (tid == 0) TL(5);
                break;
            }
            uint32_t hp[32];
#pragma unroll
            for (int i = 0; i < 32; i++) hp[i] = pack_bf(d[2 * i], d[2 * i + 1]);
#pragma unroll
            for (int g = 0; g < 4; g++) {
                float c[4] = {0.f, 0.f, 0.f, 0.f};
#pragma unroll
                for (int i = 0; i < 4; i++) stat_mma(c, hp[8 * g + 2 * i], hp[8 * g + 2 * i + 1]);
                stat_store(c, SM_RED + (g * 4 + wq) * 48, lane);
            }
            bar_sync(2, 128);
            if (wq == 0) stat_publish(SM_RED, &gs->acc2[b * LS], lane, true);
            if (tid == 0) TL(11);
            const uint32_t hbase = SM_ACT + (lane >> 4) * CH_PITCH + (2 + wq * 16 + (lane & 15)) * 16;
#pragma unroll
            for (int kc = 0; kc < 8; kc++) stsm4(hbase + kc * 2 * CH_PITCH, hp[4 * kc], hp[4 * kc + 1], hp[4 * kc + 2], hp[4 * kc + 3]);
            __syncwarp();
            if (lane == 0) mbar_arrive(BAR(BAR_HW));
            if (lane < LAG) mbar_arrive(BAR(BAR_WEMPTY + (NSTAGE - LAG) % NS) + 8 * lane);
            if (has_outer) {
                uint4* outbox = gs->box + (cta + ((r & 1) ? 1 : -1)) * 1024 + tid;
#pragma unroll
                for (int kc = 0; kc < 8; kc++) outbox[kc * 128] = make_uint4(~hp[4 * kc], ~hp[4 * kc + 1], ~hp[4 * kc + 2], ~hp[4 * kc + 3]);
            }
            if (tid == 0) TL(12);
#pragma unroll
            for (int kc = 0; kc < 8; kc++) {
                uint32_t p[4];
                ldsm4t(p, xbase + kc * 2048);
#pragma unroll
                for (int i = 0; i < 4; i++) { d[8 * kc + 2 * i] = bf_lo(p[i]); d[8 * kc + 2 * i + 1] = bf_hi(p[i]); }
            }
            fence_async_smem();
            __syncwarp();
            if (lane == 0) mbar_arrive(BAR(BAR_XFREE));
        }
        {
        }
    } else if (warp < 6) {
        if (warp == 5) {
            bar_sync(5, 64);
            mbar_wait(BAR(BAR_FULL), 0);
            if (has_outer && elect_one()) {
                mbar_expect(BAR(BAR_X + 4), 16384);
#pragma unroll
                for (int i = 0; i < 4; i++) tma_x(SM_XOUT + i * 4096, &xmap, r + ((r & 1) ? 1 : -1), b * C + i * 32, BAR(BAR_X + 4));
            }
            __syncwarp();
            asm volatile("barrier.cluster.wait.acquire.aligned;" ::: "memory");
            const uint32_t peer = (r & 1) ^ 1;
            const uint32_t self0 = mapa(0, r & 1), peer0 = mapa(0, peer);
#pragma unroll 1
            for (int conv = 0; conv < 2; conv++) {
#pragma unroll 1
                for (int kc = 0; kc < 8; kc++) {
                    mbar_wait(BAR(BAR_FULL) + 8 * kc, conv);
                    if (elect_one())
                        asm volatile("cp.async.bulk.shared::cluster.shared::cta.mbarrier::complete_tx::bytes [%0], [%1], %2, [%3];"
                                     ::"r"(peer0 + SM_ACT + ROW_BYTES + kc * KC_BYTES), "r"(self0 + SM_ACT + kc * KC_BYTES), "r"(KC_BYTES),
                                       "r"(peer0 + BAR(BAR_FULL + 8) + 8 * kc) : "memory");
                }
                if (lane == 0) TL(86 + conv);
#pragma unroll 1
                for (int kc = 0; kc < 8; kc++) mbar_wait(BAR(BAR_FULL + 8) + 8 * kc, conv);
                if (lane == 0)
                    asm volatile("mbarrier.arrive.relaxed.cluster.shared::cluster.b64 _, [%0];" ::"r"(peer0 + (conv ? BAR(BAR_ACK) : BAR(BAR_EMB))) : "memory");
            }
            mbar_wait(BAR(BAR_ACK), 0);
        } else {
            mbar_wait(BAR(BAR_STATS), 0);
            unsigned it = 0;
            while (!__all_sync(0xffffffffu, ld_relaxed(&gs->wcnt[(2 * NB + b) * LS]) >= (unsigned)NXTRA) && ++it < SPIN_LIMIT) __nanosleep(100);
            fence_acquire();
            float ev[4] = {0.f, 0.f, 0.f, 0.f};
#pragma unroll
            for (int j = 0; j < NXTRA; j++) {
                const uint4 ef = ld_relaxed_v4(&gs->emb[(j * NB + b) * C + lane * 4]);
                ev[0] += __uint_as_float(ef.x); ev[1] += __uint_as_float(ef.y); ev[2] += __uint_as_float(ef.z); ev[3] += __uint_as_float(ef.w);
            }
#pragma unroll
            for (int i = 0; i < 4; i++) {
                const float hi = bf_lo(pack_bf(ev[i], 0.f));
                sts128(SM_EMB + (lane * 4 + i) * 16, make_uint4(pack_bf(hi, ev[i] - hi), 0, 0, 0));
            }
            fence_async_smem();
            __syncwarp();
            if (lane == 0) { mbar_arrive(BAR(BAR_EMB)); TL(19); }
        }
    } else if (warp == 6) {
        bar_sync(0, 96);
        const uint32_t ebytes = STAGE_BYTES + ((lane >> 3) == 1 ? KC_BYTES : 0);
        if (lane < NSTAGE) mbar_expect(BAR(BAR_FULL) + 8 * lane, ebytes);
        const int swap = (r & 1) ? 0 : 8 * STAGE_BYTES;
        unsigned it = 0;
        {
            int g = 0;
            const unsigned* cnt = &gs->w1cnt[(b * 8 + (lane & 7)) * KS];
            unsigned cv = ld_relaxed(cnt);
#pragma unroll 1
            while (g < NS) {
                unsigned ready = __ballot_sync(0xffffffffu, (lane < 8 ? cv & 0xffffu : cv >> 16) >= 16u);
                if ((ready >> 8 & 0xff) != 0xff) ready &= 0xff;
                if (ready != ~0u) cv = ld_relaxed(cnt);
                ready >>= g;
                if (++it > SPIN_LIMIT) ready = ~0u;
                if (!(ready & 1)) continue;
                fence_async_global();
                if (lane == 0) TL(g ? 3 : 6);
#pragma unroll 1
                for (; (ready & 1) && g < NS; g++, ready >>= 1)
                    if (elect_one())
                        bulk_g2s(S0 + SM_W + g * STAGE_BYTES, gs->wt + g * STAGE_BYTES + (g >= 8 ? swap : 0), STAGE_BYTES, S0 + BAR(BAR_FULL) + 8 * g);
            }
        }
#pragma unroll 1
        for (int q = 3; q < 12; q++) {
            const int conv = q >= 6, qs = conv ? q - 6 : q, sl = q % 3;
            const unsigned char* wsrc = gs->wt + q * 4 * STAGE_BYTES + (qs < 2 ? 0 : (qs < 4 ? swap : -swap));
            const uint32_t par = (q / 3 - 1) & 1;
            if (q == 6) {
                it = 0;
                while (!__all_sync(0xffffffffu, ld_relaxed(&gs->wcnt[(NB + b) * LS]) == NCTA * 0x10001u) && ++it < SPIN_LIMIT) {}
                fence_acquire();
                fence_async_global();
                if (lane == 0) { mbar_arrive(BAR(BAR_EMB)); TL(2); }
            }
#pragma unroll
            for (int i = 0; i < 4; i++) {
                mbar_wait(BAR(BAR_WEMPTY + i) + 32 * sl, par);
                if (i == 0 && (q == 6 || q == 9)) {
                    if ((lane >= NS) == (q == 9) && lane < NSTAGE) mbar_expect(BAR(BAR_FULL) + 8 * lane, ebytes);
                    __syncwarp();
                }
                if (elect_one())
                    bulk_g2s(S0 + SM_W + (sl * 4 + i) * STAGE_BYTES, wsrc + i * STAGE_BYTES, STAGE_BYTES, S0 + BAR(BAR_FULL + i) + 32 * qs);
            }
        }
    } else {
        bar_sync(0, 96);
#pragma unroll 1
        for (int conv = 0; conv < 2; conv++) {
            if (conv == 1) mbar_wait(BAR(BAR_HW), 0);
            const float* asrc = (conv ? gs->acc2 : gs->acc1) + b * LS + (lane & 3) * 4;
            unsigned it = 0;
#pragma unroll 1
            while (true) {
                const uint4 f = ld_relaxed_v4(asrc);
                const bool ok = ((f.x == 0x42800000u) & (f.w == 0x42800000u)) || ++it > SPIN_LIMIT;
                if (ok && lane < 4) {
                    const float inv_n = 1.0f / (32.0f * HW * HW);
                    const float mean = __uint_as_float(f.y) * inv_n;
                    float rs;
                    asm("rsqrt.approx.ftz.f32 %0, %1;" : "=f"(rs) : "f"(fmaxf(fmaf(-mean, mean, __uint_as_float(f.z) * inv_n), 0.f) + 1e-5f));
                    asm volatile("st.shared.v2.f32 [%0], {%1,%2};" ::"r"(S0 + SM_GST + conv * 32 + lane * 8), "f"(rs == 0.f ? 1.2e-38f : rs), "f"(mean * rs) : "memory");
                }
                if (__all_sync(0xffffffffu, ok)) break;
            }
            if (lane == 0) { mbar_arrive(BAR(BAR_STATS)); TL(7 + conv * 8); }
        }
        mbar_wait(BAR(BAR_XFREE), 0);
        if (has_outer && elect_one()) {
            mbar_expect(BAR(BAR_X + 4), 16384);
            bulk_g2s(S0 + SM_XOWN, gs->box + cta * 1024, 16384, S0 + BAR(BAR_X + 4));
        }
        if (r == 0) {
            if (lane < 16) gs->acc1[b * LS + lane] = 0.f;
            if (lane < 3) gs->wcnt[(lane * NB + b) * LS] = 0;
            if (lane < 8) gs->w1cnt[(b * 8 + lane) * KS] = 0;
        }
    }
}

}

extern "C" void kernel_launch(void* const* d_in, const int* in_sizes, int n_in, void* d_out, int out_size) {
    (void)in_sizes; (void)n_in; (void)out_size;
    typedef CUresult (*EncodeFn)(CUtensorMap*, CUtensorMapDataType, cuuint32_t, void*, const cuuint64_t*, const cuuint64_t*,
                                 const cuuint32_t*, const cuuint32_t*, CUtensorMapInterleave, CUtensorMapSwizzle,
                                 CUtensorMapL2promotion, CUtensorMapFloatOOBfill);
    static Scratch* gs = nullptr;
    static EncodeFn encode = nullptr;
    if (!gs) {
        cudaFuncSetAttribute(resblock_kernel, cudaFuncAttributeMaxDynamicSharedMemorySize, SM_TOTAL);
        cudaGetSymbolAddress((void**)&gs, g_scratch);
        cudaDriverEntryPointQueryResult qr;
        cudaGetDriverEntryPoint("cuTensorMapEncodeTiled", (void**)&encode, cudaEnableDefault, &qr);
    }
    CUtensorMap xmap;
    const cuuint64_t dims[3] = {HW, HW, NB * C}, strides[2] = {HW * 2, HW * HW * 2};
    const cuuint32_t box[3] = {HW, 1, 32}, es[3] = {1, 1, 1};
    encode(&xmap, CU_TENSOR_MAP_DATA_TYPE_BFLOAT16, 3, d_in[0], dims, strides, box, es, CU_TENSOR_MAP_INTERLEAVE_NONE,
           CU_TENSOR_MAP_SWIZZLE_128B, CU_TENSOR_MAP_L2_PROMOTION_NONE, CU_TENSOR_MAP_FLOAT_OOB_FILL_NONE);
    resblock_kernel<<<NCTA + NXTRA, NTHREADS, SM_TOTAL>>>(
        (const __nv_bfloat16*)d_in[4], (const __nv_bfloat16*)d_in[0], (const __nv_bfloat16*)d_in[1],
        (const __nv_bfloat16*)d_in[2], (const __nv_bfloat16*)d_in[3], (const __nv_bfloat16*)d_in[5],
        (const __nv_bfloat16*)d_in[6], (const __nv_bfloat16*)d_in[7], (const __nv_bfloat16*)d_in[8],
        (__nv_bfloat16*)d_out, gs, xmap);
}
```

```cpp
#include <cuda_runtime.h>
#include <cuda.h>
#include <cuda_bf16.h>
#include <stdint.h>

namespace {

constexpr int C = 128, HW = 64, NB = 2, E = 768;
constexpr int NCTA = NB * HW;
constexpr int NXTRA = 4;
constexpr int NTHREADS = 16 * 32;
constexpr int CH_PITCH = 66 * 16;
constexpr int KC_BYTES = 2 * CH_PITCH;
constexpr int STAGE_BYTES = 12288;
constexpr int NSTAGE = 16;
constexpr int NS = 8;
#define XDELAY 300
#define XSTAG 800
#define XSTAG2 100
#define SDELAY 600
#define W2DELAY 2400
#define PDELAY 200
#define FDELAY 200

constexpr uint32_t SMEM_BASE = 0x400;
constexpr uint32_t SM_XA = SMEM_BASE;
constexpr uint32_t SM_XB = SM_XA + 16384;
constexpr uint32_t SM_M = SM_XB + 16384;
constexpr uint32_t SM_V = SM_M + 16384;
constexpr uint32_t SM_W = SM_V + NSTAGE * KC_BYTES + 128;
constexpr uint32_t SM_COEF = SM_W + NS * STAGE_BYTES;
constexpr uint32_t SM_GST = SM_COEF + 2048;
constexpr uint32_t SM_EMB = SM_GST + 128;
constexpr uint32_t SM_ONES = SM_EMB + 2048;
constexpr uint32_t SM_RED = SM_ONES + 256;
constexpr uint32_t SM_BNC = SM_RED + 1024;
constexpr uint32_t SM_BAR = SM_BNC + 2 * 2304;
constexpr int BAR_FULL = 0, BAR_WEMPTY = NSTAGE, BAR_HW = BAR_WEMPTY + NS, BAR_STATS = BAR_HW + 1, BAR_EMB = BAR_STATS + 1,
              BAR_RV = BAR_EMB + 1  , BAR_M = BAR_RV + 4, BAR_RH = BAR_M + 1, BAR_XO = BAR_RH + 1, BAR_XR = BAR_XO + 1,
              BAR_X = BAR_XR + 1  , NBAR = BAR_X + 4;
constexpr int SM_TOTAL = SM_BAR + NBAR * 8 - SMEM_BASE;
static_assert(SM_TOTAL <= 232448, "smem");
__host__ __device__ constexpr uint32_t BAR(int i) { return SM_BAR + 8 * i; }

constexpr unsigned SPIN_LIMIT = 1u << 16;
constexpr int LS = 1056, KS = 32;

struct Scratch {
    float acc1[NB * LS];
    float acc2[NB * LS];
    unsigned wcnt[3 * NB * LS];
    unsigned w1cnt[NB * 8 * KS];
    float emb[NXTRA * NB * C];
    alignas(1024) unsigned char wt[2 * 32 * STAGE_BYTES];
    uint4 box[NCTA * 1024];
};
__device__ __align__(1024) Scratch g_scratch;
#define TL(i) do {} while (0)
#define TLG(i) do {} while (0)

__device__ __forceinline__ unsigned clock32() { unsigned c; asm volatile("mov.u32 %0, %%clock;" : "=r"(c)); return c; }
__device__ __forceinline__ uint32_t mapa(uint32_t a, uint32_t rank) {
    uint32_t d;
    asm("mapa.shared::cluster.u32 %0, %1, %2;" : "=r"(d) : "r"(a), "r"(rank));
    return d;
}
#define S0 mapa(0, blockIdx.x & 1)
__device__ __forceinline__ void mbar_init(uint32_t bar, int cnt) {
    asm volatile("mbarrier.init.shared::cta.b64 [%0], %1;" ::"r"(bar + S0), "r"(cnt) : "memory");
}
__device__ __forceinline__ void mbar_arrive(uint32_t bar) {
    asm volatile("mbarrier.arrive.shared::cta.b64 _, [%0];" ::"r"(bar + S0) : "memory");
}
__device__ __forceinline__ void mbar_expect(uint32_t bar, uint32_t bytes) {
    asm volatile("mbarrier.arrive.expect_tx.shared::cta.b64 _, [%0], %1;" ::"r"(bar + S0), "r"(bytes) : "memory");
}
__device__ __forceinline__ bool mbar_try(uint32_t bar, uint32_t par) {
    uint32_t ok;
    asm volatile("{\n.reg .pred p;\nmbarrier.try_wait.parity.shared::cta.b64 p, [%1], %2;\nselp.u32 %0, 1, 0, p;\n}"
                 : "=r"(ok) : "r"(bar + S0), "r"(par) : "memory");
    return ok;
}
__device__ __forceinline__ bool mbar_test(uint32_t bar, uint32_t par) {
    uint32_t ok;
    asm volatile("{\n.reg .pred p;\nmbarrier.test_wait.parity.shared::cta.b64 p, [%1], %2;\nselp.u32 %0, 1, 0, p;\n}"
                 : "=r"(ok) : "r"(bar + S0), "r"(par) : "memory");
    return ok;
}
__device__ __forceinline__ void mbar_wait(uint32_t bar, uint32_t par) {
    unsigned it = 0;
#pragma unroll 1
    while (!mbar_try(bar, par) && ++it < SPIN_LIMIT) {}
}
__device__ __forceinline__ bool elect_one() {
    uint32_t p;
    asm volatile("{\n.reg .pred p;\nelect.sync _|p, 0xffffffff;\nselp.u32 %0, 1, 0, p;\n}" : "=r"(p));
    return p;
}
__device__ __forceinline__ void fence_async_smem() { asm volatile("fence.proxy.async.shared::cta;" ::: "memory"); }
__device__ __forceinline__ void fence_async_global() { asm volatile("fence.proxy.async.global;" ::: "memory"); }
__device__ __forceinline__ void fence_acquire() { asm volatile("fence.acquire.gpu;" ::: "memory"); }
__device__ __forceinline__ void bar_sync(int id, int n) { asm volatile("bar.sync %0, %1;" ::"r"(id), "r"(n) : "memory"); }
__device__ __forceinline__ void bar_arrive(int id, int n) { asm volatile("bar.arrive %0, %1;" ::"r"(id), "r"(n) : "memory"); }
__device__ __forceinline__ void bulk_g2s(uint32_t dst, const void* src, uint32_t bytes, uint32_t bar) {
    asm volatile("cp.async.bulk.shared::cluster.global.mbarrier::complete_tx::bytes [%0], [%1], %2, [%3];"
                 ::"r"(dst), "l"(src), "r"(bytes), "r"(bar) : "memory");
}
__device__ __forceinline__ void tma_x(uint32_t dst, const CUtensorMap* tm, int row, int ch, uint32_t bar) {
    asm volatile("cp.async.bulk.tensor.3d.shared::cluster.global.mbarrier::complete_tx::bytes [%0], [%1, {%2, %3, %4}], [%5];"
                 ::"r"(dst + S0), "l"(tm), "r"(0), "r"(row), "r"(ch), "r"(bar + S0) : "memory");
}
__device__ __forceinline__ uint4 ld_relaxed_v4(const void* p) {
    uint4 v;
    asm volatile("ld.relaxed.gpu.global.v4.u32 {%0,%1,%2,%3}, [%4];" : "=r"(v.x), "=r"(v.y), "=r"(v.z), "=r"(v.w) : "l"(p) : "memory");
    return v;
}
__device__ __forceinline__ unsigned ld_relaxed(const void* p) {
    unsigned v;
    asm volatile("ld.relaxed.gpu.global.u32 %0, [%1];" : "=r"(v) : "l"(p) : "memory");
    return v;
}
__device__ __forceinline__ void red_add4(float* p, float a, float b, float c, float d) {
    asm volatile("red.relaxed.gpu.global.add.v4.f32 [%0], {%1,%2,%3,%4};" ::"l"(p), "f"(a), "f"(b), "f"(c), "f"(d) : "memory");
}
__device__ __forceinline__ void sts128(uint32_t a, uint4 v) {
    asm volatile("st.shared.v4.u32 [%0], {%1,%2,%3,%4};" ::"r"(a + S0), "r"(v.x), "r"(v.y), "r"(v.z), "r"(v.w) : "memory");
}
__device__ __forceinline__ void sts128f(uint32_t a, float4 v) {
    asm volatile("st.shared.v4.f32 [%0], {%1,%2,%3,%4};" ::"r"(a + S0), "f"(v.x), "f"(v.y), "f"(v.z), "f"(v.w) : "memory");
}
__device__ __forceinline__ void sts32f(uint32_t a, float v) { asm volatile("st.shared.f32 [%0], %1;" ::"r"(a + S0), "f"(v) : "memory"); }
__device__ __forceinline__ uint4 lds128(uint32_t a) {
    uint4 v;
    asm volatile("ld.shared.v4.u32 {%0,%1,%2,%3}, [%4];" : "=r"(v.x), "=r"(v.y), "=r"(v.z), "=r"(v.w) : "r"(a + S0) : "memory");
    return v;
}
__device__ __forceinline__ float4 lds128f(uint32_t a) {
    float4 v;
    asm volatile("ld.shared.v4.f32 {%0,%1,%2,%3}, [%4];" : "=f"(v.x), "=f"(v.y), "=f"(v.z), "=f"(v.w) : "r"(a + S0) : "memory");
    return v;
}
__device__ __forceinline__ float2 lds64f(uint32_t a) {
    float2 v;
    asm volatile("ld.shared.v2.f32 {%0,%1}, [%2];" : "=f"(v.x), "=f"(v.y) : "r"(a + S0) : "memory");
    return v;
}
__device__ __forceinline__ float bf_lo(uint32_t u) { return __uint_as_float(u << 16); }
__device__ __forceinline__ float bf_hi(uint32_t u) { return __uint_as_float(u & 0xffff0000u); }
__device__ __forceinline__ uint32_t pack_bf(float lo, float hi) {
    uint32_t r;
    asm("cvt.rn.bf16x2.f32 %0, %1, %2;" : "=r"(r) : "f"(hi), "f"(lo));
    return r;
}
__device__ __forceinline__ float tanh_fast(float x) {
    float r;
    asm("tanh.approx.f32 %0, %1;" : "=f"(r) : "f"(x));
    return r;
}
__device__ __forceinline__ float silu_half(float h) { return fmaf(h, tanh_fast(h), h); }
__device__ __forceinline__ void ldsm4(uint32_t (&u)[4], uint32_t a) {
    asm volatile("ldmatrix.sync.aligned.m8n8.x4.shared.b16 {%0,%1,%2,%3}, [%4];"
                 : "=r"(u[0]), "=r"(u[1]), "=r"(u[2]), "=r"(u[3]) : "r"(a + S0) : "memory");
}
__device__ __forceinline__ void ldsm4t(uint32_t (&u)[4], uint32_t a) {
    asm volatile("ldmatrix.sync.aligned.m8n8.x4.trans.shared.b16 {%0,%1,%2,%3}, [%4];"
                 : "=r"(u[0]), "=r"(u[1]), "=r"(u[2]), "=r"(u[3]) : "r"(a + S0) : "memory");
}
__device__ __forceinline__ void stsm4(uint32_t a, uint32_t p0, uint32_t p1, uint32_t p2, uint32_t p3) {
    asm volatile("stmatrix.sync.aligned.m8n8.x4.shared.b16 [%0], {%1,%2,%3,%4};" ::"r"(a + S0), "r"(p0), "r"(p1), "r"(p2), "r"(p3) : "memory");
}
__device__ __forceinline__ void stsm4t(uint32_t a, uint32_t p0, uint32_t p1, uint32_t p2, uint32_t p3) {
    asm volatile("stmatrix.sync.aligned.m8n8.x4.trans.shared.b16 [%0], {%1,%2,%3,%4};" ::"r"(a + S0), "r"(p0), "r"(p1), "r"(p2), "r"(p3) : "memory");
}

#define R8(o) "+f"(d[o]), "+f"(d[o + 1]), "+f"(d[o + 2]), "+f"(d[o + 3]), "+f"(d[o + 4]), "+f"(d[o + 5]), "+f"(d[o + 6]), "+f"(d[o + 7])
template <uint32_t ALO, uint32_t BLO, uint64_t AHI = 8, uint64_t BHI = 48>
__device__ __forceinline__ void wgmma128(float (&d)[64]) {
    asm volatile(
        "wgmma.mma_async.sync.aligned.m64n128k16.f32.bf16.bf16 "
        "{%0,%1,%2,%3,%4,%5,%6,%7,%8,%9,%10,%11,%12,%13,%14,%15,%16,%17,%18,%19,%20,%21,%22,%23,%24,%25,%26,%27,%28,%29,%30,%31,"
        "%32,%33,%34,%35,%36,%37,%38,%39,%40,%41,%42,%43,%44,%45,%46,%47,%48,%49,%50,%51,%52,%53,%54,%55,%56,%57,%58,%59,%60,%61,%62,%63},"
        " %64, %65, 1, 1, 1, 0, 0;"
        : R8(0), R8(8), R8(16), R8(24), R8(32), R8(40), R8(48), R8(56)
        : "l"((AHI << 32) | ALO), "l"((BHI << 32) | BLO));
}
__device__ __forceinline__ void stat_mma(float (&c)[4], uint32_t p, uint32_t q) {
    asm("mma.sync.aligned.m16n8k16.row.col.f32.bf16.bf16.f32 {%0,%1,%2,%3}, {%4,%5,%6,%5}, {%4,%6}, {%0,%1,%2,%3};"
        : "+f"(c[0]), "+f"(c[1]), "+f"(c[2]), "+f"(c[3]) : "r"(p), "r"(0x3f803f80u), "r"(q));
}
__device__ __forceinline__ void stat_store(const float (&c)[4], uint32_t dst, int lane) {
    const int g = lane >> 2, t = lane & 3;
    if (t == (g >> 1)) sts32f(dst + g * 4, (g & 1) ? c[1] : c[0]);
    if (g == 7) sts32f(dst + 32 + t * 4, c[2] + c[3]);
}
__device__ __forceinline__ float sum4(float4 v) { return (v.x + v.y) + (v.z + v.w); }
__device__ __forceinline__ void stat_publish(uint32_t src, float* acc, int lane, bool real) {
    const uint32_t a = src + (lane & 15) * 48;
    float q = sum4(lds128f(a)) + sum4(lds128f(a + 16)), sm = sum4(lds128f(a + 32));
    q += __shfl_xor_sync(0xffffffffu, q, 1); sm += __shfl_xor_sync(0xffffffffu, sm, 1);
    q += __shfl_xor_sync(0xffffffffu, q, 2); sm += __shfl_xor_sync(0xffffffffu, sm, 2);
    if (real && (lane & 19) == 0) red_add4(acc + lane, 1.f, sm, q, 1.f);
}
__device__ __forceinline__ void fence_acc(float (&d)[64]) {
#pragma unroll
    for (int i = 0; i < 64; i++) asm volatile("" : "+f"(d[i])::"memory");
}
__device__ __forceinline__ void ld_unit(uint32_t (&u)[4], const uint4* p) {
    asm volatile("ld.relaxed.gpu.global.v4.u32 {%0,%1,%2,%3}, [%4];" : "=r"(u[0]), "=r"(u[1]), "=r"(u[2]), "=r"(u[3]) : "l"(p) : "memory");
}

__device__ __forceinline__ void st_async(uint32_t dst, uint32_t a, uint32_t b, uint32_t c, uint32_t d, uint32_t bar) {
    asm volatile("st.async.shared::cluster.mbarrier::complete_tx::bytes.v4.b32 [%0], {%1,%2,%3,%4}, [%5];"
                 ::"r"(dst), "r"(a), "r"(b), "r"(c), "r"(d), "r"(bar) : "memory");
}
template <int S>
__device__ __forceinline__ void mma_stages(float (&d)[64], uint32_t (&hp)[32], int conv, int tid, uint32_t peer0, Scratch* gs) {
    constexpr uint32_t A = ((SM_V + S * KC_BYTES + 16) >> 4) | ((CH_PITCH >> 4) << 16);
    constexpr uint32_t B = ((SM_W + (S % NS) * STAGE_BYTES) >> 4) | (8u << 16);
    if (S == 0) mbar_wait(BAR(BAR_FULL), conv);
    constexpr uint32_t NEXT = S + 1 < NSTAGE ? BAR(BAR_FULL + S + 1) : BAR(BAR_EMB);
    const int npar = S + 1 < NSTAGE ? conv : 0;
    const bool next_ok = mbar_test(NEXT, npar);
    if ((S & 7) == 0 && tid == 0) TL(32 + conv * 16 + S);
    asm volatile("wgmma.fence.sync.aligned;" ::: "memory");
    wgmma128<A, B>(d);
    if (S >= 8 && S < 12) st_async(peer0 + SM_M + (S & 3) * 4096 + tid * 16, hp[(S & 3) * 8], hp[(S & 3) * 8 + 1], hp[(S & 3) * 8 + 2], hp[(S & 3) * 8 + 3], peer0 + BAR(BAR_M));
    wgmma128<A + 1, B + 16>(d);
    if (S >= 8 && S < 12) st_async(peer0 + SM_M + (S & 3) * 4096 + 2048 + tid * 16, hp[(S & 3) * 8 + 4], hp[(S & 3) * 8 + 5], hp[(S & 3) * 8 + 6], hp[(S & 3) * 8 + 7], peer0 + BAR(BAR_M));
    wgmma128<A + 2, B + 32>(d);
    asm volatile("wgmma.commit_group.sync.aligned;" ::: "memory");
    if ((S & 7) != 0) {
        asm volatile("wgmma.wait_group.sync.aligned 1;" ::: "memory");
        if ((tid & 31) == 0) mbar_arrive(BAR(BAR_WEMPTY + (S - 1) % NS));
    }
    if (S == 7) {
        asm volatile("wgmma.wait_group.sync.aligned 0;" ::: "memory");
        fence_acc(d);
#pragma unroll
        for (int i = 0; i < 32; i++) hp[i] = pack_bf(d[2 * i], d[2 * i + 1]);
        fence_acc(d);
        if ((tid & 31) == 0) mbar_arrive(BAR(BAR_WEMPTY + 7));
    }
    if (!next_ok) mbar_wait(NEXT, npar);
    if constexpr (S + 1 < NSTAGE) mma_stages<S + 1>(d, hp, conv, tid, peer0, gs);
}

__device__ __forceinline__ int wblk_kc(int cta) { const int i = cta >> 4; return (i & 1) | ((i & 2) << 1) | ((i & 4) >> 1); }
__device__ __forceinline__ int n_to_oc(int n) { return (n & ~31) | ((n & 6) << 2) | ((n >> 2) & 6) | (n & 1); }
__device__ __forceinline__ void weight_load(uint4 (&t)[5], const __nv_bfloat16* w, int cta, int lane, bool perm) {
    const int n = (cta & 15) * 8 + (lane >> 2);
    const char* base = reinterpret_cast<const char*>(w) + (uint32_t)(((perm ? n_to_oc(n) : n) * 8 + wblk_kc(cta)) * 288 + (lane & 3) * 16);
#pragma unroll
    for (int k = 0; k < 5; k++)
        if (k < 4 || !(lane & 2)) t[k] = __ldg(reinterpret_cast<const uint4*>(base + k * 64));
}
__device__ __forceinline__ void st_global64(void* p, uint32_t a, uint32_t b) { asm volatile("st.global.v2.u32 [%0], {%1,%2};" ::"l"(p), "r"(a), "r"(b) : "memory"); }
__device__ __forceinline__ void weight_block(uint32_t bounce, unsigned char* wt, int cta, int lane, unsigned* cnt) {
    const unsigned opaque_one = gridDim.y;
    unsigned char* piece = wt + wblk_kc(cta) * STAGE_BYTES + (cta & 15) * 768;
    uint32_t v[18];
#pragma unroll
    for (int i = 0; i < 9; i++) {
        const float2 q = lds64f(bounce + (lane & 7) * 288 + (lane >> 3) * 72 + i * 8);
        v[2 * i] = __float_as_uint(q.x); v[2 * i + 1] = __float_as_uint(q.y);
    }
    unsigned char* dst = piece + (lane >> 4) * 128 + (lane & 7) * 16 + ((lane >> 3) & 1) * 8;
#pragma unroll
    for (int kx = 0; kx < 3; kx++) {
        float u1[4], u2[4];
#pragma unroll
        for (int c = 0; c < 4; c++) {
            const int i0 = 9 * c + kx, i1 = i0 + 3, i2 = i0 + 6;
            const float g0 = (i0 & 1) ? bf_hi(v[i0 >> 1]) : bf_lo(v[i0 >> 1]);
            const float g1 = (i1 & 1) ? bf_hi(v[i1 >> 1]) : bf_lo(v[i1 >> 1]);
            const float g2 = (i2 & 1) ? bf_hi(v[i2 >> 1]) : bf_lo(v[i2 >> 1]);
            const float t = 0.5f * (g0 + g2);
            u1[c] = fmaf(g1, 0.5f, t); u2[c] = fmaf(g1, -0.5f, t);
        }
        st_global64(dst + kx * 256, pack_bf(u1[0], u1[1]), pack_bf(u1[2], u1[3]));
        st_global64(dst + 8 * STAGE_BYTES + kx * 256, pack_bf(u2[0], u2[1]), pack_bf(u2[2], u2[3]));
    }
    const unsigned char* rb = piece + (lane < 24 ? lane : 0) * 32;
    const unsigned r0 = ld_relaxed(rb), r1 = ld_relaxed(rb + 8 * STAGE_BYTES);
#pragma unroll
    for (int j = 0; j < 6; j++) {
        const int tap = (j / 3) * 6 + j % 3;
        uint32_t o[2];
#pragma unroll
        for (int m = 0; m < 2; m++) {
            const int i0 = 18 * m + tap, i1 = i0 + 9;
            o[m] = __byte_perm(v[i0 >> 1], v[i1 >> 1], ((i0 & 1) ? 0x32u : 0x10u) | ((i1 & 1) ? 0x7600u : 0x5400u));
        }
        st_global64(dst + (16 + (j / 3) * 8) * STAGE_BYTES + (j % 3) * 256, o[0], o[1]);
    }
    const unsigned r2 = ld_relaxed(rb + 16 * STAGE_BYTES), r3 = ld_relaxed(rb + 24 * STAGE_BYTES);
    const unsigned i0 = __any_sync(0xffffffffu, (r0 ^ r1) == 0x9e3779b9u) ? opaque_one : 1u;
    if (lane < 2) asm volatile("red.relaxed.gpu.global.add.u32 [%0], %1;" ::"l"(cnt), "r"(i0) : "memory");
    const unsigned i1 = __any_sync(0xffffffffu, (r2 ^ r3) == 0x9e3779b9u) ? opaque_one : 1u;
    if (lane < 2) asm volatile("red.relaxed.gpu.global.add.u32 [%0], %1;" ::"l"(cnt), "r"(i1 << 16) : "memory");
}
__device__ __forceinline__ void publish(uint32_t bar, int lane) {
    fence_async_smem();
    __syncwarp();
    if (lane == 0) mbar_arrive(bar);
}
__device__ __forceinline__ void lds_piece(uint32_t (&u)[4], uint32_t a) {
    const uint4 q = lds128(a);
    u[0] = q.x; u[1] = q.y; u[2] = q.z; u[3] = q.w;
}
__device__ __noinline__ void side_jobs(const __nv_bfloat16* __restrict__ t_emb, const __nv_bfloat16* __restrict__ w_emb,
                                       const __nv_bfloat16* __restrict__ w2, Scratch* __restrict__ gs, unsigned clk0) {
    const int tid = threadIdx.x, warp = tid >> 5, lane = tid & 31, j = blockIdx.x;
    float tv = 0.f;
    if (lane < 24) tv = __bfloat162float(t_emb[(lane / 12) * E + j * 192 + warp * 12 + lane % 12]);
    if (tid == 0) {
        mbar_init(BAR(0), 1);
        mbar_expect(BAR(0), 192 * C * 2);
        fence_async_smem();
        while (clock32() - clk0 < SDELAY) {}
#pragma unroll
        for (int i = 0; i < 4; i++)
            asm volatile("cp.async.bulk.prefetch.L2.global [%0], 18432;" ::"l"(reinterpret_cast<const char*>(w2) + (j * 4 + i) * 18432) : "memory");
#pragma unroll
        for (int i = 0; i < 4; i++) bulk_g2s(S0 + SM_W + i * 12288, w_emb + (j * 192 + i * 48) * C, 12288, S0 + BAR(0));
    }
    if (j == 0 && tid < 32) gs->acc2[(tid >> 4) * LS + (tid & 15)] = 0.f;
    const float sv = silu_half(0.5f * tv);
    __syncthreads();
    mbar_wait(BAR(0), 0);
    float acc[8] = {0.f, 0.f, 0.f, 0.f, 0.f, 0.f, 0.f, 0.f};
#pragma unroll
    for (int i = 0; i < 12; i++) {
        const float2 wq = lds64f(SM_W + (warp * 12 + i) * 256 + lane * 8);
        const uint32_t wx = __float_as_uint(wq.x), wy = __float_as_uint(wq.y);
#pragma unroll
        for (int bb = 0; bb < 2; bb++) {
            const float sx = __shfl_sync(0xffffffffu, sv, bb * 12 + i);
            acc[4 * bb + 0] = fmaf(sx, bf_lo(wx), acc[4 * bb + 0]); acc[4 * bb + 1] = fmaf(sx, bf_hi(wx), acc[4 * bb + 1]);
            acc[4 * bb + 2] = fmaf(sx, bf_lo(wy), acc[4 * bb + 2]); acc[4 * bb + 3] = fmaf(sx, bf_hi(wy), acc[4 * bb + 3]);
        }
    }
    sts128f(SM_V + warp * 1024 + lane * 16, make_float4(acc[0], acc[1], acc[2], acc[3]));
    sts128f(SM_V + warp * 1024 + 512 + lane * 16, make_float4(acc[4], acc[5], acc[6], acc[7]));
    __syncthreads();
    if (tid < 128) {
        float2 sum = make_float2(0.f, 0.f);
#pragma unroll
        for (int w = 0; w < 16; w++) { const float2 p = lds64f(SM_V + w * 1024 + tid * 8); sum.x += p.x; sum.y += p.y; }
        *reinterpret_cast<float2*>(&gs->emb[j * NB * C + tid * 2]) = sum;
        bar_sync(1, 128);
        if (tid < 2) asm volatile("red.release.gpu.global.add.u32 [%0], 1;" ::"l"(&gs->wcnt[(2 * NB + tid) * LS]) : "memory");
    }
}

__global__ void __cluster_dims__(2, 1, 1) __launch_bounds__(NTHREADS, 1)
resblock_kernel(const __nv_bfloat16* __restrict__ w1, const __nv_bfloat16* __restrict__ x,
                const __nv_bfloat16* __restrict__ t_emb, const __nv_bfloat16* __restrict__ g1,
                const __nv_bfloat16* __restrict__ be1, const __nv_bfloat16* __restrict__ w_emb,
                const __nv_bfloat16* __restrict__ g2, const __nv_bfloat16* __restrict__ be2,
                const __nv_bfloat16* __restrict__ w2, __nv_bfloat16* __restrict__ out, Scratch* __restrict__ gs,
                const __grid_constant__ CUtensorMap xmap) {
    const unsigned clk0 = clock32();
    if (threadIdx.x == 480 && blockIdx.x >= NXTRA) TLG(1);
    const int tid = threadIdx.x, lane = tid & 31;
    const int cta = blockIdx.x - NXTRA, b = cta >> 6, r = cta & 63, rk = cta & 1;
    uint4 v[5];
    if (tid < 32) weight_load(v, w1, cta & (NCTA - 1), lane, true);
    uint4 xv[8];
    const int ch0 = (b & 1) * C + rk * 64;
    if (tid >= 32 && tid < 96) {
        const char* src = reinterpret_cast<const char*>(x) + (uint32_t)(((ch0 + (lane >> 3)) * HW + (r ^ (tid >> 6))) * HW * 2 + (lane & 7) * 16);
        while (clock32() - clk0 < XDELAY + (tid >> 6) * XSTAG2) {}
#pragma unroll
        for (int i = 0; i < 8; i++) xv[i] = __ldg(reinterpret_cast<const uint4*>(src + i * (4 * HW * HW * 2)));
    }
    const int warp = __shfl_sync(0xffffffffu, tid >> 5, 0);
    if (cta < 0) { side_jobs(t_emb, w_emb, w2, gs, clk0); return; }

    if (warp != 4) asm volatile("barrier.cluster.arrive.relaxed.aligned;" ::: "memory");
    const bool has_near = r != 0 && r != HW - 1, has_far = r != 1 && r != HW - 2;
    const uint32_t peer0 = mapa(0, rk ^ 1);
    if (warp == 1 || warp == 2 || warp == 3 || warp == 5) {
        const int i = warp < 4 ? warp - 1 : 3, gl = i >> 1, row = i & 1;
        const uint32_t tile = SM_XA + row * 8192 + gl * 4096;
        if (elect_one()) {
            if (gl) asm volatile("prefetch.tensormap [%0];" ::"l"(&xmap) : "memory");
            mbar_init(BAR(BAR_X) + 8 * i, 1);
            if (gl) { mbar_expect(BAR(BAR_X) + 8 * i, 4096); fence_async_smem(); }
        }
        __syncwarp();
        bar_arrive(4, 256 + 32 + 128);
        if (gl) {
            while (clock32() - clk0 < XDELAY + XSTAG + row * XSTAG2) {}
            if (elect_one()) tma_x(tile, &xmap, r ^ row, ch0 + 32, BAR(BAR_X) + 8 * i);
            __syncwarp();
            mbar_wait(BAR(BAR_X) + 8 * i, 0);
#pragma unroll
            for (int k = 0; k < 8; k++) xv[k] = lds128(tile + k * 512 + lane * 16);
        }
        float c[8][4];
#pragma unroll
        for (int k = 0; k < 8; k++) {
            c[k][0] = c[k][1] = c[k][2] = c[k][3] = 0.f;
            stat_mma(c[k], xv[k].x, xv[k].y); stat_mma(c[k], xv[k].z, xv[k].w);
        }
#pragma unroll
        for (int k = 0; k < 4; k++) c[0][k] = ((c[0][k] + c[1][k]) + (c[2][k] + c[3][k])) + ((c[4][k] + c[5][k]) + (c[6][k] + c[7][k]));
        stat_store(c[0], SM_RED + i * 48, lane);
        __syncwarp();
        if (lane == 0) {
            const uint32_t a = SM_RED + i * 48;
            red_add4(&gs->acc1[b * LS + (rk * 2 + gl) * 4], 1.f, sum4(lds128f(a + 32)), sum4(lds128f(a)) + sum4(lds128f(a + 16)), 1.f);
            TL(74 + i);
        }
        if (!gl) {
#pragma unroll
            for (int k = 0; k < 8; k++)
                sts128(tile + k * 512 + (lane >> 3) * 128 + (((lane & 7) ^ ((lane >> 3) + 4 * (k & 1))) << 4), xv[k]);
            __syncwarp();
            if (lane == 0) mbar_arrive(BAR(BAR_X) + 8 * i);
        }
    }
    if (warp == 4) {
        if (elect_one()) {
#pragma unroll
            for (int i = 0; i < NSTAGE; i++) mbar_init(BAR(BAR_FULL + i), (i & 1) ? 1 : ((i & 2) ? 2 : 5));
#pragma unroll
            for (int i = 0; i <= NS; i++) mbar_init(BAR(BAR_WEMPTY + i), 4);
#pragma unroll
            for (int i = BAR_STATS; i < BAR_X; i++) mbar_init(BAR(i), i == BAR_EMB ? 2 : 1);
            asm volatile("fence.mbarrier_init.release.cluster;" ::: "memory");
        }
        if (lane < 2) sts128(SM_GST + lane * 16, make_uint4(0, 0, 0, 0));
        __syncwarp();
        if (lane < 6) mbar_expect(BAR(BAR_RV) + 8 * lane, lane < 4 ? 4096 : (lane == 4 ? 16384 : 8192));
        fence_async_smem();
        bar_arrive(0, 96);
        bar_arrive(5, 64);
        bar_arrive(4, 256 + 32 + 128);
        const uint4 z = make_uint4(0, 0, 0, 0);
#pragma unroll
        for (int i = 0; i < 2; i++) sts128(SM_V + (i * 16 + (lane >> 1)) * CH_PITCH + (lane & 1) * 16, z);
        if (lane < 2) sts128(SM_V + NSTAGE * KC_BYTES + lane * 16, z);
        if (lane < 16) sts128(SM_ONES + lane * 16, make_uint4(lane < 8 ? 0x3f803f80u : 0u, 0, 0, 0));
        fence_async_smem();
        bar_arrive(7, 160);
        asm volatile("barrier.cluster.arrive.relaxed.aligned;" ::: "memory");
        while (clock32() - clk0 < W2DELAY) {}
        weight_load(v, w2, cta, lane, false);
    }
    if (warp == 0 || warp == 4) {
        const int k = warp >> 2;
#pragma unroll
        for (int i = 0; i < 5; i++)
            if (i < 4 || !(lane & 2)) sts128(SM_BNC + k * 2304 + (lane >> 2) * 288 + (lane & 3) * 16 + i * 64, v[i]);
        if (lane == 0) TL(k ? 14 : 81);
        __syncwarp();
        weight_block(SM_BNC + k * 2304, gs->wt + k * 32 * STAGE_BYTES, cta, lane,
                     k ? &gs->wcnt[(NB + (lane & 1)) * LS] : &gs->w1cnt[((lane & 1) * 8 + wblk_kc(cta)) * KS]);
        if (lane == 0) TL(k ? 13 : 4);
    }

    if (warp >= 8) {
        const int nw = warp - 8;
        if (nw < 4) {
            const uint2 q = __ldg(reinterpret_cast<const uint2*>(nw == 0 ? g1 : (nw == 1 ? be1 : (nw == 2 ? g2 : be2))) + lane);
            sts128f(SM_COEF + nw * 512 + lane * 16, make_float4(0.5f * bf_lo(q.x), 0.5f * bf_hi(q.x), 0.5f * bf_lo(q.y), 0.5f * bf_hi(q.y)));
        }
        bar_sync(4, 256 + 32 + 128);
        asm volatile("barrier.cluster.wait.acquire.aligned;" ::: "memory");
        const int gl = nw >> 2, wq = nw & 3;
        const uint32_t v_off = SM_V + (gl * 8 + (lane & 3)) * CH_PITCH + (2 + wq * 16 + (lane >> 2)) * 16;
        const int crow = ((lane & 6) << 2) | ((lane >> 3) << 1) | (lane & 1);
        const uint32_t stg_off = (gl * 32 + crow) * 128, stg_sw = crow & 7;
        const uint32_t img_off = gl * 4096 + (tid & 127) * 16;
        const float sg = rk ? -1.f : 1.f;
        uint4* inbox = gs->box + cta * 1024 + gl * 256 + (tid & 127);
#pragma unroll 1
        for (int conv = 0; conv < 2; conv++) {
            uint32_t u[4][4];
            if (conv == 0) {
#pragma unroll
                for (int i = 0; i < 4; i++) {
                    if (!(i & 1)) mbar_wait(BAR(BAR_X) + 16 * gl + 4 * i, 0);
                    ldsm4t(u[i], SM_XA + (i >> 1) * 8192 + stg_off + (((2 * wq + (i & 1)) ^ stg_sw) << 4));
                }
            } else {
                mbar_wait(BAR(BAR_HW), 0);
                mbar_wait(BAR(BAR_RH), 0);
#pragma unroll
                for (int i = 0; i < 4; i++) lds_piece(u[i], SM_XA + (i >> 1) * 8192 + (i & 1) * 2048 + img_off);
            }
            float ga[8], be[8], a[4][8];
            {
                const uint32_t ca = SM_COEF + conv * 1024 + (rk * 64 + gl * 32 + (lane & 3) * 8) * 4;
                const float4 q0 = lds128f(ca), q1 = lds128f(ca + 16), q2 = lds128f(ca + 512), q3 = lds128f(ca + 528);
                ga[0] = q0.x; ga[1] = q0.y; ga[2] = q0.z; ga[3] = q0.w; ga[4] = q1.x; ga[5] = q1.y; ga[6] = q1.z; ga[7] = q1.w;
                be[0] = q2.x; be[1] = q2.y; be[2] = q2.z; be[3] = q2.w; be[4] = q3.x; be[5] = q3.y; be[6] = q3.z; be[7] = q3.w;
            }
#pragma unroll
            for (int i = 0; i < 16; i++) {
                a[i >> 2][2 * (i & 3)] = bf_lo(u[i >> 2][i & 3]) * ga[2 * (i & 3)]; a[i >> 2][2 * (i & 3) + 1] = bf_hi(u[i >> 2][i & 3]) * ga[2 * (i & 3) + 1];
                asm volatile("" : "+f"(a[i >> 2][2 * (i & 3)]), "+f"(a[i >> 2][2 * (i & 3) + 1]));
            }
            float rs, mr;
            {
                unsigned it = 0;
#pragma unroll 1
                do {
                    asm volatile("ld.volatile.shared.v2.f32 {%0,%1}, [%2];" : "=f"(rs), "=f"(mr) : "r"(S0 + SM_GST + conv * 16 + gl * 8) : "memory");
                } while (!__all_sync(0xffffffffu, rs != 0.f) && ++it < 8 * SPIN_LIMIT);
            }
            if (tid == 256) TL(22 + conv * 4);
            if (gl && conv) { const unsigned c1 = clock32(); while (clock32() - c1 < PDELAY) {} }
#pragma unroll
            for (int i = 0; i < 8; i++) be[i] = fmaf(-mr, ga[i], be[i]);
#pragma unroll
            for (int h = 0; h < 2; h++) {
                uint32_t kp[4], sd[4];
#pragma unroll
                for (int i = 0; i < 8; i++) { a[h][i] = silu_half(fmaf(a[h][i], rs, be[i])); a[2 + h][i] = silu_half(fmaf(a[2 + h][i], rs, be[i])); }
#pragma unroll
                for (int i = 0; i < 4; i++) {
                    kp[i] = pack_bf(fmaf(a[h][2 * i], sg, a[2 + h][2 * i]), fmaf(a[h][2 * i + 1], sg, a[2 + h][2 * i + 1]));
                    sd[i] = pack_bf(fmaf(a[2 + h][2 * i], -sg, a[h][2 * i]), fmaf(a[2 + h][2 * i + 1], -sg, a[h][2 * i + 1]));
                }
                st_async(peer0 + v_off + 2 * KC_BYTES + h * 128, sd[0], sd[1], sd[2], sd[3], peer0 + BAR(BAR_RV) + 8 * gl);
                sts128(v_off + h * 128, make_uint4(kp[0], kp[1], kp[2], kp[3]));
            }
            publish(BAR(BAR_FULL) + 32 * gl, lane);
            if (tid == 256) TL(8 + conv * 8);
            if (tid == 384) TL(84 + conv);
            mbar_wait(BAR(BAR_XO), conv);
            if (conv == 0) {
#pragma unroll
                for (int i = 0; i < 4; i++) ldsm4t(u[i], SM_XB + (i >> 1) * 8192 + stg_off + (((2 * wq + (i & 1)) ^ stg_sw) << 4));
            } else {
#pragma unroll
                for (int i = 0; i < 4; i++) lds_piece(u[i], SM_XB + (i >> 1) * 8192 + (i & 1) * 2048 + img_off);
                unsigned it = 0;
                while (true) {
                    bool okn = true, okf = true;
#pragma unroll
                    for (int i = 0; i < 8; i++) { okn = okn && u[i >> 2][i & 3] != 0; okf = okf && u[2 + (i >> 2)][i & 3] != 0; }
                    if (__all_sync(0xffffffffu, (okn || !has_near) && (okf || !has_far)) || ++it > SPIN_LIMIT) break;
#pragma unroll
                    for (int i = 0; i < 4; i++) ld_unit(u[i], inbox + (i >> 1) * 512 + (i & 1) * 128);
                    if (tid == 256) TL(93);
                }
#pragma unroll
                for (int i = 0; i < 16; i++) u[i >> 2][i & 3] = ~u[i >> 2][i & 3];
            }
            if (tid == 256) TL(24 + conv * 4);
#pragma unroll
            for (int i = 0; i < 8; i++) ga[i] *= rs;
#pragma unroll
            for (int j = 0; j < 4; j++) {
                const int i4 = j ^ 2;
                const bool ok = i4 < 2 ? has_near : has_far;
                uint32_t o[4];
#pragma unroll
                for (int i = 0; i < 4; i++) {
                    const float lo = silu_half(fmaf(bf_lo(u[i4][i]), ga[2 * i], be[2 * i])), hi = silu_half(fmaf(bf_hi(u[i4][i]), ga[2 * i + 1], be[2 * i + 1]));
                    o[i] = pack_bf((ok ? lo : 0.f) - a[i4 ^ 2][2 * i], (ok ? hi : 0.f) - a[i4 ^ 2][2 * i + 1]);
                }
                if (i4 < 2) sts128(v_off + 8 * KC_BYTES + (i4 & 1) * 128, make_uint4(o[0], o[1], o[2], o[3]));
                else st_async(peer0 + v_off + 10 * KC_BYTES + (i4 & 1) * 128, o[0], o[1], o[2], o[3], peer0 + BAR(BAR_RV + 2) + 8 * gl);
            }
            publish(BAR(BAR_FULL + 8) + 32 * gl, lane);
            if (tid == 256) TL(23 + conv * 4);
            if (tid == 384) TL(88 + conv);
        }
        mbar_wait(BAR(BAR_FULL + NSTAGE - 1), 1);
#pragma unroll
        for (int i = 0; i < 4; i++) inbox[(i >> 1) * 512 + (i & 1) * 128] = make_uint4(0, 0, 0, 0);
        {
            const int oc0 = gl * 64 + ((tid & 127) >> 3), seg = lane & 7;
            __nv_bfloat16* dst = out + ((size_t)(b * C + oc0) * HW + r) * HW + seg * 8;
            const uint32_t src = oc0 * 128 + ((seg ^ (oc0 & 7)) << 4);
            mbar_wait(BAR(BAR_XR), 0);
            uint4 xr[4];
#pragma unroll
            for (int i = 0; i < 4; i++) xr[i] = lds128(SM_XA + src + i * 2048);
            asm volatile("{\n.reg .pred p;\nsetp.eq.u64 p, %0, 0;\n@p st.shared.u32 [%1], 0;\n}" ::"l"(dst), "r"(src + S0) : "memory");
            bar_sync(gl ? 1 : 6, 128 + 128);
#pragma unroll
            for (int i = 0; i < 4; i++) {
                uint4 o = lds128(SM_XB + src + i * 2048);
                asm("add.rn.bf16x2 %0, %0, %1;" : "+r"(o.x) : "r"(xr[i].x)); asm("add.rn.bf16x2 %0, %0, %1;" : "+r"(o.y) : "r"(xr[i].y));
                asm("add.rn.bf16x2 %0, %0, %1;" : "+r"(o.z) : "r"(xr[i].z)); asm("add.rn.bf16x2 %0, %0, %1;" : "+r"(o.w) : "r"(xr[i].w));
                *reinterpret_cast<uint4*>(dst + (size_t)i * 16 * HW * HW) = o;
            }
            if (tid == 384) { TL(20); TLG(21); }
        }
    } else if (warp < 4) {
        const int wq = warp;
        bar_sync(7, 160);
        asm volatile("barrier.cluster.wait.acquire.aligned;" ::: "memory");
        const float sg = rk ? 1.f : -1.f;
        float d[64];
#pragma unroll 1
        for (int conv = 0; conv < 2; conv++) {
#pragma unroll
            for (int i = 0; i < 64; i++) d[i] = 0.f;
            uint32_t hp[32];
            fence_acc(d);
            mma_stages<0>(d, hp, conv, tid, peer0, gs);
            if (conv == 0) {
                asm volatile("wgmma.fence.sync.aligned;" ::: "memory");
                wgmma128<(SM_ONES >> 4) | (8u << 16), (SM_EMB >> 4), 0, 8>(d);
                asm volatile("wgmma.commit_group.sync.aligned;" ::: "memory");
            }
            mbar_wait(BAR(BAR_M), conv);
#pragma unroll
            for (int j = 0; j < 8; j++) {
                const uint4 q = lds128(SM_M + j * 2048 + tid * 16);
                hp[4 * j] = q.x; hp[4 * j + 1] = q.y; hp[4 * j + 2] = q.z; hp[4 * j + 3] = q.w;
            }
            asm volatile("wgmma.wait_group.sync.aligned 0;" ::: "memory");
            fence_acc(d);
            if (tid == 0) TL(10 + conv * 8);
#pragma unroll
            for (int i = 0; i < 32; i++) hp[i] = pack_bf(fmaf(bf_lo(hp[i]), sg, d[2 * i]), fmaf(bf_hi(hp[i]), sg, d[2 * i + 1]));
            if (conv == 1) {
                const uint32_t obase = SM_XB + ((lane >> 4) * 8 + (lane & 7)) * 128 + (((2 * wq + ((lane >> 3) & 1)) ^ (lane & 7)) << 4);
#pragma unroll
                for (int kc = 0; kc < 8; kc++) {
                    stsm4t(obase + kc * 2048, hp[4 * kc], hp[4 * kc + 1], hp[4 * kc + 2], hp[4 * kc + 3]);
                    if (kc == 3) bar_arrive(6, 128 + 128);
                }
                bar_arrive(1, 128 + 128);
                break;
            }
#pragma unroll
            for (int g = 0; g < 4; g++) {
                float c[4] = {0.f, 0.f, 0.f, 0.f};
#pragma unroll
                for (int i = 0; i < 4; i++) stat_mma(c, hp[8 * g + 2 * i], hp[8 * g + 2 * i + 1]);
                stat_store(c, SM_RED + (g * 4 + wq) * 48, lane);
            }
            bar_sync(2, 128);
            if (wq == 0) stat_publish(SM_RED, &gs->acc2[b * LS], lane, true);
            if (tid == 0) TL(11);
            if (tid == 32) mbar_expect(BAR(BAR_M), 16384);
#pragma unroll
            for (int j = 0; j < 8; j++) {
                const uint32_t p0 = hp[(j >> 1) * 8 + (j & 1)], p1 = hp[(j >> 1) * 8 + (j & 1) + 2], p2 = hp[(j >> 1) * 8 + (j & 1) + 4], p3 = hp[(j >> 1) * 8 + (j & 1) + 6];
                if ((j >> 2) == rk) sts128(SM_XA + (j & 3) * 2048 + tid * 16, make_uint4(p0, p1, p2, p3));
                else st_async(peer0 + SM_XA + 8192 + (j & 3) * 2048 + tid * 16, p0, p1, p2, p3, peer0 + BAR(BAR_RH));
            }
            __syncwarp();
            if (lane == 0) { mbar_arrive(BAR(BAR_HW)); mbar_arrive(BAR(BAR_WEMPTY + 7)); }
            if (has_near) {
                const int oc2 = (cta & ~1) + (rk ? 2 : -2);
#pragma unroll
                for (int j = 0; j < 8; j++) {
                    uint4* outbox = gs->box + (oc2 + (j >> 2)) * 1024 + (((j >> 2) == rk) ? 512 : 0) + (j & 3) * 128 + tid;
                    *outbox = make_uint4(~hp[(j >> 1) * 8 + (j & 1)], ~hp[(j >> 1) * 8 + (j & 1) + 2], ~hp[(j >> 1) * 8 + (j & 1) + 4], ~hp[(j >> 1) * 8 + (j & 1) + 6]);
                }
            }
            if (tid == 0) TL(12);
        }
    } else if (warp < 6) {
        if (warp == 5) {
            bar_sync(5, 64);
            if (elect_one()) {
                mbar_expect(BAR(BAR_XO), 16384);
#pragma unroll
                for (int i = 0; i < 4; i++)
                    tma_x(SM_XB + i * 4096, &xmap, ((i >> 1) ^ rk) ? (r | 1) + 1 : (r & ~1) - 1, ch0 + (i & 1) * 32, BAR(BAR_XO));
            }
            __syncwarp();
#pragma unroll 1
            for (int i = 0; i < 8; i++) {
                mbar_wait(BAR(BAR_RV) + 8 * (i & 3), i >> 2);
                fence_async_smem();
                if (lane == 0) {
                    mbar_arrive(BAR(BAR_FULL + 2) + 32 * (i & 3));
                    if (i < 4) mbar_expect(BAR(BAR_RV) + 8 * i, 4096);
                    TL(64 + i);
                }
                __syncwarp();
            }
        } else {
            mbar_wait(BAR(BAR_STATS), 0);
            unsigned it = 0;
            while (!__all_sync(0xffffffffu, ld_relaxed(&gs->wcnt[(2 * NB + b) * LS]) >= (unsigned)NXTRA) && ++it < SPIN_LIMIT) __nanosleep(100);
            fence_acquire();
            float ev[4] = {0.f, 0.f, 0.f, 0.f};
#pragma unroll
            for (int j = 0; j < NXTRA; j++) {
                const uint4 ef = ld_relaxed_v4(&gs->emb[(j * NB + b) * C + lane * 4]);
                ev[0] += __uint_as_float(ef.x); ev[1] += __uint_as_float(ef.y); ev[2] += __uint_as_float(ef.z); ev[3] += __uint_as_float(ef.w);
            }
#pragma unroll
            for (int i = 0; i < 4; i++) {
                const float hi = bf_lo(pack_bf(ev[i], 0.f));
                sts128(SM_EMB + n_to_oc(lane * 4 + i) * 16, make_uint4(pack_bf(hi, ev[i] - hi), 0, 0, 0));
            }
            fence_async_smem();
            __syncwarp();
            if (lane == 0) { mbar_arrive(BAR(BAR_EMB)); TL(19); }
            mbar_wait(BAR(BAR_HW), 0);
            mbar_wait(BAR(BAR_FULL + 4), 1);
            mbar_wait(BAR(BAR_FULL + 8), 1);
            if (elect_one()) {
                mbar_expect(BAR(BAR_XR), 16384);
#pragma unroll
                for (int i = 0; i < 4; i++) tma_x(SM_XA + i * 4096, &xmap, r, b * C + i * 32, BAR(BAR_XR));
            }
        }
    } else if (warp == 6) {
        bar_sync(0, 96);
        if (lane < NSTAGE) mbar_expect(BAR(BAR_FULL) + 8 * lane, STAGE_BYTES);
        const unsigned char* wbase = gs->wt + rk * 8 * STAGE_BYTES;
        unsigned it = 0;
        {
            int g = 0;
            const int l7 = lane & 7;
            const unsigned* cnt = &gs->w1cnt[(b * 8 + ((((l7 >> 1) ^ rk) & 1) * 4 + (l7 >> 2) * 2 + (l7 & 1))) * KS];
            unsigned cv = ld_relaxed(cnt);
#pragma unroll 1
            while (g <= NS) {
                unsigned ready = __ballot_sync(0xffffffffu, (lane < 8 ? cv & 0xffffu : cv >> 16) >= 16u);
                if ((ready >> 8 & 0xff) != 0xff) ready &= 0xff;
                if (ready != ~0u) cv = ld_relaxed(cnt);
                ready >>= g;
                if (++it > SPIN_LIMIT) ready = ~0u;
                if (!(ready & 1)) continue;
                fence_async_global();
                if (lane == 0) TL(g ? 3 : 6);
#pragma unroll 1
                for (; (ready & 1) && g <= NS; g++, ready >>= 1)
                    if (g < NS && elect_one())
                        bulk_g2s(S0 + SM_W + g * STAGE_BYTES, wbase + ((((g >> 1) ^ rk) & 1) * 4 + (g >> 2) * 2 + (g & 1)) * STAGE_BYTES, STAGE_BYTES,
                                 S0 + BAR(BAR_FULL) + 8 * g);
            }
        }
#pragma unroll 1
        for (int q = 2; q < 8; q++) {
            const unsigned char* wsrc = wbase + ((q >> 1) * 16 + (q & 1) * 2) * STAGE_BYTES;
            const uint32_t par = ((q >> 1) - 1) & 1;
            if (q == 4) {
                it = 0;
                while (!__all_sync(0xffffffffu, ld_relaxed(&gs->wcnt[(NB + b) * LS]) == NCTA * 0x10001u) && ++it < SPIN_LIMIT) {}
                fence_acquire();
                fence_async_global();
                if (lane == 0) { mbar_arrive(BAR(BAR_EMB)); TL(2); }
            }
#pragma unroll
            for (int i = 0; i < 4; i++) {
                mbar_wait(BAR(BAR_WEMPTY + i) + 32 * (q & 1), par);
                if (i == 0 && (q == 4 || q == 6)) {
                    if ((lane >> 3) == (q - 4) / 2) mbar_expect(BAR(BAR_FULL) + 8 * lane, STAGE_BYTES);
                    __syncwarp();
                }
                if (elect_one())
                    bulk_g2s(S0 + SM_W + ((q & 1) * 4 + i) * STAGE_BYTES, wsrc + ((((i >> 1) ^ rk) & 1) * 4 + (i & 1)) * STAGE_BYTES, STAGE_BYTES,
                             S0 + BAR(BAR_FULL + i) + 32 * (q & 3));
            }
        }
    } else {
        bar_sync(0, 96);
#pragma unroll 1
        for (int conv = 0; conv < 2; conv++) {
            if (conv == 1) mbar_wait(BAR(BAR_HW), 0);
            const float* asrc = (conv ? gs->acc2 : gs->acc1) + b * LS + (rk * 2 + (lane & 1)) * 4;
            unsigned it = 0;
#pragma unroll 1
            while (true) {
                const uint4 f = ld_relaxed_v4(asrc);
                const bool ok = ((f.x == 0x42800000u) & (f.w == 0x42800000u)) || ++it > SPIN_LIMIT;
                if (ok && lane < 2) {
                    const float inv_n = 1.0f / (32.0f * HW * HW);
                    const float mean = __uint_as_float(f.y) * inv_n;
                    float rs;
                    asm("rsqrt.approx.ftz.f32 %0, %1;" : "=f"(rs) : "f"(fmaxf(fmaf(-mean, mean, __uint_as_float(f.z) * inv_n), 0.f) + 1e-5f));
                    asm volatile("st.shared.v2.f32 [%0], {%1,%2};" ::"r"(S0 + SM_GST + conv * 16 + lane * 8), "f"(rs == 0.f ? 1.2e-38f : rs), "f"(mean * rs) : "memory");
                }
                if (__all_sync(0xffffffffu, ok)) break;
            }
            if (lane == 0) { if (conv == 0) mbar_arrive(BAR(BAR_STATS)); TL(7 + conv * 8); }
        }
        { const unsigned c1 = clock32(); while (clock32() - c1 < FDELAY) {} }
        if (elect_one()) {
            mbar_expect(BAR(BAR_XO), 16384);
            bulk_g2s(S0 + SM_XB, gs->box + cta * 1024, 16384, S0 + BAR(BAR_XO));
        }
        if (r == 0) {
            if (lane < 16) gs->acc1[b * LS + lane] = 0.f;
            if (lane < 3) gs->wcnt[(lane * NB + b) * LS] = 0;
            if (lane < 8) gs->w1cnt[(b * 8 + lane) * KS] = 0;
        }
    }
}

}

extern "C" void kernel_launch(void* const* d_in, const int* in_sizes, int n_in, void* d_out, int out_size) {
    (void)in_sizes; (void)n_in; (void)out_size;
    typedef CUresult (*EncodeFn)(CUtensorMap*, CUtensorMapDataType, cuuint32_t, void*, const cuuint64_t*, const cuuint64_t*,
                                 const cuuint32_t*, const cuuint32_t*, CUtensorMapInterleave, CUtensorMapSwizzle,
                                 CUtensorMapL2promotion, CUtensorMapFloatOOBfill);
    static Scratch* gs = nullptr;
    static EncodeFn encode = nullptr;
    if (!gs) {
        cudaFuncSetAttribute(resblock_kernel, cudaFuncAttributeMaxDynamicSharedMemorySize, SM_TOTAL);
        cudaGetSymbolAddress((void**)&gs, g_scratch);
        cudaDriverEntryPointQueryResult qr;
        cudaGetDriverEntryPoint("cuTensorMapEncodeTiled", (void**)&encode, cudaEnableDefault, &qr);
    }
    CUtensorMap xmap;
    const cuuint64_t dims[3] = {HW, HW, NB * C}, strides[2] = {HW * 2, HW * HW * 2};
    const cuuint32_t box[3] = {HW, 1, 32}, es[3] = {1, 1, 1};
    encode(&xmap, CU_TENSOR_MAP_DATA_TYPE_BFLOAT16, 3, d_in[0], dims, strides, box, es, CU_TENSOR_MAP_INTERLEAVE_NONE,
           CU_TENSOR_MAP_SWIZZLE_128B, CU_TENSOR_MAP_L2_PROMOTION_NONE, CU_TENSOR_MAP_FLOAT_OOB_FILL_NONE);
    resblock_kernel<<<NCTA + NXTRA, NTHREADS, SM_TOTAL>>>(
        (const __nv_bfloat16*)d_in[4], (const __nv_bfloat16*)d_in[0], (const __nv_bfloat16*)d_in[1],
        (const __nv_bfloat16*)d_in[2], (const __nv_bfloat16*)d_in[3], (const __nv_bfloat16*)d_in[5],
        (const __nv_bfloat16*)d_in[6], (const __nv_bfloat16*)d_in[7], (const __nv_bfloat16*)d_in[8],
        (__nv_bfloat16*)d_out, gs, xmap);
}
```

```cpp
#include <cuda_runtime.h>
#include <cuda.h>
#include <cuda_bf16.h>
#include <stdint.h>

namespace {

constexpr int C = 128, HW = 64, NB = 2, E = 768;
constexpr int NCTA = NB * HW;
constexpr int NXTRA = 4;
constexpr int NTHREADS = 16 * 32;
constexpr int CH_PITCH = 66 * 16;
constexpr int KC_BYTES = 2 * CH_PITCH;
constexpr int STAGE_BYTES = 12288;
constexpr int NSTAGE = 16;
constexpr int NS = 8;
#define XDELAY 300
#define XSTAG 800
#define XSTAG2 100
#define SDELAY 600
#define W2DELAY 2400
#define MLOAD 15
#define ODELAY 3600
#define FDELAY 200

constexpr uint32_t SMEM_BASE = 0x400;
constexpr uint32_t SM_XA = SMEM_BASE;
constexpr uint32_t SM_XB = SM_XA + 16384;
constexpr uint32_t SM_M = SM_XB + 16384;
constexpr uint32_t SM_V = SM_M + 16384;
constexpr uint32_t SM_W = SM_V + NSTAGE * KC_BYTES + 128;
constexpr uint32_t SM_COEF = SM_W + NS * STAGE_BYTES;
constexpr uint32_t SM_GST = SM_COEF + 2048;
constexpr uint32_t SM_EMB = SM_GST + 128;
constexpr uint32_t SM_ONES = SM_EMB + 2048;
constexpr uint32_t SM_RED = SM_ONES + 256;
constexpr uint32_t SM_BNC = SM_RED + 1024;
constexpr uint32_t SM_BAR = SM_BNC + 2 * 2304;
constexpr int BAR_FULL = 0, BAR_WEMPTY = NSTAGE, BAR_HW = BAR_WEMPTY + NS, BAR_STATS = BAR_HW + 1, BAR_EMB = BAR_STATS + 1,
              BAR_RV = BAR_EMB + 1  , BAR_M = BAR_RV + 4, BAR_RH = BAR_M + 1, BAR_XO = BAR_RH + 1, BAR_XR = BAR_XO + 1,
              BAR_X = BAR_XR + 1  , NBAR = BAR_X + 4;
constexpr int SM_TOTAL = SM_BAR + NBAR * 8 - SMEM_BASE;
static_assert(SM_TOTAL <= 232448, "smem");
__host__ __device__ constexpr uint32_t BAR(int i) { return SM_BAR + 8 * i; }

constexpr unsigned SPIN_LIMIT = 1u << 16;
constexpr int LS = 1056, KS = 32;

struct Scratch {
    float acc1[NB * LS];
    float acc2[NB * LS];
    unsigned wcnt[3 * NB * LS];
    unsigned w1cnt[NB * 8 * KS];
    float emb[NXTRA * NB * C];
    alignas(1024) unsigned char wt[2 * 32 * STAGE_BYTES];
    uint4 box[NCTA * 1024];
};
__device__ __align__(1024) Scratch g_scratch;
#define TL(i) do {} while (0)
#define TLG(i) do {} while (0)

__device__ __forceinline__ unsigned clock32() { unsigned c; asm volatile("mov.u32 %0, %%clock;" : "=r"(c)); return c; }
__device__ __forceinline__ uint32_t mapa(uint32_t a, uint32_t rank) {
    uint32_t d;
    asm("mapa.shared::cluster.u32 %0, %1, %2;" : "=r"(d) : "r"(a), "r"(rank));
    return d;
}
#define S0 mapa(0, blockIdx.x & 1)
__device__ __forceinline__ void mbar_init(uint32_t bar, int cnt) {
    asm volatile("mbarrier.init.shared::cta.b64 [%0], %1;" ::"r"(bar + S0), "r"(cnt) : "memory");
}
__device__ __forceinline__ void mbar_arrive(uint32_t bar) {
    asm volatile("mbarrier.arrive.shared::cta.b64 _, [%0];" ::"r"(bar + S0) : "memory");
}
__device__ __forceinline__ void mbar_expect(uint32_t bar, uint32_t bytes) {
    asm volatile("mbarrier.arrive.expect_tx.shared::cta.b64 _, [%0], %1;" ::"r"(bar + S0), "r"(bytes) : "memory");
}
__device__ __forceinline__ bool mbar_try(uint32_t bar, uint32_t par) {
    uint32_t ok;
    asm volatile("{\n.reg .pred p;\nmbarrier.try_wait.parity.shared::cta.b64 p, [%1], %2;\nselp.u32 %0, 1, 0, p;\n}"
                 : "=r"(ok) : "r"(bar + S0), "r"(par) : "memory");
    return ok;
}
__device__ __forceinline__ bool mbar_test(uint32_t bar, uint32_t par) {
    uint32_t ok;
    asm volatile("{\n.reg .pred p;\nmbarrier.test_wait.parity.shared::cta.b64 p, [%1], %2;\nselp.u32 %0, 1, 0, p;\n}"
                 : "=r"(ok) : "r"(bar + S0), "r"(par) : "memory");
    return ok;
}
__device__ __forceinline__ void mbar_wait(uint32_t bar, uint32_t par) {
    unsigned it = 0;
#pragma unroll 1
    while (!mbar_try(bar, par) && ++it < SPIN_LIMIT) {}
}
__device__ __forceinline__ bool elect_one() {
    uint32_t p;
    asm volatile("{\n.reg .pred p;\nelect.sync _|p, 0xffffffff;\nselp.u32 %0, 1, 0, p;\n}" : "=r"(p));
    return p;
}
__device__ __forceinline__ void fence_async_smem() { asm volatile("fence.proxy.async.shared::cta;" ::: "memory"); }
__device__ __forceinline__ void fence_async_global() { asm volatile("fence.proxy.async.global;" ::: "memory"); }
__device__ __forceinline__ void fence_acquire() { asm volatile("fence.acquire.gpu;" ::: "memory"); }
__device__ __forceinline__ void bar_sync(int id, int n) { asm volatile("bar.sync %0, %1;" ::"r"(id), "r"(n) : "memory"); }
__device__ __forceinline__ void bar_arrive(int id, int n) { asm volatile("bar.arrive %0, %1;" ::"r"(id), "r"(n) : "memory"); }
__device__ __forceinline__ void bulk_g2s(uint32_t dst, const void* src, uint32_t bytes, uint32_t bar) {
    asm volatile("cp.async.bulk.shared::cluster.global.mbarrier::complete_tx::bytes [%0], [%1], %2, [%3];"
                 ::"r"(dst), "l"(src), "r"(bytes), "r"(bar) : "memory");
}
__device__ __forceinline__ void tma_x(uint32_t dst, const CUtensorMap* tm, int row, int ch, uint32_t bar) {
    asm volatile("cp.async.bulk.tensor.3d.shared::cluster.global.mbarrier::complete_tx::bytes [%0], [%1, {%2, %3, %4}], [%5];"
                 ::"r"(dst + S0), "l"(tm), "r"(0), "r"(row), "r"(ch), "r"(bar + S0) : "memory");
}
__device__ __forceinline__ uint4 ld_relaxed_v4(const void* p) {
    uint4 v;
    asm volatile("ld.relaxed.gpu.global.v4.u32 {%0,%1,%2,%3}, [%4];" : "=r"(v.x), "=r"(v.y), "=r"(v.z), "=r"(v.w) : "l"(p) : "memory");
    return v;
}
__device__ __forceinline__ unsigned ld_relaxed(const void* p) {
    unsigned v;
    asm volatile("ld.relaxed.gpu.global.u32 %0, [%1];" : "=r"(v) : "l"(p) : "memory");
    return v;
}
__device__ __forceinline__ void red_add4(float* p, float a, float b, float c, float d) {
    asm volatile("red.relaxed.gpu.global.add.v4.f32 [%0], {%1,%2,%3,%4};" ::"l"(p), "f"(a), "f"(b), "f"(c), "f"(d) : "memory");
}
__device__ __forceinline__ void sts128(uint32_t a, uint4 v) {
    asm volatile("st.shared.v4.u32 [%0], {%1,%2,%3,%4};" ::"r"(a + S0), "r"(v.x), "r"(v.y), "r"(v.z), "r"(v.w) : "memory");
}
__device__ __forceinline__ void sts128f(uint32_t a, float4 v) {
    asm volatile("st.shared.v4.f32 [%0], {%1,%2,%3,%4};" ::"r"(a + S0), "f"(v.x), "f"(v.y), "f"(v.z), "f"(v.w) : "memory");
}
__device__ __forceinline__ void sts32f(uint32_t a, float v) { asm volatile("st.shared.f32 [%0], %1;" ::"r"(a + S0), "f"(v) : "memory"); }
__device__ __forceinline__ uint4 lds128(uint32_t a) {
    uint4 v;
    asm volatile("ld.shared.v4.u32 {%0,%1,%2,%3}, [%4];" : "=r"(v.x), "=r"(v.y), "=r"(v.z), "=r"(v.w) : "r"(a + S0) : "memory");
    return v;
}
__device__ __forceinline__ float4 lds128f(uint32_t a) {
    float4 v;
    asm volatile("ld.shared.v4.f32 {%0,%1,%2,%3}, [%4];" : "=f"(v.x), "=f"(v.y), "=f"(v.z), "=f"(v.w) : "r"(a + S0) : "memory");
    return v;
}
__device__ __forceinline__ float2 lds64f(uint32_t a) {
    float2 v;
    asm volatile("ld.shared.v2.f32 {%0,%1}, [%2];" : "=f"(v.x), "=f"(v.y) : "r"(a + S0) : "memory");
    return v;
}
__device__ __forceinline__ float bf_lo(uint32_t u) { return __uint_as_float(u << 16); }
__device__ __forceinline__ float bf_hi(uint32_t u) { return __uint_as_float(u & 0xffff0000u); }
__device__ __forceinline__ uint32_t pack_bf(float lo, float hi) {
    uint32_t r;
    asm("cvt.rn.bf16x2.f32 %0, %1, %2;" : "=r"(r) : "f"(hi), "f"(lo));
    return r;
}
__device__ __forceinline__ float tanh_fast(float x) {
    float r;
    asm("tanh.approx.f32 %0, %1;" : "=f"(r) : "f"(x));
    return r;
}
__device__ __forceinline__ float silu_half(float h) { return fmaf(h, tanh_fast(h), h); }
__device__ __forceinline__ void ldsm4(uint32_t (&u)[4], uint32_t a) {
    asm volatile("ldmatrix.sync.aligned.m8n8.x4.shared.b16 {%0,%1,%2,%3}, [%4];"
                 : "=r"(u[0]), "=r"(u[1]), "=r"(u[2]), "=r"(u[3]) : "r"(a + S0) : "memory");
}
__device__ __forceinline__ void ldsm4t(uint32_t (&u)[4], uint32_t a) {
    asm volatile("ldmatrix.sync.aligned.m8n8.x4.trans.shared.b16 {%0,%1,%2,%3}, [%4];"
                 : "=r"(u[0]), "=r"(u[1]), "=r"(u[2]), "=r"(u[3]) : "r"(a + S0) : "memory");
}
__device__ __forceinline__ void stsm4(uint32_t a, uint32_t p0, uint32_t p1, uint32_t p2, uint32_t p3) {
    asm volatile("stmatrix.sync.aligned.m8n8.x4.shared.b16 [%0], {%1,%2,%3,%4};" ::"r"(a + S0), "r"(p0), "r"(p1), "r"(p2), "r"(p3) : "memory");
}
__device__ __forceinline__ void stsm4t(uint32_t a, uint32_t p0, uint32_t p1, uint32_t p2, uint32_t p3) {
    asm volatile("stmatrix.sync.aligned.m8n8.x4.trans.shared.b16 [%0], {%1,%2,%3,%4};" ::"r"(a + S0), "r"(p0), "r"(p1), "r"(p2), "r"(p3) : "memory");
}

#define R8(o) "+f"(d[o]), "+f"(d[o + 1]), "+f"(d[o + 2]), "+f"(d[o + 3]), "+f"(d[o + 4]), "+f"(d[o + 5]), "+f"(d[o + 6]), "+f"(d[o + 7])
template <uint32_t ALO, uint32_t BLO, uint64_t AHI = 8, uint64_t BHI = 48>
__device__ __forceinline__ void wgmma128(float (&d)[64]) {
    asm volatile(
        "wgmma.mma_async.sync.aligned.m64n128k16.f32.bf16.bf16 "
        "{%0,%1,%2,%3,%4,%5,%6,%7,%8,%9,%10,%11,%12,%13,%14,%15,%16,%17,%18,%19,%20,%21,%22,%23,%24,%25,%26,%27,%28,%29,%30,%31,"
        "%32,%33,%34,%35,%36,%37,%38,%39,%40,%41,%42,%43,%44,%45,%46,%47,%48,%49,%50,%51,%52,%53,%54,%55,%56,%57,%58,%59,%60,%61,%62,%63},"
        " %64, %65, 1, 1, 1, 0, 0;"
        : R8(0), R8(8), R8(16), R8(24), R8(32), R8(40), R8(48), R8(56)
        : "l"((AHI << 32) | ALO), "l"((BHI << 32) | BLO));
}
__device__ __forceinline__ void stat_mma(float (&c)[4], uint32_t p, uint32_t q) {
    asm("mma.sync.aligned.m16n8k16.row.col.f32.bf16.bf16.f32 {%0,%1,%2,%3}, {%4,%5,%6,%5}, {%4,%6}, {%0,%1,%2,%3};"
        : "+f"(c[0]), "+f"(c[1]), "+f"(c[2]), "+f"(c[3]) : "r"(p), "r"(0x3f803f80u), "r"(q));
}
__device__ __forceinline__ void stat_store(const float (&c)[4], uint32_t dst, int lane) {
    const int g = lane >> 2, t = lane & 3;
    if (t == (g >> 1)) sts32f(dst + g * 4, (g & 1) ? c[1] : c[0]);
    if (g == 7) sts32f(dst + 32 + t * 4, c[2] + c[3]);
}
__device__ __forceinline__ float sum4(float4 v) { return (v.x + v.y) + (v.z + v.w); }
__device__ __forceinline__ void stat_publish(uint32_t src, float* acc, int lane, bool real) {
    const uint32_t a = src + (lane & 15) * 48;
    float q = sum4(lds128f(a)) + sum4(lds128f(a + 16)), sm = sum4(lds128f(a + 32));
    q += __shfl_xor_sync(0xffffffffu, q, 1); sm += __shfl_xor_sync(0xffffffffu, sm, 1);
    q += __shfl_xor_sync(0xffffffffu, q, 2); sm += __shfl_xor_sync(0xffffffffu, sm, 2);
    if (real && (lane & 19) == 0) red_add4(acc + lane, 1.f, sm, q, 1.f);
}
__device__ __forceinline__ void fence_acc(float (&d)[64]) {
#pragma unroll
    for (int i = 0; i < 64; i++) asm volatile("" : "+f"(d[i])::"memory");
}
__device__ __forceinline__ void ld_unit(uint32_t (&u)[4], const uint4* p) {
    asm volatile("ld.relaxed.gpu.global.v4.u32 {%0,%1,%2,%3}, [%4];" : "=r"(u[0]), "=r"(u[1]), "=r"(u[2]), "=r"(u[3]) : "l"(p) : "memory");
}

__device__ __forceinline__ void st_async(uint32_t dst, uint32_t a, uint32_t b, uint32_t c, uint32_t d, uint32_t bar) {
    asm volatile("st.async.shared::cluster.mbarrier::complete_tx::bytes.v4.b32 [%0], {%1,%2,%3,%4}, [%5];"
                 ::"r"(dst), "r"(a), "r"(b), "r"(c), "r"(d), "r"(bar) : "memory");
}
template <int S>
__device__ __forceinline__ void mma_stages(float (&d)[64], uint32_t (&hp)[32], int conv, int tid, uint32_t peer0, Scratch* gs) {
    constexpr uint32_t A = ((SM_V + S * KC_BYTES + 16) >> 4) | ((CH_PITCH >> 4) << 16);
    constexpr uint32_t B = ((SM_W + (S % NS) * STAGE_BYTES) >> 4) | (8u << 16);
    if (S == 0) mbar_wait(BAR(BAR_FULL), conv);
    constexpr uint32_t NEXT = S + 1 < NSTAGE ? BAR(BAR_FULL + S + 1) : BAR(BAR_EMB);
    const int npar = S + 1 < NSTAGE ? conv : 0;
    const bool next_ok = mbar_test(NEXT, npar);
    if ((S & 7) == 0 && tid == 0) TL(32 + conv * 16 + S);
    asm volatile("wgmma.fence.sync.aligned;" ::: "memory");
#define SEND_M(j) st_async(peer0 + SM_M + (j) * 2048 + tid * 16, hp[4 * (j)], hp[4 * (j) + 1], hp[4 * (j) + 2], hp[4 * (j) + 3], peer0 + BAR(BAR_M))
    wgmma128<A, B>(d);
    if (S == 8 || S == 9) { SEND_M((S & 1) * 4); SEND_M((S & 1) * 4 + 1); }
    wgmma128<A + 1, B + 16>(d);
    if (S == 8 || S == 9) { SEND_M((S & 1) * 4 + 2); SEND_M((S & 1) * 4 + 3); }
    wgmma128<A + 2, B + 32>(d);
    asm volatile("wgmma.commit_group.sync.aligned;" ::: "memory");
    if ((S & 7) != 0) {
        asm volatile("wgmma.wait_group.sync.aligned 1;" ::: "memory");
        if ((tid & 31) == 0) mbar_arrive(BAR(BAR_WEMPTY + (S - 1) % NS));
    }
    if (S == 7) {
        asm volatile("wgmma.wait_group.sync.aligned 0;" ::: "memory");
        fence_acc(d);
#pragma unroll
        for (int i = 0; i < 32; i++) hp[i] = pack_bf(d[2 * i], d[2 * i + 1]);
        fence_acc(d);
        if ((tid & 31) == 0) mbar_arrive(BAR(BAR_WEMPTY + 7));
    }
    if (!next_ok) mbar_wait(NEXT, npar);
    if (S == MLOAD) {
        mbar_wait(BAR(BAR_M), conv);
#pragma unroll
        for (int j = 0; j < 8; j++) {
            const uint4 q = lds128(SM_M + j * 2048 + tid * 16);
            hp[4 * j] = q.x; hp[4 * j + 1] = q.y; hp[4 * j + 2] = q.z; hp[4 * j + 3] = q.w;
        }
    }
    if constexpr (S + 1 < NSTAGE) mma_stages<S + 1>(d, hp, conv, tid, peer0, gs);
}

__device__ __forceinline__ int wblk_kc(int cta) { const int i = cta >> 4; return (i & 1) | ((i & 2) << 1) | ((i & 4) >> 1); }
__device__ __forceinline__ int n_to_oc(int n) { return (n & ~31) | ((n & 6) << 2) | ((n >> 2) & 6) | (n & 1); }
__device__ __forceinline__ void weight_load(uint4 (&t)[5], const __nv_bfloat16* w, int cta, int lane, bool perm) {
    const int n = (cta & 15) * 8 + (lane >> 2);
    const char* base = reinterpret_cast<const char*>(w) + (uint32_t)(((perm ? n_to_oc(n) : n) * 8 + wblk_kc(cta)) * 288 + (lane & 3) * 16);
#pragma unroll
    for (int k = 0; k < 5; k++)
        if (k < 4 || !(lane & 2)) t[k] = __ldg(reinterpret_cast<const uint4*>(base + k * 64));
}
__device__ __forceinline__ void st_global64(void* p, uint32_t a, uint32_t b) { asm volatile("st.global.v2.u32 [%0], {%1,%2};" ::"l"(p), "r"(a), "r"(b) : "memory"); }
__device__ __forceinline__ void weight_block(uint32_t bounce, unsigned char* wt, int cta, int lane, unsigned* cnt) {
    const unsigned opaque_one = gridDim.y;
    unsigned char* piece = wt + wblk_kc(cta) * STAGE_BYTES + (cta & 15) * 768;
    uint32_t v[18];
#pragma unroll
    for (int i = 0; i < 9; i++) {
        const float2 q = lds64f(bounce + (lane & 7) * 288 + (lane >> 3) * 72 + i * 8);
        v[2 * i] = __float_as_uint(q.x); v[2 * i + 1] = __float_as_uint(q.y);
    }
    unsigned char* dst = piece + (lane >> 4) * 128 + (lane & 7) * 16 + ((lane >> 3) & 1) * 8;
#pragma unroll
    for (int kx = 0; kx < 3; kx++) {
        float u1[4], u2[4];
#pragma unroll
        for (int c = 0; c < 4; c++) {
            const int i0 = 9 * c + kx, i1 = i0 + 3, i2 = i0 + 6;
            const float g0 = (i0 & 1) ? bf_hi(v[i0 >> 1]) : bf_lo(v[i0 >> 1]);
            const float g1 = (i1 & 1) ? bf_hi(v[i1 >> 1]) : bf_lo(v[i1 >> 1]);
            const float g2 = (i2 & 1) ? bf_hi(v[i2 >> 1]) : bf_lo(v[i2 >> 1]);
            const float t = 0.5f * (g0 + g2);
            u1[c] = fmaf(g1, 0.5f, t); u2[c] = fmaf(g1, -0.5f, t);
        }
        st_global64(dst + kx * 256, pack_bf(u1[0], u1[1]), pack_bf(u1[2], u1[3]));
        st_global64(dst + 8 * STAGE_BYTES + kx * 256, pack_bf(u2[0], u2[1]), pack_bf(u2[2], u2[3]));
    }
    const unsigned char* rb = piece + (lane < 24 ? lane : 0) * 32;
    const unsigned r0 = ld_relaxed(rb), r1 = ld_relaxed(rb + 8 * STAGE_BYTES);
#pragma unroll
    for (int j = 0; j < 6; j++) {
        const int tap = (j / 3) * 6 + j % 3;
        uint32_t o[2];
#pragma unroll
        for (int m = 0; m < 2; m++) {
            const int i0 = 18 * m + tap, i1 = i0 + 9;
            o[m] = __byte_perm(v[i0 >> 1], v[i1 >> 1], ((i0 & 1) ? 0x32u : 0x10u) | ((i1 & 1) ? 0x7600u : 0x5400u));
        }
        st_global64(dst + (16 + (j / 3) * 8) * STAGE_BYTES + (j % 3) * 256, o[0], o[1]);
    }
    const unsigned r2 = ld_relaxed(rb + 16 * STAGE_BYTES), r3 = ld_relaxed(rb + 24 * STAGE_BYTES);
    const unsigned i0 = __any_sync(0xffffffffu, (r0 ^ r1) == 0x9e3779b9u) ? opaque_one : 1u;
    if (lane < 2) asm volatile("red.relaxed.gpu.global.add.u32 [%0], %1;" ::"l"(cnt), "r"(i0) : "memory");
    const unsigned i1 = __any_sync(0xffffffffu, (r2 ^ r3) == 0x9e3779b9u) ? opaque_one : 1u;
    if (lane < 2) asm volatile("red.relaxed.gpu.global.add.u32 [%0], %1;" ::"l"(cnt), "r"(i1 << 16) : "memory");
}
__device__ __forceinline__ void publish(uint32_t bar, int lane) {
    fence_async_smem();
    __syncwarp();
    if (lane == 0) mbar_arrive(bar);
}
__device__ __forceinline__ void lds_piece(uint32_t (&u)[4], uint32_t a) {
    const uint4 q = lds128(a);
    u[0] = q.x; u[1] = q.y; u[2] = q.z; u[3] = q.w;
}
__device__ __noinline__ void side_jobs(const __nv_bfloat16* __restrict__ t_emb, const __nv_bfloat16* __restrict__ w_emb,
                                       const __nv_bfloat16* __restrict__ w2, Scratch* __restrict__ gs, unsigned clk0) {
    const int tid = threadIdx.x, warp = tid >> 5, lane = tid & 31, j = blockIdx.x;
    float tv = 0.f;
    if (lane < 24) tv = __bfloat162float(t_emb[(lane / 12) * E + j * 192 + warp * 12 + lane % 12]);
    if (tid == 0) {
        mbar_init(BAR(0), 1);
        mbar_expect(BAR(0), 192 * C * 2);
        fence_async_smem();
        while (clock32() - clk0 < SDELAY) {}
#pragma unroll
        for (int i = 0; i < 4; i++)
            asm volatile("cp.async.bulk.prefetch.L2.global [%0], 18432;" ::"l"(reinterpret_cast<const char*>(w2) + (j * 4 + i) * 18432) : "memory");
#pragma unroll
        for (int i = 0; i < 4; i++) bulk_g2s(S0 + SM_W + i * 12288, w_emb + (j * 192 + i * 48) * C, 12288, S0 + BAR(0));
    }
    if (j == 0 && tid < 32) gs->acc2[(tid >> 4) * LS + (tid & 15)] = 0.f;
    const float sv = silu_half(0.5f * tv);
    __syncthreads();
    mbar_wait(BAR(0), 0);
    float acc[8] = {0.f, 0.f, 0.f, 0.f, 0.f, 0.f, 0.f, 0.f};
#pragma unroll
    for (int i = 0; i < 12; i++) {
        const float2 wq = lds64f(SM_W + (warp * 12 + i) * 256 + lane * 8);
        const uint32_t wx = __float_as_uint(wq.x), wy = __float_as_uint(wq.y);
#pragma unroll
        for (int bb = 0; bb < 2; bb++) {
            const float sx = __shfl_sync(0xffffffffu, sv, bb * 12 + i);
            acc[4 * bb + 0] = fmaf(sx, bf_lo(wx), acc[4 * bb + 0]); acc[4 * bb + 1] = fmaf(sx, bf_hi(wx), acc[4 * bb + 1]);
            acc[4 * bb + 2] = fmaf(sx, bf_lo(wy), acc[4 * bb + 2]); acc[4 * bb + 3] = fmaf(sx, bf_hi(wy), acc[4 * bb + 3]);
        }
    }
    sts128f(SM_V + warp * 1024 + lane * 16, make_float4(acc[0], acc[1], acc[2], acc[3]));
    sts128f(SM_V + warp * 1024 + 512 + lane * 16, make_float4(acc[4], acc[5], acc[6], acc[7]));
    __syncthreads();
    if (tid < 128) {
        float2 sum = make_float2(0.f, 0.f);
#pragma unroll
        for (int w = 0; w < 16; w++) { const float2 p = lds64f(SM_V + w * 1024 + tid * 8); sum.x += p.x; sum.y += p.y; }
        *reinterpret_cast<float2*>(&gs->emb[j * NB * C + tid * 2]) = sum;
        bar_sync(1, 128);
        if (tid < 2) asm volatile("red.release.gpu.global.add.u32 [%0], 1;" ::"l"(&gs->wcnt[(2 * NB + tid) * LS]) : "memory");
    }
}

__global__ void __cluster_dims__(2, 1, 1) __launch_bounds__(NTHREADS, 1)
resblock_kernel(const __nv_bfloat16* __restrict__ w1, const __nv_bfloat16* __restrict__ x,
                const __nv_bfloat16* __restrict__ t_emb, const __nv_bfloat16* __restrict__ g1,
                const __nv_bfloat16* __restrict__ be1, const __nv_bfloat16* __restrict__ w_emb,
                const __nv_bfloat16* __restrict__ g2, const __nv_bfloat16* __restrict__ be2,
                const __nv_bfloat16* __restrict__ w2, __nv_bfloat16* __restrict__ out, Scratch* __restrict__ gs,
                const __grid_constant__ CUtensorMap xmap) {
    const unsigned clk0 = clock32();
    if (threadIdx.x == 480 && blockIdx.x >= NXTRA) TLG(1);
    const int tid = threadIdx.x, lane = tid & 31;
    const int cta = blockIdx.x - NXTRA, b = cta >> 6, r = cta & 63, rk = cta & 1;
    uint4 v[5];
    if (tid < 32) weight_load(v, w1, cta & (NCTA - 1), lane, true);
    uint4 xv[8];
    const int ch0 = (b & 1) * C + rk * 64;
    if (tid >= 32 && tid < 96) {
        const char* src = reinterpret_cast<const char*>(x) + (uint32_t)(((ch0 + (lane >> 3)) * HW + (r ^ (tid >> 6))) * HW * 2 + (lane & 7) * 16);
        while (clock32() - clk0 < XDELAY + (tid >> 6) * XSTAG2) {}
#pragma unroll
        for (int i = 0; i < 8; i++) xv[i] = __ldg(reinterpret_cast<const uint4*>(src + i * (4 * HW * HW * 2)));
    }
    const int warp = __shfl_sync(0xffffffffu, tid >> 5, 0);
    if (cta < 0) { side_jobs(t_emb, w_emb, w2, gs, clk0); return; }

    if (warp != 4) asm volatile("barrier.cluster.arrive.relaxed.aligned;" ::: "memory");
    const bool has_near = r != 0 && r != HW - 1, has_far = r != 1 && r != HW - 2;
    const uint32_t peer0 = mapa(0, rk ^ 1);
    if (warp == 1 || warp == 2 || warp == 3 || warp == 5) {
        const int i = warp < 4 ? warp - 1 : 3, gl = i >> 1, row = i & 1;
        const uint32_t tile = SM_XA + row * 8192 + gl * 4096;
        if (elect_one()) {
            if (gl) asm volatile("prefetch.tensormap [%0];" ::"l"(&xmap) : "memory");
            mbar_init(BAR(BAR_X) + 8 * i, 1);
            if (gl) { mbar_expect(BAR(BAR_X) + 8 * i, 4096); fence_async_smem(); }
        }
        __syncwarp();
        bar_arrive(4, 256 + 32 + 128);
        if (gl) {
            while (clock32() - clk0 < XDELAY + XSTAG + row * XSTAG2) {}
            if (elect_one()) tma_x(tile, &xmap, r ^ row, ch0 + 32, BAR(BAR_X) + 8 * i);
            __syncwarp();
            mbar_wait(BAR(BAR_X) + 8 * i, 0);
#pragma unroll
            for (int k = 0; k < 8; k++) xv[k] = lds128(tile + k * 512 + lane * 16);
        }
        float c[8][4];
#pragma unroll
        for (int k = 0; k < 8; k++) {
            c[k][0] = c[k][1] = c[k][2] = c[k][3] = 0.f;
            stat_mma(c[k], xv[k].x, xv[k].y); stat_mma(c[k], xv[k].z, xv[k].w);
        }
#pragma unroll
        for (int k = 0; k < 4; k++) c[0][k] = ((c[0][k] + c[1][k]) + (c[2][k] + c[3][k])) + ((c[4][k] + c[5][k]) + (c[6][k] + c[7][k]));
        stat_store(c[0], SM_RED + i * 48, lane);
        __syncwarp();
        if (lane == 0) {
            const uint32_t a = SM_RED + i * 48;
            red_add4(&gs->acc1[b * LS + (rk * 2 + gl) * 4], 1.f, sum4(lds128f(a + 32)), sum4(lds128f(a)) + sum4(lds128f(a + 16)), 1.f);
            TL(74 + i);
        }
        if (!gl) {
#pragma unroll
            for (int k = 0; k < 8; k++)
                sts128(tile + k * 512 + (lane >> 3) * 128 + (((lane & 7) ^ ((lane >> 3) + 4 * (k & 1))) << 4), xv[k]);
            __syncwarp();
            if (lane == 0) mbar_arrive(BAR(BAR_X) + 8 * i);
        }
    }
    if (warp == 4) {
        if (elect_one()) {
#pragma unroll
            for (int i = 0; i < NSTAGE; i++) mbar_init(BAR(BAR_FULL + i), (i & 1) ? 1 : ((i & 2) ? 2 : 9));
#pragma unroll
            for (int i = 0; i <= NS; i++) mbar_init(BAR(BAR_WEMPTY + i), 4);
#pragma unroll
            for (int i = BAR_STATS; i < BAR_X; i++) mbar_init(BAR(i), i == BAR_EMB ? 2 : 1);
            asm volatile("fence.mbarrier_init.release.cluster;" ::: "memory");
        }
        if (lane < 2) sts128(SM_GST + lane * 16, make_uint4(0, 0, 0, 0));
        __syncwarp();
        if (lane < 6) mbar_expect(BAR(BAR_RV) + 8 * lane, lane < 4 ? 4096 : (lane == 4 ? 16384 : 8192));
        fence_async_smem();
        bar_arrive(0, 96);
        bar_arrive(5, 64);
        bar_arrive(4, 256 + 32 + 128);
        const uint4 z = make_uint4(0, 0, 0, 0);
#pragma unroll
        for (int i = 0; i < 2; i++) sts128(SM_V + (i * 16 + (lane >> 1)) * CH_PITCH + (lane & 1) * 16, z);
        if (lane < 2) sts128(SM_V + NSTAGE * KC_BYTES + lane * 16, z);
        if (lane < 16) sts128(SM_ONES + lane * 16, make_uint4(lane < 8 ? 0x3f803f80u : 0u, 0, 0, 0));
        fence_async_smem();
        bar_arrive(7, 160);
        asm volatile("barrier.cluster.arrive.relaxed.aligned;" ::: "memory");
        while (clock32() - clk0 < W2DELAY) {}
        weight_load(v, w2, cta, lane, false);
    }
    if (warp == 0 || warp == 4) {
        const int k = warp >> 2;
#pragma unroll
        for (int i = 0; i < 5; i++)
            if (i < 4 || !(lane & 2)) sts128(SM_BNC + k * 2304 + (lane >> 2) * 288 + (lane & 3) * 16 + i * 64, v[i]);
        if (lane == 0) TL(k ? 14 : 81);
        __syncwarp();
        weight_block(SM_BNC + k * 2304, gs->wt + k * 32 * STAGE_BYTES, cta, lane,
                     k ? &gs->wcnt[(NB + (lane & 1)) * LS] : &gs->w1cnt[((lane & 1) * 8 + wblk_kc(cta)) * KS]);
        if (lane == 0) TL(k ? 13 : 4);
    }

    if (warp >= 8) {
        const int nw = warp - 8;
        const unsigned one = gridDim.y;
        if (nw < 4) {
            const uint2 q = __ldg(reinterpret_cast<const uint2*>(nw == 0 ? g1 : (nw == 1 ? be1 : (nw == 2 ? g2 : be2))) + lane);
            sts128f(SM_COEF + nw * 512 + lane * 16, make_float4(0.5f * bf_lo(q.x), 0.5f * bf_hi(q.x), 0.5f * bf_lo(q.y), 0.5f * bf_hi(q.y)));
        }
        bar_sync(4, 256 + 32 + 128);
        asm volatile("barrier.cluster.wait.acquire.aligned;" ::: "memory");
        const int hf = nw >> 2, wq = nw & 3;
        const uint32_t v_off = SM_V + (lane & 3) * CH_PITCH + (2 + wq * 16 + hf * 8 + (lane >> 2)) * 16;
        const int crow = ((lane & 6) << 2) | ((lane >> 3) << 1) | (lane & 1);
        const uint32_t stg_off = crow * 128 + (((2 * wq + hf) ^ (crow & 7)) << 4);
        const uint32_t img_off = (tid - 256) * 16;
        const float sg = rk ? -1.f : 1.f;
        uint4* inbox = gs->box + cta * 1024 + (tid - 256);
#pragma unroll 1
        for (int conv = 0; conv < 2; conv++) {
            uint32_t u[4][4];
            if (conv == 0) {
#pragma unroll
                for (int i = 0; i < 4; i++) { mbar_wait(BAR(BAR_X + i), 0); ldsm4t(u[i], SM_XA + (i & 1) * 8192 + (i >> 1) * 4096 + stg_off); }
            } else {
                mbar_wait(BAR(BAR_HW), 0);
                mbar_wait(BAR(BAR_RH), 0);
#pragma unroll
                for (int i = 0; i < 4; i++) lds_piece(u[i], SM_XA + (i & 1) * 8192 + (i >> 1) * 4096 + img_off);
            }
            float ga[2][8], be[2][8], a[4][8];
#pragma unroll
            for (int g = 0; g < 2; g++) {
                const uint32_t ca = SM_COEF + conv * 1024 + (rk * 64 + g * 32 + (lane & 3) * 8) * 4;
                const float4 q0 = lds128f(ca), q1 = lds128f(ca + 16), q2 = lds128f(ca + 512), q3 = lds128f(ca + 528);
                ga[g][0] = q0.x; ga[g][1] = q0.y; ga[g][2] = q0.z; ga[g][3] = q0.w; ga[g][4] = q1.x; ga[g][5] = q1.y; ga[g][6] = q1.z; ga[g][7] = q1.w;
                be[g][0] = q2.x; be[g][1] = q2.y; be[g][2] = q2.z; be[g][3] = q2.w; be[g][4] = q3.x; be[g][5] = q3.y; be[g][6] = q3.z; be[g][7] = q3.w;
            }
#pragma unroll
            for (int i = 0; i < 16; i++) {
                a[i >> 2][2 * (i & 3)] = bf_lo(u[i >> 2][i & 3]) * ga[i >> 3][2 * (i & 3)];
                a[i >> 2][2 * (i & 3) + 1] = bf_hi(u[i >> 2][i & 3]) * ga[i >> 3][2 * (i & 3) + 1];
                asm volatile("" : "+f"(a[i >> 2][2 * (i & 3)]), "+f"(a[i >> 2][2 * (i & 3) + 1]));
            }
            float4 gv = make_float4(0.f, 0.f, 0.f, 0.f);
#pragma unroll
            for (int g = 0; g < 2; g++) {
                unsigned it = 0;
#pragma unroll 1
                while (!__all_sync(0xffffffffu, (g ? gv.z : gv.x) != 0.f) && ++it < 8 * SPIN_LIMIT)
                    asm volatile("ld.volatile.shared.v4.f32 {%0,%1,%2,%3}, [%4];" : "=f"(gv.x), "=f"(gv.y), "=f"(gv.z), "=f"(gv.w) : "r"(S0 + SM_GST + conv * 16) : "memory");
                if (g == 0 && tid == 256) TL(22 + conv * 4);
                const float rs = g ? gv.z : gv.x, mr = g ? gv.w : gv.y;
                uint32_t kp[4], sd[4];
#pragma unroll
                for (int i = 0; i < 8; i++) {
                    be[g][i] = fmaf(-mr, ga[g][i], be[g][i]);
                    a[2 * g][i] = silu_half(fmaf(a[2 * g][i], rs, be[g][i])); a[2 * g + 1][i] = silu_half(fmaf(a[2 * g + 1][i], rs, be[g][i]));
                }
#pragma unroll
                for (int i = 0; i < 4; i++) {
                    kp[i] = pack_bf(fmaf(a[2 * g][2 * i], sg, a[2 * g + 1][2 * i]), fmaf(a[2 * g][2 * i + 1], sg, a[2 * g + 1][2 * i + 1]));
                    sd[i] = pack_bf(fmaf(a[2 * g + 1][2 * i], -sg, a[2 * g][2 * i]), fmaf(a[2 * g + 1][2 * i + 1], -sg, a[2 * g][2 * i + 1]));
                }
                sts128(v_off + g * 4 * KC_BYTES, make_uint4(kp[0], kp[1], kp[2], kp[3]));
                st_async(peer0 + v_off + (g * 4 + 2) * KC_BYTES, sd[0], sd[1], sd[2], sd[3], peer0 + BAR(BAR_RV + g));
                publish(BAR(BAR_FULL + 4 * g), lane);
                if (tid == 256) TL(g ? 84 + conv : 8 + conv * 8);
            }
            mbar_wait(BAR(BAR_XO), conv);
            if (conv == 0) {
#pragma unroll
                for (int i = 0; i < 4; i++) ldsm4t(u[i], SM_XB + (i & 1) * 8192 + (i >> 1) * 4096 + stg_off);
            } else {
#pragma unroll
                for (int i = 0; i < 4; i++) lds_piece(u[i], SM_XB + (i & 1) * 8192 + (i >> 1) * 4096 + img_off);
                unsigned it = 0;
                while (true) {
                    bool okn = true, okf = true;
#pragma unroll
                    for (int i = 0; i < 8; i++) { okn = okn && u[(i >> 2) * 2][i & 3] != 0; okf = okf && u[(i >> 2) * 2 + 1][i & 3] != 0; }
                    if (__all_sync(0xffffffffu, (okn || !has_near) && (okf || !has_far)) || ++it > SPIN_LIMIT) break;
#pragma unroll
                    for (int i = 0; i < 4; i++) ld_unit(u[i], inbox + (i & 1) * 512 + (i >> 1) * 256);
                    if (tid == 256) TL(93);
                }
#pragma unroll
                for (int i = 0; i < 16; i++) u[i >> 2][i & 3] = ~u[i >> 2][i & 3];
            }
            if (tid == 256) TL(24 + conv * 4);
#pragma unroll
            for (int g = 0; g < 2; g++) {
                const float rs = g ? gv.z : gv.x;
                uint32_t o[2][4];
#pragma unroll
                for (int f = 0; f < 2; f++) {
                    const bool ok = f ? has_far : has_near;
#pragma unroll
                    for (int i = 0; i < 4; i++) {
                        const float lo = silu_half(fmaf(bf_lo(u[2 * g + f][i]), ga[g][2 * i] * rs, be[g][2 * i]));
                        const float hi = silu_half(fmaf(bf_hi(u[2 * g + f][i]), ga[g][2 * i + 1] * rs, be[g][2 * i + 1]));
                        o[f][i] = pack_bf((ok ? lo : 0.f) - a[2 * g + (f ^ 1)][2 * i], (ok ? hi : 0.f) - a[2 * g + (f ^ 1)][2 * i + 1]);
                    }
                }
                sts128(v_off + (8 + g * 4) * KC_BYTES, make_uint4(o[0][0], o[0][1], o[0][2], o[0][3]));
                st_async(peer0 + v_off + (10 + g * 4) * KC_BYTES, o[1][0], o[1][1], o[1][2], o[1][3], peer0 + BAR(BAR_RV + 2 + g));
                publish(BAR(BAR_FULL + 8 + 4 * g), lane);
                if (tid == 256) TL(g ? 88 + conv : 23 + conv * 4);
                if (one == 0) break;
            }
        }
        mbar_wait(BAR(BAR_FULL + NSTAGE - 1), 1);
#pragma unroll
        for (int i = 0; i < 4; i++) inbox[i * 256] = make_uint4(0, 0, 0, 0);
        {
            const int oc0 = hf * 64 + ((tid & 127) >> 3), seg = lane & 7;
            __nv_bfloat16* dst = out + ((size_t)(b * C + oc0) * HW + r) * HW + seg * 8;
            const uint32_t src = oc0 * 128 + ((seg ^ (oc0 & 7)) << 4);
            mbar_wait(BAR(BAR_XR), 0);
            uint4 xr[4];
#pragma unroll
            for (int i = 0; i < 4; i++) xr[i] = lds128(SM_XA + src + i * 2048);
            asm volatile("{\n.reg .pred p;\nsetp.eq.u64 p, %0, 0;\n@p st.shared.u32 [%1], 0;\n}" ::"l"(dst), "r"(src + S0) : "memory");
            bar_sync(hf ? 1 : 6, 128 + 128);
#pragma unroll
            for (int i = 0; i < 4; i++) {
                uint4 o = lds128(SM_XB + src + i * 2048);
                asm("add.rn.bf16x2 %0, %0, %1;" : "+r"(o.x) : "r"(xr[i].x)); asm("add.rn.bf16x2 %0, %0, %1;" : "+r"(o.y) : "r"(xr[i].y));
                asm("add.rn.bf16x2 %0, %0, %1;" : "+r"(o.z) : "r"(xr[i].z)); asm("add.rn.bf16x2 %0, %0, %1;" : "+r"(o.w) : "r"(xr[i].w));
                *reinterpret_cast<uint4*>(dst + (size_t)i * 16 * HW * HW) = o;
            }
            if (tid == 384) { TL(20); TLG(21); }
        }
    } else if (warp < 4) {
        const int wq = warp;
        bar_sync(7, 160);
        asm volatile("barrier.cluster.wait.acquire.aligned;" ::: "memory");
        const float sg = rk ? 1.f : -1.f;
        float d[64];
#pragma unroll 1
        for (int conv = 0; conv < 2; conv++) {
#pragma unroll
            for (int i = 0; i < 64; i++) d[i] = 0.f;
            uint32_t hp[32];
            fence_acc(d);
            mma_stages<0>(d, hp, conv, tid, peer0, gs);
            if (conv == 0) {
                asm volatile("wgmma.fence.sync.aligned;" ::: "memory");
                wgmma128<(SM_ONES >> 4) | (8u << 16), (SM_EMB >> 4), 0, 8>(d);
                asm volatile("wgmma.commit_group.sync.aligned;" ::: "memory");
            }
            asm volatile("wgmma.wait_group.sync.aligned 0;" ::: "memory");
            fence_acc(d);
            if (tid == 0) TL(10 + conv * 8);
#pragma unroll
            for (int i = 0; i < 32; i++) hp[i] = pack_bf(fmaf(bf_lo(hp[i]), sg, d[2 * i]), fmaf(bf_hi(hp[i]), sg, d[2 * i + 1]));
            if (conv == 1) {
                const uint32_t obase = SM_XB + ((lane >> 4) * 8 + (lane & 7)) * 128 + (((2 * wq + ((lane >> 3) & 1)) ^ (lane & 7)) << 4);
#pragma unroll
                for (int kc = 0; kc < 8; kc++) {
                    stsm4t(obase + kc * 2048, hp[4 * kc], hp[4 * kc + 1], hp[4 * kc + 2], hp[4 * kc + 3]);
                    if (kc == 3) bar_arrive(6, 128 + 128);
                }
                bar_arrive(1, 128 + 128);
                break;
            }
#pragma unroll
            for (int g = 0; g < 4; g++) {
                float c[4] = {0.f, 0.f, 0.f, 0.f};
#pragma unroll
                for (int i = 0; i < 4; i++) stat_mma(c, hp[8 * g + 2 * i], hp[8 * g + 2 * i + 1]);
                stat_store(c, SM_RED + (g * 4 + wq) * 48, lane);
            }
            bar_sync(2, 128);
            if (wq == 0) stat_publish(SM_RED, &gs->acc2[b * LS], lane, true);
            if (tid == 0) TL(11);
            if (tid == 32) mbar_expect(BAR(BAR_M), 16384);
#pragma unroll
            for (int j = 0; j < 8; j++) {
                const uint32_t p0 = hp[(j >> 1) * 8 + (j & 1)], p1 = hp[(j >> 1) * 8 + (j & 1) + 2], p2 = hp[(j >> 1) * 8 + (j & 1) + 4], p3 = hp[(j >> 1) * 8 + (j & 1) + 6];
                if ((j >> 2) == rk) sts128(SM_XA + (j & 3) * 2048 + tid * 16, make_uint4(p0, p1, p2, p3));
                else st_async(peer0 + SM_XA + 8192 + (j & 3) * 2048 + tid * 16, p0, p1, p2, p3, peer0 + BAR(BAR_RH));
            }
            __syncwarp();
            if (lane == 0) { mbar_arrive(BAR(BAR_HW)); mbar_arrive(BAR(BAR_WEMPTY + 7)); }
            if (has_near) {
                const int oc2 = (cta & ~1) + (rk ? 2 : -2);
#pragma unroll
                for (int j = 0; j < 8; j++) {
                    uint4* outbox = gs->box + (oc2 + (j >> 2)) * 1024 + (((j >> 2) == rk) ? 512 : 0) + (j & 3) * 128 + tid;
                    *outbox = make_uint4(~hp[(j >> 1) * 8 + (j & 1)], ~hp[(j >> 1) * 8 + (j & 1) + 2], ~hp[(j >> 1) * 8 + (j & 1) + 4], ~hp[(j >> 1) * 8 + (j & 1) + 6]);
                }
            }
            if (tid == 0) TL(12);
        }
    } else if (warp < 6) {
        if (warp == 5) {
            bar_sync(5, 64);
            if (elect_one()) {
                mbar_expect(BAR(BAR_XO), 16384);
                while (clock32() - clk0 < ODELAY) {}
#pragma unroll
                for (int i = 0; i < 4; i++)
                    tma_x(SM_XB + i * 4096, &xmap, ((i >> 1) ^ rk) ? (r | 1) + 1 : (r & ~1) - 1, ch0 + (i & 1) * 32, BAR(BAR_XO));
            }
            __syncwarp();
#pragma unroll 1
            for (int i = 0; i < 8; i++) {
                mbar_wait(BAR(BAR_RV) + 8 * (i & 3), i >> 2);
                fence_async_smem();
                if (lane == 0) {
                    mbar_arrive(BAR(BAR_FULL + 2) + 32 * (i & 3));
                    if (i < 4) mbar_expect(BAR(BAR_RV) + 8 * i, 4096);
                    TL(64 + i);
                }
                __syncwarp();
            }
        } else {
            mbar_wait(BAR(BAR_STATS), 0);
            unsigned it = 0;
            while (!__all_sync(0xffffffffu, ld_relaxed(&gs->wcnt[(2 * NB + b) * LS]) >= (unsigned)NXTRA) && ++it < SPIN_LIMIT) __nanosleep(100);
            fence_acquire();
            float ev[4] = {0.f, 0.f, 0.f, 0.f};
#pragma unroll
            for (int j = 0; j < NXTRA; j++) {
                const uint4 ef = ld_relaxed_v4(&gs->emb[(j * NB + b) * C + lane * 4]);
                ev[0] += __uint_as_float(ef.x); ev[1] += __uint_as_float(ef.y); ev[2] += __uint_as_float(ef.z); ev[3] += __uint_as_float(ef.w);
            }
#pragma unroll
            for (int i = 0; i < 4; i++) {
                const float hi = bf_lo(pack_bf(ev[i], 0.f));
                sts128(SM_EMB + n_to_oc(lane * 4 + i) * 16, make_uint4(pack_bf(hi, ev[i] - hi), 0, 0, 0));
            }
            fence_async_smem();
            __syncwarp();
            if (lane == 0) { mbar_arrive(BAR(BAR_EMB)); TL(19); }
            mbar_wait(BAR(BAR_HW), 0);
            mbar_wait(BAR(BAR_FULL + 8), 1);
            if (elect_one()) {
                mbar_expect(BAR(BAR_XR), 16384);
#pragma unroll
                for (int i = 0; i < 4; i++) tma_x(SM_XA + i * 4096, &xmap, r, b * C + i * 32, BAR(BAR_XR));
            }
        }
    } else if (warp == 6) {
        bar_sync(0, 96);
        if (lane < NSTAGE) mbar_expect(BAR(BAR_FULL) + 8 * lane, STAGE_BYTES);
        const unsigned char* wbase = gs->wt + rk * 8 * STAGE_BYTES;
        unsigned it = 0;
        {
            int g = 0;
            const int l7 = lane & 7;
            const unsigned* cnt = &gs->w1cnt[(b * 8 + ((((l7 >> 1) ^ rk) & 1) * 4 + (l7 >> 2) * 2 + (l7 & 1))) * KS];
            unsigned cv = ld_relaxed(cnt);
#pragma unroll 1
            while (g <= NS) {
                unsigned ready = __ballot_sync(0xffffffffu, (lane < 8 ? cv & 0xffffu : cv >> 16) >= 16u);
                if ((ready >> 8 & 0xff) != 0xff) ready &= 0xff;
                if (ready != ~0u) cv = ld_relaxed(cnt);
                ready >>= g;
                if (++it > SPIN_LIMIT) ready = ~0u;
                if (!(ready & 1)) continue;
                fence_async_global();
                if (lane == 0) TL(g ? 3 : 6);
#pragma unroll 1
                for (; (ready & 1) && g <= NS; g++, ready >>= 1)
                    if (g < NS && elect_one())
                        bulk_g2s(S0 + SM_W + g * STAGE_BYTES, wbase + ((((g >> 1) ^ rk) & 1) * 4 + (g >> 2) * 2 + (g & 1)) * STAGE_BYTES, STAGE_BYTES,
                                 S0 + BAR(BAR_FULL) + 8 * g);
            }
        }
#pragma unroll 1
        for (int q = 2; q < 8; q++) {
            const unsigned char* wsrc = wbase + ((q >> 1) * 16 + (q & 1) * 2) * STAGE_BYTES;
            const uint32_t par = ((q >> 1) - 1) & 1;
            if (q == 4) {
                it = 0;
                while (!__all_sync(0xffffffffu, ld_relaxed(&gs->wcnt[(NB + b) * LS]) == NCTA * 0x10001u) && ++it < SPIN_LIMIT) {}
                fence_acquire();
                fence_async_global();
                if (lane == 0) { mbar_arrive(BAR(BAR_EMB)); TL(2); }
            }
#pragma unroll
            for (int i = 0; i < 4; i++) {
                mbar_wait(BAR(BAR_WEMPTY + i) + 32 * (q & 1), par);
                if (i == 0 && (q == 4 || q == 6)) {
                    if ((lane >> 3) == (q - 4) / 2) mbar_expect(BAR(BAR_FULL) + 8 * lane, STAGE_BYTES);
                    __syncwarp();
                }
                if (elect_one())
                    bulk_g2s(S0 + SM_W + ((q & 1) * 4 + i) * STAGE_BYTES, wsrc + ((((i >> 1) ^ rk) & 1) * 4 + (i & 1)) * STAGE_BYTES, STAGE_BYTES,
                             S0 + BAR(BAR_FULL + i) + 32 * (q & 3));
            }
        }
    } else {
        bar_sync(0, 96);
#pragma unroll 1
        for (int conv = 0; conv < 2; conv++) {
            if (conv == 1) mbar_wait(BAR(BAR_HW), 0);
            const float* asrc = (conv ? gs->acc2 : gs->acc1) + b * LS + (rk * 2 + (lane & 1)) * 4;
            unsigned it = 0;
#pragma unroll 1
            while (true) {
                const uint4 f = ld_relaxed_v4(asrc);
                const bool ok = ((f.x == 0x42800000u) & (f.w == 0x42800000u)) || ++it > SPIN_LIMIT;
                if (ok && lane < 2) {
                    const float inv_n = 1.0f / (32.0f * HW * HW);
                    const float mean = __uint_as_float(f.y) * inv_n;
                    float rs;
                    asm("rsqrt.approx.ftz.f32 %0, %1;" : "=f"(rs) : "f"(fmaxf(fmaf(-mean, mean, __uint_as_float(f.z) * inv_n), 0.f) + 1e-5f));
                    asm volatile("st.shared.v2.f32 [%0], {%1,%2};" ::"r"(S0 + SM_GST + conv * 16 + lane * 8), "f"(rs == 0.f ? 1.2e-38f : rs), "f"(mean * rs) : "memory");
                }
                if (__all_sync(0xffffffffu, ok)) break;
            }
            if (lane == 0) { if (conv == 0) mbar_arrive(BAR(BAR_STATS)); TL(7 + conv * 8); }
        }
        { const unsigned c1 = clock32(); while (clock32() - c1 < FDELAY) {} }
        if (elect_one()) {
            mbar_expect(BAR(BAR_XO), 16384);
            bulk_g2s(S0 + SM_XB, gs->box + cta * 1024, 16384, S0 + BAR(BAR_XO));
        }
        if (r == 0) {
            if (lane < 16) gs->acc1[b * LS + lane] = 0.f;
            if (lane < 3) gs->wcnt[(lane * NB + b) * LS] = 0;
            if (lane < 8) gs->w1cnt[(b * 8 + lane) * KS] = 0;
        }
    }
}

}

extern "C" void kernel_launch(void* const* d_in, const int* in_sizes, int n_in, void* d_out, int out_size) {
    (void)in_sizes; (void)n_in; (void)out_size;
    typedef CUresult (*EncodeFn)(CUtensorMap*, CUtensorMapDataType, cuuint32_t, void*, const cuuint64_t*, const cuuint64_t*,
                                 const cuuint32_t*, const cuuint32_t*, CUtensorMapInterleave, CUtensorMapSwizzle,
                                 CUtensorMapL2promotion, CUtensorMapFloatOOBfill);
    static Scratch* gs = nullptr;
    static EncodeFn encode = nullptr;
    if (!gs) {
        cudaFuncSetAttribute(resblock_kernel, cudaFuncAttributeMaxDynamicSharedMemorySize, SM_TOTAL);
        cudaGetSymbolAddress((void**)&gs, g_scratch);
        cudaDriverEntryPointQueryResult qr;
        cudaGetDriverEntryPoint("cuTensorMapEncodeTiled", (void**)&encode, cudaEnableDefault, &qr);
    }
    CUtensorMap xmap;
    const cuuint64_t dims[3] = {HW, HW, NB * C}, strides[2] = {HW * 2, HW * HW * 2};
    const cuuint32_t box[3] = {HW, 1, 32}, es[3] = {1, 1, 1};
    encode(&xmap, CU_TENSOR_MAP_DATA_TYPE_BFLOAT16, 3, d_in[0], dims, strides, box, es, CU_TENSOR_MAP_INTERLEAVE_NONE,
           CU_TENSOR_MAP_SWIZZLE_128B, CU_TENSOR_MAP_L2_PROMOTION_NONE, CU_TENSOR_MAP_FLOAT_OOB_FILL_NONE);
    resblock_kernel<<<NCTA + NXTRA, NTHREADS, SM_TOTAL>>>(
        (const __nv_bfloat16*)d_in[4], (const __nv_bfloat16*)d_in[0], (const __nv_bfloat16*)d_in[1],
        (const __nv_bfloat16*)d_in[2], (const __nv_bfloat16*)d_in[3], (const __nv_bfloat16*)d_in[5],
        (const __nv_bfloat16*)d_in[6], (const __nv_bfloat16*)d_in[7], (const __nv_bfloat16*)d_in[8],
        (__nv_bfloat16*)d_out, gs, xmap);
}
```

```cpp
#include <cuda_runtime.h>
#include <cuda.h>
#include <cuda_bf16.h>
#include <stdint.h>

namespace {

constexpr int C = 128, HW = 64, NB = 2, E = 768;
constexpr int NCTA = NB * HW;
constexpr int NXTRA = 4;
constexpr int NTHREADS = 16 * 32;
constexpr int CH_PITCH = 66 * 16;
constexpr int KC_BYTES = 2 * CH_PITCH;
constexpr int STAGE_BYTES = 12288;
constexpr int NSTAGE = 16;
constexpr int NS = 8;
#define XDELAY 300
#define XSTAG 800
#define XSTAG2 100
#define SDELAY 600
#define W2DELAY 1800
#define MLOAD 15
#define ODELAY 2800
#define FDELAY 1400

constexpr uint32_t SMEM_BASE = 0x400;
constexpr uint32_t SM_XA = SMEM_BASE;
constexpr uint32_t SM_XB = SM_XA + 16384;
constexpr uint32_t SM_M = SM_XB + 16384;
constexpr uint32_t SM_V = SM_M + 16384;
constexpr uint32_t SM_W = SM_V + NSTAGE * KC_BYTES + 128;
constexpr uint32_t SM_COEF = SM_W + NS * STAGE_BYTES;
constexpr uint32_t SM_GST = SM_COEF + 2048;
constexpr uint32_t SM_EMB = SM_GST + 128;
constexpr uint32_t SM_ONES = SM_EMB + 2048;
constexpr uint32_t SM_RED = SM_ONES + 256;
constexpr uint32_t SM_BNC = SM_RED + 1024;
constexpr uint32_t SM_BAR = SM_BNC + 2 * 2304;
constexpr int BAR_FULL = 0, BAR_WEMPTY = NSTAGE, BAR_HW = BAR_WEMPTY + NS, BAR_STATS = BAR_HW + 1, BAR_EMB = BAR_STATS + 1,
              BAR_RV = BAR_EMB + 1  , BAR_M = BAR_RV + 4, BAR_RH = BAR_M + 1, BAR_XO = BAR_RH + 1, BAR_XR = BAR_XO + 1,
              BAR_X = BAR_XR + 1  , NBAR = BAR_X + 4;
constexpr int SM_TOTAL = SM_BAR + NBAR * 8 - SMEM_BASE;
static_assert(SM_TOTAL <= 232448, "smem");
__host__ __device__ constexpr uint32_t BAR(int i) { return SM_BAR + 8 * i; }

constexpr unsigned SPIN_LIMIT = 1u << 16;
constexpr int LS = 1056, KS = 32;

struct Scratch {
    float acc1[NB * LS];
    float acc2[NB * LS];
    unsigned wcnt[3 * NB * LS];
    unsigned w1cnt[NB * 8 * KS];
    float emb[NXTRA * NB * C];
    alignas(1024) unsigned char wt[2 * 32 * STAGE_BYTES];
    uint4 box[NCTA * 1024];
};
__device__ __align__(1024) Scratch g_scratch;
#define TL(i) do {} while (0)
#define TLG(i) do {} while (0)

__device__ __forceinline__ unsigned clock32() { unsigned c; asm volatile("mov.u32 %0, %%clock;" : "=r"(c)); return c; }
__device__ __forceinline__ uint32_t mapa(uint32_t a, uint32_t rank) {
    uint32_t d;
    asm("mapa.shared::cluster.u32 %0, %1, %2;" : "=r"(d) : "r"(a), "r"(rank));
    return d;
}
#define S0 mapa(0, blockIdx.x & 1)
__device__ __forceinline__ void mbar_init(uint32_t bar, int cnt) {
    asm volatile("mbarrier.init.shared::cta.b64 [%0], %1;" ::"r"(bar + S0), "r"(cnt) : "memory");
}
__device__ __forceinline__ void mbar_arrive(uint32_t bar) {
    asm volatile("mbarrier.arrive.shared::cta.b64 _, [%0];" ::"r"(bar + S0) : "memory");
}
__device__ __forceinline__ void mbar_expect(uint32_t bar, uint32_t bytes) {
    asm volatile("mbarrier.arrive.expect_tx.shared::cta.b64 _, [%0], %1;" ::"r"(bar + S0), "r"(bytes) : "memory");
}
__device__ __forceinline__ bool mbar_try(uint32_t bar, uint32_t par) {
    uint32_t ok;
    asm volatile("{\n.reg .pred p;\nmbarrier.try_wait.parity.shared::cta.b64 p, [%1], %2;\nselp.u32 %0, 1, 0, p;\n}"
                 : "=r"(ok) : "r"(bar + S0), "r"(par) : "memory");
    return ok;
}
__device__ __forceinline__ bool mbar_test(uint32_t bar, uint32_t par) {
    uint32_t ok;
    asm volatile("{\n.reg .pred p;\nmbarrier.test_wait.parity.shared::cta.b64 p, [%1], %2;\nselp.u32 %0, 1, 0, p;\n}"
                 : "=r"(ok) : "r"(bar + S0), "r"(par) : "memory");
    return ok;
}
__device__ __forceinline__ void mbar_wait(uint32_t bar, uint32_t par) {
    unsigned it = 0;
#pragma unroll 1
    while (!mbar_try(bar, par) && ++it < SPIN_LIMIT) {}
}
__device__ __forceinline__ bool elect_one() {
    uint32_t p;
    asm volatile("{\n.reg .pred p;\nelect.sync _|p, 0xffffffff;\nselp.u32 %0, 1, 0, p;\n}" : "=r"(p));
    return p;
}
__device__ __forceinline__ void fence_async_smem() { asm volatile("fence.proxy.async.shared::cta;" ::: "memory"); }
__device__ __forceinline__ void fence_async_global() { asm volatile("fence.proxy.async.global;" ::: "memory"); }
__device__ __forceinline__ void fence_acquire() { asm volatile("fence.acquire.gpu;" ::: "memory"); }
__device__ __forceinline__ void bar_sync(int id, int n) { asm volatile("bar.sync %0, %1;" ::"r"(id), "r"(n) : "memory"); }
__device__ __forceinline__ void bar_arrive(int id, int n) { asm volatile("bar.arrive %0, %1;" ::"r"(id), "r"(n) : "memory"); }
__device__ __forceinline__ void bulk_g2s(uint32_t dst, const void* src, uint32_t bytes, uint32_t bar) {
    asm volatile("cp.async.bulk.shared::cluster.global.mbarrier::complete_tx::bytes [%0], [%1], %2, [%3];"
                 ::"r"(dst), "l"(src), "r"(bytes), "r"(bar) : "memory");
}
__device__ __forceinline__ void tma_x(uint32_t dst, const CUtensorMap* tm, int row, int ch, uint32_t bar) {
    asm volatile("cp.async.bulk.tensor.3d.shared::cluster.global.mbarrier::complete_tx::bytes [%0], [%1, {%2, %3, %4}], [%5];"
                 ::"r"(dst + S0), "l"(tm), "r"(0), "r"(row), "r"(ch), "r"(bar + S0) : "memory");
}
__device__ __forceinline__ uint4 ld_relaxed_v4(const void* p) {
    uint4 v;
    asm volatile("ld.relaxed.gpu.global.v4.u32 {%0,%1,%2,%3}, [%4];" : "=r"(v.x), "=r"(v.y), "=r"(v.z), "=r"(v.w) : "l"(p) : "memory");
    return v;
}
__device__ __forceinline__ unsigned ld_relaxed(const void* p) {
    unsigned v;
    asm volatile("ld.relaxed.gpu.global.u32 %0, [%1];" : "=r"(v) : "l"(p) : "memory");
    return v;
}
__device__ __forceinline__ void red_add4(float* p, float a, float b, float c, float d) {
    asm volatile("red.relaxed.gpu.global.add.v4.f32 [%0], {%1,%2,%3,%4};" ::"l"(p), "f"(a), "f"(b), "f"(c), "f"(d) : "memory");
}
__device__ __forceinline__ void sts128(uint32_t a, uint4 v) {
    asm volatile("st.shared.v4.u32 [%0], {%1,%2,%3,%4};" ::"r"(a + S0), "r"(v.x), "r"(v.y), "r"(v.z), "r"(v.w) : "memory");
}
__device__ __forceinline__ void sts128f(uint32_t a, float4 v) {
    asm volatile("st.shared.v4.f32 [%0], {%1,%2,%3,%4};" ::"r"(a + S0), "f"(v.x), "f"(v.y), "f"(v.z), "f"(v.w) : "memory");
}
__device__ __forceinline__ void sts32f(uint32_t a, float v) { asm volatile("st.shared.f32 [%0], %1;" ::"r"(a + S0), "f"(v) : "memory"); }
__device__ __forceinline__ uint4 lds128(uint32_t a) {
    uint4 v;
    asm volatile("ld.shared.v4.u32 {%0,%1,%2,%3}, [%4];" : "=r"(v.x), "=r"(v.y), "=r"(v.z), "=r"(v.w) : "r"(a + S0) : "memory");
    return v;
}
__device__ __forceinline__ float4 lds128f(uint32_t a) {
    float4 v;
    asm volatile("ld.shared.v4.f32 {%0,%1,%2,%3}, [%4];" : "=f"(v.x), "=f"(v.y), "=f"(v.z), "=f"(v.w) : "r"(a + S0) : "memory");
    return v;
}
__device__ __forceinline__ float2 lds64f(uint32_t a) {
    float2 v;
    asm volatile("ld.shared.v2.f32 {%0,%1}, [%2];" : "=f"(v.x), "=f"(v.y) : "r"(a + S0) : "memory");
    return v;
}
__device__ __forceinline__ float bf_lo(uint32_t u) { return __uint_as_float(u << 16); }
__device__ __forceinline__ float bf_hi(uint32_t u) { return __uint_as_float(u & 0xffff0000u); }
__device__ __forceinline__ uint32_t pack_bf(float lo, float hi) {
    uint32_t r;
    asm("cvt.rn.bf16x2.f32 %0, %1, %2;" : "=r"(r) : "f"(hi), "f"(lo));
    return r;
}
__device__ __forceinline__ float tanh_fast(float x) {
    float r;
    asm("tanh.approx.f32 %0, %1;" : "=f"(r) : "f"(x));
    return r;
}
__device__ __forceinline__ float silu_half(float h) { return fmaf(h, tanh_fast(h), h); }
__device__ __forceinline__ void ldsm4(uint32_t (&u)[4], uint32_t a) {
    asm volatile("ldmatrix.sync.aligned.m8n8.x4.shared.b16 {%0,%1,%2,%3}, [%4];"
                 : "=r"(u[0]), "=r"(u[1]), "=r"(u[2]), "=r"(u[3]) : "r"(a + S0) : "memory");
}
__device__ __forceinline__ void ldsm4t(uint32_t (&u)[4], uint32_t a) {
    asm volatile("ldmatrix.sync.aligned.m8n8.x4.trans.shared.b16 {%0,%1,%2,%3}, [%4];"
                 : "=r"(u[0]), "=r"(u[1]), "=r"(u[2]), "=r"(u[3]) : "r"(a + S0) : "memory");
}
__device__ __forceinline__ void stsm4(uint32_t a, uint32_t p0, uint32_t p1, uint32_t p2, uint32_t p3) {
    asm volatile("stmatrix.sync.aligned.m8n8.x4.shared.b16 [%0], {%1,%2,%3,%4};" ::"r"(a + S0), "r"(p0), "r"(p1), "r"(p2), "r"(p3) : "memory");
}
__device__ __forceinline__ void stsm4t(uint32_t a, uint32_t p0, uint32_t p1, uint32_t p2, uint32_t p3) {
    asm volatile("stmatrix.sync.aligned.m8n8.x4.trans.shared.b16 [%0], {%1,%2,%3,%4};" ::"r"(a + S0), "r"(p0), "r"(p1), "r"(p2), "r"(p3) : "memory");
}

#define R8(o) "+f"(d[o]), "+f"(d[o + 1]), "+f"(d[o + 2]), "+f"(d[o + 3]), "+f"(d[o + 4]), "+f"(d[o + 5]), "+f"(d[o + 6]), "+f"(d[o + 7])
template <uint32_t ALO, uint32_t BLO, uint64_t AHI = 8, uint64_t BHI = 48>
__device__ __forceinline__ void wgmma128(float (&d)[64]) {
    asm volatile(
        "wgmma.mma_async.sync.aligned.m64n128k16.f32.bf16.bf16 "
        "{%0,%1,%2,%3,%4,%5,%6,%7,%8,%9,%10,%11,%12,%13,%14,%15,%16,%17,%18,%19,%20,%21,%22,%23,%24,%25,%26,%27,%28,%29,%30,%31,"
        "%32,%33,%34,%35,%36,%37,%38,%39,%40,%41,%42,%43,%44,%45,%46,%47,%48,%49,%50,%51,%52,%53,%54,%55,%56,%57,%58,%59,%60,%61,%62,%63},"
        " %64, %65, 1, 1, 1, 0, 0;"
        : R8(0), R8(8), R8(16), R8(24), R8(32), R8(40), R8(48), R8(56)
        : "l"((AHI << 32) | ALO), "l"((BHI << 32) | BLO));
}
__device__ __forceinline__ void stat_mma(float (&c)[4], uint32_t p, uint32_t q) {
    asm("mma.sync.aligned.m16n8k16.row.col.f32.bf16.bf16.f32 {%0,%1,%2,%3}, {%4,%5,%6,%5}, {%4,%6}, {%0,%1,%2,%3};"
        : "+f"(c[0]), "+f"(c[1]), "+f"(c[2]), "+f"(c[3]) : "r"(p), "r"(0x3f803f80u), "r"(q));
}
__device__ __forceinline__ void stat_store(const float (&c)[4], uint32_t dst, int lane) {
    const int g = lane >> 2, t = lane & 3;
    if (t == (g >> 1)) sts32f(dst + g * 4, (g & 1) ? c[1] : c[0]);
    if (g == 7) sts32f(dst + 32 + t * 4, c[2] + c[3]);
}
__device__ __forceinline__ float sum4(float4 v) { return (v.x + v.y) + (v.z + v.w); }
__device__ __forceinline__ void stat_publish(uint32_t src, float* acc, int lane, bool real) {
    const uint32_t a = src + (lane & 15) * 48;
    float q = sum4(lds128f(a)) + sum4(lds128f(a + 16)), sm = sum4(lds128f(a + 32));
    q += __shfl_xor_sync(0xffffffffu, q, 1); sm += __shfl_xor_sync(0xffffffffu, sm, 1);
    q += __shfl_xor_sync(0xffffffffu, q, 2); sm += __shfl_xor_sync(0xffffffffu, sm, 2);
    if (real && (lane & 19) == 0) red_add4(acc + lane, 1.f, sm, q, 1.f);
}
__device__ __forceinline__ void fence_acc(float (&d)[64]) {
#pragma unroll
    for (int i = 0; i < 64; i++) asm volatile("" : "+f"(d[i])::"memory");
}
__device__ __forceinline__ void ld_unit(uint32_t (&u)[4], const uint4* p) {
    asm volatile("ld.relaxed.gpu.global.v4.u32 {%0,%1,%2,%3}, [%4];" : "=r"(u[0]), "=r"(u[1]), "=r"(u[2]), "=r"(u[3]) : "l"(p) : "memory");
}

__device__ __forceinline__ void st_async(uint32_t dst, uint32_t a, uint32_t b, uint32_t c, uint32_t d, uint32_t bar) {
    asm volatile("st.async.shared::cluster.mbarrier::complete_tx::bytes.v4.b32 [%0], {%1,%2,%3,%4}, [%5];"
                 ::"r"(dst), "r"(a), "r"(b), "r"(c), "r"(d), "r"(bar) : "memory");
}
template <int S>
__device__ __forceinline__ void mma_stages(float (&d)[64], uint32_t (&hp)[32], int conv, int tid, uint32_t peer0, Scratch* gs) {
    constexpr uint32_t A = ((SM_V + S * KC_BYTES + 16) >> 4) | ((CH_PITCH >> 4) << 16);
    constexpr uint32_t B = ((SM_W + (S % NS) * STAGE_BYTES) >> 4) | (8u << 16);
    if (S == 0) mbar_wait(BAR(BAR_FULL), conv);
    constexpr uint32_t NEXT = S + 1 < NSTAGE ? BAR(BAR_FULL + S + 1) : BAR(BAR_EMB);
    const int npar = S + 1 < NSTAGE ? conv : 0;
    const bool next_ok = mbar_test(NEXT, npar);
    if ((S & 7) == 0 && tid == 0) TL(32 + conv * 16 + S);
    asm volatile("wgmma.fence.sync.aligned;" ::: "memory");
#define SEND_M(j) st_async(peer0 + SM_M + (j) * 2048 + tid * 16, hp[4 * (j)], hp[4 * (j) + 1], hp[4 * (j) + 2], hp[4 * (j) + 3], peer0 + BAR(BAR_M))
    wgmma128<A, B>(d);
    if (S >= 8 && S < 12) SEND_M((S & 3) * 2);
    wgmma128<A + 1, B + 16>(d);
    if (S >= 8 && S < 12) SEND_M((S & 3) * 2 + 1);
    wgmma128<A + 2, B + 32>(d);
    asm volatile("wgmma.commit_group.sync.aligned;" ::: "memory");
    if ((S & 7) != 0) {
        asm volatile("wgmma.wait_group.sync.aligned 1;" ::: "memory");
        if ((tid & 31) == 0) mbar_arrive(BAR(BAR_WEMPTY + (S - 1) % NS));
    }
    if (S == 7) {
        asm volatile("wgmma.wait_group.sync.aligned 0;" ::: "memory");
        fence_acc(d);
#pragma unroll
        for (int i = 0; i < 32; i++) hp[i] = pack_bf(d[2 * i], d[2 * i + 1]);
        fence_acc(d);
        if ((tid & 31) == 0) mbar_arrive(BAR(BAR_WEMPTY + 7));
    }
    if (!next_ok) mbar_wait(NEXT, npar);
    if (S == MLOAD) {
        mbar_wait(BAR(BAR_M), conv);
#pragma unroll
        for (int j = 0; j < 8; j++) {
            const uint4 q = lds128(SM_M + j * 2048 + tid * 16);
            hp[4 * j] = q.x; hp[4 * j + 1] = q.y; hp[4 * j + 2] = q.z; hp[4 * j + 3] = q.w;
        }
    }
    if constexpr (S + 1 < NSTAGE) mma_stages<S + 1>(d, hp, conv, tid, peer0, gs);
}

__device__ __forceinline__ int wblk_kc(int cta) { const int i = cta >> 4; return (i & 1) | ((i & 2) << 1) | ((i & 4) >> 1); }
__device__ __forceinline__ int n_to_oc(int n) { return (n & ~31) | ((n & 6) << 2) | ((n >> 2) & 6) | (n & 1); }
__device__ __forceinline__ void weight_load(uint4 (&t)[5], const __nv_bfloat16* w, int cta, int lane, bool perm) {
    const int n = (cta & 15) * 8 + (lane >> 2);
    const char* base = reinterpret_cast<const char*>(w) + (uint32_t)(((perm ? n_to_oc(n) : n) * 8 + wblk_kc(cta)) * 288 + (lane & 3) * 16);
#pragma unroll
    for (int k = 0; k < 5; k++)
        if (k < 4 || !(lane & 2)) t[k] = __ldg(reinterpret_cast<const uint4*>(base + k * 64));
}
__device__ __forceinline__ void st_global64(void* p, uint32_t a, uint32_t b) { asm volatile("st.global.v2.u32 [%0], {%1,%2};" ::"l"(p), "r"(a), "r"(b) : "memory"); }
__device__ __forceinline__ void weight_block(uint32_t bounce, unsigned char* wt, int cta, int lane, int kx) {
    unsigned char* piece = wt + wblk_kc(cta) * STAGE_BYTES + (cta & 15) * 768 + kx * 256;
    uint32_t g[3][4];
#pragma unroll
    for (int i = 0; i < 12; i++)
        asm volatile("ld.shared.u16 %0, [%1];" : "=r"(g[i % 3][i / 3]) : "r"(S0 + bounce + (lane & 7) * 288 + (lane >> 3) * 72 + kx * 2 + i * 6) : "memory");
    float u1[4], u2[4];
#pragma unroll
    for (int c = 0; c < 4; c++) {
        const float t = 0.5f * (bf_lo(g[0][c]) + bf_lo(g[2][c]));
        u1[c] = fmaf(bf_lo(g[1][c]), 0.5f, t); u2[c] = fmaf(bf_lo(g[1][c]), -0.5f, t);
    }
    unsigned char* dst = piece + (lane >> 4) * 128 + (lane & 7) * 16 + ((lane >> 3) & 1) * 8;
    st_global64(dst, pack_bf(u1[0], u1[1]), pack_bf(u1[2], u1[3]));
    st_global64(dst + 8 * STAGE_BYTES, pack_bf(u2[0], u2[1]), pack_bf(u2[2], u2[3]));
    st_global64(dst + 16 * STAGE_BYTES, __byte_perm(g[0][0], g[0][1], 0x5410), __byte_perm(g[0][2], g[0][3], 0x5410));
    st_global64(dst + 24 * STAGE_BYTES, __byte_perm(g[2][0], g[2][1], 0x5410), __byte_perm(g[2][2], g[2][3], 0x5410));
    const unsigned rb = ld_relaxed(piece + (lane >> 3) * 8 * STAGE_BYTES + (lane & 7) * 32);
    asm volatile("{\n.reg .pred p;\nsetp.eq.u32 p, %0, 0x9e3779b9;\n@p st.shared.u32 [%1], %0;\n}" ::"r"(rb), "r"(S0 + SM_RED + 1020) : "memory");
}
__device__ __forceinline__ void publish(uint32_t bar, int lane) {
    fence_async_smem();
    __syncwarp();
    if (lane == 0) mbar_arrive(bar);
}
__device__ __forceinline__ void lds_piece(uint32_t (&u)[4], uint32_t a) {
    const uint4 q = lds128(a);
    u[0] = q.x; u[1] = q.y; u[2] = q.z; u[3] = q.w;
}
__device__ __forceinline__ void load_outer(uint32_t (&u)[4][4], int conv, uint32_t stg_off, uint32_t img_off) {
#pragma unroll
    for (int i = 0; i < 4; i++) {
        if (conv == 0) ldsm4t(u[i], SM_XB + (i & 1) * 8192 + (i >> 1) * 4096 + stg_off);
        else lds_piece(u[i], SM_XB + (i & 1) * 8192 + (i >> 1) * 4096 + img_off);
    }
}
__device__ __noinline__ void side_jobs(const __nv_bfloat16* __restrict__ t_emb, const __nv_bfloat16* __restrict__ w_emb,
                                       const __nv_bfloat16* __restrict__ w2, Scratch* __restrict__ gs, unsigned clk0) {
    const int tid = threadIdx.x, warp = tid >> 5, lane = tid & 31, j = blockIdx.x;
    float tv = 0.f;
    if (lane < 24) tv = __bfloat162float(t_emb[(lane / 12) * E + j * 192 + warp * 12 + lane % 12]);
    if (tid == 0) {
        mbar_init(BAR(0), 1);
        mbar_expect(BAR(0), 192 * C * 2);
        fence_async_smem();
        while (clock32() - clk0 < SDELAY) {}
#pragma unroll
        for (int i = 0; i < 4; i++)
            asm volatile("cp.async.bulk.prefetch.L2.global [%0], 18432;" ::"l"(reinterpret_cast<const char*>(w2) + (j * 4 + i) * 18432) : "memory");
#pragma unroll
        for (int i = 0; i < 4; i++) bulk_g2s(S0 + SM_W + i * 12288, w_emb + (j * 192 + i * 48) * C, 12288, S0 + BAR(0));
    }
    if (j == 0 && tid < 32) gs->acc2[(tid >> 4) * LS + (tid & 15)] = 0.f;
    const float sv = silu_half(0.5f * tv);
    __syncthreads();
    mbar_wait(BAR(0), 0);
    float acc[8] = {0.f, 0.f, 0.f, 0.f, 0.f, 0.f, 0.f, 0.f};
#pragma unroll
    for (int i = 0; i < 12; i++) {
        const float2 wq = lds64f(SM_W + (warp * 12 + i) * 256 + lane * 8);
        const uint32_t wx = __float_as_uint(wq.x), wy = __float_as_uint(wq.y);
#pragma unroll
        for (int bb = 0; bb < 2; bb++) {
            const float sx = __shfl_sync(0xffffffffu, sv, bb * 12 + i);
            acc[4 * bb + 0] = fmaf(sx, bf_lo(wx), acc[4 * bb + 0]); acc[4 * bb + 1] = fmaf(sx, bf_hi(wx), acc[4 * bb + 1]);
            acc[4 * bb + 2] = fmaf(sx, bf_lo(wy), acc[4 * bb + 2]); acc[4 * bb + 3] = fmaf(sx, bf_hi(wy), acc[4 * bb + 3]);
        }
    }
    sts128f(SM_V + warp * 1024 + lane * 16, make_float4(acc[0], acc[1], acc[2], acc[3]));
    sts128f(SM_V + warp * 1024 + 512 + lane * 16, make_float4(acc[4], acc[5], acc[6], acc[7]));
    __syncthreads();
    if (tid < 128) {
        float2 sum = make_float2(0.f, 0.f);
#pragma unroll
        for (int w = 0; w < 16; w++) { const float2 p = lds64f(SM_V + w * 1024 + tid * 8); sum.x += p.x; sum.y += p.y; }
        *reinterpret_cast<float2*>(&gs->emb[j * NB * C + tid * 2]) = sum;
        bar_sync(1, 128);
        if (tid < 2) asm volatile("red.release.gpu.global.add.u32 [%0], 1;" ::"l"(&gs->wcnt[(2 * NB + tid) * LS]) : "memory");
    }
}

__global__ void __cluster_dims__(2, 1, 1) __launch_bounds__(NTHREADS, 1)
resblock_kernel(const __nv_bfloat16* __restrict__ w1, const __nv_bfloat16* __restrict__ x,
                const __nv_bfloat16* __restrict__ t_emb, const __nv_bfloat16* __restrict__ g1,
                const __nv_bfloat16* __restrict__ be1, const __nv_bfloat16* __restrict__ w_emb,
                const __nv_bfloat16* __restrict__ g2, const __nv_bfloat16* __restrict__ be2,
                const __nv_bfloat16* __restrict__ w2, __nv_bfloat16* __restrict__ out, Scratch* __restrict__ gs,
                const __grid_constant__ CUtensorMap xmap) {
    const unsigned clk0 = clock32();
    if (threadIdx.x == 480 && blockIdx.x >= NXTRA) TLG(1);
    const int tid = threadIdx.x, lane = tid & 31;
    const int cta = blockIdx.x - NXTRA, b = cta >> 6, r = cta & 63, rk = cta & 1;
    uint4 v[5];
    if (tid < 32) weight_load(v, w1, cta & (NCTA - 1), lane, true);
    uint4 xv[8];
    const int ch0 = (b & 1) * C + rk * 64;
    if (tid >= 32 && tid < 96) {
        const char* src = reinterpret_cast<const char*>(x) + (uint32_t)(((ch0 + (lane >> 3)) * HW + (r ^ (tid >> 6))) * HW * 2 + (lane & 7) * 16);
        while (clock32() - clk0 < XDELAY + (tid >> 6) * XSTAG2) {}
#pragma unroll
        for (int i = 0; i < 8; i++) xv[i] = __ldg(reinterpret_cast<const uint4*>(src + i * (4 * HW * HW * 2)));
    }
    const int warp = __shfl_sync(0xffffffffu, tid >> 5, 0);
    if (cta < 0) { side_jobs(t_emb, w_emb, w2, gs, clk0); return; }

    if (warp != 4) asm volatile("barrier.cluster.arrive.relaxed.aligned;" ::: "memory");
    const bool has_near = r != 0 && r != HW - 1, has_far = r != 1 && r != HW - 2;
    const uint32_t peer0 = mapa(0, rk ^ 1);
    if (warp == 1 || warp == 2 || warp == 3 || warp == 5) {
        const int i = warp < 4 ? warp - 1 : 3, gl = i >> 1, row = i & 1;
        const uint32_t tile = SM_XA + row * 8192 + gl * 4096;
        if (elect_one()) {
            if (gl) asm volatile("prefetch.tensormap [%0];" ::"l"(&xmap) : "memory");
            mbar_init(BAR(BAR_X) + 8 * i, 1);
            if (gl) { mbar_expect(BAR(BAR_X) + 8 * i, 4096); fence_async_smem(); }
        }
        __syncwarp();
        bar_arrive(4, 256 + 32 + 128);
        if (gl) {
            while (clock32() - clk0 < XDELAY + XSTAG + row * XSTAG2) {}
            if (elect_one()) tma_x(tile, &xmap, r ^ row, ch0 + 32, BAR(BAR_X) + 8 * i);
            __syncwarp();
            mbar_wait(BAR(BAR_X) + 8 * i, 0);
#pragma unroll
            for (int k = 0; k < 8; k++) xv[k] = lds128(tile + k * 512 + lane * 16);
        }
        float c[8][4];
#pragma unroll
        for (int k = 0; k < 8; k++) {
            c[k][0] = c[k][1] = c[k][2] = c[k][3] = 0.f;
            stat_mma(c[k], xv[k].x, xv[k].y); stat_mma(c[k], xv[k].z, xv[k].w);
        }
#pragma unroll
        for (int k = 0; k < 4; k++) c[0][k] = ((c[0][k] + c[1][k]) + (c[2][k] + c[3][k])) + ((c[4][k] + c[5][k]) + (c[6][k] + c[7][k]));
        stat_store(c[0], SM_RED + i * 48, lane);
        __syncwarp();
        if (lane == 0) {
            const uint32_t a = SM_RED + i * 48;
            red_add4(&gs->acc1[b * LS + (rk * 2 + gl) * 4], 1.f, sum4(lds128f(a + 32)), sum4(lds128f(a)) + sum4(lds128f(a + 16)), 1.f);
            TL(74 + i);
        }
        if (!gl) {
#pragma unroll
            for (int k = 0; k < 8; k++)
                sts128(tile + k * 512 + (lane >> 3) * 128 + (((lane & 7) ^ ((lane >> 3) + 4 * (k & 1))) << 4), xv[k]);
            __syncwarp();
            if (lane == 0) mbar_arrive(BAR(BAR_X) + 8 * i);
        }
    }
    if (warp == 4) {
        if (elect_one()) {
#pragma unroll
            for (int i = 0; i < NSTAGE; i++) mbar_init(BAR(BAR_FULL + i), (i & 1) ? 1 : ((i & 2) ? 2 : 9));
#pragma unroll
            for (int i = 0; i <= NS; i++) mbar_init(BAR(BAR_WEMPTY + i), 4);
#pragma unroll
            for (int i = BAR_STATS; i < BAR_X; i++) mbar_init(BAR(i), i == BAR_EMB ? 2 : 1);
            asm volatile("fence.mbarrier_init.release.cluster;" ::: "memory");
        }
        if (lane < 2) sts128(SM_GST + lane * 16, make_uint4(0, 0, 0, 0));
        __syncwarp();
        if (lane < 6) mbar_expect(BAR(BAR_RV) + 8 * lane, lane < 4 ? 4096 : (lane == 4 ? 16384 : 8192));
        fence_async_smem();
        bar_arrive(0, 96);
        bar_arrive(5, 64);
        bar_arrive(4, 256 + 32 + 128);
        const uint4 z = make_uint4(0, 0, 0, 0);
#pragma unroll
        for (int i = 0; i < 2; i++) sts128(SM_V + (i * 16 + (lane >> 1)) * CH_PITCH + (lane & 1) * 16, z);
        if (lane < 2) sts128(SM_V + NSTAGE * KC_BYTES + lane * 16, z);
        if (lane < 16) sts128(SM_ONES + lane * 16, make_uint4(lane < 8 ? 0x3f803f80u : 0u, 0, 0, 0));
        fence_async_smem();
        bar_arrive(7, 160);
        asm volatile("barrier.cluster.arrive.relaxed.aligned;" ::: "memory");
        while (clock32() - clk0 < W2DELAY) {}
        weight_load(v, w2, cta, lane, false);
    }
    if (warp == 0 || warp == 4 || warp >= 12) {
        const int k = warp < 8 ? warp >> 2 : (warp >> 1) & 1, kx = warp < 8 ? 0 : 1 + (warp & 1);
        if (kx == 0) {
#pragma unroll
            for (int i = 0; i < 5; i++)
                if (i < 4 || !(lane & 2)) sts128(SM_BNC + k * 2304 + (lane >> 2) * 288 + (lane & 3) * 16 + i * 64, v[i]);
            if (lane == 0) TL(k ? 14 : 81);
        }
        bar_sync(8 + k, 96);
        weight_block(SM_BNC + k * 2304, gs->wt + k * 32 * STAGE_BYTES, cta, lane, kx);
        if (kx) {
            bar_arrive(10 + k, 96);
        } else {
            bar_sync(10 + k, 96);
            if (lane < 2) asm volatile("red.relaxed.gpu.global.add.u32 [%0], 1;" ::"l"(k ? &gs->wcnt[(NB + lane) * LS] : &gs->w1cnt[(lane * 8 + wblk_kc(cta)) * KS]) : "memory");
            if (lane == 0) TL(k ? 13 : 4);
        }
    }

    if (warp >= 8) {
        const int nw = warp - 8;
        const unsigned one = gridDim.y;
        if (nw < 4) {
            const uint2 q = __ldg(reinterpret_cast<const uint2*>(nw == 0 ? g1 : (nw == 1 ? be1 : (nw == 2 ? g2 : be2))) + lane);
            sts128f(SM_COEF + nw * 512 + lane * 16, make_float4(0.5f * bf_lo(q.x), 0.5f * bf_hi(q.x), 0.5f * bf_lo(q.y), 0.5f * bf_hi(q.y)));
        }
        bar_sync(4, 256 + 32 + 128);
        asm volatile("barrier.cluster.wait.acquire.aligned;" ::: "memory");
        const int hf = nw >> 2, wq = nw & 3;
        const uint32_t v_off = SM_V + (lane & 3) * CH_PITCH + (2 + wq * 16 + hf * 8 + (lane >> 2)) * 16;
        const int crow = ((lane & 6) << 2) | ((lane >> 3) << 1) | (lane & 1);
        const uint32_t stg_off = crow * 128 + (((2 * wq + hf) ^ (crow & 7)) << 4);
        const uint32_t img_off = (tid - 256) * 16;
        const float sg = rk ? -1.f : 1.f;
        uint4* inbox = gs->box + cta * 1024 + (tid - 256);
#pragma unroll 1
        for (int conv = 0; conv < 2; conv++) {
            uint32_t u[4][4];
            if (conv == 0) {
#pragma unroll
                for (int i = 0; i < 4; i++) { mbar_wait(BAR(BAR_X + i), 0); ldsm4t(u[i], SM_XA + (i & 1) * 8192 + (i >> 1) * 4096 + stg_off); }
            } else {
                mbar_wait(BAR(BAR_HW), 0);
                mbar_wait(BAR(BAR_RH), 0);
#pragma unroll
                for (int i = 0; i < 4; i++) lds_piece(u[i], SM_XA + (i & 1) * 8192 + (i >> 1) * 4096 + img_off);
            }
            float ga[2][8], be[2][8], a[4][8];
#pragma unroll
            for (int g = 0; g < 2; g++) {
                const uint32_t ca = SM_COEF + conv * 1024 + (rk * 64 + g * 32 + (lane & 3) * 8) * 4;
                const float4 q0 = lds128f(ca), q1 = lds128f(ca + 16), q2 = lds128f(ca + 512), q3 = lds128f(ca + 528);
                ga[g][0] = q0.x; ga[g][1] = q0.y; ga[g][2] = q0.z; ga[g][3] = q0.w; ga[g][4] = q1.x; ga[g][5] = q1.y; ga[g][6] = q1.z; ga[g][7] = q1.w;
                be[g][0] = q2.x; be[g][1] = q2.y; be[g][2] = q2.z; be[g][3] = q2.w; be[g][4] = q3.x; be[g][5] = q3.y; be[g][6] = q3.z; be[g][7] = q3.w;
            }
#pragma unroll
            for (int i = 0; i < 16; i++) {
                a[i >> 2][2 * (i & 3)] = bf_lo(u[i >> 2][i & 3]) * ga[i >> 3][2 * (i & 3)];
                a[i >> 2][2 * (i & 3) + 1] = bf_hi(u[i >> 2][i & 3]) * ga[i >> 3][2 * (i & 3) + 1];
                asm volatile("" : "+f"(a[i >> 2][2 * (i & 3)]), "+f"(a[i >> 2][2 * (i & 3) + 1]));
            }
            float4 gv = make_float4(0.f, 0.f, 0.f, 0.f);
            bool have = false;
#pragma unroll
            for (int g = 0; g < 2; g++) {
                unsigned it = 0;
#pragma unroll 1
                while (!__all_sync(0xffffffffu, (g ? gv.z : gv.x) != 0.f) && ++it < 8 * SPIN_LIMIT)
                    asm volatile("ld.volatile.shared.v4.f32 {%0,%1,%2,%3}, [%4];" : "=f"(gv.x), "=f"(gv.y), "=f"(gv.z), "=f"(gv.w) : "r"(S0 + SM_GST + conv * 16) : "memory");
                if (g == 0 && tid == 256) TL(22 + conv * 4);
                const float rs = g ? gv.z : gv.x, mr = g ? gv.w : gv.y;
                uint32_t kp[4], sd[4];
#pragma unroll
                for (int i = 0; i < 8; i++) {
                    be[g][i] = fmaf(-mr, ga[g][i], be[g][i]);
                    a[2 * g][i] = silu_half(fmaf(a[2 * g][i], rs, be[g][i])); a[2 * g + 1][i] = silu_half(fmaf(a[2 * g + 1][i], rs, be[g][i]));
                }
#pragma unroll
                for (int i = 0; i < 4; i++) {
                    kp[i] = pack_bf(fmaf(a[2 * g][2 * i], sg, a[2 * g + 1][2 * i]), fmaf(a[2 * g][2 * i + 1], sg, a[2 * g + 1][2 * i + 1]));
                    sd[i] = pack_bf(fmaf(a[2 * g + 1][2 * i], -sg, a[2 * g][2 * i]), fmaf(a[2 * g + 1][2 * i + 1], -sg, a[2 * g][2 * i + 1]));
                }
                sts128(v_off + g * 4 * KC_BYTES, make_uint4(kp[0], kp[1], kp[2], kp[3]));
                st_async(peer0 + v_off + (g * 4 + 2) * KC_BYTES, sd[0], sd[1], sd[2], sd[3], peer0 + BAR(BAR_RV + g));
                const bool xo = g == 0 && mbar_test(BAR(BAR_XO), conv);
                publish(BAR(BAR_FULL + 4 * g), lane);
                if (tid == 256) TL(g ? 84 + conv : 8 + conv * 8);
                if (g == 0 && xo) { load_outer(u, conv, stg_off, img_off); have = true; }
            }
            if (!have) { mbar_wait(BAR(BAR_XO), conv); load_outer(u, conv, stg_off, img_off); }
            if (conv == 1) {
                unsigned it = 0;
                while (true) {
                    bool okn = true, okf = true;
#pragma unroll
                    for (int i = 0; i < 8; i++) { okn = okn && u[(i >> 2) * 2][i & 3] != 0; okf = okf && u[(i >> 2) * 2 + 1][i & 3] != 0; }
                    if (__all_sync(0xffffffffu, (okn || !has_near) && (okf || !has_far)) || ++it > SPIN_LIMIT) break;
#pragma unroll
                    for (int i = 0; i < 4; i++) ld_unit(u[i], inbox + (i & 1) * 512 + (i >> 1) * 256);
                    if (tid == 256) TL(93);
                }
            }
            if (tid == 256) TL(24 + conv * 4);
#pragma unroll
            for (int g = 0; g < 2; g++) {
                const float rs = g ? gv.z : gv.x;
                uint32_t o[2][4];
#pragma unroll
                for (int f = 0; f < 2; f++) {
                    const bool ok = f ? has_far : has_near;
#pragma unroll
                    for (int i = 0; i < 4; i++) {
                        const float lo = silu_half(fmaf(bf_lo(u[2 * g + f][i]), ga[g][2 * i] * rs, be[g][2 * i]));
                        const float hi = silu_half(fmaf(bf_hi(u[2 * g + f][i]), ga[g][2 * i + 1] * rs, be[g][2 * i + 1]));
                        o[f][i] = pack_bf((ok ? lo : 0.f) - a[2 * g + (f ^ 1)][2 * i], (ok ? hi : 0.f) - a[2 * g + (f ^ 1)][2 * i + 1]);
                    }
                }
                sts128(v_off + (8 + g * 4) * KC_BYTES, make_uint4(o[0][0], o[0][1], o[0][2], o[0][3]));
                st_async(peer0 + v_off + (10 + g * 4) * KC_BYTES, o[1][0], o[1][1], o[1][2], o[1][3], peer0 + BAR(BAR_RV + 2 + g));
                publish(BAR(BAR_FULL + 8 + 4 * g), lane);
                if (tid == 256) TL(g ? 88 + conv : 23 + conv * 4);
                if (one == 0) break;
            }
        }
        mbar_wait(BAR(BAR_FULL + NSTAGE - 1), 1);
#pragma unroll
        for (int i = 0; i < 4; i++) inbox[i * 256] = make_uint4(0, 0, 0, 0);
        {
            const int oc0 = hf * 64 + ((tid & 127) >> 3), seg = lane & 7;
            __nv_bfloat16* dst = out + ((size_t)(b * C + oc0) * HW + r) * HW + seg * 8;
            const uint32_t src = oc0 * 128 + ((seg ^ (oc0 & 7)) << 4);
            mbar_wait(BAR(BAR_XR), 0);
            uint4 xr[4];
#pragma unroll
            for (int i = 0; i < 4; i++) xr[i] = lds128(SM_XA + src + i * 2048);
            asm volatile("{\n.reg .pred p;\nsetp.eq.u64 p, %0, 0;\n@p st.shared.u32 [%1], 0;\n}" ::"l"(dst), "r"(src + S0) : "memory");
            bar_sync(hf ? 1 : 6, 128 + 128);
#pragma unroll
            for (int i = 0; i < 4; i++) {
                uint4 o = lds128(SM_XB + src + i * 2048);
                asm("add.rn.bf16x2 %0, %0, %1;" : "+r"(o.x) : "r"(xr[i].x)); asm("add.rn.bf16x2 %0, %0, %1;" : "+r"(o.y) : "r"(xr[i].y));
                asm("add.rn.bf16x2 %0, %0, %1;" : "+r"(o.z) : "r"(xr[i].z)); asm("add.rn.bf16x2 %0, %0, %1;" : "+r"(o.w) : "r"(xr[i].w));
                *reinterpret_cast<uint4*>(dst + (size_t)i * 16 * HW * HW) = o;
            }
            if (tid == 384) { TL(20); TLG(21); }
        }
    } else if (warp < 4) {
        const int wq = warp;
        bar_sync(7, 160);
        asm volatile("barrier.cluster.wait.acquire.aligned;" ::: "memory");
        const float sg = rk ? 1.f : -1.f;
        float d[64];
#pragma unroll 1
        for (int conv = 0; conv < 2; conv++) {
#pragma unroll
            for (int i = 0; i < 64; i++) d[i] = 0.f;
            uint32_t hp[32];
            fence_acc(d);
            mma_stages<0>(d, hp, conv, tid, peer0, gs);
            if (conv == 0) {
                asm volatile("wgmma.fence.sync.aligned;" ::: "memory");
                wgmma128<(SM_ONES >> 4) | (8u << 16), (SM_EMB >> 4), 0, 8>(d);
                asm volatile("wgmma.commit_group.sync.aligned;" ::: "memory");
            }
            asm volatile("wgmma.wait_group.sync.aligned 0;" ::: "memory");
            fence_acc(d);
            if (tid == 0) TL(10 + conv * 8);
#pragma unroll
            for (int i = 0; i < 32; i++) hp[i] = pack_bf(fmaf(bf_lo(hp[i]), sg, d[2 * i]), fmaf(bf_hi(hp[i]), sg, d[2 * i + 1]));
            if (conv == 1) {
                const uint32_t obase = SM_XB + ((lane >> 4) * 8 + (lane & 7)) * 128 + (((2 * wq + ((lane >> 3) & 1)) ^ (lane & 7)) << 4);
#pragma unroll
                for (int kc = 0; kc < 8; kc++) {
                    stsm4t(obase + kc * 2048, hp[4 * kc], hp[4 * kc + 1], hp[4 * kc + 2], hp[4 * kc + 3]);
                    if (kc == 3) bar_arrive(6, 128 + 128);
                }
                bar_arrive(1, 128 + 128);
                break;
            }
#pragma unroll
            for (int g = 0; g < 4; g++) {
                float c[4] = {0.f, 0.f, 0.f, 0.f};
#pragma unroll
                for (int i = 0; i < 4; i++) stat_mma(c, hp[8 * g + 2 * i], hp[8 * g + 2 * i + 1]);
                stat_store(c, SM_RED + (g * 4 + wq) * 48, lane);
            }
            bar_sync(2, 128);
            if (wq == 0) stat_publish(SM_RED, &gs->acc2[b * LS], lane, true);
            if (tid == 0) TL(11);
            if (tid == 32) mbar_expect(BAR(BAR_M), 16384);
#pragma unroll
            for (int j = 0; j < 8; j++) {
                const uint32_t p0 = hp[(j >> 1) * 8 + (j & 1)], p1 = hp[(j >> 1) * 8 + (j & 1) + 2], p2 = hp[(j >> 1) * 8 + (j & 1) + 4], p3 = hp[(j >> 1) * 8 + (j & 1) + 6];
                if ((j >> 2) == rk) sts128(SM_XA + (j & 3) * 2048 + tid * 16, make_uint4(p0, p1, p2, p3));
                else st_async(peer0 + SM_XA + 8192 + (j & 3) * 2048 + tid * 16, p0, p1, p2, p3, peer0 + BAR(BAR_RH));
            }
            __syncwarp();
            if (lane == 0) { mbar_arrive(BAR(BAR_HW)); mbar_arrive(BAR(BAR_WEMPTY + 7)); }
            if (has_near) {
                const int oc2 = (cta & ~1) + (rk ? 2 : -2);
#pragma unroll
                for (int j = 0; j < 8; j++) {
                    uint4* outbox = gs->box + (oc2 + (j >> 2)) * 1024 + (((j >> 2) == rk) ? 512 : 0) + (j & 3) * 128 + tid;
                    *outbox = make_uint4(max(hp[(j >> 1) * 8 + (j & 1)], 1u), max(hp[(j >> 1) * 8 + (j & 1) + 2], 1u),
                                         max(hp[(j >> 1) * 8 + (j & 1) + 4], 1u), max(hp[(j >> 1) * 8 + (j & 1) + 6], 1u));
                }
            }
            if (tid == 0) TL(12);
        }
    } else if (warp < 6) {
        if (warp == 5) {
            bar_sync(5, 64);
            if (elect_one()) {
                mbar_expect(BAR(BAR_XO), 16384);
                while (clock32() - clk0 < ODELAY) {}
#pragma unroll
                for (int i = 0; i < 4; i++)
                    tma_x(SM_XB + i * 4096, &xmap, ((i >> 1) ^ rk) ? (r | 1) + 1 : (r & ~1) - 1, ch0 + (i & 1) * 32, BAR(BAR_XO));
            }
            __syncwarp();
#pragma unroll 1
            for (int i = 0; i < 8; i++) {
                mbar_wait(BAR(BAR_RV) + 8 * (i & 3), i >> 2);
                fence_async_smem();
                if (lane == 0) {
                    mbar_arrive(BAR(BAR_FULL + 2) + 32 * (i & 3));
                    if (i < 4) mbar_expect(BAR(BAR_RV) + 8 * i, 4096);
                    TL(64 + i);
                }
                __syncwarp();
            }
        } else {
            mbar_wait(BAR(BAR_STATS), 0);
            unsigned it = 0;
            while (!__all_sync(0xffffffffu, ld_relaxed(&gs->wcnt[(2 * NB + b) * LS]) >= (unsigned)NXTRA) && ++it < SPIN_LIMIT) __nanosleep(100);
            fence_acquire();
            float ev[4] = {0.f, 0.f, 0.f, 0.f};
#pragma unroll
            for (int j = 0; j < NXTRA; j++) {
                const uint4 ef = ld_relaxed_v4(&gs->emb[(j * NB + b) * C + lane * 4]);
                ev[0] += __uint_as_float(ef.x); ev[1] += __uint_as_float(ef.y); ev[2] += __uint_as_float(ef.z); ev[3] += __uint_as_float(ef.w);
            }
#pragma unroll
            for (int i = 0; i < 4; i++) {
                const float hi = bf_lo(pack_bf(ev[i], 0.f));
                sts128(SM_EMB + n_to_oc(lane * 4 + i) * 16, make_uint4(pack_bf(hi, ev[i] - hi), 0, 0, 0));
            }
            fence_async_smem();
            __syncwarp();
            if (lane == 0) { mbar_arrive(BAR(BAR_EMB)); TL(19); }
            mbar_wait(BAR(BAR_HW), 0);
            {
                const unsigned c1 = clock32();
#pragma unroll 1
                while (clock32() - c1 < FDELAY && !mbar_test(BAR(BAR_STATS), 1)) {}
                if (elect_one()) {
                    mbar_expect(BAR(BAR_XO), 16384);
                    bulk_g2s(S0 + SM_XB, gs->box + cta * 1024, 16384, S0 + BAR(BAR_XO));
                }
                __syncwarp();
            }
            mbar_wait(BAR(BAR_FULL + 8), 1);
            if (elect_one()) {
                mbar_expect(BAR(BAR_XR), 16384);
#pragma unroll
                for (int i = 0; i < 4; i++) tma_x(SM_XA + i * 4096, &xmap, r, b * C + i * 32, BAR(BAR_XR));
            }
        }
    } else if (warp == 6) {
        bar_sync(0, 96);
        if (lane < NSTAGE) mbar_expect(BAR(BAR_FULL) + 8 * lane, STAGE_BYTES);
        const unsigned char* wbase = gs->wt + rk * 8 * STAGE_BYTES;
        unsigned it = 0;
        {
            int g = 0;
            const int l7 = lane & 7;
            const unsigned* cnt = &gs->w1cnt[(b * 8 + ((((l7 >> 1) ^ rk) & 1) * 4 + (l7 >> 2) * 2 + (l7 & 1))) * KS];
            unsigned cv = ld_relaxed(cnt);
#pragma unroll 1
            while (g < NS) {
                unsigned ready = __ballot_sync(0xffffffffu, cv >= 16u);
                if (ready != ~0u) cv = ld_relaxed(cnt);
                ready >>= g;
                if (++it > SPIN_LIMIT) ready = ~0u;
                if (!(ready & 1)) continue;
                fence_async_global();
                if (lane == 0) TL(g ? 3 : 6);
#pragma unroll 1
                for (; (ready & 1) && g < NS; g++, ready >>= 1)
                    if (elect_one())
                        bulk_g2s(S0 + SM_W + g * STAGE_BYTES, wbase + ((((g >> 1) ^ rk) & 1) * 4 + (g >> 2) * 2 + (g & 1)) * STAGE_BYTES, STAGE_BYTES,
                                 S0 + BAR(BAR_FULL) + 8 * g);
            }
        }
#pragma unroll 1
        for (int q = 2; q < 8; q++) {
            const unsigned char* wsrc = wbase + ((q >> 1) * 16 + (q & 1) * 2) * STAGE_BYTES;
            const uint32_t par = ((q >> 1) - 1) & 1;
            if (q == 4) {
                it = 0;
                while (!__all_sync(0xffffffffu, ld_relaxed(&gs->wcnt[(NB + b) * LS]) == (unsigned)NCTA) && ++it < SPIN_LIMIT) {}
                fence_acquire();
                fence_async_global();
                if (lane == 0) { mbar_arrive(BAR(BAR_EMB)); TL(2); }
            }
#pragma unroll
            for (int i = 0; i < 4; i++) {
                mbar_wait(BAR(BAR_WEMPTY + i) + 32 * (q & 1), par);
                if (i == 0 && (q == 4 || q == 6)) {
                    if ((lane >> 3) == (q - 4) / 2) mbar_expect(BAR(BAR_FULL) + 8 * lane, STAGE_BYTES);
                    __syncwarp();
                }
                if (elect_one())
                    bulk_g2s(S0 + SM_W + ((q & 1) * 4 + i) * STAGE_BYTES, wsrc + ((((i >> 1) ^ rk) & 1) * 4 + (i & 1)) * STAGE_BYTES, STAGE_BYTES,
                             S0 + BAR(BAR_FULL + i) + 32 * (q & 3));
            }
        }
    } else {
        bar_sync(0, 96);
#pragma unroll 1
        for (int conv = 0; conv < 2; conv++) {
            if (conv == 1) mbar_wait(BAR(BAR_HW), 0);
            const float* asrc = (conv ? gs->acc2 : gs->acc1) + b * LS + (rk * 2 + (lane & 1)) * 4;
            unsigned it = 0;
#pragma unroll 1
            while (true) {
                const uint4 f = ld_relaxed_v4(asrc);
                const bool ok = ((f.x == 0x42800000u) & (f.w == 0x42800000u)) || ++it > SPIN_LIMIT;
                if (ok && lane < 2) {
                    const float inv_n = 1.0f / (32.0f * HW * HW);
                    const float mean = __uint_as_float(f.y) * inv_n;
                    float rs;
                    asm("rsqrt.approx.ftz.f32 %0, %1;" : "=f"(rs) : "f"(fmaxf(fmaf(-mean, mean, __uint_as_float(f.z) * inv_n), 0.f) + 1e-5f));
                    asm volatile("st.shared.v2.f32 [%0], {%1,%2};" ::"r"(S0 + SM_GST + conv * 16 + lane * 8), "f"(rs == 0.f ? 1.2e-38f : rs), "f"(mean * rs) : "memory");
                }
                if (__all_sync(0xffffffffu, ok)) break;
            }
            if (lane == 0) { mbar_arrive(BAR(BAR_STATS)); TL(7 + conv * 8); }
        }
        if (r == 0) {
            if (lane < 16) gs->acc1[b * LS + lane] = 0.f;
            if (lane < 3) gs->wcnt[(lane * NB + b) * LS] = 0;
            if (lane < 8) gs->w1cnt[(b * 8 + lane) * KS] = 0;
        }
    }
}

}

extern "C" void kernel_launch(void* const* d_in, const int* in_sizes, int n_in, void* d_out, int out_size) {
    (void)in_sizes; (void)n_in; (void)out_size;
    typedef CUresult (*EncodeFn)(CUtensorMap*, CUtensorMapDataType, cuuint32_t, void*, const cuuint64_t*, const cuuint64_t*,
                                 const cuuint32_t*, const cuuint32_t*, CUtensorMapInterleave, CUtensorMapSwizzle,
                                 CUtensorMapL2promotion, CUtensorMapFloatOOBfill);
    static Scratch* gs = nullptr;
    static EncodeFn encode = nullptr;
    if (!gs) {
        cudaFuncSetAttribute(resblock_kernel, cudaFuncAttributeMaxDynamicSharedMemorySize, SM_TOTAL);
        cudaGetSymbolAddress((void**)&gs, g_scratch);
        cudaDriverEntryPointQueryResult qr;
        cudaGetDriverEntryPoint("cuTensorMapEncodeTiled", (void**)&encode, cudaEnableDefault, &qr);
    }
    CUtensorMap xmap;
    const cuuint64_t dims[3] = {HW, HW, NB * C}, strides[2] = {HW * 2, HW * HW * 2};
    const cuuint32_t box[3] = {HW, 1, 32}, es[3] = {1, 1, 1};
    encode(&xmap, CU_TENSOR_MAP_DATA_TYPE_BFLOAT16, 3, d_in[0], dims, strides, box, es, CU_TENSOR_MAP_INTERLEAVE_NONE,
           CU_TENSOR_MAP_SWIZZLE_128B, CU_TENSOR_MAP_L2_PROMOTION_NONE, CU_TENSOR_MAP_FLOAT_OOB_FILL_NONE);
    resblock_kernel<<<NCTA + NXTRA, NTHREADS, SM_TOTAL>>>(
        (const __nv_bfloat16*)d_in[4], (const __nv_bfloat16*)d_in[0], (const __nv_bfloat16*)d_in[1],
        (const __nv_bfloat16*)d_in[2], (const __nv_bfloat16*)d_in[3], (const __nv_bfloat16*)d_in[5],
        (const __nv_bfloat16*)d_in[6], (const __nv_bfloat16*)d_in[7], (const __nv_bfloat16*)d_in[8],
        (__nv_bfloat16*)d_out, gs, xmap);
}
```

```cpp
#include <cuda_runtime.h>
#include <cuda.h>
#include <cuda_bf16.h>
#include <stdint.h>

namespace {

constexpr int C = 128, HW = 64, NB = 2, E = 768;
constexpr int NCTA = NB * HW;
constexpr int NXTRA = 4;
constexpr int NTHREADS = 16 * 32;
constexpr int CH_PITCH = 66 * 16;
constexpr int KC_BYTES = 2 * CH_PITCH;
constexpr int STAGE_BYTES = 12288;
constexpr int NSTAGE = 16;
constexpr int NS = 8;
#define XDELAY 300
#define XSTAG 800
#define XSTAG2 100
#define SDELAY 600
#define W2DELAY 2400
#define ODELAY 3400
#define FDELAY 1400

constexpr uint32_t SMEM_BASE = 0x400;
constexpr uint32_t SM_XA = SMEM_BASE;
constexpr uint32_t SM_XB = SM_XA + 16384;
constexpr uint32_t SM_M = SM_XB + 16384;
constexpr uint32_t SM_V = SM_M + 16384;
constexpr uint32_t SM_W = SM_V + NSTAGE * KC_BYTES + 128;
constexpr uint32_t SM_COEF = SM_W + NS * STAGE_BYTES;
constexpr uint32_t SM_GST = SM_COEF + 2048;
constexpr uint32_t SM_EMB = SM_GST + 128;
constexpr uint32_t SM_ONES = SM_EMB + 2048;
constexpr uint32_t SM_RED = SM_ONES + 256;
constexpr uint32_t SM_BNC = SM_RED + 1024;
constexpr uint32_t SM_BAR = SM_BNC + 2 * 2304;
constexpr int BAR_FULL = 0, BAR_WEMPTY = NSTAGE, BAR_HW = BAR_WEMPTY + NS, BAR_STATS = BAR_HW + 1, BAR_EMB = BAR_STATS + 1,
              BAR_RV = BAR_EMB + 1  , BAR_M = BAR_RV + 4, BAR_RH = BAR_M + 1, BAR_XO = BAR_RH + 1, BAR_XR = BAR_XO + 1,
              BAR_X = BAR_XR + 1  , NBAR = BAR_X + 4;
constexpr int SM_TOTAL = SM_BAR + NBAR * 8 - SMEM_BASE;
static_assert(SM_TOTAL <= 232448, "smem");
__host__ __device__ constexpr uint32_t BAR(int i) { return SM_BAR + 8 * i; }

constexpr unsigned SPIN_LIMIT = 1u << 16;
constexpr int LS = 1056, KS = 32;

struct Scratch {
    float acc1[NB * LS];
    float acc2[NB * LS];
    unsigned wcnt[3 * NB * LS];
    unsigned w1cnt[NB * 8 * KS];
    float emb[NXTRA * NB * C];
    alignas(1024) unsigned char wt[2 * 32 * STAGE_BYTES];
    uint4 box[NCTA * 1024];
};
__device__ __align__(1024) Scratch g_scratch;
#define TL(i) do {} while (0)
#define TLG(i) do {} while (0)

__device__ __forceinline__ unsigned clock32() { unsigned c; asm volatile("mov.u32 %0, %%clock;" : "=r"(c)); return c; }
__device__ __forceinline__ uint32_t mapa(uint32_t a, uint32_t rank) {
    uint32_t d;
    asm("mapa.shared::cluster.u32 %0, %1, %2;" : "=r"(d) : "r"(a), "r"(rank));
    return d;
}
#define S0 mapa(0, blockIdx.x & 1)
__device__ __forceinline__ void mbar_init(uint32_t bar, int cnt) {
    asm volatile("mbarrier.init.shared::cta.b64 [%0], %1;" ::"r"(bar + S0), "r"(cnt) : "memory");
}
__device__ __forceinline__ void mbar_arrive(uint32_t bar) {
    asm volatile("mbarrier.arrive.shared::cta.b64 _, [%0];" ::"r"(bar + S0) : "memory");
}
__device__ __forceinline__ void mbar_expect(uint32_t bar, uint32_t bytes) {
    asm volatile("mbarrier.arrive.expect_tx.shared::cta.b64 _, [%0], %1;" ::"r"(bar + S0), "r"(bytes) : "memory");
}
__device__ __forceinline__ bool mbar_try(uint32_t bar, uint32_t par) {
    uint32_t ok;
    asm volatile("{\n.reg .pred p;\nmbarrier.try_wait.parity.shared::cta.b64 p, [%1], %2;\nselp.u32 %0, 1, 0, p;\n}"
                 : "=r"(ok) : "r"(bar + S0), "r"(par) : "memory");
    return ok;
}
__device__ __forceinline__ bool mbar_test(uint32_t bar, uint32_t par) {
    uint32_t ok;
    asm volatile("{\n.reg .pred p;\nmbarrier.test_wait.parity.shared::cta.b64 p, [%1], %2;\nselp.u32 %0, 1, 0, p;\n}"
                 : "=r"(ok) : "r"(bar + S0), "r"(par) : "memory");
    return ok;
}
__device__ __forceinline__ void mbar_wait(uint32_t bar, uint32_t par) {
    unsigned it = 0;
#pragma unroll 1
    while (!mbar_try(bar, par) && ++it < SPIN_LIMIT) {}
}
__device__ __forceinline__ bool elect_one() {
    uint32_t p;
    asm volatile("{\n.reg .pred p;\nelect.sync _|p, 0xffffffff;\nselp.u32 %0, 1, 0, p;\n}" : "=r"(p));
    return p;
}
__device__ __forceinline__ void fence_async_smem() { asm volatile("fence.proxy.async.shared::cta;" ::: "memory"); }
__device__ __forceinline__ void fence_async_global() { asm volatile("fence.proxy.async.global;" ::: "memory"); }
__device__ __forceinline__ void fence_acquire() { asm volatile("fence.acquire.gpu;" ::: "memory"); }
__device__ __forceinline__ void bar_sync(int id, int n) { asm volatile("bar.sync %0, %1;" ::"r"(id), "r"(n) : "memory"); }
__device__ __forceinline__ void bar_arrive(int id, int n) { asm volatile("bar.arrive %0, %1;" ::"r"(id), "r"(n) : "memory"); }
__device__ __forceinline__ void bulk_g2s(uint32_t dst, const void* src, uint32_t bytes, uint32_t bar) {
    asm volatile("cp.async.bulk.shared::cluster.global.mbarrier::complete_tx::bytes [%0], [%1], %2, [%3];"
                 ::"r"(dst), "l"(src), "r"(bytes), "r"(bar) : "memory");
}
__device__ __forceinline__ void tma_x(uint32_t dst, const CUtensorMap* tm, int row, int ch, uint32_t bar) {
    asm volatile("cp.async.bulk.tensor.3d.shared::cluster.global.mbarrier::complete_tx::bytes [%0], [%1, {%2, %3, %4}], [%5];"
                 ::"r"(dst + S0), "l"(tm), "r"(0), "r"(row), "r"(ch), "r"(bar + S0) : "memory");
}
__device__ __forceinline__ uint4 ld_relaxed_v4(const void* p) {
    uint4 v;
    asm volatile("ld.relaxed.gpu.global.v4.u32 {%0,%1,%2,%3}, [%4];" : "=r"(v.x), "=r"(v.y), "=r"(v.z), "=r"(v.w) : "l"(p) : "memory");
    return v;
}
__device__ __forceinline__ unsigned ld_relaxed(const void* p) {
    unsigned v;
    asm volatile("ld.relaxed.gpu.global.u32 %0, [%1];" : "=r"(v) : "l"(p) : "memory");
    return v;
}
__device__ __forceinline__ void red_add4(float* p, float a, float b, float c, float d) {
    asm volatile("red.relaxed.gpu.global.add.v4.f32 [%0], {%1,%2,%3,%4};" ::"l"(p), "f"(a), "f"(b), "f"(c), "f"(d) : "memory");
}
__device__ __forceinline__ void sts128(uint32_t a, uint4 v) {
    asm volatile("st.shared.v4.u32 [%0], {%1,%2,%3,%4};" ::"r"(a + S0), "r"(v.x), "r"(v.y), "r"(v.z), "r"(v.w) : "memory");
}
__device__ __forceinline__ void sts128f(uint32_t a, float4 v) {
    asm volatile("st.shared.v4.f32 [%0], {%1,%2,%3,%4};" ::"r"(a + S0), "f"(v.x), "f"(v.y), "f"(v.z), "f"(v.w) : "memory");
}
__device__ __forceinline__ void sts32f(uint32_t a, float v) { asm volatile("st.shared.f32 [%0], %1;" ::"r"(a + S0), "f"(v) : "memory"); }
__device__ __forceinline__ uint4 lds128(uint32_t a) {
    uint4 v;
    asm volatile("ld.shared.v4.u32 {%0,%1,%2,%3}, [%4];" : "=r"(v.x), "=r"(v.y), "=r"(v.z), "=r"(v.w) : "r"(a + S0) : "memory");
    return v;
}
__device__ __forceinline__ float4 lds128f(uint32_t a) {
    float4 v;
    asm volatile("ld.shared.v4.f32 {%0,%1,%2,%3}, [%4];" : "=f"(v.x), "=f"(v.y), "=f"(v.z), "=f"(v.w) : "r"(a + S0) : "memory");
    return v;
}
__device__ __forceinline__ float2 lds64f(uint32_t a) {
    float2 v;
    asm volatile("ld.shared.v2.f32 {%0,%1}, [%2];" : "=f"(v.x), "=f"(v.y) : "r"(a + S0) : "memory");
    return v;
}
__device__ __forceinline__ float bf_lo(uint32_t u) { return __uint_as_float(u << 16); }
__device__ __forceinline__ float bf_hi(uint32_t u) { return __uint_as_float(u & 0xffff0000u); }
__device__ __forceinline__ uint32_t pack_bf(float lo, float hi) {
    uint32_t r;
    asm("cvt.rn.bf16x2.f32 %0, %1, %2;" : "=r"(r) : "f"(hi), "f"(lo));
    return r;
}
__device__ __forceinline__ float tanh_fast(float x) {
    float r;
    asm("tanh.approx.f32 %0, %1;" : "=f"(r) : "f"(x));
    return r;
}
__device__ __forceinline__ float silu_half(float h) { return fmaf(h, tanh_fast(h), h); }
__device__ __forceinline__ void ldsm4(uint32_t (&u)[4], uint32_t a) {
    asm volatile("ldmatrix.sync.aligned.m8n8.x4.shared.b16 {%0,%1,%2,%3}, [%4];"
                 : "=r"(u[0]), "=r"(u[1]), "=r"(u[2]), "=r"(u[3]) : "r"(a + S0) : "memory");
}
__device__ __forceinline__ void ldsm4t(uint32_t (&u)[4], uint32_t a) {
    asm volatile("ldmatrix.sync.aligned.m8n8.x4.trans.shared.b16 {%0,%1,%2,%3}, [%4];"
                 : "=r"(u[0]), "=r"(u[1]), "=r"(u[2]), "=r"(u[3]) : "r"(a + S0) : "memory");
}
__device__ __forceinline__ void stsm4(uint32_t a, uint32_t p0, uint32_t p1, uint32_t p2, uint32_t p3) {
    asm volatile("stmatrix.sync.aligned.m8n8.x4.shared.b16 [%0], {%1,%2,%3,%4};" ::"r"(a + S0), "r"(p0), "r"(p1), "r"(p2), "r"(p3) : "memory");
}
__device__ __forceinline__ void stsm4t(uint32_t a, uint32_t p0, uint32_t p1, uint32_t p2, uint32_t p3) {
    asm volatile("stmatrix.sync.aligned.m8n8.x4.trans.shared.b16 [%0], {%1,%2,%3,%4};" ::"r"(a + S0), "r"(p0), "r"(p1), "r"(p2), "r"(p3) : "memory");
}

#define R8(o) "+f"(d[o]), "+f"(d[o + 1]), "+f"(d[o + 2]), "+f"(d[o + 3]), "+f"(d[o + 4]), "+f"(d[o + 5]), "+f"(d[o + 6]), "+f"(d[o + 7])
template <uint32_t ALO, uint32_t BLO, uint64_t AHI = 8, uint64_t BHI = 48>
__device__ __forceinline__ void wgmma128(float (&d)[64]) {
    asm volatile(
        "wgmma.mma_async.sync.aligned.m64n128k16.f32.bf16.bf16 "
        "{%0,%1,%2,%3,%4,%5,%6,%7,%8,%9,%10,%11,%12,%13,%14,%15,%16,%17,%18,%19,%20,%21,%22,%23,%24,%25,%26,%27,%28,%29,%30,%31,"
        "%32,%33,%34,%35,%36,%37,%38,%39,%40,%41,%42,%43,%44,%45,%46,%47,%48,%49,%50,%51,%52,%53,%54,%55,%56,%57,%58,%59,%60,%61,%62,%63},"
        " %64, %65, 1, 1, 1, 0, 0;"
        : R8(0), R8(8), R8(16), R8(24), R8(32), R8(40), R8(48), R8(56)
        : "l"((AHI << 32) | ALO), "l"((BHI << 32) | BLO));
}
__device__ __forceinline__ void stat_mma(float (&c)[4], uint32_t p, uint32_t q) {
    asm("mma.sync.aligned.m16n8k16.row.col.f32.bf16.bf16.f32 {%0,%1,%2,%3}, {%4,%5,%6,%5}, {%4,%6}, {%0,%1,%2,%3};"
        : "+f"(c[0]), "+f"(c[1]), "+f"(c[2]), "+f"(c[3]) : "r"(p), "r"(0x3f803f80u), "r"(q));
}
__device__ __forceinline__ void stat_store(const float (&c)[4], uint32_t dst, int lane) {
    const int g = lane >> 2, t = lane & 3;
    if (t == (g >> 1)) sts32f(dst + g * 4, (g & 1) ? c[1] : c[0]);
    if (g == 7) sts32f(dst + 32 + t * 4, c[2] + c[3]);
}
__device__ __forceinline__ float sum4(float4 v) { return (v.x + v.y) + (v.z + v.w); }
__device__ __forceinline__ void stat_publish(uint32_t src, float* acc, int lane, bool real) {
    const uint32_t a = src + (lane & 15) * 48;
    float q = sum4(lds128f(a)) + sum4(lds128f(a + 16)), sm = sum4(lds128f(a + 32));
    q += __shfl_xor_sync(0xffffffffu, q, 1); sm += __shfl_xor_sync(0xffffffffu, sm, 1);
    q += __shfl_xor_sync(0xffffffffu, q, 2); sm += __shfl_xor_sync(0xffffffffu, sm, 2);
    if (real && (lane & 19) == 0) red_add4(acc + lane, 1.f, sm, q, 1.f);
}
__device__ __forceinline__ void fence_acc(float (&d)[64]) {
#pragma unroll
    for (int i = 0; i < 64; i++) asm volatile("" : "+f"(d[i])::"memory");
}
__device__ __forceinline__ void ld_unit(uint32_t (&u)[4], const uint4* p) {
    asm volatile("ld.relaxed.gpu.global.v4.u32 {%0,%1,%2,%3}, [%4];" : "=r"(u[0]), "=r"(u[1]), "=r"(u[2]), "=r"(u[3]) : "l"(p) : "memory");
}

__device__ __forceinline__ void st_async(uint32_t dst, uint32_t a, uint32_t b, uint32_t c, uint32_t d, uint32_t bar) {
    asm volatile("st.async.shared::cluster.mbarrier::complete_tx::bytes.v4.b32 [%0], {%1,%2,%3,%4}, [%5];"
                 ::"r"(dst), "r"(a), "r"(b), "r"(c), "r"(d), "r"(bar) : "memory");
}
template <int J>
__device__ __forceinline__ void send_m(const float (&d)[64], int tid, uint32_t peer0) {
    st_async(peer0 + SM_M + J * 2048 + tid * 16, pack_bf(d[8 * J], d[8 * J + 1]), pack_bf(d[8 * J + 2], d[8 * J + 3]),
             pack_bf(d[8 * J + 4], d[8 * J + 5]), pack_bf(d[8 * J + 6], d[8 * J + 7]), peer0 + BAR(BAR_M));
}
template <int S>
__device__ __forceinline__ void mma_stages(float (&d)[64], float (&e)[64], int conv, int tid, uint32_t peer0, Scratch* gs) {
    constexpr uint32_t A = ((SM_V + S * KC_BYTES + 16) >> 4) | ((CH_PITCH >> 4) << 16);
    constexpr uint32_t B = ((SM_W + (S % NS) * STAGE_BYTES) >> 4) | (8u << 16);
    if (S == 0) mbar_wait(BAR(BAR_FULL), conv);
    constexpr uint32_t NEXT = S + 1 < NSTAGE ? BAR(BAR_FULL + S + 1) : BAR(BAR_EMB);
    const int npar = S + 1 < NSTAGE ? conv : 0;
    const bool next_ok = mbar_test(NEXT, npar);
    if ((S & 7) == 0 && tid == 0) TL(32 + conv * 16 + S);
    asm volatile("wgmma.fence.sync.aligned;" ::: "memory");
    wgmma128<A, B>(S < 8 ? d : e);
    if constexpr (S >= 9 && S < 12) send_m<(S - 9) * 2 + 2>(d, tid, peer0);
    wgmma128<A + 1, B + 16>(S < 8 ? d : e);
    if constexpr (S >= 9 && S < 12) send_m<(S - 9) * 2 + 3>(d, tid, peer0);
    wgmma128<A + 2, B + 32>(S < 8 ? d : e);
    asm volatile("wgmma.commit_group.sync.aligned;" ::: "memory");
    if (S > 0) {
        asm volatile("wgmma.wait_group.sync.aligned 1;" ::: "memory");
        if ((tid & 31) == 0) mbar_arrive(BAR(BAR_WEMPTY + (S - 1) % NS));
    }
    if constexpr (S == 8) { fence_acc(d); send_m<0>(d, tid, peer0); send_m<1>(d, tid, peer0); }
    if (!next_ok) mbar_wait(NEXT, npar);
    if constexpr (S + 1 < NSTAGE) mma_stages<S + 1>(d, e, conv, tid, peer0, gs);
}

__device__ __forceinline__ int wblk_kc(int cta) { const int i = cta >> 4; return (i & 1) | ((i & 2) << 1) | ((i & 4) >> 1); }
__device__ __forceinline__ int n_to_oc(int n) { return (n & ~31) | ((n & 6) << 2) | ((n >> 2) & 6) | (n & 1); }
__device__ __forceinline__ void weight_load(uint4 (&t)[5], const __nv_bfloat16* w, int cta, int lane, bool perm) {
    const int n = (cta & 15) * 8 + (lane >> 2);
    const char* base = reinterpret_cast<const char*>(w) + (uint32_t)(((perm ? n_to_oc(n) : n) * 8 + wblk_kc(cta)) * 288 + (lane & 3) * 16);
#pragma unroll
    for (int k = 0; k < 5; k++)
        if (k < 4 || !(lane & 2)) t[k] = __ldg(reinterpret_cast<const uint4*>(base + k * 64));
}
__device__ __forceinline__ void st_global64(void* p, uint32_t a, uint32_t b) { asm volatile("st.global.v2.u32 [%0], {%1,%2};" ::"l"(p), "r"(a), "r"(b) : "memory"); }
__device__ __forceinline__ unsigned weight_block(uint32_t bounce, unsigned char* wt, int cta, int lane, int kx) {
    unsigned char* piece = wt + wblk_kc(cta) * STAGE_BYTES + (cta & 15) * 768 + kx * 256;
    uint32_t g[3][4];
#pragma unroll
    for (int i = 0; i < 12; i++)
        asm volatile("ld.shared.u16 %0, [%1];" : "=r"(g[i % 3][i / 3]) : "r"(S0 + bounce + (lane & 7) * 288 + (lane >> 3) * 72 + kx * 2 + i * 6) : "memory");
    float u1[4], u2[4];
#pragma unroll
    for (int c = 0; c < 4; c++) {
        const float t = 0.5f * (bf_lo(g[0][c]) + bf_lo(g[2][c]));
        u1[c] = fmaf(bf_lo(g[1][c]), 0.5f, t); u2[c] = fmaf(bf_lo(g[1][c]), -0.5f, t);
    }
    unsigned char* dst = piece + (lane >> 4) * 128 + (lane & 7) * 16 + ((lane >> 3) & 1) * 8;
    st_global64(dst, pack_bf(u1[0], u1[1]), pack_bf(u1[2], u1[3]));
    st_global64(dst + 8 * STAGE_BYTES, pack_bf(u2[0], u2[1]), pack_bf(u2[2], u2[3]));
    st_global64(dst + 16 * STAGE_BYTES, __byte_perm(g[0][0], g[0][1], 0x5410), __byte_perm(g[0][2], g[0][3], 0x5410));
    st_global64(dst + 24 * STAGE_BYTES, __byte_perm(g[2][0], g[2][1], 0x5410), __byte_perm(g[2][2], g[2][3], 0x5410));
    return ld_relaxed(piece + (lane >> 3) * 8 * STAGE_BYTES + (lane & 7) * 32);
}
__device__ __forceinline__ void publish(uint32_t bar, int lane) {
    fence_async_smem();
    __syncwarp();
    if (lane == 0) mbar_arrive(bar);
}
__device__ __forceinline__ void lds_piece(uint32_t (&u)[4], uint32_t a) {
    const uint4 q = lds128(a);
    u[0] = q.x; u[1] = q.y; u[2] = q.z; u[3] = q.w;
}
__device__ __forceinline__ void load_outer(uint32_t (&u)[4][4], int conv, uint32_t stg_off, uint32_t img_off) {
#pragma unroll
    for (int i = 0; i < 4; i++) {
        if (conv == 0) ldsm4t(u[i], SM_XB + (i & 1) * 8192 + (i >> 1) * 4096 + stg_off);
        else lds_piece(u[i], SM_XB + (i & 1) * 8192 + (i >> 1) * 4096 + img_off);
    }
}
__device__ __noinline__ void side_jobs(const __nv_bfloat16* __restrict__ t_emb, const __nv_bfloat16* __restrict__ w_emb,
                                       const __nv_bfloat16* __restrict__ w2, Scratch* __restrict__ gs, unsigned clk0) {
    const int tid = threadIdx.x, warp = tid >> 5, lane = tid & 31, j = blockIdx.x;
    float tv = 0.f;
    if (lane < 24) tv = __bfloat162float(t_emb[(lane / 12) * E + j * 192 + warp * 12 + lane % 12]);
    if (tid == 0) {
        mbar_init(BAR(0), 1);
        mbar_expect(BAR(0), 192 * C * 2);
        fence_async_smem();
        while (clock32() - clk0 < SDELAY) {}
#pragma unroll
        for (int i = 0; i < 4; i++)
            asm volatile("cp.async.bulk.prefetch.L2.global [%0], 18432;" ::"l"(reinterpret_cast<const char*>(w2) + (j * 4 + i) * 18432) : "memory");
#pragma unroll
        for (int i = 0; i < 4; i++) bulk_g2s(S0 + SM_W + i * 12288, w_emb + (j * 192 + i * 48) * C, 12288, S0 + BAR(0));
    }
    if (j == 0 && tid < 32) gs->acc2[(tid >> 4) * LS + (tid & 15)] = 0.f;
    const float sv = silu_half(0.5f * tv);
    __syncthreads();
    mbar_wait(BAR(0), 0);
    float acc[8] = {0.f, 0.f, 0.f, 0.f, 0.f, 0.f, 0.f, 0.f};
#pragma unroll
    for (int i = 0; i < 12; i++) {
        const float2 wq = lds64f(SM_W + (warp * 12 + i) * 256 + lane * 8);
        const uint32_t wx = __float_as_uint(wq.x), wy = __float_as_uint(wq.y);
#pragma unroll
        for (int bb = 0; bb < 2; bb++) {
            const float sx = __shfl_sync(0xffffffffu, sv, bb * 12 + i);
            acc[4 * bb + 0] = fmaf(sx, bf_lo(wx), acc[4 * bb + 0]); acc[4 * bb + 1] = fmaf(sx, bf_hi(wx), acc[4 * bb + 1]);
            acc[4 * bb + 2] = fmaf(sx, bf_lo(wy), acc[4 * bb + 2]); acc[4 * bb + 3] = fmaf(sx, bf_hi(wy), acc[4 * bb + 3]);
        }
    }
    sts128f(SM_V + warp * 1024 + lane * 16, make_float4(acc[0], acc[1], acc[2], acc[3]));
    sts128f(SM_V + warp * 1024 + 512 + lane * 16, make_float4(acc[4], acc[5], acc[6], acc[7]));
    __syncthreads();
    if (tid < 128) {
        float2 sum = make_float2(0.f, 0.f);
#pragma unroll
        for (int w = 0; w < 16; w++) { const float2 p = lds64f(SM_V + w * 1024 + tid * 8); sum.x += p.x; sum.y += p.y; }
        *reinterpret_cast<float2*>(&gs->emb[j * NB * C + tid * 2]) = sum;
        bar_sync(1, 128);
        if (tid < 2) asm volatile("red.release.gpu.global.add.u32 [%0], 1;" ::"l"(&gs->wcnt[(2 * NB + tid) * LS]) : "memory");
    }
}

__global__ void __cluster_dims__(2, 1, 1) __launch_bounds__(NTHREADS, 1)
resblock_kernel(const __nv_bfloat16* __restrict__ w1, const __nv_bfloat16* __restrict__ x,
                const __nv_bfloat16* __restrict__ t_emb, const __nv_bfloat16* __restrict__ g1,
                const __nv_bfloat16* __restrict__ be1, const __nv_bfloat16* __restrict__ w_emb,
                const __nv_bfloat16* __restrict__ g2, const __nv_bfloat16* __restrict__ be2,
                const __nv_bfloat16* __restrict__ w2, __nv_bfloat16* __restrict__ out, Scratch* __restrict__ gs,
                const __grid_constant__ CUtensorMap xmap) {
    const unsigned clk0 = clock32();
    if (threadIdx.x == 480 && blockIdx.x >= NXTRA) TLG(1);
    const int tid = threadIdx.x, lane = tid & 31;
    const int cta = blockIdx.x - NXTRA, b = cta >> 6, r = cta & 63, rk = cta & 1;
    uint4 v[5];
    if (tid < 32) weight_load(v, w1, cta & (NCTA - 1), lane, true);
    uint4 xv[8];
    const int ch0 = (b & 1) * C + rk * 64;
    if (tid >= 32 && tid < 96) {
        const char* src = reinterpret_cast<const char*>(x) + (uint32_t)(((ch0 + (lane >> 3)) * HW + (r ^ (tid >> 6))) * HW * 2 + (lane & 7) * 16);
        while (clock32() - clk0 < XDELAY + (tid >> 6) * XSTAG2) {}
#pragma unroll
        for (int i = 0; i < 8; i++) xv[i] = __ldg(reinterpret_cast<const uint4*>(src + i * (4 * HW * HW * 2)));
    }
    const int warp = __shfl_sync(0xffffffffu, tid >> 5, 0);
    if (cta < 0) { side_jobs(t_emb, w_emb, w2, gs, clk0); return; }

    if (warp != 4) asm volatile("barrier.cluster.arrive.relaxed.aligned;" ::: "memory");
    const bool has_near = r != 0 && r != HW - 1, has_far = r != 1 && r != HW - 2;
    const uint32_t peer0 = mapa(0, rk ^ 1);
    if (warp == 1 || warp == 2 || warp == 3 || warp == 5) {
        const int i = warp < 4 ? warp - 1 : 3, gl = i >> 1, row = i & 1;
        const uint32_t tile = SM_XA + row * 8192 + gl * 4096;
        if (elect_one()) {
            if (gl) asm volatile("prefetch.tensormap [%0];" ::"l"(&xmap) : "memory");
            mbar_init(BAR(BAR_X) + 8 * i, 1);
            if (gl) { mbar_expect(BAR(BAR_X) + 8 * i, 4096); fence_async_smem(); }
        }
        __syncwarp();
        bar_arrive(4, 256 + 32 + 128);
        if (gl) {
            while (clock32() - clk0 < XDELAY + XSTAG + row * XSTAG2) {}
            if (elect_one()) tma_x(tile, &xmap, r ^ row, ch0 + 32, BAR(BAR_X) + 8 * i);
            __syncwarp();
            mbar_wait(BAR(BAR_X) + 8 * i, 0);
#pragma unroll
            for (int k = 0; k < 8; k++) xv[k] = lds128(tile + k * 512 + lane * 16);
        }
        float c[8][4];
#pragma unroll
        for (int k = 0; k < 8; k++) {
            c[k][0] = c[k][1] = c[k][2] = c[k][3] = 0.f;
            stat_mma(c[k], xv[k].x, xv[k].y); stat_mma(c[k], xv[k].z, xv[k].w);
        }
#pragma unroll
        for (int k = 0; k < 4; k++) c[0][k] = ((c[0][k] + c[1][k]) + (c[2][k] + c[3][k])) + ((c[4][k] + c[5][k]) + (c[6][k] + c[7][k]));
        stat_store(c[0], SM_RED + i * 48, lane);
        __syncwarp();
        if (lane == 0) {
            const uint32_t a = SM_RED + i * 48;
            red_add4(&gs->acc1[b * LS + (rk * 2 + gl) * 4], 1.f, sum4(lds128f(a + 32)), sum4(lds128f(a)) + sum4(lds128f(a + 16)), 1.f);
            TL(74 + i);
        }
        if (!gl) {
#pragma unroll
            for (int k = 0; k < 8; k++)
                sts128(tile + k * 512 + (lane >> 3) * 128 + (((lane & 7) ^ ((lane >> 3) + 4 * (k & 1))) << 4), xv[k]);
            __syncwarp();
            if (lane == 0) mbar_arrive(BAR(BAR_X) + 8 * i);
        }
    }
    if (warp == 4) {
        if (elect_one()) {
#pragma unroll
            for (int i = 0; i < NSTAGE; i++) mbar_init(BAR(BAR_FULL + i), (i & 1) ? 1 : ((i & 2) ? 2 : 9));
#pragma unroll
            for (int i = 0; i <= NS; i++) mbar_init(BAR(BAR_WEMPTY + i), 4);
#pragma unroll
            for (int i = BAR_STATS; i < BAR_X; i++) mbar_init(BAR(i), i == BAR_EMB ? 2 : 1);
            asm volatile("fence.mbarrier_init.release.cluster;" ::: "memory");
        }
        if (lane < 2) sts128(SM_GST + lane * 16, make_uint4(0, 0, 0, 0));
        __syncwarp();
        if (lane < 6) mbar_expect(BAR(BAR_RV) + 8 * lane, lane < 4 ? 4096 : (lane == 4 ? 16384 : 8192));
        fence_async_smem();
        bar_arrive(0, 96);
        bar_arrive(5, 64);
        bar_arrive(4, 256 + 32 + 128);
        const uint4 z = make_uint4(0, 0, 0, 0);
#pragma unroll
        for (int i = 0; i < 2; i++) sts128(SM_V + (i * 16 + (lane >> 1)) * CH_PITCH + (lane & 1) * 16, z);
        if (lane < 2) sts128(SM_V + NSTAGE * KC_BYTES + lane * 16, z);
        if (lane < 16) sts128(SM_ONES + lane * 16, make_uint4(lane < 8 ? 0x3f803f80u : 0u, 0, 0, 0));
        fence_async_smem();
        bar_arrive(7, 160);
        asm volatile("barrier.cluster.arrive.relaxed.aligned;" ::: "memory");
        while (clock32() - clk0 < W2DELAY) {}
        weight_load(v, w2, cta, lane, false);
    }
    if (warp == 0 || warp == 4 || warp >= 14) {
        const int k = warp == 4;
        int kx = warp < 8 ? 0 : warp - 13;
        if (kx == 0) {
#pragma unroll
            for (int i = 0; i < 5; i++)
                if (i < 4 || !(lane & 2)) sts128(SM_BNC + k * 2304 + (lane >> 2) * 288 + (lane & 3) * 16 + i * 64, v[i]);
            if (lane == 0) TL(k ? 14 : 81);
        }
        if (k) __syncwarp(); else bar_sync(8, 96);
        unsigned rb = 0;
#pragma unroll 1
        do { rb |= weight_block(SM_BNC + k * 2304, gs->wt + k * 32 * STAGE_BYTES, cta, lane, kx); } while (k && ++kx < 3);
        asm volatile("{\n.reg .pred p;\nsetp.eq.u32 p, %0, 0x9e3779b9;\n@p st.shared.u32 [%1], %0;\n}" ::"r"(rb), "r"(S0 + SM_RED + 1020) : "memory");
        if (warp >= 8) {
            bar_arrive(9, 96);
        } else {
            if (k) __syncwarp(); else bar_sync(9, 96);
            if (lane < 2) asm volatile("red.relaxed.gpu.global.add.u32 [%0], 1;" ::"l"(k ? &gs->wcnt[(NB + lane) * LS] : &gs->w1cnt[(lane * 8 + wblk_kc(cta)) * KS]) : "memory");
            if (lane == 0) TL(k ? 13 : 4);
        }
    }

    if (warp >= 8) {
        asm volatile("setmaxnreg.dec.sync.aligned.u32 104;");
        const int nw = warp - 8;
        const unsigned one = gridDim.y;
        if (nw < 4) {
            const uint2 q = __ldg(reinterpret_cast<const uint2*>(nw == 0 ? g1 : (nw == 1 ? be1 : (nw == 2 ? g2 : be2))) + lane);
            sts128f(SM_COEF + nw * 512 + lane * 16, make_float4(0.5f * bf_lo(q.x), 0.5f * bf_hi(q.x), 0.5f * bf_lo(q.y), 0.5f * bf_hi(q.y)));
        }
        bar_sync(4, 256 + 32 + 128);
        asm volatile("barrier.cluster.wait.acquire.aligned;" ::: "memory");
        const int hf = nw >> 2, wq = nw & 3;
        const uint32_t v_off = SM_V + (lane & 3) * CH_PITCH + (2 + wq * 16 + hf * 8 + (lane >> 2)) * 16;
        const int crow = ((lane & 6) << 2) | ((lane >> 3) << 1) | (lane & 1);
        const uint32_t stg_off = crow * 128 + (((2 * wq + hf) ^ (crow & 7)) << 4);
        const uint32_t img_off = (tid - 256) * 16;
        const float sg = rk ? -1.f : 1.f;
        uint4* inbox = gs->box + cta * 1024 + (tid - 256);
#pragma unroll 1
        for (int conv = 0; conv < 2; conv++) {
            uint32_t u[4][4];
            if (conv == 0) {
#pragma unroll
                for (int i = 0; i < 4; i++) { mbar_wait(BAR(BAR_X + i), 0); ldsm4t(u[i], SM_XA + (i & 1) * 8192 + (i >> 1) * 4096 + stg_off); }
            } else {
                mbar_wait(BAR(BAR_HW), 0);
                mbar_wait(BAR(BAR_RH), 0);
#pragma unroll
                for (int i = 0; i < 4; i++) lds_piece(u[i], SM_XA + (i & 1) * 8192 + (i >> 1) * 4096 + img_off);
            }
            float ga[2][8], be[2][8], a[4][8];
#pragma unroll
            for (int g = 0; g < 2; g++) {
                const uint32_t ca = SM_COEF + conv * 1024 + (rk * 64 + g * 32 + (lane & 3) * 8) * 4;
                const float4 q0 = lds128f(ca), q1 = lds128f(ca + 16), q2 = lds128f(ca + 512), q3 = lds128f(ca + 528);
                ga[g][0] = q0.x; ga[g][1] = q0.y; ga[g][2] = q0.z; ga[g][3] = q0.w; ga[g][4] = q1.x; ga[g][5] = q1.y; ga[g][6] = q1.z; ga[g][7] = q1.w;
                be[g][0] = q2.x; be[g][1] = q2.y; be[g][2] = q2.z; be[g][3] = q2.w; be[g][4] = q3.x; be[g][5] = q3.y; be[g][6] = q3.z; be[g][7] = q3.w;
            }
#pragma unroll
            for (int i = 0; i < 16; i++) {
                a[i >> 2][2 * (i & 3)] = bf_lo(u[i >> 2][i & 3]) * ga[i >> 3][2 * (i & 3)];
                a[i >> 2][2 * (i & 3) + 1] = bf_hi(u[i >> 2][i & 3]) * ga[i >> 3][2 * (i & 3) + 1];
                asm volatile("" : "+f"(a[i >> 2][2 * (i & 3)]), "+f"(a[i >> 2][2 * (i & 3) + 1]));
            }
            float4 gv = make_float4(0.f, 0.f, 0.f, 0.f);
            bool have = false;
#pragma unroll
            for (int g = 0; g < 2; g++) {
                unsigned it = 0;
#pragma unroll 1
                while (!__all_sync(0xffffffffu, (g ? gv.z : gv.x) != 0.f) && ++it < 8 * SPIN_LIMIT)
                    asm volatile("ld.volatile.shared.v4.f32 {%0,%1,%2,%3}, [%4];" : "=f"(gv.x), "=f"(gv.y), "=f"(gv.z), "=f"(gv.w) : "r"(S0 + SM_GST + conv * 16) : "memory");
                if (g == 0 && tid == 256) TL(22 + conv * 4);
                const float rs = g ? gv.z : gv.x, mr = g ? gv.w : gv.y;
                uint32_t kp[4], sd[4];
#pragma unroll
                for (int i = 0; i < 8; i++) {
                    be[g][i] = fmaf(-mr, ga[g][i], be[g][i]);
                    a[2 * g][i] = silu_half(fmaf(a[2 * g][i], rs, be[g][i])); a[2 * g + 1][i] = silu_half(fmaf(a[2 * g + 1][i], rs, be[g][i]));
                }
#pragma unroll
                for (int i = 0; i < 4; i++) {
                    kp[i] = pack_bf(fmaf(a[2 * g][2 * i], sg, a[2 * g + 1][2 * i]), fmaf(a[2 * g][2 * i + 1], sg, a[2 * g + 1][2 * i + 1]));
                    sd[i] = pack_bf(fmaf(a[2 * g + 1][2 * i], -sg, a[2 * g][2 * i]), fmaf(a[2 * g + 1][2 * i + 1], -sg, a[2 * g][2 * i + 1]));
                }
                sts128(v_off + g * 4 * KC_BYTES, make_uint4(kp[0], kp[1], kp[2], kp[3]));
                st_async(peer0 + v_off + (g * 4 + 2) * KC_BYTES, sd[0], sd[1], sd[2], sd[3], peer0 + BAR(BAR_RV + g));
                const bool xo = g == 0 && mbar_test(BAR(BAR_XO), conv);
                publish(BAR(BAR_FULL + 4 * g), lane);
                if (tid == 256) TL(g ? 84 + conv : 8 + conv * 8);
                if (g == 0 && xo) { load_outer(u, conv, stg_off, img_off); have = true; }
            }
            if (!have) { mbar_wait(BAR(BAR_XO), conv); load_outer(u, conv, stg_off, img_off); }
            if (conv == 1) {
                unsigned it = 0;
                while (true) {
                    bool okn = true, okf = true;
#pragma unroll
                    for (int i = 0; i < 8; i++) { okn = okn && u[(i >> 2) * 2][i & 3] != 0; okf = okf && u[(i >> 2) * 2 + 1][i & 3] != 0; }
                    if (__all_sync(0xffffffffu, (okn || !has_near) && (okf || !has_far)) || ++it > SPIN_LIMIT) break;
#pragma unroll
                    for (int i = 0; i < 4; i++) ld_unit(u[i], inbox + (i & 1) * 512 + (i >> 1) * 256);
                    if (tid == 256) TL(93);
                }
            }
            if (tid == 256) TL(24 + conv * 4);
#pragma unroll
            for (int g = 0; g < 2; g++) {
                const float rs = g ? gv.z : gv.x;
                uint32_t o[2][4];
#pragma unroll
                for (int f = 0; f < 2; f++) {
                    const bool ok = f ? has_far : has_near;
#pragma unroll
                    for (int i = 0; i < 4; i++) {
                        const float lo = silu_half(fmaf(bf_lo(u[2 * g + f][i]), ga[g][2 * i] * rs, be[g][2 * i]));
                        const float hi = silu_half(fmaf(bf_hi(u[2 * g + f][i]), ga[g][2 * i + 1] * rs, be[g][2 * i + 1]));
                        o[f][i] = pack_bf((ok ? lo : 0.f) - a[2 * g + (f ^ 1)][2 * i], (ok ? hi : 0.f) - a[2 * g + (f ^ 1)][2 * i + 1]);
                    }
                }
                sts128(v_off + (8 + g * 4) * KC_BYTES, make_uint4(o[0][0], o[0][1], o[0][2], o[0][3]));
                st_async(peer0 + v_off + (10 + g * 4) * KC_BYTES, o[1][0], o[1][1], o[1][2], o[1][3], peer0 + BAR(BAR_RV + 2 + g));
                publish(BAR(BAR_FULL + 8 + 4 * g), lane);
                if (tid == 256) TL(g ? 88 + conv : 23 + conv * 4);
                if (one == 0) break;
            }
        }
        mbar_wait(BAR(BAR_FULL + NSTAGE - 1), 1);
#pragma unroll
        for (int i = 0; i < 4; i++) inbox[i * 256] = make_uint4(0, 0, 0, 0);
        {
            const int oc0 = hf * 64 + ((tid & 127) >> 3), seg = lane & 7;
            __nv_bfloat16* dst = out + ((size_t)(b * C + oc0) * HW + r) * HW + seg * 8;
            const uint32_t src = oc0 * 128 + ((seg ^ (oc0 & 7)) << 4);
            mbar_wait(BAR(BAR_XR), 0);
            uint4 xr[4];
#pragma unroll
            for (int i = 0; i < 4; i++) xr[i] = lds128(SM_XA + src + i * 2048);
            asm volatile("{\n.reg .pred p;\nsetp.eq.u64 p, %0, 0;\n@p st.shared.u32 [%1], 0;\n}" ::"l"(dst), "r"(src + S0) : "memory");
            bar_sync(hf ? 1 : 6, 128 + 128);
#pragma unroll
            for (int i = 0; i < 4; i++) {
                uint4 o = lds128(SM_XB + src + i * 2048);
                asm("add.rn.bf16x2 %0, %0, %1;" : "+r"(o.x) : "r"(xr[i].x)); asm("add.rn.bf16x2 %0, %0, %1;" : "+r"(o.y) : "r"(xr[i].y));
                asm("add.rn.bf16x2 %0, %0, %1;" : "+r"(o.z) : "r"(xr[i].z)); asm("add.rn.bf16x2 %0, %0, %1;" : "+r"(o.w) : "r"(xr[i].w));
                *reinterpret_cast<uint4*>(dst + (size_t)i * 16 * HW * HW) = o;
            }
            if (tid == 384) { TL(20); TLG(21); }
        }
    } else if (warp < 4) {
        const int wq = warp;
        asm volatile("setmaxnreg.inc.sync.aligned.u32 176;");
        bar_sync(7, 160);
        asm volatile("barrier.cluster.wait.acquire.aligned;" ::: "memory");
        const float sg = rk ? 1.f : -1.f;
        float d[64], e[64];
#pragma unroll 1
        for (int conv = 0; conv < 2; conv++) {
#pragma unroll
            for (int i = 0; i < 64; i++) { d[i] = 0.f; e[i] = 0.f; }
            fence_acc(d); fence_acc(e);
            mma_stages<0>(d, e, conv, tid, peer0, gs);
            if (conv == 0) {
                asm volatile("wgmma.fence.sync.aligned;" ::: "memory");
                wgmma128<(SM_ONES >> 4) | (8u << 16), (SM_EMB >> 4), 0, 8>(e);
                asm volatile("wgmma.commit_group.sync.aligned;" ::: "memory");
            }
            mbar_wait(BAR(BAR_M), conv);
#pragma unroll
            for (int j = 0; j < 8; j++) {
                uint32_t q[4];
                lds_piece(q, SM_M + j * 2048 + tid * 16);
#pragma unroll
                for (int i = 0; i < 4; i++) { d[8 * j + 2 * i] = fmaf(bf_lo(q[i]), sg, d[8 * j + 2 * i]); d[8 * j + 2 * i + 1] = fmaf(bf_hi(q[i]), sg, d[8 * j + 2 * i + 1]); }
            }
            fence_acc(d);
            asm volatile("wgmma.wait_group.sync.aligned 0;" ::: "memory");
            fence_acc(e);
            if (tid == 0) TL(10 + conv * 8);
            uint32_t hp[32];
#pragma unroll
            for (int i = 0; i < 32; i++) hp[i] = pack_bf(d[2 * i] + e[2 * i], d[2 * i + 1] + e[2 * i + 1]);
            if (conv == 1) {
                const uint32_t obase = SM_XB + ((lane >> 4) * 8 + (lane & 7)) * 128 + (((2 * wq + ((lane >> 3) & 1)) ^ (lane & 7)) << 4);
#pragma unroll
                for (int kc = 0; kc < 8; kc++) {
                    stsm4t(obase + kc * 2048, hp[4 * kc], hp[4 * kc + 1], hp[4 * kc + 2], hp[4 * kc + 3]);
                    if (kc == 3) bar_arrive(6, 128 + 128);
                }
                bar_arrive(1, 128 + 128);
                break;
            }
#pragma unroll
            for (int g = 0; g < 4; g++) {
                float c[4] = {0.f, 0.f, 0.f, 0.f};
#pragma unroll
                for (int i = 0; i < 4; i++) stat_mma(c, hp[8 * g + 2 * i], hp[8 * g + 2 * i + 1]);
                stat_store(c, SM_RED + (g * 4 + wq) * 48, lane);
            }
            bar_sync(2, 128);
            if (wq == 0) stat_publish(SM_RED, &gs->acc2[b * LS], lane, true);
            if (tid == 0) TL(11);
            if (tid == 32) mbar_expect(BAR(BAR_M), 16384);
#pragma unroll
            for (int j = 0; j < 8; j++) {
                const uint32_t p0 = hp[(j >> 1) * 8 + (j & 1)], p1 = hp[(j >> 1) * 8 + (j & 1) + 2], p2 = hp[(j >> 1) * 8 + (j & 1) + 4], p3 = hp[(j >> 1) * 8 + (j & 1) + 6];
                if ((j >> 2) == rk) sts128(SM_XA + (j & 3) * 2048 + tid * 16, make_uint4(p0, p1, p2, p3));
                else st_async(peer0 + SM_XA + 8192 + (j & 3) * 2048 + tid * 16, p0, p1, p2, p3, peer0 + BAR(BAR_RH));
            }
            __syncwarp();
            if (lane == 0) { mbar_arrive(BAR(BAR_HW)); mbar_arrive(BAR(BAR_WEMPTY + 7)); }
            if (has_near) {
                const int oc2 = (cta & ~1) + (rk ? 2 : -2);
#pragma unroll
                for (int j = 0; j < 8; j++) {
                    uint4* outbox = gs->box + (oc2 + (j >> 2)) * 1024 + (((j >> 2) == rk) ? 512 : 0) + (j & 3) * 128 + tid;
                    *outbox = make_uint4(max(hp[(j >> 1) * 8 + (j & 1)], 1u), max(hp[(j >> 1) * 8 + (j & 1) + 2], 1u),
                                         max(hp[(j >> 1) * 8 + (j & 1) + 4], 1u), max(hp[(j >> 1) * 8 + (j & 1) + 6], 1u));
                }
            }
            if (tid == 0) TL(12);
        }
    } else {
    if (warp < 6) {
        if (warp == 5) {
            bar_sync(5, 64);
            if (elect_one()) {
                mbar_expect(BAR(BAR_XO), 16384);
                while (clock32() - clk0 < ODELAY) {}
#pragma unroll
                for (int i = 0; i < 4; i++)
                    tma_x(SM_XB + i * 4096, &xmap, ((i >> 1) ^ rk) ? (r | 1) + 1 : (r & ~1) - 1, ch0 + (i & 1) * 32, BAR(BAR_XO));
            }
            __syncwarp();
#pragma unroll 1
            for (int i = 0; i < 8; i++) {
                mbar_wait(BAR(BAR_RV) + 8 * (i & 3), i >> 2);
                fence_async_smem();
                if (lane == 0) {
                    mbar_arrive(BAR(BAR_FULL + 2) + 32 * (i & 3));
                    if (i < 4) mbar_expect(BAR(BAR_RV) + 8 * i, 4096);
                    TL(64 + i);
                }
                __syncwarp();
            }
        } else {
            mbar_wait(BAR(BAR_STATS), 0);
            unsigned it = 0;
            while (!__all_sync(0xffffffffu, ld_relaxed(&gs->wcnt[(2 * NB + b) * LS]) >= (unsigned)NXTRA) && ++it < SPIN_LIMIT) __nanosleep(100);
            fence_acquire();
            float ev[4] = {0.f, 0.f, 0.f, 0.f};
#pragma unroll
            for (int j = 0; j < NXTRA; j++) {
                const uint4 ef = ld_relaxed_v4(&gs->emb[(j * NB + b) * C + lane * 4]);
                ev[0] += __uint_as_float(ef.x); ev[1] += __uint_as_float(ef.y); ev[2] += __uint_as_float(ef.z); ev[3] += __uint_as_float(ef.w);
            }
#pragma unroll
            for (int i = 0; i < 4; i++) {
                const float hi = bf_lo(pack_bf(ev[i], 0.f));
                sts128(SM_EMB + n_to_oc(lane * 4 + i) * 16, make_uint4(pack_bf(hi, ev[i] - hi), 0, 0, 0));
            }
            fence_async_smem();
            __syncwarp();
            if (lane == 0) { mbar_arrive(BAR(BAR_EMB)); TL(19); }
            mbar_wait(BAR(BAR_HW), 0);
            {
                const unsigned c1 = clock32();
#pragma unroll 1
                while (clock32() - c1 < FDELAY && !mbar_test(BAR(BAR_STATS), 1)) {}
                if (elect_one()) {
                    mbar_expect(BAR(BAR_XO), 16384);
                    bulk_g2s(S0 + SM_XB, gs->box + cta * 1024, 16384, S0 + BAR(BAR_XO));
                }
                __syncwarp();
            }
            mbar_wait(BAR(BAR_FULL + 8), 1);
            if (elect_one()) {
                mbar_expect(BAR(BAR_XR), 16384);
#pragma unroll
                for (int i = 0; i < 4; i++) tma_x(SM_XA + i * 4096, &xmap, r, b * C + i * 32, BAR(BAR_XR));
            }
        }
    } else if (warp == 6) {
        bar_sync(0, 96);
        if (lane < NSTAGE) mbar_expect(BAR(BAR_FULL) + 8 * lane, STAGE_BYTES);
        const unsigned char* wbase = gs->wt + rk * 8 * STAGE_BYTES;
        unsigned it = 0;
        {
            int g = 0;
            const int l7 = lane & 7;
            const unsigned* cnt = &gs->w1cnt[(b * 8 + ((((l7 >> 1) ^ rk) & 1) * 4 + (l7 >> 2) * 2 + (l7 & 1))) * KS];
            unsigned cv = ld_relaxed(cnt);
#pragma unroll 1
            while (g < NS) {
                unsigned ready = __ballot_sync(0xffffffffu, cv >= 16u);
                if (ready != ~0u) cv = ld_relaxed(cnt);
                ready >>= g;
                if (++it > SPIN_LIMIT) ready = ~0u;
                if (!(ready & 1)) continue;
                fence_async_global();
                if (lane == 0) TL(g ? 3 : 6);
#pragma unroll 1
                for (; (ready & 1) && g < NS; g++, ready >>= 1)
                    if (elect_one())
                        bulk_g2s(S0 + SM_W + g * STAGE_BYTES, wbase + ((((g >> 1) ^ rk) & 1) * 4 + (g >> 2) * 2 + (g & 1)) * STAGE_BYTES, STAGE_BYTES,
                                 S0 + BAR(BAR_FULL) + 8 * g);
            }
        }
#pragma unroll 1
        for (int q = 2; q < 8; q++) {
            const unsigned char* wsrc = wbase + ((q >> 1) * 16 + (q & 1) * 2) * STAGE_BYTES;
            const uint32_t par = ((q >> 1) - 1) & 1;
            if (q == 4) {
                it = 0;
                while (!__all_sync(0xffffffffu, ld_relaxed(&gs->wcnt[(NB + b) * LS]) == (unsigned)NCTA) && ++it < SPIN_LIMIT) {}
                fence_acquire();
                fence_async_global();
                if (lane == 0) { mbar_arrive(BAR(BAR_EMB)); TL(2); }
            }
#pragma unroll
            for (int i = 0; i < 4; i++) {
                mbar_wait(BAR(BAR_WEMPTY + i) + 32 * (q & 1), par);
                if (i == 0 && (q == 4 || q == 6)) {
                    if ((lane >> 3) == (q - 4) / 2) mbar_expect(BAR(BAR_FULL) + 8 * lane, STAGE_BYTES);
                    __syncwarp();
                }
                if (elect_one())
                    bulk_g2s(S0 + SM_W + ((q & 1) * 4 + i) * STAGE_BYTES, wsrc + ((((i >> 1) ^ rk) & 1) * 4 + (i & 1)) * STAGE_BYTES, STAGE_BYTES,
                             S0 + BAR(BAR_FULL + i) + 32 * (q & 3));
            }
        }
    } else {
        bar_sync(0, 96);
#pragma unroll 1
        for (int conv = 0; conv < 2; conv++) {
            if (conv == 1) mbar_wait(BAR(BAR_HW), 0);
            const float* asrc = (conv ? gs->acc2 : gs->acc1) + b * LS + (rk * 2 + (lane & 1)) * 4;
            unsigned it = 0;
#pragma unroll 1
            while (true) {
                const uint4 f = ld_relaxed_v4(asrc);
                const bool ok = ((f.x == 0x42800000u) & (f.w == 0x42800000u)) || ++it > SPIN_LIMIT;
                if (ok && lane < 2) {
                    const float inv_n = 1.0f / (32.0f * HW * HW);
                    const float mean = __uint_as_float(f.y) * inv_n;
                    float rs;
                    asm("rsqrt.approx.ftz.f32 %0, %1;" : "=f"(rs) : "f"(fmaxf(fmaf(-mean, mean, __uint_as_float(f.z) * inv_n), 0.f) + 1e-5f));
                    asm volatile("st.shared.v2.f32 [%0], {%1,%2};" ::"r"(S0 + SM_GST + conv * 16 + lane * 8), "f"(rs == 0.f ? 1.2e-38f : rs), "f"(mean * rs) : "memory");
                }
                if (__all_sync(0xffffffffu, ok)) break;
            }
            if (lane == 0) { mbar_arrive(BAR(BAR_STATS)); TL(7 + conv * 8); }
        }
        if (r == 0) {
            if (lane < 16) gs->acc1[b * LS + lane] = 0.f;
            if (lane < 3) gs->wcnt[(lane * NB + b) * LS] = 0;
            if (lane < 8) gs->w1cnt[(b * 8 + lane) * KS] = 0;
        }
    }
    }
}

}

extern "C" void kernel_launch(void* const* d_in, const int* in_sizes, int n_in, void* d_out, int out_size) {
    (void)in_sizes; (void)n_in; (void)out_size;
    typedef CUresult (*EncodeFn)(CUtensorMap*, CUtensorMapDataType, cuuint32_t, void*, const cuuint64_t*, const cuuint64_t*,
                                 const cuuint32_t*, const cuuint32_t*, CUtensorMapInterleave, CUtensorMapSwizzle,
                                 CUtensorMapL2promotion, CUtensorMapFloatOOBfill);
    static Scratch* gs = nullptr;
    static EncodeFn encode = nullptr;
    if (!gs) {
        cudaFuncSetAttribute(resblock_kernel, cudaFuncAttributeMaxDynamicSharedMemorySize, SM_TOTAL);
        cudaGetSymbolAddress((void**)&gs, g_scratch);
        cudaDriverEntryPointQueryResult qr;
        cudaGetDriverEntryPoint("cuTensorMapEncodeTiled", (void**)&encode, cudaEnableDefault, &qr);
    }
    CUtensorMap xmap;
    const cuuint64_t dims[3] = {HW, HW, NB * C}, strides[2] = {HW * 2, HW * HW * 2};
    const cuuint32_t box[3] = {HW, 1, 32}, es[3] = {1, 1, 1};
    encode(&xmap, CU_TENSOR_MAP_DATA_TYPE_BFLOAT16, 3, d_in[0], dims, strides, box, es, CU_TENSOR_MAP_INTERLEAVE_NONE,
           CU_TENSOR_MAP_SWIZZLE_128B, CU_TENSOR_MAP_L2_PROMOTION_NONE, CU_TENSOR_MAP_FLOAT_OOB_FILL_NONE);
    resblock_kernel<<<NCTA + NXTRA, NTHREADS, SM_TOTAL>>>(
        (const __nv_bfloat16*)d_in[4], (const __nv_bfloat16*)d_in[0], (const __nv_bfloat16*)d_in[1],
        (const __nv_bfloat16*)d_in[2], (const __nv_bfloat16*)d_in[3], (const __nv_bfloat16*)d_in[5],
        (const __nv_bfloat16*)d_in[6], (const __nv_bfloat16*)d_in[7], (const __nv_bfloat16*)d_in[8],
        (__nv_bfloat16*)d_out, gs, xmap);
}
```

```cpp
#include <cuda_runtime.h>
#include <cuda.h>
#include <cuda_bf16.h>
#include <stdint.h>

namespace {

constexpr int C = 128, HW = 64, NB = 2, E = 768;
constexpr int NCTA = NB * HW;
constexpr int NXTRA = 4;
constexpr int NTHREADS = 16 * 32;
constexpr int CH_PITCH = 66 * 16;
constexpr int KC_BYTES = 2 * CH_PITCH;
constexpr int STAGE_BYTES = 12288;
constexpr int NSTAGE = 16;
constexpr int NS = 8;
#define XDELAY 300
#define XSTAG 800
#define XSTAG2 100
#define SDELAY 600
#define W2DELAY 2400
#define ODELAY 2000
#define LDAT 0

constexpr uint32_t SMEM_BASE = 0x400;
constexpr uint32_t SM_XA = SMEM_BASE;
constexpr uint32_t SM_XB = SM_XA + 16384;
constexpr uint32_t SM_M = SM_XB + 16384;
constexpr uint32_t SM_V = SM_M + 16384;
constexpr uint32_t SM_W = SM_V + NSTAGE * KC_BYTES + 128;
constexpr uint32_t SM_COEF = SM_W + NS * STAGE_BYTES;
constexpr uint32_t SM_GST = SM_COEF + 2048;
constexpr uint32_t SM_EMB = SM_GST + 128;
constexpr uint32_t SM_ONES = SM_EMB + 2048;
constexpr uint32_t SM_RED = SM_ONES + 256;
constexpr uint32_t SM_BNC = SM_RED + 1024;
constexpr uint32_t SM_BAR = SM_BNC + 2 * 2304;
constexpr int BAR_FULL = 0, BAR_WEMPTY = NSTAGE, BAR_HW = BAR_WEMPTY + NS, BAR_STATS = BAR_HW + 1, BAR_EMB = BAR_STATS + 1,
              BAR_RV = BAR_EMB + 1  , BAR_M = BAR_RV + 4, BAR_RH = BAR_M + 1, BAR_XO = BAR_RH + 1, BAR_XR = BAR_XO + 1,
              BAR_X = BAR_XR + 1  , NBAR = BAR_X + 4;
constexpr int SM_TOTAL = SM_BAR + NBAR * 8 - SMEM_BASE;
static_assert(SM_TOTAL <= 232448, "smem");
__host__ __device__ constexpr uint32_t BAR(int i) { return SM_BAR + 8 * i; }

constexpr unsigned SPIN_LIMIT = 1u << 16;
constexpr int LS = 1056, KS = 32;

struct Scratch {
    float acc1[NB * LS];
    float acc2[NB * LS];
    unsigned wcnt[3 * NB * LS];
    unsigned w1cnt[NB * 8 * KS];
    float emb[NXTRA * NB * C];
    alignas(1024) unsigned char wt[2 * 32 * STAGE_BYTES];
    uint4 box[NCTA * 1024];
};
__device__ __align__(1024) Scratch g_scratch;
#define TL(i) do {} while (0)
#define TLG(i) do {} while (0)

__device__ __forceinline__ unsigned clock32() { unsigned c; asm volatile("mov.u32 %0, %%clock;" : "=r"(c)); return c; }
__device__ __forceinline__ uint32_t mapa(uint32_t a, uint32_t rank) {
    uint32_t d;
    asm("mapa.shared::cluster.u32 %0, %1, %2;" : "=r"(d) : "r"(a), "r"(rank));
    return d;
}
#define S0 mapa(0, blockIdx.x & 1)
__device__ __forceinline__ void mbar_init(uint32_t bar, int cnt) {
    asm volatile("mbarrier.init.shared::cta.b64 [%0], %1;" ::"r"(bar + S0), "r"(cnt) : "memory");
}
__device__ __forceinline__ void mbar_arrive(uint32_t bar) {
    asm volatile("mbarrier.arrive.shared::cta.b64 _, [%0];" ::"r"(bar + S0) : "memory");
}
__device__ __forceinline__ void mbar_expect(uint32_t bar, uint32_t bytes) {
    asm volatile("mbarrier.arrive.expect_tx.shared::cta.b64 _, [%0], %1;" ::"r"(bar + S0), "r"(bytes) : "memory");
}
__device__ __forceinline__ bool mbar_try(uint32_t bar, uint32_t par) {
    uint32_t ok;
    asm volatile("{\n.reg .pred p;\nmbarrier.try_wait.parity.shared::cta.b64 p, [%1], %2;\nselp.u32 %0, 1, 0, p;\n}"
                 : "=r"(ok) : "r"(bar + S0), "r"(par) : "memory");
    return ok;
}
__device__ __forceinline__ bool mbar_test(uint32_t bar, uint32_t par) {
    uint32_t ok;
    asm volatile("{\n.reg .pred p;\nmbarrier.test_wait.parity.shared::cta.b64 p, [%1], %2;\nselp.u32 %0, 1, 0, p;\n}"
                 : "=r"(ok) : "r"(bar + S0), "r"(par) : "memory");
    return ok;
}
__device__ __forceinline__ void mbar_wait(uint32_t bar, uint32_t par) {
    unsigned it = 0;
#pragma unroll 1
    while (!mbar_try(bar, par) && ++it < SPIN_LIMIT) {}
}
__device__ __forceinline__ bool elect_one() {
    uint32_t p;
    asm volatile("{\n.reg .pred p;\nelect.sync _|p, 0xffffffff;\nselp.u32 %0, 1, 0, p;\n}" : "=r"(p));
    return p;
}
__device__ __forceinline__ void fence_async_smem() { asm volatile("fence.proxy.async.shared::cta;" ::: "memory"); }
__device__ __forceinline__ void fence_async_global() { asm volatile("fence.proxy.async.global;" ::: "memory"); }
__device__ __forceinline__ void fence_acquire() { asm volatile("fence.acquire.gpu;" ::: "memory"); }
__device__ __forceinline__ void bar_sync(int id, int n) { asm volatile("bar.sync %0, %1;" ::"r"(id), "r"(n) : "memory"); }
__device__ __forceinline__ void bar_arrive(int id, int n) { asm volatile("bar.arrive %0, %1;" ::"r"(id), "r"(n) : "memory"); }
__device__ __forceinline__ void bulk_g2s(uint32_t dst, const void* src, uint32_t bytes, uint32_t bar) {
    asm volatile("cp.async.bulk.shared::cluster.global.mbarrier::complete_tx::bytes [%0], [%1], %2, [%3];"
                 ::"r"(dst), "l"(src), "r"(bytes), "r"(bar) : "memory");
}
__device__ __forceinline__ void tma_x(uint32_t dst, const CUtensorMap* tm, int row, int ch, uint32_t bar) {
    asm volatile("cp.async.bulk.tensor.3d.shared::cluster.global.mbarrier::complete_tx::bytes [%0], [%1, {%2, %3, %4}], [%5];"
                 ::"r"(dst + S0), "l"(tm), "r"(0), "r"(row), "r"(ch), "r"(bar + S0) : "memory");
}
__device__ __forceinline__ uint4 ld_relaxed_v4(const void* p) {
    uint4 v;
    asm volatile("ld.relaxed.gpu.global.v4.u32 {%0,%1,%2,%3}, [%4];" : "=r"(v.x), "=r"(v.y), "=r"(v.z), "=r"(v.w) : "l"(p) : "memory");
    return v;
}
__device__ __forceinline__ unsigned ld_relaxed(const void* p) {
    unsigned v;
    asm volatile("ld.relaxed.gpu.global.u32 %0, [%1];" : "=r"(v) : "l"(p) : "memory");
    return v;
}
__device__ __forceinline__ void red_add4(float* p, float a, float b, float c, float d) {
    asm volatile("red.relaxed.gpu.global.add.v4.f32 [%0], {%1,%2,%3,%4};" ::"l"(p), "f"(a), "f"(b), "f"(c), "f"(d) : "memory");
}
__device__ __forceinline__ void sts128(uint32_t a, uint4 v) {
    asm volatile("st.shared.v4.u32 [%0], {%1,%2,%3,%4};" ::"r"(a + S0), "r"(v.x), "r"(v.y), "r"(v.z), "r"(v.w) : "memory");
}
__device__ __forceinline__ void sts128f(uint32_t a, float4 v) {
    asm volatile("st.shared.v4.f32 [%0], {%1,%2,%3,%4};" ::"r"(a + S0), "f"(v.x), "f"(v.y), "f"(v.z), "f"(v.w) : "memory");
}
__device__ __forceinline__ void sts32f(uint32_t a, float v) { asm volatile("st.shared.f32 [%0], %1;" ::"r"(a + S0), "f"(v) : "memory"); }
__device__ __forceinline__ uint4 lds128(uint32_t a) {
    uint4 v;
    asm volatile("ld.shared.v4.u32 {%0,%1,%2,%3}, [%4];" : "=r"(v.x), "=r"(v.y), "=r"(v.z), "=r"(v.w) : "r"(a + S0) : "memory");
    return v;
}
__device__ __forceinline__ float4 lds128f(uint32_t a) {
    float4 v;
    asm volatile("ld.shared.v4.f32 {%0,%1,%2,%3}, [%4];" : "=f"(v.x), "=f"(v.y), "=f"(v.z), "=f"(v.w) : "r"(a + S0) : "memory");
    return v;
}
__device__ __forceinline__ float2 lds64f(uint32_t a) {
    float2 v;
    asm volatile("ld.shared.v2.f32 {%0,%1}, [%2];" : "=f"(v.x), "=f"(v.y) : "r"(a + S0) : "memory");
    return v;
}
__device__ __forceinline__ float bf_lo(uint32_t u) { return __uint_as_float(u << 16); }
__device__ __forceinline__ float bf_hi(uint32_t u) { return __uint_as_float(u & 0xffff0000u); }
__device__ __forceinline__ uint32_t pack_bf(float lo, float hi) {
    uint32_t r;
    asm("cvt.rn.bf16x2.f32 %0, %1, %2;" : "=r"(r) : "f"(hi), "f"(lo));
    return r;
}
__device__ __forceinline__ float tanh_fast(float x) {
    float r;
    asm("tanh.approx.f32 %0, %1;" : "=f"(r) : "f"(x));
    return r;
}
__device__ __forceinline__ float silu_half(float h) { return fmaf(h, tanh_fast(h), h); }
__device__ __forceinline__ void ldsm4(uint32_t (&u)[4], uint32_t a) {
    asm volatile("ldmatrix.sync.aligned.m8n8.x4.shared.b16 {%0,%1,%2,%3}, [%4];"
                 : "=r"(u[0]), "=r"(u[1]), "=r"(u[2]), "=r"(u[3]) : "r"(a + S0) : "memory");
}
__device__ __forceinline__ void ldsm4t(uint32_t (&u)[4], uint32_t a) {
    asm volatile("ldmatrix.sync.aligned.m8n8.x4.trans.shared.b16 {%0,%1,%2,%3}, [%4];"
                 : "=r"(u[0]), "=r"(u[1]), "=r"(u[2]), "=r"(u[3]) : "r"(a + S0) : "memory");
}
__device__ __forceinline__ void stsm4(uint32_t a, uint32_t p0, uint32_t p1, uint32_t p2, uint32_t p3) {
    asm volatile("stmatrix.sync.aligned.m8n8.x4.shared.b16 [%0], {%1,%2,%3,%4};" ::"r"(a + S0), "r"(p0), "r"(p1), "r"(p2), "r"(p3) : "memory");
}
__device__ __forceinline__ void stsm4t(uint32_t a, uint32_t p0, uint32_t p1, uint32_t p2, uint32_t p3) {
    asm volatile("stmatrix.sync.aligned.m8n8.x4.trans.shared.b16 [%0], {%1,%2,%3,%4};" ::"r"(a + S0), "r"(p0), "r"(p1), "r"(p2), "r"(p3) : "memory");
}

#define R8(o) "+f"(d[o]), "+f"(d[o + 1]), "+f"(d[o + 2]), "+f"(d[o + 3]), "+f"(d[o + 4]), "+f"(d[o + 5]), "+f"(d[o + 6]), "+f"(d[o + 7])
template <uint32_t ALO, uint32_t BLO, uint64_t AHI = 8, uint64_t BHI = 48>
__device__ __forceinline__ void wgmma128(float (&d)[64]) {
    asm volatile(
        "wgmma.mma_async.sync.aligned.m64n128k16.f32.bf16.bf16 "
        "{%0,%1,%2,%3,%4,%5,%6,%7,%8,%9,%10,%11,%12,%13,%14,%15,%16,%17,%18,%19,%20,%21,%22,%23,%24,%25,%26,%27,%28,%29,%30,%31,"
        "%32,%33,%34,%35,%36,%37,%38,%39,%40,%41,%42,%43,%44,%45,%46,%47,%48,%49,%50,%51,%52,%53,%54,%55,%56,%57,%58,%59,%60,%61,%62,%63},"
        " %64, %65, 1, 1, 1, 0, 0;"
        : R8(0), R8(8), R8(16), R8(24), R8(32), R8(40), R8(48), R8(56)
        : "l"((AHI << 32) | ALO), "l"((BHI << 32) | BLO));
}
__device__ __forceinline__ void stat_mma(float (&c)[4], uint32_t p, uint32_t q) {
    asm("mma.sync.aligned.m16n8k16.row.col.f32.bf16.bf16.f32 {%0,%1,%2,%3}, {%4,%5,%6,%5}, {%4,%6}, {%0,%1,%2,%3};"
        : "+f"(c[0]), "+f"(c[1]), "+f"(c[2]), "+f"(c[3]) : "r"(p), "r"(0x3f803f80u), "r"(q));
}
__device__ __forceinline__ void stat_store(const float (&c)[4], uint32_t dst, int lane) {
    const int g = lane >> 2, t = lane & 3;
    if (t == (g >> 1)) sts32f(dst + g * 4, (g & 1) ? c[1] : c[0]);
    if (g == 7) sts32f(dst + 32 + t * 4, c[2] + c[3]);
}
__device__ __forceinline__ float sum4(float4 v) { return (v.x + v.y) + (v.z + v.w); }
__device__ __forceinline__ void stat_publish(uint32_t src, float* acc, int lane, bool real) {
    const uint32_t a = src + (lane & 15) * 48;
    float q = sum4(lds128f(a)) + sum4(lds128f(a + 16)), sm = sum4(lds128f(a + 32));
    q += __shfl_xor_sync(0xffffffffu, q, 1); sm += __shfl_xor_sync(0xffffffffu, sm, 1);
    q += __shfl_xor_sync(0xffffffffu, q, 2); sm += __shfl_xor_sync(0xffffffffu, sm, 2);
    if (real && (lane & 19) == 0) red_add4(acc + lane, 1.f, sm, q, 1.f);
}
__device__ __forceinline__ void fence_acc(float (&d)[64]) {
#pragma unroll
    for (int i = 0; i < 64; i++) asm volatile("" : "+f"(d[i])::"memory");
}
__device__ __forceinline__ void ld_unit(uint32_t (&u)[4], const uint4* p) {
    asm volatile("ld.relaxed.gpu.global.v4.u32 {%0,%1,%2,%3}, [%4];" : "=r"(u[0]), "=r"(u[1]), "=r"(u[2]), "=r"(u[3]) : "l"(p) : "memory");
}

__device__ __forceinline__ void st_async(uint32_t dst, uint32_t a, uint32_t b, uint32_t c, uint32_t d, uint32_t bar) {
    asm volatile("st.async.shared::cluster.mbarrier::complete_tx::bytes.v4.b32 [%0], {%1,%2,%3,%4}, [%5];"
                 ::"r"(dst), "r"(a), "r"(b), "r"(c), "r"(d), "r"(bar) : "memory");
}
template <int J>
__device__ __forceinline__ void send_m(const float (&d)[64], int tid, uint32_t peer0) {
    st_async(peer0 + SM_M + J * 2048 + tid * 16, pack_bf(d[8 * J], d[8 * J + 1]), pack_bf(d[8 * J + 2], d[8 * J + 3]),
             pack_bf(d[8 * J + 4], d[8 * J + 5]), pack_bf(d[8 * J + 6], d[8 * J + 7]), peer0 + BAR(BAR_M));
}
template <int S>
__device__ __forceinline__ void mma_stages(float (&d)[64], float (&e)[64], int conv, int tid, uint32_t peer0, Scratch* gs) {
    constexpr uint32_t A = ((SM_V + S * KC_BYTES + 16) >> 4) | ((CH_PITCH >> 4) << 16);
    constexpr uint32_t B = ((SM_W + (S % NS) * STAGE_BYTES) >> 4) | (8u << 16);
    if (S == 0) mbar_wait(BAR(BAR_FULL), conv);
    constexpr uint32_t NEXT = S + 1 < NSTAGE ? BAR(BAR_FULL + S + 1) : BAR(BAR_EMB);
    const int npar = S + 1 < NSTAGE ? conv : 0;
    const bool next_ok = mbar_test(NEXT, npar);
    if ((S & 7) == 0 && tid == 0) TL(32 + conv * 16 + S);
    asm volatile("wgmma.fence.sync.aligned;" ::: "memory");
    wgmma128<A, B>(S < 8 ? d : e);
    if constexpr (S >= 9 && S < 12) send_m<(S - 9) * 2 + 2>(d, tid, peer0);
    wgmma128<A + 1, B + 16>(S < 8 ? d : e);
    if constexpr (S >= 9 && S < 12) send_m<(S - 9) * 2 + 3>(d, tid, peer0);
    wgmma128<A + 2, B + 32>(S < 8 ? d : e);
    asm volatile("wgmma.commit_group.sync.aligned;" ::: "memory");
    if (S > 0) {
        asm volatile("wgmma.wait_group.sync.aligned 1;" ::: "memory");
        if ((tid & 31) == 0) mbar_arrive(BAR(BAR_WEMPTY + (S - 1) % NS));
    }
    if constexpr (S == 8) { fence_acc(d); send_m<0>(d, tid, peer0); send_m<1>(d, tid, peer0); }
    if (!next_ok) mbar_wait(NEXT, npar);
    if constexpr (S + 1 < NSTAGE) mma_stages<S + 1>(d, e, conv, tid, peer0, gs);
}

__device__ __forceinline__ int wblk_kc(int cta) { const int i = cta >> 4; return (i & 1) | ((i & 2) << 1) | ((i & 4) >> 1); }
__device__ __forceinline__ int n_to_oc(int n) { return (n & ~31) | ((n & 6) << 2) | ((n >> 2) & 6) | (n & 1); }
__device__ __forceinline__ void weight_load(uint4 (&t)[5], const __nv_bfloat16* w, int cta, int lane, bool perm) {
    const int n = (cta & 15) * 8 + (lane >> 2);
    const char* base = reinterpret_cast<const char*>(w) + (uint32_t)(((perm ? n_to_oc(n) : n) * 8 + wblk_kc(cta)) * 288 + (lane & 3) * 16);
#pragma unroll
    for (int k = 0; k < 5; k++)
        if (k < 4 || !(lane & 2)) t[k] = __ldg(reinterpret_cast<const uint4*>(base + k * 64));
}
__device__ __forceinline__ void st_global64(void* p, uint32_t a, uint32_t b) { asm volatile("st.global.v2.u32 [%0], {%1,%2};" ::"l"(p), "r"(a), "r"(b) : "memory"); }
__device__ __forceinline__ const unsigned char* weight_block(uint32_t bounce, unsigned char* wt, int cta, int lane, int kx) {
    unsigned char* piece = wt + wblk_kc(cta) * STAGE_BYTES + (cta & 15) * 768 + kx * 256;
    uint32_t g[3][4];
#pragma unroll
    for (int i = 0; i < 12; i++)
        asm volatile("ld.shared.u16 %0, [%1];" : "=r"(g[i % 3][i / 3]) : "r"(S0 + bounce + (lane & 7) * 288 + (lane >> 3) * 72 + kx * 2 + i * 6) : "memory");
    float u1[4], u2[4];
#pragma unroll
    for (int c = 0; c < 4; c++) {
        const float t = 0.5f * (bf_lo(g[0][c]) + bf_lo(g[2][c]));
        u1[c] = fmaf(bf_lo(g[1][c]), 0.5f, t); u2[c] = fmaf(bf_lo(g[1][c]), -0.5f, t);
    }
    unsigned char* dst = piece + (lane >> 4) * 128 + (lane & 7) * 16 + ((lane >> 3) & 1) * 8;
    st_global64(dst, pack_bf(u1[0], u1[1]), pack_bf(u1[2], u1[3]));
    st_global64(dst + 8 * STAGE_BYTES, pack_bf(u2[0], u2[1]), pack_bf(u2[2], u2[3]));
    st_global64(dst + 16 * STAGE_BYTES, __byte_perm(g[0][0], g[0][1], 0x5410), __byte_perm(g[0][2], g[0][3], 0x5410));
    st_global64(dst + 24 * STAGE_BYTES, __byte_perm(g[2][0], g[2][1], 0x5410), __byte_perm(g[2][2], g[2][3], 0x5410));
    return piece + (lane >> 3) * 8 * STAGE_BYTES + (lane & 7) * 32;
}
__device__ __forceinline__ void publish(uint32_t bar, int lane) {
    fence_async_smem();
    __syncwarp();
    if (lane == 0) mbar_arrive(bar);
}
__device__ __forceinline__ void lds_piece(uint32_t (&u)[4], uint32_t a) {
    const uint4 q = lds128(a);
    u[0] = q.x; u[1] = q.y; u[2] = q.z; u[3] = q.w;
}
__device__ __noinline__ void side_jobs(const __nv_bfloat16* __restrict__ t_emb, const __nv_bfloat16* __restrict__ w_emb,
                                       const __nv_bfloat16* __restrict__ w2, Scratch* __restrict__ gs, unsigned clk0) {
    const int tid = threadIdx.x, warp = tid >> 5, lane = tid & 31, j = blockIdx.x;
    float tv = 0.f;
    if (lane < 24) tv = __bfloat162float(t_emb[(lane / 12) * E + j * 192 + warp * 12 + lane % 12]);
    if (tid == 0) {
        mbar_init(BAR(0), 1);
        mbar_expect(BAR(0), 192 * C * 2);
        fence_async_smem();
        while (clock32() - clk0 < SDELAY) {}
#pragma unroll
        for (int i = 0; i < 4; i++)
            asm volatile("cp.async.bulk.prefetch.L2.global [%0], 18432;" ::"l"(reinterpret_cast<const char*>(w2) + (j * 4 + i) * 18432) : "memory");
#pragma unroll
        for (int i = 0; i < 4; i++) bulk_g2s(S0 + SM_W + i * 12288, w_emb + (j * 192 + i * 48) * C, 12288, S0 + BAR(0));
    }
    if (j == 0 && tid < 32) gs->acc2[(tid >> 4) * LS + (tid & 15)] = 0.f;
    const float sv = silu_half(0.5f * tv);
    __syncthreads();
    mbar_wait(BAR(0), 0);
    float acc[8] = {0.f, 0.f, 0.f, 0.f, 0.f, 0.f, 0.f, 0.f};
#pragma unroll
    for (int i = 0; i < 12; i++) {
        const float2 wq = lds64f(SM_W + (warp * 12 + i) * 256 + lane * 8);
        const uint32_t wx = __float_as_uint(wq.x), wy = __float_as_uint(wq.y);
#pragma unroll
        for (int bb = 0; bb < 2; bb++) {
            const float sx = __shfl_sync(0xffffffffu, sv, bb * 12 + i);
            acc[4 * bb + 0] = fmaf(sx, bf_lo(wx), acc[4 * bb + 0]); acc[4 * bb + 1] = fmaf(sx, bf_hi(wx), acc[4 * bb + 1]);
            acc[4 * bb + 2] = fmaf(sx, bf_lo(wy), acc[4 * bb + 2]); acc[4 * bb + 3] = fmaf(sx, bf_hi(wy), acc[4 * bb + 3]);
        }
    }
    sts128f(SM_V + warp * 1024 + lane * 16, make_float4(acc[0], acc[1], acc[2], acc[3]));
    sts128f(SM_V + warp * 1024 + 512 + lane * 16, make_float4(acc[4], acc[5], acc[6], acc[7]));
    __syncthreads();
    if (tid < 128) {
        float2 sum = make_float2(0.f, 0.f);
#pragma unroll
        for (int w = 0; w < 16; w++) { const float2 p = lds64f(SM_V + w * 1024 + tid * 8); sum.x += p.x; sum.y += p.y; }
        *reinterpret_cast<float2*>(&gs->emb[j * NB * C + tid * 2]) = sum;
        bar_sync(1, 128);
        if (tid < 2) asm volatile("red.release.gpu.global.add.u32 [%0], 1;" ::"l"(&gs->wcnt[(2 * NB + tid) * LS]) : "memory");
    }
}

__global__ void __cluster_dims__(2, 1, 1) __launch_bounds__(NTHREADS, 1)
resblock_kernel(const __nv_bfloat16* __restrict__ w1, const __nv_bfloat16* __restrict__ x,
                const __nv_bfloat16* __restrict__ t_emb, const __nv_bfloat16* __restrict__ g1,
                const __nv_bfloat16* __restrict__ be1, const __nv_bfloat16* __restrict__ w_emb,
                const __nv_bfloat16* __restrict__ g2, const __nv_bfloat16* __restrict__ be2,
                const __nv_bfloat16* __restrict__ w2, __nv_bfloat16* __restrict__ out, Scratch* __restrict__ gs,
                const __grid_constant__ CUtensorMap xmap) {
    const unsigned clk0 = clock32();
    if (threadIdx.x == 480 && blockIdx.x >= NXTRA) TLG(1);
    const int tid = threadIdx.x, lane = tid & 31;
    const int cta = blockIdx.x - NXTRA, b = cta >> 6, r = cta & 63, rk = cta & 1;
    uint4 v[5];
    if (tid < 32) weight_load(v, w1, cta & (NCTA - 1), lane, true);
    uint4 xv[8];
    const int ch0 = (b & 1) * C + rk * 64;
    if (tid >= 32 && tid < 96) {
        const char* src = reinterpret_cast<const char*>(x) + (uint32_t)(((ch0 + (lane >> 3)) * HW + (r ^ (tid >> 6))) * HW * 2 + (lane & 7) * 16);
        while (clock32() - clk0 < XDELAY + (tid >> 6) * XSTAG2) {}
#pragma unroll
        for (int i = 0; i < 8; i++) xv[i] = __ldg(reinterpret_cast<const uint4*>(src + i * (4 * HW * HW * 2)));
    }
    const int warp = __shfl_sync(0xffffffffu, tid >> 5, 0);
    if (cta < 0) { side_jobs(t_emb, w_emb, w2, gs, clk0); return; }

    if (warp != 4) asm volatile("barrier.cluster.arrive.relaxed.aligned;" ::: "memory");
    const bool has_near = r != 0 && r != HW - 1, has_far = r != 1 && r != HW - 2;
    const uint32_t peer0 = mapa(0, rk ^ 1);
    if (warp == 1 || warp == 2 || warp == 3 || warp == 5) {
        const int i = warp < 4 ? warp - 1 : 3, gl = i >> 1, row = i & 1;
        const uint32_t tile = SM_XA + row * 8192 + gl * 4096;
        if (elect_one()) {
            if (gl) asm volatile("prefetch.tensormap [%0];" ::"l"(&xmap) : "memory");
            mbar_init(BAR(BAR_X) + 8 * i, 1);
            if (gl) { mbar_expect(BAR(BAR_X) + 8 * i, 4096); fence_async_smem(); }
        }
        __syncwarp();
        bar_arrive(4, 256 + 32 + 128);
        if (gl) {
            while (clock32() - clk0 < XDELAY + XSTAG + row * XSTAG2) {}
            if (elect_one()) tma_x(tile, &xmap, r ^ row, ch0 + 32, BAR(BAR_X) + 8 * i);
            __syncwarp();
            mbar_wait(BAR(BAR_X) + 8 * i, 0);
#pragma unroll
            for (int k = 0; k < 8; k++) xv[k] = lds128(tile + k * 512 + lane * 16);
        }
        float c[8][4];
#pragma unroll
        for (int k = 0; k < 8; k++) {
            c[k][0] = c[k][1] = c[k][2] = c[k][3] = 0.f;
            stat_mma(c[k], xv[k].x, xv[k].y); stat_mma(c[k], xv[k].z, xv[k].w);
        }
#pragma unroll
        for (int k = 0; k < 4; k++) c[0][k] = ((c[0][k] + c[1][k]) + (c[2][k] + c[3][k])) + ((c[4][k] + c[5][k]) + (c[6][k] + c[7][k]));
        stat_store(c[0], SM_RED + i * 48, lane);
        __syncwarp();
        if (lane == 0) {
            const uint32_t a = SM_RED + i * 48;
            red_add4(&gs->acc1[b * LS + (rk * 2 + gl) * 4], 1.f, sum4(lds128f(a + 32)), sum4(lds128f(a)) + sum4(lds128f(a + 16)), 1.f);
            TL(74 + i);
        }
        if (!gl) {
#pragma unroll
            for (int k = 0; k < 8; k++)
                sts128(tile + k * 512 + (lane >> 3) * 128 + (((lane & 7) ^ ((lane >> 3) + 4 * (k & 1))) << 4), xv[k]);
            __syncwarp();
            if (lane == 0) mbar_arrive(BAR(BAR_X) + 8 * i);
        }
    }
    if (warp == 4) {
        if (elect_one()) {
#pragma unroll
            for (int i = 0; i < NSTAGE; i++) mbar_init(BAR(BAR_FULL + i), (i & 1) ? 1 : ((i & 2) ? 2 : 9));
#pragma unroll
            for (int i = 0; i <= NS; i++) mbar_init(BAR(BAR_WEMPTY + i), 4);
#pragma unroll
            for (int i = BAR_STATS; i < BAR_X; i++) mbar_init(BAR(i), i == BAR_EMB ? 2 : 1);
            asm volatile("fence.mbarrier_init.release.cluster;" ::: "memory");
        }
        if (lane < 2) sts128(SM_GST + lane * 16, make_uint4(0, 0, 0, 0));
        __syncwarp();
        if (lane < 6) mbar_expect(BAR(BAR_RV) + 8 * lane, lane < 4 ? 4096 : (lane == 4 ? 16384 : 8192));
        fence_async_smem();
        bar_arrive(0, 96);
        bar_arrive(5, 64);
        bar_arrive(4, 256 + 32 + 128);
        const uint4 z = make_uint4(0, 0, 0, 0);
#pragma unroll
        for (int i = 0; i < 2; i++) sts128(SM_V + (i * 16 + (lane >> 1)) * CH_PITCH + (lane & 1) * 16, z);
        if (lane < 2) sts128(SM_V + NSTAGE * KC_BYTES + lane * 16, z);
        if (lane < 16) sts128(SM_ONES + lane * 16, make_uint4(lane < 8 ? 0x3f803f80u : 0u, 0, 0, 0));
        fence_async_smem();
        bar_arrive(7, 160);
        asm volatile("barrier.cluster.arrive.relaxed.aligned;" ::: "memory");
            if (elect_one()) {
                mbar_expect(BAR(BAR_XO), 16384);
                while (clock32() - clk0 < ODELAY) {}
#pragma unroll
                for (int i = 0; i < 4; i++)
                    tma_x(SM_XB + i * 4096, &xmap, ((i >> 1) ^ rk) ? (r | 1) + 1 : (r & ~1) - 1, ch0 + (i & 1) * 32, BAR(BAR_XO));
            }
            __syncwarp();
        while (clock32() - clk0 < W2DELAY) {}
        weight_load(v, w2, cta, lane, false);
    }
    if (warp == 0 || warp == 4 || warp >= 14) {
        const int k = warp == 4;
        int kx = warp < 8 ? 0 : warp - 13;
        if (kx == 0) {
#pragma unroll
            for (int i = 0; i < 5; i++)
                if (i < 4 || !(lane & 2)) sts128(SM_BNC + k * 2304 + (lane >> 2) * 288 + (lane & 3) * 16 + i * 64, v[i]);
            if (lane == 0) TL(k ? 14 : 81);
        }
        if (k) __syncwarp(); else bar_sync(8, 96);
        const unsigned char* rp;
#pragma unroll 1
        do { rp = weight_block(SM_BNC + k * 2304, gs->wt + k * 32 * STAGE_BYTES, cta, lane, kx); } while (k && ++kx < 3);
        unsigned rb = ld_relaxed(rp);
        if (k) rb |= ld_relaxed(rp - 256) | ld_relaxed(rp - 512);
        asm volatile("{\n.reg .pred p;\nsetp.eq.u32 p, %0, 0x9e3779b9;\n@p st.shared.u32 [%1], %0;\n}" ::"r"(rb), "r"(S0 + SM_RED + 1020) : "memory");
        if (warp >= 8) {
            bar_arrive(9, 96);
        } else {
            if (k) __syncwarp(); else bar_sync(9, 96);
            if (lane < 2) asm volatile("red.relaxed.gpu.global.add.u32 [%0], 1;" ::"l"(k ? &gs->wcnt[(NB + lane) * LS] : &gs->w1cnt[(lane * 8 + wblk_kc(cta)) * KS]) : "memory");
            if (lane == 0) TL(k ? 13 : 4);
        }
    }

    if (warp >= 8) {
        asm volatile("setmaxnreg.dec.sync.aligned.u32 104;");
        const int nw = warp - 8;
        const unsigned one = gridDim.y;
        if (nw < 4) {
            const uint2 q = __ldg(reinterpret_cast<const uint2*>(nw == 0 ? g1 : (nw == 1 ? be1 : (nw == 2 ? g2 : be2))) + lane);
            sts128f(SM_COEF + nw * 512 + lane * 16, make_float4(0.5f * bf_lo(q.x), 0.5f * bf_hi(q.x), 0.5f * bf_lo(q.y), 0.5f * bf_hi(q.y)));
        }
        bar_sync(4, 256 + 32 + 128);
        asm volatile("barrier.cluster.wait.acquire.aligned;" ::: "memory");
        const int hf = nw >> 2, wq = nw & 3;
        const uint32_t v_off = SM_V + (lane & 3) * CH_PITCH + (2 + wq * 16 + hf * 8 + (lane >> 2)) * 16;
        const int crow = ((lane & 6) << 2) | ((lane >> 3) << 1) | (lane & 1);
        const uint32_t stg_off = crow * 128 + (((2 * wq + hf) ^ (crow & 7)) << 4);
        const uint32_t img_off = (tid - 256) * 16;
        const float sg = rk ? -1.f : 1.f;
        uint4* inbox = gs->box + cta * 1024 + (tid - 256);
#pragma unroll 1
        for (int conv = 0; conv < 2; conv++) {
            uint32_t u[4][4];
            if (conv == 0) {
#pragma unroll
                for (int i = 0; i < 4; i++) { mbar_wait(BAR(BAR_X + i), 0); ldsm4t(u[i], SM_XA + (i & 1) * 8192 + (i >> 1) * 4096 + stg_off); }
            } else {
                mbar_wait(BAR(BAR_HW), 0);
                mbar_wait(BAR(BAR_RH), 0);
#pragma unroll
                for (int i = 0; i < 4; i++) lds_piece(u[i], SM_XA + (i & 1) * 8192 + (i >> 1) * 4096 + img_off);
            }
            float ga[2][8], be[2][8], a[4][8];
#pragma unroll
            for (int g = 0; g < 2; g++) {
                const uint32_t ca = SM_COEF + conv * 1024 + (rk * 64 + g * 32 + (lane & 3) * 8) * 4;
                const float4 q0 = lds128f(ca), q1 = lds128f(ca + 16), q2 = lds128f(ca + 512), q3 = lds128f(ca + 528);
                ga[g][0] = q0.x; ga[g][1] = q0.y; ga[g][2] = q0.z; ga[g][3] = q0.w; ga[g][4] = q1.x; ga[g][5] = q1.y; ga[g][6] = q1.z; ga[g][7] = q1.w;
                be[g][0] = q2.x; be[g][1] = q2.y; be[g][2] = q2.z; be[g][3] = q2.w; be[g][4] = q3.x; be[g][5] = q3.y; be[g][6] = q3.z; be[g][7] = q3.w;
            }
#pragma unroll
            for (int i = 0; i < 16; i++) {
                a[i >> 2][2 * (i & 3)] = bf_lo(u[i >> 2][i & 3]) * ga[i >> 3][2 * (i & 3)];
                a[i >> 2][2 * (i & 3) + 1] = bf_hi(u[i >> 2][i & 3]) * ga[i >> 3][2 * (i & 3) + 1];
                asm volatile("" : "+f"(a[i >> 2][2 * (i & 3)]), "+f"(a[i >> 2][2 * (i & 3) + 1]));
            }
            float4 gv = make_float4(0.f, 0.f, 0.f, 0.f);
            if (conv == 0) {
                mbar_wait(BAR(BAR_XO), 0);
#pragma unroll
                for (int i = 0; i < 4; i++) ldsm4t(u[i], SM_XB + (i & 1) * 8192 + (i >> 1) * 4096 + stg_off);
            }
#pragma unroll
            for (int g = 0; g < 2; g++) {
                unsigned it = 0;
#pragma unroll 1
                while (!__all_sync(0xffffffffu, (g ? gv.z : gv.x) != 0.f) && ++it < 8 * SPIN_LIMIT)
                    asm volatile("ld.volatile.shared.v4.f32 {%0,%1,%2,%3}, [%4];" : "=f"(gv.x), "=f"(gv.y), "=f"(gv.z), "=f"(gv.w) : "r"(S0 + SM_GST + conv * 16) : "memory");
                if (g == 0 && tid == 256) TL(22 + conv * 4);
                const float rs = g ? gv.z : gv.x, mr = g ? gv.w : gv.y;
                uint32_t kp[4], sd[4];
#pragma unroll
                for (int i = 0; i < 8; i++) {
                    be[g][i] = fmaf(-mr, ga[g][i], be[g][i]);
                    a[2 * g][i] = silu_half(fmaf(a[2 * g][i], rs, be[g][i])); a[2 * g + 1][i] = silu_half(fmaf(a[2 * g + 1][i], rs, be[g][i]));
                }
#pragma unroll
                for (int i = 0; i < 4; i++) {
                    kp[i] = pack_bf(fmaf(a[2 * g][2 * i], sg, a[2 * g + 1][2 * i]), fmaf(a[2 * g][2 * i + 1], sg, a[2 * g + 1][2 * i + 1]));
                    sd[i] = pack_bf(fmaf(a[2 * g + 1][2 * i], -sg, a[2 * g][2 * i]), fmaf(a[2 * g + 1][2 * i + 1], -sg, a[2 * g][2 * i + 1]));
                }
                sts128(v_off + g * 4 * KC_BYTES, make_uint4(kp[0], kp[1], kp[2], kp[3]));
                st_async(peer0 + v_off + (g * 4 + 2) * KC_BYTES, sd[0], sd[1], sd[2], sd[3], peer0 + BAR(BAR_RV + g));
                publish(BAR(BAR_FULL + 4 * g), lane);
                if (tid == 256) TL(g ? 84 + conv : 8 + conv * 8);
                if (g == LDAT && conv == 1) {
#pragma unroll
                    for (int i = 0; i < 4; i++) ld_unit(u[i], inbox + (i & 1) * 512 + (i >> 1) * 256);
                }
            }
            if (conv == 1) {
                unsigned it = 0;
                while (true) {
                    bool okn = true, okf = true;
#pragma unroll
                    for (int i = 0; i < 8; i++) { okn = okn && u[(i >> 2) * 2][i & 3] != 0; okf = okf && u[(i >> 2) * 2 + 1][i & 3] != 0; }
                    if (__all_sync(0xffffffffu, (okn || !has_near) && (okf || !has_far)) || ++it > SPIN_LIMIT) break;
#pragma unroll
                    for (int i = 0; i < 4; i++) ld_unit(u[i], inbox + (i & 1) * 512 + (i >> 1) * 256);
                    if (tid == 256) TL(93);
                }
            }
            if (tid == 256) TL(24 + conv * 4);
#pragma unroll
            for (int g = 0; g < 2; g++) {
                const float rs = g ? gv.z : gv.x;
                uint32_t o[2][4];
#pragma unroll
                for (int f = 0; f < 2; f++) {
                    const bool ok = f ? has_far : has_near;
#pragma unroll
                    for (int i = 0; i < 4; i++) {
                        const float lo = silu_half(fmaf(bf_lo(u[2 * g + f][i]), ga[g][2 * i] * rs, be[g][2 * i]));
                        const float hi = silu_half(fmaf(bf_hi(u[2 * g + f][i]), ga[g][2 * i + 1] * rs, be[g][2 * i + 1]));
                        o[f][i] = pack_bf((ok ? lo : 0.f) - a[2 * g + (f ^ 1)][2 * i], (ok ? hi : 0.f) - a[2 * g + (f ^ 1)][2 * i + 1]);
                    }
                }
                sts128(v_off + (8 + g * 4) * KC_BYTES, make_uint4(o[0][0], o[0][1], o[0][2], o[0][3]));
                st_async(peer0 + v_off + (10 + g * 4) * KC_BYTES, o[1][0], o[1][1], o[1][2], o[1][3], peer0 + BAR(BAR_RV + 2 + g));
                publish(BAR(BAR_FULL + 8 + 4 * g), lane);
                if (tid == 256) TL(g ? 88 + conv : 23 + conv * 4);
                if (one == 0) break;
            }
        }
        mbar_wait(BAR(BAR_FULL + NSTAGE - 1), 1);
#pragma unroll
        for (int i = 0; i < 4; i++) inbox[i * 256] = make_uint4(0, 0, 0, 0);
        {
            const int oc0 = hf * 64 + ((tid & 127) >> 3), seg = lane & 7;
            __nv_bfloat16* dst = out + ((size_t)(b * C + oc0) * HW + r) * HW + seg * 8;
            const uint32_t src = oc0 * 128 + ((seg ^ (oc0 & 7)) << 4);
            mbar_wait(BAR(BAR_XR), 0);
            uint4 xr[4];
#pragma unroll
            for (int i = 0; i < 4; i++) xr[i] = lds128(SM_XA + src + i * 2048);
            asm volatile("{\n.reg .pred p;\nsetp.eq.u64 p, %0, 0;\n@p st.shared.u32 [%1], 0;\n}" ::"l"(dst), "r"(src + S0) : "memory");
            bar_sync(hf ? 1 : 6, 128 + 128);
#pragma unroll
            for (int i = 0; i < 4; i++) {
                uint4 o = lds128(SM_XB + src + i * 2048);
                asm("add.rn.bf16x2 %0, %0, %1;" : "+r"(o.x) : "r"(xr[i].x)); asm("add.rn.bf16x2 %0, %0, %1;" : "+r"(o.y) : "r"(xr[i].y));
                asm("add.rn.bf16x2 %0, %0, %1;" : "+r"(o.z) : "r"(xr[i].z)); asm("add.rn.bf16x2 %0, %0, %1;" : "+r"(o.w) : "r"(xr[i].w));
                *reinterpret_cast<uint4*>(dst + (size_t)i * 16 * HW * HW) = o;
            }
            if (tid == 384) { TL(20); TLG(21); }
        }
    } else if (warp < 4) {
        const int wq = warp;
        asm volatile("setmaxnreg.inc.sync.aligned.u32 176;");
        bar_sync(7, 160);
        asm volatile("barrier.cluster.wait.acquire.aligned;" ::: "memory");
        const float sg = rk ? 1.f : -1.f;
        float d[64], e[64];
#pragma unroll 1
        for (int conv = 0; conv < 2; conv++) {
#pragma unroll
            for (int i = 0; i < 64; i++) { d[i] = 0.f; e[i] = 0.f; }
            fence_acc(d); fence_acc(e);
            mma_stages<0>(d, e, conv, tid, peer0, gs);
            if (conv == 0) {
                asm volatile("wgmma.fence.sync.aligned;" ::: "memory");
                wgmma128<(SM_ONES >> 4) | (8u << 16), (SM_EMB >> 4), 0, 8>(e);
                asm volatile("wgmma.commit_group.sync.aligned;" ::: "memory");
            }
            mbar_wait(BAR(BAR_M), conv);
#pragma unroll
            for (int j = 0; j < 8; j++) {
                uint32_t q[4];
                lds_piece(q, SM_M + j * 2048 + tid * 16);
#pragma unroll
                for (int i = 0; i < 4; i++) { d[8 * j + 2 * i] = fmaf(bf_lo(q[i]), sg, d[8 * j + 2 * i]); d[8 * j + 2 * i + 1] = fmaf(bf_hi(q[i]), sg, d[8 * j + 2 * i + 1]); }
            }
            fence_acc(d);
            asm volatile("wgmma.wait_group.sync.aligned 0;" ::: "memory");
            fence_acc(e);
            if (tid == 0) TL(10 + conv * 8);
            uint32_t hp[32];
#pragma unroll
            for (int i = 0; i < 32; i++) hp[i] = pack_bf(d[2 * i] + e[2 * i], d[2 * i + 1] + e[2 * i + 1]);
            if (conv == 1) {
                const uint32_t obase = SM_XB + ((lane >> 4) * 8 + (lane & 7)) * 128 + (((2 * wq + ((lane >> 3) & 1)) ^ (lane & 7)) << 4);
#pragma unroll
                for (int kc = 0; kc < 8; kc++) {
                    stsm4t(obase + kc * 2048, hp[4 * kc], hp[4 * kc + 1], hp[4 * kc + 2], hp[4 * kc + 3]);
                    if (kc == 3) bar_arrive(6, 128 + 128);
                }
                bar_arrive(1, 128 + 128);
                break;
            }
#pragma unroll
            for (int g = 0; g < 4; g++) {
                float c[4] = {0.f, 0.f, 0.f, 0.f};
#pragma unroll
                for (int i = 0; i < 4; i++) stat_mma(c, hp[8 * g + 2 * i], hp[8 * g + 2 * i + 1]);
                stat_store(c, SM_RED + (g * 4 + wq) * 48, lane);
            }
            bar_sync(2, 128);
            if (wq == 0) stat_publish(SM_RED, &gs->acc2[b * LS], lane, true);
            if (tid == 0) TL(11);
            if (tid == 32) mbar_expect(BAR(BAR_M), 16384);
#pragma unroll
            for (int j = 0; j < 8; j++) {
                const uint32_t p0 = hp[(j >> 1) * 8 + (j & 1)], p1 = hp[(j >> 1) * 8 + (j & 1) + 2], p2 = hp[(j >> 1) * 8 + (j & 1) + 4], p3 = hp[(j >> 1) * 8 + (j & 1) + 6];
                if ((j >> 2) == rk) sts128(SM_XA + (j & 3) * 2048 + tid * 16, make_uint4(p0, p1, p2, p3));
                else st_async(peer0 + SM_XA + 8192 + (j & 3) * 2048 + tid * 16, p0, p1, p2, p3, peer0 + BAR(BAR_RH));
            }
            __syncwarp();
            if (lane == 0) { mbar_arrive(BAR(BAR_HW)); mbar_arrive(BAR(BAR_WEMPTY + 7)); }
            if (has_near) {
                const int oc2 = (cta & ~1) + (rk ? 2 : -2);
#pragma unroll
                for (int j = 0; j < 8; j++) {
                    uint4* outbox = gs->box + (oc2 + (j >> 2)) * 1024 + (((j >> 2) == rk) ? 512 : 0) + (j & 3) * 128 + tid;
                    *outbox = make_uint4(max(hp[(j >> 1) * 8 + (j & 1)], 1u), max(hp[(j >> 1) * 8 + (j & 1) + 2], 1u),
                                         max(hp[(j >> 1) * 8 + (j & 1) + 4], 1u), max(hp[(j >> 1) * 8 + (j & 1) + 6], 1u));
                }
            }
            if (tid == 0) TL(12);
        }
    } else {
    if (warp < 6) {
        if (warp == 5) {
            bar_sync(5, 64);
#pragma unroll 1
            for (int i = 0; i < 8; i++) {
                mbar_wait(BAR(BAR_RV) + 8 * (i & 3), i >> 2);
                fence_async_smem();
                if (lane == 0) {
                    mbar_arrive(BAR(BAR_FULL + 2) + 32 * (i & 3));
                    if (i < 4) mbar_expect(BAR(BAR_RV) + 8 * i, 4096);
                    TL(64 + i);
                }
                __syncwarp();
            }
        } else {
            mbar_wait(BAR(BAR_STATS), 0);
            unsigned it = 0;
            while (!__all_sync(0xffffffffu, ld_relaxed(&gs->wcnt[(2 * NB + b) * LS]) >= (unsigned)NXTRA) && ++it < SPIN_LIMIT) __nanosleep(100);
            fence_acquire();
            float ev[4] = {0.f, 0.f, 0.f, 0.f};
#pragma unroll
            for (int j = 0; j < NXTRA; j++) {
                const uint4 ef = ld_relaxed_v4(&gs->emb[(j * NB + b) * C + lane * 4]);
                ev[0] += __uint_as_float(ef.x); ev[1] += __uint_as_float(ef.y); ev[2] += __uint_as_float(ef.z); ev[3] += __uint_as_float(ef.w);
            }
#pragma unroll
            for (int i = 0; i < 4; i++) {
                const float hi = bf_lo(pack_bf(ev[i], 0.f));
                sts128(SM_EMB + n_to_oc(lane * 4 + i) * 16, make_uint4(pack_bf(hi, ev[i] - hi), 0, 0, 0));
            }
            fence_async_smem();
            __syncwarp();
            if (lane == 0) { mbar_arrive(BAR(BAR_EMB)); TL(19); }
            mbar_wait(BAR(BAR_HW), 0);
            mbar_wait(BAR(BAR_FULL + 8), 1);
            if (elect_one()) {
                mbar_expect(BAR(BAR_XR), 16384);
#pragma unroll
                for (int i = 0; i < 4; i++) tma_x(SM_XA + i * 4096, &xmap, r, b * C + i * 32, BAR(BAR_XR));
            }
        }
    } else if (warp == 6) {
        bar_sync(0, 96);
        if (lane < NSTAGE) mbar_expect(BAR(BAR_FULL) + 8 * lane, STAGE_BYTES);
        const unsigned char* wbase = gs->wt + rk * 8 * STAGE_BYTES;
        unsigned it = 0;
        {
            int g = 0;
            const int l7 = lane & 7;
            const unsigned* cnt = &gs->w1cnt[(b * 8 + ((((l7 >> 1) ^ rk) & 1) * 4 + (l7 >> 2) * 2 + (l7 & 1))) * KS];
            unsigned cv = ld_relaxed(cnt);
#pragma unroll 1
            while (g < NS) {
                unsigned ready = __ballot_sync(0xffffffffu, cv >= 16u);
                if (ready != ~0u) cv = ld_relaxed(cnt);
                ready >>= g;
                if (++it > SPIN_LIMIT) ready = ~0u;
                if (!(ready & 1)) continue;
                fence_async_global();
                if (lane == 0) TL(g ? 3 : 6);
#pragma unroll 1
                for (; (ready & 1) && g < NS; g++, ready >>= 1)
                    if (elect_one())
                        bulk_g2s(S0 + SM_W + g * STAGE_BYTES, wbase + ((((g >> 1) ^ rk) & 1) * 4 + (g >> 2) * 2 + (g & 1)) * STAGE_BYTES, STAGE_BYTES,
                                 S0 + BAR(BAR_FULL) + 8 * g);
            }
        }
#pragma unroll 1
        for (int q = 2; q < 8; q++) {
            const unsigned char* wsrc = wbase + ((q >> 1) * 16 + (q & 1) * 2) * STAGE_BYTES;
            const uint32_t par = ((q >> 1) - 1) & 1;
            if (q == 4) {
                it = 0;
                while (!__all_sync(0xffffffffu, ld_relaxed(&gs->wcnt[(NB + b) * LS]) == (unsigned)NCTA) && ++it < SPIN_LIMIT) {}
                fence_acquire();
                fence_async_global();
                if (lane == 0) { mbar_arrive(BAR(BAR_EMB)); TL(2); }
            }
#pragma unroll
            for (int i = 0; i < 4; i++) {
                mbar_wait(BAR(BAR_WEMPTY + i) + 32 * (q & 1), par);
                if (i == 0 && (q == 4 || q == 6)) {
                    if ((lane >> 3) == (q - 4) / 2) mbar_expect(BAR(BAR_FULL) + 8 * lane, STAGE_BYTES);
                    __syncwarp();
                }
                if (elect_one())
                    bulk_g2s(S0 + SM_W + ((q & 1) * 4 + i) * STAGE_BYTES, wsrc + ((((i >> 1) ^ rk) & 1) * 4 + (i & 1)) * STAGE_BYTES, STAGE_BYTES,
                             S0 + BAR(BAR_FULL + i) + 32 * (q & 3));
            }
        }
    } else {
        bar_sync(0, 96);
#pragma unroll 1
        for (int conv = 0; conv < 2; conv++) {
            if (conv == 1) mbar_wait(BAR(BAR_HW), 0);
            const float* asrc = (conv ? gs->acc2 : gs->acc1) + b * LS + (rk * 2 + (lane & 1)) * 4;
            unsigned it = 0;
#pragma unroll 1
            while (true) {
                const uint4 f = ld_relaxed_v4(asrc);
                const bool ok = ((f.x == 0x42800000u) & (f.w == 0x42800000u)) || ++it > SPIN_LIMIT;
                if (ok && lane < 2) {
                    const float inv_n = 1.0f / (32.0f * HW * HW);
                    const float mean = __uint_as_float(f.y) * inv_n;
                    float rs;
                    asm("rsqrt.approx.ftz.f32 %0, %1;" : "=f"(rs) : "f"(fmaxf(fmaf(-mean, mean, __uint_as_float(f.z) * inv_n), 0.f) + 1e-5f));
                    asm volatile("st.shared.v2.f32 [%0], {%1,%2};" ::"r"(S0 + SM_GST + conv * 16 + lane * 8), "f"(rs == 0.f ? 1.2e-38f : rs), "f"(mean * rs) : "memory");
                }
                if (__all_sync(0xffffffffu, ok)) break;
            }
            if (lane == 0) { mbar_arrive(BAR(BAR_STATS)); TL(7 + conv * 8); }
        }
        if (r == 0) {
            if (lane < 16) gs->acc1[b * LS + lane] = 0.f;
            if (lane < 3) gs->wcnt[(lane * NB + b) * LS] = 0;
            if (lane < 8) gs->w1cnt[(b * 8 + lane) * KS] = 0;
        }
    }
    }
}

}

extern "C" void kernel_launch(void* const* d_in, const int* in_sizes, int n_in, void* d_out, int out_size) {
    (void)in_sizes; (void)n_in; (void)out_size;
    typedef CUresult (*EncodeFn)(CUtensorMap*, CUtensorMapDataType, cuuint32_t, void*, const cuuint64_t*, const cuuint64_t*,
                                 const cuuint32_t*, const cuuint32_t*, CUtensorMapInterleave, CUtensorMapSwizzle,
                                 CUtensorMapL2promotion, CUtensorMapFloatOOBfill);
    static Scratch* gs = nullptr;
    static EncodeFn encode = nullptr;
    if (!gs) {
        cudaFuncSetAttribute(resblock_kernel, cudaFuncAttributeMaxDynamicSharedMemorySize, SM_TOTAL);
        cudaGetSymbolAddress((void**)&gs, g_scratch);
        cudaDriverEntryPointQueryResult qr;
        cudaGetDriverEntryPoint("cuTensorMapEncodeTiled", (void**)&encode, cudaEnableDefault, &qr);
    }
    CUtensorMap xmap;
    const cuuint64_t dims[3] = {HW, HW, NB * C}, strides[2] = {HW * 2, HW * HW * 2};
    const cuuint32_t box[3] = {HW, 1, 32}, es[3] = {1, 1, 1};
    encode(&xmap, CU_TENSOR_MAP_DATA_TYPE_BFLOAT16, 3, d_in[0], dims, strides, box, es, CU_TENSOR_MAP_INTERLEAVE_NONE,
           CU_TENSOR_MAP_SWIZZLE_128B, CU_TENSOR_MAP_L2_PROMOTION_NONE, CU_TENSOR_MAP_FLOAT_OOB_FILL_NONE);
    resblock_kernel<<<NCTA + NXTRA, NTHREADS, SM_TOTAL>>>(
        (const __nv_bfloat16*)d_in[4], (const __nv_bfloat16*)d_in[0], (const __nv_bfloat16*)d_in[1],
        (const __nv_bfloat16*)d_in[2], (const __nv_bfloat16*)d_in[3], (const __nv_bfloat16*)d_in[5],
        (const __nv_bfloat16*)d_in[6], (const __nv_bfloat16*)d_in[7], (const __nv_bfloat16*)d_in[8],
        (__nv_bfloat16*)d_out, gs, xmap);
}
```

```cpp
#include <cuda_runtime.h>
#include <cuda.h>
#include <cuda_bf16.h>
#include <stdint.h>

namespace {

constexpr int C = 128, HW = 64, NB = 2, E = 768;
constexpr int NCTA = NB * HW;
constexpr int NXTRA = 4;
constexpr int NTHREADS = 16 * 32;
constexpr int CH_PITCH = 66 * 16;
constexpr int KC_BYTES = 2 * CH_PITCH;
constexpr int STAGE_BYTES = 12288;
constexpr int NSTAGE = 16;
constexpr int NS = 12;
#define XDELAY 300
#define XSTAG 800
#define XSTAG2 100
#define SDELAY 600
#define W2DELAY 2400
#define ODELAY 2400
#define SAFTER 1
#define HOP 1
#define LDAT 0

constexpr uint32_t SMEM_BASE = 0x400;
constexpr uint32_t SM_XA = SMEM_BASE;
constexpr uint32_t SM_XB = SM_XA + 16384;
constexpr uint32_t SM_M = SM_XB;
constexpr uint32_t SM_V = SM_M + 16384;
constexpr uint32_t SM_W = SM_V + NSTAGE * KC_BYTES + 128;
constexpr uint32_t SM_OUT = SM_W + 4 * STAGE_BYTES;
constexpr uint32_t SM_COEF = SM_W + NS * STAGE_BYTES;
constexpr uint32_t SM_GST = SM_COEF + 2048;
constexpr uint32_t SM_EMB = SM_GST + 128;
constexpr uint32_t SM_ONES = SM_EMB + 2048;
constexpr uint32_t SM_RED = SM_ONES + 256;
constexpr uint32_t SM_BNC = SM_RED + 1024;
constexpr uint32_t SM_BAR = SM_BNC + 2 * 2304;
constexpr int BAR_FULL = 0, BAR_WEMPTY = NSTAGE, BAR_HW = BAR_WEMPTY + NS, BAR_STATS = BAR_HW + 1, BAR_EMB = BAR_STATS + 1,
              BAR_RV = BAR_EMB + 1  , BAR_M = BAR_RV + 4, BAR_RH = BAR_M + 1, BAR_XO = BAR_RH + 1, BAR_XR = BAR_XO + 1,
              BAR_X = BAR_XR + 1  , NBAR = BAR_X + 4;
constexpr int SM_TOTAL = SM_BAR + NBAR * 8 - SMEM_BASE;
static_assert(SM_TOTAL <= 232448, "smem");
__host__ __device__ constexpr uint32_t BAR(int i) { return SM_BAR + 8 * i; }

constexpr unsigned SPIN_LIMIT = 1u << 16;
constexpr int LS = 1056, KS = 32;

struct Scratch {
    float acc1[NB * LS];
    float acc2[NB * LS];
    unsigned wcnt[3 * NB * LS];
    unsigned w1cnt[NB * 8 * KS];
    float emb[NXTRA * NB * C];
    alignas(1024) unsigned char wt[2 * 32 * STAGE_BYTES];
    uint4 box[NCTA * 1024];
};
__device__ __align__(1024) Scratch g_scratch;
#define TL(i) do {} while (0)
#define TLG(i) do {} while (0)

__device__ __forceinline__ unsigned clock32() { unsigned c; asm volatile("mov.u32 %0, %%clock;" : "=r"(c)); return c; }
__device__ __forceinline__ uint32_t mapa(uint32_t a, uint32_t rank) {
    uint32_t d;
    asm("mapa.shared::cluster.u32 %0, %1, %2;" : "=r"(d) : "r"(a), "r"(rank));
    return d;
}
#define S0 mapa(0, blockIdx.x & 1)
__device__ __forceinline__ void mbar_init(uint32_t bar, int cnt) {
    asm volatile("mbarrier.init.shared::cta.b64 [%0], %1;" ::"r"(bar + S0), "r"(cnt) : "memory");
}
__device__ __forceinline__ void mbar_arrive(uint32_t bar) {
    asm volatile("mbarrier.arrive.shared::cta.b64 _, [%0];" ::"r"(bar + S0) : "memory");
}
__device__ __forceinline__ void mbar_expect(uint32_t bar, uint32_t bytes) {
    asm volatile("mbarrier.arrive.expect_tx.shared::cta.b64 _, [%0], %1;" ::"r"(bar + S0), "r"(bytes) : "memory");
}
__device__ __forceinline__ bool mbar_try(uint32_t bar, uint32_t par) {
    uint32_t ok;
    asm volatile("{\n.reg .pred p;\nmbarrier.try_wait.parity.shared::cta.b64 p, [%1], %2;\nselp.u32 %0, 1, 0, p;\n}"
                 : "=r"(ok) : "r"(bar + S0), "r"(par) : "memory");
    return ok;
}
__device__ __forceinline__ bool mbar_test(uint32_t bar, uint32_t par) {
    uint32_t ok;
    asm volatile("{\n.reg .pred p;\nmbarrier.test_wait.parity.shared::cta.b64 p, [%1], %2;\nselp.u32 %0, 1, 0, p;\n}"
                 : "=r"(ok) : "r"(bar + S0), "r"(par) : "memory");
    return ok;
}
__device__ __forceinline__ void mbar_wait(uint32_t bar, uint32_t par) {
    unsigned it = 0;
#pragma unroll 1
    while (!mbar_try(bar, par) && ++it < SPIN_LIMIT) {}
}
__device__ __forceinline__ bool elect_one() {
    uint32_t p;
    asm volatile("{\n.reg .pred p;\nelect.sync _|p, 0xffffffff;\nselp.u32 %0, 1, 0, p;\n}" : "=r"(p));
    return p;
}
__device__ __forceinline__ void fence_async_smem() { asm volatile("fence.proxy.async.shared::cta;" ::: "memory"); }
__device__ __forceinline__ void fence_async_global() { asm volatile("fence.proxy.async.global;" ::: "memory"); }
__device__ __forceinline__ void fence_acquire() { asm volatile("fence.acquire.gpu;" ::: "memory"); }
__device__ __forceinline__ void bar_sync(int id, int n) { asm volatile("bar.sync %0, %1;" ::"r"(id), "r"(n) : "memory"); }
__device__ __forceinline__ void bar_arrive(int id, int n) { asm volatile("bar.arrive %0, %1;" ::"r"(id), "r"(n) : "memory"); }
__device__ __forceinline__ void bulk_g2s(uint32_t dst, const void* src, uint32_t bytes, uint32_t bar) {
    asm volatile("cp.async.bulk.shared::cluster.global.mbarrier::complete_tx::bytes [%0], [%1], %2, [%3];"
                 ::"r"(dst), "l"(src), "r"(bytes), "r"(bar) : "memory");
}
__device__ __forceinline__ void tma_x(uint32_t dst, const CUtensorMap* tm, int row, int ch, uint32_t bar) {
    asm volatile("cp.async.bulk.tensor.3d.shared::cluster.global.mbarrier::complete_tx::bytes [%0], [%1, {%2, %3, %4}], [%5];"
                 ::"r"(dst + S0), "l"(tm), "r"(0), "r"(row), "r"(ch), "r"(bar + S0) : "memory");
}
__device__ __forceinline__ uint4 ld_relaxed_v4(const void* p) {
    uint4 v;
    asm volatile("ld.relaxed.gpu.global.v4.u32 {%0,%1,%2,%3}, [%4];" : "=r"(v.x), "=r"(v.y), "=r"(v.z), "=r"(v.w) : "l"(p) : "memory");
    return v;
}
__device__ __forceinline__ unsigned ld_relaxed(const void* p) {
    unsigned v;
    asm volatile("ld.relaxed.gpu.global.u32 %0, [%1];" : "=r"(v) : "l"(p) : "memory");
    return v;
}
__device__ __forceinline__ void red_add4(float* p, float a, float b, float c, float d) {
    asm volatile("red.relaxed.gpu.global.add.v4.f32 [%0], {%1,%2,%3,%4};" ::"l"(p), "f"(a), "f"(b), "f"(c), "f"(d) : "memory");
}
__device__ __forceinline__ void sts128(uint32_t a, uint4 v) {
    asm volatile("st.shared.v4.u32 [%0], {%1,%2,%3,%4};" ::"r"(a + S0), "r"(v.x), "r"(v.y), "r"(v.z), "r"(v.w) : "memory");
}
__device__ __forceinline__ void sts128f(uint32_t a, float4 v) {
    asm volatile("st.shared.v4.f32 [%0], {%1,%2,%3,%4};" ::"r"(a + S0), "f"(v.x), "f"(v.y), "f"(v.z), "f"(v.w) : "memory");
}
__device__ __forceinline__ void sts32f(uint32_t a, float v) { asm volatile("st.shared.f32 [%0], %1;" ::"r"(a + S0), "f"(v) : "memory"); }
__device__ __forceinline__ uint4 lds128(uint32_t a) {
    uint4 v;
    asm volatile("ld.shared.v4.u32 {%0,%1,%2,%3}, [%4];" : "=r"(v.x), "=r"(v.y), "=r"(v.z), "=r"(v.w) : "r"(a + S0) : "memory");
    return v;
}
__device__ __forceinline__ float4 lds128f(uint32_t a) {
    float4 v;
    asm volatile("ld.shared.v4.f32 {%0,%1,%2,%3}, [%4];" : "=f"(v.x), "=f"(v.y), "=f"(v.z), "=f"(v.w) : "r"(a + S0) : "memory");
    return v;
}
__device__ __forceinline__ float2 lds64f(uint32_t a) {
    float2 v;
    asm volatile("ld.shared.v2.f32 {%0,%1}, [%2];" : "=f"(v.x), "=f"(v.y) : "r"(a + S0) : "memory");
    return v;
}
__device__ __forceinline__ float bf_lo(uint32_t u) { return __uint_as_float(u << 16); }
__device__ __forceinline__ float bf_hi(uint32_t u) { return __uint_as_float(u & 0xffff0000u); }
__device__ __forceinline__ uint32_t pack_bf(float lo, float hi) {
    uint32_t r;
    asm("cvt.rn.bf16x2.f32 %0, %1, %2;" : "=r"(r) : "f"(hi), "f"(lo));
    return r;
}
__device__ __forceinline__ float tanh_fast(float x) {
    float r;
    asm("tanh.approx.f32 %0, %1;" : "=f"(r) : "f"(x));
    return r;
}
__device__ __forceinline__ float silu_half(float h) { return fmaf(h, tanh_fast(h), h); }
__device__ __forceinline__ void ldsm4(uint32_t (&u)[4], uint32_t a) {
    asm volatile("ldmatrix.sync.aligned.m8n8.x4.shared.b16 {%0,%1,%2,%3}, [%4];"
                 : "=r"(u[0]), "=r"(u[1]), "=r"(u[2]), "=r"(u[3]) : "r"(a + S0) : "memory");
}
__device__ __forceinline__ void ldsm4t(uint32_t (&u)[4], uint32_t a) {
    asm volatile("ldmatrix.sync.aligned.m8n8.x4.trans.shared.b16 {%0,%1,%2,%3}, [%4];"
                 : "=r"(u[0]), "=r"(u[1]), "=r"(u[2]), "=r"(u[3]) : "r"(a + S0) : "memory");
}
__device__ __forceinline__ void stsm4(uint32_t a, uint32_t p0, uint32_t p1, uint32_t p2, uint32_t p3) {
    asm volatile("stmatrix.sync.aligned.m8n8.x4.shared.b16 [%0], {%1,%2,%3,%4};" ::"r"(a + S0), "r"(p0), "r"(p1), "r"(p2), "r"(p3) : "memory");
}
__device__ __forceinline__ void stsm4t(uint32_t a, uint32_t p0, uint32_t p1, uint32_t p2, uint32_t p3) {
    asm volatile("stmatrix.sync.aligned.m8n8.x4.trans.shared.b16 [%0], {%1,%2,%3,%4};" ::"r"(a + S0), "r"(p0), "r"(p1), "r"(p2), "r"(p3) : "memory");
}

#define R8(o) "+f"(d[o]), "+f"(d[o + 1]), "+f"(d[o + 2]), "+f"(d[o + 3]), "+f"(d[o + 4]), "+f"(d[o + 5]), "+f"(d[o + 6]), "+f"(d[o + 7])
template <uint32_t ALO, uint32_t BLO, uint64_t AHI = 8, uint64_t BHI = 48>
__device__ __forceinline__ void wgmma128(float (&d)[64]) {
    asm volatile(
        "wgmma.mma_async.sync.aligned.m64n128k16.f32.bf16.bf16 "
        "{%0,%1,%2,%3,%4,%5,%6,%7,%8,%9,%10,%11,%12,%13,%14,%15,%16,%17,%18,%19,%20,%21,%22,%23,%24,%25,%26,%27,%28,%29,%30,%31,"
        "%32,%33,%34,%35,%36,%37,%38,%39,%40,%41,%42,%43,%44,%45,%46,%47,%48,%49,%50,%51,%52,%53,%54,%55,%56,%57,%58,%59,%60,%61,%62,%63},"
        " %64, %65, 1, 1, 1, 0, 0;"
        : R8(0), R8(8), R8(16), R8(24), R8(32), R8(40), R8(48), R8(56)
        : "l"((AHI << 32) | ALO), "l"((BHI << 32) | BLO));
}
__device__ __forceinline__ void stat_mma(float (&c)[4], uint32_t p, uint32_t q) {
    asm("mma.sync.aligned.m16n8k16.row.col.f32.bf16.bf16.f32 {%0,%1,%2,%3}, {%4,%5,%6,%5}, {%4,%6}, {%0,%1,%2,%3};"
        : "+f"(c[0]), "+f"(c[1]), "+f"(c[2]), "+f"(c[3]) : "r"(p), "r"(0x3f803f80u), "r"(q));
}
__device__ __forceinline__ void stat_store(const float (&c)[4], uint32_t dst, int lane) {
    const int g = lane >> 2, t = lane & 3;
    if (t == (g >> 1)) sts32f(dst + g * 4, (g & 1) ? c[1] : c[0]);
    if (g == 7) sts32f(dst + 32 + t * 4, c[2] + c[3]);
}
__device__ __forceinline__ float sum4(float4 v) { return (v.x + v.y) + (v.z + v.w); }
__device__ __forceinline__ void stat_publish(uint32_t src, float* acc, int lane, bool real) {
    const uint32_t a = src + (lane & 15) * 48;
    float q = sum4(lds128f(a)) + sum4(lds128f(a + 16)), sm = sum4(lds128f(a + 32));
    q += __shfl_xor_sync(0xffffffffu, q, 1); sm += __shfl_xor_sync(0xffffffffu, sm, 1);
    q += __shfl_xor_sync(0xffffffffu, q, 2); sm += __shfl_xor_sync(0xffffffffu, sm, 2);
    if (real && (lane & 19) == 0) red_add4(acc + lane, 1.f, sm, q, 1.f);
}
__device__ __forceinline__ void fence_acc(float (&d)[64]) {
#pragma unroll
    for (int i = 0; i < 64; i++) asm volatile("" : "+f"(d[i])::"memory");
}
__device__ __forceinline__ void ld_unit(uint32_t (&u)[4], const uint4* p) {
    asm volatile("ld.relaxed.gpu.global.v4.u32 {%0,%1,%2,%3}, [%4];" : "=r"(u[0]), "=r"(u[1]), "=r"(u[2]), "=r"(u[3]) : "l"(p) : "memory");
}

__device__ __forceinline__ void st_async(uint32_t dst, uint32_t a, uint32_t b, uint32_t c, uint32_t d, uint32_t bar) {
    asm volatile("st.async.shared::cluster.mbarrier::complete_tx::bytes.v4.b32 [%0], {%1,%2,%3,%4}, [%5];"
                 ::"r"(dst), "r"(a), "r"(b), "r"(c), "r"(d), "r"(bar) : "memory");
}
template <int J>
__device__ __forceinline__ void send_m(const uint32_t (&hp)[32], int tid, uint32_t peer0) {
    st_async(peer0 + SM_M + J * 2048 + tid * 16, hp[4 * J], hp[4 * J + 1], hp[4 * J + 2], hp[4 * J + 3], peer0 + BAR(BAR_M));
}
template <int J>
__device__ __forceinline__ void pack_m(uint32_t (&hp)[32], const float (&d)[64]) {
#pragma unroll
    for (int i = 8 * J; i < 8 * J + 8; i++) { hp[i] = pack_bf(d[2 * i], d[2 * i + 1]); asm volatile("" : "+r"(hp[i])); }
}
template <int S>
__device__ __forceinline__ void mma_stages(float (&d)[64], float (&e)[64], uint32_t (&hp)[32], int conv, int tid, uint32_t peer0, Scratch* gs) {
    constexpr uint32_t A = ((SM_V + S * KC_BYTES + 16) >> 4) | ((CH_PITCH >> 4) << 16);
    constexpr uint32_t B = ((SM_W + (S % NS) * STAGE_BYTES) >> 4) | (8u << 16);
    if (S == 0) mbar_wait(BAR(BAR_FULL), conv);
    constexpr uint32_t NEXT = S + 1 < NSTAGE ? BAR(BAR_FULL + S + 1) : BAR(BAR_EMB);
    const int npar = S + 1 < NSTAGE ? conv : 0;
    const bool next_ok = mbar_test(NEXT, npar);
    if ((S & 7) == 0 && tid == 0) TL(32 + conv * 16 + S);
    asm volatile("wgmma.fence.sync.aligned;" ::: "memory");
    wgmma128<A, B>(S < 8 ? d : e);
    if constexpr (S == 9) { pack_m<1>(hp, d); pack_m<2>(hp, d); }
    if constexpr (S >= 9 && S < 12) send_m<(S - 9) * 2 + 2>(hp, tid, peer0);
    wgmma128<A + 1, B + 16>(S < 8 ? d : e);
    if constexpr (S == 9) pack_m<3>(hp, d);
    if constexpr (S >= 9 && S < 12) send_m<(S - 9) * 2 + 3>(hp, tid, peer0);
    wgmma128<A + 2, B + 32>(S < 8 ? d : e);
    asm volatile("wgmma.commit_group.sync.aligned;" ::: "memory");
    if (S > 0) {
        asm volatile("wgmma.wait_group.sync.aligned 1;" ::: "memory");
        if ((tid & 31) == 0) mbar_arrive(BAR(BAR_WEMPTY + (S - 1) % NS));
    }
    if constexpr (S == 8) { fence_acc(d); pack_m<0>(hp, d); send_m<0>(hp, tid, peer0); send_m<1>(hp, tid, peer0); }
    if (!next_ok) mbar_wait(NEXT, npar);
    if constexpr (S + 1 < NSTAGE) mma_stages<S + 1>(d, e, hp, conv, tid, peer0, gs);
}

__device__ __forceinline__ int wblk_kc(int cta) { const int i = cta >> 4; return (i & 1) | ((i & 2) << 1) | ((i & 4) >> 1); }
__device__ __forceinline__ int n_to_oc(int n) { return (n & ~31) | ((n & 6) << 2) | ((n >> 2) & 6) | (n & 1); }
__device__ __forceinline__ void weight_load(uint4 (&t)[5], const __nv_bfloat16* w, int cta, int lane, bool perm) {
    const int n = (cta & 15) * 8 + (lane >> 2);
    const char* base = reinterpret_cast<const char*>(w) + (uint32_t)(((perm ? n_to_oc(n) : n) * 8 + wblk_kc(cta)) * 288 + (lane & 3) * 16);
#pragma unroll
    for (int k = 0; k < 5; k++)
        if (k < 4 || !(lane & 2)) t[k] = __ldg(reinterpret_cast<const uint4*>(base + k * 64));
}
__device__ __forceinline__ void st_global64(void* p, uint32_t a, uint32_t b) { asm volatile("st.global.v2.u32 [%0], {%1,%2};" ::"l"(p), "r"(a), "r"(b) : "memory"); }
__device__ __forceinline__ const unsigned char* weight_block(uint32_t bounce, unsigned char* wt, int cta, int lane, int kx) {
    unsigned char* piece = wt + wblk_kc(cta) * STAGE_BYTES + (cta & 15) * 768 + kx * 256;
    uint32_t g[3][4];
#pragma unroll
    for (int i = 0; i < 12; i++)
        asm volatile("ld.shared.u16 %0, [%1];" : "=r"(g[i % 3][i / 3]) : "r"(S0 + bounce + (lane & 7) * 288 + (lane >> 3) * 72 + kx * 2 + i * 6) : "memory");
    float u1[4], u2[4];
#pragma unroll
    for (int c = 0; c < 4; c++) {
        const float t = 0.5f * (bf_lo(g[0][c]) + bf_lo(g[2][c]));
        u1[c] = fmaf(bf_lo(g[1][c]), 0.5f, t); u2[c] = fmaf(bf_lo(g[1][c]), -0.5f, t);
    }
    unsigned char* dst = piece + (lane >> 4) * 128 + (lane & 7) * 16 + ((lane >> 3) & 1) * 8;
    st_global64(dst, pack_bf(u1[0], u1[1]), pack_bf(u1[2], u1[3]));
    st_global64(dst + 8 * STAGE_BYTES, pack_bf(u2[0], u2[1]), pack_bf(u2[2], u2[3]));
    st_global64(dst + 16 * STAGE_BYTES, __byte_perm(g[0][0], g[0][1], 0x5410), __byte_perm(g[0][2], g[0][3], 0x5410));
    st_global64(dst + 24 * STAGE_BYTES, __byte_perm(g[2][0], g[2][1], 0x5410), __byte_perm(g[2][2], g[2][3], 0x5410));
    return piece + (lane >> 3) * 8 * STAGE_BYTES + (lane & 7) * 32;
}
__device__ __forceinline__ void publish(uint32_t bar, int lane) {
    fence_async_smem();
    __syncwarp();
    if (lane == 0) mbar_arrive(bar);
}
__device__ __forceinline__ void lds_piece(uint32_t (&u)[4], uint32_t a) {
    const uint4 q = lds128(a);
    u[0] = q.x; u[1] = q.y; u[2] = q.z; u[3] = q.w;
}
__device__ __noinline__ void side_jobs(const __nv_bfloat16* __restrict__ t_emb, const __nv_bfloat16* __restrict__ w_emb,
                                       const __nv_bfloat16* __restrict__ w2, Scratch* __restrict__ gs, unsigned clk0) {
    const int tid = threadIdx.x, warp = tid >> 5, lane = tid & 31, j = blockIdx.x;
    float tv = 0.f;
    if (lane < 24) tv = __bfloat162float(t_emb[(lane / 12) * E + j * 192 + warp * 12 + lane % 12]);
    if (tid == 0) {
        mbar_init(BAR(0), 1);
        mbar_expect(BAR(0), 192 * C * 2);
        fence_async_smem();
        while (clock32() - clk0 < SDELAY) {}
#pragma unroll
        for (int i = 0; i < 4; i++)
            asm volatile("cp.async.bulk.prefetch.L2.global [%0], 18432;" ::"l"(reinterpret_cast<const char*>(w2) + (j * 4 + i) * 18432) : "memory");
#pragma unroll
        for (int i = 0; i < 4; i++) bulk_g2s(S0 + SM_W + i * 12288, w_emb + (j * 192 + i * 48) * C, 12288, S0 + BAR(0));
    }
    if (j == 0 && tid < 32) gs->acc2[(tid >> 4) * LS + (tid & 15)] = 0.f;
    const float sv = silu_half(0.5f * tv);
    __syncthreads();
    mbar_wait(BAR(0), 0);
    float acc[8] = {0.f, 0.f, 0.f, 0.f, 0.f, 0.f, 0.f, 0.f};
#pragma unroll
    for (int i = 0; i < 12; i++) {
        const float2 wq = lds64f(SM_W + (warp * 12 + i) * 256 + lane * 8);
        const uint32_t wx = __float_as_uint(wq.x), wy = __float_as_uint(wq.y);
#pragma unroll
        for (int bb = 0; bb < 2; bb++) {
            const float sx = __shfl_sync(0xffffffffu, sv, bb * 12 + i);
            acc[4 * bb + 0] = fmaf(sx, bf_lo(wx), acc[4 * bb + 0]); acc[4 * bb + 1] = fmaf(sx, bf_hi(wx), acc[4 * bb + 1]);
            acc[4 * bb + 2] = fmaf(sx, bf_lo(wy), acc[4 * bb + 2]); acc[4 * bb + 3] = fmaf(sx, bf_hi(wy), acc[4 * bb + 3]);
        }
    }
    sts128f(SM_V + warp * 1024 + lane * 16, make_float4(acc[0], acc[1], acc[2], acc[3]));
    sts128f(SM_V + warp * 1024 + 512 + lane * 16, make_float4(acc[4], acc[5], acc[6], acc[7]));
    __syncthreads();
    if (tid < 128) {
        float2 sum = make_float2(0.f, 0.f);
#pragma unroll
        for (int w = 0; w < 16; w++) { const float2 p = lds64f(SM_V + w * 1024 + tid * 8); sum.x += p.x; sum.y += p.y; }
        *reinterpret_cast<float2*>(&gs->emb[j * NB * C + tid * 2]) = sum;
        bar_sync(1, 128);
        if (tid < 2) asm volatile("red.release.gpu.global.add.u32 [%0], 1;" ::"l"(&gs->wcnt[(2 * NB + tid) * LS]) : "memory");
    }
}

__global__ void __cluster_dims__(2, 1, 1) __launch_bounds__(NTHREADS, 1)
resblock_kernel(const __nv_bfloat16* __restrict__ w1, const __nv_bfloat16* __restrict__ x,
                const __nv_bfloat16* __restrict__ t_emb, const __nv_bfloat16* __restrict__ g1,
                const __nv_bfloat16* __restrict__ be1, const __nv_bfloat16* __restrict__ w_emb,
                const __nv_bfloat16* __restrict__ g2, const __nv_bfloat16* __restrict__ be2,
                const __nv_bfloat16* __restrict__ w2, __nv_bfloat16* __restrict__ out, Scratch* __restrict__ gs,
                const __grid_constant__ CUtensorMap xmap) {
    const unsigned clk0 = clock32();
    if (threadIdx.x == 480 && blockIdx.x >= NXTRA) TLG(1);
    const int tid = threadIdx.x, lane = tid & 31;
    const int cta = blockIdx.x - NXTRA, b = cta >> 6, r = cta & 63, rk = cta & 1;
    uint4 v[5];
    if (tid < 32) weight_load(v, w1, cta & (NCTA - 1), lane, true);
    uint4 xv[8];
    const int ch0 = (b & 1) * C + rk * 64;
    if (tid >= 32 && tid < 96) {
        const char* src = reinterpret_cast<const char*>(x) + (uint32_t)(((ch0 + (lane >> 3)) * HW + (r ^ (tid >> 6))) * HW * 2 + (lane & 7) * 16);
        while (clock32() - clk0 < XDELAY + (tid >> 6) * XSTAG2) {}
#pragma unroll
        for (int i = 0; i < 8; i++) xv[i] = __ldg(reinterpret_cast<const uint4*>(src + i * (4 * HW * HW * 2)));
    }
    const int warp = __shfl_sync(0xffffffffu, tid >> 5, 0);
    if (cta < 0) { side_jobs(t_emb, w_emb, w2, gs, clk0); return; }

    if (warp != 4) asm volatile("barrier.cluster.arrive.relaxed.aligned;" ::: "memory");
    const bool has_near = r != 0 && r != HW - 1, has_far = r != 1 && r != HW - 2;
    const uint32_t peer0 = mapa(0, rk ^ 1);
    if (warp == 1 || warp == 2 || warp == 3 || warp == 5) {
        const int i = warp < 4 ? warp - 1 : 3, gl = i >> 1, row = i & 1;
        const uint32_t tile = SM_XA + row * 8192 + gl * 4096;
        if (elect_one()) {
            if (gl) asm volatile("prefetch.tensormap [%0];" ::"l"(&xmap) : "memory");
            mbar_init(BAR(BAR_X) + 8 * i, 1);
            if (gl) { mbar_expect(BAR(BAR_X) + 8 * i, 4096); fence_async_smem(); }
        }
        __syncwarp();
        bar_arrive(4, 256 + 32 + 128);
        if (gl) {
            while (clock32() - clk0 < XDELAY + XSTAG + row * XSTAG2) {}
            if (elect_one()) tma_x(tile, &xmap, r ^ row, ch0 + 32, BAR(BAR_X) + 8 * i);
            __syncwarp();
            mbar_wait(BAR(BAR_X) + 8 * i, 0);
#pragma unroll
            for (int k = 0; k < 8; k++) xv[k] = lds128(tile + k * 512 + lane * 16);
        }
        float c[8][4];
#pragma unroll
        for (int k = 0; k < 8; k++) {
            c[k][0] = c[k][1] = c[k][2] = c[k][3] = 0.f;
            stat_mma(c[k], xv[k].x, xv[k].y); stat_mma(c[k], xv[k].z, xv[k].w);
        }
#pragma unroll
        for (int k = 0; k < 4; k++) c[0][k] = ((c[0][k] + c[1][k]) + (c[2][k] + c[3][k])) + ((c[4][k] + c[5][k]) + (c[6][k] + c[7][k]));
        stat_store(c[0], SM_RED + i * 48, lane);
        __syncwarp();
        if (lane == 0) {
            const uint32_t a = SM_RED + i * 48;
            red_add4(&gs->acc1[b * LS + (rk * 2 + gl) * 4], 1.f, sum4(lds128f(a + 32)), sum4(lds128f(a)) + sum4(lds128f(a + 16)), 1.f);
            TL(74 + i);
        }
        if (!gl) {
#pragma unroll
            for (int k = 0; k < 8; k++)
                sts128(tile + k * 512 + (lane >> 3) * 128 + (((lane & 7) ^ ((lane >> 3) + 4 * (k & 1))) << 4), xv[k]);
            __syncwarp();
            if (lane == 0) mbar_arrive(BAR(BAR_X) + 8 * i);
        }
    }
    if (warp == 4) {
        if (elect_one()) {
#pragma unroll
            for (int i = 0; i < NSTAGE; i++) mbar_init(BAR(BAR_FULL + i), (i & 1) ? 1 : ((i & 2) ? 1 + HOP : 9));
#pragma unroll
            for (int i = 0; i <= NS; i++) mbar_init(BAR(BAR_WEMPTY + i), 4);
#pragma unroll
            for (int i = BAR_STATS; i < BAR_X; i++) mbar_init(BAR(i), i == BAR_EMB ? 2 : 1);
            asm volatile("fence.mbarrier_init.release.cluster;" ::: "memory");
        }
        if (lane < 2) sts128(SM_GST + lane * 16, make_uint4(0, 0, 0, 0));
        __syncwarp();
        if (lane < 6) mbar_expect(BAR(BAR_RV) + 8 * lane, lane < 4 ? 4096 : (lane == 4 ? 16384 : 8192));
        fence_async_smem();
        bar_arrive(0, 96);
        bar_arrive(5, 64);
        bar_arrive(4, 256 + 32 + 128);
        const uint4 z = make_uint4(0, 0, 0, 0);
#pragma unroll
        for (int i = 0; i < 2; i++) sts128(SM_V + (i * 16 + (lane >> 1)) * CH_PITCH + (lane & 1) * 16, z);
        if (lane < 2) sts128(SM_V + NSTAGE * KC_BYTES + lane * 16, z);
        if (lane < 16) sts128(SM_ONES + lane * 16, make_uint4(lane < 8 ? 0x3f803f80u : 0u, 0, 0, 0));
        fence_async_smem();
        bar_arrive(7, 160);
        asm volatile("barrier.cluster.arrive.relaxed.aligned;" ::: "memory");
            if (elect_one()) {
                mbar_expect(BAR(BAR_XO), 16384);
                while (clock32() - clk0 < ODELAY) {}
#pragma unroll
                for (int i = 0; i < 4; i++)
                    tma_x(SM_XB + i * 4096, &xmap, ((i >> 1) ^ rk) ? (r | 1) + 1 : (r & ~1) - 1, ch0 + (i & 1) * 32, BAR(BAR_XO));
            }
            __syncwarp();
        while (clock32() - clk0 < W2DELAY) {}
        weight_load(v, w2, cta, lane, false);
    }
    if (warp == 0 || warp == 4 || warp >= 14) {
        const int k = warp == 4;
        int kx = warp < 8 ? 0 : warp - 13;
        if (kx == 0) {
#pragma unroll
            for (int i = 0; i < 5; i++)
                if (i < 4 || !(lane & 2)) sts128(SM_BNC + k * 2304 + (lane >> 2) * 288 + (lane & 3) * 16 + i * 64, v[i]);
            if (lane == 0) TL(k ? 14 : 81);
        }
        if (k) __syncwarp(); else bar_sync(8, 96);
        const unsigned char* rp;
#pragma unroll 1
        do { rp = weight_block(SM_BNC + k * 2304, gs->wt + k * 32 * STAGE_BYTES, cta, lane, kx); } while (k && ++kx < 3);
        unsigned rb = ld_relaxed(rp);
        if (k) rb |= ld_relaxed(rp - 256) | ld_relaxed(rp - 512);
        asm volatile("{\n.reg .pred p;\nsetp.eq.u32 p, %0, 0x9e3779b9;\n@p st.shared.u32 [%1], %0;\n}" ::"r"(rb), "r"(S0 + SM_RED + 1020) : "memory");
        if (warp >= 8) {
            bar_arrive(9, 96);
        } else {
            if (k) __syncwarp(); else bar_sync(9, 96);
            if (lane < 2) asm volatile("red.relaxed.gpu.global.add.u32 [%0], 1;" ::"l"(k ? &gs->wcnt[(NB + lane) * LS] : &gs->w1cnt[(lane * 8 + wblk_kc(cta)) * KS]) : "memory");
            if (lane == 0) TL(k ? 13 : 4);
        }
    }

    if (warp >= 8) {
        asm volatile("setmaxnreg.dec.sync.aligned.u32 104;");
        const int nw = warp - 8;
        const unsigned one = gridDim.y;
        if (nw < 4) {
            const uint2 q = __ldg(reinterpret_cast<const uint2*>(nw == 0 ? g1 : (nw == 1 ? be1 : (nw == 2 ? g2 : be2))) + lane);
            sts128f(SM_COEF + nw * 512 + lane * 16, make_float4(0.5f * bf_lo(q.x), 0.5f * bf_hi(q.x), 0.5f * bf_lo(q.y), 0.5f * bf_hi(q.y)));
        }
        bar_sync(4, 256 + 32 + 128);
        asm volatile("barrier.cluster.wait.acquire.aligned;" ::: "memory");
        const int hf = nw >> 2, wq = nw & 3;
        const uint32_t v_off = SM_V + (lane & 3) * CH_PITCH + (2 + wq * 16 + hf * 8 + (lane >> 2)) * 16;
        const int crow = ((lane & 6) << 2) | ((lane >> 3) << 1) | (lane & 1);
        const uint32_t stg_off = crow * 128 + (((2 * wq + hf) ^ (crow & 7)) << 4);
        const uint32_t img_off = (tid - 256) * 16;
        const float sg = rk ? -1.f : 1.f;
        uint4* inbox = gs->box + cta * 1024 + (tid - 256);
#pragma unroll 1
        for (int conv = 0; conv < 2; conv++) {
            uint32_t u[4][4];
            if (conv == 0) {
#pragma unroll
                for (int i = 0; i < 4; i++) { mbar_wait(BAR(BAR_X + i), 0); ldsm4t(u[i], SM_XA + (i & 1) * 8192 + (i >> 1) * 4096 + stg_off); }
            } else {
                mbar_wait(BAR(BAR_HW), 0);
                mbar_wait(BAR(BAR_RH), 0);
#pragma unroll
                for (int i = 0; i < 4; i++) lds_piece(u[i], SM_XA + (i & 1) * 8192 + (i >> 1) * 4096 + img_off);
            }
            float ga[2][8], be[2][8], a[4][8];
#pragma unroll
            for (int g = 0; g < 2; g++) {
                const uint32_t ca = SM_COEF + conv * 1024 + (rk * 64 + g * 32 + (lane & 3) * 8) * 4;
                const float4 q0 = lds128f(ca), q1 = lds128f(ca + 16), q2 = lds128f(ca + 512), q3 = lds128f(ca + 528);
                ga[g][0] = q0.x; ga[g][1] = q0.y; ga[g][2] = q0.z; ga[g][3] = q0.w; ga[g][4] = q1.x; ga[g][5] = q1.y; ga[g][6] = q1.z; ga[g][7] = q1.w;
                be[g][0] = q2.x; be[g][1] = q2.y; be[g][2] = q2.z; be[g][3] = q2.w; be[g][4] = q3.x; be[g][5] = q3.y; be[g][6] = q3.z; be[g][7] = q3.w;
            }
#pragma unroll
            for (int i = 0; i < 16; i++) {
                a[i >> 2][2 * (i & 3)] = bf_lo(u[i >> 2][i & 3]) * ga[i >> 3][2 * (i & 3)];
                a[i >> 2][2 * (i & 3) + 1] = bf_hi(u[i >> 2][i & 3]) * ga[i >> 3][2 * (i & 3) + 1];
                asm volatile("" : "+f"(a[i >> 2][2 * (i & 3)]), "+f"(a[i >> 2][2 * (i & 3) + 1]));
            }
            float4 gv = make_float4(0.f, 0.f, 0.f, 0.f);
            if (conv == 0) {
                mbar_wait(BAR(BAR_XO), 0);
#pragma unroll
                for (int i = 0; i < 4; i++) ldsm4t(u[i], SM_XB + (i & 1) * 8192 + (i >> 1) * 4096 + stg_off);
            }
#pragma unroll
            for (int g = 0; g < 2; g++) {
                unsigned it = 0;
#pragma unroll 1
                while (!__all_sync(0xffffffffu, (g ? gv.z : gv.x) != 0.f) && ++it < 8 * SPIN_LIMIT)
                    asm volatile("ld.volatile.shared.v4.f32 {%0,%1,%2,%3}, [%4];" : "=f"(gv.x), "=f"(gv.y), "=f"(gv.z), "=f"(gv.w) : "r"(S0 + SM_GST + conv * 16) : "memory");
                if (g == 0 && tid == 256) TL(22 + conv * 4);
                const float rs = g ? gv.z : gv.x, mr = g ? gv.w : gv.y;
                uint32_t kp[4], sd[4];
#pragma unroll
                for (int i = 0; i < 8; i++) {
                    be[g][i] = fmaf(-mr, ga[g][i], be[g][i]);
                    a[2 * g][i] = silu_half(fmaf(a[2 * g][i], rs, be[g][i])); a[2 * g + 1][i] = silu_half(fmaf(a[2 * g + 1][i], rs, be[g][i]));
                }
#pragma unroll
                for (int i = 0; i < 4; i++) {
                    kp[i] = pack_bf(fmaf(a[2 * g][2 * i], sg, a[2 * g + 1][2 * i]), fmaf(a[2 * g][2 * i + 1], sg, a[2 * g + 1][2 * i + 1]));
                    sd[i] = pack_bf(fmaf(a[2 * g + 1][2 * i], -sg, a[2 * g][2 * i]), fmaf(a[2 * g + 1][2 * i + 1], -sg, a[2 * g][2 * i + 1]));
                }
                sts128(v_off + g * 4 * KC_BYTES, make_uint4(kp[0], kp[1], kp[2], kp[3]));
                if (!SAFTER) st_async(peer0 + v_off + (g * 4 + 2) * KC_BYTES, sd[0], sd[1], sd[2], sd[3], peer0 + (HOP ? BAR(BAR_RV + g) : BAR(BAR_FULL + 4 * g + 2)));
                fence_async_smem();
                if (SAFTER) st_async(peer0 + v_off + (g * 4 + 2) * KC_BYTES, sd[0], sd[1], sd[2], sd[3], peer0 + (HOP ? BAR(BAR_RV + g) : BAR(BAR_FULL + 4 * g + 2)));
                __syncwarp();
                if (lane == 0) mbar_arrive(BAR(BAR_FULL + 4 * g));
                if (tid == 256) TL(g ? 84 + conv : 8 + conv * 8);
                if (g == LDAT && conv == 1) {
#pragma unroll
                    for (int i = 0; i < 4; i++) ld_unit(u[i], inbox + (i & 1) * 512 + (i >> 1) * 256);
                }
            }
            if (conv == 1) {
                unsigned it = 0;
                while (true) {
                    bool okn = true, okf = true;
#pragma unroll
                    for (int i = 0; i < 8; i++) { okn = okn && u[(i >> 2) * 2][i & 3] != 0; okf = okf && u[(i >> 2) * 2 + 1][i & 3] != 0; }
                    if (__all_sync(0xffffffffu, (okn || !has_near) && (okf || !has_far)) || ++it > SPIN_LIMIT) break;
#pragma unroll
                    for (int i = 0; i < 4; i++) ld_unit(u[i], inbox + (i & 1) * 512 + (i >> 1) * 256);
                    if (tid == 256) TL(93);
                }
            }
            if (tid == 256) TL(24 + conv * 4);
#pragma unroll
            for (int g = 0; g < 2; g++) {
                const float rs = g ? gv.z : gv.x;
                uint32_t o[2][4];
#pragma unroll
                for (int f = 0; f < 2; f++) {
                    const bool ok = f ? has_far : has_near;
#pragma unroll
                    for (int i = 0; i < 4; i++) {
                        const float lo = silu_half(fmaf(bf_lo(u[2 * g + f][i]), ga[g][2 * i] * rs, be[g][2 * i]));
                        const float hi = silu_half(fmaf(bf_hi(u[2 * g + f][i]), ga[g][2 * i + 1] * rs, be[g][2 * i + 1]));
                        o[f][i] = pack_bf((ok ? lo : 0.f) - a[2 * g + (f ^ 1)][2 * i], (ok ? hi : 0.f) - a[2 * g + (f ^ 1)][2 * i + 1]);
                    }
                }
                sts128(v_off + (8 + g * 4) * KC_BYTES, make_uint4(o[0][0], o[0][1], o[0][2], o[0][3]));
                if (!SAFTER) st_async(peer0 + v_off + (10 + g * 4) * KC_BYTES, o[1][0], o[1][1], o[1][2], o[1][3], peer0 + (HOP ? BAR(BAR_RV + 2 + g) : BAR(BAR_FULL + 10 + 4 * g)));
                fence_async_smem();
                if (SAFTER) st_async(peer0 + v_off + (10 + g * 4) * KC_BYTES, o[1][0], o[1][1], o[1][2], o[1][3], peer0 + (HOP ? BAR(BAR_RV + 2 + g) : BAR(BAR_FULL + 10 + 4 * g)));
                __syncwarp();
                if (lane == 0) mbar_arrive(BAR(BAR_FULL + 8 + 4 * g));
                if (tid == 256) TL(g ? 88 + conv : 23 + conv * 4);
                if (one == 0) break;
            }
        }
        mbar_wait(BAR(BAR_FULL + NSTAGE - 1), 1);
#pragma unroll
        for (int i = 0; i < 4; i++) inbox[i * 256] = make_uint4(0, 0, 0, 0);
        {
            const int oc0 = hf * 64 + ((tid & 127) >> 3), seg = lane & 7;
            __nv_bfloat16* dst = out + ((size_t)(b * C + oc0) * HW + r) * HW + seg * 8;
            const uint32_t src = oc0 * 128 + ((seg ^ (oc0 & 7)) << 4);
            mbar_wait(BAR(BAR_XR), 0);
            uint4 xr[4];
#pragma unroll
            for (int i = 0; i < 4; i++) xr[i] = lds128(SM_XA + src + i * 2048);
            asm volatile("{\n.reg .pred p;\nsetp.eq.u64 p, %0, 0;\n@p st.shared.u32 [%1], 0;\n}" ::"l"(dst), "r"(src + S0) : "memory");
            bar_sync(hf ? 1 : 6, 128 + 128);
#pragma unroll
            for (int i = 0; i < 4; i++) {
                uint4 o = lds128(SM_OUT + src + i * 2048);
                asm("add.rn.bf16x2 %0, %0, %1;" : "+r"(o.x) : "r"(xr[i].x)); asm("add.rn.bf16x2 %0, %0, %1;" : "+r"(o.y) : "r"(xr[i].y));
                asm("add.rn.bf16x2 %0, %0, %1;" : "+r"(o.z) : "r"(xr[i].z)); asm("add.rn.bf16x2 %0, %0, %1;" : "+r"(o.w) : "r"(xr[i].w));
                *reinterpret_cast<uint4*>(dst + (size_t)i * 16 * HW * HW) = o;
            }
            if (tid == 384) { TL(20); TLG(21); }
        }
    } else if (warp < 4) {
        const int wq = warp;
        asm volatile("setmaxnreg.inc.sync.aligned.u32 176;");
        bar_sync(7, 160);
        asm volatile("barrier.cluster.wait.acquire.aligned;" ::: "memory");
        const float sg = rk ? 1.f : -1.f;
        float d[64], e[64];
#pragma unroll 1
        for (int conv = 0; conv < 2; conv++) {
#pragma unroll
            for (int i = 0; i < 64; i++) { d[i] = 0.f; e[i] = 0.f; }
            fence_acc(d); fence_acc(e);
            uint32_t hp[32];
            mma_stages<0>(d, e, hp, conv, tid, peer0, gs);
            if (conv == 0) {
                asm volatile("wgmma.fence.sync.aligned;" ::: "memory");
                wgmma128<(SM_ONES >> 4) | (8u << 16), (SM_EMB >> 4), 0, 8>(e);
                asm volatile("wgmma.commit_group.sync.aligned;" ::: "memory");
            }
            mbar_wait(BAR(BAR_M), conv);
#pragma unroll
            for (int j = 0; j < 8; j++) {
                uint32_t q[4];
                lds_piece(q, SM_M + j * 2048 + tid * 16);
#pragma unroll
                for (int i = 0; i < 4; i++) { d[8 * j + 2 * i] = fmaf(bf_lo(q[i]), sg, d[8 * j + 2 * i]); d[8 * j + 2 * i + 1] = fmaf(bf_hi(q[i]), sg, d[8 * j + 2 * i + 1]); }
            }
            fence_acc(d);
            asm volatile("wgmma.wait_group.sync.aligned 0;" ::: "memory");
            fence_acc(e);
            if (tid == 0) TL(10 + conv * 8);
#pragma unroll
            for (int i = 0; i < 32; i++) hp[i] = pack_bf(d[2 * i] + e[2 * i], d[2 * i + 1] + e[2 * i + 1]);
            if (conv == 1) {
                const uint32_t obase = SM_OUT + ((lane >> 4) * 8 + (lane & 7)) * 128 + (((2 * wq + ((lane >> 3) & 1)) ^ (lane & 7)) << 4);
#pragma unroll
                for (int kc = 0; kc < 8; kc++) {
                    stsm4t(obase + kc * 2048, hp[4 * kc], hp[4 * kc + 1], hp[4 * kc + 2], hp[4 * kc + 3]);
                    if (kc == 3) bar_arrive(6, 128 + 128);
                }
                bar_arrive(1, 128 + 128);
                break;
            }
#pragma unroll
            for (int g = 0; g < 4; g++) {
                float c[4] = {0.f, 0.f, 0.f, 0.f};
#pragma unroll
                for (int i = 0; i < 4; i++) stat_mma(c, hp[8 * g + 2 * i], hp[8 * g + 2 * i + 1]);
                stat_store(c, SM_RED + (g * 4 + wq) * 48, lane);
            }
            bar_sync(2, 128);
            if (wq == 0) stat_publish(SM_RED, &gs->acc2[b * LS], lane, true);
            if (tid == 0) TL(11);
            if (tid == 32) mbar_expect(BAR(BAR_M), 16384);
#pragma unroll
            for (int j = 0; j < 8; j++) {
                const uint32_t p0 = hp[(j >> 1) * 8 + (j & 1)], p1 = hp[(j >> 1) * 8 + (j & 1) + 2], p2 = hp[(j >> 1) * 8 + (j & 1) + 4], p3 = hp[(j >> 1) * 8 + (j & 1) + 6];
                if ((j >> 2) == rk) sts128(SM_XA + (j & 3) * 2048 + tid * 16, make_uint4(p0, p1, p2, p3));
                else st_async(peer0 + SM_XA + 8192 + (j & 3) * 2048 + tid * 16, p0, p1, p2, p3, peer0 + BAR(BAR_RH));
            }
            __syncwarp();
            if (lane == 0) { mbar_arrive(BAR(BAR_HW)); mbar_arrive(BAR(BAR_WEMPTY + (NSTAGE - 1) % NS)); }
            if (has_near) {
                const int oc2 = (cta & ~1) + (rk ? 2 : -2);
#pragma unroll
                for (int j = 0; j < 8; j++) {
                    uint4* outbox = gs->box + (oc2 + (j >> 2)) * 1024 + (((j >> 2) == rk) ? 512 : 0) + (j & 3) * 128 + tid;
                    *outbox = make_uint4(max(hp[(j >> 1) * 8 + (j & 1)], 1u), max(hp[(j >> 1) * 8 + (j & 1) + 2], 1u),
                                         max(hp[(j >> 1) * 8 + (j & 1) + 4], 1u), max(hp[(j >> 1) * 8 + (j & 1) + 6], 1u));
                }
            }
            if (tid == 0) TL(12);
        }
    } else {
    if (warp < 6) {
        if (warp == 5) {
            bar_sync(5, 64);
#pragma unroll 1
            for (int i = 0; i < 8 * HOP; i++) {
                mbar_wait(BAR(BAR_RV) + 8 * (i & 3), i >> 2);
                fence_async_smem();
                if (lane == 0) {
                    mbar_arrive(BAR(BAR_FULL + 2) + 32 * (i & 3));
                    if (i < 4) mbar_expect(BAR(BAR_RV) + 8 * i, 4096);
                    TL(64 + i);
                }
                __syncwarp();
            }
        } else {
            mbar_wait(BAR(BAR_STATS), 0);
            unsigned it = 0;
            while (!__all_sync(0xffffffffu, ld_relaxed(&gs->wcnt[(2 * NB + b) * LS]) >= (unsigned)NXTRA) && ++it < SPIN_LIMIT) __nanosleep(100);
            fence_acquire();
            float ev[4] = {0.f, 0.f, 0.f, 0.f};
#pragma unroll
            for (int j = 0; j < NXTRA; j++) {
                const uint4 ef = ld_relaxed_v4(&gs->emb[(j * NB + b) * C + lane * 4]);
                ev[0] += __uint_as_float(ef.x); ev[1] += __uint_as_float(ef.y); ev[2] += __uint_as_float(ef.z); ev[3] += __uint_as_float(ef.w);
            }
#pragma unroll
            for (int i = 0; i < 4; i++) {
                const float hi = bf_lo(pack_bf(ev[i], 0.f));
                sts128(SM_EMB + n_to_oc(lane * 4 + i) * 16, make_uint4(pack_bf(hi, ev[i] - hi), 0, 0, 0));
            }
            fence_async_smem();
            __syncwarp();
            if (lane == 0) { mbar_arrive(BAR(BAR_EMB)); TL(19); }
            mbar_wait(BAR(BAR_HW), 0);
            mbar_wait(BAR(BAR_FULL + 8), 1);
            if (elect_one()) {
                mbar_expect(BAR(BAR_XR), 16384);
#pragma unroll
                for (int i = 0; i < 4; i++) tma_x(SM_XA + i * 4096, &xmap, r, b * C + i * 32, BAR(BAR_XR));
            }
        }
    } else if (warp == 6) {
        bar_sync(0, 96);
        if (lane < NSTAGE) mbar_expect(BAR(BAR_FULL) + 8 * lane, STAGE_BYTES + (!HOP && (lane & 3) == 2 ? 4096 : 0));
        const unsigned char* wbase = gs->wt + rk * 8 * STAGE_BYTES;
        unsigned it = 0;
        {
            int g = 0;
            const int l7 = lane & 7;
            const unsigned* cnt = &gs->w1cnt[(b * 8 + ((((l7 >> 1) ^ rk) & 1) * 4 + (l7 >> 2) * 2 + (l7 & 1))) * KS];
            unsigned cv = ld_relaxed(cnt);
#pragma unroll 1
            while (g < NS) {
                unsigned ready = __ballot_sync(0xffffffffu, cv >= 16u);
                if (ready != ~0u) cv = ld_relaxed(cnt);
                ready >>= g;
                if (++it > SPIN_LIMIT) ready = ~0u;
                if (!(ready & 1)) continue;
                fence_async_global();
                if (lane == 0) TL(g ? 3 : 6);
#pragma unroll 1
                for (; (ready & 1) && g < NS; g++, ready >>= 1)
                    if (elect_one())
                        bulk_g2s(S0 + SM_W + g * STAGE_BYTES, wbase + ((g >> 3) * 16 + (((g >> 1) ^ rk) & 1) * 4 + (g >> 2 & 1) * 2 + (g & 1)) * STAGE_BYTES, STAGE_BYTES,
                                 S0 + BAR(BAR_FULL) + 8 * g);
            }
        }
#pragma unroll 1
        for (int n = 0; n < 5; n++) {
            const int q = (0x74653 >> (4 * n)) & 7, sl = (q & 3) == 3 ? 0 : (q & 3);
            const unsigned char* wsrc = wbase + ((q >> 1) * 16 + (q & 1) * 2) * STAGE_BYTES;
            const uint32_t par = q == 4;
            if (n == 1) {
                it = 0;
                while (!__all_sync(0xffffffffu, ld_relaxed(&gs->wcnt[(NB + b) * LS]) == (unsigned)NCTA) && ++it < SPIN_LIMIT) {}
                fence_acquire();
                fence_async_global();
                if (lane == 0) { mbar_arrive(BAR(BAR_EMB)); TL(2); }
            }
#pragma unroll
            for (int i = 0; i < 4; i++) {
                mbar_wait(BAR(BAR_WEMPTY + i) + 32 * sl, par);
                if (elect_one()) {
                    if (n) mbar_expect(BAR(BAR_FULL + i) + 32 * (q & 3), STAGE_BYTES + (!HOP && i == 2 ? 4096 : 0));
                    bulk_g2s(S0 + SM_W + (sl * 4 + i) * STAGE_BYTES, wsrc + ((((i >> 1) ^ rk) & 1) * 4 + (i & 1)) * STAGE_BYTES, STAGE_BYTES,
                             S0 + BAR(BAR_FULL + i) + 32 * (q & 3));
                }
            }
        }
    } else {
        bar_sync(0, 96);
#pragma unroll 1
        for (int conv = 0; conv < 2; conv++) {
            if (conv == 1) mbar_wait(BAR(BAR_HW), 0);
            const float* asrc = (conv ? gs->acc2 : gs->acc1) + b * LS + (rk * 2 + (lane & 1)) * 4;
            unsigned it = 0;
#pragma unroll 1
            while (true) {
                const uint4 f = ld_relaxed_v4(asrc);
                const bool ok = ((f.x == 0x42800000u) & (f.w == 0x42800000u)) || ++it > SPIN_LIMIT;
                if (ok && lane < 2) {
                    const float inv_n = 1.0f / (32.0f * HW * HW);
                    const float mean = __uint_as_float(f.y) * inv_n;
                    float rs;
                    asm("rsqrt.approx.ftz.f32 %0, %1;" : "=f"(rs) : "f"(fmaxf(fmaf(-mean, mean, __uint_as_float(f.z) * inv_n), 0.f) + 1e-5f));
                    asm volatile("st.shared.v2.f32 [%0], {%1,%2};" ::"r"(S0 + SM_GST + conv * 16 + lane * 8), "f"(rs == 0.f ? 1.2e-38f : rs), "f"(mean * rs) : "memory");
                }
                if (__all_sync(0xffffffffu, ok)) break;
            }
            if (lane == 0) { mbar_arrive(BAR(BAR_STATS)); TL(7 + conv * 8); }
        }
        if (r == 0) {
            if (lane < 16) gs->acc1[b * LS + lane] = 0.f;
            if (lane < 3) gs->wcnt[(lane * NB + b) * LS] = 0;
            if (lane < 8) gs->w1cnt[(b * 8 + lane) * KS] = 0;
        }
    }
    }
}

}

extern "C" void kernel_launch(void* const* d_in, const int* in_sizes, int n_in, void* d_out, int out_size) {
    (void)in_sizes; (void)n_in; (void)out_size;
    typedef CUresult (*EncodeFn)(CUtensorMap*, CUtensorMapDataType, cuuint32_t, void*, const cuuint64_t*, const cuuint64_t*,
                                 const cuuint32_t*, const cuuint32_t*, CUtensorMapInterleave, CUtensorMapSwizzle,
                                 CUtensorMapL2promotion, CUtensorMapFloatOOBfill);
    static Scratch* gs = nullptr;
    static EncodeFn encode = nullptr;
    if (!gs) {
        cudaFuncSetAttribute(resblock_kernel, cudaFuncAttributeMaxDynamicSharedMemorySize, SM_TOTAL);
        cudaGetSymbolAddress((void**)&gs, g_scratch);
        cudaDriverEntryPointQueryResult qr;
        cudaGetDriverEntryPoint("cuTensorMapEncodeTiled", (void**)&encode, cudaEnableDefault, &qr);
    }
    CUtensorMap xmap;
    const cuuint64_t dims[3] = {HW, HW, NB * C}, strides[2] = {HW * 2, HW * HW * 2};
    const cuuint32_t box[3] = {HW, 1, 32}, es[3] = {1, 1, 1};
    encode(&xmap, CU_TENSOR_MAP_DATA_TYPE_BFLOAT16, 3, d_in[0], dims, strides, box, es, CU_TENSOR_MAP_INTERLEAVE_NONE,
           CU_TENSOR_MAP_SWIZZLE_128B, CU_TENSOR_MAP_L2_PROMOTION_NONE, CU_TENSOR_MAP_FLOAT_OOB_FILL_NONE);
    resblock_kernel<<<NCTA + NXTRA, NTHREADS, SM_TOTAL>>>(
        (const __nv_bfloat16*)d_in[4], (const __nv_bfloat16*)d_in[0], (const __nv_bfloat16*)d_in[1],
        (const __nv_bfloat16*)d_in[2], (const __nv_bfloat16*)d_in[3], (const __nv_bfloat16*)d_in[5],
        (const __nv_bfloat16*)d_in[6], (const __nv_bfloat16*)d_in[7], (const __nv_bfloat16*)d_in[8],
        (__nv_bfloat16*)d_out, gs, xmap);
}
```

```cpp
#include <cuda_runtime.h>
#include <cuda.h>
#include <cuda_bf16.h>
#include <stdint.h>

namespace {

constexpr int C = 128, HW = 64, NB = 2, E = 768;
constexpr int NCTA = NB * HW;
constexpr int NXTRA = 4;
constexpr int NTHREADS = 16 * 32;
constexpr int CH_PITCH = 66 * 16;
constexpr int ROW_BYTES = 16 * CH_PITCH;
constexpr int STAGE_BYTES = 12288;
constexpr int NSTAGE = 24;
constexpr int KC_BYTES = 2 * CH_PITCH;
constexpr int NS = 12;
constexpr int LAG = 1;
#define XDELAY 300
#define XSTAG 800
#define XSTAG2 300
#define SDELAY 600
#define W2DELAY 2400
#define PDELAY 60
#define NB0 1
constexpr int NLDG = 2;

constexpr uint32_t SMEM_BASE = 0x400;
constexpr uint32_t SM_XOWN = SMEM_BASE;
constexpr uint32_t SM_ACT = SM_XOWN + 16384 + 512;
constexpr uint32_t SM_XOUT = SM_ACT + 2 * ROW_BYTES + 512;
static_assert(SM_XOUT % 1024 == 0, "swizzle atom alignment");
constexpr uint32_t SM_W = SM_ACT + 3 * ROW_BYTES + 128;
__host__ __device__ constexpr uint32_t slot_addr(int slot) { return SM_W + slot * STAGE_BYTES; }
constexpr uint32_t SM_COEF = SM_W + NS * STAGE_BYTES;
constexpr uint32_t SM_GST = SM_COEF + 2048;
constexpr uint32_t SM_EMB = SM_GST + 128;
constexpr uint32_t SM_ONES = SM_EMB + 2048;
constexpr uint32_t SM_RED = SM_ONES + 256;
constexpr uint32_t SM_BNC = SM_RED + 1536;
constexpr uint32_t SM_BAR = SM_BNC + 2 * 2304;
constexpr int BAR_FULL = 0, BAR_WEMPTY = NSTAGE, BAR_HW = BAR_WEMPTY + NS, BAR_XFREE = BAR_HW + 1, BAR_STATS = BAR_XFREE + 1,
              BAR_EMB = BAR_STATS + 1, BAR_ACK = BAR_EMB + 1, BAR_W0 = BAR_ACK + 1, BAR_X = BAR_W0 + 1  , NBAR = BAR_X + 5;
constexpr int SM_TOTAL = SM_BAR + NBAR * 8 - SMEM_BASE;
static_assert(SM_TOTAL <= 232448, "smem");
__host__ __device__ constexpr uint32_t BAR(int i) { return SM_BAR + 8 * i; }
__host__ __device__ constexpr int ky_of(int kyo) { return kyo == 0 ? 1 : (kyo == 1 ? 0 : 2); }

constexpr unsigned SPIN_LIMIT = 1u << 16;

constexpr int LS = 1056, KS = 32;
struct Scratch {
    float acc1[NB * LS];
    float acc2[NB * LS];
    unsigned wcnt[3 * NB * LS];
    unsigned w1cnt[NB * 8 * KS];
    float emb[NXTRA * NB * C];
    alignas(1024) unsigned char wt[2 * NSTAGE * STAGE_BYTES];
    uint4 box[NCTA * 1024];
};
__device__ __align__(1024) Scratch g_scratch;
#define TL(i) do {} while (0)
#define TLG(i) do {} while (0)

__device__ __forceinline__ unsigned clock32() { unsigned c; asm volatile("mov.u32 %0, %%clock;" : "=r"(c)); return c; }
__device__ __forceinline__ uint32_t mapa(uint32_t a, uint32_t rank) {
    uint32_t d;
    asm("mapa.shared::cluster.u32 %0, %1, %2;" : "=r"(d) : "r"(a), "r"(rank));
    return d;
}
#define S0 mapa(0, blockIdx.x & 1)
__device__ __forceinline__ void mbar_init(uint32_t bar, int cnt) {
    asm volatile("mbarrier.init.shared::cta.b64 [%0], %1;" ::"r"(bar + S0), "r"(cnt) : "memory");
}
__device__ __forceinline__ void mbar_arrive(uint32_t bar) {
    asm volatile("mbarrier.arrive.shared::cta.b64 _, [%0];" ::"r"(bar + S0) : "memory");
}
__device__ __forceinline__ void mbar_expect(uint32_t bar, uint32_t bytes) {
    asm volatile("mbarrier.arrive.expect_tx.shared::cta.b64 _, [%0], %1;" ::"r"(bar + S0), "r"(bytes) : "memory");
}
__device__ __forceinline__ bool mbar_try(uint32_t bar, uint32_t par) {
    uint32_t ok;
    asm volatile("{\n.reg .pred p;\nmbarrier.try_wait.parity.shared::cta.b64 p, [%1], %2;\nselp.u32 %0, 1, 0, p;\n}"
                 : "=r"(ok) : "r"(bar + S0), "r"(par) : "memory");
    return ok;
}
__device__ __forceinline__ bool mbar_test(uint32_t bar, uint32_t par) {
    uint32_t ok;
    asm volatile("{\n.reg .pred p;\nmbarrier.test_wait.parity.shared::cta.b64 p, [%1], %2;\nselp.u32 %0, 1, 0, p;\n}"
                 : "=r"(ok) : "r"(bar + S0), "r"(par) : "memory");
    return ok;
}
__device__ __forceinline__ void mbar_wait(uint32_t bar, uint32_t par) {
    unsigned it = 0;
#pragma unroll 1
    while (!mbar_try(bar, par) && ++it < SPIN_LIMIT) {}
}
__device__ __forceinline__ bool elect_one() {
    uint32_t p;
    asm volatile("{\n.reg .pred p;\nelect.sync _|p, 0xffffffff;\nselp.u32 %0, 1, 0, p;\n}" : "=r"(p));
    return p;
}
__device__ __forceinline__ void fence_async_smem() { asm volatile("fence.proxy.async.shared::cta;" ::: "memory"); }
__device__ __forceinline__ void fence_async_global() { asm volatile("fence.proxy.async.global;" ::: "memory"); }
__device__ __forceinline__ void fence_acquire() { asm volatile("fence.acquire.gpu;" ::: "memory"); }
__device__ __forceinline__ void bar_sync(int id, int n) { asm volatile("bar.sync %0, %1;" ::"r"(id), "r"(n) : "memory"); }
__device__ __forceinline__ void bar_arrive(int id, int n) { asm volatile("bar.arrive %0, %1;" ::"r"(id), "r"(n) : "memory"); }
__device__ __forceinline__ void bulk_g2s(uint32_t dst, const void* src, uint32_t bytes, uint32_t bar) {
    asm volatile("cp.async.bulk.shared::cluster.global.mbarrier::complete_tx::bytes [%0], [%1], %2, [%3];"
                 ::"r"(dst), "l"(src), "r"(bytes), "r"(bar) : "memory");
}
__device__ __forceinline__ void tma_x(uint32_t dst, const CUtensorMap* tm, int row, int ch, uint32_t bar) {
    asm volatile("cp.async.bulk.tensor.3d.shared::cluster.global.mbarrier::complete_tx::bytes [%0], [%1, {%2, %3, %4}], [%5];"
                 ::"r"(dst + S0), "l"(tm), "r"(0), "r"(row), "r"(ch), "r"(bar + S0) : "memory");
}
__device__ __forceinline__ uint4 ld_relaxed_v4(const void* p) {
    uint4 v;
    asm volatile("ld.relaxed.gpu.global.v4.u32 {%0,%1,%2,%3}, [%4];" : "=r"(v.x), "=r"(v.y), "=r"(v.z), "=r"(v.w) : "l"(p) : "memory");
    return v;
}
__device__ __forceinline__ unsigned ld_relaxed(const void* p) {
    unsigned v;
    asm volatile("ld.relaxed.gpu.global.u32 %0, [%1];" : "=r"(v) : "l"(p) : "memory");
    return v;
}
__device__ __forceinline__ void red_add4(float* p, float a, float b, float c, float d) {
    asm volatile("red.relaxed.gpu.global.add.v4.f32 [%0], {%1,%2,%3,%4};" ::"l"(p), "f"(a), "f"(b), "f"(c), "f"(d) : "memory");
}
__device__ __forceinline__ void sts128(uint32_t a, uint4 v) {
    asm volatile("st.shared.v4.u32 [%0], {%1,%2,%3,%4};" ::"r"(a + S0), "r"(v.x), "r"(v.y), "r"(v.z), "r"(v.w) : "memory");
}
__device__ __forceinline__ void sts128f(uint32_t a, float4 v) {
    asm volatile("st.shared.v4.f32 [%0], {%1,%2,%3,%4};" ::"r"(a + S0), "f"(v.x), "f"(v.y), "f"(v.z), "f"(v.w) : "memory");
}
__device__ __forceinline__ void sts32f(uint32_t a, float v) { asm volatile("st.shared.f32 [%0], %1;" ::"r"(a + S0), "f"(v) : "memory"); }
__device__ __forceinline__ uint4 lds128(uint32_t a) {
    uint4 v;
    asm volatile("ld.shared.v4.u32 {%0,%1,%2,%3}, [%4];" : "=r"(v.x), "=r"(v.y), "=r"(v.z), "=r"(v.w) : "r"(a + S0) : "memory");
    return v;
}
__device__ __forceinline__ float4 lds128f(uint32_t a) {
    float4 v;
    asm volatile("ld.shared.v4.f32 {%0,%1,%2,%3}, [%4];" : "=f"(v.x), "=f"(v.y), "=f"(v.z), "=f"(v.w) : "r"(a + S0) : "memory");
    return v;
}
__device__ __forceinline__ float2 lds64f(uint32_t a) {
    float2 v;
    asm volatile("ld.shared.v2.f32 {%0,%1}, [%2];" : "=f"(v.x), "=f"(v.y) : "r"(a + S0) : "memory");
    return v;
}
__device__ __forceinline__ float bf_lo(uint32_t u) { return __uint_as_float(u << 16); }
__device__ __forceinline__ float bf_hi(uint32_t u) { return __uint_as_float(u & 0xffff0000u); }
__device__ __forceinline__ uint32_t pack_bf(float lo, float hi) {
    uint32_t r;
    asm("cvt.rn.bf16x2.f32 %0, %1, %2;" : "=r"(r) : "f"(hi), "f"(lo));
    return r;
}
__device__ __forceinline__ float tanh_fast(float x) {
    float r;
    asm("tanh.approx.f32 %0, %1;" : "=f"(r) : "f"(x));
    return r;
}
__device__ __forceinline__ float silu_half(float h) { return fmaf(h, tanh_fast(h), h); }
__device__ __forceinline__ void ldsm4(uint32_t (&u)[4], uint32_t a) {
    asm volatile("ldmatrix.sync.aligned.m8n8.x4.shared.b16 {%0,%1,%2,%3}, [%4];"
                 : "=r"(u[0]), "=r"(u[1]), "=r"(u[2]), "=r"(u[3]) : "r"(a + S0) : "memory");
}
__device__ __forceinline__ void ldsm4t(uint32_t (&u)[4], uint32_t a) {
    asm volatile("ldmatrix.sync.aligned.m8n8.x4.trans.shared.b16 {%0,%1,%2,%3}, [%4];"
                 : "=r"(u[0]), "=r"(u[1]), "=r"(u[2]), "=r"(u[3]) : "r"(a + S0) : "memory");
}
__device__ __forceinline__ void stsm4(uint32_t a, uint32_t p0, uint32_t p1, uint32_t p2, uint32_t p3) {
    asm volatile("stmatrix.sync.aligned.m8n8.x4.shared.b16 [%0], {%1,%2,%3,%4};" ::"r"(a + S0), "r"(p0), "r"(p1), "r"(p2), "r"(p3) : "memory");
}
__device__ __forceinline__ void stsm4t(uint32_t a, uint32_t p0, uint32_t p1, uint32_t p2, uint32_t p3) {
    asm volatile("stmatrix.sync.aligned.m8n8.x4.trans.shared.b16 [%0], {%1,%2,%3,%4};" ::"r"(a + S0), "r"(p0), "r"(p1), "r"(p2), "r"(p3) : "memory");
}

#define R8(o) "+f"(d[o]), "+f"(d[o + 1]), "+f"(d[o + 2]), "+f"(d[o + 3]), "+f"(d[o + 4]), "+f"(d[o + 5]), "+f"(d[o + 6]), "+f"(d[o + 7])
template <uint32_t ALO, uint32_t BLO, uint64_t AHI = 8, uint64_t BHI = 48>
__device__ __forceinline__ void wgmma128(float (&d)[64]) {
    asm volatile(
        "wgmma.mma_async.sync.aligned.m64n128k16.f32.bf16.bf16 "
        "{%0,%1,%2,%3,%4,%5,%6,%7,%8,%9,%10,%11,%12,%13,%14,%15,%16,%17,%18,%19,%20,%21,%22,%23,%24,%25,%26,%27,%28,%29,%30,%31,"
        "%32,%33,%34,%35,%36,%37,%38,%39,%40,%41,%42,%43,%44,%45,%46,%47,%48,%49,%50,%51,%52,%53,%54,%55,%56,%57,%58,%59,%60,%61,%62,%63},"
        " %64, %65, 1, 1, 1, 0, 0;"
        : R8(0), R8(8), R8(16), R8(24), R8(32), R8(40), R8(48), R8(56)
        : "l"((AHI << 32) | ALO), "l"((BHI << 32) | BLO));
}
template <int S>
__device__ __forceinline__ void mma_stages(float (&d)[64], int conv, int tid, Scratch* gs) {
    constexpr uint32_t A = ((SM_ACT + S * 2 * CH_PITCH + 16) >> 4) | ((CH_PITCH >> 4) << 16);
    constexpr uint32_t B = (slot_addr(S % NS) >> 4) | (8u << 16);
    if (S == 0) {
        if (NB0) { mbar_wait(BAR(BAR_W0), conv); bar_sync(8, 256); }
        else mbar_wait(BAR(BAR_FULL), conv);
    }
    bool next_ok = true;
    constexpr uint32_t NEXT = S + 1 < NSTAGE ? BAR(BAR_FULL + S + 1) : BAR(BAR_EMB);
    const int npar = S + 1 < NSTAGE ? conv : 0;
    next_ok = mbar_test(NEXT, npar);
    if (S == 0 && tid == 0) TL(32 + conv * 24);
    asm volatile("wgmma.fence.sync.aligned;" ::: "memory");
    wgmma128<A, B>(d);
    wgmma128<A + 1, B + 16>(d);
    wgmma128<A + 2, B + 32>(d);
    asm volatile("wgmma.commit_group.sync.aligned;" ::: "memory");
    if (S >= LAG) {
        asm volatile("wgmma.wait_group.sync.aligned %0;" ::"n"(LAG) : "memory");
        if ((tid & 31) == 0) mbar_arrive(BAR(BAR_WEMPTY + (S + NS - LAG) % NS));
    }
    if (!next_ok) mbar_wait(NEXT, npar);
    if constexpr (S + 1 < NSTAGE) mma_stages<S + 1>(d, conv, tid, gs);
}

__device__ __forceinline__ void weight_load(uint4 (&t)[5], const __nv_bfloat16* w, int cta, int lane) {
    const char* base = reinterpret_cast<const char*>(w) + (uint32_t)((((cta & 15) * 8 + (lane >> 2)) * 8 + (cta >> 4)) * 288 + (lane & 3) * 16);
#pragma unroll
    for (int k = 0; k < 5; k++)
        if (k < 4 || !(lane & 2)) t[k] = __ldg(reinterpret_cast<const uint4*>(base + k * 64));
}
__device__ __forceinline__ void weight_block(uint32_t bounce, unsigned char* wt, int cta, int lane, unsigned* cnt) {
    const unsigned opaque_one = gridDim.y;
    unsigned char* piece = wt + (cta >> 4) * STAGE_BYTES + (cta & 15) * 768;
    uint32_t v[18];
#pragma unroll
    for (int i = 0; i < 9; i++) {
        const float2 q = lds64f(bounce + (lane & 7) * 288 + (lane >> 3) * 72 + i * 8);
        v[2 * i] = __float_as_uint(q.x); v[2 * i + 1] = __float_as_uint(q.y);
    }
    unsigned char* dst = piece + (lane >> 4) * 128 + (lane & 7) * 16 + ((lane >> 3) & 1) * 8;
    unsigned rb[3];
#pragma unroll
    for (int kyo = 0; kyo < 3; kyo++) {
#pragma unroll
        for (int kx = 0; kx < 3; kx++) {
            const int tap = ky_of(kyo) * 3 + kx;
            uint32_t o[2];
#pragma unroll
            for (int m = 0; m < 2; m++) {
                const int i0 = 18 * m + tap, i1 = i0 + 9;
                o[m] = __byte_perm(v[i0 >> 1], v[i1 >> 1], ((i0 & 1) ? 0x32u : 0x10u) | ((i1 & 1) ? 0x7600u : 0x5400u));
            }
            asm volatile("st.relaxed.gpu.global.v2.u32 [%0], {%1,%2};" ::"l"(dst + kyo * 8 * STAGE_BYTES + kx * 256), "r"(o[0]), "r"(o[1]) : "memory");
        }
        rb[kyo] = ld_relaxed(piece + kyo * 8 * STAGE_BYTES + (lane < 24 ? lane : 0) * 32);
    }
    const unsigned i0 = __any_sync(0xffffffffu, rb[0] == 0x9e3779b9u) ? opaque_one : 1u;
    if (lane < 2) asm volatile("red.relaxed.gpu.global.add.u32 [%0], %1;" ::"l"(cnt), "r"(i0) : "memory");
    const unsigned i1 = __any_sync(0xffffffffu, (rb[1] ^ rb[2]) == 0x9e3779b9u) ? opaque_one : 1u;
    if (lane < 2) asm volatile("red.relaxed.gpu.global.add.u32 [%0], %1;" ::"l"(cnt), "r"(i1 << 16) : "memory");
}
__device__ __forceinline__ uint32_t act2(uint32_t u, const float4& cf) {
    return pack_bf(silu_half(fmaf(bf_lo(u), cf.x, cf.z)), silu_half(fmaf(bf_hi(u), cf.y, cf.w)));
}
__device__ __forceinline__ void norm_unit(uint32_t (&u)[4], const float4& ca, const float4& cb) {
    u[0] = act2(u[0], ca); u[1] = act2(u[1], ca); u[2] = act2(u[2], cb); u[3] = act2(u[3], cb);
}
__device__ __forceinline__ void read_stats(uint32_t gst, float (&g)[8]) {
    asm volatile("ld.volatile.shared.v4.f32 {%0,%1,%2,%3}, [%4];" : "=f"(g[0]), "=f"(g[1]), "=f"(g[2]), "=f"(g[3]) : "r"(gst + S0) : "memory");
    asm volatile("ld.volatile.shared.v4.f32 {%0,%1,%2,%3}, [%4];" : "=f"(g[4]), "=f"(g[5]), "=f"(g[6]), "=f"(g[7]) : "r"(gst + 16 + S0) : "memory");
}
template <int T>
__device__ __forceinline__ void wait_stats(uint32_t gst, float (&g)[8]) {
    float rs, mr;
    unsigned it = 0;
#pragma unroll 1
    do {
        asm volatile("ld.volatile.shared.v2.f32 {%0,%1}, [%2];" : "=f"(rs), "=f"(mr) : "r"(gst + 8 * T + S0) : "memory");
    } while (!__all_sync(0xffffffffu, rs != 0.f) && ++it < 8 * SPIN_LIMIT);
    if (T < 3) read_stats(gst, g);
    g[2 * T] = rs; g[2 * T + 1] = mr;
}
template <int T>
__device__ __forceinline__ void own_unit(uint32_t (&o)[4], const float (&z)[8], float4 (&cf)[8], const float (&g)[8]) {
    float4 &ca = cf[2 * T], &cb = cf[2 * T + 1];
    const float rs = g[2 * T], mr = g[2 * T + 1];
    ca.z = fmaf(-mr, ca.x, ca.z); ca.w = fmaf(-mr, ca.y, ca.w);
    cb.z = fmaf(-mr, cb.x, cb.z); cb.w = fmaf(-mr, cb.y, cb.w);
#pragma unroll
    for (int i = 0; i < 4; i++)
        o[i] = pack_bf(silu_half(fmaf(z[2 * i], rs, i < 2 ? ca.z : cb.z)), silu_half(fmaf(z[2 * i + 1], rs, i < 2 ? ca.w : cb.w)));
}
template <int FIRST, int N>
__device__ __forceinline__ void norm_block(uint32_t (&u)[4][4], float4 (&cf)[8], uint32_t act, uint32_t mask, uint32_t fbar, int lane) {
#pragma unroll
    for (int t = FIRST; t < FIRST + N; t++) {
        norm_unit(u[t], cf[2 * t], cf[2 * t + 1]);
        stsm4(act + t * 2 * KC_BYTES, u[t][0] & mask, u[t][1] & mask, u[t][2] & mask, u[t][3] & mask);
    }
    fence_async_smem();
    __syncwarp();
    if (lane < N) mbar_arrive(fbar + 16 * (FIRST + lane));
}
__device__ __forceinline__ void publish(uint32_t bar, int lane) {
    fence_async_smem();
    __syncwarp();
    if (lane == 0) mbar_arrive(bar);
}
template <int T>
__device__ __forceinline__ void next_unit(const float (&z)[8], float4 (&cf)[8], uint32_t gst, float (&g)[8], uint32_t act, uint32_t fbar, int lane) {
    const bool have = __all_sync(0xffffffffu, g[2 * T] != 0.f);
    if (!have) { publish(fbar + 16 * (T - 1), lane); wait_stats<T>(gst, g); }
    uint32_t o[4];
    own_unit<T>(o, z, cf, g);
    if (have) publish(fbar + 16 * (T - 1), lane);
    stsm4(act + T * 2 * KC_BYTES, o[0], o[1], o[2], o[3]);
}
__device__ __forceinline__ void stat_mma(float (&c)[4], uint32_t p, uint32_t q) {
    asm("mma.sync.aligned.m16n8k16.row.col.f32.bf16.bf16.f32 {%0,%1,%2,%3}, {%4,%5,%6,%5}, {%4,%6}, {%0,%1,%2,%3};"
        : "+f"(c[0]), "+f"(c[1]), "+f"(c[2]), "+f"(c[3]) : "r"(p), "r"(0x3f803f80u), "r"(q));
}
__device__ __forceinline__ void stat_store(const float (&c)[4], uint32_t dst, int lane) {
    const int g = lane >> 2, t = lane & 3;
    if (t == (g >> 1)) sts32f(dst + g * 4, (g & 1) ? c[1] : c[0]);
    if (g == 7) sts32f(dst + 32 + t * 4, c[2] + c[3]);
}
__device__ __forceinline__ float sum4(float4 v) { return (v.x + v.y) + (v.z + v.w); }
__device__ __forceinline__ void stat_publish(uint32_t src, float* acc, int lane, bool real) {
    const uint32_t a = src + (lane & 15) * 48;
    float q = sum4(lds128f(a)) + sum4(lds128f(a + 16)), sm = sum4(lds128f(a + 32));
    q += __shfl_xor_sync(0xffffffffu, q, 1); sm += __shfl_xor_sync(0xffffffffu, sm, 1);
    q += __shfl_xor_sync(0xffffffffu, q, 2); sm += __shfl_xor_sync(0xffffffffu, sm, 2);
    if (real && (lane & 19) == 0) red_add4(acc + lane, 1.f, sm, q, 1.f);
}
__device__ __forceinline__ void fence_acc(float (&d)[64]) {
#pragma unroll
    for (int i = 0; i < 64; i++) asm volatile("" : "+f"(d[i])::"memory");
}
__device__ __forceinline__ void ld_unit(uint32_t (&u)[4], const uint4* p) {
    asm volatile("ld.relaxed.gpu.global.v4.u32 {%0,%1,%2,%3}, [%4];" : "=r"(u[0]), "=r"(u[1]), "=r"(u[2]), "=r"(u[3]) : "l"(p) : "memory");
}

__device__ __noinline__ void side_jobs(const __nv_bfloat16* __restrict__ t_emb, const __nv_bfloat16* __restrict__ w_emb,
                                       const __nv_bfloat16* __restrict__ w2, Scratch* __restrict__ gs, unsigned clk0) {
    const int tid = threadIdx.x, warp = tid >> 5, lane = tid & 31, j = blockIdx.x;
    float tv = 0.f;
    if (lane < 24) tv = __bfloat162float(t_emb[(lane / 12) * E + j * 192 + warp * 12 + lane % 12]);
    if (tid == 0) {
        mbar_init(BAR(0), 1);
        mbar_expect(BAR(0), 192 * C * 2);
        fence_async_smem();
        while (clock32() - clk0 < SDELAY) {}
#pragma unroll
        for (int i = 0; i < 4; i++)
            asm volatile("cp.async.bulk.prefetch.L2.global [%0], 18432;" ::"l"(reinterpret_cast<const char*>(w2) + (j * 4 + i) * 18432) : "memory");
#pragma unroll
        for (int i = 0; i < 4; i++) bulk_g2s(S0 + SM_W + i * 12288, w_emb + (j * 192 + i * 48) * C, 12288, S0 + BAR(0));
    }
    if (j == 0 && tid < 32) gs->acc2[(tid >> 4) * LS + (tid & 15)] = 0.f;
    const float sv = silu_half(0.5f * tv);
    __syncthreads();
    mbar_wait(BAR(0), 0);
    float acc[8] = {0.f, 0.f, 0.f, 0.f, 0.f, 0.f, 0.f, 0.f};
#pragma unroll
    for (int i = 0; i < 12; i++) {
        const float2 wq = lds64f(SM_W + (warp * 12 + i) * 256 + lane * 8);
        const uint32_t wx = __float_as_uint(wq.x), wy = __float_as_uint(wq.y);
#pragma unroll
        for (int bb = 0; bb < 2; bb++) {
            const float sx = __shfl_sync(0xffffffffu, sv, bb * 12 + i);
            acc[4 * bb + 0] = fmaf(sx, bf_lo(wx), acc[4 * bb + 0]); acc[4 * bb + 1] = fmaf(sx, bf_hi(wx), acc[4 * bb + 1]);
            acc[4 * bb + 2] = fmaf(sx, bf_lo(wy), acc[4 * bb + 2]); acc[4 * bb + 3] = fmaf(sx, bf_hi(wy), acc[4 * bb + 3]);
        }
    }
    sts128f(SM_ACT + warp * 1024 + lane * 16, make_float4(acc[0], acc[1], acc[2], acc[3]));
    sts128f(SM_ACT + warp * 1024 + 512 + lane * 16, make_float4(acc[4], acc[5], acc[6], acc[7]));
    __syncthreads();
    if (tid < 128) {
        float2 sum = make_float2(0.f, 0.f);
#pragma unroll
        for (int w = 0; w < 16; w++) { const float2 p = lds64f(SM_ACT + w * 1024 + tid * 8); sum.x += p.x; sum.y += p.y; }
        *reinterpret_cast<float2*>(&gs->emb[j * NB * C + tid * 2]) = sum;
        bar_sync(1, 128);
        if (tid < 2) asm volatile("red.release.gpu.global.add.u32 [%0], 1;" ::"l"(&gs->wcnt[(2 * NB + tid) * LS]) : "memory");
    }
}

__global__ void __cluster_dims__(2, 1, 1) __launch_bounds__(NTHREADS, 1)
resblock_kernel(const __nv_bfloat16* __restrict__ w1, const __nv_bfloat16* __restrict__ x,
                const __nv_bfloat16* __restrict__ t_emb, const __nv_bfloat16* __restrict__ g1,
                const __nv_bfloat16* __restrict__ be1, const __nv_bfloat16* __restrict__ w_emb,
                const __nv_bfloat16* __restrict__ g2, const __nv_bfloat16* __restrict__ be2,
                const __nv_bfloat16* __restrict__ w2, __nv_bfloat16* __restrict__ out, Scratch* __restrict__ gs,
                const __grid_constant__ CUtensorMap xmap) {
    const unsigned clk0 = clock32();
    if (threadIdx.x == 480 && blockIdx.x >= NXTRA) TLG(1);
    const int tid = threadIdx.x, lane = tid & 31;
    const int cta = blockIdx.x - NXTRA, b = cta >> 6, r = cta & 63;
    uint4 v[5];
    if (tid < 32) weight_load(v, w1, cta & (NCTA - 1), lane);
    if (tid >= 192 && tid < 192 + 72) {
        const int c2 = (cta + 64) & (NCTA - 1), t = tid - 192;
        asm volatile("prefetch.global.L2 [%0];" ::"l"(reinterpret_cast<const char*>(w1) + (uint32_t)((((c2 & 15) * 8 + (t & 7)) * 8 + (c2 >> 4)) * 288 + (t >> 3) * 32)));
    }
    uint4 xv[8];
    const int wg4 = (tid >> 5) - 1;
    const bool early = tid >= 32 && wg4 < NLDG;
    if (early) {
        const char* src = reinterpret_cast<const char*>(x) + (uint32_t)((((b & 1) * C + wg4 * 32 + (lane >> 3)) * HW + r) * HW * 2 + (lane & 7) * 16);
        while (clock32() - clk0 < XDELAY + (wg4 >> 1) * XSTAG + (wg4 & 1) * XSTAG2) {}
#pragma unroll
        for (int i = 0; i < 8; i++) xv[i] = __ldg(reinterpret_cast<const uint4*>(src + i * (4 * HW * HW * 2)));
    }
    const int warp = __shfl_sync(0xffffffffu, tid >> 5, 0);
    if (cta < 0) { side_jobs(t_emb, w_emb, w2, gs, clk0); return; }

    if (warp != 4) asm volatile("barrier.cluster.arrive.relaxed.aligned;" ::: "memory");
    const bool has_outer = (r != 0) && (r != HW - 1);
    if (warp == 1 || warp == 2 || warp == 3 || warp == 5) {
        const int g = warp < 4 ? warp - 1 : 3;
        if (elect_one()) {
            if (g >= NLDG) asm volatile("prefetch.tensormap [%0];" ::"l"(&xmap) : "memory");
            mbar_init(BAR(BAR_X) + 8 * g, 1);
            if (g >= NLDG) { mbar_expect(BAR(BAR_X) + 8 * g, 4096); fence_async_smem(); }
        }
        __syncwarp();
        bar_arrive(4, 256 + 32 + 128);
        if (g >= NLDG) {
            while (clock32() - clk0 < XDELAY + (g >> 1) * XSTAG + (g & 1) * XSTAG2) {}
            if (elect_one()) tma_x(SM_XOWN + g * 4096, &xmap, r, b * C + g * 32, BAR(BAR_X) + 8 * g);
            __syncwarp();
            mbar_wait(BAR(BAR_X) + 8 * g, 0);
#pragma unroll
            for (int k = 0; k < 8; k++) xv[k] = lds128(SM_XOWN + g * 4096 + k * 512 + lane * 16);
        }
        float c[8][4];
#pragma unroll
        for (int k = 0; k < 8; k++) {
            c[k][0] = c[k][1] = c[k][2] = c[k][3] = 0.f;
            stat_mma(c[k], xv[k].x, xv[k].y); stat_mma(c[k], xv[k].z, xv[k].w);
        }
#pragma unroll
        for (int i = 0; i < 4; i++) c[0][i] = ((c[0][i] + c[1][i]) + (c[2][i] + c[3][i])) + ((c[4][i] + c[5][i]) + (c[6][i] + c[7][i]));
        stat_store(c[0], SM_RED + g * 48, lane);
        __syncwarp();
        if (lane == 0) {
            const uint32_t a = SM_RED + g * 48;
            red_add4(&gs->acc1[b * LS + g * 4], 1.f, sum4(lds128f(a + 32)), sum4(lds128f(a)) + sum4(lds128f(a + 16)), 1.f);
            TL(74 + g);
        }
        if (g < NLDG) {
#pragma unroll
            for (int i = 0; i < 8; i++)
                sts128(SM_XOWN + g * 4096 + i * 512 + (lane >> 3) * 128 + (((lane & 7) ^ ((lane >> 3) + 4 * (i & 1))) << 4), xv[i]);
            __syncwarp();
            if (lane == 0) mbar_arrive(BAR(BAR_X) + 8 * g);
        }
    }
    if (warp == 4) {
            if (elect_one()) {
#pragma unroll
                for (int i = 0; i < NSTAGE; i++) mbar_init(BAR(BAR_FULL + i), (i >> 3) == 1 ? 1 : (NB0 && i == 0 ? 4 : 5));
#pragma unroll
                for (int i = 0; i < NS + 2; i++) mbar_init(BAR(BAR_WEMPTY + i), 4);
#pragma unroll
                for (int i = BAR_STATS; i < BAR_X; i++) mbar_init(BAR(i), i == BAR_EMB ? 3 : 1);
                mbar_init(BAR(BAR_X + 4), 1);
                asm volatile("fence.mbarrier_init.release.cluster;" ::: "memory");
            }
            if (lane < 4) sts128(SM_GST + lane * 16, make_uint4(0, 0, 0, 0));
            __syncwarp();
            fence_async_smem();
            bar_arrive(0, 96);
            bar_arrive(5, 64);
            bar_arrive(4, 256 + 32 + 128);
            const uint4 z = make_uint4(0, 0, 0, 0);
#pragma unroll
            for (int i = 0; i < 2; i++) sts128(SM_ACT + (i * 16 + (lane >> 1)) * CH_PITCH + (lane & 1) * 16, z);
            if (lane < 4) sts128(SM_ACT + (2 + (lane >> 1)) * ROW_BYTES + (lane & 1) * 16, z);
            if (lane < 16) sts128(SM_ONES + lane * 16, make_uint4(lane < 8 ? 0x3f803f80u : 0u, 0, 0, 0));
            fence_async_smem();
            bar_arrive(7, 160);
            asm volatile("barrier.cluster.arrive.relaxed.aligned;" ::: "memory");
            while (clock32() - clk0 < W2DELAY) {}
            weight_load(v, w2, cta, lane);
        }
    if (warp == 0 || warp == 4) {
        const int k = warp >> 2;
#pragma unroll
        for (int i = 0; i < 5; i++)
            if (i < 4 || !(lane & 2)) sts128(SM_BNC + k * 2304 + (lane >> 2) * 288 + (lane & 3) * 16 + i * 64, v[i]);
        if (lane == 0) TL(k ? 14 : 81);
        __syncwarp();
        weight_block(SM_BNC + k * 2304, gs->wt + k * NSTAGE * STAGE_BYTES, cta, lane,
                     k ? &gs->wcnt[(NB + (lane & 1)) * LS] : &gs->w1cnt[((lane & 1) * 8 + (cta >> 4)) * KS]);
        if (lane == 0) TL(k ? 13 : 4);
    }

    if (warp >= 8) {
        const int nw = warp - 8;
        if (nw < 2) {
            const uint2 ga = __ldg(reinterpret_cast<const uint2*>(nw ? g2 : g1) + lane), bt = __ldg(reinterpret_cast<const uint2*>(nw ? be2 : be1) + lane);
            sts128f(SM_COEF + nw * 1024 + lane * 32, make_float4(0.5f * bf_lo(ga.x), 0.5f * bf_hi(ga.x), 0.5f * bf_lo(bt.x), 0.5f * bf_hi(bt.x)));
            sts128f(SM_COEF + nw * 1024 + lane * 32 + 16, make_float4(0.5f * bf_lo(ga.y), 0.5f * bf_hi(ga.y), 0.5f * bf_lo(bt.y), 0.5f * bf_hi(bt.y)));
        }
        bar_sync(4, 256 + 32 + 128);
        const int par = nw >> 2, wq = nw & 3;
        const uint32_t act_off = SM_ACT + (par * 2 + (lane >> 4)) * CH_PITCH + (2 + wq * 16 + (lane & 15)) * 16;
        const uint32_t stg_off = (par * 16 + (lane >> 4) * 8 + (lane & 7)) * 128 + (((2 * wq + ((lane >> 3) & 1)) ^ (lane & 7)) << 4);
        const uint32_t cfa = SM_COEF + par * 128 + (lane & 3) * 16;
        const uint32_t fbar = BAR(BAR_FULL) + 8 * par;
        uint4* inbox = gs->box + cta * 1024 + nw * 32 + lane;
#pragma unroll 1
        for (int conv = 0; conv < 2; conv++) {
            uint32_t u[4][4], w[4][4];
            float4 cf[8];
            if (conv == 0) {
#pragma unroll
                for (int i = 0; i < 4; i++) { mbar_wait(BAR(BAR_X + i), 0); ldsm4t(u[i], SM_XOWN + stg_off + i * 4096); }
            } else {
                mbar_wait(BAR(BAR_HW), 0);
#pragma unroll
                for (int i = 0; i < 4; i++) ldsm4(u[i], act_off + i * 2 * KC_BYTES);
            }
#pragma unroll
            for (int i = 0; i < 8; i++) cf[i] = lds128f(cfa + conv * 1024 + (i >> 1) * 256 + (i & 1) * 64);
            const uint32_t gst = SM_GST + conv * 32;
            float gv[8], z[4][8];
#pragma unroll
            for (int i = 0; i < 16; i++) {
                const float4& c = cf[i >> 1];
                z[i >> 2][2 * (i & 3)] = bf_lo(u[i >> 2][i & 3]) * c.x; z[i >> 2][2 * (i & 3) + 1] = bf_hi(u[i >> 2][i & 3]) * c.y;
                asm volatile("" : "+f"(z[i >> 2][2 * (i & 3)]), "+f"(z[i >> 2][2 * (i & 3) + 1]));
            }
            wait_stats<0>(gst, gv);
            if (tid == 256) TL(22 + conv * 4);
            if (par) { const unsigned c1 = clock32(); while (clock32() - c1 < PDELAY) {} }
            uint32_t o[4];
            own_unit<0>(o, z[0], cf, gv);
            stsm4(act_off, o[0], o[1], o[2], o[3]);
            fence_async_smem();
            if (NB0 && !par) bar_arrive(8, 256);
            __syncwarp();
            if (lane == 0) mbar_arrive(fbar);
            if (tid == 256) TL(8 + conv * 8);
            if (!__all_sync(0xffffffffu, gv[2] != 0.f)) wait_stats<1>(gst, gv);
            own_unit<1>(o, z[1], cf, gv);
            stsm4(act_off + 2 * KC_BYTES, o[0], o[1], o[2], o[3]);
            next_unit<2>(z[2], cf, gst, gv, act_off, fbar, lane);
            next_unit<3>(z[3], cf, gst, gv, act_off, fbar, lane);
            publish(fbar + 48, lane);
#pragma unroll
            for (int i = 0; i < 8; i++) { cf[i].x *= gv[i & ~1]; cf[i].y *= gv[i & ~1]; }
            if (tid == 256) TL(84 + conv);
            if (has_outer) {
                mbar_wait(BAR(BAR_X + 4), conv);
                if (conv == 0) {
#pragma unroll
                    for (int i = 0; i < 4; i++) ldsm4t(w[i], SM_XOUT + stg_off + i * 4096);
                } else {
#pragma unroll
                    for (int i = 0; i < 4; i++) {
                        const uint4 q = lds128(SM_XOWN + (tid - 256) * 16 + i * 4096);
                        w[i][0] = q.x; w[i][1] = q.y; w[i][2] = q.z; w[i][3] = q.w;
                    }
                    unsigned it = 0;
                    while (true) {
                        bool ok = true;
#pragma unroll
                        for (int i = 0; i < 16; i++) ok = ok && w[i >> 2][i & 3] != 0;
                        if (__all_sync(0xffffffffu, ok) || ++it > SPIN_LIMIT) break;
#pragma unroll
                        for (int i = 0; i < 4; i++) ld_unit(w[i], inbox + i * 256);
                    }
#pragma unroll
                    for (int i = 0; i < 16; i++) w[i >> 2][i & 3] = ~w[i >> 2][i & 3];
                }
            }
            if (conv == 0) {
                bar_sync(3, 256);
                if (nw == 0) sts128(SM_ACT + 2 * ROW_BYTES + (lane >> 1) * CH_PITCH + (lane & 1) * 16, make_uint4(0, 0, 0, 0));
            }
            if (tid == 256) TL(24 + conv * 4);
            norm_block<0, 2>(w, cf, act_off + 2 * ROW_BYTES, has_outer ? ~0u : 0u, fbar + 128, lane);
            if (tid == 256) TL(88 + conv);
            norm_block<2, 2>(w, cf, act_off + 2 * ROW_BYTES, has_outer ? ~0u : 0u, fbar + 128, lane);
            if (tid == 256) TL(23 + conv * 4);
        }
        if (has_outer) {
            mbar_wait(BAR(BAR_FULL + NSTAGE - 1), 1);
#pragma unroll
            for (int i = 0; i < 4; i++) inbox[i * 256] = make_uint4(0, 0, 0, 0);
        }
        {
            const int oc0 = par * 64 + ((tid & 127) >> 3), seg = lane & 7;
            __nv_bfloat16* dst = out + ((size_t)(b * C + oc0) * HW + r) * HW + seg * 8;
            const uint32_t src = SM_XOWN + oc0 * 128 + ((seg ^ (oc0 & 7)) << 4);
            asm volatile("{\n.reg .pred p;\nsetp.eq.u64 p, %0, 0;\n@p st.shared.u32 [%1], 0;\n}" ::"l"(dst), "r"(src + S0) : "memory");
            bar_sync(par ? 1 : 6, 128 + 128);
#pragma unroll
            for (int i = 0; i < 4; i++) *reinterpret_cast<uint4*>(dst + (size_t)i * 16 * HW * HW) = lds128(src + i * 2048);
            if (tid == 384) { TL(20); TLG(21); }
        }
    } else if (warp < 4) {
        const int wq = warp;
        bar_sync(7, 160);

        const uint32_t xbase = SM_XOWN + ((lane >> 4) * 8 + (lane & 7)) * 128 + (((2 * wq + ((lane >> 3) & 1)) ^ (lane & 7)) << 4);
        float d[64];
#pragma unroll
        for (int i = 0; i < 64; i++) d[i] = 0.f;
#pragma unroll 1
        for (int conv = 0; conv < 2; conv++) {
            fence_acc(d);
            mma_stages<0>(d, conv, tid, gs);
            if (conv == 0) {
                asm volatile("wgmma.fence.sync.aligned;" ::: "memory");
                wgmma128<(SM_ONES >> 4) | (8u << 16), (SM_EMB >> 4), 0, 8>(d);
                asm volatile("wgmma.commit_group.sync.aligned;" ::: "memory");
            }
            asm volatile("wgmma.wait_group.sync.aligned 0;" ::: "memory");
            fence_acc(d);
            if (tid == 0) TL(10 + conv * 8);
            if (conv == 1) {
                fence_acc(d);
#pragma unroll
                for (int kc = 0; kc < 8; kc++) {
                    stsm4t(xbase + kc * 2048, pack_bf(d[8 * kc], d[8 * kc + 1]), pack_bf(d[8 * kc + 2], d[8 * kc + 3]),
                           pack_bf(d[8 * kc + 4], d[8 * kc + 5]), pack_bf(d[8 * kc + 6], d[8 * kc + 7]));
                    if (kc == 3) bar_arrive(6, 128 + 128);
                }
                bar_arrive(1, 128 + 128);
                if (tid == 0) TL(5);
                break;
            }
            uint32_t hp[32];
#pragma unroll
            for (int i = 0; i < 32; i++) hp[i] = pack_bf(d[2 * i], d[2 * i + 1]);
#pragma unroll
            for (int g = 0; g < 4; g++) {
                float c[4] = {0.f, 0.f, 0.f, 0.f};
#pragma unroll
                for (int i = 0; i < 4; i++) stat_mma(c, hp[8 * g + 2 * i], hp[8 * g + 2 * i + 1]);
                stat_store(c, SM_RED + (g * 4 + wq) * 48, lane);
            }
            bar_sync(2, 128);
            if (wq == 0) stat_publish(SM_RED, &gs->acc2[b * LS], lane, true);
            if (tid == 0) TL(11);
            const uint32_t hbase = SM_ACT + (lane >> 4) * CH_PITCH + (2 + wq * 16 + (lane & 15)) * 16;
#pragma unroll
            for (int kc = 0; kc < 8; kc++) stsm4(hbase + kc * 2 * CH_PITCH, hp[4 * kc], hp[4 * kc + 1], hp[4 * kc + 2], hp[4 * kc + 3]);
            __syncwarp();
            if (lane == 0) mbar_arrive(BAR(BAR_HW));
            if (lane < LAG) mbar_arrive(BAR(BAR_WEMPTY + (NSTAGE - LAG) % NS) + 8 * lane);
            if (has_outer) {
                uint4* outbox = gs->box + (cta + ((r & 1) ? 1 : -1)) * 1024 + tid;
#pragma unroll
                for (int kc = 0; kc < 8; kc++) outbox[kc * 128] = make_uint4(~hp[4 * kc], ~hp[4 * kc + 1], ~hp[4 * kc + 2], ~hp[4 * kc + 3]);
            }
            if (tid == 0) TL(12);
#pragma unroll
            for (int kc = 0; kc < 8; kc++) {
                uint32_t p[4];
                ldsm4t(p, xbase + kc * 2048);
#pragma unroll
                for (int i = 0; i < 4; i++) { d[8 * kc + 2 * i] = bf_lo(p[i]); d[8 * kc + 2 * i + 1] = bf_hi(p[i]); }
            }
            fence_async_smem();
            __syncwarp();
            if (lane == 0) mbar_arrive(BAR(BAR_XFREE));
        }
        {
        }
    } else if (warp < 6) {
        if (warp == 5) {
            bar_sync(5, 64);
            mbar_wait(BAR(NB0 ? BAR_W0 : BAR_FULL), 0);
            if (has_outer && elect_one()) {
                mbar_expect(BAR(BAR_X + 4), 16384);
#pragma unroll
                for (int i = 0; i < 4; i++) tma_x(SM_XOUT + i * 4096, &xmap, r + ((r & 1) ? 1 : -1), b * C + i * 32, BAR(BAR_X + 4));
            }
            __syncwarp();
            asm volatile("barrier.cluster.wait.acquire.aligned;" ::: "memory");
            const uint32_t peer = (r & 1) ^ 1;
            const uint32_t self0 = mapa(0, r & 1), peer0 = mapa(0, peer);
#pragma unroll 1
            for (int conv = 0; conv < 2; conv++) {
#pragma unroll 1
                for (int kc = 0; kc < 8; kc++) {
                    mbar_wait(BAR(BAR_FULL) + 8 * kc, conv);
                    if (elect_one())
                        asm volatile("cp.async.bulk.shared::cluster.shared::cta.mbarrier::complete_tx::bytes [%0], [%1], %2, [%3];"
                                     ::"r"(peer0 + SM_ACT + ROW_BYTES + kc * KC_BYTES), "r"(self0 + SM_ACT + kc * KC_BYTES), "r"(KC_BYTES),
                                       "r"(peer0 + BAR(BAR_FULL + 8) + 8 * kc) : "memory");
                }
                if (lane == 0) TL(86 + conv);
#pragma unroll 1
                for (int kc = 0; kc < 8; kc++) mbar_wait(BAR(BAR_FULL + 8) + 8 * kc, conv);
                if (lane == 0)
                    asm volatile("mbarrier.arrive.relaxed.cluster.shared::cluster.b64 _, [%0];" ::"r"(peer0 + (conv ? BAR(BAR_ACK) : BAR(BAR_EMB))) : "memory");
            }
            mbar_wait(BAR(BAR_ACK), 0);
        } else {
            mbar_wait(BAR(BAR_STATS), 0);
            unsigned it = 0;
            while (!__all_sync(0xffffffffu, ld_relaxed(&gs->wcnt[(2 * NB + b) * LS]) >= (unsigned)NXTRA) && ++it < SPIN_LIMIT) __nanosleep(100);
            fence_acquire();
            float ev[4] = {0.f, 0.f, 0.f, 0.f};
#pragma unroll
            for (int j = 0; j < NXTRA; j++) {
                const uint4 ef = ld_relaxed_v4(&gs->emb[(j * NB + b) * C + lane * 4]);
                ev[0] += __uint_as_float(ef.x); ev[1] += __uint_as_float(ef.y); ev[2] += __uint_as_float(ef.z); ev[3] += __uint_as_float(ef.w);
            }
#pragma unroll
            for (int i = 0; i < 4; i++) {
                const float hi = bf_lo(pack_bf(ev[i], 0.f));
                sts128(SM_EMB + (lane * 4 + i) * 16, make_uint4(pack_bf(hi, ev[i] - hi), 0, 0, 0));
            }
            fence_async_smem();
            __syncwarp();
            if (lane == 0) { mbar_arrive(BAR(BAR_EMB)); TL(19); }
        }
    } else if (warp == 6) {
        bar_sync(0, 96);
        const uint32_t ebytes = STAGE_BYTES + ((lane >> 3) == 1 ? KC_BYTES : 0);
        const uint32_t ebar = (NB0 && lane == 0) ? BAR(BAR_W0) : BAR(BAR_FULL) + 8 * lane;
        if (lane < NSTAGE) mbar_expect(ebar, ebytes);
        const int swap = (r & 1) ? 0 : 8 * STAGE_BYTES;
        unsigned it = 0;
        {
            int g = 0;
            const unsigned* cnt = &gs->w1cnt[(b * 8 + (lane & 7)) * KS];
            unsigned cv = ld_relaxed(cnt);
#pragma unroll 1
            while (g < NS) {
                unsigned ready = __ballot_sync(0xffffffffu, (lane < 8 ? cv & 0xffffu : cv >> 16) >= 16u);
                if ((ready >> 8 & 0xff) != 0xff) ready &= 0xff;
                if (ready != ~0u) cv = ld_relaxed(cnt);
                ready >>= g;
                if (++it > SPIN_LIMIT) ready = ~0u;
                if (!(ready & 1)) continue;
                fence_async_global();
                if (lane == 0) TL(g ? 3 : 6);
#pragma unroll 1
                for (; (ready & 1) && g < NS; g++, ready >>= 1)
                    if (elect_one())
                        bulk_g2s(S0 + SM_W + g * STAGE_BYTES, gs->wt + g * STAGE_BYTES + (g >= 8 ? swap : 0), STAGE_BYTES, S0 + ((NB0 && g == 0) ? BAR(BAR_W0) : BAR(BAR_FULL) + 8 * g));
            }
        }
#pragma unroll 1
        for (int q = 3; q < 12; q++) {
            const int conv = q >= 6, qs = conv ? q - 6 : q, sl = q % 3;
            const unsigned char* wsrc = gs->wt + q * 4 * STAGE_BYTES + (qs < 2 ? 0 : (qs < 4 ? swap : -swap));
            const uint32_t par = (q / 3 - 1) & 1;
            if (q == 6) {
                it = 0;
                while (!__all_sync(0xffffffffu, ld_relaxed(&gs->wcnt[(NB + b) * LS]) == NCTA * 0x10001u) && ++it < SPIN_LIMIT) {}
                fence_acquire();
                fence_async_global();
                if (lane == 0) { mbar_arrive(BAR(BAR_EMB)); TL(2); }
            }
#pragma unroll
            for (int i = 0; i < 4; i++) {
                mbar_wait(BAR(BAR_WEMPTY + i) + 32 * sl, par);
                if (i == 0 && (q == 6 || q == 9)) {
                    if ((lane >= NS) == (q == 9) && lane < NSTAGE) mbar_expect(ebar, ebytes);
                    __syncwarp();
                }
                if (elect_one())
                    bulk_g2s(S0 + SM_W + (sl * 4 + i) * STAGE_BYTES, wsrc + i * STAGE_BYTES, STAGE_BYTES,
                             S0 + ((NB0 && i == 0 && qs == 0) ? BAR(BAR_W0) : BAR(BAR_FULL + i) + 32 * qs));
            }
        }
    } else {
        bar_sync(0, 96);
#pragma unroll 1
        for (int conv = 0; conv < 2; conv++) {
            if (conv == 1) mbar_wait(BAR(BAR_HW), 0);
            const float* asrc = (conv ? gs->acc2 : gs->acc1) + b * LS + (lane & 3) * 4;
            unsigned it = 0;
#pragma unroll 1
            while (true) {
                const uint4 f = ld_relaxed_v4(asrc);
                const bool ok = ((f.x == 0x42800000u) & (f.w == 0x42800000u)) || ++it > SPIN_LIMIT;
                if (ok && lane < 4) {
                    const float inv_n = 1.0f / (32.0f * HW * HW);
                    const float mean = __uint_as_float(f.y) * inv_n;
                    float rs;
                    asm("rsqrt.approx.ftz.f32 %0, %1;" : "=f"(rs) : "f"(fmaxf(fmaf(-mean, mean, __uint_as_float(f.z) * inv_n), 0.f) + 1e-5f));
                    asm volatile("st.shared.v2.f32 [%0], {%1,%2};" ::"r"(S0 + SM_GST + conv * 32 + lane * 8), "f"(rs == 0.f ? 1.2e-38f : rs), "f"(mean * rs) : "memory");
                }
                if (__all_sync(0xffffffffu, ok)) break;
            }
            if (lane == 0) { mbar_arrive(BAR(BAR_STATS)); TL(7 + conv * 8); }
        }
        mbar_wait(BAR(BAR_XFREE), 0);
        if (has_outer && elect_one()) {
            mbar_expect(BAR(BAR_X + 4), 16384);
            bulk_g2s(S0 + SM_XOWN, gs->box + cta * 1024, 16384, S0 + BAR(BAR_X + 4));
        }
        if (r == 0) {
            if (lane < 16) gs->acc1[b * LS + lane] = 0.f;
            if (lane < 3) gs->wcnt[(lane * NB + b) * LS] = 0;
            if (lane < 8) gs->w1cnt[(b * 8 + lane) * KS] = 0;
        }
    }
}

}

extern "C" void kernel_launch(void* const* d_in, const int* in_sizes, int n_in, void* d_out, int out_size) {
    (void)in_sizes; (void)n_in; (void)out_size;
    typedef CUresult (*EncodeFn)(CUtensorMap*, CUtensorMapDataType, cuuint32_t, void*, const cuuint64_t*, const cuuint64_t*,
                                 const cuuint32_t*, const cuuint32_t*, CUtensorMapInterleave, CUtensorMapSwizzle,
                                 CUtensorMapL2promotion, CUtensorMapFloatOOBfill);
    static Scratch* gs = nullptr;
    static EncodeFn encode = nullptr;
    if (!gs) {
        cudaFuncSetAttribute(resblock_kernel, cudaFuncAttributeMaxDynamicSharedMemorySize, SM_TOTAL);
        cudaGetSymbolAddress((void**)&gs, g_scratch);
        cudaDriverEntryPointQueryResult qr;
        cudaGetDriverEntryPoint("cuTensorMapEncodeTiled", (void**)&encode, cudaEnableDefault, &qr);
    }
    CUtensorMap xmap;
    const cuuint64_t dims[3] = {HW, HW, NB * C}, strides[2] = {HW * 2, HW * HW * 2};
    const cuuint32_t box[3] = {HW, 1, 32}, es[3] = {1, 1, 1};
    encode(&xmap, CU_TENSOR_MAP_DATA_TYPE_BFLOAT16, 3, d_in[0], dims, strides, box, es, CU_TENSOR_MAP_INTERLEAVE_NONE,
           CU_TENSOR_MAP_SWIZZLE_128B, CU_TENSOR_MAP_L2_PROMOTION_NONE, CU_TENSOR_MAP_FLOAT_OOB_FILL_NONE);
    resblock_kernel<<<NCTA + NXTRA, NTHREADS, SM_TOTAL>>>(
        (const __nv_bfloat16*)d_in[4], (const __nv_bfloat16*)d_in[0], (const __nv_bfloat16*)d_in[1],
        (const __nv_bfloat16*)d_in[2], (const __nv_bfloat16*)d_in[3], (const __nv_bfloat16*)d_in[5],
        (const __nv_bfloat16*)d_in[6], (const __nv_bfloat16*)d_in[7], (const __nv_bfloat16*)d_in[8],
        (__nv_bfloat16*)d_out, gs, xmap);
}
```

```cpp
#include <cuda_runtime.h>
#include <cuda.h>
#include <cuda_bf16.h>
#include <stdint.h>

namespace {

constexpr int C = 128, HW = 64, NB = 2, E = 768;
constexpr int NCTA = NB * HW;
constexpr int NXTRA = 4;
constexpr int NTHREADS = 16 * 32;
constexpr int CH_PITCH = 66 * 16;
constexpr int ROW_BYTES = 16 * CH_PITCH;
constexpr int STAGE_BYTES = 12288;
constexpr int NSTAGE = 24;
constexpr int KC_BYTES = 2 * CH_PITCH;
constexpr int NS = 12;
constexpr int LAG = 1;
#define XDELAY 300
#define XSTAG 800
#define XSTAG2 300
#define SDELAY 600
#define W2DELAY 2400
#define PDELAY 60
#define SEQ 0
constexpr int NLDG = 2;

constexpr uint32_t SMEM_BASE = 0x400;
constexpr uint32_t SM_XOWN = SMEM_BASE;
constexpr uint32_t SM_ACT = SM_XOWN + 16384 + 512;
constexpr uint32_t SM_XOUT = SM_ACT + 2 * ROW_BYTES + 512;
static_assert(SM_XOUT % 1024 == 0, "swizzle atom alignment");
constexpr uint32_t SM_W = SM_ACT + 3 * ROW_BYTES + 128;
__host__ __device__ constexpr uint32_t slot_addr(int slot) { return SM_W + slot * STAGE_BYTES; }
constexpr uint32_t SM_COEF = SM_W + NS * STAGE_BYTES;
constexpr uint32_t SM_GST = SM_COEF + 2048;
constexpr uint32_t SM_EMB = SM_GST + 128;
constexpr uint32_t SM_ONES = SM_EMB + 2048;
constexpr uint32_t SM_RED = SM_ONES + 256;
constexpr uint32_t SM_BNC = SM_RED + 1536;
constexpr uint32_t SM_BAR = SM_BNC + 2 * 2304;
constexpr int BAR_FULL = 0, BAR_WEMPTY = NSTAGE, BAR_HW = BAR_WEMPTY + NS, BAR_XFREE = BAR_HW + 1, BAR_STATS = BAR_XFREE + 1,
              BAR_EMB = BAR_STATS + 1, BAR_ACK = BAR_EMB + 1, BAR_X = BAR_ACK + 1  , NBAR = BAR_X + 5;
constexpr int SM_TOTAL = SM_BAR + NBAR * 8 - SMEM_BASE;
static_assert(SM_TOTAL <= 232448, "smem");
__host__ __device__ constexpr uint32_t BAR(int i) { return SM_BAR + 8 * i; }
__host__ __device__ constexpr int ky_of(int kyo) { return kyo == 0 ? 1 : (kyo == 1 ? 0 : 2); }

constexpr unsigned SPIN_LIMIT = 1u << 16;

constexpr int LS = 1056, KS = 32;
struct Scratch {
    float acc1[NB * LS];
    float acc2[NB * LS];
    unsigned wcnt[3 * NB * LS];
    unsigned w1cnt[NB * 8 * KS];
    float emb[NXTRA * NB * C];
    alignas(1024) unsigned char wt[2 * NSTAGE * STAGE_BYTES];
    uint4 box[NCTA * 1024];
};
__device__ __align__(1024) Scratch g_scratch;
#define TL(i) do {} while (0)
#define TLG(i) do {} while (0)

__device__ __forceinline__ unsigned clock32() { unsigned c; asm volatile("mov.u32 %0, %%clock;" : "=r"(c)); return c; }
__device__ __forceinline__ uint32_t mapa(uint32_t a, uint32_t rank) {
    uint32_t d;
    asm("mapa.shared::cluster.u32 %0, %1, %2;" : "=r"(d) : "r"(a), "r"(rank));
    return d;
}
#define S0 mapa(0, blockIdx.x & 1)
__device__ __forceinline__ void mbar_init(uint32_t bar, int cnt) {
    asm volatile("mbarrier.init.shared::cta.b64 [%0], %1;" ::"r"(bar + S0), "r"(cnt) : "memory");
}
__device__ __forceinline__ void mbar_arrive(uint32_t bar) {
    asm volatile("mbarrier.arrive.shared::cta.b64 _, [%0];" ::"r"(bar + S0) : "memory");
}
__device__ __forceinline__ void mbar_expect(uint32_t bar, uint32_t bytes) {
    asm volatile("mbarrier.arrive.expect_tx.shared::cta.b64 _, [%0], %1;" ::"r"(bar + S0), "r"(bytes) : "memory");
}
__device__ __forceinline__ bool mbar_try(uint32_t bar, uint32_t par) {
    uint32_t ok;
    asm volatile("{\n.reg .pred p;\nmbarrier.try_wait.parity.shared::cta.b64 p, [%1], %2;\nselp.u32 %0, 1, 0, p;\n}"
                 : "=r"(ok) : "r"(bar + S0), "r"(par) : "memory");
    return ok;
}
__device__ __forceinline__ bool mbar_test(uint32_t bar, uint32_t par) {
    uint32_t ok;
    asm volatile("{\n.reg .pred p;\nmbarrier.test_wait.parity.shared::cta.b64 p, [%1], %2;\nselp.u32 %0, 1, 0, p;\n}"
                 : "=r"(ok) : "r"(bar + S0), "r"(par) : "memory");
    return ok;
}
__device__ __forceinline__ void mbar_wait(uint32_t bar, uint32_t par) {
    unsigned it = 0;
#pragma unroll 1
    while (!mbar_try(bar, par) && ++it < SPIN_LIMIT) {}
}
__device__ __forceinline__ bool elect_one() {
    uint32_t p;
    asm volatile("{\n.reg .pred p;\nelect.sync _|p, 0xffffffff;\nselp.u32 %0, 1, 0, p;\n}" : "=r"(p));
    return p;
}
__device__ __forceinline__ void fence_async_smem() { asm volatile("fence.proxy.async.shared::cta;" ::: "memory"); }
__device__ __forceinline__ void fence_async_global() { asm volatile("fence.proxy.async.global;" ::: "memory"); }
__device__ __forceinline__ void fence_acquire() { asm volatile("fence.acquire.gpu;" ::: "memory"); }
__device__ __forceinline__ void bar_sync(int id, int n) { asm volatile("bar.sync %0, %1;" ::"r"(id), "r"(n) : "memory"); }
__device__ __forceinline__ void bar_arrive(int id, int n) { asm volatile("bar.arrive %0, %1;" ::"r"(id), "r"(n) : "memory"); }
__device__ __forceinline__ void bulk_g2s(uint32_t dst, const void* src, uint32_t bytes, uint32_t bar) {
    asm volatile("cp.async.bulk.shared::cluster.global.mbarrier::complete_tx::bytes [%0], [%1], %2, [%3];"
                 ::"r"(dst), "l"(src), "r"(bytes), "r"(bar) : "memory");
}
__device__ __forceinline__ void tma_x(uint32_t dst, const CUtensorMap* tm, int row, int ch, uint32_t bar) {
    asm volatile("cp.async.bulk.tensor.3d.shared::cluster.global.mbarrier::complete_tx::bytes [%0], [%1, {%2, %3, %4}], [%5];"
                 ::"r"(dst + S0), "l"(tm), "r"(0), "r"(row), "r"(ch), "r"(bar + S0) : "memory");
}
__device__ __forceinline__ uint4 ld_relaxed_v4(const void* p) {
    uint4 v;
    asm volatile("ld.relaxed.gpu.global.v4.u32 {%0,%1,%2,%3}, [%4];" : "=r"(v.x), "=r"(v.y), "=r"(v.z), "=r"(v.w) : "l"(p) : "memory");
    return v;
}
__device__ __forceinline__ unsigned ld_relaxed(const void* p) {
    unsigned v;
    asm volatile("ld.relaxed.gpu.global.u32 %0, [%1];" : "=r"(v) : "l"(p) : "memory");
    return v;
}
__device__ __forceinline__ void red_add4(float* p, float a, float b, float c, float d) {
    asm volatile("red.relaxed.gpu.global.add.v4.f32 [%0], {%1,%2,%3,%4};" ::"l"(p), "f"(a), "f"(b), "f"(c), "f"(d) : "memory");
}
__device__ __forceinline__ void sts128(uint32_t a, uint4 v) {
    asm volatile("st.shared.v4.u32 [%0], {%1,%2,%3,%4};" ::"r"(a + S0), "r"(v.x), "r"(v.y), "r"(v.z), "r"(v.w) : "memory");
}
__device__ __forceinline__ void sts128f(uint32_t a, float4 v) {
    asm volatile("st.shared.v4.f32 [%0], {%1,%2,%3,%4};" ::"r"(a + S0), "f"(v.x), "f"(v.y), "f"(v.z), "f"(v.w) : "memory");
}
__device__ __forceinline__ void sts32f(uint32_t a, float v) { asm volatile("st.shared.f32 [%0], %1;" ::"r"(a + S0), "f"(v) : "memory"); }
__device__ __forceinline__ uint4 lds128(uint32_t a) {
    uint4 v;
    asm volatile("ld.shared.v4.u32 {%0,%1,%2,%3}, [%4];" : "=r"(v.x), "=r"(v.y), "=r"(v.z), "=r"(v.w) : "r"(a + S0) : "memory");
    return v;
}
__device__ __forceinline__ float4 lds128f(uint32_t a) {
    float4 v;
    asm volatile("ld.shared.v4.f32 {%0,%1,%2,%3}, [%4];" : "=f"(v.x), "=f"(v.y), "=f"(v.z), "=f"(v.w) : "r"(a + S0) : "memory");
    return v;
}
__device__ __forceinline__ float2 lds64f(uint32_t a) {
    float2 v;
    asm volatile("ld.shared.v2.f32 {%0,%1}, [%2];" : "=f"(v.x), "=f"(v.y) : "r"(a + S0) : "memory");
    return v;
}
__device__ __forceinline__ float bf_lo(uint32_t u) { return __uint_as_float(u << 16); }
__device__ __forceinline__ float bf_hi(uint32_t u) { return __uint_as_float(u & 0xffff0000u); }
__device__ __forceinline__ uint32_t pack_bf(float lo, float hi) {
    uint32_t r;
    asm("cvt.rn.bf16x2.f32 %0, %1, %2;" : "=r"(r) : "f"(hi), "f"(lo));
    return r;
}
__device__ __forceinline__ float tanh_fast(float x) {
    float r;
    asm("tanh.approx.f32 %0, %1;" : "=f"(r) : "f"(x));
    return r;
}
__device__ __forceinline__ float silu_half(float h) { return fmaf(h, tanh_fast(h), h); }
__device__ __forceinline__ void ldsm4(uint32_t (&u)[4], uint32_t a) {
    asm volatile("ldmatrix.sync.aligned.m8n8.x4.shared.b16 {%0,%1,%2,%3}, [%4];"
                 : "=r"(u[0]), "=r"(u[1]), "=r"(u[2]), "=r"(u[3]) : "r"(a + S0) : "memory");
}
__device__ __forceinline__ void ldsm4t(uint32_t (&u)[4], uint32_t a) {
    asm volatile("ldmatrix.sync.aligned.m8n8.x4.trans.shared.b16 {%0,%1,%2,%3}, [%4];"
                 : "=r"(u[0]), "=r"(u[1]), "=r"(u[2]), "=r"(u[3]) : "r"(a + S0) : "memory");
}
__device__ __forceinline__ void stsm4(uint32_t a, uint32_t p0, uint32_t p1, uint32_t p2, uint32_t p3) {
    asm volatile("stmatrix.sync.aligned.m8n8.x4.shared.b16 [%0], {%1,%2,%3,%4};" ::"r"(a + S0), "r"(p0), "r"(p1), "r"(p2), "r"(p3) : "memory");
}
__device__ __forceinline__ void stsm4t(uint32_t a, uint32_t p0, uint32_t p1, uint32_t p2, uint32_t p3) {
    asm volatile("stmatrix.sync.aligned.m8n8.x4.trans.shared.b16 [%0], {%1,%2,%3,%4};" ::"r"(a + S0), "r"(p0), "r"(p1), "r"(p2), "r"(p3) : "memory");
}

#define R8(o) "+f"(d[o]), "+f"(d[o + 1]), "+f"(d[o + 2]), "+f"(d[o + 3]), "+f"(d[o + 4]), "+f"(d[o + 5]), "+f"(d[o + 6]), "+f"(d[o + 7])
template <uint32_t ALO, uint32_t BLO, uint64_t AHI = 8, uint64_t BHI = 48>
__device__ __forceinline__ void wgmma128(float (&d)[64]) {
    asm volatile(
        "wgmma.mma_async.sync.aligned.m64n128k16.f32.bf16.bf16 "
        "{%0,%1,%2,%3,%4,%5,%6,%7,%8,%9,%10,%11,%12,%13,%14,%15,%16,%17,%18,%19,%20,%21,%22,%23,%24,%25,%26,%27,%28,%29,%30,%31,"
        "%32,%33,%34,%35,%36,%37,%38,%39,%40,%41,%42,%43,%44,%45,%46,%47,%48,%49,%50,%51,%52,%53,%54,%55,%56,%57,%58,%59,%60,%61,%62,%63},"
        " %64, %65, 1, 1, 1, 0, 0;"
        : R8(0), R8(8), R8(16), R8(24), R8(32), R8(40), R8(48), R8(56)
        : "l"((AHI << 32) | ALO), "l"((BHI << 32) | BLO));
}
template <int S>
__device__ __forceinline__ void mma_stages(float (&d)[64], int conv, int tid, Scratch* gs) {
    constexpr uint32_t A = ((SM_ACT + S * 2 * CH_PITCH + 16) >> 4) | ((CH_PITCH >> 4) << 16);
    constexpr uint32_t B = (slot_addr(S % NS) >> 4) | (8u << 16);
    if (S == 0) mbar_wait(BAR(BAR_FULL), conv);
    bool next_ok = true;
    constexpr uint32_t NEXT = S + 1 < NSTAGE ? BAR(BAR_FULL + S + 1) : BAR(BAR_EMB);
    const int npar = S + 1 < NSTAGE ? conv : 0;
    next_ok = mbar_test(NEXT, npar);
    if (S == 0 && tid == 0) TL(32 + conv * 24);
    asm volatile("wgmma.fence.sync.aligned;" ::: "memory");
    wgmma128<A, B>(d);
    wgmma128<A + 1, B + 16>(d);
    wgmma128<A + 2, B + 32>(d);
    asm volatile("wgmma.commit_group.sync.aligned;" ::: "memory");
    if (S >= LAG) {
        asm volatile("wgmma.wait_group.sync.aligned %0;" ::"n"(LAG) : "memory");
        if ((tid & 31) == 0) mbar_arrive(BAR(BAR_WEMPTY + (S + NS - LAG) % NS));
    }
    if (!next_ok) mbar_wait(NEXT, npar);
    if constexpr (S + 1 < NSTAGE) mma_stages<S + 1>(d, conv, tid, gs);
}

__device__ __forceinline__ void weight_load(uint4 (&t)[5], const __nv_bfloat16* w, int cta, int lane) {
    const char* base = reinterpret_cast<const char*>(w) + (uint32_t)((((cta & 15) * 8 + (lane >> 2)) * 8 + (cta >> 4)) * 288 + (lane & 3) * 16);
#pragma unroll
    for (int k = 0; k < 5; k++)
        if (k < 4 || !(lane & 2)) t[k] = __ldg(reinterpret_cast<const uint4*>(base + k * 64));
}
__device__ __forceinline__ void weight_block(uint32_t bounce, unsigned char* wt, int cta, int lane, unsigned* cnt) {
    const unsigned opaque_one = gridDim.y;
    unsigned char* piece = wt + (cta >> 4) * STAGE_BYTES + (cta & 15) * 768;
    uint32_t v[18];
#pragma unroll
    for (int i = 0; i < 9; i++) {
        const float2 q = lds64f(bounce + (lane & 7) * 288 + (lane >> 3) * 72 + i * 8);
        v[2 * i] = __float_as_uint(q.x); v[2 * i + 1] = __float_as_uint(q.y);
    }
    unsigned char* dst = piece + (lane >> 4) * 128 + (lane & 7) * 16 + ((lane >> 3) & 1) * 8;
    unsigned rb[3];
#pragma unroll
    for (int kyo = 0; kyo < 3; kyo++) {
#pragma unroll
        for (int kx = 0; kx < 3; kx++) {
            const int tap = ky_of(kyo) * 3 + kx;
            uint32_t o[2];
#pragma unroll
            for (int m = 0; m < 2; m++) {
                const int i0 = 18 * m + tap, i1 = i0 + 9;
                o[m] = __byte_perm(v[i0 >> 1], v[i1 >> 1], ((i0 & 1) ? 0x32u : 0x10u) | ((i1 & 1) ? 0x7600u : 0x5400u));
            }
            asm volatile("st.relaxed.gpu.global.v2.u32 [%0], {%1,%2};" ::"l"(dst + kyo * 8 * STAGE_BYTES + kx * 256), "r"(o[0]), "r"(o[1]) : "memory");
        }
        rb[kyo] = ld_relaxed(piece + kyo * 8 * STAGE_BYTES + (lane < 24 ? lane : 0) * 32);
    }
    const unsigned i0 = __any_sync(0xffffffffu, rb[0] == 0x9e3779b9u) ? opaque_one : 1u;
    if (lane < 2) asm volatile("red.relaxed.gpu.global.add.u32 [%0], %1;" ::"l"(cnt), "r"(i0) : "memory");
    const unsigned i1 = __any_sync(0xffffffffu, (rb[1] ^ rb[2]) == 0x9e3779b9u) ? opaque_one : 1u;
    if (lane < 2) asm volatile("red.relaxed.gpu.global.add.u32 [%0], %1;" ::"l"(cnt), "r"(i1 << 16) : "memory");
}
__device__ __forceinline__ uint32_t act2(uint32_t u, const float4& cf) {
    return pack_bf(silu_half(fmaf(bf_lo(u), cf.x, cf.z)), silu_half(fmaf(bf_hi(u), cf.y, cf.w)));
}
__device__ __forceinline__ void norm_unit(uint32_t (&u)[4], const float4& ca, const float4& cb) {
    u[0] = act2(u[0], ca); u[1] = act2(u[1], ca); u[2] = act2(u[2], cb); u[3] = act2(u[3], cb);
}
__device__ __forceinline__ float2 wait_stats(uint32_t slot, float2 g) {
    unsigned it = 0;
#pragma unroll 1
    while (!__all_sync(0xffffffffu, g.x != 0.f) && ++it < 8 * SPIN_LIMIT)
        asm volatile("ld.volatile.shared.v2.f32 {%0,%1}, [%2];" : "=f"(g.x), "=f"(g.y) : "r"(slot + S0) : "memory");
    return g;
}
__host__ __device__ constexpr int unit_kc(int t) { return (t & 1) + 4 * (t >> 1); }
template <int T>
__device__ __forceinline__ void own_unit(const float (&z)[8], float4 (&cf)[8], float2 g, uint32_t act) {
    float4 &ca = cf[2 * T], &cb = cf[2 * T + 1];
    ca.z = fmaf(-g.y, ca.x, ca.z); ca.w = fmaf(-g.y, ca.y, ca.w);
    cb.z = fmaf(-g.y, cb.x, cb.z); cb.w = fmaf(-g.y, cb.y, cb.w);
    uint32_t o[4];
#pragma unroll
    for (int i = 0; i < 4; i++)
        o[i] = pack_bf(silu_half(fmaf(z[2 * i], g.x, i < 2 ? ca.z : cb.z)), silu_half(fmaf(z[2 * i + 1], g.x, i < 2 ? ca.w : cb.w)));
    stsm4(act + unit_kc(T) * KC_BYTES, o[0], o[1], o[2], o[3]);
}
__device__ __forceinline__ void publish(uint32_t bar, int n, int lane) {
    fence_async_smem();
    __syncwarp();
    if (lane < n) mbar_arrive(bar + 8 * lane);
}
template <int FIRST>
__device__ __forceinline__ void outer_pair(uint32_t (&u)[4][4], const float4 (&cf)[8], uint32_t act, uint32_t mask, uint32_t fbar, int lane) {
#pragma unroll
    for (int t = FIRST; t < FIRST + 2; t++) {
        norm_unit(u[t], cf[2 * t], cf[2 * t + 1]);
        stsm4(act + unit_kc(t) * KC_BYTES, u[t][0] & mask, u[t][1] & mask, u[t][2] & mask, u[t][3] & mask);
    }
    publish(fbar + 8 * unit_kc(FIRST), 2, lane);
}
__device__ __forceinline__ void stat_mma(float (&c)[4], uint32_t p, uint32_t q) {
    asm("mma.sync.aligned.m16n8k16.row.col.f32.bf16.bf16.f32 {%0,%1,%2,%3}, {%4,%5,%6,%5}, {%4,%6}, {%0,%1,%2,%3};"
        : "+f"(c[0]), "+f"(c[1]), "+f"(c[2]), "+f"(c[3]) : "r"(p), "r"(0x3f803f80u), "r"(q));
}
__device__ __forceinline__ void stat_store(const float (&c)[4], uint32_t dst, int lane) {
    const int g = lane >> 2, t = lane & 3;
    if (t == (g >> 1)) sts32f(dst + g * 4, (g & 1) ? c[1] : c[0]);
    if (g == 7) sts32f(dst + 32 + t * 4, c[2] + c[3]);
}
__device__ __forceinline__ float sum4(float4 v) { return (v.x + v.y) + (v.z + v.w); }
__device__ __forceinline__ void stat_publish(uint32_t src, float* acc, int lane, bool real) {
    const uint32_t a = src + (lane & 15) * 48;
    float q = sum4(lds128f(a)) + sum4(lds128f(a + 16)), sm = sum4(lds128f(a + 32));
    q += __shfl_xor_sync(0xffffffffu, q, 1); sm += __shfl_xor_sync(0xffffffffu, sm, 1);
    q += __shfl_xor_sync(0xffffffffu, q, 2); sm += __shfl_xor_sync(0xffffffffu, sm, 2);
    if (real && (lane & 19) == 0) red_add4(acc + lane, 1.f, sm, q, 1.f);
}
__device__ __forceinline__ void fence_acc(float (&d)[64]) {
#pragma unroll
    for (int i = 0; i < 64; i++) asm volatile("" : "+f"(d[i])::"memory");
}
__device__ __forceinline__ void ld_unit(uint32_t (&u)[4], const uint4* p) {
    asm volatile("ld.relaxed.gpu.global.v4.u32 {%0,%1,%2,%3}, [%4];" : "=r"(u[0]), "=r"(u[1]), "=r"(u[2]), "=r"(u[3]) : "l"(p) : "memory");
}

__device__ __noinline__ void side_jobs(const __nv_bfloat16* __restrict__ t_emb, const __nv_bfloat16* __restrict__ w_emb,
                                       const __nv_bfloat16* __restrict__ w2, Scratch* __restrict__ gs, unsigned clk0) {
    const int tid = threadIdx.x, warp = tid >> 5, lane = tid & 31, j = blockIdx.x;
    float tv = 0.f;
    if (lane < 24) tv = __bfloat162float(t_emb[(lane / 12) * E + j * 192 + warp * 12 + lane % 12]);
    if (tid == 0) {
        mbar_init(BAR(0), 1);
        mbar_expect(BAR(0), 192 * C * 2);
        fence_async_smem();
        while (clock32() - clk0 < SDELAY) {}
#pragma unroll
        for (int i = 0; i < 4; i++)
            asm volatile("cp.async.bulk.prefetch.L2.global [%0], 18432;" ::"l"(reinterpret_cast<const char*>(w2) + (j * 4 + i) * 18432) : "memory");
#pragma unroll
        for (int i = 0; i < 4; i++) bulk_g2s(S0 + SM_W + i * 12288, w_emb + (j * 192 + i * 48) * C, 12288, S0 + BAR(0));
    }
    if (j == 0 && tid < 32) gs->acc2[(tid >> 4) * LS + (tid & 15)] = 0.f;
    const float sv = silu_half(0.5f * tv);
    __syncthreads();
    mbar_wait(BAR(0), 0);
    float acc[8] = {0.f, 0.f, 0.f, 0.f, 0.f, 0.f, 0.f, 0.f};
#pragma unroll
    for (int i = 0; i < 12; i++) {
        const float2 wq = lds64f(SM_W + (warp * 12 + i) * 256 + lane * 8);
        const uint32_t wx = __float_as_uint(wq.x), wy = __float_as_uint(wq.y);
#pragma unroll
        for (int bb = 0; bb < 2; bb++) {
            const float sx = __shfl_sync(0xffffffffu, sv, bb * 12 + i);
            acc[4 * bb + 0] = fmaf(sx, bf_lo(wx), acc[4 * bb + 0]); acc[4 * bb + 1] = fmaf(sx, bf_hi(wx), acc[4 * bb + 1]);
            acc[4 * bb + 2] = fmaf(sx, bf_lo(wy), acc[4 * bb + 2]); acc[4 * bb + 3] = fmaf(sx, bf_hi(wy), acc[4 * bb + 3]);
        }
    }
    sts128f(SM_ACT + warp * 1024 + lane * 16, make_float4(acc[0], acc[1], acc[2], acc[3]));
    sts128f(SM_ACT + warp * 1024 + 512 + lane * 16, make_float4(acc[4], acc[5], acc[6], acc[7]));
    __syncthreads();
    if (tid < 128) {
        float2 sum = make_float2(0.f, 0.f);
#pragma unroll
        for (int w = 0; w < 16; w++) { const float2 p = lds64f(SM_ACT + w * 1024 + tid * 8); sum.x += p.x; sum.y += p.y; }
        *reinterpret_cast<float2*>(&gs->emb[j * NB * C + tid * 2]) = sum;
        bar_sync(1, 128);
        if (tid < 2) asm volatile("red.release.gpu.global.add.u32 [%0], 1;" ::"l"(&gs->wcnt[(2 * NB + tid) * LS]) : "memory");
    }
}

__global__ void __cluster_dims__(2, 1, 1) __launch_bounds__(NTHREADS, 1)
resblock_kernel(const __nv_bfloat16* __restrict__ w1, const __nv_bfloat16* __restrict__ x,
                const __nv_bfloat16* __restrict__ t_emb, const __nv_bfloat16* __restrict__ g1,
                const __nv_bfloat16* __restrict__ be1, const __nv_bfloat16* __restrict__ w_emb,
                const __nv_bfloat16* __restrict__ g2, const __nv_bfloat16* __restrict__ be2,
                const __nv_bfloat16* __restrict__ w2, __nv_bfloat16* __restrict__ out, Scratch* __restrict__ gs,
                const __grid_constant__ CUtensorMap xmap) {
    const unsigned clk0 = clock32();
    if (threadIdx.x == 480 && blockIdx.x >= NXTRA) TLG(1);
    const int tid = threadIdx.x, lane = tid & 31;
    const int cta = blockIdx.x - NXTRA, b = cta >> 6, r = cta & 63;
    uint4 v[5];
    if (tid < 32) weight_load(v, w1, cta & (NCTA - 1), lane);
    if (tid >= 192 && tid < 192 + 72) {
        const int c2 = (cta + 64) & (NCTA - 1), t = tid - 192;
        asm volatile("prefetch.global.L2 [%0];" ::"l"(reinterpret_cast<const char*>(w1) + (uint32_t)((((c2 & 15) * 8 + (t & 7)) * 8 + (c2 >> 4)) * 288 + (t >> 3) * 32)));
    }
    uint4 xv[8];
    const int wg4 = (tid >> 5) - 1;
    const bool early = tid >= 32 && wg4 < NLDG;
    if (early) {
        const char* src = reinterpret_cast<const char*>(x) + (uint32_t)((((b & 1) * C + wg4 * 32 + (lane >> 3)) * HW + r) * HW * 2 + (lane & 7) * 16);
        while (clock32() - clk0 < XDELAY + (wg4 >> 1) * XSTAG + (wg4 & 1) * XSTAG2) {}
#pragma unroll
        for (int i = 0; i < 8; i++) xv[i] = __ldg(reinterpret_cast<const uint4*>(src + i * (4 * HW * HW * 2)));
    }
    const int warp = __shfl_sync(0xffffffffu, tid >> 5, 0);
    if (cta < 0) { side_jobs(t_emb, w_emb, w2, gs, clk0); return; }

    if (warp != 4) asm volatile("barrier.cluster.arrive.relaxed.aligned;" ::: "memory");
    const bool has_outer = (r != 0) && (r != HW - 1);
    if (warp == 1 || warp == 2 || warp == 3 || warp == 5) {
        const int g = warp < 4 ? warp - 1 : 3;
        if (elect_one()) {
            if (g >= NLDG) asm volatile("prefetch.tensormap [%0];" ::"l"(&xmap) : "memory");
            mbar_init(BAR(BAR_X) + 8 * g, 1);
            if (g >= NLDG) { mbar_expect(BAR(BAR_X) + 8 * g, 4096); fence_async_smem(); }
        }
        __syncwarp();
        bar_arrive(4, 256 + 32 + 128);
        if (g >= NLDG) {
            while (clock32() - clk0 < XDELAY + (g >> 1) * XSTAG + (g & 1) * XSTAG2) {}
            if (elect_one()) tma_x(SM_XOWN + g * 4096, &xmap, r, b * C + g * 32, BAR(BAR_X) + 8 * g);
            __syncwarp();
            mbar_wait(BAR(BAR_X) + 8 * g, 0);
#pragma unroll
            for (int k = 0; k < 8; k++) xv[k] = lds128(SM_XOWN + g * 4096 + k * 512 + lane * 16);
        }
        float c[8][4];
#pragma unroll
        for (int k = 0; k < 8; k++) {
            c[k][0] = c[k][1] = c[k][2] = c[k][3] = 0.f;
            stat_mma(c[k], xv[k].x, xv[k].y); stat_mma(c[k], xv[k].z, xv[k].w);
        }
#pragma unroll
        for (int i = 0; i < 4; i++) c[0][i] = ((c[0][i] + c[1][i]) + (c[2][i] + c[3][i])) + ((c[4][i] + c[5][i]) + (c[6][i] + c[7][i]));
        stat_store(c[0], SM_RED + g * 48, lane);
        __syncwarp();
        if (lane == 0) {
            const uint32_t a = SM_RED + g * 48;
            red_add4(&gs->acc1[b * LS + g * 4], 1.f, sum4(lds128f(a + 32)), sum4(lds128f(a)) + sum4(lds128f(a + 16)), 1.f);
            TL(74 + g);
        }
        if (g < NLDG) {
#pragma unroll
            for (int i = 0; i < 8; i++)
                sts128(SM_XOWN + g * 4096 + i * 512 + (lane >> 3) * 128 + (((lane & 7) ^ ((lane >> 3) + 4 * (i & 1))) << 4), xv[i]);
            __syncwarp();
            if (lane == 0) mbar_arrive(BAR(BAR_X) + 8 * g);
        }
    }
    if (warp == 4) {
            if (elect_one()) {
#pragma unroll
                for (int i = 0; i < NSTAGE; i++) mbar_init(BAR(BAR_FULL + i), (i >> 3) == 1 ? 1 : 5);
#pragma unroll
                for (int i = 0; i < NS + 2; i++) mbar_init(BAR(BAR_WEMPTY + i), 4);
#pragma unroll
                for (int i = BAR_STATS; i < BAR_X; i++) mbar_init(BAR(i), i == BAR_EMB ? 3 : 1);
                mbar_init(BAR(BAR_X + 4), 1);
                asm volatile("fence.mbarrier_init.release.cluster;" ::: "memory");
            }
            if (lane < 4) sts128(SM_GST + lane * 16, make_uint4(0, 0, 0, 0));
            __syncwarp();
            fence_async_smem();
            bar_arrive(0, 96);
            bar_arrive(5, 64);
            bar_arrive(4, 256 + 32 + 128);
            const uint4 z = make_uint4(0, 0, 0, 0);
#pragma unroll
            for (int i = 0; i < 2; i++) sts128(SM_ACT + (i * 16 + (lane >> 1)) * CH_PITCH + (lane & 1) * 16, z);
            if (lane < 4) sts128(SM_ACT + (2 + (lane >> 1)) * ROW_BYTES + (lane & 1) * 16, z);
            if (lane < 16) sts128(SM_ONES + lane * 16, make_uint4(lane < 8 ? 0x3f803f80u : 0u, 0, 0, 0));
            fence_async_smem();
            bar_arrive(7, 160);
            asm volatile("barrier.cluster.arrive.relaxed.aligned;" ::: "memory");
            while (clock32() - clk0 < W2DELAY) {}
            weight_load(v, w2, cta, lane);
        }
    if (warp == 0 || warp == 4) {
        const int k = warp >> 2;
#pragma unroll
        for (int i = 0; i < 5; i++)
            if (i < 4 || !(lane & 2)) sts128(SM_BNC + k * 2304 + (lane >> 2) * 288 + (lane & 3) * 16 + i * 64, v[i]);
        if (lane == 0) TL(k ? 14 : 81);
        __syncwarp();
        weight_block(SM_BNC + k * 2304, gs->wt + k * NSTAGE * STAGE_BYTES, cta, lane,
                     k ? &gs->wcnt[(NB + (lane & 1)) * LS] : &gs->w1cnt[((lane & 1) * 8 + (cta >> 4)) * KS]);
        if (lane == 0) TL(k ? 13 : 4);
    }

    if (warp >= 8) {
        const int nw = warp - 8;
        if (nw < 2) {
            const uint2 ga = __ldg(reinterpret_cast<const uint2*>(nw ? g2 : g1) + lane), bt = __ldg(reinterpret_cast<const uint2*>(nw ? be2 : be1) + lane);
            sts128f(SM_COEF + nw * 1024 + lane * 32, make_float4(0.5f * bf_lo(ga.x), 0.5f * bf_hi(ga.x), 0.5f * bf_lo(bt.x), 0.5f * bf_hi(bt.x)));
            sts128f(SM_COEF + nw * 1024 + lane * 32 + 16, make_float4(0.5f * bf_lo(ga.y), 0.5f * bf_hi(ga.y), 0.5f * bf_lo(bt.y), 0.5f * bf_hi(bt.y)));
        }
        bar_sync(4, 256 + 32 + 128);
        const int par = nw >> 2, wq = nw & 3;
        const uint32_t act_off = SM_ACT + (par * 4 + (lane >> 4)) * CH_PITCH + (2 + wq * 16 + (lane & 15)) * 16;
        const uint32_t stg_off = (par * 32 + (lane >> 4) * 8 + (lane & 7)) * 128 + (((2 * wq + ((lane >> 3) & 1)) ^ (lane & 7)) << 4);
        const uint32_t cfa = SM_COEF + par * 256 + (lane & 3) * 16;
        const uint32_t fbar = BAR(BAR_FULL) + 16 * par;
        uint4* inbox = gs->box + cta * 1024 + par * 256 + (tid & 127);
#pragma unroll 1
        for (int conv = 0; conv < 2; conv++) {
            uint32_t u[4][4], w[4][4];
            float4 cf[8];
            if (conv == 0) {
#pragma unroll
                for (int i = 0; i < 4; i++) {
                    if (!(i & 1)) mbar_wait(BAR(BAR_X + i) + 8 * par, 0);
                    ldsm4t(u[i], SM_XOWN + stg_off + unit_kc(i) * 2048);
                }
            } else {
                mbar_wait(BAR(BAR_HW), 0);
#pragma unroll
                for (int i = 0; i < 4; i++) ldsm4(u[i], act_off + unit_kc(i) * KC_BYTES);
            }
#pragma unroll
            for (int i = 0; i < 8; i++) cf[i] = lds128f(cfa + conv * 1024 + unit_kc(i >> 1) * 128 + (i & 1) * 64);
            const uint32_t gst = SM_GST + conv * 32 + par * 8;
            float z[4][8];
#pragma unroll
            for (int i = 0; i < 16; i++) {
                const float4& c = cf[i >> 1];
                z[i >> 2][2 * (i & 3)] = bf_lo(u[i >> 2][i & 3]) * c.x; z[i >> 2][2 * (i & 3) + 1] = bf_hi(u[i >> 2][i & 3]) * c.y;
                asm volatile("" : "+f"(z[i >> 2][2 * (i & 3)]), "+f"(z[i >> 2][2 * (i & 3) + 1]));
            }
            const float2 g0 = wait_stats(gst, make_float2(0.f, 0.f));
            if (tid == 256) TL(22 + conv * 4);
            if (par) { const unsigned c1 = clock32(); while (clock32() - c1 < PDELAY) {} }
            own_unit<0>(z[0], cf, g0, act_off);
            float2 g1;
            asm volatile("ld.volatile.shared.v2.f32 {%0,%1}, [%2];" : "=f"(g1.x), "=f"(g1.y) : "r"(gst + 16 + S0) : "memory");
            if (!par) publish(fbar, 1, lane);
            if (tid == 256) TL(8 + conv * 8);
            own_unit<1>(z[1], cf, g0, act_off);
            publish(fbar + (par ? 0 : 8), par ? 2 : 1, lane);
            g1 = wait_stats(gst + 16, g1);
            own_unit<2>(z[2], cf, g1, act_off);
            own_unit<3>(z[3], cf, g1, act_off);
            publish(fbar + 32, 2, lane);
#pragma unroll
            for (int i = 0; i < 8; i++) { const float rs = i < 4 ? g0.x : g1.x; cf[i].x *= rs; cf[i].y *= rs; }
            if (tid == 256) TL(84 + conv);
            if (has_outer) {
                mbar_wait(BAR(BAR_X + 4), conv);
                if (conv == 0) {
#pragma unroll
                    for (int i = 0; i < 4; i++) ldsm4t(w[i], SM_XOUT + stg_off + unit_kc(i) * 2048);
                } else {
#pragma unroll
                    for (int i = 0; i < 4; i++) {
                        const uint4 q = lds128(SM_XOWN + par * 4096 + (tid & 127) * 16 + unit_kc(i) * 2048);
                        w[i][0] = q.x; w[i][1] = q.y; w[i][2] = q.z; w[i][3] = q.w;
                    }
                    unsigned it = 0;
                    while (true) {
                        bool ok = true;
#pragma unroll
                        for (int i = 0; i < 16; i++) ok = ok && w[i >> 2][i & 3] != 0;
                        if (__all_sync(0xffffffffu, ok) || ++it > SPIN_LIMIT) break;
#pragma unroll
                        for (int i = 0; i < 4; i++) ld_unit(w[i], inbox + unit_kc(i) * 128);
                    }
#pragma unroll
                    for (int i = 0; i < 16; i++) w[i >> 2][i & 3] = ~w[i >> 2][i & 3];
                }
            }
            if (conv == 0) {
                bar_sync(3, 256);
                if (nw == 0) sts128(SM_ACT + 2 * ROW_BYTES + (lane >> 1) * CH_PITCH + (lane & 1) * 16, make_uint4(0, 0, 0, 0));
            }
            if (tid == 256) TL(24 + conv * 4);
            outer_pair<0>(w, cf, act_off + 2 * ROW_BYTES, has_outer ? ~0u : 0u, fbar + 128, lane);
            if (tid == 256) TL(88 + conv);
            outer_pair<2>(w, cf, act_off + 2 * ROW_BYTES, has_outer ? ~0u : 0u, fbar + 128, lane);
            if (tid == 256) TL(23 + conv * 4);
        }
        if (has_outer) {
            mbar_wait(BAR(BAR_FULL + NSTAGE - 1), 1);
#pragma unroll
            for (int i = 0; i < 4; i++) inbox[unit_kc(i) * 128] = make_uint4(0, 0, 0, 0);
        }
        {
            const int oc0 = par * 64 + ((tid & 127) >> 3), seg = lane & 7;
            __nv_bfloat16* dst = out + ((size_t)(b * C + oc0) * HW + r) * HW + seg * 8;
            const uint32_t src = SM_XOWN + oc0 * 128 + ((seg ^ (oc0 & 7)) << 4);
            asm volatile("{\n.reg .pred p;\nsetp.eq.u64 p, %0, 0;\n@p st.shared.u32 [%1], 0;\n}" ::"l"(dst), "r"(src + S0) : "memory");
            bar_sync(par ? 1 : 6, 128 + 128);
#pragma unroll
            for (int i = 0; i < 4; i++) *reinterpret_cast<uint4*>(dst + (size_t)i * 16 * HW * HW) = lds128(src + i * 2048);
            if (tid == 384) { TL(20); TLG(21); }
        }
    } else if (warp < 4) {
        const int wq = warp;
        bar_sync(7, 160);

        const uint32_t xbase = SM_XOWN + ((lane >> 4) * 8 + (lane & 7)) * 128 + (((2 * wq + ((lane >> 3) & 1)) ^ (lane & 7)) << 4);
        float d[64];
#pragma unroll
        for (int i = 0; i < 64; i++) d[i] = 0.f;
#pragma unroll 1
        for (int conv = 0; conv < 2; conv++) {
            fence_acc(d);
            mma_stages<0>(d, conv, tid, gs);
            if (conv == 0) {
                asm volatile("wgmma.fence.sync.aligned;" ::: "memory");
                wgmma128<(SM_ONES >> 4) | (8u << 16), (SM_EMB >> 4), 0, 8>(d);
                asm volatile("wgmma.commit_group.sync.aligned;" ::: "memory");
            }
            asm volatile("wgmma.wait_group.sync.aligned 0;" ::: "memory");
            fence_acc(d);
            if (tid == 0) TL(10 + conv * 8);
            if (conv == 1) {
                fence_acc(d);
#pragma unroll
                for (int kc = 0; kc < 8; kc++) {
                    stsm4t(xbase + kc * 2048, pack_bf(d[8 * kc], d[8 * kc + 1]), pack_bf(d[8 * kc + 2], d[8 * kc + 3]),
                           pack_bf(d[8 * kc + 4], d[8 * kc + 5]), pack_bf(d[8 * kc + 6], d[8 * kc + 7]));
                    if (kc == 3) bar_arrive(6, 128 + 128);
                }
                bar_arrive(1, 128 + 128);
                if (tid == 0) TL(5);
                break;
            }
            uint32_t hp[32];
#pragma unroll
            for (int i = 0; i < 32; i++) hp[i] = pack_bf(d[2 * i], d[2 * i + 1]);
#pragma unroll
            for (int g = 0; g < 4; g++) {
                float c[4] = {0.f, 0.f, 0.f, 0.f};
#pragma unroll
                for (int i = 0; i < 4; i++) stat_mma(c, hp[8 * g + 2 * i], hp[8 * g + 2 * i + 1]);
                stat_store(c, SM_RED + (g * 4 + wq) * 48, lane);
            }
            bar_sync(2, 128);
            if (wq == 0) stat_publish(SM_RED, &gs->acc2[b * LS], lane, true);
            if (tid == 0) TL(11);
            const uint32_t hbase = SM_ACT + (lane >> 4) * CH_PITCH + (2 + wq * 16 + (lane & 15)) * 16;
#pragma unroll
            for (int kc = 0; kc < 8; kc++) stsm4(hbase + kc * 2 * CH_PITCH, hp[4 * kc], hp[4 * kc + 1], hp[4 * kc + 2], hp[4 * kc + 3]);
            __syncwarp();
            if (lane == 0) mbar_arrive(BAR(BAR_HW));
            if (lane < LAG) mbar_arrive(BAR(BAR_WEMPTY + (NSTAGE - LAG) % NS) + 8 * lane);
            if (has_outer) {
                uint4* outbox = gs->box + (cta + ((r & 1) ? 1 : -1)) * 1024 + tid;
#pragma unroll
                for (int kc = 0; kc < 8; kc++) outbox[kc * 128] = make_uint4(~hp[4 * kc], ~hp[4 * kc + 1], ~hp[4 * kc + 2], ~hp[4 * kc + 3]);
            }
            if (tid == 0) TL(12);
#pragma unroll
            for (int kc = 0; kc < 8; kc++) {
                uint32_t p[4];
                ldsm4t(p, xbase + kc * 2048);
#pragma unroll
                for (int i = 0; i < 4; i++) { d[8 * kc + 2 * i] = bf_lo(p[i]); d[8 * kc + 2 * i + 1] = bf_hi(p[i]); }
            }
            fence_async_smem();
            __syncwarp();
            if (lane == 0) mbar_arrive(BAR(BAR_XFREE));
        }
        {
        }
    } else if (warp < 6) {
        if (warp == 5) {
            bar_sync(5, 64);
            mbar_wait(BAR(BAR_FULL), 0);
            if (has_outer && elect_one()) {
                mbar_expect(BAR(BAR_X + 4), 16384);
#pragma unroll
                for (int i = 0; i < 4; i++) tma_x(SM_XOUT + i * 4096, &xmap, r + ((r & 1) ? 1 : -1), b * C + i * 32, BAR(BAR_X + 4));
            }
            __syncwarp();
            asm volatile("barrier.cluster.wait.acquire.aligned;" ::: "memory");
            const uint32_t peer = (r & 1) ^ 1;
            const uint32_t self0 = mapa(0, r & 1), peer0 = mapa(0, peer);
#pragma unroll 1
            for (int conv = 0; conv < 2; conv++) {
#pragma unroll 1
                for (int kc = 0; kc < 8; kc++) {
                    mbar_wait(BAR(BAR_FULL) + 8 * kc, conv);
                    if (elect_one())
                        asm volatile("cp.async.bulk.shared::cluster.shared::cta.mbarrier::complete_tx::bytes [%0], [%1], %2, [%3];"
                                     ::"r"(peer0 + SM_ACT + ROW_BYTES + kc * KC_BYTES), "r"(self0 + SM_ACT + kc * KC_BYTES), "r"(KC_BYTES),
                                       "r"(peer0 + BAR(BAR_FULL + 8) + 8 * kc) : "memory");
                }
                if (lane == 0) TL(86 + conv);
#pragma unroll 1
                for (int kc = 0; kc < 8; kc++) mbar_wait(BAR(BAR_FULL + 8) + 8 * kc, conv);
                if (lane == 0)
                    asm volatile("mbarrier.arrive.relaxed.cluster.shared::cluster.b64 _, [%0];" ::"r"(peer0 + (conv ? BAR(BAR_ACK) : BAR(BAR_EMB))) : "memory");
            }
            mbar_wait(BAR(BAR_ACK), 0);
        } else {
            mbar_wait(BAR(BAR_STATS), 0);
            unsigned it = 0;
            while (!__all_sync(0xffffffffu, ld_relaxed(&gs->wcnt[(2 * NB + b) * LS]) >= (unsigned)NXTRA) && ++it < SPIN_LIMIT) __nanosleep(100);
            fence_acquire();
            float ev[4] = {0.f, 0.f, 0.f, 0.f};
#pragma unroll
            for (int j = 0; j < NXTRA; j++) {
                const uint4 ef = ld_relaxed_v4(&gs->emb[(j * NB + b) * C + lane * 4]);
                ev[0] += __uint_as_float(ef.x); ev[1] += __uint_as_float(ef.y); ev[2] += __uint_as_float(ef.z); ev[3] += __uint_as_float(ef.w);
            }
#pragma unroll
            for (int i = 0; i < 4; i++) {
                const float hi = bf_lo(pack_bf(ev[i], 0.f));
                sts128(SM_EMB + (lane * 4 + i) * 16, make_uint4(pack_bf(hi, ev[i] - hi), 0, 0, 0));
            }
            fence_async_smem();
            __syncwarp();
            if (lane == 0) { mbar_arrive(BAR(BAR_EMB)); TL(19); }
        }
    } else if (warp == 6) {
        bar_sync(0, 96);
        const uint32_t ebytes = STAGE_BYTES + ((lane >> 3) == 1 ? KC_BYTES : 0);
        if (lane < NSTAGE) mbar_expect(BAR(BAR_FULL) + 8 * lane, ebytes);
        const int swap = (r & 1) ? 0 : 8 * STAGE_BYTES;
        unsigned it = 0;
        {
            int g = 0;
            const unsigned* cnt = &gs->w1cnt[(b * 8 + (lane & 7)) * KS];
            unsigned cv = ld_relaxed(cnt);
#pragma unroll 1
            while (g < NS) {
                unsigned ready = __ballot_sync(0xffffffffu, (lane < 8 ? cv & 0xffffu : cv >> 16) >= 16u);
                if ((ready >> 8 & 0xff) != 0xff) ready &= 0xff;
                if (ready != ~0u) cv = ld_relaxed(cnt);
                ready >>= g;
                if (++it > SPIN_LIMIT) ready = ~0u;
                if (!(ready & 1)) continue;
                fence_async_global();
                if (lane == 0) TL(g ? 3 : 6);
#pragma unroll 1
                for (; (ready & 1) && g < NS; g++, ready >>= 1)
                    if (elect_one())
                        bulk_g2s(S0 + SM_W + g * STAGE_BYTES, gs->wt + g * STAGE_BYTES + (g >= 8 ? swap : 0), STAGE_BYTES, S0 + BAR(BAR_FULL) + 8 * g);
            }
        }
#pragma unroll 1
        for (int q = 3; q < 12; q++) {
            const int conv = q >= 6, qs = conv ? q - 6 : q, sl = q % 3;
            const unsigned char* wsrc = gs->wt + q * 4 * STAGE_BYTES + (qs < 2 ? 0 : (qs < 4 ? swap : -swap));
            const uint32_t par = (q / 3 - 1) & 1;
            if (q == 6) {
                it = 0;
                while (!__all_sync(0xffffffffu, ld_relaxed(&gs->wcnt[(NB + b) * LS]) == NCTA * 0x10001u) && ++it < SPIN_LIMIT) {}
                fence_acquire();
                fence_async_global();
                if (lane == 0) { mbar_arrive(BAR(BAR_EMB)); TL(2); }
            }
#pragma unroll
            for (int i = 0; i < 4; i++) {
                mbar_wait(BAR(BAR_WEMPTY + i) + 32 * sl, par);
                if (i == 0 && (q == 6 || q == 9)) {
                    if ((lane >= NS) == (q == 9) && lane < NSTAGE) mbar_expect(BAR(BAR_FULL) + 8 * lane, ebytes);
                    __syncwarp();
                }
                if (elect_one())
                    bulk_g2s(S0 + SM_W + (sl * 4 + i) * STAGE_BYTES, wsrc + i * STAGE_BYTES, STAGE_BYTES, S0 + BAR(BAR_FULL + i) + 32 * qs);
            }
        }
    } else {
        bar_sync(0, 96);
#pragma unroll 1
        for (int conv = 0; conv < 2; conv++) {
            if (conv == 1) mbar_wait(BAR(BAR_HW), 0);
            const float* asrc = (conv ? gs->acc2 : gs->acc1) + b * LS + (lane & 3) * 4;
            unsigned it = 0;
#pragma unroll 1
            while (true) {
                const uint4 f = ld_relaxed_v4(asrc);
                const bool ok = ((f.x == 0x42800000u) & (f.w == 0x42800000u)) || ++it > SPIN_LIMIT;
                if (ok && lane < 4) {
                    const float inv_n = 1.0f / (32.0f * HW * HW);
                    const float mean = __uint_as_float(f.y) * inv_n;
                    float rs;
                    asm("rsqrt.approx.ftz.f32 %0, %1;" : "=f"(rs) : "f"(fmaxf(fmaf(-mean, mean, __uint_as_float(f.z) * inv_n), 0.f) + 1e-5f));
                    asm volatile("st.shared.v2.f32 [%0], {%1,%2};" ::"r"(S0 + SM_GST + conv * 32 + lane * 8), "f"(rs == 0.f ? 1.2e-38f : rs), "f"(mean * rs) : "memory");
                }
                if (__all_sync(0xffffffffu, ok)) break;
            }
            if (lane == 0) { mbar_arrive(BAR(BAR_STATS)); TL(7 + conv * 8); }
        }
        mbar_wait(BAR(BAR_XFREE), 0);
        if (has_outer && elect_one()) {
            mbar_expect(BAR(BAR_X + 4), 16384);
            bulk_g2s(S0 + SM_XOWN, gs->box + cta * 1024, 16384, S0 + BAR(BAR_X + 4));
        }
        if (r == 0) {
            if (lane < 16) gs->acc1[b * LS + lane] = 0.f;
            if (lane < 3) gs->wcnt[(lane * NB + b) * LS] = 0;
            if (lane < 8) gs->w1cnt[(b * 8 + lane) * KS] = 0;
        }
    }
}

}

extern "C" void kernel_launch(void* const* d_in, const int* in_sizes, int n_in, void* d_out, int out_size) {
    (void)in_sizes; (void)n_in; (void)out_size;
    typedef CUresult (*EncodeFn)(CUtensorMap*, CUtensorMapDataType, cuuint32_t, void*, const cuuint64_t*, const cuuint64_t*,
                                 const cuuint32_t*, const cuuint32_t*, CUtensorMapInterleave, CUtensorMapSwizzle,
                                 CUtensorMapL2promotion, CUtensorMapFloatOOBfill);
    static Scratch* gs = nullptr;
    static EncodeFn encode = nullptr;
    if (!gs) {
        cudaFuncSetAttribute(resblock_kernel, cudaFuncAttributeMaxDynamicSharedMemorySize, SM_TOTAL);
        cudaGetSymbolAddress((void**)&gs, g_scratch);
        cudaDriverEntryPointQueryResult qr;
        cudaGetDriverEntryPoint("cuTensorMapEncodeTiled", (void**)&encode, cudaEnableDefault, &qr);
    }
    CUtensorMap xmap;
    const cuuint64_t dims[3] = {HW, HW, NB * C}, strides[2] = {HW * 2, HW * HW * 2};
    const cuuint32_t box[3] = {HW, 1, 32}, es[3] = {1, 1, 1};
    encode(&xmap, CU_TENSOR_MAP_DATA_TYPE_BFLOAT16, 3, d_in[0], dims, strides, box, es, CU_TENSOR_MAP_INTERLEAVE_NONE,
           CU_TENSOR_MAP_SWIZZLE_128B, CU_TENSOR_MAP_L2_PROMOTION_NONE, CU_TENSOR_MAP_FLOAT_OOB_FILL_NONE);
    resblock_kernel<<<NCTA + NXTRA, NTHREADS, SM_TOTAL>>>(
        (const __nv_bfloat16*)d_in[4], (const __nv_bfloat16*)d_in[0], (const __nv_bfloat16*)d_in[1],
        (const __nv_bfloat16*)d_in[2], (const __nv_bfloat16*)d_in[3], (const __nv_bfloat16*)d_in[5],
        (const __nv_bfloat16*)d_in[6], (const __nv_bfloat16*)d_in[7], (const __nv_bfloat16*)d_in[8],
        (__nv_bfloat16*)d_out, gs, xmap);
}
```

```cpp
#include <cuda_runtime.h>
#include <cuda.h>
#include <cuda_bf16.h>
#include <stdint.h>

namespace {

constexpr int C = 128, HW = 64, NB = 2, E = 768;
constexpr int NCTA = NB * HW;
constexpr int NXTRA = 4;
constexpr int NTHREADS = 16 * 32;
constexpr int CH_PITCH = 66 * 16;
constexpr int ROW_BYTES = 16 * CH_PITCH;
constexpr int STAGE_BYTES = 12288;
constexpr int NSTAGE = 24;
constexpr int KC_BYTES = 2 * CH_PITCH;
constexpr int NS = 12;
constexpr int LAG = 1;
#define XDELAY 300
#define XSTAG 800
#define XSTAG2 300
#define SDELAY 600
#define W2DELAY 2400
constexpr int NLDG = 2;

constexpr uint32_t SMEM_BASE = 0x400;
constexpr uint32_t SM_XOWN = SMEM_BASE;
constexpr uint32_t SM_ACT = SM_XOWN + 16384 + 512;
constexpr uint32_t SM_XOUT = SM_ACT + 2 * ROW_BYTES + 512;
static_assert(SM_XOUT % 1024 == 0, "swizzle atom alignment");
constexpr uint32_t SM_W = SM_ACT + 3 * ROW_BYTES + 128;
__host__ __device__ constexpr uint32_t slot_addr(int slot) { return SM_W + slot * STAGE_BYTES; }
constexpr uint32_t SM_COEF = SM_W + NS * STAGE_BYTES;
constexpr uint32_t SM_GST = SM_COEF + 2048;
constexpr uint32_t SM_EMB = SM_GST + 128;
constexpr uint32_t SM_ONES = SM_EMB + 2048;
constexpr uint32_t SM_RED = SM_ONES + 256;
constexpr uint32_t SM_BNC = SM_RED + 1536;
constexpr uint32_t SM_BAR = SM_BNC + 2 * 2304;
constexpr int BAR_FULL = 0, BAR_WEMPTY = NSTAGE, BAR_HW = BAR_WEMPTY + NS, BAR_XFREE = BAR_HW + 1, BAR_STATS = BAR_XFREE + 1,
              BAR_EMB = BAR_STATS + 1, BAR_ACK = BAR_EMB + 1, BAR_X = BAR_ACK + 1  , NBAR = BAR_X + 5;
constexpr int SM_TOTAL = SM_BAR + NBAR * 8 - SMEM_BASE;
static_assert(SM_TOTAL <= 232448, "smem");
__host__ __device__ constexpr uint32_t BAR(int i) { return SM_BAR + 8 * i; }
__host__ __device__ constexpr int ky_of(int kyo) { return kyo == 0 ? 1 : (kyo == 1 ? 0 : 2); }

constexpr unsigned SPIN_LIMIT = 1u << 16;

constexpr int LS = 1056, KS = 32;
struct Scratch {
    float acc1[NB * LS];
    float acc2[NB * LS];
    unsigned wcnt[3 * NB * LS];
    unsigned w1cnt[NB * 8 * KS];
    float emb[NXTRA * NB * C];
    alignas(1024) unsigned char wt[2 * NSTAGE * STAGE_BYTES];
    uint4 box[NCTA * 1024];
};
__device__ __align__(1024) Scratch g_scratch;
#define TL(i) do {} while (0)
#define TLG(i) do {} while (0)

__device__ __forceinline__ unsigned clock32() { unsigned c; asm volatile("mov.u32 %0, %%clock;" : "=r"(c)); return c; }
__device__ __forceinline__ uint32_t mapa(uint32_t a, uint32_t rank) {
    uint32_t d;
    asm("mapa.shared::cluster.u32 %0, %1, %2;" : "=r"(d) : "r"(a), "r"(rank));
    return d;
}
#define S0 mapa(0, blockIdx.x & 1)
__device__ __forceinline__ void mbar_init(uint32_t bar, int cnt) {
    asm volatile("mbarrier.init.shared::cta.b64 [%0], %1;" ::"r"(bar + S0), "r"(cnt) : "memory");
}
__device__ __forceinline__ void mbar_arrive(uint32_t bar) {
    asm volatile("mbarrier.arrive.shared::cta.b64 _, [%0];" ::"r"(bar + S0) : "memory");
}
__device__ __forceinline__ void mbar_expect(uint32_t bar, uint32_t bytes) {
    asm volatile("mbarrier.arrive.expect_tx.shared::cta.b64 _, [%0], %1;" ::"r"(bar + S0), "r"(bytes) : "memory");
}
__device__ __forceinline__ bool mbar_try(uint32_t bar, uint32_t par) {
    uint32_t ok;
    asm volatile("{\n.reg .pred p;\nmbarrier.try_wait.parity.shared::cta.b64 p, [%1], %2;\nselp.u32 %0, 1, 0, p;\n}"
                 : "=r"(ok) : "r"(bar + S0), "r"(par) : "memory");
    return ok;
}
__device__ __forceinline__ bool mbar_test(uint32_t bar, uint32_t par) {
    uint32_t ok;
    asm volatile("{\n.reg .pred p;\nmbarrier.test_wait.parity.shared::cta.b64 p, [%1], %2;\nselp.u32 %0, 1, 0, p;\n}"
                 : "=r"(ok) : "r"(bar + S0), "r"(par) : "memory");
    return ok;
}
__device__ __forceinline__ void mbar_wait(uint32_t bar, uint32_t par) {
    unsigned it = 0;
#pragma unroll 1
    while (!mbar_try(bar, par) && ++it < SPIN_LIMIT) {}
}
__device__ __forceinline__ bool elect_one() {
    uint32_t p;
    asm volatile("{\n.reg .pred p;\nelect.sync _|p, 0xffffffff;\nselp.u32 %0, 1, 0, p;\n}" : "=r"(p));
    return p;
}
__device__ __forceinline__ void fence_async_smem() { asm volatile("fence.proxy.async.shared::cta;" ::: "memory"); }
__device__ __forceinline__ void fence_async_global() { asm volatile("fence.proxy.async.global;" ::: "memory"); }
__device__ __forceinline__ void fence_acquire() { asm volatile("fence.acquire.gpu;" ::: "memory"); }
__device__ __forceinline__ void bar_sync(int id, int n) { asm volatile("bar.sync %0, %1;" ::"r"(id), "r"(n) : "memory"); }
__device__ __forceinline__ void bar_arrive(int id, int n) { asm volatile("bar.arrive %0, %1;" ::"r"(id), "r"(n) : "memory"); }
__device__ __forceinline__ void bulk_g2s(uint32_t dst, const void* src, uint32_t bytes, uint32_t bar) {
    asm volatile("cp.async.bulk.shared::cluster.global.mbarrier::complete_tx::bytes [%0], [%1], %2, [%3];"
                 ::"r"(dst), "l"(src), "r"(bytes), "r"(bar) : "memory");
}
__device__ __forceinline__ void tma_x(uint32_t dst, const CUtensorMap* tm, int row, int ch, uint32_t bar) {
    asm volatile("cp.async.bulk.tensor.3d.shared::cluster.global.mbarrier::complete_tx::bytes [%0], [%1, {%2, %3, %4}], [%5];"
                 ::"r"(dst + S0), "l"(tm), "r"(0), "r"(row), "r"(ch), "r"(bar + S0) : "memory");
}
__device__ __forceinline__ uint4 ld_relaxed_v4(const void* p) {
    uint4 v;
    asm volatile("ld.relaxed.gpu.global.v4.u32 {%0,%1,%2,%3}, [%4];" : "=r"(v.x), "=r"(v.y), "=r"(v.z), "=r"(v.w) : "l"(p) : "memory");
    return v;
}
__device__ __forceinline__ unsigned ld_relaxed(const void* p) {
    unsigned v;
    asm volatile("ld.relaxed.gpu.global.u32 %0, [%1];" : "=r"(v) : "l"(p) : "memory");
    return v;
}
__device__ __forceinline__ void red_add4(float* p, float a, float b, float c, float d) {
    asm volatile("red.relaxed.gpu.global.add.v4.f32 [%0], {%1,%2,%3,%4};" ::"l"(p), "f"(a), "f"(b), "f"(c), "f"(d) : "memory");
}
__device__ __forceinline__ void sts128(uint32_t a, uint4 v) {
    asm volatile("st.shared.v4.u32 [%0], {%1,%2,%3,%4};" ::"r"(a + S0), "r"(v.x), "r"(v.y), "r"(v.z), "r"(v.w) : "memory");
}
__device__ __forceinline__ void sts128f(uint32_t a, float4 v) {
    asm volatile("st.shared.v4.f32 [%0], {%1,%2,%3,%4};" ::"r"(a + S0), "f"(v.x), "f"(v.y), "f"(v.z), "f"(v.w) : "memory");
}
__device__ __forceinline__ void sts32f(uint32_t a, float v) { asm volatile("st.shared.f32 [%0], %1;" ::"r"(a + S0), "f"(v) : "memory"); }
__device__ __forceinline__ uint4 lds128(uint32_t a) {
    uint4 v;
    asm volatile("ld.shared.v4.u32 {%0,%1,%2,%3}, [%4];" : "=r"(v.x), "=r"(v.y), "=r"(v.z), "=r"(v.w) : "r"(a + S0) : "memory");
    return v;
}
__device__ __forceinline__ float4 lds128f(uint32_t a) {
    float4 v;
    asm volatile("ld.shared.v4.f32 {%0,%1,%2,%3}, [%4];" : "=f"(v.x), "=f"(v.y), "=f"(v.z), "=f"(v.w) : "r"(a + S0) : "memory");
    return v;
}
__device__ __forceinline__ float2 lds64f(uint32_t a) {
    float2 v;
    asm volatile("ld.shared.v2.f32 {%0,%1}, [%2];" : "=f"(v.x), "=f"(v.y) : "r"(a + S0) : "memory");
    return v;
}
__device__ __forceinline__ float bf_lo(uint32_t u) { return __uint_as_float(u << 16); }
__device__ __forceinline__ float bf_hi(uint32_t u) { return __uint_as_float(u & 0xffff0000u); }
__device__ __forceinline__ uint32_t pack_bf(float lo, float hi) {
    uint32_t r;
    asm("cvt.rn.bf16x2.f32 %0, %1, %2;" : "=r"(r) : "f"(hi), "f"(lo));
    return r;
}
__device__ __forceinline__ float tanh_fast(float x) {
    float r;
    asm("tanh.approx.f32 %0, %1;" : "=f"(r) : "f"(x));
    return r;
}
__device__ __forceinline__ float silu_half(float h) { return fmaf(h, tanh_fast(h), h); }
__device__ __forceinline__ void ldsm4(uint32_t (&u)[4], uint32_t a) {
    asm volatile("ldmatrix.sync.aligned.m8n8.x4.shared.b16 {%0,%1,%2,%3}, [%4];"
                 : "=r"(u[0]), "=r"(u[1]), "=r"(u[2]), "=r"(u[3]) : "r"(a + S0) : "memory");
}
__device__ __forceinline__ void ldsm4t(uint32_t (&u)[4], uint32_t a) {
    asm volatile("ldmatrix.sync.aligned.m8n8.x4.trans.shared.b16 {%0,%1,%2,%3}, [%4];"
                 : "=r"(u[0]), "=r"(u[1]), "=r"(u[2]), "=r"(u[3]) : "r"(a + S0) : "memory");
}
__device__ __forceinline__ void stsm4(uint32_t a, uint32_t p0, uint32_t p1, uint32_t p2, uint32_t p3) {
    asm volatile("stmatrix.sync.aligned.m8n8.x4.shared.b16 [%0], {%1,%2,%3,%4};" ::"r"(a + S0), "r"(p0), "r"(p1), "r"(p2), "r"(p3) : "memory");
}
__device__ __forceinline__ void stsm4t(uint32_t a, uint32_t p0, uint32_t p1, uint32_t p2, uint32_t p3) {
    asm volatile("stmatrix.sync.aligned.m8n8.x4.trans.shared.b16 [%0], {%1,%2,%3,%4};" ::"r"(a + S0), "r"(p0), "r"(p1), "r"(p2), "r"(p3) : "memory");
}

#define R8(o) "+f"(d[o]), "+f"(d[o + 1]), "+f"(d[o + 2]), "+f"(d[o + 3]), "+f"(d[o + 4]), "+f"(d[o + 5]), "+f"(d[o + 6]), "+f"(d[o + 7])
template <uint32_t ALO, uint32_t BLO, uint64_t AHI = 8, uint64_t BHI = 48>
__device__ __forceinline__ void wgmma128(float (&d)[64]) {
    asm volatile(
        "wgmma.mma_async.sync.aligned.m64n128k16.f32.bf16.bf16 "
        "{%0,%1,%2,%3,%4,%5,%6,%7,%8,%9,%10,%11,%12,%13,%14,%15,%16,%17,%18,%19,%20,%21,%22,%23,%24,%25,%26,%27,%28,%29,%30,%31,"
        "%32,%33,%34,%35,%36,%37,%38,%39,%40,%41,%42,%43,%44,%45,%46,%47,%48,%49,%50,%51,%52,%53,%54,%55,%56,%57,%58,%59,%60,%61,%62,%63},"
        " %64, %65, 1, 1, 1, 0, 0;"
        : R8(0), R8(8), R8(16), R8(24), R8(32), R8(40), R8(48), R8(56)
        : "l"((AHI << 32) | ALO), "l"((BHI << 32) | BLO));
}
template <int S>
__device__ __forceinline__ void mma_stages(float (&d)[64], int conv, int tid, Scratch* gs) {
    constexpr uint32_t A = ((SM_ACT + S * 2 * CH_PITCH + 16) >> 4) | ((CH_PITCH >> 4) << 16);
    constexpr uint32_t B = (slot_addr(S % NS) >> 4) | (8u << 16);
    if (S == 0) mbar_wait(BAR(BAR_FULL), conv);
    bool next_ok = true;
    constexpr uint32_t NEXT = S + 1 < NSTAGE ? BAR(BAR_FULL + S + 1) : BAR(BAR_EMB);
    const int npar = S + 1 < NSTAGE ? conv : 0;
    next_ok = mbar_test(NEXT, npar);
    if (S == 0 && tid == 0) TL(32 + conv * 24);
    asm volatile("wgmma.fence.sync.aligned;" ::: "memory");
    wgmma128<A, B>(d);
    wgmma128<A + 1, B + 16>(d);
    wgmma128<A + 2, B + 32>(d);
    asm volatile("wgmma.commit_group.sync.aligned;" ::: "memory");
    if (S >= LAG) {
        asm volatile("wgmma.wait_group.sync.aligned %0;" ::"n"(LAG) : "memory");
        if ((tid & 31) == 0) mbar_arrive(BAR(BAR_WEMPTY + (S + NS - LAG) % NS));
    }
    if (!next_ok) mbar_wait(NEXT, npar);
    if constexpr (S + 1 < NSTAGE) mma_stages<S + 1>(d, conv, tid, gs);
}

__device__ __forceinline__ void weight_load(uint4 (&t)[5], const __nv_bfloat16* w, int cta, int lane) {
    const char* base = reinterpret_cast<const char*>(w) + (uint32_t)((((cta & 15) * 8 + (lane >> 2)) * 8 + (cta >> 4)) * 288 + (lane & 3) * 16);
#pragma unroll
    for (int k = 0; k < 5; k++)
        if (k < 4 || !(lane & 2)) t[k] = __ldg(reinterpret_cast<const uint4*>(base + k * 64));
}
__device__ __forceinline__ void weight_block(uint32_t bounce, unsigned char* wt, int cta, int lane, unsigned* cnt) {
    const unsigned opaque_one = gridDim.y;
    unsigned char* piece = wt + (cta >> 4) * STAGE_BYTES + (cta & 15) * 768;
    uint32_t v[18];
#pragma unroll
    for (int i = 0; i < 9; i++) {
        const float2 q = lds64f(bounce + (lane & 7) * 288 + (lane >> 3) * 72 + i * 8);
        v[2 * i] = __float_as_uint(q.x); v[2 * i + 1] = __float_as_uint(q.y);
    }
    unsigned char* dst = piece + (lane >> 4) * 128 + (lane & 7) * 16 + ((lane >> 3) & 1) * 8;
    unsigned rb[3];
#pragma unroll
    for (int kyo = 0; kyo < 3; kyo++) {
#pragma unroll
        for (int kx = 0; kx < 3; kx++) {
            const int tap = ky_of(kyo) * 3 + kx;
            uint32_t o[2];
#pragma unroll
            for (int m = 0; m < 2; m++) {
                const int i0 = 18 * m + tap, i1 = i0 + 9;
                o[m] = __byte_perm(v[i0 >> 1], v[i1 >> 1], ((i0 & 1) ? 0x32u : 0x10u) | ((i1 & 1) ? 0x7600u : 0x5400u));
            }
            asm volatile("st.relaxed.gpu.global.v2.u32 [%0], {%1,%2};" ::"l"(dst + kyo * 8 * STAGE_BYTES + kx * 256), "r"(o[0]), "r"(o[1]) : "memory");
        }
        rb[kyo] = ld_relaxed(piece + kyo * 8 * STAGE_BYTES + (lane < 24 ? lane : 0) * 32);
    }
    const unsigned i0 = __any_sync(0xffffffffu, rb[0] == 0x9e3779b9u) ? opaque_one : 1u;
    if (lane < 2) asm volatile("red.relaxed.gpu.global.add.u32 [%0], %1;" ::"l"(cnt), "r"(i0) : "memory");
    const unsigned i1 = __any_sync(0xffffffffu, (rb[1] ^ rb[2]) == 0x9e3779b9u) ? opaque_one : 1u;
    if (lane < 2) asm volatile("red.relaxed.gpu.global.add.u32 [%0], %1;" ::"l"(cnt), "r"(i1 << 16) : "memory");
}
__device__ __forceinline__ uint32_t act2(uint32_t u, const float4& cf) {
    return pack_bf(silu_half(fmaf(bf_lo(u), cf.x, cf.z)), silu_half(fmaf(bf_hi(u), cf.y, cf.w)));
}
__device__ __forceinline__ void norm_unit(uint32_t (&u)[4], const float4& ca, const float4& cb) {
    u[0] = act2(u[0], ca); u[1] = act2(u[1], ca); u[2] = act2(u[2], cb); u[3] = act2(u[3], cb);
}
__device__ __forceinline__ float2 wait_stats(uint32_t slot, float2 g) {
    unsigned it = 0;
#pragma unroll 1
    while (!__all_sync(0xffffffffu, g.x != 0.f) && ++it < 8 * SPIN_LIMIT)
        asm volatile("ld.volatile.shared.v2.f32 {%0,%1}, [%2];" : "=f"(g.x), "=f"(g.y) : "r"(slot + S0) : "memory");
    return g;
}
__host__ __device__ constexpr int unit_kc(int t) { return (t & 1) + 4 * (t >> 1); }
template <int T>
__device__ __forceinline__ void own_unit(const float (&z)[8], float4 (&cf)[8], float2 g, uint32_t act) {
    float4 &ca = cf[2 * T], &cb = cf[2 * T + 1];
    ca.z = fmaf(-g.y, ca.x, ca.z); ca.w = fmaf(-g.y, ca.y, ca.w);
    cb.z = fmaf(-g.y, cb.x, cb.z); cb.w = fmaf(-g.y, cb.y, cb.w);
    uint32_t o[4];
#pragma unroll
    for (int i = 0; i < 4; i++)
        o[i] = pack_bf(silu_half(fmaf(z[2 * i], g.x, i < 2 ? ca.z : cb.z)), silu_half(fmaf(z[2 * i + 1], g.x, i < 2 ? ca.w : cb.w)));
    stsm4(act + unit_kc(T) * KC_BYTES, o[0], o[1], o[2], o[3]);
}
__device__ __forceinline__ void publish(uint32_t bar, int n, int lane) {
    fence_async_smem();
    __syncwarp();
    if (lane < n) mbar_arrive(bar + 8 * lane);
}
template <int FIRST>
__device__ __forceinline__ void outer_pair(uint32_t (&u)[4][4], const float4 (&cf)[8], uint32_t act, uint32_t mask, uint32_t fbar, int lane) {
#pragma unroll
    for (int t = FIRST; t < FIRST + 2; t++) {
        norm_unit(u[t], cf[2 * t], cf[2 * t + 1]);
        stsm4(act + unit_kc(t) * KC_BYTES, u[t][0] & mask, u[t][1] & mask, u[t][2] & mask, u[t][3] & mask);
    }
    publish(fbar + 8 * unit_kc(FIRST), 2, lane);
}
__device__ __forceinline__ void stat_mma(float (&c)[4], uint32_t p, uint32_t q) {
    asm("mma.sync.aligned.m16n8k16.row.col.f32.bf16.bf16.f32 {%0,%1,%2,%3}, {%4,%5,%6,%5}, {%4,%6}, {%0,%1,%2,%3};"
        : "+f"(c[0]), "+f"(c[1]), "+f"(c[2]), "+f"(c[3]) : "r"(p), "r"(0x3f803f80u), "r"(q));
}
__device__ __forceinline__ void stat_store(const float (&c)[4], uint32_t dst, int lane) {
    const int g = lane >> 2, t = lane & 3;
    if (t == (g >> 1)) sts32f(dst + g * 4, (g & 1) ? c[1] : c[0]);
    if (g == 7) sts32f(dst + 32 + t * 4, c[2] + c[3]);
}
__device__ __forceinline__ float sum4(float4 v) { return (v.x + v.y) + (v.z + v.w); }
__device__ __forceinline__ void stat_publish(uint32_t src, float* acc, int lane, bool real) {
    const uint32_t a = src + (lane & 15) * 48;
    float q = sum4(lds128f(a)) + sum4(lds128f(a + 16)), sm = sum4(lds128f(a + 32));
    q += __shfl_xor_sync(0xffffffffu, q, 1); sm += __shfl_xor_sync(0xffffffffu, sm, 1);
    q += __shfl_xor_sync(0xffffffffu, q, 2); sm += __shfl_xor_sync(0xffffffffu, sm, 2);
    if (real && (lane & 19) == 0) red_add4(acc + lane, 1.f, sm, q, 1.f);
}
__device__ __forceinline__ void fence_acc(float (&d)[64]) {
#pragma unroll
    for (int i = 0; i < 64; i++) asm volatile("" : "+f"(d[i])::"memory");
}
__device__ __forceinline__ void ld_unit(uint32_t (&u)[4], const uint4* p) {
    asm volatile("ld.relaxed.gpu.global.v4.u32 {%0,%1,%2,%3}, [%4];" : "=r"(u[0]), "=r"(u[1]), "=r"(u[2]), "=r"(u[3]) : "l"(p) : "memory");
}

__device__ __noinline__ void side_jobs(const __nv_bfloat16* __restrict__ t_emb, const __nv_bfloat16* __restrict__ w_emb,
                                       const __nv_bfloat16* __restrict__ w2, Scratch* __restrict__ gs, unsigned clk0) {
    const int tid = threadIdx.x, warp = tid >> 5, lane = tid & 31, j = blockIdx.x;
    float tv = 0.f;
    if (lane < 24) tv = __bfloat162float(t_emb[(lane / 12) * E + j * 192 + warp * 12 + lane % 12]);
    if (tid == 0) {
        mbar_init(BAR(0), 1);
        mbar_expect(BAR(0), 192 * C * 2);
        fence_async_smem();
        while (clock32() - clk0 < SDELAY) {}
#pragma unroll
        for (int i = 0; i < 4; i++)
            asm volatile("cp.async.bulk.prefetch.L2.global [%0], 18432;" ::"l"(reinterpret_cast<const char*>(w2) + (j * 4 + i) * 18432) : "memory");
#pragma unroll
        for (int i = 0; i < 4; i++) bulk_g2s(S0 + SM_W + i * 12288, w_emb + (j * 192 + i * 48) * C, 12288, S0 + BAR(0));
    }
    if (j == 0 && tid < 32) gs->acc2[(tid >> 4) * LS + (tid & 15)] = 0.f;
    const float sv = silu_half(0.5f * tv);
    __syncthreads();
    mbar_wait(BAR(0), 0);
    float acc[8] = {0.f, 0.f, 0.f, 0.f, 0.f, 0.f, 0.f, 0.f};
#pragma unroll
    for (int i = 0; i < 12; i++) {
        const float2 wq = lds64f(SM_W + (warp * 12 + i) * 256 + lane * 8);
        const uint32_t wx = __float_as_uint(wq.x), wy = __float_as_uint(wq.y);
#pragma unroll
        for (int bb = 0; bb < 2; bb++) {
            const float sx = __shfl_sync(0xffffffffu, sv, bb * 12 + i);
            acc[4 * bb + 0] = fmaf(sx, bf_lo(wx), acc[4 * bb + 0]); acc[4 * bb + 1] = fmaf(sx, bf_hi(wx), acc[4 * bb + 1]);
            acc[4 * bb + 2] = fmaf(sx, bf_lo(wy), acc[4 * bb + 2]); acc[4 * bb + 3] = fmaf(sx, bf_hi(wy), acc[4 * bb + 3]);
        }
    }
    sts128f(SM_ACT + warp * 1024 + lane * 16, make_float4(acc[0], acc[1], acc[2], acc[3]));
    sts128f(SM_ACT + warp * 1024 + 512 + lane * 16, make_float4(acc[4], acc[5], acc[6], acc[7]));
    __syncthreads();
    if (tid < 128) {
        float2 sum = make_float2(0.f, 0.f);
#pragma unroll
        for (int w = 0; w < 16; w++) { const float2 p = lds64f(SM_ACT + w * 1024 + tid * 8); sum.x += p.x; sum.y += p.y; }
        *reinterpret_cast<float2*>(&gs->emb[j * NB * C + tid * 2]) = sum;
        bar_sync(1, 128);
        if (tid < 2) asm volatile("red.release.gpu.global.add.u32 [%0], 1;" ::"l"(&gs->wcnt[(2 * NB + tid) * LS]) : "memory");
    }
}

__global__ void __cluster_dims__(2, 1, 1) __launch_bounds__(NTHREADS, 1)
resblock_kernel(const __nv_bfloat16* __restrict__ w1, const __nv_bfloat16* __restrict__ x,
                const __nv_bfloat16* __restrict__ t_emb, const __nv_bfloat16* __restrict__ g1,
                const __nv_bfloat16* __restrict__ be1, const __nv_bfloat16* __restrict__ w_emb,
                const __nv_bfloat16* __restrict__ g2, const __nv_bfloat16* __restrict__ be2,
                const __nv_bfloat16* __restrict__ w2, __nv_bfloat16* __restrict__ out, Scratch* __restrict__ gs,
                const __grid_constant__ CUtensorMap xmap) {
    const unsigned clk0 = clock32();
    if (threadIdx.x == 480 && blockIdx.x >= NXTRA) TLG(1);
    const int tid = threadIdx.x, lane = tid & 31;
    const int cta = blockIdx.x - NXTRA, b = cta >> 6, r = cta & 63;
    uint4 v[5];
    if (tid < 32) weight_load(v, w1, cta & (NCTA - 1), lane);
    if (tid >= 192 && tid < 192 + 72) {
        const int c2 = (cta + 64) & (NCTA - 1), t = tid - 192;
        asm volatile("prefetch.global.L2 [%0];" ::"l"(reinterpret_cast<const char*>(w1) + (uint32_t)((((c2 & 15) * 8 + (t & 7)) * 8 + (c2 >> 4)) * 288 + (t >> 3) * 32)));
    }
    uint4 xv[8];
    const int wg4 = (tid >> 5) - 1;
    const bool early = tid >= 32 && wg4 < NLDG;
    if (early) {
        const char* src = reinterpret_cast<const char*>(x) + (uint32_t)((((b & 1) * C + wg4 * 32 + (lane >> 3)) * HW + r) * HW * 2 + (lane & 7) * 16);
        while (clock32() - clk0 < XDELAY + (wg4 >> 1) * XSTAG + (wg4 & 1) * XSTAG2) {}
#pragma unroll
        for (int i = 0; i < 8; i++) xv[i] = __ldg(reinterpret_cast<const uint4*>(src + i * (4 * HW * HW * 2)));
    }
    const int warp = __shfl_sync(0xffffffffu, tid >> 5, 0);
    if (cta < 0) { side_jobs(t_emb, w_emb, w2, gs, clk0); return; }

    if (warp != 4) asm volatile("barrier.cluster.arrive.relaxed.aligned;" ::: "memory");
    const bool has_outer = (r != 0) && (r != HW - 1);
    if (warp == 1 || warp == 2 || warp == 3 || warp == 5) {
        const int g = warp < 4 ? warp - 1 : 3;
        if (elect_one()) {
            if (g >= NLDG) asm volatile("prefetch.tensormap [%0];" ::"l"(&xmap) : "memory");
            mbar_init(BAR(BAR_X) + 8 * g, 1);
            if (g >= NLDG) { mbar_expect(BAR(BAR_X) + 8 * g, 4096); fence_async_smem(); }
        }
        __syncwarp();
        bar_arrive(4, 256 + 32 + 128);
        if (g >= NLDG) {
            while (clock32() - clk0 < XDELAY + (g >> 1) * XSTAG + (g & 1) * XSTAG2) {}
            if (elect_one()) tma_x(SM_XOWN + g * 4096, &xmap, r, b * C + g * 32, BAR(BAR_X) + 8 * g);
            __syncwarp();
            mbar_wait(BAR(BAR_X) + 8 * g, 0);
#pragma unroll
            for (int k = 0; k < 8; k++) xv[k] = lds128(SM_XOWN + g * 4096 + k * 512 + lane * 16);
        }
        float c[8][4];
#pragma unroll
        for (int k = 0; k < 8; k++) {
            c[k][0] = c[k][1] = c[k][2] = c[k][3] = 0.f;
            stat_mma(c[k], xv[k].x, xv[k].y); stat_mma(c[k], xv[k].z, xv[k].w);
        }
#pragma unroll
        for (int i = 0; i < 4; i++) c[0][i] = ((c[0][i] + c[1][i]) + (c[2][i] + c[3][i])) + ((c[4][i] + c[5][i]) + (c[6][i] + c[7][i]));
        stat_store(c[0], SM_RED + g * 48, lane);
        __syncwarp();
        if (lane == 0) {
            const uint32_t a = SM_RED + g * 48;
            red_add4(&gs->acc1[b * LS + g * 4], 1.f, sum4(lds128f(a + 32)), sum4(lds128f(a)) + sum4(lds128f(a + 16)), 1.f);
            TL(74 + g);
        }
        if (g < NLDG) {
#pragma unroll
            for (int i = 0; i < 8; i++)
                sts128(SM_XOWN + g * 4096 + i * 512 + (lane >> 3) * 128 + (((lane & 7) ^ ((lane >> 3) + 4 * (i & 1))) << 4), xv[i]);
            __syncwarp();
            if (lane == 0) mbar_arrive(BAR(BAR_X) + 8 * g);
        }
    }
    if (warp == 4) {
            if (elect_one()) {
#pragma unroll
                for (int i = 0; i < NSTAGE; i++) mbar_init(BAR(BAR_FULL + i), (i >> 3) == 1 ? 1 : 5);
#pragma unroll
                for (int i = 0; i < NS + 2; i++) mbar_init(BAR(BAR_WEMPTY + i), 4);
#pragma unroll
                for (int i = BAR_STATS; i < BAR_X; i++) mbar_init(BAR(i), i == BAR_EMB ? 3 : 1);
                mbar_init(BAR(BAR_X + 4), 1);
                asm volatile("fence.mbarrier_init.release.cluster;" ::: "memory");
            }
            if (lane < 4) sts128(SM_GST + lane * 16, make_uint4(0, 0, 0, 0));
            __syncwarp();
            fence_async_smem();
            bar_arrive(0, 96);
            bar_arrive(5, 64);
            bar_arrive(4, 256 + 32 + 128);
            const uint4 z = make_uint4(0, 0, 0, 0);
#pragma unroll
            for (int i = 0; i < 2; i++) sts128(SM_ACT + (i * 16 + (lane >> 1)) * CH_PITCH + (lane & 1) * 16, z);
            if (lane < 4) sts128(SM_ACT + (2 + (lane >> 1)) * ROW_BYTES + (lane & 1) * 16, z);
            if (lane < 16) sts128(SM_ONES + lane * 16, make_uint4(lane < 8 ? 0x3f803f80u : 0u, 0, 0, 0));
            fence_async_smem();
            bar_arrive(7, 160);
            asm volatile("barrier.cluster.arrive.relaxed.aligned;" ::: "memory");
            while (clock32() - clk0 < W2DELAY) {}
            weight_load(v, w2, cta, lane);
        }
    if (warp == 0 || warp == 4) {
        const int k = warp >> 2;
#pragma unroll
        for (int i = 0; i < 5; i++)
            if (i < 4 || !(lane & 2)) sts128(SM_BNC + k * 2304 + (lane >> 2) * 288 + (lane & 3) * 16 + i * 64, v[i]);
        if (lane == 0) TL(k ? 14 : 81);
        __syncwarp();
        weight_block(SM_BNC + k * 2304, gs->wt + k * NSTAGE * STAGE_BYTES, cta, lane,
                     k ? &gs->wcnt[(NB + (lane & 1)) * LS] : &gs->w1cnt[((lane & 1) * 8 + (cta >> 4)) * KS]);
        if (lane == 0) TL(k ? 13 : 4);
    }

    if (warp >= 8) {
        const int nw = warp - 8;
        if (nw < 2) {
            const uint2 ga = __ldg(reinterpret_cast<const uint2*>(nw ? g2 : g1) + lane), bt = __ldg(reinterpret_cast<const uint2*>(nw ? be2 : be1) + lane);
            sts128f(SM_COEF + nw * 1024 + lane * 32, make_float4(0.5f * bf_lo(ga.x), 0.5f * bf_hi(ga.x), 0.5f * bf_lo(bt.x), 0.5f * bf_hi(bt.x)));
            sts128f(SM_COEF + nw * 1024 + lane * 32 + 16, make_float4(0.5f * bf_lo(ga.y), 0.5f * bf_hi(ga.y), 0.5f * bf_lo(bt.y), 0.5f * bf_hi(bt.y)));
        }
        bar_sync(4, 256 + 32 + 128);
        const int par = nw >> 2, wq = nw & 3;
        const uint32_t act_off = SM_ACT + (par * 4 + (lane >> 4)) * CH_PITCH + (2 + wq * 16 + (lane & 15)) * 16;
        const uint32_t stg_off = (par * 32 + (lane >> 4) * 8 + (lane & 7)) * 128 + (((2 * wq + ((lane >> 3) & 1)) ^ (lane & 7)) << 4);
        const uint32_t cfa = SM_COEF + par * 256 + (lane & 3) * 16;
        const uint32_t fbar = BAR(BAR_FULL) + 16 * par;
        uint4* inbox = gs->box + cta * 1024 + par * 256 + (tid & 127);
#pragma unroll 1
        for (int conv = 0; conv < 2; conv++) {
            uint32_t u[4][4], w[4][4];
            float4 cf[8];
            if (conv == 0) {
#pragma unroll
                for (int i = 0; i < 4; i++) {
                    if (!(i & 1)) mbar_wait(BAR(BAR_X + i) + 8 * par, 0);
                    ldsm4t(u[i], SM_XOWN + stg_off + unit_kc(i) * 2048);
                }
            } else {
                mbar_wait(BAR(BAR_HW), 0);
#pragma unroll
                for (int i = 0; i < 4; i++) ldsm4(u[i], act_off + unit_kc(i) * KC_BYTES);
            }
#pragma unroll
            for (int i = 0; i < 8; i++) cf[i] = lds128f(cfa + conv * 1024 + unit_kc(i >> 1) * 128 + (i & 1) * 64);
            const uint32_t gst = SM_GST + conv * 32 + par * 8;
            float z[4][8];
#pragma unroll
            for (int i = 0; i < 16; i++) {
                const float4& c = cf[i >> 1];
                z[i >> 2][2 * (i & 3)] = bf_lo(u[i >> 2][i & 3]) * c.x; z[i >> 2][2 * (i & 3) + 1] = bf_hi(u[i >> 2][i & 3]) * c.y;
                asm volatile("" : "+f"(z[i >> 2][2 * (i & 3)]), "+f"(z[i >> 2][2 * (i & 3) + 1]));
            }
            const float2 g0 = wait_stats(gst, make_float2(0.f, 0.f));
            if (tid == 256) TL(22 + conv * 4);
            own_unit<0>(z[0], cf, g0, act_off);
            float2 g1;
            asm volatile("ld.volatile.shared.v2.f32 {%0,%1}, [%2];" : "=f"(g1.x), "=f"(g1.y) : "r"(gst + 16 + S0) : "memory");
            own_unit<1>(z[1], cf, g0, act_off);
            publish(fbar, 2, lane);
            if (tid == 256) TL(8 + conv * 8);
            g1 = wait_stats(gst + 16, g1);
            own_unit<2>(z[2], cf, g1, act_off);
            own_unit<3>(z[3], cf, g1, act_off);
            publish(fbar + 32, 2, lane);
#pragma unroll
            for (int i = 0; i < 8; i++) { const float rs = i < 4 ? g0.x : g1.x; cf[i].x *= rs; cf[i].y *= rs; }
            if (tid == 256) TL(84 + conv);
            if (has_outer) {
                mbar_wait(BAR(BAR_X + 4), conv);
                if (conv == 0) {
#pragma unroll
                    for (int i = 0; i < 4; i++) ldsm4t(w[i], SM_XOUT + stg_off + unit_kc(i) * 2048);
                } else {
#pragma unroll
                    for (int i = 0; i < 4; i++) {
                        const uint4 q = lds128(SM_XOWN + par * 4096 + (tid & 127) * 16 + unit_kc(i) * 2048);
                        w[i][0] = q.x; w[i][1] = q.y; w[i][2] = q.z; w[i][3] = q.w;
                    }
                    unsigned it = 0;
                    while (true) {
                        bool ok = true;
#pragma unroll
                        for (int i = 0; i < 16; i++) ok = ok && w[i >> 2][i & 3] != 0;
                        if (__all_sync(0xffffffffu, ok) || ++it > SPIN_LIMIT) break;
#pragma unroll
                        for (int i = 0; i < 4; i++) ld_unit(w[i], inbox + unit_kc(i) * 128);
                    }
#pragma unroll
                    for (int i = 0; i < 16; i++) w[i >> 2][i & 3] = ~w[i >> 2][i & 3];
                }
            }
            if (conv == 0) {
                bar_sync(3, 256);
                if (nw == 0) sts128(SM_ACT + 2 * ROW_BYTES + (lane >> 1) * CH_PITCH + (lane & 1) * 16, make_uint4(0, 0, 0, 0));
            }
            if (tid == 256) TL(24 + conv * 4);
            outer_pair<0>(w, cf, act_off + 2 * ROW_BYTES, has_outer ? ~0u : 0u, fbar + 128, lane);
            if (tid == 256) TL(88 + conv);
            outer_pair<2>(w, cf, act_off + 2 * ROW_BYTES, has_outer ? ~0u : 0u, fbar + 128, lane);
            if (tid == 256) TL(23 + conv * 4);
        }
        if (has_outer) {
            mbar_wait(BAR(BAR_FULL + NSTAGE - 1), 1);
#pragma unroll
            for (int i = 0; i < 4; i++) inbox[unit_kc(i) * 128] = make_uint4(0, 0, 0, 0);
        }
        {
            const int oc0 = par * 64 + ((tid & 127) >> 3), seg = lane & 7;
            __nv_bfloat16* dst = out + ((size_t)(b * C + oc0) * HW + r) * HW + seg * 8;
            const uint32_t src = SM_XOWN + oc0 * 128 + ((seg ^ (oc0 & 7)) << 4);
            asm volatile("{\n.reg .pred p;\nsetp.eq.u64 p, %0, 0;\n@p st.shared.u32 [%1], 0;\n}" ::"l"(dst), "r"(src + S0) : "memory");
            bar_sync(par ? 1 : 6, 128 + 128);
#pragma unroll
            for (int i = 0; i < 4; i++) *reinterpret_cast<uint4*>(dst + (size_t)i * 16 * HW * HW) = lds128(src + i * 2048);
            if (tid == 384) { TL(20); TLG(21); }
        }
    } else if (warp < 4) {
        const int wq = warp;
        bar_sync(7, 160);

        const uint32_t xbase = SM_XOWN + ((lane >> 4) * 8 + (lane & 7)) * 128 + (((2 * wq + ((lane >> 3) & 1)) ^ (lane & 7)) << 4);
        float d[64];
#pragma unroll
        for (int i = 0; i < 64; i++) d[i] = 0.f;
#pragma unroll 1
        for (int conv = 0; conv < 2; conv++) {
            fence_acc(d);
            mma_stages<0>(d, conv, tid, gs);
            if (conv == 0) {
                asm volatile("wgmma.fence.sync.aligned;" ::: "memory");
                wgmma128<(SM_ONES >> 4) | (8u << 16), (SM_EMB >> 4), 0, 8>(d);
                asm volatile("wgmma.commit_group.sync.aligned;" ::: "memory");
            }
            asm volatile("wgmma.wait_group.sync.aligned 0;" ::: "memory");
            fence_acc(d);
            if (tid == 0) TL(10 + conv * 8);
            if (conv == 1) {
                fence_acc(d);
#pragma unroll
                for (int kc = 0; kc < 8; kc++) {
                    stsm4t(xbase + kc * 2048, pack_bf(d[8 * kc], d[8 * kc + 1]), pack_bf(d[8 * kc + 2], d[8 * kc + 3]),
                           pack_bf(d[8 * kc + 4], d[8 * kc + 5]), pack_bf(d[8 * kc + 6], d[8 * kc + 7]));
                    if (kc == 3) bar_arrive(6, 128 + 128);
                }
                bar_arrive(1, 128 + 128);
                if (tid == 0) TL(5);
                break;
            }
            uint32_t hp[32];
#pragma unroll
            for (int i = 0; i < 32; i++) hp[i] = pack_bf(d[2 * i], d[2 * i + 1]);
#pragma unroll
            for (int g = 0; g < 4; g++) {
                float c[4] = {0.f, 0.f, 0.f, 0.f};
#pragma unroll
                for (int i = 0; i < 4; i++) stat_mma(c, hp[8 * g + 2 * i], hp[8 * g + 2 * i + 1]);
                stat_store(c, SM_RED + (g * 4 + wq) * 48, lane);
            }
            bar_sync(2, 128);
            if (wq == 0) stat_publish(SM_RED, &gs->acc2[b * LS], lane, true);
            if (tid == 0) TL(11);
            const uint32_t hbase = SM_ACT + (lane >> 4) * CH_PITCH + (2 + wq * 16 + (lane & 15)) * 16;
#pragma unroll
            for (int kc = 0; kc < 8; kc++) stsm4(hbase + kc * 2 * CH_PITCH, hp[4 * kc], hp[4 * kc + 1], hp[4 * kc + 2], hp[4 * kc + 3]);
            __syncwarp();
            if (lane == 0) mbar_arrive(BAR(BAR_HW));
            if (lane < LAG) mbar_arrive(BAR(BAR_WEMPTY + (NSTAGE - LAG) % NS) + 8 * lane);
            if (has_outer) {
                uint4* outbox = gs->box + (cta + ((r & 1) ? 1 : -1)) * 1024 + tid;
#pragma unroll
                for (int kc = 0; kc < 8; kc++) outbox[kc * 128] = make_uint4(~hp[4 * kc], ~hp[4 * kc + 1], ~hp[4 * kc + 2], ~hp[4 * kc + 3]);
            }
            if (tid == 0) TL(12);
#pragma unroll
            for (int kc = 0; kc < 8; kc++) {
                uint32_t p[4];
                ldsm4t(p, xbase + kc * 2048);
#pragma unroll
                for (int i = 0; i < 4; i++) { d[8 * kc + 2 * i] = bf_lo(p[i]); d[8 * kc + 2 * i + 1] = bf_hi(p[i]); }
            }
            fence_async_smem();
            __syncwarp();
            if (lane == 0) mbar_arrive(BAR(BAR_XFREE));
        }
        {
        }
    } else if (warp < 6) {
        if (warp == 5) {
            bar_sync(5, 64);
            mbar_wait(BAR(BAR_FULL), 0);
            if (has_outer && elect_one()) {
                mbar_expect(BAR(BAR_X + 4), 16384);
#pragma unroll
                for (int i = 0; i < 4; i++) tma_x(SM_XOUT + i * 4096, &xmap, r + ((r & 1) ? 1 : -1), b * C + i * 32, BAR(BAR_X + 4));
            }
            __syncwarp();
            asm volatile("barrier.cluster.wait.acquire.aligned;" ::: "memory");
            const uint32_t peer = (r & 1) ^ 1;
            const uint32_t self0 = mapa(0, r & 1), peer0 = mapa(0, peer);
#pragma unroll 1
            for (int conv = 0; conv < 2; conv++) {
#pragma unroll 1
                for (int kc = 0; kc < 8; kc++) {
                    mbar_wait(BAR(BAR_FULL) + 8 * kc, conv);
                    if (elect_one())
                        asm volatile("cp.async.bulk.shared::cluster.shared::cta.mbarrier::complete_tx::bytes [%0], [%1], %2, [%3];"
                                     ::"r"(peer0 + SM_ACT + ROW_BYTES + kc * KC_BYTES), "r"(self0 + SM_ACT + kc * KC_BYTES), "r"(KC_BYTES),
                                       "r"(peer0 + BAR(BAR_FULL + 8) + 8 * kc) : "memory");
                }
                if (lane == 0) TL(86 + conv);
#pragma unroll 1
                for (int kc = 0; kc < 8; kc++) mbar_wait(BAR(BAR_FULL + 8) + 8 * kc, conv);
                if (lane == 0)
                    asm volatile("mbarrier.arrive.relaxed.cluster.shared::cluster.b64 _, [%0];" ::"r"(peer0 + (conv ? BAR(BAR_ACK) : BAR(BAR_EMB))) : "memory");
            }
            mbar_wait(BAR(BAR_ACK), 0);
        } else {
            mbar_wait(BAR(BAR_STATS), 0);
            unsigned it = 0;
            while (!__all_sync(0xffffffffu, ld_relaxed(&gs->wcnt[(2 * NB + b) * LS]) >= (unsigned)NXTRA) && ++it < SPIN_LIMIT) __nanosleep(100);
            fence_acquire();
            float ev[4] = {0.f, 0.f, 0.f, 0.f};
#pragma unroll
            for (int j = 0; j < NXTRA; j++) {
                const uint4 ef = ld_relaxed_v4(&gs->emb[(j * NB + b) * C + lane * 4]);
                ev[0] += __uint_as_float(ef.x); ev[1] += __uint_as_float(ef.y); ev[2] += __uint_as_float(ef.z); ev[3] += __uint_as_float(ef.w);
            }
#pragma unroll
            for (int i = 0; i < 4; i++) {
                const float hi = bf_lo(pack_bf(ev[i], 0.f));
                sts128(SM_EMB + (lane * 4 + i) * 16, make_uint4(pack_bf(hi, ev[i] - hi), 0, 0, 0));
            }
            fence_async_smem();
            __syncwarp();
            if (lane == 0) { mbar_arrive(BAR(BAR_EMB)); TL(19); }
        }
    } else if (warp == 6) {
        bar_sync(0, 96);
        const uint32_t ebytes = STAGE_BYTES + ((lane >> 3) == 1 ? KC_BYTES : 0);
        if (lane < NSTAGE) mbar_expect(BAR(BAR_FULL) + 8 * lane, ebytes);
        const int swap = (r & 1) ? 0 : 8 * STAGE_BYTES;
        unsigned it = 0;
        {
            int g = 0;
            const unsigned* cnt = &gs->w1cnt[(b * 8 + (lane & 7)) * KS];
            unsigned cv = ld_relaxed(cnt);
#pragma unroll 1
            while (g < NS) {
                unsigned ready = __ballot_sync(0xffffffffu, (lane < 8 ? cv & 0xffffu : cv >> 16) >= 16u);
                if ((ready >> 8 & 0xff) != 0xff) ready &= 0xff;
                if (ready != ~0u) cv = ld_relaxed(cnt);
                ready >>= g;
                if (++it > SPIN_LIMIT) ready = ~0u;
                if (!(ready & 1)) continue;
                fence_async_global();
                if (lane == 0) TL(g ? 3 : 6);
#pragma unroll 1
                for (; (ready & 1) && g < NS; g++, ready >>= 1)
                    if (elect_one())
                        bulk_g2s(S0 + SM_W + g * STAGE_BYTES, gs->wt + g * STAGE_BYTES + (g >= 8 ? swap : 0), STAGE_BYTES, S0 + BAR(BAR_FULL) + 8 * g);
            }
        }
#pragma unroll 1
        for (int q = 3; q < 12; q++) {
            const int conv = q >= 6, qs = conv ? q - 6 : q, sl = q % 3;
            const unsigned char* wsrc = gs->wt + q * 4 * STAGE_BYTES + (qs < 2 ? 0 : (qs < 4 ? swap : -swap));
            const uint32_t par = (q / 3 - 1) & 1;
            if (q == 6) {
                it = 0;
                while (!__all_sync(0xffffffffu, ld_relaxed(&gs->wcnt[(NB + b) * LS]) == NCTA * 0x10001u) && ++it < SPIN_LIMIT) {}
                fence_acquire();
                fence_async_global();
                if (lane == 0) { mbar_arrive(BAR(BAR_EMB)); TL(2); }
            }
#pragma unroll
            for (int i = 0; i < 4; i++) {
                mbar_wait(BAR(BAR_WEMPTY + i) + 32 * sl, par);
                if (i == 0 && (q == 6 || q == 9)) {
                    if ((lane >= NS) == (q == 9) && lane < NSTAGE) mbar_expect(BAR(BAR_FULL) + 8 * lane, ebytes);
                    __syncwarp();
                }
                if (elect_one())
                    bulk_g2s(S0 + SM_W + (sl * 4 + i) * STAGE_BYTES, wsrc + i * STAGE_BYTES, STAGE_BYTES,
                             S0 + BAR(BAR_FULL + i) + 32 * qs);
            }
        }
    } else {
        bar_sync(0, 96);
#pragma unroll 1
        for (int conv = 0; conv < 2; conv++) {
            if (conv == 1) mbar_wait(BAR(BAR_HW), 0);
            const float* asrc = (conv ? gs->acc2 : gs->acc1) + b * LS + (lane & 3) * 4;
            unsigned it = 0;
#pragma unroll 1
            while (true) {
                const uint4 f = ld_relaxed_v4(asrc);
                const bool ok = ((f.x == 0x42800000u) & (f.w == 0x42800000u)) || ++it > SPIN_LIMIT;
                if (ok && lane < 4) {
                    const float inv_n = 1.0f / (32.0f * HW * HW);
                    const float mean = __uint_as_float(f.y) * inv_n;
                    float rs;
                    asm("rsqrt.approx.ftz.f32 %0, %1;" : "=f"(rs) : "f"(fmaxf(fmaf(-mean, mean, __uint_as_float(f.z) * inv_n), 0.f) + 1e-5f));
                    asm volatile("st.shared.v2.f32 [%0], {%1,%2};" ::"r"(S0 + SM_GST + conv * 32 + lane * 8), "f"(rs == 0.f ? 1.2e-38f : rs), "f"(mean * rs) : "memory");
                }
                if (__all_sync(0xffffffffu, ok)) break;
            }
            if (lane == 0) { mbar_arrive(BAR(BAR_STATS)); TL(7 + conv * 8); }
        }
        mbar_wait(BAR(BAR_XFREE), 0);
        if (has_outer && elect_one()) {
            mbar_expect(BAR(BAR_X + 4), 16384);
            bulk_g2s(S0 + SM_XOWN, gs->box + cta * 1024, 16384, S0 + BAR(BAR_X + 4));
        }
        if (r == 0) {
            if (lane < 16) gs->acc1[b * LS + lane] = 0.f;
            if (lane < 3) gs->wcnt[(lane * NB + b) * LS] = 0;
            if (lane < 8) gs->w1cnt[(b * 8 + lane) * KS] = 0;
        }
    }
}

}

extern "C" void kernel_launch(void* const* d_in, const int* in_sizes, int n_in, void* d_out, int out_size) {
    (void)in_sizes; (void)n_in; (void)out_size;
    typedef CUresult (*EncodeFn)(CUtensorMap*, CUtensorMapDataType, cuuint32_t, void*, const cuuint64_t*, const cuuint64_t*,
                                 const cuuint32_t*, const cuuint32_t*, CUtensorMapInterleave, CUtensorMapSwizzle,
                                 CUtensorMapL2promotion, CUtensorMapFloatOOBfill);
    static Scratch* gs = nullptr;
    static EncodeFn encode = nullptr;
    if (!gs) {
        cudaFuncSetAttribute(resblock_kernel, cudaFuncAttributeMaxDynamicSharedMemorySize, SM_TOTAL);
        cudaGetSymbolAddress((void**)&gs, g_scratch);
        cudaDriverEntryPointQueryResult qr;
        cudaGetDriverEntryPoint("cuTensorMapEncodeTiled", (void**)&encode, cudaEnableDefault, &qr);
    }
    CUtensorMap xmap;
    const cuuint64_t dims[3] = {HW, HW, NB * C}, strides[2] = {HW * 2, HW * HW * 2};
    const cuuint32_t box[3] = {HW, 1, 32}, es[3] = {1, 1, 1};
    encode(&xmap, CU_TENSOR_MAP_DATA_TYPE_BFLOAT16, 3, d_in[0], dims, strides, box, es, CU_TENSOR_MAP_INTERLEAVE_NONE,
           CU_TENSOR_MAP_SWIZZLE_128B, CU_TENSOR_MAP_L2_PROMOTION_NONE, CU_TENSOR_MAP_FLOAT_OOB_FILL_NONE);
    resblock_kernel<<<NCTA + NXTRA, NTHREADS, SM_TOTAL>>>(
        (const __nv_bfloat16*)d_in[4], (const __nv_bfloat16*)d_in[0], (const __nv_bfloat16*)d_in[1],
        (const __nv_bfloat16*)d_in[2], (const __nv_bfloat16*)d_in[3], (const __nv_bfloat16*)d_in[5],
        (const __nv_bfloat16*)d_in[6], (const __nv_bfloat16*)d_in[7], (const __nv_bfloat16*)d_in[8],
        (__nv_bfloat16*)d_out, gs, xmap);
}
```
